```python
import torch

def _softmax(x, axis=-1):
    return torch.softmax(x, dim=axis)

def _gelu(x):
    return torch.nn.functional.gelu(x, approximate='tanh')

def _silu(x):
    return torch.nn.functional.silu(x)

def _sigmoid(x):
    return torch.sigmoid(x)

def _layernorm(x, axis=-1, eps=1e-05):
    m = x.mean(dim=axis, keepdim=True)
    v = x.var(dim=axis, keepdim=True, unbiased=False)
    return (x - m) / torch.sqrt(v + eps)

def _scatter_add(tgt, idx, src, axis=0):
    return tgt.clone().index_add_(axis, idx, src)

def _segment_sum(src, seg, n):
    out = torch.zeros((n,) + src.shape[1:], dtype=src.dtype)
    return out.index_add_(0, seg, src)

def _pad(x, pw):
    flat = tuple((v for pair in reversed(pw) for v in pair))
    return torch.nn.functional.pad(x, flat)
kernel_name = 'interleave_layers__memory_aug_recurrent_mem_tr__sliding_local_dilated__prompt'

def setup_inputs():

    _w = lambda a: (lambda t: t.to(torch.bfloat16) if t.is_floating_point() else t)(torch.as_tensor(a))

    def _A_setup():
        B, S, Dm = (1, 2048, 640)
        H, Dh = (32, 192)
        M, seg = (8, 32)
        seg = min(seg, S)
        S = S // seg * seg
        return {'x': _w((lambda *s: torch.randn(*s, dtype=torch.bfloat16) * 0.05)(B, S, Dm)), 'mem0': _w((lambda *s: torch.randn(*s, dtype=torch.bfloat16) * 0.8)(B, M, Dm)), 'Wq': _w((lambda *s: torch.randn(*s, dtype=torch.bfloat16) * 1.6)(Dm, H, Dh) * Dm ** (-0.5)), 'Wk': _w((lambda *s: torch.randn(*s, dtype=torch.bfloat16) * 1.6)(Dm, H, Dh) * Dm ** (-0.5)), 'Wv': _w((lambda *s: torch.randn(*s, dtype=torch.bfloat16) * 0.8)(Dm, H, Dh) * Dm ** (-0.5)), 'Wo': _w((lambda *s: torch.randn(*s, dtype=torch.bfloat16) * 0.8)(H, Dh, Dm) * (H * Dh) ** (-0.5)), 'seg_len': seg}
    _A_in = _A_setup()

    def _B_setup():
        B, S, D = (1, 2048, 640)
        return {'x': _w((lambda *s: torch.randn(*s, dtype=torch.bfloat16) * 0.05)(B, S, D)), 'wqkv': _w((lambda *s: torch.randn(*s, dtype=torch.bfloat16) * 0.05)(D, 3 * D)), 'wo': _w((lambda *s: torch.randn(*s, dtype=torch.bfloat16) * 0.05)(D, D))}
    _B_in = _B_setup()
    return {'A_x': _A_in['x'], 'A_mem0': _A_in['mem0'], 'A_Wq': _A_in['Wq'], 'A_Wk': _A_in['Wk'], 'A_Wv': _A_in['Wv'], 'A_Wo': _A_in['Wo'], 'A_seg_len': _A_in['seg_len'], 'B_x': _B_in['x'], 'B_wqkv': _B_in['wqkv'], 'B_wo': _B_in['wo']}

def reference(A_x, A_mem0, A_Wq, A_Wk, A_Wv, A_Wo, A_seg_len, B_x, B_wqkv, B_wo):

    def _A_ref(x, mem0, Wq, Wk, Wv, Wo, seg_len):
        B, S, Dm = x.shape
        H, Dh = (Wq.shape[1], Wq.shape[2])
        M = mem0.shape[1]
        scale = Dh ** (-0.5)
        n_seg = S // seg_len
        L = M + seg_len
        idx = torch.arange(L)
        mask = (idx[:, None] < M) | (idx[:, None] >= idx[None, :])
        mem = mem0
        outs = []
        for s in range(n_seg):
            xs = x[:, s * seg_len:(s + 1) * seg_len, :].clone()
            h = torch.concatenate([mem, xs], axis=1)
            q = torch.einsum('btd,dhe->bhte', h, Wq)
            k = torch.einsum('btd,dhe->bhte', h, Wk)
            v = torch.einsum('btd,dhe->bhte', h, Wv)
            scores = torch.einsum('bhqe,bhke->bhqk', q, k) * scale
            scores = torch.where(mask[None, None], scores, -1000000000.0)
            p = _softmax(scores, axis=-1)
            o = torch.einsum('bhqk,bhke->bhqe', p, v)
            o = torch.einsum('bhte,hed->btd', o, Wo)
            mem = o[:, :M, :].clone()
            outs.append(o[:, M:, :])
        return torch.concatenate(outs, axis=1)

    def _B_ref(x, wqkv, wo):
        B, S, D = x.shape
        H = 32
        Dh = D // H
        W, dil = (8, 2)
        qkv = (lambda x, *d: x.permute(*d))((x @ wqkv).reshape(B, S, 3, H, Dh), 2, 0, 3, 1, 4)
        q, k, v = (qkv[0], qkv[1], qkv[2])
        scale = Dh ** (-0.5)
        pos = torch.arange(S)
        off = torch.arange(W) * dil
        idx = pos[:, None] - off[None, :]
        mask = idx >= 0
        idx_c = torch.where(mask, idx, 0).reshape(-1)
        kg = k[:, :, idx_c, :].reshape(B, H, S, W, Dh)
        vg = v[:, :, idx_c, :].reshape(B, H, S, W, Dh)
        logits = torch.einsum('bhsd,bhswd->bhsw', q, kg) * scale
        logits = torch.where(mask[None, None, :, :], logits, -1000000000.0)
        attn = _softmax(logits, axis=-1)
        o = torch.einsum('bhsw,bhswd->bhsd', attn, vg)
        return (lambda x, *d: x.permute(*d))(o, 0, 2, 1, 3).reshape(B, S, D) @ wo
    x = A_x
    x = x + _A_ref(_layernorm(x, axis=-1), A_mem0, A_Wq, A_Wk, A_Wv, A_Wo, A_seg_len)
    x = x + _B_ref(_layernorm(x, axis=-1), B_wqkv, B_wo)
    x = x + _A_ref(_layernorm(x, axis=-1), A_mem0, A_Wq, A_Wk, A_Wv, A_Wo, A_seg_len)
    x = x + _B_ref(_layernorm(x, axis=-1), B_wqkv, B_wo)
    return x
```

```cpp
#include <cuda_runtime.h>
#include <cuda_bf16.h>
#include <cuda.h>
#include <stdint.h>

typedef __nv_bfloat16 bf16;

constexpr int SEQ = 2048, DM = 640, NH = 32, DH = 192, NSEG = 64;
#define LAG 14
constexpr int NSTEP = NSEG + LAG;
constexpr uint32_t SENT = 0xFFFFFFFFu;
constexpr int SPIN_LIM = 1 << 20;
constexpr int SPIN_MAIL = 1 << 16;
constexpr int SPIN_CNT = 1 << 16;

constexpr int MAIL9 = 288 * 2048, MAIL_BYTES = MAIL9 + 64 * 3072;
__device__ __align__(1024) uint8_t g_xn[2][NSEG * 40960];
__device__ __align__(1024) uint8_t g_xnb[2][32 * 10 * 8192];
__device__ __align__(1024) uint8_t g_ob[2][32 * 10 * 8192];
__device__ __align__(1024) uint8_t g_o[2][32 * 96 * 8192];
__device__ __align__(1024) uint8_t g_mbuf[NSTEP][20480];
__device__ __align__(1024) uint8_t g_mail[2][MAIL_BYTES];
__device__ __align__(1024) float g_acc[2][16][5][16384];
__device__ __align__(1024) float2 g_stats[16][128][16];
__device__ __align__(128) bf16 g_x1[SEQ * DM];
__device__ __align__(128) bf16 g_x2[SEQ * DM];
__device__ __align__(128) bf16 g_x3[SEQ * DM];
enum { CN_O = 0, CN_P = 1, CN_L = 2, CN_A = 3, CN_X = 4, CN_Z = 5 };
__device__ __align__(128) uint32_t g_cnt[6][2][16][32];
__device__ int g_err;
#define TS(jj, i)
#define TS1(jj, i)
#define PTS(i)
#define LTS(l, b, p, k)
#define TSB(jj, i)
#define TSV(jj, i, v)
#define TS_FLUSH(jj)
#define WTS(l, b, k)
#define WW -1

__device__ __forceinline__ uint32_t smem_u32(const void* p) { return (uint32_t)__cvta_generic_to_shared(p); }
__device__ __forceinline__ uint32_t clk32() { uint32_t t; asm volatile("mov.u32 %0, %%clock;" : "=r"(t)::"memory"); return t; }
__device__ __forceinline__ uint32_t mapa(uint32_t a, uint32_t r) { uint32_t o; asm("mapa.shared::cluster.u32 %0,%1,%2;" : "=r"(o) : "r"(a), "r"(r)); return o; }
__device__ __forceinline__ void mbar_init(uint32_t bar, uint32_t cnt) { asm volatile("mbarrier.init.shared::cta.b64 [%0],%1;" ::"r"(bar), "r"(cnt) : "memory"); }
__device__ __forceinline__ void mbar_expect_tx(uint32_t bar, uint32_t bytes) { asm volatile("mbarrier.arrive.expect_tx.shared::cta.b64 _,[%0],%1;" ::"r"(bar), "r"(bytes) : "memory"); }
__device__ __forceinline__ void mbar_arrive(uint32_t bar) { asm volatile("mbarrier.arrive.shared::cta.b64 _,[%0];" ::"r"(bar) : "memory"); }
__device__ __forceinline__ void mbar_arrive_cluster(uint32_t bar) { asm volatile("mbarrier.arrive.shared::cluster.b64 _,[%0];" ::"r"(bar) : "memory"); }
__device__ __forceinline__ bool mbar_try(uint32_t bar, uint32_t ph) {
  uint32_t ok;
  asm volatile("{.reg .pred p; mbarrier.try_wait.parity.shared::cta.b64 p,[%1],%2; selp.u32 %0,1,0,p;}" : "=r"(ok) : "r"(bar), "r"(ph) : "memory");
  return ok;
}
__device__ __forceinline__ void mbar_wait(uint32_t bar, uint32_t ph, int& dead) {
  if (mbar_try(bar, ph)) return;
  int n = dead ? SPIN_LIM : 0;
  while (!mbar_try(bar, ph)) { if (++n > SPIN_LIM) { dead = 1; g_err = 1; break; } }
}
__device__ __forceinline__ int fresh(int x) { asm volatile("" : "+r"(x)); return x; }
#define PHASE_IDS const int tid = fresh(tid0), lane = tid & 31, w = tid >> 5, g = lane >> 2, t = lane & 3; (void)w; (void)g; (void)t
__device__ __forceinline__ void bar_sync(int id, int n) { asm volatile("bar.sync %0,%1;" ::"r"(id), "r"(n) : "memory"); }
__device__ __forceinline__ void bar_arrive(int id, int n) { asm volatile("bar.arrive %0,%1;" ::"r"(id), "r"(n) : "memory"); }
__device__ __forceinline__ bool bar_red_or(int id, int n, bool v) {
  uint32_t r;
  asm volatile("{\n .reg .pred p, q;\n setp.ne.u32 q, %3, 0;\n barrier.cta.red.or.pred p, %1, %2, q;\n selp.u32 %0, 1, 0, p;\n}" : "=r"(r) : "r"(id), "r"(n), "r"((uint32_t)v) : "memory");
  return r != 0;
}
__device__ __forceinline__ void fence_async() { asm volatile("fence.proxy.async.shared::cta;" ::: "memory"); }
__device__ __forceinline__ void bulk_g2s(uint32_t dst, const void* src, uint32_t bytes, uint32_t bar) {
  asm volatile("cp.async.bulk.shared::cluster.global.mbarrier::complete_tx::bytes [%0],[%1],%2,[%3];" ::"r"(dst), "l"(src), "r"(bytes), "r"(bar) : "memory");
}
__device__ __forceinline__ void bulk_g2s_mc(uint32_t dst, const void* src, uint32_t bytes, uint32_t bar) {
  asm volatile("cp.async.bulk.shared::cluster.global.mbarrier::complete_tx::bytes.multicast::cluster [%0],[%1],%2,[%3],%4;"
               ::"r"(dst), "l"(src), "r"(bytes), "r"(bar), "h"((uint16_t)7) : "memory");
}
__device__ __forceinline__ void bulk_s2g(void* dst, uint32_t src, uint32_t bytes) {
  asm volatile("cp.async.bulk.global.shared::cta.bulk_group [%0],[%1],%2;" ::"l"(dst), "r"(src), "r"(bytes) : "memory");
}
__device__ __forceinline__ void bulk_s2c(uint32_t dst, uint32_t src, uint32_t bytes, uint32_t bar) {
  asm volatile("cp.async.bulk.shared::cluster.shared::cta.mbarrier::complete_tx::bytes [%0],[%1],%2,[%3];" ::"r"(dst), "r"(src), "r"(bytes), "r"(bar) : "memory");
}
__device__ __forceinline__ void tma2d(uint32_t dst, const CUtensorMap* tm, int c0, int c1, uint32_t bar) {
  asm volatile("cp.async.bulk.tensor.2d.shared::cluster.global.mbarrier::complete_tx::bytes [%0],[%1,{%3,%4}],[%2];"
               ::"r"(dst), "l"(tm), "r"(bar), "r"(c0), "r"(c1) : "memory");
}
__device__ __forceinline__ void tma2d_prefetch(const CUtensorMap* tm, int c0, int c1) {
  asm volatile("cp.async.bulk.prefetch.tensor.2d.L2.global.tile [%0,{%1,%2}];" ::"l"(tm), "r"(c0), "r"(c1) : "memory");
}
__device__ __forceinline__ uint32_t pack_bf16(float lo, float hi) {
  uint32_t r; asm("cvt.rn.bf16x2.f32 %0,%1,%2;" : "=r"(r) : "f"(hi), "f"(lo)); return r;
}
__device__ __forceinline__ float bf_lo(uint32_t x) { return __uint_as_float(x << 16); }
__device__ __forceinline__ float bf_hi(uint32_t x) { return __uint_as_float(x & 0xFFFF0000u); }
__device__ __forceinline__ float ex2(float x) { float y; asm("ex2.approx.ftz.f32 %0,%1;" : "=f"(y) : "f"(x)); return y; }
__device__ __forceinline__ void ldsm4(uint32_t (&r)[4], uint32_t a) {
  asm volatile("ldmatrix.sync.aligned.m8n8.x4.shared.b16 {%0,%1,%2,%3},[%4];" : "=r"(r[0]), "=r"(r[1]), "=r"(r[2]), "=r"(r[3]) : "r"(a) : "memory");
}
__device__ __forceinline__ void ldsm4t(uint32_t (&r)[4], uint32_t a) {
  asm volatile("ldmatrix.sync.aligned.m8n8.x4.trans.shared.b16 {%0,%1,%2,%3},[%4];" : "=r"(r[0]), "=r"(r[1]), "=r"(r[2]), "=r"(r[3]) : "r"(a) : "memory");
}
__device__ __forceinline__ void ldsm2(uint32_t& r0, uint32_t& r1, uint32_t a) {
  asm volatile("ldmatrix.sync.aligned.m8n8.x2.shared.b16 {%0,%1},[%2];" : "=r"(r0), "=r"(r1) : "r"(a) : "memory");
}
__device__ __forceinline__ void ldsm1(uint32_t& r0, uint32_t a) {
  asm volatile("ldmatrix.sync.aligned.m8n8.x1.shared.b16 {%0},[%1];" : "=r"(r0) : "r"(a) : "memory");
}
__device__ __forceinline__ void mma16816(float (&d)[4], uint32_t a0, uint32_t a1, uint32_t a2, uint32_t a3, uint32_t b0, uint32_t b1) {
  asm volatile("mma.sync.aligned.m16n8k16.row.col.f32.bf16.bf16.f32 {%0,%1,%2,%3},{%4,%5,%6,%7},{%8,%9},{%0,%1,%2,%3};"
               : "+f"(d[0]), "+f"(d[1]), "+f"(d[2]), "+f"(d[3]) : "r"(a0), "r"(a1), "r"(a2), "r"(a3), "r"(b0), "r"(b1));
}
__device__ __forceinline__ void mma1688(float (&d)[4], uint32_t a0, uint32_t a1, uint32_t b0) {
  asm volatile("mma.sync.aligned.m16n8k8.row.col.f32.bf16.bf16.f32 {%0,%1,%2,%3},{%4,%5},{%6},{%0,%1,%2,%3};"
               : "+f"(d[0]), "+f"(d[1]), "+f"(d[2]), "+f"(d[3]) : "r"(a0), "r"(a1), "r"(b0));
}
__device__ __forceinline__ void sts32(uint32_t a, uint32_t v) { asm volatile("st.shared.b32 [%0],%1;" ::"r"(a), "r"(v) : "memory"); }
__device__ __forceinline__ void sts64f(uint32_t a, float x, float y) { asm volatile("st.shared.v2.f32 [%0],{%1,%2};" ::"r"(a), "f"(x), "f"(y) : "memory"); }
__device__ __forceinline__ void sts128(uint32_t a, uint4 v) { asm volatile("st.shared.v4.b32 [%0],{%1,%2,%3,%4};" ::"r"(a), "r"(v.x), "r"(v.y), "r"(v.z), "r"(v.w) : "memory"); }
__device__ __forceinline__ float lds32f(uint32_t a) { float v; asm volatile("ld.shared.f32 %0,[%1];" : "=f"(v) : "r"(a) : "memory"); return v; }
__device__ __forceinline__ float2 lds64f(uint32_t a) { float2 v; asm volatile("ld.shared.v2.f32 {%0,%1},[%2];" : "=f"(v.x), "=f"(v.y) : "r"(a) : "memory"); return v; }
__device__ __forceinline__ uint4 lds128(uint32_t a) { uint4 v; asm volatile("ld.shared.v4.b32 {%0,%1,%2,%3},[%4];" : "=r"(v.x), "=r"(v.y), "=r"(v.z), "=r"(v.w) : "r"(a) : "memory"); return v; }
__device__ __forceinline__ float4 lds128f(uint32_t a) { float4 v; asm volatile("ld.shared.v4.f32 {%0,%1,%2,%3},[%4];" : "=f"(v.x), "=f"(v.y), "=f"(v.z), "=f"(v.w) : "r"(a) : "memory"); return v; }
__device__ __forceinline__ void st_async2(uint32_t a, float x, float y, uint32_t bar) {
  asm volatile("st.async.weak.shared::cluster.mbarrier::complete_tx::bytes.v2.f32 [%0],{%1,%2},[%3];" ::"r"(a), "f"(x), "f"(y), "r"(bar) : "memory");
}
__device__ __forceinline__ void st_async4(uint32_t a, const float (&v)[4], uint32_t bar) {
  asm volatile("st.async.weak.shared::cluster.mbarrier::complete_tx::bytes.v4.f32 [%0],{%1,%2,%3,%4},[%5];" ::"r"(a), "f"(v[0]), "f"(v[1]), "f"(v[2]), "f"(v[3]), "r"(bar) : "memory");
}
__device__ __forceinline__ void st_async4v(uint32_t a, float x, float y, float z, float w, uint32_t bar) {
  asm volatile("st.async.weak.shared::cluster.mbarrier::complete_tx::bytes.v4.f32 [%0],{%1,%2,%3,%4},[%5];" ::"r"(a), "f"(x), "f"(y), "f"(z), "f"(w), "r"(bar) : "memory");
}
__device__ __forceinline__ void st_async4u(uint32_t a, const uint4& v, uint32_t bar) {
  asm volatile("st.async.weak.shared::cluster.mbarrier::complete_tx::bytes.v4.b32 [%0],{%1,%2,%3,%4},[%5];" ::"r"(a), "r"(v.x), "r"(v.y), "r"(v.z), "r"(v.w), "r"(bar) : "memory");
}
__device__ __forceinline__ uint4 ld_relaxed4(const void* p) {
  uint4 v; asm volatile("ld.relaxed.gpu.global.v4.u32 {%0,%1,%2,%3},[%4];" : "=r"(v.x), "=r"(v.y), "=r"(v.z), "=r"(v.w) : "l"(p) : "memory"); return v;
}
__device__ __forceinline__ uint32_t ld_relaxed(const void* p) {
  uint32_t v; asm volatile("ld.relaxed.gpu.global.u32 %0,[%1];" : "=r"(v) : "l"(p) : "memory"); return v;
}
__device__ __forceinline__ void st_relaxed(void* p, uint32_t v) { asm volatile("st.relaxed.gpu.global.b32 [%0],%1;" ::"l"(p), "r"(v) : "memory"); }
__device__ __forceinline__ void st_relaxed4(void* p, uint32_t v) { asm volatile("st.relaxed.gpu.global.v4.b32 [%0],{%1,%1,%1,%1};" ::"l"(p), "r"(v) : "memory"); }

__device__ __forceinline__ uint32_t ld_acquire(const void* p) {
  uint32_t v; asm volatile("ld.acquire.gpu.global.u32 %0,[%1];" : "=r"(v) : "l"(p) : "memory"); return v;
}
__device__ __forceinline__ float4 ld_relaxed4f(const void* p) {
  float4 v; asm volatile("ld.relaxed.gpu.global.v4.f32 {%0,%1,%2,%3},[%4];" : "=f"(v.x), "=f"(v.y), "=f"(v.z), "=f"(v.w) : "l"(p) : "memory"); return v;
}
__device__ __forceinline__ float2 ld_relaxed2f(const void* p) {
  float2 v; asm volatile("ld.relaxed.gpu.global.v2.f32 {%0,%1},[%2];" : "=f"(v.x), "=f"(v.y) : "l"(p) : "memory"); return v;
}
__device__ __forceinline__ void prefetch_l2(const void* p) { asm volatile("prefetch.global.L2 [%0];" ::"l"(p)); }
__device__ __forceinline__ void fence_gpu() { asm volatile("fence.acq_rel.gpu;" ::: "memory"); }
#define FAG 1
__device__ __forceinline__ void fence_async_all() {
  asm volatile("fence.proxy.async.global;" ::: "memory");
}
__device__ __forceinline__ uint32_t* cnt_ptr(int kind, int layer, int b) { return &g_cnt[kind][layer][b][0]; }
#define RELS 1
__device__ __forceinline__ void cnt_signal(int kind, int layer, int b) {
  asm volatile("red.release.gpu.global.add.u32 [%0],1;" ::"l"(cnt_ptr(kind, layer, b)) : "memory");
}
#define ACQW 1
#define SIGF 1
#define HOIST 2
__device__ __forceinline__ void cnt_wait(int kind, int layer, int b, uint32_t target, int& dead) {
  int n = dead ? SPIN_CNT : 0;
  while (ld_acquire(cnt_ptr(kind, layer, b)) < target) { if (++n > SPIN_CNT) { dead = 1; g_err = 10 + kind; break; } }
}

__device__ __forceinline__ uint64_t mkdesc(uint32_t addr, uint32_t lbo, uint32_t sbo) {
  return (uint64_t)((addr & 0x3FFFF) >> 4) | ((uint64_t)(lbo >> 4) << 16) | ((uint64_t)(sbo >> 4) << 32) | ((uint64_t)1 << 62);
}
__device__ __forceinline__ uint64_t mkdesc_ns(uint32_t addr, uint32_t lbo, uint32_t sbo) {
  return (uint64_t)((addr & 0x3FFFF) >> 4) | ((uint64_t)(lbo >> 4) << 16) | ((uint64_t)(sbo >> 4) << 32);
}
__device__ __forceinline__ void wg_fence() { asm volatile("wgmma.fence.sync.aligned;" ::: "memory"); }
__device__ __forceinline__ void wg_commit() { asm volatile("wgmma.commit_group.sync.aligned;" ::: "memory"); }
template <int N> __device__ __forceinline__ void wg_wait() { asm volatile("wgmma.wait_group.sync.aligned %0;" ::"n"(N) : "memory"); }

__device__ __forceinline__ void wgmma_rs16(float (&d)[8], const uint32_t (&a)[4], uint64_t db, int sc) {
  asm volatile("{.reg .pred p; setp.ne.b32 p,%13,0; wgmma.mma_async.sync.aligned.m64n16k16.f32.bf16.bf16 "
               "{%0,%1,%2,%3,%4,%5,%6,%7},{%8,%9,%10,%11},%12,p,1,1,0;}"
               : "+f"(d[0]), "+f"(d[1]), "+f"(d[2]), "+f"(d[3]), "+f"(d[4]), "+f"(d[5]), "+f"(d[6]), "+f"(d[7])
               : "r"(a[0]), "r"(a[1]), "r"(a[2]), "r"(a[3]), "l"(db), "r"(sc));
}
__device__ __forceinline__ void wgmma_rs64(float (&d)[32], const uint32_t (&a)[4], uint64_t db, int sc) {
  asm volatile("{.reg .pred p; setp.ne.b32 p,%37,0; wgmma.mma_async.sync.aligned.m64n64k16.f32.bf16.bf16 "
               "{%0,%1,%2,%3,%4,%5,%6,%7,%8,%9,%10,%11,%12,%13,%14,%15,%16,%17,%18,%19,%20,%21,%22,%23,%24,%25,%26,%27,%28,%29,%30,%31},{%32,%33,%34,%35},%36,p,1,1,0;}"
               : "+f"(d[0]), "+f"(d[1]), "+f"(d[2]), "+f"(d[3]), "+f"(d[4]), "+f"(d[5]), "+f"(d[6]), "+f"(d[7]), "+f"(d[8]), "+f"(d[9]), "+f"(d[10]), "+f"(d[11]), "+f"(d[12]), "+f"(d[13]), "+f"(d[14]), "+f"(d[15]), "+f"(d[16]), "+f"(d[17]), "+f"(d[18]), "+f"(d[19]), "+f"(d[20]), "+f"(d[21]), "+f"(d[22]), "+f"(d[23]), "+f"(d[24]), "+f"(d[25]), "+f"(d[26]), "+f"(d[27]), "+f"(d[28]), "+f"(d[29]), "+f"(d[30]), "+f"(d[31])
               : "r"(a[0]), "r"(a[1]), "r"(a[2]), "r"(a[3]), "l"(db), "r"(sc));
}
__device__ __forceinline__ void wgmma_rt16(float (&d)[8], const uint32_t (&a)[4], uint64_t db, int sc) {
  asm volatile("{.reg .pred p; setp.ne.b32 p,%13,0; wgmma.mma_async.sync.aligned.m64n16k16.f32.bf16.bf16 "
               "{%0,%1,%2,%3,%4,%5,%6,%7},{%8,%9,%10,%11},%12,p,1,1,1;}"
               : "+f"(d[0]), "+f"(d[1]), "+f"(d[2]), "+f"(d[3]), "+f"(d[4]), "+f"(d[5]), "+f"(d[6]), "+f"(d[7])
               : "r"(a[0]), "r"(a[1]), "r"(a[2]), "r"(a[3]), "l"(db), "r"(sc));
}
__device__ __forceinline__ void wgmma_rt80(float (&d)[40], const uint32_t (&a)[4], uint64_t db, int sc) {
  asm volatile("{.reg .pred p; setp.ne.b32 p,%45,0; wgmma.mma_async.sync.aligned.m64n80k16.f32.bf16.bf16 "
               "{%0,%1,%2,%3,%4,%5,%6,%7,%8,%9,%10,%11,%12,%13,%14,%15,%16,%17,%18,%19,%20,%21,%22,%23,%24,%25,%26,%27,%28,%29,%30,%31,%32,%33,%34,%35,%36,%37,%38,%39},{%40,%41,%42,%43},%44,p,1,1,1;}"
               : "+f"(d[0]), "+f"(d[1]), "+f"(d[2]), "+f"(d[3]), "+f"(d[4]), "+f"(d[5]), "+f"(d[6]), "+f"(d[7]), "+f"(d[8]), "+f"(d[9]), "+f"(d[10]), "+f"(d[11]), "+f"(d[12]), "+f"(d[13]), "+f"(d[14]), "+f"(d[15]), "+f"(d[16]), "+f"(d[17]), "+f"(d[18]), "+f"(d[19]), "+f"(d[20]), "+f"(d[21]), "+f"(d[22]), "+f"(d[23]), "+f"(d[24]), "+f"(d[25]), "+f"(d[26]), "+f"(d[27]), "+f"(d[28]), "+f"(d[29]), "+f"(d[30]), "+f"(d[31]), "+f"(d[32]), "+f"(d[33]), "+f"(d[34]), "+f"(d[35]), "+f"(d[36]), "+f"(d[37]), "+f"(d[38]), "+f"(d[39])
               : "r"(a[0]), "r"(a[1]), "r"(a[2]), "r"(a[3]), "l"(db), "r"(sc));
}
__device__ __forceinline__ void wgmma_ts16(float (&d)[8], uint64_t da, uint64_t db, int sc) {
  asm volatile("{.reg .pred p; setp.ne.b32 p,%10,0; wgmma.mma_async.sync.aligned.m64n16k16.f32.bf16.bf16 "
               "{%0,%1,%2,%3,%4,%5,%6,%7},%8,%9,p,1,1,1,0;}"
               : "+f"(d[0]), "+f"(d[1]), "+f"(d[2]), "+f"(d[3]), "+f"(d[4]), "+f"(d[5]), "+f"(d[6]), "+f"(d[7])
               : "l"(da), "l"(db), "r"(sc));
}
__device__ __forceinline__ void wgmma_ts64(float (&d)[32], uint64_t da, uint64_t db, int sc) {
  asm volatile("{.reg .pred p; setp.ne.b32 p,%34,0; wgmma.mma_async.sync.aligned.m64n64k16.f32.bf16.bf16 "
               "{%0,%1,%2,%3,%4,%5,%6,%7,%8,%9,%10,%11,%12,%13,%14,%15,%16,%17,%18,%19,%20,%21,%22,%23,%24,%25,%26,%27,%28,%29,%30,%31},%32,%33,p,1,1,1,0;}"
               : "+f"(d[0]), "+f"(d[1]), "+f"(d[2]), "+f"(d[3]), "+f"(d[4]), "+f"(d[5]), "+f"(d[6]), "+f"(d[7]), "+f"(d[8]), "+f"(d[9]), "+f"(d[10]), "+f"(d[11]), "+f"(d[12]), "+f"(d[13]), "+f"(d[14]), "+f"(d[15]), "+f"(d[16]), "+f"(d[17]), "+f"(d[18]), "+f"(d[19]), "+f"(d[20]), "+f"(d[21]), "+f"(d[22]), "+f"(d[23]), "+f"(d[24]), "+f"(d[25]), "+f"(d[26]), "+f"(d[27]), "+f"(d[28]), "+f"(d[29]), "+f"(d[30]), "+f"(d[31])
               : "l"(da), "l"(db), "r"(sc));
}
__device__ __forceinline__ void wgmma_tt16(float (&d)[8], uint64_t da, uint64_t db, int sc) {
  asm volatile("{.reg .pred p; setp.ne.b32 p,%10,0; wgmma.mma_async.sync.aligned.m64n16k16.f32.bf16.bf16 "
               "{%0,%1,%2,%3,%4,%5,%6,%7},%8,%9,p,1,1,1,1;}"
               : "+f"(d[0]), "+f"(d[1]), "+f"(d[2]), "+f"(d[3]), "+f"(d[4]), "+f"(d[5]), "+f"(d[6]), "+f"(d[7])
               : "l"(da), "l"(db), "r"(sc));
}
__device__ __forceinline__ void wgmma_tt40(float (&d)[20], uint64_t da, uint64_t db, int sc) {
  asm volatile("{.reg .pred p; setp.ne.b32 p,%22,0; wgmma.mma_async.sync.aligned.m64n40k16.f32.bf16.bf16 "
               "{%0,%1,%2,%3,%4,%5,%6,%7,%8,%9,%10,%11,%12,%13,%14,%15,%16,%17,%18,%19},%20,%21,p,1,1,1,1;}"
               : "+f"(d[0]), "+f"(d[1]), "+f"(d[2]), "+f"(d[3]), "+f"(d[4]), "+f"(d[5]), "+f"(d[6]), "+f"(d[7]), "+f"(d[8]), "+f"(d[9]), "+f"(d[10]), "+f"(d[11]), "+f"(d[12]), "+f"(d[13]), "+f"(d[14]), "+f"(d[15]), "+f"(d[16]), "+f"(d[17]), "+f"(d[18]), "+f"(d[19])
               : "l"(da), "l"(db), "r"(sc));
}
__device__ __forceinline__ void wgmma_ss8(float (&d)[4], uint64_t da, uint64_t db, int sc) {
  asm volatile("{.reg .pred p; setp.ne.b32 p,%6,0; wgmma.mma_async.sync.aligned.m64n8k16.f32.bf16.bf16 "
               "{%0,%1,%2,%3},%4,%5,p,1,1,0,0;}"
               : "+f"(d[0]), "+f"(d[1]), "+f"(d[2]), "+f"(d[3])
               : "l"(da), "l"(db), "r"(sc));
}
__device__ __forceinline__ void wgmma_ss32(float (&d)[16], uint64_t da, uint64_t db, int sc) {
  asm volatile("{.reg .pred p; setp.ne.b32 p,%18,0; wgmma.mma_async.sync.aligned.m64n32k16.f32.bf16.bf16 "
               "{%0,%1,%2,%3,%4,%5,%6,%7,%8,%9,%10,%11,%12,%13,%14,%15},%16,%17,p,1,1,0,0;}"
               : "+f"(d[0]), "+f"(d[1]), "+f"(d[2]), "+f"(d[3]), "+f"(d[4]), "+f"(d[5]), "+f"(d[6]), "+f"(d[7]), "+f"(d[8]), "+f"(d[9]), "+f"(d[10]), "+f"(d[11]), "+f"(d[12]), "+f"(d[13]), "+f"(d[14]), "+f"(d[15])
               : "l"(da), "l"(db), "r"(sc));
}
__device__ __forceinline__ void wgmma_st64(float (&d)[32], uint64_t da, uint64_t db, int sc) {
  asm volatile("{.reg .pred p; setp.ne.b32 p,%34,0; wgmma.mma_async.sync.aligned.m64n64k16.f32.bf16.bf16 "
               "{%0,%1,%2,%3,%4,%5,%6,%7,%8,%9,%10,%11,%12,%13,%14,%15,%16,%17,%18,%19,%20,%21,%22,%23,%24,%25,%26,%27,%28,%29,%30,%31},%32,%33,p,1,1,0,1;}"
               : "+f"(d[0]), "+f"(d[1]), "+f"(d[2]), "+f"(d[3]), "+f"(d[4]), "+f"(d[5]), "+f"(d[6]), "+f"(d[7]), "+f"(d[8]), "+f"(d[9]), "+f"(d[10]), "+f"(d[11]), "+f"(d[12]), "+f"(d[13]), "+f"(d[14]), "+f"(d[15]), "+f"(d[16]), "+f"(d[17]), "+f"(d[18]), "+f"(d[19]), "+f"(d[20]), "+f"(d[21]), "+f"(d[22]), "+f"(d[23]), "+f"(d[24]), "+f"(d[25]), "+f"(d[26]), "+f"(d[27]), "+f"(d[28]), "+f"(d[29]), "+f"(d[30]), "+f"(d[31])
               : "l"(da), "l"(db), "r"(sc));
}
__device__ __forceinline__ void wgmma_st128(float (&d)[64], uint64_t da, uint64_t db, int sc) {
  asm volatile("{.reg .pred p; setp.ne.b32 p,%66,0; wgmma.mma_async.sync.aligned.m64n128k16.f32.bf16.bf16 "
               "{%0,%1,%2,%3,%4,%5,%6,%7,%8,%9,%10,%11,%12,%13,%14,%15,%16,%17,%18,%19,%20,%21,%22,%23,%24,%25,%26,%27,%28,%29,%30,%31,%32,%33,%34,%35,%36,%37,%38,%39,%40,%41,%42,%43,%44,%45,%46,%47,%48,%49,%50,%51,%52,%53,%54,%55,%56,%57,%58,%59,%60,%61,%62,%63},%64,%65,p,1,1,0,1;}"
               : "+f"(d[0]), "+f"(d[1]), "+f"(d[2]), "+f"(d[3]), "+f"(d[4]), "+f"(d[5]), "+f"(d[6]), "+f"(d[7]), "+f"(d[8]), "+f"(d[9]), "+f"(d[10]), "+f"(d[11]), "+f"(d[12]), "+f"(d[13]), "+f"(d[14]), "+f"(d[15]), "+f"(d[16]), "+f"(d[17]), "+f"(d[18]), "+f"(d[19]), "+f"(d[20]), "+f"(d[21]), "+f"(d[22]), "+f"(d[23]), "+f"(d[24]), "+f"(d[25]), "+f"(d[26]), "+f"(d[27]), "+f"(d[28]), "+f"(d[29]), "+f"(d[30]), "+f"(d[31]), "+f"(d[32]), "+f"(d[33]), "+f"(d[34]), "+f"(d[35]), "+f"(d[36]), "+f"(d[37]), "+f"(d[38]), "+f"(d[39]), "+f"(d[40]), "+f"(d[41]), "+f"(d[42]), "+f"(d[43]), "+f"(d[44]), "+f"(d[45]), "+f"(d[46]), "+f"(d[47]), "+f"(d[48]), "+f"(d[49]), "+f"(d[50]), "+f"(d[51]), "+f"(d[52]), "+f"(d[53]), "+f"(d[54]), "+f"(d[55]), "+f"(d[56]), "+f"(d[57]), "+f"(d[58]), "+f"(d[59]), "+f"(d[60]), "+f"(d[61]), "+f"(d[62]), "+f"(d[63])
               : "l"(da), "l"(db), "r"(sc));
}

__device__ __forceinline__ void stsm4(uint32_t a, uint32_t r0, uint32_t r1, uint32_t r2, uint32_t r3) {
  asm volatile("stmatrix.sync.aligned.m8n8.x4.shared.b16 [%0],{%1,%2,%3,%4};" ::"r"(a), "r"(r0), "r"(r1), "r"(r2), "r"(r3) : "memory");
}
__device__ __forceinline__ void stsm4t(uint32_t a, uint32_t r0, uint32_t r1, uint32_t r2, uint32_t r3) {
  asm volatile("stmatrix.sync.aligned.m8n8.x4.trans.shared.b16 [%0],{%1,%2,%3,%4};" ::"r"(a), "r"(r0), "r"(r1), "r"(r2), "r"(r3) : "memory");
}
__device__ __forceinline__ void sts64(uint32_t a, uint32_t x, uint32_t y) { asm volatile("st.shared.v2.b32 [%0],{%1,%2};" ::"r"(a), "r"(x), "r"(y) : "memory"); }
__device__ __forceinline__ void st_async2u(uint32_t a, uint32_t x, uint32_t y, uint32_t bar) {
  asm volatile("st.async.weak.shared::cluster.mbarrier::complete_tx::bytes.v2.b32 [%0],{%1,%2},[%3];" ::"r"(a), "r"(x), "r"(y), "r"(bar) : "memory");
}
__device__ __forceinline__ void st_relaxed128(void* p, uint32_t x, uint32_t y, uint32_t z, uint32_t w) {
  asm volatile("{.reg .b128 v; .reg .b64 lo, hi; mov.b64 lo,{%1,%2}; mov.b64 hi,{%3,%4}; mov.b128 v,{lo,hi}; st.relaxed.gpu.global.b128 [%0],v;}" ::"l"(p), "r"(x), "r"(y), "r"(z), "r"(w) : "memory");
}
__device__ __forceinline__ uint4 ld_relaxed128(const void* p) {
  uint4 v;
  asm volatile("{.reg .b128 v; .reg .b64 lo, hi; ld.relaxed.gpu.global.b128 v,[%4]; mov.b128 {lo,hi},v; mov.b64 {%0,%1},lo; mov.b64 {%2,%3},hi;}" : "=r"(v.x), "=r"(v.y), "=r"(v.z), "=r"(v.w) : "l"(p) : "memory");
  return v;
}

__device__ __forceinline__ uint32_t pack_h2(float lo, float hi) {
  uint32_t r; asm("cvt.rn.satfinite.f16x2.f32 %0,%1,%2;" : "=r"(r) : "f"(hi), "f"(lo)); return r;
}
__device__ __forceinline__ void add_h2(float& lo, float& hi, uint32_t u, uint32_t v) {
  float a, b, c, d;
  asm("{.reg .b16 l, h; mov.b32 {l,h},%2; cvt.f32.f16 %0,l; cvt.f32.f16 %1,h;}" : "=f"(a), "=f"(b) : "r"(u));
  asm("{.reg .b16 l, h; mov.b32 {l,h},%2; cvt.f32.f16 %0,l; cvt.f32.f16 %1,h;}" : "=f"(c), "=f"(d) : "r"(v));
  lo += a + c; hi += b + d;
}
__device__ __forceinline__ void st_async1u(uint32_t a, uint32_t x, uint32_t bar) {
  asm volatile("st.async.weak.shared::cluster.mbarrier::complete_tx::bytes.b32 [%0],%1,[%2];" ::"r"(a), "r"(x), "r"(bar) : "memory");
}
__device__ __forceinline__ uint32_t lds32(uint32_t a) { uint32_t v; asm volatile("ld.shared.b32 %0,[%1];" : "=r"(v) : "r"(a) : "memory"); return v; }
__device__ __forceinline__ uint2 lds64(uint32_t a) { uint2 v; asm volatile("ld.shared.v2.b32 {%0,%1},[%2];" : "=r"(v.x), "=r"(v.y) : "r"(a) : "memory"); return v; }

__device__ __forceinline__ void ln_row_to_image(const bf16* __restrict__ x, uint8_t* __restrict__ img, int row, int lane) {
  const uint4* src = reinterpret_cast<const uint4*>(x + (size_t)row * DM);
  uint4 v[3];
  v[0] = src[lane]; v[1] = src[lane + 32];
  v[2] = lane < 16 ? src[lane + 64] : make_uint4(0, 0, 0, 0);
  float s = 0.f;
#pragma unroll
  for (int i = 0; i < 3; i++) {
    s += bf_lo(v[i].x) + bf_hi(v[i].x) + bf_lo(v[i].y) + bf_hi(v[i].y) + bf_lo(v[i].z) + bf_hi(v[i].z) + bf_lo(v[i].w) + bf_hi(v[i].w);
  }
#pragma unroll
  for (int o = 16; o > 0; o >>= 1) s += __shfl_xor_sync(0xffffffffu, s, o);
  const float mean = s * (1.f / DM);
  float q = 0.f;
#pragma unroll
  for (int i = 0; i < 3; i++) {
    if (i < 2 || lane < 16) {
      const uint32_t w[4] = {v[i].x, v[i].y, v[i].z, v[i].w};
#pragma unroll
      for (int j = 0; j < 4; j++) { float a = bf_lo(w[j]) - mean, b = bf_hi(w[j]) - mean; q += a * a + b * b; }
    }
  }
#pragma unroll
  for (int o = 16; o > 0; o >>= 1) q += __shfl_xor_sync(0xffffffffu, q, o);
  const float rstd = rsqrtf(q * (1.f / DM) + 1e-5f);
#pragma unroll
  for (int i = 0; i < 3; i++) {
    if (i < 2 || lane < 16) {
      const int c = lane + 32 * i;
      uint4 o;
      o.x = pack_bf16((bf_lo(v[i].x) - mean) * rstd, (bf_hi(v[i].x) - mean) * rstd);
      o.y = pack_bf16((bf_lo(v[i].y) - mean) * rstd, (bf_hi(v[i].y) - mean) * rstd);
      o.z = pack_bf16((bf_lo(v[i].z) - mean) * rstd, (bf_hi(v[i].z) - mean) * rstd);
      o.w = pack_bf16((bf_lo(v[i].w) - mean) * rstd, (bf_hi(v[i].w) - mean) * rstd);
      const size_t off = (size_t)(row >> 5) * 40960 + (c >> 4) * 8192 + ((row >> 3) & 3) * 2048 + ((c >> 3) & 1) * 1024 + (row & 7) * 128 + (((c & 7) ^ (row & 7)) << 4);
      *reinterpret_cast<uint4*>(img + off) = o;
    }
  }
}

#define LN30 1
__global__ void __launch_bounds__(256) k_pre(const bf16* __restrict__ x, const bf16* __restrict__ mem0) {
  const int row = blockIdx.x * 8 + (threadIdx.x >> 5);
  ln_row_to_image(x, g_xn[0], row, threadIdx.x & 31);
  const int gt = blockIdx.x * 256 + threadIdx.x;
  const uint4 sent = make_uint4(SENT, SENT, SENT, SENT);
  uint4* mail = reinterpret_cast<uint4*>(&g_mail[0][0]);
  for (int i = gt; i < 2 * MAIL_BYTES / 16; i += 65536) mail[i] = sent;
  uint4* mb = reinterpret_cast<uint4*>(&g_mbuf[0][0]);
  for (int i = gt; i < NSTEP * 1280; i += 65536) {
    const int p = i % 1280, st = i / 1280, r = (p >> 3) & 7;
    uint4 v = sent;
    if (st == 0 || (st == LAG && (p & 64))) v = *reinterpret_cast<const uint4*>(mem0 + r * DM + ((p >> 7) * 8 + ((p & 7) ^ r)) * 8);
    mb[i] = v;
  }
  if (gt < 16 * 128 * 8) reinterpret_cast<uint4*>(&g_stats[0][0][0])[gt] = sent;
  if (gt < 6 * 2 * 16 * 8) reinterpret_cast<uint4*>(&g_cnt[0][0][0][0])[gt] = make_uint4(0, 0, 0, 0);
}

namespace C {
constexpr int NKR = 37;
constexpr int OFF_WQ = 0, OFF_WK = 81920;
constexpr int OFF_YO = 163840, OFF_YV = OFF_YO + 6144;
constexpr int OFF_M = 176128;
constexpr int OFF_STG = OFF_M;
constexpr int OFF_OG = OFF_M + 14336;
constexpr int OFF_KT = 196608;
constexpr int OFF_XT = OFF_KT + 10240;
constexpr int OFF_VT = OFF_XT + 7168;
constexpr int OFF_XM = OFF_VT + 11392;
constexpr int KS = 1280, VS = 1408;
__host__ __device__ constexpr int slot_off(int p) { return p == 2 ? OFF_M : OFF_KT + (p % 3) * 16384; }
constexpr int OFF_BAR = 231552;
constexpr int OFF_SAFE = OFF_BAR + 160;
constexpr int OFF_TS = OFF_BAR + 256;
constexpr int SMEM = 232448;
constexpr uint32_t SB0 = 1024;
constexpr int BAR_F = OFF_BAR, BAR_E = OFF_BAR + 40, BAR_M = OFF_BAR + 80, BAR_MOK = OFF_BAR + 88, BAR_XM = OFF_BAR + 96, BAR_XF = OFF_BAR + 104,
              BAR_XT = OFF_BAR + 112, BAR_MF = OFF_BAR + 120, BAR_OG = OFF_BAR + 128, BAR_W = OFF_BAR + 136;
constexpr int NB_PRO = 1, NB_RD = 2, NB_MR = 3, NB_QK = 4, NB_SM = 5, NB_VA = 6, NB_VQ = 7, NB_A = 8, NB_Q = 9, NB_C = 10, NB_WO = 11, NB_QI = 12, NB_SI = 13;
#define B1 300
#define B2 300
#define VSP 8
#define RFK 5
#define PFD 3
#define NOWORK 0
constexpr float SCL = 0.07216878364870322f * 1.4426950408889634f / 64;
}

#define CBAR_SYNC(id, n) bar_sync(id, n)
#define CBAR_ARRIVE(id, n) bar_arrive(id, n)

__device__ __forceinline__ uint64_t wdesc(int off) { return mkdesc(C::SB0 + off, 8192, 1024); }
__device__ __forceinline__ uint64_t mdesc(int k) { return mkdesc(C::SB0 + C::OFF_M + (k >> 2) * 2048 + (k & 3) * 32, 16, 1024); }
__device__ __forceinline__ uint64_t tdesc(int k) { return mkdesc(C::SB0 + C::slot_off(k >> 3) + ((k >> 2) & 1) * 1024 + (k & 3) * 32, 16, 2048); }

__device__ __forceinline__ void load_weights_rs(uint32_t (&wf)[C::NKR][4], uint32_t sb, int stage, int yoff, int tid0) {
  using namespace C;
  const int i = (tid0 >> 3) & 3, r = tid0 & 7;
  const int chunk = 2 * ((tid0 >> 5) & 3) + (i & 1);
  const uint32_t a0 = sb + stage + (r + (i >> 1) * 8) * 128 + ((chunk ^ r) << 4);
#pragma unroll
  for (int k = 0; k < NKR; k++) ldsm4t(wf[k], a0 + k * 2048);
#pragma unroll
  for (int k = 0; k < 40 - NKR; k++) sts128(sb + yoff + k * 2048 + (tid0 & 127) * 16, lds128(sb + stage + (NKR + k) * 2048 + (tid0 & 127) * 16));
  fence_async();
  CBAR_SYNC(NB_PRO, 384);
}
template <int STRIDE>
__device__ __forceinline__ void store_mem(const float (&d)[8], uint32_t base, int tid) {
  const int m = (tid >> 3) & 3;
  stsm4(base + (((tid >> 5) & 3) * 2 + (m & 1)) * STRIDE + (m >> 1) * 640 + (tid & 7) * 16, pack_bf16(d[0], d[1]), pack_bf16(d[2], d[3]),
        pack_bf16(d[4], d[5]), pack_bf16(d[6], d[7]));
}

__device__ __forceinline__ void load_pair(uint32_t sb, int i, int p, uint32_t slot) {
  using namespace C;
  const uint8_t* s0 = g_xn[0] + (size_t)i * 40960 + p * 8192;
  const uint8_t* s1 = g_xn[NOWORK ? 0 : 1] + (size_t)(i - LAG) * 40960 + p * 8192;
  bulk_g2s_mc(sb + slot, i < NSEG ? s0 : s1, 8192, sb + BAR_F + 8 * p);
  bulk_g2s_mc(sb + slot + 8192, i >= LAG ? s1 : s0, 8192, sb + BAR_F + 8 * p);
}
__device__ __forceinline__ void first_fill(uint32_t sb, int i, int p, uint32_t slot, int& dead) {
  using namespace C;
  const int s1 = i - LAG;
  if (!NOWORK && s1 >= 0 && (s1 & 3) == 0) { cnt_wait(CN_X, 0, s1 >> 2, 5, dead); fence_async_all(); }
  if (i > 0) mbar_wait(sb + BAR_E + 8 * p, (i - 1) & 1, dead);
  load_pair(sb, i, p, slot);
}
__device__ __forceinline__ void release_round(uint32_t sb, int p, int tid) {
  using namespace C;
  const int lane = tid & 31;
  if (p < 2) { if (lane == 0) mbar_arrive_cluster(mapa(sb, p) + BAR_E + 8 * (3 + p)); }
  else if (lane < 3) mbar_arrive_cluster(mapa(sb, lane) + BAR_MOK);
}

template <int K0, int K1>
__device__ __forceinline__ void v_mem_pass(float (&d)[8], const uint32_t (&wf)[C::NKR][4]) {
  using namespace C;
  wg_fence();
#pragma unroll
  for (int k = K0; k < K1; k++) {
    if (k < NKR) wgmma_rs16(d, wf[k < NKR ? k : 0], mdesc(k), k);
    else wgmma_ts16(d, wdesc(OFF_YV + (k - NKR) * 2048), mdesc(k), 1);
  }
  wg_commit();
}
__device__ __forceinline__ void chain_v(const uint32_t sb, const int tid0, const int cta, const int rank) {
  using namespace C;
  asm volatile("setmaxnreg.inc.sync.aligned.u32 208;");
  int dead = 0;
  uint32_t wf[NKR][4];
  if (tid0 == 256 && rank < 2) first_fill(sb, 0, rank, OFF_KT + rank * 16384, dead);
  __syncwarp();
  mbar_wait(sb + BAR_W, 0, dead);
  load_weights_rs(wf, sb, OFF_WK, OFF_YV, tid0);
#pragma unroll 1
  for (int i = 0; i < NSTEP; i++) {
    {
      float d[32];
      if (i > 0) CBAR_SYNC(NB_WO, 384);
#pragma unroll
      for (int p = 0; p < 5; p++) {
        mbar_wait(sb + BAR_F + 8 * p, i & 1, dead);
        TS(i, 25 + p);
        wg_fence();
#pragma unroll
        for (int k = 8 * p; k < 8 * p + 8; k++) {
          if (k < NKR) wgmma_rs64(d, wf[k < NKR ? k : 0], tdesc(k), k);
          else wgmma_ts64(d, wdesc(OFF_YV + (k - NKR) * 2048), tdesc(k), 1);
          if (k == 8 * p + 1 && p >= 1 && p <= 3) {
            wg_commit(); wg_wait<1>();
            release_round(sb, p - 1, fresh(tid0));
            wg_fence();
          }
          if (k == 8 * p + RFK && (p == 1 || p == 2)) {
            wg_commit();
            if (rank == p - 1 && tid0 == 256) { mbar_wait(sb + BAR_E + 8 * (p + 2), i & 1, dead); load_pair(sb, i, p + 2, slot_off(p + 2)); }
            __syncwarp();
            wg_fence();
          }
        }
        wg_commit();
      }
      wg_wait<0>();
      TS(i, 23);
      CBAR_SYNC(NB_RD, 256);
      const int tid = fresh(tid0) & 127, m = (tid >> 3) & 3;
      if (tid >= 96) {
        if (tid < 101) { if (i + 1 < NSTEP) mbar_expect_tx(sb + BAR_F + 8 * (tid - 96), 16384); }
        else if (tid == 101) mbar_expect_tx(sb + BAR_XM, 2560);
        else if (tid == 102) mbar_expect_tx(sb + BAR_XT, 7168);
        else if (tid == 103) mbar_expect_tx(sb + BAR_OG, 4096);
        else if (tid < 106) mbar_arrive_cluster(mapa(sb, (rank + tid - 103) % 3) + BAR_XF);
        __syncwarp();
      }
      const uint32_t a = sb + OFF_VT + 256 + ((tid >> 5) * 2 + (m & 1)) * VS + (m >> 1) * 128 + (tid & 7) * 16;
#pragma unroll
      for (int s = 0; s < 4; s++)
        stsm4(a + (s & 1) * 256 + (s >> 1) * 640, pack_bf16(d[8 * s], d[8 * s + 1]), pack_bf16(d[8 * s + 2], d[8 * s + 3]),
              pack_bf16(d[8 * s + 4], d[8 * s + 5]), pack_bf16(d[8 * s + 6], d[8 * s + 7]));
      if (tid < 72) sts128(sb + OFF_VT + (tid >> 3) * VS + (tid & 7) * 16, make_uint4(0, 0, 0, 0));
      fence_async();
    }
    CBAR_ARRIVE(NB_QK, 384);
    CBAR_SYNC(NB_QI, 256);
    float d[8];
    v_mem_pass<0, VSP>(d, wf);
    CBAR_SYNC(NB_SM, 256);
    v_mem_pass<VSP, 40>(d, wf);
    wg_wait<0>();
    TS(i, 24);
    const int tid = fresh(tid0);
    if ((tid & 31) < 2) mbar_arrive_cluster(mapa(sb, (rank + 1 + (tid & 1)) % 3) + BAR_MF);
    store_mem<VS>(d, sb + OFF_VT + 128, tid);
    fence_async();
    CBAR_ARRIVE(NB_VA, 256);
    CBAR_ARRIVE(NB_VQ, 256);
    if (tid == 256) {
      if (rank < 2 && i + 1 < NSTEP) { first_fill(sb, i + 1, rank, OFF_KT + rank * 16384, dead); TS1(i + 1, 37); }
    } else if (tid >= 288 && tid < 294) {
      const int lane = tid & 31, ip = i + PFD;
      if (cta < 80 && ip < NSTEP) {
        if (lane < 2) prefetch_l2(g_mbuf[ip] + (cta * 2 + lane) * 128);
        else if (ip < NSEG) prefetch_l2(g_xn[0] + (size_t)ip * 40960 + (cta * 4 + lane - 2) * 128);
      }
    }
    TS_FLUSH(i - 1);
    __syncwarp();
  }
}

__device__ __forceinline__ float quad_max(float x) {
  const float a = __shfl_xor_sync(0xffffffffu, x, 1), b = __shfl_xor_sync(0xffffffffu, x, 2), c = __shfl_xor_sync(0xffffffffu, x, 3);
  return fmaxf(fmaxf(x, a), fmaxf(b, c));
}
__device__ __forceinline__ float quad_sum(float x) {
  const float a = __shfl_xor_sync(0xffffffffu, x, 1), b = __shfl_xor_sync(0xffffffffu, x, 2), c = __shfl_xor_sync(0xffffffffu, x, 3);
  return (x + a) + (b + c);
}
__device__ __forceinline__ float max10(const float (&y)[10]) {
  return fmaxf(fmaxf(fmaxf(fmaxf(y[0], y[1]), fmaxf(y[2], y[3])), fmaxf(fmaxf(y[4], y[5]), fmaxf(y[6], y[7]))), fmaxf(y[8], y[9]));
}
__device__ __forceinline__ float sum10(const float (&y)[10]) {
  return (((y[0] + y[1]) + (y[2] + y[3])) + ((y[4] + y[5]) + (y[6] + y[7]))) + (y[8] + y[9]);
}
__device__ __forceinline__ float rcp(float x) { float y; asm("rcp.approx.ftz.f32 %0,%1;" : "=f"(y) : "f"(x)); return y; }

__device__ __forceinline__ void signal_o(int i) {
  const int s1 = i - LAG;
  const bool e0 = i < NSEG && (i & 3) == 3, e1 = s1 >= 0 && (s1 & 3) == 3;
  if (e0 || e1) {
    asm volatile("cp.async.bulk.wait_group 0;" ::: "memory");
    fence_async_all();
    if (e0) cnt_signal(CN_O, 0, i >> 2);
    if (e1) cnt_signal(CN_O, 1, s1 >> 2);
  }
}

__device__ __forceinline__ void chain_q(const CUtensorMap& tmWq, const CUtensorMap& tmWk, const uint32_t sb, const int tid0, const int cta, const int rank) {
  using namespace C;
  asm volatile("setmaxnreg.dec.sync.aligned.u32 96;");
  int dead = 0;
  CBAR_SYNC(NB_PRO, 384);
  PTS(5);
  if (tid0 == 128) {
    const int col = (cta / 3) * DH + rank * 64;
    mbar_expect_tx(sb + BAR_W, 163840);
    for (int i = 0; i < 5; i++) {
      tma2d(sb + OFF_WQ + i * 16384, &tmWq, col, i * 128, sb + BAR_W);
      tma2d(sb + OFF_WK + i * 16384, &tmWk, col, i * 128, sb + BAR_W);
    }
  }
  mbar_wait(sb + BAR_W, 1, dead);
  PTS(6);
#pragma unroll 1
  for (int i = 0; i < NSTEP; i++) {
    const int ph = i & 1;
    uint32_t qf[4][4];
    {
      float d[64];
      if (i > 0) CBAR_SYNC(NB_WO, 384);
#pragma unroll
      for (int p = 0; p < 5; p++) {
        mbar_wait(sb + BAR_F + 8 * p, ph, dead);
        if (p == 0) TS(i, 0);
        wg_fence();
#pragma unroll
        for (int k = 8 * p; k < 8 * p + 8; k++) {
          wgmma_st128(d, tdesc(k), mkdesc(SB0 + OFF_WQ + k * 2048, OFF_WK - OFF_WQ, 1024), k);
          if (k == 8 * p + 1 && p >= 1 && p <= 3) {
            wg_commit(); wg_wait<1>();
            release_round(sb, p - 1, fresh(tid0));
            wg_fence();
          }
        }
        wg_commit();
        if (p == 0 && i > 0) { if (tid0 == 224) signal_o(i - 1); __syncwarp(); }
      }
      wg_wait<0>();
      TS(i, 1);
      CBAR_SYNC(NB_RD, 256);
      TSB(i, 2);
      const int tid = fresh(tid0), w = (tid >> 5) & 3, m = (tid >> 3) & 3;
      const uint32_t a = sb + OFF_KT + (m >> 1) * KS + (1 + 5 * (w >> 1) + 2 * (w & 1) + (m & 1)) * 128 + (tid & 7) * 16;
#pragma unroll
      for (int s = 0; s < 4; s++)
        stsm4t(a + s * 2 * KS, pack_bf16(d[32 + 8 * s], d[33 + 8 * s]), pack_bf16(d[34 + 8 * s], d[35 + 8 * s]),
               pack_bf16(d[36 + 8 * s], d[37 + 8 * s]), pack_bf16(d[38 + 8 * s], d[39 + 8 * s]));
#pragma unroll
      for (int kk = 0; kk < 4; kk++)
#pragma unroll
        for (int j = 0; j < 4; j++) asm volatile("cvt.rn.bf16x2.f32 %0,%1,%2;" : "=r"(qf[kk][j]) : "f"(d[8 * kk + 2 * j + 1]), "f"(d[8 * kk + 2 * j]));
    }
    CBAR_SYNC(NB_MR, 256);
    TSB(i, 3);
    {
      float dq[8], dk[8];
      wg_fence();
#pragma unroll
      for (int k = 0; k < 40; k++) wgmma_ts16(dq, wdesc(OFF_WQ + k * 2048), mdesc(k), k);
      wg_commit();
#pragma unroll
      for (int k = 0; k < 40; k++) wgmma_ts16(dk, wdesc(OFF_WK + k * 2048), mdesc(k), k);
      wg_commit();
      CBAR_ARRIVE(NB_QI, 256);
      wg_wait<1>();
      const int tid = fresh(tid0);
      store_mem<VS>(dq, sb + OFF_VT + 128, tid);
      wg_wait<0>();
      TS(i, 4);
      store_mem<KS>(dk, sb + OFF_KT, tid);
      fence_async();
    }
    CBAR_ARRIVE(NB_QK, 384);
    CBAR_SYNC(NB_SI, 256);
    uint32_t pf[5][4];
    float s0, s1;
    {
      float y0[10], y1[10];
      const int tid = fresh(tid0), lane = tid & 31, u = (tid >> 5) & 1;
      const bool c1 = tid & 64;
      {
        float x[40];
        wg_fence();
#pragma unroll
        for (int kk = 0; kk < 4; kk++) wgmma_rt80(x, qf[kk], mkdesc_ns(SB0 + OFF_KT + kk * 2 * KS, KS, 128), kk);
        wg_commit();
        mbar_wait(sb + BAR_XF, ph, dead);
        wg_wait<0>();
#pragma unroll
        for (int j = 0; j < 5; j++) {
          y0[2 * j] = (c1 ? x[20 + 4 * j] : x[4 * j]) * SCL; y0[2 * j + 1] = (c1 ? x[21 + 4 * j] : x[4 * j + 1]) * SCL;
          y1[2 * j] = (c1 ? x[22 + 4 * j] : x[4 * j + 2]) * SCL; y1[2 * j + 1] = (c1 ? x[23 + 4 * j] : x[4 * j + 3]) * SCL;
        }
      }
      TS(i, 17);
      const uint32_t xo = OFF_XT + (c1 ? 1792 : 0) + u * 640 + lane * 16, x2 = xo + u * 512 + 512 - lane * 12;
      {
        const uint4 h0 = make_uint4(pack_h2(y0[0], y0[1]), pack_h2(y0[2], y0[3]), pack_h2(y1[0], y1[1]), pack_h2(y1[2], y1[3]));
        const uint4 h1 = make_uint4(pack_h2(y0[4], y0[5]), pack_h2(y0[6], y0[7]), pack_h2(y1[4], y1[5]), pack_h2(y1[6], y1[7]));
        const uint32_t h2 = u ? pack_h2(y1[8], y1[9]) : h1.z;
#pragma unroll
        for (int dd = 0; dd < 2; dd++) {
          const uint32_t rb = mapa(sb, (rank + 1 + dd) % 3), ro = rb + (1 - dd) * 3584;
          st_async4u(ro + xo, h0, rb + BAR_XT);
          if (u) st_async4u(ro + xo + 512, h1, rb + BAR_XT);
          st_async1u(ro + x2, h2, rb + BAR_XT);
        }
      }
      TS(i, 18);
      const int lim = 16 * u + (lane >> 2) + 8 - 2 * (lane & 3);
#pragma unroll
      for (int j = 1; j < 5; j++) {
        if (8 * j > lim) y0[2 * j] = -INFINITY;
        if (8 * j + 1 > lim) y0[2 * j + 1] = -INFINITY;
        if (8 * j - 8 > lim) y1[2 * j] = -INFINITY;
        if (8 * j - 7 > lim) y1[2 * j + 1] = -INFINITY;
      }
      mbar_wait(sb + BAR_XT, ph, dead);
      TS(i, 19);
      {
        const uint4 u0 = lds128(sb + xo), v0 = lds128(sb + xo + 3584);
        const uint32_t u2 = lds32(sb + x2), v2 = lds32(sb + x2 + 3584);
        uint4 u1 = make_uint4(0, 0, u2, 0), v1 = make_uint4(0, 0, v2, 0);
        if (u) { u1 = lds128(sb + xo + 512); v1 = lds128(sb + xo + 512 + 3584); }
        add_h2(y0[0], y0[1], u0.x, v0.x); add_h2(y0[2], y0[3], u0.y, v0.y); add_h2(y1[0], y1[1], u0.z, v0.z); add_h2(y1[2], y1[3], u0.w, v0.w);
        add_h2(y0[4], y0[5], u1.x, v1.x); add_h2(y0[6], y0[7], u1.y, v1.y); add_h2(y1[4], y1[5], u1.z, v1.z); add_h2(y1[6], y1[7], u1.w, v1.w);
        add_h2(y1[8], y1[9], u2, v2);
      }
      const float m0 = quad_max(max10(y0)) * -64.f, m1 = quad_max(max10(y1)) * -64.f;
      if (lane == 0) mbar_arrive_cluster(mapa(sb, 0) + BAR_E);
      s0 = 0.f; s1 = 0.f;
#pragma unroll
      for (int j = 0; j < 5; j++) {
        const uint32_t p0 = j < 4 ? pack_bf16(ex2(fmaf(y0[2 * j], 64.f, m0)), ex2(fmaf(y0[2 * j + 1], 64.f, m0))) : 0u;
        const uint32_t p1 = pack_bf16(ex2(fmaf(y1[2 * j], 64.f, m1)), ex2(fmaf(y1[2 * j + 1], 64.f, m1)));
        s0 += bf_lo(p0) + bf_hi(p0); s1 += bf_lo(p1) + bf_hi(p1);
        pf[j >> 1][2 * (j & 1)] = c1 ? 0u : p0; pf[j >> 1][2 * (j & 1) + 1] = c1 ? 0u : p1;
        pf[(j + 5) >> 1][2 * ((j + 5) & 1)] = c1 ? p0 : 0u; pf[(j + 5) >> 1][2 * ((j + 5) & 1) + 1] = c1 ? p1 : 0u;
      }
    }
    CBAR_SYNC(NB_VQ, 256);
    TSB(i, 20);
    {
      float o[32];
      wg_fence();
#pragma unroll
      for (int q = 0; q < 5; q++) wgmma_rs64(o, pf[q], mkdesc_ns(SB0 + OFF_VT + 128 + q * 256, 128, VS), q);
      wg_commit();
      s0 = rcp(quad_sum(s0)); s1 = rcp(quad_sum(s1));
      wg_wait<0>();
      TS(i, 21);
      const int tid = fresh(tid0), m = (tid >> 3) & 3, r = tid & 7;
      if ((tid & 31) == 0) mbar_arrive_cluster(mapa(sb, 1) + BAR_E + 8);
      const uint32_t a = sb + OFF_STG + (((tid >> 5) & 3) * 16 + (m & 1) * 8 + r) * 128;
#pragma unroll
      for (int s = 0; s < 4; s++)
        stsm4(a + (((2 * s + (m >> 1)) ^ r) << 4), pack_bf16(o[8 * s] * s0, o[8 * s + 1] * s0), pack_bf16(o[8 * s + 2] * s1, o[8 * s + 3] * s1),
              pack_bf16(o[8 * s + 4] * s0, o[8 * s + 5] * s0), pack_bf16(o[8 * s + 6] * s1, o[8 * s + 7] * s1));
      fence_async();
      CBAR_SYNC(NB_Q, 128);
      if (tid == 224) {
        const int sg = i - LAG;
        if (i < NSEG) bulk_s2g(g_o[0] + ((size_t)(i >> 1) * 96 + cta) * 8192 + (i & 1) * 4096, sb + OFF_STG, 4096);
        if (sg >= 0) bulk_s2g(g_o[1] + ((size_t)(sg >> 1) * 96 + cta) * 8192 + (sg & 1) * 4096, sb + OFF_STG + 4096, 4096);
        asm volatile("cp.async.bulk.commit_group;" ::: "memory");
        asm volatile("cp.async.bulk.wait_group.read 0;" ::: "memory");
        mbar_arrive_cluster(mapa(sb, 2) + BAR_E + 16);
        TS1(i, 22);
      }
      __syncwarp();
    }
  }
  if (tid0 == 224) signal_o(NSTEP - 1);
}

template <int NL>
__device__ __forceinline__ void poll_add(const uint8_t* mb, uint32_t tag, float (&f)[8], int& n, int& dead) {
  uint4 x[NL];
#pragma unroll
  for (int i = 0; i < NL; i++) x[i] = ld_relaxed128(mb + i * 512);
  while (true) {
    bool bad = false;
#pragma unroll
    for (int i = 0; i < NL; i++)
      if ((x[i].x ^ tag) & 1) { bad = true; x[i] = ld_relaxed128(mb + i * 512); }
    n++;
    if (!__any_sync(0xffffffffu, bad)) break;
    if (n > SPIN_MAIL) { dead = 1; g_err = 4; break; }
  }
#pragma unroll
  for (int i = 0; i < NL; i++) {
    const uint32_t u[4] = {x[i].x, x[i].y, x[i].z, x[i].w};
#pragma unroll
    for (int j = 0; j < 4; j++) {
      if (i == 0) { f[2 * j] = bf_lo(u[j]); f[2 * j + 1] = bf_hi(u[j]); }
      else { f[2 * j] += bf_lo(u[j]); f[2 * j + 1] += bf_hi(u[j]); }
    }
  }
}

template <int B, int SLOT>
__device__ __forceinline__ void wo_block(float (&acc)[8], const uint32_t (&wf)[C::NKR][4]) {
  using namespace C;
#pragma unroll
  for (int kk = 0; kk < 4; kk++) {
    const int k = 4 * B + kk;
    const uint64_t db = mkdesc_ns(SB0 + OFF_OG + SLOT * 2048 + kk * 512, 256, 128);
    if (k < NKR) wgmma_rt16(acc, wf[k < NKR ? k : 0], db, SLOT | kk);
    else wgmma_tt16(acc, wdesc(OFF_YO + (k - NKR) * 2048), db, 1);
  }
}

__device__ __forceinline__ void chain_a(const uint32_t sb, const int tid0, const int cta, const int rank) {
  using namespace C;
  asm volatile("setmaxnreg.inc.sync.aligned.u32 200;");
  int dead = 0;
  uint32_t wf[NKR][4];
  mbar_wait(sb + BAR_W, 0, dead);
  for (int it = tid0; it < 2560; it += 128) {
    const int row = it >> 2, q = it & 3;
    const uint32_t base = sb + OFF_WQ + row * 128;
    const uint32_t a0 = base + (((2 * q) ^ (row & 7)) << 4), a1 = base + (((2 * q + 1) ^ (row & 7)) << 4);
    const uint4 u = lds128(a0), v = lds128(a1);
    sts128(a0, make_uint4(__byte_perm(u.x, u.y, 0x5410), __byte_perm(u.z, u.w, 0x5410), __byte_perm(v.x, v.y, 0x5410), __byte_perm(v.z, v.w, 0x5410)));
    sts128(a1, make_uint4(__byte_perm(u.x, u.y, 0x7632), __byte_perm(u.z, u.w, 0x7632), __byte_perm(v.x, v.y, 0x7632), __byte_perm(v.z, v.w, 0x7632)));
  }
  CBAR_SYNC(NB_A, 128);
  load_weights_rs(wf, sb, OFF_WQ, OFF_YO, tid0);
  uint32_t mph = 0;

#pragma unroll 1
  for (int i = -1; i < NSTEP; i++) {
    const int ph = i & 1;
    if (i >= 0) {
      CBAR_SYNC(NB_QK, 384);
      TSB(i, 5);
      {
        float x[20];
        wg_fence();
#pragma unroll
        for (int kk = 0; kk < 4; kk++) wgmma_tt40(x, mkdesc_ns(SB0 + OFF_VT + 128 + kk * 2 * VS, VS, 640), mkdesc_ns(SB0 + OFF_KT + kk * 2 * KS, KS, 128), kk);
#pragma unroll
        for (int kk = 0; kk < 4; kk++) wgmma_tt40(x, mkdesc_ns(SB0 + OFF_VT + kk * 2 * VS, VS, 384), mkdesc_ns(SB0 + OFF_KT + 640 + kk * 2 * KS, KS, 128), 1);
        wg_commit();
        CBAR_ARRIVE(NB_SI, 256);
        const int tid = fresh(tid0), lane = tid & 31, w = tid >> 5;
        const uint32_t xo = OFF_XM + w * 1280 + lane * 16;
        if (w < 2) mbar_wait(sb + BAR_XF, ph, dead);
        wg_wait<0>();
        TS(i, 6);
        float y[10];
#pragma unroll
        for (int j = 0; j < 5; j++) { y[2 * j] = x[4 * j] * SCL; y[2 * j + 1] = x[4 * j + 1] * SCL; }
        if (w < 2) {
          const uint4 h0 = make_uint4(pack_h2(y[0], y[1]), pack_h2(y[2], y[3]), pack_h2(y[4], y[5]), pack_h2(y[6], y[7]));
          const uint32_t h1 = pack_h2(y[8], y[9]);
#pragma unroll
          for (int dd = 0; dd < 2; dd++) {
            const uint32_t rb = mapa(sb, (rank + 1 + dd) % 3), o = rb + xo + (1 - dd) * 640;
            st_async4u(o, h0, rb + BAR_XM);
            st_async1u(o + 512 - lane * 12, h1, rb + BAR_XM);
          }
        }
        CBAR_ARRIVE(NB_SM, 256);
        if (lane == 0) mbar_arrive_cluster(mapa(sb, 0) + BAR_E);
        TS(i, 7);
        if (w < 2) {
          const uint32_t pa = sb + xo - lane * 12;
          mbar_wait(sb + BAR_XM, ph, dead);
          TS(i, 8);
          const uint4 u0 = lds128(sb + xo), v0 = lds128(sb + xo + 640);
          const uint32_t u1 = lds32(pa + 512), v1 = lds32(pa + 1152);
          add_h2(y[0], y[1], u0.x, v0.x); add_h2(y[2], y[3], u0.y, v0.y); add_h2(y[4], y[5], u0.z, v0.z); add_h2(y[6], y[7], u0.w, v0.w);
          add_h2(y[8], y[9], u1, v1);
          const float mx = quad_max(max10(y)) * -64.f;
#pragma unroll
          for (int j = 0; j < 10; j++) y[j] = ex2(fmaf(y[j], 64.f, mx));
          const float inv = rcp(quad_sum(sum10(y)));
          __syncwarp();
          sts32(pa + 640, 0);
#pragma unroll
          for (int j = 0; j < 5; j++) sts32(pa + j * 128, pack_bf16(y[2 * j] * inv, y[2 * j + 1] * inv));
          fence_async();
          TS(i, 9);
        }
      }
      CBAR_SYNC(NB_VA, 256);
      TSB(i, 10);
      {
        float o[2][4];
        wg_fence();
#pragma unroll
        for (int c = 0; c < 2; c++)
#pragma unroll
          for (int q = 0; q < 3; q++)
            wgmma_ss8(o[c], mkdesc_ns(SB0 + OFF_VT + 128 + c * 640 + q * 256, 128, VS), mkdesc_ns(SB0 + OFF_XM + c * 1280 + q * 256, 128, 128), q);
        wg_commit();
        const int tid = fresh(tid0);
        const uint32_t oo = fresh(OFF_OG + (tid >> 5) * 512 + (tid & 2) * 64 + ((tid & 31) >> 2) * 16 + (tid & 1) * 8);
        mbar_wait(sb + BAR_MF, ph, dead);
        wg_wait<0>();
        TS(i, 11);
        const uint32_t p0 = pack_bf16(o[0][0], o[0][1]), p1 = pack_bf16(o[1][0], o[1][1]), p2 = pack_bf16(o[0][2], o[0][3]), p3 = pack_bf16(o[1][2], o[1][3]);
        sts64(sb + oo, p0, p1); sts64(sb + oo + 256, p2, p3);
        fence_async();
#pragma unroll
        for (int dd = 0; dd < 2; dd++) {
          const uint32_t rb = mapa(sb, (rank + 1 + dd) % 3);
          st_async2u(rb + oo + (2 - dd) * 2048, p0, p1, rb + BAR_OG);
          st_async2u(rb + oo + (2 - dd) * 2048 + 256, p2, p3, rb + BAR_OG);
        }
        if ((tid & 31) == 0) mbar_arrive_cluster(mapa(sb, 1) + BAR_E + 8);
      }
      if (i + 1 >= NSTEP) { mbar_wait(sb + BAR_OG, ph, dead); break; }
      CBAR_SYNC(NB_A, 128);
      TSB(i, 12);
      {
        float acc[3][8];
        wg_fence();
        wo_block<0, 0>(acc[2], wf);
        wg_commit();
        wo_block<1, 0>(acc[0], wf);
        wo_block<4, 0>(acc[1], wf);
        wg_commit();
        const int tid = fresh(tid0), w = tid >> 5, g = (tid & 31) >> 2, t = tid & 3;
        const uint32_t tag = (i >> 1) & 1, radd = tag ? 0u : 0x10000u;
#define SEND(PTR, U)                                                                                                                        \
  st_relaxed128((PTR), __byte_perm(((__float_as_uint(acc[U][0]) + radd) & 0xFFFE0000u) | (tag << 16), pack_bf16(0.f, acc[U][2]), 0x7632), \
                pack_bf16(acc[U][1], acc[U][3]), pack_bf16(acc[U][4], acc[U][6]), pack_bf16(acc[U][5], acc[U][7]))
        wg_wait<1>();
        SEND(g_mail[ph] + MAIL9 + (w * 16 + t * 4 + (g >> 1)) * 3072 + cta * 32 + (g & 1) * 16, 2);
        wg_fence();
        wo_block<7, 0>(acc[2], wf);
        wg_commit();
        uint8_t* mb = g_mail[ph] + ((rank * 12 + w) * 8 + t * 2 + (g >> 2)) * 2048 + (cta / 3) * 64 + (g & 3) * 16;
        mbar_wait(sb + BAR_OG, ph, dead);
        fence_async();
        TS(i, 13);
        wg_fence();
        wo_block<2, 1>(acc[0], wf); wo_block<3, 2>(acc[0], wf);
        wg_commit();
        wo_block<5, 1>(acc[1], wf); wo_block<6, 2>(acc[1], wf);
        wg_commit();
        wg_wait<1>(); SEND(mb, 0);
        wg_fence();
        wo_block<8, 1>(acc[2], wf); wo_block<9, 2>(acc[2], wf);
        wg_commit();
        CBAR_ARRIVE(NB_WO, 384);
        wg_wait<1>(); SEND(mb + 32 * 2048, 1);
        wg_wait<0>(); SEND(mb + 64 * 2048, 2);
#undef SEND
        if ((tid & 31) == 0) mbar_arrive_cluster(mapa(sb, 2) + BAR_E + 16);
      }
      TS(i, 14);
    }
    const uint32_t t0 = clk32();
    if (rank == 2) {
      if (tid0 == 96) { first_fill(sb, i + 1, 2, OFF_M, dead); TS1(i + 1, 37); }
      __syncwarp();
    }
    if (i >= 0) {
      if (cta < 88) {
        const int tid = fresh(tid0), lane = tid & 31;
        const uint32_t tag = (i >> 1) & 1;
        float f[8];
        int n = dead ? SPIN_MAIL : 0;
        if (cta < 72) {
          while (clk32() - t0 < B1) {}
          TS(i + 1, 30);
          poll_add<4>(g_mail[ph] + cta * 8192 + (tid >> 5) * 2048 + lane * 16, tag, f, n, dead);
        } else {
          poll_add<6>(g_mail[ph] + MAIL9 + (cta - 72) * 12288 + (tid >> 5) * 3072 + lane * 16, tag, f, n, dead);
        }
        TS(i + 1, 31); TSV(i + 1, 32, n);
        const bool h = lane & 16, q = lane & 8;
#pragma unroll
        for (int j = 0; j < 4; j++) f[j] = (h ? f[4 + j] : f[j]) + __shfl_xor_sync(0xffffffffu, h ? f[j] : f[4 + j], 16);
#pragma unroll
        for (int j = 0; j < 2; j++) f[j] = (q ? f[2 + j] : f[j]) + __shfl_xor_sync(0xffffffffu, q ? f[j] : f[2 + j], 8);
        f[0] += __shfl_xor_sync(0xffffffffu, f[0], 4); f[1] += __shfl_xor_sync(0xffffffffu, f[1], 4);
        int T, w, t, g;
        if (cta < 72) {
          const int part = cta * 4 + (tid >> 5);
          T = part >> 5; w = (part >> 3) & 3; t = (part >> 1) & 3; g = (part & 1) * 4 + (lane & 3);
        } else {
          f[0] += __shfl_xor_sync(0xffffffffu, f[0], 2); f[1] += __shfl_xor_sync(0xffffffffu, f[1], 2);
          const int part = (cta - 72) * 4 + (tid >> 5);
          T = 9; w = part >> 4; t = (part >> 2) & 3; g = (part & 3) * 2 + (lane & 1);
        }
        const int row = (lane >> 4) * 4 + (t & 2) + ((lane >> 3) & 1);
        if ((lane & (cta < 72 ? 4 : 6)) == 0 && !((t & 1) && i + 1 == LAG))
          st_relaxed(g_mbuf[i + 1] + T * 2048 + (t & 1) * 1024 + row * 128 + (((2 * w + (g >> 2)) ^ row) << 4) + (g & 3) * 4, pack_bf16(f[0], f[1]));
        TS(i + 1, 15);
        const uint32_t t1 = clk32();
        while (clk32() - t1 < B2) {}
      } else {
        while (clk32() - t0 < B1 + B2 + 600) {}
      }
    }
    {
      const int tid = fresh(tid0);
      int n = dead ? SPIN_MAIL : 0;
      if (tid == 0) {
        mbar_expect_tx(sb + BAR_M, 20480);
        mbar_wait(sb + BAR_MOK, ph ^ 1, dead);
        TS1(i + 1, 33);
        const int o = rank * 6784 + (rank ? 128 : 0);
        bulk_g2s_mc(sb + OFF_M + o, g_mbuf[i + 1] + o, rank ? 6784 : 6912, sb + BAR_M);
      }
      while (true) {
        mbar_wait(sb + BAR_M, mph & 1, dead);
        mph ^= 1;
        if (n == 0) TS(i + 1, 34);
        bool bad = false;
#pragma unroll
        for (int k = 0; k < 10; k++) {
          const uint4 v = lds128(sb + OFF_M + tid * 16 + k * 2048);
          bad |= v.x == SENT || v.y == SENT || v.z == SENT || v.w == SENT;
        }
        n++;
        if (!bar_red_or(NB_C, 128, bad && n <= SPIN_MAIL)) break;
        if (tid == 0) { mbar_expect_tx(sb + BAR_M, 20480); bulk_g2s(sb + OFF_M, g_mbuf[i + 1], 20480, sb + BAR_M); }
      }
      if (n > SPIN_MAIL) { dead = 1; g_err = 3; }
      CBAR_ARRIVE(NB_MR, 256);
      TS(i + 1, 35); TSV(i + 1, 36, n);
    }
  }
}

__global__ void __cluster_dims__(3, 1, 1) __launch_bounds__(384, 1)
k_chain(const __grid_constant__ CUtensorMap tmWq, const __grid_constant__ CUtensorMap tmWk,
        const __grid_constant__ CUtensorMap tmWv, const __grid_constant__ CUtensorMap tmWo) {
  using namespace C;
  extern __shared__ __align__(1024) uint8_t smem[];
  const uint32_t sb = smem_u32(smem);
  const int tid = threadIdx.x;
  const int wg = __shfl_sync(0xffffffffu, tid >> 7, 0);
  const int cta = blockIdx.x, rank = cta % 3;

  asm volatile("griddepcontrol.launch_dependents;");
  if (tid == 0) {
    if ((sb & 0xFFFFFF) != SB0) g_err = 100;
    for (int p = 0; p < 5; p++) { mbar_init(sb + BAR_F + 8 * p, 1); mbar_init(sb + BAR_E + 8 * p, p == 2 ? 15 : 24); }
    mbar_init(sb + BAR_M, 1); mbar_init(sb + BAR_MOK, 24); mbar_init(sb + BAR_XM, 1); mbar_init(sb + BAR_XF, 2);
    mbar_init(sb + BAR_XT, 1); mbar_init(sb + BAR_MF, 8); mbar_init(sb + BAR_OG, 1); mbar_init(sb + BAR_W, 1);
    for (int p = 0; p < 5; p++) mbar_expect_tx(sb + BAR_F + 8 * p, 16384);
    for (int p = 0; p < 16; p++) sts32(sb + OFF_SAFE + 4 * p, 0);
    asm volatile("fence.mbarrier_init.release.cluster;" ::: "memory");
    fence_async();
    mbar_expect_tx(sb + BAR_W, 163840);
    const int head = cta / 3, col = head * DH + rank * 64;
    tma2d(sb + OFF_WQ, &tmWo, 576, col, sb + BAR_W);
    for (int i = 0; i < 9; i++) tma2d(sb + OFF_WQ + (i + 1) * 8192, &tmWo, (3 * rank + i / 3) * 64, head * DH + ((rank + i) % 3) * 64, sb + BAR_W);
    for (int i = 0; i < 5; i++) tma2d(sb + OFF_WK + i * 16384, &tmWv, col, i * 128, sb + BAR_W);
  }
  __syncthreads();
  asm volatile("barrier.cluster.arrive.release.aligned;" ::: "memory");
  asm volatile("barrier.cluster.wait.acquire.aligned;" ::: "memory");

  if (wg == 0) chain_a(sb, tid, cta, rank);
  else if (wg == 1) chain_q(tmWq, tmWk, sb, tid, cta, rank);
  else chain_v(sb, tid, cta, rank);
  asm volatile("barrier.cluster.arrive.release.aligned;" ::: "memory");
  asm volatile("barrier.cluster.wait.acquire.aligned;" ::: "memory");
}

namespace W {
constexpr int NW = 36;
constexpr int NP = 30;
constexpr int OW0 = 31;
constexpr int PST = 3, PSTAGE = 32768;
constexpr int BST = 3, BSTAGE = 16384;
constexpr int OFF_P = 0;
constexpr int OFF_WQ = OFF_P + PST * PSTAGE;
constexpr int OFF_B = OFF_WQ + 81920;
constexpr int OFF_HIST = OFF_B + BST * BSTAGE;
constexpr int OFF_BAR = OFF_HIST + 2 * 14 * 80;
constexpr int SMEM = OFF_BAR + 128;
constexpr int BAR_PF = OFF_BAR, BAR_PE = OFF_BAR + 24, BAR_BF = OFF_BAR + 48, BAR_BE = OFF_BAR + 72;
constexpr int PITCH = 136;
constexpr int NB_P = 1, NB_B = 2;
}

struct WorkArgs {
  const bf16* res[2];
  bf16* xa[2];
  bf16* xb[2];
  const bf16* wqkv;
};

#define OHK 7
#define IMMREL 7
#define FOR_BATCHES(l, b)                                   \
  for (int j_ = 0; j_ < 2 * NSTEP; j_++) {                  \
    const int l = j_ & 1, s_ = (j_ >> 1) - (l ? LAG : 0);   \
    if (s_ < 0 || s_ >= NSEG || (s_ & 3) != 3) continue;    \
    const int b = s_ >> 2;

template <bool IS_O>
__device__ __forceinline__ void work_gemm_producer(const CUtensorMap& tm, const WorkArgs& a, uint32_t sb, int w) {
  using namespace W;
  constexpr int KCH = IS_O ? 10 : 96, NK = IS_O ? 10 : 16;
  int dead = 0, st = 0;
  uint32_t ph = 1;
  const int col = (IS_O ? w - OW0 : w % 5) * 128, k0 = IS_O ? 0 : (w / 5) * 16;
  FOR_BATCHES(l, b)
    const uint8_t* src = (IS_O ? g_ob[l] : g_o[l]) + ((size_t)(2 * b) * KCH + k0) * 8192;
#pragma unroll 1
    for (int kc = 0; kc < NK; kc++) {
      const uint32_t bar = sb + BAR_PF + 8 * st, d = sb + OFF_P + st * PSTAGE;
      mbar_wait(sb + BAR_PE + 8 * st, ph, dead);
      mbar_expect_tx(bar, PSTAGE);
      tma2d(d + 16384, &tm, col, (k0 + kc) * 64, bar);
      tma2d(d + 24576, &tm, col + 64, (k0 + kc) * 64, bar);
      if (kc >= PST) {
        bulk_g2s(d, src + (size_t)kc * 8192, 8192, bar);
        bulk_g2s(d + 8192, src + (size_t)(KCH + kc) * 8192, 8192, bar);
      }
      if (++st == PST) { st = 0; ph ^= 1; }
      if (kc == PST - 1) {
        cnt_wait(IS_O ? CN_A : CN_O, l, b, IS_O ? 32 : 96, dead);
        if (!IS_O && w == 0) WTS(l, b, 0);
        if (IS_O && w == 35) WTS(l, b, 3);
        fence_async_all();
#pragma unroll
        for (int i = 0; i < PST; i++) {
          const int s2 = (st + i) % PST;
          bulk_g2s(sb + OFF_P + s2 * PSTAGE, src + (size_t)i * 8192, 8192, sb + BAR_PF + 8 * s2);
          bulk_g2s(sb + OFF_P + s2 * PSTAGE + 8192, src + (size_t)(KCH + i) * 8192, 8192, sb + BAR_PF + 8 * s2);
        }
      }
    }
  }
}

__device__ __forceinline__ void quad_transpose(uint32_t* x, int t) {
  const bool h = t & 2, o = t & 1;
  uint32_t p = __shfl_xor_sync(0xffffffffu, h ? x[0] : x[2], 2), q = __shfl_xor_sync(0xffffffffu, h ? x[1] : x[3], 2);
  const uint32_t y0 = h ? p : x[0], y1 = h ? q : x[1], y2 = h ? x[2] : p, y3 = h ? x[3] : q;
  p = __shfl_xor_sync(0xffffffffu, o ? y0 : y1, 1); q = __shfl_xor_sync(0xffffffffu, o ? y2 : y3, 1);
  x[0] = o ? p : y0; x[1] = o ? y1 : p; x[2] = o ? q : y2; x[3] = o ? y3 : q;
}

template <bool IS_O>
__device__ __forceinline__ void work_gemm(const WorkArgs& a, uint32_t sb, int w, int tid0) {
  using namespace W;
  constexpr int NK = IS_O ? 10 : 16;
  int dead = 0, st = 0;
  uint32_t ph = 0;
  const int tile = IS_O ? w - OW0 : w % 5;
  bool first = true;
  FOR_BATCHES(l, b)
    float acc[64];
    uint32_t r0[16], r1[16];
    int prev = 0;
    if (IS_O) {
#pragma unroll
      for (int i = 0; i < 64; i++) acc[i] = 0.f;
    }
#pragma unroll 1
    for (int kc = 0; kc < NK; kc++) {
      mbar_wait(sb + BAR_PF + 8 * st, ph, dead);
      if (w == (IS_O ? 35 : WW) && tid0 == 0 && kc == 0) WTS(l, b, IS_O ? 16 : 5);
      const uint32_t pa = sb + OFF_P + st * PSTAGE + (tid0 >> 7) * 8192, pb = sb + OFF_P + st * PSTAGE + 16384;
      wg_fence();
#pragma unroll
      for (int kk = 0; kk < 4; kk++) wgmma_st128(acc, mkdesc(pa + kk * 32, 16, 1024), mkdesc(pb + kk * 2048, 8192, 1024), (kc | kk) != 0);
      wg_commit();
      if (IS_O && OHK >= 0 && kc == OHK) {
      const int tid = fresh(tid0), g = (tid & 31) >> 2, t = tid & 3;
      const bf16* rp = a.xa[l] + (size_t)(b * 128 + (tid >> 5) * 16 + g) * DM + tile * 128 + 8 * t;
#pragma unroll
      for (int m = 0; m < 4; m++) {
        const float4 c0 = ld_relaxed4f(rp + 32 * m), c1 = ld_relaxed4f(rp + 8 * DM + 32 * m);
        r0[4 * m] = __float_as_uint(c0.x); r0[4 * m + 1] = __float_as_uint(c0.y); r0[4 * m + 2] = __float_as_uint(c0.z); r0[4 * m + 3] = __float_as_uint(c0.w);
        r1[4 * m] = __float_as_uint(c1.x); r1[4 * m + 1] = __float_as_uint(c1.y); r1[4 * m + 2] = __float_as_uint(c1.z); r1[4 * m + 3] = __float_as_uint(c1.w);
      }
      }
      if (IMMREL & (IS_O ? 2 : 1)) {
        if (kc < NK - 1) {
          wg_wait<0>();
          if ((tid0 & 127) == 0) mbar_arrive(sb + BAR_PE + 8 * st);
        }
      } else if (kc > 0) {
        wg_wait<1>();
        if ((tid0 & 127) == 0) mbar_arrive(sb + BAR_PE + 8 * prev);
      }
      prev = st;
      if (++st == PST) { st = 0; ph ^= 1; }
    }
    if (IS_O && OHK < 0) {
      const int tid = fresh(tid0), g = (tid & 31) >> 2, t = tid & 3;
      const bf16* rp = a.xa[l] + (size_t)(b * 128 + (tid >> 5) * 16 + g) * DM + tile * 128 + 8 * t;
#pragma unroll
      for (int m = 0; m < 4; m++) {
        const float4 c0 = ld_relaxed4f(rp + 32 * m), c1 = ld_relaxed4f(rp + 8 * DM + 32 * m);
        r0[4 * m] = __float_as_uint(c0.x); r0[4 * m + 1] = __float_as_uint(c0.y); r0[4 * m + 2] = __float_as_uint(c0.z); r0[4 * m + 3] = __float_as_uint(c0.w);
        r1[4 * m] = __float_as_uint(c1.x); r1[4 * m + 1] = __float_as_uint(c1.y); r1[4 * m + 2] = __float_as_uint(c1.z); r1[4 * m + 3] = __float_as_uint(c1.w);
      }
    }
    wg_wait<0>();
    if ((tid0 & 127) == 0) mbar_arrive(sb + BAR_PE + 8 * prev);
    if (w == (IS_O ? 35 : WW) && tid0 == 0) WTS(l, b, IS_O ? 17 : 6);
    if (!IS_O) {
      if (first) {
        if ((tid0 & 31) == 0) cnt_wait(CN_Z, 0, 0, NW, dead);
        __syncwarp();
        first = false;
      }
      const int tid = fresh(tid0);
      float* dst = &g_acc[l][b][tile][0] + (tid >> 5) * 2048 + (tid & 31) * 4;
#pragma unroll
      for (int i = 0; i < 16; i++)
        asm volatile("red.relaxed.gpu.global.add.v4.f32 [%0],{%1,%2,%3,%4};" ::"l"(dst + i * 128), "f"(acc[4 * i]), "f"(acc[4 * i + 1]), "f"(acc[4 * i + 2]), "f"(acc[4 * i + 3]) : "memory");
      if (w == WW && tid0 == 0) WTS(l, b, 7);
      bar_sync(NB_P, 256);
      if (tid0 == 0) cnt_signal(CN_P, l, b);
      if (w == WW && tid0 == 0) WTS(l, b, 8);
    } else {
      const int tid = fresh(tid0), g = (tid & 31) >> 2, t = tid & 3;
      const int rb = (tid >> 5) * 16 + g, R0 = b * 128 + rb;
      float s0 = 0.f, s1 = 0.f;
      bf16* xp = a.xb[l] + (size_t)R0 * DM + tile * 128 + 8 * t;
      uint32_t c0[16], c1[16];
#pragma unroll
      for (int j = 0; j < 16; j++) { c0[j] = pack_bf16(acc[4 * j], acc[4 * j + 1]); c1[j] = pack_bf16(acc[4 * j + 2], acc[4 * j + 3]); }
#pragma unroll
      for (int m = 0; m < 4; m++) { quad_transpose(c0 + 4 * m, t); quad_transpose(c1 + 4 * m, t); }
#pragma unroll
      for (int j = 0; j < 16; j++) {
        const uint32_t u0 = c0[j], u1 = c1[j];
        const uint32_t y0 = pack_bf16(bf_lo(r0[j]) + bf_lo(u0), bf_hi(r0[j]) + bf_hi(u0));
        const uint32_t y1 = pack_bf16(bf_lo(r1[j]) + bf_lo(u1), bf_hi(r1[j]) + bf_hi(u1));
        acc[4 * j] = bf_lo(y0); acc[4 * j + 1] = bf_hi(y0); acc[4 * j + 2] = bf_lo(y1); acc[4 * j + 3] = bf_hi(y1);
        s0 += acc[4 * j] + acc[4 * j + 1]; s1 += acc[4 * j + 2] + acc[4 * j + 3];
      }
      if (l == 0) {
        s0 += __shfl_xor_sync(0xffffffffu, s0, 1); s1 += __shfl_xor_sync(0xffffffffu, s1, 1);
        s0 += __shfl_xor_sync(0xffffffffu, s0, 2); s1 += __shfl_xor_sync(0xffffffffu, s1, 2);
        const float tm0 = s0 * (1.f / 128), tm1 = s1 * (1.f / 128);
        float q0 = 0.f, q1 = 0.f;
#pragma unroll
        for (int j = 0; j < 16; j++) {
          const float a0 = acc[4 * j] - tm0, b0 = acc[4 * j + 1] - tm0, a1 = acc[4 * j + 2] - tm1, b1 = acc[4 * j + 3] - tm1;
          q0 += a0 * a0 + b0 * b0; q1 += a1 * a1 + b1 * b1;
        }
        q0 += __shfl_xor_sync(0xffffffffu, q0, 1); q1 += __shfl_xor_sync(0xffffffffu, q1, 1);
        q0 += __shfl_xor_sync(0xffffffffu, q0, 2); q1 += __shfl_xor_sync(0xffffffffu, q1, 2);
        float2* sp = &g_stats[b][rb][0];
        if (t < 2) {
          const float sx = t ? s1 : s0, qx = t ? q1 : q0;
          asm volatile("st.relaxed.gpu.global.v2.f32 [%0],{%1,%2};" ::"l"(sp + t * 8 * 16 + tile), "f"(sx), "f"(qx) : "memory");
        }
#pragma unroll
        for (int m = 0; m < 4; m++) {
          const float* c = acc + 16 * m;
          *reinterpret_cast<uint4*>(xp + 32 * m) = make_uint4(pack_bf16(c[0], c[1]), pack_bf16(c[4], c[5]), pack_bf16(c[8], c[9]), pack_bf16(c[12], c[13]));
          *reinterpret_cast<uint4*>(xp + 8 * DM + 32 * m) = make_uint4(pack_bf16(c[2], c[3]), pack_bf16(c[6], c[7]), pack_bf16(c[10], c[11]), pack_bf16(c[14], c[15]));
        }
        if (w == 35 && tid0 == 0) WTS(l, b, 18);
        float2 e0[2], e1[2];
        int n = dead ? SPIN_MAIL : 0;
        while (true) {
          e0[0] = ld_relaxed2f(sp + t); e1[0] = ld_relaxed2f(sp + 8 * 16 + t);
          e0[1] = ld_relaxed2f(sp + 4); e1[1] = ld_relaxed2f(sp + 8 * 16 + 4);
          bool bad = false;
#pragma unroll
          for (int i = 0; i < 2; i++)
            bad |= __float_as_uint(e0[i].x) == SENT || __float_as_uint(e0[i].y) == SENT || __float_as_uint(e1[i].x) == SENT || __float_as_uint(e1[i].y) == SENT;
          if (!__any_sync(0xffffffffu, bad)) break;
          if (++n > SPIN_MAIL) { dead = 1; g_err = 20; break; }
        }
        if (w == 35 && tid0 == 0) WTS(l, b, 19);
        float m0 = e0[0].x, m1 = e1[0].x;
        m0 += __shfl_xor_sync(0xffffffffu, m0, 1); m1 += __shfl_xor_sync(0xffffffffu, m1, 1);
        m0 += __shfl_xor_sync(0xffffffffu, m0, 2); m1 += __shfl_xor_sync(0xffffffffu, m1, 2);
        m0 = (m0 + e0[1].x) * (1.f / DM); m1 = (m1 + e1[1].x) * (1.f / DM);
        const float d0 = e0[0].x * (1.f / 128) - m0, d1 = e1[0].x * (1.f / 128) - m1;
        float v0 = e0[0].y + 128.f * d0 * d0, v1 = e1[0].y + 128.f * d1 * d1;
        v0 += __shfl_xor_sync(0xffffffffu, v0, 1); v1 += __shfl_xor_sync(0xffffffffu, v1, 1);
        v0 += __shfl_xor_sync(0xffffffffu, v0, 2); v1 += __shfl_xor_sync(0xffffffffu, v1, 2);
        const float d2 = e0[1].x * (1.f / 128) - m0, d3 = e1[1].x * (1.f / 128) - m1;
        v0 += e0[1].y + 128.f * d2 * d2; v1 += e1[1].y + 128.f * d3 * d3;
        const float rs0 = rsqrtf(v0 * (1.f / DM) + 1e-5f), rs1 = rsqrtf(v1 * (1.f / DM) + 1e-5f);
        uint8_t* img = g_xn[1] + (size_t)(R0 >> 5) * 40960 + tile * 8192 + ((R0 >> 3) & 3) * 2048 + g * 128;
#pragma unroll
        for (int m = 0; m < 4; m++) {
          uint8_t* o = img + (m >> 1) * 1024 + (((4 * (m & 1) + t) ^ g) << 4);
          const float* c = acc + 16 * m;
          *reinterpret_cast<uint4*>(o) = make_uint4(pack_bf16((c[0] - m0) * rs0, (c[1] - m0) * rs0), pack_bf16((c[4] - m0) * rs0, (c[5] - m0) * rs0),
                                                    pack_bf16((c[8] - m0) * rs0, (c[9] - m0) * rs0), pack_bf16((c[12] - m0) * rs0, (c[13] - m0) * rs0));
          *reinterpret_cast<uint4*>(o + 2048) = make_uint4(pack_bf16((c[2] - m1) * rs1, (c[3] - m1) * rs1), pack_bf16((c[6] - m1) * rs1, (c[7] - m1) * rs1),
                                                            pack_bf16((c[10] - m1) * rs1, (c[11] - m1) * rs1), pack_bf16((c[14] - m1) * rs1, (c[15] - m1) * rs1));
        }
        bar_sync(NB_P, 256);
        if (tid0 == 0) { fence_async_all(); cnt_signal(CN_X, 0, b); }
      } else {
#pragma unroll
        for (int m = 0; m < 4; m++) {
          const float* c = acc + 16 * m;
          *reinterpret_cast<uint4*>(xp + 32 * m) = make_uint4(pack_bf16(c[0], c[1]), pack_bf16(c[4], c[5]), pack_bf16(c[8], c[9]), pack_bf16(c[12], c[13]));
          *reinterpret_cast<uint4*>(xp + 8 * DM + 32 * m) = make_uint4(pack_bf16(c[2], c[3]), pack_bf16(c[6], c[7]), pack_bf16(c[10], c[11]), pack_bf16(c[14], c[15]));
        }
      }
      if (w == 35 && tid0 == 0) { WTS(l, b, 4); WTS(l, b, 20); }
    }
  }
}

__device__ __forceinline__ void work_q_producer(const WorkArgs& a, uint32_t sb) {
  using namespace W;
  int dead = 0, st = 0;
  uint32_t ph = 1;
  FOR_BATCHES(l, b)
    cnt_wait(CN_L, l, b, 64, dead);
    if (blockIdx.x == 0) WTS(l, b, 2);
    fence_async_all();
    const uint8_t* src = g_xnb[l] + (size_t)(2 * b) * 10 * 8192;
#pragma unroll 1
    for (int kc = 0; kc < 10; kc++) {
      const uint32_t bar = sb + BAR_BF + 8 * st, d = sb + OFF_B + st * BSTAGE;
      mbar_wait(sb + BAR_BE + 8 * st, ph, dead);
      mbar_expect_tx(bar, BSTAGE);
      bulk_g2s(d, src + (size_t)kc * 8192, 8192, bar);
      bulk_g2s(d + 8192, src + (size_t)(10 + kc) * 8192, 8192, bar);
      if (++st == BST) { st = 0; ph ^= 1; }
    }
  }
}

__device__ __forceinline__ void work_ln(const WorkArgs& a, int w, int wr, int lane0) {
  int dead = 0;
  FOR_BATCHES(l, b)
    uint32_t r0[10], r1[10];
    if (HOIST & 2) {
      if (l == 1) {
        if (lane0 == 0) cnt_wait(CN_X, 0, b, 5, dead);
        __syncwarp();
      }
      const int lane = fresh(lane0), p = 2 * w + wr;
      const bf16* rp = a.res[l] + (size_t)(b * 128 + (p >> 3) * 16 + (p & 7)) * DM + (lane >> 2) * 8 + 2 * (lane & 3);
#pragma unroll
      for (int i = 0; i < 10; i++) { r0[i] = ld_relaxed(rp + i * 64); r1[i] = ld_relaxed(rp + i * 64 + 8 * DM); }
    }
    if (lane0 == 0) cnt_wait(CN_P, l, b, W::NP, dead);
    __syncwarp();
    if (w == WW && wr == 0 && lane0 == 0) { WTS(l, b, 1); WTS(l, b, 9); }
    LTS(l, b, 2 * w + wr, 0);
    const int lane = fresh(lane0), p = 2 * w + wr;
    const int slab = p >> 3, g = p & 7, jj = lane >> 2, t = lane & 3;
    const int R0 = b * 128 + slab * 16 + g;
    const float* acc = &g_acc[l][b][0][0] + slab * 2048 + (g * 4 + t) * 4 + jj * 128;
    const bf16* rp = a.res[l] + (size_t)R0 * DM + jj * 8 + 2 * t;
    float4 v[10];
#pragma unroll
    for (int i = 0; i < 10; i++) {
      v[i] = ld_relaxed4f(acc + (i >> 1) * 16384 + (i & 1) * 1024);
      if (!(HOIST & 2)) { r0[i] = ld_relaxed(rp + i * 64); r1[i] = ld_relaxed(rp + i * 64 + 8 * DM); }
    }
    float s0 = 0.f, s1 = 0.f;
    bf16* xp = a.xa[l] + (size_t)R0 * DM + jj * 8 + 2 * t;
#pragma unroll
    for (int i = 0; i < 10; i++) {
      const uint32_t u0 = pack_bf16(v[i].x, v[i].y), u1 = pack_bf16(v[i].z, v[i].w);
      r0[i] = pack_bf16(bf_lo(r0[i]) + bf_lo(u0), bf_hi(r0[i]) + bf_hi(u0));
      r1[i] = pack_bf16(bf_lo(r1[i]) + bf_lo(u1), bf_hi(r1[i]) + bf_hi(u1));
      s0 += bf_lo(r0[i]) + bf_hi(r0[i]); s1 += bf_lo(r1[i]) + bf_hi(r1[i]);
    }
#pragma unroll
    for (int o = 16; o > 0; o >>= 1) { s0 += __shfl_xor_sync(0xffffffffu, s0, o); s1 += __shfl_xor_sync(0xffffffffu, s1, o); }
    const float m0 = s0 * (1.f / DM), m1 = s1 * (1.f / DM);
    if (m0 != 12345.678f) LTS(l, b, 2 * w + wr, 1);
    float q0 = 0.f, q1 = 0.f;
#pragma unroll
    for (int i = 0; i < 10; i++) {
      const float a0 = bf_lo(r0[i]) - m0, b0 = bf_hi(r0[i]) - m0, a1 = bf_lo(r1[i]) - m1, b1 = bf_hi(r1[i]) - m1;
      q0 += a0 * a0 + b0 * b0; q1 += a1 * a1 + b1 * b1;
    }
#pragma unroll
    for (int o = 16; o > 0; o >>= 1) { q0 += __shfl_xor_sync(0xffffffffu, q0, o); q1 += __shfl_xor_sync(0xffffffffu, q1, o); }
    const float rs0 = rsqrtf(q0 * (1.f / DM) + 1e-5f), rs1 = rsqrtf(q1 * (1.f / DM) + 1e-5f);
    uint8_t* img = g_xnb[l] + (size_t)(R0 >> 6) * 10 * 8192 + (R0 & 63) * 128 + t * 4 + ((jj ^ g) << 4);
#pragma unroll
    for (int i = 0; i < 10; i++) {
      *reinterpret_cast<uint32_t*>(img + i * 8192) = pack_bf16((bf_lo(r0[i]) - m0) * rs0, (bf_hi(r0[i]) - m0) * rs0);
      *reinterpret_cast<uint32_t*>(img + i * 8192 + 1024) = pack_bf16((bf_lo(r1[i]) - m1) * rs1, (bf_hi(r1[i]) - m1) * rs1);
    }
#pragma unroll
    for (int i = 0; i < 10; i++) {
      *reinterpret_cast<uint32_t*>(xp + i * 64) = r0[i];
      *reinterpret_cast<uint32_t*>(xp + i * 64 + 8 * DM) = r1[i];
    }
    __syncwarp();
    if (w == WW && wr == 0 && lane0 == 0) WTS(l, b, 10);
    LTS(l, b, 2 * w + wr, 2);
    if (lane0 == 0) cnt_signal(CN_L, l, b);
    LTS(l, b, 2 * w + wr, 3);
    if (w == WW && wr == 0 && lane0 == 0) WTS(l, b, 11);
  }
}

__device__ __forceinline__ void work_q(const WorkArgs& a, uint32_t sb, int w, int tid0) {
  using namespace W;
  int dead = 0, st = 0;
  uint32_t ph = 0;
  FOR_BATCHES(l, b)
    {
      float acc0[32], acc1[32];
      int prev = 0;
#pragma unroll 1
      for (int kc = 0; kc < 10; kc++) {
        mbar_wait(sb + BAR_BF + 8 * st, ph, dead);
        if (w == WW && tid0 == 0 && kc == 0) WTS(l, b, 12);
        const uint32_t pa = sb + OFF_B + st * BSTAGE, pb = sb + OFF_WQ + kc * 8192;
        wg_fence();
#pragma unroll
        for (int kk = 0; kk < 4; kk++) {
          wgmma_st64(acc0, mkdesc(pa + kk * 32, 16, 1024), mkdesc(pb + kk * 2048, 8192, 1024), (kc | kk) != 0);
          wgmma_st64(acc1, mkdesc(pa + 8192 + kk * 32, 16, 1024), mkdesc(pb + kk * 2048, 8192, 1024), (kc | kk) != 0);
        }
        wg_commit();
        if (IMMREL & 4) {
          if (kc <= 6) {
            wg_wait<0>();
            if (tid0 == 0) mbar_arrive(sb + BAR_BE + 8 * st);
          }
        } else if (kc > 0) {
          wg_wait<1>();
          if (kc <= 7 && tid0 == 0) mbar_arrive(sb + BAR_BE + 8 * prev);
        }
        prev = st;
        if (++st == BST) { st = 0; ph ^= 1; }
      }
      wg_wait<0>();
      bar_sync(NB_B, 128);
      if (w == WW && tid0 == 0) WTS(l, b, 13);
      const int tid = fresh(tid0), wr = tid >> 5, g = (tid & 31) >> 2, t = tid & 3;
      const uint32_t stg = sb + OFF_B, hist = sb + OFF_HIST + l * 1120;
      const uint32_t o = stg + (14 + 16 * wr + g) * PITCH + t * 4;
#pragma unroll
      for (int j = 0; j < 8; j++) {
        sts32(o + j * 16, pack_bf16(acc0[4 * j], acc0[4 * j + 1]));
        sts32(o + 8 * PITCH + j * 16, pack_bf16(acc0[4 * j + 2], acc0[4 * j + 3]));
        sts32(o + 64 * PITCH + j * 16, pack_bf16(acc1[4 * j], acc1[4 * j + 1]));
        sts32(o + 72 * PITCH + j * 16, pack_bf16(acc1[4 * j + 2], acc1[4 * j + 3]));
      }
      for (int i = tid; i < 280; i += 128) {
        uint32_t v; asm volatile("ld.shared.b32 %0,[%1];" : "=r"(v) : "r"(hist + i * 4) : "memory");
        sts32(stg + (i / 20) * PITCH + 40 + (i % 20) * 4, v);
      }
    }
    bar_sync(NB_B, 128);
    {
      const int tid = fresh(tid0);
      const uint32_t stg = sb + OFF_B, hist = sb + OFF_HIST + l * 1120;
      for (int i = tid; i < 280; i += 128) {
        uint32_t v; asm volatile("ld.shared.b32 %0,[%1];" : "=r"(v) : "r"(stg + (128 + i / 20) * PITCH + 40 + (i % 20) * 4) : "memory");
        sts32(hist + i * 4, v);
      }
      const float scl = 0.22360679774997896f * 1.4426950408889634f;
      const uint32_t row = stg + (14 + tid) * PITCH;
      const int pos = b * 128 + tid;
      float q[20];
#pragma unroll
      for (int i = 0; i < 5; i++) {
        uint32_t u0, u1; asm volatile("ld.shared.v2.b32 {%0,%1},[%2];" : "=r"(u0), "=r"(u1) : "r"(row + i * 8) : "memory");
        q[4 * i] = bf_lo(u0); q[4 * i + 1] = bf_hi(u0); q[4 * i + 2] = bf_lo(u1); q[4 * i + 3] = bf_hi(u1);
      }
      float sc[8], mx = -INFINITY;
#pragma unroll
      for (int j = 0; j < 8; j++) {
        float s0 = 0.f, s1 = 0.f;
#pragma unroll
        for (int i = 0; i < 5; i++) {
          uint32_t u0, u1; asm volatile("ld.shared.v2.b32 {%0,%1},[%2];" : "=r"(u0), "=r"(u1) : "r"(row - 2 * j * PITCH + 40 + i * 8) : "memory");
          s0 += q[4 * i] * bf_lo(u0) + q[4 * i + 1] * bf_hi(u0);
          s1 += q[4 * i + 2] * bf_lo(u1) + q[4 * i + 3] * bf_hi(u1);
        }
        sc[j] = pos - 2 * j >= 0 ? (s0 + s1) * scl : -INFINITY;
        mx = fmaxf(mx, sc[j]);
      }
      float sum = 0.f;
#pragma unroll
      for (int j = 0; j < 8; j++) { sc[j] = ex2(sc[j] - mx); sum += sc[j]; }
      const float inv = 1.f / sum;
      float o[20];
#pragma unroll
      for (int i = 0; i < 20; i++) o[i] = 0.f;
#pragma unroll
      for (int j = 0; j < 8; j++) {
        const float pj = __bfloat162float(__float2bfloat16(sc[j] * inv));
#pragma unroll
        for (int i = 0; i < 5; i++) {
          uint32_t u0, u1; asm volatile("ld.shared.v2.b32 {%0,%1},[%2];" : "=r"(u0), "=r"(u1) : "r"(row - 2 * j * PITCH + 80 + i * 8) : "memory");
          o[4 * i] += pj * bf_lo(u0); o[4 * i + 1] += pj * bf_hi(u0); o[4 * i + 2] += pj * bf_lo(u1); o[4 * i + 3] += pj * bf_hi(u1);
        }
      }
      uint8_t* img = g_ob[l] + (size_t)(pos >> 6) * 10 * 8192 + (pos & 63) * 128;
#pragma unroll
      for (int i = 0; i < 5; i++) {
        const int c = w * 20 + 4 * i;
        *reinterpret_cast<uint2*>(img + (c >> 6) * 8192 + ((((c >> 3) & 7) ^ (pos & 7)) << 4) + (c & 7) * 2) =
            make_uint2(pack_bf16(o[4 * i], o[4 * i + 1]), pack_bf16(o[4 * i + 2], o[4 * i + 3]));
      }
    }
    if (w == WW && tid0 == 0) WTS(l, b, 14);
    bar_sync(NB_B, 128);
    if (tid0 == 0) { cnt_signal(CN_A, l, b); if (w == WW) WTS(l, b, 15); }
    fence_async();
    bar_sync(NB_B, 128);
    if (tid0 == 0) for (int i = 0; i < BST; i++) mbar_arrive(sb + BAR_BE + 8 * i);
  }
}

__global__ void __launch_bounds__(512, 1)
k_work(const __grid_constant__ CUtensorMap tmWo, const __grid_constant__ CUtensorMap tmBo, const __grid_constant__ WorkArgs args) {
  using namespace W;
  extern __shared__ __align__(1024) uint8_t smem[];
  const uint32_t sb = smem_u32(smem);
  const int tid = threadIdx.x, w = blockIdx.x;
  const int wg = __shfl_sync(0xffffffffu, tid >> 7, 0);
  if (tid == 0) {
    for (int i = 0; i < PST; i++) { mbar_init(sb + BAR_PF + 8 * i, 1); mbar_init(sb + BAR_PE + 8 * i, 2); }
    for (int i = 0; i < BST; i++) { mbar_init(sb + BAR_BF + 8 * i, 1); mbar_init(sb + BAR_BE + 8 * i, 1); }
    asm volatile("fence.mbarrier_init.release.cluster;" ::: "memory");
  }
  for (int i = w * 512 + tid; i < 2 * 16 * 5 * 4096; i += NW * 512) reinterpret_cast<uint4*>(&g_acc[0][0][0][0])[i] = make_uint4(0, 0, 0, 0);
  if (w < 32) {
    for (int i = tid; i < 640 * 32; i += 512) {
      const int k = i >> 5, c = i & 31;
      uint32_t v = 0;
      if (c < 30) v = *reinterpret_cast<const uint32_t*>(args.wqkv + (size_t)k * 1920 + (c / 10) * 640 + w * 20 + (c % 10) * 2);
      sts32(sb + OFF_WQ + (k >> 6) * 8192 + (k & 63) * 128 + (((c >> 2) ^ (k & 7)) << 4) + (c & 3) * 4, v);
    }
  }
  for (int i = tid; i < 560; i += 512) sts32(sb + OFF_HIST + i * 4, 0);
  fence_async();
  __syncthreads();
  if (tid == 0) cnt_signal(CN_Z, 0, 0);

  if (wg < 2) {
    if (w < NP) work_gemm<false>(args, sb, w, tid);
    else if (w >= OW0) work_gemm<true>(args, sb, w, tid);
    else if (LN30 && tid < 64) work_ln(args, 31, tid >> 5, tid & 31);
  } else if (wg == 2) {
    if (w < 32) work_q(args, sb, w, tid - 256);
  } else if (tid >= 448) {
    if (w < (LN30 ? 31 : 32)) work_ln(args, w, (tid >> 5) & 1, tid & 31);
  } else if (tid == 384) {
    if (w < NP) work_gemm_producer<false>(tmWo, args, sb, w);
    else if (w >= OW0) work_gemm_producer<true>(tmBo, args, sb, w);
  } else if (tid == 416) {
    if (w < 32) work_q_producer(args, sb);
  }
  __syncthreads();
  asm volatile("griddepcontrol.wait;" ::: "memory");
}

typedef CUresult (*EncodeFn)(CUtensorMap*, CUtensorMapDataType, cuuint32_t, void*, const cuuint64_t*, const cuuint64_t*,
                             const cuuint32_t*, const cuuint32_t*, CUtensorMapInterleave, CUtensorMapSwizzle,
                             CUtensorMapL2promotion, CUtensorMapFloatOOBfill);

static void make_map(EncodeFn enc, CUtensorMap* tm, const void* ptr, uint64_t cols, uint64_t rows, uint32_t boxc, uint32_t boxr) {
  cuuint64_t dims[2] = {cols, rows};
  cuuint64_t strides[1] = {cols * 2};
  cuuint32_t box[2] = {boxc, boxr};
  cuuint32_t es[2] = {1, 1};
  enc(tm, CU_TENSOR_MAP_DATA_TYPE_BFLOAT16, 2, const_cast<void*>(ptr), dims, strides, box, es, CU_TENSOR_MAP_INTERLEAVE_NONE,
      CU_TENSOR_MAP_SWIZZLE_128B, CU_TENSOR_MAP_L2_PROMOTION_L2_256B, CU_TENSOR_MAP_FLOAT_OOB_FILL_NONE);
}

extern "C" void kernel_launch(void* const* d_in, const int* in_sizes, int n_in, void* d_out, int out_size) {
  const bf16* x0 = (const bf16*)d_in[0];
  const bf16* mem0 = (const bf16*)d_in[1];
  const bf16* Wq = (const bf16*)d_in[2];
  const bf16* Wk = (const bf16*)d_in[3];
  const bf16* Wv = (const bf16*)d_in[4];
  const bf16* Wo = (const bf16*)d_in[5];
  const bf16* Bqkv = (const bf16*)d_in[8];
  const bf16* Bwo = (const bf16*)d_in[9];
  bf16* out = (bf16*)d_out;

  static EncodeFn enc = nullptr;
  static bf16 *p_x1, *p_x2, *p_x3;
  if (!enc) {
    void* fn = nullptr;
    cudaDriverEntryPointQueryResult qr;
    cudaGetDriverEntryPoint("cuTensorMapEncodeTiled", &fn, cudaEnableDefault, &qr);
    enc = (EncodeFn)fn;
    cudaFuncSetAttribute(k_chain, cudaFuncAttributeMaxDynamicSharedMemorySize, C::SMEM);
    cudaFuncSetAttribute(k_work, cudaFuncAttributeMaxDynamicSharedMemorySize, W::SMEM);
    void* p;
    cudaGetSymbolAddress(&p, g_x1); p_x1 = (bf16*)p;
    cudaGetSymbolAddress(&p, g_x2); p_x2 = (bf16*)p;
    cudaGetSymbolAddress(&p, g_x3); p_x3 = (bf16*)p;
  }
  CUtensorMap tmWq, tmWk, tmWv, tmWo, tmBo;
  make_map(enc, &tmWq, Wq, NH * DH, DM, 64, 128);
  make_map(enc, &tmWk, Wk, NH * DH, DM, 64, 128);
  make_map(enc, &tmWv, Wv, NH * DH, DM, 64, 128);
  make_map(enc, &tmWo, Wo, DM, NH * DH, 64, 64);
  make_map(enc, &tmBo, Bwo, DM, DM, 64, 64);

  cudaStream_t st = cudaStreamPerThread;
  k_pre<<<256, 256, 0, st>>>(x0, mem0);
  cudaLaunchAttribute at[1];
  at[0].id = cudaLaunchAttributeProgrammaticStreamSerialization; at[0].val.programmaticStreamSerializationAllowed = 1;
  {
    cudaLaunchConfig_t cfg = {};
    cfg.gridDim = dim3(96); cfg.blockDim = dim3(384); cfg.dynamicSmemBytes = C::SMEM; cfg.stream = st;
    cfg.attrs = at; cfg.numAttrs = 0;
    cudaLaunchKernelEx(&cfg, k_chain, tmWq, tmWk, tmWv, tmWo);
  }
  WorkArgs wa;
  wa.res[0] = x0; wa.res[1] = p_x2; wa.xa[0] = p_x1; wa.xa[1] = p_x3; wa.xb[0] = p_x2; wa.xb[1] = out;
  wa.wqkv = Bqkv;
  cudaLaunchConfig_t cfg = {};
  cfg.gridDim = dim3(W::NW); cfg.blockDim = dim3(512); cfg.dynamicSmemBytes = W::SMEM; cfg.stream = st;
  cfg.attrs = at; cfg.numAttrs = 1;
  cudaLaunchKernelEx(&cfg, k_work, tmWo, tmBo, wa);
}
```

```cpp
#include <cuda_runtime.h>
#include <cuda_bf16.h>
#include <cuda.h>
#include <stdint.h>

typedef __nv_bfloat16 bf16;

constexpr int SEQ = 2048, DM = 640, NH = 32, DH = 192, NSEG = 64;
#define LAG 14
constexpr int NSTEP = NSEG + LAG;
constexpr uint32_t SENT = 0xFFFFFFFFu;
constexpr int SPIN_LIM = 1 << 20;
constexpr int SPIN_MAIL = 1 << 16;
constexpr int SPIN_CNT = 1 << 16;

constexpr int MAIL9 = 288 * 2048, MAIL_BYTES = MAIL9 + 64 * 3072;
__device__ __align__(1024) uint8_t g_xn[2][NSEG * 40960];
__device__ __align__(1024) uint8_t g_xnb[2][32 * 10 * 8192];
__device__ __align__(1024) uint8_t g_ob[2][32 * 10 * 8192];
__device__ __align__(1024) uint8_t g_o[2][32 * 96 * 8192];
__device__ __align__(1024) uint8_t g_mbuf[NSTEP][20480];
__device__ __align__(1024) uint8_t g_mail[2][MAIL_BYTES];
__device__ __align__(1024) float g_acc[2][16][5][16384];
__device__ __align__(1024) float2 g_stats[16][128][16];
__device__ __align__(128) bf16 g_x1[SEQ * DM];
__device__ __align__(128) bf16 g_x2[SEQ * DM];
__device__ __align__(128) bf16 g_x3[SEQ * DM];
enum { CN_O = 0, CN_P = 1, CN_L = 2, CN_A = 3, CN_X = 4, CN_Z = 5 };
__device__ __align__(128) uint32_t g_cnt[6][2][16][32];
__device__ int g_err;
#define TS(jj, i)
#define TS1(jj, i)
#define PTS(i)
#define LTS(l, b, p, k)
#define TSB(jj, i)
#define TSV(jj, i, v)
#define TS_FLUSH(jj)
#define WTS(l, b, k)
#define WW -1

__device__ __forceinline__ uint32_t smem_u32(const void* p) { return (uint32_t)__cvta_generic_to_shared(p); }
__device__ __forceinline__ uint32_t clk32() { uint32_t t; asm volatile("mov.u32 %0, %%clock;" : "=r"(t)::"memory"); return t; }
__device__ __forceinline__ uint32_t mapa(uint32_t a, uint32_t r) { uint32_t o; asm("mapa.shared::cluster.u32 %0,%1,%2;" : "=r"(o) : "r"(a), "r"(r)); return o; }
__device__ __forceinline__ void mbar_init(uint32_t bar, uint32_t cnt) { asm volatile("mbarrier.init.shared::cta.b64 [%0],%1;" ::"r"(bar), "r"(cnt) : "memory"); }
__device__ __forceinline__ void mbar_expect_tx(uint32_t bar, uint32_t bytes) { asm volatile("mbarrier.arrive.expect_tx.shared::cta.b64 _,[%0],%1;" ::"r"(bar), "r"(bytes) : "memory"); }
__device__ __forceinline__ void mbar_arrive(uint32_t bar) { asm volatile("mbarrier.arrive.shared::cta.b64 _,[%0];" ::"r"(bar) : "memory"); }
__device__ __forceinline__ void mbar_arrive_cluster(uint32_t bar) { asm volatile("mbarrier.arrive.shared::cluster.b64 _,[%0];" ::"r"(bar) : "memory"); }
__device__ __forceinline__ bool mbar_try(uint32_t bar, uint32_t ph) {
  uint32_t ok;
  asm volatile("{.reg .pred p; mbarrier.try_wait.parity.shared::cta.b64 p,[%1],%2; selp.u32 %0,1,0,p;}" : "=r"(ok) : "r"(bar), "r"(ph) : "memory");
  return ok;
}
__device__ __forceinline__ void mbar_wait(uint32_t bar, uint32_t ph, int& dead) {
  if (mbar_try(bar, ph)) return;
  int n = dead ? SPIN_LIM : 0;
  while (!mbar_try(bar, ph)) { if (++n > SPIN_LIM) { dead = 1; g_err = 1; break; } }
}
__device__ __forceinline__ int fresh(int x) { asm volatile("" : "+r"(x)); return x; }
#define PHASE_IDS const int tid = fresh(tid0), lane = tid & 31, w = tid >> 5, g = lane >> 2, t = lane & 3; (void)w; (void)g; (void)t
__device__ __forceinline__ void bar_sync(int id, int n) { asm volatile("bar.sync %0,%1;" ::"r"(id), "r"(n) : "memory"); }
__device__ __forceinline__ void bar_arrive(int id, int n) { asm volatile("bar.arrive %0,%1;" ::"r"(id), "r"(n) : "memory"); }
__device__ __forceinline__ bool bar_red_or(int id, int n, bool v) {
  uint32_t r;
  asm volatile("{\n .reg .pred p, q;\n setp.ne.u32 q, %3, 0;\n barrier.cta.red.or.pred p, %1, %2, q;\n selp.u32 %0, 1, 0, p;\n}" : "=r"(r) : "r"(id), "r"(n), "r"((uint32_t)v) : "memory");
  return r != 0;
}
__device__ __forceinline__ void fence_async() { asm volatile("fence.proxy.async.shared::cta;" ::: "memory"); }
__device__ __forceinline__ void bulk_g2s(uint32_t dst, const void* src, uint32_t bytes, uint32_t bar) {
  asm volatile("cp.async.bulk.shared::cluster.global.mbarrier::complete_tx::bytes [%0],[%1],%2,[%3];" ::"r"(dst), "l"(src), "r"(bytes), "r"(bar) : "memory");
}
__device__ __forceinline__ void bulk_g2s_mc(uint32_t dst, const void* src, uint32_t bytes, uint32_t bar) {
  asm volatile("cp.async.bulk.shared::cluster.global.mbarrier::complete_tx::bytes.multicast::cluster [%0],[%1],%2,[%3],%4;"
               ::"r"(dst), "l"(src), "r"(bytes), "r"(bar), "h"((uint16_t)7) : "memory");
}
__device__ __forceinline__ void bulk_s2g(void* dst, uint32_t src, uint32_t bytes) {
  asm volatile("cp.async.bulk.global.shared::cta.bulk_group [%0],[%1],%2;" ::"l"(dst), "r"(src), "r"(bytes) : "memory");
}
__device__ __forceinline__ void bulk_s2c(uint32_t dst, uint32_t src, uint32_t bytes, uint32_t bar) {
  asm volatile("cp.async.bulk.shared::cluster.shared::cta.mbarrier::complete_tx::bytes [%0],[%1],%2,[%3];" ::"r"(dst), "r"(src), "r"(bytes), "r"(bar) : "memory");
}
__device__ __forceinline__ void tma2d(uint32_t dst, const CUtensorMap* tm, int c0, int c1, uint32_t bar) {
  asm volatile("cp.async.bulk.tensor.2d.shared::cluster.global.mbarrier::complete_tx::bytes [%0],[%1,{%3,%4}],[%2];"
               ::"r"(dst), "l"(tm), "r"(bar), "r"(c0), "r"(c1) : "memory");
}
__device__ __forceinline__ void tma2d_prefetch(const CUtensorMap* tm, int c0, int c1) {
  asm volatile("cp.async.bulk.prefetch.tensor.2d.L2.global.tile [%0,{%1,%2}];" ::"l"(tm), "r"(c0), "r"(c1) : "memory");
}
__device__ __forceinline__ uint32_t pack_bf16(float lo, float hi) {
  uint32_t r; asm("cvt.rn.bf16x2.f32 %0,%1,%2;" : "=r"(r) : "f"(hi), "f"(lo)); return r;
}
__device__ __forceinline__ float bf_lo(uint32_t x) { return __uint_as_float(x << 16); }
__device__ __forceinline__ float bf_hi(uint32_t x) { return __uint_as_float(x & 0xFFFF0000u); }
__device__ __forceinline__ float ex2(float x) { float y; asm("ex2.approx.ftz.f32 %0,%1;" : "=f"(y) : "f"(x)); return y; }
__device__ __forceinline__ void ldsm4(uint32_t (&r)[4], uint32_t a) {
  asm volatile("ldmatrix.sync.aligned.m8n8.x4.shared.b16 {%0,%1,%2,%3},[%4];" : "=r"(r[0]), "=r"(r[1]), "=r"(r[2]), "=r"(r[3]) : "r"(a) : "memory");
}
__device__ __forceinline__ void ldsm4t(uint32_t (&r)[4], uint32_t a) {
  asm volatile("ldmatrix.sync.aligned.m8n8.x4.trans.shared.b16 {%0,%1,%2,%3},[%4];" : "=r"(r[0]), "=r"(r[1]), "=r"(r[2]), "=r"(r[3]) : "r"(a) : "memory");
}
__device__ __forceinline__ void ldsm2(uint32_t& r0, uint32_t& r1, uint32_t a) {
  asm volatile("ldmatrix.sync.aligned.m8n8.x2.shared.b16 {%0,%1},[%2];" : "=r"(r0), "=r"(r1) : "r"(a) : "memory");
}
__device__ __forceinline__ void ldsm1(uint32_t& r0, uint32_t a) {
  asm volatile("ldmatrix.sync.aligned.m8n8.x1.shared.b16 {%0},[%1];" : "=r"(r0) : "r"(a) : "memory");
}
__device__ __forceinline__ void mma16816(float (&d)[4], uint32_t a0, uint32_t a1, uint32_t a2, uint32_t a3, uint32_t b0, uint32_t b1) {
  asm volatile("mma.sync.aligned.m16n8k16.row.col.f32.bf16.bf16.f32 {%0,%1,%2,%3},{%4,%5,%6,%7},{%8,%9},{%0,%1,%2,%3};"
               : "+f"(d[0]), "+f"(d[1]), "+f"(d[2]), "+f"(d[3]) : "r"(a0), "r"(a1), "r"(a2), "r"(a3), "r"(b0), "r"(b1));
}
__device__ __forceinline__ void mma1688(float (&d)[4], uint32_t a0, uint32_t a1, uint32_t b0) {
  asm volatile("mma.sync.aligned.m16n8k8.row.col.f32.bf16.bf16.f32 {%0,%1,%2,%3},{%4,%5},{%6},{%0,%1,%2,%3};"
               : "+f"(d[0]), "+f"(d[1]), "+f"(d[2]), "+f"(d[3]) : "r"(a0), "r"(a1), "r"(b0));
}
__device__ __forceinline__ void sts32(uint32_t a, uint32_t v) { asm volatile("st.shared.b32 [%0],%1;" ::"r"(a), "r"(v) : "memory"); }
__device__ __forceinline__ void sts64f(uint32_t a, float x, float y) { asm volatile("st.shared.v2.f32 [%0],{%1,%2};" ::"r"(a), "f"(x), "f"(y) : "memory"); }
__device__ __forceinline__ void sts128(uint32_t a, uint4 v) { asm volatile("st.shared.v4.b32 [%0],{%1,%2,%3,%4};" ::"r"(a), "r"(v.x), "r"(v.y), "r"(v.z), "r"(v.w) : "memory"); }
__device__ __forceinline__ float lds32f(uint32_t a) { float v; asm volatile("ld.shared.f32 %0,[%1];" : "=f"(v) : "r"(a) : "memory"); return v; }
__device__ __forceinline__ float2 lds64f(uint32_t a) { float2 v; asm volatile("ld.shared.v2.f32 {%0,%1},[%2];" : "=f"(v.x), "=f"(v.y) : "r"(a) : "memory"); return v; }
__device__ __forceinline__ uint4 lds128(uint32_t a) { uint4 v; asm volatile("ld.shared.v4.b32 {%0,%1,%2,%3},[%4];" : "=r"(v.x), "=r"(v.y), "=r"(v.z), "=r"(v.w) : "r"(a) : "memory"); return v; }
__device__ __forceinline__ float4 lds128f(uint32_t a) { float4 v; asm volatile("ld.shared.v4.f32 {%0,%1,%2,%3},[%4];" : "=f"(v.x), "=f"(v.y), "=f"(v.z), "=f"(v.w) : "r"(a) : "memory"); return v; }
__device__ __forceinline__ void st_async2(uint32_t a, float x, float y, uint32_t bar) {
  asm volatile("st.async.weak.shared::cluster.mbarrier::complete_tx::bytes.v2.f32 [%0],{%1,%2},[%3];" ::"r"(a), "f"(x), "f"(y), "r"(bar) : "memory");
}
__device__ __forceinline__ void st_async4(uint32_t a, const float (&v)[4], uint32_t bar) {
  asm volatile("st.async.weak.shared::cluster.mbarrier::complete_tx::bytes.v4.f32 [%0],{%1,%2,%3,%4},[%5];" ::"r"(a), "f"(v[0]), "f"(v[1]), "f"(v[2]), "f"(v[3]), "r"(bar) : "memory");
}
__device__ __forceinline__ void st_async4v(uint32_t a, float x, float y, float z, float w, uint32_t bar) {
  asm volatile("st.async.weak.shared::cluster.mbarrier::complete_tx::bytes.v4.f32 [%0],{%1,%2,%3,%4},[%5];" ::"r"(a), "f"(x), "f"(y), "f"(z), "f"(w), "r"(bar) : "memory");
}
__device__ __forceinline__ void st_async4u(uint32_t a, const uint4& v, uint32_t bar) {
  asm volatile("st.async.weak.shared::cluster.mbarrier::complete_tx::bytes.v4.b32 [%0],{%1,%2,%3,%4},[%5];" ::"r"(a), "r"(v.x), "r"(v.y), "r"(v.z), "r"(v.w), "r"(bar) : "memory");
}
__device__ __forceinline__ uint4 ld_relaxed4(const void* p) {
  uint4 v; asm volatile("ld.relaxed.gpu.global.v4.u32 {%0,%1,%2,%3},[%4];" : "=r"(v.x), "=r"(v.y), "=r"(v.z), "=r"(v.w) : "l"(p) : "memory"); return v;
}
__device__ __forceinline__ uint32_t ld_relaxed(const void* p) {
  uint32_t v; asm volatile("ld.relaxed.gpu.global.u32 %0,[%1];" : "=r"(v) : "l"(p) : "memory"); return v;
}
__device__ __forceinline__ void st_relaxed(void* p, uint32_t v) { asm volatile("st.relaxed.gpu.global.b32 [%0],%1;" ::"l"(p), "r"(v) : "memory"); }
__device__ __forceinline__ void st_relaxed4(void* p, uint32_t v) { asm volatile("st.relaxed.gpu.global.v4.b32 [%0],{%1,%1,%1,%1};" ::"l"(p), "r"(v) : "memory"); }

__device__ __forceinline__ uint32_t ld_acquire(const void* p) {
  uint32_t v; asm volatile("ld.acquire.gpu.global.u32 %0,[%1];" : "=r"(v) : "l"(p) : "memory"); return v;
}
__device__ __forceinline__ float4 ld_relaxed4f(const void* p) {
  float4 v; asm volatile("ld.relaxed.gpu.global.v4.f32 {%0,%1,%2,%3},[%4];" : "=f"(v.x), "=f"(v.y), "=f"(v.z), "=f"(v.w) : "l"(p) : "memory"); return v;
}
__device__ __forceinline__ float2 ld_relaxed2f(const void* p) {
  float2 v; asm volatile("ld.relaxed.gpu.global.v2.f32 {%0,%1},[%2];" : "=f"(v.x), "=f"(v.y) : "l"(p) : "memory"); return v;
}
__device__ __forceinline__ void prefetch_l2(const void* p) { asm volatile("prefetch.global.L2 [%0];" ::"l"(p)); }
__device__ __forceinline__ void fence_gpu() { asm volatile("fence.acq_rel.gpu;" ::: "memory"); }
#define FAG 1
__device__ __forceinline__ void fence_async_all() {
  asm volatile("fence.proxy.async.global;" ::: "memory");
}
__device__ __forceinline__ uint32_t* cnt_ptr(int kind, int layer, int b) { return &g_cnt[kind][layer][b][0]; }
#define RELS 1
__device__ __forceinline__ void cnt_signal(int kind, int layer, int b) {
  asm volatile("red.release.gpu.global.add.u32 [%0],1;" ::"l"(cnt_ptr(kind, layer, b)) : "memory");
}
#define ACQW 1
#define SIGF 1
#define HOIST 2
__device__ __forceinline__ void cnt_wait(int kind, int layer, int b, uint32_t target, int& dead) {
  int n = dead ? SPIN_CNT : 0;
  while (ld_acquire(cnt_ptr(kind, layer, b)) < target) { if (++n > SPIN_CNT) { dead = 1; g_err = 10 + kind; break; } }
}

__device__ __forceinline__ uint64_t mkdesc(uint32_t addr, uint32_t lbo, uint32_t sbo) {
  return (uint64_t)((addr & 0x3FFFF) >> 4) | ((uint64_t)(lbo >> 4) << 16) | ((uint64_t)(sbo >> 4) << 32) | ((uint64_t)1 << 62);
}
__device__ __forceinline__ uint64_t mkdesc_ns(uint32_t addr, uint32_t lbo, uint32_t sbo) {
  return (uint64_t)((addr & 0x3FFFF) >> 4) | ((uint64_t)(lbo >> 4) << 16) | ((uint64_t)(sbo >> 4) << 32);
}
__device__ __forceinline__ void wg_fence() { asm volatile("wgmma.fence.sync.aligned;" ::: "memory"); }
__device__ __forceinline__ void wg_commit() { asm volatile("wgmma.commit_group.sync.aligned;" ::: "memory"); }
template <int N> __device__ __forceinline__ void wg_wait() { asm volatile("wgmma.wait_group.sync.aligned %0;" ::"n"(N) : "memory"); }

__device__ __forceinline__ void wgmma_rs16(float (&d)[8], const uint32_t (&a)[4], uint64_t db, int sc) {
  asm volatile("{.reg .pred p; setp.ne.b32 p,%13,0; wgmma.mma_async.sync.aligned.m64n16k16.f32.bf16.bf16 "
               "{%0,%1,%2,%3,%4,%5,%6,%7},{%8,%9,%10,%11},%12,p,1,1,0;}"
               : "+f"(d[0]), "+f"(d[1]), "+f"(d[2]), "+f"(d[3]), "+f"(d[4]), "+f"(d[5]), "+f"(d[6]), "+f"(d[7])
               : "r"(a[0]), "r"(a[1]), "r"(a[2]), "r"(a[3]), "l"(db), "r"(sc));
}
__device__ __forceinline__ void wgmma_rs64(float (&d)[32], const uint32_t (&a)[4], uint64_t db, int sc) {
  asm volatile("{.reg .pred p; setp.ne.b32 p,%37,0; wgmma.mma_async.sync.aligned.m64n64k16.f32.bf16.bf16 "
               "{%0,%1,%2,%3,%4,%5,%6,%7,%8,%9,%10,%11,%12,%13,%14,%15,%16,%17,%18,%19,%20,%21,%22,%23,%24,%25,%26,%27,%28,%29,%30,%31},{%32,%33,%34,%35},%36,p,1,1,0;}"
               : "+f"(d[0]), "+f"(d[1]), "+f"(d[2]), "+f"(d[3]), "+f"(d[4]), "+f"(d[5]), "+f"(d[6]), "+f"(d[7]), "+f"(d[8]), "+f"(d[9]), "+f"(d[10]), "+f"(d[11]), "+f"(d[12]), "+f"(d[13]), "+f"(d[14]), "+f"(d[15]), "+f"(d[16]), "+f"(d[17]), "+f"(d[18]), "+f"(d[19]), "+f"(d[20]), "+f"(d[21]), "+f"(d[22]), "+f"(d[23]), "+f"(d[24]), "+f"(d[25]), "+f"(d[26]), "+f"(d[27]), "+f"(d[28]), "+f"(d[29]), "+f"(d[30]), "+f"(d[31])
               : "r"(a[0]), "r"(a[1]), "r"(a[2]), "r"(a[3]), "l"(db), "r"(sc));
}
__device__ __forceinline__ void wgmma_rt16(float (&d)[8], const uint32_t (&a)[4], uint64_t db, int sc) {
  asm volatile("{.reg .pred p; setp.ne.b32 p,%13,0; wgmma.mma_async.sync.aligned.m64n16k16.f32.bf16.bf16 "
               "{%0,%1,%2,%3,%4,%5,%6,%7},{%8,%9,%10,%11},%12,p,1,1,1;}"
               : "+f"(d[0]), "+f"(d[1]), "+f"(d[2]), "+f"(d[3]), "+f"(d[4]), "+f"(d[5]), "+f"(d[6]), "+f"(d[7])
               : "r"(a[0]), "r"(a[1]), "r"(a[2]), "r"(a[3]), "l"(db), "r"(sc));
}
__device__ __forceinline__ void wgmma_rt80(float (&d)[40], const uint32_t (&a)[4], uint64_t db, int sc) {
  asm volatile("{.reg .pred p; setp.ne.b32 p,%45,0; wgmma.mma_async.sync.aligned.m64n80k16.f32.bf16.bf16 "
               "{%0,%1,%2,%3,%4,%5,%6,%7,%8,%9,%10,%11,%12,%13,%14,%15,%16,%17,%18,%19,%20,%21,%22,%23,%24,%25,%26,%27,%28,%29,%30,%31,%32,%33,%34,%35,%36,%37,%38,%39},{%40,%41,%42,%43},%44,p,1,1,1;}"
               : "+f"(d[0]), "+f"(d[1]), "+f"(d[2]), "+f"(d[3]), "+f"(d[4]), "+f"(d[5]), "+f"(d[6]), "+f"(d[7]), "+f"(d[8]), "+f"(d[9]), "+f"(d[10]), "+f"(d[11]), "+f"(d[12]), "+f"(d[13]), "+f"(d[14]), "+f"(d[15]), "+f"(d[16]), "+f"(d[17]), "+f"(d[18]), "+f"(d[19]), "+f"(d[20]), "+f"(d[21]), "+f"(d[22]), "+f"(d[23]), "+f"(d[24]), "+f"(d[25]), "+f"(d[26]), "+f"(d[27]), "+f"(d[28]), "+f"(d[29]), "+f"(d[30]), "+f"(d[31]), "+f"(d[32]), "+f"(d[33]), "+f"(d[34]), "+f"(d[35]), "+f"(d[36]), "+f"(d[37]), "+f"(d[38]), "+f"(d[39])
               : "r"(a[0]), "r"(a[1]), "r"(a[2]), "r"(a[3]), "l"(db), "r"(sc));
}
__device__ __forceinline__ void wgmma_ts16(float (&d)[8], uint64_t da, uint64_t db, int sc) {
  asm volatile("{.reg .pred p; setp.ne.b32 p,%10,0; wgmma.mma_async.sync.aligned.m64n16k16.f32.bf16.bf16 "
               "{%0,%1,%2,%3,%4,%5,%6,%7},%8,%9,p,1,1,1,0;}"
               : "+f"(d[0]), "+f"(d[1]), "+f"(d[2]), "+f"(d[3]), "+f"(d[4]), "+f"(d[5]), "+f"(d[6]), "+f"(d[7])
               : "l"(da), "l"(db), "r"(sc));
}
__device__ __forceinline__ void wgmma_ts64(float (&d)[32], uint64_t da, uint64_t db, int sc) {
  asm volatile("{.reg .pred p; setp.ne.b32 p,%34,0; wgmma.mma_async.sync.aligned.m64n64k16.f32.bf16.bf16 "
               "{%0,%1,%2,%3,%4,%5,%6,%7,%8,%9,%10,%11,%12,%13,%14,%15,%16,%17,%18,%19,%20,%21,%22,%23,%24,%25,%26,%27,%28,%29,%30,%31},%32,%33,p,1,1,1,0;}"
               : "+f"(d[0]), "+f"(d[1]), "+f"(d[2]), "+f"(d[3]), "+f"(d[4]), "+f"(d[5]), "+f"(d[6]), "+f"(d[7]), "+f"(d[8]), "+f"(d[9]), "+f"(d[10]), "+f"(d[11]), "+f"(d[12]), "+f"(d[13]), "+f"(d[14]), "+f"(d[15]), "+f"(d[16]), "+f"(d[17]), "+f"(d[18]), "+f"(d[19]), "+f"(d[20]), "+f"(d[21]), "+f"(d[22]), "+f"(d[23]), "+f"(d[24]), "+f"(d[25]), "+f"(d[26]), "+f"(d[27]), "+f"(d[28]), "+f"(d[29]), "+f"(d[30]), "+f"(d[31])
               : "l"(da), "l"(db), "r"(sc));
}
__device__ __forceinline__ void wgmma_tt16(float (&d)[8], uint64_t da, uint64_t db, int sc) {
  asm volatile("{.reg .pred p; setp.ne.b32 p,%10,0; wgmma.mma_async.sync.aligned.m64n16k16.f32.bf16.bf16 "
               "{%0,%1,%2,%3,%4,%5,%6,%7},%8,%9,p,1,1,1,1;}"
               : "+f"(d[0]), "+f"(d[1]), "+f"(d[2]), "+f"(d[3]), "+f"(d[4]), "+f"(d[5]), "+f"(d[6]), "+f"(d[7])
               : "l"(da), "l"(db), "r"(sc));
}
__device__ __forceinline__ void wgmma_tt40(float (&d)[20], uint64_t da, uint64_t db, int sc) {
  asm volatile("{.reg .pred p; setp.ne.b32 p,%22,0; wgmma.mma_async.sync.aligned.m64n40k16.f32.bf16.bf16 "
               "{%0,%1,%2,%3,%4,%5,%6,%7,%8,%9,%10,%11,%12,%13,%14,%15,%16,%17,%18,%19},%20,%21,p,1,1,1,1;}"
               : "+f"(d[0]), "+f"(d[1]), "+f"(d[2]), "+f"(d[3]), "+f"(d[4]), "+f"(d[5]), "+f"(d[6]), "+f"(d[7]), "+f"(d[8]), "+f"(d[9]), "+f"(d[10]), "+f"(d[11]), "+f"(d[12]), "+f"(d[13]), "+f"(d[14]), "+f"(d[15]), "+f"(d[16]), "+f"(d[17]), "+f"(d[18]), "+f"(d[19])
               : "l"(da), "l"(db), "r"(sc));
}
__device__ __forceinline__ void wgmma_ss8(float (&d)[4], uint64_t da, uint64_t db, int sc) {
  asm volatile("{.reg .pred p; setp.ne.b32 p,%6,0; wgmma.mma_async.sync.aligned.m64n8k16.f32.bf16.bf16 "
               "{%0,%1,%2,%3},%4,%5,p,1,1,0,0;}"
               : "+f"(d[0]), "+f"(d[1]), "+f"(d[2]), "+f"(d[3])
               : "l"(da), "l"(db), "r"(sc));
}
__device__ __forceinline__ void wgmma_ss32(float (&d)[16], uint64_t da, uint64_t db, int sc) {
  asm volatile("{.reg .pred p; setp.ne.b32 p,%18,0; wgmma.mma_async.sync.aligned.m64n32k16.f32.bf16.bf16 "
               "{%0,%1,%2,%3,%4,%5,%6,%7,%8,%9,%10,%11,%12,%13,%14,%15},%16,%17,p,1,1,0,0;}"
               : "+f"(d[0]), "+f"(d[1]), "+f"(d[2]), "+f"(d[3]), "+f"(d[4]), "+f"(d[5]), "+f"(d[6]), "+f"(d[7]), "+f"(d[8]), "+f"(d[9]), "+f"(d[10]), "+f"(d[11]), "+f"(d[12]), "+f"(d[13]), "+f"(d[14]), "+f"(d[15])
               : "l"(da), "l"(db), "r"(sc));
}
__device__ __forceinline__ void wgmma_st64(float (&d)[32], uint64_t da, uint64_t db, int sc) {
  asm volatile("{.reg .pred p; setp.ne.b32 p,%34,0; wgmma.mma_async.sync.aligned.m64n64k16.f32.bf16.bf16 "
               "{%0,%1,%2,%3,%4,%5,%6,%7,%8,%9,%10,%11,%12,%13,%14,%15,%16,%17,%18,%19,%20,%21,%22,%23,%24,%25,%26,%27,%28,%29,%30,%31},%32,%33,p,1,1,0,1;}"
               : "+f"(d[0]), "+f"(d[1]), "+f"(d[2]), "+f"(d[3]), "+f"(d[4]), "+f"(d[5]), "+f"(d[6]), "+f"(d[7]), "+f"(d[8]), "+f"(d[9]), "+f"(d[10]), "+f"(d[11]), "+f"(d[12]), "+f"(d[13]), "+f"(d[14]), "+f"(d[15]), "+f"(d[16]), "+f"(d[17]), "+f"(d[18]), "+f"(d[19]), "+f"(d[20]), "+f"(d[21]), "+f"(d[22]), "+f"(d[23]), "+f"(d[24]), "+f"(d[25]), "+f"(d[26]), "+f"(d[27]), "+f"(d[28]), "+f"(d[29]), "+f"(d[30]), "+f"(d[31])
               : "l"(da), "l"(db), "r"(sc));
}
__device__ __forceinline__ void wgmma_st128(float (&d)[64], uint64_t da, uint64_t db, int sc) {
  asm volatile("{.reg .pred p; setp.ne.b32 p,%66,0; wgmma.mma_async.sync.aligned.m64n128k16.f32.bf16.bf16 "
               "{%0,%1,%2,%3,%4,%5,%6,%7,%8,%9,%10,%11,%12,%13,%14,%15,%16,%17,%18,%19,%20,%21,%22,%23,%24,%25,%26,%27,%28,%29,%30,%31,%32,%33,%34,%35,%36,%37,%38,%39,%40,%41,%42,%43,%44,%45,%46,%47,%48,%49,%50,%51,%52,%53,%54,%55,%56,%57,%58,%59,%60,%61,%62,%63},%64,%65,p,1,1,0,1;}"
               : "+f"(d[0]), "+f"(d[1]), "+f"(d[2]), "+f"(d[3]), "+f"(d[4]), "+f"(d[5]), "+f"(d[6]), "+f"(d[7]), "+f"(d[8]), "+f"(d[9]), "+f"(d[10]), "+f"(d[11]), "+f"(d[12]), "+f"(d[13]), "+f"(d[14]), "+f"(d[15]), "+f"(d[16]), "+f"(d[17]), "+f"(d[18]), "+f"(d[19]), "+f"(d[20]), "+f"(d[21]), "+f"(d[22]), "+f"(d[23]), "+f"(d[24]), "+f"(d[25]), "+f"(d[26]), "+f"(d[27]), "+f"(d[28]), "+f"(d[29]), "+f"(d[30]), "+f"(d[31]), "+f"(d[32]), "+f"(d[33]), "+f"(d[34]), "+f"(d[35]), "+f"(d[36]), "+f"(d[37]), "+f"(d[38]), "+f"(d[39]), "+f"(d[40]), "+f"(d[41]), "+f"(d[42]), "+f"(d[43]), "+f"(d[44]), "+f"(d[45]), "+f"(d[46]), "+f"(d[47]), "+f"(d[48]), "+f"(d[49]), "+f"(d[50]), "+f"(d[51]), "+f"(d[52]), "+f"(d[53]), "+f"(d[54]), "+f"(d[55]), "+f"(d[56]), "+f"(d[57]), "+f"(d[58]), "+f"(d[59]), "+f"(d[60]), "+f"(d[61]), "+f"(d[62]), "+f"(d[63])
               : "l"(da), "l"(db), "r"(sc));
}

__device__ __forceinline__ void stsm4(uint32_t a, uint32_t r0, uint32_t r1, uint32_t r2, uint32_t r3) {
  asm volatile("stmatrix.sync.aligned.m8n8.x4.shared.b16 [%0],{%1,%2,%3,%4};" ::"r"(a), "r"(r0), "r"(r1), "r"(r2), "r"(r3) : "memory");
}
__device__ __forceinline__ void stsm4t(uint32_t a, uint32_t r0, uint32_t r1, uint32_t r2, uint32_t r3) {
  asm volatile("stmatrix.sync.aligned.m8n8.x4.trans.shared.b16 [%0],{%1,%2,%3,%4};" ::"r"(a), "r"(r0), "r"(r1), "r"(r2), "r"(r3) : "memory");
}
__device__ __forceinline__ void sts64(uint32_t a, uint32_t x, uint32_t y) { asm volatile("st.shared.v2.b32 [%0],{%1,%2};" ::"r"(a), "r"(x), "r"(y) : "memory"); }
__device__ __forceinline__ void st_async2u(uint32_t a, uint32_t x, uint32_t y, uint32_t bar) {
  asm volatile("st.async.weak.shared::cluster.mbarrier::complete_tx::bytes.v2.b32 [%0],{%1,%2},[%3];" ::"r"(a), "r"(x), "r"(y), "r"(bar) : "memory");
}
__device__ __forceinline__ void st_relaxed128(void* p, uint32_t x, uint32_t y, uint32_t z, uint32_t w) {
  asm volatile("{.reg .b128 v; .reg .b64 lo, hi; mov.b64 lo,{%1,%2}; mov.b64 hi,{%3,%4}; mov.b128 v,{lo,hi}; st.relaxed.gpu.global.b128 [%0],v;}" ::"l"(p), "r"(x), "r"(y), "r"(z), "r"(w) : "memory");
}
__device__ __forceinline__ void st_relaxed64(void* p, uint32_t x, uint32_t y) {
  asm volatile("{.reg .b64 v; mov.b64 v,{%1,%2}; st.relaxed.gpu.global.b64 [%0],v;}" ::"l"(p), "r"(x), "r"(y) : "memory");
}
__device__ __forceinline__ uint4 ld_relaxed128(const void* p) {
  uint4 v;
  asm volatile("{.reg .b128 v; .reg .b64 lo, hi; ld.relaxed.gpu.global.b128 v,[%4]; mov.b128 {lo,hi},v; mov.b64 {%0,%1},lo; mov.b64 {%2,%3},hi;}" : "=r"(v.x), "=r"(v.y), "=r"(v.z), "=r"(v.w) : "l"(p) : "memory");
  return v;
}

__device__ __forceinline__ uint32_t pack_h2(float lo, float hi) {
  uint32_t r; asm("cvt.rn.satfinite.f16x2.f32 %0,%1,%2;" : "=r"(r) : "f"(hi), "f"(lo)); return r;
}
__device__ __forceinline__ void add_h2(float& lo, float& hi, uint32_t u, uint32_t v) {
  float a, b;
  asm("{.reg .b16 l, h; .reg .b32 s; add.rn.f16x2 s,%2,%3; mov.b32 {l,h},s; cvt.f32.f16 %0,l; cvt.f32.f16 %1,h;}" : "=f"(a), "=f"(b) : "r"(u), "r"(v));
  lo += a; hi += b;
}
constexpr int SPIN_TOT = 1 << 22;
__device__ __forceinline__ void mwait(uint32_t bar, uint32_t ph, int& spin) {
  asm volatile("{.reg .pred p, q;\nWAIT_LOOP:\n mbarrier.try_wait.parity.shared::cta.b64 p,[%1],%2;\n @!p add.s32 %0,%0,1;\n setp.lt.and.s32 q,%0,%3,!p;\n @q bra WAIT_LOOP;\n}"
               : "+r"(spin) : "r"(bar), "r"(ph), "n"(SPIN_TOT) : "memory");
}
__device__ __forceinline__ uint32_t pin(uint32_t x) { asm volatile("" : "+r"(x)); return x; }
template <typename T> __device__ __forceinline__ T* pinp(T* x) { asm volatile("" : "+l"(x)); return x; }
__device__ __forceinline__ void st_async1u(uint32_t a, uint32_t x, uint32_t bar) {
  asm volatile("st.async.weak.shared::cluster.mbarrier::complete_tx::bytes.b32 [%0],%1,[%2];" ::"r"(a), "r"(x), "r"(bar) : "memory");
}
__device__ __forceinline__ uint32_t lds32(uint32_t a) { uint32_t v; asm volatile("ld.shared.b32 %0,[%1];" : "=r"(v) : "r"(a) : "memory"); return v; }
__device__ __forceinline__ uint2 lds64(uint32_t a) { uint2 v; asm volatile("ld.shared.v2.b32 {%0,%1},[%2];" : "=r"(v.x), "=r"(v.y) : "r"(a) : "memory"); return v; }

__device__ __forceinline__ void ln_row_to_image(const bf16* __restrict__ x, uint8_t* __restrict__ img, int row, int lane) {
  const uint4* src = reinterpret_cast<const uint4*>(x + (size_t)row * DM);
  uint4 v[3];
  v[0] = src[lane]; v[1] = src[lane + 32];
  v[2] = lane < 16 ? src[lane + 64] : make_uint4(0, 0, 0, 0);
  float s = 0.f;
#pragma unroll
  for (int i = 0; i < 3; i++) {
    s += bf_lo(v[i].x) + bf_hi(v[i].x) + bf_lo(v[i].y) + bf_hi(v[i].y) + bf_lo(v[i].z) + bf_hi(v[i].z) + bf_lo(v[i].w) + bf_hi(v[i].w);
  }
#pragma unroll
  for (int o = 16; o > 0; o >>= 1) s += __shfl_xor_sync(0xffffffffu, s, o);
  const float mean = s * (1.f / DM);
  float q = 0.f;
#pragma unroll
  for (int i = 0; i < 3; i++) {
    if (i < 2 || lane < 16) {
      const uint32_t w[4] = {v[i].x, v[i].y, v[i].z, v[i].w};
#pragma unroll
      for (int j = 0; j < 4; j++) { float a = bf_lo(w[j]) - mean, b = bf_hi(w[j]) - mean; q += a * a + b * b; }
    }
  }
#pragma unroll
  for (int o = 16; o > 0; o >>= 1) q += __shfl_xor_sync(0xffffffffu, q, o);
  const float rstd = rsqrtf(q * (1.f / DM) + 1e-5f);
#pragma unroll
  for (int i = 0; i < 3; i++) {
    if (i < 2 || lane < 16) {
      const int c = lane + 32 * i;
      uint4 o;
      o.x = pack_bf16((bf_lo(v[i].x) - mean) * rstd, (bf_hi(v[i].x) - mean) * rstd);
      o.y = pack_bf16((bf_lo(v[i].y) - mean) * rstd, (bf_hi(v[i].y) - mean) * rstd);
      o.z = pack_bf16((bf_lo(v[i].z) - mean) * rstd, (bf_hi(v[i].z) - mean) * rstd);
      o.w = pack_bf16((bf_lo(v[i].w) - mean) * rstd, (bf_hi(v[i].w) - mean) * rstd);
      const size_t off = (size_t)(row >> 5) * 40960 + (c >> 4) * 8192 + ((row >> 3) & 3) * 2048 + ((c >> 3) & 1) * 1024 + (row & 7) * 128 + (((c & 7) ^ (row & 7)) << 4);
      *reinterpret_cast<uint4*>(img + off) = o;
    }
  }
}

#define LN30 1
__global__ void __launch_bounds__(256) k_pre(const bf16* __restrict__ x, const bf16* __restrict__ mem0) {
  const int row = blockIdx.x * 8 + (threadIdx.x >> 5);
  ln_row_to_image(x, g_xn[0], row, threadIdx.x & 31);
  const int gt = blockIdx.x * 256 + threadIdx.x;
  const uint4 sent = make_uint4(SENT, SENT, SENT, SENT);
  uint4* mail = reinterpret_cast<uint4*>(&g_mail[0][0]);
  for (int i = gt; i < 2 * MAIL_BYTES / 16; i += 65536) mail[i] = sent;
  uint4* mb = reinterpret_cast<uint4*>(&g_mbuf[0][0]);
  for (int i = gt; i < NSTEP * 1280; i += 65536) {
    const int p = i % 1280, st = i / 1280;
    uint4 v = sent;
    if (st == 0 || (st == LAG && (p & 8))) v = *reinterpret_cast<const uint4*>(mem0 + (p & 7) * DM + (p >> 4) * 8);
    mb[i] = v;
  }
  if (gt < 16 * 128 * 8) reinterpret_cast<uint4*>(&g_stats[0][0][0])[gt] = sent;
  if (gt < 6 * 2 * 16 * 8) reinterpret_cast<uint4*>(&g_cnt[0][0][0][0])[gt] = make_uint4(0, 0, 0, 0);
}

namespace C {
constexpr int NKR = 37;
constexpr int OFF_WQ = 0, OFF_WK = 81920;
constexpr int OFF_YO = 163840, OFF_YV = OFF_YO + 6144;
constexpr int OFF_M = 176128;
constexpr int OFF_STG = OFF_M;
constexpr int OFF_OG = OFF_M + 14336;
constexpr int OFF_KT = 196608;
constexpr int OFF_XT = OFF_KT + 10240;
constexpr int OFF_VT = OFF_XT + 7168;
constexpr int OFF_XM = OFF_VT + 11392;
constexpr int KS = 1280, VS = 1408;
__host__ __device__ constexpr int slot_off(int p) { return p == 2 ? OFF_M : OFF_KT + (p % 3) * 16384; }
constexpr int OFF_BAR = 231552;
constexpr int OFF_SAFE = OFF_BAR + 160;
constexpr int OFF_TS = OFF_BAR + 256;
constexpr int SMEM = 232448;
constexpr uint32_t SB0 = 1024;
constexpr int BAR_F = OFF_BAR, BAR_E = OFF_BAR + 40, BAR_M = OFF_BAR + 80, BAR_MOK = OFF_BAR + 88, BAR_XM = OFF_BAR + 96, BAR_XF = OFF_BAR + 104,
              BAR_XT = OFF_BAR + 112, BAR_MF = OFF_BAR + 120, BAR_OG = OFF_BAR + 128, BAR_W = OFF_BAR + 136;
constexpr int NB_PRO = 1, NB_RD = 2, NB_MR = 3, NB_QK = 4, NB_SM = 5, NB_VA = 6, NB_VQ = 7, NB_A = 8, NB_Q = 9, NB_C = 10, NB_WQ = 11, NB_QI = 12, NB_SI = 13, NB_WV = 14;
#define B1 300
#define B2 400
#define PSTG 150
#define KSP 40
#define OGF 0
#define VSP 8
#define RFK 5
#define PFD 3
#define WOL 0
#define NOWORK 0
constexpr float SCL = 0.07216878364870322f * 1.4426950408889634f / 256;
}

#define CBAR_SYNC(id, n) bar_sync(id, n)
#define CBAR_ARRIVE(id, n) bar_arrive(id, n)

__device__ __forceinline__ uint64_t wdesc(int off) { return mkdesc(C::SB0 + off, 8192, 1024); }
__device__ __forceinline__ uint64_t mdesc(int k) { return mkdesc_ns(C::SB0 + C::OFF_M + k * 512, 256, 128); }
__device__ __forceinline__ uint64_t tdesc(int k) { return mkdesc(C::SB0 + C::slot_off(k >> 3) + ((k >> 2) & 1) * 1024 + (k & 3) * 32, 16, 2048); }

__device__ __forceinline__ void load_weights_rs(uint32_t (&wf)[C::NKR][4], uint32_t sb, int stage, int yoff, int tid0) {
  using namespace C;
  const int i = (tid0 >> 3) & 3, r = tid0 & 7;
  const int chunk = 2 * ((tid0 >> 5) & 3) + (i & 1);
  const uint32_t a0 = sb + stage + (r + (i >> 1) * 8) * 128 + ((chunk ^ r) << 4);
#pragma unroll
  for (int k = 0; k < NKR; k++) ldsm4t(wf[k], a0 + k * 2048);
#pragma unroll
  for (int k = 0; k < 40 - NKR; k++) sts128(sb + yoff + k * 2048 + (tid0 & 127) * 16, lds128(sb + stage + (NKR + k) * 2048 + (tid0 & 127) * 16));
  fence_async();
  CBAR_SYNC(NB_PRO, 384);
}
template <int STRIDE>
__device__ __forceinline__ void store_mem(const float (&d)[8], uint32_t base, int tid) {
  const int m = (tid >> 3) & 3;
  stsm4(base + (((tid >> 5) & 3) * 2 + (m & 1)) * STRIDE + (m >> 1) * 640 + (tid & 7) * 16, pack_bf16(d[0], d[1]), pack_bf16(d[2], d[3]),
        pack_bf16(d[4], d[5]), pack_bf16(d[6], d[7]));
}

__device__ __forceinline__ void load_pair(uint32_t sb, int i, int p, uint32_t slot) {
  using namespace C;
  const uint8_t* s0 = g_xn[0] + (size_t)i * 40960 + p * 8192;
  const uint8_t* s1 = g_xn[NOWORK ? 0 : 1] + (size_t)(i - LAG) * 40960 + p * 8192;
  bulk_g2s_mc(sb + slot, i < NSEG ? s0 : s1, 8192, sb + BAR_F + 8 * p);
  bulk_g2s_mc(sb + slot + 8192, i >= LAG ? s1 : s0, 8192, sb + BAR_F + 8 * p);
}
__device__ __forceinline__ void first_fill(uint32_t sb, int i, int p, uint32_t slot, int& spin) {
  using namespace C;
  const int s1 = i - LAG;
  if (!NOWORK && s1 >= 0 && (s1 & 3) == 0) {
    while (ld_acquire(cnt_ptr(CN_X, 0, s1 >> 2)) < 5 && spin < SPIN_TOT) spin += 16;
    fence_async_all();
  }
  if (i > 0) mwait(sb + BAR_E + 8 * p, (i - 1) & 1, spin);
  load_pair(sb, i, p, slot);
}
__device__ __forceinline__ void release_round(uint32_t sb, int p, int tid) {
  using namespace C;
  const int lane = tid & 31;
  if (p < 2) { if (lane == 0) mbar_arrive_cluster(mapa(sb, p) + BAR_E + 8 * (3 + p)); }
  else if (lane < 3) mbar_arrive_cluster(mapa(sb, lane) + BAR_MOK);
}

template <int K0, int K1>
__device__ __forceinline__ void v_mem_pass(float (&d)[8], const uint32_t (&wf)[C::NKR][4]) {
  using namespace C;
  wg_fence();
#pragma unroll
  for (int k = K0; k < K1; k++) {
    if (k < NKR) wgmma_rs16(d, wf[k < NKR ? k : 0], mdesc(k), k);
    else wgmma_ts16(d, wdesc(OFF_YV + (k - NKR) * 2048), mdesc(k), 1);
  }
  wg_commit();
}
__device__ __forceinline__ void chain_v(const uint32_t sb, const int tid0, const int cta, const int rank) {
  using namespace C;
  asm volatile("setmaxnreg.inc.sync.aligned.u32 208;");
  int spin = 0;
  uint32_t wf[NKR][4];
  if (tid0 == 256) first_fill(sb, 0, rank, rank == 2 ? OFF_M : OFF_KT + rank * 16384, spin);
  __syncwarp();
  mwait(sb + BAR_W, 0, spin);
  load_weights_rs(wf, sb, OFF_WK, OFF_YV, tid0);
#pragma unroll 1
  for (int i = 0; i < NSTEP; i++) {
    {
      float d[32];
      if (i > 0) CBAR_SYNC(NB_WV, 256);
#pragma unroll
      for (int p = 0; p < 5; p++) {
        mwait(sb + BAR_F + 8 * p, i & 1, spin);
        TS(i, 25 + p);
        wg_fence();
#pragma unroll
        for (int k = 8 * p; k < 8 * p + 8; k++) {
          if (k < NKR) wgmma_rs64(d, wf[k < NKR ? k : 0], tdesc(k), k);
          else wgmma_ts64(d, wdesc(OFF_YV + (k - NKR) * 2048), tdesc(k), 1);
          if (k == 8 * p + 1 && p >= 1 && p <= 3) {
            wg_commit(); wg_wait<1>();
            release_round(sb, p - 1, fresh(tid0));
            wg_fence();
          }
          if (k == 8 * p + RFK && (p == 1 || p == 2)) {
            wg_commit();
            if (rank == p - 1 && tid0 == 256) { mwait(sb + BAR_E + 8 * (p + 2), i & 1, spin); load_pair(sb, i, p + 2, slot_off(p + 2)); }
            __syncwarp();
            wg_fence();
          }
        }
        wg_commit();
      }
      wg_wait<0>();
      TS(i, 23);
      CBAR_SYNC(NB_RD, 256);
      const int tid = fresh(tid0) & 127, m = (tid >> 3) & 3;
      if (tid >= 96) {
        if (tid < 101) { if (i + 1 < NSTEP) mbar_expect_tx(sb + BAR_F + 8 * (tid - 96), 16384); }
        else if (tid == 101) mbar_expect_tx(sb + BAR_XM, 2560);
        else if (tid == 102) mbar_expect_tx(sb + BAR_XT, 7168);
        else if (tid == 103) mbar_expect_tx(sb + BAR_OG, 4096);
        else if (tid < 106) mbar_arrive_cluster(mapa(sb, (rank + tid - 103) % 3) + BAR_XF);
        __syncwarp();
      }
      const uint32_t a = sb + OFF_VT + 256 + ((tid >> 5) * 2 + (m & 1)) * VS + (m >> 1) * 128 + (tid & 7) * 16;
#pragma unroll
      for (int s = 0; s < 4; s++)
        stsm4(a + (s & 1) * 256 + (s >> 1) * 640, pack_bf16(d[8 * s], d[8 * s + 1]), pack_bf16(d[8 * s + 2], d[8 * s + 3]),
              pack_bf16(d[8 * s + 4], d[8 * s + 5]), pack_bf16(d[8 * s + 6], d[8 * s + 7]));
      if (tid < 72) sts128(sb + OFF_VT + (tid >> 3) * VS + (tid & 7) * 16, make_uint4(0, 0, 0, 0));
      fence_async();
    }
    CBAR_ARRIVE(NB_QK, 384);
    CBAR_SYNC(NB_QI, 256);
    float d[8];
    v_mem_pass<0, VSP>(d, wf);
    CBAR_SYNC(NB_SM, 256);
    v_mem_pass<VSP, 40>(d, wf);
    wg_wait<0>();
    TS(i, 24);
    const int tid = fresh(tid0);
    if ((tid & 31) < 2) mbar_arrive_cluster(mapa(sb, (rank + 1 + (tid & 1)) % 3) + BAR_MF);
    store_mem<VS>(d, sb + OFF_VT + 128, tid);
    fence_async();
    CBAR_ARRIVE(NB_VA, 256);
    CBAR_ARRIVE(NB_VQ, 256);
    if (tid == 256) {
      if (rank < 2 && i + 1 < NSTEP) { first_fill(sb, i + 1, rank, OFF_KT + rank * 16384, spin); TS1(i + 1, 37); }
    } else if (tid >= 288 && tid < 294) {
      const int lane = tid & 31, ip = i + PFD;
      if (cta < 80 && ip < NSTEP) {
        if (lane < 2) prefetch_l2(g_mbuf[ip] + (cta * 2 + lane) * 128);
        else if (ip < NSEG) prefetch_l2(g_xn[0] + (size_t)ip * 40960 + (cta * 4 + lane - 2) * 128);
      }
    }
    TS_FLUSH(i - 1);
    __syncwarp();
  }
  if (spin >= SPIN_TOT) g_err = 3;
}

__device__ __forceinline__ float quad_max(float x) {
  const float a = __shfl_xor_sync(0xffffffffu, x, 1), b = __shfl_xor_sync(0xffffffffu, x, 2), c = __shfl_xor_sync(0xffffffffu, x, 3);
  return fmaxf(fmaxf(x, a), fmaxf(b, c));
}
__device__ __forceinline__ float quad_sum(float x) {
  const float a = __shfl_xor_sync(0xffffffffu, x, 1), b = __shfl_xor_sync(0xffffffffu, x, 2), c = __shfl_xor_sync(0xffffffffu, x, 3);
  return (x + a) + (b + c);
}
__device__ __forceinline__ float max10(const float (&y)[10]) {
  return fmaxf(fmaxf(fmaxf(fmaxf(y[0], y[1]), fmaxf(y[2], y[3])), fmaxf(fmaxf(y[4], y[5]), fmaxf(y[6], y[7]))), fmaxf(y[8], y[9]));
}
__device__ __forceinline__ float sum10(const float (&y)[10]) {
  return (((y[0] + y[1]) + (y[2] + y[3])) + ((y[4] + y[5]) + (y[6] + y[7]))) + (y[8] + y[9]);
}
__device__ __forceinline__ float rcp(float x) { float y; asm("rcp.approx.ftz.f32 %0,%1;" : "=f"(y) : "f"(x)); return y; }

__device__ __forceinline__ void store_o(uint32_t sb, int i, int cta) {
  const int sg = i - LAG;
  if (i < NSEG) bulk_s2g(g_o[0] + ((size_t)(i >> 1) * 96 + cta) * 8192 + (i & 1) * 4096, sb + C::OFF_STG, 4096);
  if (sg >= 0) bulk_s2g(g_o[1] + ((size_t)(sg >> 1) * 96 + cta) * 8192 + (sg & 1) * 4096, sb + C::OFF_STG + 4096, 4096);
  asm volatile("cp.async.bulk.commit_group;" ::: "memory");
}
__device__ __forceinline__ void signal_o(int i) {
  const int s1 = i - LAG;
  const bool e0 = i < NSEG && (i & 3) == 3, e1 = s1 >= 0 && (s1 & 3) == 3;
  if (e0 || e1) {
    asm volatile("cp.async.bulk.wait_group 0;" ::: "memory");
    fence_async_all();
    if (e0) cnt_signal(CN_O, 0, i >> 2);
    if (e1) cnt_signal(CN_O, 1, s1 >> 2);
  }
}

__device__ __forceinline__ void chain_q(const CUtensorMap& tmWq, const CUtensorMap& tmWk, const uint32_t sb, const int tid0, const int cta, const int rank) {
  using namespace C;
  asm volatile("setmaxnreg.dec.sync.aligned.u32 96;");
  int spin = 0;
  CBAR_SYNC(NB_PRO, 384);
  PTS(5);
  if (tid0 == 128) {
    const int col = (cta / 3) * DH + rank * 64;
    mbar_expect_tx(sb + BAR_W, 163840);
    for (int i = 0; i < 5; i++) {
      tma2d(sb + OFF_WQ + i * 16384, &tmWq, col, i * 128, sb + BAR_W);
      tma2d(sb + OFF_WK + i * 16384, &tmWk, col, i * 128, sb + BAR_W);
    }
  }
  mwait(sb + BAR_W, 1, spin);
  PTS(6);
#pragma unroll 1
  for (int i = 0; i < NSTEP; i++) {
    const int ph = i & 1;
    uint32_t qf[4][4];
    {
      float d[64];
      if (i > 0) CBAR_SYNC(NB_WQ, 256);
#pragma unroll
      for (int p = 0; p < 5; p++) {
        mwait(sb + BAR_F + 8 * p, ph, spin);
        if (p == 0) TS(i, 0);
        wg_fence();
#pragma unroll
        for (int k = 8 * p; k < 8 * p + 8; k++) {
          wgmma_st128(d, tdesc(k), mkdesc(SB0 + OFF_WQ + k * 2048, OFF_WK - OFF_WQ, 1024), k);
          if (k == 8 * p + 1 && p >= 1 && p <= 3) {
            wg_commit(); wg_wait<1>();
            release_round(sb, p - 1, fresh(tid0));
            wg_fence();
          }
        }
        wg_commit();
        if (p < 2 && i > 0) {
          if (tid0 == 224) {
            if (p == 0) {
              store_o(sb, i - 1, cta);
              asm volatile("cp.async.bulk.wait_group.read 0;" ::: "memory");
              mbar_arrive_cluster(mapa(sb, 2) + BAR_E + 16);
              if (rank == 2) { first_fill(sb, i, 2, OFF_M, spin); TS1(i, 37); }
            } else signal_o(i - 1);
          }
          __syncwarp();
        }
      }
      wg_wait<0>();
      TS(i, 1);
      CBAR_SYNC(NB_RD, 256);
      TSB(i, 2);
      const int tid = fresh(tid0), w = (tid >> 5) & 3, m = (tid >> 3) & 3;
      const uint32_t a = sb + OFF_KT + (m >> 1) * KS + (1 + 5 * (w >> 1) + 2 * (w & 1) + (m & 1)) * 128 + (tid & 7) * 16;
#pragma unroll
      for (int s = 0; s < 4; s++)
        stsm4t(a + s * 2 * KS, pack_bf16(d[32 + 8 * s], d[33 + 8 * s]), pack_bf16(d[34 + 8 * s], d[35 + 8 * s]),
               pack_bf16(d[36 + 8 * s], d[37 + 8 * s]), pack_bf16(d[38 + 8 * s], d[39 + 8 * s]));
      fence_async();
      CBAR_ARRIVE(NB_QK, 384);
#pragma unroll
      for (int kk = 0; kk < 4; kk++)
#pragma unroll
        for (int j = 0; j < 4; j++) asm volatile("cvt.rn.bf16x2.f32 %0,%1,%2;" : "=r"(qf[kk][j]) : "f"(d[8 * kk + 2 * j + 1]), "f"(d[8 * kk + 2 * j]));
    }
    CBAR_SYNC(NB_SI, 256);
    uint32_t pf[5][4];
    float s0, s1;
    {
      float y0[10], y1[10];
      const int tid = fresh(tid0), lane = tid & 31, u = (tid >> 5) & 1;
      const bool c1 = tid & 64;
      {
        float x[40];
        wg_fence();
#pragma unroll
        for (int kk = 0; kk < 4; kk++) wgmma_rt80(x, qf[kk], mkdesc_ns(SB0 + OFF_KT + kk * 2 * KS, KS, 128), kk);
        wg_commit();
        mwait(sb + BAR_XF, ph, spin);
        wg_wait<0>();
#pragma unroll
        for (int j = 0; j < 5; j++) {
          y0[2 * j] = (c1 ? x[20 + 4 * j] : x[4 * j]) * SCL; y0[2 * j + 1] = (c1 ? x[21 + 4 * j] : x[4 * j + 1]) * SCL;
          y1[2 * j] = (c1 ? x[22 + 4 * j] : x[4 * j + 2]) * SCL; y1[2 * j + 1] = (c1 ? x[23 + 4 * j] : x[4 * j + 3]) * SCL;
        }
      }
      TS(i, 17);
      const uint32_t xo = OFF_XT + (c1 ? 1792 : 0) + u * 640 + lane * 16, x2 = xo + u * 512 + 512 - lane * 12;
      {
        const uint4 h0 = make_uint4(pack_h2(y0[0], y0[1]), pack_h2(y0[2], y0[3]), pack_h2(y1[0], y1[1]), pack_h2(y1[2], y1[3]));
        const uint4 h1 = make_uint4(pack_h2(y0[4], y0[5]), pack_h2(y0[6], y0[7]), pack_h2(y1[4], y1[5]), pack_h2(y1[6], y1[7]));
        const uint32_t h2 = u ? pack_h2(y1[8], y1[9]) : h1.z;
#pragma unroll
        for (int dd = 0; dd < 2; dd++) {
          const uint32_t rb = mapa(sb, (rank + 1 + dd) % 3), ro = rb + (1 - dd) * 3584;
          st_async4u(ro + xo, h0, rb + BAR_XT);
          if (u) st_async4u(ro + xo + 512, h1, rb + BAR_XT);
          st_async1u(ro + x2, h2, rb + BAR_XT);
        }
      }
      TS(i, 18);
      const int lim = 16 * u + (lane >> 2) + 8 - 2 * (lane & 3);
#pragma unroll
      for (int j = 1; j < 5; j++) {
        if (8 * j > lim) y0[2 * j] = -INFINITY;
        if (8 * j + 1 > lim) y0[2 * j + 1] = -INFINITY;
        if (8 * j - 8 > lim) y1[2 * j] = -INFINITY;
        if (8 * j - 7 > lim) y1[2 * j + 1] = -INFINITY;
      }
      mwait(sb + BAR_XT, ph, spin);
      TS(i, 19);
      {
        const uint4 u0 = lds128(sb + xo), v0 = lds128(sb + xo + 3584);
        const uint32_t u2 = lds32(sb + x2), v2 = lds32(sb + x2 + 3584);
        uint4 u1 = make_uint4(0, 0, u2, 0), v1 = make_uint4(0, 0, v2, 0);
        if (u) { u1 = lds128(sb + xo + 512); v1 = lds128(sb + xo + 512 + 3584); }
        add_h2(y0[0], y0[1], u0.x, v0.x); add_h2(y0[2], y0[3], u0.y, v0.y); add_h2(y1[0], y1[1], u0.z, v0.z); add_h2(y1[2], y1[3], u0.w, v0.w);
        add_h2(y0[4], y0[5], u1.x, v1.x); add_h2(y0[6], y0[7], u1.y, v1.y); add_h2(y1[4], y1[5], u1.z, v1.z); add_h2(y1[6], y1[7], u1.w, v1.w);
        add_h2(y1[8], y1[9], u2, v2);
      }
      y0[8] = y0[0]; y0[9] = y0[1];
      const float m0 = quad_max(max10(y0)) * -256.f, m1 = quad_max(max10(y1)) * -256.f;
      if (lane == 0) mbar_arrive_cluster(mapa(sb, 0) + BAR_E);
      s0 = 0.f; s1 = 0.f;
#pragma unroll
      for (int j = 0; j < 5; j++) {
        const uint32_t p0 = j < 4 ? pack_bf16(ex2(fmaf(y0[2 * j], 256.f, m0)), ex2(fmaf(y0[2 * j + 1], 256.f, m0))) : 0u;
        const uint32_t p1 = pack_bf16(ex2(fmaf(y1[2 * j], 256.f, m1)), ex2(fmaf(y1[2 * j + 1], 256.f, m1)));
        s0 += bf_lo(p0) + bf_hi(p0); s1 += bf_lo(p1) + bf_hi(p1);
        pf[j >> 1][2 * (j & 1)] = c1 ? 0u : p0; pf[j >> 1][2 * (j & 1) + 1] = c1 ? 0u : p1;
        pf[(j + 5) >> 1][2 * ((j + 5) & 1)] = c1 ? p0 : 0u; pf[(j + 5) >> 1][2 * ((j + 5) & 1) + 1] = c1 ? p1 : 0u;
      }
    }
    CBAR_SYNC(NB_VQ, 256);
    TSB(i, 20);
    {
      float o[32];
      wg_fence();
#pragma unroll
      for (int q = 0; q < 5; q++) wgmma_rs64(o, pf[q], mkdesc_ns(SB0 + OFF_VT + 128 + q * 256, 128, VS), q);
      wg_commit();
      s0 = rcp(quad_sum(s0)); s1 = rcp(quad_sum(s1));
      wg_wait<0>();
      TS(i, 21);
      const int tid = fresh(tid0), m = (tid >> 3) & 3, r = tid & 7;
      if ((tid & 31) == 0) mbar_arrive_cluster(mapa(sb, 1) + BAR_E + 8);
      const uint32_t a = sb + OFF_STG + (((tid >> 5) & 3) * 16 + (m & 1) * 8 + r) * 128;
#pragma unroll
      for (int s = 0; s < 4; s++)
        stsm4(a + (((2 * s + (m >> 1)) ^ r) << 4), pack_bf16(o[8 * s] * s0, o[8 * s + 1] * s0), pack_bf16(o[8 * s + 2] * s1, o[8 * s + 3] * s1),
              pack_bf16(o[8 * s + 4] * s0, o[8 * s + 5] * s0), pack_bf16(o[8 * s + 6] * s1, o[8 * s + 7] * s1));
      fence_async();
      CBAR_SYNC(NB_Q, 128);
      TSB(i, 22);
    }
  }
  if (tid0 == 224) store_o(sb, NSTEP - 1, cta);
  if (tid0 == 224) signal_o(NSTEP - 1);
  if (spin >= SPIN_TOT) g_err = 2;
}

template <int NL>
__device__ __forceinline__ void poll_add(const uint8_t* mb, uint32_t tag, float (&f)[8], int& n, int& spin) {
  uint4 x[NL];
#pragma unroll
  for (int i = 0; i < NL; i++) x[i] = ld_relaxed128(mb + i * 512);
  while (true) {
    bool bad = false;
#pragma unroll
    for (int i = 0; i < NL; i++)
      if (((x[i].x ^ tag) | (NL == 6 ? x[i].z ^ tag : 0u)) & 1) { bad = true; x[i] = ld_relaxed128(mb + i * 512); }
    n++;
    spin += 16;
    if (!__any_sync(0xffffffffu, bad && spin < SPIN_TOT)) break;
  }
#pragma unroll
  for (int i = 0; i < NL; i++) {
    const uint32_t u[4] = {x[i].x, x[i].y, x[i].z, x[i].w};
#pragma unroll
    for (int j = 0; j < 4; j++) {
      if (i == 0) { f[2 * j] = bf_lo(u[j]); f[2 * j + 1] = bf_hi(u[j]); }
      else { f[2 * j] += bf_lo(u[j]); f[2 * j + 1] += bf_hi(u[j]); }
    }
  }
}

template <int B, int SLOT>
__device__ __forceinline__ void wo_block(float (&acc)[8], const uint32_t (&wf)[C::NKR][4]) {
  using namespace C;
#pragma unroll
  for (int kk = 0; kk < 4; kk++) {
    const int k = 4 * B + kk;
    const uint64_t db = mkdesc_ns(SB0 + OFF_OG + SLOT * 2048 + kk * 512, 256, 128);
    if (k < NKR) wgmma_rt16(acc, wf[k < NKR ? k : 0], db, SLOT | kk);
    else wgmma_tt16(acc, wdesc(OFF_YO + (k - NKR) * 2048), db, 1);
  }
}

__device__ __forceinline__ void chain_a(const uint32_t sb, const int tid0, const int cta, const int rank) {
  using namespace C;
  asm volatile("setmaxnreg.inc.sync.aligned.u32 200;");
  int spin = 0;
  uint32_t wf[NKR][4];
  mwait(sb + BAR_W, 0, spin);
  for (int it = tid0; it < 2560; it += 128) {
    const int row = it >> 2, q = it & 3;
    const uint32_t base = sb + OFF_WQ + row * 128;
    const uint32_t a0 = base + (((2 * q) ^ (row & 7)) << 4), a1 = base + (((2 * q + 1) ^ (row & 7)) << 4);
    const uint4 u = lds128(a0), v = lds128(a1);
    sts128(a0, make_uint4(__byte_perm(u.x, u.y, 0x5410), __byte_perm(u.z, u.w, 0x5410), __byte_perm(v.x, v.y, 0x5410), __byte_perm(v.z, v.w, 0x5410)));
    sts128(a1, make_uint4(__byte_perm(u.x, u.y, 0x7632), __byte_perm(u.z, u.w, 0x7632), __byte_perm(v.x, v.y, 0x7632), __byte_perm(v.z, v.w, 0x7632)));
  }
  CBAR_SYNC(NB_A, 128);
  load_weights_rs(wf, sb, OFF_WQ, OFF_YO, tid0);

#pragma unroll 1
  for (int i = -1; i < NSTEP; i++) {
    const int ph = i & 1;
    if (i >= 0) {
      if (i == 0) mwait(sb + BAR_W, 1, spin);
      mwait(sb + BAR_M, ph, spin);
      TS(i, 3);
      {
        float dq[8], dk[8];
        int redo = 0;
#pragma unroll 1
        while (true) {
          wg_fence();
#pragma unroll
          for (int k = 0; k < 40; k++) wgmma_ts16(dq, wdesc(OFF_WQ + k * 2048), mdesc(k), k);
          wg_commit();
#pragma unroll
          for (int k = 0; k < 40; k++) wgmma_ts16(dk, wdesc(OFF_WK + k * 2048), mdesc(k), k);
          wg_commit();
          wg_wait<1>();
          const float chk = (dq[0] + dq[1]) + (dq[4] + dq[5]);
          if (!bar_red_or(NB_C, 128, chk != chk && !redo)) break;
          wg_wait<0>();
          const int tid = fresh(tid0);
#pragma unroll 1
          for (int k = 0; k < 10; k++) {
            uint4 v = lds128(sb + OFF_M + tid * 16 + k * 2048);
            if (v.x == SENT || v.y == SENT || v.z == SENT || v.w == SENT) {
              do { v = ld_relaxed4(g_mbuf[i] + tid * 16 + k * 2048); spin += 16; } while ((v.x == SENT || v.y == SENT || v.z == SENT || v.w == SENT) && spin < SPIN_TOT);
              sts128(sb + OFF_M + tid * 16 + k * 2048, v);
            }
          }
          fence_async();
          bar_sync(NB_C, 128);
          redo = fresh(1);
        }
        CBAR_ARRIVE(NB_QI, 256);
        CBAR_SYNC(NB_QK, 384);
        TSV(i, 36, redo);
        const int tid = fresh(tid0), m = (tid >> 3) & 3;
        const uint32_t ka = pin(sb + OFF_KT + ((tid >> 5) * 2 + (m & 1)) * KS + (m >> 1) * 640 + (tid & 7) * 16);
        store_mem<VS>(dq, sb + OFF_VT + 128, tid);
        wg_wait<0>();
        TS(i, 4);
        stsm4(ka, pack_bf16(dk[0], dk[1]), pack_bf16(dk[2], dk[3]), pack_bf16(dk[4], dk[5]), pack_bf16(dk[6], dk[7]));
        fence_async();
      }
      CBAR_SYNC(NB_A, 128);
      TSB(i, 5);
      {
        float x[20];
        wg_fence();
#pragma unroll
        for (int kk = 0; kk < 4; kk++) wgmma_tt40(x, mkdesc_ns(SB0 + OFF_VT + 128 + kk * 2 * VS, VS, 640), mkdesc_ns(SB0 + OFF_KT + kk * 2 * KS, KS, 128), kk);
#pragma unroll
        for (int kk = 0; kk < 4; kk++) wgmma_tt40(x, mkdesc_ns(SB0 + OFF_VT + kk * 2 * VS, VS, 384), mkdesc_ns(SB0 + OFF_KT + 640 + kk * 2 * KS, KS, 128), 1);
        wg_commit();
        CBAR_ARRIVE(NB_SI, 256);
        const int tid = fresh(tid0), lane = tid & 31, w = tid >> 5;
        const uint32_t xo = OFF_XM + w * 1280 + lane * 16, x1 = OFF_XM + w * 1280 + lane * 4;
        const uint32_t rb1 = mapa(sb, (rank + 1) % 3), rb2 = mapa(sb, (rank + 2) % 3);
        const uint32_t ra = pin(rb1 + xo + 640), rb = pin(rb1 + x1 + 1152), rc = pin(rb2 + xo), rd = pin(rb2 + x1 + 512);
        const uint32_t la = pin(sb + xo), lb = pin(sb + x1);
        const uint32_t pa = pin(sb + OFF_XM + w * 1280 + (lane & 7) * 4 + (lane & 8) * 8 + (lane & 16) * 2);
        mwait(sb + BAR_XF, ph, spin);
        wg_wait<0>();
        TS(i, 6);
        if (w < 2) {
          float y[10];
#pragma unroll
          for (int j = 0; j < 5; j++) { y[2 * j] = x[4 * j] * SCL; y[2 * j + 1] = x[4 * j + 1] * SCL; }
          const uint4 h0 = make_uint4(pack_h2(y[0], y[1]), pack_h2(y[2], y[3]), pack_h2(y[4], y[5]), pack_h2(y[6], y[7]));
          const uint32_t h1 = pack_h2(y[8], y[9]);
          st_async4u(ra, h0, rb1 + BAR_XM);
          st_async4u(rc, h0, rb2 + BAR_XM);
          st_async1u(rb, h1, rb1 + BAR_XM);
          st_async1u(rd, h1, rb2 + BAR_XM);
          CBAR_ARRIVE(NB_SM, 256);
          if (lane == 0) mbar_arrive_cluster(mapa(sb, 0) + BAR_E);
          TS(i, 7);
          mwait(sb + BAR_XM, ph, spin);
          TS(i, 8);
          const uint4 u0 = lds128(la), v0 = lds128(la + 640);
          const uint32_t u1 = lds32(lb + 512), v1 = lds32(lb + 1152);
          add_h2(y[0], y[1], u0.x, v0.x); add_h2(y[2], y[3], u0.y, v0.y); add_h2(y[4], y[5], u0.z, v0.z); add_h2(y[6], y[7], u0.w, v0.w);
          add_h2(y[8], y[9], u1, v1);
          const float mx = quad_max(max10(y)) * -256.f;
          sts32(pa + 640, 0);
#pragma unroll
          for (int j = 0; j < 5; j++) {
            y[2 * j] = ex2(fmaf(y[2 * j], 256.f, mx)); y[2 * j + 1] = ex2(fmaf(y[2 * j + 1], 256.f, mx));
            sts32(pa + j * 128, pack_bf16(y[2 * j], y[2 * j + 1]));
          }
          sts32(pa + 768, __float_as_uint(sum10(y)));
          fence_async();
          TS(i, 9);
        } else {
          CBAR_ARRIVE(NB_SM, 256);
          if (lane == 0) mbar_arrive_cluster(mapa(sb, 0) + BAR_E);
        }
      }
      CBAR_SYNC(NB_VA, 256);
      TSB(i, 10);
      {
        float o[2][4];
        wg_fence();
#pragma unroll
        for (int c = 0; c < 2; c++)
#pragma unroll
          for (int q = 0; q < 3; q++)
            wgmma_ss8(o[c], mkdesc_ns(SB0 + OFF_VT + 128 + c * 640 + q * 256, 128, VS), mkdesc_ns(SB0 + OFF_XM + c * 1280 + q * 256, 128, 128), q);
        wg_commit();
        const int tid = fresh(tid0);
        const float4 e = lds128f(sb + OFF_XM + 768 + (tid & 3) * 32 + (tid & 4) * 4 + (tid & 8) * 160);
        const uint32_t oo = OFF_OG + (tid >> 5) * 512 + (tid & 2) * 64 + ((tid & 31) >> 2) * 16 + (tid & 1) * 8;
        const uint32_t rb1 = mapa(sb, (rank + 1) % 3), rb2 = mapa(sb, (rank + 2) % 3);
        const uint32_t ra = pin(rb1 + oo + 4096), rc = pin(rb2 + oo + 2048), la = pin(sb + oo);
        const float inv = rcp((e.x + e.y) + (e.z + e.w));
        const float i0 = __shfl_sync(0xffffffffu, inv, tid & 3), i1 = __shfl_sync(0xffffffffu, inv, (tid & 3) + 4);
        const float i2 = __shfl_sync(0xffffffffu, inv, (tid & 3) + 8), i3 = __shfl_sync(0xffffffffu, inv, (tid & 3) + 12);
        mwait(sb + BAR_MF, ph, spin);
        wg_wait<0>();
        TS(i, 11);
        const uint32_t p0 = pack_bf16(o[0][0] * i0, o[0][1] * i1), p1 = pack_bf16(o[1][0] * i2, o[1][1] * i3);
        const uint32_t p2 = pack_bf16(o[0][2] * i0, o[0][3] * i1), p3 = pack_bf16(o[1][2] * i2, o[1][3] * i3);
        if (OGF) { sts64(la, p0, p1); sts64(la + 256, p2, p3); fence_async(); }
        st_async2u(ra, p0, p1, rb1 + BAR_OG);
        st_async2u(rc, p0, p1, rb2 + BAR_OG);
        st_async2u(ra + 256, p2, p3, rb1 + BAR_OG);
        st_async2u(rc + 256, p2, p3, rb2 + BAR_OG);
        if (!OGF) { sts64(la, p0, p1); sts64(la + 256, p2, p3); fence_async(); }
      }
      if (i + 1 >= NSTEP) { mwait(sb + BAR_OG, ph, spin); break; }
      CBAR_SYNC(NB_A, 128);
      TSB(i, 12);
      {
        float acc[3][8];
        wg_fence();
        wo_block<0, 0>(acc[2], wf);
        wg_commit();
        wo_block<1, 0>(acc[0], wf);
        wo_block<4, 0>(acc[1], wf);
        wg_commit();
        const int tid = fresh(tid0), w = tid >> 5, g = (tid & 31) >> 2, t = tid & 3;
        if ((tid & 31) == 0) mbar_arrive_cluster(mapa(sb, 1) + BAR_E + 8);
        const uint32_t tag = (i >> 1) & 1, radd = tag ? 0u : 0x10000u;
#define TAGGED(LO, HI) __byte_perm(((__float_as_uint(LO) + radd) & 0xFFFE0000u) | (tag << 16), pack_bf16(0.f, HI), 0x7632)
#define SEND(PTR, U) st_relaxed128((PTR), TAGGED(acc[U][0], acc[U][2]), pack_bf16(acc[U][1], acc[U][3]), pack_bf16(acc[U][4], acc[U][6]), pack_bf16(acc[U][5], acc[U][7]))
        uint8_t* m9 = pinp(g_mail[ph] + MAIL9 + (((2 * w + (g >> 2)) * 2 + (t & 1)) * 4 + (t & 2)) * 3072 + cta * 32 + (g & 3) * 8);
        wg_wait<1>();
        const uint32_t n0 = pin(TAGGED(acc[2][0], acc[2][2])), n1 = pin(pack_bf16(acc[2][1], acc[2][3]));
        const uint32_t n2 = pin(TAGGED(acc[2][4], acc[2][6])), n3 = pin(pack_bf16(acc[2][5], acc[2][7]));
        wg_fence();
        wo_block<7, 0>(acc[2], wf);
        wg_commit();
        uint8_t* mb = pinp(g_mail[ph] + (((rank * 12 + w) * 2 + (g >> 2)) * 4 + t) * 2048 + (cta / 3) * 64 + (g & 3) * 16);
        mwait(sb + BAR_OG, ph, spin);
        fence_async();
        TS(i, 13);
        wg_fence();
        wo_block<2, 1>(acc[0], wf); wo_block<3, 2>(acc[0], wf);
        wg_commit();
        st_relaxed64(m9, n0, n1);
        st_relaxed64(m9 + 3072, n2, n3);
        wo_block<5, 1>(acc[1], wf); wo_block<6, 2>(acc[1], wf);
        wg_commit();
        wg_wait<1>(); SEND(mb, 0);
        wg_fence();
        wo_block<8, 1>(acc[2], wf); wo_block<9, 2>(acc[2], wf);
        wg_commit();
        CBAR_ARRIVE(NB_WQ, 256);
        CBAR_ARRIVE(NB_WV, 256);
        wg_wait<1>(); SEND(mb + 32 * 2048, 1);
        wg_wait<0>(); SEND(mb + 64 * 2048, 2);
#undef SEND
#undef TAGGED
        if ((tid & 31) == 0) mbar_arrive_cluster(mapa(sb, 2) + BAR_E + 16);
      }
      TS(i, 14);
    }
    const uint32_t t0 = clk32();
    if (i >= 0) {
      const int tid = fresh(tid0), lane = tid & 31;
      const uint32_t tag = (i >> 1) & 1;
      const bool t9 = cta >= 72 && cta < 88;
      const int w = tid >> 5, j = lane >> 3;
      const uint32_t pub = pin((lane & (t9 ? 6 : 4)) == 0 && !(((t9 ? cta : w) & 1) && i + 1 == LAG) && cta < 88);
      uint8_t* dst = pinp(g_mbuf[i + 1] + (t9 ? (cta + 72) * 128 + w * 32 + (j & 1) * 16 + (lane & 1) * 8 + (j >> 1) * 4
                                               : cta * 256 + (w & 1) * 128 + (w >> 1) * 64 + j * 16 + (lane & 3) * 4));
      float f[8];
      int n = 0;
      while (clk32() - t0 < B1) {}
      TS(i + 1, 30);
      if (!t9) poll_add<4>(g_mail[ph] + (cta < 72 ? cta : cta - 24) * 8192 + (tid >> 5) * 2048 + lane * 16, tag, f, n, spin);
      else poll_add<6>(g_mail[ph] + MAIL9 + (cta - 72) * 12288 + (tid >> 5) * 3072 + lane * 16, tag, f, n, spin);
      TS(i + 1, 31); TSV(i + 1, 32, n);
      const bool h = lane & 16, q = lane & 8;
#pragma unroll
      for (int j = 0; j < 4; j++) f[j] = (h ? f[4 + j] : f[j]) + __shfl_xor_sync(0xffffffffu, h ? f[j] : f[4 + j], 16);
#pragma unroll
      for (int j = 0; j < 2; j++) f[j] = (q ? f[2 + j] : f[j]) + __shfl_xor_sync(0xffffffffu, q ? f[j] : f[2 + j], 8);
      f[0] += __shfl_xor_sync(0xffffffffu, f[0], 4); f[1] += __shfl_xor_sync(0xffffffffu, f[1], 4);
      if (t9) { f[0] += __shfl_xor_sync(0xffffffffu, f[0], 2); f[1] += __shfl_xor_sync(0xffffffffu, f[1], 2); }
      if (pub) st_relaxed(dst, pack_bf16(f[0], f[1]));
      TS(i + 1, 15);
    }
    {
      const uint32_t t1 = clk32();
      const int tid = fresh(tid0);
      const uint8_t* src = g_mbuf[i + 1] + rank * 7168;
      const uint8_t* pp = pinp(src + (rank == 2 && tid >= 64 ? 2048 + tid * 32 : (tid < 112 ? tid : 0) * 64 + 32));
      if (tid == 0) mbar_expect_tx(sb + BAR_M, 20480);
      while (clk32() - t1 < B2) {}
      TS(i + 1, 16);
      int n = 0;
      uint32_t x0;
      do { x0 = ld_relaxed(pp); n++; spin += 16; } while (__any_sync(0xffffffffu, x0 == SENT && spin < SPIN_TOT));
      TSV(i + 1, 35, n);
      if (tid >= 32) CBAR_ARRIVE(NB_MR, 128);
      else {
        CBAR_SYNC(NB_MR, 128);
        TSB(i + 1, 34);
        if (tid == 0) {
          mwait(sb + BAR_MOK, ph ^ 1, spin);
          TS1(i + 1, 33);
          bulk_g2s_mc(sb + OFF_M + rank * 7168, src, rank == 2 ? 6144 : 7168, sb + BAR_M);
        }
        __syncwarp();
      }
    }
  }
  if (spin >= SPIN_TOT) g_err = 1;
}

__global__ void __cluster_dims__(3, 1, 1) __launch_bounds__(384, 1)
k_chain(const __grid_constant__ CUtensorMap tmWq, const __grid_constant__ CUtensorMap tmWk,
        const __grid_constant__ CUtensorMap tmWv, const __grid_constant__ CUtensorMap tmWo) {
  using namespace C;
  extern __shared__ __align__(1024) uint8_t smem[];
  const uint32_t sb = smem_u32(smem);
  const int tid = threadIdx.x;
  const int wg = __shfl_sync(0xffffffffu, tid >> 7, 0);
  const int cta = blockIdx.x, rank = cta % 3;

  asm volatile("griddepcontrol.launch_dependents;");
  if (tid == 0) {
    if ((sb & 0xFFFFFF) != SB0) g_err = 100;
    for (int p = 0; p < 5; p++) { mbar_init(sb + BAR_F + 8 * p, 1); mbar_init(sb + BAR_E + 8 * p, p == 2 ? 15 : 24); }
    mbar_init(sb + BAR_M, 1); mbar_init(sb + BAR_MOK, 24); mbar_init(sb + BAR_XM, 1); mbar_init(sb + BAR_XF, 2);
    mbar_init(sb + BAR_XT, 1); mbar_init(sb + BAR_MF, 8); mbar_init(sb + BAR_OG, 1); mbar_init(sb + BAR_W, 1);
    for (int p = 0; p < 5; p++) mbar_expect_tx(sb + BAR_F + 8 * p, 16384);
    for (int p = 0; p < 16; p++) sts32(sb + OFF_SAFE + 4 * p, 0);
    asm volatile("fence.mbarrier_init.release.cluster;" ::: "memory");
    fence_async();
    mbar_expect_tx(sb + BAR_W, 163840);
    const int head = cta / 3, col = head * DH + rank * 64;
    tma2d(sb + OFF_WQ, &tmWo, 576, col, sb + BAR_W);
    for (int i = 0; i < 9; i++) tma2d(sb + OFF_WQ + (i + 1) * 8192, &tmWo, (3 * rank + i / 3) * 64, head * DH + ((rank + i) % 3) * 64, sb + BAR_W);
    for (int i = 0; i < 5; i++) tma2d(sb + OFF_WK + i * 16384, &tmWv, col, i * 128, sb + BAR_W);
  }
  __syncthreads();
  asm volatile("barrier.cluster.arrive.release.aligned;" ::: "memory");
  asm volatile("barrier.cluster.wait.acquire.aligned;" ::: "memory");

  if (wg == 0) chain_a(sb, tid, cta, rank);
  else if (wg == 1) chain_q(tmWq, tmWk, sb, tid, cta, rank);
  else chain_v(sb, tid, cta, rank);
  asm volatile("barrier.cluster.arrive.release.aligned;" ::: "memory");
  asm volatile("barrier.cluster.wait.acquire.aligned;" ::: "memory");
}

namespace W {
constexpr int NW = 36;
constexpr int NP = 30;
constexpr int OW0 = 31;
constexpr int PST = 3, PSTAGE = 32768;
constexpr int BST = 3, BSTAGE = 16384;
constexpr int OFF_P = 0;
constexpr int OFF_WQ = OFF_P + PST * PSTAGE;
constexpr int OFF_B = OFF_WQ + 81920;
constexpr int OFF_HIST = OFF_B + BST * BSTAGE;
constexpr int OFF_BAR = OFF_HIST + 2 * 14 * 80;
constexpr int SMEM = OFF_BAR + 128;
constexpr int BAR_PF = OFF_BAR, BAR_PE = OFF_BAR + 24, BAR_BF = OFF_BAR + 48, BAR_BE = OFF_BAR + 72;
constexpr int PITCH = 136;
constexpr int NB_P = 1, NB_B = 2;
}

struct WorkArgs {
  const bf16* res[2];
  bf16* xa[2];
  bf16* xb[2];
  const bf16* wqkv;
};

#define OHK 7
#define IMMREL 7
#define FOR_BATCHES(l, b)                                   \
  for (int j_ = 0; j_ < 2 * NSTEP; j_++) {                  \
    const int l = j_ & 1, s_ = (j_ >> 1) - (l ? LAG : 0);   \
    if (s_ < 0 || s_ >= NSEG || (s_ & 3) != 3) continue;    \
    const int b = s_ >> 2;

template <bool IS_O>
__device__ __forceinline__ void work_gemm_producer(const CUtensorMap& tm, const WorkArgs& a, uint32_t sb, int w) {
  using namespace W;
  constexpr int KCH = IS_O ? 10 : 96, NK = IS_O ? 10 : 16;
  int dead = 0, st = 0;
  uint32_t ph = 1;
  const int col = (IS_O ? w - OW0 : w % 5) * 128, k0 = IS_O ? 0 : (w / 5) * 16;
  FOR_BATCHES(l, b)
    const uint8_t* src = (IS_O ? g_ob[l] : g_o[l]) + ((size_t)(2 * b) * KCH + k0) * 8192;
#pragma unroll 1
    for (int kc = 0; kc < NK; kc++) {
      const uint32_t bar = sb + BAR_PF + 8 * st, d = sb + OFF_P + st * PSTAGE;
      mbar_wait(sb + BAR_PE + 8 * st, ph, dead);
      mbar_expect_tx(bar, PSTAGE);
      tma2d(d + 16384, &tm, col, (k0 + kc) * 64, bar);
      tma2d(d + 24576, &tm, col + 64, (k0 + kc) * 64, bar);
      if (kc >= PST) {
        bulk_g2s(d, src + (size_t)kc * 8192, 8192, bar);
        bulk_g2s(d + 8192, src + (size_t)(KCH + kc) * 8192, 8192, bar);
      }
      if (++st == PST) { st = 0; ph ^= 1; }
      if (kc == PST - 1) {
        cnt_wait(IS_O ? CN_A : CN_O, l, b, IS_O ? 32 : 96, dead);
        if (!IS_O && w == 0) WTS(l, b, 0);
        if (IS_O && w == 35) WTS(l, b, 3);
        fence_async_all();
#pragma unroll
        for (int i = 0; i < PST; i++) {
          const int s2 = (st + i) % PST;
          bulk_g2s(sb + OFF_P + s2 * PSTAGE, src + (size_t)i * 8192, 8192, sb + BAR_PF + 8 * s2);
          bulk_g2s(sb + OFF_P + s2 * PSTAGE + 8192, src + (size_t)(KCH + i) * 8192, 8192, sb + BAR_PF + 8 * s2);
        }
      }
    }
  }
}

__device__ __forceinline__ void quad_transpose(uint32_t* x, int t) {
  const bool h = t & 2, o = t & 1;
  uint32_t p = __shfl_xor_sync(0xffffffffu, h ? x[0] : x[2], 2), q = __shfl_xor_sync(0xffffffffu, h ? x[1] : x[3], 2);
  const uint32_t y0 = h ? p : x[0], y1 = h ? q : x[1], y2 = h ? x[2] : p, y3 = h ? x[3] : q;
  p = __shfl_xor_sync(0xffffffffu, o ? y0 : y1, 1); q = __shfl_xor_sync(0xffffffffu, o ? y2 : y3, 1);
  x[0] = o ? p : y0; x[1] = o ? y1 : p; x[2] = o ? q : y2; x[3] = o ? y3 : q;
}

template <bool IS_O>
__device__ __forceinline__ void work_gemm(const WorkArgs& a, uint32_t sb, int w, int tid0) {
  using namespace W;
  constexpr int NK = IS_O ? 10 : 16;
  int dead = 0, st = 0;
  uint32_t ph = 0;
  const int tile = IS_O ? w - OW0 : w % 5;
  bool first = true;
  FOR_BATCHES(l, b)
    float acc[64];
    uint32_t r0[16], r1[16];
    int prev = 0;
    if (IS_O) {
#pragma unroll
      for (int i = 0; i < 64; i++) acc[i] = 0.f;
    }
#pragma unroll 1
    for (int kc = 0; kc < NK; kc++) {
      mbar_wait(sb + BAR_PF + 8 * st, ph, dead);
      if (w == (IS_O ? 35 : WW) && tid0 == 0 && kc == 0) WTS(l, b, IS_O ? 16 : 5);
      const uint32_t pa = sb + OFF_P + st * PSTAGE + (tid0 >> 7) * 8192, pb = sb + OFF_P + st * PSTAGE + 16384;
      wg_fence();
#pragma unroll
      for (int kk = 0; kk < 4; kk++) wgmma_st128(acc, mkdesc(pa + kk * 32, 16, 1024), mkdesc(pb + kk * 2048, 8192, 1024), (kc | kk) != 0);
      wg_commit();
      if (IS_O && OHK >= 0 && kc == OHK) {
      const int tid = fresh(tid0), g = (tid & 31) >> 2, t = tid & 3;
      const bf16* rp = a.xa[l] + (size_t)(b * 128 + (tid >> 5) * 16 + g) * DM + tile * 128 + 8 * t;
#pragma unroll
      for (int m = 0; m < 4; m++) {
        const float4 c0 = ld_relaxed4f(rp + 32 * m), c1 = ld_relaxed4f(rp + 8 * DM + 32 * m);
        r0[4 * m] = __float_as_uint(c0.x); r0[4 * m + 1] = __float_as_uint(c0.y); r0[4 * m + 2] = __float_as_uint(c0.z); r0[4 * m + 3] = __float_as_uint(c0.w);
        r1[4 * m] = __float_as_uint(c1.x); r1[4 * m + 1] = __float_as_uint(c1.y); r1[4 * m + 2] = __float_as_uint(c1.z); r1[4 * m + 3] = __float_as_uint(c1.w);
      }
      }
      if (IMMREL & (IS_O ? 2 : 1)) {
        if (kc < NK - 1) {
          wg_wait<0>();
          if ((tid0 & 127) == 0) mbar_arrive(sb + BAR_PE + 8 * st);
        }
      } else if (kc > 0) {
        wg_wait<1>();
        if ((tid0 & 127) == 0) mbar_arrive(sb + BAR_PE + 8 * prev);
      }
      prev = st;
      if (++st == PST) { st = 0; ph ^= 1; }
    }
    if (IS_O && OHK < 0) {
      const int tid = fresh(tid0), g = (tid & 31) >> 2, t = tid & 3;
      const bf16* rp = a.xa[l] + (size_t)(b * 128 + (tid >> 5) * 16 + g) * DM + tile * 128 + 8 * t;
#pragma unroll
      for (int m = 0; m < 4; m++) {
        const float4 c0 = ld_relaxed4f(rp + 32 * m), c1 = ld_relaxed4f(rp + 8 * DM + 32 * m);
        r0[4 * m] = __float_as_uint(c0.x); r0[4 * m + 1] = __float_as_uint(c0.y); r0[4 * m + 2] = __float_as_uint(c0.z); r0[4 * m + 3] = __float_as_uint(c0.w);
        r1[4 * m] = __float_as_uint(c1.x); r1[4 * m + 1] = __float_as_uint(c1.y); r1[4 * m + 2] = __float_as_uint(c1.z); r1[4 * m + 3] = __float_as_uint(c1.w);
      }
    }
    wg_wait<0>();
    if ((tid0 & 127) == 0) mbar_arrive(sb + BAR_PE + 8 * prev);
    if (w == (IS_O ? 35 : WW) && tid0 == 0) WTS(l, b, IS_O ? 17 : 6);
    if (!IS_O) {
      if (first) {
        if ((tid0 & 31) == 0) cnt_wait(CN_Z, 0, 0, NW, dead);
        __syncwarp();
        first = false;
      }
      const int tid = fresh(tid0);
      float* dst = &g_acc[l][b][tile][0] + (tid >> 5) * 2048 + (tid & 31) * 4;
#pragma unroll
      for (int i = 0; i < 16; i++)
        asm volatile("red.relaxed.gpu.global.add.v4.f32 [%0],{%1,%2,%3,%4};" ::"l"(dst + i * 128), "f"(acc[4 * i]), "f"(acc[4 * i + 1]), "f"(acc[4 * i + 2]), "f"(acc[4 * i + 3]) : "memory");
      if (w == WW && tid0 == 0) WTS(l, b, 7);
      bar_sync(NB_P, 256);
      if (tid0 == 0) cnt_signal(CN_P, l, b);
      if (w == WW && tid0 == 0) WTS(l, b, 8);
    } else {
      const int tid = fresh(tid0), g = (tid & 31) >> 2, t = tid & 3;
      const int rb = (tid >> 5) * 16 + g, R0 = b * 128 + rb;
      float s0 = 0.f, s1 = 0.f;
      bf16* xp = a.xb[l] + (size_t)R0 * DM + tile * 128 + 8 * t;
      uint32_t c0[16], c1[16];
#pragma unroll
      for (int j = 0; j < 16; j++) { c0[j] = pack_bf16(acc[4 * j], acc[4 * j + 1]); c1[j] = pack_bf16(acc[4 * j + 2], acc[4 * j + 3]); }
#pragma unroll
      for (int m = 0; m < 4; m++) { quad_transpose(c0 + 4 * m, t); quad_transpose(c1 + 4 * m, t); }
#pragma unroll
      for (int j = 0; j < 16; j++) {
        const uint32_t u0 = c0[j], u1 = c1[j];
        const uint32_t y0 = pack_bf16(bf_lo(r0[j]) + bf_lo(u0), bf_hi(r0[j]) + bf_hi(u0));
        const uint32_t y1 = pack_bf16(bf_lo(r1[j]) + bf_lo(u1), bf_hi(r1[j]) + bf_hi(u1));
        acc[4 * j] = bf_lo(y0); acc[4 * j + 1] = bf_hi(y0); acc[4 * j + 2] = bf_lo(y1); acc[4 * j + 3] = bf_hi(y1);
        s0 += acc[4 * j] + acc[4 * j + 1]; s1 += acc[4 * j + 2] + acc[4 * j + 3];
      }
      if (l == 0) {
        s0 += __shfl_xor_sync(0xffffffffu, s0, 1); s1 += __shfl_xor_sync(0xffffffffu, s1, 1);
        s0 += __shfl_xor_sync(0xffffffffu, s0, 2); s1 += __shfl_xor_sync(0xffffffffu, s1, 2);
        const float tm0 = s0 * (1.f / 128), tm1 = s1 * (1.f / 128);
        float q0 = 0.f, q1 = 0.f;
#pragma unroll
        for (int j = 0; j < 16; j++) {
          const float a0 = acc[4 * j] - tm0, b0 = acc[4 * j + 1] - tm0, a1 = acc[4 * j + 2] - tm1, b1 = acc[4 * j + 3] - tm1;
          q0 += a0 * a0 + b0 * b0; q1 += a1 * a1 + b1 * b1;
        }
        q0 += __shfl_xor_sync(0xffffffffu, q0, 1); q1 += __shfl_xor_sync(0xffffffffu, q1, 1);
        q0 += __shfl_xor_sync(0xffffffffu, q0, 2); q1 += __shfl_xor_sync(0xffffffffu, q1, 2);
        float2* sp = &g_stats[b][rb][0];
        if (t < 2) {
          const float sx = t ? s1 : s0, qx = t ? q1 : q0;
          asm volatile("st.relaxed.gpu.global.v2.f32 [%0],{%1,%2};" ::"l"(sp + t * 8 * 16 + tile), "f"(sx), "f"(qx) : "memory");
        }
#pragma unroll
        for (int m = 0; m < 4; m++) {
          const float* c = acc + 16 * m;
          *reinterpret_cast<uint4*>(xp + 32 * m) = make_uint4(pack_bf16(c[0], c[1]), pack_bf16(c[4], c[5]), pack_bf16(c[8], c[9]), pack_bf16(c[12], c[13]));
          *reinterpret_cast<uint4*>(xp + 8 * DM + 32 * m) = make_uint4(pack_bf16(c[2], c[3]), pack_bf16(c[6], c[7]), pack_bf16(c[10], c[11]), pack_bf16(c[14], c[15]));
        }
        if (w == 35 && tid0 == 0) WTS(l, b, 18);
        float2 e0[2], e1[2];
        int n = dead ? SPIN_MAIL : 0;
        while (true) {
          e0[0] = ld_relaxed2f(sp + t); e1[0] = ld_relaxed2f(sp + 8 * 16 + t);
          e0[1] = ld_relaxed2f(sp + 4); e1[1] = ld_relaxed2f(sp + 8 * 16 + 4);
          bool bad = false;
#pragma unroll
          for (int i = 0; i < 2; i++)
            bad |= __float_as_uint(e0[i].x) == SENT || __float_as_uint(e0[i].y) == SENT || __float_as_uint(e1[i].x) == SENT || __float_as_uint(e1[i].y) == SENT;
          if (!__any_sync(0xffffffffu, bad)) break;
          if (++n > SPIN_MAIL) { dead = 1; g_err = 20; break; }
        }
        if (w == 35 && tid0 == 0) WTS(l, b, 19);
        float m0 = e0[0].x, m1 = e1[0].x;
        m0 += __shfl_xor_sync(0xffffffffu, m0, 1); m1 += __shfl_xor_sync(0xffffffffu, m1, 1);
        m0 += __shfl_xor_sync(0xffffffffu, m0, 2); m1 += __shfl_xor_sync(0xffffffffu, m1, 2);
        m0 = (m0 + e0[1].x) * (1.f / DM); m1 = (m1 + e1[1].x) * (1.f / DM);
        const float d0 = e0[0].x * (1.f / 128) - m0, d1 = e1[0].x * (1.f / 128) - m1;
        float v0 = e0[0].y + 128.f * d0 * d0, v1 = e1[0].y + 128.f * d1 * d1;
        v0 += __shfl_xor_sync(0xffffffffu, v0, 1); v1 += __shfl_xor_sync(0xffffffffu, v1, 1);
        v0 += __shfl_xor_sync(0xffffffffu, v0, 2); v1 += __shfl_xor_sync(0xffffffffu, v1, 2);
        const float d2 = e0[1].x * (1.f / 128) - m0, d3 = e1[1].x * (1.f / 128) - m1;
        v0 += e0[1].y + 128.f * d2 * d2; v1 += e1[1].y + 128.f * d3 * d3;
        const float rs0 = rsqrtf(v0 * (1.f / DM) + 1e-5f), rs1 = rsqrtf(v1 * (1.f / DM) + 1e-5f);
        uint8_t* img = g_xn[1] + (size_t)(R0 >> 5) * 40960 + tile * 8192 + ((R0 >> 3) & 3) * 2048 + g * 128;
#pragma unroll
        for (int m = 0; m < 4; m++) {
          uint8_t* o = img + (m >> 1) * 1024 + (((4 * (m & 1) + t) ^ g) << 4);
          const float* c = acc + 16 * m;
          *reinterpret_cast<uint4*>(o) = make_uint4(pack_bf16((c[0] - m0) * rs0, (c[1] - m0) * rs0), pack_bf16((c[4] - m0) * rs0, (c[5] - m0) * rs0),
                                                    pack_bf16((c[8] - m0) * rs0, (c[9] - m0) * rs0), pack_bf16((c[12] - m0) * rs0, (c[13] - m0) * rs0));
          *reinterpret_cast<uint4*>(o + 2048) = make_uint4(pack_bf16((c[2] - m1) * rs1, (c[3] - m1) * rs1), pack_bf16((c[6] - m1) * rs1, (c[7] - m1) * rs1),
                                                            pack_bf16((c[10] - m1) * rs1, (c[11] - m1) * rs1), pack_bf16((c[14] - m1) * rs1, (c[15] - m1) * rs1));
        }
        bar_sync(NB_P, 256);
        if (tid0 == 0) { fence_async_all(); cnt_signal(CN_X, 0, b); }
      } else {
#pragma unroll
        for (int m = 0; m < 4; m++) {
          const float* c = acc + 16 * m;
          *reinterpret_cast<uint4*>(xp + 32 * m) = make_uint4(pack_bf16(c[0], c[1]), pack_bf16(c[4], c[5]), pack_bf16(c[8], c[9]), pack_bf16(c[12], c[13]));
          *reinterpret_cast<uint4*>(xp + 8 * DM + 32 * m) = make_uint4(pack_bf16(c[2], c[3]), pack_bf16(c[6], c[7]), pack_bf16(c[10], c[11]), pack_bf16(c[14], c[15]));
        }
      }
      if (w == 35 && tid0 == 0) { WTS(l, b, 4); WTS(l, b, 20); }
    }
  }
}

__device__ __forceinline__ void work_q_producer(const WorkArgs& a, uint32_t sb) {
  using namespace W;
  int dead = 0, st = 0;
  uint32_t ph = 1;
  FOR_BATCHES(l, b)
    cnt_wait(CN_L, l, b, 64, dead);
    if (blockIdx.x == 0) WTS(l, b, 2);
    fence_async_all();
    const uint8_t* src = g_xnb[l] + (size_t)(2 * b) * 10 * 8192;
#pragma unroll 1
    for (int kc = 0; kc < 10; kc++) {
      const uint32_t bar = sb + BAR_BF + 8 * st, d = sb + OFF_B + st * BSTAGE;
      mbar_wait(sb + BAR_BE + 8 * st, ph, dead);
      mbar_expect_tx(bar, BSTAGE);
      bulk_g2s(d, src + (size_t)kc * 8192, 8192, bar);
      bulk_g2s(d + 8192, src + (size_t)(10 + kc) * 8192, 8192, bar);
      if (++st == BST) { st = 0; ph ^= 1; }
    }
  }
}

__device__ __forceinline__ void work_ln(const WorkArgs& a, int w, int wr, int lane0) {
  int dead = 0;
  FOR_BATCHES(l, b)
    uint32_t r0[10], r1[10];
    if (HOIST & 2) {
      if (l == 1) {
        if (lane0 == 0) cnt_wait(CN_X, 0, b, 5, dead);
        __syncwarp();
      }
      const int lane = fresh(lane0), p = 2 * w + wr;
      const bf16* rp = a.res[l] + (size_t)(b * 128 + (p >> 3) * 16 + (p & 7)) * DM + (lane >> 2) * 8 + 2 * (lane & 3);
#pragma unroll
      for (int i = 0; i < 10; i++) { r0[i] = ld_relaxed(rp + i * 64); r1[i] = ld_relaxed(rp + i * 64 + 8 * DM); }
    }
    if (lane0 == 0) cnt_wait(CN_P, l, b, W::NP, dead);
    __syncwarp();
    if (w == WW && wr == 0 && lane0 == 0) { WTS(l, b, 1); WTS(l, b, 9); }
    LTS(l, b, 2 * w + wr, 0);
    const int lane = fresh(lane0), p = 2 * w + wr;
    const int slab = p >> 3, g = p & 7, jj = lane >> 2, t = lane & 3;
    const int R0 = b * 128 + slab * 16 + g;
    const float* acc = &g_acc[l][b][0][0] + slab * 2048 + (g * 4 + t) * 4 + jj * 128;
    const bf16* rp = a.res[l] + (size_t)R0 * DM + jj * 8 + 2 * t;
    float4 v[10];
#pragma unroll
    for (int i = 0; i < 10; i++) {
      v[i] = ld_relaxed4f(acc + (i >> 1) * 16384 + (i & 1) * 1024);
      if (!(HOIST & 2)) { r0[i] = ld_relaxed(rp + i * 64); r1[i] = ld_relaxed(rp + i * 64 + 8 * DM); }
    }
    float s0 = 0.f, s1 = 0.f;
    bf16* xp = a.xa[l] + (size_t)R0 * DM + jj * 8 + 2 * t;
#pragma unroll
    for (int i = 0; i < 10; i++) {
      const uint32_t u0 = pack_bf16(v[i].x, v[i].y), u1 = pack_bf16(v[i].z, v[i].w);
      r0[i] = pack_bf16(bf_lo(r0[i]) + bf_lo(u0), bf_hi(r0[i]) + bf_hi(u0));
      r1[i] = pack_bf16(bf_lo(r1[i]) + bf_lo(u1), bf_hi(r1[i]) + bf_hi(u1));
      s0 += bf_lo(r0[i]) + bf_hi(r0[i]); s1 += bf_lo(r1[i]) + bf_hi(r1[i]);
    }
#pragma unroll
    for (int o = 16; o > 0; o >>= 1) { s0 += __shfl_xor_sync(0xffffffffu, s0, o); s1 += __shfl_xor_sync(0xffffffffu, s1, o); }
    const float m0 = s0 * (1.f / DM), m1 = s1 * (1.f / DM);
    if (m0 != 12345.678f) LTS(l, b, 2 * w + wr, 1);
    float q0 = 0.f, q1 = 0.f;
#pragma unroll
    for (int i = 0; i < 10; i++) {
      const float a0 = bf_lo(r0[i]) - m0, b0 = bf_hi(r0[i]) - m0, a1 = bf_lo(r1[i]) - m1, b1 = bf_hi(r1[i]) - m1;
      q0 += a0 * a0 + b0 * b0; q1 += a1 * a1 + b1 * b1;
    }
#pragma unroll
    for (int o = 16; o > 0; o >>= 1) { q0 += __shfl_xor_sync(0xffffffffu, q0, o); q1 += __shfl_xor_sync(0xffffffffu, q1, o); }
    const float rs0 = rsqrtf(q0 * (1.f / DM) + 1e-5f), rs1 = rsqrtf(q1 * (1.f / DM) + 1e-5f);
    uint8_t* img = g_xnb[l] + (size_t)(R0 >> 6) * 10 * 8192 + (R0 & 63) * 128 + t * 4 + ((jj ^ g) << 4);
#pragma unroll
    for (int i = 0; i < 10; i++) {
      *reinterpret_cast<uint32_t*>(img + i * 8192) = pack_bf16((bf_lo(r0[i]) - m0) * rs0, (bf_hi(r0[i]) - m0) * rs0);
      *reinterpret_cast<uint32_t*>(img + i * 8192 + 1024) = pack_bf16((bf_lo(r1[i]) - m1) * rs1, (bf_hi(r1[i]) - m1) * rs1);
    }
#pragma unroll
    for (int i = 0; i < 10; i++) {
      *reinterpret_cast<uint32_t*>(xp + i * 64) = r0[i];
      *reinterpret_cast<uint32_t*>(xp + i * 64 + 8 * DM) = r1[i];
    }
    __syncwarp();
    if (w == WW && wr == 0 && lane0 == 0) WTS(l, b, 10);
    LTS(l, b, 2 * w + wr, 2);
    if (lane0 == 0) cnt_signal(CN_L, l, b);
    LTS(l, b, 2 * w + wr, 3);
    if (w == WW && wr == 0 && lane0 == 0) WTS(l, b, 11);
  }
}

__device__ __forceinline__ void work_q(const WorkArgs& a, uint32_t sb, int w, int tid0) {
  using namespace W;
  int dead = 0, st = 0;
  uint32_t ph = 0;
  FOR_BATCHES(l, b)
    {
      float acc0[32], acc1[32];
      int prev = 0;
#pragma unroll 1
      for (int kc = 0; kc < 10; kc++) {
        mbar_wait(sb + BAR_BF + 8 * st, ph, dead);
        if (w == WW && tid0 == 0 && kc == 0) WTS(l, b, 12);
        const uint32_t pa = sb + OFF_B + st * BSTAGE, pb = sb + OFF_WQ + kc * 8192;
        wg_fence();
#pragma unroll
        for (int kk = 0; kk < 4; kk++) {
          wgmma_st64(acc0, mkdesc(pa + kk * 32, 16, 1024), mkdesc(pb + kk * 2048, 8192, 1024), (kc | kk) != 0);
          wgmma_st64(acc1, mkdesc(pa + 8192 + kk * 32, 16, 1024), mkdesc(pb + kk * 2048, 8192, 1024), (kc | kk) != 0);
        }
        wg_commit();
        if (IMMREL & 4) {
          if (kc <= 6) {
            wg_wait<0>();
            if (tid0 == 0) mbar_arrive(sb + BAR_BE + 8 * st);
          }
        } else if (kc > 0) {
          wg_wait<1>();
          if (kc <= 7 && tid0 == 0) mbar_arrive(sb + BAR_BE + 8 * prev);
        }
        prev = st;
        if (++st == BST) { st = 0; ph ^= 1; }
      }
      wg_wait<0>();
      bar_sync(NB_B, 128);
      if (w == WW && tid0 == 0) WTS(l, b, 13);
      const int tid = fresh(tid0), wr = tid >> 5, g = (tid & 31) >> 2, t = tid & 3;
      const uint32_t stg = sb + OFF_B, hist = sb + OFF_HIST + l * 1120;
      const uint32_t o = stg + (14 + 16 * wr + g) * PITCH + t * 4;
#pragma unroll
      for (int j = 0; j < 8; j++) {
        sts32(o + j * 16, pack_bf16(acc0[4 * j], acc0[4 * j + 1]));
        sts32(o + 8 * PITCH + j * 16, pack_bf16(acc0[4 * j + 2], acc0[4 * j + 3]));
        sts32(o + 64 * PITCH + j * 16, pack_bf16(acc1[4 * j], acc1[4 * j + 1]));
        sts32(o + 72 * PITCH + j * 16, pack_bf16(acc1[4 * j + 2], acc1[4 * j + 3]));
      }
      for (int i = tid; i < 280; i += 128) {
        uint32_t v; asm volatile("ld.shared.b32 %0,[%1];" : "=r"(v) : "r"(hist + i * 4) : "memory");
        sts32(stg + (i / 20) * PITCH + 40 + (i % 20) * 4, v);
      }
    }
    bar_sync(NB_B, 128);
    {
      const int tid = fresh(tid0);
      const uint32_t stg = sb + OFF_B, hist = sb + OFF_HIST + l * 1120;
      for (int i = tid; i < 280; i += 128) {
        uint32_t v; asm volatile("ld.shared.b32 %0,[%1];" : "=r"(v) : "r"(stg + (128 + i / 20) * PITCH + 40 + (i % 20) * 4) : "memory");
        sts32(hist + i * 4, v);
      }
      const float scl = 0.22360679774997896f * 1.4426950408889634f;
      const uint32_t row = stg + (14 + tid) * PITCH;
      const int pos = b * 128 + tid;
      float q[20];
#pragma unroll
      for (int i = 0; i < 5; i++) {
        uint32_t u0, u1; asm volatile("ld.shared.v2.b32 {%0,%1},[%2];" : "=r"(u0), "=r"(u1) : "r"(row + i * 8) : "memory");
        q[4 * i] = bf_lo(u0); q[4 * i + 1] = bf_hi(u0); q[4 * i + 2] = bf_lo(u1); q[4 * i + 3] = bf_hi(u1);
      }
      float sc[8], mx = -INFINITY;
#pragma unroll
      for (int j = 0; j < 8; j++) {
        float s0 = 0.f, s1 = 0.f;
#pragma unroll
        for (int i = 0; i < 5; i++) {
          uint32_t u0, u1; asm volatile("ld.shared.v2.b32 {%0,%1},[%2];" : "=r"(u0), "=r"(u1) : "r"(row - 2 * j * PITCH + 40 + i * 8) : "memory");
          s0 += q[4 * i] * bf_lo(u0) + q[4 * i + 1] * bf_hi(u0);
          s1 += q[4 * i + 2] * bf_lo(u1) + q[4 * i + 3] * bf_hi(u1);
        }
        sc[j] = pos - 2 * j >= 0 ? (s0 + s1) * scl : -INFINITY;
        mx = fmaxf(mx, sc[j]);
      }
      float sum = 0.f;
#pragma unroll
      for (int j = 0; j < 8; j++) { sc[j] = ex2(sc[j] - mx); sum += sc[j]; }
      const float inv = 1.f / sum;
      float o[20];
#pragma unroll
      for (int i = 0; i < 20; i++) o[i] = 0.f;
#pragma unroll
      for (int j = 0; j < 8; j++) {
        const float pj = __bfloat162float(__float2bfloat16(sc[j] * inv));
#pragma unroll
        for (int i = 0; i < 5; i++) {
          uint32_t u0, u1; asm volatile("ld.shared.v2.b32 {%0,%1},[%2];" : "=r"(u0), "=r"(u1) : "r"(row - 2 * j * PITCH + 80 + i * 8) : "memory");
          o[4 * i] += pj * bf_lo(u0); o[4 * i + 1] += pj * bf_hi(u0); o[4 * i + 2] += pj * bf_lo(u1); o[4 * i + 3] += pj * bf_hi(u1);
        }
      }
      uint8_t* img = g_ob[l] + (size_t)(pos >> 6) * 10 * 8192 + (pos & 63) * 128;
#pragma unroll
      for (int i = 0; i < 5; i++) {
        const int c = w * 20 + 4 * i;
        *reinterpret_cast<uint2*>(img + (c >> 6) * 8192 + ((((c >> 3) & 7) ^ (pos & 7)) << 4) + (c & 7) * 2) =
            make_uint2(pack_bf16(o[4 * i], o[4 * i + 1]), pack_bf16(o[4 * i + 2], o[4 * i + 3]));
      }
    }
    if (w == WW && tid0 == 0) WTS(l, b, 14);
    bar_sync(NB_B, 128);
    if (tid0 == 0) { cnt_signal(CN_A, l, b); if (w == WW) WTS(l, b, 15); }
    fence_async();
    bar_sync(NB_B, 128);
    if (tid0 == 0) for (int i = 0; i < BST; i++) mbar_arrive(sb + BAR_BE + 8 * i);
  }
}

__global__ void __launch_bounds__(512, 1)
k_work(const __grid_constant__ CUtensorMap tmWo, const __grid_constant__ CUtensorMap tmBo, const __grid_constant__ WorkArgs args) {
  using namespace W;
  extern __shared__ __align__(1024) uint8_t smem[];
  const uint32_t sb = smem_u32(smem);
  const int tid = threadIdx.x, w = blockIdx.x;
  const int wg = __shfl_sync(0xffffffffu, tid >> 7, 0);
  if (tid == 0) {
    for (int i = 0; i < PST; i++) { mbar_init(sb + BAR_PF + 8 * i, 1); mbar_init(sb + BAR_PE + 8 * i, 2); }
    for (int i = 0; i < BST; i++) { mbar_init(sb + BAR_BF + 8 * i, 1); mbar_init(sb + BAR_BE + 8 * i, 1); }
    asm volatile("fence.mbarrier_init.release.cluster;" ::: "memory");
  }
  for (int i = w * 512 + tid; i < 2 * 16 * 5 * 4096; i += NW * 512) reinterpret_cast<uint4*>(&g_acc[0][0][0][0])[i] = make_uint4(0, 0, 0, 0);
  if (w < 32) {
    for (int i = tid; i < 640 * 32; i += 512) {
      const int k = i >> 5, c = i & 31;
      uint32_t v = 0;
      if (c < 30) v = *reinterpret_cast<const uint32_t*>(args.wqkv + (size_t)k * 1920 + (c / 10) * 640 + w * 20 + (c % 10) * 2);
      sts32(sb + OFF_WQ + (k >> 6) * 8192 + (k & 63) * 128 + (((c >> 2) ^ (k & 7)) << 4) + (c & 3) * 4, v);
    }
  }
  for (int i = tid; i < 560; i += 512) sts32(sb + OFF_HIST + i * 4, 0);
  fence_async();
  __syncthreads();
  if (tid == 0) cnt_signal(CN_Z, 0, 0);

  if (wg < 2) {
    if (w < NP) work_gemm<false>(args, sb, w, tid);
    else if (w >= OW0) work_gemm<true>(args, sb, w, tid);
    else if (LN30 && tid < 64) work_ln(args, 31, tid >> 5, tid & 31);
  } else if (wg == 2) {
    if (w < 32) work_q(args, sb, w, tid - 256);
  } else if (tid >= 448) {
    if (w < (LN30 ? 31 : 32)) work_ln(args, w, (tid >> 5) & 1, tid & 31);
  } else if (tid == 384) {
    if (w < NP) work_gemm_producer<false>(tmWo, args, sb, w);
    else if (w >= OW0) work_gemm_producer<true>(tmBo, args, sb, w);
  } else if (tid == 416) {
    if (w < 32) work_q_producer(args, sb);
  }
  __syncthreads();
  asm volatile("griddepcontrol.wait;" ::: "memory");
}

typedef CUresult (*EncodeFn)(CUtensorMap*, CUtensorMapDataType, cuuint32_t, void*, const cuuint64_t*, const cuuint64_t*,
                             const cuuint32_t*, const cuuint32_t*, CUtensorMapInterleave, CUtensorMapSwizzle,
                             CUtensorMapL2promotion, CUtensorMapFloatOOBfill);

static void make_map(EncodeFn enc, CUtensorMap* tm, const void* ptr, uint64_t cols, uint64_t rows, uint32_t boxc, uint32_t boxr) {
  cuuint64_t dims[2] = {cols, rows};
  cuuint64_t strides[1] = {cols * 2};
  cuuint32_t box[2] = {boxc, boxr};
  cuuint32_t es[2] = {1, 1};
  enc(tm, CU_TENSOR_MAP_DATA_TYPE_BFLOAT16, 2, const_cast<void*>(ptr), dims, strides, box, es, CU_TENSOR_MAP_INTERLEAVE_NONE,
      CU_TENSOR_MAP_SWIZZLE_128B, CU_TENSOR_MAP_L2_PROMOTION_L2_256B, CU_TENSOR_MAP_FLOAT_OOB_FILL_NONE);
}

extern "C" void kernel_launch(void* const* d_in, const int* in_sizes, int n_in, void* d_out, int out_size) {
  const bf16* x0 = (const bf16*)d_in[0];
  const bf16* mem0 = (const bf16*)d_in[1];
  const bf16* Wq = (const bf16*)d_in[2];
  const bf16* Wk = (const bf16*)d_in[3];
  const bf16* Wv = (const bf16*)d_in[4];
  const bf16* Wo = (const bf16*)d_in[5];
  const bf16* Bqkv = (const bf16*)d_in[8];
  const bf16* Bwo = (const bf16*)d_in[9];
  bf16* out = (bf16*)d_out;

  static EncodeFn enc = nullptr;
  static bf16 *p_x1, *p_x2, *p_x3;
  if (!enc) {
    void* fn = nullptr;
    cudaDriverEntryPointQueryResult qr;
    cudaGetDriverEntryPoint("cuTensorMapEncodeTiled", &fn, cudaEnableDefault, &qr);
    enc = (EncodeFn)fn;
    cudaFuncSetAttribute(k_chain, cudaFuncAttributeMaxDynamicSharedMemorySize, C::SMEM);
    cudaFuncSetAttribute(k_work, cudaFuncAttributeMaxDynamicSharedMemorySize, W::SMEM);
    void* p;
    cudaGetSymbolAddress(&p, g_x1); p_x1 = (bf16*)p;
    cudaGetSymbolAddress(&p, g_x2); p_x2 = (bf16*)p;
    cudaGetSymbolAddress(&p, g_x3); p_x3 = (bf16*)p;
  }
  CUtensorMap tmWq, tmWk, tmWv, tmWo, tmBo;
  make_map(enc, &tmWq, Wq, NH * DH, DM, 64, 128);
  make_map(enc, &tmWk, Wk, NH * DH, DM, 64, 128);
  make_map(enc, &tmWv, Wv, NH * DH, DM, 64, 128);
  make_map(enc, &tmWo, Wo, DM, NH * DH, 64, 64);
  make_map(enc, &tmBo, Bwo, DM, DM, 64, 64);

  cudaStream_t st = cudaStreamPerThread;
  k_pre<<<256, 256, 0, st>>>(x0, mem0);
  cudaLaunchAttribute at[1];
  at[0].id = cudaLaunchAttributeProgrammaticStreamSerialization; at[0].val.programmaticStreamSerializationAllowed = 1;
  {
    cudaLaunchConfig_t cfg = {};
    cfg.gridDim = dim3(96); cfg.blockDim = dim3(384); cfg.dynamicSmemBytes = C::SMEM; cfg.stream = st;
    cfg.attrs = at; cfg.numAttrs = 0;
    cudaLaunchKernelEx(&cfg, k_chain, tmWq, tmWk, tmWv, tmWo);
  }
  WorkArgs wa;
  wa.res[0] = x0; wa.res[1] = p_x2; wa.xa[0] = p_x1; wa.xa[1] = p_x3; wa.xb[0] = p_x2; wa.xb[1] = out;
  wa.wqkv = Bqkv;
  cudaLaunchConfig_t cfg = {};
  cfg.gridDim = dim3(W::NW); cfg.blockDim = dim3(512); cfg.dynamicSmemBytes = W::SMEM; cfg.stream = st;
  cfg.attrs = at; cfg.numAttrs = NOWORK == 2 ? 0 : 1;
  cudaLaunchKernelEx(&cfg, k_work, tmWo, tmBo, wa);
}
```

```cpp
#include <cuda_runtime.h>
#include <cuda_bf16.h>
#include <cuda.h>
#include <stdint.h>

typedef __nv_bfloat16 bf16;

constexpr int SEQ = 2048, DM = 640, NH = 32, DH = 192, NSEG = 64;
#define LAG 14
constexpr int NSTEP = NSEG + LAG;
constexpr uint32_t SENT = 0xFFFFFFFFu;
constexpr int SPIN_LIM = 1 << 20;
constexpr int SPIN_MAIL = 1 << 16;
constexpr int SPIN_CNT = 1 << 16;

constexpr int MAIL9 = 288 * 2048, MAIL_BYTES = MAIL9 + 64 * 3072;
__device__ __align__(1024) uint8_t g_xn[2][NSEG * 40960];
__device__ __align__(1024) uint8_t g_xnb[2][32 * 10 * 8192];
__device__ __align__(1024) uint8_t g_ob[2][32 * 10 * 8192];
__device__ __align__(1024) uint8_t g_o[2][32 * 96 * 8192];
__device__ __align__(1024) uint8_t g_mbuf[NSTEP][20480];
__device__ __align__(1024) uint8_t g_mail[2][MAIL_BYTES];
__device__ __align__(1024) float g_acc[2][16][5][16384];
__device__ __align__(1024) float2 g_stats[16][128][16];
__device__ __align__(128) bf16 g_x1[SEQ * DM];
__device__ __align__(128) bf16 g_x2[SEQ * DM];
__device__ __align__(128) bf16 g_x3[SEQ * DM];
enum { CN_O = 0, CN_P = 1, CN_L = 2, CN_A = 3, CN_X = 4, CN_Z = 5 };
__device__ __align__(128) uint32_t g_cnt[6][2][16][32];
__device__ int g_err;
#define TS(jj, i)
#define TS1(jj, i)
#define PTS(i)
#define LTS(l, b, p, k)
#define TSB(jj, i)
#define TSV(jj, i, v)
#define TS_FLUSH(jj)
#define WTS(l, b, k)
#define WW -1

__device__ __forceinline__ uint32_t smem_u32(const void* p) { return (uint32_t)__cvta_generic_to_shared(p); }
__device__ __forceinline__ uint32_t clk32() { uint32_t t; asm volatile("mov.u32 %0, %%clock;" : "=r"(t)::"memory"); return t; }
__device__ __forceinline__ uint32_t mapa(uint32_t a, uint32_t r) { uint32_t o; asm("mapa.shared::cluster.u32 %0,%1,%2;" : "=r"(o) : "r"(a), "r"(r)); return o; }
__device__ __forceinline__ void mbar_init(uint32_t bar, uint32_t cnt) { asm volatile("mbarrier.init.shared::cta.b64 [%0],%1;" ::"r"(bar), "r"(cnt) : "memory"); }
__device__ __forceinline__ void mbar_expect_tx(uint32_t bar, uint32_t bytes) { asm volatile("mbarrier.arrive.expect_tx.shared::cta.b64 _,[%0],%1;" ::"r"(bar), "r"(bytes) : "memory"); }
__device__ __forceinline__ void mbar_arrive(uint32_t bar) { asm volatile("mbarrier.arrive.shared::cta.b64 _,[%0];" ::"r"(bar) : "memory"); }
__device__ __forceinline__ void mbar_arrive_cluster(uint32_t bar) { asm volatile("mbarrier.arrive.shared::cluster.b64 _,[%0];" ::"r"(bar) : "memory"); }
__device__ __forceinline__ bool mbar_try(uint32_t bar, uint32_t ph) {
  uint32_t ok;
  asm volatile("{.reg .pred p; mbarrier.try_wait.parity.shared::cta.b64 p,[%1],%2; selp.u32 %0,1,0,p;}" : "=r"(ok) : "r"(bar), "r"(ph) : "memory");
  return ok;
}
__device__ __forceinline__ void mbar_wait(uint32_t bar, uint32_t ph, int& dead) {
  if (mbar_try(bar, ph)) return;
  int n = dead ? SPIN_LIM : 0;
  while (!mbar_try(bar, ph)) { if (++n > SPIN_LIM) { dead = 1; g_err = 1; break; } }
}
__device__ __forceinline__ int fresh(int x) { asm volatile("" : "+r"(x)); return x; }
#define PHASE_IDS const int tid = fresh(tid0), lane = tid & 31, w = tid >> 5, g = lane >> 2, t = lane & 3; (void)w; (void)g; (void)t
__device__ __forceinline__ void bar_sync(int id, int n) { asm volatile("bar.sync %0,%1;" ::"r"(id), "r"(n) : "memory"); }
__device__ __forceinline__ void bar_arrive(int id, int n) { asm volatile("bar.arrive %0,%1;" ::"r"(id), "r"(n) : "memory"); }
__device__ __forceinline__ bool bar_red_or(int id, int n, bool v) {
  uint32_t r;
  asm volatile("{\n .reg .pred p, q;\n setp.ne.u32 q, %3, 0;\n barrier.cta.red.or.pred p, %1, %2, q;\n selp.u32 %0, 1, 0, p;\n}" : "=r"(r) : "r"(id), "r"(n), "r"((uint32_t)v) : "memory");
  return r != 0;
}
__device__ __forceinline__ void fence_async() { asm volatile("fence.proxy.async.shared::cta;" ::: "memory"); }
__device__ __forceinline__ void bulk_g2s(uint32_t dst, const void* src, uint32_t bytes, uint32_t bar) {
  asm volatile("cp.async.bulk.shared::cluster.global.mbarrier::complete_tx::bytes [%0],[%1],%2,[%3];" ::"r"(dst), "l"(src), "r"(bytes), "r"(bar) : "memory");
}
__device__ __forceinline__ void bulk_g2s_mc(uint32_t dst, const void* src, uint32_t bytes, uint32_t bar) {
  asm volatile("cp.async.bulk.shared::cluster.global.mbarrier::complete_tx::bytes.multicast::cluster [%0],[%1],%2,[%3],%4;"
               ::"r"(dst), "l"(src), "r"(bytes), "r"(bar), "h"((uint16_t)7) : "memory");
}
__device__ __forceinline__ void bulk_s2g(void* dst, uint32_t src, uint32_t bytes) {
  asm volatile("cp.async.bulk.global.shared::cta.bulk_group [%0],[%1],%2;" ::"l"(dst), "r"(src), "r"(bytes) : "memory");
}
__device__ __forceinline__ void bulk_s2c(uint32_t dst, uint32_t src, uint32_t bytes, uint32_t bar) {
  asm volatile("cp.async.bulk.shared::cluster.shared::cta.mbarrier::complete_tx::bytes [%0],[%1],%2,[%3];" ::"r"(dst), "r"(src), "r"(bytes), "r"(bar) : "memory");
}
__device__ __forceinline__ void tma2d(uint32_t dst, const CUtensorMap* tm, int c0, int c1, uint32_t bar) {
  asm volatile("cp.async.bulk.tensor.2d.shared::cluster.global.mbarrier::complete_tx::bytes [%0],[%1,{%3,%4}],[%2];"
               ::"r"(dst), "l"(tm), "r"(bar), "r"(c0), "r"(c1) : "memory");
}
__device__ __forceinline__ void tma2d_prefetch(const CUtensorMap* tm, int c0, int c1) {
  asm volatile("cp.async.bulk.prefetch.tensor.2d.L2.global.tile [%0,{%1,%2}];" ::"l"(tm), "r"(c0), "r"(c1) : "memory");
}
__device__ __forceinline__ uint32_t pack_bf16(float lo, float hi) {
  uint32_t r; asm("cvt.rn.bf16x2.f32 %0,%1,%2;" : "=r"(r) : "f"(hi), "f"(lo)); return r;
}
__device__ __forceinline__ float bf_lo(uint32_t x) { return __uint_as_float(x << 16); }
__device__ __forceinline__ float bf_hi(uint32_t x) { return __uint_as_float(x & 0xFFFF0000u); }
__device__ __forceinline__ float ex2(float x) { float y; asm("ex2.approx.ftz.f32 %0,%1;" : "=f"(y) : "f"(x)); return y; }
__device__ __forceinline__ void ldsm4(uint32_t (&r)[4], uint32_t a) {
  asm volatile("ldmatrix.sync.aligned.m8n8.x4.shared.b16 {%0,%1,%2,%3},[%4];" : "=r"(r[0]), "=r"(r[1]), "=r"(r[2]), "=r"(r[3]) : "r"(a) : "memory");
}
__device__ __forceinline__ void ldsm4t(uint32_t (&r)[4], uint32_t a) {
  asm volatile("ldmatrix.sync.aligned.m8n8.x4.trans.shared.b16 {%0,%1,%2,%3},[%4];" : "=r"(r[0]), "=r"(r[1]), "=r"(r[2]), "=r"(r[3]) : "r"(a) : "memory");
}
__device__ __forceinline__ void ldsm2(uint32_t& r0, uint32_t& r1, uint32_t a) {
  asm volatile("ldmatrix.sync.aligned.m8n8.x2.shared.b16 {%0,%1},[%2];" : "=r"(r0), "=r"(r1) : "r"(a) : "memory");
}
__device__ __forceinline__ void ldsm1(uint32_t& r0, uint32_t a) {
  asm volatile("ldmatrix.sync.aligned.m8n8.x1.shared.b16 {%0},[%1];" : "=r"(r0) : "r"(a) : "memory");
}
__device__ __forceinline__ void mma16816(float (&d)[4], uint32_t a0, uint32_t a1, uint32_t a2, uint32_t a3, uint32_t b0, uint32_t b1) {
  asm volatile("mma.sync.aligned.m16n8k16.row.col.f32.bf16.bf16.f32 {%0,%1,%2,%3},{%4,%5,%6,%7},{%8,%9},{%0,%1,%2,%3};"
               : "+f"(d[0]), "+f"(d[1]), "+f"(d[2]), "+f"(d[3]) : "r"(a0), "r"(a1), "r"(a2), "r"(a3), "r"(b0), "r"(b1));
}
__device__ __forceinline__ void mma1688(float (&d)[4], uint32_t a0, uint32_t a1, uint32_t b0) {
  asm volatile("mma.sync.aligned.m16n8k8.row.col.f32.bf16.bf16.f32 {%0,%1,%2,%3},{%4,%5},{%6},{%0,%1,%2,%3};"
               : "+f"(d[0]), "+f"(d[1]), "+f"(d[2]), "+f"(d[3]) : "r"(a0), "r"(a1), "r"(b0));
}
__device__ __forceinline__ void sts32(uint32_t a, uint32_t v) { asm volatile("st.shared.b32 [%0],%1;" ::"r"(a), "r"(v) : "memory"); }
__device__ __forceinline__ void sts64f(uint32_t a, float x, float y) { asm volatile("st.shared.v2.f32 [%0],{%1,%2};" ::"r"(a), "f"(x), "f"(y) : "memory"); }
__device__ __forceinline__ void sts128(uint32_t a, uint4 v) { asm volatile("st.shared.v4.b32 [%0],{%1,%2,%3,%4};" ::"r"(a), "r"(v.x), "r"(v.y), "r"(v.z), "r"(v.w) : "memory"); }
__device__ __forceinline__ float lds32f(uint32_t a) { float v; asm volatile("ld.shared.f32 %0,[%1];" : "=f"(v) : "r"(a) : "memory"); return v; }
__device__ __forceinline__ float2 lds64f(uint32_t a) { float2 v; asm volatile("ld.shared.v2.f32 {%0,%1},[%2];" : "=f"(v.x), "=f"(v.y) : "r"(a) : "memory"); return v; }
__device__ __forceinline__ uint4 lds128(uint32_t a) { uint4 v; asm volatile("ld.shared.v4.b32 {%0,%1,%2,%3},[%4];" : "=r"(v.x), "=r"(v.y), "=r"(v.z), "=r"(v.w) : "r"(a) : "memory"); return v; }
__device__ __forceinline__ float4 lds128f(uint32_t a) { float4 v; asm volatile("ld.shared.v4.f32 {%0,%1,%2,%3},[%4];" : "=f"(v.x), "=f"(v.y), "=f"(v.z), "=f"(v.w) : "r"(a) : "memory"); return v; }
__device__ __forceinline__ void st_async2(uint32_t a, float x, float y, uint32_t bar) {
  asm volatile("st.async.weak.shared::cluster.mbarrier::complete_tx::bytes.v2.f32 [%0],{%1,%2},[%3];" ::"r"(a), "f"(x), "f"(y), "r"(bar) : "memory");
}
__device__ __forceinline__ void st_async4(uint32_t a, const float (&v)[4], uint32_t bar) {
  asm volatile("st.async.weak.shared::cluster.mbarrier::complete_tx::bytes.v4.f32 [%0],{%1,%2,%3,%4},[%5];" ::"r"(a), "f"(v[0]), "f"(v[1]), "f"(v[2]), "f"(v[3]), "r"(bar) : "memory");
}
__device__ __forceinline__ void st_async4v(uint32_t a, float x, float y, float z, float w, uint32_t bar) {
  asm volatile("st.async.weak.shared::cluster.mbarrier::complete_tx::bytes.v4.f32 [%0],{%1,%2,%3,%4},[%5];" ::"r"(a), "f"(x), "f"(y), "f"(z), "f"(w), "r"(bar) : "memory");
}
__device__ __forceinline__ void st_async4u(uint32_t a, const uint4& v, uint32_t bar) {
  asm volatile("st.async.weak.shared::cluster.mbarrier::complete_tx::bytes.v4.b32 [%0],{%1,%2,%3,%4},[%5];" ::"r"(a), "r"(v.x), "r"(v.y), "r"(v.z), "r"(v.w), "r"(bar) : "memory");
}
__device__ __forceinline__ uint4 ld_relaxed4(const void* p) {
  uint4 v; asm volatile("ld.relaxed.gpu.global.v4.u32 {%0,%1,%2,%3},[%4];" : "=r"(v.x), "=r"(v.y), "=r"(v.z), "=r"(v.w) : "l"(p) : "memory"); return v;
}
__device__ __forceinline__ uint32_t ld_relaxed(const void* p) {
  uint32_t v; asm volatile("ld.relaxed.gpu.global.u32 %0,[%1];" : "=r"(v) : "l"(p) : "memory"); return v;
}
__device__ __forceinline__ void st_relaxed(void* p, uint32_t v) { asm volatile("st.relaxed.gpu.global.b32 [%0],%1;" ::"l"(p), "r"(v) : "memory"); }
__device__ __forceinline__ void st_relaxed4(void* p, uint32_t v) { asm volatile("st.relaxed.gpu.global.v4.b32 [%0],{%1,%1,%1,%1};" ::"l"(p), "r"(v) : "memory"); }

__device__ __forceinline__ uint32_t ld_acquire(const void* p) {
  uint32_t v; asm volatile("ld.acquire.gpu.global.u32 %0,[%1];" : "=r"(v) : "l"(p) : "memory"); return v;
}
__device__ __forceinline__ float4 ld_relaxed4f(const void* p) {
  float4 v; asm volatile("ld.relaxed.gpu.global.v4.f32 {%0,%1,%2,%3},[%4];" : "=f"(v.x), "=f"(v.y), "=f"(v.z), "=f"(v.w) : "l"(p) : "memory"); return v;
}
__device__ __forceinline__ float2 ld_relaxed2f(const void* p) {
  float2 v; asm volatile("ld.relaxed.gpu.global.v2.f32 {%0,%1},[%2];" : "=f"(v.x), "=f"(v.y) : "l"(p) : "memory"); return v;
}
__device__ __forceinline__ void prefetch_l2(const void* p) { asm volatile("prefetch.global.L2 [%0];" ::"l"(p)); }
__device__ __forceinline__ void fence_gpu() { asm volatile("fence.acq_rel.gpu;" ::: "memory"); }
#define FAG 1
__device__ __forceinline__ void fence_async_all() {
  asm volatile("fence.proxy.async.global;" ::: "memory");
}
__device__ __forceinline__ uint32_t* cnt_ptr(int kind, int layer, int b) { return &g_cnt[kind][layer][b][0]; }
#define RELS 1
__device__ __forceinline__ void cnt_signal(int kind, int layer, int b) {
  asm volatile("red.release.gpu.global.add.u32 [%0],1;" ::"l"(cnt_ptr(kind, layer, b)) : "memory");
}
#define ACQW 1
#define SIGF 1
#define HOIST 2
__device__ __forceinline__ void cnt_wait(int kind, int layer, int b, uint32_t target, int& dead) {
  int n = dead ? SPIN_CNT : 0;
  while (ld_acquire(cnt_ptr(kind, layer, b)) < target) { if (++n > SPIN_CNT) { dead = 1; g_err = 10 + kind; break; } }
}

__device__ __forceinline__ uint64_t mkdesc(uint32_t addr, uint32_t lbo, uint32_t sbo) {
  return (uint64_t)((addr & 0x3FFFF) >> 4) | ((uint64_t)(lbo >> 4) << 16) | ((uint64_t)(sbo >> 4) << 32) | ((uint64_t)1 << 62);
}
__device__ __forceinline__ uint64_t mkdesc_ns(uint32_t addr, uint32_t lbo, uint32_t sbo) {
  return (uint64_t)((addr & 0x3FFFF) >> 4) | ((uint64_t)(lbo >> 4) << 16) | ((uint64_t)(sbo >> 4) << 32);
}
__device__ __forceinline__ void wg_fence() { asm volatile("wgmma.fence.sync.aligned;" ::: "memory"); }
__device__ __forceinline__ void wg_commit() { asm volatile("wgmma.commit_group.sync.aligned;" ::: "memory"); }
template <int N> __device__ __forceinline__ void wg_wait() { asm volatile("wgmma.wait_group.sync.aligned %0;" ::"n"(N) : "memory"); }

__device__ __forceinline__ void wgmma_rs16(float (&d)[8], const uint32_t (&a)[4], uint64_t db, int sc) {
  asm volatile("{.reg .pred p; setp.ne.b32 p,%13,0; wgmma.mma_async.sync.aligned.m64n16k16.f32.bf16.bf16 "
               "{%0,%1,%2,%3,%4,%5,%6,%7},{%8,%9,%10,%11},%12,p,1,1,0;}"
               : "+f"(d[0]), "+f"(d[1]), "+f"(d[2]), "+f"(d[3]), "+f"(d[4]), "+f"(d[5]), "+f"(d[6]), "+f"(d[7])
               : "r"(a[0]), "r"(a[1]), "r"(a[2]), "r"(a[3]), "l"(db), "r"(sc));
}
__device__ __forceinline__ void wgmma_rs64(float (&d)[32], const uint32_t (&a)[4], uint64_t db, int sc) {
  asm volatile("{.reg .pred p; setp.ne.b32 p,%37,0; wgmma.mma_async.sync.aligned.m64n64k16.f32.bf16.bf16 "
               "{%0,%1,%2,%3,%4,%5,%6,%7,%8,%9,%10,%11,%12,%13,%14,%15,%16,%17,%18,%19,%20,%21,%22,%23,%24,%25,%26,%27,%28,%29,%30,%31},{%32,%33,%34,%35},%36,p,1,1,0;}"
               : "+f"(d[0]), "+f"(d[1]), "+f"(d[2]), "+f"(d[3]), "+f"(d[4]), "+f"(d[5]), "+f"(d[6]), "+f"(d[7]), "+f"(d[8]), "+f"(d[9]), "+f"(d[10]), "+f"(d[11]), "+f"(d[12]), "+f"(d[13]), "+f"(d[14]), "+f"(d[15]), "+f"(d[16]), "+f"(d[17]), "+f"(d[18]), "+f"(d[19]), "+f"(d[20]), "+f"(d[21]), "+f"(d[22]), "+f"(d[23]), "+f"(d[24]), "+f"(d[25]), "+f"(d[26]), "+f"(d[27]), "+f"(d[28]), "+f"(d[29]), "+f"(d[30]), "+f"(d[31])
               : "r"(a[0]), "r"(a[1]), "r"(a[2]), "r"(a[3]), "l"(db), "r"(sc));
}
__device__ __forceinline__ void wgmma_rt16(float (&d)[8], const uint32_t (&a)[4], uint64_t db, int sc) {
  asm volatile("{.reg .pred p; setp.ne.b32 p,%13,0; wgmma.mma_async.sync.aligned.m64n16k16.f32.bf16.bf16 "
               "{%0,%1,%2,%3,%4,%5,%6,%7},{%8,%9,%10,%11},%12,p,1,1,1;}"
               : "+f"(d[0]), "+f"(d[1]), "+f"(d[2]), "+f"(d[3]), "+f"(d[4]), "+f"(d[5]), "+f"(d[6]), "+f"(d[7])
               : "r"(a[0]), "r"(a[1]), "r"(a[2]), "r"(a[3]), "l"(db), "r"(sc));
}
__device__ __forceinline__ void wgmma_rt80(float (&d)[40], const uint32_t (&a)[4], uint64_t db, int sc) {
  asm volatile("{.reg .pred p; setp.ne.b32 p,%45,0; wgmma.mma_async.sync.aligned.m64n80k16.f32.bf16.bf16 "
               "{%0,%1,%2,%3,%4,%5,%6,%7,%8,%9,%10,%11,%12,%13,%14,%15,%16,%17,%18,%19,%20,%21,%22,%23,%24,%25,%26,%27,%28,%29,%30,%31,%32,%33,%34,%35,%36,%37,%38,%39},{%40,%41,%42,%43},%44,p,1,1,1;}"
               : "+f"(d[0]), "+f"(d[1]), "+f"(d[2]), "+f"(d[3]), "+f"(d[4]), "+f"(d[5]), "+f"(d[6]), "+f"(d[7]), "+f"(d[8]), "+f"(d[9]), "+f"(d[10]), "+f"(d[11]), "+f"(d[12]), "+f"(d[13]), "+f"(d[14]), "+f"(d[15]), "+f"(d[16]), "+f"(d[17]), "+f"(d[18]), "+f"(d[19]), "+f"(d[20]), "+f"(d[21]), "+f"(d[22]), "+f"(d[23]), "+f"(d[24]), "+f"(d[25]), "+f"(d[26]), "+f"(d[27]), "+f"(d[28]), "+f"(d[29]), "+f"(d[30]), "+f"(d[31]), "+f"(d[32]), "+f"(d[33]), "+f"(d[34]), "+f"(d[35]), "+f"(d[36]), "+f"(d[37]), "+f"(d[38]), "+f"(d[39])
               : "r"(a[0]), "r"(a[1]), "r"(a[2]), "r"(a[3]), "l"(db), "r"(sc));
}
__device__ __forceinline__ void wgmma_ts16(float (&d)[8], uint64_t da, uint64_t db, int sc) {
  asm volatile("{.reg .pred p; setp.ne.b32 p,%10,0; wgmma.mma_async.sync.aligned.m64n16k16.f32.bf16.bf16 "
               "{%0,%1,%2,%3,%4,%5,%6,%7},%8,%9,p,1,1,1,0;}"
               : "+f"(d[0]), "+f"(d[1]), "+f"(d[2]), "+f"(d[3]), "+f"(d[4]), "+f"(d[5]), "+f"(d[6]), "+f"(d[7])
               : "l"(da), "l"(db), "r"(sc));
}
__device__ __forceinline__ void wgmma_ts64(float (&d)[32], uint64_t da, uint64_t db, int sc) {
  asm volatile("{.reg .pred p; setp.ne.b32 p,%34,0; wgmma.mma_async.sync.aligned.m64n64k16.f32.bf16.bf16 "
               "{%0,%1,%2,%3,%4,%5,%6,%7,%8,%9,%10,%11,%12,%13,%14,%15,%16,%17,%18,%19,%20,%21,%22,%23,%24,%25,%26,%27,%28,%29,%30,%31},%32,%33,p,1,1,1,0;}"
               : "+f"(d[0]), "+f"(d[1]), "+f"(d[2]), "+f"(d[3]), "+f"(d[4]), "+f"(d[5]), "+f"(d[6]), "+f"(d[7]), "+f"(d[8]), "+f"(d[9]), "+f"(d[10]), "+f"(d[11]), "+f"(d[12]), "+f"(d[13]), "+f"(d[14]), "+f"(d[15]), "+f"(d[16]), "+f"(d[17]), "+f"(d[18]), "+f"(d[19]), "+f"(d[20]), "+f"(d[21]), "+f"(d[22]), "+f"(d[23]), "+f"(d[24]), "+f"(d[25]), "+f"(d[26]), "+f"(d[27]), "+f"(d[28]), "+f"(d[29]), "+f"(d[30]), "+f"(d[31])
               : "l"(da), "l"(db), "r"(sc));
}
__device__ __forceinline__ void wgmma_tt16(float (&d)[8], uint64_t da, uint64_t db, int sc) {
  asm volatile("{.reg .pred p; setp.ne.b32 p,%10,0; wgmma.mma_async.sync.aligned.m64n16k16.f32.bf16.bf16 "
               "{%0,%1,%2,%3,%4,%5,%6,%7},%8,%9,p,1,1,1,1;}"
               : "+f"(d[0]), "+f"(d[1]), "+f"(d[2]), "+f"(d[3]), "+f"(d[4]), "+f"(d[5]), "+f"(d[6]), "+f"(d[7])
               : "l"(da), "l"(db), "r"(sc));
}
__device__ __forceinline__ void wgmma_tt40(float (&d)[20], uint64_t da, uint64_t db, int sc) {
  asm volatile("{.reg .pred p; setp.ne.b32 p,%22,0; wgmma.mma_async.sync.aligned.m64n40k16.f32.bf16.bf16 "
               "{%0,%1,%2,%3,%4,%5,%6,%7,%8,%9,%10,%11,%12,%13,%14,%15,%16,%17,%18,%19},%20,%21,p,1,1,1,1;}"
               : "+f"(d[0]), "+f"(d[1]), "+f"(d[2]), "+f"(d[3]), "+f"(d[4]), "+f"(d[5]), "+f"(d[6]), "+f"(d[7]), "+f"(d[8]), "+f"(d[9]), "+f"(d[10]), "+f"(d[11]), "+f"(d[12]), "+f"(d[13]), "+f"(d[14]), "+f"(d[15]), "+f"(d[16]), "+f"(d[17]), "+f"(d[18]), "+f"(d[19])
               : "l"(da), "l"(db), "r"(sc));
}
__device__ __forceinline__ void wgmma_ss8(float (&d)[4], uint64_t da, uint64_t db, int sc) {
  asm volatile("{.reg .pred p; setp.ne.b32 p,%6,0; wgmma.mma_async.sync.aligned.m64n8k16.f32.bf16.bf16 "
               "{%0,%1,%2,%3},%4,%5,p,1,1,0,0;}"
               : "+f"(d[0]), "+f"(d[1]), "+f"(d[2]), "+f"(d[3])
               : "l"(da), "l"(db), "r"(sc));
}
__device__ __forceinline__ void wgmma_ss32(float (&d)[16], uint64_t da, uint64_t db, int sc) {
  asm volatile("{.reg .pred p; setp.ne.b32 p,%18,0; wgmma.mma_async.sync.aligned.m64n32k16.f32.bf16.bf16 "
               "{%0,%1,%2,%3,%4,%5,%6,%7,%8,%9,%10,%11,%12,%13,%14,%15},%16,%17,p,1,1,0,0;}"
               : "+f"(d[0]), "+f"(d[1]), "+f"(d[2]), "+f"(d[3]), "+f"(d[4]), "+f"(d[5]), "+f"(d[6]), "+f"(d[7]), "+f"(d[8]), "+f"(d[9]), "+f"(d[10]), "+f"(d[11]), "+f"(d[12]), "+f"(d[13]), "+f"(d[14]), "+f"(d[15])
               : "l"(da), "l"(db), "r"(sc));
}
__device__ __forceinline__ void wgmma_st64(float (&d)[32], uint64_t da, uint64_t db, int sc) {
  asm volatile("{.reg .pred p; setp.ne.b32 p,%34,0; wgmma.mma_async.sync.aligned.m64n64k16.f32.bf16.bf16 "
               "{%0,%1,%2,%3,%4,%5,%6,%7,%8,%9,%10,%11,%12,%13,%14,%15,%16,%17,%18,%19,%20,%21,%22,%23,%24,%25,%26,%27,%28,%29,%30,%31},%32,%33,p,1,1,0,1;}"
               : "+f"(d[0]), "+f"(d[1]), "+f"(d[2]), "+f"(d[3]), "+f"(d[4]), "+f"(d[5]), "+f"(d[6]), "+f"(d[7]), "+f"(d[8]), "+f"(d[9]), "+f"(d[10]), "+f"(d[11]), "+f"(d[12]), "+f"(d[13]), "+f"(d[14]), "+f"(d[15]), "+f"(d[16]), "+f"(d[17]), "+f"(d[18]), "+f"(d[19]), "+f"(d[20]), "+f"(d[21]), "+f"(d[22]), "+f"(d[23]), "+f"(d[24]), "+f"(d[25]), "+f"(d[26]), "+f"(d[27]), "+f"(d[28]), "+f"(d[29]), "+f"(d[30]), "+f"(d[31])
               : "l"(da), "l"(db), "r"(sc));
}
__device__ __forceinline__ void wgmma_st128(float (&d)[64], uint64_t da, uint64_t db, int sc) {
  asm volatile("{.reg .pred p; setp.ne.b32 p,%66,0; wgmma.mma_async.sync.aligned.m64n128k16.f32.bf16.bf16 "
               "{%0,%1,%2,%3,%4,%5,%6,%7,%8,%9,%10,%11,%12,%13,%14,%15,%16,%17,%18,%19,%20,%21,%22,%23,%24,%25,%26,%27,%28,%29,%30,%31,%32,%33,%34,%35,%36,%37,%38,%39,%40,%41,%42,%43,%44,%45,%46,%47,%48,%49,%50,%51,%52,%53,%54,%55,%56,%57,%58,%59,%60,%61,%62,%63},%64,%65,p,1,1,0,1;}"
               : "+f"(d[0]), "+f"(d[1]), "+f"(d[2]), "+f"(d[3]), "+f"(d[4]), "+f"(d[5]), "+f"(d[6]), "+f"(d[7]), "+f"(d[8]), "+f"(d[9]), "+f"(d[10]), "+f"(d[11]), "+f"(d[12]), "+f"(d[13]), "+f"(d[14]), "+f"(d[15]), "+f"(d[16]), "+f"(d[17]), "+f"(d[18]), "+f"(d[19]), "+f"(d[20]), "+f"(d[21]), "+f"(d[22]), "+f"(d[23]), "+f"(d[24]), "+f"(d[25]), "+f"(d[26]), "+f"(d[27]), "+f"(d[28]), "+f"(d[29]), "+f"(d[30]), "+f"(d[31]), "+f"(d[32]), "+f"(d[33]), "+f"(d[34]), "+f"(d[35]), "+f"(d[36]), "+f"(d[37]), "+f"(d[38]), "+f"(d[39]), "+f"(d[40]), "+f"(d[41]), "+f"(d[42]), "+f"(d[43]), "+f"(d[44]), "+f"(d[45]), "+f"(d[46]), "+f"(d[47]), "+f"(d[48]), "+f"(d[49]), "+f"(d[50]), "+f"(d[51]), "+f"(d[52]), "+f"(d[53]), "+f"(d[54]), "+f"(d[55]), "+f"(d[56]), "+f"(d[57]), "+f"(d[58]), "+f"(d[59]), "+f"(d[60]), "+f"(d[61]), "+f"(d[62]), "+f"(d[63])
               : "l"(da), "l"(db), "r"(sc));
}

__device__ __forceinline__ void stsm4(uint32_t a, uint32_t r0, uint32_t r1, uint32_t r2, uint32_t r3) {
  asm volatile("stmatrix.sync.aligned.m8n8.x4.shared.b16 [%0],{%1,%2,%3,%4};" ::"r"(a), "r"(r0), "r"(r1), "r"(r2), "r"(r3) : "memory");
}
__device__ __forceinline__ void stsm4t(uint32_t a, uint32_t r0, uint32_t r1, uint32_t r2, uint32_t r3) {
  asm volatile("stmatrix.sync.aligned.m8n8.x4.trans.shared.b16 [%0],{%1,%2,%3,%4};" ::"r"(a), "r"(r0), "r"(r1), "r"(r2), "r"(r3) : "memory");
}
__device__ __forceinline__ void sts64(uint32_t a, uint32_t x, uint32_t y) { asm volatile("st.shared.v2.b32 [%0],{%1,%2};" ::"r"(a), "r"(x), "r"(y) : "memory"); }
__device__ __forceinline__ void st_async2u(uint32_t a, uint32_t x, uint32_t y, uint32_t bar) {
  asm volatile("st.async.weak.shared::cluster.mbarrier::complete_tx::bytes.v2.b32 [%0],{%1,%2},[%3];" ::"r"(a), "r"(x), "r"(y), "r"(bar) : "memory");
}
__device__ __forceinline__ void st_relaxed128(void* p, uint32_t x, uint32_t y, uint32_t z, uint32_t w) {
  asm volatile("{.reg .b128 v; .reg .b64 lo, hi; mov.b64 lo,{%1,%2}; mov.b64 hi,{%3,%4}; mov.b128 v,{lo,hi}; st.relaxed.gpu.global.b128 [%0],v;}" ::"l"(p), "r"(x), "r"(y), "r"(z), "r"(w) : "memory");
}
__device__ __forceinline__ void st_relaxed64(void* p, uint32_t x, uint32_t y) {
  asm volatile("{.reg .b64 v; mov.b64 v,{%1,%2}; st.relaxed.gpu.global.b64 [%0],v;}" ::"l"(p), "r"(x), "r"(y) : "memory");
}
__device__ __forceinline__ uint4 ld_relaxed128(const void* p) {
  uint4 v;
  asm volatile("{.reg .b128 v; .reg .b64 lo, hi; ld.relaxed.gpu.global.b128 v,[%4]; mov.b128 {lo,hi},v; mov.b64 {%0,%1},lo; mov.b64 {%2,%3},hi;}" : "=r"(v.x), "=r"(v.y), "=r"(v.z), "=r"(v.w) : "l"(p) : "memory");
  return v;
}

__device__ __forceinline__ uint32_t pack_h2(float lo, float hi) {
  uint32_t r; asm("cvt.rn.satfinite.f16x2.f32 %0,%1,%2;" : "=r"(r) : "f"(hi), "f"(lo)); return r;
}
__device__ __forceinline__ void add_h2(float& lo, float& hi, uint32_t u, uint32_t v) {
  float a, b;
  asm("{.reg .b16 l, h; .reg .b32 s; add.rn.f16x2 s,%2,%3; mov.b32 {l,h},s; cvt.f32.f16 %0,l; cvt.f32.f16 %1,h;}" : "=f"(a), "=f"(b) : "r"(u), "r"(v));
  lo += a; hi += b;
}
constexpr int SPIN_TOT = 1 << 22;
__device__ __forceinline__ void mwait(uint32_t bar, uint32_t ph, int& spin) {
  asm volatile("{.reg .pred p, q;\nWAIT_LOOP:\n mbarrier.try_wait.parity.shared::cta.b64 p,[%1],%2;\n @!p add.s32 %0,%0,1;\n setp.lt.and.s32 q,%0,%3,!p;\n @q bra WAIT_LOOP;\n}"
               : "+r"(spin) : "r"(bar), "r"(ph), "n"(SPIN_TOT) : "memory");
}
__device__ __forceinline__ uint32_t pin(uint32_t x) { asm volatile("" : "+r"(x)); return x; }
template <typename T> __device__ __forceinline__ T* pinp(T* x) { asm volatile("" : "+l"(x)); return x; }
__device__ __forceinline__ void st_async1u(uint32_t a, uint32_t x, uint32_t bar) {
  asm volatile("st.async.weak.shared::cluster.mbarrier::complete_tx::bytes.b32 [%0],%1,[%2];" ::"r"(a), "r"(x), "r"(bar) : "memory");
}
__device__ __forceinline__ uint32_t lds32(uint32_t a) { uint32_t v; asm volatile("ld.shared.b32 %0,[%1];" : "=r"(v) : "r"(a) : "memory"); return v; }
__device__ __forceinline__ uint2 lds64(uint32_t a) { uint2 v; asm volatile("ld.shared.v2.b32 {%0,%1},[%2];" : "=r"(v.x), "=r"(v.y) : "r"(a) : "memory"); return v; }

__device__ __forceinline__ void ln_row_to_image(const bf16* __restrict__ x, uint8_t* __restrict__ img, int row, int lane) {
  const uint4* src = reinterpret_cast<const uint4*>(x + (size_t)row * DM);
  uint4 v[3];
  v[0] = src[lane]; v[1] = src[lane + 32];
  v[2] = lane < 16 ? src[lane + 64] : make_uint4(0, 0, 0, 0);
  float s = 0.f;
#pragma unroll
  for (int i = 0; i < 3; i++) {
    s += bf_lo(v[i].x) + bf_hi(v[i].x) + bf_lo(v[i].y) + bf_hi(v[i].y) + bf_lo(v[i].z) + bf_hi(v[i].z) + bf_lo(v[i].w) + bf_hi(v[i].w);
  }
#pragma unroll
  for (int o = 16; o > 0; o >>= 1) s += __shfl_xor_sync(0xffffffffu, s, o);
  const float mean = s * (1.f / DM);
  float q = 0.f;
#pragma unroll
  for (int i = 0; i < 3; i++) {
    if (i < 2 || lane < 16) {
      const uint32_t w[4] = {v[i].x, v[i].y, v[i].z, v[i].w};
#pragma unroll
      for (int j = 0; j < 4; j++) { float a = bf_lo(w[j]) - mean, b = bf_hi(w[j]) - mean; q += a * a + b * b; }
    }
  }
#pragma unroll
  for (int o = 16; o > 0; o >>= 1) q += __shfl_xor_sync(0xffffffffu, q, o);
  const float rstd = rsqrtf(q * (1.f / DM) + 1e-5f);
#pragma unroll
  for (int i = 0; i < 3; i++) {
    if (i < 2 || lane < 16) {
      const int c = lane + 32 * i;
      uint4 o;
      o.x = pack_bf16((bf_lo(v[i].x) - mean) * rstd, (bf_hi(v[i].x) - mean) * rstd);
      o.y = pack_bf16((bf_lo(v[i].y) - mean) * rstd, (bf_hi(v[i].y) - mean) * rstd);
      o.z = pack_bf16((bf_lo(v[i].z) - mean) * rstd, (bf_hi(v[i].z) - mean) * rstd);
      o.w = pack_bf16((bf_lo(v[i].w) - mean) * rstd, (bf_hi(v[i].w) - mean) * rstd);
      const size_t off = (size_t)(row >> 5) * 40960 + (c >> 4) * 8192 + ((row >> 3) & 3) * 2048 + ((c >> 3) & 1) * 1024 + (row & 7) * 128 + (((c & 7) ^ (row & 7)) << 4);
      *reinterpret_cast<uint4*>(img + off) = o;
    }
  }
}

#define LN30 1
__global__ void __launch_bounds__(256) k_pre(const bf16* __restrict__ x, const bf16* __restrict__ mem0) {
  const int row = blockIdx.x * 8 + (threadIdx.x >> 5);
  ln_row_to_image(x, g_xn[0], row, threadIdx.x & 31);
  const int gt = blockIdx.x * 256 + threadIdx.x;
  const uint4 sent = make_uint4(SENT, SENT, SENT, SENT);
  uint4* mail = reinterpret_cast<uint4*>(&g_mail[0][0]);
  for (int i = gt; i < 2 * MAIL_BYTES / 16; i += 65536) mail[i] = sent;
  uint4* mb = reinterpret_cast<uint4*>(&g_mbuf[0][0]);
  for (int i = gt; i < NSTEP * 1280; i += 65536) {
    const int p = i % 1280, st = i / 1280;
    uint4 v = sent;
    if (st == 0 || (st == LAG && (p & 8))) v = *reinterpret_cast<const uint4*>(mem0 + (p & 7) * DM + (p >> 4) * 8);
    mb[i] = v;
  }
  if (gt < 16 * 128 * 8) reinterpret_cast<uint4*>(&g_stats[0][0][0])[gt] = sent;
  if (gt < 6 * 2 * 16 * 8) reinterpret_cast<uint4*>(&g_cnt[0][0][0][0])[gt] = make_uint4(0, 0, 0, 0);
}

namespace C {
constexpr int NKR = 37;
constexpr int OFF_WQ = 0, OFF_WK = 81920;
constexpr int OFF_YO = 163840, OFF_YV = OFF_YO + 6144;
constexpr int OFF_M = 176128;
__host__ __device__ constexpr int og_off(int c) { return c ? OFF_M + 14336 + c * 2048 : 229376; }
constexpr int OFF_KT = 196608;
constexpr int OFF_XT = OFF_KT + 10240;
constexpr int OFF_VT = OFF_XT + 7168;
constexpr int OFF_XM = OFF_VT + 11392;
constexpr int KS = 1280, VS = 1408;
__host__ __device__ constexpr int slot_off(int p) { return p == 2 ? OFF_M : OFF_KT + (p % 3) * 16384; }
constexpr int OFF_BAR = 231552;
constexpr int OFF_SAFE = OFF_BAR + 160;
constexpr int OFF_TS = OFF_BAR + 256;
constexpr int SMEM = 232448;
constexpr uint32_t SB0 = 1024;
constexpr int BAR_F = OFF_BAR, BAR_E = OFF_BAR + 40, BAR_M = OFF_BAR + 80, BAR_MOK = OFF_BAR + 88, BAR_XM = OFF_BAR + 96, BAR_XF = OFF_BAR + 104,
              BAR_XT = OFF_BAR + 112, BAR_MF = OFF_BAR + 120, BAR_OG = OFF_BAR + 128, BAR_W = OFF_BAR + 136;
constexpr int NB_PRO = 1, NB_RD = 2, NB_MR = 3, NB_QK = 4, NB_SM = 5, NB_VA = 6, NB_VQ = 7, NB_A = 8, NB_Q = 9, NB_C = 10, NB_WQ = 11, NB_QI = 12, NB_SI = 13, NB_WV = 14;
#define B1 300
#define B2 400
#define PSTG 150
#define KSP 40
#define OGF 0
#define VSP 8
#define RFK 5
#define PFD 3
#define WOL 0
#define NOWORK 0
constexpr float SCL = 0.07216878364870322f * 1.4426950408889634f / 256;
}

#define CBAR_SYNC(id, n) bar_sync(id, n)
#define CBAR_ARRIVE(id, n) bar_arrive(id, n)

__device__ __forceinline__ uint64_t wdesc(int off) { return mkdesc(C::SB0 + off, 8192, 1024); }
__device__ __forceinline__ uint64_t mdesc(int k) { return mkdesc_ns(C::SB0 + C::OFF_M + k * 512, 256, 128); }
__device__ __forceinline__ uint64_t tdesc(int k) { return mkdesc(C::SB0 + C::slot_off(k >> 3) + ((k >> 2) & 1) * 1024 + (k & 3) * 32, 16, 2048); }

__device__ __forceinline__ int dh_row(int n) { return (n & ~63) + (n & 32) + ((n >> 1) & 3) * 8 + ((n >> 3) & 3) * 2 + (n & 1); }
template <bool PERM>
__device__ __forceinline__ void load_weights_rs(uint32_t (&wf)[C::NKR][4], uint32_t sb, int stage, int yoff, int tid0) {
  using namespace C;
  const int i = (tid0 >> 3) & 3, n0 = (tid0 & 7) + (i >> 1) * 8;
  const int chunk = 2 * ((tid0 >> 5) & 3) + (i & 1);
  const int r0 = PERM ? dh_row(n0) : n0, r1 = PERM ? dh_row(n0 + 16) : n0 + 16;
  const uint32_t a0 = sb + stage + r0 * 128 + ((chunk ^ (r0 & 7)) << 4), a1 = sb + stage + r1 * 128 + ((chunk ^ (r1 & 7)) << 4);
#pragma unroll
  for (int k = 0; k < NKR; k++) ldsm4t(wf[k], ((k & 1) ? a1 : a0) + (k >> 1) * 4096);
#pragma unroll
  for (int k = 0; k < 40 - NKR; k++) {
    const int n = (NKR + k) * 16 + ((tid0 & 127) >> 3), r = PERM ? dh_row(n) : n, c = tid0 & 7;
    sts128(sb + yoff + (n - NKR * 16) * 128 + ((c ^ (n & 7)) << 4), lds128(sb + stage + r * 128 + ((c ^ (r & 7)) << 4)));
  }
  fence_async();
  CBAR_SYNC(NB_PRO, 384);
}
template <int STRIDE>
__device__ __forceinline__ void store_mem(const float (&d)[8], uint32_t base, int tid) {
  const int m = (tid >> 3) & 3;
  stsm4(base + (((tid >> 5) & 3) * 2 + (m & 1)) * STRIDE + (m >> 1) * 640 + (tid & 7) * 16, pack_bf16(d[0], d[1]), pack_bf16(d[2], d[3]),
        pack_bf16(d[4], d[5]), pack_bf16(d[6], d[7]));
}

__device__ __forceinline__ void load_pair(uint32_t sb, int i, int p, uint32_t slot, uint32_t bar, uint32_t ph, int& spin) {
  using namespace C;
  const uint8_t* s0 = g_xn[0] + (size_t)i * 40960 + p * 8192;
  const uint8_t* s1 = g_xn[NOWORK ? 0 : 1] + (size_t)(i - LAG) * 40960 + p * 8192;
  const uint8_t* sa = pinp(i < NSEG ? s0 : s1);
  const uint8_t* sc = pinp(i >= LAG ? s1 : s0);
  const uint32_t dst = pin(sb + slot), fb = pin(sb + BAR_F + 8 * p);
  mwait(bar, ph, spin);
  bulk_g2s_mc(dst, sa, 8192, fb);
  bulk_g2s_mc(dst + 8192, sc, 8192, fb);
}
__device__ __forceinline__ void first_fill(uint32_t sb, int i, int rank, int& spin) {
  using namespace C;
  const int s1 = i - LAG;
  if (!NOWORK && s1 >= 0 && (s1 & 3) == 0) {
    while (ld_acquire(cnt_ptr(CN_X, 0, s1 >> 2)) < 5 && spin < SPIN_TOT) spin += 16;
    fence_async_all();
  }
  load_pair(sb, i, rank, rank == 2 ? OFF_M : OFF_KT + rank * 16384, sb + BAR_E + 8 * rank, (i - 1) & 1, spin);
}
__device__ __forceinline__ void release_round(uint32_t sb, int p, int tid) {
  using namespace C;
  const int lane = tid & 31;
  if (p < 2) { if (lane == 0) mbar_arrive_cluster(mapa(sb, p) + BAR_E + 8 * (3 + p)); }
  else if (lane < 3) mbar_arrive_cluster(mapa(sb, lane) + BAR_MOK);
}

template <int K0, int K1>
__device__ __forceinline__ void v_mem_pass(float (&d)[8], const uint32_t (&wf)[C::NKR][4]) {
  using namespace C;
  wg_fence();
#pragma unroll
  for (int k = K0; k < K1; k++) {
    if (k < NKR) wgmma_rs16(d, wf[k < NKR ? k : 0], mdesc(k), k);
    else wgmma_ts16(d, wdesc(OFF_YV + (k - NKR) * 2048), mdesc(k), 1);
  }
  wg_commit();
}
__device__ __forceinline__ void chain_v(const uint32_t sb, const int tid0, const int cta, const int rank) {
  using namespace C;
  asm volatile("setmaxnreg.inc.sync.aligned.u32 208;");
  int spin = 0;
  uint32_t wf[NKR][4];
  if (tid0 == 256) first_fill(sb, 0, rank, spin);
  __syncwarp();
  mwait(sb + BAR_W, 0, spin);
  for (int it = tid0 & 127; it < 1280; it += 128) {
    const uint32_t base = sb + OFF_WK + (it >> 1) * 128;
    const int sw = ((it >> 1) & 7) ^ ((it & 1) * 4);
    const uint4 u0 = lds128(base + (sw << 4)), u1 = lds128(base + ((sw ^ 1) << 4)), u2 = lds128(base + ((sw ^ 2) << 4)), u3 = lds128(base + ((sw ^ 3) << 4));
    sts128(base + (sw << 4), make_uint4(u0.x, u1.x, u2.x, u3.x)); sts128(base + ((sw ^ 1) << 4), make_uint4(u0.y, u1.y, u2.y, u3.y));
    sts128(base + ((sw ^ 2) << 4), make_uint4(u0.z, u1.z, u2.z, u3.z)); sts128(base + ((sw ^ 3) << 4), make_uint4(u0.w, u1.w, u2.w, u3.w));
  }
  bar_sync(NB_RD, 128);
  load_weights_rs<false>(wf, sb, OFF_WK, OFF_YV, tid0);
#pragma unroll 1
  for (int i = 0; i < NSTEP; i++) {
    {
      float d[32];
      if (i > 0) CBAR_SYNC(NB_WV, 256);
#pragma unroll
      for (int p = 0; p < 5; p++) {
        mwait(sb + BAR_F + 8 * p, i & 1, spin);
        TS(i, 25 + p);
        wg_fence();
#pragma unroll
        for (int k = 8 * p; k < 8 * p + 8; k++) {
          if (k < NKR) wgmma_rs64(d, wf[k < NKR ? k : 0], tdesc(k), k);
          else wgmma_ts64(d, wdesc(OFF_YV + (k - NKR) * 2048), tdesc(k), 1);
          if (k == 8 * p + 1 && p >= 1 && p <= 3) {
            wg_commit(); wg_wait<1>();
            release_round(sb, p - 1, fresh(tid0));
            wg_fence();
          }
          if (k == 8 * p + RFK && (p == 1 || p == 2)) {
            wg_commit();
            if (rank == p - 1 && tid0 == 256) load_pair(sb, i, p + 2, slot_off(p + 2), sb + BAR_E + 8 * (p + 2), i & 1, spin);
            __syncwarp();
            wg_fence();
          }
        }
        wg_commit();
      }
      wg_wait<0>();
      TS(i, 23);
      CBAR_SYNC(NB_RD, 256);
      const int tid = fresh(tid0) & 127, m = (tid >> 3) & 3;
      if (tid >= 96) {
        if (tid < 101) { if (i + 1 < NSTEP) mbar_expect_tx(sb + BAR_F + 8 * (tid - 96), 16384); }
        else if (tid == 101) mbar_expect_tx(sb + BAR_XM, 2560);
        else if (tid == 102) mbar_expect_tx(sb + BAR_XT, 7168);
        else if (tid == 103) mbar_expect_tx(sb + BAR_OG, 4096);
        else if (tid < 106) mbar_arrive_cluster(mapa(sb, (rank + tid - 103) % 3) + BAR_XF);
        __syncwarp();
      }
      const uint32_t a = sb + OFF_VT + 256 + ((tid >> 5) * 2 + (m & 1)) * VS + (m >> 1) * 128 + (tid & 7) * 16;
#pragma unroll
      for (int s = 0; s < 4; s++)
        stsm4(a + (s & 1) * 256 + (s >> 1) * 640, pack_bf16(d[8 * s], d[8 * s + 1]), pack_bf16(d[8 * s + 2], d[8 * s + 3]),
              pack_bf16(d[8 * s + 4], d[8 * s + 5]), pack_bf16(d[8 * s + 6], d[8 * s + 7]));
      if (tid < 72) sts128(sb + OFF_VT + (tid >> 3) * VS + (tid & 7) * 16, make_uint4(0, 0, 0, 0));
      fence_async();
    }
    CBAR_ARRIVE(NB_QK, 384);
    CBAR_SYNC(NB_QI, 256);
    float d[8];
    v_mem_pass<0, VSP>(d, wf);
    CBAR_SYNC(NB_SM, 256);
    v_mem_pass<VSP, 40>(d, wf);
    wg_wait<0>();
    TS(i, 24);
    const int tid = fresh(tid0);
    if ((tid & 31) < 3) mbar_arrive_cluster((tid & 2) ? mapa(sb, 2) + BAR_E + 16 : mapa(sb, (rank + 1 + (tid & 1)) % 3) + BAR_MF);
    store_mem<VS>(d, sb + OFF_VT + 128, tid);
    fence_async();
    CBAR_ARRIVE(NB_VA, 256);
    CBAR_ARRIVE(NB_VQ, 256);
    if (tid == 256) {
      if (i + 1 < NSTEP) { first_fill(sb, i + 1, rank, spin); TS1(i + 1, 37); }
    } else if (tid >= 288 && tid < 294) {
      const int lane = tid & 31, ip = i + PFD;
      if (cta < 80 && ip < NSTEP) {
        if (lane < 2) prefetch_l2(g_mbuf[ip] + (cta * 2 + lane) * 128);
        else if (ip < NSEG) prefetch_l2(g_xn[0] + (size_t)ip * 40960 + (cta * 4 + lane - 2) * 128);
      }
    }
    TS_FLUSH(i - 1);
    __syncwarp();
  }
  if (spin >= SPIN_TOT) g_err = 3;
}

__device__ __forceinline__ float quad_max(float x) {
  const float a = __shfl_xor_sync(0xffffffffu, x, 1), b = __shfl_xor_sync(0xffffffffu, x, 2), c = __shfl_xor_sync(0xffffffffu, x, 3);
  return fmaxf(fmaxf(x, a), fmaxf(b, c));
}
__device__ __forceinline__ float quad_sum(float x) {
  const float a = __shfl_xor_sync(0xffffffffu, x, 1), b = __shfl_xor_sync(0xffffffffu, x, 2), c = __shfl_xor_sync(0xffffffffu, x, 3);
  return (x + a) + (b + c);
}
__device__ __forceinline__ float max10(const float (&y)[10]) {
  return fmaxf(fmaxf(fmaxf(fmaxf(y[0], y[1]), fmaxf(y[2], y[3])), fmaxf(fmaxf(y[4], y[5]), fmaxf(y[6], y[7]))), fmaxf(y[8], y[9]));
}
__device__ __forceinline__ float sum10(const float (&y)[10]) {
  return (((y[0] + y[1]) + (y[2] + y[3])) + ((y[4] + y[5]) + (y[6] + y[7]))) + (y[8] + y[9]);
}
__device__ __forceinline__ float rcp(float x) { float y; asm("rcp.approx.ftz.f32 %0,%1;" : "=f"(y) : "f"(x)); return y; }

__device__ __forceinline__ void signal_o(int i) {
  const int s1 = i - LAG;
  if (i < NSEG && (i & 3) == 3) cnt_signal(CN_O, 0, i >> 2);
  if (s1 >= 0 && (s1 & 3) == 3) cnt_signal(CN_O, 1, s1 >> 2);
}

__device__ __forceinline__ void chain_q(const CUtensorMap& tmWq, const CUtensorMap& tmWk, const uint32_t sb, const int tid0, const int cta, const int rank) {
  using namespace C;
  asm volatile("setmaxnreg.dec.sync.aligned.u32 96;");
  int spin = 0;
  CBAR_SYNC(NB_PRO, 384);
  PTS(5);
  if (tid0 == 128) {
    const int col = (cta / 3) * DH + rank * 64;
    mbar_expect_tx(sb + BAR_W, 163840);
    for (int i = 0; i < 5; i++) {
      tma2d(sb + OFF_WQ + i * 16384, &tmWq, col, i * 128, sb + BAR_W);
      tma2d(sb + OFF_WK + i * 16384, &tmWk, col, i * 128, sb + BAR_W);
    }
  }
  mwait(sb + BAR_W, 1, spin);
  PTS(6);
#pragma unroll 1
  for (int i = 0; i < NSTEP; i++) {
    const int ph = i & 1;
    uint32_t qf[4][4];
    {
      float d[64];
      if (i > 0) CBAR_SYNC(NB_WQ, 256);
#pragma unroll
      for (int p = 0; p < 5; p++) {
        mwait(sb + BAR_F + 8 * p, ph, spin);
        if (p == 0) TS(i, 0);
        wg_fence();
#pragma unroll
        for (int k = 8 * p; k < 8 * p + 8; k++) {
          wgmma_st128(d, tdesc(k), mkdesc(SB0 + OFF_WQ + k * 2048, OFF_WK - OFF_WQ, 1024), k);
          if (k == 8 * p + 1 && p >= 1 && p <= 3) {
            wg_commit(); wg_wait<1>();
            release_round(sb, p - 1, fresh(tid0));
            wg_fence();
          }
        }
        wg_commit();
      }
      wg_wait<0>();
      TS(i, 1);
      CBAR_SYNC(NB_RD, 256);
      TSB(i, 2);
      const int tid = fresh(tid0), w = (tid >> 5) & 3, m = (tid >> 3) & 3;
      const uint32_t a = sb + OFF_KT + (m >> 1) * KS + (1 + 5 * (w >> 1) + 2 * (w & 1) + (m & 1)) * 128 + (tid & 7) * 16;
#pragma unroll
      for (int s = 0; s < 4; s++)
        stsm4t(a + s * 2 * KS, pack_bf16(d[32 + 8 * s], d[33 + 8 * s]), pack_bf16(d[34 + 8 * s], d[35 + 8 * s]),
               pack_bf16(d[36 + 8 * s], d[37 + 8 * s]), pack_bf16(d[38 + 8 * s], d[39 + 8 * s]));
      fence_async();
      CBAR_ARRIVE(NB_QK, 384);
#pragma unroll
      for (int kk = 0; kk < 4; kk++)
#pragma unroll
        for (int j = 0; j < 4; j++) asm volatile("cvt.rn.bf16x2.f32 %0,%1,%2;" : "=r"(qf[kk][j]) : "f"(d[8 * kk + 2 * j + 1]), "f"(d[8 * kk + 2 * j]));
    }
    CBAR_SYNC(NB_SI, 256);
    uint32_t pf[5][4];
    float s0, s1;
    {
      float y0[10], y1[10];
      const int tid = fresh(tid0), lane = tid & 31, u = (tid >> 5) & 1;
      const bool c1 = tid & 64;
      {
        float x[40];
        wg_fence();
#pragma unroll
        for (int kk = 0; kk < 4; kk++) wgmma_rt80(x, qf[kk], mkdesc_ns(SB0 + OFF_KT + kk * 2 * KS, KS, 128), kk);
        wg_commit();
        mwait(sb + BAR_XF, ph, spin);
        wg_wait<0>();
#pragma unroll
        for (int j = 0; j < 5; j++) {
          y0[2 * j] = (c1 ? x[20 + 4 * j] : x[4 * j]) * SCL; y0[2 * j + 1] = (c1 ? x[21 + 4 * j] : x[4 * j + 1]) * SCL;
          y1[2 * j] = (c1 ? x[22 + 4 * j] : x[4 * j + 2]) * SCL; y1[2 * j + 1] = (c1 ? x[23 + 4 * j] : x[4 * j + 3]) * SCL;
        }
      }
      TS(i, 17);
      const uint32_t xo = OFF_XT + (c1 ? 1792 : 0) + u * 640 + lane * 16, x2 = xo + u * 512 + 512 - lane * 12;
      {
        const uint4 h0 = make_uint4(pack_h2(y0[0], y0[1]), pack_h2(y0[2], y0[3]), pack_h2(y1[0], y1[1]), pack_h2(y1[2], y1[3]));
        const uint4 h1 = make_uint4(pack_h2(y0[4], y0[5]), pack_h2(y0[6], y0[7]), pack_h2(y1[4], y1[5]), pack_h2(y1[6], y1[7]));
        const uint32_t h2 = u ? pack_h2(y1[8], y1[9]) : h1.z;
#pragma unroll
        for (int dd = 0; dd < 2; dd++) {
          const uint32_t rb = mapa(sb, (rank + 1 + dd) % 3), ro = rb + (1 - dd) * 3584;
          st_async4u(ro + xo, h0, rb + BAR_XT);
          if (u) st_async4u(ro + xo + 512, h1, rb + BAR_XT);
          st_async1u(ro + x2, h2, rb + BAR_XT);
        }
      }
      TS(i, 18);
      const int lim = 16 * u + (lane >> 2) + 8 - 2 * (lane & 3);
#pragma unroll
      for (int j = 1; j < 5; j++) {
        if (8 * j > lim) y0[2 * j] = -INFINITY;
        if (8 * j + 1 > lim) y0[2 * j + 1] = -INFINITY;
        if (8 * j - 8 > lim) y1[2 * j] = -INFINITY;
        if (8 * j - 7 > lim) y1[2 * j + 1] = -INFINITY;
      }
      mwait(sb + BAR_XT, ph, spin);
      TS(i, 19);
      {
        const uint4 u0 = lds128(sb + xo), v0 = lds128(sb + xo + 3584);
        const uint32_t u2 = lds32(sb + x2), v2 = lds32(sb + x2 + 3584);
        uint4 u1 = make_uint4(0, 0, u2, 0), v1 = make_uint4(0, 0, v2, 0);
        if (u) { u1 = lds128(sb + xo + 512); v1 = lds128(sb + xo + 512 + 3584); }
        __syncwarp();
        if (lane == 0) mbar_arrive_cluster(mapa(sb, 0) + BAR_E);
        add_h2(y0[0], y0[1], u0.x, v0.x); add_h2(y0[2], y0[3], u0.y, v0.y); add_h2(y1[0], y1[1], u0.z, v0.z); add_h2(y1[2], y1[3], u0.w, v0.w);
        add_h2(y0[4], y0[5], u1.x, v1.x); add_h2(y0[6], y0[7], u1.y, v1.y); add_h2(y1[4], y1[5], u1.z, v1.z); add_h2(y1[6], y1[7], u1.w, v1.w);
        add_h2(y1[8], y1[9], u2, v2);
      }
      y0[8] = y0[0]; y0[9] = y0[1];
      const float m0 = quad_max(max10(y0)) * -256.f, m1 = quad_max(max10(y1)) * -256.f;
      s0 = 0.f; s1 = 0.f;
#pragma unroll
      for (int j = 0; j < 5; j++) {
        const uint32_t p0 = j < 4 ? pack_bf16(ex2(fmaf(y0[2 * j], 256.f, m0)), ex2(fmaf(y0[2 * j + 1], 256.f, m0))) : 0u;
        const uint32_t p1 = pack_bf16(ex2(fmaf(y1[2 * j], 256.f, m1)), ex2(fmaf(y1[2 * j + 1], 256.f, m1)));
        s0 += bf_lo(p0) + bf_hi(p0); s1 += bf_lo(p1) + bf_hi(p1);
        pf[j >> 1][2 * (j & 1)] = c1 ? 0u : p0; pf[j >> 1][2 * (j & 1) + 1] = c1 ? 0u : p1;
        pf[(j + 5) >> 1][2 * ((j + 5) & 1)] = c1 ? p0 : 0u; pf[(j + 5) >> 1][2 * ((j + 5) & 1) + 1] = c1 ? p1 : 0u;
      }
    }
    CBAR_SYNC(NB_VQ, 256);
    TSB(i, 20);
    {
      float o[32];
      wg_fence();
#pragma unroll
      for (int q = 0; q < 5; q++) wgmma_rs64(o, pf[q], mkdesc_ns(SB0 + OFF_VT + 128 + q * 256, 128, VS), q);
      wg_commit();
      s0 = rcp(quad_sum(s0)); s1 = rcp(quad_sum(s1));
      const int tid = fresh(tid0), g = (tid >> 2) & 7, c = (tid >> 6) & 1, sg = i - c * LAG;
      uint8_t* op = pinp(g_o[c] + ((size_t)(sg >> 1) * 96 + cta) * 8192 + (sg & 1) * 4096 + (((tid >> 5) & 1) * 16 + g) * 128);
      const uint32_t o0 = pin(((tid & 3) ^ g) << 4), live = pin(sg >= 0 && sg < NSEG);
      wg_wait<0>();
      TS(i, 21);
      if ((tid & 31) == 0) mbar_arrive_cluster(mapa(sb, 1) + BAR_E + 8);
      if (live) {
#pragma unroll
        for (int h = 0; h < 2; h++) {
          const float* x = o + 16 * h;
          *reinterpret_cast<uint4*>(op + (o0 ^ (h * 64))) =
              make_uint4(pack_bf16(x[0] * s0, x[1] * s0), pack_bf16(x[4] * s0, x[5] * s0), pack_bf16(x[8] * s0, x[9] * s0), pack_bf16(x[12] * s0, x[13] * s0));
          *reinterpret_cast<uint4*>(op + 1024 + (o0 ^ (h * 64))) =
              make_uint4(pack_bf16(x[2] * s1, x[3] * s1), pack_bf16(x[6] * s1, x[7] * s1), pack_bf16(x[10] * s1, x[11] * s1), pack_bf16(x[14] * s1, x[15] * s1));
        }
      }
      CBAR_ARRIVE(NB_Q, 160);
      TS(i, 22);
    }
  }
  if (spin >= SPIN_TOT) g_err = 2;
}

template <int NL>
__device__ __forceinline__ void poll_add(const uint8_t* mb, uint32_t tag, float (&f)[8], int& n, int& spin) {
  uint4 x[NL];
#pragma unroll
  for (int i = 0; i < NL; i++) x[i] = ld_relaxed128(mb + i * 512);
  while (true) {
    bool bad = false;
#pragma unroll
    for (int i = 0; i < NL; i++)
      if (((x[i].x ^ tag) | (NL == 6 ? x[i].z ^ tag : 0u)) & 1) { bad = true; x[i] = ld_relaxed128(mb + i * 512); }
    n++;
    spin += 16;
    if (!__any_sync(0xffffffffu, bad && spin < SPIN_TOT)) break;
  }
#pragma unroll
  for (int i = 0; i < NL; i++) {
    const uint32_t u[4] = {x[i].x, x[i].y, x[i].z, x[i].w};
#pragma unroll
    for (int j = 0; j < 4; j++) {
      if (i == 0) { f[2 * j] = bf_lo(u[j]); f[2 * j + 1] = bf_hi(u[j]); }
      else { f[2 * j] += bf_lo(u[j]); f[2 * j + 1] += bf_hi(u[j]); }
    }
  }
}

template <int B, int SLOT>
__device__ __forceinline__ void wo_block(float (&acc)[8], const uint32_t (&wf)[C::NKR][4]) {
  using namespace C;
#pragma unroll
  for (int kk = 0; kk < 4; kk++) {
    const int k = 4 * B + kk;
    const uint64_t db = mkdesc_ns(SB0 + og_off(SLOT) + kk * 512, 256, 128);
    if (k < NKR) wgmma_rt16(acc, wf[k < NKR ? k : 0], db, SLOT | kk);
    else wgmma_tt16(acc, wdesc(OFF_YO + (k - NKR) * 2048), db, 1);
  }
}

__device__ __forceinline__ void chain_a(const uint32_t sb, const int tid0, const int cta, const int rank) {
  using namespace C;
  asm volatile("setmaxnreg.inc.sync.aligned.u32 200;");
  int spin = 0;
  uint32_t wf[NKR][4];
  mwait(sb + BAR_W, 0, spin);
  for (int it = tid0; it < 2560; it += 128) {
    const int row = it >> 2, q = it & 3;
    const uint32_t base = sb + OFF_WQ + row * 128;
    const uint32_t a0 = base + (((2 * q) ^ (row & 7)) << 4), a1 = base + (((2 * q + 1) ^ (row & 7)) << 4);
    const uint4 u = lds128(a0), v = lds128(a1);
    sts128(a0, make_uint4(__byte_perm(u.x, u.y, 0x5410), __byte_perm(u.z, u.w, 0x5410), __byte_perm(v.x, v.y, 0x5410), __byte_perm(v.z, v.w, 0x5410)));
    sts128(a1, make_uint4(__byte_perm(u.x, u.y, 0x7632), __byte_perm(u.z, u.w, 0x7632), __byte_perm(v.x, v.y, 0x7632), __byte_perm(v.z, v.w, 0x7632)));
  }
  CBAR_SYNC(NB_A, 128);
  load_weights_rs<true>(wf, sb, OFF_WQ, OFF_YO, tid0);

#pragma unroll 1
  for (int i = -1; i < NSTEP; i++) {
    const int ph = i & 1;
    if (i >= 0) {
      if (i == 0) mwait(sb + BAR_W, 1, spin);
      mwait(sb + BAR_M, ph, spin);
      TS(i, 3);
      {
        float dq[8], dk[8];
        int redo = 0;
#pragma unroll 1
        while (true) {
          wg_fence();
#pragma unroll
          for (int k = 0; k < 40; k++) wgmma_ts16(dq, wdesc(OFF_WQ + k * 2048), mdesc(k), k);
          wg_commit();
#pragma unroll
          for (int k = 0; k < 40; k++) wgmma_ts16(dk, wdesc(OFF_WK + k * 2048), mdesc(k), k);
          wg_commit();
          wg_wait<1>();
          const float chk = (dq[0] + dq[1]) + (dq[4] + dq[5]);
          if (!bar_red_or(NB_C, 128, chk != chk && !redo)) break;
          wg_wait<0>();
          const int tid = fresh(tid0);
#pragma unroll 1
          for (int k = 0; k < 10; k++) {
            uint4 v = lds128(sb + OFF_M + tid * 16 + k * 2048);
            if (v.x == SENT || v.y == SENT || v.z == SENT || v.w == SENT) {
              do { v = ld_relaxed4(g_mbuf[i] + tid * 16 + k * 2048); spin += 16; } while ((v.x == SENT || v.y == SENT || v.z == SENT || v.w == SENT) && spin < SPIN_TOT);
              sts128(sb + OFF_M + tid * 16 + k * 2048, v);
            }
          }
          fence_async();
          bar_sync(NB_C, 128);
          redo = fresh(1);
        }
        CBAR_ARRIVE(NB_QI, 256);
        CBAR_SYNC(NB_QK, 384);
        TSV(i, 36, redo);
        const int tid = fresh(tid0), m = (tid >> 3) & 3;
        const uint32_t ka = pin(sb + OFF_KT + ((tid >> 5) * 2 + (m & 1)) * KS + (m >> 1) * 640 + (tid & 7) * 16);
        store_mem<VS>(dq, sb + OFF_VT + 128, tid);
        wg_wait<0>();
        TS(i, 4);
        stsm4(ka, pack_bf16(dk[0], dk[1]), pack_bf16(dk[2], dk[3]), pack_bf16(dk[4], dk[5]), pack_bf16(dk[6], dk[7]));
        fence_async();
      }
      CBAR_SYNC(NB_A, 128);
      TSB(i, 5);
      {
        float x[20];
        wg_fence();
#pragma unroll
        for (int kk = 0; kk < 4; kk++) wgmma_tt40(x, mkdesc_ns(SB0 + OFF_VT + 128 + kk * 2 * VS, VS, 640), mkdesc_ns(SB0 + OFF_KT + kk * 2 * KS, KS, 128), kk);
#pragma unroll
        for (int kk = 0; kk < 4; kk++) wgmma_tt40(x, mkdesc_ns(SB0 + OFF_VT + kk * 2 * VS, VS, 384), mkdesc_ns(SB0 + OFF_KT + 640 + kk * 2 * KS, KS, 128), 1);
        wg_commit();
        CBAR_ARRIVE(NB_SI, 256);
        const int tid = fresh(tid0), lane = tid & 31, w = tid >> 5;
        const uint32_t xo = OFF_XM + w * 1280 + lane * 16, x1 = OFF_XM + w * 1280 + lane * 4;
        const uint32_t rb1 = mapa(sb, (rank + 1) % 3), rb2 = mapa(sb, (rank + 2) % 3);
        const uint32_t ra = pin(rb1 + xo + 640), rb = pin(rb1 + x1 + 1152), rc = pin(rb2 + xo), rd = pin(rb2 + x1 + 512);
        const uint32_t la = pin(sb + xo), lb = pin(sb + x1);
        const uint32_t pa = pin(sb + OFF_XM + w * 1280 + (lane & 7) * 4 + (lane & 8) * 8 + (lane & 16) * 2);
        mwait(sb + BAR_XF, ph, spin);
        wg_wait<0>();
        TS(i, 6);
        if (w < 2) {
          float y[10];
#pragma unroll
          for (int j = 0; j < 5; j++) { y[2 * j] = x[4 * j] * SCL; y[2 * j + 1] = x[4 * j + 1] * SCL; }
          const uint4 h0 = make_uint4(pack_h2(y[0], y[1]), pack_h2(y[2], y[3]), pack_h2(y[4], y[5]), pack_h2(y[6], y[7]));
          const uint32_t h1 = pack_h2(y[8], y[9]);
          st_async4u(ra, h0, rb1 + BAR_XM);
          st_async4u(rc, h0, rb2 + BAR_XM);
          st_async1u(rb, h1, rb1 + BAR_XM);
          st_async1u(rd, h1, rb2 + BAR_XM);
          CBAR_ARRIVE(NB_SM, 256);
          if (lane == 0) mbar_arrive_cluster(mapa(sb, 0) + BAR_E);
          TS(i, 7);
          mwait(sb + BAR_XM, ph, spin);
          TS(i, 8);
          const uint4 u0 = lds128(la), v0 = lds128(la + 640);
          const uint32_t u1 = lds32(lb + 512), v1 = lds32(lb + 1152);
          add_h2(y[0], y[1], u0.x, v0.x); add_h2(y[2], y[3], u0.y, v0.y); add_h2(y[4], y[5], u0.z, v0.z); add_h2(y[6], y[7], u0.w, v0.w);
          add_h2(y[8], y[9], u1, v1);
          const float mx = quad_max(max10(y)) * -256.f;
          sts32(pa + 640, 0);
#pragma unroll
          for (int j = 0; j < 5; j++) {
            y[2 * j] = ex2(fmaf(y[2 * j], 256.f, mx)); y[2 * j + 1] = ex2(fmaf(y[2 * j + 1], 256.f, mx));
            sts32(pa + j * 128, pack_bf16(y[2 * j], y[2 * j + 1]));
          }
          sts32(pa + 768, __float_as_uint(sum10(y)));
          fence_async();
          TS(i, 9);
        } else {
          CBAR_ARRIVE(NB_SM, 256);
          if (lane == 0) mbar_arrive_cluster(mapa(sb, 0) + BAR_E);
        }
      }
      CBAR_SYNC(NB_VA, 256);
      TSB(i, 10);
      {
        float o[2][4];
        wg_fence();
#pragma unroll
        for (int c = 0; c < 2; c++)
#pragma unroll
          for (int q = 0; q < 3; q++)
            wgmma_ss8(o[c], mkdesc_ns(SB0 + OFF_VT + 128 + c * 640 + q * 256, 128, VS), mkdesc_ns(SB0 + OFF_XM + c * 1280 + q * 256, 128, 128), q);
        wg_commit();
        const int tid = fresh(tid0);
        const float4 e = lds128f(sb + OFF_XM + 768 + (tid & 3) * 32 + (tid & 4) * 4 + (tid & 8) * 160);
        const uint32_t oo = (tid >> 5) * 512 + (tid & 2) * 64 + ((tid & 31) >> 2) * 16 + (tid & 1) * 8;
        const uint32_t rb1 = mapa(sb, (rank + 1) % 3), rb2 = mapa(sb, (rank + 2) % 3);
        const uint32_t ra = pin(rb1 + oo + og_off(2)), rc = pin(rb2 + oo + og_off(1)), la = pin(sb + oo + og_off(0));
        const float inv = rcp((e.x + e.y) + (e.z + e.w));
        const float i0 = __shfl_sync(0xffffffffu, inv, tid & 3), i1 = __shfl_sync(0xffffffffu, inv, (tid & 3) + 4);
        const float i2 = __shfl_sync(0xffffffffu, inv, (tid & 3) + 8), i3 = __shfl_sync(0xffffffffu, inv, (tid & 3) + 12);
        mwait(sb + BAR_MF, ph, spin);
        wg_wait<0>();
        TS(i, 11);
        const uint32_t p0 = pack_bf16(o[0][0] * i0, o[0][1] * i1), p1 = pack_bf16(o[1][0] * i2, o[1][1] * i3);
        const uint32_t p2 = pack_bf16(o[0][2] * i0, o[0][3] * i1), p3 = pack_bf16(o[1][2] * i2, o[1][3] * i3);
        if (OGF) { sts64(la, p0, p1); sts64(la + 256, p2, p3); fence_async(); }
        st_async2u(ra, p0, p1, rb1 + BAR_OG);
        st_async2u(rc, p0, p1, rb2 + BAR_OG);
        st_async2u(ra + 256, p2, p3, rb1 + BAR_OG);
        st_async2u(rc + 256, p2, p3, rb2 + BAR_OG);
        if (!OGF) { sts64(la, p0, p1); sts64(la + 256, p2, p3); fence_async(); }
      }
      if (i + 1 >= NSTEP) {
        if (tid0 >= 96) { CBAR_SYNC(NB_Q, 160); if (tid0 == 96) signal_o(i); }
        mwait(sb + BAR_OG, ph, spin);
        break;
      }
      CBAR_SYNC(NB_A, 128);
      TSB(i, 12);
      {
        float acc[3][8];
        wg_fence();
        wo_block<0, 0>(acc[2], wf);
        wg_commit();
        wo_block<1, 0>(acc[0], wf);
        wo_block<4, 0>(acc[1], wf);
        wg_commit();
        const int tid = fresh(tid0), w = tid >> 5, g = (tid & 31) >> 2, t = tid & 3;
        if ((tid & 31) == 0) mbar_arrive_cluster(mapa(sb, 1) + BAR_E + 8);
        const uint32_t tag = (i >> 1) & 1, radd = tag ? 0u : 0x10000u;
#define TAGGED(LO, HI) __byte_perm(((__float_as_uint(LO) + radd) & 0xFFFE0000u) | (tag << 16), pack_bf16(0.f, HI), 0x7632)
#define SEND(PTR, U) st_relaxed128((PTR), TAGGED(acc[U][0], acc[U][2]), pack_bf16(acc[U][1], acc[U][3]), pack_bf16(acc[U][4], acc[U][6]), pack_bf16(acc[U][5], acc[U][7]))
        uint8_t* m9 = pinp(g_mail[ph] + MAIL9 + (((2 * w + (g >> 2)) * 2 + (t & 1)) * 4 + (t & 2)) * 3072 + cta * 32 + (g & 3) * 8);
        wg_wait<1>();
        const uint32_t n0 = pin(TAGGED(acc[2][0], acc[2][2])), n1 = pin(pack_bf16(acc[2][1], acc[2][3]));
        const uint32_t n2 = pin(TAGGED(acc[2][4], acc[2][6])), n3 = pin(pack_bf16(acc[2][5], acc[2][7]));
        wg_fence();
        wo_block<7, 0>(acc[2], wf);
        wg_commit();
        uint8_t* mb = pinp(g_mail[ph] + (((rank * 12 + w) * 2 + (g >> 2)) * 4 + t) * 2048 + (cta / 3) * 64 + (g & 3) * 16);
        mwait(sb + BAR_OG, ph, spin);
        fence_async();
        TS(i, 13);
        wg_fence();
        wo_block<2, 1>(acc[0], wf); wo_block<3, 2>(acc[0], wf);
        wg_commit();
        st_relaxed64(m9, n0, n1);
        st_relaxed64(m9 + 3072, n2, n3);
        wo_block<5, 1>(acc[1], wf); wo_block<6, 2>(acc[1], wf);
        wg_commit();
        wg_wait<1>(); SEND(mb, 0);
        wg_fence();
        wo_block<8, 1>(acc[2], wf); wo_block<9, 2>(acc[2], wf);
        wg_commit();
        CBAR_ARRIVE(NB_WQ, 256);
        CBAR_ARRIVE(NB_WV, 256);
        wg_wait<1>(); SEND(mb + 32 * 2048, 1);
        wg_wait<0>(); SEND(mb + 64 * 2048, 2);
#undef SEND
#undef TAGGED
      }
      TS(i, 14);
    }
    const uint32_t t0 = clk32();
    if (i >= 0) {
      const int tid = fresh(tid0), lane = tid & 31;
      const uint32_t tag = (i >> 1) & 1;
      const bool t9 = cta >= 72 && cta < 88;
      const int w = tid >> 5, j = lane >> 3;
      const uint32_t pub = pin((lane & (t9 ? 6 : 4)) == 0 && !(((t9 ? cta : w) & 1) && i + 1 == LAG) && cta < 88);
      uint8_t* dst = pinp(g_mbuf[i + 1] + (t9 ? (cta + 72) * 128 + w * 32 + (j & 1) * 16 + (lane & 1) * 8 + (j >> 1) * 4
                                               : cta * 256 + (w & 1) * 128 + (w >> 1) * 64 + j * 16 + (lane & 3) * 4));
      float f[8];
      int n = 0;
      while (clk32() - t0 < B1) {}
      TS(i + 1, 30);
      if (!t9) poll_add<4>(g_mail[ph] + (cta < 72 ? cta : cta - 24) * 8192 + (tid >> 5) * 2048 + lane * 16, tag, f, n, spin);
      else poll_add<6>(g_mail[ph] + MAIL9 + (cta - 72) * 12288 + (tid >> 5) * 3072 + lane * 16, tag, f, n, spin);
      TS(i + 1, 31); TSV(i + 1, 32, n);
      const bool h = lane & 16, q = lane & 8;
#pragma unroll
      for (int j = 0; j < 4; j++) f[j] = (h ? f[4 + j] : f[j]) + __shfl_xor_sync(0xffffffffu, h ? f[j] : f[4 + j], 16);
#pragma unroll
      for (int j = 0; j < 2; j++) f[j] = (q ? f[2 + j] : f[j]) + __shfl_xor_sync(0xffffffffu, q ? f[j] : f[2 + j], 8);
      f[0] += __shfl_xor_sync(0xffffffffu, f[0], 4); f[1] += __shfl_xor_sync(0xffffffffu, f[1], 4);
      if (t9) { f[0] += __shfl_xor_sync(0xffffffffu, f[0], 2); f[1] += __shfl_xor_sync(0xffffffffu, f[1], 2); }
      if (pub) st_relaxed(dst, pack_bf16(f[0], f[1]));
      TS(i + 1, 15);
    }
    {
      const uint32_t t1 = clk32();
      const int tid = fresh(tid0);
      const uint8_t* src = g_mbuf[i + 1] + rank * 7168;
      const uint8_t* pp = pinp(src + (rank == 2 && tid >= 64 ? 2048 + tid * 32 : (tid < 112 ? tid : 0) * 64 + 32));
      if (tid == 0) mbar_expect_tx(sb + BAR_M, 20480);
      while (clk32() - t1 < B2) {}
      TS(i + 1, 16);
      int n = 0;
      uint32_t x0;
      do { x0 = ld_relaxed(pp); n++; spin += 16; } while (__any_sync(0xffffffffu, x0 == SENT && spin < SPIN_TOT));
      TSV(i + 1, 35, n);
      if (tid >= 32) {
        CBAR_ARRIVE(NB_MR, 128);
        if (tid >= 96 && i >= 0) { CBAR_SYNC(NB_Q, 160); if (tid == 96) signal_o(i); __syncwarp(); }
      } else {
        CBAR_SYNC(NB_MR, 128);
        TSB(i + 1, 34);
        if (tid == 0) {
          mwait(sb + BAR_MOK, ph ^ 1, spin);
          TS1(i + 1, 33);
          bulk_g2s_mc(sb + OFF_M + rank * 7168, src, rank == 2 ? 6144 : 7168, sb + BAR_M);
        }
        __syncwarp();
      }
    }
  }
  if (spin >= SPIN_TOT) g_err = 1;
}

__global__ void __cluster_dims__(3, 1, 1) __launch_bounds__(384, 1)
k_chain(const __grid_constant__ CUtensorMap tmWq, const __grid_constant__ CUtensorMap tmWk,
        const __grid_constant__ CUtensorMap tmWv, const __grid_constant__ CUtensorMap tmWo) {
  using namespace C;
  extern __shared__ __align__(1024) uint8_t smem[];
  const uint32_t sb = smem_u32(smem);
  const int tid = threadIdx.x;
  const int wg = __shfl_sync(0xffffffffu, tid >> 7, 0);
  const int cta = blockIdx.x, rank = cta % 3;

  asm volatile("griddepcontrol.launch_dependents;");
  if (tid == 0) {
    if ((sb & 0xFFFFFF) != SB0) g_err = 100;
    for (int p = 0; p < 5; p++) { mbar_init(sb + BAR_F + 8 * p, 1); mbar_init(sb + BAR_E + 8 * p, p == 2 ? 12 : 24); }
    mbar_init(sb + BAR_M, 1); mbar_init(sb + BAR_MOK, 24); mbar_init(sb + BAR_XM, 1); mbar_init(sb + BAR_XF, 2);
    mbar_init(sb + BAR_XT, 1); mbar_init(sb + BAR_MF, 8); mbar_init(sb + BAR_OG, 1); mbar_init(sb + BAR_W, 1);
    for (int p = 0; p < 5; p++) mbar_expect_tx(sb + BAR_F + 8 * p, 16384);
    for (int p = 0; p < 16; p++) sts32(sb + OFF_SAFE + 4 * p, 0);
    asm volatile("fence.mbarrier_init.release.cluster;" ::: "memory");
    fence_async();
    mbar_expect_tx(sb + BAR_W, 163840);
    const int head = cta / 3, col = head * DH + rank * 64;
    tma2d(sb + OFF_WQ, &tmWo, 576, col, sb + BAR_W);
    for (int i = 0; i < 9; i++) tma2d(sb + OFF_WQ + (i + 1) * 8192, &tmWo, (3 * rank + i / 3) * 64, head * DH + ((rank + i) % 3) * 64, sb + BAR_W);
    for (int i = 0; i < 5; i++) tma2d(sb + OFF_WK + i * 16384, &tmWv, col, i * 128, sb + BAR_W);
  }
  __syncthreads();
  asm volatile("barrier.cluster.arrive.release.aligned;" ::: "memory");
  asm volatile("barrier.cluster.wait.acquire.aligned;" ::: "memory");

  if (wg == 0) chain_a(sb, tid, cta, rank);
  else if (wg == 1) chain_q(tmWq, tmWk, sb, tid, cta, rank);
  else chain_v(sb, tid, cta, rank);
  asm volatile("barrier.cluster.arrive.release.aligned;" ::: "memory");
  asm volatile("barrier.cluster.wait.acquire.aligned;" ::: "memory");
}

namespace W {
constexpr int NW = 36;
constexpr int NP = 30;
constexpr int OW0 = 31;
constexpr int PST = 3, PSTAGE = 32768;
constexpr int BST = 3, BSTAGE = 16384;
constexpr int OFF_P = 0;
constexpr int OFF_WQ = OFF_P + PST * PSTAGE;
constexpr int OFF_B = OFF_WQ + 81920;
constexpr int OFF_HIST = OFF_B + BST * BSTAGE;
constexpr int OFF_BAR = OFF_HIST + 2 * 14 * 80;
constexpr int SMEM = OFF_BAR + 128;
constexpr int BAR_PF = OFF_BAR, BAR_PE = OFF_BAR + 24, BAR_BF = OFF_BAR + 48, BAR_BE = OFF_BAR + 72;
constexpr int PITCH = 136;
constexpr int NB_P = 1, NB_B = 2;
}

struct WorkArgs {
  const bf16* res[2];
  bf16* xa[2];
  bf16* xb[2];
  const bf16* wqkv;
};

#define OHK 7
#define IMMREL 7
#define FOR_BATCHES(l, b)                                   \
  for (int j_ = 0; j_ < 2 * NSTEP; j_++) {                  \
    const int l = j_ & 1, s_ = (j_ >> 1) - (l ? LAG : 0);   \
    if (s_ < 0 || s_ >= NSEG || (s_ & 3) != 3) continue;    \
    const int b = s_ >> 2;

template <bool IS_O>
__device__ __forceinline__ void work_gemm_producer(const CUtensorMap& tm, const WorkArgs& a, uint32_t sb, int w) {
  using namespace W;
  constexpr int KCH = IS_O ? 10 : 96, NK = IS_O ? 10 : 16;
  int dead = 0, st = 0;
  uint32_t ph = 1;
  const int col = (IS_O ? w - OW0 : w % 5) * 128, k0 = IS_O ? 0 : (w / 5) * 16;
  FOR_BATCHES(l, b)
    const uint8_t* src = (IS_O ? g_ob[l] : g_o[l]) + ((size_t)(2 * b) * KCH + k0) * 8192;
#pragma unroll 1
    for (int kc = 0; kc < NK; kc++) {
      const uint32_t bar = sb + BAR_PF + 8 * st, d = sb + OFF_P + st * PSTAGE;
      mbar_wait(sb + BAR_PE + 8 * st, ph, dead);
      mbar_expect_tx(bar, PSTAGE);
      tma2d(d + 16384, &tm, col, (k0 + kc) * 64, bar);
      tma2d(d + 24576, &tm, col + 64, (k0 + kc) * 64, bar);
      if (kc >= PST) {
        bulk_g2s(d, src + (size_t)kc * 8192, 8192, bar);
        bulk_g2s(d + 8192, src + (size_t)(KCH + kc) * 8192, 8192, bar);
      }
      if (++st == PST) { st = 0; ph ^= 1; }
      if (kc == PST - 1) {
        cnt_wait(IS_O ? CN_A : CN_O, l, b, IS_O ? 32 : 96, dead);
        if (!IS_O && w == 0) WTS(l, b, 0);
        if (IS_O && w == 35) WTS(l, b, 3);
        fence_async_all();
#pragma unroll
        for (int i = 0; i < PST; i++) {
          const int s2 = (st + i) % PST;
          bulk_g2s(sb + OFF_P + s2 * PSTAGE, src + (size_t)i * 8192, 8192, sb + BAR_PF + 8 * s2);
          bulk_g2s(sb + OFF_P + s2 * PSTAGE + 8192, src + (size_t)(KCH + i) * 8192, 8192, sb + BAR_PF + 8 * s2);
        }
      }
    }
  }
}

__device__ __forceinline__ void quad_transpose(uint32_t* x, int t) {
  const bool h = t & 2, o = t & 1;
  uint32_t p = __shfl_xor_sync(0xffffffffu, h ? x[0] : x[2], 2), q = __shfl_xor_sync(0xffffffffu, h ? x[1] : x[3], 2);
  const uint32_t y0 = h ? p : x[0], y1 = h ? q : x[1], y2 = h ? x[2] : p, y3 = h ? x[3] : q;
  p = __shfl_xor_sync(0xffffffffu, o ? y0 : y1, 1); q = __shfl_xor_sync(0xffffffffu, o ? y2 : y3, 1);
  x[0] = o ? p : y0; x[1] = o ? y1 : p; x[2] = o ? q : y2; x[3] = o ? y3 : q;
}

template <bool IS_O>
__device__ __forceinline__ void work_gemm(const WorkArgs& a, uint32_t sb, int w, int tid0) {
  using namespace W;
  constexpr int NK = IS_O ? 10 : 16;
  int dead = 0, st = 0;
  uint32_t ph = 0;
  const int tile = IS_O ? w - OW0 : w % 5;
  bool first = true;
  FOR_BATCHES(l, b)
    float acc[64];
    uint32_t r0[16], r1[16];
    int prev = 0;
    if (IS_O) {
#pragma unroll
      for (int i = 0; i < 64; i++) acc[i] = 0.f;
    }
#pragma unroll 1
    for (int kc = 0; kc < NK; kc++) {
      mbar_wait(sb + BAR_PF + 8 * st, ph, dead);
      if (w == (IS_O ? 35 : WW) && tid0 == 0 && kc == 0) WTS(l, b, IS_O ? 16 : 5);
      const uint32_t pa = sb + OFF_P + st * PSTAGE + (tid0 >> 7) * 8192, pb = sb + OFF_P + st * PSTAGE + 16384;
      wg_fence();
#pragma unroll
      for (int kk = 0; kk < 4; kk++) wgmma_st128(acc, mkdesc(pa + kk * 32, 16, 1024), mkdesc(pb + kk * 2048, 8192, 1024), (kc | kk) != 0);
      wg_commit();
      if (IS_O && OHK >= 0 && kc == OHK) {
      const int tid = fresh(tid0), g = (tid & 31) >> 2, t = tid & 3;
      const bf16* rp = a.xa[l] + (size_t)(b * 128 + (tid >> 5) * 16 + g) * DM + tile * 128 + 8 * t;
#pragma unroll
      for (int m = 0; m < 4; m++) {
        const float4 c0 = ld_relaxed4f(rp + 32 * m), c1 = ld_relaxed4f(rp + 8 * DM + 32 * m);
        r0[4 * m] = __float_as_uint(c0.x); r0[4 * m + 1] = __float_as_uint(c0.y); r0[4 * m + 2] = __float_as_uint(c0.z); r0[4 * m + 3] = __float_as_uint(c0.w);
        r1[4 * m] = __float_as_uint(c1.x); r1[4 * m + 1] = __float_as_uint(c1.y); r1[4 * m + 2] = __float_as_uint(c1.z); r1[4 * m + 3] = __float_as_uint(c1.w);
      }
      }
      if (IMMREL & (IS_O ? 2 : 1)) {
        if (kc < NK - 1) {
          wg_wait<0>();
          if ((tid0 & 127) == 0) mbar_arrive(sb + BAR_PE + 8 * st);
        }
      } else if (kc > 0) {
        wg_wait<1>();
        if ((tid0 & 127) == 0) mbar_arrive(sb + BAR_PE + 8 * prev);
      }
      prev = st;
      if (++st == PST) { st = 0; ph ^= 1; }
    }
    if (IS_O && OHK < 0) {
      const int tid = fresh(tid0), g = (tid & 31) >> 2, t = tid & 3;
      const bf16* rp = a.xa[l] + (size_t)(b * 128 + (tid >> 5) * 16 + g) * DM + tile * 128 + 8 * t;
#pragma unroll
      for (int m = 0; m < 4; m++) {
        const float4 c0 = ld_relaxed4f(rp + 32 * m), c1 = ld_relaxed4f(rp + 8 * DM + 32 * m);
        r0[4 * m] = __float_as_uint(c0.x); r0[4 * m + 1] = __float_as_uint(c0.y); r0[4 * m + 2] = __float_as_uint(c0.z); r0[4 * m + 3] = __float_as_uint(c0.w);
        r1[4 * m] = __float_as_uint(c1.x); r1[4 * m + 1] = __float_as_uint(c1.y); r1[4 * m + 2] = __float_as_uint(c1.z); r1[4 * m + 3] = __float_as_uint(c1.w);
      }
    }
    wg_wait<0>();
    if ((tid0 & 127) == 0) mbar_arrive(sb + BAR_PE + 8 * prev);
    if (w == (IS_O ? 35 : WW) && tid0 == 0) WTS(l, b, IS_O ? 17 : 6);
    if (!IS_O) {
      if (first) {
        if ((tid0 & 31) == 0) cnt_wait(CN_Z, 0, 0, NW, dead);
        __syncwarp();
        first = false;
      }
      const int tid = fresh(tid0);
      float* dst = &g_acc[l][b][tile][0] + (tid >> 5) * 2048 + (tid & 31) * 4;
#pragma unroll
      for (int i = 0; i < 16; i++)
        asm volatile("red.relaxed.gpu.global.add.v4.f32 [%0],{%1,%2,%3,%4};" ::"l"(dst + i * 128), "f"(acc[4 * i]), "f"(acc[4 * i + 1]), "f"(acc[4 * i + 2]), "f"(acc[4 * i + 3]) : "memory");
      if (w == WW && tid0 == 0) WTS(l, b, 7);
      bar_sync(NB_P, 256);
      if (tid0 == 0) cnt_signal(CN_P, l, b);
      if (w == WW && tid0 == 0) WTS(l, b, 8);
    } else {
      const int tid = fresh(tid0), g = (tid & 31) >> 2, t = tid & 3;
      const int rb = (tid >> 5) * 16 + g, R0 = b * 128 + rb;
      float s0 = 0.f, s1 = 0.f;
      bf16* xp = a.xb[l] + (size_t)R0 * DM + tile * 128 + 8 * t;
      uint32_t c0[16], c1[16];
#pragma unroll
      for (int j = 0; j < 16; j++) { c0[j] = pack_bf16(acc[4 * j], acc[4 * j + 1]); c1[j] = pack_bf16(acc[4 * j + 2], acc[4 * j + 3]); }
#pragma unroll
      for (int m = 0; m < 4; m++) { quad_transpose(c0 + 4 * m, t); quad_transpose(c1 + 4 * m, t); }
#pragma unroll
      for (int j = 0; j < 16; j++) {
        const uint32_t u0 = c0[j], u1 = c1[j];
        const uint32_t y0 = pack_bf16(bf_lo(r0[j]) + bf_lo(u0), bf_hi(r0[j]) + bf_hi(u0));
        const uint32_t y1 = pack_bf16(bf_lo(r1[j]) + bf_lo(u1), bf_hi(r1[j]) + bf_hi(u1));
        acc[4 * j] = bf_lo(y0); acc[4 * j + 1] = bf_hi(y0); acc[4 * j + 2] = bf_lo(y1); acc[4 * j + 3] = bf_hi(y1);
        s0 += acc[4 * j] + acc[4 * j + 1]; s1 += acc[4 * j + 2] + acc[4 * j + 3];
      }
      if (l == 0) {
        s0 += __shfl_xor_sync(0xffffffffu, s0, 1); s1 += __shfl_xor_sync(0xffffffffu, s1, 1);
        s0 += __shfl_xor_sync(0xffffffffu, s0, 2); s1 += __shfl_xor_sync(0xffffffffu, s1, 2);
        const float tm0 = s0 * (1.f / 128), tm1 = s1 * (1.f / 128);
        float q0 = 0.f, q1 = 0.f;
#pragma unroll
        for (int j = 0; j < 16; j++) {
          const float a0 = acc[4 * j] - tm0, b0 = acc[4 * j + 1] - tm0, a1 = acc[4 * j + 2] - tm1, b1 = acc[4 * j + 3] - tm1;
          q0 += a0 * a0 + b0 * b0; q1 += a1 * a1 + b1 * b1;
        }
        q0 += __shfl_xor_sync(0xffffffffu, q0, 1); q1 += __shfl_xor_sync(0xffffffffu, q1, 1);
        q0 += __shfl_xor_sync(0xffffffffu, q0, 2); q1 += __shfl_xor_sync(0xffffffffu, q1, 2);
        float2* sp = &g_stats[b][rb][0];
        if (t < 2) {
          const float sx = t ? s1 : s0, qx = t ? q1 : q0;
          asm volatile("st.relaxed.gpu.global.v2.f32 [%0],{%1,%2};" ::"l"(sp + t * 8 * 16 + tile), "f"(sx), "f"(qx) : "memory");
        }
#pragma unroll
        for (int m = 0; m < 4; m++) {
          const float* c = acc + 16 * m;
          *reinterpret_cast<uint4*>(xp + 32 * m) = make_uint4(pack_bf16(c[0], c[1]), pack_bf16(c[4], c[5]), pack_bf16(c[8], c[9]), pack_bf16(c[12], c[13]));
          *reinterpret_cast<uint4*>(xp + 8 * DM + 32 * m) = make_uint4(pack_bf16(c[2], c[3]), pack_bf16(c[6], c[7]), pack_bf16(c[10], c[11]), pack_bf16(c[14], c[15]));
        }
        if (w == 35 && tid0 == 0) WTS(l, b, 18);
        float2 e0[2], e1[2];
        int n = dead ? SPIN_MAIL : 0;
        while (true) {
          e0[0] = ld_relaxed2f(sp + t); e1[0] = ld_relaxed2f(sp + 8 * 16 + t);
          e0[1] = ld_relaxed2f(sp + 4); e1[1] = ld_relaxed2f(sp + 8 * 16 + 4);
          bool bad = false;
#pragma unroll
          for (int i = 0; i < 2; i++)
            bad |= __float_as_uint(e0[i].x) == SENT || __float_as_uint(e0[i].y) == SENT || __float_as_uint(e1[i].x) == SENT || __float_as_uint(e1[i].y) == SENT;
          if (!__any_sync(0xffffffffu, bad)) break;
          if (++n > SPIN_MAIL) { dead = 1; g_err = 20; break; }
        }
        if (w == 35 && tid0 == 0) WTS(l, b, 19);
        float m0 = e0[0].x, m1 = e1[0].x;
        m0 += __shfl_xor_sync(0xffffffffu, m0, 1); m1 += __shfl_xor_sync(0xffffffffu, m1, 1);
        m0 += __shfl_xor_sync(0xffffffffu, m0, 2); m1 += __shfl_xor_sync(0xffffffffu, m1, 2);
        m0 = (m0 + e0[1].x) * (1.f / DM); m1 = (m1 + e1[1].x) * (1.f / DM);
        const float d0 = e0[0].x * (1.f / 128) - m0, d1 = e1[0].x * (1.f / 128) - m1;
        float v0 = e0[0].y + 128.f * d0 * d0, v1 = e1[0].y + 128.f * d1 * d1;
        v0 += __shfl_xor_sync(0xffffffffu, v0, 1); v1 += __shfl_xor_sync(0xffffffffu, v1, 1);
        v0 += __shfl_xor_sync(0xffffffffu, v0, 2); v1 += __shfl_xor_sync(0xffffffffu, v1, 2);
        const float d2 = e0[1].x * (1.f / 128) - m0, d3 = e1[1].x * (1.f / 128) - m1;
        v0 += e0[1].y + 128.f * d2 * d2; v1 += e1[1].y + 128.f * d3 * d3;
        const float rs0 = rsqrtf(v0 * (1.f / DM) + 1e-5f), rs1 = rsqrtf(v1 * (1.f / DM) + 1e-5f);
        uint8_t* img = g_xn[1] + (size_t)(R0 >> 5) * 40960 + tile * 8192 + ((R0 >> 3) & 3) * 2048 + g * 128;
#pragma unroll
        for (int m = 0; m < 4; m++) {
          uint8_t* o = img + (m >> 1) * 1024 + (((4 * (m & 1) + t) ^ g) << 4);
          const float* c = acc + 16 * m;
          *reinterpret_cast<uint4*>(o) = make_uint4(pack_bf16((c[0] - m0) * rs0, (c[1] - m0) * rs0), pack_bf16((c[4] - m0) * rs0, (c[5] - m0) * rs0),
                                                    pack_bf16((c[8] - m0) * rs0, (c[9] - m0) * rs0), pack_bf16((c[12] - m0) * rs0, (c[13] - m0) * rs0));
          *reinterpret_cast<uint4*>(o + 2048) = make_uint4(pack_bf16((c[2] - m1) * rs1, (c[3] - m1) * rs1), pack_bf16((c[6] - m1) * rs1, (c[7] - m1) * rs1),
                                                            pack_bf16((c[10] - m1) * rs1, (c[11] - m1) * rs1), pack_bf16((c[14] - m1) * rs1, (c[15] - m1) * rs1));
        }
        bar_sync(NB_P, 256);
        if (tid0 == 0) { fence_async_all(); cnt_signal(CN_X, 0, b); }
      } else {
#pragma unroll
        for (int m = 0; m < 4; m++) {
          const float* c = acc + 16 * m;
          *reinterpret_cast<uint4*>(xp + 32 * m) = make_uint4(pack_bf16(c[0], c[1]), pack_bf16(c[4], c[5]), pack_bf16(c[8], c[9]), pack_bf16(c[12], c[13]));
          *reinterpret_cast<uint4*>(xp + 8 * DM + 32 * m) = make_uint4(pack_bf16(c[2], c[3]), pack_bf16(c[6], c[7]), pack_bf16(c[10], c[11]), pack_bf16(c[14], c[15]));
        }
      }
      if (w == 35 && tid0 == 0) { WTS(l, b, 4); WTS(l, b, 20); }
    }
  }
}

__device__ __forceinline__ void work_q_producer(const WorkArgs& a, uint32_t sb) {
  using namespace W;
  int dead = 0, st = 0;
  uint32_t ph = 1;
  FOR_BATCHES(l, b)
    cnt_wait(CN_L, l, b, 64, dead);
    if (blockIdx.x == 0) WTS(l, b, 2);
    fence_async_all();
    const uint8_t* src = g_xnb[l] + (size_t)(2 * b) * 10 * 8192;
#pragma unroll 1
    for (int kc = 0; kc < 10; kc++) {
      const uint32_t bar = sb + BAR_BF + 8 * st, d = sb + OFF_B + st * BSTAGE;
      mbar_wait(sb + BAR_BE + 8 * st, ph, dead);
      mbar_expect_tx(bar, BSTAGE);
      bulk_g2s(d, src + (size_t)kc * 8192, 8192, bar);
      bulk_g2s(d + 8192, src + (size_t)(10 + kc) * 8192, 8192, bar);
      if (++st == BST) { st = 0; ph ^= 1; }
    }
  }
}

__device__ __forceinline__ void work_ln(const WorkArgs& a, int w, int wr, int lane0) {
  int dead = 0;
  FOR_BATCHES(l, b)
    uint32_t r0[10], r1[10];
    if (HOIST & 2) {
      if (l == 1) {
        if (lane0 == 0) cnt_wait(CN_X, 0, b, 5, dead);
        __syncwarp();
      }
      const int lane = fresh(lane0), p = 2 * w + wr;
      const bf16* rp = a.res[l] + (size_t)(b * 128 + (p >> 3) * 16 + (p & 7)) * DM + (lane >> 2) * 8 + 2 * (lane & 3);
#pragma unroll
      for (int i = 0; i < 10; i++) { r0[i] = ld_relaxed(rp + i * 64); r1[i] = ld_relaxed(rp + i * 64 + 8 * DM); }
    }
    if (lane0 == 0) cnt_wait(CN_P, l, b, W::NP, dead);
    __syncwarp();
    if (w == WW && wr == 0 && lane0 == 0) { WTS(l, b, 1); WTS(l, b, 9); }
    LTS(l, b, 2 * w + wr, 0);
    const int lane = fresh(lane0), p = 2 * w + wr;
    const int slab = p >> 3, g = p & 7, jj = lane >> 2, t = lane & 3;
    const int R0 = b * 128 + slab * 16 + g;
    const float* acc = &g_acc[l][b][0][0] + slab * 2048 + (g * 4 + t) * 4 + jj * 128;
    const bf16* rp = a.res[l] + (size_t)R0 * DM + jj * 8 + 2 * t;
    float4 v[10];
#pragma unroll
    for (int i = 0; i < 10; i++) {
      v[i] = ld_relaxed4f(acc + (i >> 1) * 16384 + (i & 1) * 1024);
      if (!(HOIST & 2)) { r0[i] = ld_relaxed(rp + i * 64); r1[i] = ld_relaxed(rp + i * 64 + 8 * DM); }
    }
    float s0 = 0.f, s1 = 0.f;
    bf16* xp = a.xa[l] + (size_t)R0 * DM + jj * 8 + 2 * t;
#pragma unroll
    for (int i = 0; i < 10; i++) {
      const uint32_t u0 = pack_bf16(v[i].x, v[i].y), u1 = pack_bf16(v[i].z, v[i].w);
      r0[i] = pack_bf16(bf_lo(r0[i]) + bf_lo(u0), bf_hi(r0[i]) + bf_hi(u0));
      r1[i] = pack_bf16(bf_lo(r1[i]) + bf_lo(u1), bf_hi(r1[i]) + bf_hi(u1));
      s0 += bf_lo(r0[i]) + bf_hi(r0[i]); s1 += bf_lo(r1[i]) + bf_hi(r1[i]);
    }
#pragma unroll
    for (int o = 16; o > 0; o >>= 1) { s0 += __shfl_xor_sync(0xffffffffu, s0, o); s1 += __shfl_xor_sync(0xffffffffu, s1, o); }
    const float m0 = s0 * (1.f / DM), m1 = s1 * (1.f / DM);
    if (m0 != 12345.678f) LTS(l, b, 2 * w + wr, 1);
    float q0 = 0.f, q1 = 0.f;
#pragma unroll
    for (int i = 0; i < 10; i++) {
      const float a0 = bf_lo(r0[i]) - m0, b0 = bf_hi(r0[i]) - m0, a1 = bf_lo(r1[i]) - m1, b1 = bf_hi(r1[i]) - m1;
      q0 += a0 * a0 + b0 * b0; q1 += a1 * a1 + b1 * b1;
    }
#pragma unroll
    for (int o = 16; o > 0; o >>= 1) { q0 += __shfl_xor_sync(0xffffffffu, q0, o); q1 += __shfl_xor_sync(0xffffffffu, q1, o); }
    const float rs0 = rsqrtf(q0 * (1.f / DM) + 1e-5f), rs1 = rsqrtf(q1 * (1.f / DM) + 1e-5f);
    uint8_t* img = g_xnb[l] + (size_t)(R0 >> 6) * 10 * 8192 + (R0 & 63) * 128 + t * 4 + ((jj ^ g) << 4);
#pragma unroll
    for (int i = 0; i < 10; i++) {
      *reinterpret_cast<uint32_t*>(img + i * 8192) = pack_bf16((bf_lo(r0[i]) - m0) * rs0, (bf_hi(r0[i]) - m0) * rs0);
      *reinterpret_cast<uint32_t*>(img + i * 8192 + 1024) = pack_bf16((bf_lo(r1[i]) - m1) * rs1, (bf_hi(r1[i]) - m1) * rs1);
    }
#pragma unroll
    for (int i = 0; i < 10; i++) {
      *reinterpret_cast<uint32_t*>(xp + i * 64) = r0[i];
      *reinterpret_cast<uint32_t*>(xp + i * 64 + 8 * DM) = r1[i];
    }
    __syncwarp();
    if (w == WW && wr == 0 && lane0 == 0) WTS(l, b, 10);
    LTS(l, b, 2 * w + wr, 2);
    if (lane0 == 0) cnt_signal(CN_L, l, b);
    LTS(l, b, 2 * w + wr, 3);
    if (w == WW && wr == 0 && lane0 == 0) WTS(l, b, 11);
  }
}

__device__ __forceinline__ void work_q(const WorkArgs& a, uint32_t sb, int w, int tid0) {
  using namespace W;
  int dead = 0, st = 0;
  uint32_t ph = 0;
  FOR_BATCHES(l, b)
    {
      float acc0[32], acc1[32];
      int prev = 0;
#pragma unroll 1
      for (int kc = 0; kc < 10; kc++) {
        mbar_wait(sb + BAR_BF + 8 * st, ph, dead);
        if (w == WW && tid0 == 0 && kc == 0) WTS(l, b, 12);
        const uint32_t pa = sb + OFF_B + st * BSTAGE, pb = sb + OFF_WQ + kc * 8192;
        wg_fence();
#pragma unroll
        for (int kk = 0; kk < 4; kk++) {
          wgmma_st64(acc0, mkdesc(pa + kk * 32, 16, 1024), mkdesc(pb + kk * 2048, 8192, 1024), (kc | kk) != 0);
          wgmma_st64(acc1, mkdesc(pa + 8192 + kk * 32, 16, 1024), mkdesc(pb + kk * 2048, 8192, 1024), (kc | kk) != 0);
        }
        wg_commit();
        if (IMMREL & 4) {
          if (kc <= 6) {
            wg_wait<0>();
            if (tid0 == 0) mbar_arrive(sb + BAR_BE + 8 * st);
          }
        } else if (kc > 0) {
          wg_wait<1>();
          if (kc <= 7 && tid0 == 0) mbar_arrive(sb + BAR_BE + 8 * prev);
        }
        prev = st;
        if (++st == BST) { st = 0; ph ^= 1; }
      }
      wg_wait<0>();
      bar_sync(NB_B, 128);
      if (w == WW && tid0 == 0) WTS(l, b, 13);
      const int tid = fresh(tid0), wr = tid >> 5, g = (tid & 31) >> 2, t = tid & 3;
      const uint32_t stg = sb + OFF_B, hist = sb + OFF_HIST + l * 1120;
      const uint32_t o = stg + (14 + 16 * wr + g) * PITCH + t * 4;
#pragma unroll
      for (int j = 0; j < 8; j++) {
        sts32(o + j * 16, pack_bf16(acc0[4 * j], acc0[4 * j + 1]));
        sts32(o + 8 * PITCH + j * 16, pack_bf16(acc0[4 * j + 2], acc0[4 * j + 3]));
        sts32(o + 64 * PITCH + j * 16, pack_bf16(acc1[4 * j], acc1[4 * j + 1]));
        sts32(o + 72 * PITCH + j * 16, pack_bf16(acc1[4 * j + 2], acc1[4 * j + 3]));
      }
      for (int i = tid; i < 280; i += 128) {
        uint32_t v; asm volatile("ld.shared.b32 %0,[%1];" : "=r"(v) : "r"(hist + i * 4) : "memory");
        sts32(stg + (i / 20) * PITCH + 40 + (i % 20) * 4, v);
      }
    }
    bar_sync(NB_B, 128);
    {
      const int tid = fresh(tid0);
      const uint32_t stg = sb + OFF_B, hist = sb + OFF_HIST + l * 1120;
      for (int i = tid; i < 280; i += 128) {
        uint32_t v; asm volatile("ld.shared.b32 %0,[%1];" : "=r"(v) : "r"(stg + (128 + i / 20) * PITCH + 40 + (i % 20) * 4) : "memory");
        sts32(hist + i * 4, v);
      }
      const float scl = 0.22360679774997896f * 1.4426950408889634f;
      const uint32_t row = stg + (14 + tid) * PITCH;
      const int pos = b * 128 + tid;
      float q[20];
#pragma unroll
      for (int i = 0; i < 5; i++) {
        uint32_t u0, u1; asm volatile("ld.shared.v2.b32 {%0,%1},[%2];" : "=r"(u0), "=r"(u1) : "r"(row + i * 8) : "memory");
        q[4 * i] = bf_lo(u0); q[4 * i + 1] = bf_hi(u0); q[4 * i + 2] = bf_lo(u1); q[4 * i + 3] = bf_hi(u1);
      }
      float sc[8], mx = -INFINITY;
#pragma unroll
      for (int j = 0; j < 8; j++) {
        float s0 = 0.f, s1 = 0.f;
#pragma unroll
        for (int i = 0; i < 5; i++) {
          uint32_t u0, u1; asm volatile("ld.shared.v2.b32 {%0,%1},[%2];" : "=r"(u0), "=r"(u1) : "r"(row - 2 * j * PITCH + 40 + i * 8) : "memory");
          s0 += q[4 * i] * bf_lo(u0) + q[4 * i + 1] * bf_hi(u0);
          s1 += q[4 * i + 2] * bf_lo(u1) + q[4 * i + 3] * bf_hi(u1);
        }
        sc[j] = pos - 2 * j >= 0 ? (s0 + s1) * scl : -INFINITY;
        mx = fmaxf(mx, sc[j]);
      }
      float sum = 0.f;
#pragma unroll
      for (int j = 0; j < 8; j++) { sc[j] = ex2(sc[j] - mx); sum += sc[j]; }
      const float inv = 1.f / sum;
      float o[20];
#pragma unroll
      for (int i = 0; i < 20; i++) o[i] = 0.f;
#pragma unroll
      for (int j = 0; j < 8; j++) {
        const float pj = __bfloat162float(__float2bfloat16(sc[j] * inv));
#pragma unroll
        for (int i = 0; i < 5; i++) {
          uint32_t u0, u1; asm volatile("ld.shared.v2.b32 {%0,%1},[%2];" : "=r"(u0), "=r"(u1) : "r"(row - 2 * j * PITCH + 80 + i * 8) : "memory");
          o[4 * i] += pj * bf_lo(u0); o[4 * i + 1] += pj * bf_hi(u0); o[4 * i + 2] += pj * bf_lo(u1); o[4 * i + 3] += pj * bf_hi(u1);
        }
      }
      uint8_t* img = g_ob[l] + (size_t)(pos >> 6) * 10 * 8192 + (pos & 63) * 128;
#pragma unroll
      for (int i = 0; i < 5; i++) {
        const int c = w * 20 + 4 * i;
        *reinterpret_cast<uint2*>(img + (c >> 6) * 8192 + ((((c >> 3) & 7) ^ (pos & 7)) << 4) + (c & 7) * 2) =
            make_uint2(pack_bf16(o[4 * i], o[4 * i + 1]), pack_bf16(o[4 * i + 2], o[4 * i + 3]));
      }
    }
    if (w == WW && tid0 == 0) WTS(l, b, 14);
    bar_sync(NB_B, 128);
    if (tid0 == 0) { cnt_signal(CN_A, l, b); if (w == WW) WTS(l, b, 15); }
    fence_async();
    bar_sync(NB_B, 128);
    if (tid0 == 0) for (int i = 0; i < BST; i++) mbar_arrive(sb + BAR_BE + 8 * i);
  }
}

__global__ void __launch_bounds__(512, 1)
k_work(const __grid_constant__ CUtensorMap tmWo, const __grid_constant__ CUtensorMap tmBo, const __grid_constant__ WorkArgs args) {
  using namespace W;
  extern __shared__ __align__(1024) uint8_t smem[];
  const uint32_t sb = smem_u32(smem);
  const int tid = threadIdx.x, w = blockIdx.x;
  const int wg = __shfl_sync(0xffffffffu, tid >> 7, 0);
  if (tid == 0) {
    for (int i = 0; i < PST; i++) { mbar_init(sb + BAR_PF + 8 * i, 1); mbar_init(sb + BAR_PE + 8 * i, 2); }
    for (int i = 0; i < BST; i++) { mbar_init(sb + BAR_BF + 8 * i, 1); mbar_init(sb + BAR_BE + 8 * i, 1); }
    asm volatile("fence.mbarrier_init.release.cluster;" ::: "memory");
  }
  for (int i = w * 512 + tid; i < 2 * 16 * 5 * 4096; i += NW * 512) reinterpret_cast<uint4*>(&g_acc[0][0][0][0])[i] = make_uint4(0, 0, 0, 0);
  if (w < 32) {
    for (int i = tid; i < 640 * 32; i += 512) {
      const int k = i >> 5, c = i & 31;
      uint32_t v = 0;
      if (c < 30) v = *reinterpret_cast<const uint32_t*>(args.wqkv + (size_t)k * 1920 + (c / 10) * 640 + w * 20 + (c % 10) * 2);
      sts32(sb + OFF_WQ + (k >> 6) * 8192 + (k & 63) * 128 + (((c >> 2) ^ (k & 7)) << 4) + (c & 3) * 4, v);
    }
  }
  for (int i = tid; i < 560; i += 512) sts32(sb + OFF_HIST + i * 4, 0);
  fence_async();
  __syncthreads();
  if (tid == 0) cnt_signal(CN_Z, 0, 0);

  if (wg < 2) {
    if (w < NP) work_gemm<false>(args, sb, w, tid);
    else if (w >= OW0) work_gemm<true>(args, sb, w, tid);
    else if (LN30 && tid < 64) work_ln(args, 31, tid >> 5, tid & 31);
  } else if (wg == 2) {
    if (w < 32) work_q(args, sb, w, tid - 256);
  } else if (tid >= 448) {
    if (w < (LN30 ? 31 : 32)) work_ln(args, w, (tid >> 5) & 1, tid & 31);
  } else if (tid == 384) {
    if (w < NP) work_gemm_producer<false>(tmWo, args, sb, w);
    else if (w >= OW0) work_gemm_producer<true>(tmBo, args, sb, w);
  } else if (tid == 416) {
    if (w < 32) work_q_producer(args, sb);
  }
  __syncthreads();
  asm volatile("griddepcontrol.wait;" ::: "memory");
}

typedef CUresult (*EncodeFn)(CUtensorMap*, CUtensorMapDataType, cuuint32_t, void*, const cuuint64_t*, const cuuint64_t*,
                             const cuuint32_t*, const cuuint32_t*, CUtensorMapInterleave, CUtensorMapSwizzle,
                             CUtensorMapL2promotion, CUtensorMapFloatOOBfill);

static void make_map(EncodeFn enc, CUtensorMap* tm, const void* ptr, uint64_t cols, uint64_t rows, uint32_t boxc, uint32_t boxr) {
  cuuint64_t dims[2] = {cols, rows};
  cuuint64_t strides[1] = {cols * 2};
  cuuint32_t box[2] = {boxc, boxr};
  cuuint32_t es[2] = {1, 1};
  enc(tm, CU_TENSOR_MAP_DATA_TYPE_BFLOAT16, 2, const_cast<void*>(ptr), dims, strides, box, es, CU_TENSOR_MAP_INTERLEAVE_NONE,
      CU_TENSOR_MAP_SWIZZLE_128B, CU_TENSOR_MAP_L2_PROMOTION_L2_256B, CU_TENSOR_MAP_FLOAT_OOB_FILL_NONE);
}

extern "C" void kernel_launch(void* const* d_in, const int* in_sizes, int n_in, void* d_out, int out_size) {
  const bf16* x0 = (const bf16*)d_in[0];
  const bf16* mem0 = (const bf16*)d_in[1];
  const bf16* Wq = (const bf16*)d_in[2];
  const bf16* Wk = (const bf16*)d_in[3];
  const bf16* Wv = (const bf16*)d_in[4];
  const bf16* Wo = (const bf16*)d_in[5];
  const bf16* Bqkv = (const bf16*)d_in[8];
  const bf16* Bwo = (const bf16*)d_in[9];
  bf16* out = (bf16*)d_out;

  static EncodeFn enc = nullptr;
  static bf16 *p_x1, *p_x2, *p_x3;
  if (!enc) {
    void* fn = nullptr;
    cudaDriverEntryPointQueryResult qr;
    cudaGetDriverEntryPoint("cuTensorMapEncodeTiled", &fn, cudaEnableDefault, &qr);
    enc = (EncodeFn)fn;
    cudaFuncSetAttribute(k_chain, cudaFuncAttributeMaxDynamicSharedMemorySize, C::SMEM);
    cudaFuncSetAttribute(k_work, cudaFuncAttributeMaxDynamicSharedMemorySize, W::SMEM);
    void* p;
    cudaGetSymbolAddress(&p, g_x1); p_x1 = (bf16*)p;
    cudaGetSymbolAddress(&p, g_x2); p_x2 = (bf16*)p;
    cudaGetSymbolAddress(&p, g_x3); p_x3 = (bf16*)p;
  }
  CUtensorMap tmWq, tmWk, tmWv, tmWo, tmBo;
  make_map(enc, &tmWq, Wq, NH * DH, DM, 64, 128);
  make_map(enc, &tmWk, Wk, NH * DH, DM, 64, 128);
  make_map(enc, &tmWv, Wv, NH * DH, DM, 64, 128);
  make_map(enc, &tmWo, Wo, DM, NH * DH, 64, 64);
  make_map(enc, &tmBo, Bwo, DM, DM, 64, 64);

  cudaStream_t st = cudaStreamPerThread;
  k_pre<<<256, 256, 0, st>>>(x0, mem0);
  cudaLaunchAttribute at[1];
  at[0].id = cudaLaunchAttributeProgrammaticStreamSerialization; at[0].val.programmaticStreamSerializationAllowed = 1;
  {
    cudaLaunchConfig_t cfg = {};
    cfg.gridDim = dim3(96); cfg.blockDim = dim3(384); cfg.dynamicSmemBytes = C::SMEM; cfg.stream = st;
    cfg.attrs = at; cfg.numAttrs = 0;
    cudaLaunchKernelEx(&cfg, k_chain, tmWq, tmWk, tmWv, tmWo);
  }
  WorkArgs wa;
  wa.res[0] = x0; wa.res[1] = p_x2; wa.xa[0] = p_x1; wa.xa[1] = p_x3; wa.xb[0] = p_x2; wa.xb[1] = out;
  wa.wqkv = Bqkv;
  cudaLaunchConfig_t cfg = {};
  cfg.gridDim = dim3(W::NW); cfg.blockDim = dim3(512); cfg.dynamicSmemBytes = W::SMEM; cfg.stream = st;
  cfg.attrs = at; cfg.numAttrs = NOWORK == 2 ? 0 : 1;
  cudaLaunchKernelEx(&cfg, k_work, tmWo, tmBo, wa);
}
```

```cpp
#include <cuda_runtime.h>
#include <cuda_bf16.h>
#include <cuda.h>
#include <stdint.h>

typedef __nv_bfloat16 bf16;

constexpr int SEQ = 2048, DM = 640, NH = 32, DH = 192, NSEG = 64;
#define LAG 14
constexpr int NSTEP = NSEG + LAG;
constexpr uint32_t SENT = 0xFFFFFFFFu;
constexpr int SPIN_LIM = 1 << 20;
constexpr int SPIN_MAIL = 1 << 16;
constexpr int SPIN_CNT = 1 << 16;

constexpr int MAIL9 = 288 * 2048, MAIL_BYTES = MAIL9 + 64 * 3072;
__device__ __align__(1024) uint8_t g_xn[2][NSEG * 40960];
__device__ __align__(1024) uint8_t g_xnb[2][32 * 10 * 8192];
__device__ __align__(1024) uint8_t g_ob[2][32 * 10 * 8192];
__device__ __align__(1024) uint8_t g_o[2][32 * 96 * 8192];
__device__ __align__(1024) uint8_t g_mbuf[NSTEP][20480];
__device__ __align__(1024) uint32_t g_flag[NSTEP][768];
__device__ __align__(1024) uint8_t g_mail[2][MAIL_BYTES];
__device__ __align__(1024) float g_acc[2][16][5][16384];
__device__ __align__(1024) float2 g_stats[16][128][16];
__device__ __align__(128) bf16 g_x1[SEQ * DM];
__device__ __align__(128) bf16 g_x2[SEQ * DM];
__device__ __align__(128) bf16 g_x3[SEQ * DM];
enum { CN_O = 0, CN_P = 1, CN_L = 2, CN_A = 3, CN_X = 4, CN_Z = 5 };
__device__ __align__(128) uint32_t g_cnt[6][2][16][32];
__device__ int g_err;
#define TS(jj, i)
#define TS1(jj, i)
#define PTS(i)
#define LTS(l, b, p, k)
#define TSB(jj, i)
#define TSV(jj, i, v)
#define TS_FLUSH(jj)
#define WTS(l, b, k)
#define WW -1

__device__ __forceinline__ uint32_t smem_u32(const void* p) { return (uint32_t)__cvta_generic_to_shared(p); }
__device__ __forceinline__ uint32_t clk32() { uint32_t t; asm volatile("mov.u32 %0, %%clock;" : "=r"(t)::"memory"); return t; }
__device__ __forceinline__ uint32_t mapa(uint32_t a, uint32_t r) { uint32_t o; asm("mapa.shared::cluster.u32 %0,%1,%2;" : "=r"(o) : "r"(a), "r"(r)); return o; }
__device__ __forceinline__ void mbar_init(uint32_t bar, uint32_t cnt) { asm volatile("mbarrier.init.shared::cta.b64 [%0],%1;" ::"r"(bar), "r"(cnt) : "memory"); }
__device__ __forceinline__ void mbar_expect_tx(uint32_t bar, uint32_t bytes) { asm volatile("mbarrier.arrive.expect_tx.shared::cta.b64 _,[%0],%1;" ::"r"(bar), "r"(bytes) : "memory"); }
__device__ __forceinline__ void mbar_arrive(uint32_t bar) { asm volatile("mbarrier.arrive.shared::cta.b64 _,[%0];" ::"r"(bar) : "memory"); }
__device__ __forceinline__ void mbar_arrive_cluster(uint32_t bar) { asm volatile("mbarrier.arrive.shared::cluster.b64 _,[%0];" ::"r"(bar) : "memory"); }
__device__ __forceinline__ bool mbar_try(uint32_t bar, uint32_t ph) {
  uint32_t ok;
  asm volatile("{.reg .pred p; mbarrier.try_wait.parity.shared::cta.b64 p,[%1],%2; selp.u32 %0,1,0,p;}" : "=r"(ok) : "r"(bar), "r"(ph) : "memory");
  return ok;
}
__device__ __forceinline__ void mbar_wait(uint32_t bar, uint32_t ph, int& dead) {
  if (mbar_try(bar, ph)) return;
  int n = dead ? SPIN_LIM : 0;
  while (!mbar_try(bar, ph)) { if (++n > SPIN_LIM) { dead = 1; g_err = 1; break; } }
}
__device__ __forceinline__ int fresh(int x) { asm volatile("" : "+r"(x)); return x; }
#define PHASE_IDS const int tid = fresh(tid0), lane = tid & 31, w = tid >> 5, g = lane >> 2, t = lane & 3; (void)w; (void)g; (void)t
__device__ __forceinline__ void bar_sync(int id, int n) { asm volatile("bar.sync %0,%1;" ::"r"(id), "r"(n) : "memory"); }
__device__ __forceinline__ void bar_arrive(int id, int n) { asm volatile("bar.arrive %0,%1;" ::"r"(id), "r"(n) : "memory"); }
__device__ __forceinline__ bool bar_red_or(int id, int n, bool v) {
  uint32_t r;
  asm volatile("{\n .reg .pred p, q;\n setp.ne.u32 q, %3, 0;\n barrier.cta.red.or.pred p, %1, %2, q;\n selp.u32 %0, 1, 0, p;\n}" : "=r"(r) : "r"(id), "r"(n), "r"((uint32_t)v) : "memory");
  return r != 0;
}
__device__ __forceinline__ void fence_async() { asm volatile("fence.proxy.async.shared::cta;" ::: "memory"); }
__device__ __forceinline__ void bulk_g2s(uint32_t dst, const void* src, uint32_t bytes, uint32_t bar) {
  asm volatile("cp.async.bulk.shared::cluster.global.mbarrier::complete_tx::bytes [%0],[%1],%2,[%3];" ::"r"(dst), "l"(src), "r"(bytes), "r"(bar) : "memory");
}
__device__ __forceinline__ void bulk_g2s_mc(uint32_t dst, const void* src, uint32_t bytes, uint32_t bar) {
  asm volatile("cp.async.bulk.shared::cluster.global.mbarrier::complete_tx::bytes.multicast::cluster [%0],[%1],%2,[%3],%4;"
               ::"r"(dst), "l"(src), "r"(bytes), "r"(bar), "h"((uint16_t)7) : "memory");
}
__device__ __forceinline__ void bulk_s2g(void* dst, uint32_t src, uint32_t bytes) {
  asm volatile("cp.async.bulk.global.shared::cta.bulk_group [%0],[%1],%2;" ::"l"(dst), "r"(src), "r"(bytes) : "memory");
}
__device__ __forceinline__ void bulk_s2c(uint32_t dst, uint32_t src, uint32_t bytes, uint32_t bar) {
  asm volatile("cp.async.bulk.shared::cluster.shared::cta.mbarrier::complete_tx::bytes [%0],[%1],%2,[%3];" ::"r"(dst), "r"(src), "r"(bytes), "r"(bar) : "memory");
}
__device__ __forceinline__ void tma2d(uint32_t dst, const CUtensorMap* tm, int c0, int c1, uint32_t bar) {
  asm volatile("cp.async.bulk.tensor.2d.shared::cluster.global.mbarrier::complete_tx::bytes [%0],[%1,{%3,%4}],[%2];"
               ::"r"(dst), "l"(tm), "r"(bar), "r"(c0), "r"(c1) : "memory");
}
__device__ __forceinline__ void tma2d_prefetch(const CUtensorMap* tm, int c0, int c1) {
  asm volatile("cp.async.bulk.prefetch.tensor.2d.L2.global.tile [%0,{%1,%2}];" ::"l"(tm), "r"(c0), "r"(c1) : "memory");
}
__device__ __forceinline__ uint32_t pack_bf16(float lo, float hi) {
  uint32_t r; asm("cvt.rn.bf16x2.f32 %0,%1,%2;" : "=r"(r) : "f"(hi), "f"(lo)); return r;
}
__device__ __forceinline__ float bf_lo(uint32_t x) { return __uint_as_float(x << 16); }
__device__ __forceinline__ float bf_hi(uint32_t x) { return __uint_as_float(x & 0xFFFF0000u); }
__device__ __forceinline__ float ex2(float x) { float y; asm("ex2.approx.ftz.f32 %0,%1;" : "=f"(y) : "f"(x)); return y; }
__device__ __forceinline__ void ldsm4(uint32_t (&r)[4], uint32_t a) {
  asm volatile("ldmatrix.sync.aligned.m8n8.x4.shared.b16 {%0,%1,%2,%3},[%4];" : "=r"(r[0]), "=r"(r[1]), "=r"(r[2]), "=r"(r[3]) : "r"(a) : "memory");
}
__device__ __forceinline__ void ldsm4t(uint32_t (&r)[4], uint32_t a) {
  asm volatile("ldmatrix.sync.aligned.m8n8.x4.trans.shared.b16 {%0,%1,%2,%3},[%4];" : "=r"(r[0]), "=r"(r[1]), "=r"(r[2]), "=r"(r[3]) : "r"(a) : "memory");
}
__device__ __forceinline__ void ldsm2(uint32_t& r0, uint32_t& r1, uint32_t a) {
  asm volatile("ldmatrix.sync.aligned.m8n8.x2.shared.b16 {%0,%1},[%2];" : "=r"(r0), "=r"(r1) : "r"(a) : "memory");
}
__device__ __forceinline__ void ldsm1(uint32_t& r0, uint32_t a) {
  asm volatile("ldmatrix.sync.aligned.m8n8.x1.shared.b16 {%0},[%1];" : "=r"(r0) : "r"(a) : "memory");
}
__device__ __forceinline__ void mma16816(float (&d)[4], uint32_t a0, uint32_t a1, uint32_t a2, uint32_t a3, uint32_t b0, uint32_t b1) {
  asm volatile("mma.sync.aligned.m16n8k16.row.col.f32.bf16.bf16.f32 {%0,%1,%2,%3},{%4,%5,%6,%7},{%8,%9},{%0,%1,%2,%3};"
               : "+f"(d[0]), "+f"(d[1]), "+f"(d[2]), "+f"(d[3]) : "r"(a0), "r"(a1), "r"(a2), "r"(a3), "r"(b0), "r"(b1));
}
__device__ __forceinline__ void mma1688(float (&d)[4], uint32_t a0, uint32_t a1, uint32_t b0) {
  asm volatile("mma.sync.aligned.m16n8k8.row.col.f32.bf16.bf16.f32 {%0,%1,%2,%3},{%4,%5},{%6},{%0,%1,%2,%3};"
               : "+f"(d[0]), "+f"(d[1]), "+f"(d[2]), "+f"(d[3]) : "r"(a0), "r"(a1), "r"(b0));
}
__device__ __forceinline__ void sts32(uint32_t a, uint32_t v) { asm volatile("st.shared.b32 [%0],%1;" ::"r"(a), "r"(v) : "memory"); }
__device__ __forceinline__ void sts64f(uint32_t a, float x, float y) { asm volatile("st.shared.v2.f32 [%0],{%1,%2};" ::"r"(a), "f"(x), "f"(y) : "memory"); }
__device__ __forceinline__ void sts128(uint32_t a, uint4 v) { asm volatile("st.shared.v4.b32 [%0],{%1,%2,%3,%4};" ::"r"(a), "r"(v.x), "r"(v.y), "r"(v.z), "r"(v.w) : "memory"); }
__device__ __forceinline__ float lds32f(uint32_t a) { float v; asm volatile("ld.shared.f32 %0,[%1];" : "=f"(v) : "r"(a) : "memory"); return v; }
__device__ __forceinline__ float2 lds64f(uint32_t a) { float2 v; asm volatile("ld.shared.v2.f32 {%0,%1},[%2];" : "=f"(v.x), "=f"(v.y) : "r"(a) : "memory"); return v; }
__device__ __forceinline__ uint4 lds128(uint32_t a) { uint4 v; asm volatile("ld.shared.v4.b32 {%0,%1,%2,%3},[%4];" : "=r"(v.x), "=r"(v.y), "=r"(v.z), "=r"(v.w) : "r"(a) : "memory"); return v; }
__device__ __forceinline__ float4 lds128f(uint32_t a) { float4 v; asm volatile("ld.shared.v4.f32 {%0,%1,%2,%3},[%4];" : "=f"(v.x), "=f"(v.y), "=f"(v.z), "=f"(v.w) : "r"(a) : "memory"); return v; }
__device__ __forceinline__ void st_async2(uint32_t a, float x, float y, uint32_t bar) {
  asm volatile("st.async.weak.shared::cluster.mbarrier::complete_tx::bytes.v2.f32 [%0],{%1,%2},[%3];" ::"r"(a), "f"(x), "f"(y), "r"(bar) : "memory");
}
__device__ __forceinline__ void st_async4(uint32_t a, const float (&v)[4], uint32_t bar) {
  asm volatile("st.async.weak.shared::cluster.mbarrier::complete_tx::bytes.v4.f32 [%0],{%1,%2,%3,%4},[%5];" ::"r"(a), "f"(v[0]), "f"(v[1]), "f"(v[2]), "f"(v[3]), "r"(bar) : "memory");
}
__device__ __forceinline__ void st_async4v(uint32_t a, float x, float y, float z, float w, uint32_t bar) {
  asm volatile("st.async.weak.shared::cluster.mbarrier::complete_tx::bytes.v4.f32 [%0],{%1,%2,%3,%4},[%5];" ::"r"(a), "f"(x), "f"(y), "f"(z), "f"(w), "r"(bar) : "memory");
}
__device__ __forceinline__ void st_async4u(uint32_t a, const uint4& v, uint32_t bar) {
  asm volatile("st.async.weak.shared::cluster.mbarrier::complete_tx::bytes.v4.b32 [%0],{%1,%2,%3,%4},[%5];" ::"r"(a), "r"(v.x), "r"(v.y), "r"(v.z), "r"(v.w), "r"(bar) : "memory");
}
__device__ __forceinline__ uint4 ld_relaxed4(const void* p) {
  uint4 v; asm volatile("ld.relaxed.gpu.global.v4.u32 {%0,%1,%2,%3},[%4];" : "=r"(v.x), "=r"(v.y), "=r"(v.z), "=r"(v.w) : "l"(p) : "memory"); return v;
}
__device__ __forceinline__ uint32_t ld_relaxed(const void* p) {
  uint32_t v; asm volatile("ld.relaxed.gpu.global.u32 %0,[%1];" : "=r"(v) : "l"(p) : "memory"); return v;
}
__device__ __forceinline__ void st_relaxed(void* p, uint32_t v) { asm volatile("st.relaxed.gpu.global.b32 [%0],%1;" ::"l"(p), "r"(v) : "memory"); }
__device__ __forceinline__ void st_relaxed4(void* p, uint32_t v) { asm volatile("st.relaxed.gpu.global.v4.b32 [%0],{%1,%1,%1,%1};" ::"l"(p), "r"(v) : "memory"); }

__device__ __forceinline__ uint32_t ld_acquire(const void* p) {
  uint32_t v; asm volatile("ld.acquire.gpu.global.u32 %0,[%1];" : "=r"(v) : "l"(p) : "memory"); return v;
}
__device__ __forceinline__ float4 ld_relaxed4f(const void* p) {
  float4 v; asm volatile("ld.relaxed.gpu.global.v4.f32 {%0,%1,%2,%3},[%4];" : "=f"(v.x), "=f"(v.y), "=f"(v.z), "=f"(v.w) : "l"(p) : "memory"); return v;
}
__device__ __forceinline__ float2 ld_relaxed2f(const void* p) {
  float2 v; asm volatile("ld.relaxed.gpu.global.v2.f32 {%0,%1},[%2];" : "=f"(v.x), "=f"(v.y) : "l"(p) : "memory"); return v;
}
__device__ __forceinline__ void prefetch_l2(const void* p) { asm volatile("prefetch.global.L2 [%0];" ::"l"(p)); }
__device__ __forceinline__ void fence_gpu() { asm volatile("fence.acq_rel.gpu;" ::: "memory"); }
#define FAG 1
__device__ __forceinline__ void fence_async_all() {
  asm volatile("fence.proxy.async.global;" ::: "memory");
}
__device__ __forceinline__ uint32_t* cnt_ptr(int kind, int layer, int b) { return &g_cnt[kind][layer][b][0]; }
#define RELS 1
__device__ __forceinline__ void cnt_signal(int kind, int layer, int b) {
  asm volatile("red.release.gpu.global.add.u32 [%0],1;" ::"l"(cnt_ptr(kind, layer, b)) : "memory");
}
#define ACQW 1
#define SIGF 1
#define HOIST 2
__device__ __forceinline__ void cnt_wait(int kind, int layer, int b, uint32_t target, int& dead) {
  int n = dead ? SPIN_CNT : 0;
  while (ld_acquire(cnt_ptr(kind, layer, b)) < target) { if (++n > SPIN_CNT) { dead = 1; g_err = 10 + kind; break; } }
}

__device__ __forceinline__ uint64_t mkdesc(uint32_t addr, uint32_t lbo, uint32_t sbo) {
  return (uint64_t)((addr & 0x3FFFF) >> 4) | ((uint64_t)(lbo >> 4) << 16) | ((uint64_t)(sbo >> 4) << 32) | ((uint64_t)1 << 62);
}
__device__ __forceinline__ uint64_t mkdesc_ns(uint32_t addr, uint32_t lbo, uint32_t sbo) {
  return (uint64_t)((addr & 0x3FFFF) >> 4) | ((uint64_t)(lbo >> 4) << 16) | ((uint64_t)(sbo >> 4) << 32);
}
__device__ __forceinline__ void wg_fence() { asm volatile("wgmma.fence.sync.aligned;" ::: "memory"); }
__device__ __forceinline__ void wg_commit() { asm volatile("wgmma.commit_group.sync.aligned;" ::: "memory"); }
template <int N> __device__ __forceinline__ void wg_wait() { asm volatile("wgmma.wait_group.sync.aligned %0;" ::"n"(N) : "memory"); }

__device__ __forceinline__ void wgmma_rs16(float (&d)[8], const uint32_t (&a)[4], uint64_t db, int sc) {
  asm volatile("{.reg .pred p; setp.ne.b32 p,%13,0; wgmma.mma_async.sync.aligned.m64n16k16.f32.bf16.bf16 "
               "{%0,%1,%2,%3,%4,%5,%6,%7},{%8,%9,%10,%11},%12,p,1,1,0;}"
               : "+f"(d[0]), "+f"(d[1]), "+f"(d[2]), "+f"(d[3]), "+f"(d[4]), "+f"(d[5]), "+f"(d[6]), "+f"(d[7])
               : "r"(a[0]), "r"(a[1]), "r"(a[2]), "r"(a[3]), "l"(db), "r"(sc));
}
__device__ __forceinline__ void wgmma_rs64(float (&d)[32], const uint32_t (&a)[4], uint64_t db, int sc) {
  asm volatile("{.reg .pred p; setp.ne.b32 p,%37,0; wgmma.mma_async.sync.aligned.m64n64k16.f32.bf16.bf16 "
               "{%0,%1,%2,%3,%4,%5,%6,%7,%8,%9,%10,%11,%12,%13,%14,%15,%16,%17,%18,%19,%20,%21,%22,%23,%24,%25,%26,%27,%28,%29,%30,%31},{%32,%33,%34,%35},%36,p,1,1,0;}"
               : "+f"(d[0]), "+f"(d[1]), "+f"(d[2]), "+f"(d[3]), "+f"(d[4]), "+f"(d[5]), "+f"(d[6]), "+f"(d[7]), "+f"(d[8]), "+f"(d[9]), "+f"(d[10]), "+f"(d[11]), "+f"(d[12]), "+f"(d[13]), "+f"(d[14]), "+f"(d[15]), "+f"(d[16]), "+f"(d[17]), "+f"(d[18]), "+f"(d[19]), "+f"(d[20]), "+f"(d[21]), "+f"(d[22]), "+f"(d[23]), "+f"(d[24]), "+f"(d[25]), "+f"(d[26]), "+f"(d[27]), "+f"(d[28]), "+f"(d[29]), "+f"(d[30]), "+f"(d[31])
               : "r"(a[0]), "r"(a[1]), "r"(a[2]), "r"(a[3]), "l"(db), "r"(sc));
}
__device__ __forceinline__ void wgmma_rt16(float (&d)[8], const uint32_t (&a)[4], uint64_t db, int sc) {
  asm volatile("{.reg .pred p; setp.ne.b32 p,%13,0; wgmma.mma_async.sync.aligned.m64n16k16.f32.bf16.bf16 "
               "{%0,%1,%2,%3,%4,%5,%6,%7},{%8,%9,%10,%11},%12,p,1,1,1;}"
               : "+f"(d[0]), "+f"(d[1]), "+f"(d[2]), "+f"(d[3]), "+f"(d[4]), "+f"(d[5]), "+f"(d[6]), "+f"(d[7])
               : "r"(a[0]), "r"(a[1]), "r"(a[2]), "r"(a[3]), "l"(db), "r"(sc));
}
__device__ __forceinline__ void wgmma_rt80(float (&d)[40], const uint32_t (&a)[4], uint64_t db, int sc) {
  asm volatile("{.reg .pred p; setp.ne.b32 p,%45,0; wgmma.mma_async.sync.aligned.m64n80k16.f32.bf16.bf16 "
               "{%0,%1,%2,%3,%4,%5,%6,%7,%8,%9,%10,%11,%12,%13,%14,%15,%16,%17,%18,%19,%20,%21,%22,%23,%24,%25,%26,%27,%28,%29,%30,%31,%32,%33,%34,%35,%36,%37,%38,%39},{%40,%41,%42,%43},%44,p,1,1,1;}"
               : "+f"(d[0]), "+f"(d[1]), "+f"(d[2]), "+f"(d[3]), "+f"(d[4]), "+f"(d[5]), "+f"(d[6]), "+f"(d[7]), "+f"(d[8]), "+f"(d[9]), "+f"(d[10]), "+f"(d[11]), "+f"(d[12]), "+f"(d[13]), "+f"(d[14]), "+f"(d[15]), "+f"(d[16]), "+f"(d[17]), "+f"(d[18]), "+f"(d[19]), "+f"(d[20]), "+f"(d[21]), "+f"(d[22]), "+f"(d[23]), "+f"(d[24]), "+f"(d[25]), "+f"(d[26]), "+f"(d[27]), "+f"(d[28]), "+f"(d[29]), "+f"(d[30]), "+f"(d[31]), "+f"(d[32]), "+f"(d[33]), "+f"(d[34]), "+f"(d[35]), "+f"(d[36]), "+f"(d[37]), "+f"(d[38]), "+f"(d[39])
               : "r"(a[0]), "r"(a[1]), "r"(a[2]), "r"(a[3]), "l"(db), "r"(sc));
}
__device__ __forceinline__ void wgmma_ts16(float (&d)[8], uint64_t da, uint64_t db, int sc) {
  asm volatile("{.reg .pred p; setp.ne.b32 p,%10,0; wgmma.mma_async.sync.aligned.m64n16k16.f32.bf16.bf16 "
               "{%0,%1,%2,%3,%4,%5,%6,%7},%8,%9,p,1,1,1,0;}"
               : "+f"(d[0]), "+f"(d[1]), "+f"(d[2]), "+f"(d[3]), "+f"(d[4]), "+f"(d[5]), "+f"(d[6]), "+f"(d[7])
               : "l"(da), "l"(db), "r"(sc));
}
__device__ __forceinline__ void wgmma_ts64(float (&d)[32], uint64_t da, uint64_t db, int sc) {
  asm volatile("{.reg .pred p; setp.ne.b32 p,%34,0; wgmma.mma_async.sync.aligned.m64n64k16.f32.bf16.bf16 "
               "{%0,%1,%2,%3,%4,%5,%6,%7,%8,%9,%10,%11,%12,%13,%14,%15,%16,%17,%18,%19,%20,%21,%22,%23,%24,%25,%26,%27,%28,%29,%30,%31},%32,%33,p,1,1,1,0;}"
               : "+f"(d[0]), "+f"(d[1]), "+f"(d[2]), "+f"(d[3]), "+f"(d[4]), "+f"(d[5]), "+f"(d[6]), "+f"(d[7]), "+f"(d[8]), "+f"(d[9]), "+f"(d[10]), "+f"(d[11]), "+f"(d[12]), "+f"(d[13]), "+f"(d[14]), "+f"(d[15]), "+f"(d[16]), "+f"(d[17]), "+f"(d[18]), "+f"(d[19]), "+f"(d[20]), "+f"(d[21]), "+f"(d[22]), "+f"(d[23]), "+f"(d[24]), "+f"(d[25]), "+f"(d[26]), "+f"(d[27]), "+f"(d[28]), "+f"(d[29]), "+f"(d[30]), "+f"(d[31])
               : "l"(da), "l"(db), "r"(sc));
}
__device__ __forceinline__ void wgmma_tt16(float (&d)[8], uint64_t da, uint64_t db, int sc) {
  asm volatile("{.reg .pred p; setp.ne.b32 p,%10,0; wgmma.mma_async.sync.aligned.m64n16k16.f32.bf16.bf16 "
               "{%0,%1,%2,%3,%4,%5,%6,%7},%8,%9,p,1,1,1,1;}"
               : "+f"(d[0]), "+f"(d[1]), "+f"(d[2]), "+f"(d[3]), "+f"(d[4]), "+f"(d[5]), "+f"(d[6]), "+f"(d[7])
               : "l"(da), "l"(db), "r"(sc));
}
__device__ __forceinline__ void wgmma_tt40(float (&d)[20], uint64_t da, uint64_t db, int sc) {
  asm volatile("{.reg .pred p; setp.ne.b32 p,%22,0; wgmma.mma_async.sync.aligned.m64n40k16.f32.bf16.bf16 "
               "{%0,%1,%2,%3,%4,%5,%6,%7,%8,%9,%10,%11,%12,%13,%14,%15,%16,%17,%18,%19},%20,%21,p,1,1,1,1;}"
               : "+f"(d[0]), "+f"(d[1]), "+f"(d[2]), "+f"(d[3]), "+f"(d[4]), "+f"(d[5]), "+f"(d[6]), "+f"(d[7]), "+f"(d[8]), "+f"(d[9]), "+f"(d[10]), "+f"(d[11]), "+f"(d[12]), "+f"(d[13]), "+f"(d[14]), "+f"(d[15]), "+f"(d[16]), "+f"(d[17]), "+f"(d[18]), "+f"(d[19])
               : "l"(da), "l"(db), "r"(sc));
}
__device__ __forceinline__ void wgmma_ss8(float (&d)[4], uint64_t da, uint64_t db, int sc) {
  asm volatile("{.reg .pred p; setp.ne.b32 p,%6,0; wgmma.mma_async.sync.aligned.m64n8k16.f32.bf16.bf16 "
               "{%0,%1,%2,%3},%4,%5,p,1,1,0,0;}"
               : "+f"(d[0]), "+f"(d[1]), "+f"(d[2]), "+f"(d[3])
               : "l"(da), "l"(db), "r"(sc));
}
__device__ __forceinline__ void wgmma_ss32(float (&d)[16], uint64_t da, uint64_t db, int sc) {
  asm volatile("{.reg .pred p; setp.ne.b32 p,%18,0; wgmma.mma_async.sync.aligned.m64n32k16.f32.bf16.bf16 "
               "{%0,%1,%2,%3,%4,%5,%6,%7,%8,%9,%10,%11,%12,%13,%14,%15},%16,%17,p,1,1,0,0;}"
               : "+f"(d[0]), "+f"(d[1]), "+f"(d[2]), "+f"(d[3]), "+f"(d[4]), "+f"(d[5]), "+f"(d[6]), "+f"(d[7]), "+f"(d[8]), "+f"(d[9]), "+f"(d[10]), "+f"(d[11]), "+f"(d[12]), "+f"(d[13]), "+f"(d[14]), "+f"(d[15])
               : "l"(da), "l"(db), "r"(sc));
}
__device__ __forceinline__ void wgmma_st64(float (&d)[32], uint64_t da, uint64_t db, int sc) {
  asm volatile("{.reg .pred p; setp.ne.b32 p,%34,0; wgmma.mma_async.sync.aligned.m64n64k16.f32.bf16.bf16 "
               "{%0,%1,%2,%3,%4,%5,%6,%7,%8,%9,%10,%11,%12,%13,%14,%15,%16,%17,%18,%19,%20,%21,%22,%23,%24,%25,%26,%27,%28,%29,%30,%31},%32,%33,p,1,1,0,1;}"
               : "+f"(d[0]), "+f"(d[1]), "+f"(d[2]), "+f"(d[3]), "+f"(d[4]), "+f"(d[5]), "+f"(d[6]), "+f"(d[7]), "+f"(d[8]), "+f"(d[9]), "+f"(d[10]), "+f"(d[11]), "+f"(d[12]), "+f"(d[13]), "+f"(d[14]), "+f"(d[15]), "+f"(d[16]), "+f"(d[17]), "+f"(d[18]), "+f"(d[19]), "+f"(d[20]), "+f"(d[21]), "+f"(d[22]), "+f"(d[23]), "+f"(d[24]), "+f"(d[25]), "+f"(d[26]), "+f"(d[27]), "+f"(d[28]), "+f"(d[29]), "+f"(d[30]), "+f"(d[31])
               : "l"(da), "l"(db), "r"(sc));
}
__device__ __forceinline__ void wgmma_st128(float (&d)[64], uint64_t da, uint64_t db, int sc) {
  asm volatile("{.reg .pred p; setp.ne.b32 p,%66,0; wgmma.mma_async.sync.aligned.m64n128k16.f32.bf16.bf16 "
               "{%0,%1,%2,%3,%4,%5,%6,%7,%8,%9,%10,%11,%12,%13,%14,%15,%16,%17,%18,%19,%20,%21,%22,%23,%24,%25,%26,%27,%28,%29,%30,%31,%32,%33,%34,%35,%36,%37,%38,%39,%40,%41,%42,%43,%44,%45,%46,%47,%48,%49,%50,%51,%52,%53,%54,%55,%56,%57,%58,%59,%60,%61,%62,%63},%64,%65,p,1,1,0,1;}"
               : "+f"(d[0]), "+f"(d[1]), "+f"(d[2]), "+f"(d[3]), "+f"(d[4]), "+f"(d[5]), "+f"(d[6]), "+f"(d[7]), "+f"(d[8]), "+f"(d[9]), "+f"(d[10]), "+f"(d[11]), "+f"(d[12]), "+f"(d[13]), "+f"(d[14]), "+f"(d[15]), "+f"(d[16]), "+f"(d[17]), "+f"(d[18]), "+f"(d[19]), "+f"(d[20]), "+f"(d[21]), "+f"(d[22]), "+f"(d[23]), "+f"(d[24]), "+f"(d[25]), "+f"(d[26]), "+f"(d[27]), "+f"(d[28]), "+f"(d[29]), "+f"(d[30]), "+f"(d[31]), "+f"(d[32]), "+f"(d[33]), "+f"(d[34]), "+f"(d[35]), "+f"(d[36]), "+f"(d[37]), "+f"(d[38]), "+f"(d[39]), "+f"(d[40]), "+f"(d[41]), "+f"(d[42]), "+f"(d[43]), "+f"(d[44]), "+f"(d[45]), "+f"(d[46]), "+f"(d[47]), "+f"(d[48]), "+f"(d[49]), "+f"(d[50]), "+f"(d[51]), "+f"(d[52]), "+f"(d[53]), "+f"(d[54]), "+f"(d[55]), "+f"(d[56]), "+f"(d[57]), "+f"(d[58]), "+f"(d[59]), "+f"(d[60]), "+f"(d[61]), "+f"(d[62]), "+f"(d[63])
               : "l"(da), "l"(db), "r"(sc));
}

__device__ __forceinline__ void stsm4(uint32_t a, uint32_t r0, uint32_t r1, uint32_t r2, uint32_t r3) {
  asm volatile("stmatrix.sync.aligned.m8n8.x4.shared.b16 [%0],{%1,%2,%3,%4};" ::"r"(a), "r"(r0), "r"(r1), "r"(r2), "r"(r3) : "memory");
}
__device__ __forceinline__ void stsm4t(uint32_t a, uint32_t r0, uint32_t r1, uint32_t r2, uint32_t r3) {
  asm volatile("stmatrix.sync.aligned.m8n8.x4.trans.shared.b16 [%0],{%1,%2,%3,%4};" ::"r"(a), "r"(r0), "r"(r1), "r"(r2), "r"(r3) : "memory");
}
__device__ __forceinline__ void sts64(uint32_t a, uint32_t x, uint32_t y) { asm volatile("st.shared.v2.b32 [%0],{%1,%2};" ::"r"(a), "r"(x), "r"(y) : "memory"); }
__device__ __forceinline__ void st_async2u(uint32_t a, uint32_t x, uint32_t y, uint32_t bar) {
  asm volatile("st.async.weak.shared::cluster.mbarrier::complete_tx::bytes.v2.b32 [%0],{%1,%2},[%3];" ::"r"(a), "r"(x), "r"(y), "r"(bar) : "memory");
}
__device__ __forceinline__ void st_relaxed128(void* p, uint32_t x, uint32_t y, uint32_t z, uint32_t w) {
  asm volatile("{.reg .b128 v; mov.b128 v,{%1,%2,%3,%4}; st.relaxed.gpu.global.b128 [%0],v;}" ::"l"(p), "r"(x), "r"(y), "r"(z), "r"(w) : "memory");
}
__device__ __forceinline__ void st_relaxed64(void* p, uint32_t x, uint32_t y) {
  asm volatile("{.reg .b64 v; mov.b64 v,{%1,%2}; st.relaxed.gpu.global.b64 [%0],v;}" ::"l"(p), "r"(x), "r"(y) : "memory");
}
__device__ __forceinline__ uint4 ld_relaxed128(const void* p) {
  uint4 v;
  asm volatile("{.reg .b128 v; .reg .b64 lo, hi; ld.relaxed.gpu.global.b128 v,[%4]; mov.b128 {lo,hi},v; mov.b64 {%0,%1},lo; mov.b64 {%2,%3},hi;}" : "=r"(v.x), "=r"(v.y), "=r"(v.z), "=r"(v.w) : "l"(p) : "memory");
  return v;
}

__device__ __forceinline__ uint32_t pack_h2(float lo, float hi) {
  uint32_t r; asm("cvt.rn.satfinite.f16x2.f32 %0,%1,%2;" : "=r"(r) : "f"(hi), "f"(lo)); return r;
}
__device__ __forceinline__ void add_h2(float& lo, float& hi, uint32_t u, uint32_t v) {
  float a, b;
  asm("{.reg .b16 l, h; .reg .b32 s; add.rn.f16x2 s,%2,%3; mov.b32 {l,h},s; cvt.f32.f16 %0,l; cvt.f32.f16 %1,h;}" : "=f"(a), "=f"(b) : "r"(u), "r"(v));
  lo += a; hi += b;
}
constexpr int SPIN_TOT = 1 << 22;
__device__ __forceinline__ void mwait(uint32_t bar, uint32_t ph, int& spin) {
  asm volatile("{.reg .pred p, q;\nWAIT_LOOP:\n add.s32 %0,%0,1;\n setp.lt.s32 q,%0,%3;\n mbarrier.try_wait.parity.shared::cta.b64 p,[%1],%2;\n not.pred p,p;\n and.pred q,q,p;\n @q bra.uni WAIT_LOOP;\n}"
               : "+r"(spin) : "r"(bar), "r"(ph), "n"(SPIN_TOT) : "memory");
}
__device__ __forceinline__ int keep(int x) { return __shfl_sync(0xffffffffu, x, threadIdx.x & 31); }
__device__ __forceinline__ uint32_t pin(uint32_t x) { asm volatile("" : "+r"(x)); return x; }
template <typename T> __device__ __forceinline__ T* pinp(T* x) { asm volatile("" : "+l"(x)); return x; }
__device__ __forceinline__ void st_async1u(uint32_t a, uint32_t x, uint32_t bar) {
  asm volatile("st.async.weak.shared::cluster.mbarrier::complete_tx::bytes.b32 [%0],%1,[%2];" ::"r"(a), "r"(x), "r"(bar) : "memory");
}
__device__ __forceinline__ uint32_t lds32(uint32_t a) { uint32_t v; asm volatile("ld.shared.b32 %0,[%1];" : "=r"(v) : "r"(a) : "memory"); return v; }
__device__ __forceinline__ uint2 lds64(uint32_t a) { uint2 v; asm volatile("ld.shared.v2.b32 {%0,%1},[%2];" : "=r"(v.x), "=r"(v.y) : "r"(a) : "memory"); return v; }

__device__ __forceinline__ void ln_row_to_image(const bf16* __restrict__ x, uint8_t* __restrict__ img, int row, int lane) {
  const uint4* src = reinterpret_cast<const uint4*>(x + (size_t)row * DM);
  uint4 v[3];
  v[0] = src[lane]; v[1] = src[lane + 32];
  v[2] = lane < 16 ? src[lane + 64] : make_uint4(0, 0, 0, 0);
  float s = 0.f;
#pragma unroll
  for (int i = 0; i < 3; i++) {
    s += bf_lo(v[i].x) + bf_hi(v[i].x) + bf_lo(v[i].y) + bf_hi(v[i].y) + bf_lo(v[i].z) + bf_hi(v[i].z) + bf_lo(v[i].w) + bf_hi(v[i].w);
  }
#pragma unroll
  for (int o = 16; o > 0; o >>= 1) s += __shfl_xor_sync(0xffffffffu, s, o);
  const float mean = s * (1.f / DM);
  float q = 0.f;
#pragma unroll
  for (int i = 0; i < 3; i++) {
    if (i < 2 || lane < 16) {
      const uint32_t w[4] = {v[i].x, v[i].y, v[i].z, v[i].w};
#pragma unroll
      for (int j = 0; j < 4; j++) { float a = bf_lo(w[j]) - mean, b = bf_hi(w[j]) - mean; q += a * a + b * b; }
    }
  }
#pragma unroll
  for (int o = 16; o > 0; o >>= 1) q += __shfl_xor_sync(0xffffffffu, q, o);
  const float rstd = rsqrtf(q * (1.f / DM) + 1e-5f);
#pragma unroll
  for (int i = 0; i < 3; i++) {
    if (i < 2 || lane < 16) {
      const int c = lane + 32 * i;
      uint4 o;
      o.x = pack_bf16((bf_lo(v[i].x) - mean) * rstd, (bf_hi(v[i].x) - mean) * rstd);
      o.y = pack_bf16((bf_lo(v[i].y) - mean) * rstd, (bf_hi(v[i].y) - mean) * rstd);
      o.z = pack_bf16((bf_lo(v[i].z) - mean) * rstd, (bf_hi(v[i].z) - mean) * rstd);
      o.w = pack_bf16((bf_lo(v[i].w) - mean) * rstd, (bf_hi(v[i].w) - mean) * rstd);
      const size_t off = (size_t)(row >> 5) * 40960 + (c >> 4) * 8192 + ((row >> 3) & 3) * 2048 + ((c >> 3) & 1) * 1024 + (row & 7) * 128 + (((c & 7) ^ (row & 7)) << 4);
      *reinterpret_cast<uint4*>(img + off) = o;
    }
  }
}

#define LN30 1
__global__ void __launch_bounds__(256) k_pre(const bf16* __restrict__ x, const bf16* __restrict__ mem0) {
  const int row = blockIdx.x * 8 + (threadIdx.x >> 5);
  ln_row_to_image(x, g_xn[0], row, threadIdx.x & 31);
  const int gt = blockIdx.x * 256 + threadIdx.x;
  const uint4 sent = make_uint4(SENT, SENT, SENT, SENT);
  uint4* mail = reinterpret_cast<uint4*>(&g_mail[0][0]);
  for (int i = gt; i < 2 * MAIL_BYTES / 16; i += 65536) mail[i] = sent;
  uint4* mb = reinterpret_cast<uint4*>(&g_mbuf[0][0]);
  for (int i = gt; i < NSTEP * 1280; i += 65536) {
    const int p = i % 1280, st = i / 1280;
    uint4 v = sent;
    if (st == 0 || (st == LAG && (p & 8))) v = *reinterpret_cast<const uint4*>(mem0 + (p & 7) * DM + (p >> 4) * 8);
    mb[i] = v;
  }
  if (gt < NSTEP * 192) reinterpret_cast<uint4*>(&g_flag[0][0])[gt] = gt < 192 ? make_uint4(0, 0, 0, 0) : sent;
  if (gt < 16 * 128 * 8) reinterpret_cast<uint4*>(&g_stats[0][0][0])[gt] = sent;
  if (gt < 6 * 2 * 16 * 8) reinterpret_cast<uint4*>(&g_cnt[0][0][0][0])[gt] = make_uint4(0, 0, 0, 0);
}

namespace C {
constexpr int NKR = 37;
constexpr int OFF_WQ = 0, OFF_WK = 81920;
constexpr int OFF_YO = 163840, OFF_YV = OFF_YO + 6144;
constexpr int OFF_M = 176128;
__host__ __device__ constexpr int og_off(int c) { return c ? OFF_M + 14336 + c * 2048 : 229376; }
constexpr int OFF_KT = 196608;
constexpr int OFF_XT = OFF_KT + 10240;
constexpr int OFF_VT = OFF_XT + 7168;
constexpr int OFF_XM = OFF_VT + 11392;
constexpr int KS = 1280, VS = 1408;
__host__ __device__ constexpr int slot_off(int p) { return p == 2 ? OFF_M : OFF_KT + (p % 3) * 16384; }
constexpr int OFF_BAR = 231552;
constexpr int OFF_SAFE = OFF_BAR + 160;
constexpr int OFF_TS = OFF_BAR + 256;
constexpr int SMEM = 232448;
constexpr uint32_t SB0 = 1024;
constexpr int BAR_F = OFF_BAR, BAR_E = OFF_BAR + 40, BAR_M = OFF_BAR + 80, BAR_MOK = OFF_BAR + 88, BAR_XM = OFF_BAR + 96, BAR_XF = OFF_BAR + 104,
              BAR_XT = OFF_BAR + 112, BAR_MF = OFF_BAR + 120, BAR_OG = OFF_BAR + 128, BAR_W = OFF_BAR + 136, FLG_REDO = OFF_BAR + 144;
constexpr int NB_PRO = 1, NB_RD = 2, NB_MR = 3, NB_QK = 4, NB_SM = 5, NB_VA = 6, NB_VQ = 7, NB_A = 8, NB_Q = 9, NB_C = 10, NB_WQ = 11, NB_QI = 12, NB_SI = 13, NB_WV = 14;
#define B1 300
#define B2 400
#define FLP 1
#define QIE 4
#define SIE 2
#define WOE 1
#define OGF 0
#define VSP 8
#define RFK 5
#define PFD 3
#define WOL 0
#define NOWORK 0
constexpr float SCL = 0.07216878364870322f * 1.4426950408889634f / 256;
}

#define CBAR_SYNC(id, n) bar_sync(id, n)
#define CBAR_ARRIVE(id, n) bar_arrive(id, n)

__device__ __forceinline__ uint64_t wdesc(int off) { return mkdesc(C::SB0 + off, 8192, 1024); }
__device__ __forceinline__ uint64_t mdesc(int k) { return mkdesc_ns(C::SB0 + C::OFF_M + k * 512, 256, 128); }
__device__ __forceinline__ uint64_t tdesc(int k) { return mkdesc(C::SB0 + C::slot_off(k >> 3) + ((k >> 2) & 1) * 1024 + (k & 3) * 32, 16, 2048); }

__device__ __forceinline__ int dh_row(int n) { return (n & ~63) + (n & 32) + ((n >> 1) & 3) * 8 + ((n >> 3) & 3) * 2 + (n & 1); }
template <bool PERM>
__device__ __forceinline__ void load_weights_rs(uint32_t (&wf)[C::NKR][4], uint32_t sb, int stage, int yoff, int tid0) {
  using namespace C;
  const int i = (tid0 >> 3) & 3, n0 = (tid0 & 7) + (i >> 1) * 8;
  const int chunk = 2 * ((tid0 >> 5) & 3) + (i & 1);
  const int r0 = PERM ? dh_row(n0) : n0, r1 = PERM ? dh_row(n0 + 16) : n0 + 16;
  const uint32_t a0 = sb + stage + r0 * 128 + ((chunk ^ (r0 & 7)) << 4), a1 = sb + stage + r1 * 128 + ((chunk ^ (r1 & 7)) << 4);
#pragma unroll
  for (int k = 0; k < NKR; k++) ldsm4t(wf[k], ((k & 1) ? a1 : a0) + (k >> 1) * 4096);
#pragma unroll
  for (int k = 0; k < 40 - NKR; k++) {
    const int n = (NKR + k) * 16 + ((tid0 & 127) >> 3), r = PERM ? dh_row(n) : n, c = tid0 & 7;
    sts128(sb + yoff + (n - NKR * 16) * 128 + ((c ^ (n & 7)) << 4), lds128(sb + stage + r * 128 + ((c ^ (r & 7)) << 4)));
  }
  fence_async();
  CBAR_SYNC(NB_PRO, 384);
}
template <int STRIDE>
__device__ __forceinline__ void store_mem(const float (&d)[8], uint32_t base, int tid) {
  const int m = (tid >> 3) & 3;
  stsm4(base + (((tid >> 5) & 3) * 2 + (m & 1)) * STRIDE + (m >> 1) * 640 + (tid & 7) * 16, pack_bf16(d[0], d[1]), pack_bf16(d[2], d[3]),
        pack_bf16(d[4], d[5]), pack_bf16(d[6], d[7]));
}

__device__ __forceinline__ void load_pair(uint32_t sb, int i, int p, uint32_t slot, uint32_t bar, uint32_t ph, int& spin) {
  using namespace C;
  const uint8_t* s0 = g_xn[0] + (size_t)i * 40960 + p * 8192;
  const uint8_t* s1 = g_xn[NOWORK ? 0 : 1] + (size_t)(i - LAG) * 40960 + p * 8192;
  const uint8_t* sa = pinp(i < NSEG ? s0 : s1);
  const uint8_t* sc = pinp(i >= LAG ? s1 : s0);
  const uint32_t dst = pin(sb + slot), fb = pin(sb + BAR_F + 8 * p);
  mwait(bar, ph, spin);
  bulk_g2s_mc(dst, sa, 8192, fb);
  bulk_g2s_mc(dst + 8192, sc, 8192, fb);
}
__device__ __forceinline__ void first_fill(uint32_t sb, int i, int rank, int& spin) {
  using namespace C;
  const int s1 = i - LAG;
  if (!NOWORK && s1 >= 0 && (s1 & 3) == 0) {
    while (ld_acquire(cnt_ptr(CN_X, 0, s1 >> 2)) < 5 && spin < SPIN_TOT) spin += 16;
    fence_async_all();
  }
  load_pair(sb, i, rank, rank == 2 ? OFF_M : OFF_KT + rank * 16384, sb + BAR_E + 8 * rank, (i - 1) & 1, spin);
}
__device__ __forceinline__ void release_round(uint32_t sb, int p, int tid) {
  using namespace C;
  const int lane = tid & 31;
  if (p < 2) { if (lane == 0) mbar_arrive_cluster(mapa(sb, p) + BAR_E + 8 * (3 + p)); }
  else if (lane < 3) mbar_arrive_cluster(mapa(sb, lane) + BAR_MOK);
}

template <int K0, int K1>
__device__ __forceinline__ void v_mem_pass(float (&d)[8], const uint32_t (&wf)[C::NKR][4]) {
  using namespace C;
  wg_fence();
#pragma unroll
  for (int k = K0; k < K1; k++) {
    if (k < NKR) wgmma_rs16(d, wf[k < NKR ? k : 0], mdesc(k), k != 32);
    else wgmma_ts16(d, wdesc(OFF_YV + (k - NKR) * 2048), mdesc(k), 1);
  }
  wg_commit();
}
__device__ __forceinline__ void chain_v(const uint32_t sb, const int tid0, const int cta, const int rank) {
  using namespace C;
  asm volatile("setmaxnreg.inc.sync.aligned.u32 208;");
  int spin = 0;
  uint32_t wf[NKR][4];
  if (tid0 == 256) first_fill(sb, 0, rank, spin);
  __syncwarp();
  mwait(sb + BAR_W, 0, spin);
  for (int it = tid0 & 127; it < 1280; it += 128) {
    const uint32_t base = sb + OFF_WK + (it >> 1) * 128;
    const int sw = ((it >> 1) & 7) ^ ((it & 1) * 4);
    const uint4 u0 = lds128(base + (sw << 4)), u1 = lds128(base + ((sw ^ 1) << 4)), u2 = lds128(base + ((sw ^ 2) << 4)), u3 = lds128(base + ((sw ^ 3) << 4));
    sts128(base + (sw << 4), make_uint4(u0.x, u1.x, u2.x, u3.x)); sts128(base + ((sw ^ 1) << 4), make_uint4(u0.y, u1.y, u2.y, u3.y));
    sts128(base + ((sw ^ 2) << 4), make_uint4(u0.z, u1.z, u2.z, u3.z)); sts128(base + ((sw ^ 3) << 4), make_uint4(u0.w, u1.w, u2.w, u3.w));
  }
  bar_sync(NB_RD, 128);
  load_weights_rs<false>(wf, sb, OFF_WK, OFF_YV, tid0);
#pragma unroll 1
  for (int i = 0; i < NSTEP; i++) {
    {
      float d[32];
      if (i > 0) CBAR_SYNC(NB_WV, 256);
#pragma unroll
      for (int p = 0; p < 5; p++) {
        mwait(sb + BAR_F + 8 * p, i & 1, spin);
        TS(i, 25 + p);
        wg_fence();
#pragma unroll
        for (int k = 8 * p; k < 8 * p + 8; k++) {
          if (k < NKR) wgmma_rs64(d, wf[k < NKR ? k : 0], tdesc(k), k);
          else wgmma_ts64(d, wdesc(OFF_YV + (k - NKR) * 2048), tdesc(k), 1);
          if (k == 8 * p + 1 && p >= 1 && p <= 3) {
            wg_commit(); wg_wait<1>();
            release_round(sb, p - 1, fresh(tid0));
            wg_fence();
          }
          if (k == 8 * p + RFK && (p == 1 || p == 2)) {
            wg_commit();
            if (rank == p - 1 && tid0 == 256) load_pair(sb, i, p + 2, slot_off(p + 2), sb + BAR_E + 8 * (p + 2), i & 1, spin);
            __syncwarp();
            wg_fence();
          }
        }
        wg_commit();
      }
      wg_wait<0>();
      TS(i, 23);
      CBAR_SYNC(NB_RD, 256);
      const int tid = fresh(tid0) & 127, m = (tid >> 3) & 3;
      if (tid >= 96) {
        if (tid < 101) { if (i + 1 < NSTEP) mbar_expect_tx(sb + BAR_F + 8 * (tid - 96), 16384); }
        else if (tid == 101) mbar_expect_tx(sb + BAR_XM, 2560);
        else if (tid == 102) mbar_expect_tx(sb + BAR_XT, 7168);
        else if (tid == 103) mbar_expect_tx(sb + BAR_OG, 4096);
        else if (tid < 106) mbar_arrive_cluster(mapa(sb, (rank + tid - 103) % 3) + BAR_XF);
        __syncwarp();
      }
      const uint32_t a = sb + OFF_VT + 256 + ((tid >> 5) * 2 + (m & 1)) * VS + (m >> 1) * 128 + (tid & 7) * 16;
#pragma unroll
      for (int s = 0; s < 4; s++)
        stsm4(a + (s & 1) * 256 + (s >> 1) * 640, pack_bf16(d[8 * s], d[8 * s + 1]), pack_bf16(d[8 * s + 2], d[8 * s + 3]),
              pack_bf16(d[8 * s + 4], d[8 * s + 5]), pack_bf16(d[8 * s + 6], d[8 * s + 7]));
      if (tid < 72) sts128(sb + OFF_VT + (tid >> 3) * VS + (tid & 7) * 16, make_uint4(0, 0, 0, 0));
      fence_async();
    }
    mwait(sb + BAR_XF, i & 1, spin);
    CBAR_ARRIVE(NB_QK, 384);
    CBAR_SYNC(NB_QI, 256);
    float d[8];
    v_mem_pass<32, 40>(d, wf);
    CBAR_SYNC(NB_SM, 256);
    wg_wait<0>();
    if (__builtin_expect(lds32(sb + FLG_REDO), 0)) { v_mem_pass<32, 40>(d, wf); wg_wait<0>(); }
    if ((tid0 & 31) < 2) mbar_arrive_cluster(mapa(sb, (rank + 1 + (tid0 & 1)) % 3) + BAR_MF);
    v_mem_pass<0, 32>(d, wf);
    wg_wait<0>();
    TS(i, 24);
    const int tid = fresh(tid0);
    if ((tid & 31) == 0) mbar_arrive_cluster(mapa(sb, 2) + BAR_E + 16);
    store_mem<VS>(d, sb + OFF_VT + 128, tid);
    fence_async();
    CBAR_ARRIVE(NB_VA, 256);
    CBAR_ARRIVE(NB_VQ, 256);
    if (tid == 256) {
      if (i + 1 < NSTEP) { first_fill(sb, i + 1, rank, spin); TS1(i + 1, 37); }
    } else if (tid >= 288 && tid < 295) {
      const int lane = tid & 31, ip = i + PFD;
      if (cta < 80 && ip < NSTEP) {
        if (lane < 2) prefetch_l2(g_mbuf[ip] + (cta * 2 + lane) * 128);
        else if (lane == 6) { if (cta < 22) prefetch_l2(&g_flag[ip][cta * 32]); }
        else if (ip < NSEG) prefetch_l2(g_xn[0] + (size_t)ip * 40960 + (cta * 4 + lane - 2) * 128);
      }
    }
    TS_FLUSH(i - 1);
    __syncwarp();
  }
  if (spin >= SPIN_TOT) g_err = 3;
}

__device__ __forceinline__ float quad_max(float x) {
  const float a = __shfl_xor_sync(0xffffffffu, x, 1), b = __shfl_xor_sync(0xffffffffu, x, 2), c = __shfl_xor_sync(0xffffffffu, x, 3);
  return fmaxf(fmaxf(x, a), fmaxf(b, c));
}
__device__ __forceinline__ float quad_sum(float x) {
  const float a = __shfl_xor_sync(0xffffffffu, x, 1), b = __shfl_xor_sync(0xffffffffu, x, 2), c = __shfl_xor_sync(0xffffffffu, x, 3);
  return (x + a) + (b + c);
}
__device__ __forceinline__ float max10(const float (&y)[10]) {
  return fmaxf(fmaxf(fmaxf(fmaxf(y[0], y[1]), fmaxf(y[2], y[3])), fmaxf(fmaxf(y[4], y[5]), fmaxf(y[6], y[7]))), fmaxf(y[8], y[9]));
}
__device__ __forceinline__ float sum10(const float (&y)[10]) {
  return (((y[0] + y[1]) + (y[2] + y[3])) + ((y[4] + y[5]) + (y[6] + y[7]))) + (y[8] + y[9]);
}
__device__ __forceinline__ float rcp(float x) { float y; asm("rcp.approx.ftz.f32 %0,%1;" : "=f"(y) : "f"(x)); return y; }

__device__ __forceinline__ void signal_o(int i) {
  const int s1 = i - LAG;
  if (i < NSEG && (i & 3) == 3) cnt_signal(CN_O, 0, i >> 2);
  if (s1 >= 0 && (s1 & 3) == 3) cnt_signal(CN_O, 1, s1 >> 2);
}

__device__ __forceinline__ void chain_q(const CUtensorMap& tmWq, const CUtensorMap& tmWk, const uint32_t sb, const int tid0, const int cta, const int rank) {
  using namespace C;
  asm volatile("setmaxnreg.dec.sync.aligned.u32 96;");
  int spin = 0;
  CBAR_SYNC(NB_PRO, 384);
  PTS(5);
  if (tid0 == 128) {
    const int col = (cta / 3) * DH + rank * 64;
    mbar_expect_tx(sb + BAR_W, 163840);
    for (int i = 0; i < 5; i++) {
      tma2d(sb + OFF_WQ + i * 16384, &tmWq, col, i * 128, sb + BAR_W);
      tma2d(sb + OFF_WK + i * 16384, &tmWk, col, i * 128, sb + BAR_W);
    }
  }
  mwait(sb + BAR_W, 1, spin);
  PTS(6);
#pragma unroll 1
  for (int i = 0; i < NSTEP; i++) {
    const int ph = i & 1;
    uint32_t qf[4][4];
    {
      float d[64];
#pragma unroll
      for (int p = 0; p < 5; p++) {
        mwait(sb + BAR_F + 8 * p, ph, spin);
        if (p == 0) TS(i, 0);
        wg_fence();
#pragma unroll
        for (int k = 8 * p; k < 8 * p + 8; k++) {
          wgmma_st128(d, tdesc(k), mkdesc(SB0 + OFF_WQ + k * 2048, OFF_WK - OFF_WQ, 1024), k);
          if (k == 8 * p + 1 && p >= 1 && p <= 3) {
            wg_commit(); wg_wait<1>();
            release_round(sb, p - 1, fresh(tid0));
            wg_fence();
          }
        }
        wg_commit();
      }
      wg_wait<0>();
      TS(i, 1);
      CBAR_SYNC(NB_RD, 256);
      TSB(i, 2);
      const int tid = fresh(tid0), w = (tid >> 5) & 3, m = (tid >> 3) & 3;
      const uint32_t a = sb + OFF_KT + (m >> 1) * KS + (1 + 5 * (w >> 1) + 2 * (w & 1) + (m & 1)) * 128 + (tid & 7) * 16;
#pragma unroll
      for (int s = 0; s < 4; s++)
        stsm4t(a + s * 2 * KS, pack_bf16(d[32 + 8 * s], d[33 + 8 * s]), pack_bf16(d[34 + 8 * s], d[35 + 8 * s]),
               pack_bf16(d[36 + 8 * s], d[37 + 8 * s]), pack_bf16(d[38 + 8 * s], d[39 + 8 * s]));
      fence_async();
      CBAR_ARRIVE(NB_QK, 384);
      if (tid == 224 && i > 0) signal_o(i - 1);
      __syncwarp();
#pragma unroll
      for (int kk = 0; kk < 4; kk++)
#pragma unroll
        for (int j = 0; j < 4; j++) asm volatile("cvt.rn.bf16x2.f32 %0,%1,%2;" : "=r"(qf[kk][j]) : "f"(d[8 * kk + 2 * j + 1]), "f"(d[8 * kk + 2 * j]));
    }
    CBAR_SYNC(NB_SI, 256);
    uint32_t pf[5][4];
    float s0, s1;
    {
      float y0[10], y1[10];
      const int tid = fresh(tid0), lane = tid & 31, u = (tid >> 5) & 1;
      const bool c1 = tid & 64;
      {
        float x[40];
        wg_fence();
#pragma unroll
        for (int kk = 0; kk < 4; kk++) wgmma_rt80(x, qf[kk], mkdesc_ns(SB0 + OFF_KT + kk * 2 * KS, KS, 128), kk);
        wg_commit();
        wg_wait<0>();
#pragma unroll
        for (int j = 0; j < 5; j++) {
          y0[2 * j] = (c1 ? x[20 + 4 * j] : x[4 * j]) * SCL; y0[2 * j + 1] = (c1 ? x[21 + 4 * j] : x[4 * j + 1]) * SCL;
          y1[2 * j] = (c1 ? x[22 + 4 * j] : x[4 * j + 2]) * SCL; y1[2 * j + 1] = (c1 ? x[23 + 4 * j] : x[4 * j + 3]) * SCL;
        }
      }
      TS(i, 17);
      const uint32_t xo = OFF_XT + (c1 ? 1792 : 0) + u * 640 + lane * 16, x2 = xo + u * 512 + 512 - lane * 12;
      {
        const uint4 h0 = make_uint4(pack_h2(y0[0], y0[1]), pack_h2(y0[2], y0[3]), pack_h2(y1[0], y1[1]), pack_h2(y1[2], y1[3]));
        const uint4 h1 = make_uint4(pack_h2(y0[4], y0[5]), pack_h2(y0[6], y0[7]), pack_h2(y1[4], y1[5]), pack_h2(y1[6], y1[7]));
        const uint32_t h2 = u ? pack_h2(y1[8], y1[9]) : h1.z;
#pragma unroll
        for (int dd = 0; dd < 2; dd++) {
          const uint32_t rb = mapa(sb, (rank + 1 + dd) % 3), ro = rb + (1 - dd) * 3584;
          st_async4u(ro + xo, h0, rb + BAR_XT);
          if (u) st_async4u(ro + xo + 512, h1, rb + BAR_XT);
          st_async1u(ro + x2, h2, rb + BAR_XT);
        }
      }
      TS(i, 18);
      const int lim = 16 * u + (lane >> 2) + 8 - 2 * (lane & 3);
#pragma unroll
      for (int j = 1; j < 5; j++) {
        if (8 * j > lim) y0[2 * j] = -INFINITY;
        if (8 * j + 1 > lim) y0[2 * j + 1] = -INFINITY;
        if (8 * j - 8 > lim) y1[2 * j] = -INFINITY;
        if (8 * j - 7 > lim) y1[2 * j + 1] = -INFINITY;
      }
      mwait(sb + BAR_XT, ph, spin);
      TS(i, 19);
      {
        const uint4 u0 = lds128(sb + xo), v0 = lds128(sb + xo + 3584);
        const uint32_t u2 = lds32(sb + x2), v2 = lds32(sb + x2 + 3584);
        uint4 u1 = make_uint4(0, 0, u2, 0), v1 = make_uint4(0, 0, v2, 0);
        if (u) { u1 = lds128(sb + xo + 512); v1 = lds128(sb + xo + 512 + 3584); }
        __syncwarp();
        if (lane == 0) mbar_arrive_cluster(mapa(sb, 0) + BAR_E);
        add_h2(y0[0], y0[1], u0.x, v0.x); add_h2(y0[2], y0[3], u0.y, v0.y); add_h2(y1[0], y1[1], u0.z, v0.z); add_h2(y1[2], y1[3], u0.w, v0.w);
        add_h2(y0[4], y0[5], u1.x, v1.x); add_h2(y0[6], y0[7], u1.y, v1.y); add_h2(y1[4], y1[5], u1.z, v1.z); add_h2(y1[6], y1[7], u1.w, v1.w);
        add_h2(y1[8], y1[9], u2, v2);
      }
      y0[8] = y0[0]; y0[9] = y0[1];
      const float m0 = quad_max(max10(y0)) * -256.f, m1 = quad_max(max10(y1)) * -256.f;
      s0 = 0.f; s1 = 0.f;
#pragma unroll
      for (int j = 0; j < 5; j++) {
        const uint32_t p0 = j < 4 ? pack_bf16(ex2(fmaf(y0[2 * j], 256.f, m0)), ex2(fmaf(y0[2 * j + 1], 256.f, m0))) : 0u;
        const uint32_t p1 = pack_bf16(ex2(fmaf(y1[2 * j], 256.f, m1)), ex2(fmaf(y1[2 * j + 1], 256.f, m1)));
        s0 += bf_lo(p0) + bf_hi(p0); s1 += bf_lo(p1) + bf_hi(p1);
        pf[j >> 1][2 * (j & 1)] = c1 ? 0u : p0; pf[j >> 1][2 * (j & 1) + 1] = c1 ? 0u : p1;
        pf[(j + 5) >> 1][2 * ((j + 5) & 1)] = c1 ? p0 : 0u; pf[(j + 5) >> 1][2 * ((j + 5) & 1) + 1] = c1 ? p1 : 0u;
      }
    }
    CBAR_SYNC(NB_VQ, 256);
    TSB(i, 20);
    {
      float o[32];
      wg_fence();
#pragma unroll
      for (int q = 0; q < 5; q++) wgmma_rs64(o, pf[q], mkdesc_ns(SB0 + OFF_VT + 128 + q * 256, 128, VS), q);
      wg_commit();
      s0 = rcp(quad_sum(s0)); s1 = rcp(quad_sum(s1));
      const int tid = fresh(tid0), g = (tid >> 2) & 7, c = (tid >> 6) & 1, sg = i - c * LAG;
      uint8_t* op = pinp(g_o[c] + ((size_t)(sg >> 1) * 96 + cta) * 8192 + (sg & 1) * 4096 + (((tid >> 5) & 1) * 16 + g) * 128);
      const uint32_t o0 = pin(((tid & 3) ^ g) << 4), live = pin(sg >= 0 && sg < NSEG);
      wg_wait<0>();
      TS(i, 21);
      if ((tid & 31) == 0) mbar_arrive_cluster(mapa(sb, 1) + BAR_E + 8);
      uint4 ov[4];
#pragma unroll
      for (int h = 0; h < 2; h++) {
        const float* x = o + 16 * h;
        ov[2 * h] = make_uint4(pin(pack_bf16(x[0] * s0, x[1] * s0)), pin(pack_bf16(x[4] * s0, x[5] * s0)), pin(pack_bf16(x[8] * s0, x[9] * s0)), pin(pack_bf16(x[12] * s0, x[13] * s0)));
        ov[2 * h + 1] = make_uint4(pin(pack_bf16(x[2] * s1, x[3] * s1)), pin(pack_bf16(x[6] * s1, x[7] * s1)), pin(pack_bf16(x[10] * s1, x[11] * s1)), pin(pack_bf16(x[14] * s1, x[15] * s1)));
      }
      TS(i, 22);
      if (i + 1 < NSTEP) CBAR_SYNC(NB_WQ, 256);
      if (live) {
#pragma unroll
        for (int h = 0; h < 4; h++) *reinterpret_cast<uint4*>(op + (h & 1) * 1024 + (o0 ^ ((h >> 1) * 64))) = ov[h];
      }
    }
  }
  CBAR_SYNC(NB_Q, 128);
  if (tid0 == 224) signal_o(NSTEP - 1);
  if (spin >= SPIN_TOT) g_err = 2;
}

template <int NL>
__device__ __forceinline__ void poll_add(const uint8_t* mb, uint32_t tag, float (&f)[8], uint32_t* flag, int& n, int& spin) {
  uint4 x[NL];
#pragma unroll
  for (int i = 0; i < NL; i++) x[i] = ld_relaxed128(mb + i * 512);
  while (true) {
    bool bad = false;
#pragma unroll
    for (int i = 0; i < NL; i++)
      if (((x[i].x ^ tag) | (NL == 6 ? x[i].z ^ tag : 0u)) & 1) { bad = true; x[i] = ld_relaxed128(mb + i * 512); }
    n++;
    spin += 16;
    if (!__any_sync(0xffffffffu, bad && spin < SPIN_TOT)) break;
  }
  if (FLP == 0 && flag) st_relaxed(flag, 0);
#pragma unroll
  for (int i = 0; i < NL; i++) {
    const uint32_t u[4] = {x[i].x, x[i].y, x[i].z, x[i].w};
#pragma unroll
    for (int j = 0; j < 4; j++) {
      if (i == 0) { f[2 * j] = bf_lo(u[j]); f[2 * j + 1] = bf_hi(u[j]); }
      else { f[2 * j] += bf_lo(u[j]); f[2 * j + 1] += bf_hi(u[j]); }
    }
  }
}

template <int B, int SLOT>
__device__ __forceinline__ void wo_block(float (&acc)[8], const uint32_t (&wf)[C::NKR][4]) {
  using namespace C;
#pragma unroll
  for (int kk = 0; kk < 4; kk++) {
    const int k = 4 * B + kk;
    const uint64_t db = mkdesc_ns(SB0 + og_off(SLOT) + kk * 512, 256, 128);
    if (k < NKR) wgmma_rt16(acc, wf[k < NKR ? k : 0], db, SLOT | kk);
    else wgmma_tt16(acc, wdesc(OFF_YO + (k - NKR) * 2048), db, 1);
  }
}

__device__ __forceinline__ void chain_a(const uint32_t sb, const int tid0, const int cta, const int rank) {
  using namespace C;
  asm volatile("setmaxnreg.inc.sync.aligned.u32 200;");
  int spin = 0;
  uint32_t wf[NKR][4];
  mwait(sb + BAR_W, 0, spin);
  for (int it = tid0; it < 2560; it += 128) {
    const int row = it >> 2, q = it & 3;
    const uint32_t base = sb + OFF_WQ + row * 128;
    const uint32_t a0 = base + (((2 * q) ^ (row & 7)) << 4), a1 = base + (((2 * q + 1) ^ (row & 7)) << 4);
    const uint4 u = lds128(a0), v = lds128(a1);
    sts128(a0, make_uint4(__byte_perm(u.x, u.y, 0x5410), __byte_perm(u.z, u.w, 0x5410), __byte_perm(v.x, v.y, 0x5410), __byte_perm(v.z, v.w, 0x5410)));
    sts128(a1, make_uint4(__byte_perm(u.x, u.y, 0x7632), __byte_perm(u.z, u.w, 0x7632), __byte_perm(v.x, v.y, 0x7632), __byte_perm(v.z, v.w, 0x7632)));
  }
  CBAR_SYNC(NB_A, 128);
  load_weights_rs<true>(wf, sb, OFF_WQ, OFF_YO, tid0);

#pragma unroll 1
  for (int i = -1; i < NSTEP; i++) {
    const int ph = i & 1;
    if (i >= 0) {
      if (i == 0) mwait(sb + BAR_W, 1, spin);
      mwait(sb + BAR_M, ph, spin);
      TS(i, 3);
      {
        float x[20];
        int redo = 0;
      retry:
        bool bad;
        {
          float dq[8], dk[8];
          wg_fence();
#pragma unroll
          for (int k = 0; k < 40; k++) wgmma_ts16(dq, wdesc(OFF_WQ + k * 2048), mdesc(k), k);
          wg_commit();
#pragma unroll
          for (int k = 0; k < 40; k++) {
            if (k == 40 - QIE && !redo) CBAR_ARRIVE(NB_QI, 256);
            wgmma_ts16(dk, wdesc(OFF_WK + k * 2048), mdesc(k), k);
          }
          wg_commit();
          const int m = (tid0 >> 3) & 3, dg = (tid0 >> 5) * 2 + (m & 1);
          const uint32_t ka = sb + OFF_KT + dg * KS + (m >> 1) * 640 + (tid0 & 7) * 16;
          wg_wait<1>();
          const float chk = (dq[0] + dq[1]) + (dq[4] + dq[5]);
          const uint32_t q0 = pack_bf16(dq[0], dq[1]), q1 = pack_bf16(dq[2], dq[3]), q2 = pack_bf16(dq[4], dq[5]), q3 = pack_bf16(dq[6], dq[7]);
          if (!redo) CBAR_SYNC(NB_QK, 384);
          stsm4(ka + dg * (VS - KS) + (OFF_VT + 128 - OFF_KT), q0, q1, q2, q3);
          sts32(sb + FLG_REDO, redo);
          wg_wait<0>();
          TS(i, 4);
          stsm4(ka, pack_bf16(dk[0], dk[1]), pack_bf16(dk[2], dk[3]), pack_bf16(dk[4], dk[5]), pack_bf16(dk[6], dk[7]));
          fence_async();
          bad = bar_red_or(NB_C, 128, chk != chk && !redo);
        }
        TSB(i, 5);
        wg_fence();
#pragma unroll
        for (int kk = 0; kk < 4; kk++) wgmma_tt40(x, mkdesc_ns(SB0 + OFF_VT + 128 + kk * 2 * VS, VS, 640), mkdesc_ns(SB0 + OFF_KT + kk * 2 * KS, KS, 128), kk);
#pragma unroll
        for (int kk = 0; kk < 4; kk++) {
          if (kk == 4 - SIE && !bad) CBAR_ARRIVE(NB_SI, 256);
          wgmma_tt40(x, mkdesc_ns(SB0 + OFF_VT + kk * 2 * VS, VS, 384), mkdesc_ns(SB0 + OFF_KT + 640 + kk * 2 * KS, KS, 128), 1);
        }
        wg_commit();
        if (__builtin_expect(bad, 0)) {
          wg_wait<0>();
#pragma unroll 1
          for (int k = 0; k < 10; k++) {
            uint4 v = lds128(sb + OFF_M + tid0 * 16 + k * 2048);
            if (v.x == SENT || v.y == SENT || v.z == SENT || v.w == SENT) {
              do { v = ld_relaxed4(g_mbuf[i] + tid0 * 16 + k * 2048); spin += 16; } while ((v.x == SENT || v.y == SENT || v.z == SENT || v.w == SENT) && spin < SPIN_TOT);
              sts128(sb + OFF_M + tid0 * 16 + k * 2048, v);
            }
          }
          fence_async();
          bar_sync(NB_C, 128);
          redo = fresh(1);
          goto retry;
        }
        TSV(i, 36, redo);
        const int tid = fresh(tid0), lane = tid & 31, w = tid >> 5;
        const uint32_t xo = OFF_XM + w * 1280 + lane * 16, x1 = OFF_XM + w * 1280 + lane * 4;
        const uint32_t rb1 = mapa(sb, (rank + 1) % 3), rb2 = mapa(sb, (rank + 2) % 3);
        const uint32_t ra = pin(rb1 + xo + 640), rb = pin(rb1 + x1 + 1152), rc = pin(rb2 + xo), rd = pin(rb2 + x1 + 512);
        const uint32_t la = pin(sb + xo), lb = pin(sb + x1);
        const uint32_t pa = pin(sb + OFF_XM + w * 1280 + (lane & 7) * 4 + (lane & 8) * 8 + (lane & 16) * 2);
        wg_wait<0>();
        TS(i, 6);
        if (w < 2) {
          float y[10];
#pragma unroll
          for (int j = 0; j < 5; j++) { y[2 * j] = x[4 * j] * SCL; y[2 * j + 1] = x[4 * j + 1] * SCL; }
          const uint4 h0 = make_uint4(pack_h2(y[0], y[1]), pack_h2(y[2], y[3]), pack_h2(y[4], y[5]), pack_h2(y[6], y[7]));
          const uint32_t h1 = pack_h2(y[8], y[9]);
          st_async4u(ra, h0, rb1 + BAR_XM);
          st_async4u(rc, h0, rb2 + BAR_XM);
          st_async1u(rb, h1, rb1 + BAR_XM);
          st_async1u(rd, h1, rb2 + BAR_XM);
          CBAR_ARRIVE(NB_SM, 256);
          if (lane == 0) mbar_arrive_cluster(mapa(sb, 0) + BAR_E);
          TS(i, 7);
          mwait(sb + BAR_XM, ph, spin);
          TS(i, 8);
          const uint4 u0 = lds128(la), v0 = lds128(la + 640);
          const uint32_t u1 = lds32(lb + 512), v1 = lds32(lb + 1152);
          add_h2(y[0], y[1], u0.x, v0.x); add_h2(y[2], y[3], u0.y, v0.y); add_h2(y[4], y[5], u0.z, v0.z); add_h2(y[6], y[7], u0.w, v0.w);
          add_h2(y[8], y[9], u1, v1);
          const float mx = quad_max(max10(y)) * -256.f;
          sts32(pa + 640, 0);
#pragma unroll
          for (int j = 0; j < 5; j++) {
            y[2 * j] = ex2(fmaf(y[2 * j], 256.f, mx)); y[2 * j + 1] = ex2(fmaf(y[2 * j + 1], 256.f, mx));
            sts32(pa + j * 128, pack_bf16(y[2 * j], y[2 * j + 1]));
          }
          sts32(pa + 768, __float_as_uint(sum10(y)));
          fence_async();
          TS(i, 9);
        } else {
          CBAR_ARRIVE(NB_SM, 256);
          if (lane == 0) mbar_arrive_cluster(mapa(sb, 0) + BAR_E);
          mwait(sb + BAR_MF, ph, spin);
        }
      }
      CBAR_SYNC(NB_VA, 256);
      TSB(i, 10);
      {
        float o[2][4];
        wg_fence();
#pragma unroll
        for (int c = 0; c < 2; c++)
#pragma unroll
          for (int q = 0; q < 3; q++)
            wgmma_ss8(o[c], mkdesc_ns(SB0 + OFF_VT + 128 + c * 640 + q * 256, 128, VS), mkdesc_ns(SB0 + OFF_XM + c * 1280 + q * 256, 128, 128), q);
        wg_commit();
        const int tid = fresh(tid0);
        const float4 e = lds128f(sb + OFF_XM + 768 + (tid & 3) * 32 + (tid & 4) * 4 + (tid & 8) * 160);
        const uint32_t oo = (tid >> 5) * 512 + (tid & 2) * 64 + ((tid & 31) >> 2) * 16 + (tid & 1) * 8;
        const uint32_t rb1 = mapa(sb, (rank + 1) % 3), rb2 = mapa(sb, (rank + 2) % 3);
        const uint32_t ra = pin(rb1 + oo + og_off(2)), rc = pin(rb2 + oo + og_off(1)), la = pin(sb + oo + og_off(0));
        const float inv = rcp((e.x + e.y) + (e.z + e.w));
        const float i0 = __shfl_sync(0xffffffffu, inv, tid & 3), i1 = __shfl_sync(0xffffffffu, inv, (tid & 3) + 4);
        const float i2 = __shfl_sync(0xffffffffu, inv, (tid & 3) + 8), i3 = __shfl_sync(0xffffffffu, inv, (tid & 3) + 12);
        wg_wait<0>();
        TS(i, 11);
        const uint32_t p0 = pack_bf16(o[0][0] * i0, o[0][1] * i1), p1 = pack_bf16(o[1][0] * i2, o[1][1] * i3);
        const uint32_t p2 = pack_bf16(o[0][2] * i0, o[0][3] * i1), p3 = pack_bf16(o[1][2] * i2, o[1][3] * i3);
        if (OGF) { sts64(la, p0, p1); sts64(la + 256, p2, p3); fence_async(); }
        st_async2u(ra, p0, p1, rb1 + BAR_OG);
        st_async2u(rc, p0, p1, rb2 + BAR_OG);
        st_async2u(ra + 256, p2, p3, rb1 + BAR_OG);
        st_async2u(rc + 256, p2, p3, rb2 + BAR_OG);
        if (!OGF) { sts64(la, p0, p1); sts64(la + 256, p2, p3); fence_async(); }
      }
      if (i + 1 >= NSTEP) { mwait(sb + BAR_OG, ph, spin); break; }
      CBAR_SYNC(NB_A, 128);
      TSB(i, 12);
      {
        float acc[3][8];
        wg_fence();
        wo_block<0, 0>(acc[2], wf);
        wg_commit();
        wo_block<1, 0>(acc[0], wf);
        wo_block<4, 0>(acc[1], wf);
        wg_commit();
        const int tid = fresh(tid0), w = tid >> 5, g = (tid & 31) >> 2, t = tid & 3;
        if ((tid & 31) == 0) mbar_arrive_cluster(mapa(sb, 1) + BAR_E + 8);
        const uint32_t tag = (i >> 1) & 1, radd = tag ? 0u : 0x10000u;
#define TAGGED(LO, HI) __byte_perm(((__float_as_uint(LO) + radd) & 0xFFFE0000u) | (tag << 16), pack_bf16(0.f, HI), 0x7632)
#define SEND(PTR, U) st_relaxed128((PTR), TAGGED(acc[U][0], acc[U][2]), pack_bf16(acc[U][1], acc[U][3]), pack_bf16(acc[U][4], acc[U][6]), pack_bf16(acc[U][5], acc[U][7]))
        uint8_t* m9 = pinp(g_mail[ph] + MAIL9 + (((2 * w + (g >> 2)) * 2 + (t & 1)) * 4 + (t & 2)) * 3072 + cta * 32 + (g & 3) * 8);
        wg_wait<1>();
        const uint32_t n0 = pin(TAGGED(acc[2][0], acc[2][2])), n1 = pin(pack_bf16(acc[2][1], acc[2][3]));
        const uint32_t n2 = pin(TAGGED(acc[2][4], acc[2][6])), n3 = pin(pack_bf16(acc[2][5], acc[2][7]));
        wg_fence();
        wo_block<7, 0>(acc[2], wf);
        wg_commit();
        st_relaxed64(m9, n0, n1);
        st_relaxed64(m9 + 3072, n2, n3);
        uint8_t* mb = pinp(g_mail[ph] + (((rank * 12 + w) * 2 + (g >> 2)) * 4 + t) * 2048 + (cta / 3) * 64 + (g & 3) * 16);
        mwait(sb + BAR_OG, ph, spin);
        asm volatile("fence.proxy.async::generic.acquire.sync_restrict::shared::cluster.cluster;" ::: "memory");
        TS(i, 13);
        wg_fence();
        wo_block<2, 1>(acc[0], wf); wo_block<3, 2>(acc[0], wf);
        wg_commit();
        wo_block<5, 1>(acc[1], wf); wo_block<6, 2>(acc[1], wf);
        wg_commit();
        wg_wait<1>(); SEND(mb, 0);
        wg_fence();
        wo_block<8, 1>(acc[2], wf); wo_block<9, 2>(acc[2], wf);
        wg_commit();
        if (WOE == 0) { CBAR_ARRIVE(NB_WV, 256); CBAR_ARRIVE(NB_WQ, 256); }
        wg_wait<1>(); SEND(mb + 32 * 2048, 1);
        if (WOE == 1) CBAR_ARRIVE(NB_WV, 256);
        wg_wait<0>(); SEND(mb + 64 * 2048, 2);
        if (WOE == 2) CBAR_ARRIVE(NB_WV, 256);
        if (WOE >= 1) CBAR_ARRIVE(NB_WQ, 256);
#undef SEND
#undef TAGGED
      }
      TS(i, 14);
    }
    const uint32_t t0 = clk32();
    uint32_t t1 = t0;
    if (i >= 0) {
      const int tid = fresh(tid0), lane = tid & 31;
      const uint32_t tag = (i >> 1) & 1;
      const bool t9 = cta >= 72 && cta < 88;
      const int w = tid >> 5, j = lane >> 3;
      const uint32_t pub = pin((lane & (t9 ? 6 : 4)) == 0 && !(((t9 ? cta : w) & 1) && i + 1 == LAG) && cta < 88);
      uint8_t* dst = pinp(g_mbuf[i + 1] + (t9 ? (cta + 72) * 128 + w * 32 + (j & 1) * 16 + (lane & 1) * 8 + (j >> 1) * 4
                                               : cta * 256 + (w & 1) * 128 + (w >> 1) * 64 + j * 16 + (lane & 3) * 4));
      uint32_t* flag = pinp(lane == 0 && cta < 88 ? &g_flag[i + 1][cta * 8 + w] : nullptr);
      float f[8];
      int n = 0;
      while (clk32() - t0 < B1) {}
      TS(i + 1, 30);
      if (!t9) poll_add<4>(g_mail[ph] + (cta < 72 ? cta : cta - 24) * 8192 + (tid >> 5) * 2048 + lane * 16, tag, f, flag, n, spin);
      else poll_add<6>(g_mail[ph] + MAIL9 + (cta - 72) * 12288 + (tid >> 5) * 3072 + lane * 16, tag, f, flag, n, spin);
      if (FLP == 1 && flag) st_relaxed(flag, __float_as_uint(f[0] + f[7]) >> 1);
      t1 = clk32();
      TS(i + 1, 31); TSV(i + 1, 32, n);
      const bool h = lane & 16, q = lane & 8;
#pragma unroll
      for (int j = 0; j < 4; j++) f[j] = (h ? f[4 + j] : f[j]) + __shfl_xor_sync(0xffffffffu, h ? f[j] : f[4 + j], 16);
#pragma unroll
      for (int j = 0; j < 2; j++) f[j] = (q ? f[2 + j] : f[j]) + __shfl_xor_sync(0xffffffffu, q ? f[j] : f[2 + j], 8);
      f[0] += __shfl_xor_sync(0xffffffffu, f[0], 4); f[1] += __shfl_xor_sync(0xffffffffu, f[1], 4);
      if (t9) { f[0] += __shfl_xor_sync(0xffffffffu, f[0], 2); f[1] += __shfl_xor_sync(0xffffffffu, f[1], 2); }
      if (pub) st_relaxed(dst, pack_bf16(f[0], f[1]));
      if (FLP == 2 && flag) st_relaxed(flag, 0);
      TS(i + 1, 15);
    }
    if (tid0 < 32) {
      const uint8_t* src = pinp(g_mbuf[i + 1] + rank * 7168);
      const uint32_t* pp = pinp(&g_flag[i + 1][(rank * 28 + (tid0 < 28 || rank == 2 ? tid0 : 0)) * 8]);
      const uint32_t dst = pin(sb + OFF_M + rank * 7168), len = pin(rank == 2 ? 6144 : 7168);
      if (tid0 == 0) mbar_expect_tx(sb + BAR_M, 20480);
      while (clk32() - t1 < B2) {}
      TS(i + 1, 16);
      int n = 0;
      uint4 x;
      do { x = ld_relaxed4(pp); n++; spin += 16; } while (__any_sync(0xffffffffu, (int)(x.x | x.y | x.z | x.w) < 0 && spin < SPIN_TOT));
      TSV(i + 1, 35, n);
      TS(i + 1, 34);
      mwait(sb + BAR_MOK, ph ^ 1, spin);
      if (tid0 == 0) bulk_g2s_mc(dst, src, len, sb + BAR_M);
      TS(i + 1, 33);
      __syncwarp();
    }
  }
  if (spin >= SPIN_TOT) g_err = 1;
}

__global__ void __cluster_dims__(3, 1, 1) __launch_bounds__(384, 1)
k_chain(const __grid_constant__ CUtensorMap tmWq, const __grid_constant__ CUtensorMap tmWk,
        const __grid_constant__ CUtensorMap tmWv, const __grid_constant__ CUtensorMap tmWo) {
  using namespace C;
  extern __shared__ __align__(1024) uint8_t smem[];
  const uint32_t sb = smem_u32(smem);
  const int tid = threadIdx.x;
  const int wg = __shfl_sync(0xffffffffu, tid >> 7, 0);
  const int cta = blockIdx.x, rank = cta % 3;

  asm volatile("griddepcontrol.launch_dependents;");
  if (tid == 0) {
    if ((sb & 0xFFFFFF) != SB0) g_err = 100;
    for (int p = 0; p < 5; p++) { mbar_init(sb + BAR_F + 8 * p, 1); mbar_init(sb + BAR_E + 8 * p, p == 2 ? 12 : 24); }
    mbar_init(sb + BAR_M, 1); mbar_init(sb + BAR_MOK, 24); mbar_init(sb + BAR_XM, 1); mbar_init(sb + BAR_XF, 2);
    mbar_init(sb + BAR_XT, 1); mbar_init(sb + BAR_MF, 8); mbar_init(sb + BAR_OG, 1); mbar_init(sb + BAR_W, 1);
    for (int p = 0; p < 5; p++) mbar_expect_tx(sb + BAR_F + 8 * p, 16384);
    for (int p = 0; p < 16; p++) sts32(sb + OFF_SAFE + 4 * p, 0);
    asm volatile("fence.mbarrier_init.release.cluster;" ::: "memory");
    fence_async();
    mbar_expect_tx(sb + BAR_W, 163840);
    const int head = cta / 3, col = head * DH + rank * 64;
    tma2d(sb + OFF_WQ, &tmWo, 576, col, sb + BAR_W);
    for (int i = 0; i < 9; i++) tma2d(sb + OFF_WQ + (i + 1) * 8192, &tmWo, (3 * rank + i / 3) * 64, head * DH + ((rank + i) % 3) * 64, sb + BAR_W);
    for (int i = 0; i < 5; i++) tma2d(sb + OFF_WK + i * 16384, &tmWv, col, i * 128, sb + BAR_W);
  }
  __syncthreads();
  asm volatile("barrier.cluster.arrive.release.aligned;" ::: "memory");
  asm volatile("barrier.cluster.wait.acquire.aligned;" ::: "memory");

  if (wg == 0) chain_a(sb, keep(tid), cta, rank);
  else if (wg == 1) chain_q(tmWq, tmWk, sb, keep(tid), cta, rank);
  else chain_v(sb, keep(tid), cta, rank);
  asm volatile("barrier.cluster.arrive.release.aligned;" ::: "memory");
  asm volatile("barrier.cluster.wait.acquire.aligned;" ::: "memory");
}

namespace W {
constexpr int NW = 36;
constexpr int NP = 30;
constexpr int OW0 = 31;
constexpr int PST = 3, PSTAGE = 32768;
constexpr int BST = 3, BSTAGE = 16384;
constexpr int OFF_P = 0;
constexpr int OFF_WQ = OFF_P + PST * PSTAGE;
constexpr int OFF_B = OFF_WQ + 81920;
constexpr int OFF_HIST = OFF_B + BST * BSTAGE;
constexpr int OFF_BAR = OFF_HIST + 2 * 14 * 80;
constexpr int SMEM = OFF_BAR + 128;
constexpr int BAR_PF = OFF_BAR, BAR_PE = OFF_BAR + 24, BAR_BF = OFF_BAR + 48, BAR_BE = OFF_BAR + 72;
constexpr int PITCH = 136;
constexpr int NB_P = 1, NB_B = 2;
}

struct WorkArgs {
  const bf16* res[2];
  bf16* xa[2];
  bf16* xb[2];
  const bf16* wqkv;
};

#define OHK 7
#define IMMREL 7
#define FOR_BATCHES(l, b)                                   \
  for (int j_ = 0; j_ < 2 * NSTEP; j_++) {                  \
    const int l = j_ & 1, s_ = (j_ >> 1) - (l ? LAG : 0);   \
    if (s_ < 0 || s_ >= NSEG || (s_ & 3) != 3) continue;    \
    const int b = s_ >> 2;

template <bool IS_O>
__device__ __forceinline__ void work_gemm_producer(const CUtensorMap& tm, const WorkArgs& a, uint32_t sb, int w) {
  using namespace W;
  constexpr int KCH = IS_O ? 10 : 96, NK = IS_O ? 10 : 16;
  int dead = 0, st = 0;
  uint32_t ph = 1;
  const int col = (IS_O ? w - OW0 : w % 5) * 128, k0 = IS_O ? 0 : (w / 5) * 16;
  FOR_BATCHES(l, b)
    const uint8_t* src = (IS_O ? g_ob[l] : g_o[l]) + ((size_t)(2 * b) * KCH + k0) * 8192;
#pragma unroll 1
    for (int kc = 0; kc < NK; kc++) {
      const uint32_t bar = sb + BAR_PF + 8 * st, d = sb + OFF_P + st * PSTAGE;
      mbar_wait(sb + BAR_PE + 8 * st, ph, dead);
      mbar_expect_tx(bar, PSTAGE);
      tma2d(d + 16384, &tm, col, (k0 + kc) * 64, bar);
      tma2d(d + 24576, &tm, col + 64, (k0 + kc) * 64, bar);
      if (kc >= PST) {
        bulk_g2s(d, src + (size_t)kc * 8192, 8192, bar);
        bulk_g2s(d + 8192, src + (size_t)(KCH + kc) * 8192, 8192, bar);
      }
      if (++st == PST) { st = 0; ph ^= 1; }
      if (kc == PST - 1) {
        cnt_wait(IS_O ? CN_A : CN_O, l, b, IS_O ? 32 : 96, dead);
        if (!IS_O && w == 0) WTS(l, b, 0);
        if (IS_O && w == 35) WTS(l, b, 3);
        fence_async_all();
#pragma unroll
        for (int i = 0; i < PST; i++) {
          const int s2 = (st + i) % PST;
          bulk_g2s(sb + OFF_P + s2 * PSTAGE, src + (size_t)i * 8192, 8192, sb + BAR_PF + 8 * s2);
          bulk_g2s(sb + OFF_P + s2 * PSTAGE + 8192, src + (size_t)(KCH + i) * 8192, 8192, sb + BAR_PF + 8 * s2);
        }
      }
    }
  }
}

__device__ __forceinline__ void quad_transpose(uint32_t* x, int t) {
  const bool h = t & 2, o = t & 1;
  uint32_t p = __shfl_xor_sync(0xffffffffu, h ? x[0] : x[2], 2), q = __shfl_xor_sync(0xffffffffu, h ? x[1] : x[3], 2);
  const uint32_t y0 = h ? p : x[0], y1 = h ? q : x[1], y2 = h ? x[2] : p, y3 = h ? x[3] : q;
  p = __shfl_xor_sync(0xffffffffu, o ? y0 : y1, 1); q = __shfl_xor_sync(0xffffffffu, o ? y2 : y3, 1);
  x[0] = o ? p : y0; x[1] = o ? y1 : p; x[2] = o ? q : y2; x[3] = o ? y3 : q;
}

template <bool IS_O>
__device__ __forceinline__ void work_gemm(const WorkArgs& a, uint32_t sb, int w, int tid0) {
  using namespace W;
  constexpr int NK = IS_O ? 10 : 16;
  int dead = 0, st = 0;
  uint32_t ph = 0;
  const int tile = IS_O ? w - OW0 : w % 5;
  bool first = true;
  FOR_BATCHES(l, b)
    float acc[64];
    uint32_t r0[16], r1[16];
    int prev = 0;
    if (IS_O) {
#pragma unroll
      for (int i = 0; i < 64; i++) acc[i] = 0.f;
    }
#pragma unroll 1
    for (int kc = 0; kc < NK; kc++) {
      mbar_wait(sb + BAR_PF + 8 * st, ph, dead);
      if (w == (IS_O ? 35 : WW) && tid0 == 0 && kc == 0) WTS(l, b, IS_O ? 16 : 5);
      const uint32_t pa = sb + OFF_P + st * PSTAGE + (tid0 >> 7) * 8192, pb = sb + OFF_P + st * PSTAGE + 16384;
      wg_fence();
#pragma unroll
      for (int kk = 0; kk < 4; kk++) wgmma_st128(acc, mkdesc(pa + kk * 32, 16, 1024), mkdesc(pb + kk * 2048, 8192, 1024), (kc | kk) != 0);
      wg_commit();
      if (IS_O && OHK >= 0 && kc == OHK) {
      const int tid = fresh(tid0), g = (tid & 31) >> 2, t = tid & 3;
      const bf16* rp = a.xa[l] + (size_t)(b * 128 + (tid >> 5) * 16 + g) * DM + tile * 128 + 8 * t;
#pragma unroll
      for (int m = 0; m < 4; m++) {
        const float4 c0 = ld_relaxed4f(rp + 32 * m), c1 = ld_relaxed4f(rp + 8 * DM + 32 * m);
        r0[4 * m] = __float_as_uint(c0.x); r0[4 * m + 1] = __float_as_uint(c0.y); r0[4 * m + 2] = __float_as_uint(c0.z); r0[4 * m + 3] = __float_as_uint(c0.w);
        r1[4 * m] = __float_as_uint(c1.x); r1[4 * m + 1] = __float_as_uint(c1.y); r1[4 * m + 2] = __float_as_uint(c1.z); r1[4 * m + 3] = __float_as_uint(c1.w);
      }
      }
      if (IMMREL & (IS_O ? 2 : 1)) {
        if (kc < NK - 1) {
          wg_wait<0>();
          if ((tid0 & 127) == 0) mbar_arrive(sb + BAR_PE + 8 * st);
        }
      } else if (kc > 0) {
        wg_wait<1>();
        if ((tid0 & 127) == 0) mbar_arrive(sb + BAR_PE + 8 * prev);
      }
      prev = st;
      if (++st == PST) { st = 0; ph ^= 1; }
    }
    if (IS_O && OHK < 0) {
      const int tid = fresh(tid0), g = (tid & 31) >> 2, t = tid & 3;
      const bf16* rp = a.xa[l] + (size_t)(b * 128 + (tid >> 5) * 16 + g) * DM + tile * 128 + 8 * t;
#pragma unroll
      for (int m = 0; m < 4; m++) {
        const float4 c0 = ld_relaxed4f(rp + 32 * m), c1 = ld_relaxed4f(rp + 8 * DM + 32 * m);
        r0[4 * m] = __float_as_uint(c0.x); r0[4 * m + 1] = __float_as_uint(c0.y); r0[4 * m + 2] = __float_as_uint(c0.z); r0[4 * m + 3] = __float_as_uint(c0.w);
        r1[4 * m] = __float_as_uint(c1.x); r1[4 * m + 1] = __float_as_uint(c1.y); r1[4 * m + 2] = __float_as_uint(c1.z); r1[4 * m + 3] = __float_as_uint(c1.w);
      }
    }
    wg_wait<0>();
    if ((tid0 & 127) == 0) mbar_arrive(sb + BAR_PE + 8 * prev);
    if (w == (IS_O ? 35 : WW) && tid0 == 0) WTS(l, b, IS_O ? 17 : 6);
    if (!IS_O) {
      if (first) {
        if ((tid0 & 31) == 0) cnt_wait(CN_Z, 0, 0, NW, dead);
        __syncwarp();
        first = false;
      }
      const int tid = fresh(tid0);
      float* dst = &g_acc[l][b][tile][0] + (tid >> 5) * 2048 + (tid & 31) * 4;
#pragma unroll
      for (int i = 0; i < 16; i++)
        asm volatile("red.relaxed.gpu.global.add.v4.f32 [%0],{%1,%2,%3,%4};" ::"l"(dst + i * 128), "f"(acc[4 * i]), "f"(acc[4 * i + 1]), "f"(acc[4 * i + 2]), "f"(acc[4 * i + 3]) : "memory");
      if (w == WW && tid0 == 0) WTS(l, b, 7);
      bar_sync(NB_P, 256);
      if (tid0 == 0) cnt_signal(CN_P, l, b);
      if (w == WW && tid0 == 0) WTS(l, b, 8);
    } else {
      const int tid = fresh(tid0), g = (tid & 31) >> 2, t = tid & 3;
      const int rb = (tid >> 5) * 16 + g, R0 = b * 128 + rb;
      float s0 = 0.f, s1 = 0.f;
      bf16* xp = a.xb[l] + (size_t)R0 * DM + tile * 128 + 8 * t;
      uint32_t c0[16], c1[16];
#pragma unroll
      for (int j = 0; j < 16; j++) { c0[j] = pack_bf16(acc[4 * j], acc[4 * j + 1]); c1[j] = pack_bf16(acc[4 * j + 2], acc[4 * j + 3]); }
#pragma unroll
      for (int m = 0; m < 4; m++) { quad_transpose(c0 + 4 * m, t); quad_transpose(c1 + 4 * m, t); }
#pragma unroll
      for (int j = 0; j < 16; j++) {
        const uint32_t u0 = c0[j], u1 = c1[j];
        const uint32_t y0 = pack_bf16(bf_lo(r0[j]) + bf_lo(u0), bf_hi(r0[j]) + bf_hi(u0));
        const uint32_t y1 = pack_bf16(bf_lo(r1[j]) + bf_lo(u1), bf_hi(r1[j]) + bf_hi(u1));
        acc[4 * j] = bf_lo(y0); acc[4 * j + 1] = bf_hi(y0); acc[4 * j + 2] = bf_lo(y1); acc[4 * j + 3] = bf_hi(y1);
        s0 += acc[4 * j] + acc[4 * j + 1]; s1 += acc[4 * j + 2] + acc[4 * j + 3];
      }
      if (l == 0) {
        s0 += __shfl_xor_sync(0xffffffffu, s0, 1); s1 += __shfl_xor_sync(0xffffffffu, s1, 1);
        s0 += __shfl_xor_sync(0xffffffffu, s0, 2); s1 += __shfl_xor_sync(0xffffffffu, s1, 2);
        const float tm0 = s0 * (1.f / 128), tm1 = s1 * (1.f / 128);
        float q0 = 0.f, q1 = 0.f;
#pragma unroll
        for (int j = 0; j < 16; j++) {
          const float a0 = acc[4 * j] - tm0, b0 = acc[4 * j + 1] - tm0, a1 = acc[4 * j + 2] - tm1, b1 = acc[4 * j + 3] - tm1;
          q0 += a0 * a0 + b0 * b0; q1 += a1 * a1 + b1 * b1;
        }
        q0 += __shfl_xor_sync(0xffffffffu, q0, 1); q1 += __shfl_xor_sync(0xffffffffu, q1, 1);
        q0 += __shfl_xor_sync(0xffffffffu, q0, 2); q1 += __shfl_xor_sync(0xffffffffu, q1, 2);
        float2* sp = &g_stats[b][rb][0];
        if (t < 2) {
          const float sx = t ? s1 : s0, qx = t ? q1 : q0;
          asm volatile("st.relaxed.gpu.global.v2.f32 [%0],{%1,%2};" ::"l"(sp + t * 8 * 16 + tile), "f"(sx), "f"(qx) : "memory");
        }
#pragma unroll
        for (int m = 0; m < 4; m++) {
          const float* c = acc + 16 * m;
          *reinterpret_cast<uint4*>(xp + 32 * m) = make_uint4(pack_bf16(c[0], c[1]), pack_bf16(c[4], c[5]), pack_bf16(c[8], c[9]), pack_bf16(c[12], c[13]));
          *reinterpret_cast<uint4*>(xp + 8 * DM + 32 * m) = make_uint4(pack_bf16(c[2], c[3]), pack_bf16(c[6], c[7]), pack_bf16(c[10], c[11]), pack_bf16(c[14], c[15]));
        }
        if (w == 35 && tid0 == 0) WTS(l, b, 18);
        float2 e0[2], e1[2];
        int n = dead ? SPIN_MAIL : 0;
        while (true) {
          e0[0] = ld_relaxed2f(sp + t); e1[0] = ld_relaxed2f(sp + 8 * 16 + t);
          e0[1] = ld_relaxed2f(sp + 4); e1[1] = ld_relaxed2f(sp + 8 * 16 + 4);
          bool bad = false;
#pragma unroll
          for (int i = 0; i < 2; i++)
            bad |= __float_as_uint(e0[i].x) == SENT || __float_as_uint(e0[i].y) == SENT || __float_as_uint(e1[i].x) == SENT || __float_as_uint(e1[i].y) == SENT;
          if (!__any_sync(0xffffffffu, bad)) break;
          if (++n > SPIN_MAIL) { dead = 1; g_err = 20; break; }
        }
        if (w == 35 && tid0 == 0) WTS(l, b, 19);
        float m0 = e0[0].x, m1 = e1[0].x;
        m0 += __shfl_xor_sync(0xffffffffu, m0, 1); m1 += __shfl_xor_sync(0xffffffffu, m1, 1);
        m0 += __shfl_xor_sync(0xffffffffu, m0, 2); m1 += __shfl_xor_sync(0xffffffffu, m1, 2);
        m0 = (m0 + e0[1].x) * (1.f / DM); m1 = (m1 + e1[1].x) * (1.f / DM);
        const float d0 = e0[0].x * (1.f / 128) - m0, d1 = e1[0].x * (1.f / 128) - m1;
        float v0 = e0[0].y + 128.f * d0 * d0, v1 = e1[0].y + 128.f * d1 * d1;
        v0 += __shfl_xor_sync(0xffffffffu, v0, 1); v1 += __shfl_xor_sync(0xffffffffu, v1, 1);
        v0 += __shfl_xor_sync(0xffffffffu, v0, 2); v1 += __shfl_xor_sync(0xffffffffu, v1, 2);
        const float d2 = e0[1].x * (1.f / 128) - m0, d3 = e1[1].x * (1.f / 128) - m1;
        v0 += e0[1].y + 128.f * d2 * d2; v1 += e1[1].y + 128.f * d3 * d3;
        const float rs0 = rsqrtf(v0 * (1.f / DM) + 1e-5f), rs1 = rsqrtf(v1 * (1.f / DM) + 1e-5f);
        uint8_t* img = g_xn[1] + (size_t)(R0 >> 5) * 40960 + tile * 8192 + ((R0 >> 3) & 3) * 2048 + g * 128;
#pragma unroll
        for (int m = 0; m < 4; m++) {
          uint8_t* o = img + (m >> 1) * 1024 + (((4 * (m & 1) + t) ^ g) << 4);
          const float* c = acc + 16 * m;
          *reinterpret_cast<uint4*>(o) = make_uint4(pack_bf16((c[0] - m0) * rs0, (c[1] - m0) * rs0), pack_bf16((c[4] - m0) * rs0, (c[5] - m0) * rs0),
                                                    pack_bf16((c[8] - m0) * rs0, (c[9] - m0) * rs0), pack_bf16((c[12] - m0) * rs0, (c[13] - m0) * rs0));
          *reinterpret_cast<uint4*>(o + 2048) = make_uint4(pack_bf16((c[2] - m1) * rs1, (c[3] - m1) * rs1), pack_bf16((c[6] - m1) * rs1, (c[7] - m1) * rs1),
                                                            pack_bf16((c[10] - m1) * rs1, (c[11] - m1) * rs1), pack_bf16((c[14] - m1) * rs1, (c[15] - m1) * rs1));
        }
        bar_sync(NB_P, 256);
        if (tid0 == 0) { fence_async_all(); cnt_signal(CN_X, 0, b); }
      } else {
#pragma unroll
        for (int m = 0; m < 4; m++) {
          const float* c = acc + 16 * m;
          *reinterpret_cast<uint4*>(xp + 32 * m) = make_uint4(pack_bf16(c[0], c[1]), pack_bf16(c[4], c[5]), pack_bf16(c[8], c[9]), pack_bf16(c[12], c[13]));
          *reinterpret_cast<uint4*>(xp + 8 * DM + 32 * m) = make_uint4(pack_bf16(c[2], c[3]), pack_bf16(c[6], c[7]), pack_bf16(c[10], c[11]), pack_bf16(c[14], c[15]));
        }
      }
      if (w == 35 && tid0 == 0) { WTS(l, b, 4); WTS(l, b, 20); }
    }
  }
}

__device__ __forceinline__ void work_q_producer(const WorkArgs& a, uint32_t sb) {
  using namespace W;
  int dead = 0, st = 0;
  uint32_t ph = 1;
  FOR_BATCHES(l, b)
    cnt_wait(CN_L, l, b, 64, dead);
    if (blockIdx.x == 0) WTS(l, b, 2);
    fence_async_all();
    const uint8_t* src = g_xnb[l] + (size_t)(2 * b) * 10 * 8192;
#pragma unroll 1
    for (int kc = 0; kc < 10; kc++) {
      const uint32_t bar = sb + BAR_BF + 8 * st, d = sb + OFF_B + st * BSTAGE;
      mbar_wait(sb + BAR_BE + 8 * st, ph, dead);
      mbar_expect_tx(bar, BSTAGE);
      bulk_g2s(d, src + (size_t)kc * 8192, 8192, bar);
      bulk_g2s(d + 8192, src + (size_t)(10 + kc) * 8192, 8192, bar);
      if (++st == BST) { st = 0; ph ^= 1; }
    }
  }
}

__device__ __forceinline__ void work_ln(const WorkArgs& a, int w, int wr, int lane0) {
  int dead = 0;
  FOR_BATCHES(l, b)
    uint32_t r0[10], r1[10];
    if (HOIST & 2) {
      if (l == 1) {
        if (lane0 == 0) cnt_wait(CN_X, 0, b, 5, dead);
        __syncwarp();
      }
      const int lane = fresh(lane0), p = 2 * w + wr;
      const bf16* rp = a.res[l] + (size_t)(b * 128 + (p >> 3) * 16 + (p & 7)) * DM + (lane >> 2) * 8 + 2 * (lane & 3);
#pragma unroll
      for (int i = 0; i < 10; i++) { r0[i] = ld_relaxed(rp + i * 64); r1[i] = ld_relaxed(rp + i * 64 + 8 * DM); }
    }
    if (lane0 == 0) cnt_wait(CN_P, l, b, W::NP, dead);
    __syncwarp();
    if (w == WW && wr == 0 && lane0 == 0) { WTS(l, b, 1); WTS(l, b, 9); }
    LTS(l, b, 2 * w + wr, 0);
    const int lane = fresh(lane0), p = 2 * w + wr;
    const int slab = p >> 3, g = p & 7, jj = lane >> 2, t = lane & 3;
    const int R0 = b * 128 + slab * 16 + g;
    const float* acc = &g_acc[l][b][0][0] + slab * 2048 + (g * 4 + t) * 4 + jj * 128;
    const bf16* rp = a.res[l] + (size_t)R0 * DM + jj * 8 + 2 * t;
    float4 v[10];
#pragma unroll
    for (int i = 0; i < 10; i++) {
      v[i] = ld_relaxed4f(acc + (i >> 1) * 16384 + (i & 1) * 1024);
      if (!(HOIST & 2)) { r0[i] = ld_relaxed(rp + i * 64); r1[i] = ld_relaxed(rp + i * 64 + 8 * DM); }
    }
    float s0 = 0.f, s1 = 0.f;
    bf16* xp = a.xa[l] + (size_t)R0 * DM + jj * 8 + 2 * t;
#pragma unroll
    for (int i = 0; i < 10; i++) {
      const uint32_t u0 = pack_bf16(v[i].x, v[i].y), u1 = pack_bf16(v[i].z, v[i].w);
      r0[i] = pack_bf16(bf_lo(r0[i]) + bf_lo(u0), bf_hi(r0[i]) + bf_hi(u0));
      r1[i] = pack_bf16(bf_lo(r1[i]) + bf_lo(u1), bf_hi(r1[i]) + bf_hi(u1));
      s0 += bf_lo(r0[i]) + bf_hi(r0[i]); s1 += bf_lo(r1[i]) + bf_hi(r1[i]);
    }
#pragma unroll
    for (int o = 16; o > 0; o >>= 1) { s0 += __shfl_xor_sync(0xffffffffu, s0, o); s1 += __shfl_xor_sync(0xffffffffu, s1, o); }
    const float m0 = s0 * (1.f / DM), m1 = s1 * (1.f / DM);
    if (m0 != 12345.678f) LTS(l, b, 2 * w + wr, 1);
    float q0 = 0.f, q1 = 0.f;
#pragma unroll
    for (int i = 0; i < 10; i++) {
      const float a0 = bf_lo(r0[i]) - m0, b0 = bf_hi(r0[i]) - m0, a1 = bf_lo(r1[i]) - m1, b1 = bf_hi(r1[i]) - m1;
      q0 += a0 * a0 + b0 * b0; q1 += a1 * a1 + b1 * b1;
    }
#pragma unroll
    for (int o = 16; o > 0; o >>= 1) { q0 += __shfl_xor_sync(0xffffffffu, q0, o); q1 += __shfl_xor_sync(0xffffffffu, q1, o); }
    const float rs0 = rsqrtf(q0 * (1.f / DM) + 1e-5f), rs1 = rsqrtf(q1 * (1.f / DM) + 1e-5f);
    uint8_t* img = g_xnb[l] + (size_t)(R0 >> 6) * 10 * 8192 + (R0 & 63) * 128 + t * 4 + ((jj ^ g) << 4);
#pragma unroll
    for (int i = 0; i < 10; i++) {
      *reinterpret_cast<uint32_t*>(img + i * 8192) = pack_bf16((bf_lo(r0[i]) - m0) * rs0, (bf_hi(r0[i]) - m0) * rs0);
      *reinterpret_cast<uint32_t*>(img + i * 8192 + 1024) = pack_bf16((bf_lo(r1[i]) - m1) * rs1, (bf_hi(r1[i]) - m1) * rs1);
    }
#pragma unroll
    for (int i = 0; i < 10; i++) {
      *reinterpret_cast<uint32_t*>(xp + i * 64) = r0[i];
      *reinterpret_cast<uint32_t*>(xp + i * 64 + 8 * DM) = r1[i];
    }
    __syncwarp();
    if (w == WW && wr == 0 && lane0 == 0) WTS(l, b, 10);
    LTS(l, b, 2 * w + wr, 2);
    if (lane0 == 0) cnt_signal(CN_L, l, b);
    LTS(l, b, 2 * w + wr, 3);
    if (w == WW && wr == 0 && lane0 == 0) WTS(l, b, 11);
  }
}

__device__ __forceinline__ void work_q(const WorkArgs& a, uint32_t sb, int w, int tid0) {
  using namespace W;
  int dead = 0, st = 0;
  uint32_t ph = 0;
  FOR_BATCHES(l, b)
    {
      float acc0[32], acc1[32];
      int prev = 0;
#pragma unroll 1
      for (int kc = 0; kc < 10; kc++) {
        mbar_wait(sb + BAR_BF + 8 * st, ph, dead);
        if (w == WW && tid0 == 0 && kc == 0) WTS(l, b, 12);
        const uint32_t pa = sb + OFF_B + st * BSTAGE, pb = sb + OFF_WQ + kc * 8192;
        wg_fence();
#pragma unroll
        for (int kk = 0; kk < 4; kk++) {
          wgmma_st64(acc0, mkdesc(pa + kk * 32, 16, 1024), mkdesc(pb + kk * 2048, 8192, 1024), (kc | kk) != 0);
          wgmma_st64(acc1, mkdesc(pa + 8192 + kk * 32, 16, 1024), mkdesc(pb + kk * 2048, 8192, 1024), (kc | kk) != 0);
        }
        wg_commit();
        if (IMMREL & 4) {
          if (kc <= 6) {
            wg_wait<0>();
            if (tid0 == 0) mbar_arrive(sb + BAR_BE + 8 * st);
          }
        } else if (kc > 0) {
          wg_wait<1>();
          if (kc <= 7 && tid0 == 0) mbar_arrive(sb + BAR_BE + 8 * prev);
        }
        prev = st;
        if (++st == BST) { st = 0; ph ^= 1; }
      }
      wg_wait<0>();
      bar_sync(NB_B, 128);
      if (w == WW && tid0 == 0) WTS(l, b, 13);
      const int tid = fresh(tid0), wr = tid >> 5, g = (tid & 31) >> 2, t = tid & 3;
      const uint32_t stg = sb + OFF_B, hist = sb + OFF_HIST + l * 1120;
      const uint32_t o = stg + (14 + 16 * wr + g) * PITCH + t * 4;
#pragma unroll
      for (int j = 0; j < 8; j++) {
        sts32(o + j * 16, pack_bf16(acc0[4 * j], acc0[4 * j + 1]));
        sts32(o + 8 * PITCH + j * 16, pack_bf16(acc0[4 * j + 2], acc0[4 * j + 3]));
        sts32(o + 64 * PITCH + j * 16, pack_bf16(acc1[4 * j], acc1[4 * j + 1]));
        sts32(o + 72 * PITCH + j * 16, pack_bf16(acc1[4 * j + 2], acc1[4 * j + 3]));
      }
      for (int i = tid; i < 280; i += 128) {
        uint32_t v; asm volatile("ld.shared.b32 %0,[%1];" : "=r"(v) : "r"(hist + i * 4) : "memory");
        sts32(stg + (i / 20) * PITCH + 40 + (i % 20) * 4, v);
      }
    }
    bar_sync(NB_B, 128);
    {
      const int tid = fresh(tid0);
      const uint32_t stg = sb + OFF_B, hist = sb + OFF_HIST + l * 1120;
      for (int i = tid; i < 280; i += 128) {
        uint32_t v; asm volatile("ld.shared.b32 %0,[%1];" : "=r"(v) : "r"(stg + (128 + i / 20) * PITCH + 40 + (i % 20) * 4) : "memory");
        sts32(hist + i * 4, v);
      }
      const float scl = 0.22360679774997896f * 1.4426950408889634f;
      const uint32_t row = stg + (14 + tid) * PITCH;
      const int pos = b * 128 + tid;
      float q[20];
#pragma unroll
      for (int i = 0; i < 5; i++) {
        uint32_t u0, u1; asm volatile("ld.shared.v2.b32 {%0,%1},[%2];" : "=r"(u0), "=r"(u1) : "r"(row + i * 8) : "memory");
        q[4 * i] = bf_lo(u0); q[4 * i + 1] = bf_hi(u0); q[4 * i + 2] = bf_lo(u1); q[4 * i + 3] = bf_hi(u1);
      }
      float sc[8], mx = -INFINITY;
#pragma unroll
      for (int j = 0; j < 8; j++) {
        float s0 = 0.f, s1 = 0.f;
#pragma unroll
        for (int i = 0; i < 5; i++) {
          uint32_t u0, u1; asm volatile("ld.shared.v2.b32 {%0,%1},[%2];" : "=r"(u0), "=r"(u1) : "r"(row - 2 * j * PITCH + 40 + i * 8) : "memory");
          s0 += q[4 * i] * bf_lo(u0) + q[4 * i + 1] * bf_hi(u0);
          s1 += q[4 * i + 2] * bf_lo(u1) + q[4 * i + 3] * bf_hi(u1);
        }
        sc[j] = pos - 2 * j >= 0 ? (s0 + s1) * scl : -INFINITY;
        mx = fmaxf(mx, sc[j]);
      }
      float sum = 0.f;
#pragma unroll
      for (int j = 0; j < 8; j++) { sc[j] = ex2(sc[j] - mx); sum += sc[j]; }
      const float inv = 1.f / sum;
      float o[20];
#pragma unroll
      for (int i = 0; i < 20; i++) o[i] = 0.f;
#pragma unroll
      for (int j = 0; j < 8; j++) {
        const float pj = __bfloat162float(__float2bfloat16(sc[j] * inv));
#pragma unroll
        for (int i = 0; i < 5; i++) {
          uint32_t u0, u1; asm volatile("ld.shared.v2.b32 {%0,%1},[%2];" : "=r"(u0), "=r"(u1) : "r"(row - 2 * j * PITCH + 80 + i * 8) : "memory");
          o[4 * i] += pj * bf_lo(u0); o[4 * i + 1] += pj * bf_hi(u0); o[4 * i + 2] += pj * bf_lo(u1); o[4 * i + 3] += pj * bf_hi(u1);
        }
      }
      uint8_t* img = g_ob[l] + (size_t)(pos >> 6) * 10 * 8192 + (pos & 63) * 128;
#pragma unroll
      for (int i = 0; i < 5; i++) {
        const int c = w * 20 + 4 * i;
        *reinterpret_cast<uint2*>(img + (c >> 6) * 8192 + ((((c >> 3) & 7) ^ (pos & 7)) << 4) + (c & 7) * 2) =
            make_uint2(pack_bf16(o[4 * i], o[4 * i + 1]), pack_bf16(o[4 * i + 2], o[4 * i + 3]));
      }
    }
    if (w == WW && tid0 == 0) WTS(l, b, 14);
    bar_sync(NB_B, 128);
    if (tid0 == 0) { cnt_signal(CN_A, l, b); if (w == WW) WTS(l, b, 15); }
    fence_async();
    bar_sync(NB_B, 128);
    if (tid0 == 0) for (int i = 0; i < BST; i++) mbar_arrive(sb + BAR_BE + 8 * i);
  }
}

__global__ void __launch_bounds__(512, 1)
k_work(const __grid_constant__ CUtensorMap tmWo, const __grid_constant__ CUtensorMap tmBo, const __grid_constant__ WorkArgs args) {
  using namespace W;
  extern __shared__ __align__(1024) uint8_t smem[];
  const uint32_t sb = smem_u32(smem);
  const int tid = threadIdx.x, w = blockIdx.x;
  const int wg = __shfl_sync(0xffffffffu, tid >> 7, 0);
  if (tid == 0) {
    for (int i = 0; i < PST; i++) { mbar_init(sb + BAR_PF + 8 * i, 1); mbar_init(sb + BAR_PE + 8 * i, 2); }
    for (int i = 0; i < BST; i++) { mbar_init(sb + BAR_BF + 8 * i, 1); mbar_init(sb + BAR_BE + 8 * i, 1); }
    asm volatile("fence.mbarrier_init.release.cluster;" ::: "memory");
  }
  for (int i = w * 512 + tid; i < 2 * 16 * 5 * 4096; i += NW * 512) reinterpret_cast<uint4*>(&g_acc[0][0][0][0])[i] = make_uint4(0, 0, 0, 0);
  if (w < 32) {
    for (int i = tid; i < 640 * 32; i += 512) {
      const int k = i >> 5, c = i & 31;
      uint32_t v = 0;
      if (c < 30) v = *reinterpret_cast<const uint32_t*>(args.wqkv + (size_t)k * 1920 + (c / 10) * 640 + w * 20 + (c % 10) * 2);
      sts32(sb + OFF_WQ + (k >> 6) * 8192 + (k & 63) * 128 + (((c >> 2) ^ (k & 7)) << 4) + (c & 3) * 4, v);
    }
  }
  for (int i = tid; i < 560; i += 512) sts32(sb + OFF_HIST + i * 4, 0);
  fence_async();
  __syncthreads();
  if (tid == 0) cnt_signal(CN_Z, 0, 0);

  if (wg < 2) {
    if (w < NP) work_gemm<false>(args, sb, w, tid);
    else if (w >= OW0) work_gemm<true>(args, sb, w, tid);
    else if (LN30 && tid < 64) work_ln(args, 31, tid >> 5, tid & 31);
  } else if (wg == 2) {
    if (w < 32) work_q(args, sb, w, tid - 256);
  } else if (tid >= 448) {
    if (w < (LN30 ? 31 : 32)) work_ln(args, w, (tid >> 5) & 1, tid & 31);
  } else if (tid == 384) {
    if (w < NP) work_gemm_producer<false>(tmWo, args, sb, w);
    else if (w >= OW0) work_gemm_producer<true>(tmBo, args, sb, w);
  } else if (tid == 416) {
    if (w < 32) work_q_producer(args, sb);
  }
  __syncthreads();
  asm volatile("griddepcontrol.wait;" ::: "memory");
}

typedef CUresult (*EncodeFn)(CUtensorMap*, CUtensorMapDataType, cuuint32_t, void*, const cuuint64_t*, const cuuint64_t*,
                             const cuuint32_t*, const cuuint32_t*, CUtensorMapInterleave, CUtensorMapSwizzle,
                             CUtensorMapL2promotion, CUtensorMapFloatOOBfill);

static void make_map(EncodeFn enc, CUtensorMap* tm, const void* ptr, uint64_t cols, uint64_t rows, uint32_t boxc, uint32_t boxr) {
  cuuint64_t dims[2] = {cols, rows};
  cuuint64_t strides[1] = {cols * 2};
  cuuint32_t box[2] = {boxc, boxr};
  cuuint32_t es[2] = {1, 1};
  enc(tm, CU_TENSOR_MAP_DATA_TYPE_BFLOAT16, 2, const_cast<void*>(ptr), dims, strides, box, es, CU_TENSOR_MAP_INTERLEAVE_NONE,
      CU_TENSOR_MAP_SWIZZLE_128B, CU_TENSOR_MAP_L2_PROMOTION_L2_256B, CU_TENSOR_MAP_FLOAT_OOB_FILL_NONE);
}

extern "C" void kernel_launch(void* const* d_in, const int* in_sizes, int n_in, void* d_out, int out_size) {
  const bf16* x0 = (const bf16*)d_in[0];
  const bf16* mem0 = (const bf16*)d_in[1];
  const bf16* Wq = (const bf16*)d_in[2];
  const bf16* Wk = (const bf16*)d_in[3];
  const bf16* Wv = (const bf16*)d_in[4];
  const bf16* Wo = (const bf16*)d_in[5];
  const bf16* Bqkv = (const bf16*)d_in[8];
  const bf16* Bwo = (const bf16*)d_in[9];
  bf16* out = (bf16*)d_out;

  static EncodeFn enc = nullptr;
  static bf16 *p_x1, *p_x2, *p_x3;
  if (!enc) {
    void* fn = nullptr;
    cudaDriverEntryPointQueryResult qr;
    cudaGetDriverEntryPoint("cuTensorMapEncodeTiled", &fn, cudaEnableDefault, &qr);
    enc = (EncodeFn)fn;
    cudaFuncSetAttribute(k_chain, cudaFuncAttributeMaxDynamicSharedMemorySize, C::SMEM);
    cudaFuncSetAttribute(k_work, cudaFuncAttributeMaxDynamicSharedMemorySize, W::SMEM);
    void* p;
    cudaGetSymbolAddress(&p, g_x1); p_x1 = (bf16*)p;
    cudaGetSymbolAddress(&p, g_x2); p_x2 = (bf16*)p;
    cudaGetSymbolAddress(&p, g_x3); p_x3 = (bf16*)p;
  }
  CUtensorMap tmWq, tmWk, tmWv, tmWo, tmBo;
  make_map(enc, &tmWq, Wq, NH * DH, DM, 64, 128);
  make_map(enc, &tmWk, Wk, NH * DH, DM, 64, 128);
  make_map(enc, &tmWv, Wv, NH * DH, DM, 64, 128);
  make_map(enc, &tmWo, Wo, DM, NH * DH, 64, 64);
  make_map(enc, &tmBo, Bwo, DM, DM, 64, 64);

  cudaStream_t st = cudaStreamPerThread;
  k_pre<<<256, 256, 0, st>>>(x0, mem0);
  cudaLaunchAttribute at[1];
  at[0].id = cudaLaunchAttributeProgrammaticStreamSerialization; at[0].val.programmaticStreamSerializationAllowed = 1;
  {
    cudaLaunchConfig_t cfg = {};
    cfg.gridDim = dim3(96); cfg.blockDim = dim3(384); cfg.dynamicSmemBytes = C::SMEM; cfg.stream = st;
    cfg.attrs = at; cfg.numAttrs = 0;
    cudaLaunchKernelEx(&cfg, k_chain, tmWq, tmWk, tmWv, tmWo);
  }
  WorkArgs wa;
  wa.res[0] = x0; wa.res[1] = p_x2; wa.xa[0] = p_x1; wa.xa[1] = p_x3; wa.xb[0] = p_x2; wa.xb[1] = out;
  wa.wqkv = Bqkv;
  cudaLaunchConfig_t cfg = {};
  cfg.gridDim = dim3(W::NW); cfg.blockDim = dim3(512); cfg.dynamicSmemBytes = W::SMEM; cfg.stream = st;
  cfg.attrs = at; cfg.numAttrs = NOWORK == 2 ? 0 : 1;
  cudaLaunchKernelEx(&cfg, k_work, tmWo, tmBo, wa);
}
```

```cpp
#include <cuda_runtime.h>
#include <cuda_bf16.h>
#include <cuda.h>
#include <stdint.h>

typedef __nv_bfloat16 bf16;

constexpr int SEQ = 2048, DM = 640, NH = 32, DH = 192, NSEG = 64;
#define LAG 6
constexpr int NSTEP = NSEG + LAG;
constexpr uint32_t SENT = 0xFFFFFFFFu;

constexpr int MAIL9 = 288 * 2048, MAIL_BYTES = MAIL9 + 64 * 3072;
__device__ __align__(1024) uint8_t g_xn[2][NSEG * 40960];
__device__ __align__(1024) uint8_t g_xnb[2][NSEG * 40960];
__device__ __align__(1024) uint8_t g_ob[2][NSEG * 40960];
#define ORING 8
static_assert(ORING > LAG, "a slot is free again LAG + 1 steps later");
__device__ __align__(1024) uint8_t g_o[ORING][2][96][4096];
__device__ __align__(1024) float g_x[SEQ * DM];
__device__ __align__(1024) uint8_t g_mbuf[NSTEP][20480];
__device__ __align__(1024) uint32_t g_flag[NSTEP][768];
__device__ __align__(1024) uint8_t g_mail[2][MAIL_BYTES];
enum { CN_P = 0, CN_L = 128, CN_A = 256, CN_W = 384, CN_X = 512, CN_O = 576, CN_NUM = CN_O + 5 * NSTEP };
__device__ __align__(128) uint32_t g_cnt[CN_NUM][32];
__device__ int g_err;
#define TS(jj, i)
#define TS1(jj, i)
#define PTS(i)
#define TSB(jj, i)
#define TSV(jj, i, v)
#define TS_FLUSH(jj)
#define WTS(l, b, k)
#define WTS1(l, b, k)
#define WW -1

__device__ __forceinline__ uint32_t smem_u32(const void* p) { return (uint32_t)__cvta_generic_to_shared(p); }
__device__ __forceinline__ uint32_t clk32() { uint32_t t; asm volatile("mov.u32 %0, %%clock;" : "=r"(t)::"memory"); return t; }
__device__ __forceinline__ uint32_t mapa(uint32_t a, uint32_t r) { uint32_t o; asm("mapa.shared::cluster.u32 %0,%1,%2;" : "=r"(o) : "r"(a), "r"(r)); return o; }
__device__ __forceinline__ void mbar_init(uint32_t bar, uint32_t cnt) { asm volatile("mbarrier.init.shared::cta.b64 [%0],%1;" ::"r"(bar), "r"(cnt) : "memory"); }
__device__ __forceinline__ void mbar_expect_tx(uint32_t bar, uint32_t bytes) { asm volatile("mbarrier.arrive.expect_tx.shared::cta.b64 _,[%0],%1;" ::"r"(bar), "r"(bytes) : "memory"); }
__device__ __forceinline__ void mbar_arrive(uint32_t bar) { asm volatile("mbarrier.arrive.shared::cta.b64 _,[%0];" ::"r"(bar) : "memory"); }
__device__ __forceinline__ void mbar_arrive_cluster(uint32_t bar) { asm volatile("mbarrier.arrive.shared::cluster.b64 _,[%0];" ::"r"(bar) : "memory"); }
__device__ __forceinline__ bool mbar_try(uint32_t bar, uint32_t ph) {
  uint32_t ok;
  asm volatile("{.reg .pred p; mbarrier.try_wait.parity.shared::cta.b64 p,[%1],%2; selp.u32 %0,1,0,p;}" : "=r"(ok) : "r"(bar), "r"(ph) : "memory");
  return ok;
}
__device__ __forceinline__ int fresh(int x) { asm volatile("" : "+r"(x)); return x; }
#define PHASE_IDS const int tid = fresh(tid0), lane = tid & 31, w = tid >> 5, g = lane >> 2, t = lane & 3; (void)w; (void)g; (void)t
__device__ __forceinline__ void bar_sync(int id, int n) { asm volatile("bar.sync %0,%1;" ::"r"(id), "r"(n) : "memory"); }
__device__ __forceinline__ void bar_arrive(int id, int n) { asm volatile("bar.arrive %0,%1;" ::"r"(id), "r"(n) : "memory"); }
__device__ __forceinline__ bool bar_red_or(int id, int n, bool v) {
  uint32_t r;
  asm volatile("{\n .reg .pred p, q;\n setp.ne.u32 q, %3, 0;\n barrier.cta.red.or.pred p, %1, %2, q;\n selp.u32 %0, 1, 0, p;\n}" : "=r"(r) : "r"(id), "r"(n), "r"((uint32_t)v) : "memory");
  return r != 0;
}
__device__ __forceinline__ void fence_async() { asm volatile("fence.proxy.async.shared::cta;" ::: "memory"); }
__device__ __forceinline__ void bulk_g2s(uint32_t dst, const void* src, uint32_t bytes, uint32_t bar) {
  asm volatile("cp.async.bulk.shared::cluster.global.mbarrier::complete_tx::bytes [%0],[%1],%2,[%3];" ::"r"(dst), "l"(src), "r"(bytes), "r"(bar) : "memory");
}
__device__ __forceinline__ void bulk_g2s_mc(uint32_t dst, const void* src, uint32_t bytes, uint32_t bar) {
  asm volatile("cp.async.bulk.shared::cluster.global.mbarrier::complete_tx::bytes.multicast::cluster [%0],[%1],%2,[%3],%4;"
               ::"r"(dst), "l"(src), "r"(bytes), "r"(bar), "h"((uint16_t)7) : "memory");
}
__device__ __forceinline__ void bulk_s2g(void* dst, uint32_t src, uint32_t bytes) {
  asm volatile("cp.async.bulk.global.shared::cta.bulk_group [%0],[%1],%2;" ::"l"(dst), "r"(src), "r"(bytes) : "memory");
}
__device__ __forceinline__ void bulk_s2c(uint32_t dst, uint32_t src, uint32_t bytes, uint32_t bar) {
  asm volatile("cp.async.bulk.shared::cluster.shared::cta.mbarrier::complete_tx::bytes [%0],[%1],%2,[%3];" ::"r"(dst), "r"(src), "r"(bytes), "r"(bar) : "memory");
}
__device__ __forceinline__ void tma2d(uint32_t dst, const CUtensorMap* tm, int c0, int c1, uint32_t bar) {
  asm volatile("cp.async.bulk.tensor.2d.shared::cluster.global.mbarrier::complete_tx::bytes [%0],[%1,{%3,%4}],[%2];"
               ::"r"(dst), "l"(tm), "r"(bar), "r"(c0), "r"(c1) : "memory");
}
__device__ __forceinline__ void tma2d_prefetch(const CUtensorMap* tm, int c0, int c1) {
  asm volatile("cp.async.bulk.prefetch.tensor.2d.L2.global.tile [%0,{%1,%2}];" ::"l"(tm), "r"(c0), "r"(c1) : "memory");
}
__device__ __forceinline__ uint32_t pack_bf16(float lo, float hi) {
  uint32_t r; asm("cvt.rn.bf16x2.f32 %0,%1,%2;" : "=r"(r) : "f"(hi), "f"(lo)); return r;
}
__device__ __forceinline__ float bf_lo(uint32_t x) { return __uint_as_float(x << 16); }
__device__ __forceinline__ float bf_hi(uint32_t x) { return __uint_as_float(x & 0xFFFF0000u); }
__device__ __forceinline__ float ex2(float x) { float y; asm("ex2.approx.ftz.f32 %0,%1;" : "=f"(y) : "f"(x)); return y; }
__device__ __forceinline__ void ldsm4(uint32_t (&r)[4], uint32_t a) {
  asm volatile("ldmatrix.sync.aligned.m8n8.x4.shared.b16 {%0,%1,%2,%3},[%4];" : "=r"(r[0]), "=r"(r[1]), "=r"(r[2]), "=r"(r[3]) : "r"(a) : "memory");
}
__device__ __forceinline__ void ldsm4t(uint32_t (&r)[4], uint32_t a) {
  asm volatile("ldmatrix.sync.aligned.m8n8.x4.trans.shared.b16 {%0,%1,%2,%3},[%4];" : "=r"(r[0]), "=r"(r[1]), "=r"(r[2]), "=r"(r[3]) : "r"(a) : "memory");
}
__device__ __forceinline__ void ldsm2(uint32_t& r0, uint32_t& r1, uint32_t a) {
  asm volatile("ldmatrix.sync.aligned.m8n8.x2.shared.b16 {%0,%1},[%2];" : "=r"(r0), "=r"(r1) : "r"(a) : "memory");
}
__device__ __forceinline__ void ldsm1(uint32_t& r0, uint32_t a) {
  asm volatile("ldmatrix.sync.aligned.m8n8.x1.shared.b16 {%0},[%1];" : "=r"(r0) : "r"(a) : "memory");
}
__device__ __forceinline__ void mma16816(float (&d)[4], uint32_t a0, uint32_t a1, uint32_t a2, uint32_t a3, uint32_t b0, uint32_t b1) {
  asm volatile("mma.sync.aligned.m16n8k16.row.col.f32.bf16.bf16.f32 {%0,%1,%2,%3},{%4,%5,%6,%7},{%8,%9},{%0,%1,%2,%3};"
               : "+f"(d[0]), "+f"(d[1]), "+f"(d[2]), "+f"(d[3]) : "r"(a0), "r"(a1), "r"(a2), "r"(a3), "r"(b0), "r"(b1));
}
__device__ __forceinline__ void mma1688(float (&d)[4], uint32_t a0, uint32_t a1, uint32_t b0) {
  asm volatile("mma.sync.aligned.m16n8k8.row.col.f32.bf16.bf16.f32 {%0,%1,%2,%3},{%4,%5},{%6},{%0,%1,%2,%3};"
               : "+f"(d[0]), "+f"(d[1]), "+f"(d[2]), "+f"(d[3]) : "r"(a0), "r"(a1), "r"(b0));
}
__device__ __forceinline__ void sts32(uint32_t a, uint32_t v) { asm volatile("st.shared.b32 [%0],%1;" ::"r"(a), "r"(v) : "memory"); }
__device__ __forceinline__ void sts64f(uint32_t a, float x, float y) { asm volatile("st.shared.v2.f32 [%0],{%1,%2};" ::"r"(a), "f"(x), "f"(y) : "memory"); }
__device__ __forceinline__ void sts128(uint32_t a, uint4 v) { asm volatile("st.shared.v4.b32 [%0],{%1,%2,%3,%4};" ::"r"(a), "r"(v.x), "r"(v.y), "r"(v.z), "r"(v.w) : "memory"); }
__device__ __forceinline__ float lds32f(uint32_t a) { float v; asm volatile("ld.shared.f32 %0,[%1];" : "=f"(v) : "r"(a) : "memory"); return v; }
__device__ __forceinline__ float2 lds64f(uint32_t a) { float2 v; asm volatile("ld.shared.v2.f32 {%0,%1},[%2];" : "=f"(v.x), "=f"(v.y) : "r"(a) : "memory"); return v; }
__device__ __forceinline__ uint4 lds128(uint32_t a) { uint4 v; asm volatile("ld.shared.v4.b32 {%0,%1,%2,%3},[%4];" : "=r"(v.x), "=r"(v.y), "=r"(v.z), "=r"(v.w) : "r"(a) : "memory"); return v; }
__device__ __forceinline__ float4 lds128f(uint32_t a) { float4 v; asm volatile("ld.shared.v4.f32 {%0,%1,%2,%3},[%4];" : "=f"(v.x), "=f"(v.y), "=f"(v.z), "=f"(v.w) : "r"(a) : "memory"); return v; }
__device__ __forceinline__ void st_async2(uint32_t a, float x, float y, uint32_t bar) {
  asm volatile("st.async.weak.shared::cluster.mbarrier::complete_tx::bytes.v2.f32 [%0],{%1,%2},[%3];" ::"r"(a), "f"(x), "f"(y), "r"(bar) : "memory");
}
__device__ __forceinline__ void st_async4(uint32_t a, const float (&v)[4], uint32_t bar) {
  asm volatile("st.async.weak.shared::cluster.mbarrier::complete_tx::bytes.v4.f32 [%0],{%1,%2,%3,%4},[%5];" ::"r"(a), "f"(v[0]), "f"(v[1]), "f"(v[2]), "f"(v[3]), "r"(bar) : "memory");
}
__device__ __forceinline__ void st_async4v(uint32_t a, float x, float y, float z, float w, uint32_t bar) {
  asm volatile("st.async.weak.shared::cluster.mbarrier::complete_tx::bytes.v4.f32 [%0],{%1,%2,%3,%4},[%5];" ::"r"(a), "f"(x), "f"(y), "f"(z), "f"(w), "r"(bar) : "memory");
}
__device__ __forceinline__ void st_async4u(uint32_t a, const uint4& v, uint32_t bar) {
  asm volatile("st.async.weak.shared::cluster.mbarrier::complete_tx::bytes.v4.b32 [%0],{%1,%2,%3,%4},[%5];" ::"r"(a), "r"(v.x), "r"(v.y), "r"(v.z), "r"(v.w), "r"(bar) : "memory");
}
__device__ __forceinline__ uint4 ld_relaxed4(const void* p) {
  uint4 v; asm volatile("ld.relaxed.gpu.global.v4.u32 {%0,%1,%2,%3},[%4];" : "=r"(v.x), "=r"(v.y), "=r"(v.z), "=r"(v.w) : "l"(p) : "memory"); return v;
}
__device__ __forceinline__ uint32_t ld_relaxed(const void* p) {
  uint32_t v; asm volatile("ld.relaxed.gpu.global.u32 %0,[%1];" : "=r"(v) : "l"(p) : "memory"); return v;
}
__device__ __forceinline__ void st_relaxed(void* p, uint32_t v) { asm volatile("st.relaxed.gpu.global.b32 [%0],%1;" ::"l"(p), "r"(v) : "memory"); }
__device__ __forceinline__ void st_relaxed4(void* p, uint32_t v) { asm volatile("st.relaxed.gpu.global.v4.b32 [%0],{%1,%1,%1,%1};" ::"l"(p), "r"(v) : "memory"); }

__device__ __forceinline__ uint32_t ld_acquire(const void* p) {
  uint32_t v; asm volatile("ld.acquire.gpu.global.u32 %0,[%1];" : "=r"(v) : "l"(p) : "memory"); return v;
}
__device__ __forceinline__ float4 ld_relaxed4f(const void* p) {
  float4 v; asm volatile("ld.relaxed.gpu.global.v4.f32 {%0,%1,%2,%3},[%4];" : "=f"(v.x), "=f"(v.y), "=f"(v.z), "=f"(v.w) : "l"(p) : "memory"); return v;
}
__device__ __forceinline__ float2 ld_relaxed2f(const void* p) {
  float2 v; asm volatile("ld.relaxed.gpu.global.v2.f32 {%0,%1},[%2];" : "=f"(v.x), "=f"(v.y) : "l"(p) : "memory"); return v;
}
__device__ __forceinline__ void prefetch_l2(const void* p) { asm volatile("prefetch.global.L2 [%0];" ::"l"(p)); }
__device__ __forceinline__ void fence_gpu() { asm volatile("fence.acq_rel.gpu;" ::: "memory"); }
__device__ __forceinline__ void fence_async_all() { asm volatile("fence.proxy.async.global;" ::: "memory"); }
constexpr int SPIN_TOT = 1 << 22;
__device__ __forceinline__ void csignal(int idx) { asm volatile("red.release.gpu.global.add.u32 [%0],1;" ::"l"(&g_cnt[idx][0]) : "memory"); }
__device__ __forceinline__ void cwait(int idx, uint32_t target, int& spin) {
  while (ld_acquire(&g_cnt[idx][0]) < target && spin < SPIN_TOT) spin += 16;
}

__device__ __forceinline__ uint64_t mkdesc(uint32_t addr, uint32_t lbo, uint32_t sbo) {
  return (uint64_t)((addr & 0x3FFFF) >> 4) | ((uint64_t)(lbo >> 4) << 16) | ((uint64_t)(sbo >> 4) << 32) | ((uint64_t)1 << 62);
}
__device__ __forceinline__ uint64_t mkdesc_ns(uint32_t addr, uint32_t lbo, uint32_t sbo) {
  return (uint64_t)((addr & 0x3FFFF) >> 4) | ((uint64_t)(lbo >> 4) << 16) | ((uint64_t)(sbo >> 4) << 32);
}
__device__ __forceinline__ void wg_fence() { asm volatile("wgmma.fence.sync.aligned;" ::: "memory"); }
__device__ __forceinline__ void wg_commit() { asm volatile("wgmma.commit_group.sync.aligned;" ::: "memory"); }
template <int N> __device__ __forceinline__ void wg_wait() { asm volatile("wgmma.wait_group.sync.aligned %0;" ::"n"(N) : "memory"); }

__device__ __forceinline__ void wgmma_rs16(float (&d)[8], const uint32_t (&a)[4], uint64_t db, int sc) {
  asm volatile("{.reg .pred p; setp.ne.b32 p,%13,0; wgmma.mma_async.sync.aligned.m64n16k16.f32.bf16.bf16 "
               "{%0,%1,%2,%3,%4,%5,%6,%7},{%8,%9,%10,%11},%12,p,1,1,0;}"
               : "+f"(d[0]), "+f"(d[1]), "+f"(d[2]), "+f"(d[3]), "+f"(d[4]), "+f"(d[5]), "+f"(d[6]), "+f"(d[7])
               : "r"(a[0]), "r"(a[1]), "r"(a[2]), "r"(a[3]), "l"(db), "r"(sc));
}
__device__ __forceinline__ void wgmma_rs64(float (&d)[32], const uint32_t (&a)[4], uint64_t db, int sc) {
  asm volatile("{.reg .pred p; setp.ne.b32 p,%37,0; wgmma.mma_async.sync.aligned.m64n64k16.f32.bf16.bf16 "
               "{%0,%1,%2,%3,%4,%5,%6,%7,%8,%9,%10,%11,%12,%13,%14,%15,%16,%17,%18,%19,%20,%21,%22,%23,%24,%25,%26,%27,%28,%29,%30,%31},{%32,%33,%34,%35},%36,p,1,1,0;}"
               : "+f"(d[0]), "+f"(d[1]), "+f"(d[2]), "+f"(d[3]), "+f"(d[4]), "+f"(d[5]), "+f"(d[6]), "+f"(d[7]), "+f"(d[8]), "+f"(d[9]), "+f"(d[10]), "+f"(d[11]), "+f"(d[12]), "+f"(d[13]), "+f"(d[14]), "+f"(d[15]), "+f"(d[16]), "+f"(d[17]), "+f"(d[18]), "+f"(d[19]), "+f"(d[20]), "+f"(d[21]), "+f"(d[22]), "+f"(d[23]), "+f"(d[24]), "+f"(d[25]), "+f"(d[26]), "+f"(d[27]), "+f"(d[28]), "+f"(d[29]), "+f"(d[30]), "+f"(d[31])
               : "r"(a[0]), "r"(a[1]), "r"(a[2]), "r"(a[3]), "l"(db), "r"(sc));
}
__device__ __forceinline__ void wgmma_rt16(float (&d)[8], const uint32_t (&a)[4], uint64_t db, int sc) {
  asm volatile("{.reg .pred p; setp.ne.b32 p,%13,0; wgmma.mma_async.sync.aligned.m64n16k16.f32.bf16.bf16 "
               "{%0,%1,%2,%3,%4,%5,%6,%7},{%8,%9,%10,%11},%12,p,1,1,1;}"
               : "+f"(d[0]), "+f"(d[1]), "+f"(d[2]), "+f"(d[3]), "+f"(d[4]), "+f"(d[5]), "+f"(d[6]), "+f"(d[7])
               : "r"(a[0]), "r"(a[1]), "r"(a[2]), "r"(a[3]), "l"(db), "r"(sc));
}
__device__ __forceinline__ void wgmma_rt80(float (&d)[40], const uint32_t (&a)[4], uint64_t db, int sc) {
  asm volatile("{.reg .pred p; setp.ne.b32 p,%45,0; wgmma.mma_async.sync.aligned.m64n80k16.f32.bf16.bf16 "
               "{%0,%1,%2,%3,%4,%5,%6,%7,%8,%9,%10,%11,%12,%13,%14,%15,%16,%17,%18,%19,%20,%21,%22,%23,%24,%25,%26,%27,%28,%29,%30,%31,%32,%33,%34,%35,%36,%37,%38,%39},{%40,%41,%42,%43},%44,p,1,1,1;}"
               : "+f"(d[0]), "+f"(d[1]), "+f"(d[2]), "+f"(d[3]), "+f"(d[4]), "+f"(d[5]), "+f"(d[6]), "+f"(d[7]), "+f"(d[8]), "+f"(d[9]), "+f"(d[10]), "+f"(d[11]), "+f"(d[12]), "+f"(d[13]), "+f"(d[14]), "+f"(d[15]), "+f"(d[16]), "+f"(d[17]), "+f"(d[18]), "+f"(d[19]), "+f"(d[20]), "+f"(d[21]), "+f"(d[22]), "+f"(d[23]), "+f"(d[24]), "+f"(d[25]), "+f"(d[26]), "+f"(d[27]), "+f"(d[28]), "+f"(d[29]), "+f"(d[30]), "+f"(d[31]), "+f"(d[32]), "+f"(d[33]), "+f"(d[34]), "+f"(d[35]), "+f"(d[36]), "+f"(d[37]), "+f"(d[38]), "+f"(d[39])
               : "r"(a[0]), "r"(a[1]), "r"(a[2]), "r"(a[3]), "l"(db), "r"(sc));
}
__device__ __forceinline__ void wgmma_rs32(float (&d)[16], const uint32_t (&a)[4], uint64_t db, int sc) {
  asm volatile("{.reg .pred p; setp.ne.b32 p,%21,0; wgmma.mma_async.sync.aligned.m64n32k16.f32.bf16.bf16 "
               "{%0,%1,%2,%3,%4,%5,%6,%7,%8,%9,%10,%11,%12,%13,%14,%15},{%16,%17,%18,%19},%20,p,1,1,0;}"
               : "+f"(d[0]), "+f"(d[1]), "+f"(d[2]), "+f"(d[3]), "+f"(d[4]), "+f"(d[5]), "+f"(d[6]), "+f"(d[7]), "+f"(d[8]), "+f"(d[9]), "+f"(d[10]), "+f"(d[11]), "+f"(d[12]), "+f"(d[13]), "+f"(d[14]), "+f"(d[15])
               : "r"(a[0]), "r"(a[1]), "r"(a[2]), "r"(a[3]), "l"(db), "r"(sc));
}
__device__ __forceinline__ void wgmma_ts32(float (&d)[16], uint64_t da, uint64_t db, int sc) {
  asm volatile("{.reg .pred p; setp.ne.b32 p,%18,0; wgmma.mma_async.sync.aligned.m64n32k16.f32.bf16.bf16 "
               "{%0,%1,%2,%3,%4,%5,%6,%7,%8,%9,%10,%11,%12,%13,%14,%15},%16,%17,p,1,1,1,0;}"
               : "+f"(d[0]), "+f"(d[1]), "+f"(d[2]), "+f"(d[3]), "+f"(d[4]), "+f"(d[5]), "+f"(d[6]), "+f"(d[7]), "+f"(d[8]), "+f"(d[9]), "+f"(d[10]), "+f"(d[11]), "+f"(d[12]), "+f"(d[13]), "+f"(d[14]), "+f"(d[15])
               : "l"(da), "l"(db), "r"(sc));
}
__device__ __forceinline__ void wgmma_ts16(float (&d)[8], uint64_t da, uint64_t db, int sc) {
  asm volatile("{.reg .pred p; setp.ne.b32 p,%10,0; wgmma.mma_async.sync.aligned.m64n16k16.f32.bf16.bf16 "
               "{%0,%1,%2,%3,%4,%5,%6,%7},%8,%9,p,1,1,1,0;}"
               : "+f"(d[0]), "+f"(d[1]), "+f"(d[2]), "+f"(d[3]), "+f"(d[4]), "+f"(d[5]), "+f"(d[6]), "+f"(d[7])
               : "l"(da), "l"(db), "r"(sc));
}
__device__ __forceinline__ void wgmma_ts64(float (&d)[32], uint64_t da, uint64_t db, int sc) {
  asm volatile("{.reg .pred p; setp.ne.b32 p,%34,0; wgmma.mma_async.sync.aligned.m64n64k16.f32.bf16.bf16 "
               "{%0,%1,%2,%3,%4,%5,%6,%7,%8,%9,%10,%11,%12,%13,%14,%15,%16,%17,%18,%19,%20,%21,%22,%23,%24,%25,%26,%27,%28,%29,%30,%31},%32,%33,p,1,1,1,0;}"
               : "+f"(d[0]), "+f"(d[1]), "+f"(d[2]), "+f"(d[3]), "+f"(d[4]), "+f"(d[5]), "+f"(d[6]), "+f"(d[7]), "+f"(d[8]), "+f"(d[9]), "+f"(d[10]), "+f"(d[11]), "+f"(d[12]), "+f"(d[13]), "+f"(d[14]), "+f"(d[15]), "+f"(d[16]), "+f"(d[17]), "+f"(d[18]), "+f"(d[19]), "+f"(d[20]), "+f"(d[21]), "+f"(d[22]), "+f"(d[23]), "+f"(d[24]), "+f"(d[25]), "+f"(d[26]), "+f"(d[27]), "+f"(d[28]), "+f"(d[29]), "+f"(d[30]), "+f"(d[31])
               : "l"(da), "l"(db), "r"(sc));
}
__device__ __forceinline__ void wgmma_tt16(float (&d)[8], uint64_t da, uint64_t db, int sc) {
  asm volatile("{.reg .pred p; setp.ne.b32 p,%10,0; wgmma.mma_async.sync.aligned.m64n16k16.f32.bf16.bf16 "
               "{%0,%1,%2,%3,%4,%5,%6,%7},%8,%9,p,1,1,1,1;}"
               : "+f"(d[0]), "+f"(d[1]), "+f"(d[2]), "+f"(d[3]), "+f"(d[4]), "+f"(d[5]), "+f"(d[6]), "+f"(d[7])
               : "l"(da), "l"(db), "r"(sc));
}
__device__ __forceinline__ void wgmma_tt40(float (&d)[20], uint64_t da, uint64_t db, int sc) {
  asm volatile("{.reg .pred p; setp.ne.b32 p,%22,0; wgmma.mma_async.sync.aligned.m64n40k16.f32.bf16.bf16 "
               "{%0,%1,%2,%3,%4,%5,%6,%7,%8,%9,%10,%11,%12,%13,%14,%15,%16,%17,%18,%19},%20,%21,p,1,1,1,1;}"
               : "+f"(d[0]), "+f"(d[1]), "+f"(d[2]), "+f"(d[3]), "+f"(d[4]), "+f"(d[5]), "+f"(d[6]), "+f"(d[7]), "+f"(d[8]), "+f"(d[9]), "+f"(d[10]), "+f"(d[11]), "+f"(d[12]), "+f"(d[13]), "+f"(d[14]), "+f"(d[15]), "+f"(d[16]), "+f"(d[17]), "+f"(d[18]), "+f"(d[19])
               : "l"(da), "l"(db), "r"(sc));
}
__device__ __forceinline__ void wgmma_ss8(float (&d)[4], uint64_t da, uint64_t db, int sc) {
  asm volatile("{.reg .pred p; setp.ne.b32 p,%6,0; wgmma.mma_async.sync.aligned.m64n8k16.f32.bf16.bf16 "
               "{%0,%1,%2,%3},%4,%5,p,1,1,0,0;}"
               : "+f"(d[0]), "+f"(d[1]), "+f"(d[2]), "+f"(d[3])
               : "l"(da), "l"(db), "r"(sc));
}
__device__ __forceinline__ void wgmma_ss32(float (&d)[16], uint64_t da, uint64_t db, int sc) {
  asm volatile("{.reg .pred p; setp.ne.b32 p,%18,0; wgmma.mma_async.sync.aligned.m64n32k16.f32.bf16.bf16 "
               "{%0,%1,%2,%3,%4,%5,%6,%7,%8,%9,%10,%11,%12,%13,%14,%15},%16,%17,p,1,1,0,0;}"
               : "+f"(d[0]), "+f"(d[1]), "+f"(d[2]), "+f"(d[3]), "+f"(d[4]), "+f"(d[5]), "+f"(d[6]), "+f"(d[7]), "+f"(d[8]), "+f"(d[9]), "+f"(d[10]), "+f"(d[11]), "+f"(d[12]), "+f"(d[13]), "+f"(d[14]), "+f"(d[15])
               : "l"(da), "l"(db), "r"(sc));
}
__device__ __forceinline__ void wgmma_st64(float (&d)[32], uint64_t da, uint64_t db, int sc) {
  asm volatile("{.reg .pred p; setp.ne.b32 p,%34,0; wgmma.mma_async.sync.aligned.m64n64k16.f32.bf16.bf16 "
               "{%0,%1,%2,%3,%4,%5,%6,%7,%8,%9,%10,%11,%12,%13,%14,%15,%16,%17,%18,%19,%20,%21,%22,%23,%24,%25,%26,%27,%28,%29,%30,%31},%32,%33,p,1,1,0,1;}"
               : "+f"(d[0]), "+f"(d[1]), "+f"(d[2]), "+f"(d[3]), "+f"(d[4]), "+f"(d[5]), "+f"(d[6]), "+f"(d[7]), "+f"(d[8]), "+f"(d[9]), "+f"(d[10]), "+f"(d[11]), "+f"(d[12]), "+f"(d[13]), "+f"(d[14]), "+f"(d[15]), "+f"(d[16]), "+f"(d[17]), "+f"(d[18]), "+f"(d[19]), "+f"(d[20]), "+f"(d[21]), "+f"(d[22]), "+f"(d[23]), "+f"(d[24]), "+f"(d[25]), "+f"(d[26]), "+f"(d[27]), "+f"(d[28]), "+f"(d[29]), "+f"(d[30]), "+f"(d[31])
               : "l"(da), "l"(db), "r"(sc));
}
__device__ __forceinline__ void wgmma_st128(float (&d)[64], uint64_t da, uint64_t db, int sc) {
  asm volatile("{.reg .pred p; setp.ne.b32 p,%66,0; wgmma.mma_async.sync.aligned.m64n128k16.f32.bf16.bf16 "
               "{%0,%1,%2,%3,%4,%5,%6,%7,%8,%9,%10,%11,%12,%13,%14,%15,%16,%17,%18,%19,%20,%21,%22,%23,%24,%25,%26,%27,%28,%29,%30,%31,%32,%33,%34,%35,%36,%37,%38,%39,%40,%41,%42,%43,%44,%45,%46,%47,%48,%49,%50,%51,%52,%53,%54,%55,%56,%57,%58,%59,%60,%61,%62,%63},%64,%65,p,1,1,0,1;}"
               : "+f"(d[0]), "+f"(d[1]), "+f"(d[2]), "+f"(d[3]), "+f"(d[4]), "+f"(d[5]), "+f"(d[6]), "+f"(d[7]), "+f"(d[8]), "+f"(d[9]), "+f"(d[10]), "+f"(d[11]), "+f"(d[12]), "+f"(d[13]), "+f"(d[14]), "+f"(d[15]), "+f"(d[16]), "+f"(d[17]), "+f"(d[18]), "+f"(d[19]), "+f"(d[20]), "+f"(d[21]), "+f"(d[22]), "+f"(d[23]), "+f"(d[24]), "+f"(d[25]), "+f"(d[26]), "+f"(d[27]), "+f"(d[28]), "+f"(d[29]), "+f"(d[30]), "+f"(d[31]), "+f"(d[32]), "+f"(d[33]), "+f"(d[34]), "+f"(d[35]), "+f"(d[36]), "+f"(d[37]), "+f"(d[38]), "+f"(d[39]), "+f"(d[40]), "+f"(d[41]), "+f"(d[42]), "+f"(d[43]), "+f"(d[44]), "+f"(d[45]), "+f"(d[46]), "+f"(d[47]), "+f"(d[48]), "+f"(d[49]), "+f"(d[50]), "+f"(d[51]), "+f"(d[52]), "+f"(d[53]), "+f"(d[54]), "+f"(d[55]), "+f"(d[56]), "+f"(d[57]), "+f"(d[58]), "+f"(d[59]), "+f"(d[60]), "+f"(d[61]), "+f"(d[62]), "+f"(d[63])
               : "l"(da), "l"(db), "r"(sc));
}

__device__ __forceinline__ void stsm4(uint32_t a, uint32_t r0, uint32_t r1, uint32_t r2, uint32_t r3) {
  asm volatile("stmatrix.sync.aligned.m8n8.x4.shared.b16 [%0],{%1,%2,%3,%4};" ::"r"(a), "r"(r0), "r"(r1), "r"(r2), "r"(r3) : "memory");
}
__device__ __forceinline__ void stsm4t(uint32_t a, uint32_t r0, uint32_t r1, uint32_t r2, uint32_t r3) {
  asm volatile("stmatrix.sync.aligned.m8n8.x4.trans.shared.b16 [%0],{%1,%2,%3,%4};" ::"r"(a), "r"(r0), "r"(r1), "r"(r2), "r"(r3) : "memory");
}
__device__ __forceinline__ void sts64(uint32_t a, uint32_t x, uint32_t y) { asm volatile("st.shared.v2.b32 [%0],{%1,%2};" ::"r"(a), "r"(x), "r"(y) : "memory"); }
__device__ __forceinline__ void st_async2u(uint32_t a, uint32_t x, uint32_t y, uint32_t bar) {
  asm volatile("st.async.weak.shared::cluster.mbarrier::complete_tx::bytes.v2.b32 [%0],{%1,%2},[%3];" ::"r"(a), "r"(x), "r"(y), "r"(bar) : "memory");
}
__device__ __forceinline__ void st_relaxed128(void* p, uint32_t x, uint32_t y, uint32_t z, uint32_t w) {
  asm volatile("{.reg .b128 v; mov.b128 v,{%1,%2,%3,%4}; st.relaxed.gpu.global.b128 [%0],v;}" ::"l"(p), "r"(x), "r"(y), "r"(z), "r"(w) : "memory");
}
__device__ __forceinline__ void st_relaxed64(void* p, uint32_t x, uint32_t y) {
  asm volatile("{.reg .b64 v; mov.b64 v,{%1,%2}; st.relaxed.gpu.global.b64 [%0],v;}" ::"l"(p), "r"(x), "r"(y) : "memory");
}
__device__ __forceinline__ uint4 ld_relaxed128(const void* p) {
  uint4 v;
  asm volatile("{.reg .b128 v; .reg .b64 lo, hi; ld.relaxed.gpu.global.b128 v,[%4]; mov.b128 {lo,hi},v; mov.b64 {%0,%1},lo; mov.b64 {%2,%3},hi;}" : "=r"(v.x), "=r"(v.y), "=r"(v.z), "=r"(v.w) : "l"(p) : "memory");
  return v;
}

__device__ __forceinline__ uint32_t pack_h2(float lo, float hi) {
  uint32_t r; asm("cvt.rn.satfinite.f16x2.f32 %0,%1,%2;" : "=r"(r) : "f"(hi), "f"(lo)); return r;
}
__device__ __forceinline__ void add_h2(float& lo, float& hi, uint32_t u, uint32_t v) {
  float a, b;
  asm("{.reg .b16 l, h; .reg .b32 s; add.rn.f16x2 s,%2,%3; mov.b32 {l,h},s; cvt.f32.f16 %0,l; cvt.f32.f16 %1,h;}" : "=f"(a), "=f"(b) : "r"(u), "r"(v));
  lo += a; hi += b;
}
__device__ __forceinline__ void mwait(uint32_t bar, uint32_t ph, int& spin) {
  asm volatile("{.reg .pred p, q;\nWAIT_LOOP:\n add.s32 %0,%0,1;\n setp.lt.s32 q,%0,%3;\n mbarrier.try_wait.parity.shared::cta.b64 p,[%1],%2;\n not.pred p,p;\n and.pred q,q,p;\n @q bra.uni WAIT_LOOP;\n}"
               : "+&r"(spin) : "r"(bar), "r"(ph), "n"(SPIN_TOT) : "memory");
}
__device__ __forceinline__ int keep(int x) { return __shfl_sync(0xffffffffu, x, threadIdx.x & 31); }
__device__ __forceinline__ uint32_t pin(uint32_t x) { asm volatile("" : "+r"(x)); return x; }
template <typename T> __device__ __forceinline__ T* pinp(T* x) { asm volatile("" : "+l"(x)); return x; }
__device__ __forceinline__ void st_async1u(uint32_t a, uint32_t x, uint32_t bar) {
  asm volatile("st.async.weak.shared::cluster.mbarrier::complete_tx::bytes.b32 [%0],%1,[%2];" ::"r"(a), "r"(x), "r"(bar) : "memory");
}
__device__ __forceinline__ uint32_t lds32(uint32_t a) { uint32_t v; asm volatile("ld.shared.b32 %0,[%1];" : "=r"(v) : "r"(a) : "memory"); return v; }
__device__ __forceinline__ uint2 lds64(uint32_t a) { uint2 v; asm volatile("ld.shared.v2.b32 {%0,%1},[%2];" : "=r"(v.x), "=r"(v.y) : "r"(a) : "memory"); return v; }

__device__ __forceinline__ void permute_cols(uint32_t tile, int tid) {
  for (int it = tid; it < 2560; it += 128) {
    const int row = it >> 2, q = it & 3;
    const uint32_t a0 = tile + row * 128 + (((2 * q) ^ (row & 7)) << 4), a1 = tile + row * 128 + (((2 * q + 1) ^ (row & 7)) << 4);
    const uint4 u = lds128(a0), v = lds128(a1);
    sts128(a0, make_uint4(__byte_perm(u.x, u.y, 0x5410), __byte_perm(u.z, u.w, 0x5410), __byte_perm(v.x, v.y, 0x5410), __byte_perm(v.z, v.w, 0x5410)));
    sts128(a1, make_uint4(__byte_perm(u.x, u.y, 0x7632), __byte_perm(u.z, u.w, 0x7632), __byte_perm(v.x, v.y, 0x7632), __byte_perm(v.z, v.w, 0x7632)));
  }
}

__device__ __forceinline__ void ln_row_to_image(const bf16* __restrict__ x, uint8_t* __restrict__ img, int row, int lane) {
  const uint4* src = reinterpret_cast<const uint4*>(x + (size_t)row * DM);
  uint4 v[3];
  v[0] = src[lane]; v[1] = src[lane + 32];
  v[2] = lane < 16 ? src[lane + 64] : make_uint4(0, 0, 0, 0);
  float s = 0.f;
#pragma unroll
  for (int i = 0; i < 3; i++) {
    s += bf_lo(v[i].x) + bf_hi(v[i].x) + bf_lo(v[i].y) + bf_hi(v[i].y) + bf_lo(v[i].z) + bf_hi(v[i].z) + bf_lo(v[i].w) + bf_hi(v[i].w);
  }
#pragma unroll
  for (int o = 16; o > 0; o >>= 1) s += __shfl_xor_sync(0xffffffffu, s, o);
  const float mean = s * (1.f / DM);
  float q = 0.f;
#pragma unroll
  for (int i = 0; i < 3; i++) {
    if (i < 2 || lane < 16) {
      const uint32_t w[4] = {v[i].x, v[i].y, v[i].z, v[i].w};
#pragma unroll
      for (int j = 0; j < 4; j++) { float a = bf_lo(w[j]) - mean, b = bf_hi(w[j]) - mean; q += a * a + b * b; }
    }
  }
#pragma unroll
  for (int o = 16; o > 0; o >>= 1) q += __shfl_xor_sync(0xffffffffu, q, o);
  const float rstd = rsqrtf(q * (1.f / DM) + 1e-5f);
#pragma unroll
  for (int i = 0; i < 3; i++) {
    if (i < 2 || lane < 16) {
      const int c = lane + 32 * i;
      uint4 o;
      o.x = pack_bf16((bf_lo(v[i].x) - mean) * rstd, (bf_hi(v[i].x) - mean) * rstd);
      o.y = pack_bf16((bf_lo(v[i].y) - mean) * rstd, (bf_hi(v[i].y) - mean) * rstd);
      o.z = pack_bf16((bf_lo(v[i].z) - mean) * rstd, (bf_hi(v[i].z) - mean) * rstd);
      o.w = pack_bf16((bf_lo(v[i].w) - mean) * rstd, (bf_hi(v[i].w) - mean) * rstd);
      const size_t off = (size_t)(row >> 5) * 40960 + (c >> 4) * 8192 + ((row >> 3) & 3) * 2048 + ((c >> 3) & 1) * 1024 + (row & 7) * 128 + (((c & 7) ^ (row & 7)) << 4);
      *reinterpret_cast<uint4*>(img + off) = o;
      float4* xf = reinterpret_cast<float4*>(g_x + (size_t)row * DM + c * 8);
      xf[0] = make_float4(bf_lo(v[i].x), bf_hi(v[i].x), bf_lo(v[i].y), bf_hi(v[i].y));
      xf[1] = make_float4(bf_lo(v[i].z), bf_hi(v[i].z), bf_lo(v[i].w), bf_hi(v[i].w));
    }
  }
}

__global__ void __launch_bounds__(256) k_pre(const bf16* __restrict__ x, const bf16* __restrict__ mem0) {
  const int row = blockIdx.x * 8 + (threadIdx.x >> 5);
  ln_row_to_image(x, g_xn[0], row, threadIdx.x & 31);
  const int gt = blockIdx.x * 256 + threadIdx.x;
  const uint4 sent = make_uint4(SENT, SENT, SENT, SENT);
  uint4* mail = reinterpret_cast<uint4*>(&g_mail[0][0]);
  for (int i = gt; i < 2 * MAIL_BYTES / 16; i += 65536) mail[i] = sent;
  uint4* mb = reinterpret_cast<uint4*>(&g_mbuf[0][0]);
  for (int i = gt; i < NSTEP * 1280; i += 65536) {
    const int p = i % 1280, st = i / 1280;
    uint4 v = sent;
    if (st == 0 || (st == LAG && (p & 8))) v = *reinterpret_cast<const uint4*>(mem0 + (p & 7) * DM + (p >> 4) * 8);
    mb[i] = v;
  }
  if (gt < NSTEP * 192) reinterpret_cast<uint4*>(&g_flag[0][0])[gt] = gt < 192 ? make_uint4(0, 0, 0, 0) : sent;
  if (gt < CN_NUM) g_cnt[gt][0] = 0;
}

namespace C {
constexpr int NKR = 37;
constexpr int OFF_WQ = 0, OFF_WK = 81920;
constexpr int OFF_YO = 163840, OFF_YV = OFF_YO + 6144;
constexpr int OFF_M = 176128;
__host__ __device__ constexpr int og_off(int c) { return c ? OFF_M + 14336 + c * 2048 : 229376; }
constexpr int OFF_KT = 196608;
constexpr int OFF_XT = OFF_KT + 10240;
constexpr int OFF_VT = OFF_XT + 7168;
constexpr int OFF_XM = OFF_VT + 11392;
constexpr int KS = 1280, VS = 1408;
__host__ __device__ constexpr int slot_off(int p) { return p == 2 ? OFF_M : OFF_KT + (p % 3) * 16384; }
constexpr int OFF_BAR = 231552;
constexpr int OFF_SAFE = OFF_BAR + 160;
constexpr int OFF_TS = OFF_BAR + 256;
constexpr int SMEM = 232448;
constexpr uint32_t SB0 = 1024;
constexpr int BAR_F = OFF_BAR, BAR_E = OFF_BAR + 40, BAR_M = OFF_BAR + 80, BAR_MOK = OFF_BAR + 88, BAR_XM = OFF_BAR + 96, BAR_XF = OFF_BAR + 104,
              BAR_XT = OFF_BAR + 112, BAR_MF = OFF_BAR + 120, BAR_OG = OFF_BAR + 128, BAR_W = OFF_BAR + 136, FLG_REDO = OFF_BAR + 144;
constexpr int NB_PRO = 1, NB_RD = 2, NB_MR = 3, NB_QK = 4, NB_SM = 5, NB_VA = 6, NB_VQ = 7, NB_A = 8, NB_Q = 9, NB_C = 10, NB_WQ = 11, NB_QI = 12, NB_SI = 13, NB_WV = 14;
#define B1 300
#define B2 400
#define FLP 0
#define OSG 2
#define QIE 4
#define SIE 2
#define WOE 1
#define OGF 0
#define VSP 8
#define RFK 5
#define PFD 3
#define WOL 0
#define NOWORK 0
constexpr float SCL = 0.07216878364870322f * 1.4426950408889634f / 256;
}

#define CBAR_SYNC(id, n) bar_sync(id, n)
#define CBAR_ARRIVE(id, n) bar_arrive(id, n)

__device__ __forceinline__ uint64_t wdesc(int off) { return mkdesc(C::SB0 + off, 8192, 1024); }
__device__ __forceinline__ uint64_t mdesc(int k) { return mkdesc_ns(C::SB0 + C::OFF_M + k * 512, 256, 128); }
__device__ __forceinline__ uint64_t tdesc(int k) { return mkdesc(C::SB0 + C::slot_off(k >> 3) + ((k >> 2) & 1) * 1024 + (k & 3) * 32, 16, 2048); }

__device__ __forceinline__ int dh_row(int n) { return (n & ~63) + (n & 32) + ((n >> 1) & 3) * 8 + ((n >> 3) & 3) * 2 + (n & 1); }
template <bool PERM>
__device__ __forceinline__ void load_weights_rs(uint32_t (&wf)[C::NKR][4], uint32_t sb, int stage, int yoff, int tid0) {
  using namespace C;
  const int i = (tid0 >> 3) & 3, n0 = (tid0 & 7) + (i >> 1) * 8;
  const int chunk = 2 * ((tid0 >> 5) & 3) + (i & 1);
  const int r0 = PERM ? dh_row(n0) : n0, r1 = PERM ? dh_row(n0 + 16) : n0 + 16;
  const uint32_t a0 = sb + stage + r0 * 128 + ((chunk ^ (r0 & 7)) << 4), a1 = sb + stage + r1 * 128 + ((chunk ^ (r1 & 7)) << 4);
#pragma unroll
  for (int k = 0; k < NKR; k++) ldsm4t(wf[k], ((k & 1) ? a1 : a0) + (k >> 1) * 4096);
#pragma unroll
  for (int k = 0; k < 40 - NKR; k++) {
    const int n = (NKR + k) * 16 + ((tid0 & 127) >> 3), r = PERM ? dh_row(n) : n, c = tid0 & 7;
    sts128(sb + yoff + (n - NKR * 16) * 128 + ((c ^ (n & 7)) << 4), lds128(sb + stage + r * 128 + ((c ^ (r & 7)) << 4)));
  }
  fence_async();
  CBAR_SYNC(NB_PRO, 384);
}
template <int STRIDE>
__device__ __forceinline__ void store_mem(const float (&d)[8], uint32_t base, int tid) {
  const int m = (tid >> 3) & 3;
  stsm4(base + (((tid >> 5) & 3) * 2 + (m & 1)) * STRIDE + (m >> 1) * 640 + (tid & 7) * 16, pack_bf16(d[0], d[1]), pack_bf16(d[2], d[3]),
        pack_bf16(d[4], d[5]), pack_bf16(d[6], d[7]));
}

__device__ __forceinline__ void load_pair(uint32_t sb, int i, int p, uint32_t slot, uint32_t bar, uint32_t ph, int& spin) {
  using namespace C;
  const uint8_t* s0 = g_xn[0] + (size_t)i * 40960 + p * 8192;
  const uint8_t* s1 = g_xn[NOWORK ? 0 : 1] + (size_t)(i - LAG) * 40960 + p * 8192;
  const uint8_t* sa = pinp(i < NSEG ? s0 : s1);
  const uint8_t* sc = pinp(i >= LAG ? s1 : s0);
  const uint32_t dst = pin(sb + slot), fb = pin(sb + BAR_F + 8 * p);
  mwait(bar, ph, spin);
  bulk_g2s_mc(dst, sa, 8192, fb);
  bulk_g2s_mc(dst + 8192, sc, 8192, fb);
}
__device__ __forceinline__ void first_fill(uint32_t sb, int i, int rank, int& spin) {
  using namespace C;
  const int s1 = i - LAG;
  if (!NOWORK && s1 >= 0) { cwait(CN_X + s1, 32, spin); fence_async_all(); }
  load_pair(sb, i, rank, rank == 2 ? OFF_M : OFF_KT + rank * 16384, sb + BAR_E + 8 * rank, (i - 1) & 1, spin);
}
__device__ __forceinline__ void release_round(uint32_t sb, int p, int tid) {
  using namespace C;
  const int lane = tid & 31;
  if (p < 2) { if (lane == 0) mbar_arrive_cluster(mapa(sb, p) + BAR_E + 8 * (3 + p)); }
  else if (lane < 3) mbar_arrive_cluster(mapa(sb, lane) + BAR_MOK);
}

template <int K0, int K1>
__device__ __forceinline__ void v_mem_pass(float (&d)[8], const uint32_t (&wf)[C::NKR][4]) {
  using namespace C;
  wg_fence();
#pragma unroll
  for (int k = K0; k < K1; k++) {
    if (k < NKR) wgmma_rs16(d, wf[k < NKR ? k : 0], mdesc(k), k != 32);
    else wgmma_ts16(d, wdesc(OFF_YV + (k - NKR) * 2048), mdesc(k), 1);
  }
  wg_commit();
}
__device__ __forceinline__ void chain_v(const uint32_t sb, const int tid0, const int cta, const int rank) {
  using namespace C;
  asm volatile("setmaxnreg.inc.sync.aligned.u32 208;");
  int spin = 0;
  uint32_t wf[NKR][4];
  if (tid0 == 256) first_fill(sb, 0, rank, spin);
  __syncwarp();
  mwait(sb + BAR_W, 0, spin);
  for (int it = tid0 & 127; it < 1280; it += 128) {
    const uint32_t base = sb + OFF_WK + (it >> 1) * 128;
    const int sw = ((it >> 1) & 7) ^ ((it & 1) * 4);
    const uint4 u0 = lds128(base + (sw << 4)), u1 = lds128(base + ((sw ^ 1) << 4)), u2 = lds128(base + ((sw ^ 2) << 4)), u3 = lds128(base + ((sw ^ 3) << 4));
    sts128(base + (sw << 4), make_uint4(u0.x, u1.x, u2.x, u3.x)); sts128(base + ((sw ^ 1) << 4), make_uint4(u0.y, u1.y, u2.y, u3.y));
    sts128(base + ((sw ^ 2) << 4), make_uint4(u0.z, u1.z, u2.z, u3.z)); sts128(base + ((sw ^ 3) << 4), make_uint4(u0.w, u1.w, u2.w, u3.w));
  }
  bar_sync(NB_RD, 128);
  load_weights_rs<false>(wf, sb, OFF_WK, OFF_YV, tid0);
#pragma unroll 1
  for (int i = 0; i < NSTEP; i++) {
    {
      float d[32];
      if (i > 0) CBAR_SYNC(NB_WV, 256);
#pragma unroll
      for (int p = 0; p < 5; p++) {
        mwait(sb + BAR_F + 8 * p, i & 1, spin);
        TS(i, 25 + p);
        wg_fence();
#pragma unroll
        for (int k = 8 * p; k < 8 * p + 8; k++) {
          if (k < NKR) wgmma_rs64(d, wf[k < NKR ? k : 0], tdesc(k), k);
          else wgmma_ts64(d, wdesc(OFF_YV + (k - NKR) * 2048), tdesc(k), 1);
          if (k == 8 * p + 1 && p >= 1 && p <= 3) {
            wg_commit(); wg_wait<1>();
            release_round(sb, p - 1, fresh(tid0));
            wg_fence();
          }
          if (k == 8 * p + RFK && (p == 1 || p == 2)) {
            wg_commit();
            if (rank == p - 1 && tid0 == 256) load_pair(sb, i, p + 2, slot_off(p + 2), sb + BAR_E + 8 * (p + 2), i & 1, spin);
            __syncwarp();
            wg_fence();
          }
        }
        wg_commit();
      }
      wg_wait<0>();
      TS(i, 23);
      CBAR_SYNC(NB_RD, 256);
      const int tid = fresh(tid0) & 127, m = (tid >> 3) & 3;
      if (tid >= 96) {
        if (tid < 101) { if (i + 1 < NSTEP) mbar_expect_tx(sb + BAR_F + 8 * (tid - 96), 16384); }
        else if (tid == 101) mbar_expect_tx(sb + BAR_XM, 2560);
        else if (tid == 102) mbar_expect_tx(sb + BAR_XT, 7168);
        else if (tid == 103) mbar_expect_tx(sb + BAR_OG, 4096);
        else if (tid < 106) mbar_arrive_cluster(mapa(sb, (rank + tid - 103) % 3) + BAR_XF);
        __syncwarp();
      }
      const uint32_t a = sb + OFF_VT + 256 + ((tid >> 5) * 2 + (m & 1)) * VS + (m >> 1) * 128 + (tid & 7) * 16;
#pragma unroll
      for (int s = 0; s < 4; s++)
        stsm4(a + (s & 1) * 256 + (s >> 1) * 640, pack_bf16(d[8 * s], d[8 * s + 1]), pack_bf16(d[8 * s + 2], d[8 * s + 3]),
              pack_bf16(d[8 * s + 4], d[8 * s + 5]), pack_bf16(d[8 * s + 6], d[8 * s + 7]));
      if (tid < 72) sts128(sb + OFF_VT + (tid >> 3) * VS + (tid & 7) * 16, make_uint4(0, 0, 0, 0));
      fence_async();
    }
    mwait(sb + BAR_XF, i & 1, spin);
    CBAR_ARRIVE(NB_QK, 384);
    CBAR_SYNC(NB_QI, 256);
    float d[8];
    v_mem_pass<32, 40>(d, wf);
    CBAR_SYNC(NB_SM, 256);
    wg_wait<0>();
    if (__builtin_expect(lds32(sb + FLG_REDO), 0)) { v_mem_pass<32, 40>(d, wf); wg_wait<0>(); }
    if ((tid0 & 31) < 2) mbar_arrive_cluster(mapa(sb, (rank + 1 + (tid0 & 1)) % 3) + BAR_MF);
    v_mem_pass<0, 32>(d, wf);
    wg_wait<0>();
    TS(i, 24);
    const int tid = fresh(tid0);
    if ((tid & 31) == 0) mbar_arrive_cluster(mapa(sb, 2) + BAR_E + 16);
    store_mem<VS>(d, sb + OFF_VT + 128, tid);
    fence_async();
    CBAR_ARRIVE(NB_VA, 256);
    CBAR_ARRIVE(NB_VQ, 256);
    if (tid == 256) {
      if (i + 1 < NSTEP) { first_fill(sb, i + 1, rank, spin); TS1(i + 1, 37); }
    } else if (tid >= 288 && tid < 295) {
      const int lane = tid & 31, ip = i + PFD;
      if (cta < 80 && ip < NSTEP) {
        if (lane < 2) prefetch_l2(g_mbuf[ip] + (cta * 2 + lane) * 128);
        else if (lane == 6) { if (cta < 22) prefetch_l2(&g_flag[ip][cta * 32]); }
        else if (ip < NSEG) prefetch_l2(g_xn[0] + (size_t)ip * 40960 + (cta * 4 + lane - 2) * 128);
      }
    }
    TS_FLUSH(i - 1);
    __syncwarp();
  }
  if (spin >= SPIN_TOT) g_err = 3;
}

__device__ __forceinline__ float quad_max(float x) {
  const float a = __shfl_xor_sync(0xffffffffu, x, 1), b = __shfl_xor_sync(0xffffffffu, x, 2), c = __shfl_xor_sync(0xffffffffu, x, 3);
  return fmaxf(fmaxf(x, a), fmaxf(b, c));
}
__device__ __forceinline__ float quad_sum(float x) {
  const float a = __shfl_xor_sync(0xffffffffu, x, 1), b = __shfl_xor_sync(0xffffffffu, x, 2), c = __shfl_xor_sync(0xffffffffu, x, 3);
  return (x + a) + (b + c);
}
__device__ __forceinline__ float max10(const float (&y)[10]) {
  return fmaxf(fmaxf(fmaxf(fmaxf(y[0], y[1]), fmaxf(y[2], y[3])), fmaxf(fmaxf(y[4], y[5]), fmaxf(y[6], y[7]))), fmaxf(y[8], y[9]));
}
__device__ __forceinline__ float sum10(const float (&y)[10]) {
  return (((y[0] + y[1]) + (y[2] + y[3])) + ((y[4] + y[5]) + (y[6] + y[7]))) + (y[8] + y[9]);
}
__device__ __forceinline__ float rcp(float x) { float y; asm("rcp.approx.ftz.f32 %0,%1;" : "=f"(y) : "f"(x)); return y; }

__device__ __forceinline__ void signal_o(int i, int cta) { csignal(CN_O + i * 5 + min(cta / 19, 4)); }

__device__ __forceinline__ void chain_q(const CUtensorMap& tmWq, const CUtensorMap& tmWk, const uint32_t sb, const int tid0, const int cta, const int rank) {
  using namespace C;
  asm volatile("setmaxnreg.dec.sync.aligned.u32 96;");
  int spin = 0;
  CBAR_SYNC(NB_PRO, 384);
  PTS(5);
  if (tid0 == 128) {
    const int col = (cta / 3) * DH + rank * 64;
    mbar_expect_tx(sb + BAR_W, 163840);
    for (int i = 0; i < 5; i++) {
      tma2d(sb + OFF_WQ + i * 16384, &tmWq, col, i * 128, sb + BAR_W);
      tma2d(sb + OFF_WK + i * 16384, &tmWk, col, i * 128, sb + BAR_W);
    }
  }
  __syncwarp();
  mwait(sb + BAR_W, 1, spin);
  PTS(6);
#pragma unroll 1
  for (int i = 0; i < NSTEP; i++) {
    const int ph = i & 1;
    uint32_t qf[4][4];
    {
      float d[64];
#pragma unroll
      for (int p = 0; p < 5; p++) {
        mwait(sb + BAR_F + 8 * p, ph, spin);
        if (p == 0) TS(i, 0);
        wg_fence();
#pragma unroll
        for (int k = 8 * p; k < 8 * p + 8; k++) {
          wgmma_st128(d, tdesc(k), mkdesc(SB0 + OFF_WQ + k * 2048, OFF_WK - OFF_WQ, 1024), k);
          if (k == 8 * p + 1 && p >= 1 && p <= 3) {
            wg_commit(); wg_wait<1>();
            release_round(sb, p - 1, fresh(tid0));
            wg_fence();
          }
        }
        wg_commit();
      }
      wg_wait<0>();
      TS(i, 1);
      CBAR_SYNC(NB_RD, 256);
      TSB(i, 2);
      const int tid = fresh(tid0), w = (tid >> 5) & 3, m = (tid >> 3) & 3;
      const uint32_t a = sb + OFF_KT + (m >> 1) * KS + (1 + 5 * (w >> 1) + 2 * (w & 1) + (m & 1)) * 128 + (tid & 7) * 16;
#pragma unroll
      for (int s = 0; s < 4; s++)
        stsm4t(a + s * 2 * KS, pack_bf16(d[32 + 8 * s], d[33 + 8 * s]), pack_bf16(d[34 + 8 * s], d[35 + 8 * s]),
               pack_bf16(d[36 + 8 * s], d[37 + 8 * s]), pack_bf16(d[38 + 8 * s], d[39 + 8 * s]));
      fence_async();
      CBAR_ARRIVE(NB_QK, 384);
      if (OSG == 0) { if (tid == 224 && i > 0) signal_o(i - 1, cta); __syncwarp(); }
#pragma unroll
      for (int kk = 0; kk < 4; kk++)
#pragma unroll
        for (int j = 0; j < 4; j++) asm volatile("cvt.rn.bf16x2.f32 %0,%1,%2;" : "=r"(qf[kk][j]) : "f"(d[8 * kk + 2 * j + 1]), "f"(d[8 * kk + 2 * j]));
    }
    CBAR_SYNC(NB_SI, 256);
    uint32_t pf[5][4];
    float s0, s1;
    {
      float y0[10], y1[10];
      const int tid = fresh(tid0), lane = tid & 31, u = (tid >> 5) & 1;
      const bool c1 = tid & 64;
      {
        float x[40];
        wg_fence();
#pragma unroll
        for (int kk = 0; kk < 4; kk++) wgmma_rt80(x, qf[kk], mkdesc_ns(SB0 + OFF_KT + kk * 2 * KS, KS, 128), kk);
        wg_commit();
        wg_wait<0>();
#pragma unroll
        for (int j = 0; j < 5; j++) {
          y0[2 * j] = (c1 ? x[20 + 4 * j] : x[4 * j]) * SCL; y0[2 * j + 1] = (c1 ? x[21 + 4 * j] : x[4 * j + 1]) * SCL;
          y1[2 * j] = (c1 ? x[22 + 4 * j] : x[4 * j + 2]) * SCL; y1[2 * j + 1] = (c1 ? x[23 + 4 * j] : x[4 * j + 3]) * SCL;
        }
      }
      TS(i, 17);
      const uint32_t xo = OFF_XT + (c1 ? 1792 : 0) + u * 640 + lane * 16, x2 = xo + u * 512 + 512 - lane * 12;
      {
        const uint4 h0 = make_uint4(pack_h2(y0[0], y0[1]), pack_h2(y0[2], y0[3]), pack_h2(y1[0], y1[1]), pack_h2(y1[2], y1[3]));
        const uint4 h1 = make_uint4(pack_h2(y0[4], y0[5]), pack_h2(y0[6], y0[7]), pack_h2(y1[4], y1[5]), pack_h2(y1[6], y1[7]));
        const uint32_t h2 = u ? pack_h2(y1[8], y1[9]) : h1.z;
#pragma unroll
        for (int dd = 0; dd < 2; dd++) {
          const uint32_t rb = mapa(sb, (rank + 1 + dd) % 3), ro = rb + (1 - dd) * 3584;
          st_async4u(ro + xo, h0, rb + BAR_XT);
          if (u) st_async4u(ro + xo + 512, h1, rb + BAR_XT);
          st_async1u(ro + x2, h2, rb + BAR_XT);
        }
      }
      TS(i, 18);
      const int lim = 16 * u + (lane >> 2) + 8 - 2 * (lane & 3);
#pragma unroll
      for (int j = 1; j < 5; j++) {
        if (8 * j > lim) y0[2 * j] = -INFINITY;
        if (8 * j + 1 > lim) y0[2 * j + 1] = -INFINITY;
        if (8 * j - 8 > lim) y1[2 * j] = -INFINITY;
        if (8 * j - 7 > lim) y1[2 * j + 1] = -INFINITY;
      }
      mwait(sb + BAR_XT, ph, spin);
      TS(i, 19);
      {
        const uint4 u0 = lds128(sb + xo), v0 = lds128(sb + xo + 3584);
        const uint32_t u2 = lds32(sb + x2), v2 = lds32(sb + x2 + 3584);
        uint4 u1 = make_uint4(0, 0, u2, 0), v1 = make_uint4(0, 0, v2, 0);
        if (u) { u1 = lds128(sb + xo + 512); v1 = lds128(sb + xo + 512 + 3584); }
        __syncwarp();
        if (lane == 0) mbar_arrive_cluster(mapa(sb, 0) + BAR_E);
        add_h2(y0[0], y0[1], u0.x, v0.x); add_h2(y0[2], y0[3], u0.y, v0.y); add_h2(y1[0], y1[1], u0.z, v0.z); add_h2(y1[2], y1[3], u0.w, v0.w);
        add_h2(y0[4], y0[5], u1.x, v1.x); add_h2(y0[6], y0[7], u1.y, v1.y); add_h2(y1[4], y1[5], u1.z, v1.z); add_h2(y1[6], y1[7], u1.w, v1.w);
        add_h2(y1[8], y1[9], u2, v2);
      }
      y0[8] = y0[0]; y0[9] = y0[1];
      const float m0 = quad_max(max10(y0)) * -256.f, m1 = quad_max(max10(y1)) * -256.f;
      s0 = 0.f; s1 = 0.f;
#pragma unroll
      for (int j = 0; j < 5; j++) {
        const uint32_t p0 = j < 4 ? pack_bf16(ex2(fmaf(y0[2 * j], 256.f, m0)), ex2(fmaf(y0[2 * j + 1], 256.f, m0))) : 0u;
        const uint32_t p1 = pack_bf16(ex2(fmaf(y1[2 * j], 256.f, m1)), ex2(fmaf(y1[2 * j + 1], 256.f, m1)));
        s0 += bf_lo(p0) + bf_hi(p0); s1 += bf_lo(p1) + bf_hi(p1);
        pf[j >> 1][2 * (j & 1)] = c1 ? 0u : p0; pf[j >> 1][2 * (j & 1) + 1] = c1 ? 0u : p1;
        pf[(j + 5) >> 1][2 * ((j + 5) & 1)] = c1 ? p0 : 0u; pf[(j + 5) >> 1][2 * ((j + 5) & 1) + 1] = c1 ? p1 : 0u;
      }
    }
    CBAR_SYNC(NB_VQ, 256);
    TSB(i, 20);
    {
      float o[32];
      wg_fence();
#pragma unroll
      for (int q = 0; q < 5; q++) wgmma_rs64(o, pf[q], mkdesc_ns(SB0 + OFF_VT + 128 + q * 256, 128, VS), q);
      wg_commit();
      s0 = rcp(quad_sum(s0)); s1 = rcp(quad_sum(s1));
      const int tid = fresh(tid0), g = (tid >> 2) & 7, c = (tid >> 6) & 1, sg = i - c * LAG;
      uint8_t* op = pinp(&g_o[i % ORING][c][cta][(((tid >> 5) & 1) * 16 + g) * 128]);
      const uint32_t o0 = pin(((tid & 3) ^ g) << 4), live = pin(sg >= 0 && sg < NSEG);
      wg_wait<0>();
      TS(i, 21);
      if ((tid & 31) == 0) mbar_arrive_cluster(mapa(sb, 1) + BAR_E + 8);
      uint4 ov[4];
#pragma unroll
      for (int h = 0; h < 2; h++) {
        const float* x = o + 16 * h;
        ov[2 * h] = make_uint4(pin(pack_bf16(x[0] * s0, x[1] * s0)), pin(pack_bf16(x[4] * s0, x[5] * s0)), pin(pack_bf16(x[8] * s0, x[9] * s0)), pin(pack_bf16(x[12] * s0, x[13] * s0)));
        ov[2 * h + 1] = make_uint4(pin(pack_bf16(x[2] * s1, x[3] * s1)), pin(pack_bf16(x[6] * s1, x[7] * s1)), pin(pack_bf16(x[10] * s1, x[11] * s1)), pin(pack_bf16(x[14] * s1, x[15] * s1)));
      }
      TS(i, 22);
      if (i + 1 < NSTEP) CBAR_SYNC(NB_WQ, 256);
      if (live) {
#pragma unroll
        for (int h = 0; h < 4; h++) *reinterpret_cast<uint4*>(op + (h & 1) * 1024 + (o0 ^ ((h >> 1) * 64))) = ov[h];
      }
      if (OSG && i + 1 < NSTEP) CBAR_ARRIVE(NB_MR, 160);
    }
  }
  CBAR_SYNC(NB_Q, 128);
  if (tid0 == 224) signal_o(NSTEP - 1, cta);
  if (spin >= SPIN_TOT) g_err = 2;
}

template <int NL>
__device__ __forceinline__ void poll_add(const uint8_t* mb, uint32_t tag, float (&f)[8], uint32_t* flag, int osig, int& n, int& spin) {
  uint4 x[NL];
#pragma unroll
  for (int i = 0; i < NL; i++) x[i] = ld_relaxed128(mb + i * 512);
  if (OSG == 1 && osig >= 0) csignal(osig);
  while (true) {
    bool bad = false;
#pragma unroll
    for (int i = 0; i < NL; i++)
      if (((x[i].x ^ tag) | (NL == 6 ? x[i].z ^ tag : 0u)) & 1) { bad = true; x[i] = ld_relaxed128(mb + i * 512); }
    n++;
    spin += 16;
    if (!__any_sync(0xffffffffu, bad && spin < SPIN_TOT)) break;
  }
  if (FLP == 0 && flag) st_relaxed(flag, 0);
#pragma unroll
  for (int i = 0; i < NL; i++) {
    const uint32_t u[4] = {x[i].x, x[i].y, x[i].z, x[i].w};
#pragma unroll
    for (int j = 0; j < 4; j++) {
      if (i == 0) { f[2 * j] = bf_lo(u[j]); f[2 * j + 1] = bf_hi(u[j]); }
      else { f[2 * j] += bf_lo(u[j]); f[2 * j + 1] += bf_hi(u[j]); }
    }
  }
}

template <int B, int SLOT>
__device__ __forceinline__ void wo_block(float (&acc)[8], const uint32_t (&wf)[C::NKR][4]) {
  using namespace C;
#pragma unroll
  for (int kk = 0; kk < 4; kk++) {
    const int k = 4 * B + kk;
    const uint64_t db = mkdesc_ns(SB0 + og_off(SLOT) + kk * 512, 256, 128);
    if (k < NKR) wgmma_rt16(acc, wf[k < NKR ? k : 0], db, SLOT | kk);
    else wgmma_tt16(acc, wdesc(OFF_YO + (k - NKR) * 2048), db, 1);
  }
}

__device__ __forceinline__ void chain_a(const uint32_t sb, const int tid0, const int cta, const int rank) {
  using namespace C;
  asm volatile("setmaxnreg.inc.sync.aligned.u32 200;");
  int spin = 0;
  uint32_t wf[NKR][4];
  mwait(sb + BAR_W, 0, spin);
  permute_cols(sb + OFF_WQ, tid0);
  CBAR_SYNC(NB_A, 128);
  load_weights_rs<true>(wf, sb, OFF_WQ, OFF_YO, tid0);

#pragma unroll 1
  for (int i = -1; i < NSTEP; i++) {
    const int ph = i & 1;
    if (i >= 0) {
      if (i == 0) mwait(sb + BAR_W, 1, spin);
      mwait(sb + BAR_M, ph, spin);
      TS(i, 3);
      {
        float x[20];
        int redo = 0;
      retry:
        bool bad;
        {
          float dq[8], dk[8];
          wg_fence();
#pragma unroll
          for (int k = 0; k < 40; k++) wgmma_ts16(dq, wdesc(OFF_WQ + k * 2048), mdesc(k), k);
          wg_commit();
#pragma unroll
          for (int k = 0; k < 40; k++) {
            if (k == 40 - QIE && !redo) CBAR_ARRIVE(NB_QI, 256);
            wgmma_ts16(dk, wdesc(OFF_WK + k * 2048), mdesc(k), k);
          }
          wg_commit();
          const int m = (tid0 >> 3) & 3, dg = (tid0 >> 5) * 2 + (m & 1);
          const uint32_t ka = sb + OFF_KT + dg * KS + (m >> 1) * 640 + (tid0 & 7) * 16;
          wg_wait<1>();
          const float chk = (dq[0] + dq[1]) + (dq[4] + dq[5]);
          const uint32_t q0 = pack_bf16(dq[0], dq[1]), q1 = pack_bf16(dq[2], dq[3]), q2 = pack_bf16(dq[4], dq[5]), q3 = pack_bf16(dq[6], dq[7]);
          if (!redo) CBAR_SYNC(NB_QK, 384);
          stsm4(ka + dg * (VS - KS) + (OFF_VT + 128 - OFF_KT), q0, q1, q2, q3);
          sts32(sb + FLG_REDO, redo);
          wg_wait<0>();
          TS(i, 4);
          stsm4(ka, pack_bf16(dk[0], dk[1]), pack_bf16(dk[2], dk[3]), pack_bf16(dk[4], dk[5]), pack_bf16(dk[6], dk[7]));
          fence_async();
          bad = bar_red_or(NB_C, 128, chk != chk && !redo);
        }
        TSB(i, 5);
        wg_fence();
#pragma unroll
        for (int kk = 0; kk < 4; kk++) wgmma_tt40(x, mkdesc_ns(SB0 + OFF_VT + 128 + kk * 2 * VS, VS, 640), mkdesc_ns(SB0 + OFF_KT + kk * 2 * KS, KS, 128), kk);
#pragma unroll
        for (int kk = 0; kk < 4; kk++) {
          if (kk == 4 - SIE && !bad) CBAR_ARRIVE(NB_SI, 256);
          wgmma_tt40(x, mkdesc_ns(SB0 + OFF_VT + kk * 2 * VS, VS, 384), mkdesc_ns(SB0 + OFF_KT + 640 + kk * 2 * KS, KS, 128), 1);
        }
        wg_commit();
        if (__builtin_expect(bad, 0)) {
          wg_wait<0>();
#pragma unroll 1
          for (int k = 0; k < 10; k++) {
            uint4 v = lds128(sb + OFF_M + tid0 * 16 + k * 2048);
            if (v.x == SENT || v.y == SENT || v.z == SENT || v.w == SENT) {
              do { v = ld_relaxed4(g_mbuf[i] + tid0 * 16 + k * 2048); spin += 16; } while ((v.x == SENT || v.y == SENT || v.z == SENT || v.w == SENT) && spin < SPIN_TOT);
              sts128(sb + OFF_M + tid0 * 16 + k * 2048, v);
            }
          }
          fence_async();
          bar_sync(NB_C, 128);
          redo = fresh(1);
          goto retry;
        }
        TSV(i, 36, redo);
        const int tid = fresh(tid0), lane = tid & 31, w = tid >> 5;
        const uint32_t xo = OFF_XM + w * 1280 + lane * 16, x1 = OFF_XM + w * 1280 + lane * 4;
        const uint32_t rb1 = mapa(sb, (rank + 1) % 3), rb2 = mapa(sb, (rank + 2) % 3);
        const uint32_t ra = pin(rb1 + xo + 640), rb = pin(rb1 + x1 + 1152), rc = pin(rb2 + xo), rd = pin(rb2 + x1 + 512);
        const uint32_t la = pin(sb + xo), lb = pin(sb + x1);
        const uint32_t pa = pin(sb + OFF_XM + w * 1280 + (lane & 7) * 4 + (lane & 8) * 8 + (lane & 16) * 2);
        wg_wait<0>();
        TS(i, 6);
        if (w < 2) {
          float y[10];
#pragma unroll
          for (int j = 0; j < 5; j++) { y[2 * j] = x[4 * j] * SCL; y[2 * j + 1] = x[4 * j + 1] * SCL; }
          const uint4 h0 = make_uint4(pack_h2(y[0], y[1]), pack_h2(y[2], y[3]), pack_h2(y[4], y[5]), pack_h2(y[6], y[7]));
          const uint32_t h1 = pack_h2(y[8], y[9]);
          st_async4u(ra, h0, rb1 + BAR_XM);
          st_async4u(rc, h0, rb2 + BAR_XM);
          st_async1u(rb, h1, rb1 + BAR_XM);
          st_async1u(rd, h1, rb2 + BAR_XM);
          CBAR_ARRIVE(NB_SM, 256);
          if (lane == 0) mbar_arrive_cluster(mapa(sb, 0) + BAR_E);
          TS(i, 7);
          mwait(sb + BAR_XM, ph, spin);
          TS(i, 8);
          const uint4 u0 = lds128(la), v0 = lds128(la + 640);
          const uint32_t u1 = lds32(lb + 512), v1 = lds32(lb + 1152);
          add_h2(y[0], y[1], u0.x, v0.x); add_h2(y[2], y[3], u0.y, v0.y); add_h2(y[4], y[5], u0.z, v0.z); add_h2(y[6], y[7], u0.w, v0.w);
          add_h2(y[8], y[9], u1, v1);
          const float mx = quad_max(max10(y)) * -256.f;
          sts32(pa + 640, 0);
#pragma unroll
          for (int j = 0; j < 5; j++) {
            y[2 * j] = ex2(fmaf(y[2 * j], 256.f, mx)); y[2 * j + 1] = ex2(fmaf(y[2 * j + 1], 256.f, mx));
            sts32(pa + j * 128, pack_bf16(y[2 * j], y[2 * j + 1]));
          }
          sts32(pa + 768, __float_as_uint(sum10(y)));
          fence_async();
          TS(i, 9);
        } else {
          CBAR_ARRIVE(NB_SM, 256);
          if (lane == 0) mbar_arrive_cluster(mapa(sb, 0) + BAR_E);
          mwait(sb + BAR_MF, ph, spin);
        }
      }
      CBAR_SYNC(NB_VA, 256);
      TSB(i, 10);
      {
        float o[2][4];
        wg_fence();
#pragma unroll
        for (int c = 0; c < 2; c++)
#pragma unroll
          for (int q = 0; q < 3; q++)
            wgmma_ss8(o[c], mkdesc_ns(SB0 + OFF_VT + 128 + c * 640 + q * 256, 128, VS), mkdesc_ns(SB0 + OFF_XM + c * 1280 + q * 256, 128, 128), q);
        wg_commit();
        const int tid = fresh(tid0);
        const float4 e = lds128f(sb + OFF_XM + 768 + (tid & 3) * 32 + (tid & 4) * 4 + (tid & 8) * 160);
        const uint32_t oo = (tid >> 5) * 512 + (tid & 2) * 64 + ((tid & 31) >> 2) * 16 + (tid & 1) * 8;
        const uint32_t rb1 = mapa(sb, (rank + 1) % 3), rb2 = mapa(sb, (rank + 2) % 3);
        const uint32_t ra = pin(rb1 + oo + og_off(2)), rc = pin(rb2 + oo + og_off(1)), la = pin(sb + oo + og_off(0));
        const float inv = rcp((e.x + e.y) + (e.z + e.w));
        const float i0 = __shfl_sync(0xffffffffu, inv, tid & 3), i1 = __shfl_sync(0xffffffffu, inv, (tid & 3) + 4);
        const float i2 = __shfl_sync(0xffffffffu, inv, (tid & 3) + 8), i3 = __shfl_sync(0xffffffffu, inv, (tid & 3) + 12);
        wg_wait<0>();
        TS(i, 11);
        const uint32_t p0 = pack_bf16(o[0][0] * i0, o[0][1] * i1), p1 = pack_bf16(o[1][0] * i2, o[1][1] * i3);
        const uint32_t p2 = pack_bf16(o[0][2] * i0, o[0][3] * i1), p3 = pack_bf16(o[1][2] * i2, o[1][3] * i3);
        if (OGF) { sts64(la, p0, p1); sts64(la + 256, p2, p3); fence_async(); }
        st_async2u(ra, p0, p1, rb1 + BAR_OG);
        st_async2u(rc, p0, p1, rb2 + BAR_OG);
        st_async2u(ra + 256, p2, p3, rb1 + BAR_OG);
        st_async2u(rc + 256, p2, p3, rb2 + BAR_OG);
        if (!OGF) { sts64(la, p0, p1); sts64(la + 256, p2, p3); fence_async(); }
      }
      if (i + 1 >= NSTEP) { mwait(sb + BAR_OG, ph, spin); break; }
      CBAR_SYNC(NB_A, 128);
      TSB(i, 12);
      {
        float acc[3][8];
        wg_fence();
        wo_block<0, 0>(acc[2], wf);
        wg_commit();
        wo_block<1, 0>(acc[0], wf);
        wo_block<4, 0>(acc[1], wf);
        wg_commit();
        const int tid = fresh(tid0), w = tid >> 5, g = (tid & 31) >> 2, t = tid & 3;
        if ((tid & 31) == 0) mbar_arrive_cluster(mapa(sb, 1) + BAR_E + 8);
        const uint32_t tag = (i >> 1) & 1, radd = tag ? 0u : 0x10000u;
#define TAGGED(LO, HI) __byte_perm(((__float_as_uint(LO) + radd) & 0xFFFE0000u) | (tag << 16), pack_bf16(0.f, HI), 0x7632)
#define SEND(PTR, U) st_relaxed128((PTR), TAGGED(acc[U][0], acc[U][2]), pack_bf16(acc[U][1], acc[U][3]), pack_bf16(acc[U][4], acc[U][6]), pack_bf16(acc[U][5], acc[U][7]))
        uint8_t* m9 = pinp(g_mail[ph] + MAIL9 + (((2 * w + (g >> 2)) * 2 + (t & 1)) * 4 + (t & 2)) * 3072 + cta * 32 + (g & 3) * 8);
        wg_wait<1>();
        const uint32_t n0 = pin(TAGGED(acc[2][0], acc[2][2])), n1 = pin(pack_bf16(acc[2][1], acc[2][3]));
        const uint32_t n2 = pin(TAGGED(acc[2][4], acc[2][6])), n3 = pin(pack_bf16(acc[2][5], acc[2][7]));
        wg_fence();
        wo_block<7, 0>(acc[2], wf);
        wg_commit();
        st_relaxed64(m9, n0, n1);
        st_relaxed64(m9 + 3072, n2, n3);
        uint8_t* mb = pinp(g_mail[ph] + (((rank * 12 + w) * 2 + (g >> 2)) * 4 + t) * 2048 + (cta / 3) * 64 + (g & 3) * 16);
        mwait(sb + BAR_OG, ph, spin);
        asm volatile("fence.proxy.async::generic.acquire.sync_restrict::shared::cluster.cluster;" ::: "memory");
        TS(i, 13);
        wg_fence();
        wo_block<2, 1>(acc[0], wf); wo_block<3, 2>(acc[0], wf);
        wg_commit();
        wo_block<5, 1>(acc[1], wf); wo_block<6, 2>(acc[1], wf);
        wg_commit();
        wg_wait<1>(); SEND(mb, 0);
        wg_fence();
        wo_block<8, 1>(acc[2], wf); wo_block<9, 2>(acc[2], wf);
        wg_commit();
        if (WOE == 0) { CBAR_ARRIVE(NB_WV, 256); CBAR_ARRIVE(NB_WQ, 256); }
        wg_wait<1>(); SEND(mb + 32 * 2048, 1);
        if (WOE == 1) CBAR_ARRIVE(NB_WV, 256);
        wg_wait<0>(); SEND(mb + 64 * 2048, 2);
        if (WOE == 2) CBAR_ARRIVE(NB_WV, 256);
        if (WOE >= 1) CBAR_ARRIVE(NB_WQ, 256);
#undef SEND
#undef TAGGED
      }
      TS(i, 14);
    }
    const uint32_t t0 = clk32();
    uint32_t t1 = t0;
    if (i >= 0) {
      const int tid = fresh(tid0), lane = tid & 31;
      const uint32_t tag = (i >> 1) & 1;
      const bool t9 = cta >= 72 && cta < 88;
      const int w = tid >> 5, j = lane >> 3;
      const uint32_t pub = pin((lane & (t9 ? 6 : 4)) == 0 && !(((t9 ? cta : w) & 1) && i + 1 == LAG) && cta < 88);
      uint8_t* dst = pinp(g_mbuf[i + 1] + (t9 ? (cta + 72) * 128 + w * 32 + (j & 1) * 16 + (lane & 1) * 8 + (j >> 1) * 4
                                               : cta * 256 + (w & 1) * 128 + (w >> 1) * 64 + j * 16 + (lane & 3) * 4));
      uint32_t* flag = pinp(lane == 0 && cta < 88 ? &g_flag[i + 1][cta * 8 + w] : nullptr);
      float f[8];
      int n = 0;
      if (OSG && w == 3) CBAR_SYNC(NB_MR, 160);
      const int osig = tid == 96 ? CN_O + i * 5 + min(cta / 19, 4) : -1;
      while (clk32() - t0 < B1) {}
      TS(i + 1, 30);
      if (!t9) poll_add<4>(g_mail[ph] + (cta < 72 ? cta : cta - 24) * 8192 + (tid >> 5) * 2048 + lane * 16, tag, f, flag, osig, n, spin);
      else poll_add<6>(g_mail[ph] + MAIL9 + (cta - 72) * 12288 + (tid >> 5) * 3072 + lane * 16, tag, f, flag, osig, n, spin);
      if (FLP == 1 && flag) st_relaxed(flag, __float_as_uint(f[0] + f[7]) >> 1);
      t1 = clk32();
      TS(i + 1, 31); TSV(i + 1, 32, n);
      const bool h = lane & 16, q = lane & 8;
#pragma unroll
      for (int j = 0; j < 4; j++) f[j] = (h ? f[4 + j] : f[j]) + __shfl_xor_sync(0xffffffffu, h ? f[j] : f[4 + j], 16);
#pragma unroll
      for (int j = 0; j < 2; j++) f[j] = (q ? f[2 + j] : f[j]) + __shfl_xor_sync(0xffffffffu, q ? f[j] : f[2 + j], 8);
      f[0] += __shfl_xor_sync(0xffffffffu, f[0], 4); f[1] += __shfl_xor_sync(0xffffffffu, f[1], 4);
      if (t9) { f[0] += __shfl_xor_sync(0xffffffffu, f[0], 2); f[1] += __shfl_xor_sync(0xffffffffu, f[1], 2); }
      if (pub) st_relaxed(dst, pack_bf16(f[0], f[1]));
      if (FLP == 2 && flag) st_relaxed(flag, 0);
      if (OSG == 2 && osig >= 0) csignal(osig);
      TS(i + 1, 15);
    }
    if (tid0 < 32) {
      const uint8_t* src = pinp(g_mbuf[i + 1] + rank * 7168);
      const uint32_t* pp = pinp(&g_flag[i + 1][(rank * 28 + (tid0 < 28 || rank == 2 ? tid0 : 0)) * 8]);
      const uint32_t dst = pin(sb + OFF_M + rank * 7168), len = pin(rank == 2 ? 6144 : 7168);
      if (tid0 == 0) mbar_expect_tx(sb + BAR_M, 20480);
      while (clk32() - t1 < B2) {}
      TS(i + 1, 16);
      int n = 0;
      uint4 x;
      do { x = ld_relaxed4(pp); n++; spin += 16; } while (__any_sync(0xffffffffu, (int)(x.x | x.y | x.z | x.w) < 0 && spin < SPIN_TOT));
      TSV(i + 1, 35, n);
      TS(i + 1, 34);
      mwait(sb + BAR_MOK, ph ^ 1, spin);
      if (tid0 == 0) bulk_g2s_mc(dst, src, len, sb + BAR_M);
      TS(i + 1, 33);
      __syncwarp();
    }
  }
  if (spin >= SPIN_TOT) g_err = 1;
}

__global__ void __cluster_dims__(3, 1, 1) __launch_bounds__(384, 1)
k_chain(const __grid_constant__ CUtensorMap tmWq, const __grid_constant__ CUtensorMap tmWk,
        const __grid_constant__ CUtensorMap tmWv, const __grid_constant__ CUtensorMap tmWo) {
  using namespace C;
  extern __shared__ __align__(1024) uint8_t smem[];
  const uint32_t sb = smem_u32(smem);
  const int tid = threadIdx.x;
  const int wg = __shfl_sync(0xffffffffu, tid >> 7, 0);
  const int cta = blockIdx.x, rank = cta % 3;

  asm volatile("griddepcontrol.launch_dependents;");
  if (tid == 0) {
    if ((sb & 0xFFFFFF) != SB0) g_err = 100;
    for (int p = 0; p < 5; p++) { mbar_init(sb + BAR_F + 8 * p, 1); mbar_init(sb + BAR_E + 8 * p, p == 2 ? 12 : 24); }
    mbar_init(sb + BAR_M, 1); mbar_init(sb + BAR_MOK, 24); mbar_init(sb + BAR_XM, 1); mbar_init(sb + BAR_XF, 2);
    mbar_init(sb + BAR_XT, 1); mbar_init(sb + BAR_MF, 8); mbar_init(sb + BAR_OG, 1); mbar_init(sb + BAR_W, 1);
    for (int p = 0; p < 5; p++) mbar_expect_tx(sb + BAR_F + 8 * p, 16384);
    for (int p = 0; p < 16; p++) sts32(sb + OFF_SAFE + 4 * p, 0);
    asm volatile("fence.mbarrier_init.release.cluster;" ::: "memory");
    fence_async();
    mbar_expect_tx(sb + BAR_W, 163840);
    const int head = cta / 3, col = head * DH + rank * 64;
    tma2d(sb + OFF_WQ, &tmWo, 576, col, sb + BAR_W);
    for (int i = 0; i < 9; i++) tma2d(sb + OFF_WQ + (i + 1) * 8192, &tmWo, (3 * rank + i / 3) * 64, head * DH + ((rank + i) % 3) * 64, sb + BAR_W);
    for (int i = 0; i < 5; i++) tma2d(sb + OFF_WK + i * 16384, &tmWv, col, i * 128, sb + BAR_W);
  }
  __syncthreads();
  asm volatile("barrier.cluster.arrive.release.aligned;" ::: "memory");
  asm volatile("barrier.cluster.wait.acquire.aligned;" ::: "memory");

  if (wg == 0) chain_a(sb, keep(tid), cta, rank);
  else if (wg == 1) chain_q(tmWq, tmWk, sb, keep(tid), cta, rank);
  else chain_v(sb, keep(tid), cta, rank);
  asm volatile("barrier.cluster.arrive.release.aligned;" ::: "memory");
  asm volatile("barrier.cluster.wait.acquire.aligned;" ::: "memory");
}

namespace W {
constexpr int NP = 25, NBC = 11, NW = NP + NBC;
constexpr int OFF_W = 0;
constexpr int OFF_R = 163840;
constexpr int KVP = 248, KVR = 46, QP = 120;
constexpr int OFF_KV = OFF_R + 40960;
constexpr int OFF_Q = OFF_KV + 2 * KVR * KVP;
constexpr int OFF_BAR = OFF_Q + 32 * QP;
constexpr int OFF_SAFE = OFF_BAR + 128;
constexpr int SMEM = 232448;
constexpr uint32_t SB0 = 1024;
constexpr int BAR_F = OFF_BAR, BAR_E = OFF_BAR + 40, BAR_W = OFF_BAR + 80;
constexpr int NB_G0 = 1, NB_SG = 3, NB_SF = 4, NB_ST = 5;
}
#define WBAR_SYNC(id, n) bar_sync(id, n)
#define WBAR_ARRIVE(id, n) bar_arrive(id, n)

__device__ __forceinline__ uint64_t rdesc(int st, int k) { return mkdesc(W::SB0 + W::OFF_R + st * 8192 + (k >> 2) * 4096 + (k & 3) * 32, 16, 1024); }
__device__ __forceinline__ void load_frags40(uint32_t (&wf)[40][4], uint32_t base, int tid) {
  const int i = (tid >> 3) & 3, r = tid & 7;
  const uint32_t a0 = base + (r + (i >> 1) * 8) * 128 + (((2 * ((tid >> 5) & 3) + (i & 1)) ^ r) << 4);
#pragma unroll
  for (int k = 0; k < 40; k++) ldsm4t(wf[k], a0 + k * 2048);
}
__device__ __forceinline__ void red_tile(const float (&d)[16], int seg, int col0, int tid) {
  float* p = g_x + (size_t)(seg * 32 + 2 * (tid & 3)) * DM + col0 + ((tid >> 5) & 3) * 16 + ((tid >> 2) & 7) * 2;
#pragma unroll
  for (int j = 0; j < 8; j++)
    asm volatile("red.relaxed.gpu.global.add.v2.f32 [%0],{%1,%2};" ::"l"(p + ((j >> 1) * 8 + (j & 1)) * DM), "f"(d[4 * (j >> 1) + (j & 1)]), "f"(d[4 * (j >> 1) + 2 + (j & 1)]) : "memory");
}

#define FOR_P_JOBS(k, l, s)                               \
  for (int j_ = 0; j_ < 2 * NSTEP; j_++) {                \
    const int k = j_ >> 1, l = j_ & 1, s = k - l * LAG;   \
    if (s < 0 || s >= NSEG) continue;
#define FOR_B_JOBS(wo, l, s)                                                                  \
  for (int j_ = 0; j_ < 4 * (NSTEP + 1); j_++) {                                              \
    const int wo = j_ & 1, l = ((j_ + 1) >> 1) & 1, s = (j_ >> 2) - l * (LAG + wo);           \
    if (s < 0 || s >= NSEG || (wo && bc == 10)) continue;

template <int WG>
__device__ __forceinline__ void work_p(const CUtensorMap& tmWo, uint32_t sb, int pc, int tid0) {
  using namespace W;
  asm volatile("setmaxnreg.inc.sync.aligned.u32 208;");
  int spin = 0;
  const int ks = pc / 5, col0 = (pc % 5) * 128 + WG * 64;
  const uint32_t wb = sb + OFF_W + WG * 81920;
  uint32_t wf[40][4];
#pragma unroll 1
  for (int hf = 0; hf < 2; hf++) {
    if ((tid0 & 127) == 0) {
      mbar_expect_tx(sb + BAR_W + 8 * WG, 81920);
      for (int i = 0; i < 10; i++) tma2d(wb + i * 8192, &tmWo, col0, (ks * 19 + 2 * i + hf) * 64, sb + BAR_W + 8 * WG);
    }
    __syncwarp();
    mwait(sb + BAR_W + 8 * WG, hf, spin);
    permute_cols(wb, tid0 & 127);
    if (hf == 1 && ks < 4) for (int it = 2304 + (tid0 & 127); it < 2560; it += 128) {
      const uint32_t a = wb + (it >> 2) * 128 + (((2 * (it & 3)) ^ ((it >> 2) & 6)) << 4);
      sts128(a, make_uint4(0, 0, 0, 0)); sts128(a + 16, make_uint4(0, 0, 0, 0));
    }
    fence_async();
    WBAR_SYNC(NB_G0 + WG, 128);
    if (hf == 0) {
      load_frags40(wf, wb, tid0);
      fence_async();
      WBAR_SYNC(NB_G0 + WG, 128);
    }
  }
  FOR_P_JOBS(k_, l, s)
    float d[16];
#pragma unroll
    for (int f = 0; f < 10; f++) {
      mwait(sb + BAR_F + 8 * (f % 5), f / 5, spin);
      if (f == 0 && WG == 0 && pc == WW) WTS(l, s, 1);
      wg_fence();
#pragma unroll
      for (int kk = 0; kk < 4; kk++) {
        wgmma_rs32(d, wf[4 * f + kk], rdesc(f % 5, kk), f | kk);
        wgmma_ts32(d, mkdesc(SB0 + OFF_W + WG * 81920 + (4 * f + kk) * 2048, 8192, 1024), rdesc(f % 5, 4 + kk), 1);
      }
      wg_commit();
      if (f > 0) {
        wg_wait<1>();
        if ((tid0 & 31) == 0) mbar_arrive(sb + BAR_E + 8 * ((f - 1) % 5));
      }
    }
    wg_wait<0>();
    if ((tid0 & 31) == 0) mbar_arrive(sb + BAR_E + 32);
    if (WG == 0 && pc == WW) WTS(l, s, 2);
    red_tile(d, s, col0, tid0);
    WBAR_SYNC(NB_SG, 288);
  }
  if (spin >= SPIN_TOT) g_err = 11;
}
__device__ __forceinline__ void work_p_producer(uint32_t sb, int pc) {
  using namespace W;
  int spin = 0;
  const int ks = pc / 5;
  FOR_P_JOBS(k, l, s)
    cwait(CN_O + k * 5 + ks, ks == 4 ? 20 : 19, spin);
    fence_async_all();
    if (pc == WW) WTS1(l, s, 0);
    const uint8_t* src = &g_o[k % ORING][l][ks * 19][0];
#pragma unroll 1
    for (int f = 0; f < 10; f++) {
      const int st = f < 5 ? f : f - 5;
      const uint32_t len = f == 9 && ks < 4 ? 4096 : 8192;
      mwait(sb + BAR_E + 8 * st, f < 5, spin);
      mbar_expect_tx(sb + BAR_F + 8 * st, len);
      bulk_g2s(sb + OFF_R + st * 8192, src + f * 8192, len, sb + BAR_F + 8 * st);
    }
  }
  if (spin >= SPIN_TOT) g_err = 12;
}
__device__ __forceinline__ float warp_sum(float x) {
  x = quad_sum(x);
  const float a = __shfl_xor_sync(0xffffffffu, x, 4), b = __shfl_xor_sync(0xffffffffu, x, 8), c = __shfl_xor_sync(0xffffffffu, x, 12);
  x = (x + a) + (b + c);
  return x + __shfl_xor_sync(0xffffffffu, x, 16);
}
__device__ __forceinline__ void work_ln(int kind, int r, int lane, bf16* out) {
  int spin = 0;
  const int l = kind & 1;
  const uint32_t sw = ((((lane >> 1) & 7) ^ (r & 7)) << 4) + (lane & 1) * 8;
  uint8_t* dst = kind < 2 ? g_xnb[l] + (lane >> 4) * 4096 + r * 128 + sw
               : kind == 2 ? g_xn[1] + (r >> 3) * 2048 + (lane >> 4) * 1024 + (r & 7) * 128 + sw
                           : reinterpret_cast<uint8_t*>(out) + r * 1280 + lane * 8;
  const int dm = kind == 3 ? 256 : 8192;
#pragma unroll 1
  for (int s = 0; s < NSEG; s++) {
    const float* xr = g_x + (size_t)(s * 32 + r) * DM;
    if (kind == 0 && lane < 20 && s + 3 < NSEG) prefetch_l2(xr + 96 * DM + lane * 32);
    if (lane == 0) cwait((kind < 2 ? CN_P : CN_W) + l * 64 + s, kind < 2 ? W::NP : 10, spin);
    __syncwarp();
    if (r == 0 && lane == 0) WTS1(l, s, kind < 2 ? 3 : 11);
    float4 v[5];
#pragma unroll
    for (int m = 0; m < 5; m++) v[m] = ld_relaxed4f(xr + m * 128 + lane * 4);
    if (kind < 3) {
      float t = 0.f;
#pragma unroll
      for (int m = 0; m < 5; m++) t += (v[m].x + v[m].y) + (v[m].z + v[m].w);
      const float mean = warp_sum(t) * (1.f / DM);
      float q0 = 0.f, q1 = 0.f;
#pragma unroll
      for (int m = 0; m < 5; m++) {
        v[m].x -= mean; v[m].y -= mean; v[m].z -= mean; v[m].w -= mean;
        q0 += v[m].x * v[m].x + v[m].y * v[m].y; q1 += v[m].z * v[m].z + v[m].w * v[m].w;
      }
      const float rs = rsqrtf(warp_sum(q0 + q1) * (1.f / DM) + 1e-5f);
#pragma unroll
      for (int m = 0; m < 5; m++) { v[m].x *= rs; v[m].y *= rs; v[m].z *= rs; v[m].w *= rs; }
    }
#pragma unroll
    for (int m = 0; m < 5; m++) *reinterpret_cast<uint2*>(dst + (size_t)s * 40960 + m * dm) = make_uint2(pack_bf16(v[m].x, v[m].y), pack_bf16(v[m].z, v[m].w));
    __syncwarp();
    if (r == 0 && lane == 0) WTS1(l, s, kind < 2 ? 4 : 12);
    if (lane == 0 && kind < 3) csignal(kind < 2 ? CN_L + l * 64 + s : CN_X + s);
  }
  if (spin >= SPIN_TOT) g_err = 13;
}

__device__ __forceinline__ void stage_qkv(const bf16* wqkv, uint32_t base, int T, int bc, int tid) {
  const int q = tid & 15, c = 64 * T + 4 * q, cc = c % 60;
  const bool ok = c < 180 && bc * 60 + cc < DM;
  const bf16* src = wqkv + (c / 60) * DM + bc * 60 + cc;
#pragma unroll 1
  for (int k0 = tid >> 4; k0 < 640; k0 += 80) {
    uint2 v[10];
#pragma unroll
    for (int u = 0; u < 10; u++) v[u] = ok ? *reinterpret_cast<const uint2*>(src + (size_t)(k0 + 8 * u) * 1920) : make_uint2(0, 0);
#pragma unroll
    for (int u = 0; u < 10; u++) sts64(base + (k0 + 8 * u) * 128 + (((q >> 1) ^ (k0 & 7)) << 4) + (q & 1) * 8, v[u].x, v[u].y);
  }
}
template <int T>
__device__ __forceinline__ void stage_out(const float (&d)[16], uint32_t sb, int l, int row0, int tid) {
  using namespace W;
  const int c = 64 * T + ((tid >> 5) & 3) * 16 + ((tid >> 2) & 7) * 2;
  if (c < 180) {
#pragma unroll
    for (int j = 0; j < 8; j++) {
      const int tk = (j >> 1) * 8 + 2 * (tid & 3) + (j & 1);
      int rr = row0 + tk; rr -= rr >= KVR ? KVR : 0;
      sts32(c < 60 ? sb + OFF_Q + tk * QP + c * 2 : sb + OFF_KV + (l * KVR + rr) * KVP + (c - 60) * 2, pack_bf16(d[4 * (j >> 1) + (j & 1)], d[4 * (j >> 1) + 2 + (j & 1)]));
    }
  }
}
template <int WG>
__device__ __forceinline__ void work_b(const CUtensorMap& tmBo, const bf16* wqkv, uint32_t sb, int bc, int tid0) {
  using namespace W;
  if (WG == 0) asm volatile("setmaxnreg.inc.sync.aligned.u32 224;");
  else asm volatile("setmaxnreg.inc.sync.aligned.u32 208;");
  int spin = 0;
  const uint32_t wb = sb + OFF_W + WG * 81920;
  uint32_t wf[40][4];
  stage_qkv(wqkv, wb, WG, bc, tid0 & 127);
  WBAR_SYNC(NB_G0 + WG, 128);
  permute_cols(wb, tid0 & 127);
  WBAR_SYNC(NB_G0 + WG, 128);
  load_frags40(wf, wb, tid0);
  fence_async();
  WBAR_SYNC(NB_G0 + WG, 128);
  if (WG == 0) {
    stage_qkv(wqkv, wb, 2, bc, tid0 & 127);
    WBAR_SYNC(NB_G0 + WG, 128);
  } else if (bc < 10) {
    if ((tid0 & 127) == 0) {
      mbar_expect_tx(sb + BAR_W + 8, 81920);
      for (int i = 0; i < 10; i++) tma2d(wb + i * 8192, &tmBo, bc * 64, i * 64, sb + BAR_W + 8);
    }
    __syncwarp();
    mwait(sb + BAR_W + 8, 0, spin);
  }
  permute_cols(wb, tid0 & 127);
  fence_async();
  WBAR_SYNC(NB_G0 + WG, 128);

  uint32_t ph = 0;
  FOR_B_JOBS(wo, l, s)
    if (!wo) {
      float d[16], e[16];
#pragma unroll
      for (int f = 0; f < 5; f++) {
        mwait(sb + BAR_F + 8 * f, ph, spin);
        if (f == 0 && WG == 0 && bc == 0) WTS(l, s, 6);
        wg_fence();
#pragma unroll
        for (int kk = 0; kk < 8; kk++) {
          wgmma_rs32(d, wf[8 * f + kk], rdesc(f, kk), f | kk);
          if (WG == 0) wgmma_ts32(e, mkdesc(SB0 + OFF_W + (8 * f + kk) * 2048, 8192, 1024), rdesc(f, kk), f | kk);
        }
        wg_commit();
        if (f > 0) {
          wg_wait<1>();
          if ((tid0 & 31) == 0) mbar_arrive(sb + BAR_E + 8 * (f - 1));
        }
      }
      wg_wait<0>();
      if ((tid0 & 31) == 0) mbar_arrive(sb + BAR_E + 32);
      WBAR_SYNC(NB_SF, 352);
      const int row0 = (s * 32) % KVR;
      stage_out<WG>(d, sb, l, row0, tid0);
      if (WG == 0) stage_out<2>(e, sb, l, row0, tid0);
      WBAR_ARRIVE(NB_ST, 352);
    } else if (WG == 0) {
#pragma unroll 1
      for (int f = 0; f < 5; f++) {
        mwait(sb + BAR_F + 8 * f, ph, spin);
        if ((tid0 & 31) == 0) mbar_arrive(sb + BAR_E + 8 * f);
      }
    } else {
      float d[16];
#pragma unroll
      for (int f = 0; f < 5; f++) {
        mwait(sb + BAR_F + 8 * f, ph, spin);
        wg_fence();
#pragma unroll
        for (int kk = 0; kk < 8; kk++) wgmma_ts32(d, mkdesc(SB0 + OFF_W + 81920 + (8 * f + kk) * 2048, 8192, 1024), rdesc(f, kk), f | kk);
        wg_commit();
        if (f > 0) {
          wg_wait<1>();
          if ((tid0 & 31) == 0) mbar_arrive(sb + BAR_E + 8 * (f - 1));
        }
      }
      wg_wait<0>();
      if ((tid0 & 31) == 0) mbar_arrive(sb + BAR_E + 32);
      if (bc == 0) WTS(l, s, 10);
      red_tile(d, s, bc * 64, tid0);
      WBAR_SYNC(NB_SG, 160);
    }
    ph ^= 1;
  }
  if (spin >= SPIN_TOT) g_err = 14;
}
__device__ __forceinline__ void work_b_producer(uint32_t sb, int bc) {
  using namespace W;
  int spin = 0;
  uint32_t ph = 1;
  FOR_B_JOBS(wo, l, s)
    cwait((wo ? CN_A : CN_L) + l * 64 + s, 32, spin);
    fence_async_all();
    if (bc == 0) WTS1(l, s, wo ? 9 : 5);
    const uint8_t* src = (wo ? g_ob[l] : g_xnb[l]) + (size_t)s * 40960;
#pragma unroll 1
    for (int f = 0; f < 5; f++) {
      mwait(sb + BAR_E + 8 * f, ph, spin);
      mbar_expect_tx(sb + BAR_F + 8 * f, 8192);
      bulk_g2s(sb + OFF_R + f * 8192, src + f * 8192, 8192, sb + BAR_F + 8 * f);
    }
    ph ^= 1;
  }
  if (spin >= SPIN_TOT) g_err = 15;
}
__device__ __forceinline__ void work_att(uint32_t sb, int bc, int hh, int lane) {
  using namespace W;
  const int head = bc * 3 + hh;
  FOR_B_JOBS(wo, l, s)
    if (wo) continue;
    WBAR_ARRIVE(NB_SF, 352);
    WBAR_SYNC(NB_ST, 352);
    if (bc == 0 && hh == 0 && lane == 0) WTS1(l, s, 7);
    if (head < NH) {
      const float scl = 0.22360679774997896f * 1.4426950408889634f;
      const int pos = s * 32 + lane, r0 = pos % KVR;
      const uint32_t kv = sb + OFF_KV + l * KVR * KVP + hh * 40;
      float sc[8], mx = -INFINITY;
      {
        float q[20];
#pragma unroll
        for (int i = 0; i < 5; i++) {
          const uint2 u = lds64(sb + OFF_Q + lane * QP + hh * 40 + i * 8);
          q[4 * i] = bf_lo(u.x); q[4 * i + 1] = bf_hi(u.x); q[4 * i + 2] = bf_lo(u.y); q[4 * i + 3] = bf_hi(u.y);
        }
#pragma unroll
        for (int j = 0; j < 8; j++) {
          const uint32_t row = kv + (r0 - 2 * j + (r0 < 2 * j ? KVR : 0)) * KVP;
          float s0 = 0.f, s1 = 0.f;
#pragma unroll
          for (int i = 0; i < 5; i++) {
            const uint2 u = lds64(row + i * 8);
            s0 += q[4 * i] * bf_lo(u.x) + q[4 * i + 1] * bf_hi(u.x);
            s1 += q[4 * i + 2] * bf_lo(u.y) + q[4 * i + 3] * bf_hi(u.y);
          }
          sc[j] = pos - 2 * j >= 0 ? (s0 + s1) * scl : -INFINITY;
          if (j & 1) asm volatile("" : "+f"(sc[j]), "+f"(sc[j - 1]) :: "memory");
          mx = fmaxf(mx, sc[j]);
        }
      }
      float sum = 0.f;
#pragma unroll
      for (int j = 0; j < 8; j++) { sc[j] = ex2(sc[j] - mx); sum += sc[j]; }
      const float inv = rcp(sum);
      float o[20];
#pragma unroll
      for (int j = 0; j < 8; j++) {
        const uint32_t row = kv + 120 + (r0 - 2 * j + (r0 < 2 * j ? KVR : 0)) * KVP;
        const float pj = sc[j] * inv;
#pragma unroll
        for (int i = 0; i < 5; i++) {
          const uint2 u = lds64(row + i * 8);
          if (j == 0) { o[4 * i] = pj * bf_lo(u.x); o[4 * i + 1] = pj * bf_hi(u.x); o[4 * i + 2] = pj * bf_lo(u.y); o[4 * i + 3] = pj * bf_hi(u.y); }
          else { o[4 * i] += pj * bf_lo(u.x); o[4 * i + 1] += pj * bf_hi(u.x); o[4 * i + 2] += pj * bf_lo(u.y); o[4 * i + 3] += pj * bf_hi(u.y); }
        }
      }
      uint8_t* img = g_ob[l] + (size_t)s * 40960 + lane * 128;
#pragma unroll
      for (int i = 0; i < 5; i++) {
        const int c = head * 20 + 4 * i;
        *reinterpret_cast<uint2*>(img + (c >> 6) * 4096 + ((((c >> 3) & 7) ^ (lane & 7)) << 4) + (c & 7) * 2) =
            make_uint2(pack_bf16(o[4 * i], o[4 * i + 1]), pack_bf16(o[4 * i + 2], o[4 * i + 3]));
      }
      __syncwarp();
      if (bc == 0 && hh == 0 && lane == 0) WTS1(l, s, 8);
      if (lane == 0) csignal(CN_A + l * 64 + s);
      __syncwarp();
    }
  }
}

__global__ void __launch_bounds__(512, 1)
k_work(const __grid_constant__ CUtensorMap tmWo, const __grid_constant__ CUtensorMap tmBo, const bf16* __restrict__ wqkv, bf16* __restrict__ out) {
  using namespace W;
  extern __shared__ __align__(1024) uint8_t smem[];
  const uint32_t sb = smem_u32(smem);
  const int tid = threadIdx.x, w = blockIdx.x;
  const int wg = __shfl_sync(0xffffffffu, tid >> 7, 0);
  if (tid == 0) {
    if (sb != SB0) g_err = 101;
    for (int i = 0; i < 5; i++) { mbar_init(sb + BAR_F + 8 * i, 1); mbar_init(sb + BAR_E + 8 * i, 8); }
    mbar_init(sb + BAR_W, 1); mbar_init(sb + BAR_W + 8, 1);
    for (int p = 0; p < 16; p++) sts32(sb + OFF_SAFE + 4 * p, 0);
    asm volatile("fence.mbarrier_init.release.cluster;" ::: "memory");
  }
  for (int i = tid; i < 2 * KVR * KVP / 16; i += 512) sts128(sb + OFF_KV + i * 16, make_uint4(0, 0, 0, 0));
  fence_async();
  __syncthreads();

  if (w < NP) {
    if (wg == 0) work_p<0>(tmWo, sb, w, keep(tid));
    else if (wg == 1) work_p<1>(tmWo, sb, w, keep(tid));
    else {
      asm volatile("setmaxnreg.dec.sync.aligned.u32 48;");
      const int aw = (tid >> 5) - 8;
      if (aw == 0) {
        if (tid == 256) work_p_producer(sb, w);
      } else if (aw == 1) {
        FOR_P_JOBS(k_, l, s)
          WBAR_SYNC(NB_SG, 288);
          if (tid == 288) csignal(CN_P + l * 64 + s);
          __syncwarp();
        }
      } else {
        const int id = (aw - 2) * NP + w;
        if (id < 128) work_ln(id & 3, id >> 2, tid & 31, out);
      }
    }
  } else {
    const int bc = w - NP;
    if (wg == 0) work_b<0>(tmBo, wqkv, sb, bc, keep(tid));
    else if (wg == 1) work_b<1>(tmBo, wqkv, sb, bc, keep(tid));
    else if (wg == 2) {
      asm volatile("setmaxnreg.dec.sync.aligned.u32 56;");
      if (tid < 352) work_att(sb, bc, (tid >> 5) & 3, tid & 31);
    } else {
      asm volatile("setmaxnreg.dec.sync.aligned.u32 24;");
      if (tid == 384) work_b_producer(sb, bc);
      else if (tid >= 416 && tid < 448) {
        FOR_B_JOBS(wo, l, s)
          if (!wo) continue;
          WBAR_SYNC(NB_SG, 160);
          if (tid == 416) csignal(CN_W + l * 64 + s);
          __syncwarp();
        }
      }
    }
  }
  __syncthreads();
  asm volatile("griddepcontrol.wait;" ::: "memory");
}

typedef CUresult (*EncodeFn)(CUtensorMap*, CUtensorMapDataType, cuuint32_t, void*, const cuuint64_t*, const cuuint64_t*,
                             const cuuint32_t*, const cuuint32_t*, CUtensorMapInterleave, CUtensorMapSwizzle,
                             CUtensorMapL2promotion, CUtensorMapFloatOOBfill);

static void make_map(EncodeFn enc, CUtensorMap* tm, const void* ptr, uint64_t cols, uint64_t rows, uint32_t boxc, uint32_t boxr) {
  cuuint64_t dims[2] = {cols, rows};
  cuuint64_t strides[1] = {cols * 2};
  cuuint32_t box[2] = {boxc, boxr};
  cuuint32_t es[2] = {1, 1};
  enc(tm, CU_TENSOR_MAP_DATA_TYPE_BFLOAT16, 2, const_cast<void*>(ptr), dims, strides, box, es, CU_TENSOR_MAP_INTERLEAVE_NONE,
      CU_TENSOR_MAP_SWIZZLE_128B, CU_TENSOR_MAP_L2_PROMOTION_L2_256B, CU_TENSOR_MAP_FLOAT_OOB_FILL_NONE);
}

extern "C" void kernel_launch(void* const* d_in, const int* in_sizes, int n_in, void* d_out, int out_size) {
  const bf16* x0 = (const bf16*)d_in[0];
  const bf16* mem0 = (const bf16*)d_in[1];
  const bf16* Wq = (const bf16*)d_in[2];
  const bf16* Wk = (const bf16*)d_in[3];
  const bf16* Wv = (const bf16*)d_in[4];
  const bf16* Wo = (const bf16*)d_in[5];
  const bf16* Bqkv = (const bf16*)d_in[8];
  const bf16* Bwo = (const bf16*)d_in[9];
  bf16* out = (bf16*)d_out;

  static EncodeFn enc = nullptr;
  if (!enc) {
    void* fn = nullptr;
    cudaDriverEntryPointQueryResult qr;
    cudaGetDriverEntryPoint("cuTensorMapEncodeTiled", &fn, cudaEnableDefault, &qr);
    enc = (EncodeFn)fn;
    cudaFuncSetAttribute(k_chain, cudaFuncAttributeMaxDynamicSharedMemorySize, C::SMEM);
    cudaFuncSetAttribute(k_work, cudaFuncAttributeMaxDynamicSharedMemorySize, W::SMEM);
  }
  CUtensorMap tmWq, tmWk, tmWv, tmWo, tmBo;
  make_map(enc, &tmWq, Wq, NH * DH, DM, 64, 128);
  make_map(enc, &tmWk, Wk, NH * DH, DM, 64, 128);
  make_map(enc, &tmWv, Wv, NH * DH, DM, 64, 128);
  make_map(enc, &tmWo, Wo, DM, NH * DH, 64, 64);
  make_map(enc, &tmBo, Bwo, DM, DM, 64, 64);

  cudaStream_t st = cudaStreamPerThread;
  k_pre<<<256, 256, 0, st>>>(x0, mem0);
  cudaLaunchAttribute at[1];
  at[0].id = cudaLaunchAttributeProgrammaticStreamSerialization; at[0].val.programmaticStreamSerializationAllowed = 1;
  {
    cudaLaunchConfig_t cfg = {};
    cfg.gridDim = dim3(96); cfg.blockDim = dim3(384); cfg.dynamicSmemBytes = C::SMEM; cfg.stream = st;
    cfg.attrs = at; cfg.numAttrs = 0;
    cudaLaunchKernelEx(&cfg, k_chain, tmWq, tmWk, tmWv, tmWo);
  }
  cudaLaunchConfig_t cfg = {};
  cfg.gridDim = dim3(W::NW); cfg.blockDim = dim3(512); cfg.dynamicSmemBytes = W::SMEM; cfg.stream = st;
  cfg.attrs = at; cfg.numAttrs = NOWORK == 2 ? 0 : 1;
  cudaLaunchKernelEx(&cfg, k_work, tmWo, tmBo, Bqkv, out);
}
```

```cpp
#include <cuda_runtime.h>
#include <cuda_bf16.h>
#include <cuda.h>
#include <stdint.h>

typedef __nv_bfloat16 bf16;

constexpr int SEQ = 2048, DM = 640, NH = 32, DH = 192, NSEG = 64;
#define LAG 6
constexpr int NSTEP = NSEG + LAG;
constexpr uint32_t SENT = 0xFFFFFFFFu;

constexpr int MAIL9 = 288 * 2048, MAIL_BYTES = MAIL9 + 64 * 3072;
__device__ __align__(1024) uint8_t g_xn[2][NSEG * 40960];
__device__ __align__(1024) uint8_t g_xnb[2][NSEG * 40960];
__device__ __align__(1024) uint8_t g_ob[2][NSEG * 40960];
#define ORING 8
static_assert(ORING > LAG, "a slot is free again LAG + 1 steps later");
__device__ __align__(1024) uint8_t g_o[ORING][2][96][4096];
__device__ __align__(1024) float g_x[SEQ * DM];
__device__ __align__(1024) uint8_t g_mbuf[NSTEP][20480];
__device__ __align__(1024) uint32_t g_flag[NSTEP][768];
__device__ __align__(1024) uint8_t g_mail[2][MAIL_BYTES];
enum { CN_P = 0, CN_L = 128, CN_A = 256, CN_W = 384, CN_X = 512, CN_O = 576, CN_NUM = CN_O + 5 * NSTEP };
__device__ __align__(128) uint32_t g_cnt[CN_NUM][32];
__device__ int g_err;
#define TS(jj, i)
#define TS1(jj, i)
#define PTS(i)
#define TSB(jj, i)
#define TSV(jj, i, v)
#define TS_FLUSH(jj)
#define WTS(l, b, k)
#define WTS1(l, b, k)
#define WW -1

__device__ __forceinline__ uint32_t smem_u32(const void* p) { return (uint32_t)__cvta_generic_to_shared(p); }
__device__ __forceinline__ uint32_t clk32() { uint32_t t; asm volatile("mov.u32 %0, %%clock;" : "=r"(t)::"memory"); return t; }
__device__ __forceinline__ uint32_t mapa(uint32_t a, uint32_t r) { uint32_t o; asm("mapa.shared::cluster.u32 %0,%1,%2;" : "=r"(o) : "r"(a), "r"(r)); return o; }
__device__ __forceinline__ void mbar_init(uint32_t bar, uint32_t cnt) { asm volatile("mbarrier.init.shared::cta.b64 [%0],%1;" ::"r"(bar), "r"(cnt) : "memory"); }
__device__ __forceinline__ void mbar_expect_tx(uint32_t bar, uint32_t bytes) { asm volatile("mbarrier.arrive.expect_tx.shared::cta.b64 _,[%0],%1;" ::"r"(bar), "r"(bytes) : "memory"); }
__device__ __forceinline__ void mbar_arrive(uint32_t bar) { asm volatile("mbarrier.arrive.shared::cta.b64 _,[%0];" ::"r"(bar) : "memory"); }
__device__ __forceinline__ void mbar_arrive_cluster(uint32_t bar) { asm volatile("mbarrier.arrive.shared::cluster.b64 _,[%0];" ::"r"(bar) : "memory"); }
__device__ __forceinline__ bool mbar_try(uint32_t bar, uint32_t ph) {
  uint32_t ok;
  asm volatile("{.reg .pred p; mbarrier.try_wait.parity.shared::cta.b64 p,[%1],%2; selp.u32 %0,1,0,p;}" : "=r"(ok) : "r"(bar), "r"(ph) : "memory");
  return ok;
}
__device__ __forceinline__ int fresh(int x) { asm volatile("" : "+r"(x)); return x; }
#define PHASE_IDS const int tid = fresh(tid0), lane = tid & 31, w = tid >> 5, g = lane >> 2, t = lane & 3; (void)w; (void)g; (void)t
__device__ __forceinline__ void bar_sync(int id, int n) { asm volatile("bar.sync %0,%1;" ::"r"(id), "r"(n) : "memory"); }
__device__ __forceinline__ void bar_arrive(int id, int n) { asm volatile("bar.arrive %0,%1;" ::"r"(id), "r"(n) : "memory"); }
__device__ __forceinline__ bool bar_red_or(int id, int n, bool v) {
  uint32_t r;
  asm volatile("{\n .reg .pred p, q;\n setp.ne.u32 q, %3, 0;\n barrier.cta.red.or.pred p, %1, %2, q;\n selp.u32 %0, 1, 0, p;\n}" : "=r"(r) : "r"(id), "r"(n), "r"((uint32_t)v) : "memory");
  return r != 0;
}
__device__ __forceinline__ void fence_async() { asm volatile("fence.proxy.async.shared::cta;" ::: "memory"); }
__device__ __forceinline__ void bulk_g2s(uint32_t dst, const void* src, uint32_t bytes, uint32_t bar) {
  asm volatile("cp.async.bulk.shared::cluster.global.mbarrier::complete_tx::bytes [%0],[%1],%2,[%3];" ::"r"(dst), "l"(src), "r"(bytes), "r"(bar) : "memory");
}
__device__ __forceinline__ void bulk_g2s_mc(uint32_t dst, const void* src, uint32_t bytes, uint32_t bar) {
  asm volatile("cp.async.bulk.shared::cluster.global.mbarrier::complete_tx::bytes.multicast::cluster [%0],[%1],%2,[%3],%4;"
               ::"r"(dst), "l"(src), "r"(bytes), "r"(bar), "h"((uint16_t)7) : "memory");
}
__device__ __forceinline__ void bulk_s2g(void* dst, uint32_t src, uint32_t bytes) {
  asm volatile("cp.async.bulk.global.shared::cta.bulk_group [%0],[%1],%2;" ::"l"(dst), "r"(src), "r"(bytes) : "memory");
}
__device__ __forceinline__ void bulk_s2c(uint32_t dst, uint32_t src, uint32_t bytes, uint32_t bar) {
  asm volatile("cp.async.bulk.shared::cluster.shared::cta.mbarrier::complete_tx::bytes [%0],[%1],%2,[%3];" ::"r"(dst), "r"(src), "r"(bytes), "r"(bar) : "memory");
}
__device__ __forceinline__ void tma2d(uint32_t dst, const CUtensorMap* tm, int c0, int c1, uint32_t bar) {
  asm volatile("cp.async.bulk.tensor.2d.shared::cluster.global.mbarrier::complete_tx::bytes [%0],[%1,{%3,%4}],[%2];"
               ::"r"(dst), "l"(tm), "r"(bar), "r"(c0), "r"(c1) : "memory");
}
__device__ __forceinline__ void tma2d_prefetch(const CUtensorMap* tm, int c0, int c1) {
  asm volatile("cp.async.bulk.prefetch.tensor.2d.L2.global.tile [%0,{%1,%2}];" ::"l"(tm), "r"(c0), "r"(c1) : "memory");
}
__device__ __forceinline__ uint32_t pack_bf16(float lo, float hi) {
  uint32_t r; asm("cvt.rn.bf16x2.f32 %0,%1,%2;" : "=r"(r) : "f"(hi), "f"(lo)); return r;
}
__device__ __forceinline__ float bf_lo(uint32_t x) { return __uint_as_float(x << 16); }
__device__ __forceinline__ float bf_hi(uint32_t x) { return __uint_as_float(x & 0xFFFF0000u); }
__device__ __forceinline__ float ex2(float x) { float y; asm("ex2.approx.ftz.f32 %0,%1;" : "=f"(y) : "f"(x)); return y; }
__device__ __forceinline__ void ldsm4(uint32_t (&r)[4], uint32_t a) {
  asm volatile("ldmatrix.sync.aligned.m8n8.x4.shared.b16 {%0,%1,%2,%3},[%4];" : "=r"(r[0]), "=r"(r[1]), "=r"(r[2]), "=r"(r[3]) : "r"(a) : "memory");
}
__device__ __forceinline__ void ldsm4t(uint32_t (&r)[4], uint32_t a) {
  asm volatile("ldmatrix.sync.aligned.m8n8.x4.trans.shared.b16 {%0,%1,%2,%3},[%4];" : "=r"(r[0]), "=r"(r[1]), "=r"(r[2]), "=r"(r[3]) : "r"(a) : "memory");
}
__device__ __forceinline__ void ldsm2(uint32_t& r0, uint32_t& r1, uint32_t a) {
  asm volatile("ldmatrix.sync.aligned.m8n8.x2.shared.b16 {%0,%1},[%2];" : "=r"(r0), "=r"(r1) : "r"(a) : "memory");
}
__device__ __forceinline__ void ldsm1(uint32_t& r0, uint32_t a) {
  asm volatile("ldmatrix.sync.aligned.m8n8.x1.shared.b16 {%0},[%1];" : "=r"(r0) : "r"(a) : "memory");
}
__device__ __forceinline__ void mma16816(float (&d)[4], uint32_t a0, uint32_t a1, uint32_t a2, uint32_t a3, uint32_t b0, uint32_t b1) {
  asm volatile("mma.sync.aligned.m16n8k16.row.col.f32.bf16.bf16.f32 {%0,%1,%2,%3},{%4,%5,%6,%7},{%8,%9},{%0,%1,%2,%3};"
               : "+f"(d[0]), "+f"(d[1]), "+f"(d[2]), "+f"(d[3]) : "r"(a0), "r"(a1), "r"(a2), "r"(a3), "r"(b0), "r"(b1));
}
__device__ __forceinline__ void mma1688(float (&d)[4], uint32_t a0, uint32_t a1, uint32_t b0) {
  asm volatile("mma.sync.aligned.m16n8k8.row.col.f32.bf16.bf16.f32 {%0,%1,%2,%3},{%4,%5},{%6},{%0,%1,%2,%3};"
               : "+f"(d[0]), "+f"(d[1]), "+f"(d[2]), "+f"(d[3]) : "r"(a0), "r"(a1), "r"(b0));
}
__device__ __forceinline__ void sts32(uint32_t a, uint32_t v) { asm volatile("st.shared.b32 [%0],%1;" ::"r"(a), "r"(v) : "memory"); }
__device__ __forceinline__ void sts64f(uint32_t a, float x, float y) { asm volatile("st.shared.v2.f32 [%0],{%1,%2};" ::"r"(a), "f"(x), "f"(y) : "memory"); }
__device__ __forceinline__ void sts128(uint32_t a, uint4 v) { asm volatile("st.shared.v4.b32 [%0],{%1,%2,%3,%4};" ::"r"(a), "r"(v.x), "r"(v.y), "r"(v.z), "r"(v.w) : "memory"); }
__device__ __forceinline__ float lds32f(uint32_t a) { float v; asm volatile("ld.shared.f32 %0,[%1];" : "=f"(v) : "r"(a) : "memory"); return v; }
__device__ __forceinline__ float2 lds64f(uint32_t a) { float2 v; asm volatile("ld.shared.v2.f32 {%0,%1},[%2];" : "=f"(v.x), "=f"(v.y) : "r"(a) : "memory"); return v; }
__device__ __forceinline__ uint4 lds128(uint32_t a) { uint4 v; asm volatile("ld.shared.v4.b32 {%0,%1,%2,%3},[%4];" : "=r"(v.x), "=r"(v.y), "=r"(v.z), "=r"(v.w) : "r"(a) : "memory"); return v; }
__device__ __forceinline__ float4 lds128f(uint32_t a) { float4 v; asm volatile("ld.shared.v4.f32 {%0,%1,%2,%3},[%4];" : "=f"(v.x), "=f"(v.y), "=f"(v.z), "=f"(v.w) : "r"(a) : "memory"); return v; }
__device__ __forceinline__ void st_async2(uint32_t a, float x, float y, uint32_t bar) {
  asm volatile("st.async.weak.shared::cluster.mbarrier::complete_tx::bytes.v2.f32 [%0],{%1,%2},[%3];" ::"r"(a), "f"(x), "f"(y), "r"(bar) : "memory");
}
__device__ __forceinline__ void st_async4(uint32_t a, const float (&v)[4], uint32_t bar) {
  asm volatile("st.async.weak.shared::cluster.mbarrier::complete_tx::bytes.v4.f32 [%0],{%1,%2,%3,%4},[%5];" ::"r"(a), "f"(v[0]), "f"(v[1]), "f"(v[2]), "f"(v[3]), "r"(bar) : "memory");
}
__device__ __forceinline__ void st_async4v(uint32_t a, float x, float y, float z, float w, uint32_t bar) {
  asm volatile("st.async.weak.shared::cluster.mbarrier::complete_tx::bytes.v4.f32 [%0],{%1,%2,%3,%4},[%5];" ::"r"(a), "f"(x), "f"(y), "f"(z), "f"(w), "r"(bar) : "memory");
}
__device__ __forceinline__ void st_async4u(uint32_t a, const uint4& v, uint32_t bar) {
  asm volatile("st.async.weak.shared::cluster.mbarrier::complete_tx::bytes.v4.b32 [%0],{%1,%2,%3,%4},[%5];" ::"r"(a), "r"(v.x), "r"(v.y), "r"(v.z), "r"(v.w), "r"(bar) : "memory");
}
__device__ __forceinline__ uint4 ld_relaxed4(const void* p) {
  uint4 v; asm volatile("ld.relaxed.gpu.global.v4.u32 {%0,%1,%2,%3},[%4];" : "=r"(v.x), "=r"(v.y), "=r"(v.z), "=r"(v.w) : "l"(p) : "memory"); return v;
}
__device__ __forceinline__ uint32_t ld_relaxed(const void* p) {
  uint32_t v; asm volatile("ld.relaxed.gpu.global.u32 %0,[%1];" : "=r"(v) : "l"(p) : "memory"); return v;
}
__device__ __forceinline__ void st_relaxed(void* p, uint32_t v) { asm volatile("st.relaxed.gpu.global.b32 [%0],%1;" ::"l"(p), "r"(v) : "memory"); }
__device__ __forceinline__ void st_relaxed4(void* p, uint32_t v) { asm volatile("st.relaxed.gpu.global.v4.b32 [%0],{%1,%1,%1,%1};" ::"l"(p), "r"(v) : "memory"); }

__device__ __forceinline__ uint32_t ld_acquire(const void* p) {
  uint32_t v; asm volatile("ld.acquire.gpu.global.u32 %0,[%1];" : "=r"(v) : "l"(p) : "memory"); return v;
}
__device__ __forceinline__ float4 ld_relaxed4f(const void* p) {
  float4 v; asm volatile("ld.relaxed.gpu.global.v4.f32 {%0,%1,%2,%3},[%4];" : "=f"(v.x), "=f"(v.y), "=f"(v.z), "=f"(v.w) : "l"(p) : "memory"); return v;
}
__device__ __forceinline__ float2 ld_relaxed2f(const void* p) {
  float2 v; asm volatile("ld.relaxed.gpu.global.v2.f32 {%0,%1},[%2];" : "=f"(v.x), "=f"(v.y) : "l"(p) : "memory"); return v;
}
__device__ __forceinline__ void prefetch_l2(const void* p) { asm volatile("prefetch.global.L2 [%0];" ::"l"(p)); }
__device__ __forceinline__ void fence_gpu() { asm volatile("fence.acq_rel.gpu;" ::: "memory"); }
__device__ __forceinline__ void fence_async_all() { asm volatile("fence.proxy.async.global;" ::: "memory"); }
constexpr int SPIN_TOT = 1 << 22;
__device__ __forceinline__ void csignal(int idx) { asm volatile("red.release.gpu.global.add.u32 [%0],1;" ::"l"(&g_cnt[idx][0]) : "memory"); }
__device__ __forceinline__ void cwait(int idx, uint32_t target, int& spin) {
  while (ld_acquire(&g_cnt[idx][0]) < target && spin < SPIN_TOT) spin += 16;
}

__device__ __forceinline__ uint64_t mkdesc(uint32_t addr, uint32_t lbo, uint32_t sbo) {
  return (uint64_t)((addr & 0x3FFFF) >> 4) | ((uint64_t)(lbo >> 4) << 16) | ((uint64_t)(sbo >> 4) << 32) | ((uint64_t)1 << 62);
}
__device__ __forceinline__ uint64_t mkdesc_ns(uint32_t addr, uint32_t lbo, uint32_t sbo) {
  return (uint64_t)((addr & 0x3FFFF) >> 4) | ((uint64_t)(lbo >> 4) << 16) | ((uint64_t)(sbo >> 4) << 32);
}
__device__ __forceinline__ void wg_fence() { asm volatile("wgmma.fence.sync.aligned;" ::: "memory"); }
__device__ __forceinline__ void wg_commit() { asm volatile("wgmma.commit_group.sync.aligned;" ::: "memory"); }
template <int N> __device__ __forceinline__ void wg_wait() { asm volatile("wgmma.wait_group.sync.aligned %0;" ::"n"(N) : "memory"); }

__device__ __forceinline__ void wgmma_rs16(float (&d)[8], const uint32_t (&a)[4], uint64_t db, int sc) {
  asm volatile("{.reg .pred p; setp.ne.b32 p,%13,0; wgmma.mma_async.sync.aligned.m64n16k16.f32.bf16.bf16 "
               "{%0,%1,%2,%3,%4,%5,%6,%7},{%8,%9,%10,%11},%12,p,1,1,0;}"
               : "+f"(d[0]), "+f"(d[1]), "+f"(d[2]), "+f"(d[3]), "+f"(d[4]), "+f"(d[5]), "+f"(d[6]), "+f"(d[7])
               : "r"(a[0]), "r"(a[1]), "r"(a[2]), "r"(a[3]), "l"(db), "r"(sc));
}
__device__ __forceinline__ void wgmma_rs64(float (&d)[32], const uint32_t (&a)[4], uint64_t db, int sc) {
  asm volatile("{.reg .pred p; setp.ne.b32 p,%37,0; wgmma.mma_async.sync.aligned.m64n64k16.f32.bf16.bf16 "
               "{%0,%1,%2,%3,%4,%5,%6,%7,%8,%9,%10,%11,%12,%13,%14,%15,%16,%17,%18,%19,%20,%21,%22,%23,%24,%25,%26,%27,%28,%29,%30,%31},{%32,%33,%34,%35},%36,p,1,1,0;}"
               : "+f"(d[0]), "+f"(d[1]), "+f"(d[2]), "+f"(d[3]), "+f"(d[4]), "+f"(d[5]), "+f"(d[6]), "+f"(d[7]), "+f"(d[8]), "+f"(d[9]), "+f"(d[10]), "+f"(d[11]), "+f"(d[12]), "+f"(d[13]), "+f"(d[14]), "+f"(d[15]), "+f"(d[16]), "+f"(d[17]), "+f"(d[18]), "+f"(d[19]), "+f"(d[20]), "+f"(d[21]), "+f"(d[22]), "+f"(d[23]), "+f"(d[24]), "+f"(d[25]), "+f"(d[26]), "+f"(d[27]), "+f"(d[28]), "+f"(d[29]), "+f"(d[30]), "+f"(d[31])
               : "r"(a[0]), "r"(a[1]), "r"(a[2]), "r"(a[3]), "l"(db), "r"(sc));
}
__device__ __forceinline__ void wgmma_rt16(float (&d)[8], const uint32_t (&a)[4], uint64_t db, int sc) {
  asm volatile("{.reg .pred p; setp.ne.b32 p,%13,0; wgmma.mma_async.sync.aligned.m64n16k16.f32.bf16.bf16 "
               "{%0,%1,%2,%3,%4,%5,%6,%7},{%8,%9,%10,%11},%12,p,1,1,1;}"
               : "+f"(d[0]), "+f"(d[1]), "+f"(d[2]), "+f"(d[3]), "+f"(d[4]), "+f"(d[5]), "+f"(d[6]), "+f"(d[7])
               : "r"(a[0]), "r"(a[1]), "r"(a[2]), "r"(a[3]), "l"(db), "r"(sc));
}
__device__ __forceinline__ void wgmma_rt80(float (&d)[40], const uint32_t (&a)[4], uint64_t db, int sc) {
  asm volatile("{.reg .pred p; setp.ne.b32 p,%45,0; wgmma.mma_async.sync.aligned.m64n80k16.f32.bf16.bf16 "
               "{%0,%1,%2,%3,%4,%5,%6,%7,%8,%9,%10,%11,%12,%13,%14,%15,%16,%17,%18,%19,%20,%21,%22,%23,%24,%25,%26,%27,%28,%29,%30,%31,%32,%33,%34,%35,%36,%37,%38,%39},{%40,%41,%42,%43},%44,p,1,1,1;}"
               : "+f"(d[0]), "+f"(d[1]), "+f"(d[2]), "+f"(d[3]), "+f"(d[4]), "+f"(d[5]), "+f"(d[6]), "+f"(d[7]), "+f"(d[8]), "+f"(d[9]), "+f"(d[10]), "+f"(d[11]), "+f"(d[12]), "+f"(d[13]), "+f"(d[14]), "+f"(d[15]), "+f"(d[16]), "+f"(d[17]), "+f"(d[18]), "+f"(d[19]), "+f"(d[20]), "+f"(d[21]), "+f"(d[22]), "+f"(d[23]), "+f"(d[24]), "+f"(d[25]), "+f"(d[26]), "+f"(d[27]), "+f"(d[28]), "+f"(d[29]), "+f"(d[30]), "+f"(d[31]), "+f"(d[32]), "+f"(d[33]), "+f"(d[34]), "+f"(d[35]), "+f"(d[36]), "+f"(d[37]), "+f"(d[38]), "+f"(d[39])
               : "r"(a[0]), "r"(a[1]), "r"(a[2]), "r"(a[3]), "l"(db), "r"(sc));
}
__device__ __forceinline__ void wgmma_rs32(float (&d)[16], const uint32_t (&a)[4], uint64_t db, int sc) {
  asm volatile("{.reg .pred p; setp.ne.b32 p,%21,0; wgmma.mma_async.sync.aligned.m64n32k16.f32.bf16.bf16 "
               "{%0,%1,%2,%3,%4,%5,%6,%7,%8,%9,%10,%11,%12,%13,%14,%15},{%16,%17,%18,%19},%20,p,1,1,0;}"
               : "+f"(d[0]), "+f"(d[1]), "+f"(d[2]), "+f"(d[3]), "+f"(d[4]), "+f"(d[5]), "+f"(d[6]), "+f"(d[7]), "+f"(d[8]), "+f"(d[9]), "+f"(d[10]), "+f"(d[11]), "+f"(d[12]), "+f"(d[13]), "+f"(d[14]), "+f"(d[15])
               : "r"(a[0]), "r"(a[1]), "r"(a[2]), "r"(a[3]), "l"(db), "r"(sc));
}
__device__ __forceinline__ void wgmma_ts32(float (&d)[16], uint64_t da, uint64_t db, int sc) {
  asm volatile("{.reg .pred p; setp.ne.b32 p,%18,0; wgmma.mma_async.sync.aligned.m64n32k16.f32.bf16.bf16 "
               "{%0,%1,%2,%3,%4,%5,%6,%7,%8,%9,%10,%11,%12,%13,%14,%15},%16,%17,p,1,1,1,0;}"
               : "+f"(d[0]), "+f"(d[1]), "+f"(d[2]), "+f"(d[3]), "+f"(d[4]), "+f"(d[5]), "+f"(d[6]), "+f"(d[7]), "+f"(d[8]), "+f"(d[9]), "+f"(d[10]), "+f"(d[11]), "+f"(d[12]), "+f"(d[13]), "+f"(d[14]), "+f"(d[15])
               : "l"(da), "l"(db), "r"(sc));
}
__device__ __forceinline__ void wgmma_ts16(float (&d)[8], uint64_t da, uint64_t db, int sc) {
  asm volatile("{.reg .pred p; setp.ne.b32 p,%10,0; wgmma.mma_async.sync.aligned.m64n16k16.f32.bf16.bf16 "
               "{%0,%1,%2,%3,%4,%5,%6,%7},%8,%9,p,1,1,1,0;}"
               : "+f"(d[0]), "+f"(d[1]), "+f"(d[2]), "+f"(d[3]), "+f"(d[4]), "+f"(d[5]), "+f"(d[6]), "+f"(d[7])
               : "l"(da), "l"(db), "r"(sc));
}
__device__ __forceinline__ void wgmma_ts64(float (&d)[32], uint64_t da, uint64_t db, int sc) {
  asm volatile("{.reg .pred p; setp.ne.b32 p,%34,0; wgmma.mma_async.sync.aligned.m64n64k16.f32.bf16.bf16 "
               "{%0,%1,%2,%3,%4,%5,%6,%7,%8,%9,%10,%11,%12,%13,%14,%15,%16,%17,%18,%19,%20,%21,%22,%23,%24,%25,%26,%27,%28,%29,%30,%31},%32,%33,p,1,1,1,0;}"
               : "+f"(d[0]), "+f"(d[1]), "+f"(d[2]), "+f"(d[3]), "+f"(d[4]), "+f"(d[5]), "+f"(d[6]), "+f"(d[7]), "+f"(d[8]), "+f"(d[9]), "+f"(d[10]), "+f"(d[11]), "+f"(d[12]), "+f"(d[13]), "+f"(d[14]), "+f"(d[15]), "+f"(d[16]), "+f"(d[17]), "+f"(d[18]), "+f"(d[19]), "+f"(d[20]), "+f"(d[21]), "+f"(d[22]), "+f"(d[23]), "+f"(d[24]), "+f"(d[25]), "+f"(d[26]), "+f"(d[27]), "+f"(d[28]), "+f"(d[29]), "+f"(d[30]), "+f"(d[31])
               : "l"(da), "l"(db), "r"(sc));
}
__device__ __forceinline__ void wgmma_tt16(float (&d)[8], uint64_t da, uint64_t db, int sc) {
  asm volatile("{.reg .pred p; setp.ne.b32 p,%10,0; wgmma.mma_async.sync.aligned.m64n16k16.f32.bf16.bf16 "
               "{%0,%1,%2,%3,%4,%5,%6,%7},%8,%9,p,1,1,1,1;}"
               : "+f"(d[0]), "+f"(d[1]), "+f"(d[2]), "+f"(d[3]), "+f"(d[4]), "+f"(d[5]), "+f"(d[6]), "+f"(d[7])
               : "l"(da), "l"(db), "r"(sc));
}
__device__ __forceinline__ void wgmma_tt40(float (&d)[20], uint64_t da, uint64_t db, int sc) {
  asm volatile("{.reg .pred p; setp.ne.b32 p,%22,0; wgmma.mma_async.sync.aligned.m64n40k16.f32.bf16.bf16 "
               "{%0,%1,%2,%3,%4,%5,%6,%7,%8,%9,%10,%11,%12,%13,%14,%15,%16,%17,%18,%19},%20,%21,p,1,1,1,1;}"
               : "+f"(d[0]), "+f"(d[1]), "+f"(d[2]), "+f"(d[3]), "+f"(d[4]), "+f"(d[5]), "+f"(d[6]), "+f"(d[7]), "+f"(d[8]), "+f"(d[9]), "+f"(d[10]), "+f"(d[11]), "+f"(d[12]), "+f"(d[13]), "+f"(d[14]), "+f"(d[15]), "+f"(d[16]), "+f"(d[17]), "+f"(d[18]), "+f"(d[19])
               : "l"(da), "l"(db), "r"(sc));
}
__device__ __forceinline__ void wgmma_ss8(float (&d)[4], uint64_t da, uint64_t db, int sc) {
  asm volatile("{.reg .pred p; setp.ne.b32 p,%6,0; wgmma.mma_async.sync.aligned.m64n8k16.f32.bf16.bf16 "
               "{%0,%1,%2,%3},%4,%5,p,1,1,0,0;}"
               : "+f"(d[0]), "+f"(d[1]), "+f"(d[2]), "+f"(d[3])
               : "l"(da), "l"(db), "r"(sc));
}
__device__ __forceinline__ void wgmma_ss32(float (&d)[16], uint64_t da, uint64_t db, int sc) {
  asm volatile("{.reg .pred p; setp.ne.b32 p,%18,0; wgmma.mma_async.sync.aligned.m64n32k16.f32.bf16.bf16 "
               "{%0,%1,%2,%3,%4,%5,%6,%7,%8,%9,%10,%11,%12,%13,%14,%15},%16,%17,p,1,1,0,0;}"
               : "+f"(d[0]), "+f"(d[1]), "+f"(d[2]), "+f"(d[3]), "+f"(d[4]), "+f"(d[5]), "+f"(d[6]), "+f"(d[7]), "+f"(d[8]), "+f"(d[9]), "+f"(d[10]), "+f"(d[11]), "+f"(d[12]), "+f"(d[13]), "+f"(d[14]), "+f"(d[15])
               : "l"(da), "l"(db), "r"(sc));
}
__device__ __forceinline__ void wgmma_st64(float (&d)[32], uint64_t da, uint64_t db, int sc) {
  asm volatile("{.reg .pred p; setp.ne.b32 p,%34,0; wgmma.mma_async.sync.aligned.m64n64k16.f32.bf16.bf16 "
               "{%0,%1,%2,%3,%4,%5,%6,%7,%8,%9,%10,%11,%12,%13,%14,%15,%16,%17,%18,%19,%20,%21,%22,%23,%24,%25,%26,%27,%28,%29,%30,%31},%32,%33,p,1,1,0,1;}"
               : "+f"(d[0]), "+f"(d[1]), "+f"(d[2]), "+f"(d[3]), "+f"(d[4]), "+f"(d[5]), "+f"(d[6]), "+f"(d[7]), "+f"(d[8]), "+f"(d[9]), "+f"(d[10]), "+f"(d[11]), "+f"(d[12]), "+f"(d[13]), "+f"(d[14]), "+f"(d[15]), "+f"(d[16]), "+f"(d[17]), "+f"(d[18]), "+f"(d[19]), "+f"(d[20]), "+f"(d[21]), "+f"(d[22]), "+f"(d[23]), "+f"(d[24]), "+f"(d[25]), "+f"(d[26]), "+f"(d[27]), "+f"(d[28]), "+f"(d[29]), "+f"(d[30]), "+f"(d[31])
               : "l"(da), "l"(db), "r"(sc));
}
__device__ __forceinline__ void wgmma_st128(float (&d)[64], uint64_t da, uint64_t db, int sc) {
  asm volatile("{.reg .pred p; setp.ne.b32 p,%66,0; wgmma.mma_async.sync.aligned.m64n128k16.f32.bf16.bf16 "
               "{%0,%1,%2,%3,%4,%5,%6,%7,%8,%9,%10,%11,%12,%13,%14,%15,%16,%17,%18,%19,%20,%21,%22,%23,%24,%25,%26,%27,%28,%29,%30,%31,%32,%33,%34,%35,%36,%37,%38,%39,%40,%41,%42,%43,%44,%45,%46,%47,%48,%49,%50,%51,%52,%53,%54,%55,%56,%57,%58,%59,%60,%61,%62,%63},%64,%65,p,1,1,0,1;}"
               : "+f"(d[0]), "+f"(d[1]), "+f"(d[2]), "+f"(d[3]), "+f"(d[4]), "+f"(d[5]), "+f"(d[6]), "+f"(d[7]), "+f"(d[8]), "+f"(d[9]), "+f"(d[10]), "+f"(d[11]), "+f"(d[12]), "+f"(d[13]), "+f"(d[14]), "+f"(d[15]), "+f"(d[16]), "+f"(d[17]), "+f"(d[18]), "+f"(d[19]), "+f"(d[20]), "+f"(d[21]), "+f"(d[22]), "+f"(d[23]), "+f"(d[24]), "+f"(d[25]), "+f"(d[26]), "+f"(d[27]), "+f"(d[28]), "+f"(d[29]), "+f"(d[30]), "+f"(d[31]), "+f"(d[32]), "+f"(d[33]), "+f"(d[34]), "+f"(d[35]), "+f"(d[36]), "+f"(d[37]), "+f"(d[38]), "+f"(d[39]), "+f"(d[40]), "+f"(d[41]), "+f"(d[42]), "+f"(d[43]), "+f"(d[44]), "+f"(d[45]), "+f"(d[46]), "+f"(d[47]), "+f"(d[48]), "+f"(d[49]), "+f"(d[50]), "+f"(d[51]), "+f"(d[52]), "+f"(d[53]), "+f"(d[54]), "+f"(d[55]), "+f"(d[56]), "+f"(d[57]), "+f"(d[58]), "+f"(d[59]), "+f"(d[60]), "+f"(d[61]), "+f"(d[62]), "+f"(d[63])
               : "l"(da), "l"(db), "r"(sc));
}

__device__ __forceinline__ void stsm4(uint32_t a, uint32_t r0, uint32_t r1, uint32_t r2, uint32_t r3) {
  asm volatile("stmatrix.sync.aligned.m8n8.x4.shared.b16 [%0],{%1,%2,%3,%4};" ::"r"(a), "r"(r0), "r"(r1), "r"(r2), "r"(r3) : "memory");
}
__device__ __forceinline__ void stsm4t(uint32_t a, uint32_t r0, uint32_t r1, uint32_t r2, uint32_t r3) {
  asm volatile("stmatrix.sync.aligned.m8n8.x4.trans.shared.b16 [%0],{%1,%2,%3,%4};" ::"r"(a), "r"(r0), "r"(r1), "r"(r2), "r"(r3) : "memory");
}
__device__ __forceinline__ void sts64(uint32_t a, uint32_t x, uint32_t y) { asm volatile("st.shared.v2.b32 [%0],{%1,%2};" ::"r"(a), "r"(x), "r"(y) : "memory"); }
__device__ __forceinline__ void st_async2u(uint32_t a, uint32_t x, uint32_t y, uint32_t bar) {
  asm volatile("st.async.weak.shared::cluster.mbarrier::complete_tx::bytes.v2.b32 [%0],{%1,%2},[%3];" ::"r"(a), "r"(x), "r"(y), "r"(bar) : "memory");
}
__device__ __forceinline__ void st_relaxed128(void* p, uint32_t x, uint32_t y, uint32_t z, uint32_t w) {
  asm volatile("{.reg .b128 v; mov.b128 v,{%1,%2,%3,%4}; st.relaxed.gpu.global.b128 [%0],v;}" ::"l"(p), "r"(x), "r"(y), "r"(z), "r"(w) : "memory");
}
__device__ __forceinline__ void st_relaxed64(void* p, uint32_t x, uint32_t y) {
  asm volatile("{.reg .b64 v; mov.b64 v,{%1,%2}; st.relaxed.gpu.global.b64 [%0],v;}" ::"l"(p), "r"(x), "r"(y) : "memory");
}
__device__ __forceinline__ uint4 ld_relaxed128(const void* p) {
  uint4 v;
  asm volatile("{.reg .b128 v; .reg .b64 lo, hi; ld.relaxed.gpu.global.b128 v,[%4]; mov.b128 {lo,hi},v; mov.b64 {%0,%1},lo; mov.b64 {%2,%3},hi;}" : "=r"(v.x), "=r"(v.y), "=r"(v.z), "=r"(v.w) : "l"(p) : "memory");
  return v;
}

__device__ __forceinline__ uint32_t pack_h2(float lo, float hi) {
  uint32_t r; asm("cvt.rn.satfinite.f16x2.f32 %0,%1,%2;" : "=r"(r) : "f"(hi), "f"(lo)); return r;
}
__device__ __forceinline__ void add_h2(float& lo, float& hi, uint32_t u, uint32_t v) {
  float a, b;
  asm("{.reg .b16 l, h; .reg .b32 s; add.rn.f16x2 s,%2,%3; mov.b32 {l,h},s; cvt.f32.f16 %0,l; cvt.f32.f16 %1,h;}" : "=f"(a), "=f"(b) : "r"(u), "r"(v));
  lo += a; hi += b;
}
__device__ __forceinline__ void mwait(uint32_t bar, uint32_t ph, int& spin) {
  asm volatile("{.reg .pred p, q;\nWAIT_LOOP:\n add.s32 %0,%0,1;\n setp.lt.s32 q,%0,%3;\n mbarrier.try_wait.parity.shared::cta.b64 p,[%1],%2;\n not.pred p,p;\n and.pred q,q,p;\n @q bra.uni WAIT_LOOP;\n}"
               : "+&r"(spin) : "r"(bar), "r"(ph), "n"(SPIN_TOT) : "memory");
}
__device__ __forceinline__ int keep(int x) { return __shfl_sync(0xffffffffu, x, threadIdx.x & 31); }
__device__ __forceinline__ uint32_t pin(uint32_t x) { asm volatile("" : "+r"(x)); return x; }
template <typename T> __device__ __forceinline__ T* pinp(T* x) { asm volatile("" : "+l"(x)); return x; }
__device__ __forceinline__ void st_async1u(uint32_t a, uint32_t x, uint32_t bar) {
  asm volatile("st.async.weak.shared::cluster.mbarrier::complete_tx::bytes.b32 [%0],%1,[%2];" ::"r"(a), "r"(x), "r"(bar) : "memory");
}
__device__ __forceinline__ uint32_t lds32(uint32_t a) { uint32_t v; asm volatile("ld.shared.b32 %0,[%1];" : "=r"(v) : "r"(a) : "memory"); return v; }
__device__ __forceinline__ uint2 lds64(uint32_t a) { uint2 v; asm volatile("ld.shared.v2.b32 {%0,%1},[%2];" : "=r"(v.x), "=r"(v.y) : "r"(a) : "memory"); return v; }

__device__ __forceinline__ void permute_cols(uint32_t tile, int tid) {
  for (int it = tid; it < 2560; it += 128) {
    const int row = it >> 2, q = it & 3;
    const uint32_t a0 = tile + row * 128 + (((2 * q) ^ (row & 7)) << 4), a1 = tile + row * 128 + (((2 * q + 1) ^ (row & 7)) << 4);
    const uint4 u = lds128(a0), v = lds128(a1);
    sts128(a0, make_uint4(__byte_perm(u.x, u.y, 0x5410), __byte_perm(u.z, u.w, 0x5410), __byte_perm(v.x, v.y, 0x5410), __byte_perm(v.z, v.w, 0x5410)));
    sts128(a1, make_uint4(__byte_perm(u.x, u.y, 0x7632), __byte_perm(u.z, u.w, 0x7632), __byte_perm(v.x, v.y, 0x7632), __byte_perm(v.z, v.w, 0x7632)));
  }
}

__device__ __forceinline__ void ln_row_to_image(const bf16* __restrict__ x, uint8_t* __restrict__ img, int row, int lane) {
  const uint4* src = reinterpret_cast<const uint4*>(x + (size_t)row * DM);
  uint4 v[3];
  v[0] = src[lane]; v[1] = src[lane + 32];
  v[2] = lane < 16 ? src[lane + 64] : make_uint4(0, 0, 0, 0);
  float s = 0.f;
#pragma unroll
  for (int i = 0; i < 3; i++) {
    s += bf_lo(v[i].x) + bf_hi(v[i].x) + bf_lo(v[i].y) + bf_hi(v[i].y) + bf_lo(v[i].z) + bf_hi(v[i].z) + bf_lo(v[i].w) + bf_hi(v[i].w);
  }
#pragma unroll
  for (int o = 16; o > 0; o >>= 1) s += __shfl_xor_sync(0xffffffffu, s, o);
  const float mean = s * (1.f / DM);
  float q = 0.f;
#pragma unroll
  for (int i = 0; i < 3; i++) {
    if (i < 2 || lane < 16) {
      const uint32_t w[4] = {v[i].x, v[i].y, v[i].z, v[i].w};
#pragma unroll
      for (int j = 0; j < 4; j++) { float a = bf_lo(w[j]) - mean, b = bf_hi(w[j]) - mean; q += a * a + b * b; }
    }
  }
#pragma unroll
  for (int o = 16; o > 0; o >>= 1) q += __shfl_xor_sync(0xffffffffu, q, o);
  const float rstd = rsqrtf(q * (1.f / DM) + 1e-5f);
#pragma unroll
  for (int i = 0; i < 3; i++) {
    if (i < 2 || lane < 16) {
      const int c = lane + 32 * i;
      uint4 o;
      o.x = pack_bf16((bf_lo(v[i].x) - mean) * rstd, (bf_hi(v[i].x) - mean) * rstd);
      o.y = pack_bf16((bf_lo(v[i].y) - mean) * rstd, (bf_hi(v[i].y) - mean) * rstd);
      o.z = pack_bf16((bf_lo(v[i].z) - mean) * rstd, (bf_hi(v[i].z) - mean) * rstd);
      o.w = pack_bf16((bf_lo(v[i].w) - mean) * rstd, (bf_hi(v[i].w) - mean) * rstd);
      const size_t off = (size_t)(row >> 5) * 40960 + (c >> 4) * 8192 + ((row >> 3) & 3) * 2048 + ((c >> 3) & 1) * 1024 + (row & 7) * 128 + (((c & 7) ^ (row & 7)) << 4);
      *reinterpret_cast<uint4*>(img + off) = o;
      float4* xf = reinterpret_cast<float4*>(g_x + (size_t)row * DM + c * 8);
      xf[0] = make_float4(bf_lo(v[i].x), bf_hi(v[i].x), bf_lo(v[i].y), bf_hi(v[i].y));
      xf[1] = make_float4(bf_lo(v[i].z), bf_hi(v[i].z), bf_lo(v[i].w), bf_hi(v[i].w));
    }
  }
}

__global__ void __launch_bounds__(256) k_pre(const bf16* __restrict__ x, const bf16* __restrict__ mem0) {
  const int row = blockIdx.x * 8 + (threadIdx.x >> 5);
  ln_row_to_image(x, g_xn[0], row, threadIdx.x & 31);
  const int gt = blockIdx.x * 256 + threadIdx.x;
  const uint4 sent = make_uint4(SENT, SENT, SENT, SENT);
  uint4* mail = reinterpret_cast<uint4*>(&g_mail[0][0]);
  for (int i = gt; i < 2 * MAIL_BYTES / 16; i += 65536) mail[i] = sent;
  uint4* mb = reinterpret_cast<uint4*>(&g_mbuf[0][0]);
  for (int i = gt; i < NSTEP * 1280; i += 65536) {
    const int p = i % 1280, st = i / 1280;
    uint4 v = sent;
    if (st == 0 || (st == LAG && (p & 8))) v = *reinterpret_cast<const uint4*>(mem0 + (p & 7) * DM + (p >> 4) * 8);
    mb[i] = v;
  }
  if (gt < NSTEP * 192) reinterpret_cast<uint4*>(&g_flag[0][0])[gt] = gt < 192 ? make_uint4(0, 0, 0, 0) : sent;
  if (gt < CN_NUM) g_cnt[gt][0] = 0;
}

namespace C {
constexpr int NKR = 37;
constexpr int OFF_WQ = 0, OFF_WK = 81920;
constexpr int OFF_YO = 163840, OFF_YV = OFF_YO + 6144;
constexpr int OFF_M = 176128;
__host__ __device__ constexpr int og_off(int c) { return c ? OFF_M + 14336 + c * 2048 : 229376; }
constexpr int OFF_KT = 196608;
constexpr int OFF_XT = OFF_KT + 10240;
constexpr int OFF_VT = OFF_XT + 7168;
constexpr int OFF_XM = OFF_VT + 11392;
constexpr int KS = 1280, VS = 1408;
__host__ __device__ constexpr int slot_off(int p) { return p == 2 ? OFF_M : OFF_KT + (p % 3) * 16384; }
constexpr int OFF_BAR = 231552;
constexpr int OFF_SAFE = OFF_BAR + 160;
constexpr int OFF_TS = OFF_BAR + 256;
constexpr int SMEM = 232448;
constexpr uint32_t SB0 = 1024;
constexpr int BAR_F = OFF_BAR, BAR_E = OFF_BAR + 40, BAR_M = OFF_BAR + 80, BAR_MOK = OFF_BAR + 88, BAR_XM = OFF_BAR + 96, BAR_XF = OFF_BAR + 104,
              BAR_XT = OFF_BAR + 112, BAR_MF = OFF_BAR + 120, BAR_OG = OFF_BAR + 128, BAR_W = OFF_BAR + 136, FLG_REDO = OFF_BAR + 144;
constexpr int NB_PRO = 1, NB_RD = 2, NB_MR = 3, NB_QK = 4, NB_SM = 5, NB_VA = 6, NB_VQ = 7, NB_A = 8, NB_Q = 9, NB_C = 10, NB_WQ = 11, NB_QI = 12, NB_SI = 13, NB_WV = 14;
#define B1 300
#define B2 400
#define FLP 0
#define OSG 2
#define QIE 4
#define SIE 2
#define WOE 1
#define OGF 0
#define VSP 8
#define RFK 5
#define PFD 3
#define WOL 0
#define NOWORK 0
constexpr float SCL = 0.07216878364870322f * 1.4426950408889634f / 256;
}

#define CBAR_SYNC(id, n) bar_sync(id, n)
#define CBAR_ARRIVE(id, n) bar_arrive(id, n)

__device__ __forceinline__ uint64_t wdesc(int off) { return mkdesc(C::SB0 + off, 8192, 1024); }
__device__ __forceinline__ uint64_t mdesc(int k) { return mkdesc_ns(C::SB0 + C::OFF_M + k * 512, 256, 128); }
__device__ __forceinline__ uint64_t tdesc(int k) { return mkdesc(C::SB0 + C::slot_off(k >> 3) + ((k >> 2) & 1) * 1024 + (k & 3) * 32, 16, 2048); }

__device__ __forceinline__ int dh_row(int n) { return (n & ~63) + (n & 32) + ((n >> 1) & 3) * 8 + ((n >> 3) & 3) * 2 + (n & 1); }
template <bool PERM>
__device__ __forceinline__ void load_weights_rs(uint32_t (&wf)[C::NKR][4], uint32_t sb, int stage, int yoff, int tid0) {
  using namespace C;
  const int i = (tid0 >> 3) & 3, n0 = (tid0 & 7) + (i >> 1) * 8;
  const int chunk = 2 * ((tid0 >> 5) & 3) + (i & 1);
  const int r0 = PERM ? dh_row(n0) : n0, r1 = PERM ? dh_row(n0 + 16) : n0 + 16;
  const uint32_t a0 = sb + stage + r0 * 128 + ((chunk ^ (r0 & 7)) << 4), a1 = sb + stage + r1 * 128 + ((chunk ^ (r1 & 7)) << 4);
#pragma unroll
  for (int k = 0; k < NKR; k++) ldsm4t(wf[k], ((k & 1) ? a1 : a0) + (k >> 1) * 4096);
#pragma unroll
  for (int k = 0; k < 40 - NKR; k++) {
    const int n = (NKR + k) * 16 + ((tid0 & 127) >> 3), r = PERM ? dh_row(n) : n, c = tid0 & 7;
    sts128(sb + yoff + (n - NKR * 16) * 128 + ((c ^ (n & 7)) << 4), lds128(sb + stage + r * 128 + ((c ^ (r & 7)) << 4)));
  }
  fence_async();
  CBAR_SYNC(NB_PRO, 384);
}
template <int STRIDE>
__device__ __forceinline__ void store_mem(const float (&d)[8], uint32_t base, int tid) {
  const int m = (tid >> 3) & 3;
  stsm4(base + (((tid >> 5) & 3) * 2 + (m & 1)) * STRIDE + (m >> 1) * 640 + (tid & 7) * 16, pack_bf16(d[0], d[1]), pack_bf16(d[2], d[3]),
        pack_bf16(d[4], d[5]), pack_bf16(d[6], d[7]));
}

__device__ __forceinline__ void load_pair(uint32_t sb, int i, int p, uint32_t slot, uint32_t bar, uint32_t ph, int& spin) {
  using namespace C;
  const uint8_t* s0 = g_xn[0] + (size_t)i * 40960 + p * 8192;
  const uint8_t* s1 = g_xn[NOWORK ? 0 : 1] + (size_t)(i - LAG) * 40960 + p * 8192;
  const uint8_t* sa = pinp(i < NSEG ? s0 : s1);
  const uint8_t* sc = pinp(i >= LAG ? s1 : s0);
  const uint32_t dst = pin(sb + slot), fb = pin(sb + BAR_F + 8 * p);
  mwait(bar, ph, spin);
  bulk_g2s_mc(dst, sa, 8192, fb);
  bulk_g2s_mc(dst + 8192, sc, 8192, fb);
}
__device__ __forceinline__ void first_fill(uint32_t sb, int i, int rank, int& spin) {
  using namespace C;
  const int s1 = i - LAG;
  if (!NOWORK && s1 >= 0) { cwait(CN_X + s1, 32, spin); fence_async_all(); }
  load_pair(sb, i, rank, rank == 2 ? OFF_M : OFF_KT + rank * 16384, sb + BAR_E + 8 * rank, (i - 1) & 1, spin);
}
__device__ __forceinline__ void release_round(uint32_t sb, int p, int tid) {
  using namespace C;
  const int lane = tid & 31;
  if (p < 2) { if (lane == 0) mbar_arrive_cluster(mapa(sb, p) + BAR_E + 8 * (3 + p)); }
  else if (lane < 3) mbar_arrive_cluster(mapa(sb, lane) + BAR_MOK);
}

template <int K0, int K1>
__device__ __forceinline__ void v_mem_pass(float (&d)[8], const uint32_t (&wf)[C::NKR][4]) {
  using namespace C;
  wg_fence();
#pragma unroll
  for (int k = K0; k < K1; k++) {
    if (k < NKR) wgmma_rs16(d, wf[k < NKR ? k : 0], mdesc(k), k != 32);
    else wgmma_ts16(d, wdesc(OFF_YV + (k - NKR) * 2048), mdesc(k), 1);
  }
  wg_commit();
}
__device__ __forceinline__ void chain_v(const uint32_t sb, const int tid0, const int cta, const int rank) {
  using namespace C;
  asm volatile("setmaxnreg.inc.sync.aligned.u32 208;");
  int spin = 0;
  uint32_t wf[NKR][4];
  if (tid0 == 256) first_fill(sb, 0, rank, spin);
  __syncwarp();
  mwait(sb + BAR_W, 0, spin);
  for (int it = tid0 & 127; it < 1280; it += 128) {
    const uint32_t base = sb + OFF_WK + (it >> 1) * 128;
    const int sw = ((it >> 1) & 7) ^ ((it & 1) * 4);
    const uint4 u0 = lds128(base + (sw << 4)), u1 = lds128(base + ((sw ^ 1) << 4)), u2 = lds128(base + ((sw ^ 2) << 4)), u3 = lds128(base + ((sw ^ 3) << 4));
    sts128(base + (sw << 4), make_uint4(u0.x, u1.x, u2.x, u3.x)); sts128(base + ((sw ^ 1) << 4), make_uint4(u0.y, u1.y, u2.y, u3.y));
    sts128(base + ((sw ^ 2) << 4), make_uint4(u0.z, u1.z, u2.z, u3.z)); sts128(base + ((sw ^ 3) << 4), make_uint4(u0.w, u1.w, u2.w, u3.w));
  }
  bar_sync(NB_RD, 128);
  load_weights_rs<false>(wf, sb, OFF_WK, OFF_YV, tid0);
#pragma unroll 1
  for (int i = 0; i < NSTEP; i++) {
    {
      float d[32];
      if (i > 0) CBAR_SYNC(NB_WV, 256);
#pragma unroll
      for (int p = 0; p < 5; p++) {
        mwait(sb + BAR_F + 8 * p, i & 1, spin);
        TS(i, 25 + p);
        wg_fence();
#pragma unroll
        for (int k = 8 * p; k < 8 * p + 8; k++) {
          if (k < NKR) wgmma_rs64(d, wf[k < NKR ? k : 0], tdesc(k), k);
          else wgmma_ts64(d, wdesc(OFF_YV + (k - NKR) * 2048), tdesc(k), 1);
          if (k == 8 * p + 1 && p >= 1 && p <= 3) {
            wg_commit(); wg_wait<1>();
            release_round(sb, p - 1, fresh(tid0));
            wg_fence();
          }
          if (k == 8 * p + RFK && (p == 1 || p == 2)) {
            wg_commit();
            if (rank == p - 1 && tid0 == 256) load_pair(sb, i, p + 2, slot_off(p + 2), sb + BAR_E + 8 * (p + 2), i & 1, spin);
            __syncwarp();
            wg_fence();
          }
        }
        wg_commit();
      }
      wg_wait<0>();
      TS(i, 23);
      CBAR_SYNC(NB_RD, 256);
      const int tid = fresh(tid0) & 127, m = (tid >> 3) & 3;
      if (tid >= 96) {
        if (tid < 101) { if (i + 1 < NSTEP) mbar_expect_tx(sb + BAR_F + 8 * (tid - 96), 16384); }
        else if (tid == 101) mbar_expect_tx(sb + BAR_XM, 2560);
        else if (tid == 102) mbar_expect_tx(sb + BAR_XT, 7168);
        else if (tid == 103) mbar_expect_tx(sb + BAR_OG, 4096);
        else if (tid < 106) mbar_arrive_cluster(mapa(sb, (rank + tid - 103) % 3) + BAR_XF);
        __syncwarp();
      }
      const uint32_t a = sb + OFF_VT + 256 + ((tid >> 5) * 2 + (m & 1)) * VS + (m >> 1) * 128 + (tid & 7) * 16;
#pragma unroll
      for (int s = 0; s < 4; s++)
        stsm4(a + (s & 1) * 256 + (s >> 1) * 640, pack_bf16(d[8 * s], d[8 * s + 1]), pack_bf16(d[8 * s + 2], d[8 * s + 3]),
              pack_bf16(d[8 * s + 4], d[8 * s + 5]), pack_bf16(d[8 * s + 6], d[8 * s + 7]));
      if (tid < 72) sts128(sb + OFF_VT + (tid >> 3) * VS + (tid & 7) * 16, make_uint4(0, 0, 0, 0));
      fence_async();
    }
    mwait(sb + BAR_XF, i & 1, spin);
    CBAR_ARRIVE(NB_QK, 384);
    CBAR_SYNC(NB_QI, 256);
    float d[8];
    v_mem_pass<32, 40>(d, wf);
    CBAR_SYNC(NB_SM, 256);
    wg_wait<0>();
    if (__builtin_expect(lds32(sb + FLG_REDO), 0)) { v_mem_pass<32, 40>(d, wf); wg_wait<0>(); }
    if ((tid0 & 31) < 2) mbar_arrive_cluster(mapa(sb, (rank + 1 + (tid0 & 1)) % 3) + BAR_MF);
    v_mem_pass<0, 32>(d, wf);
    wg_wait<0>();
    TS(i, 24);
    const int tid = fresh(tid0);
    if ((tid & 31) == 0) mbar_arrive_cluster(mapa(sb, 2) + BAR_E + 16);
    store_mem<VS>(d, sb + OFF_VT + 128, tid);
    fence_async();
    CBAR_ARRIVE(NB_VA, 256);
    CBAR_ARRIVE(NB_VQ, 256);
    if (tid == 256) {
      if (i + 1 < NSTEP) { first_fill(sb, i + 1, rank, spin); TS1(i + 1, 37); }
    } else if (tid >= 288 && tid < 295) {
      const int lane = tid & 31, ip = i + PFD;
      if (cta < 80 && ip < NSTEP) {
        if (lane < 2) prefetch_l2(g_mbuf[ip] + (cta * 2 + lane) * 128);
        else if (lane == 6) { if (cta < 22) prefetch_l2(&g_flag[ip][cta * 32]); }
        else if (ip < NSEG) prefetch_l2(g_xn[0] + (size_t)ip * 40960 + (cta * 4 + lane - 2) * 128);
      }
    }
    TS_FLUSH(i - 1);
    __syncwarp();
  }
  if (spin >= SPIN_TOT) g_err = 3;
}

__device__ __forceinline__ float quad_max(float x) {
  const float a = __shfl_xor_sync(0xffffffffu, x, 1), b = __shfl_xor_sync(0xffffffffu, x, 2), c = __shfl_xor_sync(0xffffffffu, x, 3);
  return fmaxf(fmaxf(x, a), fmaxf(b, c));
}
__device__ __forceinline__ float quad_sum(float x) {
  const float a = __shfl_xor_sync(0xffffffffu, x, 1), b = __shfl_xor_sync(0xffffffffu, x, 2), c = __shfl_xor_sync(0xffffffffu, x, 3);
  return (x + a) + (b + c);
}
__device__ __forceinline__ float max10(const float (&y)[10]) {
  return fmaxf(fmaxf(fmaxf(fmaxf(y[0], y[1]), fmaxf(y[2], y[3])), fmaxf(fmaxf(y[4], y[5]), fmaxf(y[6], y[7]))), fmaxf(y[8], y[9]));
}
__device__ __forceinline__ float sum10(const float (&y)[10]) {
  return (((y[0] + y[1]) + (y[2] + y[3])) + ((y[4] + y[5]) + (y[6] + y[7]))) + (y[8] + y[9]);
}
__device__ __forceinline__ float rcp(float x) { float y; asm("rcp.approx.ftz.f32 %0,%1;" : "=f"(y) : "f"(x)); return y; }

__device__ __forceinline__ void signal_o(int i, int cta) { csignal(CN_O + i * 5 + min(cta / 19, 4)); }

__device__ __forceinline__ void chain_q(const CUtensorMap& tmWq, const CUtensorMap& tmWk, const uint32_t sb, const int tid0, const int cta, const int rank) {
  using namespace C;
  asm volatile("setmaxnreg.dec.sync.aligned.u32 96;");
  int spin = 0;
  CBAR_SYNC(NB_PRO, 384);
  PTS(5);
  if (tid0 == 128) {
    const int col = (cta / 3) * DH + rank * 64;
    mbar_expect_tx(sb + BAR_W, 163840);
    for (int i = 0; i < 5; i++) {
      tma2d(sb + OFF_WQ + i * 16384, &tmWq, col, i * 128, sb + BAR_W);
      tma2d(sb + OFF_WK + i * 16384, &tmWk, col, i * 128, sb + BAR_W);
    }
  }
  __syncwarp();
  mwait(sb + BAR_W, 1, spin);
  PTS(6);
#pragma unroll 1
  for (int i = 0; i < NSTEP; i++) {
    const int ph = i & 1;
    uint32_t qf[4][4];
    {
      float d[64];
#pragma unroll
      for (int p = 0; p < 5; p++) {
        mwait(sb + BAR_F + 8 * p, ph, spin);
        if (p == 0) TS(i, 0);
        wg_fence();
#pragma unroll
        for (int k = 8 * p; k < 8 * p + 8; k++) {
          wgmma_st128(d, tdesc(k), mkdesc(SB0 + OFF_WQ + k * 2048, OFF_WK - OFF_WQ, 1024), k);
          if (k == 8 * p + 1 && p >= 1 && p <= 3) {
            wg_commit(); wg_wait<1>();
            release_round(sb, p - 1, fresh(tid0));
            wg_fence();
          }
        }
        wg_commit();
      }
      wg_wait<0>();
      TS(i, 1);
      CBAR_SYNC(NB_RD, 256);
      TSB(i, 2);
      const int tid = fresh(tid0), w = (tid >> 5) & 3, m = (tid >> 3) & 3;
      const uint32_t a = sb + OFF_KT + (m >> 1) * KS + (1 + 5 * (w >> 1) + 2 * (w & 1) + (m & 1)) * 128 + (tid & 7) * 16;
#pragma unroll
      for (int s = 0; s < 4; s++)
        stsm4t(a + s * 2 * KS, pack_bf16(d[32 + 8 * s], d[33 + 8 * s]), pack_bf16(d[34 + 8 * s], d[35 + 8 * s]),
               pack_bf16(d[36 + 8 * s], d[37 + 8 * s]), pack_bf16(d[38 + 8 * s], d[39 + 8 * s]));
      fence_async();
      CBAR_ARRIVE(NB_QK, 384);
      if (OSG == 0) { if (tid == 224 && i > 0) signal_o(i - 1, cta); __syncwarp(); }
#pragma unroll
      for (int kk = 0; kk < 4; kk++)
#pragma unroll
        for (int j = 0; j < 4; j++) asm volatile("cvt.rn.bf16x2.f32 %0,%1,%2;" : "=r"(qf[kk][j]) : "f"(d[8 * kk + 2 * j + 1]), "f"(d[8 * kk + 2 * j]));
    }
    CBAR_SYNC(NB_SI, 256);
    uint32_t pf[5][4];
    float s0, s1;
    {
      float y0[10], y1[10];
      const int tid = fresh(tid0), lane = tid & 31, u = (tid >> 5) & 1;
      const bool c1 = tid & 64;
      {
        float x[40];
        wg_fence();
#pragma unroll
        for (int kk = 0; kk < 4; kk++) wgmma_rt80(x, qf[kk], mkdesc_ns(SB0 + OFF_KT + kk * 2 * KS, KS, 128), kk);
        wg_commit();
        wg_wait<0>();
#pragma unroll
        for (int j = 0; j < 5; j++) {
          y0[2 * j] = (c1 ? x[20 + 4 * j] : x[4 * j]) * SCL; y0[2 * j + 1] = (c1 ? x[21 + 4 * j] : x[4 * j + 1]) * SCL;
          y1[2 * j] = (c1 ? x[22 + 4 * j] : x[4 * j + 2]) * SCL; y1[2 * j + 1] = (c1 ? x[23 + 4 * j] : x[4 * j + 3]) * SCL;
        }
      }
      TS(i, 17);
      const uint32_t xo = OFF_XT + (c1 ? 1792 : 0) + u * 640 + lane * 16, x2 = xo + u * 512 + 512 - lane * 12;
      {
        const uint4 h0 = make_uint4(pack_h2(y0[0], y0[1]), pack_h2(y0[2], y0[3]), pack_h2(y1[0], y1[1]), pack_h2(y1[2], y1[3]));
        const uint4 h1 = make_uint4(pack_h2(y0[4], y0[5]), pack_h2(y0[6], y0[7]), pack_h2(y1[4], y1[5]), pack_h2(y1[6], y1[7]));
        const uint32_t h2 = u ? pack_h2(y1[8], y1[9]) : h1.z;
#pragma unroll
        for (int dd = 0; dd < 2; dd++) {
          const uint32_t rb = mapa(sb, (rank + 1 + dd) % 3), ro = rb + (1 - dd) * 3584;
          st_async4u(ro + xo, h0, rb + BAR_XT);
          if (u) st_async4u(ro + xo + 512, h1, rb + BAR_XT);
          st_async1u(ro + x2, h2, rb + BAR_XT);
        }
      }
      TS(i, 18);
      const int lim = 16 * u + (lane >> 2) + 8 - 2 * (lane & 3);
#pragma unroll
      for (int j = 1; j < 5; j++) {
        if (8 * j > lim) y0[2 * j] = -INFINITY;
        if (8 * j + 1 > lim) y0[2 * j + 1] = -INFINITY;
        if (8 * j - 8 > lim) y1[2 * j] = -INFINITY;
        if (8 * j - 7 > lim) y1[2 * j + 1] = -INFINITY;
      }
      mwait(sb + BAR_XT, ph, spin);
      TS(i, 19);
      {
        const uint4 u0 = lds128(sb + xo), v0 = lds128(sb + xo + 3584);
        const uint32_t u2 = lds32(sb + x2), v2 = lds32(sb + x2 + 3584);
        uint4 u1 = make_uint4(0, 0, u2, 0), v1 = make_uint4(0, 0, v2, 0);
        if (u) { u1 = lds128(sb + xo + 512); v1 = lds128(sb + xo + 512 + 3584); }
        __syncwarp();
        if (lane == 0) mbar_arrive_cluster(mapa(sb, 0) + BAR_E);
        add_h2(y0[0], y0[1], u0.x, v0.x); add_h2(y0[2], y0[3], u0.y, v0.y); add_h2(y1[0], y1[1], u0.z, v0.z); add_h2(y1[2], y1[3], u0.w, v0.w);
        add_h2(y0[4], y0[5], u1.x, v1.x); add_h2(y0[6], y0[7], u1.y, v1.y); add_h2(y1[4], y1[5], u1.z, v1.z); add_h2(y1[6], y1[7], u1.w, v1.w);
        add_h2(y1[8], y1[9], u2, v2);
      }
      y0[8] = y0[0]; y0[9] = y0[1];
      const float m0 = quad_max(max10(y0)) * -256.f, m1 = quad_max(max10(y1)) * -256.f;
      s0 = 0.f; s1 = 0.f;
#pragma unroll
      for (int j = 0; j < 5; j++) {
        const uint32_t p0 = j < 4 ? pack_bf16(ex2(fmaf(y0[2 * j], 256.f, m0)), ex2(fmaf(y0[2 * j + 1], 256.f, m0))) : 0u;
        const uint32_t p1 = pack_bf16(ex2(fmaf(y1[2 * j], 256.f, m1)), ex2(fmaf(y1[2 * j + 1], 256.f, m1)));
        s0 += bf_lo(p0) + bf_hi(p0); s1 += bf_lo(p1) + bf_hi(p1);
        pf[j >> 1][2 * (j & 1)] = c1 ? 0u : p0; pf[j >> 1][2 * (j & 1) + 1] = c1 ? 0u : p1;
        pf[(j + 5) >> 1][2 * ((j + 5) & 1)] = c1 ? p0 : 0u; pf[(j + 5) >> 1][2 * ((j + 5) & 1) + 1] = c1 ? p1 : 0u;
      }
    }
    CBAR_SYNC(NB_VQ, 256);
    TSB(i, 20);
    {
      float o[32];
      wg_fence();
#pragma unroll
      for (int q = 0; q < 5; q++) wgmma_rs64(o, pf[q], mkdesc_ns(SB0 + OFF_VT + 128 + q * 256, 128, VS), q);
      wg_commit();
      s0 = rcp(quad_sum(s0)); s1 = rcp(quad_sum(s1));
      const int tid = fresh(tid0), g = (tid >> 2) & 7, c = (tid >> 6) & 1, sg = i - c * LAG;
      uint8_t* op = pinp(&g_o[i % ORING][c][cta][(((tid >> 5) & 1) * 16 + g) * 128]);
      const uint32_t o0 = pin(((tid & 3) ^ g) << 4), live = pin(sg >= 0 && sg < NSEG);
      wg_wait<0>();
      TS(i, 21);
      if ((tid & 31) == 0) mbar_arrive_cluster(mapa(sb, 1) + BAR_E + 8);
      uint4 ov[4];
#pragma unroll
      for (int h = 0; h < 2; h++) {
        const float* x = o + 16 * h;
        ov[2 * h] = make_uint4(pin(pack_bf16(x[0] * s0, x[1] * s0)), pin(pack_bf16(x[4] * s0, x[5] * s0)), pin(pack_bf16(x[8] * s0, x[9] * s0)), pin(pack_bf16(x[12] * s0, x[13] * s0)));
        ov[2 * h + 1] = make_uint4(pin(pack_bf16(x[2] * s1, x[3] * s1)), pin(pack_bf16(x[6] * s1, x[7] * s1)), pin(pack_bf16(x[10] * s1, x[11] * s1)), pin(pack_bf16(x[14] * s1, x[15] * s1)));
      }
      TS(i, 22);
      if (i + 1 < NSTEP) CBAR_SYNC(NB_WQ, 256);
      if (live) {
#pragma unroll
        for (int h = 0; h < 4; h++) *reinterpret_cast<uint4*>(op + (h & 1) * 1024 + (o0 ^ ((h >> 1) * 64))) = ov[h];
      }
      if (OSG && i + 1 < NSTEP) CBAR_ARRIVE(NB_MR, 160);
    }
  }
  CBAR_SYNC(NB_Q, 128);
  if (tid0 == 224) signal_o(NSTEP - 1, cta);
  if (spin >= SPIN_TOT) g_err = 2;
}

template <int NL>
__device__ __forceinline__ void poll_add(const uint8_t* mb, uint32_t tag, float (&f)[8], uint32_t* flag, int osig, int& n, int& spin) {
  uint4 x[NL];
#pragma unroll
  for (int i = 0; i < NL; i++) x[i] = ld_relaxed128(mb + i * 512);
  if (OSG == 1 && osig >= 0) csignal(osig);
  while (true) {
    bool bad = false;
#pragma unroll
    for (int i = 0; i < NL; i++)
      if (((x[i].x ^ tag) | (NL == 6 ? x[i].z ^ tag : 0u)) & 1) { bad = true; x[i] = ld_relaxed128(mb + i * 512); }
    n++;
    spin += 16;
    if (!__any_sync(0xffffffffu, bad && spin < SPIN_TOT)) break;
  }
  if (FLP == 0 && flag) st_relaxed(flag, 0);
#pragma unroll
  for (int i = 0; i < NL; i++) {
    const uint32_t u[4] = {x[i].x, x[i].y, x[i].z, x[i].w};
#pragma unroll
    for (int j = 0; j < 4; j++) {
      if (i == 0) { f[2 * j] = bf_lo(u[j]); f[2 * j + 1] = bf_hi(u[j]); }
      else { f[2 * j] += bf_lo(u[j]); f[2 * j + 1] += bf_hi(u[j]); }
    }
  }
}

template <int B, int SLOT>
__device__ __forceinline__ void wo_block(float (&acc)[8], const uint32_t (&wf)[C::NKR][4]) {
  using namespace C;
#pragma unroll
  for (int kk = 0; kk < 4; kk++) {
    const int k = 4 * B + kk;
    const uint64_t db = mkdesc_ns(SB0 + og_off(SLOT) + kk * 512, 256, 128);
    if (k < NKR) wgmma_rt16(acc, wf[k < NKR ? k : 0], db, SLOT | kk);
    else wgmma_tt16(acc, wdesc(OFF_YO + (k - NKR) * 2048), db, 1);
  }
}

__device__ __forceinline__ void chain_a(const uint32_t sb, const int tid0, const int cta, const int rank) {
  using namespace C;
  asm volatile("setmaxnreg.inc.sync.aligned.u32 200;");
  int spin = 0;
  uint32_t wf[NKR][4];
  mwait(sb + BAR_W, 0, spin);
  permute_cols(sb + OFF_WQ, tid0);
  CBAR_SYNC(NB_A, 128);
  load_weights_rs<true>(wf, sb, OFF_WQ, OFF_YO, tid0);

#pragma unroll 1
  for (int i = -1; i < NSTEP; i++) {
    const int ph = i & 1;
    if (i >= 0) {
      if (i == 0) mwait(sb + BAR_W, 1, spin);
      mwait(sb + BAR_M, ph, spin);
      TS(i, 3);
      {
        float x[20];
        int redo = 0;
      retry:
        bool bad;
        {
          float dq[8], dk[8];
          wg_fence();
#pragma unroll
          for (int k = 0; k < 40; k++) wgmma_ts16(dq, wdesc(OFF_WQ + k * 2048), mdesc(k), k);
          wg_commit();
#pragma unroll
          for (int k = 0; k < 40; k++) {
            if (k == 40 - QIE && !redo) CBAR_ARRIVE(NB_QI, 256);
            wgmma_ts16(dk, wdesc(OFF_WK + k * 2048), mdesc(k), k);
          }
          wg_commit();
          const int m = (tid0 >> 3) & 3, dg = (tid0 >> 5) * 2 + (m & 1);
          const uint32_t ka = sb + OFF_KT + dg * KS + (m >> 1) * 640 + (tid0 & 7) * 16;
          wg_wait<1>();
          const float chk = (dq[0] + dq[1]) + (dq[4] + dq[5]);
          const uint32_t q0 = pack_bf16(dq[0], dq[1]), q1 = pack_bf16(dq[2], dq[3]), q2 = pack_bf16(dq[4], dq[5]), q3 = pack_bf16(dq[6], dq[7]);
          if (!redo) CBAR_SYNC(NB_QK, 384);
          stsm4(ka + dg * (VS - KS) + (OFF_VT + 128 - OFF_KT), q0, q1, q2, q3);
          sts32(sb + FLG_REDO, redo);
          wg_wait<0>();
          TS(i, 4);
          stsm4(ka, pack_bf16(dk[0], dk[1]), pack_bf16(dk[2], dk[3]), pack_bf16(dk[4], dk[5]), pack_bf16(dk[6], dk[7]));
          fence_async();
          bad = bar_red_or(NB_C, 128, chk != chk && !redo);
        }
        TSB(i, 5);
        wg_fence();
#pragma unroll
        for (int kk = 0; kk < 4; kk++) wgmma_tt40(x, mkdesc_ns(SB0 + OFF_VT + 128 + kk * 2 * VS, VS, 640), mkdesc_ns(SB0 + OFF_KT + kk * 2 * KS, KS, 128), kk);
#pragma unroll
        for (int kk = 0; kk < 4; kk++) {
          if (kk == 4 - SIE && !bad) CBAR_ARRIVE(NB_SI, 256);
          wgmma_tt40(x, mkdesc_ns(SB0 + OFF_VT + kk * 2 * VS, VS, 384), mkdesc_ns(SB0 + OFF_KT + 640 + kk * 2 * KS, KS, 128), 1);
        }
        wg_commit();
        if (__builtin_expect(bad, 0)) {
          wg_wait<0>();
#pragma unroll 1
          for (int k = 0; k < 10; k++) {
            uint4 v = lds128(sb + OFF_M + tid0 * 16 + k * 2048);
            if (v.x == SENT || v.y == SENT || v.z == SENT || v.w == SENT) {
              do { v = ld_relaxed4(g_mbuf[i] + tid0 * 16 + k * 2048); spin += 16; } while ((v.x == SENT || v.y == SENT || v.z == SENT || v.w == SENT) && spin < SPIN_TOT);
              sts128(sb + OFF_M + tid0 * 16 + k * 2048, v);
            }
          }
          fence_async();
          bar_sync(NB_C, 128);
          redo = fresh(1);
          goto retry;
        }
        TSV(i, 36, redo);
        const int tid = fresh(tid0), lane = tid & 31, w = tid >> 5;
        const uint32_t xo = OFF_XM + w * 1280 + lane * 16, x1 = OFF_XM + w * 1280 + lane * 4;
        const uint32_t rb1 = mapa(sb, (rank + 1) % 3), rb2 = mapa(sb, (rank + 2) % 3);
        const uint32_t ra = pin(rb1 + xo + 640), rb = pin(rb1 + x1 + 1152), rc = pin(rb2 + xo), rd = pin(rb2 + x1 + 512);
        const uint32_t la = pin(sb + xo), lb = pin(sb + x1);
        const uint32_t pa = pin(sb + OFF_XM + w * 1280 + (lane & 7) * 4 + (lane & 8) * 8 + (lane & 16) * 2);
        wg_wait<0>();
        TS(i, 6);
        if (w < 2) {
          float y[10];
#pragma unroll
          for (int j = 0; j < 5; j++) { y[2 * j] = x[4 * j] * SCL; y[2 * j + 1] = x[4 * j + 1] * SCL; }
          const uint4 h0 = make_uint4(pack_h2(y[0], y[1]), pack_h2(y[2], y[3]), pack_h2(y[4], y[5]), pack_h2(y[6], y[7]));
          const uint32_t h1 = pack_h2(y[8], y[9]);
          st_async4u(ra, h0, rb1 + BAR_XM);
          st_async4u(rc, h0, rb2 + BAR_XM);
          st_async1u(rb, h1, rb1 + BAR_XM);
          st_async1u(rd, h1, rb2 + BAR_XM);
          CBAR_ARRIVE(NB_SM, 256);
          if (lane == 0) mbar_arrive_cluster(mapa(sb, 0) + BAR_E);
          TS(i, 7);
          mwait(sb + BAR_XM, ph, spin);
          TS(i, 8);
          const uint4 u0 = lds128(la), v0 = lds128(la + 640);
          const uint32_t u1 = lds32(lb + 512), v1 = lds32(lb + 1152);
          add_h2(y[0], y[1], u0.x, v0.x); add_h2(y[2], y[3], u0.y, v0.y); add_h2(y[4], y[5], u0.z, v0.z); add_h2(y[6], y[7], u0.w, v0.w);
          add_h2(y[8], y[9], u1, v1);
          const float mx = quad_max(max10(y)) * -256.f;
          sts32(pa + 640, 0);
#pragma unroll
          for (int j = 0; j < 5; j++) {
            y[2 * j] = ex2(fmaf(y[2 * j], 256.f, mx)); y[2 * j + 1] = ex2(fmaf(y[2 * j + 1], 256.f, mx));
            sts32(pa + j * 128, pack_bf16(y[2 * j], y[2 * j + 1]));
          }
          sts32(pa + 768, __float_as_uint(sum10(y)));
          fence_async();
          TS(i, 9);
        } else {
          CBAR_ARRIVE(NB_SM, 256);
          if (lane == 0) mbar_arrive_cluster(mapa(sb, 0) + BAR_E);
          mwait(sb + BAR_MF, ph, spin);
        }
      }
      CBAR_SYNC(NB_VA, 256);
      TSB(i, 10);
      {
        float o[2][4];
        wg_fence();
#pragma unroll
        for (int c = 0; c < 2; c++)
#pragma unroll
          for (int q = 0; q < 3; q++)
            wgmma_ss8(o[c], mkdesc_ns(SB0 + OFF_VT + 128 + c * 640 + q * 256, 128, VS), mkdesc_ns(SB0 + OFF_XM + c * 1280 + q * 256, 128, 128), q);
        wg_commit();
        const int tid = fresh(tid0);
        const float4 e = lds128f(sb + OFF_XM + 768 + (tid & 3) * 32 + (tid & 4) * 4 + (tid & 8) * 160);
        const uint32_t oo = (tid >> 5) * 512 + (tid & 2) * 64 + ((tid & 31) >> 2) * 16 + (tid & 1) * 8;
        const uint32_t rb1 = mapa(sb, (rank + 1) % 3), rb2 = mapa(sb, (rank + 2) % 3);
        const uint32_t ra = pin(rb1 + oo + og_off(2)), rc = pin(rb2 + oo + og_off(1)), la = pin(sb + oo + og_off(0));
        const float inv = rcp((e.x + e.y) + (e.z + e.w));
        const float i0 = __shfl_sync(0xffffffffu, inv, tid & 3), i1 = __shfl_sync(0xffffffffu, inv, (tid & 3) + 4);
        const float i2 = __shfl_sync(0xffffffffu, inv, (tid & 3) + 8), i3 = __shfl_sync(0xffffffffu, inv, (tid & 3) + 12);
        wg_wait<0>();
        TS(i, 11);
        const uint32_t p0 = pack_bf16(o[0][0] * i0, o[0][1] * i1), p1 = pack_bf16(o[1][0] * i2, o[1][1] * i3);
        const uint32_t p2 = pack_bf16(o[0][2] * i0, o[0][3] * i1), p3 = pack_bf16(o[1][2] * i2, o[1][3] * i3);
        if (OGF) { sts64(la, p0, p1); sts64(la + 256, p2, p3); fence_async(); }
        st_async2u(ra, p0, p1, rb1 + BAR_OG);
        st_async2u(rc, p0, p1, rb2 + BAR_OG);
        st_async2u(ra + 256, p2, p3, rb1 + BAR_OG);
        st_async2u(rc + 256, p2, p3, rb2 + BAR_OG);
        if (!OGF) { sts64(la, p0, p1); sts64(la + 256, p2, p3); fence_async(); }
      }
      if (i + 1 >= NSTEP) { mwait(sb + BAR_OG, ph, spin); break; }
      CBAR_SYNC(NB_A, 128);
      TSB(i, 12);
      {
        float acc[3][8];
        wg_fence();
        wo_block<0, 0>(acc[2], wf);
        wg_commit();
        wo_block<1, 0>(acc[0], wf);
        wo_block<4, 0>(acc[1], wf);
        wg_commit();
        const int tid = fresh(tid0), w = tid >> 5, g = (tid & 31) >> 2, t = tid & 3;
        if ((tid & 31) == 0) mbar_arrive_cluster(mapa(sb, 1) + BAR_E + 8);
        const uint32_t tag = (i >> 1) & 1, radd = tag ? 0u : 0x10000u;
#define TAGGED(LO, HI) __byte_perm(((__float_as_uint(LO) + radd) & 0xFFFE0000u) | (tag << 16), pack_bf16(0.f, HI), 0x7632)
#define SEND(PTR, U) st_relaxed128((PTR), TAGGED(acc[U][0], acc[U][2]), pack_bf16(acc[U][1], acc[U][3]), pack_bf16(acc[U][4], acc[U][6]), pack_bf16(acc[U][5], acc[U][7]))
        uint8_t* m9 = pinp(g_mail[ph] + MAIL9 + (((2 * w + (g >> 2)) * 2 + (t & 1)) * 4 + (t & 2)) * 3072 + cta * 32 + (g & 3) * 8);
        wg_wait<1>();
        const uint32_t n0 = pin(TAGGED(acc[2][0], acc[2][2])), n1 = pin(pack_bf16(acc[2][1], acc[2][3]));
        const uint32_t n2 = pin(TAGGED(acc[2][4], acc[2][6])), n3 = pin(pack_bf16(acc[2][5], acc[2][7]));
        wg_fence();
        wo_block<7, 0>(acc[2], wf);
        wg_commit();
        st_relaxed64(m9, n0, n1);
        st_relaxed64(m9 + 3072, n2, n3);
        uint8_t* mb = pinp(g_mail[ph] + (((rank * 12 + w) * 2 + (g >> 2)) * 4 + t) * 2048 + (cta / 3) * 64 + (g & 3) * 16);
        mwait(sb + BAR_OG, ph, spin);
        asm volatile("fence.proxy.async::generic.acquire.sync_restrict::shared::cluster.cluster;" ::: "memory");
        TS(i, 13);
        wg_fence();
        wo_block<2, 1>(acc[0], wf); wo_block<3, 2>(acc[0], wf);
        wg_commit();
        wo_block<5, 1>(acc[1], wf); wo_block<6, 2>(acc[1], wf);
        wg_commit();
        wg_wait<1>(); SEND(mb, 0);
        wg_fence();
        wo_block<8, 1>(acc[2], wf); wo_block<9, 2>(acc[2], wf);
        wg_commit();
        if (WOE == 0) { CBAR_ARRIVE(NB_WV, 256); CBAR_ARRIVE(NB_WQ, 256); }
        wg_wait<1>(); SEND(mb + 32 * 2048, 1);
        if (WOE == 1) CBAR_ARRIVE(NB_WV, 256);
        wg_wait<0>(); SEND(mb + 64 * 2048, 2);
        if (WOE == 2) CBAR_ARRIVE(NB_WV, 256);
        if (WOE >= 1) CBAR_ARRIVE(NB_WQ, 256);
#undef SEND
#undef TAGGED
      }
      TS(i, 14);
    }
    const uint32_t t0 = clk32();
    uint32_t t1 = t0;
    if (i >= 0) {
      const int tid = fresh(tid0), lane = tid & 31;
      const uint32_t tag = (i >> 1) & 1;
      const bool t9 = cta >= 72 && cta < 88;
      const int w = tid >> 5, j = lane >> 3;
      const uint32_t pub = pin((lane & (t9 ? 6 : 4)) == 0 && !(((t9 ? cta : w) & 1) && i + 1 == LAG) && cta < 88);
      uint8_t* dst = pinp(g_mbuf[i + 1] + (t9 ? (cta + 72) * 128 + w * 32 + (j & 1) * 16 + (lane & 1) * 8 + (j >> 1) * 4
                                               : cta * 256 + (w & 1) * 128 + (w >> 1) * 64 + j * 16 + (lane & 3) * 4));
      uint32_t* flag = pinp(lane == 0 && cta < 88 ? &g_flag[i + 1][cta * 8 + w] : nullptr);
      float f[8];
      int n = 0;
      if (OSG && w == 3) CBAR_SYNC(NB_MR, 160);
      const int osig = tid == 96 ? CN_O + i * 5 + min(cta / 19, 4) : -1;
      while (clk32() - t0 < B1) {}
      TS(i + 1, 30);
      if (!t9) poll_add<4>(g_mail[ph] + (cta < 72 ? cta : cta - 24) * 8192 + (tid >> 5) * 2048 + lane * 16, tag, f, flag, osig, n, spin);
      else poll_add<6>(g_mail[ph] + MAIL9 + (cta - 72) * 12288 + (tid >> 5) * 3072 + lane * 16, tag, f, flag, osig, n, spin);
      if (FLP == 1 && flag) st_relaxed(flag, __float_as_uint(f[0] + f[7]) >> 1);
      t1 = clk32();
      TS(i + 1, 31); TSV(i + 1, 32, n);
      const bool h = lane & 16, q = lane & 8;
#pragma unroll
      for (int j = 0; j < 4; j++) f[j] = (h ? f[4 + j] : f[j]) + __shfl_xor_sync(0xffffffffu, h ? f[j] : f[4 + j], 16);
#pragma unroll
      for (int j = 0; j < 2; j++) f[j] = (q ? f[2 + j] : f[j]) + __shfl_xor_sync(0xffffffffu, q ? f[j] : f[2 + j], 8);
      f[0] += __shfl_xor_sync(0xffffffffu, f[0], 4); f[1] += __shfl_xor_sync(0xffffffffu, f[1], 4);
      if (t9) { f[0] += __shfl_xor_sync(0xffffffffu, f[0], 2); f[1] += __shfl_xor_sync(0xffffffffu, f[1], 2); }
      if (pub) st_relaxed(dst, pack_bf16(f[0], f[1]));
      if (FLP == 2 && flag) st_relaxed(flag, 0);
      if (OSG == 2 && osig >= 0) csignal(osig);
      TS(i + 1, 15);
    }
    if (tid0 < 32) {
      const uint8_t* src = pinp(g_mbuf[i + 1] + rank * 7168);
      const uint32_t* pp = pinp(&g_flag[i + 1][(rank * 28 + (tid0 < 28 || rank == 2 ? tid0 : 0)) * 8]);
      const uint32_t dst = pin(sb + OFF_M + rank * 7168), len = pin(rank == 2 ? 6144 : 7168);
      if (tid0 == 0) mbar_expect_tx(sb + BAR_M, 20480);
      while (clk32() - t1 < B2) {}
      TS(i + 1, 16);
      int n = 0;
      uint4 x;
      do { x = ld_relaxed4(pp); n++; spin += 16; } while (__any_sync(0xffffffffu, (int)(x.x | x.y | x.z | x.w) < 0 && spin < SPIN_TOT));
      TSV(i + 1, 35, n);
      TS(i + 1, 34);
      mwait(sb + BAR_MOK, ph ^ 1, spin);
      if (tid0 == 0) bulk_g2s_mc(dst, src, len, sb + BAR_M);
      TS(i + 1, 33);
      __syncwarp();
    }
  }
  if (spin >= SPIN_TOT) g_err = 1;
}

__global__ void __cluster_dims__(3, 1, 1) __launch_bounds__(384, 1)
k_chain(const __grid_constant__ CUtensorMap tmWq, const __grid_constant__ CUtensorMap tmWk,
        const __grid_constant__ CUtensorMap tmWv, const __grid_constant__ CUtensorMap tmWo) {
  using namespace C;
  extern __shared__ __align__(1024) uint8_t smem[];
  const uint32_t sb = smem_u32(smem);
  const int tid = threadIdx.x;
  const int wg = __shfl_sync(0xffffffffu, tid >> 7, 0);
  const int cta = blockIdx.x, rank = cta % 3;

  asm volatile("griddepcontrol.launch_dependents;");
  if (tid == 0) {
    if ((sb & 0xFFFFFF) != SB0) g_err = 100;
    for (int p = 0; p < 5; p++) { mbar_init(sb + BAR_F + 8 * p, 1); mbar_init(sb + BAR_E + 8 * p, p == 2 ? 12 : 24); }
    mbar_init(sb + BAR_M, 1); mbar_init(sb + BAR_MOK, 24); mbar_init(sb + BAR_XM, 1); mbar_init(sb + BAR_XF, 2);
    mbar_init(sb + BAR_XT, 1); mbar_init(sb + BAR_MF, 8); mbar_init(sb + BAR_OG, 1); mbar_init(sb + BAR_W, 1);
    for (int p = 0; p < 5; p++) mbar_expect_tx(sb + BAR_F + 8 * p, 16384);
    for (int p = 0; p < 16; p++) sts32(sb + OFF_SAFE + 4 * p, 0);
    asm volatile("fence.mbarrier_init.release.cluster;" ::: "memory");
    fence_async();
    mbar_expect_tx(sb + BAR_W, 163840);
    const int head = cta / 3, col = head * DH + rank * 64;
    tma2d(sb + OFF_WQ, &tmWo, 576, col, sb + BAR_W);
    for (int i = 0; i < 9; i++) tma2d(sb + OFF_WQ + (i + 1) * 8192, &tmWo, (3 * rank + i / 3) * 64, head * DH + ((rank + i) % 3) * 64, sb + BAR_W);
    for (int i = 0; i < 5; i++) tma2d(sb + OFF_WK + i * 16384, &tmWv, col, i * 128, sb + BAR_W);
  }
  __syncthreads();
  asm volatile("barrier.cluster.arrive.release.aligned;" ::: "memory");
  asm volatile("barrier.cluster.wait.acquire.aligned;" ::: "memory");

  if (wg == 0) chain_a(sb, keep(tid), cta, rank);
  else if (wg == 1) chain_q(tmWq, tmWk, sb, keep(tid), cta, rank);
  else chain_v(sb, keep(tid), cta, rank);
  asm volatile("barrier.cluster.arrive.release.aligned;" ::: "memory");
  asm volatile("barrier.cluster.wait.acquire.aligned;" ::: "memory");
}

namespace W {
constexpr int NP = 25, NBC = 11, NW = NP + NBC;
constexpr int OFF_W = 0;
constexpr int OFF_R = 163840;
constexpr int KVP = 248, KVR = 46, QP = 120;
constexpr int OFF_KV = OFF_R + 40960;
constexpr int OFF_Q = OFF_KV + 2 * KVR * KVP;
constexpr int OFF_BAR = OFF_Q + 32 * QP;
constexpr int OFF_SAFE = OFF_BAR + 192;
constexpr int SMEM = 232448;
constexpr uint32_t SB0 = 1024;
constexpr int BAR_F = OFF_BAR, BAR_E = OFF_BAR + 40, BAR_W = OFF_BAR + 80, JOB = OFF_BAR + 96, BAR_J = OFF_BAR + 104, BAR_G = OFF_BAR + 112;
constexpr int NB_G0 = 1, NB_SG = 3, NB_SF = 4, NB_ST = 5;
}
#define WBAR_SYNC(id, n) bar_sync(id, n)
#define WBAR_ARRIVE(id, n) bar_arrive(id, n)

__device__ __forceinline__ uint64_t rdesc(int st, int k) { return mkdesc(W::SB0 + W::OFF_R + st * 8192 + (k >> 2) * 4096 + (k & 3) * 32, 16, 1024); }
__device__ __forceinline__ void load_frags40(uint32_t (&wf)[40][4], uint32_t base, int tid) {
  const int i = (tid >> 3) & 3, r = tid & 7;
  const uint32_t a0 = base + (r + (i >> 1) * 8) * 128 + (((2 * ((tid >> 5) & 3) + (i & 1)) ^ r) << 4);
#pragma unroll
  for (int k = 0; k < 40; k++) ldsm4t(wf[k], a0 + k * 2048);
}
__device__ __forceinline__ void red_tile(const float (&d)[16], int seg, int col0, int tid) {
  float* p = g_x + (size_t)(seg * 32 + 2 * (tid & 3)) * DM + col0 + ((tid >> 5) & 3) * 16 + ((tid >> 2) & 7) * 2;
#pragma unroll
  for (int j = 0; j < 8; j++)
    asm volatile("red.relaxed.gpu.global.add.v2.f32 [%0],{%1,%2};" ::"l"(p + ((j >> 1) * 8 + (j & 1)) * DM), "f"(d[4 * (j >> 1) + (j & 1)]), "f"(d[4 * (j >> 1) + 2 + (j & 1)]) : "memory");
}

#define FOR_P_JOBS(k, l, s)                               \
  for (int j_ = 0; j_ < 2 * NSTEP; j_++) {                \
    const int k = j_ >> 1, l = j_ & 1, s = k - l * LAG;   \
    if (s < 0 || s >= NSEG) continue;
__device__ __forceinline__ int next_job(int j) {
  j++;
  if (j < 2 * LAG) j += j & 1;
  else if (j >= 2 * NSEG) j |= j < 2 * NSTEP;
  return j;
}
__device__ __forceinline__ int job_index(int j) { return (j >> 1) + (j & 1) * (64 - LAG); }

template <int WG>
__device__ __forceinline__ void work_p(const CUtensorMap& tmWo, uint32_t sb, int pc, int tid0) {
  using namespace W;
  asm volatile("setmaxnreg.inc.sync.aligned.u32 208;");
  int spin = 0;
  const int ks = pc / 5, col0 = (pc % 5) * 128 + WG * 64;
  const uint32_t wb = sb + OFF_W + WG * 81920;
  uint32_t wf[40][4];
#pragma unroll 1
  for (int hf = 0; hf < 2; hf++) {
    if ((tid0 & 127) == 0) {
      mbar_expect_tx(sb + BAR_W + 8 * WG, 81920);
      for (int i = 0; i < 10; i++) tma2d(wb + i * 8192, &tmWo, col0, (ks * 19 + 2 * i + hf) * 64, sb + BAR_W + 8 * WG);
    }
    __syncwarp();
    mwait(sb + BAR_W + 8 * WG, hf, spin);
    permute_cols(wb, tid0 & 127);
    if (hf == 1 && ks < 4) for (int it = 2304 + (tid0 & 127); it < 2560; it += 128) {
      const uint32_t a = wb + (it >> 2) * 128 + (((2 * (it & 3)) ^ ((it >> 2) & 6)) << 4);
      sts128(a, make_uint4(0, 0, 0, 0)); sts128(a + 16, make_uint4(0, 0, 0, 0));
    }
    fence_async();
    WBAR_SYNC(NB_G0 + WG, 128);
    if (hf == 0) {
      load_frags40(wf, wb, tid0);
      fence_async();
      WBAR_SYNC(NB_G0 + WG, 128);
    }
  }
  FOR_P_JOBS(k_, l, s)
    float d[16];
#pragma unroll
    for (int f = 0; f < 10; f++) {
      mwait(sb + BAR_F + 8 * (f % 5), f / 5, spin);
      if (f == 0 && WG == 0 && pc == WW) WTS(l, s, 1);
      wg_fence();
#pragma unroll
      for (int kk = 0; kk < 4; kk++) {
        wgmma_rs32(d, wf[4 * f + kk], rdesc(f % 5, kk), f | kk);
        wgmma_ts32(d, mkdesc(SB0 + OFF_W + WG * 81920 + (4 * f + kk) * 2048, 8192, 1024), rdesc(f % 5, 4 + kk), 1);
      }
      wg_commit();
      if (f > 0) {
        wg_wait<1>();
        if ((tid0 & 31) == 0) mbar_arrive(sb + BAR_E + 8 * ((f - 1) % 5));
      }
    }
    wg_wait<0>();
    if ((tid0 & 31) == 0) mbar_arrive(sb + BAR_E + 32);
    if (WG == 0 && pc == WW) WTS(l, s, 2);
    red_tile(d, s, col0, tid0);
    WBAR_SYNC(NB_SG, 288);
  }
  if (spin >= SPIN_TOT) g_err = 11;
}
__device__ __forceinline__ void work_p_producer(uint32_t sb, int pc) {
  using namespace W;
  int spin = 0;
  const int ks = pc / 5;
  FOR_P_JOBS(k, l, s)
    if (l == 0 || k >= NSEG) { cwait(CN_O + k * 5 + ks, ks == 4 ? 20 : 19, spin); fence_async_all(); }
    if (pc == WW) WTS1(l, s, 0);
    const uint8_t* src = &g_o[k % ORING][l][ks * 19][0];
#pragma unroll
    for (int f = 0; f < 10; f++) {
      const int st = f < 5 ? f : f - 5;
      const uint32_t len = f == 9 && ks < 4 ? 4096 : 8192;
      mwait(sb + BAR_E + 8 * st, f < 5, spin);
      mbar_expect_tx(sb + BAR_F + 8 * st, len);
      bulk_g2s(sb + OFF_R + st * 8192, src + f * 8192, len, sb + BAR_F + 8 * st);
    }
  }
  if (spin >= SPIN_TOT) g_err = 12;
}
__device__ __forceinline__ float warp_sum(float x) {
  x = quad_sum(x);
  const float a = __shfl_xor_sync(0xffffffffu, x, 4), b = __shfl_xor_sync(0xffffffffu, x, 8), c = __shfl_xor_sync(0xffffffffu, x, 12);
  x = (x + a) + (b + c);
  return x + __shfl_xor_sync(0xffffffffu, x, 16);
}
__device__ __forceinline__ void work_ln(int kind, int r, int lane, bf16* out) {
  int spin = 0;
  const int l = kind & 1;
  const uint32_t sw = ((((lane >> 1) & 7) ^ (r & 7)) << 4) + (lane & 1) * 8;
  uint8_t* dst = kind < 2 ? g_xnb[l] + (lane >> 4) * 4096 + r * 128 + sw
               : kind == 2 ? g_xn[1] + (r >> 3) * 2048 + (lane >> 4) * 1024 + (r & 7) * 128 + sw
                           : reinterpret_cast<uint8_t*>(out) + r * 1280 + lane * 8;
  const int dm = kind == 3 ? 256 : 8192;
#pragma unroll 1
  for (int s = 0; s < NSEG; s++) {
    const float* xr = g_x + (size_t)(s * 32 + r) * DM;
    if (kind == 0 && lane < 20 && s + 3 < NSEG) prefetch_l2(xr + 96 * DM + lane * 32);
    if (lane == 0) cwait((kind < 2 ? CN_P : CN_W) + l * 64 + s, kind < 2 ? W::NP : 10, spin);
    __syncwarp();
    if (r == 0 && lane == 0) WTS1(l, s, kind < 2 ? 3 : 11);
    float4 v[5];
#pragma unroll
    for (int m = 0; m < 5; m++) v[m] = ld_relaxed4f(xr + m * 128 + lane * 4);
    if (kind < 3) {
      float t = 0.f;
#pragma unroll
      for (int m = 0; m < 5; m++) t += (v[m].x + v[m].y) + (v[m].z + v[m].w);
      const float mean = warp_sum(t) * (1.f / DM);
      float q0 = 0.f, q1 = 0.f;
#pragma unroll
      for (int m = 0; m < 5; m++) {
        v[m].x -= mean; v[m].y -= mean; v[m].z -= mean; v[m].w -= mean;
        q0 += v[m].x * v[m].x + v[m].y * v[m].y; q1 += v[m].z * v[m].z + v[m].w * v[m].w;
      }
      const float rs = rsqrtf(warp_sum(q0 + q1) * (1.f / DM) + 1e-5f);
#pragma unroll
      for (int m = 0; m < 5; m++) { v[m].x *= rs; v[m].y *= rs; v[m].z *= rs; v[m].w *= rs; }
    }
#pragma unroll
    for (int m = 0; m < 5; m++) *reinterpret_cast<uint2*>(dst + (size_t)s * 40960 + m * dm) = make_uint2(pack_bf16(v[m].x, v[m].y), pack_bf16(v[m].z, v[m].w));
    __syncwarp();
    if (r == 0 && lane == 0) WTS1(l, s, kind < 2 ? 4 : 12);
    if (lane == 0 && kind < 3) csignal(kind < 2 ? CN_L + l * 64 + s : CN_X + s);
  }
  if (spin >= SPIN_TOT) g_err = 13;
}

__device__ __forceinline__ void stage_qkv(const bf16* wqkv, uint32_t base, int T, int bc, int tid) {
  const int q = tid & 15, c = 64 * T + 4 * q, cc = c % 60;
  const bool ok = c < 180 && bc * 60 + cc < DM;
  const bf16* src = wqkv + (c / 60) * DM + bc * 60 + cc;
#pragma unroll 1
  for (int k0 = tid >> 4; k0 < 640; k0 += 80) {
    uint2 v[10];
#pragma unroll
    for (int u = 0; u < 10; u++) v[u] = ok ? *reinterpret_cast<const uint2*>(src + (size_t)(k0 + 8 * u) * 1920) : make_uint2(0, 0);
#pragma unroll
    for (int u = 0; u < 10; u++) sts64(base + (k0 + 8 * u) * 128 + (((q >> 1) ^ (k0 & 7)) << 4) + (q & 1) * 8, v[u].x, v[u].y);
  }
}
template <int T>
__device__ __forceinline__ void stage_out(const float (&d)[16], uint32_t sb, int l, int row0, int tid) {
  using namespace W;
  const int c = 64 * T + ((tid >> 5) & 3) * 16 + ((tid >> 2) & 7) * 2;
  if (c < 180) {
#pragma unroll
    for (int j = 0; j < 8; j++) {
      const int tk = (j >> 1) * 8 + 2 * (tid & 3) + (j & 1);
      int rr = row0 + tk; rr -= rr >= KVR ? KVR : 0;
      sts32(c < 60 ? sb + OFF_Q + tk * QP + c * 2 : sb + OFF_KV + (l * KVR + rr) * KVP + (c - 60) * 2, pack_bf16(d[4 * (j >> 1) + (j & 1)], d[4 * (j >> 1) + 2 + (j & 1)]));
    }
  }
}
template <int WG>
__device__ __forceinline__ void work_b(const CUtensorMap& tmBo, const bf16* wqkv, uint32_t sb, int bc, int tid0) {
  using namespace W;
  if (WG == 0) asm volatile("setmaxnreg.inc.sync.aligned.u32 224;");
  else asm volatile("setmaxnreg.inc.sync.aligned.u32 208;");
  int spin = 0;
  const uint32_t wb = sb + OFF_W + WG * 81920;
  uint32_t wf[40][4];
  stage_qkv(wqkv, wb, WG, bc, tid0 & 127);
  WBAR_SYNC(NB_G0 + WG, 128);
  permute_cols(wb, tid0 & 127);
  WBAR_SYNC(NB_G0 + WG, 128);
  load_frags40(wf, wb, tid0);
  fence_async();
  WBAR_SYNC(NB_G0 + WG, 128);
  if (WG == 0) {
    stage_qkv(wqkv, wb, 2, bc, tid0 & 127);
    WBAR_SYNC(NB_G0 + WG, 128);
  } else if (bc < 10) {
    if ((tid0 & 127) == 0) {
      mbar_expect_tx(sb + BAR_W + 8, 81920);
      for (int i = 0; i < 10; i++) tma2d(wb + i * 8192, &tmBo, bc * 64, i * 64, sb + BAR_W + 8);
    }
    __syncwarp();
    mwait(sb + BAR_W + 8, 0, spin);
  }
  permute_cols(wb, tid0 & 127);
  fence_async();
  WBAR_SYNC(NB_G0 + WG, 128);

  uint32_t ph = 0, pg = 0;
  int jq = 0;
#pragma unroll 1
  for (int n = WG && bc < 10 ? 256 : 128; n > 0; n--) {
    int job;
    if (WG) {
      mwait(sb + BAR_J, n & 1, spin);
      job = __shfl_sync(0xffffffffu, lds32(sb + JOB + 4 * (n & 1)), 0);
    } else {
      job = job_index(jq); jq = next_job(jq);
    }
    const int l = (job >> 6) & 1, s = job & 63;
    if (WG == 0 || job < 128) {
      float d[16], e[16];
#pragma unroll
      for (int f = 0; f < 5; f++) {
        mwait(sb + BAR_F + 8 * f, ph, spin);
        if (f == 0 && WG == 0 && bc == 0) WTS(l, s, 6);
        wg_fence();
#pragma unroll
        for (int kk = 0; kk < 8; kk++) {
          wgmma_rs32(d, wf[8 * f + kk], rdesc(f, kk), f | kk);
          if (WG == 0) wgmma_ts32(e, mkdesc(SB0 + OFF_W + (8 * f + kk) * 2048, 8192, 1024), rdesc(f, kk), f | kk);
        }
        wg_commit();
        if (f > 0) {
          wg_wait<1>();
          if ((tid0 & 31) == 0) mbar_arrive(sb + BAR_E + 8 * (f - 1));
        }
      }
      wg_wait<0>();
      if ((tid0 & 31) == 0) mbar_arrive(sb + BAR_E + 32);
      WBAR_SYNC(NB_SF, 352);
      const int row0 = (s * 32) % KVR;
      stage_out<WG>(d, sb, l, row0, tid0);
      if (WG == 0) stage_out<2>(e, sb, l, row0, tid0);
      WBAR_ARRIVE(NB_ST, 352);
      ph ^= 1;
    } else {
      float d[16];
#pragma unroll
      for (int f = 0; f < 5; f++) {
        mwait(sb + BAR_G + 8 * f, pg, spin);
        wg_fence();
#pragma unroll
        for (int kk = 0; kk < 8; kk++) wgmma_ts32(d, mkdesc(SB0 + OFF_W + 81920 + (8 * f + kk) * 2048, 8192, 1024), rdesc(f, kk), f | kk);
        wg_commit();
        wg_wait<0>();
        if ((tid0 & 31) < 2) mbar_arrive(sb + BAR_E + 8 * f);
      }
      if (bc == 0) WTS(l, s, 10);
      red_tile(d, s, bc * 64, tid0);
      WBAR_SYNC(NB_SG, 160);
      pg ^= 1;
    }
  }
  if (spin >= SPIN_TOT) g_err = 14;
}
__device__ __forceinline__ void work_b_producer(uint32_t sb, int bc, int lane) {
  using namespace W;
  int spin = 0, jq = 0, jw = bc < 10 ? 0 : 2 * NSTEP;
  uint32_t ph = 1;
  while (jq < 2 * NSTEP || jw < 2 * NSTEP) {
    const int iq = job_index(jq), iw = job_index(jw);
    const bool watch = lane == 0 ? jq < 2 * NSTEP : (lane == 1 && jw < jq);
    uint32_t rdy;
    do {
      rdy = __ballot_sync(0xffffffffu, watch && (ld_acquire(&g_cnt[lane ? CN_A + iw : CN_L + iq][0]) >= 32 || spin >= SPIN_TOT));
      spin += 16;
    } while (!rdy);
    const bool wo = rdy & 2;
    if (lane == wo) {
      fence_async_all();
      const int job = wo ? iw : iq;
      if (bc == 0) WTS1(job >> 6, job & 63, wo ? 9 : 5);
      const uint8_t* src = (wo ? g_ob[0] : g_xnb[0]) + (size_t)job * 40960;
      const uint32_t fb = sb + (wo ? BAR_G : BAR_F);
#pragma unroll
      for (int f = 0; f < 5; f++) {
        mwait(sb + BAR_E + 8 * f, ph, spin);
        mbar_expect_tx(fb + 8 * f, 8192);
        bulk_g2s(sb + OFF_R + f * 8192, src + f * 8192, 8192, fb + 8 * f);
        if (f == 0) { sts32(sb + JOB + 4 * (ph ^ 1), job + (wo ? 128 : 0)); mbar_arrive(sb + BAR_J); }
      }
    }
    __syncwarp();
    if (wo) jw = next_job(jw); else jq = next_job(jq);
    ph ^= 1;
  }
  if (spin >= SPIN_TOT) g_err = 15;
}
__device__ __forceinline__ void work_att(uint32_t sb, int bc, int tid0) {
  using namespace W;
  WBAR_ARRIVE(NB_SF, 352);
  FOR_P_JOBS(k_, l, s)
    const int tid = fresh(tid0), lane = tid & 31, hh = (tid >> 5) & 3, head = bc * 3 + hh;
    const int pos = s * 32 + lane;
    const uint32_t kv = sb + OFF_KV + l * KVR * KVP + hh * 40;
    uint32_t row[8];
    row[0] = kv + (pos % KVR) * KVP;
#pragma unroll
    for (int j = 1; j < 8; j++) { row[j] = row[j - 1] - 2 * KVP; row[j] += row[j] < kv ? KVR * KVP : 0; }
    const uint32_t qa = sb + OFF_Q + lane * QP + hh * 40;
    WBAR_SYNC(NB_ST, 352);
    const float scl = 0.22360679774997896f * 1.4426950408889634f;
    float sc[8];
#pragma unroll
    for (int i = 0; i < 5; i++) {
      const uint2 uq = lds64(qa + i * 8);
      uint2 u[8];
#pragma unroll
      for (int j = 0; j < 8; j++) u[j] = lds64(row[j] + i * 8);
      const float q0 = bf_lo(uq.x), q1 = bf_hi(uq.x), q2 = bf_lo(uq.y), q3 = bf_hi(uq.y);
#pragma unroll
      for (int j = 0; j < 8; j++)
        sc[j] = fmaf(q3, bf_hi(u[j].y), fmaf(q2, bf_lo(u[j].y), fmaf(q1, bf_hi(u[j].x), i ? fmaf(q0, bf_lo(u[j].x), sc[j]) : q0 * bf_lo(u[j].x))));
    }
    if (bc == 0 && tid == 256 && sc[0] != 123.456f) WTS1(l, s, 7);
#pragma unroll
    for (int j = 1; j < 8; j++) sc[j] = pos >= 2 * j ? sc[j] : -INFINITY;
    const float mx = fmaxf(fmaxf(fmaxf(sc[0], sc[1]), fmaxf(sc[2], sc[3])), fmaxf(fmaxf(sc[4], sc[5]), fmaxf(sc[6], sc[7]))) * -scl;
#pragma unroll
    for (int j = 0; j < 8; j++) sc[j] = ex2(fmaf(sc[j], scl, mx));
    const float inv = rcp(((sc[0] + sc[1]) + (sc[2] + sc[3])) + ((sc[4] + sc[5]) + (sc[6] + sc[7])));
    uint8_t* img = g_ob[l] + (size_t)s * 40960 + lane * 128;
#pragma unroll
    for (int i = 0; i < 5; i++) {
      uint2 u[8];
#pragma unroll
      for (int j = 0; j < 8; j++) u[j] = lds64(row[j] + 120 + i * 8);
      if (i == 4 && j_ + 1 < 2 * NSTEP) WBAR_ARRIVE(NB_SF, 352);
      float o0 = sc[0] * bf_lo(u[0].x), o1 = sc[0] * bf_hi(u[0].x), o2 = sc[0] * bf_lo(u[0].y), o3 = sc[0] * bf_hi(u[0].y);
#pragma unroll
      for (int j = 1; j < 8; j++) {
        o0 = fmaf(sc[j], bf_lo(u[j].x), o0); o1 = fmaf(sc[j], bf_hi(u[j].x), o1); o2 = fmaf(sc[j], bf_lo(u[j].y), o2); o3 = fmaf(sc[j], bf_hi(u[j].y), o3);
      }
      const uint32_t c = head * 20 + 4 * i;
      if (head < NH)
        *reinterpret_cast<uint2*>(img + ((c >> 6) * 4096 + (((c >> 3) ^ lane) & 7) * 16 + (c & 4) * 2)) = make_uint2(pack_bf16(o0 * inv, o1 * inv), pack_bf16(o2 * inv, o3 * inv));
    }
    __syncwarp();
    if (bc == 0 && tid == 256) WTS1(l, s, 8);
    if (lane == 0 && head < NH) csignal(CN_A + l * 64 + s);
    __syncwarp();
  }
}

__global__ void __launch_bounds__(512, 1)
k_work(const __grid_constant__ CUtensorMap tmWo, const __grid_constant__ CUtensorMap tmBo, const bf16* __restrict__ wqkv, bf16* __restrict__ out) {
  using namespace W;
  extern __shared__ __align__(1024) uint8_t smem[];
  const uint32_t sb = smem_u32(smem);
  const int tid = threadIdx.x, w = blockIdx.x;
  const int wg = __shfl_sync(0xffffffffu, tid >> 7, 0);
  if (tid == 0) {
    if (sb != SB0) g_err = 101;
    for (int i = 0; i < 5; i++) { mbar_init(sb + BAR_F + 8 * i, 1); mbar_init(sb + BAR_E + 8 * i, 8); mbar_init(sb + BAR_G + 8 * i, 1); }
    mbar_init(sb + BAR_J, 1);
    mbar_init(sb + BAR_W, 1); mbar_init(sb + BAR_W + 8, 1);
    for (int p = 0; p < 16; p++) sts32(sb + OFF_SAFE + 4 * p, 0);
    asm volatile("fence.mbarrier_init.release.cluster;" ::: "memory");
  }
  for (int i = tid; i < 2 * KVR * KVP / 16; i += 512) sts128(sb + OFF_KV + i * 16, make_uint4(0, 0, 0, 0));
  fence_async();
  __syncthreads();

  if (w < NP) {
    if (wg == 0) work_p<0>(tmWo, sb, w, keep(tid));
    else if (wg == 1) work_p<1>(tmWo, sb, w, keep(tid));
    else {
      asm volatile("setmaxnreg.dec.sync.aligned.u32 48;");
      const int aw = (tid >> 5) - 8;
      if (aw == 0) {
        if (tid == 256) work_p_producer(sb, w);
      } else if (aw == 1) {
        FOR_P_JOBS(k_, l, s)
          WBAR_SYNC(NB_SG, 288);
          if (tid == 288) csignal(CN_P + l * 64 + s);
          __syncwarp();
        }
      } else {
        const int id = (aw - 2) * NP + w;
        if (id < 128) work_ln(id & 3, id >> 2, tid & 31, out);
      }
    }
  } else {
    const int bc = w - NP;
    if (wg == 0) work_b<0>(tmBo, wqkv, sb, bc, keep(tid));
    else if (wg == 1) work_b<1>(tmBo, wqkv, sb, bc, keep(tid));
    else if (wg == 2) {
      asm volatile("setmaxnreg.dec.sync.aligned.u32 56;");
      if (tid < 352) work_att(sb, bc, keep(tid));
    } else {
      asm volatile("setmaxnreg.dec.sync.aligned.u32 24;");
      if (tid < 416) work_b_producer(sb, bc, tid & 31);
      else if (tid >= 416 && tid < 448 && bc < 10) {
        FOR_P_JOBS(k_, l, s)
          WBAR_SYNC(NB_SG, 160);
          if (tid == 416) csignal(CN_W + l * 64 + s);
          __syncwarp();
        }
      }
    }
  }
  __syncthreads();
  asm volatile("griddepcontrol.wait;" ::: "memory");
}

typedef CUresult (*EncodeFn)(CUtensorMap*, CUtensorMapDataType, cuuint32_t, void*, const cuuint64_t*, const cuuint64_t*,
                             const cuuint32_t*, const cuuint32_t*, CUtensorMapInterleave, CUtensorMapSwizzle,
                             CUtensorMapL2promotion, CUtensorMapFloatOOBfill);

static void make_map(EncodeFn enc, CUtensorMap* tm, const void* ptr, uint64_t cols, uint64_t rows, uint32_t boxc, uint32_t boxr) {
  cuuint64_t dims[2] = {cols, rows};
  cuuint64_t strides[1] = {cols * 2};
  cuuint32_t box[2] = {boxc, boxr};
  cuuint32_t es[2] = {1, 1};
  enc(tm, CU_TENSOR_MAP_DATA_TYPE_BFLOAT16, 2, const_cast<void*>(ptr), dims, strides, box, es, CU_TENSOR_MAP_INTERLEAVE_NONE,
      CU_TENSOR_MAP_SWIZZLE_128B, CU_TENSOR_MAP_L2_PROMOTION_L2_256B, CU_TENSOR_MAP_FLOAT_OOB_FILL_NONE);
}

extern "C" void kernel_launch(void* const* d_in, const int* in_sizes, int n_in, void* d_out, int out_size) {
  const bf16* x0 = (const bf16*)d_in[0];
  const bf16* mem0 = (const bf16*)d_in[1];
  const bf16* Wq = (const bf16*)d_in[2];
  const bf16* Wk = (const bf16*)d_in[3];
  const bf16* Wv = (const bf16*)d_in[4];
  const bf16* Wo = (const bf16*)d_in[5];
  const bf16* Bqkv = (const bf16*)d_in[8];
  const bf16* Bwo = (const bf16*)d_in[9];
  bf16* out = (bf16*)d_out;

  static EncodeFn enc = nullptr;
  if (!enc) {
    void* fn = nullptr;
    cudaDriverEntryPointQueryResult qr;
    cudaGetDriverEntryPoint("cuTensorMapEncodeTiled", &fn, cudaEnableDefault, &qr);
    enc = (EncodeFn)fn;
    cudaFuncSetAttribute(k_chain, cudaFuncAttributeMaxDynamicSharedMemorySize, C::SMEM);
    cudaFuncSetAttribute(k_work, cudaFuncAttributeMaxDynamicSharedMemorySize, W::SMEM);
  }
  CUtensorMap tmWq, tmWk, tmWv, tmWo, tmBo;
  make_map(enc, &tmWq, Wq, NH * DH, DM, 64, 128);
  make_map(enc, &tmWk, Wk, NH * DH, DM, 64, 128);
  make_map(enc, &tmWv, Wv, NH * DH, DM, 64, 128);
  make_map(enc, &tmWo, Wo, DM, NH * DH, 64, 64);
  make_map(enc, &tmBo, Bwo, DM, DM, 64, 64);

  cudaStream_t st = cudaStreamPerThread;
  k_pre<<<256, 256, 0, st>>>(x0, mem0);
  cudaLaunchAttribute at[1];
  at[0].id = cudaLaunchAttributeProgrammaticStreamSerialization; at[0].val.programmaticStreamSerializationAllowed = 1;
  {
    cudaLaunchConfig_t cfg = {};
    cfg.gridDim = dim3(96); cfg.blockDim = dim3(384); cfg.dynamicSmemBytes = C::SMEM; cfg.stream = st;
    cfg.attrs = at; cfg.numAttrs = 0;
    cudaLaunchKernelEx(&cfg, k_chain, tmWq, tmWk, tmWv, tmWo);
  }
  cudaLaunchConfig_t cfg = {};
  cfg.gridDim = dim3(W::NW); cfg.blockDim = dim3(512); cfg.dynamicSmemBytes = W::SMEM; cfg.stream = st;
  cfg.attrs = at; cfg.numAttrs = NOWORK == 2 ? 0 : 1;
  cudaLaunchKernelEx(&cfg, k_work, tmWo, tmBo, Bqkv, out);
}
```

```cpp
#include <cuda_runtime.h>
#include <cuda_bf16.h>
#include <cuda.h>
#include <stdint.h>

typedef __nv_bfloat16 bf16;

constexpr int SEQ = 2048, DM = 640, NH = 32, DH = 192, NSEG = 64;
#define LAG 5
constexpr int NSTEP = NSEG + LAG;
constexpr uint32_t SENT = 0xFFFFFFFFu;

constexpr int MAIL9 = 288 * 2048, MAIL_BYTES = MAIL9 + 64 * 3072;
__device__ __align__(1024) uint8_t g_xn[2][NSEG * 40960];
__device__ __align__(1024) uint8_t g_xnb[2][NSEG * 40960];
__device__ __align__(1024) uint8_t g_ob[2][NSEG * 40960];
#define ORING 8
static_assert(ORING > LAG, "a slot is free again LAG + 1 steps later");
__device__ __align__(1024) uint8_t g_o[ORING][2][96][4096];
__device__ __align__(1024) float g_x[SEQ * DM];
__device__ __align__(1024) uint8_t g_mbuf[NSTEP][20480];
__device__ __align__(1024) uint32_t g_flag[NSTEP][768];
__device__ __align__(1024) uint8_t g_mail[2][MAIL_BYTES];
enum { CN_P = 0, CN_L = 128, CN_A = 256, CN_W = 384, CN_X = 512, CN_O = 576, CN_NUM = CN_O + 5 * NSTEP };
__device__ __align__(128) uint32_t g_cnt[CN_NUM][32];
__device__ int g_err;
#define TS(jj, i)
#define TS1(jj, i)
#define PTS(i)
#define TSB(jj, i)
#define TSV(jj, i, v)
#define TS_FLUSH(jj)
#define WTS(l, b, k)
#define WTS1(l, b, k)
#define WW -1

__device__ __forceinline__ uint32_t smem_u32(const void* p) { return (uint32_t)__cvta_generic_to_shared(p); }
__device__ __forceinline__ uint32_t clk32() { uint32_t t; asm volatile("mov.u32 %0, %%clock;" : "=r"(t)::"memory"); return t; }
__device__ __forceinline__ uint32_t mapa(uint32_t a, uint32_t r) { uint32_t o; asm("mapa.shared::cluster.u32 %0,%1,%2;" : "=r"(o) : "r"(a), "r"(r)); return o; }
__device__ __forceinline__ void mbar_init(uint32_t bar, uint32_t cnt) { asm volatile("mbarrier.init.shared::cta.b64 [%0],%1;" ::"r"(bar), "r"(cnt) : "memory"); }
__device__ __forceinline__ void mbar_expect_tx(uint32_t bar, uint32_t bytes) { asm volatile("mbarrier.arrive.expect_tx.shared::cta.b64 _,[%0],%1;" ::"r"(bar), "r"(bytes) : "memory"); }
__device__ __forceinline__ void mbar_arrive(uint32_t bar) { asm volatile("mbarrier.arrive.shared::cta.b64 _,[%0];" ::"r"(bar) : "memory"); }
__device__ __forceinline__ void mbar_arrive_cluster(uint32_t bar) { asm volatile("mbarrier.arrive.shared::cluster.b64 _,[%0];" ::"r"(bar) : "memory"); }
__device__ __forceinline__ bool mbar_try(uint32_t bar, uint32_t ph) {
  uint32_t ok;
  asm volatile("{.reg .pred p; mbarrier.try_wait.parity.shared::cta.b64 p,[%1],%2; selp.u32 %0,1,0,p;}" : "=r"(ok) : "r"(bar), "r"(ph) : "memory");
  return ok;
}
__device__ __forceinline__ int fresh(int x) { asm volatile("" : "+r"(x)); return x; }
#define PHASE_IDS const int tid = fresh(tid0), lane = tid & 31, w = tid >> 5, g = lane >> 2, t = lane & 3; (void)w; (void)g; (void)t
__device__ __forceinline__ void bar_sync(int id, int n) { asm volatile("bar.sync %0,%1;" ::"r"(id), "r"(n) : "memory"); }
__device__ __forceinline__ void bar_arrive(int id, int n) { asm volatile("bar.arrive %0,%1;" ::"r"(id), "r"(n) : "memory"); }
__device__ __forceinline__ bool bar_red_or(int id, int n, bool v) {
  uint32_t r;
  asm volatile("{\n .reg .pred p, q;\n setp.ne.u32 q, %3, 0;\n barrier.cta.red.or.pred p, %1, %2, q;\n selp.u32 %0, 1, 0, p;\n}" : "=r"(r) : "r"(id), "r"(n), "r"((uint32_t)v) : "memory");
  return r != 0;
}
__device__ __forceinline__ void fence_async() { asm volatile("fence.proxy.async.shared::cta;" ::: "memory"); }
__device__ __forceinline__ void bulk_g2s(uint32_t dst, const void* src, uint32_t bytes, uint32_t bar) {
  asm volatile("cp.async.bulk.shared::cluster.global.mbarrier::complete_tx::bytes [%0],[%1],%2,[%3];" ::"r"(dst), "l"(src), "r"(bytes), "r"(bar) : "memory");
}
__device__ __forceinline__ void bulk_g2s_mc(uint32_t dst, const void* src, uint32_t bytes, uint32_t bar) {
  asm volatile("cp.async.bulk.shared::cluster.global.mbarrier::complete_tx::bytes.multicast::cluster [%0],[%1],%2,[%3],%4;"
               ::"r"(dst), "l"(src), "r"(bytes), "r"(bar), "h"((uint16_t)7) : "memory");
}
__device__ __forceinline__ void bulk_s2g(void* dst, uint32_t src, uint32_t bytes) {
  asm volatile("cp.async.bulk.global.shared::cta.bulk_group [%0],[%1],%2;" ::"l"(dst), "r"(src), "r"(bytes) : "memory");
}
__device__ __forceinline__ void bulk_s2c(uint32_t dst, uint32_t src, uint32_t bytes, uint32_t bar) {
  asm volatile("cp.async.bulk.shared::cluster.shared::cta.mbarrier::complete_tx::bytes [%0],[%1],%2,[%3];" ::"r"(dst), "r"(src), "r"(bytes), "r"(bar) : "memory");
}
__device__ __forceinline__ void tma2d(uint32_t dst, const CUtensorMap* tm, int c0, int c1, uint32_t bar) {
  asm volatile("cp.async.bulk.tensor.2d.shared::cluster.global.mbarrier::complete_tx::bytes [%0],[%1,{%3,%4}],[%2];"
               ::"r"(dst), "l"(tm), "r"(bar), "r"(c0), "r"(c1) : "memory");
}
__device__ __forceinline__ void tma2d_prefetch(const CUtensorMap* tm, int c0, int c1) {
  asm volatile("cp.async.bulk.prefetch.tensor.2d.L2.global.tile [%0,{%1,%2}];" ::"l"(tm), "r"(c0), "r"(c1) : "memory");
}
__device__ __forceinline__ uint32_t pack_bf16(float lo, float hi) {
  uint32_t r; asm("cvt.rn.bf16x2.f32 %0,%1,%2;" : "=r"(r) : "f"(hi), "f"(lo)); return r;
}
__device__ __forceinline__ float bf_lo(uint32_t x) { return __uint_as_float(x << 16); }
__device__ __forceinline__ float bf_hi(uint32_t x) { return __uint_as_float(x & 0xFFFF0000u); }
__device__ __forceinline__ float ex2(float x) { float y; asm("ex2.approx.ftz.f32 %0,%1;" : "=f"(y) : "f"(x)); return y; }
__device__ __forceinline__ void ldsm4(uint32_t (&r)[4], uint32_t a) {
  asm volatile("ldmatrix.sync.aligned.m8n8.x4.shared.b16 {%0,%1,%2,%3},[%4];" : "=r"(r[0]), "=r"(r[1]), "=r"(r[2]), "=r"(r[3]) : "r"(a) : "memory");
}
__device__ __forceinline__ void ldsm4t(uint32_t (&r)[4], uint32_t a) {
  asm volatile("ldmatrix.sync.aligned.m8n8.x4.trans.shared.b16 {%0,%1,%2,%3},[%4];" : "=r"(r[0]), "=r"(r[1]), "=r"(r[2]), "=r"(r[3]) : "r"(a) : "memory");
}
__device__ __forceinline__ void ldsm2(uint32_t& r0, uint32_t& r1, uint32_t a) {
  asm volatile("ldmatrix.sync.aligned.m8n8.x2.shared.b16 {%0,%1},[%2];" : "=r"(r0), "=r"(r1) : "r"(a) : "memory");
}
__device__ __forceinline__ void ldsm1(uint32_t& r0, uint32_t a) {
  asm volatile("ldmatrix.sync.aligned.m8n8.x1.shared.b16 {%0},[%1];" : "=r"(r0) : "r"(a) : "memory");
}
__device__ __forceinline__ void mma16816(float (&d)[4], uint32_t a0, uint32_t a1, uint32_t a2, uint32_t a3, uint32_t b0, uint32_t b1) {
  asm volatile("mma.sync.aligned.m16n8k16.row.col.f32.bf16.bf16.f32 {%0,%1,%2,%3},{%4,%5,%6,%7},{%8,%9},{%0,%1,%2,%3};"
               : "+f"(d[0]), "+f"(d[1]), "+f"(d[2]), "+f"(d[3]) : "r"(a0), "r"(a1), "r"(a2), "r"(a3), "r"(b0), "r"(b1));
}
__device__ __forceinline__ void mma1688(float (&d)[4], uint32_t a0, uint32_t a1, uint32_t b0) {
  asm volatile("mma.sync.aligned.m16n8k8.row.col.f32.bf16.bf16.f32 {%0,%1,%2,%3},{%4,%5},{%6},{%0,%1,%2,%3};"
               : "+f"(d[0]), "+f"(d[1]), "+f"(d[2]), "+f"(d[3]) : "r"(a0), "r"(a1), "r"(b0));
}
__device__ __forceinline__ void sts32(uint32_t a, uint32_t v) { asm volatile("st.shared.b32 [%0],%1;" ::"r"(a), "r"(v) : "memory"); }
__device__ __forceinline__ void sts64f(uint32_t a, float x, float y) { asm volatile("st.shared.v2.f32 [%0],{%1,%2};" ::"r"(a), "f"(x), "f"(y) : "memory"); }
__device__ __forceinline__ void sts128(uint32_t a, uint4 v) { asm volatile("st.shared.v4.b32 [%0],{%1,%2,%3,%4};" ::"r"(a), "r"(v.x), "r"(v.y), "r"(v.z), "r"(v.w) : "memory"); }
__device__ __forceinline__ float lds32f(uint32_t a) { float v; asm volatile("ld.shared.f32 %0,[%1];" : "=f"(v) : "r"(a) : "memory"); return v; }
__device__ __forceinline__ float2 lds64f(uint32_t a) { float2 v; asm volatile("ld.shared.v2.f32 {%0,%1},[%2];" : "=f"(v.x), "=f"(v.y) : "r"(a) : "memory"); return v; }
__device__ __forceinline__ uint4 lds128(uint32_t a) { uint4 v; asm volatile("ld.shared.v4.b32 {%0,%1,%2,%3},[%4];" : "=r"(v.x), "=r"(v.y), "=r"(v.z), "=r"(v.w) : "r"(a) : "memory"); return v; }
__device__ __forceinline__ float4 lds128f(uint32_t a) { float4 v; asm volatile("ld.shared.v4.f32 {%0,%1,%2,%3},[%4];" : "=f"(v.x), "=f"(v.y), "=f"(v.z), "=f"(v.w) : "r"(a) : "memory"); return v; }
__device__ __forceinline__ void st_async2(uint32_t a, float x, float y, uint32_t bar) {
  asm volatile("st.async.weak.shared::cluster.mbarrier::complete_tx::bytes.v2.f32 [%0],{%1,%2},[%3];" ::"r"(a), "f"(x), "f"(y), "r"(bar) : "memory");
}
__device__ __forceinline__ void st_async4(uint32_t a, const float (&v)[4], uint32_t bar) {
  asm volatile("st.async.weak.shared::cluster.mbarrier::complete_tx::bytes.v4.f32 [%0],{%1,%2,%3,%4},[%5];" ::"r"(a), "f"(v[0]), "f"(v[1]), "f"(v[2]), "f"(v[3]), "r"(bar) : "memory");
}
__device__ __forceinline__ void st_async4v(uint32_t a, float x, float y, float z, float w, uint32_t bar) {
  asm volatile("st.async.weak.shared::cluster.mbarrier::complete_tx::bytes.v4.f32 [%0],{%1,%2,%3,%4},[%5];" ::"r"(a), "f"(x), "f"(y), "f"(z), "f"(w), "r"(bar) : "memory");
}
__device__ __forceinline__ void st_async4u(uint32_t a, const uint4& v, uint32_t bar) {
  asm volatile("st.async.weak.shared::cluster.mbarrier::complete_tx::bytes.v4.b32 [%0],{%1,%2,%3,%4},[%5];" ::"r"(a), "r"(v.x), "r"(v.y), "r"(v.z), "r"(v.w), "r"(bar) : "memory");
}
__device__ __forceinline__ uint4 ld_relaxed4(const void* p) {
  uint4 v; asm volatile("ld.relaxed.gpu.global.v4.u32 {%0,%1,%2,%3},[%4];" : "=r"(v.x), "=r"(v.y), "=r"(v.z), "=r"(v.w) : "l"(p) : "memory"); return v;
}
__device__ __forceinline__ uint32_t ld_relaxed(const void* p) {
  uint32_t v; asm volatile("ld.relaxed.gpu.global.u32 %0,[%1];" : "=r"(v) : "l"(p) : "memory"); return v;
}
__device__ __forceinline__ void st_relaxed(void* p, uint32_t v) { asm volatile("st.relaxed.gpu.global.b32 [%0],%1;" ::"l"(p), "r"(v) : "memory"); }
__device__ __forceinline__ void st_relaxed4(void* p, uint32_t v) { asm volatile("st.relaxed.gpu.global.v4.b32 [%0],{%1,%1,%1,%1};" ::"l"(p), "r"(v) : "memory"); }

__device__ __forceinline__ uint32_t ld_acquire(const void* p) {
  uint32_t v; asm volatile("ld.acquire.gpu.global.u32 %0,[%1];" : "=r"(v) : "l"(p) : "memory"); return v;
}
__device__ __forceinline__ float4 ld_relaxed4f(const void* p) {
  float4 v; asm volatile("ld.relaxed.gpu.global.v4.f32 {%0,%1,%2,%3},[%4];" : "=f"(v.x), "=f"(v.y), "=f"(v.z), "=f"(v.w) : "l"(p) : "memory"); return v;
}
__device__ __forceinline__ float2 ld_relaxed2f(const void* p) {
  float2 v; asm volatile("ld.relaxed.gpu.global.v2.f32 {%0,%1},[%2];" : "=f"(v.x), "=f"(v.y) : "l"(p) : "memory"); return v;
}
__device__ __forceinline__ void prefetch_l2(const void* p) { asm volatile("prefetch.global.L2 [%0];" ::"l"(p)); }
__device__ __forceinline__ void fence_gpu() { asm volatile("fence.acq_rel.gpu;" ::: "memory"); }
__device__ __forceinline__ void fence_async_all() { asm volatile("fence.proxy.async.global;" ::: "memory"); }
constexpr int SPIN_TOT = 1 << 22;
__device__ __forceinline__ void csignal(int idx) { asm volatile("red.release.gpu.global.add.u32 [%0],1;" ::"l"(&g_cnt[idx][0]) : "memory"); }
__device__ __forceinline__ void cwait(int idx, uint32_t target, int& spin) {
  while (ld_acquire(&g_cnt[idx][0]) < target && spin < SPIN_TOT) spin += 16;
}

__device__ __forceinline__ uint64_t mkdesc(uint32_t addr, uint32_t lbo, uint32_t sbo) {
  return (uint64_t)((addr & 0x3FFFF) >> 4) | ((uint64_t)(lbo >> 4) << 16) | ((uint64_t)(sbo >> 4) << 32) | ((uint64_t)1 << 62);
}
__device__ __forceinline__ uint64_t mkdesc_ns(uint32_t addr, uint32_t lbo, uint32_t sbo) {
  return (uint64_t)((addr & 0x3FFFF) >> 4) | ((uint64_t)(lbo >> 4) << 16) | ((uint64_t)(sbo >> 4) << 32);
}
__device__ __forceinline__ void wg_fence() { asm volatile("wgmma.fence.sync.aligned;" ::: "memory"); }
__device__ __forceinline__ void wg_commit() { asm volatile("wgmma.commit_group.sync.aligned;" ::: "memory"); }
template <int N> __device__ __forceinline__ void wg_wait() { asm volatile("wgmma.wait_group.sync.aligned %0;" ::"n"(N) : "memory"); }

__device__ __forceinline__ void wgmma_rs16(float (&d)[8], const uint32_t (&a)[4], uint64_t db, int sc) {
  asm volatile("{.reg .pred p; setp.ne.b32 p,%13,0; wgmma.mma_async.sync.aligned.m64n16k16.f32.bf16.bf16 "
               "{%0,%1,%2,%3,%4,%5,%6,%7},{%8,%9,%10,%11},%12,p,1,1,0;}"
               : "+f"(d[0]), "+f"(d[1]), "+f"(d[2]), "+f"(d[3]), "+f"(d[4]), "+f"(d[5]), "+f"(d[6]), "+f"(d[7])
               : "r"(a[0]), "r"(a[1]), "r"(a[2]), "r"(a[3]), "l"(db), "r"(sc));
}
__device__ __forceinline__ void wgmma_rs64(float (&d)[32], const uint32_t (&a)[4], uint64_t db, int sc) {
  asm volatile("{.reg .pred p; setp.ne.b32 p,%37,0; wgmma.mma_async.sync.aligned.m64n64k16.f32.bf16.bf16 "
               "{%0,%1,%2,%3,%4,%5,%6,%7,%8,%9,%10,%11,%12,%13,%14,%15,%16,%17,%18,%19,%20,%21,%22,%23,%24,%25,%26,%27,%28,%29,%30,%31},{%32,%33,%34,%35},%36,p,1,1,0;}"
               : "+f"(d[0]), "+f"(d[1]), "+f"(d[2]), "+f"(d[3]), "+f"(d[4]), "+f"(d[5]), "+f"(d[6]), "+f"(d[7]), "+f"(d[8]), "+f"(d[9]), "+f"(d[10]), "+f"(d[11]), "+f"(d[12]), "+f"(d[13]), "+f"(d[14]), "+f"(d[15]), "+f"(d[16]), "+f"(d[17]), "+f"(d[18]), "+f"(d[19]), "+f"(d[20]), "+f"(d[21]), "+f"(d[22]), "+f"(d[23]), "+f"(d[24]), "+f"(d[25]), "+f"(d[26]), "+f"(d[27]), "+f"(d[28]), "+f"(d[29]), "+f"(d[30]), "+f"(d[31])
               : "r"(a[0]), "r"(a[1]), "r"(a[2]), "r"(a[3]), "l"(db), "r"(sc));
}
__device__ __forceinline__ void wgmma_rt16(float (&d)[8], const uint32_t (&a)[4], uint64_t db, int sc) {
  asm volatile("{.reg .pred p; setp.ne.b32 p,%13,0; wgmma.mma_async.sync.aligned.m64n16k16.f32.bf16.bf16 "
               "{%0,%1,%2,%3,%4,%5,%6,%7},{%8,%9,%10,%11},%12,p,1,1,1;}"
               : "+f"(d[0]), "+f"(d[1]), "+f"(d[2]), "+f"(d[3]), "+f"(d[4]), "+f"(d[5]), "+f"(d[6]), "+f"(d[7])
               : "r"(a[0]), "r"(a[1]), "r"(a[2]), "r"(a[3]), "l"(db), "r"(sc));
}
__device__ __forceinline__ void wgmma_rt80(float (&d)[40], const uint32_t (&a)[4], uint64_t db, int sc) {
  asm volatile("{.reg .pred p; setp.ne.b32 p,%45,0; wgmma.mma_async.sync.aligned.m64n80k16.f32.bf16.bf16 "
               "{%0,%1,%2,%3,%4,%5,%6,%7,%8,%9,%10,%11,%12,%13,%14,%15,%16,%17,%18,%19,%20,%21,%22,%23,%24,%25,%26,%27,%28,%29,%30,%31,%32,%33,%34,%35,%36,%37,%38,%39},{%40,%41,%42,%43},%44,p,1,1,1;}"
               : "+f"(d[0]), "+f"(d[1]), "+f"(d[2]), "+f"(d[3]), "+f"(d[4]), "+f"(d[5]), "+f"(d[6]), "+f"(d[7]), "+f"(d[8]), "+f"(d[9]), "+f"(d[10]), "+f"(d[11]), "+f"(d[12]), "+f"(d[13]), "+f"(d[14]), "+f"(d[15]), "+f"(d[16]), "+f"(d[17]), "+f"(d[18]), "+f"(d[19]), "+f"(d[20]), "+f"(d[21]), "+f"(d[22]), "+f"(d[23]), "+f"(d[24]), "+f"(d[25]), "+f"(d[26]), "+f"(d[27]), "+f"(d[28]), "+f"(d[29]), "+f"(d[30]), "+f"(d[31]), "+f"(d[32]), "+f"(d[33]), "+f"(d[34]), "+f"(d[35]), "+f"(d[36]), "+f"(d[37]), "+f"(d[38]), "+f"(d[39])
               : "r"(a[0]), "r"(a[1]), "r"(a[2]), "r"(a[3]), "l"(db), "r"(sc));
}
__device__ __forceinline__ void wgmma_rs32(float (&d)[16], const uint32_t (&a)[4], uint64_t db, int sc) {
  asm volatile("{.reg .pred p; setp.ne.b32 p,%21,0; wgmma.mma_async.sync.aligned.m64n32k16.f32.bf16.bf16 "
               "{%0,%1,%2,%3,%4,%5,%6,%7,%8,%9,%10,%11,%12,%13,%14,%15},{%16,%17,%18,%19},%20,p,1,1,0;}"
               : "+f"(d[0]), "+f"(d[1]), "+f"(d[2]), "+f"(d[3]), "+f"(d[4]), "+f"(d[5]), "+f"(d[6]), "+f"(d[7]), "+f"(d[8]), "+f"(d[9]), "+f"(d[10]), "+f"(d[11]), "+f"(d[12]), "+f"(d[13]), "+f"(d[14]), "+f"(d[15])
               : "r"(a[0]), "r"(a[1]), "r"(a[2]), "r"(a[3]), "l"(db), "r"(sc));
}
__device__ __forceinline__ void wgmma_ts32(float (&d)[16], uint64_t da, uint64_t db, int sc) {
  asm volatile("{.reg .pred p; setp.ne.b32 p,%18,0; wgmma.mma_async.sync.aligned.m64n32k16.f32.bf16.bf16 "
               "{%0,%1,%2,%3,%4,%5,%6,%7,%8,%9,%10,%11,%12,%13,%14,%15},%16,%17,p,1,1,1,0;}"
               : "+f"(d[0]), "+f"(d[1]), "+f"(d[2]), "+f"(d[3]), "+f"(d[4]), "+f"(d[5]), "+f"(d[6]), "+f"(d[7]), "+f"(d[8]), "+f"(d[9]), "+f"(d[10]), "+f"(d[11]), "+f"(d[12]), "+f"(d[13]), "+f"(d[14]), "+f"(d[15])
               : "l"(da), "l"(db), "r"(sc));
}
__device__ __forceinline__ void wgmma_ts16(float (&d)[8], uint64_t da, uint64_t db, int sc) {
  asm volatile("{.reg .pred p; setp.ne.b32 p,%10,0; wgmma.mma_async.sync.aligned.m64n16k16.f32.bf16.bf16 "
               "{%0,%1,%2,%3,%4,%5,%6,%7},%8,%9,p,1,1,1,0;}"
               : "+f"(d[0]), "+f"(d[1]), "+f"(d[2]), "+f"(d[3]), "+f"(d[4]), "+f"(d[5]), "+f"(d[6]), "+f"(d[7])
               : "l"(da), "l"(db), "r"(sc));
}
__device__ __forceinline__ void wgmma_ts64(float (&d)[32], uint64_t da, uint64_t db, int sc) {
  asm volatile("{.reg .pred p; setp.ne.b32 p,%34,0; wgmma.mma_async.sync.aligned.m64n64k16.f32.bf16.bf16 "
               "{%0,%1,%2,%3,%4,%5,%6,%7,%8,%9,%10,%11,%12,%13,%14,%15,%16,%17,%18,%19,%20,%21,%22,%23,%24,%25,%26,%27,%28,%29,%30,%31},%32,%33,p,1,1,1,0;}"
               : "+f"(d[0]), "+f"(d[1]), "+f"(d[2]), "+f"(d[3]), "+f"(d[4]), "+f"(d[5]), "+f"(d[6]), "+f"(d[7]), "+f"(d[8]), "+f"(d[9]), "+f"(d[10]), "+f"(d[11]), "+f"(d[12]), "+f"(d[13]), "+f"(d[14]), "+f"(d[15]), "+f"(d[16]), "+f"(d[17]), "+f"(d[18]), "+f"(d[19]), "+f"(d[20]), "+f"(d[21]), "+f"(d[22]), "+f"(d[23]), "+f"(d[24]), "+f"(d[25]), "+f"(d[26]), "+f"(d[27]), "+f"(d[28]), "+f"(d[29]), "+f"(d[30]), "+f"(d[31])
               : "l"(da), "l"(db), "r"(sc));
}
__device__ __forceinline__ void wgmma_tt16(float (&d)[8], uint64_t da, uint64_t db, int sc) {
  asm volatile("{.reg .pred p; setp.ne.b32 p,%10,0; wgmma.mma_async.sync.aligned.m64n16k16.f32.bf16.bf16 "
               "{%0,%1,%2,%3,%4,%5,%6,%7},%8,%9,p,1,1,1,1;}"
               : "+f"(d[0]), "+f"(d[1]), "+f"(d[2]), "+f"(d[3]), "+f"(d[4]), "+f"(d[5]), "+f"(d[6]), "+f"(d[7])
               : "l"(da), "l"(db), "r"(sc));
}
__device__ __forceinline__ void wgmma_tt40(float (&d)[20], uint64_t da, uint64_t db, int sc) {
  asm volatile("{.reg .pred p; setp.ne.b32 p,%22,0; wgmma.mma_async.sync.aligned.m64n40k16.f32.bf16.bf16 "
               "{%0,%1,%2,%3,%4,%5,%6,%7,%8,%9,%10,%11,%12,%13,%14,%15,%16,%17,%18,%19},%20,%21,p,1,1,1,1;}"
               : "+f"(d[0]), "+f"(d[1]), "+f"(d[2]), "+f"(d[3]), "+f"(d[4]), "+f"(d[5]), "+f"(d[6]), "+f"(d[7]), "+f"(d[8]), "+f"(d[9]), "+f"(d[10]), "+f"(d[11]), "+f"(d[12]), "+f"(d[13]), "+f"(d[14]), "+f"(d[15]), "+f"(d[16]), "+f"(d[17]), "+f"(d[18]), "+f"(d[19])
               : "l"(da), "l"(db), "r"(sc));
}
__device__ __forceinline__ void wgmma_ss8(float (&d)[4], uint64_t da, uint64_t db, int sc) {
  asm volatile("{.reg .pred p; setp.ne.b32 p,%6,0; wgmma.mma_async.sync.aligned.m64n8k16.f32.bf16.bf16 "
               "{%0,%1,%2,%3},%4,%5,p,1,1,0,0;}"
               : "+f"(d[0]), "+f"(d[1]), "+f"(d[2]), "+f"(d[3])
               : "l"(da), "l"(db), "r"(sc));
}
__device__ __forceinline__ void wgmma_ss32(float (&d)[16], uint64_t da, uint64_t db, int sc) {
  asm volatile("{.reg .pred p; setp.ne.b32 p,%18,0; wgmma.mma_async.sync.aligned.m64n32k16.f32.bf16.bf16 "
               "{%0,%1,%2,%3,%4,%5,%6,%7,%8,%9,%10,%11,%12,%13,%14,%15},%16,%17,p,1,1,0,0;}"
               : "+f"(d[0]), "+f"(d[1]), "+f"(d[2]), "+f"(d[3]), "+f"(d[4]), "+f"(d[5]), "+f"(d[6]), "+f"(d[7]), "+f"(d[8]), "+f"(d[9]), "+f"(d[10]), "+f"(d[11]), "+f"(d[12]), "+f"(d[13]), "+f"(d[14]), "+f"(d[15])
               : "l"(da), "l"(db), "r"(sc));
}
__device__ __forceinline__ void wgmma_st64(float (&d)[32], uint64_t da, uint64_t db, int sc) {
  asm volatile("{.reg .pred p; setp.ne.b32 p,%34,0; wgmma.mma_async.sync.aligned.m64n64k16.f32.bf16.bf16 "
               "{%0,%1,%2,%3,%4,%5,%6,%7,%8,%9,%10,%11,%12,%13,%14,%15,%16,%17,%18,%19,%20,%21,%22,%23,%24,%25,%26,%27,%28,%29,%30,%31},%32,%33,p,1,1,0,1;}"
               : "+f"(d[0]), "+f"(d[1]), "+f"(d[2]), "+f"(d[3]), "+f"(d[4]), "+f"(d[5]), "+f"(d[6]), "+f"(d[7]), "+f"(d[8]), "+f"(d[9]), "+f"(d[10]), "+f"(d[11]), "+f"(d[12]), "+f"(d[13]), "+f"(d[14]), "+f"(d[15]), "+f"(d[16]), "+f"(d[17]), "+f"(d[18]), "+f"(d[19]), "+f"(d[20]), "+f"(d[21]), "+f"(d[22]), "+f"(d[23]), "+f"(d[24]), "+f"(d[25]), "+f"(d[26]), "+f"(d[27]), "+f"(d[28]), "+f"(d[29]), "+f"(d[30]), "+f"(d[31])
               : "l"(da), "l"(db), "r"(sc));
}
__device__ __forceinline__ void wgmma_st128(float (&d)[64], uint64_t da, uint64_t db, int sc) {
  asm volatile("{.reg .pred p; setp.ne.b32 p,%66,0; wgmma.mma_async.sync.aligned.m64n128k16.f32.bf16.bf16 "
               "{%0,%1,%2,%3,%4,%5,%6,%7,%8,%9,%10,%11,%12,%13,%14,%15,%16,%17,%18,%19,%20,%21,%22,%23,%24,%25,%26,%27,%28,%29,%30,%31,%32,%33,%34,%35,%36,%37,%38,%39,%40,%41,%42,%43,%44,%45,%46,%47,%48,%49,%50,%51,%52,%53,%54,%55,%56,%57,%58,%59,%60,%61,%62,%63},%64,%65,p,1,1,0,1;}"
               : "+f"(d[0]), "+f"(d[1]), "+f"(d[2]), "+f"(d[3]), "+f"(d[4]), "+f"(d[5]), "+f"(d[6]), "+f"(d[7]), "+f"(d[8]), "+f"(d[9]), "+f"(d[10]), "+f"(d[11]), "+f"(d[12]), "+f"(d[13]), "+f"(d[14]), "+f"(d[15]), "+f"(d[16]), "+f"(d[17]), "+f"(d[18]), "+f"(d[19]), "+f"(d[20]), "+f"(d[21]), "+f"(d[22]), "+f"(d[23]), "+f"(d[24]), "+f"(d[25]), "+f"(d[26]), "+f"(d[27]), "+f"(d[28]), "+f"(d[29]), "+f"(d[30]), "+f"(d[31]), "+f"(d[32]), "+f"(d[33]), "+f"(d[34]), "+f"(d[35]), "+f"(d[36]), "+f"(d[37]), "+f"(d[38]), "+f"(d[39]), "+f"(d[40]), "+f"(d[41]), "+f"(d[42]), "+f"(d[43]), "+f"(d[44]), "+f"(d[45]), "+f"(d[46]), "+f"(d[47]), "+f"(d[48]), "+f"(d[49]), "+f"(d[50]), "+f"(d[51]), "+f"(d[52]), "+f"(d[53]), "+f"(d[54]), "+f"(d[55]), "+f"(d[56]), "+f"(d[57]), "+f"(d[58]), "+f"(d[59]), "+f"(d[60]), "+f"(d[61]), "+f"(d[62]), "+f"(d[63])
               : "l"(da), "l"(db), "r"(sc));
}

__device__ __forceinline__ void stsm4(uint32_t a, uint32_t r0, uint32_t r1, uint32_t r2, uint32_t r3) {
  asm volatile("stmatrix.sync.aligned.m8n8.x4.shared.b16 [%0],{%1,%2,%3,%4};" ::"r"(a), "r"(r0), "r"(r1), "r"(r2), "r"(r3) : "memory");
}
__device__ __forceinline__ void stsm4t(uint32_t a, uint32_t r0, uint32_t r1, uint32_t r2, uint32_t r3) {
  asm volatile("stmatrix.sync.aligned.m8n8.x4.trans.shared.b16 [%0],{%1,%2,%3,%4};" ::"r"(a), "r"(r0), "r"(r1), "r"(r2), "r"(r3) : "memory");
}
__device__ __forceinline__ void sts64(uint32_t a, uint32_t x, uint32_t y) { asm volatile("st.shared.v2.b32 [%0],{%1,%2};" ::"r"(a), "r"(x), "r"(y) : "memory"); }
__device__ __forceinline__ void st_async2u(uint32_t a, uint32_t x, uint32_t y, uint32_t bar) {
  asm volatile("st.async.weak.shared::cluster.mbarrier::complete_tx::bytes.v2.b32 [%0],{%1,%2},[%3];" ::"r"(a), "r"(x), "r"(y), "r"(bar) : "memory");
}
__device__ __forceinline__ void st_relaxed128(void* p, uint32_t x, uint32_t y, uint32_t z, uint32_t w) {
  asm volatile("{.reg .b128 v; mov.b128 v,{%1,%2,%3,%4}; st.relaxed.gpu.global.b128 [%0],v;}" ::"l"(p), "r"(x), "r"(y), "r"(z), "r"(w) : "memory");
}
__device__ __forceinline__ void st_relaxed64(void* p, uint32_t x, uint32_t y) {
  asm volatile("{.reg .b64 v; mov.b64 v,{%1,%2}; st.relaxed.gpu.global.b64 [%0],v;}" ::"l"(p), "r"(x), "r"(y) : "memory");
}
__device__ __forceinline__ uint4 ld_relaxed128(const void* p) {
  uint4 v;
  asm volatile("{.reg .b128 v; .reg .b64 lo, hi; ld.relaxed.gpu.global.b128 v,[%4]; mov.b128 {lo,hi},v; mov.b64 {%0,%1},lo; mov.b64 {%2,%3},hi;}" : "=r"(v.x), "=r"(v.y), "=r"(v.z), "=r"(v.w) : "l"(p) : "memory");
  return v;
}

__device__ __forceinline__ uint32_t pack_h2(float lo, float hi) {
  uint32_t r; asm("cvt.rn.satfinite.f16x2.f32 %0,%1,%2;" : "=r"(r) : "f"(hi), "f"(lo)); return r;
}
__device__ __forceinline__ void add_h2(float& lo, float& hi, uint32_t u, uint32_t v) {
  float a, b;
  asm("{.reg .b16 l, h; .reg .b32 s; add.rn.f16x2 s,%2,%3; mov.b32 {l,h},s; cvt.f32.f16 %0,l; cvt.f32.f16 %1,h;}" : "=f"(a), "=f"(b) : "r"(u), "r"(v));
  lo += a; hi += b;
}
__device__ __forceinline__ void mwait(uint32_t bar, uint32_t ph, int& spin) {
  asm volatile("{.reg .pred p, q;\nWAIT_LOOP:\n add.s32 %0,%0,1;\n setp.lt.s32 q,%0,%3;\n mbarrier.try_wait.parity.shared::cta.b64 p,[%1],%2;\n not.pred p,p;\n and.pred q,q,p;\n @q bra.uni WAIT_LOOP;\n}"
               : "+&r"(spin) : "r"(bar), "r"(ph), "n"(SPIN_TOT) : "memory");
}
__device__ __forceinline__ int keep(int x) { return __shfl_sync(0xffffffffu, x, threadIdx.x & 31); }
__device__ __forceinline__ uint32_t pin(uint32_t x) { asm volatile("" : "+r"(x)); return x; }
template <typename T> __device__ __forceinline__ T* pinp(T* x) { asm volatile("" : "+l"(x)); return x; }
__device__ __forceinline__ void st_async1u(uint32_t a, uint32_t x, uint32_t bar) {
  asm volatile("st.async.weak.shared::cluster.mbarrier::complete_tx::bytes.b32 [%0],%1,[%2];" ::"r"(a), "r"(x), "r"(bar) : "memory");
}
__device__ __forceinline__ uint32_t lds32(uint32_t a) { uint32_t v; asm volatile("ld.shared.b32 %0,[%1];" : "=r"(v) : "r"(a) : "memory"); return v; }
__device__ __forceinline__ uint2 lds64(uint32_t a) { uint2 v; asm volatile("ld.shared.v2.b32 {%0,%1},[%2];" : "=r"(v.x), "=r"(v.y) : "r"(a) : "memory"); return v; }

__device__ __forceinline__ void permute_cols(uint32_t tile, int tid) {
  for (int it = tid; it < 2560; it += 128) {
    const int row = it >> 2, q = it & 3;
    const uint32_t a0 = tile + row * 128 + (((2 * q) ^ (row & 7)) << 4), a1 = tile + row * 128 + (((2 * q + 1) ^ (row & 7)) << 4);
    const uint4 u = lds128(a0), v = lds128(a1);
    sts128(a0, make_uint4(__byte_perm(u.x, u.y, 0x5410), __byte_perm(u.z, u.w, 0x5410), __byte_perm(v.x, v.y, 0x5410), __byte_perm(v.z, v.w, 0x5410)));
    sts128(a1, make_uint4(__byte_perm(u.x, u.y, 0x7632), __byte_perm(u.z, u.w, 0x7632), __byte_perm(v.x, v.y, 0x7632), __byte_perm(v.z, v.w, 0x7632)));
  }
}

__device__ __forceinline__ void ln_row_to_image(const bf16* __restrict__ x, uint8_t* __restrict__ img, int row, int lane) {
  const uint4* src = reinterpret_cast<const uint4*>(x + (size_t)row * DM);
  uint4 v[3];
  v[0] = src[lane]; v[1] = src[lane + 32];
  v[2] = lane < 16 ? src[lane + 64] : make_uint4(0, 0, 0, 0);
  float s = 0.f;
#pragma unroll
  for (int i = 0; i < 3; i++) {
    s += bf_lo(v[i].x) + bf_hi(v[i].x) + bf_lo(v[i].y) + bf_hi(v[i].y) + bf_lo(v[i].z) + bf_hi(v[i].z) + bf_lo(v[i].w) + bf_hi(v[i].w);
  }
#pragma unroll
  for (int o = 16; o > 0; o >>= 1) s += __shfl_xor_sync(0xffffffffu, s, o);
  const float mean = s * (1.f / DM);
  float q = 0.f;
#pragma unroll
  for (int i = 0; i < 3; i++) {
    if (i < 2 || lane < 16) {
      const uint32_t w[4] = {v[i].x, v[i].y, v[i].z, v[i].w};
#pragma unroll
      for (int j = 0; j < 4; j++) { float a = bf_lo(w[j]) - mean, b = bf_hi(w[j]) - mean; q += a * a + b * b; }
    }
  }
#pragma unroll
  for (int o = 16; o > 0; o >>= 1) q += __shfl_xor_sync(0xffffffffu, q, o);
  const float rstd = rsqrtf(q * (1.f / DM) + 1e-5f);
#pragma unroll
  for (int i = 0; i < 3; i++) {
    if (i < 2 || lane < 16) {
      const int c = lane + 32 * i;
      uint4 o;
      o.x = pack_bf16((bf_lo(v[i].x) - mean) * rstd, (bf_hi(v[i].x) - mean) * rstd);
      o.y = pack_bf16((bf_lo(v[i].y) - mean) * rstd, (bf_hi(v[i].y) - mean) * rstd);
      o.z = pack_bf16((bf_lo(v[i].z) - mean) * rstd, (bf_hi(v[i].z) - mean) * rstd);
      o.w = pack_bf16((bf_lo(v[i].w) - mean) * rstd, (bf_hi(v[i].w) - mean) * rstd);
      const size_t off = (size_t)(row >> 5) * 40960 + (c >> 4) * 8192 + ((row >> 3) & 3) * 2048 + ((c >> 3) & 1) * 1024 + (row & 7) * 128 + (((c & 7) ^ (row & 7)) << 4);
      *reinterpret_cast<uint4*>(img + off) = o;
      float4* xf = reinterpret_cast<float4*>(g_x + (size_t)row * DM + c * 8);
      xf[0] = make_float4(bf_lo(v[i].x), bf_hi(v[i].x), bf_lo(v[i].y), bf_hi(v[i].y));
      xf[1] = make_float4(bf_lo(v[i].z), bf_hi(v[i].z), bf_lo(v[i].w), bf_hi(v[i].w));
    }
  }
}

__global__ void __launch_bounds__(256) k_pre(const bf16* __restrict__ x, const bf16* __restrict__ mem0) {
  const int row = blockIdx.x * 8 + (threadIdx.x >> 5);
  ln_row_to_image(x, g_xn[0], row, threadIdx.x & 31);
  const int gt = blockIdx.x * 256 + threadIdx.x;
  const uint4 sent = make_uint4(SENT, SENT, SENT, SENT);
  uint4* mail = reinterpret_cast<uint4*>(&g_mail[0][0]);
  for (int i = gt; i < 2 * MAIL_BYTES / 16; i += 65536) mail[i] = sent;
  uint4* mb = reinterpret_cast<uint4*>(&g_mbuf[0][0]);
  for (int i = gt; i < NSTEP * 1280; i += 65536) {
    const int p = i % 1280, st = i / 1280;
    uint4 v = sent;
    if (st == 0 || (st == LAG && (p & 8))) v = *reinterpret_cast<const uint4*>(mem0 + (p & 7) * DM + (p >> 4) * 8);
    mb[i] = v;
  }
  if (gt < NSTEP * 192) reinterpret_cast<uint4*>(&g_flag[0][0])[gt] = gt < 192 ? make_uint4(0, 0, 0, 0) : sent;
  if (gt < CN_NUM) g_cnt[gt][0] = 0;
}

namespace C {
constexpr int NKR = 37;
constexpr int OFF_WQ = 0, OFF_WK = 81920;
constexpr int OFF_YO = 163840, OFF_YV = OFF_YO + 6144;
constexpr int OFF_M = 176128;
__host__ __device__ constexpr int og_off(int c) { return c ? OFF_M + 14336 + c * 2048 : 229376; }
constexpr int OFF_KT = 196608;
constexpr int OFF_XT = OFF_KT + 10240;
constexpr int OFF_VT = OFF_XT + 7168;
constexpr int OFF_XM = OFF_VT + 11392;
constexpr int KS = 1280, VS = 1408;
__host__ __device__ constexpr int slot_off(int p) { return p == 2 ? OFF_M : OFF_KT + (p % 3) * 16384; }
constexpr int OFF_BAR = 231552;
constexpr int OFF_SAFE = OFF_BAR + 160;
constexpr int OFF_TS = OFF_BAR + 256;
constexpr int SMEM = 232448;
constexpr uint32_t SB0 = 1024;
constexpr int BAR_F = OFF_BAR, BAR_E = OFF_BAR + 40, BAR_M = OFF_BAR + 80, BAR_MOK = OFF_BAR + 88, BAR_XM = OFF_BAR + 96, BAR_XF = OFF_BAR + 104,
              BAR_XT = OFF_BAR + 112, BAR_MF = OFF_BAR + 120, BAR_OG = OFF_BAR + 128, BAR_W = OFF_BAR + 136, FLG_REDO = OFF_BAR + 144;
constexpr int NB_PRO = 1, NB_RD = 2, NB_MR = 3, NB_QK = 4, NB_SM = 5, NB_VA = 6, NB_VQ = 7, NB_A = 8, NB_Q = 9, NB_C = 10, NB_WQ = 11, NB_QI = 12, NB_SI = 13, NB_WV = 14;
#define B1 300
#define B2 400
#define FLP 0
#define OSG 2
#define QIE 4
#define SIE 2
#define WOE 1
#define OGF 0
#define VSP 8
#define RFK 5
#define PFD 3
#define WOL 0
#define NOWORK 0
constexpr float SCL = 0.07216878364870322f * 1.4426950408889634f / 256;
}

#define CBAR_SYNC(id, n) bar_sync(id, n)
#define CBAR_ARRIVE(id, n) bar_arrive(id, n)

__device__ __forceinline__ uint64_t wdesc(int off) { return mkdesc(C::SB0 + off, 8192, 1024); }
__device__ __forceinline__ uint64_t mdesc(int k) { return mkdesc_ns(C::SB0 + C::OFF_M + k * 512, 256, 128); }
__device__ __forceinline__ uint64_t tdesc(int k) { return mkdesc(C::SB0 + C::slot_off(k >> 3) + ((k >> 2) & 1) * 1024 + (k & 3) * 32, 16, 2048); }

__device__ __forceinline__ int dh_row(int n) { return (n & ~63) + (n & 32) + ((n >> 1) & 3) * 8 + ((n >> 3) & 3) * 2 + (n & 1); }
template <bool PERM>
__device__ __forceinline__ void load_weights_rs(uint32_t (&wf)[C::NKR][4], uint32_t sb, int stage, int yoff, int tid0) {
  using namespace C;
  const int i = (tid0 >> 3) & 3, n0 = (tid0 & 7) + (i >> 1) * 8;
  const int chunk = 2 * ((tid0 >> 5) & 3) + (i & 1);
  const int r0 = PERM ? dh_row(n0) : n0, r1 = PERM ? dh_row(n0 + 16) : n0 + 16;
  const uint32_t a0 = sb + stage + r0 * 128 + ((chunk ^ (r0 & 7)) << 4), a1 = sb + stage + r1 * 128 + ((chunk ^ (r1 & 7)) << 4);
#pragma unroll
  for (int k = 0; k < NKR; k++) ldsm4t(wf[k], ((k & 1) ? a1 : a0) + (k >> 1) * 4096);
#pragma unroll
  for (int k = 0; k < 40 - NKR; k++) {
    const int n = (NKR + k) * 16 + ((tid0 & 127) >> 3), r = PERM ? dh_row(n) : n, c = tid0 & 7;
    sts128(sb + yoff + (n - NKR * 16) * 128 + ((c ^ (n & 7)) << 4), lds128(sb + stage + r * 128 + ((c ^ (r & 7)) << 4)));
  }
  fence_async();
  CBAR_SYNC(NB_PRO, 384);
}
template <int STRIDE>
__device__ __forceinline__ void store_mem(const float (&d)[8], uint32_t base, int tid) {
  const int m = (tid >> 3) & 3;
  stsm4(base + (((tid >> 5) & 3) * 2 + (m & 1)) * STRIDE + (m >> 1) * 640 + (tid & 7) * 16, pack_bf16(d[0], d[1]), pack_bf16(d[2], d[3]),
        pack_bf16(d[4], d[5]), pack_bf16(d[6], d[7]));
}

__device__ __forceinline__ void load_pair(uint32_t sb, int i, int p, uint32_t slot, uint32_t bar, uint32_t ph, int& spin) {
  using namespace C;
  const uint8_t* s0 = g_xn[0] + (size_t)i * 40960 + p * 8192;
  const uint8_t* s1 = g_xn[NOWORK ? 0 : 1] + (size_t)(i - LAG) * 40960 + p * 8192;
  const uint8_t* sa = pinp(i < NSEG ? s0 : s1);
  const uint8_t* sc = pinp(i >= LAG ? s1 : s0);
  const uint32_t dst = pin(sb + slot), fb = pin(sb + BAR_F + 8 * p);
  mwait(bar, ph, spin);
  bulk_g2s_mc(dst, sa, 8192, fb);
  bulk_g2s_mc(dst + 8192, sc, 8192, fb);
}
__device__ __forceinline__ void first_fill(uint32_t sb, int i, int rank, int& spin) {
  using namespace C;
  const int s1 = i - LAG;
  if (!NOWORK && s1 >= 0) { cwait(CN_X + s1, 32, spin); fence_async_all(); }
  load_pair(sb, i, rank, rank == 2 ? OFF_M : OFF_KT + rank * 16384, sb + BAR_E + 8 * rank, (i - 1) & 1, spin);
}
__device__ __forceinline__ void release_round(uint32_t sb, int p, int tid) {
  using namespace C;
  const int lane = tid & 31;
  if (p < 2) { if (lane == 0) mbar_arrive_cluster(mapa(sb, p) + BAR_E + 8 * (3 + p)); }
  else if (lane < 3) mbar_arrive_cluster(mapa(sb, lane) + BAR_MOK);
}

template <int K0, int K1>
__device__ __forceinline__ void v_mem_pass(float (&d)[8], const uint32_t (&wf)[C::NKR][4]) {
  using namespace C;
  wg_fence();
#pragma unroll
  for (int k = K0; k < K1; k++) {
    if (k < NKR) wgmma_rs16(d, wf[k < NKR ? k : 0], mdesc(k), k != 32);
    else wgmma_ts16(d, wdesc(OFF_YV + (k - NKR) * 2048), mdesc(k), 1);
  }
  wg_commit();
}
__device__ __forceinline__ void chain_v(const uint32_t sb, const int tid0, const int cta, const int rank) {
  using namespace C;
  asm volatile("setmaxnreg.inc.sync.aligned.u32 208;");
  int spin = 0;
  uint32_t wf[NKR][4];
  if (tid0 == 256) first_fill(sb, 0, rank, spin);
  __syncwarp();
  mwait(sb + BAR_W, 0, spin);
  for (int it = tid0 & 127; it < 1280; it += 128) {
    const uint32_t base = sb + OFF_WK + (it >> 1) * 128;
    const int sw = ((it >> 1) & 7) ^ ((it & 1) * 4);
    const uint4 u0 = lds128(base + (sw << 4)), u1 = lds128(base + ((sw ^ 1) << 4)), u2 = lds128(base + ((sw ^ 2) << 4)), u3 = lds128(base + ((sw ^ 3) << 4));
    sts128(base + (sw << 4), make_uint4(u0.x, u1.x, u2.x, u3.x)); sts128(base + ((sw ^ 1) << 4), make_uint4(u0.y, u1.y, u2.y, u3.y));
    sts128(base + ((sw ^ 2) << 4), make_uint4(u0.z, u1.z, u2.z, u3.z)); sts128(base + ((sw ^ 3) << 4), make_uint4(u0.w, u1.w, u2.w, u3.w));
  }
  bar_sync(NB_RD, 128);
  load_weights_rs<false>(wf, sb, OFF_WK, OFF_YV, tid0);
#pragma unroll 1
  for (int i = 0; i < NSTEP; i++) {
    {
      float d[32];
      if (i > 0) CBAR_SYNC(NB_WV, 256);
#pragma unroll
      for (int p = 0; p < 5; p++) {
        mwait(sb + BAR_F + 8 * p, i & 1, spin);
        TS(i, 25 + p);
        wg_fence();
#pragma unroll
        for (int k = 8 * p; k < 8 * p + 8; k++) {
          if (k < NKR) wgmma_rs64(d, wf[k < NKR ? k : 0], tdesc(k), k);
          else wgmma_ts64(d, wdesc(OFF_YV + (k - NKR) * 2048), tdesc(k), 1);
          if (k == 8 * p + 1 && p >= 1 && p <= 3) {
            wg_commit(); wg_wait<1>();
            release_round(sb, p - 1, fresh(tid0));
            wg_fence();
          }
          if (k == 8 * p + RFK && (p == 1 || p == 2)) {
            wg_commit();
            if (rank == p - 1 && tid0 == 256) load_pair(sb, i, p + 2, slot_off(p + 2), sb + BAR_E + 8 * (p + 2), i & 1, spin);
            __syncwarp();
            wg_fence();
          }
        }
        wg_commit();
      }
      wg_wait<0>();
      TS(i, 23);
      CBAR_SYNC(NB_RD, 256);
      const int tid = fresh(tid0) & 127, m = (tid >> 3) & 3;
      if (tid >= 96) {
        if (tid < 101) { if (i + 1 < NSTEP) mbar_expect_tx(sb + BAR_F + 8 * (tid - 96), 16384); }
        else if (tid == 101) mbar_expect_tx(sb + BAR_XM, 2560);
        else if (tid == 102) mbar_expect_tx(sb + BAR_XT, 7168);
        else if (tid == 103) mbar_expect_tx(sb + BAR_OG, 4096);
        else if (tid < 106) mbar_arrive_cluster(mapa(sb, (rank + tid - 103) % 3) + BAR_XF);
        __syncwarp();
      }
      const uint32_t a = sb + OFF_VT + 256 + ((tid >> 5) * 2 + (m & 1)) * VS + (m >> 1) * 128 + (tid & 7) * 16;
#pragma unroll
      for (int s = 0; s < 4; s++)
        stsm4(a + (s & 1) * 256 + (s >> 1) * 640, pack_bf16(d[8 * s], d[8 * s + 1]), pack_bf16(d[8 * s + 2], d[8 * s + 3]),
              pack_bf16(d[8 * s + 4], d[8 * s + 5]), pack_bf16(d[8 * s + 6], d[8 * s + 7]));
      if (tid < 72) sts128(sb + OFF_VT + (tid >> 3) * VS + (tid & 7) * 16, make_uint4(0, 0, 0, 0));
      fence_async();
    }
    mwait(sb + BAR_XF, i & 1, spin);
    CBAR_ARRIVE(NB_QK, 384);
    CBAR_SYNC(NB_QI, 256);
    float d[8];
    v_mem_pass<32, 40>(d, wf);
    CBAR_SYNC(NB_SM, 256);
    wg_wait<0>();
    if (__builtin_expect(lds32(sb + FLG_REDO), 0)) { v_mem_pass<32, 40>(d, wf); wg_wait<0>(); }
    if ((tid0 & 31) < 2) mbar_arrive_cluster(mapa(sb, (rank + 1 + (tid0 & 1)) % 3) + BAR_MF);
    v_mem_pass<0, 32>(d, wf);
    wg_wait<0>();
    TS(i, 24);
    const int tid = fresh(tid0);
    if ((tid & 31) == 0) mbar_arrive_cluster(mapa(sb, 2) + BAR_E + 16);
    store_mem<VS>(d, sb + OFF_VT + 128, tid);
    fence_async();
    CBAR_ARRIVE(NB_VA, 256);
    CBAR_ARRIVE(NB_VQ, 256);
    if (tid == 256) {
      if (i + 1 < NSTEP) { first_fill(sb, i + 1, rank, spin); TS1(i + 1, 37); }
    } else if (tid >= 288 && tid < 295) {
      const int lane = tid & 31, ip = i + PFD;
      if (cta < 80 && ip < NSTEP) {
        if (lane < 2) prefetch_l2(g_mbuf[ip] + (cta * 2 + lane) * 128);
        else if (lane == 6) { if (cta < 22) prefetch_l2(&g_flag[ip][cta * 32]); }
        else if (ip < NSEG) prefetch_l2(g_xn[0] + (size_t)ip * 40960 + (cta * 4 + lane - 2) * 128);
      }
    }
    TS_FLUSH(i - 1);
    __syncwarp();
  }
  if (spin >= SPIN_TOT) g_err = 3;
}

__device__ __forceinline__ float quad_max(float x) {
  const float a = __shfl_xor_sync(0xffffffffu, x, 1), b = __shfl_xor_sync(0xffffffffu, x, 2), c = __shfl_xor_sync(0xffffffffu, x, 3);
  return fmaxf(fmaxf(x, a), fmaxf(b, c));
}
__device__ __forceinline__ float quad_sum(float x) {
  const float a = __shfl_xor_sync(0xffffffffu, x, 1), b = __shfl_xor_sync(0xffffffffu, x, 2), c = __shfl_xor_sync(0xffffffffu, x, 3);
  return (x + a) + (b + c);
}
__device__ __forceinline__ float max10(const float (&y)[10]) {
  return fmaxf(fmaxf(fmaxf(fmaxf(y[0], y[1]), fmaxf(y[2], y[3])), fmaxf(fmaxf(y[4], y[5]), fmaxf(y[6], y[7]))), fmaxf(y[8], y[9]));
}
__device__ __forceinline__ float sum10(const float (&y)[10]) {
  return (((y[0] + y[1]) + (y[2] + y[3])) + ((y[4] + y[5]) + (y[6] + y[7]))) + (y[8] + y[9]);
}
__device__ __forceinline__ float rcp(float x) { float y; asm("rcp.approx.ftz.f32 %0,%1;" : "=f"(y) : "f"(x)); return y; }

__device__ __forceinline__ void signal_o(int i, int cta) { csignal(CN_O + i * 5 + min(cta / 19, 4)); }

__device__ __forceinline__ void chain_q(const CUtensorMap& tmWq, const CUtensorMap& tmWk, const uint32_t sb, const int tid0, const int cta, const int rank) {
  using namespace C;
  asm volatile("setmaxnreg.dec.sync.aligned.u32 96;");
  int spin = 0;
  CBAR_SYNC(NB_PRO, 384);
  PTS(5);
  if (tid0 == 128) {
    const int col = (cta / 3) * DH + rank * 64;
    mbar_expect_tx(sb + BAR_W, 163840);
    for (int i = 0; i < 5; i++) {
      tma2d(sb + OFF_WQ + i * 16384, &tmWq, col, i * 128, sb + BAR_W);
      tma2d(sb + OFF_WK + i * 16384, &tmWk, col, i * 128, sb + BAR_W);
    }
  }
  __syncwarp();
  mwait(sb + BAR_W, 1, spin);
  PTS(6);
#pragma unroll 1
  for (int i = 0; i < NSTEP; i++) {
    const int ph = i & 1;
    uint32_t qf[4][4];
    {
      float d[64];
#pragma unroll
      for (int p = 0; p < 5; p++) {
        mwait(sb + BAR_F + 8 * p, ph, spin);
        if (p == 0) TS(i, 0);
        wg_fence();
#pragma unroll
        for (int k = 8 * p; k < 8 * p + 8; k++) {
          wgmma_st128(d, tdesc(k), mkdesc(SB0 + OFF_WQ + k * 2048, OFF_WK - OFF_WQ, 1024), k);
          if (k == 8 * p + 1 && p >= 1 && p <= 3) {
            wg_commit(); wg_wait<1>();
            release_round(sb, p - 1, fresh(tid0));
            wg_fence();
          }
        }
        wg_commit();
      }
      wg_wait<0>();
      TS(i, 1);
      CBAR_SYNC(NB_RD, 256);
      TSB(i, 2);
      const int tid = fresh(tid0), w = (tid >> 5) & 3, m = (tid >> 3) & 3;
      const uint32_t a = sb + OFF_KT + (m >> 1) * KS + (1 + 5 * (w >> 1) + 2 * (w & 1) + (m & 1)) * 128 + (tid & 7) * 16;
#pragma unroll
      for (int s = 0; s < 4; s++)
        stsm4t(a + s * 2 * KS, pack_bf16(d[32 + 8 * s], d[33 + 8 * s]), pack_bf16(d[34 + 8 * s], d[35 + 8 * s]),
               pack_bf16(d[36 + 8 * s], d[37 + 8 * s]), pack_bf16(d[38 + 8 * s], d[39 + 8 * s]));
      fence_async();
      CBAR_ARRIVE(NB_QK, 384);
      if (OSG == 0) { if (tid == 224 && i > 0) signal_o(i - 1, cta); __syncwarp(); }
#pragma unroll
      for (int kk = 0; kk < 4; kk++)
#pragma unroll
        for (int j = 0; j < 4; j++) asm volatile("cvt.rn.bf16x2.f32 %0,%1,%2;" : "=r"(qf[kk][j]) : "f"(d[8 * kk + 2 * j + 1]), "f"(d[8 * kk + 2 * j]));
    }
    CBAR_SYNC(NB_SI, 256);
    uint32_t pf[5][4];
    float s0, s1;
    {
      float y0[10], y1[10];
      const int tid = fresh(tid0), lane = tid & 31, u = (tid >> 5) & 1;
      const bool c1 = tid & 64;
      {
        float x[40];
        wg_fence();
#pragma unroll
        for (int kk = 0; kk < 4; kk++) wgmma_rt80(x, qf[kk], mkdesc_ns(SB0 + OFF_KT + kk * 2 * KS, KS, 128), kk);
        wg_commit();
        wg_wait<0>();
#pragma unroll
        for (int j = 0; j < 5; j++) {
          y0[2 * j] = (c1 ? x[20 + 4 * j] : x[4 * j]) * SCL; y0[2 * j + 1] = (c1 ? x[21 + 4 * j] : x[4 * j + 1]) * SCL;
          y1[2 * j] = (c1 ? x[22 + 4 * j] : x[4 * j + 2]) * SCL; y1[2 * j + 1] = (c1 ? x[23 + 4 * j] : x[4 * j + 3]) * SCL;
        }
      }
      TS(i, 17);
      const uint32_t xo = OFF_XT + (c1 ? 1792 : 0) + u * 640 + lane * 16, x2 = xo + u * 512 + 512 - lane * 12;
      {
        const uint4 h0 = make_uint4(pack_h2(y0[0], y0[1]), pack_h2(y0[2], y0[3]), pack_h2(y1[0], y1[1]), pack_h2(y1[2], y1[3]));
        const uint4 h1 = make_uint4(pack_h2(y0[4], y0[5]), pack_h2(y0[6], y0[7]), pack_h2(y1[4], y1[5]), pack_h2(y1[6], y1[7]));
        const uint32_t h2 = u ? pack_h2(y1[8], y1[9]) : h1.z;
#pragma unroll
        for (int dd = 0; dd < 2; dd++) {
          const uint32_t rb = mapa(sb, (rank + 1 + dd) % 3), ro = rb + (1 - dd) * 3584;
          st_async4u(ro + xo, h0, rb + BAR_XT);
          if (u) st_async4u(ro + xo + 512, h1, rb + BAR_XT);
          st_async1u(ro + x2, h2, rb + BAR_XT);
        }
      }
      TS(i, 18);
      const int lim = 16 * u + (lane >> 2) + 8 - 2 * (lane & 3);
#pragma unroll
      for (int j = 1; j < 5; j++) {
        if (8 * j > lim) y0[2 * j] = -INFINITY;
        if (8 * j + 1 > lim) y0[2 * j + 1] = -INFINITY;
        if (8 * j - 8 > lim) y1[2 * j] = -INFINITY;
        if (8 * j - 7 > lim) y1[2 * j + 1] = -INFINITY;
      }
      mwait(sb + BAR_XT, ph, spin);
      TS(i, 19);
      {
        const uint4 u0 = lds128(sb + xo), v0 = lds128(sb + xo + 3584);
        const uint32_t u2 = lds32(sb + x2), v2 = lds32(sb + x2 + 3584);
        uint4 u1 = make_uint4(0, 0, u2, 0), v1 = make_uint4(0, 0, v2, 0);
        if (u) { u1 = lds128(sb + xo + 512); v1 = lds128(sb + xo + 512 + 3584); }
        __syncwarp();
        if (lane == 0) mbar_arrive_cluster(mapa(sb, 0) + BAR_E);
        add_h2(y0[0], y0[1], u0.x, v0.x); add_h2(y0[2], y0[3], u0.y, v0.y); add_h2(y1[0], y1[1], u0.z, v0.z); add_h2(y1[2], y1[3], u0.w, v0.w);
        add_h2(y0[4], y0[5], u1.x, v1.x); add_h2(y0[6], y0[7], u1.y, v1.y); add_h2(y1[4], y1[5], u1.z, v1.z); add_h2(y1[6], y1[7], u1.w, v1.w);
        add_h2(y1[8], y1[9], u2, v2);
      }
      y0[8] = y0[0]; y0[9] = y0[1];
      const float m0 = quad_max(max10(y0)) * -256.f, m1 = quad_max(max10(y1)) * -256.f;
      s0 = 0.f; s1 = 0.f;
#pragma unroll
      for (int j = 0; j < 5; j++) {
        const uint32_t p0 = j < 4 ? pack_bf16(ex2(fmaf(y0[2 * j], 256.f, m0)), ex2(fmaf(y0[2 * j + 1], 256.f, m0))) : 0u;
        const uint32_t p1 = pack_bf16(ex2(fmaf(y1[2 * j], 256.f, m1)), ex2(fmaf(y1[2 * j + 1], 256.f, m1)));
        s0 += bf_lo(p0) + bf_hi(p0); s1 += bf_lo(p1) + bf_hi(p1);
        pf[j >> 1][2 * (j & 1)] = c1 ? 0u : p0; pf[j >> 1][2 * (j & 1) + 1] = c1 ? 0u : p1;
        pf[(j + 5) >> 1][2 * ((j + 5) & 1)] = c1 ? p0 : 0u; pf[(j + 5) >> 1][2 * ((j + 5) & 1) + 1] = c1 ? p1 : 0u;
      }
    }
    CBAR_SYNC(NB_VQ, 256);
    TSB(i, 20);
    {
      float o[32];
      wg_fence();
#pragma unroll
      for (int q = 0; q < 5; q++) wgmma_rs64(o, pf[q], mkdesc_ns(SB0 + OFF_VT + 128 + q * 256, 128, VS), q);
      wg_commit();
      s0 = rcp(quad_sum(s0)); s1 = rcp(quad_sum(s1));
      const int tid = fresh(tid0), g = (tid >> 2) & 7, c = (tid >> 6) & 1, sg = i - c * LAG;
      uint8_t* op = pinp(&g_o[i % ORING][c][cta][(((tid >> 5) & 1) * 16 + g) * 128]);
      const uint32_t o0 = pin(((tid & 3) ^ g) << 4), live = pin(sg >= 0 && sg < NSEG);
      wg_wait<0>();
      TS(i, 21);
      if ((tid & 31) == 0) mbar_arrive_cluster(mapa(sb, 1) + BAR_E + 8);
      uint4 ov[4];
#pragma unroll
      for (int h = 0; h < 2; h++) {
        const float* x = o + 16 * h;
        ov[2 * h] = make_uint4(pin(pack_bf16(x[0] * s0, x[1] * s0)), pin(pack_bf16(x[4] * s0, x[5] * s0)), pin(pack_bf16(x[8] * s0, x[9] * s0)), pin(pack_bf16(x[12] * s0, x[13] * s0)));
        ov[2 * h + 1] = make_uint4(pin(pack_bf16(x[2] * s1, x[3] * s1)), pin(pack_bf16(x[6] * s1, x[7] * s1)), pin(pack_bf16(x[10] * s1, x[11] * s1)), pin(pack_bf16(x[14] * s1, x[15] * s1)));
      }
      TS(i, 22);
      if (i + 1 < NSTEP) CBAR_SYNC(NB_WQ, 256);
      if (live) {
#pragma unroll
        for (int h = 0; h < 4; h++) *reinterpret_cast<uint4*>(op + (h & 1) * 1024 + (o0 ^ ((h >> 1) * 64))) = ov[h];
      }
      if (OSG && i + 1 < NSTEP) CBAR_ARRIVE(NB_MR, 160);
    }
  }
  CBAR_SYNC(NB_Q, 128);
  if (tid0 == 224) signal_o(NSTEP - 1, cta);
  if (spin >= SPIN_TOT) g_err = 2;
}

template <int NL>
__device__ __forceinline__ void poll_add(const uint8_t* mb, uint32_t tag, float (&f)[8], uint32_t* flag, int osig, int& n, int& spin) {
  uint4 x[NL];
#pragma unroll
  for (int i = 0; i < NL; i++) x[i] = ld_relaxed128(mb + i * 512);
  if (OSG == 1 && osig >= 0) csignal(osig);
  while (true) {
    bool bad = false;
#pragma unroll
    for (int i = 0; i < NL; i++)
      if (((x[i].x ^ tag) | (NL == 6 ? x[i].z ^ tag : 0u)) & 1) { bad = true; x[i] = ld_relaxed128(mb + i * 512); }
    n++;
    spin += 16;
    if (!__any_sync(0xffffffffu, bad && spin < SPIN_TOT)) break;
  }
  if (FLP == 0 && flag) st_relaxed(flag, 0);
#pragma unroll
  for (int i = 0; i < NL; i++) {
    const uint32_t u[4] = {x[i].x, x[i].y, x[i].z, x[i].w};
#pragma unroll
    for (int j = 0; j < 4; j++) {
      if (i == 0) { f[2 * j] = bf_lo(u[j]); f[2 * j + 1] = bf_hi(u[j]); }
      else { f[2 * j] += bf_lo(u[j]); f[2 * j + 1] += bf_hi(u[j]); }
    }
  }
}

template <int B, int SLOT>
__device__ __forceinline__ void wo_block(float (&acc)[8], const uint32_t (&wf)[C::NKR][4]) {
  using namespace C;
#pragma unroll
  for (int kk = 0; kk < 4; kk++) {
    const int k = 4 * B + kk;
    const uint64_t db = mkdesc_ns(SB0 + og_off(SLOT) + kk * 512, 256, 128);
    if (k < NKR) wgmma_rt16(acc, wf[k < NKR ? k : 0], db, SLOT | kk);
    else wgmma_tt16(acc, wdesc(OFF_YO + (k - NKR) * 2048), db, 1);
  }
}

__device__ __forceinline__ void chain_a(const uint32_t sb, const int tid0, const int cta, const int rank) {
  using namespace C;
  asm volatile("setmaxnreg.inc.sync.aligned.u32 200;");
  int spin = 0;
  uint32_t wf[NKR][4];
  mwait(sb + BAR_W, 0, spin);
  permute_cols(sb + OFF_WQ, tid0);
  CBAR_SYNC(NB_A, 128);
  load_weights_rs<true>(wf, sb, OFF_WQ, OFF_YO, tid0);

#pragma unroll 1
  for (int i = -1; i < NSTEP; i++) {
    const int ph = i & 1;
    if (i >= 0) {
      if (i == 0) mwait(sb + BAR_W, 1, spin);
      mwait(sb + BAR_M, ph, spin);
      TS(i, 3);
      {
        float x[20];
        int redo = 0;
      retry:
        bool bad;
        {
          float dq[8], dk[8];
          wg_fence();
#pragma unroll
          for (int k = 0; k < 40; k++) wgmma_ts16(dq, wdesc(OFF_WQ + k * 2048), mdesc(k), k);
          wg_commit();
#pragma unroll
          for (int k = 0; k < 40; k++) {
            if (k == 40 - QIE && !redo) CBAR_ARRIVE(NB_QI, 256);
            wgmma_ts16(dk, wdesc(OFF_WK + k * 2048), mdesc(k), k);
          }
          wg_commit();
          const int m = (tid0 >> 3) & 3, dg = (tid0 >> 5) * 2 + (m & 1);
          const uint32_t ka = sb + OFF_KT + dg * KS + (m >> 1) * 640 + (tid0 & 7) * 16;
          wg_wait<1>();
          const float chk = (dq[0] + dq[1]) + (dq[4] + dq[5]);
          const uint32_t q0 = pack_bf16(dq[0], dq[1]), q1 = pack_bf16(dq[2], dq[3]), q2 = pack_bf16(dq[4], dq[5]), q3 = pack_bf16(dq[6], dq[7]);
          if (!redo) CBAR_SYNC(NB_QK, 384);
          stsm4(ka + dg * (VS - KS) + (OFF_VT + 128 - OFF_KT), q0, q1, q2, q3);
          sts32(sb + FLG_REDO, redo);
          wg_wait<0>();
          TS(i, 4);
          stsm4(ka, pack_bf16(dk[0], dk[1]), pack_bf16(dk[2], dk[3]), pack_bf16(dk[4], dk[5]), pack_bf16(dk[6], dk[7]));
          fence_async();
          bad = bar_red_or(NB_C, 128, chk != chk && !redo);
        }
        TSB(i, 5);
        wg_fence();
#pragma unroll
        for (int kk = 0; kk < 4; kk++) wgmma_tt40(x, mkdesc_ns(SB0 + OFF_VT + 128 + kk * 2 * VS, VS, 640), mkdesc_ns(SB0 + OFF_KT + kk * 2 * KS, KS, 128), kk);
#pragma unroll
        for (int kk = 0; kk < 4; kk++) {
          if (kk == 4 - SIE && !bad) CBAR_ARRIVE(NB_SI, 256);
          wgmma_tt40(x, mkdesc_ns(SB0 + OFF_VT + kk * 2 * VS, VS, 384), mkdesc_ns(SB0 + OFF_KT + 640 + kk * 2 * KS, KS, 128), 1);
        }
        wg_commit();
        if (__builtin_expect(bad, 0)) {
          wg_wait<0>();
#pragma unroll 1
          for (int k = 0; k < 10; k++) {
            uint4 v = lds128(sb + OFF_M + tid0 * 16 + k * 2048);
            if (v.x == SENT || v.y == SENT || v.z == SENT || v.w == SENT) {
              do { v = ld_relaxed4(g_mbuf[i] + tid0 * 16 + k * 2048); spin += 16; } while ((v.x == SENT || v.y == SENT || v.z == SENT || v.w == SENT) && spin < SPIN_TOT);
              sts128(sb + OFF_M + tid0 * 16 + k * 2048, v);
            }
          }
          fence_async();
          bar_sync(NB_C, 128);
          redo = fresh(1);
          goto retry;
        }
        TSV(i, 36, redo);
        const int tid = fresh(tid0), lane = tid & 31, w = tid >> 5;
        const uint32_t xo = OFF_XM + w * 1280 + lane * 16, x1 = OFF_XM + w * 1280 + lane * 4;
        const uint32_t rb1 = mapa(sb, (rank + 1) % 3), rb2 = mapa(sb, (rank + 2) % 3);
        const uint32_t ra = pin(rb1 + xo + 640), rb = pin(rb1 + x1 + 1152), rc = pin(rb2 + xo), rd = pin(rb2 + x1 + 512);
        const uint32_t la = pin(sb + xo), lb = pin(sb + x1);
        const uint32_t pa = pin(sb + OFF_XM + w * 1280 + (lane & 7) * 4 + (lane & 8) * 8 + (lane & 16) * 2);
        wg_wait<0>();
        TS(i, 6);
        if (w < 2) {
          float y[10];
#pragma unroll
          for (int j = 0; j < 5; j++) { y[2 * j] = x[4 * j] * SCL; y[2 * j + 1] = x[4 * j + 1] * SCL; }
          const uint4 h0 = make_uint4(pack_h2(y[0], y[1]), pack_h2(y[2], y[3]), pack_h2(y[4], y[5]), pack_h2(y[6], y[7]));
          const uint32_t h1 = pack_h2(y[8], y[9]);
          st_async4u(ra, h0, rb1 + BAR_XM);
          st_async4u(rc, h0, rb2 + BAR_XM);
          st_async1u(rb, h1, rb1 + BAR_XM);
          st_async1u(rd, h1, rb2 + BAR_XM);
          CBAR_ARRIVE(NB_SM, 256);
          if (lane == 0) mbar_arrive_cluster(mapa(sb, 0) + BAR_E);
          TS(i, 7);
          mwait(sb + BAR_XM, ph, spin);
          TS(i, 8);
          const uint4 u0 = lds128(la), v0 = lds128(la + 640);
          const uint32_t u1 = lds32(lb + 512), v1 = lds32(lb + 1152);
          add_h2(y[0], y[1], u0.x, v0.x); add_h2(y[2], y[3], u0.y, v0.y); add_h2(y[4], y[5], u0.z, v0.z); add_h2(y[6], y[7], u0.w, v0.w);
          add_h2(y[8], y[9], u1, v1);
          const float mx = quad_max(max10(y)) * -256.f;
          sts32(pa + 640, 0);
#pragma unroll
          for (int j = 0; j < 5; j++) {
            y[2 * j] = ex2(fmaf(y[2 * j], 256.f, mx)); y[2 * j + 1] = ex2(fmaf(y[2 * j + 1], 256.f, mx));
            sts32(pa + j * 128, pack_bf16(y[2 * j], y[2 * j + 1]));
          }
          sts32(pa + 768, __float_as_uint(sum10(y)));
          fence_async();
          TS(i, 9);
        } else {
          CBAR_ARRIVE(NB_SM, 256);
          if (lane == 0) mbar_arrive_cluster(mapa(sb, 0) + BAR_E);
          mwait(sb + BAR_MF, ph, spin);
        }
      }
      CBAR_SYNC(NB_VA, 256);
      TSB(i, 10);
      {
        float o[2][4];
        wg_fence();
#pragma unroll
        for (int c = 0; c < 2; c++)
#pragma unroll
          for (int q = 0; q < 3; q++)
            wgmma_ss8(o[c], mkdesc_ns(SB0 + OFF_VT + 128 + c * 640 + q * 256, 128, VS), mkdesc_ns(SB0 + OFF_XM + c * 1280 + q * 256, 128, 128), q);
        wg_commit();
        const int tid = fresh(tid0);
        const float4 e = lds128f(sb + OFF_XM + 768 + (tid & 3) * 32 + (tid & 4) * 4 + (tid & 8) * 160);
        const uint32_t oo = (tid >> 5) * 512 + (tid & 2) * 64 + ((tid & 31) >> 2) * 16 + (tid & 1) * 8;
        const uint32_t rb1 = mapa(sb, (rank + 1) % 3), rb2 = mapa(sb, (rank + 2) % 3);
        const uint32_t ra = pin(rb1 + oo + og_off(2)), rc = pin(rb2 + oo + og_off(1)), la = pin(sb + oo + og_off(0));
        const float inv = rcp((e.x + e.y) + (e.z + e.w));
        const float i0 = __shfl_sync(0xffffffffu, inv, tid & 3), i1 = __shfl_sync(0xffffffffu, inv, (tid & 3) + 4);
        const float i2 = __shfl_sync(0xffffffffu, inv, (tid & 3) + 8), i3 = __shfl_sync(0xffffffffu, inv, (tid & 3) + 12);
        wg_wait<0>();
        TS(i, 11);
        const uint32_t p0 = pack_bf16(o[0][0] * i0, o[0][1] * i1), p1 = pack_bf16(o[1][0] * i2, o[1][1] * i3);
        const uint32_t p2 = pack_bf16(o[0][2] * i0, o[0][3] * i1), p3 = pack_bf16(o[1][2] * i2, o[1][3] * i3);
        if (OGF) { sts64(la, p0, p1); sts64(la + 256, p2, p3); fence_async(); }
        st_async2u(ra, p0, p1, rb1 + BAR_OG);
        st_async2u(rc, p0, p1, rb2 + BAR_OG);
        st_async2u(ra + 256, p2, p3, rb1 + BAR_OG);
        st_async2u(rc + 256, p2, p3, rb2 + BAR_OG);
        if (!OGF) { sts64(la, p0, p1); sts64(la + 256, p2, p3); fence_async(); }
      }
      if (i + 1 >= NSTEP) { mwait(sb + BAR_OG, ph, spin); break; }
      CBAR_SYNC(NB_A, 128);
      TSB(i, 12);
      {
        float acc[3][8];
        wg_fence();
        wo_block<0, 0>(acc[2], wf);
        wg_commit();
        wo_block<1, 0>(acc[0], wf);
        wo_block<4, 0>(acc[1], wf);
        wg_commit();
        const int tid = fresh(tid0), w = tid >> 5, g = (tid & 31) >> 2, t = tid & 3;
        if ((tid & 31) == 0) mbar_arrive_cluster(mapa(sb, 1) + BAR_E + 8);
        const uint32_t tag = (i >> 1) & 1, radd = tag ? 0u : 0x10000u;
#define TAGGED(LO, HI) __byte_perm(((__float_as_uint(LO) + radd) & 0xFFFE0000u) | (tag << 16), pack_bf16(0.f, HI), 0x7632)
#define SEND(PTR, U) st_relaxed128((PTR), TAGGED(acc[U][0], acc[U][2]), pack_bf16(acc[U][1], acc[U][3]), pack_bf16(acc[U][4], acc[U][6]), pack_bf16(acc[U][5], acc[U][7]))
        uint8_t* m9 = pinp(g_mail[ph] + MAIL9 + (((2 * w + (g >> 2)) * 2 + (t & 1)) * 4 + (t & 2)) * 3072 + cta * 32 + (g & 3) * 8);
        wg_wait<1>();
        const uint32_t n0 = pin(TAGGED(acc[2][0], acc[2][2])), n1 = pin(pack_bf16(acc[2][1], acc[2][3]));
        const uint32_t n2 = pin(TAGGED(acc[2][4], acc[2][6])), n3 = pin(pack_bf16(acc[2][5], acc[2][7]));
        wg_fence();
        wo_block<7, 0>(acc[2], wf);
        wg_commit();
        st_relaxed64(m9, n0, n1);
        st_relaxed64(m9 + 3072, n2, n3);
        uint8_t* mb = pinp(g_mail[ph] + (((rank * 12 + w) * 2 + (g >> 2)) * 4 + t) * 2048 + (cta / 3) * 64 + (g & 3) * 16);
        mwait(sb + BAR_OG, ph, spin);
        asm volatile("fence.proxy.async::generic.acquire.sync_restrict::shared::cluster.cluster;" ::: "memory");
        TS(i, 13);
        wg_fence();
        wo_block<2, 1>(acc[0], wf); wo_block<3, 2>(acc[0], wf);
        wg_commit();
        wo_block<5, 1>(acc[1], wf); wo_block<6, 2>(acc[1], wf);
        wg_commit();
        wg_wait<1>(); SEND(mb, 0);
        wg_fence();
        wo_block<8, 1>(acc[2], wf); wo_block<9, 2>(acc[2], wf);
        wg_commit();
        if (WOE == 0) { CBAR_ARRIVE(NB_WV, 256); CBAR_ARRIVE(NB_WQ, 256); }
        wg_wait<1>(); SEND(mb + 32 * 2048, 1);
        if (WOE == 1) CBAR_ARRIVE(NB_WV, 256);
        wg_wait<0>(); SEND(mb + 64 * 2048, 2);
        if (WOE == 2) CBAR_ARRIVE(NB_WV, 256);
        if (WOE >= 1) CBAR_ARRIVE(NB_WQ, 256);
#undef SEND
#undef TAGGED
      }
      TS(i, 14);
    }
    const uint32_t t0 = clk32();
    uint32_t t1 = t0;
    if (i >= 0) {
      const int tid = fresh(tid0), lane = tid & 31;
      const uint32_t tag = (i >> 1) & 1;
      const bool t9 = cta >= 72 && cta < 88;
      const int w = tid >> 5, j = lane >> 3;
      const uint32_t pub = pin((lane & (t9 ? 6 : 4)) == 0 && !(((t9 ? cta : w) & 1) && i + 1 == LAG) && cta < 88);
      uint8_t* dst = pinp(g_mbuf[i + 1] + (t9 ? (cta + 72) * 128 + w * 32 + (j & 1) * 16 + (lane & 1) * 8 + (j >> 1) * 4
                                               : cta * 256 + (w & 1) * 128 + (w >> 1) * 64 + j * 16 + (lane & 3) * 4));
      uint32_t* flag = pinp(lane == 0 && cta < 88 ? &g_flag[i + 1][cta * 8 + w] : nullptr);
      float f[8];
      int n = 0;
      if (OSG && w == 3) CBAR_SYNC(NB_MR, 160);
      const int osig = tid == 96 ? CN_O + i * 5 + min(cta / 19, 4) : -1;
      while (clk32() - t0 < B1) {}
      TS(i + 1, 30);
      if (!t9) poll_add<4>(g_mail[ph] + (cta < 72 ? cta : cta - 24) * 8192 + (tid >> 5) * 2048 + lane * 16, tag, f, flag, osig, n, spin);
      else poll_add<6>(g_mail[ph] + MAIL9 + (cta - 72) * 12288 + (tid >> 5) * 3072 + lane * 16, tag, f, flag, osig, n, spin);
      if (FLP == 1 && flag) st_relaxed(flag, __float_as_uint(f[0] + f[7]) >> 1);
      t1 = clk32();
      TS(i + 1, 31); TSV(i + 1, 32, n);
      const bool h = lane & 16, q = lane & 8;
#pragma unroll
      for (int j = 0; j < 4; j++) f[j] = (h ? f[4 + j] : f[j]) + __shfl_xor_sync(0xffffffffu, h ? f[j] : f[4 + j], 16);
#pragma unroll
      for (int j = 0; j < 2; j++) f[j] = (q ? f[2 + j] : f[j]) + __shfl_xor_sync(0xffffffffu, q ? f[j] : f[2 + j], 8);
      f[0] += __shfl_xor_sync(0xffffffffu, f[0], 4); f[1] += __shfl_xor_sync(0xffffffffu, f[1], 4);
      if (t9) { f[0] += __shfl_xor_sync(0xffffffffu, f[0], 2); f[1] += __shfl_xor_sync(0xffffffffu, f[1], 2); }
      if (pub) st_relaxed(dst, pack_bf16(f[0], f[1]));
      if (FLP == 2 && flag) st_relaxed(flag, 0);
      if (OSG == 2 && osig >= 0) csignal(osig);
      TS(i + 1, 15);
    }
    if (tid0 < 32) {
      const uint8_t* src = pinp(g_mbuf[i + 1] + rank * 7168);
      const uint32_t* pp = pinp(&g_flag[i + 1][(rank * 28 + (tid0 < 28 || rank == 2 ? tid0 : 0)) * 8]);
      const uint32_t dst = pin(sb + OFF_M + rank * 7168), len = pin(rank == 2 ? 6144 : 7168);
      if (tid0 == 0) mbar_expect_tx(sb + BAR_M, 20480);
      while (clk32() - t1 < B2) {}
      TS(i + 1, 16);
      int n = 0;
      uint4 x;
      do { x = ld_relaxed4(pp); n++; spin += 16; } while (__any_sync(0xffffffffu, (int)(x.x | x.y | x.z | x.w) < 0 && spin < SPIN_TOT));
      TSV(i + 1, 35, n);
      TS(i + 1, 34);
      mwait(sb + BAR_MOK, ph ^ 1, spin);
      if (tid0 == 0) bulk_g2s_mc(dst, src, len, sb + BAR_M);
      TS(i + 1, 33);
      __syncwarp();
    }
  }
  if (spin >= SPIN_TOT) g_err = 1;
}

__global__ void __cluster_dims__(3, 1, 1) __launch_bounds__(384, 1)
k_chain(const __grid_constant__ CUtensorMap tmWq, const __grid_constant__ CUtensorMap tmWk,
        const __grid_constant__ CUtensorMap tmWv, const __grid_constant__ CUtensorMap tmWo) {
  using namespace C;
  extern __shared__ __align__(1024) uint8_t smem[];
  const uint32_t sb = smem_u32(smem);
  const int tid = threadIdx.x;
  const int wg = __shfl_sync(0xffffffffu, tid >> 7, 0);
  const int cta = blockIdx.x, rank = cta % 3;

  asm volatile("griddepcontrol.launch_dependents;");
  if (tid == 0) {
    if ((sb & 0xFFFFFF) != SB0) g_err = 100;
    for (int p = 0; p < 5; p++) { mbar_init(sb + BAR_F + 8 * p, 1); mbar_init(sb + BAR_E + 8 * p, p == 2 ? 12 : 24); }
    mbar_init(sb + BAR_M, 1); mbar_init(sb + BAR_MOK, 24); mbar_init(sb + BAR_XM, 1); mbar_init(sb + BAR_XF, 2);
    mbar_init(sb + BAR_XT, 1); mbar_init(sb + BAR_MF, 8); mbar_init(sb + BAR_OG, 1); mbar_init(sb + BAR_W, 1);
    for (int p = 0; p < 5; p++) mbar_expect_tx(sb + BAR_F + 8 * p, 16384);
    for (int p = 0; p < 16; p++) sts32(sb + OFF_SAFE + 4 * p, 0);
    asm volatile("fence.mbarrier_init.release.cluster;" ::: "memory");
    fence_async();
    mbar_expect_tx(sb + BAR_W, 163840);
    const int head = cta / 3, col = head * DH + rank * 64;
    tma2d(sb + OFF_WQ, &tmWo, 576, col, sb + BAR_W);
    for (int i = 0; i < 9; i++) tma2d(sb + OFF_WQ + (i + 1) * 8192, &tmWo, (3 * rank + i / 3) * 64, head * DH + ((rank + i) % 3) * 64, sb + BAR_W);
    for (int i = 0; i < 5; i++) tma2d(sb + OFF_WK + i * 16384, &tmWv, col, i * 128, sb + BAR_W);
  }
  __syncthreads();
  asm volatile("barrier.cluster.arrive.release.aligned;" ::: "memory");
  asm volatile("barrier.cluster.wait.acquire.aligned;" ::: "memory");

  if (wg == 0) chain_a(sb, keep(tid), cta, rank);
  else if (wg == 1) chain_q(tmWq, tmWk, sb, keep(tid), cta, rank);
  else chain_v(sb, keep(tid), cta, rank);
  asm volatile("barrier.cluster.arrive.release.aligned;" ::: "memory");
  asm volatile("barrier.cluster.wait.acquire.aligned;" ::: "memory");
}

namespace W {
constexpr int NP = 25, NBC = 11, NW = NP + NBC;
constexpr int OFF_W = 0;
constexpr int OFF_R = 163840;
constexpr int COL = 976;
constexpr int OFF_Q = OFF_R + 40960, OFF_KV = OFF_Q + 4 * COL;
constexpr int OFF_BAR = OFF_KV + 24 * COL;
constexpr int OFF_SAFE = OFF_BAR + 192;
constexpr int SMEM = 232448;
constexpr uint32_t SB0 = 1024;
constexpr int BAR_F = OFF_BAR, BAR_E = OFF_BAR + 40, BAR_W = OFF_BAR + 80, JOB = OFF_BAR + 96, BAR_J = OFF_BAR + 104, BAR_G = OFF_BAR + 112, RDY = OFF_BAR + 152;
constexpr int NB_G0 = 1, NB_SG = 3, NB_ST = 4, NB_SF = 5, NB_AS = 7;
}
#define WBAR_SYNC(id, n) bar_sync(id, n)
#define WBAR_ARRIVE(id, n) bar_arrive(id, n)

__device__ __forceinline__ uint64_t rdesc(int st, int k) { return mkdesc(W::SB0 + W::OFF_R + st * 8192 + (k >> 2) * 4096 + (k & 3) * 32, 16, 1024); }
__device__ __forceinline__ void load_frags40(uint32_t (&wf)[40][4], uint32_t base, int tid) {
  const int i = (tid >> 3) & 3, r = tid & 7;
  const uint32_t a0 = base + (r + (i >> 1) * 8) * 128 + (((2 * ((tid >> 5) & 3) + (i & 1)) ^ r) << 4);
#pragma unroll
  for (int k = 0; k < 40; k++) ldsm4t(wf[k], a0 + k * 2048);
}
__device__ __forceinline__ void red_tile(const float (&d)[16], int seg, int col0, int tid) {
  float* p = g_x + (size_t)(seg * 32 + 2 * (tid & 3)) * DM + col0 + ((tid >> 5) & 3) * 16 + ((tid >> 2) & 7) * 2;
#pragma unroll
  for (int j = 0; j < 8; j++)
    asm volatile("red.relaxed.gpu.global.add.v2.f32 [%0],{%1,%2};" ::"l"(p + ((j >> 1) * 8 + (j & 1)) * DM), "f"(d[4 * (j >> 1) + (j & 1)]), "f"(d[4 * (j >> 1) + 2 + (j & 1)]) : "memory");
}

#define FOR_P_JOBS(k, l, s)                               \
  for (int j_ = 0; j_ < 2 * NSTEP; j_++) {                \
    const int k = j_ >> 1, l = j_ & 1, s = k - l * LAG;   \
    if (s < 0 || s >= NSEG) continue;
__device__ __forceinline__ int next_job(int j) {
  j++;
  if (j < 2 * LAG) j += j & 1;
  else if (j >= 2 * NSEG) j |= j < 2 * NSTEP;
  return j;
}
__device__ __forceinline__ int job_index(int j) { return (j >> 1) + (j & 1) * (64 - LAG); }

template <int WG>
__device__ __forceinline__ void work_p(const CUtensorMap& tmWo, uint32_t sb, int pc, int tid0) {
  using namespace W;
  asm volatile("setmaxnreg.inc.sync.aligned.u32 208;");
  int spin = 0;
  const int ks = pc / 5, col0 = (pc % 5) * 128 + WG * 64;
  const uint32_t wb = sb + OFF_W + WG * 81920;
  uint32_t wf[40][4];
#pragma unroll 1
  for (int hf = 0; hf < 2; hf++) {
    if ((tid0 & 127) == 0) {
      mbar_expect_tx(sb + BAR_W + 8 * WG, 81920);
      for (int i = 0; i < 10; i++) tma2d(wb + i * 8192, &tmWo, col0, (ks * 19 + 2 * i + hf) * 64, sb + BAR_W + 8 * WG);
    }
    __syncwarp();
    mwait(sb + BAR_W + 8 * WG, hf, spin);
    permute_cols(wb, tid0 & 127);
    if (hf == 1 && ks < 4) for (int it = 2304 + (tid0 & 127); it < 2560; it += 128) {
      const uint32_t a = wb + (it >> 2) * 128 + (((2 * (it & 3)) ^ ((it >> 2) & 6)) << 4);
      sts128(a, make_uint4(0, 0, 0, 0)); sts128(a + 16, make_uint4(0, 0, 0, 0));
    }
    fence_async();
    WBAR_SYNC(NB_G0 + WG, 128);
    if (hf == 0) {
      load_frags40(wf, wb, tid0);
      fence_async();
      WBAR_SYNC(NB_G0 + WG, 128);
    }
  }
  FOR_P_JOBS(k_, l, s)
    float d[16];
#pragma unroll
    for (int f = 0; f < 10; f++) {
      mwait(sb + BAR_F + 8 * (f % 5), f / 5, spin);
      if (f == 0 && WG == 0 && pc == WW) WTS(l, s, 1);
      wg_fence();
#pragma unroll
      for (int kk = 0; kk < 4; kk++) {
        wgmma_rs32(d, wf[4 * f + kk], rdesc(f % 5, kk), f | kk);
        wgmma_ts32(d, mkdesc(SB0 + OFF_W + WG * 81920 + (4 * f + kk) * 2048, 8192, 1024), rdesc(f % 5, 4 + kk), 1);
      }
      wg_commit();
      if (f > 0) {
        wg_wait<1>();
        if ((tid0 & 31) == 0) mbar_arrive(sb + BAR_E + 8 * ((f - 1) % 5));
      }
    }
    wg_wait<0>();
    if ((tid0 & 31) == 0) mbar_arrive(sb + BAR_E + 32);
    if (WG == 0 && pc == WW) WTS(l, s, 2);
    red_tile(d, s, col0, tid0);
    WBAR_SYNC(NB_SG, 288);
  }
  if (spin >= SPIN_TOT) g_err = 11;
}
__device__ __forceinline__ void work_p_producer(uint32_t sb, int pc) {
  using namespace W;
  int spin = 0;
  const int ks = pc / 5;
  FOR_P_JOBS(k, l, s)
    if (l == 0 || k >= NSEG) { cwait(CN_O + k * 5 + ks, ks == 4 ? 20 : 19, spin); fence_async_all(); }
    if (pc == WW) WTS1(l, s, 0);
    const uint8_t* src = &g_o[k % ORING][l][ks * 19][0];
#pragma unroll
    for (int f = 0; f < 10; f++) {
      const int st = f < 5 ? f : f - 5;
      const uint32_t len = f == 9 && ks < 4 ? 4096 : 8192;
      mwait(sb + BAR_E + 8 * st, f < 5, spin);
      mbar_expect_tx(sb + BAR_F + 8 * st, len);
      bulk_g2s(sb + OFF_R + st * 8192, src + f * 8192, len, sb + BAR_F + 8 * st);
    }
  }
  if (spin >= SPIN_TOT) g_err = 12;
}
__device__ __forceinline__ float warp_sum(float x) {
  x = quad_sum(x);
  const float a = __shfl_xor_sync(0xffffffffu, x, 4), b = __shfl_xor_sync(0xffffffffu, x, 8), c = __shfl_xor_sync(0xffffffffu, x, 12);
  x = (x + a) + (b + c);
  return x + __shfl_xor_sync(0xffffffffu, x, 16);
}
__device__ __forceinline__ void work_ln(int kind, int r, int lane, bf16* out) {
  int spin = 0;
  const int l = kind & 1;
  const int rp = kind < 2 ? (r & 1) * 16 + (r >> 1) : r;
  const uint32_t sw = ((((lane >> 1) & 7) ^ (rp & 7)) << 4) + (lane & 1) * 8;
  uint8_t* dst = kind < 2 ? g_xnb[l] + (lane >> 4) * 4096 + rp * 128 + sw
               : kind == 2 ? g_xn[1] + (r >> 3) * 2048 + (lane >> 4) * 1024 + (r & 7) * 128 + sw
                           : reinterpret_cast<uint8_t*>(out) + r * 1280 + lane * 8;
  const int dm = kind == 3 ? 256 : 8192;
#pragma unroll 1
  for (int s = 0; s < NSEG; s++) {
    const float* xr = g_x + (size_t)(s * 32 + r) * DM;
    if (kind == 0 && lane < 20 && s + 3 < NSEG) prefetch_l2(xr + 96 * DM + lane * 32);
    if (lane == 0) cwait((kind < 2 ? CN_P : CN_W) + l * 64 + s, kind < 2 ? W::NP : 10, spin);
    __syncwarp();
    if (r == 0 && lane == 0) WTS1(l, s, kind < 2 ? 3 : 11);
    float4 v[5];
#pragma unroll
    for (int m = 0; m < 5; m++) v[m] = ld_relaxed4f(xr + m * 128 + lane * 4);
    if (kind < 3) {
      float t = 0.f;
#pragma unroll
      for (int m = 0; m < 5; m++) t += (v[m].x + v[m].y) + (v[m].z + v[m].w);
      const float mean = warp_sum(t) * (1.f / DM);
      float q0 = 0.f, q1 = 0.f;
#pragma unroll
      for (int m = 0; m < 5; m++) {
        v[m].x -= mean; v[m].y -= mean; v[m].z -= mean; v[m].w -= mean;
        q0 += v[m].x * v[m].x + v[m].y * v[m].y; q1 += v[m].z * v[m].z + v[m].w * v[m].w;
      }
      const float rs = rsqrtf(warp_sum(q0 + q1) * (1.f / DM) + 1e-5f);
#pragma unroll
      for (int m = 0; m < 5; m++) { v[m].x *= rs; v[m].y *= rs; v[m].z *= rs; v[m].w *= rs; }
    }
#pragma unroll
    for (int m = 0; m < 5; m++) *reinterpret_cast<uint2*>(dst + (size_t)s * 40960 + m * dm) = make_uint2(pack_bf16(v[m].x, v[m].y), pack_bf16(v[m].z, v[m].w));
    __syncwarp();
    if (r == 0 && lane == 0) WTS1(l, s, kind < 2 ? 4 : 12);
    if (lane == 0 && kind < 3) csignal(kind < 2 ? CN_L + l * 64 + s : CN_X + s);
  }
  if (spin >= SPIN_TOT) g_err = 13;
}

__device__ __forceinline__ void stage_qkv(const bf16* wqkv, uint32_t base, int T, int bc, int tid) {
  const int q = tid & 15;
  const bool ok = q < 15 && bc * 60 + 4 * q < DM;
  const bf16* src = wqkv + T * DM + bc * 60 + 4 * q;
#pragma unroll 1
  for (int k0 = tid >> 4; k0 < 640; k0 += 80) {
    uint2 v[10];
#pragma unroll
    for (int u = 0; u < 10; u++) v[u] = ok ? *reinterpret_cast<const uint2*>(src + (size_t)(k0 + 8 * u) * 1920) : make_uint2(0, 0);
#pragma unroll
    for (int u = 0; u < 10; u++) sts64(base + (k0 + 8 * u) * 128 + (((q >> 1) ^ (k0 & 7)) << 4) + (q & 1) * 8, v[u].x, v[u].y);
  }
}
template <int T>
__device__ __forceinline__ void stage_out(const float (&d)[16], uint32_t sb, int l, int s, int tid) {
  using namespace W;
  const int m = (tid >> 3) & 3, f = min(((tid >> 5) & 3) * 16 + (m & 1) * 8 + (tid & 7), 60);
  const uint32_t a = sb + f * 16 + (T == 0 ? OFF_Q + (m >> 1) * COL : OFF_KV + (l * 12 + (T - 1) * 6 + (2 * s + (m >> 1)) % 3) * COL);
#pragma unroll
  for (int p = 0; p < 2; p++)
    stsm4(a + p * (T == 0 ? 2 : 3) * COL, pack_bf16(d[8 * p], d[8 * p + 1]), pack_bf16(d[8 * p + 2], d[8 * p + 3]),
          pack_bf16(d[8 * p + 4], d[8 * p + 5]), pack_bf16(d[8 * p + 6], d[8 * p + 7]));
}
template <int WG>
__device__ __forceinline__ void work_b(const CUtensorMap& tmBo, const bf16* wqkv, uint32_t sb, int bc, int tid0) {
  using namespace W;
  if (WG == 0) asm volatile("setmaxnreg.inc.sync.aligned.u32 224;");
  else asm volatile("setmaxnreg.inc.sync.aligned.u32 208;");
  int spin = 0;
  const uint32_t wb = sb + OFF_W + WG * 81920;
  uint32_t wf[40][4];
  stage_qkv(wqkv, wb, WG, bc, tid0 & 127);
  WBAR_SYNC(NB_G0 + WG, 128);
  load_frags40(wf, wb, tid0);
  fence_async();
  WBAR_SYNC(NB_G0 + WG, 128);
  if (WG == 0) {
    stage_qkv(wqkv, wb, 2, bc, tid0 & 127);
  } else if (bc < 10) {
    if ((tid0 & 127) == 0) {
      mbar_expect_tx(sb + BAR_W + 8, 81920);
      for (int i = 0; i < 10; i++) tma2d(wb + i * 8192, &tmBo, bc * 64, i * 64, sb + BAR_W + 8);
    }
    __syncwarp();
    mwait(sb + BAR_W + 8, 0, spin);
    permute_cols(wb, tid0 & 127);
  }
  fence_async();
  WBAR_SYNC(NB_G0 + WG, 128);

  uint32_t ph = 0, pg = 0;
  int jq = 0;
#pragma unroll 1
  for (int n = WG && bc < 10 ? 256 : 128; n > 0; n--) {
    int job;
    if (WG) {
      mwait(sb + BAR_J, n & 1, spin);
      job = __shfl_sync(0xffffffffu, lds32(sb + JOB + 4 * (n & 1)), 0);
    } else {
      job = job_index(jq); jq = next_job(jq);
    }
    const int l = (job >> 6) & 1, s = job & 63;
    if (WG == 0 || job < 128) {
      float d[16], e[16];
#pragma unroll
      for (int f = 0; f < 5; f++) {
        mwait(sb + BAR_F + 8 * f, ph, spin);
        if (f == 0 && WG == 0 && bc == 0) WTS(l, s, 6);
        wg_fence();
#pragma unroll
        for (int kk = 0; kk < 8; kk++) {
          wgmma_rs32(d, wf[8 * f + kk], rdesc(f, kk), f | kk);
          if (WG == 0) wgmma_ts32(e, mkdesc(SB0 + OFF_W + (8 * f + kk) * 2048, 8192, 1024), rdesc(f, kk), f | kk);
        }
        wg_commit();
        if (f > 0) {
          wg_wait<1>();
          if ((tid0 & 31) == 0) mbar_arrive(sb + BAR_E + 8 * (f - 1));
        }
      }
      wg_wait<0>();
      if ((tid0 & 31) == 0) mbar_arrive(sb + BAR_E + 32);
      if (WG) WBAR_SYNC(NB_SF + 1, 224);
      stage_out<WG>(d, sb, l, s, tid0);
      if (WG == 0) stage_out<2>(e, sb, l, s, tid0);
      WBAR_ARRIVE(NB_ST, 352);
      if (!WG) WBAR_SYNC(NB_SF, 224);
      ph ^= 1;
    } else {
      float d[16];
#pragma unroll
      for (int f = 0; f < 5; f++) {
        mwait(sb + BAR_G + 8 * f, pg, spin);
        wg_fence();
#pragma unroll
        for (int kk = 0; kk < 8; kk++) wgmma_ts32(d, mkdesc(SB0 + OFF_W + 81920 + (8 * f + kk) * 2048, 8192, 1024), rdesc(f, kk), f | kk);
        wg_commit();
        if (f > 0) {
          wg_wait<1>();
          if ((tid0 & 31) < 2) mbar_arrive(sb + BAR_E + 8 * (f - 1));
        }
      }
      wg_wait<0>();
      if ((tid0 & 31) < 2) mbar_arrive(sb + BAR_E + 32);
      if (bc == 0) WTS(l, s, 10);
      red_tile(d, s, bc * 64, tid0);
      WBAR_SYNC(NB_SG, 160);
      pg ^= 1;
    }
  }
  if (spin >= SPIN_TOT) g_err = 14;
}
__device__ __forceinline__ void work_b_watch(uint32_t sb, int bc, int wo) {
  int spin = 0;
  for (int j = 0; j < 2 * NSTEP;) {
    cwait((wo ? CN_A : CN_L) + job_index(j), wo ? W::NBC : 32, spin);
    if (bc == 0) WTS1(job_index(j) >> 6, job_index(j) & 63, wo ? 9 : 5);
    j = next_job(j);
    asm volatile("st.release.cta.shared.b32 [%0],%1;" ::"r"(sb + W::RDY + 4 * wo), "r"(j) : "memory");
  }
  if (spin >= SPIN_TOT) g_err = 16;
}
__device__ __forceinline__ void work_b_producer(uint32_t sb, int bc) {
  using namespace W;
  int spin = 0, jq = 0, jw = bc < 10 ? 0 : 2 * NSTEP;
  uint32_t ph = 1;
  while (jq < 2 * NSTEP || jw < 2 * NSTEP) {
    mwait(sb + BAR_E, ph, spin);
    int rq, rw;
    do {
      asm volatile("ld.acquire.cta.shared.v2.b32 {%0,%1},[%2];" : "=r"(rq), "=r"(rw) : "r"(sb + RDY) : "memory");
    } while (rq <= jq && rw <= jw);
    const bool wo = rw > jw;
    fence_async_all();
    const int job = job_index(wo ? jw : jq);
    const uint8_t* src = (wo ? g_ob[0] : g_xnb[0]) + (size_t)job * 40960;
    const uint32_t fb = sb + (wo ? BAR_G : BAR_F);
#pragma unroll
    for (int f = 0; f < 5; f++) {
      if (f) mwait(sb + BAR_E + 8 * f, ph, spin);
      mbar_expect_tx(fb + 8 * f, 8192);
      bulk_g2s(sb + OFF_R + f * 8192, src + f * 8192, 8192, fb + 8 * f);
      if (f == 0) { sts32(sb + JOB + 4 * (ph ^ 1), job + (wo ? 128 : 0)); mbar_arrive(sb + BAR_J); }
    }
    if (wo) jw = next_job(jw); else jq = next_job(jq);
    ph ^= 1;
  }
  if (spin >= SPIN_TOT) g_err = 15;
}
__device__ __forceinline__ void work_att(uint32_t sb, int bc, int tid0) {
  using namespace W;
  WBAR_ARRIVE(NB_SF + 1, 224);
  FOR_P_JOBS(k_, l, s)
    const int tid = fresh(tid0), r = tid & 7, m = (tid >> 3) & 3, hh = (tid >> 5) & 3, g = (tid >> 2) & 7, t = tid & 3;
    const int f2 = r < 4 ? 20 * hh + 16 + r : 60;
    const uint32_t qa = sb + OFF_Q + (m & 1) * COL + (20 * hh + (m >> 1) * 8 + r) * 16, qb = sb + OFF_Q + m * COL + f2 * 16;
    const uint32_t kv = sb + OFF_KV + l * 12 * COL;
    const uint32_t ka = kv + (m < 2 ? 20 * hh + 8 * m + r : f2) * 16, va = kv + 6 * COL + (m < 2 ? 20 * hh + 4 * (r >> 1) + 2 * m + (r & 1) : f2) * 16;
    const int c1 = (2 * s) % 3;
    const uint32_t cc[3] = {(uint32_t)(c1 == 0 ? 2 : c1 - 1) * COL, (uint32_t)c1 * COL, (uint32_t)(c1 == 2 ? 0 : c1 + 1) * COL};
    WBAR_SYNC(NB_ST, 352);
    const float scl = 0.22360679774997896f * 1.4426950408889634f;
    uint32_t pw[2][2];
    float inv[2][2];
    {
      float sc[2][3][4];
      uint32_t q8[4];
      ldsm4t(q8, qb);
#pragma unroll
      for (int p = 0; p < 2; p++) {
        uint32_t q[4];
        ldsm4t(q, qa + p * 2 * COL);
#pragma unroll
        for (int c = 0; c < 3; c++) {
          uint32_t k[4];
          ldsm4t(k, ka + p * 3 * COL + cc[c]);
          sc[p][c][0] = sc[p][c][1] = sc[p][c][2] = sc[p][c][3] = 0.f;
          mma16816(sc[p][c], q[0], q[1], q[2], q[3], k[0], k[1]);
          mma1688(sc[p][c], q8[2 * p], q8[2 * p + 1], k[2]);
        }
      }
      if (j_ + 1 < 2 * NSTEP) WBAR_ARRIVE(NB_SF + 1, 224);
      const bool lo0 = 2 * t > g, lo1 = 2 * t + 1 > g;
#pragma unroll
      for (int p = 0; p < 2; p++)
#pragma unroll
        for (int h = 0; h < 2; h++) {
          float y0 = lo0 ? sc[p][h][2 * h] : sc[p][h + 1][2 * h], y1 = lo1 ? sc[p][h][2 * h + 1] : sc[p][h + 1][2 * h + 1];
          if (h == 0 && s == 0) { y0 = lo0 ? -INFINITY : y0; y1 = lo1 ? -INFINITY : y1; }
          const float mx = quad_max(fmaxf(y0, y1)) * -scl;
          y0 = ex2(fmaf(y0, scl, mx)); y1 = ex2(fmaf(y1, scl, mx));
          pw[p][h] = pack_bf16(y0, y1);
          inv[p][h] = bf_lo(pw[p][h]) + bf_hi(pw[p][h]);
        }
    }
    if (bc == 0 && tid == 256 && inv[0][0] != 123.456f) WTS1(l, s, 7);
    const uint32_t ml = (2 * t > g ? 0xFFFFu : 0u) | (2 * t + 1 > g ? 0xFFFF0000u : 0u);
    float o[2][3][4];
#pragma unroll
    for (int p = 0; p < 2; p++) {
      uint32_t v0[4], v1[4], v2[4];
      ldsm4(v0, va + p * 3 * COL + cc[0]); ldsm4(v1, va + p * 3 * COL + cc[1]); ldsm4(v2, va + p * 3 * COL + cc[2]);
#pragma unroll
      for (int j = 0; j < 3; j++) {
        o[p][j][0] = o[p][j][1] = o[p][j][2] = o[p][j][3] = 0.f;
        mma16816(o[p][j], pw[p][0] & ml, 0u, pw[p][0] & ~ml, pw[p][1] & ml, v0[j], v1[j]);
        mma1688(o[p][j], 0u, pw[p][1] & ~ml, v2[j]);
      }
    }
#pragma unroll
    for (int p = 0; p < 2; p++) { inv[p][0] = rcp(quad_sum(inv[p][0])); inv[p][1] = rcp(quad_sum(inv[p][1])); }
    uint32_t w[2][2][3];
#pragma unroll
    for (int p = 0; p < 2; p++)
#pragma unroll
      for (int h = 0; h < 2; h++)
#pragma unroll
        for (int j = 0; j < 3; j++) w[p][h][j] = pin(pack_bf16(o[p][j][2 * h] * inv[p][h], o[p][j][2 * h + 1] * inv[p][h]));
    WBAR_ARRIVE(NB_SF, 224);
    {
      const int tid = fresh(tid0), g = (tid >> 2) & 7, t = tid & 3, head = bc * 3 + ((tid >> 5) & 3);
      const uint32_t ca = head * 20 + 4 * t, cb = head * 20 + 16 + 2 * t;
      const uint32_t oa = g * 256 + (ca >> 6) * 4096 + (((ca >> 3) ^ (2 * g)) & 7) * 16 + (ca & 4) * 2;
      const uint32_t ob = g * 256 + (cb >> 6) * 4096 + (((cb >> 3) ^ (2 * g)) & 7) * 16 + (cb & 6) * 2;
      uint8_t* img = g_ob[l] + (size_t)s * 40960;
      if (head < NH) {
#pragma unroll
        for (int p = 0; p < 2; p++)
#pragma unroll
          for (int h = 0; h < 2; h++) {
            *reinterpret_cast<uint2*>(img + (oa ^ (p * 144)) + h * 2048) = make_uint2(w[p][h][0], w[p][h][1]);
            if (t < 2) *reinterpret_cast<uint32_t*>(img + (ob ^ (p * 144)) + h * 2048) = w[p][h][2];
          }
      }
      if (bc == 0 && tid == 256) WTS1(l, s, 8);
    }
    WBAR_SYNC(NB_AS, 128);
  }
}

__global__ void __launch_bounds__(512, 1)
k_work(const __grid_constant__ CUtensorMap tmWo, const __grid_constant__ CUtensorMap tmBo, const bf16* __restrict__ wqkv, bf16* __restrict__ out) {
  using namespace W;
  extern __shared__ __align__(1024) uint8_t smem[];
  const uint32_t sb = smem_u32(smem);
  const int tid = threadIdx.x, w = blockIdx.x;
  const int wg = __shfl_sync(0xffffffffu, tid >> 7, 0);
  if (tid == 0) {
    if (sb != SB0) g_err = 101;
    for (int i = 0; i < 5; i++) { mbar_init(sb + BAR_F + 8 * i, 1); mbar_init(sb + BAR_E + 8 * i, 8); mbar_init(sb + BAR_G + 8 * i, 1); }
    mbar_init(sb + BAR_J, 1);
    sts64(sb + RDY, 0, 0);
    mbar_init(sb + BAR_W, 1); mbar_init(sb + BAR_W + 8, 1);
    for (int p = 0; p < 16; p++) sts32(sb + OFF_SAFE + 4 * p, 0);
    asm volatile("fence.mbarrier_init.release.cluster;" ::: "memory");
  }
  for (int i = tid; i < 24 * COL / 16; i += 512) sts128(sb + OFF_KV + i * 16, make_uint4(0, 0, 0, 0));
  fence_async();
  __syncthreads();

  if (w < NP) {
    if (wg == 0) work_p<0>(tmWo, sb, w, keep(tid));
    else if (wg == 1) work_p<1>(tmWo, sb, w, keep(tid));
    else {
      asm volatile("setmaxnreg.dec.sync.aligned.u32 48;");
      const int aw = (tid >> 5) - 8;
      if (aw == 0) {
        if (tid == 256) work_p_producer(sb, w);
      } else if (aw == 1) {
        FOR_P_JOBS(k_, l, s)
          WBAR_SYNC(NB_SG, 288);
          if (tid == 288) csignal(CN_P + l * 64 + s);
          __syncwarp();
        }
      } else {
        const int id = (aw - 2) * NP + w;
        if (id < 128) work_ln(id & 3, id >> 2, tid & 31, out);
      }
    }
  } else {
    const int bc = w - NP;
    if (wg == 0) work_b<0>(tmBo, wqkv, sb, bc, keep(tid));
    else if (wg == 1) work_b<1>(tmBo, wqkv, sb, bc, keep(tid));
    else if (wg == 2) {
      asm volatile("setmaxnreg.dec.sync.aligned.u32 56;");
      if (tid < 352) work_att(sb, bc, keep(tid));
      else {
        FOR_P_JOBS(k_, l, s)
          WBAR_SYNC(NB_AS, 128);
          if (tid == 352) csignal(CN_A + l * 64 + s);
          __syncwarp();
        }
      }
    } else {
      asm volatile("setmaxnreg.dec.sync.aligned.u32 24;");
      if (tid == 384) work_b_producer(sb, bc);
      else if (tid == 448 || (tid == 480 && bc < 10)) work_b_watch(sb, bc, tid == 480);
      else if (tid >= 416 && tid < 448 && bc < 10) {
        FOR_P_JOBS(k_, l, s)
          WBAR_SYNC(NB_SG, 160);
          if (tid == 416) csignal(CN_W + l * 64 + s);
          __syncwarp();
        }
      }
    }
  }
  __syncthreads();
  asm volatile("griddepcontrol.wait;" ::: "memory");
}

typedef CUresult (*EncodeFn)(CUtensorMap*, CUtensorMapDataType, cuuint32_t, void*, const cuuint64_t*, const cuuint64_t*,
                             const cuuint32_t*, const cuuint32_t*, CUtensorMapInterleave, CUtensorMapSwizzle,
                             CUtensorMapL2promotion, CUtensorMapFloatOOBfill);

static void make_map(EncodeFn enc, CUtensorMap* tm, const void* ptr, uint64_t cols, uint64_t rows, uint32_t boxc, uint32_t boxr) {
  cuuint64_t dims[2] = {cols, rows};
  cuuint64_t strides[1] = {cols * 2};
  cuuint32_t box[2] = {boxc, boxr};
  cuuint32_t es[2] = {1, 1};
  enc(tm, CU_TENSOR_MAP_DATA_TYPE_BFLOAT16, 2, const_cast<void*>(ptr), dims, strides, box, es, CU_TENSOR_MAP_INTERLEAVE_NONE,
      CU_TENSOR_MAP_SWIZZLE_128B, CU_TENSOR_MAP_L2_PROMOTION_L2_256B, CU_TENSOR_MAP_FLOAT_OOB_FILL_NONE);
}

extern "C" void kernel_launch(void* const* d_in, const int* in_sizes, int n_in, void* d_out, int out_size) {
  const bf16* x0 = (const bf16*)d_in[0];
  const bf16* mem0 = (const bf16*)d_in[1];
  const bf16* Wq = (const bf16*)d_in[2];
  const bf16* Wk = (const bf16*)d_in[3];
  const bf16* Wv = (const bf16*)d_in[4];
  const bf16* Wo = (const bf16*)d_in[5];
  const bf16* Bqkv = (const bf16*)d_in[8];
  const bf16* Bwo = (const bf16*)d_in[9];
  bf16* out = (bf16*)d_out;

  static EncodeFn enc = nullptr;
  if (!enc) {
    void* fn = nullptr;
    cudaDriverEntryPointQueryResult qr;
    cudaGetDriverEntryPoint("cuTensorMapEncodeTiled", &fn, cudaEnableDefault, &qr);
    enc = (EncodeFn)fn;
    cudaFuncSetAttribute(k_chain, cudaFuncAttributeMaxDynamicSharedMemorySize, C::SMEM);
    cudaFuncSetAttribute(k_work, cudaFuncAttributeMaxDynamicSharedMemorySize, W::SMEM);
  }
  CUtensorMap tmWq, tmWk, tmWv, tmWo, tmBo;
  make_map(enc, &tmWq, Wq, NH * DH, DM, 64, 128);
  make_map(enc, &tmWk, Wk, NH * DH, DM, 64, 128);
  make_map(enc, &tmWv, Wv, NH * DH, DM, 64, 128);
  make_map(enc, &tmWo, Wo, DM, NH * DH, 64, 64);
  make_map(enc, &tmBo, Bwo, DM, DM, 64, 64);

  cudaStream_t st = cudaStreamPerThread;
  k_pre<<<256, 256, 0, st>>>(x0, mem0);
  cudaLaunchAttribute at[1];
  at[0].id = cudaLaunchAttributeProgrammaticStreamSerialization; at[0].val.programmaticStreamSerializationAllowed = 1;
  {
    cudaLaunchConfig_t cfg = {};
    cfg.gridDim = dim3(96); cfg.blockDim = dim3(384); cfg.dynamicSmemBytes = C::SMEM; cfg.stream = st;
    cfg.attrs = at; cfg.numAttrs = 0;
    cudaLaunchKernelEx(&cfg, k_chain, tmWq, tmWk, tmWv, tmWo);
  }
  cudaLaunchConfig_t cfg = {};
  cfg.gridDim = dim3(W::NW); cfg.blockDim = dim3(512); cfg.dynamicSmemBytes = W::SMEM; cfg.stream = st;
  cfg.attrs = at; cfg.numAttrs = NOWORK == 2 ? 0 : 1;
  cudaLaunchKernelEx(&cfg, k_work, tmWo, tmBo, Bqkv, out);
}
```

```cpp
#include <cuda_runtime.h>
#include <cuda_bf16.h>
#include <cuda.h>
#include <stdint.h>

typedef __nv_bfloat16 bf16;

constexpr int SEQ = 2048, DM = 640, NH = 32, DH = 192, NSEG = 64;
#define LAG 5
constexpr int NSTEP = NSEG + LAG;
constexpr uint32_t SENT = 0xFFFFFFFFu;

constexpr int MAIL9 = 288 * 2048, MAIL_BYTES = MAIL9 + 64 * 3072;
__device__ __align__(1024) uint8_t g_xn[2][NSEG * 40960];
__device__ __align__(1024) uint8_t g_xnb[2][NSEG * 40960];
__device__ __align__(1024) uint8_t g_ob[2][NSEG * 40960];
#define ORING 8
static_assert(ORING > LAG, "a slot is free again LAG + 1 steps later");
__device__ __align__(1024) uint8_t g_o[ORING][2][96][4096];
__device__ __align__(1024) float g_x[SEQ * DM];
__device__ __align__(1024) uint8_t g_mbuf[NSTEP][20480];
__device__ __align__(1024) uint32_t g_flag[NSTEP][768];
__device__ __align__(1024) uint8_t g_mail[2][MAIL_BYTES];
enum { CN_P = 0, CN_L = 128, CN_A = 256, CN_W = 384, CN_X = 512, CN_O = 576, CN_NUM = CN_O + 5 * NSTEP };
__device__ __align__(128) uint32_t g_cnt[CN_NUM][32];
__device__ int g_err;
#define TS(jj, i)
#define TS1(jj, i)
#define PTS(i)
#define TSB(jj, i)
#define TSV(jj, i, v)
#define TS_FLUSH(jj)
#define WTS(l, b, k)
#define WTS1(l, b, k)
#define WW -1

__device__ __forceinline__ uint32_t smem_u32(const void* p) { return (uint32_t)__cvta_generic_to_shared(p); }
__device__ __forceinline__ uint32_t clk32() { uint32_t t; asm volatile("mov.u32 %0, %%clock;" : "=r"(t)::"memory"); return t; }
__device__ __forceinline__ uint32_t mapa(uint32_t a, uint32_t r) { uint32_t o; asm("mapa.shared::cluster.u32 %0,%1,%2;" : "=r"(o) : "r"(a), "r"(r)); return o; }
__device__ __forceinline__ void mbar_init(uint32_t bar, uint32_t cnt) { asm volatile("mbarrier.init.shared::cta.b64 [%0],%1;" ::"r"(bar), "r"(cnt) : "memory"); }
__device__ __forceinline__ void mbar_expect_tx(uint32_t bar, uint32_t bytes) { asm volatile("mbarrier.arrive.expect_tx.shared::cta.b64 _,[%0],%1;" ::"r"(bar), "r"(bytes) : "memory"); }
__device__ __forceinline__ void mbar_arrive(uint32_t bar) { asm volatile("mbarrier.arrive.shared::cta.b64 _,[%0];" ::"r"(bar) : "memory"); }
__device__ __forceinline__ void mbar_arrive_cluster(uint32_t bar) { asm volatile("mbarrier.arrive.shared::cluster.b64 _,[%0];" ::"r"(bar) : "memory"); }
__device__ __forceinline__ bool mbar_try(uint32_t bar, uint32_t ph) {
  uint32_t ok;
  asm volatile("{.reg .pred p; mbarrier.try_wait.parity.shared::cta.b64 p,[%1],%2; selp.u32 %0,1,0,p;}" : "=r"(ok) : "r"(bar), "r"(ph) : "memory");
  return ok;
}
__device__ __forceinline__ bool mbar_test(uint32_t bar, uint32_t ph) {
  uint32_t ok;
  asm volatile("{.reg .pred p; mbarrier.test_wait.parity.shared::cta.b64 p,[%1],%2; selp.u32 %0,1,0,p;}" : "=r"(ok) : "r"(bar), "r"(ph) : "memory");
  return ok;
}
__device__ __forceinline__ int fresh(int x) { asm volatile("" : "+r"(x)); return x; }
#define PHASE_IDS const int tid = fresh(tid0), lane = tid & 31, w = tid >> 5, g = lane >> 2, t = lane & 3; (void)w; (void)g; (void)t
__device__ __forceinline__ void bar_sync(int id, int n) { asm volatile("bar.sync %0,%1;" ::"r"(id), "r"(n) : "memory"); }
__device__ __forceinline__ void bar_arrive(int id, int n) { asm volatile("bar.arrive %0,%1;" ::"r"(id), "r"(n) : "memory"); }
__device__ __forceinline__ bool bar_red_or(int id, int n, bool v) {
  uint32_t r;
  asm volatile("{\n .reg .pred p, q;\n setp.ne.u32 q, %3, 0;\n barrier.cta.red.or.pred p, %1, %2, q;\n selp.u32 %0, 1, 0, p;\n}" : "=r"(r) : "r"(id), "r"(n), "r"((uint32_t)v) : "memory");
  return r != 0;
}
__device__ __forceinline__ void fence_async() { asm volatile("fence.proxy.async.shared::cta;" ::: "memory"); }
__device__ __forceinline__ void bulk_g2s(uint32_t dst, const void* src, uint32_t bytes, uint32_t bar) {
  asm volatile("cp.async.bulk.shared::cluster.global.mbarrier::complete_tx::bytes [%0],[%1],%2,[%3];" ::"r"(dst), "l"(src), "r"(bytes), "r"(bar) : "memory");
}
__device__ __forceinline__ void bulk_g2s_mc(uint32_t dst, const void* src, uint32_t bytes, uint32_t bar) {
  asm volatile("cp.async.bulk.shared::cluster.global.mbarrier::complete_tx::bytes.multicast::cluster [%0],[%1],%2,[%3],%4;"
               ::"r"(dst), "l"(src), "r"(bytes), "r"(bar), "h"((uint16_t)7) : "memory");
}
__device__ __forceinline__ void bulk_s2g(void* dst, uint32_t src, uint32_t bytes) {
  asm volatile("cp.async.bulk.global.shared::cta.bulk_group [%0],[%1],%2;" ::"l"(dst), "r"(src), "r"(bytes) : "memory");
}
__device__ __forceinline__ void bulk_s2c(uint32_t dst, uint32_t src, uint32_t bytes, uint32_t bar) {
  asm volatile("cp.async.bulk.shared::cluster.shared::cta.mbarrier::complete_tx::bytes [%0],[%1],%2,[%3];" ::"r"(dst), "r"(src), "r"(bytes), "r"(bar) : "memory");
}
__device__ __forceinline__ void tma2d(uint32_t dst, const CUtensorMap* tm, int c0, int c1, uint32_t bar) {
  asm volatile("cp.async.bulk.tensor.2d.shared::cluster.global.mbarrier::complete_tx::bytes [%0],[%1,{%3,%4}],[%2];"
               ::"r"(dst), "l"(tm), "r"(bar), "r"(c0), "r"(c1) : "memory");
}
__device__ __forceinline__ void tma2d_prefetch(const CUtensorMap* tm, int c0, int c1) {
  asm volatile("cp.async.bulk.prefetch.tensor.2d.L2.global.tile [%0,{%1,%2}];" ::"l"(tm), "r"(c0), "r"(c1) : "memory");
}
__device__ __forceinline__ uint32_t pack_bf16(float lo, float hi) {
  uint32_t r; asm("cvt.rn.bf16x2.f32 %0,%1,%2;" : "=r"(r) : "f"(hi), "f"(lo)); return r;
}
__device__ __forceinline__ float bf_lo(uint32_t x) { return __uint_as_float(x << 16); }
__device__ __forceinline__ float bf_hi(uint32_t x) { return __uint_as_float(x & 0xFFFF0000u); }
__device__ __forceinline__ float ex2(float x) { float y; asm("ex2.approx.ftz.f32 %0,%1;" : "=f"(y) : "f"(x)); return y; }
__device__ __forceinline__ void ldsm4(uint32_t (&r)[4], uint32_t a) {
  asm volatile("ldmatrix.sync.aligned.m8n8.x4.shared.b16 {%0,%1,%2,%3},[%4];" : "=r"(r[0]), "=r"(r[1]), "=r"(r[2]), "=r"(r[3]) : "r"(a) : "memory");
}
__device__ __forceinline__ void ldsm4t(uint32_t (&r)[4], uint32_t a) {
  asm volatile("ldmatrix.sync.aligned.m8n8.x4.trans.shared.b16 {%0,%1,%2,%3},[%4];" : "=r"(r[0]), "=r"(r[1]), "=r"(r[2]), "=r"(r[3]) : "r"(a) : "memory");
}
__device__ __forceinline__ void ldsm2(uint32_t& r0, uint32_t& r1, uint32_t a) {
  asm volatile("ldmatrix.sync.aligned.m8n8.x2.shared.b16 {%0,%1},[%2];" : "=r"(r0), "=r"(r1) : "r"(a) : "memory");
}
__device__ __forceinline__ void ldsm2t(uint32_t& r0, uint32_t& r1, uint32_t a) {
  asm volatile("ldmatrix.sync.aligned.m8n8.x2.trans.shared.b16 {%0,%1},[%2];" : "=r"(r0), "=r"(r1) : "r"(a) : "memory");
}
__device__ __forceinline__ void ldsm1(uint32_t& r0, uint32_t a) {
  asm volatile("ldmatrix.sync.aligned.m8n8.x1.shared.b16 {%0},[%1];" : "=r"(r0) : "r"(a) : "memory");
}
__device__ __forceinline__ void mma16816(float (&d)[4], uint32_t a0, uint32_t a1, uint32_t a2, uint32_t a3, uint32_t b0, uint32_t b1) {
  asm volatile("mma.sync.aligned.m16n8k16.row.col.f32.bf16.bf16.f32 {%0,%1,%2,%3},{%4,%5,%6,%7},{%8,%9},{%0,%1,%2,%3};"
               : "+f"(d[0]), "+f"(d[1]), "+f"(d[2]), "+f"(d[3]) : "r"(a0), "r"(a1), "r"(a2), "r"(a3), "r"(b0), "r"(b1));
}
__device__ __forceinline__ void mma1688(float (&d)[4], uint32_t a0, uint32_t a1, uint32_t b0) {
  asm volatile("mma.sync.aligned.m16n8k8.row.col.f32.bf16.bf16.f32 {%0,%1,%2,%3},{%4,%5},{%6},{%0,%1,%2,%3};"
               : "+f"(d[0]), "+f"(d[1]), "+f"(d[2]), "+f"(d[3]) : "r"(a0), "r"(a1), "r"(b0));
}
__device__ __forceinline__ void sts32(uint32_t a, uint32_t v) { asm volatile("st.shared.b32 [%0],%1;" ::"r"(a), "r"(v) : "memory"); }
__device__ __forceinline__ void sts64f(uint32_t a, float x, float y) { asm volatile("st.shared.v2.f32 [%0],{%1,%2};" ::"r"(a), "f"(x), "f"(y) : "memory"); }
__device__ __forceinline__ void sts128(uint32_t a, uint4 v) { asm volatile("st.shared.v4.b32 [%0],{%1,%2,%3,%4};" ::"r"(a), "r"(v.x), "r"(v.y), "r"(v.z), "r"(v.w) : "memory"); }
__device__ __forceinline__ float lds32f(uint32_t a) { float v; asm volatile("ld.shared.f32 %0,[%1];" : "=f"(v) : "r"(a) : "memory"); return v; }
__device__ __forceinline__ float2 lds64f(uint32_t a) { float2 v; asm volatile("ld.shared.v2.f32 {%0,%1},[%2];" : "=f"(v.x), "=f"(v.y) : "r"(a) : "memory"); return v; }
__device__ __forceinline__ uint4 lds128(uint32_t a) { uint4 v; asm volatile("ld.shared.v4.b32 {%0,%1,%2,%3},[%4];" : "=r"(v.x), "=r"(v.y), "=r"(v.z), "=r"(v.w) : "r"(a) : "memory"); return v; }
__device__ __forceinline__ float4 lds128f(uint32_t a) { float4 v; asm volatile("ld.shared.v4.f32 {%0,%1,%2,%3},[%4];" : "=f"(v.x), "=f"(v.y), "=f"(v.z), "=f"(v.w) : "r"(a) : "memory"); return v; }
__device__ __forceinline__ void st_async2(uint32_t a, float x, float y, uint32_t bar) {
  asm volatile("st.async.weak.shared::cluster.mbarrier::complete_tx::bytes.v2.f32 [%0],{%1,%2},[%3];" ::"r"(a), "f"(x), "f"(y), "r"(bar) : "memory");
}
__device__ __forceinline__ void st_async4(uint32_t a, const float (&v)[4], uint32_t bar) {
  asm volatile("st.async.weak.shared::cluster.mbarrier::complete_tx::bytes.v4.f32 [%0],{%1,%2,%3,%4},[%5];" ::"r"(a), "f"(v[0]), "f"(v[1]), "f"(v[2]), "f"(v[3]), "r"(bar) : "memory");
}
__device__ __forceinline__ void st_async4v(uint32_t a, float x, float y, float z, float w, uint32_t bar) {
  asm volatile("st.async.weak.shared::cluster.mbarrier::complete_tx::bytes.v4.f32 [%0],{%1,%2,%3,%4},[%5];" ::"r"(a), "f"(x), "f"(y), "f"(z), "f"(w), "r"(bar) : "memory");
}
__device__ __forceinline__ void st_async4u(uint32_t a, const uint4& v, uint32_t bar) {
  asm volatile("st.async.weak.shared::cluster.mbarrier::complete_tx::bytes.v4.b32 [%0],{%1,%2,%3,%4},[%5];" ::"r"(a), "r"(v.x), "r"(v.y), "r"(v.z), "r"(v.w), "r"(bar) : "memory");
}
__device__ __forceinline__ uint4 ld_relaxed4(const void* p) {
  uint4 v; asm volatile("ld.relaxed.gpu.global.v4.u32 {%0,%1,%2,%3},[%4];" : "=r"(v.x), "=r"(v.y), "=r"(v.z), "=r"(v.w) : "l"(p) : "memory"); return v;
}
__device__ __forceinline__ uint32_t ld_relaxed(const void* p) {
  uint32_t v; asm volatile("ld.relaxed.gpu.global.u32 %0,[%1];" : "=r"(v) : "l"(p) : "memory"); return v;
}
__device__ __forceinline__ void st_relaxed(void* p, uint32_t v) { asm volatile("st.relaxed.gpu.global.b32 [%0],%1;" ::"l"(p), "r"(v) : "memory"); }
__device__ __forceinline__ void st_relaxed4(void* p, uint32_t v) { asm volatile("st.relaxed.gpu.global.v4.b32 [%0],{%1,%1,%1,%1};" ::"l"(p), "r"(v) : "memory"); }

__device__ __forceinline__ uint32_t ld_acquire(const void* p) {
  uint32_t v; asm volatile("ld.acquire.gpu.global.u32 %0,[%1];" : "=r"(v) : "l"(p) : "memory"); return v;
}
__device__ __forceinline__ float4 ld_relaxed4f(const void* p) {
  float4 v; asm volatile("ld.relaxed.gpu.global.v4.f32 {%0,%1,%2,%3},[%4];" : "=f"(v.x), "=f"(v.y), "=f"(v.z), "=f"(v.w) : "l"(p) : "memory"); return v;
}
__device__ __forceinline__ float2 ld_relaxed2f(const void* p) {
  float2 v; asm volatile("ld.relaxed.gpu.global.v2.f32 {%0,%1},[%2];" : "=f"(v.x), "=f"(v.y) : "l"(p) : "memory"); return v;
}
__device__ __forceinline__ void prefetch_l2(const void* p) { asm volatile("prefetch.global.L2 [%0];" ::"l"(p)); }
__device__ __forceinline__ void fence_gpu() { asm volatile("fence.acq_rel.gpu;" ::: "memory"); }
__device__ __forceinline__ void fence_async_all() { asm volatile("fence.proxy.async.global;" ::: "memory"); }
constexpr int SPIN_TOT = 1 << 22;
__device__ __forceinline__ void csignal(int idx) { asm volatile("red.release.gpu.global.add.u32 [%0],1;" ::"l"(&g_cnt[idx][0]) : "memory"); }
__device__ __forceinline__ void cwait(int idx, uint32_t target, int& spin) {
  while (ld_acquire(&g_cnt[idx][0]) < target && spin < SPIN_TOT) spin += 16;
}

__device__ __forceinline__ uint64_t mkdesc(uint32_t addr, uint32_t lbo, uint32_t sbo) {
  return (uint64_t)((addr & 0x3FFFF) >> 4) | ((uint64_t)(lbo >> 4) << 16) | ((uint64_t)(sbo >> 4) << 32) | ((uint64_t)1 << 62);
}
__device__ __forceinline__ uint64_t mkdesc_ns(uint32_t addr, uint32_t lbo, uint32_t sbo) {
  return (uint64_t)((addr & 0x3FFFF) >> 4) | ((uint64_t)(lbo >> 4) << 16) | ((uint64_t)(sbo >> 4) << 32);
}
__device__ __forceinline__ void wg_fence() { asm volatile("wgmma.fence.sync.aligned;" ::: "memory"); }
__device__ __forceinline__ void wg_commit() { asm volatile("wgmma.commit_group.sync.aligned;" ::: "memory"); }
template <int N> __device__ __forceinline__ void wg_wait() { asm volatile("wgmma.wait_group.sync.aligned %0;" ::"n"(N) : "memory"); }

__device__ __forceinline__ void wgmma_rs16(float (&d)[8], const uint32_t (&a)[4], uint64_t db, int sc) {
  asm volatile("{.reg .pred p; setp.ne.b32 p,%13,0; wgmma.mma_async.sync.aligned.m64n16k16.f32.bf16.bf16 "
               "{%0,%1,%2,%3,%4,%5,%6,%7},{%8,%9,%10,%11},%12,p,1,1,0;}"
               : "+f"(d[0]), "+f"(d[1]), "+f"(d[2]), "+f"(d[3]), "+f"(d[4]), "+f"(d[5]), "+f"(d[6]), "+f"(d[7])
               : "r"(a[0]), "r"(a[1]), "r"(a[2]), "r"(a[3]), "l"(db), "r"(sc));
}
__device__ __forceinline__ void wgmma_rs64(float (&d)[32], const uint32_t (&a)[4], uint64_t db, int sc) {
  asm volatile("{.reg .pred p; setp.ne.b32 p,%37,0; wgmma.mma_async.sync.aligned.m64n64k16.f32.bf16.bf16 "
               "{%0,%1,%2,%3,%4,%5,%6,%7,%8,%9,%10,%11,%12,%13,%14,%15,%16,%17,%18,%19,%20,%21,%22,%23,%24,%25,%26,%27,%28,%29,%30,%31},{%32,%33,%34,%35},%36,p,1,1,0;}"
               : "+f"(d[0]), "+f"(d[1]), "+f"(d[2]), "+f"(d[3]), "+f"(d[4]), "+f"(d[5]), "+f"(d[6]), "+f"(d[7]), "+f"(d[8]), "+f"(d[9]), "+f"(d[10]), "+f"(d[11]), "+f"(d[12]), "+f"(d[13]), "+f"(d[14]), "+f"(d[15]), "+f"(d[16]), "+f"(d[17]), "+f"(d[18]), "+f"(d[19]), "+f"(d[20]), "+f"(d[21]), "+f"(d[22]), "+f"(d[23]), "+f"(d[24]), "+f"(d[25]), "+f"(d[26]), "+f"(d[27]), "+f"(d[28]), "+f"(d[29]), "+f"(d[30]), "+f"(d[31])
               : "r"(a[0]), "r"(a[1]), "r"(a[2]), "r"(a[3]), "l"(db), "r"(sc));
}
__device__ __forceinline__ void wgmma_rt16(float (&d)[8], const uint32_t (&a)[4], uint64_t db, int sc) {
  asm volatile("{.reg .pred p; setp.ne.b32 p,%13,0; wgmma.mma_async.sync.aligned.m64n16k16.f32.bf16.bf16 "
               "{%0,%1,%2,%3,%4,%5,%6,%7},{%8,%9,%10,%11},%12,p,1,1,1;}"
               : "+f"(d[0]), "+f"(d[1]), "+f"(d[2]), "+f"(d[3]), "+f"(d[4]), "+f"(d[5]), "+f"(d[6]), "+f"(d[7])
               : "r"(a[0]), "r"(a[1]), "r"(a[2]), "r"(a[3]), "l"(db), "r"(sc));
}
__device__ __forceinline__ void wgmma_rt80(float (&d)[40], const uint32_t (&a)[4], uint64_t db, int sc) {
  asm volatile("{.reg .pred p; setp.ne.b32 p,%45,0; wgmma.mma_async.sync.aligned.m64n80k16.f32.bf16.bf16 "
               "{%0,%1,%2,%3,%4,%5,%6,%7,%8,%9,%10,%11,%12,%13,%14,%15,%16,%17,%18,%19,%20,%21,%22,%23,%24,%25,%26,%27,%28,%29,%30,%31,%32,%33,%34,%35,%36,%37,%38,%39},{%40,%41,%42,%43},%44,p,1,1,1;}"
               : "+f"(d[0]), "+f"(d[1]), "+f"(d[2]), "+f"(d[3]), "+f"(d[4]), "+f"(d[5]), "+f"(d[6]), "+f"(d[7]), "+f"(d[8]), "+f"(d[9]), "+f"(d[10]), "+f"(d[11]), "+f"(d[12]), "+f"(d[13]), "+f"(d[14]), "+f"(d[15]), "+f"(d[16]), "+f"(d[17]), "+f"(d[18]), "+f"(d[19]), "+f"(d[20]), "+f"(d[21]), "+f"(d[22]), "+f"(d[23]), "+f"(d[24]), "+f"(d[25]), "+f"(d[26]), "+f"(d[27]), "+f"(d[28]), "+f"(d[29]), "+f"(d[30]), "+f"(d[31]), "+f"(d[32]), "+f"(d[33]), "+f"(d[34]), "+f"(d[35]), "+f"(d[36]), "+f"(d[37]), "+f"(d[38]), "+f"(d[39])
               : "r"(a[0]), "r"(a[1]), "r"(a[2]), "r"(a[3]), "l"(db), "r"(sc));
}
__device__ __forceinline__ void wgmma_rs32(float (&d)[16], const uint32_t (&a)[4], uint64_t db, int sc) {
  asm volatile("{.reg .pred p; setp.ne.b32 p,%21,0; wgmma.mma_async.sync.aligned.m64n32k16.f32.bf16.bf16 "
               "{%0,%1,%2,%3,%4,%5,%6,%7,%8,%9,%10,%11,%12,%13,%14,%15},{%16,%17,%18,%19},%20,p,1,1,0;}"
               : "+f"(d[0]), "+f"(d[1]), "+f"(d[2]), "+f"(d[3]), "+f"(d[4]), "+f"(d[5]), "+f"(d[6]), "+f"(d[7]), "+f"(d[8]), "+f"(d[9]), "+f"(d[10]), "+f"(d[11]), "+f"(d[12]), "+f"(d[13]), "+f"(d[14]), "+f"(d[15])
               : "r"(a[0]), "r"(a[1]), "r"(a[2]), "r"(a[3]), "l"(db), "r"(sc));
}
__device__ __forceinline__ void wgmma_ts32(float (&d)[16], uint64_t da, uint64_t db, int sc) {
  asm volatile("{.reg .pred p; setp.ne.b32 p,%18,0; wgmma.mma_async.sync.aligned.m64n32k16.f32.bf16.bf16 "
               "{%0,%1,%2,%3,%4,%5,%6,%7,%8,%9,%10,%11,%12,%13,%14,%15},%16,%17,p,1,1,1,0;}"
               : "+f"(d[0]), "+f"(d[1]), "+f"(d[2]), "+f"(d[3]), "+f"(d[4]), "+f"(d[5]), "+f"(d[6]), "+f"(d[7]), "+f"(d[8]), "+f"(d[9]), "+f"(d[10]), "+f"(d[11]), "+f"(d[12]), "+f"(d[13]), "+f"(d[14]), "+f"(d[15])
               : "l"(da), "l"(db), "r"(sc));
}
__device__ __forceinline__ void wgmma_ts16(float (&d)[8], uint64_t da, uint64_t db, int sc) {
  asm volatile("{.reg .pred p; setp.ne.b32 p,%10,0; wgmma.mma_async.sync.aligned.m64n16k16.f32.bf16.bf16 "
               "{%0,%1,%2,%3,%4,%5,%6,%7},%8,%9,p,1,1,1,0;}"
               : "+f"(d[0]), "+f"(d[1]), "+f"(d[2]), "+f"(d[3]), "+f"(d[4]), "+f"(d[5]), "+f"(d[6]), "+f"(d[7])
               : "l"(da), "l"(db), "r"(sc));
}
__device__ __forceinline__ void wgmma_ts64(float (&d)[32], uint64_t da, uint64_t db, int sc) {
  asm volatile("{.reg .pred p; setp.ne.b32 p,%34,0; wgmma.mma_async.sync.aligned.m64n64k16.f32.bf16.bf16 "
               "{%0,%1,%2,%3,%4,%5,%6,%7,%8,%9,%10,%11,%12,%13,%14,%15,%16,%17,%18,%19,%20,%21,%22,%23,%24,%25,%26,%27,%28,%29,%30,%31},%32,%33,p,1,1,1,0;}"
               : "+f"(d[0]), "+f"(d[1]), "+f"(d[2]), "+f"(d[3]), "+f"(d[4]), "+f"(d[5]), "+f"(d[6]), "+f"(d[7]), "+f"(d[8]), "+f"(d[9]), "+f"(d[10]), "+f"(d[11]), "+f"(d[12]), "+f"(d[13]), "+f"(d[14]), "+f"(d[15]), "+f"(d[16]), "+f"(d[17]), "+f"(d[18]), "+f"(d[19]), "+f"(d[20]), "+f"(d[21]), "+f"(d[22]), "+f"(d[23]), "+f"(d[24]), "+f"(d[25]), "+f"(d[26]), "+f"(d[27]), "+f"(d[28]), "+f"(d[29]), "+f"(d[30]), "+f"(d[31])
               : "l"(da), "l"(db), "r"(sc));
}
__device__ __forceinline__ void wgmma_tt16(float (&d)[8], uint64_t da, uint64_t db, int sc) {
  asm volatile("{.reg .pred p; setp.ne.b32 p,%10,0; wgmma.mma_async.sync.aligned.m64n16k16.f32.bf16.bf16 "
               "{%0,%1,%2,%3,%4,%5,%6,%7},%8,%9,p,1,1,1,1;}"
               : "+f"(d[0]), "+f"(d[1]), "+f"(d[2]), "+f"(d[3]), "+f"(d[4]), "+f"(d[5]), "+f"(d[6]), "+f"(d[7])
               : "l"(da), "l"(db), "r"(sc));
}
__device__ __forceinline__ void wgmma_tt40(float (&d)[20], uint64_t da, uint64_t db, int sc) {
  asm volatile("{.reg .pred p; setp.ne.b32 p,%22,0; wgmma.mma_async.sync.aligned.m64n40k16.f32.bf16.bf16 "
               "{%0,%1,%2,%3,%4,%5,%6,%7,%8,%9,%10,%11,%12,%13,%14,%15,%16,%17,%18,%19},%20,%21,p,1,1,1,1;}"
               : "+f"(d[0]), "+f"(d[1]), "+f"(d[2]), "+f"(d[3]), "+f"(d[4]), "+f"(d[5]), "+f"(d[6]), "+f"(d[7]), "+f"(d[8]), "+f"(d[9]), "+f"(d[10]), "+f"(d[11]), "+f"(d[12]), "+f"(d[13]), "+f"(d[14]), "+f"(d[15]), "+f"(d[16]), "+f"(d[17]), "+f"(d[18]), "+f"(d[19])
               : "l"(da), "l"(db), "r"(sc));
}
__device__ __forceinline__ void wgmma_ss8(float (&d)[4], uint64_t da, uint64_t db, int sc) {
  asm volatile("{.reg .pred p; setp.ne.b32 p,%6,0; wgmma.mma_async.sync.aligned.m64n8k16.f32.bf16.bf16 "
               "{%0,%1,%2,%3},%4,%5,p,1,1,0,0;}"
               : "+f"(d[0]), "+f"(d[1]), "+f"(d[2]), "+f"(d[3])
               : "l"(da), "l"(db), "r"(sc));
}
__device__ __forceinline__ void wgmma_ss32(float (&d)[16], uint64_t da, uint64_t db, int sc) {
  asm volatile("{.reg .pred p; setp.ne.b32 p,%18,0; wgmma.mma_async.sync.aligned.m64n32k16.f32.bf16.bf16 "
               "{%0,%1,%2,%3,%4,%5,%6,%7,%8,%9,%10,%11,%12,%13,%14,%15},%16,%17,p,1,1,0,0;}"
               : "+f"(d[0]), "+f"(d[1]), "+f"(d[2]), "+f"(d[3]), "+f"(d[4]), "+f"(d[5]), "+f"(d[6]), "+f"(d[7]), "+f"(d[8]), "+f"(d[9]), "+f"(d[10]), "+f"(d[11]), "+f"(d[12]), "+f"(d[13]), "+f"(d[14]), "+f"(d[15])
               : "l"(da), "l"(db), "r"(sc));
}
__device__ __forceinline__ void wgmma_st64(float (&d)[32], uint64_t da, uint64_t db, int sc) {
  asm volatile("{.reg .pred p; setp.ne.b32 p,%34,0; wgmma.mma_async.sync.aligned.m64n64k16.f32.bf16.bf16 "
               "{%0,%1,%2,%3,%4,%5,%6,%7,%8,%9,%10,%11,%12,%13,%14,%15,%16,%17,%18,%19,%20,%21,%22,%23,%24,%25,%26,%27,%28,%29,%30,%31},%32,%33,p,1,1,0,1;}"
               : "+f"(d[0]), "+f"(d[1]), "+f"(d[2]), "+f"(d[3]), "+f"(d[4]), "+f"(d[5]), "+f"(d[6]), "+f"(d[7]), "+f"(d[8]), "+f"(d[9]), "+f"(d[10]), "+f"(d[11]), "+f"(d[12]), "+f"(d[13]), "+f"(d[14]), "+f"(d[15]), "+f"(d[16]), "+f"(d[17]), "+f"(d[18]), "+f"(d[19]), "+f"(d[20]), "+f"(d[21]), "+f"(d[22]), "+f"(d[23]), "+f"(d[24]), "+f"(d[25]), "+f"(d[26]), "+f"(d[27]), "+f"(d[28]), "+f"(d[29]), "+f"(d[30]), "+f"(d[31])
               : "l"(da), "l"(db), "r"(sc));
}
__device__ __forceinline__ void wgmma_st128(float (&d)[64], uint64_t da, uint64_t db, int sc) {
  asm volatile("{.reg .pred p; setp.ne.b32 p,%66,0; wgmma.mma_async.sync.aligned.m64n128k16.f32.bf16.bf16 "
               "{%0,%1,%2,%3,%4,%5,%6,%7,%8,%9,%10,%11,%12,%13,%14,%15,%16,%17,%18,%19,%20,%21,%22,%23,%24,%25,%26,%27,%28,%29,%30,%31,%32,%33,%34,%35,%36,%37,%38,%39,%40,%41,%42,%43,%44,%45,%46,%47,%48,%49,%50,%51,%52,%53,%54,%55,%56,%57,%58,%59,%60,%61,%62,%63},%64,%65,p,1,1,0,1;}"
               : "+f"(d[0]), "+f"(d[1]), "+f"(d[2]), "+f"(d[3]), "+f"(d[4]), "+f"(d[5]), "+f"(d[6]), "+f"(d[7]), "+f"(d[8]), "+f"(d[9]), "+f"(d[10]), "+f"(d[11]), "+f"(d[12]), "+f"(d[13]), "+f"(d[14]), "+f"(d[15]), "+f"(d[16]), "+f"(d[17]), "+f"(d[18]), "+f"(d[19]), "+f"(d[20]), "+f"(d[21]), "+f"(d[22]), "+f"(d[23]), "+f"(d[24]), "+f"(d[25]), "+f"(d[26]), "+f"(d[27]), "+f"(d[28]), "+f"(d[29]), "+f"(d[30]), "+f"(d[31]), "+f"(d[32]), "+f"(d[33]), "+f"(d[34]), "+f"(d[35]), "+f"(d[36]), "+f"(d[37]), "+f"(d[38]), "+f"(d[39]), "+f"(d[40]), "+f"(d[41]), "+f"(d[42]), "+f"(d[43]), "+f"(d[44]), "+f"(d[45]), "+f"(d[46]), "+f"(d[47]), "+f"(d[48]), "+f"(d[49]), "+f"(d[50]), "+f"(d[51]), "+f"(d[52]), "+f"(d[53]), "+f"(d[54]), "+f"(d[55]), "+f"(d[56]), "+f"(d[57]), "+f"(d[58]), "+f"(d[59]), "+f"(d[60]), "+f"(d[61]), "+f"(d[62]), "+f"(d[63])
               : "l"(da), "l"(db), "r"(sc));
}

__device__ __forceinline__ void stsm4(uint32_t a, uint32_t r0, uint32_t r1, uint32_t r2, uint32_t r3) {
  asm volatile("stmatrix.sync.aligned.m8n8.x4.shared.b16 [%0],{%1,%2,%3,%4};" ::"r"(a), "r"(r0), "r"(r1), "r"(r2), "r"(r3) : "memory");
}
__device__ __forceinline__ void stsm4t(uint32_t a, uint32_t r0, uint32_t r1, uint32_t r2, uint32_t r3) {
  asm volatile("stmatrix.sync.aligned.m8n8.x4.trans.shared.b16 [%0],{%1,%2,%3,%4};" ::"r"(a), "r"(r0), "r"(r1), "r"(r2), "r"(r3) : "memory");
}
__device__ __forceinline__ void sts64(uint32_t a, uint32_t x, uint32_t y) { asm volatile("st.shared.v2.b32 [%0],{%1,%2};" ::"r"(a), "r"(x), "r"(y) : "memory"); }
__device__ __forceinline__ void st_async2u(uint32_t a, uint32_t x, uint32_t y, uint32_t bar) {
  asm volatile("st.async.weak.shared::cluster.mbarrier::complete_tx::bytes.v2.b32 [%0],{%1,%2},[%3];" ::"r"(a), "r"(x), "r"(y), "r"(bar) : "memory");
}
__device__ __forceinline__ void st_relaxed128(void* p, uint32_t x, uint32_t y, uint32_t z, uint32_t w) {
  asm volatile("{.reg .b128 v; mov.b128 v,{%1,%2,%3,%4}; st.relaxed.gpu.global.b128 [%0],v;}" ::"l"(p), "r"(x), "r"(y), "r"(z), "r"(w) : "memory");
}
__device__ __forceinline__ void st_relaxed64(void* p, uint32_t x, uint32_t y) {
  asm volatile("{.reg .b64 v; mov.b64 v,{%1,%2}; st.relaxed.gpu.global.b64 [%0],v;}" ::"l"(p), "r"(x), "r"(y) : "memory");
}
__device__ __forceinline__ uint4 ld_relaxed128(const void* p) {
  uint4 v;
  asm volatile("{.reg .b128 v; .reg .b64 lo, hi; ld.relaxed.gpu.global.b128 v,[%4]; mov.b128 {lo,hi},v; mov.b64 {%0,%1},lo; mov.b64 {%2,%3},hi;}" : "=r"(v.x), "=r"(v.y), "=r"(v.z), "=r"(v.w) : "l"(p) : "memory");
  return v;
}

__device__ __forceinline__ uint32_t pack_h2(float lo, float hi) {
  uint32_t r; asm("cvt.rn.satfinite.f16x2.f32 %0,%1,%2;" : "=r"(r) : "f"(hi), "f"(lo)); return r;
}
__device__ __forceinline__ void add_h2(float& lo, float& hi, uint32_t u, uint32_t v) {
  float a, b;
  asm("{.reg .b16 l, h; .reg .b32 s; add.rn.f16x2 s,%2,%3; mov.b32 {l,h},s; cvt.f32.f16 %0,l; cvt.f32.f16 %1,h;}" : "=f"(a), "=f"(b) : "r"(u), "r"(v));
  lo += a; hi += b;
}
__device__ __forceinline__ void mwait(uint32_t bar, uint32_t ph, int& spin) {
  asm volatile("{.reg .pred p, q;\nWAIT_LOOP:\n add.s32 %0,%0,1;\n setp.lt.s32 q,%0,%3;\n mbarrier.try_wait.parity.shared::cta.b64 p,[%1],%2;\n not.pred p,p;\n and.pred q,q,p;\n @q bra.uni WAIT_LOOP;\n}"
               : "+&r"(spin) : "r"(bar), "r"(ph), "n"(SPIN_TOT) : "memory");
}
__device__ __forceinline__ int keep(int x) { return __shfl_sync(0xffffffffu, x, threadIdx.x & 31); }
__device__ __forceinline__ uint32_t pin(uint32_t x) { asm volatile("" : "+r"(x)); return x; }
template <typename T> __device__ __forceinline__ T* pinp(T* x) { asm volatile("" : "+l"(x)); return x; }
__device__ __forceinline__ void st_async1u(uint32_t a, uint32_t x, uint32_t bar) {
  asm volatile("st.async.weak.shared::cluster.mbarrier::complete_tx::bytes.b32 [%0],%1,[%2];" ::"r"(a), "r"(x), "r"(bar) : "memory");
}
__device__ __forceinline__ uint32_t lds32(uint32_t a) { uint32_t v; asm volatile("ld.shared.b32 %0,[%1];" : "=r"(v) : "r"(a) : "memory"); return v; }
__device__ __forceinline__ uint2 lds64(uint32_t a) { uint2 v; asm volatile("ld.shared.v2.b32 {%0,%1},[%2];" : "=r"(v.x), "=r"(v.y) : "r"(a) : "memory"); return v; }

__device__ __forceinline__ void permute_cols(uint32_t tile, int tid) {
  for (int it = tid; it < 2560; it += 128) {
    const int row = it >> 2, q = it & 3;
    const uint32_t a0 = tile + row * 128 + (((2 * q) ^ (row & 7)) << 4), a1 = tile + row * 128 + (((2 * q + 1) ^ (row & 7)) << 4);
    const uint4 u = lds128(a0), v = lds128(a1);
    sts128(a0, make_uint4(__byte_perm(u.x, u.y, 0x5410), __byte_perm(u.z, u.w, 0x5410), __byte_perm(v.x, v.y, 0x5410), __byte_perm(v.z, v.w, 0x5410)));
    sts128(a1, make_uint4(__byte_perm(u.x, u.y, 0x7632), __byte_perm(u.z, u.w, 0x7632), __byte_perm(v.x, v.y, 0x7632), __byte_perm(v.z, v.w, 0x7632)));
  }
}

__device__ __forceinline__ void ln_row_to_image(const bf16* __restrict__ x, uint8_t* __restrict__ img, int row, int lane) {
  const uint4* src = reinterpret_cast<const uint4*>(x + (size_t)row * DM);
  uint4 v[3];
  v[0] = src[lane]; v[1] = src[lane + 32];
  v[2] = lane < 16 ? src[lane + 64] : make_uint4(0, 0, 0, 0);
  float s = 0.f;
#pragma unroll
  for (int i = 0; i < 3; i++) {
    s += bf_lo(v[i].x) + bf_hi(v[i].x) + bf_lo(v[i].y) + bf_hi(v[i].y) + bf_lo(v[i].z) + bf_hi(v[i].z) + bf_lo(v[i].w) + bf_hi(v[i].w);
  }
#pragma unroll
  for (int o = 16; o > 0; o >>= 1) s += __shfl_xor_sync(0xffffffffu, s, o);
  const float mean = s * (1.f / DM);
  float q = 0.f;
#pragma unroll
  for (int i = 0; i < 3; i++) {
    if (i < 2 || lane < 16) {
      const uint32_t w[4] = {v[i].x, v[i].y, v[i].z, v[i].w};
#pragma unroll
      for (int j = 0; j < 4; j++) { float a = bf_lo(w[j]) - mean, b = bf_hi(w[j]) - mean; q += a * a + b * b; }
    }
  }
#pragma unroll
  for (int o = 16; o > 0; o >>= 1) q += __shfl_xor_sync(0xffffffffu, q, o);
  const float rstd = rsqrtf(q * (1.f / DM) + 1e-5f);
#pragma unroll
  for (int i = 0; i < 3; i++) {
    if (i < 2 || lane < 16) {
      const int c = lane + 32 * i;
      uint4 o;
      o.x = pack_bf16((bf_lo(v[i].x) - mean) * rstd, (bf_hi(v[i].x) - mean) * rstd);
      o.y = pack_bf16((bf_lo(v[i].y) - mean) * rstd, (bf_hi(v[i].y) - mean) * rstd);
      o.z = pack_bf16((bf_lo(v[i].z) - mean) * rstd, (bf_hi(v[i].z) - mean) * rstd);
      o.w = pack_bf16((bf_lo(v[i].w) - mean) * rstd, (bf_hi(v[i].w) - mean) * rstd);
      const size_t off = (size_t)(row >> 5) * 40960 + (c >> 4) * 8192 + ((row >> 3) & 3) * 2048 + ((c >> 3) & 1) * 1024 + (row & 7) * 128 + (((c & 7) ^ (row & 7)) << 4);
      *reinterpret_cast<uint4*>(img + off) = o;
      float4* xf = reinterpret_cast<float4*>(g_x + (size_t)row * DM + c * 8);
      xf[0] = make_float4(bf_lo(v[i].x), bf_hi(v[i].x), bf_lo(v[i].y), bf_hi(v[i].y));
      xf[1] = make_float4(bf_lo(v[i].z), bf_hi(v[i].z), bf_lo(v[i].w), bf_hi(v[i].w));
    }
  }
}

__global__ void __launch_bounds__(256) k_pre(const bf16* __restrict__ x, const bf16* __restrict__ mem0) {
  const int row = blockIdx.x * 8 + (threadIdx.x >> 5);
  ln_row_to_image(x, g_xn[0], row, threadIdx.x & 31);
  const int gt = blockIdx.x * 256 + threadIdx.x;
  const uint4 sent = make_uint4(SENT, SENT, SENT, SENT);
  uint4* mail = reinterpret_cast<uint4*>(&g_mail[0][0]);
  for (int i = gt; i < 2 * MAIL_BYTES / 16; i += 65536) mail[i] = sent;
  uint4* mb = reinterpret_cast<uint4*>(&g_mbuf[0][0]);
  for (int i = gt; i < NSTEP * 1280; i += 65536) {
    const int p = i % 1280, st = i / 1280;
    uint4 v = sent;
    if (st == 0 || (st == LAG && (p & 8))) v = *reinterpret_cast<const uint4*>(mem0 + (p & 7) * DM + (p >> 4) * 8);
    mb[i] = v;
  }
  if (gt < NSTEP * 192) reinterpret_cast<uint4*>(&g_flag[0][0])[gt] = gt < 192 ? make_uint4(0, 0, 0, 0) : sent;
  if (gt < CN_NUM) g_cnt[gt][0] = 0;
}

namespace C {
constexpr int NKR = 37;
constexpr int OFF_WQ = 0, OFF_WK = 81920;
constexpr int OFF_YO = 163840, OFF_YV = OFF_YO + 6144;
constexpr int OFF_M = 176128;
__host__ __device__ constexpr int og_off(int c) { return c ? OFF_M + 14336 + c * 2048 : 229376; }
constexpr int OFF_KT = 196608;
constexpr int OFF_XT = OFF_KT + 10240;
constexpr int OFF_VT = OFF_XT + 7168;
constexpr int OFF_XM = OFF_VT + 11392;
constexpr int KS = 1280, VS = 1408;
__host__ __device__ constexpr int slot_off(int p) { return p == 2 ? OFF_M : OFF_KT + (p % 3) * 16384; }
constexpr int OFF_BAR = 231552;
constexpr int OFF_SAFE = OFF_BAR + 160;
constexpr int OFF_TS = OFF_BAR + 256;
constexpr int SMEM = 232448;
constexpr uint32_t SB0 = 1024;
constexpr int BAR_F = OFF_BAR, BAR_E = OFF_BAR + 40, BAR_M = OFF_BAR + 80, BAR_MOK = OFF_BAR + 88, BAR_XM = OFF_BAR + 96, BAR_XF = OFF_BAR + 104,
              BAR_XT = OFF_BAR + 112, BAR_MF = OFF_BAR + 120, BAR_OG = OFF_BAR + 128, BAR_W = OFF_BAR + 136, FLG_REDO = OFF_BAR + 144;
constexpr int NB_PRO = 1, NB_RD = 2, NB_MR = 3, NB_QK = 4, NB_SM = 5, NB_VA = 6, NB_VQ = 7, NB_A = 8, NB_Q = 9, NB_C = 10, NB_WQ = 11, NB_QI = 12, NB_SI = 13, NB_WV = 14;
#define B1 300
#define B2 400
#define FLP 0
#define OSG 2
#define QIE 4
#define SIE 2
#define WOE 1
#define OGF 0
#define VSP 8
#define RFK 5
#define PFD 3
#define WOL 0
#define NOWORK 0
constexpr float SCL = 0.07216878364870322f * 1.4426950408889634f / 256;
}

#define CBAR_SYNC(id, n) bar_sync(id, n)
#define CBAR_ARRIVE(id, n) bar_arrive(id, n)

__device__ __forceinline__ uint64_t wdesc(int off) { return mkdesc(C::SB0 + off, 8192, 1024); }
__device__ __forceinline__ uint64_t mdesc(int k) { return mkdesc_ns(C::SB0 + C::OFF_M + k * 512, 256, 128); }
__device__ __forceinline__ uint64_t tdesc(int k) { return mkdesc(C::SB0 + C::slot_off(k >> 3) + ((k >> 2) & 1) * 1024 + (k & 3) * 32, 16, 2048); }

__device__ __forceinline__ int dh_row(int n) { return (n & ~63) + (n & 32) + ((n >> 1) & 3) * 8 + ((n >> 3) & 3) * 2 + (n & 1); }
template <bool PERM>
__device__ __forceinline__ void load_weights_rs(uint32_t (&wf)[C::NKR][4], uint32_t sb, int stage, int yoff, int tid0) {
  using namespace C;
  const int i = (tid0 >> 3) & 3, n0 = (tid0 & 7) + (i >> 1) * 8;
  const int chunk = 2 * ((tid0 >> 5) & 3) + (i & 1);
  const int r0 = PERM ? dh_row(n0) : n0, r1 = PERM ? dh_row(n0 + 16) : n0 + 16;
  const uint32_t a0 = sb + stage + r0 * 128 + ((chunk ^ (r0 & 7)) << 4), a1 = sb + stage + r1 * 128 + ((chunk ^ (r1 & 7)) << 4);
#pragma unroll
  for (int k = 0; k < NKR; k++) ldsm4t(wf[k], ((k & 1) ? a1 : a0) + (k >> 1) * 4096);
#pragma unroll
  for (int k = 0; k < 40 - NKR; k++) {
    const int n = (NKR + k) * 16 + ((tid0 & 127) >> 3), r = PERM ? dh_row(n) : n, c = tid0 & 7;
    sts128(sb + yoff + (n - NKR * 16) * 128 + ((c ^ (n & 7)) << 4), lds128(sb + stage + r * 128 + ((c ^ (r & 7)) << 4)));
  }
  fence_async();
  CBAR_SYNC(NB_PRO, 384);
}
template <int STRIDE>
__device__ __forceinline__ void store_mem(const float (&d)[8], uint32_t base, int tid) {
  const int m = (tid >> 3) & 3;
  stsm4(base + (((tid >> 5) & 3) * 2 + (m & 1)) * STRIDE + (m >> 1) * 640 + (tid & 7) * 16, pack_bf16(d[0], d[1]), pack_bf16(d[2], d[3]),
        pack_bf16(d[4], d[5]), pack_bf16(d[6], d[7]));
}

__device__ __forceinline__ void load_pair(uint32_t sb, int i, int p, uint32_t slot, uint32_t bar, uint32_t ph, int& spin) {
  using namespace C;
  const uint8_t* s0 = g_xn[0] + (size_t)i * 40960 + p * 8192;
  const uint8_t* s1 = g_xn[NOWORK ? 0 : 1] + (size_t)(i - LAG) * 40960 + p * 8192;
  const uint8_t* sa = pinp(i < NSEG ? s0 : s1);
  const uint8_t* sc = pinp(i >= LAG ? s1 : s0);
  const uint32_t dst = pin(sb + slot), fb = pin(sb + BAR_F + 8 * p);
  mwait(bar, ph, spin);
  bulk_g2s_mc(dst, sa, 8192, fb);
  bulk_g2s_mc(dst + 8192, sc, 8192, fb);
}
__device__ __forceinline__ void first_fill(uint32_t sb, int i, int rank, int& spin) {
  using namespace C;
  const int s1 = i - LAG;
  if (!NOWORK && s1 >= 0) { cwait(CN_X + s1, 32, spin); fence_async_all(); }
  load_pair(sb, i, rank, rank == 2 ? OFF_M : OFF_KT + rank * 16384, sb + BAR_E + 8 * rank, (i - 1) & 1, spin);
}
__device__ __forceinline__ void release_round(uint32_t sb, int p, int tid) {
  using namespace C;
  const int lane = tid & 31;
  if (p < 2) { if (lane == 0) mbar_arrive_cluster(mapa(sb, p) + BAR_E + 8 * (3 + p)); }
  else if (lane < 3) mbar_arrive_cluster(mapa(sb, lane) + BAR_MOK);
}

template <int K0, int K1>
__device__ __forceinline__ void v_mem_pass(float (&d)[8], const uint32_t (&wf)[C::NKR][4]) {
  using namespace C;
  wg_fence();
#pragma unroll
  for (int k = K0; k < K1; k++) {
    if (k < NKR) wgmma_rs16(d, wf[k < NKR ? k : 0], mdesc(k), k != 32);
    else wgmma_ts16(d, wdesc(OFF_YV + (k - NKR) * 2048), mdesc(k), 1);
  }
  wg_commit();
}
__device__ __forceinline__ void chain_v(const uint32_t sb, const int tid0, const int cta, const int rank) {
  using namespace C;
  asm volatile("setmaxnreg.inc.sync.aligned.u32 208;");
  int spin = 0;
  uint32_t wf[NKR][4];
  if (tid0 == 256) first_fill(sb, 0, rank, spin);
  __syncwarp();
  mwait(sb + BAR_W, 0, spin);
  for (int it = tid0 & 127; it < 1280; it += 128) {
    const uint32_t base = sb + OFF_WK + (it >> 1) * 128;
    const int sw = ((it >> 1) & 7) ^ ((it & 1) * 4);
    const uint4 u0 = lds128(base + (sw << 4)), u1 = lds128(base + ((sw ^ 1) << 4)), u2 = lds128(base + ((sw ^ 2) << 4)), u3 = lds128(base + ((sw ^ 3) << 4));
    sts128(base + (sw << 4), make_uint4(u0.x, u1.x, u2.x, u3.x)); sts128(base + ((sw ^ 1) << 4), make_uint4(u0.y, u1.y, u2.y, u3.y));
    sts128(base + ((sw ^ 2) << 4), make_uint4(u0.z, u1.z, u2.z, u3.z)); sts128(base + ((sw ^ 3) << 4), make_uint4(u0.w, u1.w, u2.w, u3.w));
  }
  bar_sync(NB_RD, 128);
  load_weights_rs<false>(wf, sb, OFF_WK, OFF_YV, tid0);
#pragma unroll 1
  for (int i = 0; i < NSTEP; i++) {
    {
      float d[32];
      if (i > 0) CBAR_SYNC(NB_WV, 256);
#pragma unroll
      for (int p = 0; p < 5; p++) {
        mwait(sb + BAR_F + 8 * p, i & 1, spin);
        TS(i, 25 + p);
        wg_fence();
#pragma unroll
        for (int k = 8 * p; k < 8 * p + 8; k++) {
          if (k < NKR) wgmma_rs64(d, wf[k < NKR ? k : 0], tdesc(k), k);
          else wgmma_ts64(d, wdesc(OFF_YV + (k - NKR) * 2048), tdesc(k), 1);
          if (k == 8 * p + 1 && p >= 1 && p <= 3) {
            wg_commit(); wg_wait<1>();
            release_round(sb, p - 1, fresh(tid0));
            wg_fence();
          }
          if (k == 8 * p + RFK && (p == 1 || p == 2)) {
            wg_commit();
            if (rank == p - 1 && tid0 == 256) load_pair(sb, i, p + 2, slot_off(p + 2), sb + BAR_E + 8 * (p + 2), i & 1, spin);
            __syncwarp();
            wg_fence();
          }
        }
        wg_commit();
      }
      wg_wait<0>();
      TS(i, 23);
      CBAR_SYNC(NB_RD, 256);
      const int tid = fresh(tid0) & 127, m = (tid >> 3) & 3;
      if (tid >= 96) {
        if (tid < 101) { if (i + 1 < NSTEP) mbar_expect_tx(sb + BAR_F + 8 * (tid - 96), 16384); }
        else if (tid == 101) mbar_expect_tx(sb + BAR_XM, 2560);
        else if (tid == 102) mbar_expect_tx(sb + BAR_XT, 7168);
        else if (tid == 103) mbar_expect_tx(sb + BAR_OG, 4096);
        else if (tid < 106) mbar_arrive_cluster(mapa(sb, (rank + tid - 103) % 3) + BAR_XF);
        __syncwarp();
      }
      const uint32_t a = sb + OFF_VT + 256 + ((tid >> 5) * 2 + (m & 1)) * VS + (m >> 1) * 128 + (tid & 7) * 16;
#pragma unroll
      for (int s = 0; s < 4; s++)
        stsm4(a + (s & 1) * 256 + (s >> 1) * 640, pack_bf16(d[8 * s], d[8 * s + 1]), pack_bf16(d[8 * s + 2], d[8 * s + 3]),
              pack_bf16(d[8 * s + 4], d[8 * s + 5]), pack_bf16(d[8 * s + 6], d[8 * s + 7]));
      if (tid < 72) sts128(sb + OFF_VT + (tid >> 3) * VS + (tid & 7) * 16, make_uint4(0, 0, 0, 0));
      fence_async();
    }
    mwait(sb + BAR_XF, i & 1, spin);
    CBAR_ARRIVE(NB_QK, 384);
    CBAR_SYNC(NB_QI, 256);
    float d[8];
    v_mem_pass<32, 40>(d, wf);
    CBAR_SYNC(NB_SM, 256);
    wg_wait<0>();
    if (__builtin_expect(lds32(sb + FLG_REDO), 0)) { v_mem_pass<32, 40>(d, wf); wg_wait<0>(); }
    if ((tid0 & 31) < 2) mbar_arrive_cluster(mapa(sb, (rank + 1 + (tid0 & 1)) % 3) + BAR_MF);
    v_mem_pass<0, 32>(d, wf);
    wg_wait<0>();
    TS(i, 24);
    const int tid = fresh(tid0);
    if ((tid & 31) == 0) mbar_arrive_cluster(mapa(sb, 2) + BAR_E + 16);
    store_mem<VS>(d, sb + OFF_VT + 128, tid);
    fence_async();
    CBAR_ARRIVE(NB_VA, 256);
    CBAR_ARRIVE(NB_VQ, 256);
    if (tid == 256) {
      if (i + 1 < NSTEP) { first_fill(sb, i + 1, rank, spin); TS1(i + 1, 37); }
    } else if (tid >= 288 && tid < 295) {
      const int lane = tid & 31, ip = i + PFD;
      if (cta < 80 && ip < NSTEP) {
        if (lane < 2) prefetch_l2(g_mbuf[ip] + (cta * 2 + lane) * 128);
        else if (lane == 6) { if (cta < 22) prefetch_l2(&g_flag[ip][cta * 32]); }
        else if (ip < NSEG) prefetch_l2(g_xn[0] + (size_t)ip * 40960 + (cta * 4 + lane - 2) * 128);
      }
    }
    TS_FLUSH(i - 1);
    __syncwarp();
  }
  if (spin >= SPIN_TOT) g_err = 3;
}

__device__ __forceinline__ float quad_max(float x) {
  const float a = __shfl_xor_sync(0xffffffffu, x, 1), b = __shfl_xor_sync(0xffffffffu, x, 2), c = __shfl_xor_sync(0xffffffffu, x, 3);
  return fmaxf(fmaxf(x, a), fmaxf(b, c));
}
__device__ __forceinline__ float quad_sum(float x) {
  const float a = __shfl_xor_sync(0xffffffffu, x, 1), b = __shfl_xor_sync(0xffffffffu, x, 2), c = __shfl_xor_sync(0xffffffffu, x, 3);
  return (x + a) + (b + c);
}
__device__ __forceinline__ float max10(const float (&y)[10]) {
  return fmaxf(fmaxf(fmaxf(fmaxf(y[0], y[1]), fmaxf(y[2], y[3])), fmaxf(fmaxf(y[4], y[5]), fmaxf(y[6], y[7]))), fmaxf(y[8], y[9]));
}
__device__ __forceinline__ float sum10(const float (&y)[10]) {
  return (((y[0] + y[1]) + (y[2] + y[3])) + ((y[4] + y[5]) + (y[6] + y[7]))) + (y[8] + y[9]);
}
__device__ __forceinline__ float rcp(float x) { float y; asm("rcp.approx.ftz.f32 %0,%1;" : "=f"(y) : "f"(x)); return y; }

__device__ __forceinline__ void signal_o(int i, int cta) { csignal(CN_O + i * 5 + min(cta / 19, 4)); }

__device__ __forceinline__ void chain_q(const CUtensorMap& tmWq, const CUtensorMap& tmWk, const uint32_t sb, const int tid0, const int cta, const int rank) {
  using namespace C;
  asm volatile("setmaxnreg.dec.sync.aligned.u32 96;");
  int spin = 0;
  CBAR_SYNC(NB_PRO, 384);
  PTS(5);
  if (tid0 == 128) {
    const int col = (cta / 3) * DH + rank * 64;
    mbar_expect_tx(sb + BAR_W, 163840);
    for (int i = 0; i < 5; i++) {
      tma2d(sb + OFF_WQ + i * 16384, &tmWq, col, i * 128, sb + BAR_W);
      tma2d(sb + OFF_WK + i * 16384, &tmWk, col, i * 128, sb + BAR_W);
    }
  }
  __syncwarp();
  mwait(sb + BAR_W, 1, spin);
  PTS(6);
#pragma unroll 1
  for (int i = 0; i < NSTEP; i++) {
    const int ph = i & 1;
    uint32_t qf[4][4];
    {
      float d[64];
#pragma unroll
      for (int p = 0; p < 5; p++) {
        mwait(sb + BAR_F + 8 * p, ph, spin);
        if (p == 0) TS(i, 0);
        wg_fence();
#pragma unroll
        for (int k = 8 * p; k < 8 * p + 8; k++) {
          wgmma_st128(d, tdesc(k), mkdesc(SB0 + OFF_WQ + k * 2048, OFF_WK - OFF_WQ, 1024), k);
          if (k == 8 * p + 1 && p >= 1 && p <= 3) {
            wg_commit(); wg_wait<1>();
            release_round(sb, p - 1, fresh(tid0));
            wg_fence();
          }
        }
        wg_commit();
      }
      wg_wait<0>();
      TS(i, 1);
      CBAR_SYNC(NB_RD, 256);
      TSB(i, 2);
      const int tid = fresh(tid0), w = (tid >> 5) & 3, m = (tid >> 3) & 3;
      const uint32_t a = sb + OFF_KT + (m >> 1) * KS + (1 + 5 * (w >> 1) + 2 * (w & 1) + (m & 1)) * 128 + (tid & 7) * 16;
#pragma unroll
      for (int s = 0; s < 4; s++)
        stsm4t(a + s * 2 * KS, pack_bf16(d[32 + 8 * s], d[33 + 8 * s]), pack_bf16(d[34 + 8 * s], d[35 + 8 * s]),
               pack_bf16(d[36 + 8 * s], d[37 + 8 * s]), pack_bf16(d[38 + 8 * s], d[39 + 8 * s]));
      fence_async();
      CBAR_ARRIVE(NB_QK, 384);
      if (OSG == 0) { if (tid == 224 && i > 0) signal_o(i - 1, cta); __syncwarp(); }
#pragma unroll
      for (int kk = 0; kk < 4; kk++)
#pragma unroll
        for (int j = 0; j < 4; j++) asm volatile("cvt.rn.bf16x2.f32 %0,%1,%2;" : "=r"(qf[kk][j]) : "f"(d[8 * kk + 2 * j + 1]), "f"(d[8 * kk + 2 * j]));
    }
    CBAR_SYNC(NB_SI, 256);
    uint32_t pf[5][4];
    float s0, s1;
    {
      float y0[10], y1[10];
      const int tid = fresh(tid0), lane = tid & 31, u = (tid >> 5) & 1;
      const bool c1 = tid & 64;
      {
        float x[40];
        wg_fence();
#pragma unroll
        for (int kk = 0; kk < 4; kk++) wgmma_rt80(x, qf[kk], mkdesc_ns(SB0 + OFF_KT + kk * 2 * KS, KS, 128), kk);
        wg_commit();
        wg_wait<0>();
#pragma unroll
        for (int j = 0; j < 5; j++) {
          y0[2 * j] = (c1 ? x[20 + 4 * j] : x[4 * j]) * SCL; y0[2 * j + 1] = (c1 ? x[21 + 4 * j] : x[4 * j + 1]) * SCL;
          y1[2 * j] = (c1 ? x[22 + 4 * j] : x[4 * j + 2]) * SCL; y1[2 * j + 1] = (c1 ? x[23 + 4 * j] : x[4 * j + 3]) * SCL;
        }
      }
      TS(i, 17);
      const uint32_t xo = OFF_XT + (c1 ? 1792 : 0) + u * 640 + lane * 16, x2 = xo + u * 512 + 512 - lane * 12;
      {
        const uint4 h0 = make_uint4(pack_h2(y0[0], y0[1]), pack_h2(y0[2], y0[3]), pack_h2(y1[0], y1[1]), pack_h2(y1[2], y1[3]));
        const uint4 h1 = make_uint4(pack_h2(y0[4], y0[5]), pack_h2(y0[6], y0[7]), pack_h2(y1[4], y1[5]), pack_h2(y1[6], y1[7]));
        const uint32_t h2 = u ? pack_h2(y1[8], y1[9]) : h1.z;
#pragma unroll
        for (int dd = 0; dd < 2; dd++) {
          const uint32_t rb = mapa(sb, (rank + 1 + dd) % 3), ro = rb + (1 - dd) * 3584;
          st_async4u(ro + xo, h0, rb + BAR_XT);
          if (u) st_async4u(ro + xo + 512, h1, rb + BAR_XT);
          st_async1u(ro + x2, h2, rb + BAR_XT);
        }
      }
      TS(i, 18);
      const int lim = 16 * u + (lane >> 2) + 8 - 2 * (lane & 3);
#pragma unroll
      for (int j = 1; j < 5; j++) {
        if (8 * j > lim) y0[2 * j] = -INFINITY;
        if (8 * j + 1 > lim) y0[2 * j + 1] = -INFINITY;
        if (8 * j - 8 > lim) y1[2 * j] = -INFINITY;
        if (8 * j - 7 > lim) y1[2 * j + 1] = -INFINITY;
      }
      mwait(sb + BAR_XT, ph, spin);
      TS(i, 19);
      {
        const uint4 u0 = lds128(sb + xo), v0 = lds128(sb + xo + 3584);
        const uint32_t u2 = lds32(sb + x2), v2 = lds32(sb + x2 + 3584);
        uint4 u1 = make_uint4(0, 0, u2, 0), v1 = make_uint4(0, 0, v2, 0);
        if (u) { u1 = lds128(sb + xo + 512); v1 = lds128(sb + xo + 512 + 3584); }
        __syncwarp();
        if (lane == 0) mbar_arrive_cluster(mapa(sb, 0) + BAR_E);
        add_h2(y0[0], y0[1], u0.x, v0.x); add_h2(y0[2], y0[3], u0.y, v0.y); add_h2(y1[0], y1[1], u0.z, v0.z); add_h2(y1[2], y1[3], u0.w, v0.w);
        add_h2(y0[4], y0[5], u1.x, v1.x); add_h2(y0[6], y0[7], u1.y, v1.y); add_h2(y1[4], y1[5], u1.z, v1.z); add_h2(y1[6], y1[7], u1.w, v1.w);
        add_h2(y1[8], y1[9], u2, v2);
      }
      y0[8] = y0[0]; y0[9] = y0[1];
      const float m0 = quad_max(max10(y0)) * -256.f, m1 = quad_max(max10(y1)) * -256.f;
      s0 = 0.f; s1 = 0.f;
#pragma unroll
      for (int j = 0; j < 5; j++) {
        const uint32_t p0 = j < 4 ? pack_bf16(ex2(fmaf(y0[2 * j], 256.f, m0)), ex2(fmaf(y0[2 * j + 1], 256.f, m0))) : 0u;
        const uint32_t p1 = pack_bf16(ex2(fmaf(y1[2 * j], 256.f, m1)), ex2(fmaf(y1[2 * j + 1], 256.f, m1)));
        s0 += bf_lo(p0) + bf_hi(p0); s1 += bf_lo(p1) + bf_hi(p1);
        pf[j >> 1][2 * (j & 1)] = c1 ? 0u : p0; pf[j >> 1][2 * (j & 1) + 1] = c1 ? 0u : p1;
        pf[(j + 5) >> 1][2 * ((j + 5) & 1)] = c1 ? p0 : 0u; pf[(j + 5) >> 1][2 * ((j + 5) & 1) + 1] = c1 ? p1 : 0u;
      }
    }
    CBAR_SYNC(NB_VQ, 256);
    TSB(i, 20);
    {
      float o[32];
      wg_fence();
#pragma unroll
      for (int q = 0; q < 5; q++) wgmma_rs64(o, pf[q], mkdesc_ns(SB0 + OFF_VT + 128 + q * 256, 128, VS), q);
      wg_commit();
      s0 = rcp(quad_sum(s0)); s1 = rcp(quad_sum(s1));
      const int tid = fresh(tid0), g = (tid >> 2) & 7, c = (tid >> 6) & 1, sg = i - c * LAG;
      uint8_t* op = pinp(&g_o[i % ORING][c][cta][(((tid >> 5) & 1) * 16 + g) * 128]);
      const uint32_t o0 = pin(((tid & 3) ^ g) << 4), live = pin(sg >= 0 && sg < NSEG);
      wg_wait<0>();
      TS(i, 21);
      if ((tid & 31) == 0) mbar_arrive_cluster(mapa(sb, 1) + BAR_E + 8);
      uint4 ov[4];
#pragma unroll
      for (int h = 0; h < 2; h++) {
        const float* x = o + 16 * h;
        ov[2 * h] = make_uint4(pin(pack_bf16(x[0] * s0, x[1] * s0)), pin(pack_bf16(x[4] * s0, x[5] * s0)), pin(pack_bf16(x[8] * s0, x[9] * s0)), pin(pack_bf16(x[12] * s0, x[13] * s0)));
        ov[2 * h + 1] = make_uint4(pin(pack_bf16(x[2] * s1, x[3] * s1)), pin(pack_bf16(x[6] * s1, x[7] * s1)), pin(pack_bf16(x[10] * s1, x[11] * s1)), pin(pack_bf16(x[14] * s1, x[15] * s1)));
      }
      TS(i, 22);
      if (i + 1 < NSTEP) CBAR_SYNC(NB_WQ, 256);
      if (live) {
#pragma unroll
        for (int h = 0; h < 4; h++) *reinterpret_cast<uint4*>(op + (h & 1) * 1024 + (o0 ^ ((h >> 1) * 64))) = ov[h];
      }
      if (OSG && i + 1 < NSTEP) CBAR_ARRIVE(NB_MR, 160);
    }
  }
  CBAR_SYNC(NB_Q, 128);
  if (tid0 == 224) signal_o(NSTEP - 1, cta);
  if (spin >= SPIN_TOT) g_err = 2;
}

template <int NL>
__device__ __forceinline__ void poll_add(const uint8_t* mb, uint32_t tag, float (&f)[8], uint32_t* flag, int osig, int& n, int& spin) {
  uint4 x[NL];
#pragma unroll
  for (int i = 0; i < NL; i++) x[i] = ld_relaxed128(mb + i * 512);
  if (OSG == 1 && osig >= 0) csignal(osig);
  while (true) {
    bool bad = false;
#pragma unroll
    for (int i = 0; i < NL; i++)
      if (((x[i].x ^ tag) | (NL == 6 ? x[i].z ^ tag : 0u)) & 1) { bad = true; x[i] = ld_relaxed128(mb + i * 512); }
    n++;
    spin += 16;
    if (!__any_sync(0xffffffffu, bad && spin < SPIN_TOT)) break;
  }
  if (FLP == 0 && flag) st_relaxed(flag, 0);
#pragma unroll
  for (int i = 0; i < NL; i++) {
    const uint32_t u[4] = {x[i].x, x[i].y, x[i].z, x[i].w};
#pragma unroll
    for (int j = 0; j < 4; j++) {
      if (i == 0) { f[2 * j] = bf_lo(u[j]); f[2 * j + 1] = bf_hi(u[j]); }
      else { f[2 * j] += bf_lo(u[j]); f[2 * j + 1] += bf_hi(u[j]); }
    }
  }
}

template <int B, int SLOT>
__device__ __forceinline__ void wo_block(float (&acc)[8], const uint32_t (&wf)[C::NKR][4]) {
  using namespace C;
#pragma unroll
  for (int kk = 0; kk < 4; kk++) {
    const int k = 4 * B + kk;
    const uint64_t db = mkdesc_ns(SB0 + og_off(SLOT) + kk * 512, 256, 128);
    if (k < NKR) wgmma_rt16(acc, wf[k < NKR ? k : 0], db, SLOT | kk);
    else wgmma_tt16(acc, wdesc(OFF_YO + (k - NKR) * 2048), db, 1);
  }
}

__device__ __forceinline__ void chain_a(const uint32_t sb, const int tid0, const int cta, const int rank) {
  using namespace C;
  asm volatile("setmaxnreg.inc.sync.aligned.u32 200;");
  int spin = 0;
  uint32_t wf[NKR][4];
  mwait(sb + BAR_W, 0, spin);
  permute_cols(sb + OFF_WQ, tid0);
  CBAR_SYNC(NB_A, 128);
  load_weights_rs<true>(wf, sb, OFF_WQ, OFF_YO, tid0);

#pragma unroll 1
  for (int i = -1; i < NSTEP; i++) {
    const int ph = i & 1;
    if (i >= 0) {
      if (i == 0) mwait(sb + BAR_W, 1, spin);
      mwait(sb + BAR_M, ph, spin);
      TS(i, 3);
      {
        float x[20];
        int redo = 0;
      retry:
        bool bad;
        {
          float dq[8], dk[8];
          wg_fence();
#pragma unroll
          for (int k = 0; k < 40; k++) wgmma_ts16(dq, wdesc(OFF_WQ + k * 2048), mdesc(k), k);
          wg_commit();
#pragma unroll
          for (int k = 0; k < 40; k++) {
            if (k == 40 - QIE && !redo) CBAR_ARRIVE(NB_QI, 256);
            wgmma_ts16(dk, wdesc(OFF_WK + k * 2048), mdesc(k), k);
          }
          wg_commit();
          const int m = (tid0 >> 3) & 3, dg = (tid0 >> 5) * 2 + (m & 1);
          const uint32_t ka = sb + OFF_KT + dg * KS + (m >> 1) * 640 + (tid0 & 7) * 16;
          wg_wait<1>();
          const float chk = (dq[0] + dq[1]) + (dq[4] + dq[5]);
          const uint32_t q0 = pack_bf16(dq[0], dq[1]), q1 = pack_bf16(dq[2], dq[3]), q2 = pack_bf16(dq[4], dq[5]), q3 = pack_bf16(dq[6], dq[7]);
          if (!redo) CBAR_SYNC(NB_QK, 384);
          stsm4(ka + dg * (VS - KS) + (OFF_VT + 128 - OFF_KT), q0, q1, q2, q3);
          sts32(sb + FLG_REDO, redo);
          wg_wait<0>();
          TS(i, 4);
          stsm4(ka, pack_bf16(dk[0], dk[1]), pack_bf16(dk[2], dk[3]), pack_bf16(dk[4], dk[5]), pack_bf16(dk[6], dk[7]));
          fence_async();
          bad = bar_red_or(NB_C, 128, chk != chk && !redo);
        }
        TSB(i, 5);
        wg_fence();
#pragma unroll
        for (int kk = 0; kk < 4; kk++) wgmma_tt40(x, mkdesc_ns(SB0 + OFF_VT + 128 + kk * 2 * VS, VS, 640), mkdesc_ns(SB0 + OFF_KT + kk * 2 * KS, KS, 128), kk);
#pragma unroll
        for (int kk = 0; kk < 4; kk++) {
          if (kk == 4 - SIE && !bad) CBAR_ARRIVE(NB_SI, 256);
          wgmma_tt40(x, mkdesc_ns(SB0 + OFF_VT + kk * 2 * VS, VS, 384), mkdesc_ns(SB0 + OFF_KT + 640 + kk * 2 * KS, KS, 128), 1);
        }
        wg_commit();
        if (__builtin_expect(bad, 0)) {
          wg_wait<0>();
#pragma unroll 1
          for (int k = 0; k < 10; k++) {
            uint4 v = lds128(sb + OFF_M + tid0 * 16 + k * 2048);
            if (v.x == SENT || v.y == SENT || v.z == SENT || v.w == SENT) {
              do { v = ld_relaxed4(g_mbuf[i] + tid0 * 16 + k * 2048); spin += 16; } while ((v.x == SENT || v.y == SENT || v.z == SENT || v.w == SENT) && spin < SPIN_TOT);
              sts128(sb + OFF_M + tid0 * 16 + k * 2048, v);
            }
          }
          fence_async();
          bar_sync(NB_C, 128);
          redo = fresh(1);
          goto retry;
        }
        TSV(i, 36, redo);
        const int tid = fresh(tid0), lane = tid & 31, w = tid >> 5;
        const uint32_t xo = OFF_XM + w * 1280 + lane * 16, x1 = OFF_XM + w * 1280 + lane * 4;
        const uint32_t rb1 = mapa(sb, (rank + 1) % 3), rb2 = mapa(sb, (rank + 2) % 3);
        const uint32_t ra = pin(rb1 + xo + 640), rb = pin(rb1 + x1 + 1152), rc = pin(rb2 + xo), rd = pin(rb2 + x1 + 512);
        const uint32_t la = pin(sb + xo), lb = pin(sb + x1);
        const uint32_t pa = pin(sb + OFF_XM + w * 1280 + (lane & 7) * 4 + (lane & 8) * 8 + (lane & 16) * 2);
        wg_wait<0>();
        TS(i, 6);
        if (w < 2) {
          float y[10];
#pragma unroll
          for (int j = 0; j < 5; j++) { y[2 * j] = x[4 * j] * SCL; y[2 * j + 1] = x[4 * j + 1] * SCL; }
          const uint4 h0 = make_uint4(pack_h2(y[0], y[1]), pack_h2(y[2], y[3]), pack_h2(y[4], y[5]), pack_h2(y[6], y[7]));
          const uint32_t h1 = pack_h2(y[8], y[9]);
          st_async4u(ra, h0, rb1 + BAR_XM);
          st_async4u(rc, h0, rb2 + BAR_XM);
          st_async1u(rb, h1, rb1 + BAR_XM);
          st_async1u(rd, h1, rb2 + BAR_XM);
          CBAR_ARRIVE(NB_SM, 256);
          if (lane == 0) mbar_arrive_cluster(mapa(sb, 0) + BAR_E);
          TS(i, 7);
          mwait(sb + BAR_XM, ph, spin);
          TS(i, 8);
          const uint4 u0 = lds128(la), v0 = lds128(la + 640);
          const uint32_t u1 = lds32(lb + 512), v1 = lds32(lb + 1152);
          add_h2(y[0], y[1], u0.x, v0.x); add_h2(y[2], y[3], u0.y, v0.y); add_h2(y[4], y[5], u0.z, v0.z); add_h2(y[6], y[7], u0.w, v0.w);
          add_h2(y[8], y[9], u1, v1);
          const float mx = quad_max(max10(y)) * -256.f;
          sts32(pa + 640, 0);
#pragma unroll
          for (int j = 0; j < 5; j++) {
            y[2 * j] = ex2(fmaf(y[2 * j], 256.f, mx)); y[2 * j + 1] = ex2(fmaf(y[2 * j + 1], 256.f, mx));
            sts32(pa + j * 128, pack_bf16(y[2 * j], y[2 * j + 1]));
          }
          sts32(pa + 768, __float_as_uint(sum10(y)));
          fence_async();
          TS(i, 9);
        } else {
          CBAR_ARRIVE(NB_SM, 256);
          if (lane == 0) mbar_arrive_cluster(mapa(sb, 0) + BAR_E);
          mwait(sb + BAR_MF, ph, spin);
        }
      }
      CBAR_SYNC(NB_VA, 256);
      TSB(i, 10);
      {
        float o[2][4];
        wg_fence();
#pragma unroll
        for (int c = 0; c < 2; c++)
#pragma unroll
          for (int q = 0; q < 3; q++)
            wgmma_ss8(o[c], mkdesc_ns(SB0 + OFF_VT + 128 + c * 640 + q * 256, 128, VS), mkdesc_ns(SB0 + OFF_XM + c * 1280 + q * 256, 128, 128), q);
        wg_commit();
        const int tid = fresh(tid0);
        const float4 e = lds128f(sb + OFF_XM + 768 + (tid & 3) * 32 + (tid & 4) * 4 + (tid & 8) * 160);
        const uint32_t oo = (tid >> 5) * 512 + (tid & 2) * 64 + ((tid & 31) >> 2) * 16 + (tid & 1) * 8;
        const uint32_t rb1 = mapa(sb, (rank + 1) % 3), rb2 = mapa(sb, (rank + 2) % 3);
        const uint32_t ra = pin(rb1 + oo + og_off(2)), rc = pin(rb2 + oo + og_off(1)), la = pin(sb + oo + og_off(0));
        const float inv = rcp((e.x + e.y) + (e.z + e.w));
        const float i0 = __shfl_sync(0xffffffffu, inv, tid & 3), i1 = __shfl_sync(0xffffffffu, inv, (tid & 3) + 4);
        const float i2 = __shfl_sync(0xffffffffu, inv, (tid & 3) + 8), i3 = __shfl_sync(0xffffffffu, inv, (tid & 3) + 12);
        wg_wait<0>();
        TS(i, 11);
        const uint32_t p0 = pack_bf16(o[0][0] * i0, o[0][1] * i1), p1 = pack_bf16(o[1][0] * i2, o[1][1] * i3);
        const uint32_t p2 = pack_bf16(o[0][2] * i0, o[0][3] * i1), p3 = pack_bf16(o[1][2] * i2, o[1][3] * i3);
        if (OGF) { sts64(la, p0, p1); sts64(la + 256, p2, p3); fence_async(); }
        st_async2u(ra, p0, p1, rb1 + BAR_OG);
        st_async2u(rc, p0, p1, rb2 + BAR_OG);
        st_async2u(ra + 256, p2, p3, rb1 + BAR_OG);
        st_async2u(rc + 256, p2, p3, rb2 + BAR_OG);
        if (!OGF) { sts64(la, p0, p1); sts64(la + 256, p2, p3); fence_async(); }
      }
      if (i + 1 >= NSTEP) { mwait(sb + BAR_OG, ph, spin); break; }
      CBAR_SYNC(NB_A, 128);
      TSB(i, 12);
      {
        float acc[3][8];
        wg_fence();
        wo_block<0, 0>(acc[2], wf);
        wg_commit();
        wo_block<1, 0>(acc[0], wf);
        wo_block<4, 0>(acc[1], wf);
        wg_commit();
        const int tid = fresh(tid0), w = tid >> 5, g = (tid & 31) >> 2, t = tid & 3;
        if ((tid & 31) == 0) mbar_arrive_cluster(mapa(sb, 1) + BAR_E + 8);
        const uint32_t tag = (i >> 1) & 1, radd = tag ? 0u : 0x10000u;
#define TAGGED(LO, HI) __byte_perm(((__float_as_uint(LO) + radd) & 0xFFFE0000u) | (tag << 16), pack_bf16(0.f, HI), 0x7632)
#define SEND(PTR, U) st_relaxed128((PTR), TAGGED(acc[U][0], acc[U][2]), pack_bf16(acc[U][1], acc[U][3]), pack_bf16(acc[U][4], acc[U][6]), pack_bf16(acc[U][5], acc[U][7]))
        uint8_t* m9 = pinp(g_mail[ph] + MAIL9 + (((2 * w + (g >> 2)) * 2 + (t & 1)) * 4 + (t & 2)) * 3072 + cta * 32 + (g & 3) * 8);
        wg_wait<1>();
        const uint32_t n0 = pin(TAGGED(acc[2][0], acc[2][2])), n1 = pin(pack_bf16(acc[2][1], acc[2][3]));
        const uint32_t n2 = pin(TAGGED(acc[2][4], acc[2][6])), n3 = pin(pack_bf16(acc[2][5], acc[2][7]));
        wg_fence();
        wo_block<7, 0>(acc[2], wf);
        wg_commit();
        st_relaxed64(m9, n0, n1);
        st_relaxed64(m9 + 3072, n2, n3);
        uint8_t* mb = pinp(g_mail[ph] + (((rank * 12 + w) * 2 + (g >> 2)) * 4 + t) * 2048 + (cta / 3) * 64 + (g & 3) * 16);
        mwait(sb + BAR_OG, ph, spin);
        asm volatile("fence.proxy.async::generic.acquire.sync_restrict::shared::cluster.cluster;" ::: "memory");
        TS(i, 13);
        wg_fence();
        wo_block<2, 1>(acc[0], wf); wo_block<3, 2>(acc[0], wf);
        wg_commit();
        wo_block<5, 1>(acc[1], wf); wo_block<6, 2>(acc[1], wf);
        wg_commit();
        wg_wait<1>(); SEND(mb, 0);
        wg_fence();
        wo_block<8, 1>(acc[2], wf); wo_block<9, 2>(acc[2], wf);
        wg_commit();
        if (WOE == 0) { CBAR_ARRIVE(NB_WV, 256); CBAR_ARRIVE(NB_WQ, 256); }
        wg_wait<1>(); SEND(mb + 32 * 2048, 1);
        if (WOE == 1) CBAR_ARRIVE(NB_WV, 256);
        wg_wait<0>(); SEND(mb + 64 * 2048, 2);
        if (WOE == 2) CBAR_ARRIVE(NB_WV, 256);
        if (WOE >= 1) CBAR_ARRIVE(NB_WQ, 256);
#undef SEND
#undef TAGGED
      }
      TS(i, 14);
    }
    const uint32_t t0 = clk32();
    uint32_t t1 = t0;
    if (i >= 0) {
      const int tid = fresh(tid0), lane = tid & 31;
      const uint32_t tag = (i >> 1) & 1;
      const bool t9 = cta >= 72 && cta < 88;
      const int w = tid >> 5, j = lane >> 3;
      const uint32_t pub = pin((lane & (t9 ? 6 : 4)) == 0 && !(((t9 ? cta : w) & 1) && i + 1 == LAG) && cta < 88);
      uint8_t* dst = pinp(g_mbuf[i + 1] + (t9 ? (cta + 72) * 128 + w * 32 + (j & 1) * 16 + (lane & 1) * 8 + (j >> 1) * 4
                                               : cta * 256 + (w & 1) * 128 + (w >> 1) * 64 + j * 16 + (lane & 3) * 4));
      uint32_t* flag = pinp(lane == 0 && cta < 88 ? &g_flag[i + 1][cta * 8 + w] : nullptr);
      float f[8];
      int n = 0;
      if (OSG && w == 3) CBAR_SYNC(NB_MR, 160);
      const int osig = tid == 96 ? CN_O + i * 5 + min(cta / 19, 4) : -1;
      while (clk32() - t0 < B1) {}
      TS(i + 1, 30);
      if (!t9) poll_add<4>(g_mail[ph] + (cta < 72 ? cta : cta - 24) * 8192 + (tid >> 5) * 2048 + lane * 16, tag, f, flag, osig, n, spin);
      else poll_add<6>(g_mail[ph] + MAIL9 + (cta - 72) * 12288 + (tid >> 5) * 3072 + lane * 16, tag, f, flag, osig, n, spin);
      if (FLP == 1 && flag) st_relaxed(flag, __float_as_uint(f[0] + f[7]) >> 1);
      t1 = clk32();
      TS(i + 1, 31); TSV(i + 1, 32, n);
      const bool h = lane & 16, q = lane & 8;
#pragma unroll
      for (int j = 0; j < 4; j++) f[j] = (h ? f[4 + j] : f[j]) + __shfl_xor_sync(0xffffffffu, h ? f[j] : f[4 + j], 16);
#pragma unroll
      for (int j = 0; j < 2; j++) f[j] = (q ? f[2 + j] : f[j]) + __shfl_xor_sync(0xffffffffu, q ? f[j] : f[2 + j], 8);
      f[0] += __shfl_xor_sync(0xffffffffu, f[0], 4); f[1] += __shfl_xor_sync(0xffffffffu, f[1], 4);
      if (t9) { f[0] += __shfl_xor_sync(0xffffffffu, f[0], 2); f[1] += __shfl_xor_sync(0xffffffffu, f[1], 2); }
      if (pub) st_relaxed(dst, pack_bf16(f[0], f[1]));
      if (FLP == 2 && flag) st_relaxed(flag, 0);
      if (OSG == 2 && osig >= 0) csignal(osig);
      TS(i + 1, 15);
    }
    if (tid0 < 32) {
      const uint8_t* src = pinp(g_mbuf[i + 1] + rank * 7168);
      const uint32_t* pp = pinp(&g_flag[i + 1][(rank * 28 + (tid0 < 28 || rank == 2 ? tid0 : 0)) * 8]);
      const uint32_t dst = pin(sb + OFF_M + rank * 7168), len = pin(rank == 2 ? 6144 : 7168);
      if (tid0 == 0) mbar_expect_tx(sb + BAR_M, 20480);
      while (clk32() - t1 < B2) {}
      TS(i + 1, 16);
      int n = 0;
      uint4 x;
      do { x = ld_relaxed4(pp); n++; spin += 16; } while (__any_sync(0xffffffffu, (int)(x.x | x.y | x.z | x.w) < 0 && spin < SPIN_TOT));
      TSV(i + 1, 35, n);
      TS(i + 1, 34);
      mwait(sb + BAR_MOK, ph ^ 1, spin);
      if (tid0 == 0) bulk_g2s_mc(dst, src, len, sb + BAR_M);
      TS(i + 1, 33);
      __syncwarp();
    }
  }
  if (spin >= SPIN_TOT) g_err = 1;
}

__global__ void __cluster_dims__(3, 1, 1) __launch_bounds__(384, 1)
k_chain(const __grid_constant__ CUtensorMap tmWq, const __grid_constant__ CUtensorMap tmWk,
        const __grid_constant__ CUtensorMap tmWv, const __grid_constant__ CUtensorMap tmWo) {
  using namespace C;
  extern __shared__ __align__(1024) uint8_t smem[];
  const uint32_t sb = smem_u32(smem);
  const int tid = threadIdx.x;
  const int wg = __shfl_sync(0xffffffffu, tid >> 7, 0);
  const int cta = blockIdx.x, rank = cta % 3;

  asm volatile("griddepcontrol.launch_dependents;");
  if (tid == 0) {
    if ((sb & 0xFFFFFF) != SB0) g_err = 100;
    for (int p = 0; p < 5; p++) { mbar_init(sb + BAR_F + 8 * p, 1); mbar_init(sb + BAR_E + 8 * p, p == 2 ? 12 : 24); }
    mbar_init(sb + BAR_M, 1); mbar_init(sb + BAR_MOK, 24); mbar_init(sb + BAR_XM, 1); mbar_init(sb + BAR_XF, 2);
    mbar_init(sb + BAR_XT, 1); mbar_init(sb + BAR_MF, 8); mbar_init(sb + BAR_OG, 1); mbar_init(sb + BAR_W, 1);
    for (int p = 0; p < 5; p++) mbar_expect_tx(sb + BAR_F + 8 * p, 16384);
    for (int p = 0; p < 16; p++) sts32(sb + OFF_SAFE + 4 * p, 0);
    asm volatile("fence.mbarrier_init.release.cluster;" ::: "memory");
    fence_async();
    mbar_expect_tx(sb + BAR_W, 163840);
    const int head = cta / 3, col = head * DH + rank * 64;
    tma2d(sb + OFF_WQ, &tmWo, 576, col, sb + BAR_W);
    for (int i = 0; i < 9; i++) tma2d(sb + OFF_WQ + (i + 1) * 8192, &tmWo, (3 * rank + i / 3) * 64, head * DH + ((rank + i) % 3) * 64, sb + BAR_W);
    for (int i = 0; i < 5; i++) tma2d(sb + OFF_WK + i * 16384, &tmWv, col, i * 128, sb + BAR_W);
  }
  __syncthreads();
  asm volatile("barrier.cluster.arrive.release.aligned;" ::: "memory");
  asm volatile("barrier.cluster.wait.acquire.aligned;" ::: "memory");

  if (wg == 0) chain_a(sb, keep(tid), cta, rank);
  else if (wg == 1) chain_q(tmWq, tmWk, sb, keep(tid), cta, rank);
  else chain_v(sb, keep(tid), cta, rank);
  asm volatile("barrier.cluster.arrive.release.aligned;" ::: "memory");
  asm volatile("barrier.cluster.wait.acquire.aligned;" ::: "memory");
}

namespace W {
constexpr int NP = 25, NBC = 11, NW = NP + NBC;
constexpr int OFF_W = 0;
constexpr int OFF_R = 163840;
constexpr int OFF_WO = 0, OFF_WV = 81920;
constexpr int OFF_X = 161792;
constexpr int OFF_G = OFF_X + 40960;
constexpr int COL = 976;
constexpr int OFF_T = OFF_X + 24576;
constexpr int OFF_H = OFF_G + 20480;
constexpr int OFF_BAR = OFF_H + 8 * COL;
constexpr int OFF_SAFE = OFF_BAR + 192;
constexpr int SMEM = 232448;
constexpr uint32_t SB0 = 1024;
constexpr int BAR_F = OFF_BAR, BAR_E = OFF_BAR + 40, BAR_G = OFF_BAR + 80, BAR_H = OFF_BAR + 120, BAR_W = OFF_BAR + 160;
constexpr int NB_G0 = 1, NB_SG = 4, NB_B = 5, NB_AS = 6, NB_PK = 7, NB_PV = 8;
}
#define ERP 1
#define WBAR_SYNC(id, n) bar_sync(id, n)
#define WBAR_ARRIVE(id, n) bar_arrive(id, n)

__device__ __forceinline__ uint64_t rdesc(int off, int k) { return mkdesc(W::SB0 + off + (k >> 2) * 4096 + (k & 3) * 32, 16, 1024); }
__device__ __forceinline__ void load_frags40(uint32_t (&wf)[40][4], uint32_t base, int tid) {
  const int i = (tid >> 3) & 3, r = tid & 7;
  const uint32_t a0 = base + (r + (i >> 1) * 8) * 128 + (((2 * ((tid >> 5) & 3) + (i & 1)) ^ r) << 4);
#pragma unroll
  for (int k = 0; k < 40; k++) ldsm4t(wf[k], a0 + k * 2048);
}
__device__ __forceinline__ void red_tile(const float (&d)[16], int seg, int col0, int tid) {
  float* p = g_x + (size_t)(seg * 32 + 2 * (tid & 3)) * DM + col0 + ((tid >> 5) & 3) * 16 + ((tid >> 2) & 7) * 2;
#pragma unroll
  for (int j = 0; j < 8; j++)
    asm volatile("red.relaxed.gpu.global.add.v2.f32 [%0],{%1,%2};" ::"l"(p + ((j >> 1) * 8 + (j & 1)) * DM), "f"(d[4 * (j >> 1) + (j & 1)]), "f"(d[4 * (j >> 1) + 2 + (j & 1)]) : "memory");
}

#define FOR_P_JOBS(k, l, s)                               \
  for (int j_ = 0; j_ < 2 * NSTEP; j_++) {                \
    const int k = j_ >> 1, l = j_ & 1, s = k - l * LAG;   \
    if (s < 0 || s >= NSEG) continue;
template <int WG>
__device__ __forceinline__ void work_p(const CUtensorMap& tmWo, uint32_t sb, int pc, int tid0) {
  using namespace W;
  asm volatile("setmaxnreg.inc.sync.aligned.u32 208;");
  int spin = 0;
  const int ks = pc / 5, col0 = (pc % 5) * 128 + WG * 64;
  const uint32_t wb = sb + OFF_W + WG * 81920;
  uint32_t wf[40][4];
#pragma unroll 1
  for (int hf = 0; hf < 2; hf++) {
    if ((tid0 & 127) == 0) {
      mbar_expect_tx(sb + BAR_W + 8 * WG, 81920);
      for (int i = 0; i < 10; i++) tma2d(wb + i * 8192, &tmWo, col0, (ks * 19 + 2 * i + hf) * 64, sb + BAR_W + 8 * WG);
    }
    __syncwarp();
    mwait(sb + BAR_W + 8 * WG, hf, spin);
    permute_cols(wb, tid0 & 127);
    if (hf == 1 && ks < 4) for (int it = 2304 + (tid0 & 127); it < 2560; it += 128) {
      const uint32_t a = wb + (it >> 2) * 128 + (((2 * (it & 3)) ^ ((it >> 2) & 6)) << 4);
      sts128(a, make_uint4(0, 0, 0, 0)); sts128(a + 16, make_uint4(0, 0, 0, 0));
    }
    fence_async();
    WBAR_SYNC(NB_G0 + WG, 128);
    if (hf == 0) {
      load_frags40(wf, wb, tid0);
      fence_async();
      WBAR_SYNC(NB_G0 + WG, 128);
    }
  }
  FOR_P_JOBS(k_, l, s)
    float d[16];
#pragma unroll
    for (int f = 0; f < 10; f++) {
      mwait(sb + BAR_F + 8 * (f % 5), f / 5, spin);
      if (f == 0 && WG == 0 && pc == WW) WTS(l, s, 1);
      wg_fence();
#pragma unroll
      for (int kk = 0; kk < 4; kk++) {
        wgmma_rs32(d, wf[4 * f + kk], rdesc(OFF_R, (f % 5) * 8 + kk), f | kk);
        wgmma_ts32(d, mkdesc(SB0 + OFF_W + WG * 81920 + (4 * f + kk) * 2048, 8192, 1024), rdesc(OFF_R, (f % 5) * 8 + 4 + kk), 1);
        if (kk == ERP && f > 0) {
          wg_commit();
          wg_wait<1>();
          if ((tid0 & 31) == 0) mbar_arrive(sb + BAR_E + 8 * ((f - 1) % 5));
          wg_fence();
        }
      }
      wg_commit();
    }
    wg_wait<0>();
    if ((tid0 & 31) == 0) mbar_arrive(sb + BAR_E + 32);
    if (WG == 0 && pc == WW) WTS(l, s, 2);
    red_tile(d, s, col0, tid0);
    WBAR_SYNC(NB_SG, 288);
  }
  if (spin >= SPIN_TOT) g_err = 11;
}
__device__ __forceinline__ void work_p_producer(uint32_t sb, int pc) {
  using namespace W;
  int spin = 0;
  const int ks = pc / 5;
  FOR_P_JOBS(k, l, s)
    if (l == 0 || k >= NSEG) { cwait(CN_O + k * 5 + ks, ks == 4 ? 20 : 19, spin); fence_async_all(); }
    if (pc == WW) WTS1(l, s, 0);
    const uint8_t* src = &g_o[k % ORING][l][ks * 19][0];
#pragma unroll
    for (int f = 0; f < 10; f++) {
      const int st = f < 5 ? f : f - 5;
      const uint32_t len = f == 9 && ks < 4 ? 4096 : 8192;
      mwait(sb + BAR_E + 8 * st, f < 5, spin);
      mbar_expect_tx(sb + BAR_F + 8 * st, len);
      bulk_g2s(sb + OFF_R + st * 8192, src + f * 8192, len, sb + BAR_F + 8 * st);
    }
  }
  if (spin >= SPIN_TOT) g_err = 12;
}
__device__ __forceinline__ float warp_sum(float x) {
  x = quad_sum(x);
  const float a = __shfl_xor_sync(0xffffffffu, x, 4), b = __shfl_xor_sync(0xffffffffu, x, 8), c = __shfl_xor_sync(0xffffffffu, x, 12);
  x = (x + a) + (b + c);
  return x + __shfl_xor_sync(0xffffffffu, x, 16);
}
__device__ __forceinline__ void work_ln(int kind, int r, int lane, bf16* out) {
  int spin = 0;
  const int l = kind & 1;
  const int rp = kind < 2 ? (r & 1) * 16 + (r >> 1) : r;
  const uint32_t sw = ((((lane >> 1) & 7) ^ (rp & 7)) << 4) + (lane & 1) * 8;
  uint8_t* dst = kind < 2 ? g_xnb[l] + (lane >> 4) * 4096 + rp * 128 + sw
               : kind == 2 ? g_xn[1] + (r >> 3) * 2048 + (lane >> 4) * 1024 + (r & 7) * 128 + sw
                           : reinterpret_cast<uint8_t*>(out) + r * 1280 + lane * 8;
  const int dm = kind == 3 ? 256 : 8192;
#pragma unroll 1
  for (int s = 0; s < NSEG; s++) {
    const float* xr = g_x + (size_t)(s * 32 + r) * DM;
    if (kind == 0 && lane < 20 && s + 3 < NSEG) prefetch_l2(xr + 96 * DM + lane * 32);
    if (lane == 0) cwait((kind < 2 ? CN_P : CN_W) + l * 64 + s, kind < 2 ? W::NP : 10, spin);
    __syncwarp();
    if (r == 0 && lane == 0) WTS1(l, s, kind < 2 ? 3 : 11);
    float4 v[5];
#pragma unroll
    for (int m = 0; m < 5; m++) v[m] = ld_relaxed4f(xr + m * 128 + lane * 4);
    if (kind < 3) {
      float t = 0.f;
#pragma unroll
      for (int m = 0; m < 5; m++) t += (v[m].x + v[m].y) + (v[m].z + v[m].w);
      const float mean = warp_sum(t) * (1.f / DM);
      float q0 = 0.f, q1 = 0.f;
#pragma unroll
      for (int m = 0; m < 5; m++) {
        v[m].x -= mean; v[m].y -= mean; v[m].z -= mean; v[m].w -= mean;
        q0 += v[m].x * v[m].x + v[m].y * v[m].y; q1 += v[m].z * v[m].z + v[m].w * v[m].w;
      }
      const float rs = rsqrtf(warp_sum(q0 + q1) * (1.f / DM) + 1e-5f);
#pragma unroll
      for (int m = 0; m < 5; m++) { v[m].x *= rs; v[m].y *= rs; v[m].z *= rs; v[m].w *= rs; }
    }
#pragma unroll
    for (int m = 0; m < 5; m++) *reinterpret_cast<uint2*>(dst + (size_t)s * 40960 + m * dm) = make_uint2(pack_bf16(v[m].x, v[m].y), pack_bf16(v[m].z, v[m].w));
    __syncwarp();
    if (r == 0 && lane == 0) WTS1(l, s, kind < 2 ? 4 : 12);
    if (lane == 0 && kind < 3) csignal(kind < 2 ? CN_L + l * 64 + s : CN_X + s);
  }
  if (spin >= SPIN_TOT) g_err = 13;
}

__device__ __forceinline__ void stage_qkv(const bf16* wqkv, uint32_t base, int T, int bc, int tid) {
  const int q = tid & 15;
  const bool ok = q < 15 && bc * 60 + 4 * q < DM;
  const bf16* src = wqkv + T * DM + bc * 60 + 4 * q;
#pragma unroll 1
  for (int k0 = tid >> 4; k0 < 640; k0 += 80) {
    uint2 v[10];
#pragma unroll
    for (int u = 0; u < 10; u++) v[u] = ok ? *reinterpret_cast<const uint2*>(src + (size_t)(k0 + 8 * u) * 1920) : make_uint2(0, 0);
#pragma unroll
    for (int u = 0; u < 10; u++) sts64(base + (k0 + 8 * u) * 128 + (((q >> 1) ^ (k0 & 7)) << 4) + (q & 1) * 8, v[u].x, v[u].y);
  }
}
__device__ __forceinline__ void attend(uint32_t sb, int bc, int l, int s, int p, int tid) {
  using namespace W;
  const int r = tid & 7, m = (tid >> 3) & 3, hh = (tid >> 5) & 3, g = (tid >> 2) & 7, t = tid & 3;
  const int f2 = r < 4 ? 20 * hh + 16 + r : 60;
  const uint32_t tb = sb + OFF_T + 2 * p * COL, hb = sb + OFF_H + (l * 4 + p) * COL;
  const uint32_t ko = (m < 2 ? 20 * hh + 8 * m + r : f2) * 16, vo = (m < 2 ? 20 * hh + 4 * (r >> 1) + 2 * m + (r & 1) : f2) * 16;
  const float scl = 0.22360679774997896f * 1.4426950408889634f;
  float sc[3][4];
  {
    uint32_t q[4], q8a, q8b, k[3][4];
    ldsm4t(q, tb + (m & 1) * COL + (20 * hh + (m >> 1) * 8 + r) * 16);
    ldsm2t(q8a, q8b, tb + (m & 1) * COL + f2 * 16);
    ldsm4t(k[0], hb + ko); ldsm4t(k[1], tb + 4 * COL + ko); ldsm4t(k[2], tb + 5 * COL + ko);
#pragma unroll
    for (int c = 0; c < 3; c++) { sc[c][0] = sc[c][1] = sc[c][2] = sc[c][3] = 0.f; mma16816(sc[c], q[0], q[1], q[2], q[3], k[c][0], k[c][1]); }
#pragma unroll
    for (int c = 0; c < 3; c++) mma1688(sc[c], q8a, q8b, k[c][2]);
  }
  uint32_t v[3][4];
  ldsm4(v[0], hb + 2 * COL + vo); ldsm4(v[1], tb + 8 * COL + vo); ldsm4(v[2], tb + 9 * COL + vo);
  const bool lo0 = 2 * t > g, lo1 = 2 * t + 1 > g;
  uint32_t pw[2];
  float inv[2];
#pragma unroll
  for (int h = 0; h < 2; h++) {
    float y0 = lo0 ? sc[h][2 * h] : sc[h + 1][2 * h], y1 = lo1 ? sc[h][2 * h + 1] : sc[h + 1][2 * h + 1];
    if (h == 0 && s == 0) { y0 = lo0 ? -INFINITY : y0; y1 = lo1 ? -INFINITY : y1; }
    const float mx = quad_max(fmaxf(y0, y1)) * -scl;
    pw[h] = pack_bf16(ex2(fmaf(y0, scl, mx)), ex2(fmaf(y1, scl, mx)));
    inv[h] = bf_lo(pw[h]) + bf_hi(pw[h]);
  }
  const uint32_t ml = (lo0 ? 0xFFFFu : 0u) | (lo1 ? 0xFFFF0000u : 0u);
  float o[3][4];
#pragma unroll
  for (int j = 0; j < 3; j++) { o[j][0] = o[j][1] = o[j][2] = o[j][3] = 0.f; mma16816(o[j], pw[0] & ml, 0u, pw[0] & ~ml, pw[1] & ml, v[0][j], v[1][j]); }
#pragma unroll
  for (int j = 0; j < 3; j++) mma1688(o[j], 0u, pw[1] & ~ml, v[2][j]);
  inv[0] = rcp(quad_sum(inv[0])); inv[1] = rcp(quad_sum(inv[1]));
  const uint32_t ca = (bc * 3 + hh) * 20 + 4 * t, cb = ca + 16 - 2 * t, row = 2 * g + p;
  uint8_t* img = g_ob[l] + (size_t)s * 40960 + row * 128;
  const uint32_t oa = (ca >> 6) * 4096 + (((ca >> 3) ^ row) & 7) * 16 + (ca & 4) * 2, ob = (cb >> 6) * 4096 + (((cb >> 3) ^ row) & 7) * 16 + (cb & 6) * 2;
#pragma unroll
  for (int h = 0; h < 2; h++) {
    *reinterpret_cast<uint2*>(img + oa + h * 2048) = make_uint2(pack_bf16(o[0][2 * h] * inv[h], o[0][2 * h + 1] * inv[h]), pack_bf16(o[1][2 * h] * inv[h], o[1][2 * h + 1] * inv[h]));
    if (t < 2) *reinterpret_cast<uint32_t*>(img + ob + h * 2048) = pack_bf16(o[2][2 * h] * inv[h], o[2][2 * h + 1] * inv[h]);
  }
}
template <int WG>
__device__ __forceinline__ void work_b(const bf16* wqkv, uint32_t sb, int bc, int tid0) {
  using namespace W;
  if (WG == 0) asm volatile("setmaxnreg.inc.sync.aligned.u32 224;");
  else asm volatile("setmaxnreg.inc.sync.aligned.u32 208;");
  int spin = 0;
  const uint32_t wb = sb + (WG ? OFF_WO : OFF_WV);
  uint32_t wf[40][4], wv[4];
  stage_qkv(wqkv, wb, WG, bc, tid0 & 127);
  WBAR_SYNC(NB_G0 + WG, 128);
  load_frags40(wf, wb, tid0);
  fence_async();
  if (WG == 1) WBAR_ARRIVE(NB_PK, 256);
  else {
    WBAR_SYNC(NB_G0, 128);
    stage_qkv(wqkv, wb, 2, bc, tid0);
    WBAR_SYNC(NB_G0, 128);
    const int i = (tid0 >> 3) & 3, r = tid0 & 7;
    ldsm4t(wv, wb + 39 * 2048 + (r + (i >> 1) * 8) * 128 + (((2 * (tid0 >> 5) + (i & 1)) ^ r) << 4));
    fence_async();
    WBAR_SYNC(NB_PV, 160);
  }
  uint32_t ph = 0;
  FOR_P_JOBS(k_, l, s)
    uint32_t hist[4];
    {
      float d[16], e[16];
#pragma unroll
      for (int f = 0; f < 5; f++) {
        mwait(sb + BAR_F + 8 * f, ph, spin);
        if (f == 0 && bc == 0) WTS(l, s, WG ? 15 : 6);
        wg_fence();
#pragma unroll
        for (int k = 8 * f; k < 8 * f + 8; k++) {
          wgmma_rs32(d, wf[k], rdesc(OFF_X, k), k);
          if (WG == 0) {
            if (k < 39) wgmma_ts32(e, mkdesc(SB0 + OFF_WV + k * 2048, 8192, 1024), rdesc(OFF_X, k), k);
            else wgmma_rs32(e, wv, rdesc(OFF_X, k), 1);
          }
        }
        wg_commit();
        if (f > 0 && f < 4) {
          wg_wait<1>();
          if ((tid0 & 31) == 0) mbar_arrive(sb + BAR_E + 8 * (f - 1));
        }
      }
      wg_wait<0>();
      if (bc == 0) WTS(l, s, 16 + WG);
      WBAR_SYNC(NB_B, 256);
      const int tid = fresh(tid0), m = (tid >> 3) & 3;
      const uint32_t a = sb + OFF_T + min(((tid >> 5) & 3) * 16 + (m & 1) * 8 + (tid & 7), 60) * 16 + (m >> 1) * COL;
      const float (&x)[16] = WG ? d : e;
#pragma unroll
      for (int p = 0; p < 2; p++) {
        hist[2 * p] = pack_bf16(x[8 * p + 4], x[8 * p + 5]); hist[2 * p + 1] = pack_bf16(x[8 * p + 6], x[8 * p + 7]);
        stsm4(a + (8 - 4 * WG + 2 * p) * COL, pack_bf16(x[8 * p], x[8 * p + 1]), pack_bf16(x[8 * p + 2], x[8 * p + 3]), hist[2 * p], hist[2 * p + 1]);
        if (WG == 0)
          stsm4(a + 2 * p * COL, pack_bf16(d[8 * p], d[8 * p + 1]), pack_bf16(d[8 * p + 2], d[8 * p + 3]), pack_bf16(d[8 * p + 4], d[8 * p + 5]), pack_bf16(d[8 * p + 6], d[8 * p + 7]));
      }
    }
    WBAR_SYNC(NB_B, 256);
    if (bc == 0 && WG == 0) WTS(l, s, 7);
    {
      const int tid = fresh(tid0), hh = (tid >> 5) & 3;
      if (hh < 3 && bc * 3 + hh < NH) attend(sb, bc, l, s, WG, tid);
    }
    if (bc == 0 && WG == 0) WTS(l, s, 8);
    WBAR_SYNC(NB_AS, 288);
    {
      const int tid = fresh(tid0), m = (tid >> 3) & 3;
      stsm4(sb + OFF_H + min(((tid >> 5) & 3) * 16 + (m & 1) * 8 + (tid & 7), 60) * 16 + (l * 4 + 2 - 2 * WG + (m >> 1)) * COL, hist[0], hist[1], hist[2], hist[3]);
      fence_async();
      if ((tid & 31) < 2) mbar_arrive(sb + BAR_E + 24 + 8 * (tid & 1));
    }
    ph ^= 1;
  }
  if (spin >= SPIN_TOT) g_err = 14;
}
__device__ __forceinline__ void work_wo(const CUtensorMap& tmBo, uint32_t sb, int bc, int tid0) {
  using namespace W;
  int spin = 0;
  WBAR_SYNC(NB_PK, 256);
  if (bc == 10) return;
  if ((tid0 & 127) == 0) {
    mbar_expect_tx(sb + BAR_W, 81920);
    for (int i = 0; i < 10; i++) tma2d(sb + OFF_WO + i * 8192, &tmBo, bc * 64, i * 64, sb + BAR_W);
  }
  __syncwarp();
  mwait(sb + BAR_W, 0, spin);
  permute_cols(sb + OFF_WO, tid0 & 127);
  fence_async();
  WBAR_SYNC(NB_G0 + 2, 128);
  FOR_P_JOBS(k_, l, s)
    float d[16];
#pragma unroll
    for (int f = 0; f < 10; f++) {
      mwait(sb + BAR_G + 8 * (f % 5), f / 5, spin);
      if ((f == 0 || f == 9) && bc == 0) WTS(l, s, f ? 21 : 20);
      wg_fence();
#pragma unroll
      for (int kk = 0; kk < 4; kk++) wgmma_ts32(d, mkdesc(SB0 + OFF_WO + (4 * f + kk) * 2048, 8192, 1024), rdesc(OFF_G, (f % 5) * 4 + kk), f | kk);
      wg_commit();
      if (f % 5) {
        wg_wait<1>();
        if ((tid0 & 31) == 0) mbar_arrive(sb + BAR_H + 8 * ((f - 1) % 5));
      }
      if (f == 4 || f == 9) {
        wg_wait<0>();
        if ((tid0 & 31) == 0) mbar_arrive(sb + BAR_H + 32);
      }
    }
    if (bc == 0) WTS(l, s, 10);
    red_tile(d, s, bc * 64, tid0);
    WBAR_SYNC(NB_SG, 160);
  }
  if (spin >= SPIN_TOT) g_err = 17;
}
template <bool WO>
__device__ __forceinline__ void work_b_producer(uint32_t sb, int bc) {
  using namespace W;
  int spin = 0;
  uint32_t ph = 1;
  FOR_P_JOBS(k_, l, s)
    const uint8_t* src = (WO ? g_ob[l] : g_xnb[l]) + (size_t)s * 40960;
    cwait((WO ? CN_A : CN_L) + l * 64 + s, WO ? NBC : 32, spin);
    fence_async_all();
    if (bc == 0) WTS1(l, s, WO ? 9 : 5);
#pragma unroll
    for (int f = 0; f < (WO ? 10 : 5); f++) {
      const uint32_t len = WO ? 4096 : 8192, fb = sb + (WO ? BAR_G : BAR_F) + 8 * (f % 5);
      mwait(sb + (WO ? BAR_H : BAR_E) + 8 * (f % 5), WO ? f < 5 : ph, spin);
      mbar_expect_tx(fb, len);
      bulk_g2s(sb + (WO ? OFF_G : OFF_X) + (f % 5) * len, src + f * len, len, fb);
    }
    ph ^= 1;
  }
  if (spin >= SPIN_TOT) g_err = 15;
}

__global__ void __launch_bounds__(512, 1)
k_work(const __grid_constant__ CUtensorMap tmWo, const __grid_constant__ CUtensorMap tmBo, const bf16* __restrict__ wqkv, bf16* __restrict__ out) {
  using namespace W;
  extern __shared__ __align__(1024) uint8_t smem[];
  const uint32_t sb = smem_u32(smem);
  const int tid = threadIdx.x, w = blockIdx.x;
  const int wg = __shfl_sync(0xffffffffu, tid >> 7, 0);
  if (tid == 0) {
    if (sb != SB0) g_err = 101;
    for (int i = 0; i < 5; i++) { mbar_init(sb + BAR_F + 8 * i, 1); mbar_init(sb + BAR_E + 8 * i, 8); mbar_init(sb + BAR_G + 8 * i, 1); mbar_init(sb + BAR_H + 8 * i, 4); }
    mbar_init(sb + BAR_W, 1); mbar_init(sb + BAR_W + 8, 1);
    for (int p = 0; p < 16; p++) sts32(sb + OFF_SAFE + 4 * p, 0);
    asm volatile("fence.mbarrier_init.release.cluster;" ::: "memory");
  }
  if (tid < 8 * COL / 16) sts128(sb + OFF_H + tid * 16, make_uint4(0, 0, 0, 0));
  fence_async();
  __syncthreads();

  if (w < NP) {
    if (wg == 0) work_p<0>(tmWo, sb, w, keep(tid));
    else if (wg == 1) work_p<1>(tmWo, sb, w, keep(tid));
    else {
      asm volatile("setmaxnreg.dec.sync.aligned.u32 48;");
      const int aw = (tid >> 5) - 8;
      if (aw == 0) {
        if (tid == 256) work_p_producer(sb, w);
      } else if (aw == 1) {
        FOR_P_JOBS(k_, l, s)
          WBAR_SYNC(NB_SG, 288);
          if (tid == 288) csignal(CN_P + l * 64 + s);
          __syncwarp();
        }
      } else {
        const int id = (aw - 2) * NP + w;
        if (id < 128) work_ln(id & 3, id >> 2, tid & 31, out);
      }
    }
  } else {
    const int bc = w - NP;
    if (wg == 0) work_b<0>(wqkv, sb, bc, keep(tid));
    else if (wg == 1) work_b<1>(wqkv, sb, bc, keep(tid));
    else if (wg == 2) {
      asm volatile("setmaxnreg.dec.sync.aligned.u32 56;");
      work_wo(tmBo, sb, bc, keep(tid));
    } else {
      asm volatile("setmaxnreg.dec.sync.aligned.u32 24;");
      if (tid < 416) {
        WBAR_SYNC(NB_PV, 160);
        if (tid == 384) work_b_producer<false>(sb, bc);
      } else if (tid < 448) {
        if (tid == 416 && bc < 10) work_b_producer<true>(sb, bc);
      } else if (tid < 480 || bc < 10) {
        FOR_P_JOBS(k_, l, s)
          if (tid < 480) WBAR_SYNC(NB_AS, 288); else WBAR_SYNC(NB_SG, 160);
          if ((tid & 31) == 0) csignal((tid < 480 ? CN_A : CN_W) + l * 64 + s);
          __syncwarp();
        }
      }
    }
  }
  __syncthreads();
  asm volatile("griddepcontrol.wait;" ::: "memory");
}

typedef CUresult (*EncodeFn)(CUtensorMap*, CUtensorMapDataType, cuuint32_t, void*, const cuuint64_t*, const cuuint64_t*,
                             const cuuint32_t*, const cuuint32_t*, CUtensorMapInterleave, CUtensorMapSwizzle,
                             CUtensorMapL2promotion, CUtensorMapFloatOOBfill);

static void make_map(EncodeFn enc, CUtensorMap* tm, const void* ptr, uint64_t cols, uint64_t rows, uint32_t boxc, uint32_t boxr) {
  cuuint64_t dims[2] = {cols, rows};
  cuuint64_t strides[1] = {cols * 2};
  cuuint32_t box[2] = {boxc, boxr};
  cuuint32_t es[2] = {1, 1};
  enc(tm, CU_TENSOR_MAP_DATA_TYPE_BFLOAT16, 2, const_cast<void*>(ptr), dims, strides, box, es, CU_TENSOR_MAP_INTERLEAVE_NONE,
      CU_TENSOR_MAP_SWIZZLE_128B, CU_TENSOR_MAP_L2_PROMOTION_L2_256B, CU_TENSOR_MAP_FLOAT_OOB_FILL_NONE);
}

extern "C" void kernel_launch(void* const* d_in, const int* in_sizes, int n_in, void* d_out, int out_size) {
  const bf16* x0 = (const bf16*)d_in[0];
  const bf16* mem0 = (const bf16*)d_in[1];
  const bf16* Wq = (const bf16*)d_in[2];
  const bf16* Wk = (const bf16*)d_in[3];
  const bf16* Wv = (const bf16*)d_in[4];
  const bf16* Wo = (const bf16*)d_in[5];
  const bf16* Bqkv = (const bf16*)d_in[8];
  const bf16* Bwo = (const bf16*)d_in[9];
  bf16* out = (bf16*)d_out;

  static EncodeFn enc = nullptr;
  if (!enc) {
    void* fn = nullptr;
    cudaDriverEntryPointQueryResult qr;
    cudaGetDriverEntryPoint("cuTensorMapEncodeTiled", &fn, cudaEnableDefault, &qr);
    enc = (EncodeFn)fn;
    cudaFuncSetAttribute(k_chain, cudaFuncAttributeMaxDynamicSharedMemorySize, C::SMEM);
    cudaFuncSetAttribute(k_work, cudaFuncAttributeMaxDynamicSharedMemorySize, W::SMEM);
  }
  CUtensorMap tmWq, tmWk, tmWv, tmWo, tmBo;
  make_map(enc, &tmWq, Wq, NH * DH, DM, 64, 128);
  make_map(enc, &tmWk, Wk, NH * DH, DM, 64, 128);
  make_map(enc, &tmWv, Wv, NH * DH, DM, 64, 128);
  make_map(enc, &tmWo, Wo, DM, NH * DH, 64, 64);
  make_map(enc, &tmBo, Bwo, DM, DM, 64, 64);

  cudaStream_t st = cudaStreamPerThread;
  k_pre<<<256, 256, 0, st>>>(x0, mem0);
  cudaLaunchAttribute at[1];
  at[0].id = cudaLaunchAttributeProgrammaticStreamSerialization; at[0].val.programmaticStreamSerializationAllowed = 1;
  {
    cudaLaunchConfig_t cfg = {};
    cfg.gridDim = dim3(96); cfg.blockDim = dim3(384); cfg.dynamicSmemBytes = C::SMEM; cfg.stream = st;
    cfg.attrs = at; cfg.numAttrs = 0;
    cudaLaunchKernelEx(&cfg, k_chain, tmWq, tmWk, tmWv, tmWo);
  }
  cudaLaunchConfig_t cfg = {};
  cfg.gridDim = dim3(W::NW); cfg.blockDim = dim3(512); cfg.dynamicSmemBytes = W::SMEM; cfg.stream = st;
  cfg.attrs = at; cfg.numAttrs = NOWORK == 2 ? 0 : 1;
  cudaLaunchKernelEx(&cfg, k_work, tmWo, tmBo, Bqkv, out);
}
```

```cpp
#include <cuda_runtime.h>
#include <cuda_bf16.h>
#include <cuda.h>
#include <stdint.h>

typedef __nv_bfloat16 bf16;

constexpr int SEQ = 2048, DM = 640, NH = 32, DH = 192, NSEG = 64;
#define LAG 5
constexpr int NSTEP = NSEG + LAG;
constexpr uint32_t SENT = 0xFFFFFFFFu;

constexpr int MAIL9 = 288 * 2048, MAIL_BYTES = MAIL9 + 64 * 3072;
__device__ __align__(1024) uint8_t g_xn[2][NSEG * 40960];
__device__ __align__(1024) uint8_t g_xnb[2][NSEG * 40960];
__device__ __align__(1024) uint8_t g_ob[2][NSEG * 40960];
#define ORING 8
static_assert(ORING > LAG, "a slot is free again LAG + 1 steps later");
__device__ __align__(1024) uint8_t g_o[ORING][2][96][4096];
__device__ __align__(1024) float g_x[SEQ * DM];
constexpr int EX_MAIL = 0;
constexpr int EX_M = 2 << 20;
constexpr int EX_FLAG = EX_M + NSTEP * 20480;
static_assert(EX_FLAG + NSTEP * 3072 <= (4 << 20), "");
__device__ __align__(1024) uint8_t g_ex[8 << 20];
__host__ __device__ __forceinline__ uint8_t* ex_window(uint8_t* p) { return reinterpret_cast<uint8_t*>((reinterpret_cast<uint64_t>(p) + (4 << 20) - 1) & ~(uint64_t)((4 << 20) - 1)); }
enum { CN_P = 0, CN_L = 128, CN_A = 256, CN_W = 384, CN_X = 512, CN_O = 576, CN_NUM = CN_O + 5 * NSTEP };
__device__ __align__(128) uint32_t g_cnt[CN_NUM][32];
__device__ int g_err;
#define TS(jj, i)
#define TS1(jj, i)
#define PTS(i)
#define TSB(jj, i)
#define TSV(jj, i, v)
#define TS_FLUSH(jj)
#define WTS(l, b, k)
#define WTS1(l, b, k)
#define WW -1

__device__ __forceinline__ uint32_t smem_u32(const void* p) { return (uint32_t)__cvta_generic_to_shared(p); }
__device__ __forceinline__ uint32_t clk32() { uint32_t t; asm volatile("mov.u32 %0, %%clock;" : "=r"(t)::"memory"); return t; }
__device__ __forceinline__ uint32_t mapa(uint32_t a, uint32_t r) { uint32_t o; asm("mapa.shared::cluster.u32 %0,%1,%2;" : "=r"(o) : "r"(a), "r"(r)); return o; }
__device__ __forceinline__ void mbar_init(uint32_t bar, uint32_t cnt) { asm volatile("mbarrier.init.shared::cta.b64 [%0],%1;" ::"r"(bar), "r"(cnt) : "memory"); }
__device__ __forceinline__ void mbar_expect_tx(uint32_t bar, uint32_t bytes) { asm volatile("mbarrier.arrive.expect_tx.shared::cta.b64 _,[%0],%1;" ::"r"(bar), "r"(bytes) : "memory"); }
__device__ __forceinline__ void mbar_arrive(uint32_t bar) { asm volatile("mbarrier.arrive.shared::cta.b64 _,[%0];" ::"r"(bar) : "memory"); }
__device__ __forceinline__ void mbar_arrive_cluster(uint32_t bar) { asm volatile("mbarrier.arrive.shared::cluster.b64 _,[%0];" ::"r"(bar) : "memory"); }
__device__ __forceinline__ bool mbar_try(uint32_t bar, uint32_t ph) {
  uint32_t ok;
  asm volatile("{.reg .pred p; mbarrier.try_wait.parity.shared::cta.b64 p,[%1],%2; selp.u32 %0,1,0,p;}" : "=r"(ok) : "r"(bar), "r"(ph) : "memory");
  return ok;
}
__device__ __forceinline__ bool mbar_test(uint32_t bar, uint32_t ph) {
  uint32_t ok;
  asm volatile("{.reg .pred p; mbarrier.test_wait.parity.shared::cta.b64 p,[%1],%2; selp.u32 %0,1,0,p;}" : "=r"(ok) : "r"(bar), "r"(ph) : "memory");
  return ok;
}
__device__ __forceinline__ int fresh(int x) { asm volatile("" : "+r"(x)); return x; }
#define PHASE_IDS const int tid = fresh(tid0), lane = tid & 31, w = tid >> 5, g = lane >> 2, t = lane & 3; (void)w; (void)g; (void)t
__device__ __forceinline__ void bar_sync(int id, int n) { asm volatile("bar.sync %0,%1;" ::"r"(id), "r"(n) : "memory"); }
__device__ __forceinline__ void bar_arrive(int id, int n) { asm volatile("bar.arrive %0,%1;" ::"r"(id), "r"(n) : "memory"); }
__device__ __forceinline__ bool bar_red_or(int id, int n, bool v) {
  uint32_t r;
  asm volatile("{\n .reg .pred p, q;\n setp.ne.u32 q, %3, 0;\n barrier.cta.red.or.pred p, %1, %2, q;\n selp.u32 %0, 1, 0, p;\n}" : "=r"(r) : "r"(id), "r"(n), "r"((uint32_t)v) : "memory");
  return r != 0;
}
__device__ __forceinline__ void fence_async() { asm volatile("fence.proxy.async.shared::cta;" ::: "memory"); }
__device__ __forceinline__ void bulk_g2s(uint32_t dst, const void* src, uint32_t bytes, uint32_t bar) {
  asm volatile("cp.async.bulk.shared::cluster.global.mbarrier::complete_tx::bytes [%0],[%1],%2,[%3];" ::"r"(dst), "l"(src), "r"(bytes), "r"(bar) : "memory");
}
__device__ __forceinline__ void bulk_g2s_mc(uint32_t dst, const void* src, uint32_t bytes, uint32_t bar) {
  asm volatile("cp.async.bulk.shared::cluster.global.mbarrier::complete_tx::bytes.multicast::cluster [%0],[%1],%2,[%3],%4;"
               ::"r"(dst), "l"(src), "r"(bytes), "r"(bar), "h"((uint16_t)7) : "memory");
}
__device__ __forceinline__ void bulk_s2g(void* dst, uint32_t src, uint32_t bytes) {
  asm volatile("cp.async.bulk.global.shared::cta.bulk_group [%0],[%1],%2;" ::"l"(dst), "r"(src), "r"(bytes) : "memory");
}
__device__ __forceinline__ void bulk_s2c(uint32_t dst, uint32_t src, uint32_t bytes, uint32_t bar) {
  asm volatile("cp.async.bulk.shared::cluster.shared::cta.mbarrier::complete_tx::bytes [%0],[%1],%2,[%3];" ::"r"(dst), "r"(src), "r"(bytes), "r"(bar) : "memory");
}
__device__ __forceinline__ void tma2d(uint32_t dst, const CUtensorMap* tm, int c0, int c1, uint32_t bar) {
  asm volatile("cp.async.bulk.tensor.2d.shared::cluster.global.mbarrier::complete_tx::bytes [%0],[%1,{%3,%4}],[%2];"
               ::"r"(dst), "l"(tm), "r"(bar), "r"(c0), "r"(c1) : "memory");
}
__device__ __forceinline__ void tma2d_prefetch(const CUtensorMap* tm, int c0, int c1) {
  asm volatile("cp.async.bulk.prefetch.tensor.2d.L2.global.tile [%0,{%1,%2}];" ::"l"(tm), "r"(c0), "r"(c1) : "memory");
}
__device__ __forceinline__ uint32_t pack_bf16(float lo, float hi) {
  uint32_t r; asm("cvt.rn.bf16x2.f32 %0,%1,%2;" : "=r"(r) : "f"(hi), "f"(lo)); return r;
}
__device__ __forceinline__ float bf_lo(uint32_t x) { return __uint_as_float(x << 16); }
__device__ __forceinline__ float bf_hi(uint32_t x) { return __uint_as_float(x & 0xFFFF0000u); }
__device__ __forceinline__ float ex2(float x) { float y; asm("ex2.approx.ftz.f32 %0,%1;" : "=f"(y) : "f"(x)); return y; }
__device__ __forceinline__ void ldsm4(uint32_t (&r)[4], uint32_t a) {
  asm volatile("ldmatrix.sync.aligned.m8n8.x4.shared.b16 {%0,%1,%2,%3},[%4];" : "=r"(r[0]), "=r"(r[1]), "=r"(r[2]), "=r"(r[3]) : "r"(a) : "memory");
}
__device__ __forceinline__ void ldsm4t(uint32_t (&r)[4], uint32_t a) {
  asm volatile("ldmatrix.sync.aligned.m8n8.x4.trans.shared.b16 {%0,%1,%2,%3},[%4];" : "=r"(r[0]), "=r"(r[1]), "=r"(r[2]), "=r"(r[3]) : "r"(a) : "memory");
}
__device__ __forceinline__ void ldsm2(uint32_t& r0, uint32_t& r1, uint32_t a) {
  asm volatile("ldmatrix.sync.aligned.m8n8.x2.shared.b16 {%0,%1},[%2];" : "=r"(r0), "=r"(r1) : "r"(a) : "memory");
}
__device__ __forceinline__ void ldsm2t(uint32_t& r0, uint32_t& r1, uint32_t a) {
  asm volatile("ldmatrix.sync.aligned.m8n8.x2.trans.shared.b16 {%0,%1},[%2];" : "=r"(r0), "=r"(r1) : "r"(a) : "memory");
}
__device__ __forceinline__ void ldsm1(uint32_t& r0, uint32_t a) {
  asm volatile("ldmatrix.sync.aligned.m8n8.x1.shared.b16 {%0},[%1];" : "=r"(r0) : "r"(a) : "memory");
}
__device__ __forceinline__ void mma16816(float (&d)[4], uint32_t a0, uint32_t a1, uint32_t a2, uint32_t a3, uint32_t b0, uint32_t b1) {
  asm volatile("mma.sync.aligned.m16n8k16.row.col.f32.bf16.bf16.f32 {%0,%1,%2,%3},{%4,%5,%6,%7},{%8,%9},{%0,%1,%2,%3};"
               : "+f"(d[0]), "+f"(d[1]), "+f"(d[2]), "+f"(d[3]) : "r"(a0), "r"(a1), "r"(a2), "r"(a3), "r"(b0), "r"(b1));
}
__device__ __forceinline__ void mma1688(float (&d)[4], uint32_t a0, uint32_t a1, uint32_t b0) {
  asm volatile("mma.sync.aligned.m16n8k8.row.col.f32.bf16.bf16.f32 {%0,%1,%2,%3},{%4,%5},{%6},{%0,%1,%2,%3};"
               : "+f"(d[0]), "+f"(d[1]), "+f"(d[2]), "+f"(d[3]) : "r"(a0), "r"(a1), "r"(b0));
}
__device__ __forceinline__ void sts32(uint32_t a, uint32_t v) { asm volatile("st.shared.b32 [%0],%1;" ::"r"(a), "r"(v) : "memory"); }
__device__ __forceinline__ void sts64f(uint32_t a, float x, float y) { asm volatile("st.shared.v2.f32 [%0],{%1,%2};" ::"r"(a), "f"(x), "f"(y) : "memory"); }
__device__ __forceinline__ void sts128(uint32_t a, uint4 v) { asm volatile("st.shared.v4.b32 [%0],{%1,%2,%3,%4};" ::"r"(a), "r"(v.x), "r"(v.y), "r"(v.z), "r"(v.w) : "memory"); }
__device__ __forceinline__ float lds32f(uint32_t a) { float v; asm volatile("ld.shared.f32 %0,[%1];" : "=f"(v) : "r"(a) : "memory"); return v; }
__device__ __forceinline__ float2 lds64f(uint32_t a) { float2 v; asm volatile("ld.shared.v2.f32 {%0,%1},[%2];" : "=f"(v.x), "=f"(v.y) : "r"(a) : "memory"); return v; }
__device__ __forceinline__ uint4 lds128(uint32_t a) { uint4 v; asm volatile("ld.shared.v4.b32 {%0,%1,%2,%3},[%4];" : "=r"(v.x), "=r"(v.y), "=r"(v.z), "=r"(v.w) : "r"(a) : "memory"); return v; }
__device__ __forceinline__ float4 lds128f(uint32_t a) { float4 v; asm volatile("ld.shared.v4.f32 {%0,%1,%2,%3},[%4];" : "=f"(v.x), "=f"(v.y), "=f"(v.z), "=f"(v.w) : "r"(a) : "memory"); return v; }
__device__ __forceinline__ void st_async2(uint32_t a, float x, float y, uint32_t bar) {
  asm volatile("st.async.weak.shared::cluster.mbarrier::complete_tx::bytes.v2.f32 [%0],{%1,%2},[%3];" ::"r"(a), "f"(x), "f"(y), "r"(bar) : "memory");
}
__device__ __forceinline__ void st_async4(uint32_t a, const float (&v)[4], uint32_t bar) {
  asm volatile("st.async.weak.shared::cluster.mbarrier::complete_tx::bytes.v4.f32 [%0],{%1,%2,%3,%4},[%5];" ::"r"(a), "f"(v[0]), "f"(v[1]), "f"(v[2]), "f"(v[3]), "r"(bar) : "memory");
}
__device__ __forceinline__ void st_async4v(uint32_t a, float x, float y, float z, float w, uint32_t bar) {
  asm volatile("st.async.weak.shared::cluster.mbarrier::complete_tx::bytes.v4.f32 [%0],{%1,%2,%3,%4},[%5];" ::"r"(a), "f"(x), "f"(y), "f"(z), "f"(w), "r"(bar) : "memory");
}
__device__ __forceinline__ void st_async4u(uint32_t a, const uint4& v, uint32_t bar) {
  asm volatile("st.async.weak.shared::cluster.mbarrier::complete_tx::bytes.v4.b32 [%0],{%1,%2,%3,%4},[%5];" ::"r"(a), "r"(v.x), "r"(v.y), "r"(v.z), "r"(v.w), "r"(bar) : "memory");
}
__device__ __forceinline__ uint4 ld_relaxed4(const void* p) {
  uint4 v; asm volatile("ld.relaxed.gpu.global.v4.u32 {%0,%1,%2,%3},[%4];" : "=r"(v.x), "=r"(v.y), "=r"(v.z), "=r"(v.w) : "l"(p) : "memory"); return v;
}
__device__ __forceinline__ uint32_t ld_relaxed(const void* p) {
  uint32_t v; asm volatile("ld.relaxed.gpu.global.u32 %0,[%1];" : "=r"(v) : "l"(p) : "memory"); return v;
}
__device__ __forceinline__ void st_relaxed(void* p, uint32_t v) { asm volatile("st.relaxed.gpu.global.b32 [%0],%1;" ::"l"(p), "r"(v) : "memory"); }
__device__ __forceinline__ void st_relaxed4(void* p, uint32_t v) { asm volatile("st.relaxed.gpu.global.v4.b32 [%0],{%1,%1,%1,%1};" ::"l"(p), "r"(v) : "memory"); }

__device__ __forceinline__ uint32_t ld_acquire(const void* p) {
  uint32_t v; asm volatile("ld.acquire.gpu.global.u32 %0,[%1];" : "=r"(v) : "l"(p) : "memory"); return v;
}
__device__ __forceinline__ float4 ld_relaxed4f(const void* p) {
  float4 v; asm volatile("ld.relaxed.gpu.global.v4.f32 {%0,%1,%2,%3},[%4];" : "=f"(v.x), "=f"(v.y), "=f"(v.z), "=f"(v.w) : "l"(p) : "memory"); return v;
}
__device__ __forceinline__ float2 ld_relaxed2f(const void* p) {
  float2 v; asm volatile("ld.relaxed.gpu.global.v2.f32 {%0,%1},[%2];" : "=f"(v.x), "=f"(v.y) : "l"(p) : "memory"); return v;
}
__device__ __forceinline__ void prefetch_l2(const void* p) { asm volatile("prefetch.global.L2 [%0];" ::"l"(p)); }
__device__ __forceinline__ void fence_gpu() { asm volatile("fence.acq_rel.gpu;" ::: "memory"); }
__device__ __forceinline__ void fence_async_all() { asm volatile("fence.proxy.async.global;" ::: "memory"); }
constexpr int SPIN_TOT = 1 << 22;
__device__ __forceinline__ void csignal(int idx) { asm volatile("red.release.gpu.global.add.u32 [%0],1;" ::"l"(&g_cnt[idx][0]) : "memory"); }
#define csignal_t(idx, role) csignal(idx)
__device__ __forceinline__ void cwait(int idx, uint32_t target, int& spin) {
  while (ld_acquire(&g_cnt[idx][0]) < target && spin < SPIN_TOT) spin += 16;
}

__device__ __forceinline__ uint64_t mkdesc(uint32_t addr, uint32_t lbo, uint32_t sbo) {
  return (uint64_t)((addr & 0x3FFFF) >> 4) | ((uint64_t)(lbo >> 4) << 16) | ((uint64_t)(sbo >> 4) << 32) | ((uint64_t)1 << 62);
}
__device__ __forceinline__ uint64_t mkdesc_ns(uint32_t addr, uint32_t lbo, uint32_t sbo) {
  return (uint64_t)((addr & 0x3FFFF) >> 4) | ((uint64_t)(lbo >> 4) << 16) | ((uint64_t)(sbo >> 4) << 32);
}
__device__ __forceinline__ void wg_fence() { asm volatile("wgmma.fence.sync.aligned;" ::: "memory"); }
__device__ __forceinline__ void wg_commit() { asm volatile("wgmma.commit_group.sync.aligned;" ::: "memory"); }
template <int N> __device__ __forceinline__ void wg_wait() { asm volatile("wgmma.wait_group.sync.aligned %0;" ::"n"(N) : "memory"); }

__device__ __forceinline__ void wgmma_rs16(float (&d)[8], const uint32_t (&a)[4], uint64_t db, int sc) {
  asm volatile("{.reg .pred p; setp.ne.b32 p,%13,0; wgmma.mma_async.sync.aligned.m64n16k16.f32.bf16.bf16 "
               "{%0,%1,%2,%3,%4,%5,%6,%7},{%8,%9,%10,%11},%12,p,1,1,0;}"
               : "+f"(d[0]), "+f"(d[1]), "+f"(d[2]), "+f"(d[3]), "+f"(d[4]), "+f"(d[5]), "+f"(d[6]), "+f"(d[7])
               : "r"(a[0]), "r"(a[1]), "r"(a[2]), "r"(a[3]), "l"(db), "r"(sc));
}
__device__ __forceinline__ void wgmma_rs64(float (&d)[32], const uint32_t (&a)[4], uint64_t db, int sc) {
  asm volatile("{.reg .pred p; setp.ne.b32 p,%37,0; wgmma.mma_async.sync.aligned.m64n64k16.f32.bf16.bf16 "
               "{%0,%1,%2,%3,%4,%5,%6,%7,%8,%9,%10,%11,%12,%13,%14,%15,%16,%17,%18,%19,%20,%21,%22,%23,%24,%25,%26,%27,%28,%29,%30,%31},{%32,%33,%34,%35},%36,p,1,1,0;}"
               : "+f"(d[0]), "+f"(d[1]), "+f"(d[2]), "+f"(d[3]), "+f"(d[4]), "+f"(d[5]), "+f"(d[6]), "+f"(d[7]), "+f"(d[8]), "+f"(d[9]), "+f"(d[10]), "+f"(d[11]), "+f"(d[12]), "+f"(d[13]), "+f"(d[14]), "+f"(d[15]), "+f"(d[16]), "+f"(d[17]), "+f"(d[18]), "+f"(d[19]), "+f"(d[20]), "+f"(d[21]), "+f"(d[22]), "+f"(d[23]), "+f"(d[24]), "+f"(d[25]), "+f"(d[26]), "+f"(d[27]), "+f"(d[28]), "+f"(d[29]), "+f"(d[30]), "+f"(d[31])
               : "r"(a[0]), "r"(a[1]), "r"(a[2]), "r"(a[3]), "l"(db), "r"(sc));
}
__device__ __forceinline__ void wgmma_rt16(float (&d)[8], const uint32_t (&a)[4], uint64_t db, int sc) {
  asm volatile("{.reg .pred p; setp.ne.b32 p,%13,0; wgmma.mma_async.sync.aligned.m64n16k16.f32.bf16.bf16 "
               "{%0,%1,%2,%3,%4,%5,%6,%7},{%8,%9,%10,%11},%12,p,1,1,1;}"
               : "+f"(d[0]), "+f"(d[1]), "+f"(d[2]), "+f"(d[3]), "+f"(d[4]), "+f"(d[5]), "+f"(d[6]), "+f"(d[7])
               : "r"(a[0]), "r"(a[1]), "r"(a[2]), "r"(a[3]), "l"(db), "r"(sc));
}
__device__ __forceinline__ void wgmma_rt80(float (&d)[40], const uint32_t (&a)[4], uint64_t db, int sc) {
  asm volatile("{.reg .pred p; setp.ne.b32 p,%45,0; wgmma.mma_async.sync.aligned.m64n80k16.f32.bf16.bf16 "
               "{%0,%1,%2,%3,%4,%5,%6,%7,%8,%9,%10,%11,%12,%13,%14,%15,%16,%17,%18,%19,%20,%21,%22,%23,%24,%25,%26,%27,%28,%29,%30,%31,%32,%33,%34,%35,%36,%37,%38,%39},{%40,%41,%42,%43},%44,p,1,1,1;}"
               : "+f"(d[0]), "+f"(d[1]), "+f"(d[2]), "+f"(d[3]), "+f"(d[4]), "+f"(d[5]), "+f"(d[6]), "+f"(d[7]), "+f"(d[8]), "+f"(d[9]), "+f"(d[10]), "+f"(d[11]), "+f"(d[12]), "+f"(d[13]), "+f"(d[14]), "+f"(d[15]), "+f"(d[16]), "+f"(d[17]), "+f"(d[18]), "+f"(d[19]), "+f"(d[20]), "+f"(d[21]), "+f"(d[22]), "+f"(d[23]), "+f"(d[24]), "+f"(d[25]), "+f"(d[26]), "+f"(d[27]), "+f"(d[28]), "+f"(d[29]), "+f"(d[30]), "+f"(d[31]), "+f"(d[32]), "+f"(d[33]), "+f"(d[34]), "+f"(d[35]), "+f"(d[36]), "+f"(d[37]), "+f"(d[38]), "+f"(d[39])
               : "r"(a[0]), "r"(a[1]), "r"(a[2]), "r"(a[3]), "l"(db), "r"(sc));
}
__device__ __forceinline__ void wgmma_rs32(float (&d)[16], const uint32_t (&a)[4], uint64_t db, int sc) {
  asm volatile("{.reg .pred p; setp.ne.b32 p,%21,0; wgmma.mma_async.sync.aligned.m64n32k16.f32.bf16.bf16 "
               "{%0,%1,%2,%3,%4,%5,%6,%7,%8,%9,%10,%11,%12,%13,%14,%15},{%16,%17,%18,%19},%20,p,1,1,0;}"
               : "+f"(d[0]), "+f"(d[1]), "+f"(d[2]), "+f"(d[3]), "+f"(d[4]), "+f"(d[5]), "+f"(d[6]), "+f"(d[7]), "+f"(d[8]), "+f"(d[9]), "+f"(d[10]), "+f"(d[11]), "+f"(d[12]), "+f"(d[13]), "+f"(d[14]), "+f"(d[15])
               : "r"(a[0]), "r"(a[1]), "r"(a[2]), "r"(a[3]), "l"(db), "r"(sc));
}
__device__ __forceinline__ void wgmma_ts32(float (&d)[16], uint64_t da, uint64_t db, int sc) {
  asm volatile("{.reg .pred p; setp.ne.b32 p,%18,0; wgmma.mma_async.sync.aligned.m64n32k16.f32.bf16.bf16 "
               "{%0,%1,%2,%3,%4,%5,%6,%7,%8,%9,%10,%11,%12,%13,%14,%15},%16,%17,p,1,1,1,0;}"
               : "+f"(d[0]), "+f"(d[1]), "+f"(d[2]), "+f"(d[3]), "+f"(d[4]), "+f"(d[5]), "+f"(d[6]), "+f"(d[7]), "+f"(d[8]), "+f"(d[9]), "+f"(d[10]), "+f"(d[11]), "+f"(d[12]), "+f"(d[13]), "+f"(d[14]), "+f"(d[15])
               : "l"(da), "l"(db), "r"(sc));
}
__device__ __forceinline__ void wgmma_ts16(float (&d)[8], uint64_t da, uint64_t db, int sc) {
  asm volatile("{.reg .pred p; setp.ne.b32 p,%10,0; wgmma.mma_async.sync.aligned.m64n16k16.f32.bf16.bf16 "
               "{%0,%1,%2,%3,%4,%5,%6,%7},%8,%9,p,1,1,1,0;}"
               : "+f"(d[0]), "+f"(d[1]), "+f"(d[2]), "+f"(d[3]), "+f"(d[4]), "+f"(d[5]), "+f"(d[6]), "+f"(d[7])
               : "l"(da), "l"(db), "r"(sc));
}
__device__ __forceinline__ void wgmma_ts64(float (&d)[32], uint64_t da, uint64_t db, int sc) {
  asm volatile("{.reg .pred p; setp.ne.b32 p,%34,0; wgmma.mma_async.sync.aligned.m64n64k16.f32.bf16.bf16 "
               "{%0,%1,%2,%3,%4,%5,%6,%7,%8,%9,%10,%11,%12,%13,%14,%15,%16,%17,%18,%19,%20,%21,%22,%23,%24,%25,%26,%27,%28,%29,%30,%31},%32,%33,p,1,1,1,0;}"
               : "+f"(d[0]), "+f"(d[1]), "+f"(d[2]), "+f"(d[3]), "+f"(d[4]), "+f"(d[5]), "+f"(d[6]), "+f"(d[7]), "+f"(d[8]), "+f"(d[9]), "+f"(d[10]), "+f"(d[11]), "+f"(d[12]), "+f"(d[13]), "+f"(d[14]), "+f"(d[15]), "+f"(d[16]), "+f"(d[17]), "+f"(d[18]), "+f"(d[19]), "+f"(d[20]), "+f"(d[21]), "+f"(d[22]), "+f"(d[23]), "+f"(d[24]), "+f"(d[25]), "+f"(d[26]), "+f"(d[27]), "+f"(d[28]), "+f"(d[29]), "+f"(d[30]), "+f"(d[31])
               : "l"(da), "l"(db), "r"(sc));
}
__device__ __forceinline__ void wgmma_tt16(float (&d)[8], uint64_t da, uint64_t db, int sc) {
  asm volatile("{.reg .pred p; setp.ne.b32 p,%10,0; wgmma.mma_async.sync.aligned.m64n16k16.f32.bf16.bf16 "
               "{%0,%1,%2,%3,%4,%5,%6,%7},%8,%9,p,1,1,1,1;}"
               : "+f"(d[0]), "+f"(d[1]), "+f"(d[2]), "+f"(d[3]), "+f"(d[4]), "+f"(d[5]), "+f"(d[6]), "+f"(d[7])
               : "l"(da), "l"(db), "r"(sc));
}
__device__ __forceinline__ void wgmma_tt40(float (&d)[20], uint64_t da, uint64_t db, int sc) {
  asm volatile("{.reg .pred p; setp.ne.b32 p,%22,0; wgmma.mma_async.sync.aligned.m64n40k16.f32.bf16.bf16 "
               "{%0,%1,%2,%3,%4,%5,%6,%7,%8,%9,%10,%11,%12,%13,%14,%15,%16,%17,%18,%19},%20,%21,p,1,1,1,1;}"
               : "+f"(d[0]), "+f"(d[1]), "+f"(d[2]), "+f"(d[3]), "+f"(d[4]), "+f"(d[5]), "+f"(d[6]), "+f"(d[7]), "+f"(d[8]), "+f"(d[9]), "+f"(d[10]), "+f"(d[11]), "+f"(d[12]), "+f"(d[13]), "+f"(d[14]), "+f"(d[15]), "+f"(d[16]), "+f"(d[17]), "+f"(d[18]), "+f"(d[19])
               : "l"(da), "l"(db), "r"(sc));
}
__device__ __forceinline__ void wgmma_ss8(float (&d)[4], uint64_t da, uint64_t db, int sc) {
  asm volatile("{.reg .pred p; setp.ne.b32 p,%6,0; wgmma.mma_async.sync.aligned.m64n8k16.f32.bf16.bf16 "
               "{%0,%1,%2,%3},%4,%5,p,1,1,0,0;}"
               : "+f"(d[0]), "+f"(d[1]), "+f"(d[2]), "+f"(d[3])
               : "l"(da), "l"(db), "r"(sc));
}
__device__ __forceinline__ void wgmma_ss32(float (&d)[16], uint64_t da, uint64_t db, int sc) {
  asm volatile("{.reg .pred p; setp.ne.b32 p,%18,0; wgmma.mma_async.sync.aligned.m64n32k16.f32.bf16.bf16 "
               "{%0,%1,%2,%3,%4,%5,%6,%7,%8,%9,%10,%11,%12,%13,%14,%15},%16,%17,p,1,1,0,0;}"
               : "+f"(d[0]), "+f"(d[1]), "+f"(d[2]), "+f"(d[3]), "+f"(d[4]), "+f"(d[5]), "+f"(d[6]), "+f"(d[7]), "+f"(d[8]), "+f"(d[9]), "+f"(d[10]), "+f"(d[11]), "+f"(d[12]), "+f"(d[13]), "+f"(d[14]), "+f"(d[15])
               : "l"(da), "l"(db), "r"(sc));
}
__device__ __forceinline__ void wgmma_st64(float (&d)[32], uint64_t da, uint64_t db, int sc) {
  asm volatile("{.reg .pred p; setp.ne.b32 p,%34,0; wgmma.mma_async.sync.aligned.m64n64k16.f32.bf16.bf16 "
               "{%0,%1,%2,%3,%4,%5,%6,%7,%8,%9,%10,%11,%12,%13,%14,%15,%16,%17,%18,%19,%20,%21,%22,%23,%24,%25,%26,%27,%28,%29,%30,%31},%32,%33,p,1,1,0,1;}"
               : "+f"(d[0]), "+f"(d[1]), "+f"(d[2]), "+f"(d[3]), "+f"(d[4]), "+f"(d[5]), "+f"(d[6]), "+f"(d[7]), "+f"(d[8]), "+f"(d[9]), "+f"(d[10]), "+f"(d[11]), "+f"(d[12]), "+f"(d[13]), "+f"(d[14]), "+f"(d[15]), "+f"(d[16]), "+f"(d[17]), "+f"(d[18]), "+f"(d[19]), "+f"(d[20]), "+f"(d[21]), "+f"(d[22]), "+f"(d[23]), "+f"(d[24]), "+f"(d[25]), "+f"(d[26]), "+f"(d[27]), "+f"(d[28]), "+f"(d[29]), "+f"(d[30]), "+f"(d[31])
               : "l"(da), "l"(db), "r"(sc));
}
__device__ __forceinline__ void wgmma_st128(float (&d)[64], uint64_t da, uint64_t db, int sc) {
  asm volatile("{.reg .pred p; setp.ne.b32 p,%66,0; wgmma.mma_async.sync.aligned.m64n128k16.f32.bf16.bf16 "
               "{%0,%1,%2,%3,%4,%5,%6,%7,%8,%9,%10,%11,%12,%13,%14,%15,%16,%17,%18,%19,%20,%21,%22,%23,%24,%25,%26,%27,%28,%29,%30,%31,%32,%33,%34,%35,%36,%37,%38,%39,%40,%41,%42,%43,%44,%45,%46,%47,%48,%49,%50,%51,%52,%53,%54,%55,%56,%57,%58,%59,%60,%61,%62,%63},%64,%65,p,1,1,0,1;}"
               : "+f"(d[0]), "+f"(d[1]), "+f"(d[2]), "+f"(d[3]), "+f"(d[4]), "+f"(d[5]), "+f"(d[6]), "+f"(d[7]), "+f"(d[8]), "+f"(d[9]), "+f"(d[10]), "+f"(d[11]), "+f"(d[12]), "+f"(d[13]), "+f"(d[14]), "+f"(d[15]), "+f"(d[16]), "+f"(d[17]), "+f"(d[18]), "+f"(d[19]), "+f"(d[20]), "+f"(d[21]), "+f"(d[22]), "+f"(d[23]), "+f"(d[24]), "+f"(d[25]), "+f"(d[26]), "+f"(d[27]), "+f"(d[28]), "+f"(d[29]), "+f"(d[30]), "+f"(d[31]), "+f"(d[32]), "+f"(d[33]), "+f"(d[34]), "+f"(d[35]), "+f"(d[36]), "+f"(d[37]), "+f"(d[38]), "+f"(d[39]), "+f"(d[40]), "+f"(d[41]), "+f"(d[42]), "+f"(d[43]), "+f"(d[44]), "+f"(d[45]), "+f"(d[46]), "+f"(d[47]), "+f"(d[48]), "+f"(d[49]), "+f"(d[50]), "+f"(d[51]), "+f"(d[52]), "+f"(d[53]), "+f"(d[54]), "+f"(d[55]), "+f"(d[56]), "+f"(d[57]), "+f"(d[58]), "+f"(d[59]), "+f"(d[60]), "+f"(d[61]), "+f"(d[62]), "+f"(d[63])
               : "l"(da), "l"(db), "r"(sc));
}

__device__ __forceinline__ void stsm4(uint32_t a, uint32_t r0, uint32_t r1, uint32_t r2, uint32_t r3) {
  asm volatile("stmatrix.sync.aligned.m8n8.x4.shared.b16 [%0],{%1,%2,%3,%4};" ::"r"(a), "r"(r0), "r"(r1), "r"(r2), "r"(r3) : "memory");
}
__device__ __forceinline__ void stsm4t(uint32_t a, uint32_t r0, uint32_t r1, uint32_t r2, uint32_t r3) {
  asm volatile("stmatrix.sync.aligned.m8n8.x4.trans.shared.b16 [%0],{%1,%2,%3,%4};" ::"r"(a), "r"(r0), "r"(r1), "r"(r2), "r"(r3) : "memory");
}
__device__ __forceinline__ void sts64(uint32_t a, uint32_t x, uint32_t y) { asm volatile("st.shared.v2.b32 [%0],{%1,%2};" ::"r"(a), "r"(x), "r"(y) : "memory"); }
__device__ __forceinline__ void st_async2u(uint32_t a, uint32_t x, uint32_t y, uint32_t bar) {
  asm volatile("st.async.weak.shared::cluster.mbarrier::complete_tx::bytes.v2.b32 [%0],{%1,%2},[%3];" ::"r"(a), "r"(x), "r"(y), "r"(bar) : "memory");
}
__device__ __forceinline__ void st_relaxed128(void* p, uint32_t x, uint32_t y, uint32_t z, uint32_t w) {
  asm volatile("{.reg .b128 v; mov.b128 v,{%1,%2,%3,%4}; st.relaxed.gpu.global.b128 [%0],v;}" ::"l"(p), "r"(x), "r"(y), "r"(z), "r"(w) : "memory");
}
__device__ __forceinline__ void st_relaxed64(void* p, uint32_t x, uint32_t y) {
  asm volatile("{.reg .b64 v; mov.b64 v,{%1,%2}; st.relaxed.gpu.global.b64 [%0],v;}" ::"l"(p), "r"(x), "r"(y) : "memory");
}
__device__ __forceinline__ uint4 ld_relaxed128(const void* p) {
  uint4 v;
  asm volatile("{.reg .b128 v; .reg .b64 lo, hi; ld.relaxed.gpu.global.b128 v,[%4]; mov.b128 {lo,hi},v; mov.b64 {%0,%1},lo; mov.b64 {%2,%3},hi;}" : "=r"(v.x), "=r"(v.y), "=r"(v.z), "=r"(v.w) : "l"(p) : "memory");
  return v;
}

__device__ __forceinline__ uint32_t pack_h2(float lo, float hi) {
  uint32_t r; asm("cvt.rn.satfinite.f16x2.f32 %0,%1,%2;" : "=r"(r) : "f"(hi), "f"(lo)); return r;
}
__device__ __forceinline__ void add_h2(float& lo, float& hi, uint32_t u, uint32_t v) {
  float a, b;
  asm("{.reg .b16 l, h; .reg .b32 s; add.rn.f16x2 s,%2,%3; mov.b32 {l,h},s; cvt.f32.f16 %0,l; cvt.f32.f16 %1,h;}" : "=f"(a), "=f"(b) : "r"(u), "r"(v));
  lo += a; hi += b;
}
__device__ __forceinline__ void mwait(uint32_t bar, uint32_t ph, int& spin) {
  asm volatile("{.reg .pred p, q;\nWAIT_LOOP:\n add.s32 %0,%0,1;\n setp.lt.s32 q,%0,%3;\n mbarrier.try_wait.parity.shared::cta.b64 p,[%1],%2;\n not.pred p,p;\n and.pred q,q,p;\n @q bra.uni WAIT_LOOP;\n}"
               : "+&r"(spin) : "r"(bar), "r"(ph), "n"(SPIN_TOT) : "memory");
}
__device__ __forceinline__ int keep(int x) { return __shfl_sync(0xffffffffu, x, threadIdx.x & 31); }
__device__ __forceinline__ uint32_t pin(uint32_t x) { asm volatile("" : "+r"(x)); return x; }
template <typename T> __device__ __forceinline__ T* pinp(T* x) { asm volatile("" : "+l"(x)); return x; }
__device__ __forceinline__ void st_async1u(uint32_t a, uint32_t x, uint32_t bar) {
  asm volatile("st.async.weak.shared::cluster.mbarrier::complete_tx::bytes.b32 [%0],%1,[%2];" ::"r"(a), "r"(x), "r"(bar) : "memory");
}
__device__ __forceinline__ uint32_t lds32(uint32_t a) { uint32_t v; asm volatile("ld.shared.b32 %0,[%1];" : "=r"(v) : "r"(a) : "memory"); return v; }
__device__ __forceinline__ uint2 lds64(uint32_t a) { uint2 v; asm volatile("ld.shared.v2.b32 {%0,%1},[%2];" : "=r"(v.x), "=r"(v.y) : "r"(a) : "memory"); return v; }

__device__ __forceinline__ void permute_cols(uint32_t tile, int tid) {
  for (int it = tid; it < 2560; it += 128) {
    const int row = it >> 2, q = it & 3;
    const uint32_t a0 = tile + row * 128 + (((2 * q) ^ (row & 7)) << 4), a1 = tile + row * 128 + (((2 * q + 1) ^ (row & 7)) << 4);
    const uint4 u = lds128(a0), v = lds128(a1);
    sts128(a0, make_uint4(__byte_perm(u.x, u.y, 0x5410), __byte_perm(u.z, u.w, 0x5410), __byte_perm(v.x, v.y, 0x5410), __byte_perm(v.z, v.w, 0x5410)));
    sts128(a1, make_uint4(__byte_perm(u.x, u.y, 0x7632), __byte_perm(u.z, u.w, 0x7632), __byte_perm(v.x, v.y, 0x7632), __byte_perm(v.z, v.w, 0x7632)));
  }
}

__device__ __forceinline__ uint8_t* mkptr(uint32_t lo, uint32_t hi) { uint8_t* p; asm("mov.b64 %0,{%1,%2};" : "=l"(p) : "r"(lo), "r"(hi)); return p; }
__device__ __forceinline__ int uni(int x) { return __shfl_sync(0xffffffffu, x, 0); }

__device__ __forceinline__ void ln_row_to_image(const bf16* __restrict__ x, uint8_t* __restrict__ img, int row, int lane) {
  const uint4* src = reinterpret_cast<const uint4*>(x + (size_t)row * DM);
  uint4 v[3];
  v[0] = src[lane]; v[1] = src[lane + 32];
  v[2] = lane < 16 ? src[lane + 64] : make_uint4(0, 0, 0, 0);
  float s = 0.f;
#pragma unroll
  for (int i = 0; i < 3; i++) {
    s += bf_lo(v[i].x) + bf_hi(v[i].x) + bf_lo(v[i].y) + bf_hi(v[i].y) + bf_lo(v[i].z) + bf_hi(v[i].z) + bf_lo(v[i].w) + bf_hi(v[i].w);
  }
#pragma unroll
  for (int o = 16; o > 0; o >>= 1) s += __shfl_xor_sync(0xffffffffu, s, o);
  const float mean = s * (1.f / DM);
  float q = 0.f;
#pragma unroll
  for (int i = 0; i < 3; i++) {
    if (i < 2 || lane < 16) {
      const uint32_t w[4] = {v[i].x, v[i].y, v[i].z, v[i].w};
#pragma unroll
      for (int j = 0; j < 4; j++) { float a = bf_lo(w[j]) - mean, b = bf_hi(w[j]) - mean; q += a * a + b * b; }
    }
  }
#pragma unroll
  for (int o = 16; o > 0; o >>= 1) q += __shfl_xor_sync(0xffffffffu, q, o);
  const float rstd = rsqrtf(q * (1.f / DM) + 1e-5f);
#pragma unroll
  for (int i = 0; i < 3; i++) {
    if (i < 2 || lane < 16) {
      const int c = lane + 32 * i;
      uint4 o;
      o.x = pack_bf16((bf_lo(v[i].x) - mean) * rstd, (bf_hi(v[i].x) - mean) * rstd);
      o.y = pack_bf16((bf_lo(v[i].y) - mean) * rstd, (bf_hi(v[i].y) - mean) * rstd);
      o.z = pack_bf16((bf_lo(v[i].z) - mean) * rstd, (bf_hi(v[i].z) - mean) * rstd);
      o.w = pack_bf16((bf_lo(v[i].w) - mean) * rstd, (bf_hi(v[i].w) - mean) * rstd);
      const size_t off = (size_t)(row >> 5) * 40960 + (c >> 4) * 8192 + ((row >> 3) & 3) * 2048 + ((c >> 3) & 1) * 1024 + (row & 7) * 128 + (((c & 7) ^ (row & 7)) << 4);
      *reinterpret_cast<uint4*>(img + off) = o;
      float4* xf = reinterpret_cast<float4*>(g_x + (size_t)row * DM + c * 8);
      xf[0] = make_float4(bf_lo(v[i].x), bf_hi(v[i].x), bf_lo(v[i].y), bf_hi(v[i].y));
      xf[1] = make_float4(bf_lo(v[i].z), bf_hi(v[i].z), bf_lo(v[i].w), bf_hi(v[i].w));
    }
  }
}

__global__ void __launch_bounds__(256) k_pre(const bf16* __restrict__ x, const bf16* __restrict__ mem0) {
  const int row = blockIdx.x * 8 + (threadIdx.x >> 5);
  ln_row_to_image(x, g_xn[0], row, threadIdx.x & 31);
  const int gt = blockIdx.x * 256 + threadIdx.x;
  const uint4 sent = make_uint4(SENT, SENT, SENT, SENT);
  uint8_t* ex = ex_window(g_ex);
  if (gt < MAIL_BYTES / 16) {
    reinterpret_cast<uint4*>(ex + EX_MAIL)[gt] = sent;
    reinterpret_cast<uint4*>(ex + EX_MAIL + (1 << 20))[gt] = sent;
  }
  uint4* mb = reinterpret_cast<uint4*>(ex + EX_M);
  for (int i = gt; i < NSTEP * 1280; i += 65536) {
    const int p = i % 1280, st = i / 1280;
    uint4 v = sent;
    if (st == 0 || (st == LAG && (p & 8))) v = *reinterpret_cast<const uint4*>(mem0 + (p & 7) * DM + (p >> 4) * 8);
    mb[i] = v;
  }
  if (gt < NSTEP * 192) reinterpret_cast<uint4*>(ex + EX_FLAG)[gt] = gt < 192 ? make_uint4(0, 0, 0, 0) : sent;
  if (gt < CN_NUM) g_cnt[gt][0] = 0;
}

namespace C {
constexpr int NKR = 37;
constexpr int OFF_WQ = 0, OFF_WK = 81920;
constexpr int OFF_YO = 163840, OFF_YV = OFF_YO + 6144;
constexpr int OFF_M = 176128;
__host__ __device__ constexpr int og_off(int c) { return c ? OFF_M + 14336 + c * 2048 : 229376; }
constexpr int OFF_KT = 196608;
constexpr int OFF_XT = OFF_KT + 10240;
constexpr int OFF_VT = OFF_XT + 7168;
constexpr int OFF_XM = OFF_VT + 11392;
constexpr int OFF_PT = OFF_XM + 2560;
constexpr int KS = 1280, VS = 1408;
__host__ __device__ constexpr int slot_off(int p) { return p == 2 ? OFF_M : OFF_KT + (p % 3) * 16384; }
constexpr int OFF_BAR = 231552;
constexpr int OFF_SAFE = OFF_BAR + 160;
constexpr int OFF_TS = OFF_BAR + 256;
constexpr int SMEM = 232448;
constexpr uint32_t SB0 = 1024;
constexpr int BAR_F = OFF_BAR, BAR_E = OFF_BAR + 40, BAR_M = OFF_BAR + 80, BAR_MOK = OFF_BAR + 88, BAR_XM = OFF_BAR + 96, BAR_XF = OFF_BAR + 104,
              BAR_XT = OFF_BAR + 112, BAR_MF = OFF_BAR + 120, BAR_OG = OFF_BAR + 128, BAR_W = OFF_BAR + 136, FLG_REDO = OFF_BAR + 144;
constexpr int NB_PRO = 1, NB_RD = 2, NB_MR = 3, NB_QK = 4, NB_SM = 5, NB_VA = 6, NB_VQ = 7, NB_A = 8, NB_Q = 9, NB_C = 10, NB_WQ = 11, NB_QI = 12, NB_SI = 13, NB_WV = 14;
#define B1 300
#define B2 250
#define FLP 0
#define OSG 2
#define QIE 4
#define SIE 2
#define WOE 1
#define OGF 0
#define VSP 8
#define RFK 5
#define PFD 3
#define WOL 0
#define NOWORK 0
constexpr float SCL = 1.f / 2048, SCE = 0.07216878364870322f * 1.4426950408889634f * 2048;
}

#define CBAR_SYNC(id, n) bar_sync(id, n)
#define CBAR_ARRIVE(id, n) bar_arrive(id, n)

__device__ __forceinline__ uint64_t wdesc(int off) { return mkdesc(C::SB0 + off, 8192, 1024); }
__device__ __forceinline__ uint64_t mdesc(int k) { return mkdesc_ns(C::SB0 + C::OFF_M + k * 512, 256, 128); }
__device__ __forceinline__ uint64_t tdesc(int k) { return mkdesc(C::SB0 + C::slot_off(k >> 3) + ((k >> 2) & 1) * 1024 + (k & 3) * 32, 16, 2048); }

__device__ __forceinline__ int dh_row(int n) { return (n & ~63) + (n & 32) + ((n >> 1) & 3) * 8 + ((n >> 3) & 3) * 2 + (n & 1); }
template <bool PERM>
__device__ __forceinline__ void load_weights_rs(uint32_t (&wf)[C::NKR][4], uint32_t sb, int stage, int yoff, int tid0) {
  using namespace C;
  const int i = (tid0 >> 3) & 3, n0 = (tid0 & 7) + (i >> 1) * 8;
  const int chunk = 2 * ((tid0 >> 5) & 3) + (i & 1);
  const int r0 = PERM ? dh_row(n0) : n0, r1 = PERM ? dh_row(n0 + 16) : n0 + 16;
  const uint32_t a0 = sb + stage + r0 * 128 + ((chunk ^ (r0 & 7)) << 4), a1 = sb + stage + r1 * 128 + ((chunk ^ (r1 & 7)) << 4);
#pragma unroll
  for (int k = 0; k < NKR; k++) ldsm4t(wf[k], ((k & 1) ? a1 : a0) + (k >> 1) * 4096);
#pragma unroll
  for (int k = 0; k < 40 - NKR; k++) {
    const int n = (NKR + k) * 16 + ((tid0 & 127) >> 3), r = PERM ? dh_row(n) : n, c = tid0 & 7;
    sts128(sb + yoff + (n - NKR * 16) * 128 + ((c ^ (n & 7)) << 4), lds128(sb + stage + r * 128 + ((c ^ (r & 7)) << 4)));
  }
  fence_async();
  CBAR_SYNC(NB_PRO, 384);
}
template <int STRIDE>
__device__ __forceinline__ void store_mem(const float (&d)[8], uint32_t base, int tid) {
  const int m = (tid >> 3) & 3;
  stsm4(base + (((tid >> 5) & 3) * 2 + (m & 1)) * STRIDE + (m >> 1) * 640 + (tid & 7) * 16, pack_bf16(d[0], d[1]), pack_bf16(d[2], d[3]),
        pack_bf16(d[4], d[5]), pack_bf16(d[6], d[7]));
}

__device__ __forceinline__ void load_pair(uint32_t sb, int i, int p, uint32_t slot, uint32_t bar, uint32_t ph, int& spin) {
  using namespace C;
  const uint8_t* s0 = g_xn[0] + (size_t)i * 40960 + p * 8192;
  const uint8_t* s1 = g_xn[NOWORK ? 0 : 1] + (size_t)(i - LAG) * 40960 + p * 8192;
  const uint8_t* sa = pinp(i < NSEG ? s0 : s1);
  const uint8_t* sc = pinp(i >= LAG ? s1 : s0);
  const uint32_t dst = pin(sb + slot), fb = pin(sb + BAR_F + 8 * p);
  mwait(bar, ph, spin);
  bulk_g2s_mc(dst, sa, 8192, fb);
  bulk_g2s_mc(dst + 8192, sc, 8192, fb);
}
__device__ __forceinline__ void first_fill(uint32_t sb, int i, int rank, int& spin) {
  using namespace C;
  const int s1 = i - LAG;
  if (!NOWORK && s1 >= 0) { cwait(CN_X + s1, 32, spin); fence_async_all(); }
  load_pair(sb, i, rank, rank == 2 ? OFF_M : OFF_KT + rank * 16384, sb + BAR_E + 8 * rank, (i - 1) & 1, spin);
}
__device__ __forceinline__ void release_round(uint32_t sb, int p, int tid) {
  using namespace C;
  const int lane = tid & 31;
  if (p < 2) { if (lane == 0) mbar_arrive_cluster(mapa(sb, p) + BAR_E + 8 * (3 + p)); }
  else if (lane < 3) mbar_arrive_cluster(mapa(sb, lane) + BAR_MOK);
}

template <int K0, int K1>
__device__ __forceinline__ void v_mem_pass(float (&d)[8], const uint32_t (&wf)[C::NKR][4]) {
  using namespace C;
  wg_fence();
#pragma unroll
  for (int k = K0; k < K1; k++) {
    if (k < NKR) wgmma_rs16(d, wf[k < NKR ? k : 0], mdesc(k), k != 32);
    else wgmma_ts16(d, wdesc(OFF_YV + (k - NKR) * 2048), mdesc(k), 1);
  }
  wg_commit();
}
__device__ __forceinline__ void chain_v(const uint32_t sb, const int tid0, const int cta, const int rank) {
  using namespace C;
  asm volatile("setmaxnreg.inc.sync.aligned.u32 208;");
  int spin = 0;
  uint32_t wf[NKR][4];
  if (tid0 == 256) first_fill(sb, 0, rank, spin);
  __syncwarp();
  mwait(sb + BAR_W, 0, spin);
  for (int it = tid0 & 127; it < 1280; it += 128) {
    const uint32_t base = sb + OFF_WK + (it >> 1) * 128;
    const int sw = ((it >> 1) & 7) ^ ((it & 1) * 4);
    const uint4 u0 = lds128(base + (sw << 4)), u1 = lds128(base + ((sw ^ 1) << 4)), u2 = lds128(base + ((sw ^ 2) << 4)), u3 = lds128(base + ((sw ^ 3) << 4));
    sts128(base + (sw << 4), make_uint4(u0.x, u1.x, u2.x, u3.x)); sts128(base + ((sw ^ 1) << 4), make_uint4(u0.y, u1.y, u2.y, u3.y));
    sts128(base + ((sw ^ 2) << 4), make_uint4(u0.z, u1.z, u2.z, u3.z)); sts128(base + ((sw ^ 3) << 4), make_uint4(u0.w, u1.w, u2.w, u3.w));
  }
  bar_sync(NB_RD, 128);
  load_weights_rs<false>(wf, sb, OFF_WK, OFF_YV, tid0);
#pragma unroll 1
  for (int i = 0; i < NSTEP; i++) {
    {
      float d[32];
      if (i > 0) CBAR_SYNC(NB_WV, 256);
#pragma unroll
      for (int p = 0; p < 5; p++) {
        mwait(sb + BAR_F + 8 * p, i & 1, spin);
        TS(i, 25 + p);
        wg_fence();
#pragma unroll
        for (int k = 8 * p; k < 8 * p + 8; k++) {
          if (k < NKR) wgmma_rs64(d, wf[k < NKR ? k : 0], tdesc(k), k);
          else wgmma_ts64(d, wdesc(OFF_YV + (k - NKR) * 2048), tdesc(k), 1);
          if (k == 8 * p + 1 && p >= 1 && p <= 3) {
            wg_commit(); wg_wait<1>();
            release_round(sb, p - 1, fresh(tid0));
            wg_fence();
          }
          if (k == 8 * p + RFK && (p == 1 || p == 2)) {
            wg_commit();
            if (rank == p - 1 && tid0 == 256) load_pair(sb, i, p + 2, slot_off(p + 2), sb + BAR_E + 8 * (p + 2), i & 1, spin);
            __syncwarp();
            wg_fence();
          }
        }
        wg_commit();
      }
      wg_wait<0>();
      TS(i, 23);
      CBAR_SYNC(NB_RD, 256);
      const int tid = fresh(tid0) & 127, m = (tid >> 3) & 3;
      if (tid >= 96) {
        if (tid < 101) { if (i + 1 < NSTEP) mbar_expect_tx(sb + BAR_F + 8 * (tid - 96), 16384); }
        else if (tid == 101) mbar_expect_tx(sb + BAR_XM, 2560);
        else if (tid == 102) mbar_expect_tx(sb + BAR_XT, 7168);
        else if (tid == 103) mbar_expect_tx(sb + BAR_OG, 4096);
        else if (tid < 106) mbar_arrive_cluster(mapa(sb, (rank + tid - 103) % 3) + BAR_XF);
        __syncwarp();
      }
      const uint32_t a = sb + OFF_VT + 256 + ((tid >> 5) * 2 + (m & 1)) * VS + (m >> 1) * 128 + (tid & 7) * 16;
#pragma unroll
      for (int s = 0; s < 4; s++)
        stsm4(a + (s & 1) * 256 + (s >> 1) * 640, pack_bf16(d[8 * s], d[8 * s + 1]), pack_bf16(d[8 * s + 2], d[8 * s + 3]),
              pack_bf16(d[8 * s + 4], d[8 * s + 5]), pack_bf16(d[8 * s + 6], d[8 * s + 7]));
      if (tid < 80) sts128(sb + (tid < 72 ? OFF_VT + (tid >> 3) * VS : OFF_PT + 1280) + (tid & 7) * 16, make_uint4(0, 0, 0, 0));
      fence_async();
    }
    mwait(sb + BAR_XF, i & 1, spin);
    CBAR_ARRIVE(NB_QK, 384);
    CBAR_SYNC(NB_QI, 256);
    float d[8];
    v_mem_pass<32, 40>(d, wf);
    CBAR_SYNC(NB_SM, 256);
    wg_wait<0>();
    if (__builtin_expect(lds32(sb + FLG_REDO), 0)) { v_mem_pass<32, 40>(d, wf); wg_wait<0>(); }
    if ((tid0 & 31) < 2) mbar_arrive_cluster(mapa(sb, (rank + 1 + (tid0 & 1)) % 3) + BAR_MF);
    v_mem_pass<0, 32>(d, wf);
    wg_wait<0>();
    TS(i, 24);
    const int tid = fresh(tid0);
    if ((tid & 31) == 0) mbar_arrive_cluster(mapa(sb, 2) + BAR_E + 16);
    store_mem<VS>(d, sb + OFF_VT + 128, tid);
    fence_async();
    CBAR_ARRIVE(NB_VA, 256);
    CBAR_ARRIVE(NB_VQ, 256);
    if (tid == 256) {
      if (i + 1 < NSTEP) { first_fill(sb, i + 1, rank, spin); TS1(i + 1, 37); }
    } else if (tid >= 288 && tid < 295) {
      const int lane = tid & 31, ip = i + PFD;
      if (cta < 80 && ip < NSTEP) {
        if (lane < 2) prefetch_l2(ex_window(g_ex) + EX_M + ip * 20480 + (cta * 2 + lane) * 128);
        else if (lane == 6) { if (cta < 22) prefetch_l2(ex_window(g_ex) + EX_FLAG + ip * 3072 + cta * 128); }
        else if (ip < NSEG) prefetch_l2(g_xn[0] + (size_t)ip * 40960 + (cta * 4 + lane - 2) * 128);
      }
    }
    TS_FLUSH(i - 1);
    __syncwarp();
  }
  CBAR_ARRIVE(NB_WV, 256);
  if (spin >= SPIN_TOT) g_err = 3;
}

__device__ __forceinline__ float quad_max(float x) {
  const float a = __shfl_xor_sync(0xffffffffu, x, 1), b = __shfl_xor_sync(0xffffffffu, x, 2), c = __shfl_xor_sync(0xffffffffu, x, 3);
  return fmaxf(fmaxf(x, a), fmaxf(b, c));
}
__device__ __forceinline__ float quad_sum(float x) {
  const float a = __shfl_xor_sync(0xffffffffu, x, 1), b = __shfl_xor_sync(0xffffffffu, x, 2), c = __shfl_xor_sync(0xffffffffu, x, 3);
  return (x + a) + (b + c);
}
__device__ __forceinline__ float max10(const float (&y)[10]) {
  return fmaxf(fmaxf(fmaxf(fmaxf(y[0], y[1]), fmaxf(y[2], y[3])), fmaxf(fmaxf(y[4], y[5]), fmaxf(y[6], y[7]))), fmaxf(y[8], y[9]));
}
__device__ __forceinline__ float sum10(const float (&y)[10]) {
  return (((y[0] + y[1]) + (y[2] + y[3])) + ((y[4] + y[5]) + (y[6] + y[7]))) + (y[8] + y[9]);
}
__device__ __forceinline__ float rcp(float x) { float y; asm("rcp.approx.ftz.f32 %0,%1;" : "=f"(y) : "f"(x)); return y; }

__device__ __forceinline__ void signal_o(int i, int cta) { csignal(CN_O + i * 5 + min(cta / 19, 4)); }

__device__ __forceinline__ void chain_q(const CUtensorMap& tmWq, const CUtensorMap& tmWk, const uint32_t sb, const int tid0, const int cta, const int rank) {
  using namespace C;
  asm volatile("setmaxnreg.dec.sync.aligned.u32 96;");
  int spin = 0;
  CBAR_SYNC(NB_PRO, 384);
  PTS(5);
  if (tid0 == 128) {
    const int col = (cta / 3) * DH + rank * 64;
    mbar_expect_tx(sb + BAR_W, 163840);
    for (int i = 0; i < 5; i++) {
      tma2d(sb + OFF_WQ + i * 16384, &tmWq, col, i * 128, sb + BAR_W);
      tma2d(sb + OFF_WK + i * 16384, &tmWk, col, i * 128, sb + BAR_W);
    }
  }
  __syncwarp();
  mwait(sb + BAR_W, 1, spin);
  PTS(6);
#pragma unroll 1
  for (int i = 0; i < NSTEP; i++) {
    const int ph = i & 1;
    uint32_t qf[4][4];
    {
      float d[64];
#pragma unroll
      for (int p = 0; p < 5; p++) {
        mwait(sb + BAR_F + 8 * p, ph, spin);
        if (p == 0) TS(i, 0);
        wg_fence();
#pragma unroll
        for (int k = 8 * p; k < 8 * p + 8; k++) {
          wgmma_st128(d, tdesc(k), mkdesc(SB0 + OFF_WQ + k * 2048, OFF_WK - OFF_WQ, 1024), k);
          if (k == 8 * p + 1 && p >= 1 && p <= 3) {
            wg_commit(); wg_wait<1>();
            release_round(sb, p - 1, fresh(tid0));
            wg_fence();
          }
        }
        wg_commit();
      }
      wg_wait<0>();
      TS(i, 1);
      CBAR_SYNC(NB_RD, 256);
      TSB(i, 2);
      const int tid = fresh(tid0), w = (tid >> 5) & 3, m = (tid >> 3) & 3;
      const uint32_t a = sb + OFF_KT + (m >> 1) * KS + (1 + 5 * (w >> 1) + 2 * (w & 1) + (m & 1)) * 128 + (tid & 7) * 16;
#pragma unroll
      for (int s = 0; s < 4; s++)
        stsm4t(a + s * 2 * KS, pack_bf16(d[32 + 8 * s], d[33 + 8 * s]), pack_bf16(d[34 + 8 * s], d[35 + 8 * s]),
               pack_bf16(d[36 + 8 * s], d[37 + 8 * s]), pack_bf16(d[38 + 8 * s], d[39 + 8 * s]));
      fence_async();
      CBAR_ARRIVE(NB_QK, 384);
      if (OSG == 0) { if (tid == 224 && i > 0) signal_o(i - 1, cta); __syncwarp(); }
#pragma unroll
      for (int kk = 0; kk < 4; kk++)
#pragma unroll
        for (int j = 0; j < 4; j++) asm volatile("cvt.rn.bf16x2.f32 %0,%1,%2;" : "=r"(qf[kk][j]) : "f"(d[8 * kk + 2 * j + 1] * SCL), "f"(d[8 * kk + 2 * j] * SCL));
    }
    CBAR_SYNC(NB_SI, 256);
    uint32_t pf[5][4];
    float s0, s1;
    {
      float y0[10], y1[10];
      const int tid = fresh(tid0), lane = tid & 31, u = (tid >> 5) & 1;
      const bool c1 = tid & 64;
      {
        float x[40];
        wg_fence();
#pragma unroll
        for (int kk = 0; kk < 4; kk++) wgmma_rt80(x, qf[kk], mkdesc_ns(SB0 + OFF_KT + kk * 2 * KS, KS, 128), kk);
        wg_commit();
        wg_wait<0>();
#pragma unroll
        for (int j = 0; j < 5; j++) {
          y0[2 * j] = (c1 ? x[20 + 4 * j] : x[4 * j]); y0[2 * j + 1] = (c1 ? x[21 + 4 * j] : x[4 * j + 1]);
          y1[2 * j] = (c1 ? x[22 + 4 * j] : x[4 * j + 2]); y1[2 * j + 1] = (c1 ? x[23 + 4 * j] : x[4 * j + 3]);
        }
      }
      TS(i, 17);
      const uint32_t xo = OFF_XT + (c1 ? 1792 : 0) + u * 640 + lane * 16, x2 = xo + u * 512 + 512 - lane * 12;
      {
        const uint4 h0 = make_uint4(pack_h2(y0[0], y0[1]), pack_h2(y0[2], y0[3]), pack_h2(y1[0], y1[1]), pack_h2(y1[2], y1[3]));
        const uint4 h1 = make_uint4(pack_h2(y0[4], y0[5]), pack_h2(y0[6], y0[7]), pack_h2(y1[4], y1[5]), pack_h2(y1[6], y1[7]));
        const uint32_t h2 = u ? pack_h2(y1[8], y1[9]) : h1.z;
#pragma unroll
        for (int dd = 0; dd < 2; dd++) {
          const uint32_t rb = mapa(sb, (rank + 1 + dd) % 3), ro = rb + (1 - dd) * 3584;
          st_async4u(ro + xo, h0, rb + BAR_XT);
          if (u) st_async4u(ro + xo + 512, h1, rb + BAR_XT);
          st_async1u(ro + x2, h2, rb + BAR_XT);
        }
      }
      TS(i, 18);
      const int lim = 16 * u + (lane >> 2) + 8 - 2 * (lane & 3);
#pragma unroll
      for (int j = 1; j < 5; j++) {
        if (8 * j > lim) y0[2 * j] = -INFINITY;
        if (8 * j + 1 > lim) y0[2 * j + 1] = -INFINITY;
        if (8 * j - 8 > lim) y1[2 * j] = -INFINITY;
        if (8 * j - 7 > lim) y1[2 * j + 1] = -INFINITY;
      }
      mwait(sb + BAR_XT, ph, spin);
      TS(i, 19);
      {
        const uint4 u0 = lds128(sb + xo), v0 = lds128(sb + xo + 3584);
        const uint32_t u2 = lds32(sb + x2), v2 = lds32(sb + x2 + 3584);
        uint4 u1 = make_uint4(0, 0, u2, 0), v1 = make_uint4(0, 0, v2, 0);
        if (u) { u1 = lds128(sb + xo + 512); v1 = lds128(sb + xo + 512 + 3584); }
        __syncwarp();
        if (lane == 0) mbar_arrive_cluster(mapa(sb, 0) + BAR_E);
        add_h2(y0[0], y0[1], u0.x, v0.x); add_h2(y0[2], y0[3], u0.y, v0.y); add_h2(y1[0], y1[1], u0.z, v0.z); add_h2(y1[2], y1[3], u0.w, v0.w);
        add_h2(y0[4], y0[5], u1.x, v1.x); add_h2(y0[6], y0[7], u1.y, v1.y); add_h2(y1[4], y1[5], u1.z, v1.z); add_h2(y1[6], y1[7], u1.w, v1.w);
        add_h2(y1[8], y1[9], u2, v2);
      }
      y0[8] = y0[0]; y0[9] = y0[1];
      const float m0 = quad_max(max10(y0)) * -SCE, m1 = quad_max(max10(y1)) * -SCE;
      s0 = 0.f; s1 = 0.f;
#pragma unroll
      for (int j = 0; j < 5; j++) {
        const uint32_t p0 = j < 4 ? pack_bf16(ex2(fmaf(y0[2 * j], SCE, m0)), ex2(fmaf(y0[2 * j + 1], SCE, m0))) : 0u;
        const uint32_t p1 = pack_bf16(ex2(fmaf(y1[2 * j], SCE, m1)), ex2(fmaf(y1[2 * j + 1], SCE, m1)));
        s0 += bf_lo(p0) + bf_hi(p0); s1 += bf_lo(p1) + bf_hi(p1);
        pf[j >> 1][2 * (j & 1)] = c1 ? 0u : p0; pf[j >> 1][2 * (j & 1) + 1] = c1 ? 0u : p1;
        pf[(j + 5) >> 1][2 * ((j + 5) & 1)] = c1 ? p0 : 0u; pf[(j + 5) >> 1][2 * ((j + 5) & 1) + 1] = c1 ? p1 : 0u;
      }
    }
    CBAR_SYNC(NB_VQ, 256);
    TSB(i, 20);
    {
      float o[32];
      wg_fence();
#pragma unroll
      for (int q = 0; q < 5; q++) wgmma_rs64(o, pf[q], mkdesc_ns(SB0 + OFF_VT + 128 + q * 256, 128, VS), q);
      wg_commit();
      s0 = rcp(quad_sum(s0)); s1 = rcp(quad_sum(s1));
      const int tid = fresh(tid0), g = (tid >> 2) & 7, c = (tid >> 6) & 1, sg = i - c * LAG;
      uint8_t* op = pinp(&g_o[i % ORING][c][cta][(((tid >> 5) & 1) * 16 + g) * 128]);
      const uint32_t o0 = pin(((tid & 3) ^ g) << 4), live = pin(sg >= 0 && sg < NSEG);
      wg_wait<0>();
      TS(i, 21);
      if ((tid & 31) == 0) mbar_arrive_cluster(mapa(sb, 1) + BAR_E + 8);
      uint4 ov[4];
#pragma unroll
      for (int h = 0; h < 2; h++) {
        const float* x = o + 16 * h;
        ov[2 * h] = make_uint4(pin(pack_bf16(x[0] * s0, x[1] * s0)), pin(pack_bf16(x[4] * s0, x[5] * s0)), pin(pack_bf16(x[8] * s0, x[9] * s0)), pin(pack_bf16(x[12] * s0, x[13] * s0)));
        ov[2 * h + 1] = make_uint4(pin(pack_bf16(x[2] * s1, x[3] * s1)), pin(pack_bf16(x[6] * s1, x[7] * s1)), pin(pack_bf16(x[10] * s1, x[11] * s1)), pin(pack_bf16(x[14] * s1, x[15] * s1)));
      }
      TS(i, 22);
      if (i + 1 < NSTEP) CBAR_SYNC(NB_WQ, 256); else CBAR_ARRIVE(NB_WQ, 256);
      if (live) {
#pragma unroll
        for (int h = 0; h < 4; h++) *reinterpret_cast<uint4*>(op + (h & 1) * 1024 + (o0 ^ ((h >> 1) * 64))) = ov[h];
      }
      if (OSG && i + 1 < NSTEP) CBAR_ARRIVE(NB_MR, 160);
    }
  }
  CBAR_SYNC(NB_Q, 128);
  if (tid0 == 224) signal_o(NSTEP - 1, cta);
  if (spin >= SPIN_TOT) g_err = 2;
}

template <int NL>
__device__ __forceinline__ void poll_add(const uint8_t* mb, uint32_t tag, float (&f)[8], uint8_t* flag, bool lead, int osig, int& n, int& spin) {
  uint4 x[NL];
#pragma unroll
  for (int i = 0; i < NL; i++) x[i] = ld_relaxed128(mb + i * 512);
  if (OSG == 1 && osig >= 0) csignal(osig);
  while (true) {
    uint32_t any = 0;
#pragma unroll
    for (int i = 0; i < NL; i++) any |= (x[i].x ^ tag) | (NL == 6 ? x[i].z ^ tag : 0u);
    n++;
    if (!__any_sync(0xffffffffu, (any & 1) && spin < SPIN_TOT)) break;
    spin += 16;
#pragma unroll
    for (int i = 0; i < NL; i++)
      if (((pin(x[i].x) ^ tag) | (NL == 6 ? x[i].z ^ tag : 0u)) & 1) x[i] = ld_relaxed128(mb + i * 512);
  }
  if (FLP == 0 && lead) st_relaxed(flag, 0);
#pragma unroll
  for (int i = 0; i < NL; i++) {
    const uint32_t u[4] = {x[i].x, x[i].y, x[i].z, x[i].w};
#pragma unroll
    for (int j = 0; j < 4; j++) {
      if (i == 0) { f[2 * j] = bf_lo(u[j]); f[2 * j + 1] = bf_hi(u[j]); }
      else { f[2 * j] += bf_lo(u[j]); f[2 * j + 1] += bf_hi(u[j]); }
    }
  }
}

template <int B, int SLOT>
__device__ __forceinline__ void wo_block(float (&acc)[8], const uint32_t (&wf)[C::NKR][4]) {
  using namespace C;
#pragma unroll
  for (int kk = 0; kk < 4; kk++) {
    const int k = 4 * B + kk;
    const uint64_t db = mkdesc_ns(SB0 + og_off(SLOT) + kk * 512, 256, 128);
    if (k < NKR) wgmma_rt16(acc, wf[k < NKR ? k : 0], db, SLOT | kk);
    else wgmma_tt16(acc, wdesc(OFF_YO + (k - NKR) * 2048), db, 1);
  }
}

__device__ __forceinline__ void chain_a(const uint32_t sb, const int tid0, const int cta, const int rank) {
  using namespace C;
  asm volatile("setmaxnreg.inc.sync.aligned.u32 200;");
  int spin = 0;
  uint32_t wf[NKR][4];
  mwait(sb + BAR_W, 0, spin);
  permute_cols(sb + OFF_WQ, tid0);
  CBAR_SYNC(NB_A, 128);
  load_weights_rs<true>(wf, sb, OFF_WQ, OFF_YO, tid0);
  const int wu = uni(tid0 >> 5);
  const bool t9 = cta >= 72 && cta < 88;
  const uint64_t exa = reinterpret_cast<uint64_t>(ex_window(g_ex));
  const uint32_t ehi = (uint32_t)(exa >> 32), elo = (uint32_t)exa;

#pragma unroll 1
  for (int i = -1; i < NSTEP; i++) {
    const int ph = i & 1;
    if (i >= 0) {
      const int tid = fresh(tid0);
      const uint32_t mo = __shfl_xor_sync(0xffffffffu, elo + (ph << 20) + ((rank * 24 + (tid >> 4)) * 4 + (tid & 3)) * 2048 + (cta / 3) * 64 + (tid & 12) * 4, 0);
      const uint32_t m9 = __shfl_xor_sync(0xffffffffu, elo + (ph << 20) + MAIL9 + (((tid >> 4) * 2 + (tid & 1)) * 4 + (tid & 2)) * 3072 + cta * 32 + (tid & 12) * 2, 0);
      const uint32_t oo = __shfl_xor_sync(0xffffffffu, (tid >> 5) * 512 + (tid & 2) * 64 + (tid & 28) * 4 + (tid & 1) * 8, 0);
      if (i == 0) mwait(sb + BAR_W, 1, spin);
      mwait(sb + BAR_M, ph, spin);
      TS(i, 3);
      {
        float x[20];
        int redo = 0;
      retry:
        bool bad;
        {
          float dq[8], dk[8];
          wg_fence();
#pragma unroll
          for (int k = 0; k < 40; k++) wgmma_ts16(dq, wdesc(OFF_WQ + k * 2048), mdesc(k), k);
          wg_commit();
#pragma unroll
          for (int k = 0; k < 40; k++) {
            if (k == 40 - QIE && !redo) CBAR_ARRIVE(NB_QI, 256);
            wgmma_ts16(dk, wdesc(OFF_WK + k * 2048), mdesc(k), k);
          }
          wg_commit();
          const int m = (tid >> 3) & 3, dg = (tid >> 5) * 2 + (m & 1);
          const uint32_t ka = sb + OFF_KT + dg * KS + (m >> 1) * 640 + (tid & 7) * 16;
          wg_wait<1>();
          const float chk = (dq[0] + dq[1]) + (dq[4] + dq[5]);
          const uint32_t q0 = pack_bf16(dq[0] * SCL, dq[1] * SCL), q1 = pack_bf16(dq[2] * SCL, dq[3] * SCL), q2 = pack_bf16(dq[4] * SCL, dq[5] * SCL), q3 = pack_bf16(dq[6] * SCL, dq[7] * SCL);
          if (!redo) CBAR_SYNC(NB_QK, 384);
          stsm4(ka + dg * (VS - KS) + (OFF_VT + 128 - OFF_KT), q0, q1, q2, q3);
          sts32(sb + FLG_REDO, redo);
          wg_wait<0>();
          TS(i, 4);
          stsm4(ka, pack_bf16(dk[0], dk[1]), pack_bf16(dk[2], dk[3]), pack_bf16(dk[4], dk[5]), pack_bf16(dk[6], dk[7]));
          fence_async();
          bad = bar_red_or(NB_C, 128, chk != chk && !redo);
        }
        TSB(i, 5);
        wg_fence();
#pragma unroll
        for (int kk = 0; kk < 4; kk++) wgmma_tt40(x, mkdesc_ns(SB0 + OFF_VT + 128 + kk * 2 * VS, VS, 640), mkdesc_ns(SB0 + OFF_KT + kk * 2 * KS, KS, 128), kk);
#pragma unroll
        for (int kk = 0; kk < 4; kk++) {
          if (SIE && kk == 4 - SIE && !bad) CBAR_ARRIVE(NB_SI, 256);
          wgmma_tt40(x, mkdesc_ns(SB0 + OFF_VT + kk * 2 * VS, VS, 384), mkdesc_ns(SB0 + OFF_KT + 640 + kk * 2 * KS, KS, 128), 1);
        }
        wg_commit();
        if (!SIE && !bad) CBAR_ARRIVE(NB_SI, 256);
        if (__builtin_expect(__any_sync(0xffffffffu, bad), 0)) {
          wg_wait<0>();
#pragma unroll 1
          for (int k = 0; k < 10; k++) {
            uint4 v = lds128(sb + OFF_M + tid * 16 + k * 2048);
            if (v.x == SENT || v.y == SENT || v.z == SENT || v.w == SENT) {
              do { v = ld_relaxed4(mkptr(elo + EX_M + i * 20480 + tid * 16 + k * 2048, ehi)); spin += 16; } while ((v.x == SENT || v.y == SENT || v.z == SENT || v.w == SENT) && spin < SPIN_TOT);
              sts128(sb + OFF_M + tid * 16 + k * 2048, v);
            }
          }
          fence_async();
          bar_sync(NB_C, 128);
          redo = fresh(1);
          goto retry;
        }
        TSV(i, 36, redo);
        const uint32_t rb1 = mapa(sb, (rank + 1) % 3), rb2 = mapa(sb, (rank + 2) % 3);
        wg_wait<0>();
        TS(i, 6);
        if (wu < 2) {
          float y[10];
#pragma unroll
          for (int j = 0; j < 5; j++) { y[2 * j] = x[4 * j]; y[2 * j + 1] = x[4 * j + 1]; }
          const uint4 h0 = make_uint4(pack_h2(y[0], y[1]), pack_h2(y[2], y[3]), pack_h2(y[4], y[5]), pack_h2(y[6], y[7]));
          const uint32_t h1 = pack_h2(y[8], y[9]);
          st_async4u(rb1 + OFF_XM + 1024 + tid * 16, h0, rb1 + BAR_XM);
          st_async4u(rb2 + OFF_XM + tid * 16, h0, rb2 + BAR_XM);
          st_async1u(rb1 + OFF_XM + 2304 + tid * 4, h1, rb1 + BAR_XM);
          st_async1u(rb2 + OFF_XM + 2048 + tid * 4, h1, rb2 + BAR_XM);
          CBAR_ARRIVE(NB_SM, 256);
          if ((tid & 31) == 0) mbar_arrive_cluster(mapa(sb, 0) + BAR_E);
          TS(i, 7);
          const uint32_t sw = (tid & 7) * 4 + (tid & 8) * 8 + (tid & 16) * 2;
          mwait(sb + BAR_XM, ph, spin);
          TS(i, 8);
          const uint4 u0 = lds128(sb + OFF_XM + tid * 16), v0 = lds128(sb + OFF_XM + 1024 + tid * 16);
          const uint32_t u1 = lds32(sb + OFF_XM + 2048 + tid * 4), v1 = lds32(sb + OFF_XM + 2304 + tid * 4);
          add_h2(y[0], y[1], u0.x, v0.x); add_h2(y[2], y[3], u0.y, v0.y); add_h2(y[4], y[5], u0.z, v0.z); add_h2(y[6], y[7], u0.w, v0.w);
          add_h2(y[8], y[9], u1, v1);
          const float mx = quad_max(max10(y)) * -SCE;
#pragma unroll
          for (int j = 0; j < 5; j++) {
            y[2 * j] = ex2(fmaf(y[2 * j], SCE, mx)); y[2 * j + 1] = ex2(fmaf(y[2 * j + 1], SCE, mx));
            sts32(sb + OFF_PT + wu * 640 + sw + j * 128, pack_bf16(y[2 * j], y[2 * j + 1]));
          }
          sts32(sb + OFF_XM + 2048 + wu * 128 + sw, __float_as_uint(sum10(y)));
          fence_async();
          TS(i, 9);
        } else {
          CBAR_ARRIVE(NB_SM, 256);
          if ((tid & 31) == 0) mbar_arrive_cluster(mapa(sb, 0) + BAR_E);
          mwait(sb + BAR_MF, ph, spin);
        }
      }
      CBAR_SYNC(NB_VA, 256);
      TSB(i, 10);
      {
        float o[2][4];
        wg_fence();
#pragma unroll
        for (int c = 0; c < 2; c++)
#pragma unroll
          for (int q = 0; q < 3; q++)
            wgmma_ss8(o[c], mkdesc_ns(SB0 + OFF_VT + 128 + c * 640 + q * 256, 128, VS), mkdesc_ns(SB0 + OFF_PT + c * 640 + q * 256, q == 2 && c == 0 ? 768 : 128, 128), q);
        wg_commit();
        const float4 e = lds128f(sb + OFF_XM + 2048 + (tid & 15) * 16);
        const uint32_t rb1 = mapa(sb, (rank + 1) % 3), rb2 = mapa(sb, (rank + 2) % 3);
        const float inv = rcp((e.x + e.y) + (e.z + e.w));
        const int sl = (tid & 3) * 2;
        const float i0 = __shfl_sync(0xffffffffu, inv, sl), i1 = __shfl_sync(0xffffffffu, inv, sl + 1);
        const float i2 = __shfl_sync(0xffffffffu, inv, sl + 8), i3 = __shfl_sync(0xffffffffu, inv, sl + 9);
        wg_wait<0>();
        TS(i, 11);
        const uint32_t p0 = pack_bf16(o[0][0] * i0, o[0][1] * i1), p1 = pack_bf16(o[1][0] * i2, o[1][1] * i3);
        const uint32_t p2 = pack_bf16(o[0][2] * i0, o[0][3] * i1), p3 = pack_bf16(o[1][2] * i2, o[1][3] * i3);
        if (OGF) { sts64(sb + oo + og_off(0), p0, p1); sts64(sb + oo + og_off(0) + 256, p2, p3); fence_async(); }
        st_async2u(rb1 + oo + og_off(2), p0, p1, rb1 + BAR_OG);
        st_async2u(rb2 + oo + og_off(1), p0, p1, rb2 + BAR_OG);
        st_async2u(rb1 + oo + og_off(2) + 256, p2, p3, rb1 + BAR_OG);
        st_async2u(rb2 + oo + og_off(1) + 256, p2, p3, rb2 + BAR_OG);
        if (!OGF) { sts64(sb + oo + og_off(0), p0, p1); sts64(sb + oo + og_off(0) + 256, p2, p3); fence_async(); }
      }
      CBAR_SYNC(NB_A, 128);
      TSB(i, 12);
      {
        float acc[3][8];
        wg_fence();
        wo_block<0, 0>(acc[2], wf);
        wg_commit();
        wo_block<1, 0>(acc[0], wf);
        wo_block<4, 0>(acc[1], wf);
        wg_commit();
        const bool og = mbar_try(sb + BAR_OG, ph);
        const uint32_t tag = (i >> 1) & 1;
#define TAGGED(LO, HI) ((pack_bf16(LO, HI) & ~1u) | tag)
#define SEND(OFF, U) st_relaxed128(mkptr(mo, ehi) + (OFF), TAGGED(acc[U][0], acc[U][2]), pack_bf16(acc[U][1], acc[U][3]), pack_bf16(acc[U][4], acc[U][6]), pack_bf16(acc[U][5], acc[U][7]))
        wg_wait<1>();
        const uint32_t n0 = pin(TAGGED(acc[2][0], acc[2][2])), n1 = pin(pack_bf16(acc[2][1], acc[2][3]));
        const uint32_t n2 = pin(TAGGED(acc[2][4], acc[2][6])), n3 = pin(pack_bf16(acc[2][5], acc[2][7]));
        if (__builtin_expect(!og, 0)) mwait(sb + BAR_OG, ph, spin);
        asm volatile("fence.proxy.async::generic.acquire.sync_restrict::shared::cluster.cluster;" ::: "memory");
        TS(i, 13);
        wg_fence();
        wo_block<2, 1>(acc[0], wf); wo_block<3, 2>(acc[0], wf);
        wg_commit();
        st_relaxed64(mkptr(m9, ehi), n0, n1);
        st_relaxed64(mkptr(m9, ehi) + 3072, n2, n3);
        if ((tid & 31) == 0) mbar_arrive_cluster(mapa(sb, 1) + BAR_E + 8);
        wo_block<5, 1>(acc[1], wf); wo_block<6, 2>(acc[1], wf);
        wg_commit();
        wo_block<7, 0>(acc[2], wf);
        wg_commit();
        wg_wait<2>(); SEND(0, 0);
        wo_block<8, 1>(acc[2], wf); wo_block<9, 2>(acc[2], wf);
        wg_commit();
        if (WOE == 0) { CBAR_ARRIVE(NB_WV, 256); CBAR_ARRIVE(NB_WQ, 256); }
        wg_wait<2>(); SEND(32 * 2048, 1);
        if (WOE == 1) CBAR_ARRIVE(NB_WV, 256);
        wg_wait<0>(); SEND(64 * 2048, 2);
        if (WOE == 2) CBAR_ARRIVE(NB_WV, 256);
        if (WOE >= 1) CBAR_ARRIVE(NB_WQ, 256);
#undef SEND
#undef TAGGED
      }
      TS(i, 14);
      if (i + 1 >= NSTEP) break;
    }
    uint32_t t1 = clk32();
    if (i >= 0) {
      const int lane = fresh(tid0) & 31, j = lane >> 3;
      const uint8_t* mb = mkptr(elo + (ph << 20) + (t9 ? MAIL9 + (cta - 72) * 12288 + wu * 3072 : (cta < 72 ? cta : cta - 24) * 8192 + wu * 2048) + lane * 16, ehi);
      const uint32_t tag = (i >> 1) & 1;
      const bool pub = (lane & (t9 ? 6 : 4)) == 0 && !(((t9 ? cta : wu) & 1) && i + 1 == LAG) && cta < 88;
      const uint32_t dst = pin(elo + EX_M + (i + 1) * 20480 + (t9 ? (cta + 72) * 128 + wu * 32 + (j & 1) * 16 + (lane & 1) * 8 + (j >> 1) * 4
                                                                   : cta * 256 + (wu & 1) * 128 + (wu >> 1) * 64 + j * 16 + (lane & 3) * 4));
      uint8_t* flag = mkptr(elo + EX_FLAG + (i + 1) * 3072 + cta * 32 + wu * 4, ehi);
      const int osig = OSG == 1 && tid0 == 96 ? CN_O + i * 5 + min(cta / 19, 4) : -1;
      if (OSG && wu == 3) CBAR_SYNC(NB_MR, 160);
      while (clk32() - t1 < B1) {}
      TS(i + 1, 30);
      float f[8];
      int n = 0;
      if (!t9) poll_add<4>(mb, tag, f, flag, lane == 0, osig, n, spin);
      else poll_add<6>(mb, tag, f, flag, lane == 0, osig, n, spin);
      if (FLP == 1 && lane == 0) st_relaxed(flag, __float_as_uint(f[0] + f[7]) >> 1);
      t1 = clk32();
      TS(i + 1, 31); TSV(i + 1, 32, n);
      const bool h = lane & 16, q = lane & 8;
#pragma unroll
      for (int j = 0; j < 4; j++) f[j] = (h ? f[4 + j] : f[j]) + __shfl_xor_sync(0xffffffffu, h ? f[j] : f[4 + j], 16);
#pragma unroll
      for (int j = 0; j < 2; j++) f[j] = (q ? f[2 + j] : f[j]) + __shfl_xor_sync(0xffffffffu, q ? f[j] : f[2 + j], 8);
      f[0] += __shfl_xor_sync(0xffffffffu, f[0], 4); f[1] += __shfl_xor_sync(0xffffffffu, f[1], 4);
      if (t9) { f[0] += __shfl_xor_sync(0xffffffffu, f[0], 2); f[1] += __shfl_xor_sync(0xffffffffu, f[1], 2); }
      if (pub) st_relaxed(mkptr(dst, ehi), pack_bf16(f[0], f[1]));
      if (OSG == 2 && tid0 == 96) { TS1(i + 1, 38); signal_o(i, cta); TS1(i + 1, 39); }
      if (OSG == 4 && tid0 == 96) asm volatile("red.relaxed.gpu.global.add.u32 [%0],1;" ::"l"(&g_cnt[CN_O + i * 5 + min(cta / 19, 4)][0]) : "memory");
      TS(i + 1, 15);
    }
    if (wu == 0) {
      const int tid = fresh(tid0);
      const uint8_t* pp = mkptr(elo + EX_FLAG + (i + 1) * 3072 + (rank * 28 + (tid < 28 || rank == 2 ? tid : 0)) * 32, ehi);
      while (clk32() - t1 < B2) {}
      TS(i + 1, 16);
      int n = 1;
      uint4 x = ld_relaxed4(pp);
      if (tid0 == 0) mbar_expect_tx(sb + BAR_M, 20480);
      bool mok = mbar_test(sb + BAR_MOK, ph ^ 1);
      while (__any_sync(0xffffffffu, (int)(x.x | x.y | x.z | x.w) < 0 && spin < SPIN_TOT)) { x = ld_relaxed4(pp); mok = mbar_test(sb + BAR_MOK, ph ^ 1); n++; spin += 16; }
      if (!mok) mwait(sb + BAR_MOK, ph ^ 1, spin);
      TSV(i + 1, 35, n);
      TS(i + 1, 34);
      if (tid0 == 0) bulk_g2s_mc(sb + OFF_M + rank * 7168, mkptr(elo + EX_M + (i + 1) * 20480 + rank * 7168, ehi), rank == 2 ? 6144 : 7168, sb + BAR_M);
      TS(i + 1, 33);
      __syncwarp();
    }
  }
  if (spin >= SPIN_TOT) g_err = 1;
}

__global__ void __cluster_dims__(3, 1, 1) __launch_bounds__(384, 1)
k_chain(const __grid_constant__ CUtensorMap tmWq, const __grid_constant__ CUtensorMap tmWk,
        const __grid_constant__ CUtensorMap tmWv, const __grid_constant__ CUtensorMap tmWo) {
  using namespace C;
  extern __shared__ __align__(1024) uint8_t smem[];
  const uint32_t sb = smem_u32(smem);
  const int tid = threadIdx.x;
  const int wg = __shfl_sync(0xffffffffu, tid >> 7, 0);
  const int cta = uni(blockIdx.x), rank = uni(blockIdx.x % 3);

  asm volatile("griddepcontrol.launch_dependents;");
  if (tid == 0) {
    if ((sb & 0xFFFFFF) != SB0) g_err = 100;
    for (int p = 0; p < 5; p++) { mbar_init(sb + BAR_F + 8 * p, 1); mbar_init(sb + BAR_E + 8 * p, p == 2 ? 12 : 24); }
    mbar_init(sb + BAR_M, 1); mbar_init(sb + BAR_MOK, 24); mbar_init(sb + BAR_XM, 1); mbar_init(sb + BAR_XF, 2);
    mbar_init(sb + BAR_XT, 1); mbar_init(sb + BAR_MF, 8); mbar_init(sb + BAR_OG, 1); mbar_init(sb + BAR_W, 1);
    for (int p = 0; p < 5; p++) mbar_expect_tx(sb + BAR_F + 8 * p, 16384);
    for (int p = 0; p < 16; p++) sts32(sb + OFF_SAFE + 4 * p, 0);
    asm volatile("fence.mbarrier_init.release.cluster;" ::: "memory");
    fence_async();
    mbar_expect_tx(sb + BAR_W, 163840);
    const int head = cta / 3, col = head * DH + rank * 64;
    tma2d(sb + OFF_WQ, &tmWo, 576, col, sb + BAR_W);
    for (int i = 0; i < 9; i++) tma2d(sb + OFF_WQ + (i + 1) * 8192, &tmWo, (3 * rank + i / 3) * 64, head * DH + ((rank + i) % 3) * 64, sb + BAR_W);
    for (int i = 0; i < 5; i++) tma2d(sb + OFF_WK + i * 16384, &tmWv, col, i * 128, sb + BAR_W);
  }
  __syncthreads();
  asm volatile("barrier.cluster.arrive.release.aligned;" ::: "memory");
  asm volatile("barrier.cluster.wait.acquire.aligned;" ::: "memory");

  if (wg == 0) chain_a(sb, keep(tid), cta, rank);
  else if (wg == 1) chain_q(tmWq, tmWk, sb, keep(tid), cta, rank);
  else chain_v(sb, keep(tid), cta, rank);
  asm volatile("barrier.cluster.arrive.release.aligned;" ::: "memory");
  asm volatile("barrier.cluster.wait.acquire.aligned;" ::: "memory");
}

namespace W {
constexpr int NP = 25, NBC = 11, NW = NP + NBC;
constexpr int OFF_W = 0;
constexpr int OFF_R = 163840;
constexpr int OFF_WO = 0, OFF_WV = 81920;
constexpr int OFF_X = 161792;
constexpr int OFF_G = OFF_X + 40960;
constexpr int COL = 976;
constexpr int OFF_T = OFF_X + 24576;
constexpr int OFF_H = OFF_G + 20480;
constexpr int OFF_BAR = OFF_H + 8 * COL;
constexpr int OFF_SAFE = OFF_BAR + 192;
constexpr int SMEM = 232448;
constexpr uint32_t SB0 = 1024;
constexpr int BAR_F = OFF_BAR, BAR_E = OFF_BAR + 40, BAR_G = OFF_BAR + 80, BAR_H = OFF_BAR + 120, BAR_W = OFF_BAR + 160;
constexpr int NB_G0 = 1, NB_SG = 4, NB_B = 5, NB_AS = 6, NB_PK = 7, NB_PV = 8, NB_TD = 9;
}
#define ERP 1
#define WBAR_SYNC(id, n) bar_sync(id, n)
#define WBAR_ARRIVE(id, n) bar_arrive(id, n)

__device__ __forceinline__ uint64_t rdesc(int off, int k) { return mkdesc(W::SB0 + off + (k >> 2) * 4096 + (k & 3) * 32, 16, 1024); }
__device__ __forceinline__ void load_frags40(uint32_t (&wf)[40][4], uint32_t base, int tid) {
  const int i = (tid >> 3) & 3, r = tid & 7;
  const uint32_t a0 = base + (r + (i >> 1) * 8) * 128 + (((2 * ((tid >> 5) & 3) + (i & 1)) ^ r) << 4);
#pragma unroll
  for (int k = 0; k < 40; k++) ldsm4t(wf[k], a0 + k * 2048);
}
__device__ __forceinline__ void red_tile(const float (&d)[16], int seg, int col0, int tid) {
  float* p = g_x + (size_t)(seg * 32 + 2 * (tid & 3)) * DM + col0 + ((tid >> 5) & 3) * 16 + ((tid >> 2) & 7) * 2;
#pragma unroll
  for (int j = 0; j < 8; j++)
    asm volatile("red.relaxed.gpu.global.add.v2.f32 [%0],{%1,%2};" ::"l"(p + ((j >> 1) * 8 + (j & 1)) * DM), "f"(d[4 * (j >> 1) + (j & 1)]), "f"(d[4 * (j >> 1) + 2 + (j & 1)]) : "memory");
}

#define FOR_P_JOBS(k, l, s)                               \
  for (int j_ = 0; j_ < 2 * NSTEP; j_++) {                \
    const int k = j_ >> 1, l = j_ & 1, s = k - l * LAG;   \
    if (s < 0 || s >= NSEG) continue;
template <int WG>
__device__ __forceinline__ void work_p(const CUtensorMap& tmWo, uint32_t sb, int pc, int tid0) {
  using namespace W;
  asm volatile("setmaxnreg.inc.sync.aligned.u32 208;");
  int spin = 0;
  const int ks = pc / 5, col0 = (pc % 5) * 128 + WG * 64;
  const uint32_t wb = sb + OFF_W + WG * 81920;
  uint32_t wf[40][4];
#pragma unroll 1
  for (int hf = 0; hf < 2; hf++) {
    if ((tid0 & 127) == 0) {
      mbar_expect_tx(sb + BAR_W + 8 * WG, 81920);
      for (int i = 0; i < 10; i++) tma2d(wb + i * 8192, &tmWo, col0, (ks * 19 + 2 * i + hf) * 64, sb + BAR_W + 8 * WG);
    }
    __syncwarp();
    mwait(sb + BAR_W + 8 * WG, hf, spin);
    permute_cols(wb, tid0 & 127);
    if (hf == 1 && ks < 4) for (int it = 2304 + (tid0 & 127); it < 2560; it += 128) {
      const uint32_t a = wb + (it >> 2) * 128 + (((2 * (it & 3)) ^ ((it >> 2) & 6)) << 4);
      sts128(a, make_uint4(0, 0, 0, 0)); sts128(a + 16, make_uint4(0, 0, 0, 0));
    }
    fence_async();
    WBAR_SYNC(NB_G0 + WG, 128);
    if (hf == 0) {
      load_frags40(wf, wb, tid0);
      fence_async();
      WBAR_SYNC(NB_G0 + WG, 128);
    }
  }
  FOR_P_JOBS(k_, l, s)
    float d[16];
#pragma unroll
    for (int f = 0; f < 10; f++) {
      mwait(sb + BAR_F + 8 * (f % 5), f / 5, spin);
      if (f == 0 && WG == 0 && pc == WW) WTS(l, s, 1);
      wg_fence();
#pragma unroll
      for (int kk = 0; kk < 4; kk++) {
        wgmma_rs32(d, wf[4 * f + kk], rdesc(OFF_R, (f % 5) * 8 + kk), f | kk);
        wgmma_ts32(d, mkdesc(SB0 + OFF_W + WG * 81920 + (4 * f + kk) * 2048, 8192, 1024), rdesc(OFF_R, (f % 5) * 8 + 4 + kk), 1);
        if (kk == ERP && f > 0) {
          wg_commit();
          wg_wait<1>();
          if ((tid0 & 31) == 0) mbar_arrive(sb + BAR_E + 8 * ((f - 1) % 5));
          wg_fence();
        }
      }
      wg_commit();
    }
    wg_wait<0>();
    if ((tid0 & 31) == 0) mbar_arrive(sb + BAR_E + 32);
    if (WG == 0 && pc == WW) WTS(l, s, 2);
    red_tile(d, s, col0, tid0);
    if (WG == 0 && pc == WW) WTS(l, s, 13);
    WBAR_SYNC(NB_SG, 288);
  }
  if (spin >= SPIN_TOT) g_err = 11;
}
__device__ __forceinline__ void work_p_producer(uint32_t sb, int pc) {
  using namespace W;
  int spin = 0;
  const int ks = pc / 5;
  FOR_P_JOBS(k, l, s)
    if (l == 0 || k >= NSEG) { cwait(CN_O + k * 5 + ks, ks == 4 ? 20 : 19, spin); fence_async_all(); }
    if (pc == WW) WTS1(l, s, 0);
    const uint8_t* src = &g_o[k % ORING][l][ks * 19][0];
#pragma unroll
    for (int f = 0; f < 10; f++) {
      const int st = f < 5 ? f : f - 5;
      const uint32_t len = f == 9 && ks < 4 ? 4096 : 8192;
      mwait(sb + BAR_E + 8 * st, f < 5, spin);
      mbar_expect_tx(sb + BAR_F + 8 * st, len);
      bulk_g2s(sb + OFF_R + st * 8192, src + f * 8192, len, sb + BAR_F + 8 * st);
    }
  }
  if (spin >= SPIN_TOT) g_err = 12;
}
__device__ __forceinline__ float warp_sum(float x) {
  x = quad_sum(x);
  const float a = __shfl_xor_sync(0xffffffffu, x, 4), b = __shfl_xor_sync(0xffffffffu, x, 8), c = __shfl_xor_sync(0xffffffffu, x, 12);
  x = (x + a) + (b + c);
  return x + __shfl_xor_sync(0xffffffffu, x, 16);
}
__device__ __forceinline__ void work_ln(int kind, int r, int lane, bf16* out) {
  int spin = 0;
  const int l = kind & 1;
  const int rp = kind < 2 ? (r & 1) * 16 + (r >> 1) : r;
  const uint32_t sw = ((((lane >> 1) & 7) ^ (rp & 7)) << 4) + (lane & 1) * 8;
  uint8_t* dst = kind < 2 ? g_xnb[l] + (lane >> 4) * 4096 + rp * 128 + sw
               : kind == 2 ? g_xn[1] + (r >> 3) * 2048 + (lane >> 4) * 1024 + (r & 7) * 128 + sw
                           : reinterpret_cast<uint8_t*>(out) + r * 1280 + lane * 8;
  const int dm = kind == 3 ? 256 : 8192;
#pragma unroll 1
  for (int s = 0; s < NSEG; s++) {
    const float* xr = g_x + (size_t)(s * 32 + r) * DM;
    if (kind == 0 && lane < 20 && s + 3 < NSEG) prefetch_l2(xr + 96 * DM + lane * 32);
    if (lane == 0) cwait((kind < 2 ? CN_P : CN_W) + l * 64 + s, kind < 2 ? W::NP : 10, spin);
    __syncwarp();
    if (r == 0 && lane == 0) WTS1(l, s, kind < 2 ? 3 : 11);
    float4 v[5];
#pragma unroll
    for (int m = 0; m < 5; m++) v[m] = ld_relaxed4f(xr + m * 128 + lane * 4);
    if (kind < 3) {
      float t = 0.f;
#pragma unroll
      for (int m = 0; m < 5; m++) t += (v[m].x + v[m].y) + (v[m].z + v[m].w);
      const float mean = warp_sum(t) * (1.f / DM);
      float q0 = 0.f, q1 = 0.f;
#pragma unroll
      for (int m = 0; m < 5; m++) {
        v[m].x -= mean; v[m].y -= mean; v[m].z -= mean; v[m].w -= mean;
        q0 += v[m].x * v[m].x + v[m].y * v[m].y; q1 += v[m].z * v[m].z + v[m].w * v[m].w;
      }
      const float rs = rsqrtf(warp_sum(q0 + q1) * (1.f / DM) + 1e-5f);
#pragma unroll
      for (int m = 0; m < 5; m++) { v[m].x *= rs; v[m].y *= rs; v[m].z *= rs; v[m].w *= rs; }
    }
#pragma unroll
    for (int m = 0; m < 5; m++) *reinterpret_cast<uint2*>(dst + (size_t)s * 40960 + m * dm) = make_uint2(pack_bf16(v[m].x, v[m].y), pack_bf16(v[m].z, v[m].w));
    __syncwarp();
    if (r == 0 && lane == 0) WTS1(l, s, kind < 2 ? 4 : 12);
    if (lane == 0 && kind < 3) csignal_t(kind < 2 ? CN_L + l * 64 + s : CN_X + s, kind);
  }
  if (spin >= SPIN_TOT) g_err = 13;
}

__device__ __forceinline__ void stage_qkv(const bf16* wqkv, uint32_t base, int T, int bc, int tid) {
  const int q = tid & 15;
  const bool ok = q < 15 && bc * 60 + 4 * q < DM;
  const bf16* src = wqkv + T * DM + bc * 60 + 4 * q;
#pragma unroll 1
  for (int k0 = tid >> 4; k0 < 640; k0 += 80) {
    uint2 v[10];
#pragma unroll
    for (int u = 0; u < 10; u++) v[u] = ok ? *reinterpret_cast<const uint2*>(src + (size_t)(k0 + 8 * u) * 1920) : make_uint2(0, 0);
#pragma unroll
    for (int u = 0; u < 10; u++) sts64(base + (k0 + 8 * u) * 128 + (((q >> 1) ^ (k0 & 7)) << 4) + (q & 1) * 8, v[u].x, v[u].y);
  }
}
__device__ __forceinline__ void tiles_done(uint32_t sb, int l, int wg, const uint32_t (&hist)[4], int tid) {
  using namespace W;
  const int m = (tid >> 3) & 3;
  WBAR_SYNC(NB_TD, 288);
  stsm4(sb + OFF_H + min(((tid >> 5) & 3) * 16 + (m & 1) * 8 + (tid & 7), 60) * 16 + (l * 4 + 2 - 2 * wg + (m >> 1)) * COL, hist[0], hist[1], hist[2], hist[3]);
  fence_async();
  if ((tid & 31) < 2) mbar_arrive(sb + BAR_E + 24 + 8 * (tid & 1));
}
__device__ __forceinline__ void attend(uint32_t sb, int bc, int l, int s, int p, const uint32_t (&hist)[4], int tid) {
  using namespace W;
  const int r = tid & 7, m = (tid >> 3) & 3, hh = (tid >> 5) & 3, g = (tid >> 2) & 7, t = tid & 3;
  const int f2 = r < 4 ? 20 * hh + 16 + r : 60;
  const uint32_t tb = sb + OFF_T + 2 * p * COL, hb = sb + OFF_H + (l * 4 + p) * COL;
  const uint32_t ko = (m < 2 ? 20 * hh + 8 * m + r : f2) * 16, vo = (m < 2 ? 20 * hh + 4 * (r >> 1) + 2 * m + (r & 1) : f2) * 16;
  const float scl = 0.22360679774997896f * 1.4426950408889634f;
  float sc[3][4];
  {
    uint32_t q[4], q8a, q8b, k[3][4];
    ldsm4t(q, tb + (m & 1) * COL + (20 * hh + (m >> 1) * 8 + r) * 16);
    ldsm2t(q8a, q8b, tb + (m & 1) * COL + f2 * 16);
    ldsm4t(k[0], hb + ko); ldsm4t(k[1], tb + 4 * COL + ko); ldsm4t(k[2], tb + 5 * COL + ko);
#pragma unroll
    for (int c = 0; c < 3; c++) { sc[c][0] = sc[c][1] = sc[c][2] = sc[c][3] = 0.f; mma16816(sc[c], q[0], q[1], q[2], q[3], k[c][0], k[c][1]); }
#pragma unroll
    for (int c = 0; c < 3; c++) mma1688(sc[c], q8a, q8b, k[c][2]);
  }
  uint32_t v[3][4];
  ldsm4(v[0], hb + 2 * COL + vo); ldsm4(v[1], tb + 8 * COL + vo); ldsm4(v[2], tb + 9 * COL + vo);
  tiles_done(sb, l, p, hist, tid);
  const bool lo0 = 2 * t > g, lo1 = 2 * t + 1 > g;
  uint32_t pw[2];
  float inv[2];
#pragma unroll
  for (int h = 0; h < 2; h++) {
    float y0 = lo0 ? sc[h][2 * h] : sc[h + 1][2 * h], y1 = lo1 ? sc[h][2 * h + 1] : sc[h + 1][2 * h + 1];
    if (h == 0 && s == 0) { y0 = lo0 ? -INFINITY : y0; y1 = lo1 ? -INFINITY : y1; }
    const float mx = quad_max(fmaxf(y0, y1)) * -scl;
    pw[h] = pack_bf16(ex2(fmaf(y0, scl, mx)), ex2(fmaf(y1, scl, mx)));
    inv[h] = bf_lo(pw[h]) + bf_hi(pw[h]);
  }
  const uint32_t ml = (lo0 ? 0xFFFFu : 0u) | (lo1 ? 0xFFFF0000u : 0u);
  float o[3][4];
#pragma unroll
  for (int j = 0; j < 3; j++) { o[j][0] = o[j][1] = o[j][2] = o[j][3] = 0.f; mma16816(o[j], pw[0] & ml, 0u, pw[0] & ~ml, pw[1] & ml, v[0][j], v[1][j]); }
#pragma unroll
  for (int j = 0; j < 3; j++) mma1688(o[j], 0u, pw[1] & ~ml, v[2][j]);
  inv[0] = rcp(quad_sum(inv[0])); inv[1] = rcp(quad_sum(inv[1]));
  const uint32_t ca = (bc * 3 + hh) * 20 + 4 * t, cb = ca + 16 - 2 * t, row = 2 * g + p;
  uint8_t* img = g_ob[l] + (size_t)s * 40960 + row * 128;
  const uint32_t oa = (ca >> 6) * 4096 + (((ca >> 3) ^ row) & 7) * 16 + (ca & 4) * 2, ob = (cb >> 6) * 4096 + (((cb >> 3) ^ row) & 7) * 16 + (cb & 6) * 2;
#pragma unroll
  for (int h = 0; h < 2; h++) {
    *reinterpret_cast<uint2*>(img + oa + h * 2048) = make_uint2(pack_bf16(o[0][2 * h] * inv[h], o[0][2 * h + 1] * inv[h]), pack_bf16(o[1][2 * h] * inv[h], o[1][2 * h + 1] * inv[h]));
    if (t < 2) *reinterpret_cast<uint32_t*>(img + ob + h * 2048) = pack_bf16(o[2][2 * h] * inv[h], o[2][2 * h + 1] * inv[h]);
  }
}
template <int WG>
__device__ __forceinline__ void work_b(const bf16* wqkv, uint32_t sb, int bc, int tid0) {
  using namespace W;
  if (WG == 0) asm volatile("setmaxnreg.inc.sync.aligned.u32 224;");
  else asm volatile("setmaxnreg.inc.sync.aligned.u32 208;");
  int spin = 0;
  const uint32_t wb = sb + (WG ? OFF_WO : OFF_WV);
  uint32_t wf[40][4], wv[4];
  stage_qkv(wqkv, wb, WG, bc, tid0 & 127);
  WBAR_SYNC(NB_G0 + WG, 128);
  load_frags40(wf, wb, tid0);
  fence_async();
  if (WG == 1) WBAR_ARRIVE(NB_PK, 256);
  else {
    WBAR_SYNC(NB_G0, 128);
    stage_qkv(wqkv, wb, 2, bc, tid0);
    WBAR_SYNC(NB_G0, 128);
    const int i = (tid0 >> 3) & 3, r = tid0 & 7;
    ldsm4t(wv, wb + 39 * 2048 + (r + (i >> 1) * 8) * 128 + (((2 * (tid0 >> 5) + (i & 1)) ^ r) << 4));
    fence_async();
    WBAR_SYNC(NB_PV, 160);
  }
  uint32_t ph = 0;
  FOR_P_JOBS(k_, l, s)
    uint32_t hist[4];
    {
      float d[16], e[16];
#pragma unroll
      for (int f = 0; f < 5; f++) {
        mwait(sb + BAR_F + 8 * f, ph, spin);
        if (f == 0 && bc == 0) WTS(l, s, WG ? 15 : 6);
        wg_fence();
#pragma unroll
        for (int k = 8 * f; k < 8 * f + 8; k++) {
          wgmma_rs32(d, wf[k], rdesc(OFF_X, k), k);
          if (WG == 0) {
            if (k < 39) wgmma_ts32(e, mkdesc(SB0 + OFF_WV + k * 2048, 8192, 1024), rdesc(OFF_X, k), k);
            else wgmma_rs32(e, wv, rdesc(OFF_X, k), 1);
          }
        }
        wg_commit();
        if (f > 0 && f < 4) {
          wg_wait<1>();
          if ((tid0 & 31) == 0) mbar_arrive(sb + BAR_E + 8 * (f - 1));
        }
      }
      wg_wait<0>();
      if (bc == 0) WTS(l, s, 16 + WG);
      WBAR_SYNC(NB_B, 256);
      const int tid = fresh(tid0), m = (tid >> 3) & 3;
      const uint32_t a = sb + OFF_T + min(((tid >> 5) & 3) * 16 + (m & 1) * 8 + (tid & 7), 60) * 16 + (m >> 1) * COL;
      const float (&x)[16] = WG ? d : e;
#pragma unroll
      for (int p = 0; p < 2; p++) {
        hist[2 * p] = pack_bf16(x[8 * p + 4], x[8 * p + 5]); hist[2 * p + 1] = pack_bf16(x[8 * p + 6], x[8 * p + 7]);
        stsm4(a + (8 - 4 * WG + 2 * p) * COL, pack_bf16(x[8 * p], x[8 * p + 1]), pack_bf16(x[8 * p + 2], x[8 * p + 3]), hist[2 * p], hist[2 * p + 1]);
        if (WG == 0)
          stsm4(a + 2 * p * COL, pack_bf16(d[8 * p], d[8 * p + 1]), pack_bf16(d[8 * p + 2], d[8 * p + 3]), pack_bf16(d[8 * p + 4], d[8 * p + 5]), pack_bf16(d[8 * p + 6], d[8 * p + 7]));
      }
    }
    WBAR_SYNC(NB_B, 256);
    if (bc == 0 && WG == 0) WTS(l, s, 7);
    {
      const int tid = fresh(tid0), hh = uni((tid >> 5) & 3);
      if (hh < 3 && bc * 3 + hh < NH) attend(sb, bc, l, s, WG, hist, tid);
      else tiles_done(sb, l, WG, hist, tid);
    }
    if (bc == 0 && WG == 0) WTS(l, s, 8);
    WBAR_ARRIVE(NB_AS, 288);
    ph ^= 1;
  }
  if (spin >= SPIN_TOT) g_err = 14;
}
__device__ __forceinline__ void work_wo(const CUtensorMap& tmBo, uint32_t sb, int bc, int tid0) {
  using namespace W;
  int spin = 0;
  WBAR_SYNC(NB_PK, 256);
  if (bc == 10) return;
  if ((tid0 & 127) == 0) {
    mbar_expect_tx(sb + BAR_W, 81920);
    for (int i = 0; i < 10; i++) tma2d(sb + OFF_WO + i * 8192, &tmBo, bc * 64, i * 64, sb + BAR_W);
  }
  __syncwarp();
  mwait(sb + BAR_W, 0, spin);
  permute_cols(sb + OFF_WO, tid0 & 127);
  fence_async();
  WBAR_SYNC(NB_G0 + 2, 128);
  FOR_P_JOBS(k_, l, s)
    float d[16];
#pragma unroll
    for (int f = 0; f < 10; f++) {
      mwait(sb + BAR_G + 8 * (f % 5), f / 5, spin);
      if ((f == 0 || f == 9) && bc == 0) WTS(l, s, f ? 21 : 20);
      wg_fence();
#pragma unroll
      for (int kk = 0; kk < 4; kk++) wgmma_ts32(d, mkdesc(SB0 + OFF_WO + (4 * f + kk) * 2048, 8192, 1024), rdesc(OFF_G, (f % 5) * 4 + kk), f | kk);
      wg_commit();
      if (f % 5) {
        wg_wait<1>();
        if ((tid0 & 31) == 0) mbar_arrive(sb + BAR_H + 8 * ((f - 1) % 5));
      }
      if (f == 4 || f == 9) {
        wg_wait<0>();
        if ((tid0 & 31) == 0) mbar_arrive(sb + BAR_H + 32);
      }
    }
    if (bc == 0) WTS(l, s, 10);
    red_tile(d, s, bc * 64, tid0);
    WBAR_SYNC(NB_SG, 160);
  }
  if (spin >= SPIN_TOT) g_err = 17;
}
template <bool WO>
__device__ __forceinline__ void work_b_producer(uint32_t sb, int bc) {
  using namespace W;
  int spin = 0;
  uint32_t ph = 1;
  FOR_P_JOBS(k_, l, s)
    const uint8_t* src = (WO ? g_ob[l] : g_xnb[l]) + (size_t)s * 40960;
    cwait((WO ? CN_A : CN_L) + l * 64 + s, WO ? NBC : 32, spin);
    fence_async_all();
    if (bc == 0) WTS1(l, s, WO ? 9 : 5);
#pragma unroll
    for (int f = 0; f < (WO ? 10 : 5); f++) {
      const uint32_t len = WO ? 4096 : 8192, fb = sb + (WO ? BAR_G : BAR_F) + 8 * (f % 5);
      mwait(sb + (WO ? BAR_H : BAR_E) + 8 * (f % 5), WO ? f < 5 : ph, spin);
      mbar_expect_tx(fb, len);
      bulk_g2s(sb + (WO ? OFF_G : OFF_X) + (f % 5) * len, src + f * len, len, fb);
    }
    ph ^= 1;
  }
  if (spin >= SPIN_TOT) g_err = 15;
}

__global__ void __launch_bounds__(512, 1)
k_work(const __grid_constant__ CUtensorMap tmWo, const __grid_constant__ CUtensorMap tmBo, const bf16* __restrict__ wqkv, bf16* __restrict__ out) {
  using namespace W;
  extern __shared__ __align__(1024) uint8_t smem[];
  const uint32_t sb = smem_u32(smem);
  const int tid = threadIdx.x, w = blockIdx.x;
  const int wg = __shfl_sync(0xffffffffu, tid >> 7, 0);
  if (tid == 0) {
    if (sb != SB0) g_err = 101;
    for (int i = 0; i < 5; i++) { mbar_init(sb + BAR_F + 8 * i, 1); mbar_init(sb + BAR_E + 8 * i, 8); mbar_init(sb + BAR_G + 8 * i, 1); mbar_init(sb + BAR_H + 8 * i, 4); }
    mbar_init(sb + BAR_W, 1); mbar_init(sb + BAR_W + 8, 1);
    for (int p = 0; p < 16; p++) sts32(sb + OFF_SAFE + 4 * p, 0);
    asm volatile("fence.mbarrier_init.release.cluster;" ::: "memory");
  }
  if (tid < 8 * COL / 16) sts128(sb + OFF_H + tid * 16, make_uint4(0, 0, 0, 0));
  fence_async();
  __syncthreads();

  if (w < NP) {
    if (wg == 0) work_p<0>(tmWo, sb, w, keep(tid));
    else if (wg == 1) work_p<1>(tmWo, sb, w, keep(tid));
    else {
      asm volatile("setmaxnreg.dec.sync.aligned.u32 48;");
      const int aw = (tid >> 5) - 8;
      if (aw == 0) {
        if (tid == 256) work_p_producer(sb, w);
      } else if (aw == 1) {
        FOR_P_JOBS(k_, l, s)
          WBAR_SYNC(NB_SG, 288);
          if (tid == 288) csignal_t(CN_P + l * 64 + s, 3 + l);
          __syncwarp();
        }
      } else {
        const int id = (aw - 2) * NP + w;
        if (id < 128) work_ln(id & 3, id >> 2, tid & 31, out);
      }
    }
  } else {
    const int bc = w - NP;
    if (wg == 0) work_b<0>(wqkv, sb, bc, keep(tid));
    else if (wg == 1) work_b<1>(wqkv, sb, bc, keep(tid));
    else if (wg == 2) {
      asm volatile("setmaxnreg.dec.sync.aligned.u32 56;");
      work_wo(tmBo, sb, bc, keep(tid));
    } else {
      asm volatile("setmaxnreg.dec.sync.aligned.u32 24;");
      if (tid < 416) {
        WBAR_SYNC(NB_PV, 160);
        if (tid == 384) work_b_producer<false>(sb, bc);
      } else if (tid < 448) {
        if (tid == 416 && bc < 10) work_b_producer<true>(sb, bc);
      } else if (tid < 480 || bc < 10) {
        FOR_P_JOBS(k_, l, s)
          if (tid < 480) { WBAR_SYNC(NB_TD, 288); WBAR_SYNC(NB_AS, 288); } else WBAR_SYNC(NB_SG, 160);
          if ((tid & 31) == 0) csignal_t((tid < 480 ? CN_A : CN_W) + l * 64 + s, tid < 480 ? 5 : 6);
          __syncwarp();
        }
      }
    }
  }
  __syncthreads();
  asm volatile("griddepcontrol.wait;" ::: "memory");
}

typedef CUresult (*EncodeFn)(CUtensorMap*, CUtensorMapDataType, cuuint32_t, void*, const cuuint64_t*, const cuuint64_t*,
                             const cuuint32_t*, const cuuint32_t*, CUtensorMapInterleave, CUtensorMapSwizzle,
                             CUtensorMapL2promotion, CUtensorMapFloatOOBfill);

static void make_map(EncodeFn enc, CUtensorMap* tm, const void* ptr, uint64_t cols, uint64_t rows, uint32_t boxc, uint32_t boxr) {
  cuuint64_t dims[2] = {cols, rows};
  cuuint64_t strides[1] = {cols * 2};
  cuuint32_t box[2] = {boxc, boxr};
  cuuint32_t es[2] = {1, 1};
  enc(tm, CU_TENSOR_MAP_DATA_TYPE_BFLOAT16, 2, const_cast<void*>(ptr), dims, strides, box, es, CU_TENSOR_MAP_INTERLEAVE_NONE,
      CU_TENSOR_MAP_SWIZZLE_128B, CU_TENSOR_MAP_L2_PROMOTION_L2_256B, CU_TENSOR_MAP_FLOAT_OOB_FILL_NONE);
}

extern "C" void kernel_launch(void* const* d_in, const int* in_sizes, int n_in, void* d_out, int out_size) {
  const bf16* x0 = (const bf16*)d_in[0];
  const bf16* mem0 = (const bf16*)d_in[1];
  const bf16* Wq = (const bf16*)d_in[2];
  const bf16* Wk = (const bf16*)d_in[3];
  const bf16* Wv = (const bf16*)d_in[4];
  const bf16* Wo = (const bf16*)d_in[5];
  const bf16* Bqkv = (const bf16*)d_in[8];
  const bf16* Bwo = (const bf16*)d_in[9];
  bf16* out = (bf16*)d_out;

  static EncodeFn enc = nullptr;
  if (!enc) {
    void* fn = nullptr;
    cudaDriverEntryPointQueryResult qr;
    cudaGetDriverEntryPoint("cuTensorMapEncodeTiled", &fn, cudaEnableDefault, &qr);
    enc = (EncodeFn)fn;
    cudaFuncSetAttribute(k_chain, cudaFuncAttributeMaxDynamicSharedMemorySize, C::SMEM);
    cudaFuncSetAttribute(k_work, cudaFuncAttributeMaxDynamicSharedMemorySize, W::SMEM);
  }
  CUtensorMap tmWq, tmWk, tmWv, tmWo, tmBo;
  make_map(enc, &tmWq, Wq, NH * DH, DM, 64, 128);
  make_map(enc, &tmWk, Wk, NH * DH, DM, 64, 128);
  make_map(enc, &tmWv, Wv, NH * DH, DM, 64, 128);
  make_map(enc, &tmWo, Wo, DM, NH * DH, 64, 64);
  make_map(enc, &tmBo, Bwo, DM, DM, 64, 64);

  cudaStream_t st = cudaStreamPerThread;
  k_pre<<<256, 256, 0, st>>>(x0, mem0);
  cudaLaunchAttribute at[1];
  at[0].id = cudaLaunchAttributeProgrammaticStreamSerialization; at[0].val.programmaticStreamSerializationAllowed = 1;
  {
    cudaLaunchConfig_t cfg = {};
    cfg.gridDim = dim3(96); cfg.blockDim = dim3(384); cfg.dynamicSmemBytes = C::SMEM; cfg.stream = st;
    cfg.attrs = at; cfg.numAttrs = 0;
    cudaLaunchKernelEx(&cfg, k_chain, tmWq, tmWk, tmWv, tmWo);
  }
  cudaLaunchConfig_t cfg = {};
  cfg.gridDim = dim3(W::NW); cfg.blockDim = dim3(512); cfg.dynamicSmemBytes = W::SMEM; cfg.stream = st;
  cfg.attrs = at; cfg.numAttrs = NOWORK == 2 ? 0 : 1;
  cudaLaunchKernelEx(&cfg, k_work, tmWo, tmBo, Bqkv, out);
}
```

```cpp
#include <cuda_runtime.h>
#include <cuda_bf16.h>
#include <cuda.h>
#include <stdint.h>

typedef __nv_bfloat16 bf16;

constexpr int SEQ = 2048, DM = 640, NH = 32, DH = 192, NSEG = 64;
#define LAG 5
constexpr int NSTEP = NSEG + LAG;
constexpr uint32_t SENT = 0xFFFFFFFFu;

constexpr int MAIL9 = 288 * 2048, MAIL_BYTES = MAIL9 + 64 * 3072;
__device__ __align__(1024) uint8_t g_xn[2][NSEG * 40960];
__device__ __align__(1024) uint8_t g_xnb[NSTEP][81920];
__device__ __align__(1024) uint8_t g_ob[2][NSEG * 40960];
#define ORING 8
static_assert(ORING > LAG, "a slot is free again LAG + 1 steps later");
__device__ __align__(1024) uint8_t g_o[ORING][96][8192];
__device__ __align__(1024) float g_x[SEQ * DM];
constexpr int EX_MAIL = 0;
constexpr int EX_M = 2 << 20;
constexpr int EX_FLAG = EX_M + NSTEP * 20480;
static_assert(EX_FLAG + NSTEP * 3072 <= (4 << 20), "");
__device__ __align__(1024) uint8_t g_ex[8 << 20];
__host__ __device__ __forceinline__ uint8_t* ex_window(uint8_t* p) { return reinterpret_cast<uint8_t*>((reinterpret_cast<uint64_t>(p) + (4 << 20) - 1) & ~(uint64_t)((4 << 20) - 1)); }
enum { CN_P = 0, CN_L = 128, CN_A = 256, CN_W = 384, CN_X = 512, CN_O = 576, CN_NUM = CN_O + 5 * NSTEP };
__device__ __align__(128) uint32_t g_cnt[CN_NUM][32];
__device__ int g_err;
#define TS(jj, i)
#define TS1(jj, i)
#define PTS(i)
#define TSB(jj, i)
#define TSV(jj, i, v)
#define TS_FLUSH(jj)
#define WTS(b, k)
#define WTS1(b, k)
#define WW -1

__device__ __forceinline__ uint32_t smem_u32(const void* p) { return (uint32_t)__cvta_generic_to_shared(p); }
__device__ __forceinline__ uint32_t clk32() { uint32_t t; asm volatile("mov.u32 %0, %%clock;" : "=r"(t)::"memory"); return t; }
__device__ __forceinline__ uint32_t mapa(uint32_t a, uint32_t r) { uint32_t o; asm("mapa.shared::cluster.u32 %0,%1,%2;" : "=r"(o) : "r"(a), "r"(r)); return o; }
__device__ __forceinline__ void mbar_init(uint32_t bar, uint32_t cnt) { asm volatile("mbarrier.init.shared::cta.b64 [%0],%1;" ::"r"(bar), "r"(cnt) : "memory"); }
__device__ __forceinline__ void mbar_expect_tx(uint32_t bar, uint32_t bytes) { asm volatile("mbarrier.arrive.expect_tx.shared::cta.b64 _,[%0],%1;" ::"r"(bar), "r"(bytes) : "memory"); }
__device__ __forceinline__ void mbar_arrive(uint32_t bar) { asm volatile("mbarrier.arrive.shared::cta.b64 _,[%0];" ::"r"(bar) : "memory"); }
__device__ __forceinline__ void mbar_arrive_cluster(uint32_t bar) { asm volatile("mbarrier.arrive.shared::cluster.b64 _,[%0];" ::"r"(bar) : "memory"); }
__device__ __forceinline__ bool mbar_try(uint32_t bar, uint32_t ph) {
  uint32_t ok;
  asm volatile("{.reg .pred p; mbarrier.try_wait.parity.shared::cta.b64 p,[%1],%2; selp.u32 %0,1,0,p;}" : "=r"(ok) : "r"(bar), "r"(ph) : "memory");
  return ok;
}
__device__ __forceinline__ bool mbar_test(uint32_t bar, uint32_t ph) {
  uint32_t ok;
  asm volatile("{.reg .pred p; mbarrier.test_wait.parity.shared::cta.b64 p,[%1],%2; selp.u32 %0,1,0,p;}" : "=r"(ok) : "r"(bar), "r"(ph) : "memory");
  return ok;
}
__device__ __forceinline__ int fresh(int x) { asm volatile("" : "+r"(x)); return x; }
#define PHASE_IDS const int tid = fresh(tid0), lane = tid & 31, w = tid >> 5, g = lane >> 2, t = lane & 3; (void)w; (void)g; (void)t
__device__ __forceinline__ void bar_sync(int id, int n) { asm volatile("bar.sync %0,%1;" ::"r"(id), "r"(n) : "memory"); }
__device__ __forceinline__ void bar_arrive(int id, int n) { asm volatile("bar.arrive %0,%1;" ::"r"(id), "r"(n) : "memory"); }
__device__ __forceinline__ bool bar_red_or(int id, int n, bool v) {
  uint32_t r;
  asm volatile("{\n .reg .pred p, q;\n setp.ne.u32 q, %3, 0;\n barrier.cta.red.or.pred p, %1, %2, q;\n selp.u32 %0, 1, 0, p;\n}" : "=r"(r) : "r"(id), "r"(n), "r"((uint32_t)v) : "memory");
  return r != 0;
}
__device__ __forceinline__ void fence_async() { asm volatile("fence.proxy.async.shared::cta;" ::: "memory"); }
__device__ __forceinline__ void bulk_g2s(uint32_t dst, const void* src, uint32_t bytes, uint32_t bar) {
  asm volatile("cp.async.bulk.shared::cluster.global.mbarrier::complete_tx::bytes [%0],[%1],%2,[%3];" ::"r"(dst), "l"(src), "r"(bytes), "r"(bar) : "memory");
}
__device__ __forceinline__ void bulk_g2s_mc(uint32_t dst, const void* src, uint32_t bytes, uint32_t bar) {
  asm volatile("cp.async.bulk.shared::cluster.global.mbarrier::complete_tx::bytes.multicast::cluster [%0],[%1],%2,[%3],%4;"
               ::"r"(dst), "l"(src), "r"(bytes), "r"(bar), "h"((uint16_t)7) : "memory");
}
__device__ __forceinline__ void bulk_s2g(void* dst, uint32_t src, uint32_t bytes) {
  asm volatile("cp.async.bulk.global.shared::cta.bulk_group [%0],[%1],%2;" ::"l"(dst), "r"(src), "r"(bytes) : "memory");
}
__device__ __forceinline__ void bulk_s2c(uint32_t dst, uint32_t src, uint32_t bytes, uint32_t bar) {
  asm volatile("cp.async.bulk.shared::cluster.shared::cta.mbarrier::complete_tx::bytes [%0],[%1],%2,[%3];" ::"r"(dst), "r"(src), "r"(bytes), "r"(bar) : "memory");
}
__device__ __forceinline__ void tma2d(uint32_t dst, const CUtensorMap* tm, int c0, int c1, uint32_t bar) {
  asm volatile("cp.async.bulk.tensor.2d.shared::cluster.global.mbarrier::complete_tx::bytes [%0],[%1,{%3,%4}],[%2];"
               ::"r"(dst), "l"(tm), "r"(bar), "r"(c0), "r"(c1) : "memory");
}
__device__ __forceinline__ void tma2d_prefetch(const CUtensorMap* tm, int c0, int c1) {
  asm volatile("cp.async.bulk.prefetch.tensor.2d.L2.global.tile [%0,{%1,%2}];" ::"l"(tm), "r"(c0), "r"(c1) : "memory");
}
__device__ __forceinline__ uint32_t pack_bf16(float lo, float hi) {
  uint32_t r; asm("cvt.rn.bf16x2.f32 %0,%1,%2;" : "=r"(r) : "f"(hi), "f"(lo)); return r;
}
__device__ __forceinline__ float bf_lo(uint32_t x) { return __uint_as_float(x << 16); }
__device__ __forceinline__ float bf_hi(uint32_t x) { return __uint_as_float(x & 0xFFFF0000u); }
__device__ __forceinline__ float ex2(float x) { float y; asm("ex2.approx.ftz.f32 %0,%1;" : "=f"(y) : "f"(x)); return y; }
__device__ __forceinline__ void ldsm4(uint32_t (&r)[4], uint32_t a) {
  asm volatile("ldmatrix.sync.aligned.m8n8.x4.shared.b16 {%0,%1,%2,%3},[%4];" : "=r"(r[0]), "=r"(r[1]), "=r"(r[2]), "=r"(r[3]) : "r"(a) : "memory");
}
__device__ __forceinline__ void ldsm4t(uint32_t (&r)[4], uint32_t a) {
  asm volatile("ldmatrix.sync.aligned.m8n8.x4.trans.shared.b16 {%0,%1,%2,%3},[%4];" : "=r"(r[0]), "=r"(r[1]), "=r"(r[2]), "=r"(r[3]) : "r"(a) : "memory");
}
__device__ __forceinline__ void ldsm2(uint32_t& r0, uint32_t& r1, uint32_t a) {
  asm volatile("ldmatrix.sync.aligned.m8n8.x2.shared.b16 {%0,%1},[%2];" : "=r"(r0), "=r"(r1) : "r"(a) : "memory");
}
__device__ __forceinline__ void ldsm2t(uint32_t& r0, uint32_t& r1, uint32_t a) {
  asm volatile("ldmatrix.sync.aligned.m8n8.x2.trans.shared.b16 {%0,%1},[%2];" : "=r"(r0), "=r"(r1) : "r"(a) : "memory");
}
__device__ __forceinline__ void ldsm1(uint32_t& r0, uint32_t a) {
  asm volatile("ldmatrix.sync.aligned.m8n8.x1.shared.b16 {%0},[%1];" : "=r"(r0) : "r"(a) : "memory");
}
__device__ __forceinline__ void mma16816(float (&d)[4], uint32_t a0, uint32_t a1, uint32_t a2, uint32_t a3, uint32_t b0, uint32_t b1) {
  asm volatile("mma.sync.aligned.m16n8k16.row.col.f32.bf16.bf16.f32 {%0,%1,%2,%3},{%4,%5,%6,%7},{%8,%9},{%0,%1,%2,%3};"
               : "+f"(d[0]), "+f"(d[1]), "+f"(d[2]), "+f"(d[3]) : "r"(a0), "r"(a1), "r"(a2), "r"(a3), "r"(b0), "r"(b1));
}
__device__ __forceinline__ void mma1688(float (&d)[4], uint32_t a0, uint32_t a1, uint32_t b0) {
  asm volatile("mma.sync.aligned.m16n8k8.row.col.f32.bf16.bf16.f32 {%0,%1,%2,%3},{%4,%5},{%6},{%0,%1,%2,%3};"
               : "+f"(d[0]), "+f"(d[1]), "+f"(d[2]), "+f"(d[3]) : "r"(a0), "r"(a1), "r"(b0));
}
__device__ __forceinline__ void sts32(uint32_t a, uint32_t v) { asm volatile("st.shared.b32 [%0],%1;" ::"r"(a), "r"(v) : "memory"); }
__device__ __forceinline__ void sts64f(uint32_t a, float x, float y) { asm volatile("st.shared.v2.f32 [%0],{%1,%2};" ::"r"(a), "f"(x), "f"(y) : "memory"); }
__device__ __forceinline__ void sts128(uint32_t a, uint4 v) { asm volatile("st.shared.v4.b32 [%0],{%1,%2,%3,%4};" ::"r"(a), "r"(v.x), "r"(v.y), "r"(v.z), "r"(v.w) : "memory"); }
__device__ __forceinline__ float lds32f(uint32_t a) { float v; asm volatile("ld.shared.f32 %0,[%1];" : "=f"(v) : "r"(a) : "memory"); return v; }
__device__ __forceinline__ float2 lds64f(uint32_t a) { float2 v; asm volatile("ld.shared.v2.f32 {%0,%1},[%2];" : "=f"(v.x), "=f"(v.y) : "r"(a) : "memory"); return v; }
__device__ __forceinline__ uint4 lds128(uint32_t a) { uint4 v; asm volatile("ld.shared.v4.b32 {%0,%1,%2,%3},[%4];" : "=r"(v.x), "=r"(v.y), "=r"(v.z), "=r"(v.w) : "r"(a) : "memory"); return v; }
__device__ __forceinline__ float4 lds128f(uint32_t a) { float4 v; asm volatile("ld.shared.v4.f32 {%0,%1,%2,%3},[%4];" : "=f"(v.x), "=f"(v.y), "=f"(v.z), "=f"(v.w) : "r"(a) : "memory"); return v; }
__device__ __forceinline__ void st_async2(uint32_t a, float x, float y, uint32_t bar) {
  asm volatile("st.async.weak.shared::cluster.mbarrier::complete_tx::bytes.v2.f32 [%0],{%1,%2},[%3];" ::"r"(a), "f"(x), "f"(y), "r"(bar) : "memory");
}
__device__ __forceinline__ void st_async4(uint32_t a, const float (&v)[4], uint32_t bar) {
  asm volatile("st.async.weak.shared::cluster.mbarrier::complete_tx::bytes.v4.f32 [%0],{%1,%2,%3,%4},[%5];" ::"r"(a), "f"(v[0]), "f"(v[1]), "f"(v[2]), "f"(v[3]), "r"(bar) : "memory");
}
__device__ __forceinline__ void st_async4v(uint32_t a, float x, float y, float z, float w, uint32_t bar) {
  asm volatile("st.async.weak.shared::cluster.mbarrier::complete_tx::bytes.v4.f32 [%0],{%1,%2,%3,%4},[%5];" ::"r"(a), "f"(x), "f"(y), "f"(z), "f"(w), "r"(bar) : "memory");
}
__device__ __forceinline__ void st_async4u(uint32_t a, const uint4& v, uint32_t bar) {
  asm volatile("st.async.weak.shared::cluster.mbarrier::complete_tx::bytes.v4.b32 [%0],{%1,%2,%3,%4},[%5];" ::"r"(a), "r"(v.x), "r"(v.y), "r"(v.z), "r"(v.w), "r"(bar) : "memory");
}
__device__ __forceinline__ uint4 ld_relaxed4(const void* p) {
  uint4 v; asm volatile("ld.relaxed.gpu.global.v4.u32 {%0,%1,%2,%3},[%4];" : "=r"(v.x), "=r"(v.y), "=r"(v.z), "=r"(v.w) : "l"(p) : "memory"); return v;
}
__device__ __forceinline__ uint32_t ld_relaxed(const void* p) {
  uint32_t v; asm volatile("ld.relaxed.gpu.global.u32 %0,[%1];" : "=r"(v) : "l"(p) : "memory"); return v;
}
__device__ __forceinline__ void st_relaxed(void* p, uint32_t v) { asm volatile("st.relaxed.gpu.global.b32 [%0],%1;" ::"l"(p), "r"(v) : "memory"); }
__device__ __forceinline__ void st_relaxed4(void* p, uint32_t v) { asm volatile("st.relaxed.gpu.global.v4.b32 [%0],{%1,%1,%1,%1};" ::"l"(p), "r"(v) : "memory"); }

__device__ __forceinline__ uint32_t ld_acquire(const void* p) {
  uint32_t v; asm volatile("ld.acquire.gpu.global.u32 %0,[%1];" : "=r"(v) : "l"(p) : "memory"); return v;
}
__device__ __forceinline__ float4 ld_relaxed4f(const void* p) {
  float4 v; asm volatile("ld.relaxed.gpu.global.v4.f32 {%0,%1,%2,%3},[%4];" : "=f"(v.x), "=f"(v.y), "=f"(v.z), "=f"(v.w) : "l"(p) : "memory"); return v;
}
__device__ __forceinline__ float2 ld_relaxed2f(const void* p) {
  float2 v; asm volatile("ld.relaxed.gpu.global.v2.f32 {%0,%1},[%2];" : "=f"(v.x), "=f"(v.y) : "l"(p) : "memory"); return v;
}
__device__ __forceinline__ void prefetch_l2(const void* p) { asm volatile("prefetch.global.L2 [%0];" ::"l"(p)); }
__device__ __forceinline__ void fence_gpu() { asm volatile("fence.acq_rel.gpu;" ::: "memory"); }
__device__ __forceinline__ void fence_async_all() { asm volatile("fence.proxy.async.global;" ::: "memory"); }
constexpr int SPIN_TOT = 1 << 22;
__device__ __forceinline__ void csignal(int idx) { asm volatile("red.release.gpu.global.add.u32 [%0],1;" ::"l"(&g_cnt[idx][0]) : "memory"); }
#define csignal_t(idx, role) csignal(idx)
__device__ __forceinline__ void cwait(int idx, uint32_t target, int& spin) {
  while (ld_acquire(&g_cnt[idx][0]) < target && spin < SPIN_TOT) spin += 16;
}

__device__ __forceinline__ uint64_t mkdesc(uint32_t addr, uint32_t lbo, uint32_t sbo) {
  return (uint64_t)((addr & 0x3FFFF) >> 4) | ((uint64_t)(lbo >> 4) << 16) | ((uint64_t)(sbo >> 4) << 32) | ((uint64_t)1 << 62);
}
__device__ __forceinline__ uint64_t mkdesc_ns(uint32_t addr, uint32_t lbo, uint32_t sbo) {
  return (uint64_t)((addr & 0x3FFFF) >> 4) | ((uint64_t)(lbo >> 4) << 16) | ((uint64_t)(sbo >> 4) << 32);
}
__device__ __forceinline__ void wg_fence() { asm volatile("wgmma.fence.sync.aligned;" ::: "memory"); }
__device__ __forceinline__ void wg_commit() { asm volatile("wgmma.commit_group.sync.aligned;" ::: "memory"); }
template <int N> __device__ __forceinline__ void wg_wait() { asm volatile("wgmma.wait_group.sync.aligned %0;" ::"n"(N) : "memory"); }

__device__ __forceinline__ void wgmma_rs16(float (&d)[8], const uint32_t (&a)[4], uint64_t db, int sc) {
  asm volatile("{.reg .pred p; setp.ne.b32 p,%13,0; wgmma.mma_async.sync.aligned.m64n16k16.f32.bf16.bf16 "
               "{%0,%1,%2,%3,%4,%5,%6,%7},{%8,%9,%10,%11},%12,p,1,1,0;}"
               : "+f"(d[0]), "+f"(d[1]), "+f"(d[2]), "+f"(d[3]), "+f"(d[4]), "+f"(d[5]), "+f"(d[6]), "+f"(d[7])
               : "r"(a[0]), "r"(a[1]), "r"(a[2]), "r"(a[3]), "l"(db), "r"(sc));
}
__device__ __forceinline__ void wgmma_rs64(float (&d)[32], const uint32_t (&a)[4], uint64_t db, int sc) {
  asm volatile("{.reg .pred p; setp.ne.b32 p,%37,0; wgmma.mma_async.sync.aligned.m64n64k16.f32.bf16.bf16 "
               "{%0,%1,%2,%3,%4,%5,%6,%7,%8,%9,%10,%11,%12,%13,%14,%15,%16,%17,%18,%19,%20,%21,%22,%23,%24,%25,%26,%27,%28,%29,%30,%31},{%32,%33,%34,%35},%36,p,1,1,0;}"
               : "+f"(d[0]), "+f"(d[1]), "+f"(d[2]), "+f"(d[3]), "+f"(d[4]), "+f"(d[5]), "+f"(d[6]), "+f"(d[7]), "+f"(d[8]), "+f"(d[9]), "+f"(d[10]), "+f"(d[11]), "+f"(d[12]), "+f"(d[13]), "+f"(d[14]), "+f"(d[15]), "+f"(d[16]), "+f"(d[17]), "+f"(d[18]), "+f"(d[19]), "+f"(d[20]), "+f"(d[21]), "+f"(d[22]), "+f"(d[23]), "+f"(d[24]), "+f"(d[25]), "+f"(d[26]), "+f"(d[27]), "+f"(d[28]), "+f"(d[29]), "+f"(d[30]), "+f"(d[31])
               : "r"(a[0]), "r"(a[1]), "r"(a[2]), "r"(a[3]), "l"(db), "r"(sc));
}
__device__ __forceinline__ void wgmma_rt16(float (&d)[8], const uint32_t (&a)[4], uint64_t db, int sc) {
  asm volatile("{.reg .pred p; setp.ne.b32 p,%13,0; wgmma.mma_async.sync.aligned.m64n16k16.f32.bf16.bf16 "
               "{%0,%1,%2,%3,%4,%5,%6,%7},{%8,%9,%10,%11},%12,p,1,1,1;}"
               : "+f"(d[0]), "+f"(d[1]), "+f"(d[2]), "+f"(d[3]), "+f"(d[4]), "+f"(d[5]), "+f"(d[6]), "+f"(d[7])
               : "r"(a[0]), "r"(a[1]), "r"(a[2]), "r"(a[3]), "l"(db), "r"(sc));
}
__device__ __forceinline__ void wgmma_rt80(float (&d)[40], const uint32_t (&a)[4], uint64_t db, int sc) {
  asm volatile("{.reg .pred p; setp.ne.b32 p,%45,0; wgmma.mma_async.sync.aligned.m64n80k16.f32.bf16.bf16 "
               "{%0,%1,%2,%3,%4,%5,%6,%7,%8,%9,%10,%11,%12,%13,%14,%15,%16,%17,%18,%19,%20,%21,%22,%23,%24,%25,%26,%27,%28,%29,%30,%31,%32,%33,%34,%35,%36,%37,%38,%39},{%40,%41,%42,%43},%44,p,1,1,1;}"
               : "+f"(d[0]), "+f"(d[1]), "+f"(d[2]), "+f"(d[3]), "+f"(d[4]), "+f"(d[5]), "+f"(d[6]), "+f"(d[7]), "+f"(d[8]), "+f"(d[9]), "+f"(d[10]), "+f"(d[11]), "+f"(d[12]), "+f"(d[13]), "+f"(d[14]), "+f"(d[15]), "+f"(d[16]), "+f"(d[17]), "+f"(d[18]), "+f"(d[19]), "+f"(d[20]), "+f"(d[21]), "+f"(d[22]), "+f"(d[23]), "+f"(d[24]), "+f"(d[25]), "+f"(d[26]), "+f"(d[27]), "+f"(d[28]), "+f"(d[29]), "+f"(d[30]), "+f"(d[31]), "+f"(d[32]), "+f"(d[33]), "+f"(d[34]), "+f"(d[35]), "+f"(d[36]), "+f"(d[37]), "+f"(d[38]), "+f"(d[39])
               : "r"(a[0]), "r"(a[1]), "r"(a[2]), "r"(a[3]), "l"(db), "r"(sc));
}
__device__ __forceinline__ void wgmma_rs32(float (&d)[16], const uint32_t (&a)[4], uint64_t db, int sc) {
  asm volatile("{.reg .pred p; setp.ne.b32 p,%21,0; wgmma.mma_async.sync.aligned.m64n32k16.f32.bf16.bf16 "
               "{%0,%1,%2,%3,%4,%5,%6,%7,%8,%9,%10,%11,%12,%13,%14,%15},{%16,%17,%18,%19},%20,p,1,1,0;}"
               : "+f"(d[0]), "+f"(d[1]), "+f"(d[2]), "+f"(d[3]), "+f"(d[4]), "+f"(d[5]), "+f"(d[6]), "+f"(d[7]), "+f"(d[8]), "+f"(d[9]), "+f"(d[10]), "+f"(d[11]), "+f"(d[12]), "+f"(d[13]), "+f"(d[14]), "+f"(d[15])
               : "r"(a[0]), "r"(a[1]), "r"(a[2]), "r"(a[3]), "l"(db), "r"(sc));
}
__device__ __forceinline__ void wgmma_ts32(float (&d)[16], uint64_t da, uint64_t db, int sc) {
  asm volatile("{.reg .pred p; setp.ne.b32 p,%18,0; wgmma.mma_async.sync.aligned.m64n32k16.f32.bf16.bf16 "
               "{%0,%1,%2,%3,%4,%5,%6,%7,%8,%9,%10,%11,%12,%13,%14,%15},%16,%17,p,1,1,1,0;}"
               : "+f"(d[0]), "+f"(d[1]), "+f"(d[2]), "+f"(d[3]), "+f"(d[4]), "+f"(d[5]), "+f"(d[6]), "+f"(d[7]), "+f"(d[8]), "+f"(d[9]), "+f"(d[10]), "+f"(d[11]), "+f"(d[12]), "+f"(d[13]), "+f"(d[14]), "+f"(d[15])
               : "l"(da), "l"(db), "r"(sc));
}
__device__ __forceinline__ void wgmma_ts16(float (&d)[8], uint64_t da, uint64_t db, int sc) {
  asm volatile("{.reg .pred p; setp.ne.b32 p,%10,0; wgmma.mma_async.sync.aligned.m64n16k16.f32.bf16.bf16 "
               "{%0,%1,%2,%3,%4,%5,%6,%7},%8,%9,p,1,1,1,0;}"
               : "+f"(d[0]), "+f"(d[1]), "+f"(d[2]), "+f"(d[3]), "+f"(d[4]), "+f"(d[5]), "+f"(d[6]), "+f"(d[7])
               : "l"(da), "l"(db), "r"(sc));
}
__device__ __forceinline__ void wgmma_ts64(float (&d)[32], uint64_t da, uint64_t db, int sc) {
  asm volatile("{.reg .pred p; setp.ne.b32 p,%34,0; wgmma.mma_async.sync.aligned.m64n64k16.f32.bf16.bf16 "
               "{%0,%1,%2,%3,%4,%5,%6,%7,%8,%9,%10,%11,%12,%13,%14,%15,%16,%17,%18,%19,%20,%21,%22,%23,%24,%25,%26,%27,%28,%29,%30,%31},%32,%33,p,1,1,1,0;}"
               : "+f"(d[0]), "+f"(d[1]), "+f"(d[2]), "+f"(d[3]), "+f"(d[4]), "+f"(d[5]), "+f"(d[6]), "+f"(d[7]), "+f"(d[8]), "+f"(d[9]), "+f"(d[10]), "+f"(d[11]), "+f"(d[12]), "+f"(d[13]), "+f"(d[14]), "+f"(d[15]), "+f"(d[16]), "+f"(d[17]), "+f"(d[18]), "+f"(d[19]), "+f"(d[20]), "+f"(d[21]), "+f"(d[22]), "+f"(d[23]), "+f"(d[24]), "+f"(d[25]), "+f"(d[26]), "+f"(d[27]), "+f"(d[28]), "+f"(d[29]), "+f"(d[30]), "+f"(d[31])
               : "l"(da), "l"(db), "r"(sc));
}
__device__ __forceinline__ void wgmma_tt16(float (&d)[8], uint64_t da, uint64_t db, int sc) {
  asm volatile("{.reg .pred p; setp.ne.b32 p,%10,0; wgmma.mma_async.sync.aligned.m64n16k16.f32.bf16.bf16 "
               "{%0,%1,%2,%3,%4,%5,%6,%7},%8,%9,p,1,1,1,1;}"
               : "+f"(d[0]), "+f"(d[1]), "+f"(d[2]), "+f"(d[3]), "+f"(d[4]), "+f"(d[5]), "+f"(d[6]), "+f"(d[7])
               : "l"(da), "l"(db), "r"(sc));
}
__device__ __forceinline__ void wgmma_tt40(float (&d)[20], uint64_t da, uint64_t db, int sc) {
  asm volatile("{.reg .pred p; setp.ne.b32 p,%22,0; wgmma.mma_async.sync.aligned.m64n40k16.f32.bf16.bf16 "
               "{%0,%1,%2,%3,%4,%5,%6,%7,%8,%9,%10,%11,%12,%13,%14,%15,%16,%17,%18,%19},%20,%21,p,1,1,1,1;}"
               : "+f"(d[0]), "+f"(d[1]), "+f"(d[2]), "+f"(d[3]), "+f"(d[4]), "+f"(d[5]), "+f"(d[6]), "+f"(d[7]), "+f"(d[8]), "+f"(d[9]), "+f"(d[10]), "+f"(d[11]), "+f"(d[12]), "+f"(d[13]), "+f"(d[14]), "+f"(d[15]), "+f"(d[16]), "+f"(d[17]), "+f"(d[18]), "+f"(d[19])
               : "l"(da), "l"(db), "r"(sc));
}
__device__ __forceinline__ void wgmma_ss8(float (&d)[4], uint64_t da, uint64_t db, int sc) {
  asm volatile("{.reg .pred p; setp.ne.b32 p,%6,0; wgmma.mma_async.sync.aligned.m64n8k16.f32.bf16.bf16 "
               "{%0,%1,%2,%3},%4,%5,p,1,1,0,0;}"
               : "+f"(d[0]), "+f"(d[1]), "+f"(d[2]), "+f"(d[3])
               : "l"(da), "l"(db), "r"(sc));
}
__device__ __forceinline__ void wgmma_ss32(float (&d)[16], uint64_t da, uint64_t db, int sc) {
  asm volatile("{.reg .pred p; setp.ne.b32 p,%18,0; wgmma.mma_async.sync.aligned.m64n32k16.f32.bf16.bf16 "
               "{%0,%1,%2,%3,%4,%5,%6,%7,%8,%9,%10,%11,%12,%13,%14,%15},%16,%17,p,1,1,0,0;}"
               : "+f"(d[0]), "+f"(d[1]), "+f"(d[2]), "+f"(d[3]), "+f"(d[4]), "+f"(d[5]), "+f"(d[6]), "+f"(d[7]), "+f"(d[8]), "+f"(d[9]), "+f"(d[10]), "+f"(d[11]), "+f"(d[12]), "+f"(d[13]), "+f"(d[14]), "+f"(d[15])
               : "l"(da), "l"(db), "r"(sc));
}
__device__ __forceinline__ void wgmma_st64(float (&d)[32], uint64_t da, uint64_t db, int sc) {
  asm volatile("{.reg .pred p; setp.ne.b32 p,%34,0; wgmma.mma_async.sync.aligned.m64n64k16.f32.bf16.bf16 "
               "{%0,%1,%2,%3,%4,%5,%6,%7,%8,%9,%10,%11,%12,%13,%14,%15,%16,%17,%18,%19,%20,%21,%22,%23,%24,%25,%26,%27,%28,%29,%30,%31},%32,%33,p,1,1,0,1;}"
               : "+f"(d[0]), "+f"(d[1]), "+f"(d[2]), "+f"(d[3]), "+f"(d[4]), "+f"(d[5]), "+f"(d[6]), "+f"(d[7]), "+f"(d[8]), "+f"(d[9]), "+f"(d[10]), "+f"(d[11]), "+f"(d[12]), "+f"(d[13]), "+f"(d[14]), "+f"(d[15]), "+f"(d[16]), "+f"(d[17]), "+f"(d[18]), "+f"(d[19]), "+f"(d[20]), "+f"(d[21]), "+f"(d[22]), "+f"(d[23]), "+f"(d[24]), "+f"(d[25]), "+f"(d[26]), "+f"(d[27]), "+f"(d[28]), "+f"(d[29]), "+f"(d[30]), "+f"(d[31])
               : "l"(da), "l"(db), "r"(sc));
}
__device__ __forceinline__ void wgmma_st128(float (&d)[64], uint64_t da, uint64_t db, int sc) {
  asm volatile("{.reg .pred p; setp.ne.b32 p,%66,0; wgmma.mma_async.sync.aligned.m64n128k16.f32.bf16.bf16 "
               "{%0,%1,%2,%3,%4,%5,%6,%7,%8,%9,%10,%11,%12,%13,%14,%15,%16,%17,%18,%19,%20,%21,%22,%23,%24,%25,%26,%27,%28,%29,%30,%31,%32,%33,%34,%35,%36,%37,%38,%39,%40,%41,%42,%43,%44,%45,%46,%47,%48,%49,%50,%51,%52,%53,%54,%55,%56,%57,%58,%59,%60,%61,%62,%63},%64,%65,p,1,1,0,1;}"
               : "+f"(d[0]), "+f"(d[1]), "+f"(d[2]), "+f"(d[3]), "+f"(d[4]), "+f"(d[5]), "+f"(d[6]), "+f"(d[7]), "+f"(d[8]), "+f"(d[9]), "+f"(d[10]), "+f"(d[11]), "+f"(d[12]), "+f"(d[13]), "+f"(d[14]), "+f"(d[15]), "+f"(d[16]), "+f"(d[17]), "+f"(d[18]), "+f"(d[19]), "+f"(d[20]), "+f"(d[21]), "+f"(d[22]), "+f"(d[23]), "+f"(d[24]), "+f"(d[25]), "+f"(d[26]), "+f"(d[27]), "+f"(d[28]), "+f"(d[29]), "+f"(d[30]), "+f"(d[31]), "+f"(d[32]), "+f"(d[33]), "+f"(d[34]), "+f"(d[35]), "+f"(d[36]), "+f"(d[37]), "+f"(d[38]), "+f"(d[39]), "+f"(d[40]), "+f"(d[41]), "+f"(d[42]), "+f"(d[43]), "+f"(d[44]), "+f"(d[45]), "+f"(d[46]), "+f"(d[47]), "+f"(d[48]), "+f"(d[49]), "+f"(d[50]), "+f"(d[51]), "+f"(d[52]), "+f"(d[53]), "+f"(d[54]), "+f"(d[55]), "+f"(d[56]), "+f"(d[57]), "+f"(d[58]), "+f"(d[59]), "+f"(d[60]), "+f"(d[61]), "+f"(d[62]), "+f"(d[63])
               : "l"(da), "l"(db), "r"(sc));
}

__device__ __forceinline__ void stsm4(uint32_t a, uint32_t r0, uint32_t r1, uint32_t r2, uint32_t r3) {
  asm volatile("stmatrix.sync.aligned.m8n8.x4.shared.b16 [%0],{%1,%2,%3,%4};" ::"r"(a), "r"(r0), "r"(r1), "r"(r2), "r"(r3) : "memory");
}
__device__ __forceinline__ void stsm4t(uint32_t a, uint32_t r0, uint32_t r1, uint32_t r2, uint32_t r3) {
  asm volatile("stmatrix.sync.aligned.m8n8.x4.trans.shared.b16 [%0],{%1,%2,%3,%4};" ::"r"(a), "r"(r0), "r"(r1), "r"(r2), "r"(r3) : "memory");
}
__device__ __forceinline__ void sts64(uint32_t a, uint32_t x, uint32_t y) { asm volatile("st.shared.v2.b32 [%0],{%1,%2};" ::"r"(a), "r"(x), "r"(y) : "memory"); }
__device__ __forceinline__ void st_async2u(uint32_t a, uint32_t x, uint32_t y, uint32_t bar) {
  asm volatile("st.async.weak.shared::cluster.mbarrier::complete_tx::bytes.v2.b32 [%0],{%1,%2},[%3];" ::"r"(a), "r"(x), "r"(y), "r"(bar) : "memory");
}
__device__ __forceinline__ void st_relaxed128(void* p, uint32_t x, uint32_t y, uint32_t z, uint32_t w) {
  asm volatile("{.reg .b128 v; mov.b128 v,{%1,%2,%3,%4}; st.relaxed.gpu.global.b128 [%0],v;}" ::"l"(p), "r"(x), "r"(y), "r"(z), "r"(w) : "memory");
}
__device__ __forceinline__ void st_relaxed64(void* p, uint32_t x, uint32_t y) {
  asm volatile("{.reg .b64 v; mov.b64 v,{%1,%2}; st.relaxed.gpu.global.b64 [%0],v;}" ::"l"(p), "r"(x), "r"(y) : "memory");
}
__device__ __forceinline__ uint4 ld_relaxed128(const void* p) {
  uint4 v;
  asm volatile("{.reg .b128 v; .reg .b64 lo, hi; ld.relaxed.gpu.global.b128 v,[%4]; mov.b128 {lo,hi},v; mov.b64 {%0,%1},lo; mov.b64 {%2,%3},hi;}" : "=r"(v.x), "=r"(v.y), "=r"(v.z), "=r"(v.w) : "l"(p) : "memory");
  return v;
}

__device__ __forceinline__ uint32_t pack_h2(float lo, float hi) {
  uint32_t r; asm("cvt.rn.satfinite.f16x2.f32 %0,%1,%2;" : "=r"(r) : "f"(hi), "f"(lo)); return r;
}
__device__ __forceinline__ void add_h2(float& lo, float& hi, uint32_t u, uint32_t v) {
  float a, b;
  asm("{.reg .b16 l, h; .reg .b32 s; add.rn.f16x2 s,%2,%3; mov.b32 {l,h},s; cvt.f32.f16 %0,l; cvt.f32.f16 %1,h;}" : "=f"(a), "=f"(b) : "r"(u), "r"(v));
  lo += a; hi += b;
}
__device__ __forceinline__ void mwait(uint32_t bar, uint32_t ph, int& spin) {
  asm volatile("{.reg .pred p, q;\nWAIT_LOOP:\n add.s32 %0,%0,1;\n setp.lt.s32 q,%0,%3;\n mbarrier.try_wait.parity.shared::cta.b64 p,[%1],%2;\n not.pred p,p;\n and.pred q,q,p;\n @q bra.uni WAIT_LOOP;\n}"
               : "+&r"(spin) : "r"(bar), "r"(ph), "n"(SPIN_TOT) : "memory");
}
__device__ __forceinline__ int keep(int x) { return __shfl_sync(0xffffffffu, x, threadIdx.x & 31); }
__device__ __forceinline__ uint32_t pin(uint32_t x) { asm volatile("" : "+r"(x)); return x; }
template <typename T> __device__ __forceinline__ T* pinp(T* x) { asm volatile("" : "+l"(x)); return x; }
__device__ __forceinline__ void st_async1u(uint32_t a, uint32_t x, uint32_t bar) {
  asm volatile("st.async.weak.shared::cluster.mbarrier::complete_tx::bytes.b32 [%0],%1,[%2];" ::"r"(a), "r"(x), "r"(bar) : "memory");
}
__device__ __forceinline__ uint32_t lds32(uint32_t a) { uint32_t v; asm volatile("ld.shared.b32 %0,[%1];" : "=r"(v) : "r"(a) : "memory"); return v; }
__device__ __forceinline__ uint2 lds64(uint32_t a) { uint2 v; asm volatile("ld.shared.v2.b32 {%0,%1},[%2];" : "=r"(v.x), "=r"(v.y) : "r"(a) : "memory"); return v; }

__device__ __forceinline__ void permute_cols(uint32_t tile, int tid, int n) {
  for (int it = tid; it < n; it += 128) {
    const int row = it >> 2, q = it & 3;
    const uint32_t a0 = tile + row * 128 + (((2 * q) ^ (row & 7)) << 4), a1 = tile + row * 128 + (((2 * q + 1) ^ (row & 7)) << 4);
    const uint4 u = lds128(a0), v = lds128(a1);
    sts128(a0, make_uint4(__byte_perm(u.x, u.y, 0x5410), __byte_perm(u.z, u.w, 0x5410), __byte_perm(v.x, v.y, 0x5410), __byte_perm(v.z, v.w, 0x5410)));
    sts128(a1, make_uint4(__byte_perm(u.x, u.y, 0x7632), __byte_perm(u.z, u.w, 0x7632), __byte_perm(v.x, v.y, 0x7632), __byte_perm(v.z, v.w, 0x7632)));
  }
}

__device__ __forceinline__ uint8_t* mkptr(uint32_t lo, uint32_t hi) { uint8_t* p; asm("mov.b64 %0,{%1,%2};" : "=l"(p) : "r"(lo), "r"(hi)); return p; }
__device__ __forceinline__ int uni(int x) { return __shfl_sync(0xffffffffu, x, 0); }

__device__ __forceinline__ void ln_row_to_image(const bf16* __restrict__ x, uint8_t* __restrict__ img, int row, int lane) {
  const uint4* src = reinterpret_cast<const uint4*>(x + (size_t)row * DM);
  uint4 v[3];
  v[0] = src[lane]; v[1] = src[lane + 32];
  v[2] = lane < 16 ? src[lane + 64] : make_uint4(0, 0, 0, 0);
  float s = 0.f;
#pragma unroll
  for (int i = 0; i < 3; i++) {
    s += bf_lo(v[i].x) + bf_hi(v[i].x) + bf_lo(v[i].y) + bf_hi(v[i].y) + bf_lo(v[i].z) + bf_hi(v[i].z) + bf_lo(v[i].w) + bf_hi(v[i].w);
  }
#pragma unroll
  for (int o = 16; o > 0; o >>= 1) s += __shfl_xor_sync(0xffffffffu, s, o);
  const float mean = s * (1.f / DM);
  float q = 0.f;
#pragma unroll
  for (int i = 0; i < 3; i++) {
    if (i < 2 || lane < 16) {
      const uint32_t w[4] = {v[i].x, v[i].y, v[i].z, v[i].w};
#pragma unroll
      for (int j = 0; j < 4; j++) { float a = bf_lo(w[j]) - mean, b = bf_hi(w[j]) - mean; q += a * a + b * b; }
    }
  }
#pragma unroll
  for (int o = 16; o > 0; o >>= 1) q += __shfl_xor_sync(0xffffffffu, q, o);
  const float rstd = rsqrtf(q * (1.f / DM) + 1e-5f);
#pragma unroll
  for (int i = 0; i < 3; i++) {
    if (i < 2 || lane < 16) {
      const int c = lane + 32 * i;
      uint4 o;
      o.x = pack_bf16((bf_lo(v[i].x) - mean) * rstd, (bf_hi(v[i].x) - mean) * rstd);
      o.y = pack_bf16((bf_lo(v[i].y) - mean) * rstd, (bf_hi(v[i].y) - mean) * rstd);
      o.z = pack_bf16((bf_lo(v[i].z) - mean) * rstd, (bf_hi(v[i].z) - mean) * rstd);
      o.w = pack_bf16((bf_lo(v[i].w) - mean) * rstd, (bf_hi(v[i].w) - mean) * rstd);
      const size_t off = (size_t)(row >> 5) * 40960 + (c >> 4) * 8192 + ((row >> 3) & 3) * 2048 + ((c >> 3) & 1) * 1024 + (row & 7) * 128 + (((c & 7) ^ (row & 7)) << 4);
      *reinterpret_cast<uint4*>(img + off) = o;
      float4* xf = reinterpret_cast<float4*>(g_x + (size_t)row * DM + c * 8);
      xf[0] = make_float4(bf_lo(v[i].x), bf_hi(v[i].x), bf_lo(v[i].y), bf_hi(v[i].y));
      xf[1] = make_float4(bf_lo(v[i].z), bf_hi(v[i].z), bf_lo(v[i].w), bf_hi(v[i].w));
    }
  }
}

__global__ void __launch_bounds__(256) k_pre(const bf16* __restrict__ x, const bf16* __restrict__ mem0) {
  const int row = blockIdx.x * 8 + (threadIdx.x >> 5);
  ln_row_to_image(x, g_xn[0], row, threadIdx.x & 31);
  const int gt = blockIdx.x * 256 + threadIdx.x;
  const uint4 sent = make_uint4(SENT, SENT, SENT, SENT);
  uint8_t* ex = ex_window(g_ex);
  if (gt < MAIL_BYTES / 16) {
    reinterpret_cast<uint4*>(ex + EX_MAIL)[gt] = sent;
    reinterpret_cast<uint4*>(ex + EX_MAIL + (1 << 20))[gt] = sent;
  }
  uint4* mb = reinterpret_cast<uint4*>(ex + EX_M);
  for (int i = gt; i < NSTEP * 1280; i += 65536) {
    const int p = i % 1280, st = i / 1280;
    uint4 v = sent;
    if (st == 0 || (st == LAG && (p & 8))) v = *reinterpret_cast<const uint4*>(mem0 + (p & 7) * DM + (p >> 4) * 8);
    mb[i] = v;
  }
  if (gt < NSTEP * 192) reinterpret_cast<uint4*>(ex + EX_FLAG)[gt] = gt < 192 ? make_uint4(0, 0, 0, 0) : sent;
  if (gt < CN_NUM) g_cnt[gt][0] = 0;
}

namespace C {
constexpr int NKR = 37;
constexpr int OFF_WQ = 0, OFF_WK = 81920;
constexpr int OFF_YO = 163840, OFF_YV = OFF_YO + 6144;
constexpr int OFF_M = 176128;
__host__ __device__ constexpr int og_off(int c) { return c ? OFF_M + 14336 + c * 2048 : 229376; }
constexpr int OFF_KT = 196608;
constexpr int OFF_XT = OFF_KT + 10240;
constexpr int OFF_VT = OFF_XT + 7168;
constexpr int OFF_XM = OFF_VT + 11392;
constexpr int OFF_PT = OFF_XM + 2560;
constexpr int KS = 1280, VS = 1408;
__host__ __device__ constexpr int slot_off(int p) { return p == 2 ? OFF_M : OFF_KT + (p % 3) * 16384; }
constexpr int OFF_BAR = 231552;
constexpr int OFF_SAFE = OFF_BAR + 160;
constexpr int OFF_TS = OFF_BAR + 256;
constexpr int SMEM = 232448;
constexpr uint32_t SB0 = 1024;
constexpr int BAR_F = OFF_BAR, BAR_E = OFF_BAR + 40, BAR_M = OFF_BAR + 80, BAR_MOK = OFF_BAR + 88, BAR_XM = OFF_BAR + 96, BAR_XF = OFF_BAR + 104,
              BAR_XT = OFF_BAR + 112, BAR_MF = OFF_BAR + 120, BAR_OG = OFF_BAR + 128, BAR_W = OFF_BAR + 136, FLG_REDO = OFF_BAR + 144;
constexpr int NB_PRO = 1, NB_RD = 2, NB_MR = 3, NB_QK = 4, NB_SM = 5, NB_VA = 6, NB_VQ = 7, NB_A = 8, NB_Q = 9, NB_C = 10, NB_WQ = 11, NB_QI = 12, NB_SI = 13, NB_WV = 14;
#define B1 300
#define B2 250
#define FLP 0
#define OSG 2
#define QIE 4
#define SIE 2
#define WOE 1
#define OGF 0
#define VSP 8
#define RFK 5
#define PFD 3
#define WOL 0
#define NOWORK 0
constexpr float SCL = 1.f / 2048, SCE = 0.07216878364870322f * 1.4426950408889634f * 2048;
}

#define CBAR_SYNC(id, n) bar_sync(id, n)
#define CBAR_ARRIVE(id, n) bar_arrive(id, n)

__device__ __forceinline__ uint64_t wdesc(int off) { return mkdesc(C::SB0 + off, 8192, 1024); }
__device__ __forceinline__ uint64_t mdesc(int k) { return mkdesc_ns(C::SB0 + C::OFF_M + k * 512, 256, 128); }
__device__ __forceinline__ uint64_t tdesc(int k) { return mkdesc(C::SB0 + C::slot_off(k >> 3) + ((k >> 2) & 1) * 1024 + (k & 3) * 32, 16, 2048); }

__device__ __forceinline__ int dh_row(int n) { return (n & ~63) + (n & 32) + ((n >> 1) & 3) * 8 + ((n >> 3) & 3) * 2 + (n & 1); }
template <bool PERM>
__device__ __forceinline__ void load_weights_rs(uint32_t (&wf)[C::NKR][4], uint32_t sb, int stage, int yoff, int tid0) {
  using namespace C;
  const int i = (tid0 >> 3) & 3, n0 = (tid0 & 7) + (i >> 1) * 8;
  const int chunk = 2 * ((tid0 >> 5) & 3) + (i & 1);
  const int r0 = PERM ? dh_row(n0) : n0, r1 = PERM ? dh_row(n0 + 16) : n0 + 16;
  const uint32_t a0 = sb + stage + r0 * 128 + ((chunk ^ (r0 & 7)) << 4), a1 = sb + stage + r1 * 128 + ((chunk ^ (r1 & 7)) << 4);
#pragma unroll
  for (int k = 0; k < NKR; k++) ldsm4t(wf[k], ((k & 1) ? a1 : a0) + (k >> 1) * 4096);
#pragma unroll
  for (int k = 0; k < 40 - NKR; k++) {
    const int n = (NKR + k) * 16 + ((tid0 & 127) >> 3), r = PERM ? dh_row(n) : n, c = tid0 & 7;
    sts128(sb + yoff + (n - NKR * 16) * 128 + ((c ^ (n & 7)) << 4), lds128(sb + stage + r * 128 + ((c ^ (r & 7)) << 4)));
  }
  fence_async();
  CBAR_SYNC(NB_PRO, 384);
}
template <int STRIDE>
__device__ __forceinline__ void store_mem(const float (&d)[8], uint32_t base, int tid) {
  const int m = (tid >> 3) & 3;
  stsm4(base + (((tid >> 5) & 3) * 2 + (m & 1)) * STRIDE + (m >> 1) * 640 + (tid & 7) * 16, pack_bf16(d[0], d[1]), pack_bf16(d[2], d[3]),
        pack_bf16(d[4], d[5]), pack_bf16(d[6], d[7]));
}

__device__ __forceinline__ void load_pair(uint32_t sb, int i, int p, uint32_t slot, uint32_t bar, uint32_t ph, int& spin) {
  using namespace C;
  const uint8_t* s0 = g_xn[0] + (size_t)i * 40960 + p * 8192;
  const uint8_t* s1 = g_xn[NOWORK ? 0 : 1] + (size_t)(i - LAG) * 40960 + p * 8192;
  const uint8_t* sa = pinp(i < NSEG ? s0 : s1);
  const uint8_t* sc = pinp(i >= LAG ? s1 : s0);
  const uint32_t dst = pin(sb + slot), fb = pin(sb + BAR_F + 8 * p);
  mwait(bar, ph, spin);
  bulk_g2s_mc(dst, sa, 8192, fb);
  bulk_g2s_mc(dst + 8192, sc, 8192, fb);
}
__device__ __forceinline__ void first_fill(uint32_t sb, int i, int rank, int& spin) {
  using namespace C;
  const int s1 = i - LAG;
  if (!NOWORK && s1 >= 0) { cwait(CN_X + s1, 32, spin); fence_async_all(); }
  load_pair(sb, i, rank, rank == 2 ? OFF_M : OFF_KT + rank * 16384, sb + BAR_E + 8 * rank, (i - 1) & 1, spin);
}
__device__ __forceinline__ void release_round(uint32_t sb, int p, int tid) {
  using namespace C;
  const int lane = tid & 31;
  if (p < 2) { if (lane == 0) mbar_arrive_cluster(mapa(sb, p) + BAR_E + 8 * (3 + p)); }
  else if (lane < 3) mbar_arrive_cluster(mapa(sb, lane) + BAR_MOK);
}

template <int K0, int K1>
__device__ __forceinline__ void v_mem_pass(float (&d)[8], const uint32_t (&wf)[C::NKR][4]) {
  using namespace C;
  wg_fence();
#pragma unroll
  for (int k = K0; k < K1; k++) {
    if (k < NKR) wgmma_rs16(d, wf[k < NKR ? k : 0], mdesc(k), k != 32);
    else wgmma_ts16(d, wdesc(OFF_YV + (k - NKR) * 2048), mdesc(k), 1);
  }
  wg_commit();
}
__device__ __forceinline__ void chain_v(const uint32_t sb, const int tid0, const int cta, const int rank) {
  using namespace C;
  asm volatile("setmaxnreg.inc.sync.aligned.u32 208;");
  int spin = 0;
  uint32_t wf[NKR][4];
  if (tid0 == 256) first_fill(sb, 0, rank, spin);
  __syncwarp();
  mwait(sb + BAR_W, 0, spin);
  for (int it = tid0 & 127; it < 1280; it += 128) {
    const uint32_t base = sb + OFF_WK + (it >> 1) * 128;
    const int sw = ((it >> 1) & 7) ^ ((it & 1) * 4);
    const uint4 u0 = lds128(base + (sw << 4)), u1 = lds128(base + ((sw ^ 1) << 4)), u2 = lds128(base + ((sw ^ 2) << 4)), u3 = lds128(base + ((sw ^ 3) << 4));
    sts128(base + (sw << 4), make_uint4(u0.x, u1.x, u2.x, u3.x)); sts128(base + ((sw ^ 1) << 4), make_uint4(u0.y, u1.y, u2.y, u3.y));
    sts128(base + ((sw ^ 2) << 4), make_uint4(u0.z, u1.z, u2.z, u3.z)); sts128(base + ((sw ^ 3) << 4), make_uint4(u0.w, u1.w, u2.w, u3.w));
  }
  bar_sync(NB_RD, 128);
  load_weights_rs<false>(wf, sb, OFF_WK, OFF_YV, tid0);
#pragma unroll 1
  for (int i = 0; i < NSTEP; i++) {
    {
      float d[32];
      if (i > 0) CBAR_SYNC(NB_WV, 256);
#pragma unroll
      for (int p = 0; p < 5; p++) {
        mwait(sb + BAR_F + 8 * p, i & 1, spin);
        TS(i, 25 + p);
        wg_fence();
#pragma unroll
        for (int k = 8 * p; k < 8 * p + 8; k++) {
          if (k < NKR) wgmma_rs64(d, wf[k < NKR ? k : 0], tdesc(k), k);
          else wgmma_ts64(d, wdesc(OFF_YV + (k - NKR) * 2048), tdesc(k), 1);
          if (k == 8 * p + 1 && p >= 1 && p <= 3) {
            wg_commit(); wg_wait<1>();
            release_round(sb, p - 1, fresh(tid0));
            wg_fence();
          }
          if (k == 8 * p + RFK && (p == 1 || p == 2)) {
            wg_commit();
            if (rank == p - 1 && tid0 == 256) load_pair(sb, i, p + 2, slot_off(p + 2), sb + BAR_E + 8 * (p + 2), i & 1, spin);
            __syncwarp();
            wg_fence();
          }
        }
        wg_commit();
      }
      wg_wait<0>();
      TS(i, 23);
      CBAR_SYNC(NB_RD, 256);
      const int tid = fresh(tid0) & 127, m = (tid >> 3) & 3;
      if (tid >= 96) {
        if (tid < 101) { if (i + 1 < NSTEP) mbar_expect_tx(sb + BAR_F + 8 * (tid - 96), 16384); }
        else if (tid == 101) mbar_expect_tx(sb + BAR_XM, 2560);
        else if (tid == 102) mbar_expect_tx(sb + BAR_XT, 7168);
        else if (tid == 103) mbar_expect_tx(sb + BAR_OG, 4096);
        else if (tid < 106) mbar_arrive_cluster(mapa(sb, (rank + tid - 103) % 3) + BAR_XF);
        __syncwarp();
      }
      const uint32_t a = sb + OFF_VT + 256 + ((tid >> 5) * 2 + (m & 1)) * VS + (m >> 1) * 128 + (tid & 7) * 16;
#pragma unroll
      for (int s = 0; s < 4; s++)
        stsm4(a + (s & 1) * 256 + (s >> 1) * 640, pack_bf16(d[8 * s], d[8 * s + 1]), pack_bf16(d[8 * s + 2], d[8 * s + 3]),
              pack_bf16(d[8 * s + 4], d[8 * s + 5]), pack_bf16(d[8 * s + 6], d[8 * s + 7]));
      if (tid < 80) sts128(sb + (tid < 72 ? OFF_VT + (tid >> 3) * VS : OFF_PT + 1280) + (tid & 7) * 16, make_uint4(0, 0, 0, 0));
      fence_async();
    }
    mwait(sb + BAR_XF, i & 1, spin);
    CBAR_ARRIVE(NB_QK, 384);
    CBAR_SYNC(NB_QI, 256);
    float d[8];
    v_mem_pass<32, 40>(d, wf);
    CBAR_SYNC(NB_SM, 256);
    wg_wait<0>();
    if (__builtin_expect(lds32(sb + FLG_REDO), 0)) { v_mem_pass<32, 40>(d, wf); wg_wait<0>(); }
    if ((tid0 & 31) < 2) mbar_arrive_cluster(mapa(sb, (rank + 1 + (tid0 & 1)) % 3) + BAR_MF);
    v_mem_pass<0, 32>(d, wf);
    wg_wait<0>();
    TS(i, 24);
    const int tid = fresh(tid0);
    if ((tid & 31) == 0) mbar_arrive_cluster(mapa(sb, 2) + BAR_E + 16);
    store_mem<VS>(d, sb + OFF_VT + 128, tid);
    fence_async();
    CBAR_ARRIVE(NB_VA, 256);
    CBAR_ARRIVE(NB_VQ, 256);
    if (tid == 256) {
      if (i + 1 < NSTEP) { first_fill(sb, i + 1, rank, spin); TS1(i + 1, 37); }
    } else if (tid >= 288 && tid < 295) {
      const int lane = tid & 31, ip = i + PFD;
      if (cta < 80 && ip < NSTEP) {
        if (lane < 2) prefetch_l2(ex_window(g_ex) + EX_M + ip * 20480 + (cta * 2 + lane) * 128);
        else if (lane == 6) { if (cta < 22) prefetch_l2(ex_window(g_ex) + EX_FLAG + ip * 3072 + cta * 128); }
        else if (ip < NSEG) prefetch_l2(g_xn[0] + (size_t)ip * 40960 + (cta * 4 + lane - 2) * 128);
      }
    }
    TS_FLUSH(i - 1);
    __syncwarp();
  }
  CBAR_ARRIVE(NB_WV, 256);
  if (spin >= SPIN_TOT) g_err = 3;
}

__device__ __forceinline__ float quad_max(float x) {
  const float a = __shfl_xor_sync(0xffffffffu, x, 1), b = __shfl_xor_sync(0xffffffffu, x, 2), c = __shfl_xor_sync(0xffffffffu, x, 3);
  return fmaxf(fmaxf(x, a), fmaxf(b, c));
}
__device__ __forceinline__ float quad_sum(float x) {
  const float a = __shfl_xor_sync(0xffffffffu, x, 1), b = __shfl_xor_sync(0xffffffffu, x, 2), c = __shfl_xor_sync(0xffffffffu, x, 3);
  return (x + a) + (b + c);
}
__device__ __forceinline__ float max10(const float (&y)[10]) {
  return fmaxf(fmaxf(fmaxf(fmaxf(y[0], y[1]), fmaxf(y[2], y[3])), fmaxf(fmaxf(y[4], y[5]), fmaxf(y[6], y[7]))), fmaxf(y[8], y[9]));
}
__device__ __forceinline__ float sum10(const float (&y)[10]) {
  return (((y[0] + y[1]) + (y[2] + y[3])) + ((y[4] + y[5]) + (y[6] + y[7]))) + (y[8] + y[9]);
}
__device__ __forceinline__ float rcp(float x) { float y; asm("rcp.approx.ftz.f32 %0,%1;" : "=f"(y) : "f"(x)); return y; }

__device__ __forceinline__ void signal_o(int i, int cta) { csignal(CN_O + i * 5 + min(cta / 19, 4)); }

__device__ __forceinline__ void chain_q(const CUtensorMap& tmWq, const CUtensorMap& tmWk, const uint32_t sb, const int tid0, const int cta, const int rank) {
  using namespace C;
  asm volatile("setmaxnreg.dec.sync.aligned.u32 96;");
  int spin = 0;
  CBAR_SYNC(NB_PRO, 384);
  PTS(5);
  if (tid0 == 128) {
    const int col = (cta / 3) * DH + rank * 64;
    mbar_expect_tx(sb + BAR_W, 163840);
    for (int i = 0; i < 5; i++) {
      tma2d(sb + OFF_WQ + i * 16384, &tmWq, col, i * 128, sb + BAR_W);
      tma2d(sb + OFF_WK + i * 16384, &tmWk, col, i * 128, sb + BAR_W);
    }
  }
  __syncwarp();
  mwait(sb + BAR_W, 1, spin);
  PTS(6);
#pragma unroll 1
  for (int i = 0; i < NSTEP; i++) {
    const int ph = i & 1;
    uint32_t qf[4][4];
    {
      float d[64];
#pragma unroll
      for (int p = 0; p < 5; p++) {
        mwait(sb + BAR_F + 8 * p, ph, spin);
        if (p == 0) TS(i, 0);
        wg_fence();
#pragma unroll
        for (int k = 8 * p; k < 8 * p + 8; k++) {
          wgmma_st128(d, tdesc(k), mkdesc(SB0 + OFF_WQ + k * 2048, OFF_WK - OFF_WQ, 1024), k);
          if (k == 8 * p + 1 && p >= 1 && p <= 3) {
            wg_commit(); wg_wait<1>();
            release_round(sb, p - 1, fresh(tid0));
            wg_fence();
          }
        }
        wg_commit();
      }
      wg_wait<0>();
      TS(i, 1);
      CBAR_SYNC(NB_RD, 256);
      TSB(i, 2);
      const int tid = fresh(tid0), w = (tid >> 5) & 3, m = (tid >> 3) & 3;
      const uint32_t a = sb + OFF_KT + (m >> 1) * KS + (1 + 5 * (w >> 1) + 2 * (w & 1) + (m & 1)) * 128 + (tid & 7) * 16;
#pragma unroll
      for (int s = 0; s < 4; s++)
        stsm4t(a + s * 2 * KS, pack_bf16(d[32 + 8 * s], d[33 + 8 * s]), pack_bf16(d[34 + 8 * s], d[35 + 8 * s]),
               pack_bf16(d[36 + 8 * s], d[37 + 8 * s]), pack_bf16(d[38 + 8 * s], d[39 + 8 * s]));
      fence_async();
      CBAR_ARRIVE(NB_QK, 384);
      if (OSG == 0) { if (tid == 224 && i > 0) signal_o(i - 1, cta); __syncwarp(); }
#pragma unroll
      for (int kk = 0; kk < 4; kk++)
#pragma unroll
        for (int j = 0; j < 4; j++) asm volatile("cvt.rn.bf16x2.f32 %0,%1,%2;" : "=r"(qf[kk][j]) : "f"(d[8 * kk + 2 * j + 1] * SCL), "f"(d[8 * kk + 2 * j] * SCL));
    }
    CBAR_SYNC(NB_SI, 256);
    uint32_t pf[5][4];
    float s0, s1;
    {
      float y0[10], y1[10];
      const int tid = fresh(tid0), lane = tid & 31, u = (tid >> 5) & 1;
      const bool c1 = tid & 64;
      {
        float x[40];
        wg_fence();
#pragma unroll
        for (int kk = 0; kk < 4; kk++) wgmma_rt80(x, qf[kk], mkdesc_ns(SB0 + OFF_KT + kk * 2 * KS, KS, 128), kk);
        wg_commit();
        wg_wait<0>();
#pragma unroll
        for (int j = 0; j < 5; j++) {
          y0[2 * j] = (c1 ? x[20 + 4 * j] : x[4 * j]); y0[2 * j + 1] = (c1 ? x[21 + 4 * j] : x[4 * j + 1]);
          y1[2 * j] = (c1 ? x[22 + 4 * j] : x[4 * j + 2]); y1[2 * j + 1] = (c1 ? x[23 + 4 * j] : x[4 * j + 3]);
        }
      }
      TS(i, 17);
      const uint32_t xo = OFF_XT + (c1 ? 1792 : 0) + u * 640 + lane * 16, x2 = xo + u * 512 + 512 - lane * 12;
      {
        const uint4 h0 = make_uint4(pack_h2(y0[0], y0[1]), pack_h2(y0[2], y0[3]), pack_h2(y1[0], y1[1]), pack_h2(y1[2], y1[3]));
        const uint4 h1 = make_uint4(pack_h2(y0[4], y0[5]), pack_h2(y0[6], y0[7]), pack_h2(y1[4], y1[5]), pack_h2(y1[6], y1[7]));
        const uint32_t h2 = u ? pack_h2(y1[8], y1[9]) : h1.z;
#pragma unroll
        for (int dd = 0; dd < 2; dd++) {
          const uint32_t rb = mapa(sb, (rank + 1 + dd) % 3), ro = rb + (1 - dd) * 3584;
          st_async4u(ro + xo, h0, rb + BAR_XT);
          if (u) st_async4u(ro + xo + 512, h1, rb + BAR_XT);
          st_async1u(ro + x2, h2, rb + BAR_XT);
        }
      }
      TS(i, 18);
      const int lim = 16 * u + (lane >> 2) + 8 - 2 * (lane & 3);
#pragma unroll
      for (int j = 1; j < 5; j++) {
        if (8 * j > lim) y0[2 * j] = -INFINITY;
        if (8 * j + 1 > lim) y0[2 * j + 1] = -INFINITY;
        if (8 * j - 8 > lim) y1[2 * j] = -INFINITY;
        if (8 * j - 7 > lim) y1[2 * j + 1] = -INFINITY;
      }
      mwait(sb + BAR_XT, ph, spin);
      TS(i, 19);
      {
        const uint4 u0 = lds128(sb + xo), v0 = lds128(sb + xo + 3584);
        const uint32_t u2 = lds32(sb + x2), v2 = lds32(sb + x2 + 3584);
        uint4 u1 = make_uint4(0, 0, u2, 0), v1 = make_uint4(0, 0, v2, 0);
        if (u) { u1 = lds128(sb + xo + 512); v1 = lds128(sb + xo + 512 + 3584); }
        __syncwarp();
        if (lane == 0) mbar_arrive_cluster(mapa(sb, 0) + BAR_E);
        add_h2(y0[0], y0[1], u0.x, v0.x); add_h2(y0[2], y0[3], u0.y, v0.y); add_h2(y1[0], y1[1], u0.z, v0.z); add_h2(y1[2], y1[3], u0.w, v0.w);
        add_h2(y0[4], y0[5], u1.x, v1.x); add_h2(y0[6], y0[7], u1.y, v1.y); add_h2(y1[4], y1[5], u1.z, v1.z); add_h2(y1[6], y1[7], u1.w, v1.w);
        add_h2(y1[8], y1[9], u2, v2);
      }
      y0[8] = y0[0]; y0[9] = y0[1];
      const float m0 = quad_max(max10(y0)) * -SCE, m1 = quad_max(max10(y1)) * -SCE;
      s0 = 0.f; s1 = 0.f;
#pragma unroll
      for (int j = 0; j < 5; j++) {
        const uint32_t p0 = j < 4 ? pack_bf16(ex2(fmaf(y0[2 * j], SCE, m0)), ex2(fmaf(y0[2 * j + 1], SCE, m0))) : 0u;
        const uint32_t p1 = pack_bf16(ex2(fmaf(y1[2 * j], SCE, m1)), ex2(fmaf(y1[2 * j + 1], SCE, m1)));
        s0 += bf_lo(p0) + bf_hi(p0); s1 += bf_lo(p1) + bf_hi(p1);
        pf[j >> 1][2 * (j & 1)] = c1 ? 0u : p0; pf[j >> 1][2 * (j & 1) + 1] = c1 ? 0u : p1;
        pf[(j + 5) >> 1][2 * ((j + 5) & 1)] = c1 ? p0 : 0u; pf[(j + 5) >> 1][2 * ((j + 5) & 1) + 1] = c1 ? p1 : 0u;
      }
    }
    CBAR_SYNC(NB_VQ, 256);
    TSB(i, 20);
    {
      float o[32];
      wg_fence();
#pragma unroll
      for (int q = 0; q < 5; q++) wgmma_rs64(o, pf[q], mkdesc_ns(SB0 + OFF_VT + 128 + q * 256, 128, VS), q);
      wg_commit();
      s0 = rcp(quad_sum(s0)); s1 = rcp(quad_sum(s1));
      const int tid = fresh(tid0), g = (tid >> 2) & 7, c = (tid >> 6) & 1, sg = i - c * LAG;
      uint8_t* op = pinp(&g_o[i % ORING][cta][(((tid >> 5) & 3) * 16 + g) * 128]);
      const uint32_t o0 = pin(((tid & 3) ^ g) << 4), live = pin(sg >= 0 && sg < NSEG);
      wg_wait<0>();
      TS(i, 21);
      if ((tid & 31) == 0) mbar_arrive_cluster(mapa(sb, 1) + BAR_E + 8);
      uint4 ov[4];
#pragma unroll
      for (int h = 0; h < 2; h++) {
        const float* x = o + 16 * h;
        ov[2 * h] = make_uint4(pin(pack_bf16(x[0] * s0, x[1] * s0)), pin(pack_bf16(x[4] * s0, x[5] * s0)), pin(pack_bf16(x[8] * s0, x[9] * s0)), pin(pack_bf16(x[12] * s0, x[13] * s0)));
        ov[2 * h + 1] = make_uint4(pin(pack_bf16(x[2] * s1, x[3] * s1)), pin(pack_bf16(x[6] * s1, x[7] * s1)), pin(pack_bf16(x[10] * s1, x[11] * s1)), pin(pack_bf16(x[14] * s1, x[15] * s1)));
      }
      TS(i, 22);
      if (i + 1 < NSTEP) CBAR_SYNC(NB_WQ, 256); else CBAR_ARRIVE(NB_WQ, 256);
      if (live) {
#pragma unroll
        for (int h = 0; h < 4; h++) *reinterpret_cast<uint4*>(op + (h & 1) * 1024 + (o0 ^ ((h >> 1) * 64))) = ov[h];
      }
      if (OSG && i + 1 < NSTEP) CBAR_ARRIVE(NB_MR, 160);
    }
  }
  CBAR_SYNC(NB_Q, 128);
  if (tid0 == 224) signal_o(NSTEP - 1, cta);
  if (spin >= SPIN_TOT) g_err = 2;
}

template <int NL>
__device__ __forceinline__ void poll_add(const uint8_t* mb, uint32_t tag, float (&f)[8], uint8_t* flag, bool lead, int osig, int& n, int& spin) {
  uint4 x[NL];
#pragma unroll
  for (int i = 0; i < NL; i++) x[i] = ld_relaxed128(mb + i * 512);
  if (OSG == 1 && osig >= 0) csignal(osig);
  while (true) {
    uint32_t any = 0;
#pragma unroll
    for (int i = 0; i < NL; i++) any |= (x[i].x ^ tag) | (NL == 6 ? x[i].z ^ tag : 0u);
    n++;
    if (!__any_sync(0xffffffffu, (any & 1) && spin < SPIN_TOT)) break;
    spin += 16;
#pragma unroll
    for (int i = 0; i < NL; i++)
      if (((pin(x[i].x) ^ tag) | (NL == 6 ? x[i].z ^ tag : 0u)) & 1) x[i] = ld_relaxed128(mb + i * 512);
  }
  if (FLP == 0 && lead) st_relaxed(flag, 0);
#pragma unroll
  for (int i = 0; i < NL; i++) {
    const uint32_t u[4] = {x[i].x, x[i].y, x[i].z, x[i].w};
#pragma unroll
    for (int j = 0; j < 4; j++) {
      if (i == 0) { f[2 * j] = bf_lo(u[j]); f[2 * j + 1] = bf_hi(u[j]); }
      else { f[2 * j] += bf_lo(u[j]); f[2 * j + 1] += bf_hi(u[j]); }
    }
  }
}

template <int B, int SLOT>
__device__ __forceinline__ void wo_block(float (&acc)[8], const uint32_t (&wf)[C::NKR][4]) {
  using namespace C;
#pragma unroll
  for (int kk = 0; kk < 4; kk++) {
    const int k = 4 * B + kk;
    const uint64_t db = mkdesc_ns(SB0 + og_off(SLOT) + kk * 512, 256, 128);
    if (k < NKR) wgmma_rt16(acc, wf[k < NKR ? k : 0], db, SLOT | kk);
    else wgmma_tt16(acc, wdesc(OFF_YO + (k - NKR) * 2048), db, 1);
  }
}

__device__ __forceinline__ void chain_a(const uint32_t sb, const int tid0, const int cta, const int rank) {
  using namespace C;
  asm volatile("setmaxnreg.inc.sync.aligned.u32 200;");
  int spin = 0;
  uint32_t wf[NKR][4];
  mwait(sb + BAR_W, 0, spin);
  permute_cols(sb + OFF_WQ, tid0, 2560);
  CBAR_SYNC(NB_A, 128);
  load_weights_rs<true>(wf, sb, OFF_WQ, OFF_YO, tid0);
  const int wu = uni(tid0 >> 5);
  const bool t9 = cta >= 72 && cta < 88;
  const uint64_t exa = reinterpret_cast<uint64_t>(ex_window(g_ex));
  const uint32_t ehi = (uint32_t)(exa >> 32), elo = (uint32_t)exa;

#pragma unroll 1
  for (int i = -1; i < NSTEP; i++) {
    const int ph = i & 1;
    if (i >= 0) {
      const int tid = fresh(tid0);
      const uint32_t mo = __shfl_xor_sync(0xffffffffu, elo + (ph << 20) + ((rank * 24 + (tid >> 4)) * 4 + (tid & 3)) * 2048 + (cta / 3) * 64 + (tid & 12) * 4, 0);
      const uint32_t m9 = __shfl_xor_sync(0xffffffffu, elo + (ph << 20) + MAIL9 + (((tid >> 4) * 2 + (tid & 1)) * 4 + (tid & 2)) * 3072 + cta * 32 + (tid & 12) * 2, 0);
      const uint32_t oo = __shfl_xor_sync(0xffffffffu, (tid >> 5) * 512 + (tid & 2) * 64 + (tid & 28) * 4 + (tid & 1) * 8, 0);
      if (i == 0) mwait(sb + BAR_W, 1, spin);
      mwait(sb + BAR_M, ph, spin);
      TS(i, 3);
      {
        float x[20];
        int redo = 0;
      retry:
        bool bad;
        {
          float dq[8], dk[8];
          wg_fence();
#pragma unroll
          for (int k = 0; k < 40; k++) wgmma_ts16(dq, wdesc(OFF_WQ + k * 2048), mdesc(k), k);
          wg_commit();
#pragma unroll
          for (int k = 0; k < 40; k++) {
            if (k == 40 - QIE && !redo) CBAR_ARRIVE(NB_QI, 256);
            wgmma_ts16(dk, wdesc(OFF_WK + k * 2048), mdesc(k), k);
          }
          wg_commit();
          const int m = (tid >> 3) & 3, dg = (tid >> 5) * 2 + (m & 1);
          const uint32_t ka = sb + OFF_KT + dg * KS + (m >> 1) * 640 + (tid & 7) * 16;
          wg_wait<1>();
          const float chk = (dq[0] + dq[1]) + (dq[4] + dq[5]);
          const uint32_t q0 = pack_bf16(dq[0] * SCL, dq[1] * SCL), q1 = pack_bf16(dq[2] * SCL, dq[3] * SCL), q2 = pack_bf16(dq[4] * SCL, dq[5] * SCL), q3 = pack_bf16(dq[6] * SCL, dq[7] * SCL);
          if (!redo) CBAR_SYNC(NB_QK, 384);
          stsm4(ka + dg * (VS - KS) + (OFF_VT + 128 - OFF_KT), q0, q1, q2, q3);
          sts32(sb + FLG_REDO, redo);
          wg_wait<0>();
          TS(i, 4);
          stsm4(ka, pack_bf16(dk[0], dk[1]), pack_bf16(dk[2], dk[3]), pack_bf16(dk[4], dk[5]), pack_bf16(dk[6], dk[7]));
          fence_async();
          bad = bar_red_or(NB_C, 128, chk != chk && !redo);
        }
        TSB(i, 5);
        wg_fence();
#pragma unroll
        for (int kk = 0; kk < 4; kk++) wgmma_tt40(x, mkdesc_ns(SB0 + OFF_VT + 128 + kk * 2 * VS, VS, 640), mkdesc_ns(SB0 + OFF_KT + kk * 2 * KS, KS, 128), kk);
#pragma unroll
        for (int kk = 0; kk < 4; kk++) {
          if (SIE && kk == 4 - SIE && !bad) CBAR_ARRIVE(NB_SI, 256);
          wgmma_tt40(x, mkdesc_ns(SB0 + OFF_VT + kk * 2 * VS, VS, 384), mkdesc_ns(SB0 + OFF_KT + 640 + kk * 2 * KS, KS, 128), 1);
        }
        wg_commit();
        if (!SIE && !bad) CBAR_ARRIVE(NB_SI, 256);
        if (__builtin_expect(__any_sync(0xffffffffu, bad), 0)) {
          wg_wait<0>();
#pragma unroll 1
          for (int k = 0; k < 10; k++) {
            uint4 v = lds128(sb + OFF_M + tid * 16 + k * 2048);
            if (v.x == SENT || v.y == SENT || v.z == SENT || v.w == SENT) {
              do { v = ld_relaxed4(mkptr(elo + EX_M + i * 20480 + tid * 16 + k * 2048, ehi)); spin += 16; } while ((v.x == SENT || v.y == SENT || v.z == SENT || v.w == SENT) && spin < SPIN_TOT);
              sts128(sb + OFF_M + tid * 16 + k * 2048, v);
            }
          }
          fence_async();
          bar_sync(NB_C, 128);
          redo = fresh(1);
          goto retry;
        }
        TSV(i, 36, redo);
        const uint32_t rb1 = mapa(sb, (rank + 1) % 3), rb2 = mapa(sb, (rank + 2) % 3);
        wg_wait<0>();
        TS(i, 6);
        if (wu < 2) {
          float y[10];
#pragma unroll
          for (int j = 0; j < 5; j++) { y[2 * j] = x[4 * j]; y[2 * j + 1] = x[4 * j + 1]; }
          const uint4 h0 = make_uint4(pack_h2(y[0], y[1]), pack_h2(y[2], y[3]), pack_h2(y[4], y[5]), pack_h2(y[6], y[7]));
          const uint32_t h1 = pack_h2(y[8], y[9]);
          st_async4u(rb1 + OFF_XM + 1024 + tid * 16, h0, rb1 + BAR_XM);
          st_async4u(rb2 + OFF_XM + tid * 16, h0, rb2 + BAR_XM);
          st_async1u(rb1 + OFF_XM + 2304 + tid * 4, h1, rb1 + BAR_XM);
          st_async1u(rb2 + OFF_XM + 2048 + tid * 4, h1, rb2 + BAR_XM);
          CBAR_ARRIVE(NB_SM, 256);
          if ((tid & 31) == 0) mbar_arrive_cluster(mapa(sb, 0) + BAR_E);
          TS(i, 7);
          const uint32_t sw = (tid & 7) * 4 + (tid & 8) * 8 + (tid & 16) * 2;
          mwait(sb + BAR_XM, ph, spin);
          TS(i, 8);
          const uint4 u0 = lds128(sb + OFF_XM + tid * 16), v0 = lds128(sb + OFF_XM + 1024 + tid * 16);
          const uint32_t u1 = lds32(sb + OFF_XM + 2048 + tid * 4), v1 = lds32(sb + OFF_XM + 2304 + tid * 4);
          add_h2(y[0], y[1], u0.x, v0.x); add_h2(y[2], y[3], u0.y, v0.y); add_h2(y[4], y[5], u0.z, v0.z); add_h2(y[6], y[7], u0.w, v0.w);
          add_h2(y[8], y[9], u1, v1);
          const float mx = quad_max(max10(y)) * -SCE;
#pragma unroll
          for (int j = 0; j < 5; j++) {
            y[2 * j] = ex2(fmaf(y[2 * j], SCE, mx)); y[2 * j + 1] = ex2(fmaf(y[2 * j + 1], SCE, mx));
            sts32(sb + OFF_PT + wu * 640 + sw + j * 128, pack_bf16(y[2 * j], y[2 * j + 1]));
          }
          sts32(sb + OFF_XM + 2048 + wu * 128 + sw, __float_as_uint(sum10(y)));
          fence_async();
          TS(i, 9);
        } else {
          CBAR_ARRIVE(NB_SM, 256);
          if ((tid & 31) == 0) mbar_arrive_cluster(mapa(sb, 0) + BAR_E);
          mwait(sb + BAR_MF, ph, spin);
        }
      }
      CBAR_SYNC(NB_VA, 256);
      TSB(i, 10);
      {
        float o[2][4];
        wg_fence();
#pragma unroll
        for (int c = 0; c < 2; c++)
#pragma unroll
          for (int q = 0; q < 3; q++)
            wgmma_ss8(o[c], mkdesc_ns(SB0 + OFF_VT + 128 + c * 640 + q * 256, 128, VS), mkdesc_ns(SB0 + OFF_PT + c * 640 + q * 256, q == 2 && c == 0 ? 768 : 128, 128), q);
        wg_commit();
        const float4 e = lds128f(sb + OFF_XM + 2048 + (tid & 15) * 16);
        const uint32_t rb1 = mapa(sb, (rank + 1) % 3), rb2 = mapa(sb, (rank + 2) % 3);
        const float inv = rcp((e.x + e.y) + (e.z + e.w));
        const int sl = (tid & 3) * 2;
        const float i0 = __shfl_sync(0xffffffffu, inv, sl), i1 = __shfl_sync(0xffffffffu, inv, sl + 1);
        const float i2 = __shfl_sync(0xffffffffu, inv, sl + 8), i3 = __shfl_sync(0xffffffffu, inv, sl + 9);
        wg_wait<0>();
        TS(i, 11);
        const uint32_t p0 = pack_bf16(o[0][0] * i0, o[0][1] * i1), p1 = pack_bf16(o[1][0] * i2, o[1][1] * i3);
        const uint32_t p2 = pack_bf16(o[0][2] * i0, o[0][3] * i1), p3 = pack_bf16(o[1][2] * i2, o[1][3] * i3);
        if (OGF) { sts64(sb + oo + og_off(0), p0, p1); sts64(sb + oo + og_off(0) + 256, p2, p3); fence_async(); }
        st_async2u(rb1 + oo + og_off(2), p0, p1, rb1 + BAR_OG);
        st_async2u(rb2 + oo + og_off(1), p0, p1, rb2 + BAR_OG);
        st_async2u(rb1 + oo + og_off(2) + 256, p2, p3, rb1 + BAR_OG);
        st_async2u(rb2 + oo + og_off(1) + 256, p2, p3, rb2 + BAR_OG);
        if (!OGF) { sts64(sb + oo + og_off(0), p0, p1); sts64(sb + oo + og_off(0) + 256, p2, p3); fence_async(); }
      }
      CBAR_SYNC(NB_A, 128);
      TSB(i, 12);
      {
        float acc[3][8];
        wg_fence();
        wo_block<0, 0>(acc[2], wf);
        wg_commit();
        wo_block<1, 0>(acc[0], wf);
        wo_block<4, 0>(acc[1], wf);
        wg_commit();
        const bool og = mbar_try(sb + BAR_OG, ph);
        const uint32_t tag = (i >> 1) & 1;
#define TAGGED(LO, HI) ((pack_bf16(LO, HI) & ~1u) | tag)
#define SEND(OFF, U) st_relaxed128(mkptr(mo, ehi) + (OFF), TAGGED(acc[U][0], acc[U][2]), pack_bf16(acc[U][1], acc[U][3]), pack_bf16(acc[U][4], acc[U][6]), pack_bf16(acc[U][5], acc[U][7]))
        wg_wait<1>();
        const uint32_t n0 = pin(TAGGED(acc[2][0], acc[2][2])), n1 = pin(pack_bf16(acc[2][1], acc[2][3]));
        const uint32_t n2 = pin(TAGGED(acc[2][4], acc[2][6])), n3 = pin(pack_bf16(acc[2][5], acc[2][7]));
        if (__builtin_expect(!og, 0)) mwait(sb + BAR_OG, ph, spin);
        asm volatile("fence.proxy.async::generic.acquire.sync_restrict::shared::cluster.cluster;" ::: "memory");
        TS(i, 13);
        wg_fence();
        wo_block<2, 1>(acc[0], wf); wo_block<3, 2>(acc[0], wf);
        wg_commit();
        st_relaxed64(mkptr(m9, ehi), n0, n1);
        st_relaxed64(mkptr(m9, ehi) + 3072, n2, n3);
        if ((tid & 31) == 0) mbar_arrive_cluster(mapa(sb, 1) + BAR_E + 8);
        wo_block<5, 1>(acc[1], wf); wo_block<6, 2>(acc[1], wf);
        wg_commit();
        wo_block<7, 0>(acc[2], wf);
        wg_commit();
        wg_wait<2>(); SEND(0, 0);
        wo_block<8, 1>(acc[2], wf); wo_block<9, 2>(acc[2], wf);
        wg_commit();
        if (WOE == 0) { CBAR_ARRIVE(NB_WV, 256); CBAR_ARRIVE(NB_WQ, 256); }
        wg_wait<2>(); SEND(32 * 2048, 1);
        if (WOE == 1) CBAR_ARRIVE(NB_WV, 256);
        wg_wait<0>(); SEND(64 * 2048, 2);
        if (WOE == 2) CBAR_ARRIVE(NB_WV, 256);
        if (WOE >= 1) CBAR_ARRIVE(NB_WQ, 256);
#undef SEND
#undef TAGGED
      }
      TS(i, 14);
      if (i + 1 >= NSTEP) break;
    }
    uint32_t t1 = clk32();
    if (i >= 0) {
      const int lane = fresh(tid0) & 31, j = lane >> 3;
      const uint8_t* mb = mkptr(elo + (ph << 20) + (t9 ? MAIL9 + (cta - 72) * 12288 + wu * 3072 : (cta < 72 ? cta : cta - 24) * 8192 + wu * 2048) + lane * 16, ehi);
      const uint32_t tag = (i >> 1) & 1;
      const bool pub = (lane & (t9 ? 6 : 4)) == 0 && !(((t9 ? cta : wu) & 1) && i + 1 == LAG) && cta < 88;
      const uint32_t dst = pin(elo + EX_M + (i + 1) * 20480 + (t9 ? (cta + 72) * 128 + wu * 32 + (j & 1) * 16 + (lane & 1) * 8 + (j >> 1) * 4
                                                                   : cta * 256 + (wu & 1) * 128 + (wu >> 1) * 64 + j * 16 + (lane & 3) * 4));
      uint8_t* flag = mkptr(elo + EX_FLAG + (i + 1) * 3072 + cta * 32 + wu * 4, ehi);
      const int osig = OSG == 1 && tid0 == 96 ? CN_O + i * 5 + min(cta / 19, 4) : -1;
      if (OSG && wu == 3) CBAR_SYNC(NB_MR, 160);
      while (clk32() - t1 < B1) {}
      TS(i + 1, 30);
      float f[8];
      int n = 0;
      if (!t9) poll_add<4>(mb, tag, f, flag, lane == 0, osig, n, spin);
      else poll_add<6>(mb, tag, f, flag, lane == 0, osig, n, spin);
      if (FLP == 1 && lane == 0) st_relaxed(flag, __float_as_uint(f[0] + f[7]) >> 1);
      t1 = clk32();
      TS(i + 1, 31); TSV(i + 1, 32, n);
      const bool h = lane & 16, q = lane & 8;
#pragma unroll
      for (int j = 0; j < 4; j++) f[j] = (h ? f[4 + j] : f[j]) + __shfl_xor_sync(0xffffffffu, h ? f[j] : f[4 + j], 16);
#pragma unroll
      for (int j = 0; j < 2; j++) f[j] = (q ? f[2 + j] : f[j]) + __shfl_xor_sync(0xffffffffu, q ? f[j] : f[2 + j], 8);
      f[0] += __shfl_xor_sync(0xffffffffu, f[0], 4); f[1] += __shfl_xor_sync(0xffffffffu, f[1], 4);
      if (t9) { f[0] += __shfl_xor_sync(0xffffffffu, f[0], 2); f[1] += __shfl_xor_sync(0xffffffffu, f[1], 2); }
      if (pub) st_relaxed(mkptr(dst, ehi), pack_bf16(f[0], f[1]));
      if (OSG == 2 && tid0 == 96) { TS1(i + 1, 38); signal_o(i, cta); TS1(i + 1, 39); }
      if (OSG == 4 && tid0 == 96) asm volatile("red.relaxed.gpu.global.add.u32 [%0],1;" ::"l"(&g_cnt[CN_O + i * 5 + min(cta / 19, 4)][0]) : "memory");
      TS(i + 1, 15);
    }
    if (wu == 0) {
      const int tid = fresh(tid0);
      const uint8_t* pp = mkptr(elo + EX_FLAG + (i + 1) * 3072 + (rank * 28 + (tid < 28 || rank == 2 ? tid : 0)) * 32, ehi);
      while (clk32() - t1 < B2) {}
      TS(i + 1, 16);
      int n = 1;
      uint4 x = ld_relaxed4(pp);
      if (tid0 == 0) mbar_expect_tx(sb + BAR_M, 20480);
      bool mok = mbar_test(sb + BAR_MOK, ph ^ 1);
      while (__any_sync(0xffffffffu, (int)(x.x | x.y | x.z | x.w) < 0 && spin < SPIN_TOT)) { x = ld_relaxed4(pp); mok = mbar_test(sb + BAR_MOK, ph ^ 1); n++; spin += 16; }
      if (!mok) mwait(sb + BAR_MOK, ph ^ 1, spin);
      TSV(i + 1, 35, n);
      TS(i + 1, 34);
      if (tid0 == 0) bulk_g2s_mc(sb + OFF_M + rank * 7168, mkptr(elo + EX_M + (i + 1) * 20480 + rank * 7168, ehi), rank == 2 ? 6144 : 7168, sb + BAR_M);
      TS(i + 1, 33);
      __syncwarp();
    }
  }
  if (spin >= SPIN_TOT) g_err = 1;
}

__global__ void __cluster_dims__(3, 1, 1) __launch_bounds__(384, 1)
k_chain(const __grid_constant__ CUtensorMap tmWq, const __grid_constant__ CUtensorMap tmWk,
        const __grid_constant__ CUtensorMap tmWv, const __grid_constant__ CUtensorMap tmWo) {
  using namespace C;
  extern __shared__ __align__(1024) uint8_t smem[];
  const uint32_t sb = smem_u32(smem);
  const int tid = threadIdx.x;
  const int wg = __shfl_sync(0xffffffffu, tid >> 7, 0);
  const int cta = uni(blockIdx.x), rank = uni(blockIdx.x % 3);

  asm volatile("griddepcontrol.launch_dependents;");
  if (tid == 0) {
    if ((sb & 0xFFFFFF) != SB0) g_err = 100;
    for (int p = 0; p < 5; p++) { mbar_init(sb + BAR_F + 8 * p, 1); mbar_init(sb + BAR_E + 8 * p, p == 2 ? 12 : 24); }
    mbar_init(sb + BAR_M, 1); mbar_init(sb + BAR_MOK, 24); mbar_init(sb + BAR_XM, 1); mbar_init(sb + BAR_XF, 2);
    mbar_init(sb + BAR_XT, 1); mbar_init(sb + BAR_MF, 8); mbar_init(sb + BAR_OG, 1); mbar_init(sb + BAR_W, 1);
    for (int p = 0; p < 5; p++) mbar_expect_tx(sb + BAR_F + 8 * p, 16384);
    for (int p = 0; p < 16; p++) sts32(sb + OFF_SAFE + 4 * p, 0);
    asm volatile("fence.mbarrier_init.release.cluster;" ::: "memory");
    fence_async();
    mbar_expect_tx(sb + BAR_W, 163840);
    const int head = cta / 3, col = head * DH + rank * 64;
    tma2d(sb + OFF_WQ, &tmWo, 576, col, sb + BAR_W);
    for (int i = 0; i < 9; i++) tma2d(sb + OFF_WQ + (i + 1) * 8192, &tmWo, (3 * rank + i / 3) * 64, head * DH + ((rank + i) % 3) * 64, sb + BAR_W);
    for (int i = 0; i < 5; i++) tma2d(sb + OFF_WK + i * 16384, &tmWv, col, i * 128, sb + BAR_W);
  }
  __syncthreads();
  asm volatile("barrier.cluster.arrive.release.aligned;" ::: "memory");
  asm volatile("barrier.cluster.wait.acquire.aligned;" ::: "memory");

  if (wg == 0) chain_a(sb, keep(tid), cta, rank);
  else if (wg == 1) chain_q(tmWq, tmWk, sb, keep(tid), cta, rank);
  else chain_v(sb, keep(tid), cta, rank);
  asm volatile("barrier.cluster.arrive.release.aligned;" ::: "memory");
  asm volatile("barrier.cluster.wait.acquire.aligned;" ::: "memory");
}

namespace W {
constexpr int NP = 25, NBC = 11, NW = NP + NBC;
constexpr int PRS = 37, PW = 43 * 2048;
constexpr int OFF_W = 0;
constexpr int OFF_R = 2 * PW;
constexpr int QRS = 35, KRS = 37;
constexpr int OFF_WV = 0, OFF_YQ = 81920, OFF_YK = OFF_YQ + (40 - QRS) * 2048, OFF_WO = OFF_YK + (40 - KRS) * 2048;
constexpr int OFF_G = OFF_WO + 39 * 2048;
constexpr int OFF_X = OFF_G + 12288;
constexpr int COL = 976;
constexpr int OFF_T = OFF_X + 8192;
constexpr int OFF_H = OFF_X + 32768;
constexpr int OFF_BAR = OFF_H + 8 * COL;
constexpr int OFF_SAFE = OFF_BAR + 192;
constexpr int SMEM = 232448;
static_assert(OFF_SAFE + 64 <= SMEM && OFF_R + 40960 <= OFF_BAR, "");
constexpr uint32_t SB0 = 1024;
constexpr int BAR_F = OFF_BAR, BAR_E = OFF_BAR + 40, BAR_G = OFF_BAR + 80, BAR_H = OFF_BAR + 120, BAR_W = OFF_BAR + 160;
constexpr int NB_G0 = 1, NB_SG = 4, NB_B = 5, NB_AS = 6, NB_PK = 8, NB_PV = 9, NB_TD = 10;
}
#define WBAR_SYNC(id, n) bar_sync(id, n)
#define WBAR_ARRIVE(id, n) bar_arrive(id, n)

__device__ __forceinline__ uint64_t rdesc(int off, int kk) { return mkdesc(W::SB0 + off + kk * 32, 16, 1024); }
__device__ __forceinline__ uint32_t frag_addr(uint32_t base, int tid) {
  const int i = (tid >> 3) & 3, r = tid & 7;
  return base + (r + (i >> 1) * 8) * 128 + (((2 * ((tid >> 5) & 3) + (i & 1)) ^ r) << 4);
}
template <int NK>
__device__ __forceinline__ void load_frags(uint32_t (&wf)[NK][4], uint32_t base, int tid) {
  const uint32_t a0 = frag_addr(base, tid);
#pragma unroll
  for (int k = 0; k < NK; k++) ldsm4t(wf[k], a0 + k * 2048);
}
__device__ __forceinline__ void red_tile(const float* d, int seg, int col0, int tid) {
  float* p = g_x + (size_t)(seg * 32 + 2 * (tid & 3)) * DM + col0 + ((tid >> 5) & 3) * 16 + ((tid >> 2) & 7) * 2;
#pragma unroll
  for (int j = 0; j < 8; j++)
    asm volatile("red.relaxed.gpu.global.add.v2.f32 [%0],{%1,%2};" ::"l"(p + ((j >> 1) * 8 + (j & 1)) * DM), "f"(d[4 * (j >> 1) + (j & 1)]), "f"(d[4 * (j >> 1) + 2 + (j & 1)]) : "memory");
}
#define FOR_SEGS(l, s)                                            \
  for (int j_ = 0; j_ < 2 * NSTEP; j_++) {                        \
    const int l = j_ & 1, s = (j_ >> 1) - l * LAG;                \
    if (s < 0 || s >= NSEG) continue;

template <int WG>
__device__ __forceinline__ void work_p(const CUtensorMap& tmWo, uint32_t sb, int pc, int tid0) {
  using namespace W;
  asm volatile("setmaxnreg.inc.sync.aligned.u32 208;");
  int spin = 0;
  const int ks = pc / 5, col0 = (pc % 5) * 128 + WG * 64;
  const uint32_t wb = sb + OFF_W + WG * PW;
  uint32_t wf[PRS][4];
#pragma unroll 1
  for (int hf = 0; hf < 2; hf++) {
    const int nk = hf ? 80 - PRS : PRS;
    if ((tid0 & 127) == 0) {
      mbar_expect_tx(sb + BAR_W + 8 * WG, nk * 2048);
      for (int i = 0; i < nk; i++) tma2d(wb + i * 2048, &tmWo, col0, ks * 19 * 64 + (i < PRS ? 2 * i + hf : PRS + i) * 16, sb + BAR_W + 8 * WG);
    }
    __syncwarp();
    mwait(sb + BAR_W + 8 * WG, hf, spin);
    permute_cols(wb, tid0 & 127, nk * 64);
    if (hf == 1 && ks < 4) for (int it = 39 * 64 + (tid0 & 127) - 64; it < 43 * 64; it += 128) {
      const uint32_t a = wb + (it >> 2) * 128 + (((2 * (it & 3)) ^ ((it >> 2) & 6)) << 4);
      if (it >= 39 * 64) { sts128(a, make_uint4(0, 0, 0, 0)); sts128(a + 16, make_uint4(0, 0, 0, 0)); }
    }
    fence_async();
    WBAR_SYNC(NB_G0 + WG, 128);
    if (hf == 0) {
      load_frags<PRS>(wf, wb, tid0);
      fence_async();
      WBAR_SYNC(NB_G0 + WG, 128);
    }
  }
#pragma unroll 1
  for (int k = 0; k < NSTEP; k++) {
    float d[32];
#pragma unroll
    for (int f = 0; f < 20; f++) {
      mwait(sb + BAR_F + 8 * (f % 5), (f / 5) & 1, spin);
      if (f == 0 && WG == 0 && pc == WW) WTS(k, 1);
      wg_fence();
#pragma unroll
      for (int kk = 0; kk < 4; kk++) {
        const int q = 4 * f + kk;
        if (q < 2 * PRS && !(q & 1)) wgmma_rs64(d, wf[q < 2 * PRS ? q >> 1 : 0], rdesc(OFF_R + (f % 5) * 8192, kk), q);
        else wgmma_ts64(d, mkdesc(SB0 + OFF_W + WG * PW + (q < 2 * PRS ? q >> 1 : q - PRS) * 2048, 8192, 1024), rdesc(OFF_R + (f % 5) * 8192, kk), 1);
        if (kk == 0 && f > 0) {
          wg_commit();
          wg_wait<1>();
          if ((tid0 & 31) == 0) mbar_arrive(sb + BAR_E + 8 * ((f - 1) % 5));
        }
      }
      wg_commit();
    }
    wg_wait<0>();
    if ((tid0 & 31) == 0) mbar_arrive(sb + BAR_E + 32);
    if (WG == 0 && pc == WW) WTS(k, 2);
    if (k < NSEG) red_tile(d, k, col0, tid0);
    if (k >= LAG) red_tile(d + 16, k - LAG, col0, tid0);
    if (WG == 0 && pc == WW) WTS(k, 13);
    WBAR_SYNC(NB_SG, 256);
    if (WG == 0) { if (tid0 == 0) csignal_t(CN_P + k, 3); __syncwarp(); }
  }
  if (spin >= SPIN_TOT) g_err = 11;
}
__device__ __forceinline__ void work_p_producer(uint32_t sb, int pc, int odd) {
  using namespace W;
  int spin = 0;
  const int ks = pc / 5;
#pragma unroll 1
  for (int k = 0; k < NSTEP; k++) {
    const uint32_t lo = k < NSEG ? 0 : 4096, len = k < LAG || k >= NSEG ? 4096 : 8192;
    const uint8_t* src = &g_o[k % ORING][ks * 19 + odd][lo];
    cwait(CN_O + k * 5 + ks, ks == 4 ? 20 : 19, spin);
    fence_async_all();
    if (pc == WW && !odd) WTS1(k, 0);
#pragma unroll
    for (int u = 0; u < 10; u++) {
      const int st = odd ? (2 * u + 1) % 5 : (2 * u) % 5, ph = odd ? ((2 * u + 1) / 5) & 1 : ((2 * u) / 5) & 1;
      mwait(sb + BAR_E + 8 * st, ph ^ 1, spin);
      if (u == 9 && odd && ks < 4) mbar_arrive(sb + BAR_F + 8 * st);
      else {
        mbar_expect_tx(sb + BAR_F + 8 * st, len);
        bulk_g2s(sb + OFF_R + st * 8192 + lo, src + u * 16384, len, sb + BAR_F + 8 * st);
      }
    }
  }
  if (spin >= SPIN_TOT) g_err = 12;
}
__device__ __forceinline__ float warp_sum(float x) {
  x = quad_sum(x);
  const float a = __shfl_xor_sync(0xffffffffu, x, 4), b = __shfl_xor_sync(0xffffffffu, x, 8), c = __shfl_xor_sync(0xffffffffu, x, 12);
  x = (x + a) + (b + c);
  return x + __shfl_xor_sync(0xffffffffu, x, 16);
}
__device__ __forceinline__ void work_ln(int kind, int r, int lane, bf16* out) {
  int spin = 0;
  const int l = kind & 1;
  const int rp = kind < 2 ? (r & 1) * 16 + (r >> 1) : r;
  const uint32_t sw = ((((lane >> 1) & 7) ^ (rp & 7)) << 4) + (lane & 1) * 8;
  uint8_t* dst = kind < 2 ? g_xnb[l * LAG] + (lane >> 4) * 8192 + l * 4096 + rp * 128 + sw
               : kind == 2 ? g_xn[1] + (r >> 3) * 2048 + (lane >> 4) * 1024 + (r & 7) * 128 + sw
                           : reinterpret_cast<uint8_t*>(out) + r * 1280 + lane * 8;
  const int dm = kind < 2 ? 16384 : kind == 2 ? 8192 : 256, ds = kind < 2 ? 81920 : 40960;
#pragma unroll 1
  for (int s = 0; s < NSEG; s++) {
    const float* xr = g_x + (size_t)(s * 32 + r) * DM;
    if (kind == 0 && lane < 20 && s + 3 < NSEG) prefetch_l2(xr + 96 * DM + lane * 32);
    if (lane == 0) cwait(kind < 2 ? CN_P + s + l * LAG : CN_W + l * 64 + s, kind < 2 ? W::NP : 10, spin);
    __syncwarp();
    if (r == 0 && lane == 0 && (l == 0 || s + LAG >= NSEG)) WTS1(s + l * LAG, kind < 2 ? 3 : 11);
    float4 v[5];
#pragma unroll
    for (int m = 0; m < 5; m++) v[m] = ld_relaxed4f(xr + m * 128 + lane * 4);
    if (kind < 3) {
      float t = 0.f;
#pragma unroll
      for (int m = 0; m < 5; m++) t += (v[m].x + v[m].y) + (v[m].z + v[m].w);
      const float mean = warp_sum(t) * (1.f / DM);
      float q0 = 0.f, q1 = 0.f;
#pragma unroll
      for (int m = 0; m < 5; m++) {
        v[m].x -= mean; v[m].y -= mean; v[m].z -= mean; v[m].w -= mean;
        q0 += v[m].x * v[m].x + v[m].y * v[m].y; q1 += v[m].z * v[m].z + v[m].w * v[m].w;
      }
      const float rs = rsqrtf(warp_sum(q0 + q1) * (1.f / DM) + 1e-5f);
#pragma unroll
      for (int m = 0; m < 5; m++) { v[m].x *= rs; v[m].y *= rs; v[m].z *= rs; v[m].w *= rs; }
    }
#pragma unroll
    for (int m = 0; m < 5; m++) *reinterpret_cast<uint2*>(dst + (size_t)s * ds + m * dm) = make_uint2(pack_bf16(v[m].x, v[m].y), pack_bf16(v[m].z, v[m].w));
    __syncwarp();
    if (r == 0 && lane == 0 && (l == 0 || s + LAG >= NSEG)) WTS1(s + l * LAG, kind < 2 ? 4 : 12);
    if (lane == 0 && kind < 3) csignal_t(kind < 2 ? CN_L + s + l * LAG : CN_X + s, kind);
  }
  if (spin >= SPIN_TOT) g_err = 13;
}

__device__ __forceinline__ void stage_qkv(const bf16* wqkv, uint32_t base, int T, int bc, int tid) {
  const int q = tid & 15;
  const bool ok = q < 15 && bc * 60 + 4 * q < DM;
  const bf16* src = wqkv + T * DM + bc * 60 + 4 * q;
#pragma unroll 1
  for (int k0 = tid >> 4; k0 < 640; k0 += 80) {
    uint2 v[10];
#pragma unroll
    for (int u = 0; u < 10; u++) v[u] = ok ? *reinterpret_cast<const uint2*>(src + (size_t)(k0 + 8 * u) * 1920) : make_uint2(0, 0);
#pragma unroll
    for (int u = 0; u < 10; u++) sts64(base + (k0 + 8 * u) * 128 + (((q >> 1) ^ (k0 & 7)) << 4) + (q & 1) * 8, v[u].x, v[u].y);
  }
}
__device__ __forceinline__ void attend(uint32_t sb, int bc, int l, int s, int p, int tid) {
  using namespace W;
  const int r = tid & 7, m = (tid >> 3) & 3, hh = (tid >> 5) & 3, g = (tid >> 2) & 7, t = tid & 3;
  const int f2 = r < 4 ? 20 * hh + 16 + r : 60;
  const uint32_t tb = sb + OFF_T + (l * 4 + 2 * p) * COL, hb = sb + OFF_H + (l * 2 + p) * COL;
  const uint32_t ko = (m < 2 ? 20 * hh + 8 * m + r : f2) * 16, vo = (m < 2 ? 20 * hh + 4 * (r >> 1) + 2 * m + (r & 1) : f2) * 16;
  const float scl = 0.22360679774997896f * 1.4426950408889634f;
  float sc[3][4];
  {
    uint32_t q[4], q8a, q8b, k[3][4];
    ldsm4t(q, tb + (m & 1) * COL + (20 * hh + (m >> 1) * 8 + r) * 16);
    ldsm2t(q8a, q8b, tb + (m & 1) * COL + f2 * 16);
    ldsm4t(k[0], hb + ko); ldsm4t(k[1], tb + 8 * COL + ko); ldsm4t(k[2], tb + 9 * COL + ko);
#pragma unroll
    for (int c = 0; c < 3; c++) { sc[c][0] = sc[c][1] = sc[c][2] = sc[c][3] = 0.f; mma16816(sc[c], q[0], q[1], q[2], q[3], k[c][0], k[c][1]); }
#pragma unroll
    for (int c = 0; c < 3; c++) mma1688(sc[c], q8a, q8b, k[c][2]);
  }
  uint32_t v[3][4];
  ldsm4(v[0], hb + 4 * COL + vo); ldsm4(v[1], tb + 16 * COL + vo); ldsm4(v[2], tb + 17 * COL + vo);
  const bool lo0 = 2 * t > g, lo1 = 2 * t + 1 > g;
  uint32_t pw[2];
  float inv[2];
#pragma unroll
  for (int h = 0; h < 2; h++) {
    float y0 = lo0 ? sc[h][2 * h] : sc[h + 1][2 * h], y1 = lo1 ? sc[h][2 * h + 1] : sc[h + 1][2 * h + 1];
    if (h == 0 && s == 0) { y0 = lo0 ? -INFINITY : y0; y1 = lo1 ? -INFINITY : y1; }
    const float mx = quad_max(fmaxf(y0, y1)) * -scl;
    pw[h] = pack_bf16(ex2(fmaf(y0, scl, mx)), ex2(fmaf(y1, scl, mx)));
    inv[h] = bf_lo(pw[h]) + bf_hi(pw[h]);
  }
  const uint32_t ml = (lo0 ? 0xFFFFu : 0u) | (lo1 ? 0xFFFF0000u : 0u);
  float o[3][4];
#pragma unroll
  for (int j = 0; j < 3; j++) { o[j][0] = o[j][1] = o[j][2] = o[j][3] = 0.f; mma16816(o[j], pw[0] & ml, 0u, pw[0] & ~ml, pw[1] & ml, v[0][j], v[1][j]); }
#pragma unroll
  for (int j = 0; j < 3; j++) mma1688(o[j], 0u, pw[1] & ~ml, v[2][j]);
  inv[0] = rcp(quad_sum(inv[0])); inv[1] = rcp(quad_sum(inv[1]));
  const uint32_t ca = (bc * 3 + hh) * 20 + 4 * t, cb = ca + 16 - 2 * t, row = 2 * g + p;
  uint8_t* img = g_ob[l] + (size_t)s * 40960 + row * 128;
  const uint32_t oa = (ca >> 6) * 4096 + (((ca >> 3) ^ row) & 7) * 16 + (ca & 4) * 2, ob = (cb >> 6) * 4096 + (((cb >> 3) ^ row) & 7) * 16 + (cb & 6) * 2;
#pragma unroll
  for (int h = 0; h < 2; h++) {
    *reinterpret_cast<uint2*>(img + oa + h * 2048) = make_uint2(pack_bf16(o[0][2 * h] * inv[h], o[0][2 * h + 1] * inv[h]), pack_bf16(o[1][2 * h] * inv[h], o[1][2 * h + 1] * inv[h]));
    if (t < 2) *reinterpret_cast<uint32_t*>(img + ob + h * 2048) = pack_bf16(o[2][2 * h] * inv[h], o[2][2 * h + 1] * inv[h]);
  }
}
template <int WG>
__device__ __forceinline__ void work_b(const bf16* wqkv, uint32_t sb, int bc, int tid0) {
  using namespace W;
  if (WG == 0) asm volatile("setmaxnreg.inc.sync.aligned.u32 232;");
  else asm volatile("setmaxnreg.inc.sync.aligned.u32 208;");
  constexpr int NR = WG ? KRS : QRS, OFF_Y = WG ? OFF_YK : OFF_YQ;
  int spin = 0;
  const uint32_t wb = sb + (WG ? OFF_WO : OFF_WV);
  uint32_t wf[NR][4];
  stage_qkv(wqkv, wb, WG, bc, tid0 & 127);
  WBAR_SYNC(NB_G0 + WG, 128);
  load_frags<NR>(wf, wb, tid0);
#pragma unroll
  for (int k = NR; k < 40; k++) sts128(sb + OFF_Y + (k - NR) * 2048 + (tid0 & 127) * 16, lds128(wb + k * 2048 + (tid0 & 127) * 16));
  fence_async();
  if (WG == 1) WBAR_ARRIVE(NB_PK, 256);
  WBAR_SYNC(NB_G0 + WG, 128);
  if (WG == 0) {
    stage_qkv(wqkv, wb, 2, bc, tid0);
    fence_async();
    WBAR_SYNC(NB_G0, 128);
  }
#pragma unroll 1
  for (int k = 0; k < NSTEP; k++) {
    uint32_t hist[8];
    {
      float d[32], e[32];
#pragma unroll
      for (int c = 0; c < 10; c++) {
        mwait(sb + BAR_F + 8 * (c % 4), ((c % 4 < 2 ? k : 0) + c / 4) & 1, spin);
        if (c == 0 && bc == 0) WTS(k, WG ? 15 : 6);
        wg_fence();
#pragma unroll
        for (int kk = 0; kk < 4; kk++) {
          const int q = 4 * c + kk;
          const uint64_t db = rdesc(OFF_X + (c % 4) * 8192, kk);
          if (q < NR) wgmma_rs64(d, wf[q < NR ? q : 0], db, q);
          else wgmma_ts64(d, mkdesc(SB0 + OFF_Y + (q - NR) * 2048, 8192, 1024), db, 1);
          if (WG == 0) wgmma_ts64(e, mkdesc(SB0 + OFF_WV + q * 2048, 8192, 1024), db, q);
          if (kk == 0 && c > 0 && (c <= 6 || c == 9)) {
            wg_commit();
            wg_wait<1>();
            if ((tid0 & 31) == 0) mbar_arrive(sb + BAR_E + 8 * ((c - 1) % 4));
          }
        }
        wg_commit();
      }
      wg_wait<0>();
      if (bc == 0) WTS(k, 16 + WG);
      WBAR_SYNC(NB_B, 256);
      const int tid = fresh(tid0), m = (tid >> 3) & 3;
      const uint32_t a = sb + OFF_T + min(((tid >> 5) & 3) * 16 + (m & 1) * 8 + (tid & 7), 60) * 16 + (m >> 1) * COL;
      const float (&x)[32] = WG ? d : e;
#pragma unroll
      for (int p = 0; p < 4; p++) {
        hist[2 * p] = pack_bf16(x[8 * p + 4], x[8 * p + 5]); hist[2 * p + 1] = pack_bf16(x[8 * p + 6], x[8 * p + 7]);
        stsm4(a + (16 - 8 * WG + 2 * p) * COL, pack_bf16(x[8 * p], x[8 * p + 1]), pack_bf16(x[8 * p + 2], x[8 * p + 3]), hist[2 * p], hist[2 * p + 1]);
        if (WG == 0)
          stsm4(a + 2 * p * COL, pack_bf16(d[8 * p], d[8 * p + 1]), pack_bf16(d[8 * p + 2], d[8 * p + 3]), pack_bf16(d[8 * p + 4], d[8 * p + 5]), pack_bf16(d[8 * p + 6], d[8 * p + 7]));
      }
    }
    WBAR_SYNC(NB_TD, 288);
    if (bc == 0 && WG == 0) WTS(k, 7);
#pragma unroll 1
    for (int l = 0; l < 2; l++) {
      const int tid = fresh(tid0), hh = uni((tid >> 5) & 3), s = k - l * LAG;
      if (hh < 3 && bc * 3 + hh < NH && s >= 0 && s < NSEG) attend(sb, bc, l, s, WG, tid);
      if (bc == 0 && WG == 0 && (l == 0 || k >= NSEG)) WTS(k, 8);
      if (l == 0) WBAR_ARRIVE(NB_AS, 288); else WBAR_ARRIVE(NB_AS + 1, 288);
    }
    WBAR_SYNC(NB_B, 256);
    {
      const int tid = fresh(tid0), m = (tid >> 3) & 3;
      const uint32_t a = sb + OFF_H + min(((tid >> 5) & 3) * 16 + (m & 1) * 8 + (tid & 7), 60) * 16 + (4 - 4 * WG + (m >> 1)) * COL;
      stsm4(a, hist[0], hist[1], hist[2], hist[3]);
      if (k >= LAG) stsm4(a + 2 * COL, hist[4], hist[5], hist[6], hist[7]);
      fence_async();
      if ((tid & 31) < 3) mbar_arrive(sb + BAR_E + 8 + 8 * (tid & 3));
    }
  }
  if (spin >= SPIN_TOT) g_err = 14;
}
__device__ __forceinline__ void work_wo(const CUtensorMap& tmBo, uint32_t sb, int bc, int tid0) {
  using namespace W;
  int spin = 0;
  WBAR_SYNC(NB_PK, 256);
  if (bc == 10) return;
  if ((tid0 & 127) == 0) {
    mbar_expect_tx(sb + BAR_W, 81920);
    for (int i = 0; i < 10; i++) tma2d(sb + OFF_WO + i * 8192, &tmBo, bc * 64, i * 64, sb + BAR_W);
  }
  __syncwarp();
  mwait(sb + BAR_W, 0, spin);
  permute_cols(sb + OFF_WO, tid0 & 127, 2560);
  WBAR_SYNC(NB_G0 + 2, 128);
  uint32_t wl[4];
  ldsm4t(wl, frag_addr(sb + OFF_WO + 39 * 2048, tid0));
  fence_async();
  WBAR_SYNC(NB_PV, 160);
  uint32_t n = 0;
  FOR_SEGS(l, s)
    float d[16];
#pragma unroll
    for (int c = 0; c < 10; c++) {
      mwait(sb + BAR_G + 8 * (c % 3), ((c % 3 ? n : 0) + c / 3) & 1, spin);
      if ((c == 0 || c == 9) && bc == 0 && (l == 0 || s + LAG >= NSEG)) WTS(s + l * LAG, c ? 21 : 20);
      wg_fence();
#pragma unroll
      for (int kk = 0; kk < 4; kk++) {
        if (c == 9 && kk == 3) wgmma_rs32(d, wl, rdesc(OFF_G + (c % 3) * 4096, kk), 1);
        else wgmma_ts32(d, mkdesc(SB0 + OFF_WO + (4 * c + kk) * 2048, 8192, 1024), rdesc(OFF_G + (c % 3) * 4096, kk), c | kk);
      }
      wg_commit();
      wg_wait<0>();
      if ((tid0 & 31) == 0) mbar_arrive(sb + BAR_H + 8 * (c % 3));
    }
    if (bc == 0 && (l == 0 || s + LAG >= NSEG)) WTS(s + l * LAG, 10);
    red_tile(d, s, bc * 64, tid0);
    WBAR_SYNC(NB_SG, 160);
    n++;
  }
  if (spin >= SPIN_TOT) g_err = 17;
}
__device__ __forceinline__ void work_x_producer(uint32_t sb, int bc) {
  using namespace W;
  int spin = 0;
#pragma unroll 1
  for (int k = 0; k < NSTEP; k++) {
    const uint32_t lo = k < NSEG ? 0 : 4096, len = k < LAG || k >= NSEG ? 4096 : 8192;
    const uint8_t* src = g_xnb[k] + lo;
    cwait(CN_L + k, len >> 7, spin);
    fence_async_all();
    if (bc == 0) WTS1(k, 5);
#pragma unroll
    for (int c = 0; c < 10; c++) {
      mwait(sb + BAR_E + 8 * (c % 4), (((c % 4 < 2 ? k : 0) + c / 4) & 1) ^ 1, spin);
      mbar_expect_tx(sb + BAR_F + 8 * (c % 4), len);
      bulk_g2s(sb + OFF_X + (c % 4) * 8192 + lo, src + c * 8192, len, sb + BAR_F + 8 * (c % 4));
    }
  }
  if (spin >= SPIN_TOT) g_err = 15;
}
__device__ __forceinline__ void work_g_producer(uint32_t sb, int bc) {
  using namespace W;
  int spin = 0;
  uint32_t n = 0;
  FOR_SEGS(l, s)
    const uint8_t* src = g_ob[l] + (size_t)s * 40960;
    cwait(CN_A + l * 64 + s, NBC, spin);
    fence_async_all();
    if (bc == 0 && (l == 0 || s + LAG >= NSEG)) WTS1(s + l * LAG, 9);
#pragma unroll
    for (int c = 0; c < 10; c++) {
      mwait(sb + BAR_H + 8 * (c % 3), (((c % 3 ? n : 0) + c / 3) & 1) ^ 1, spin);
      mbar_expect_tx(sb + BAR_G + 8 * (c % 3), 4096);
      bulk_g2s(sb + OFF_G + (c % 3) * 4096, src + c * 4096, 4096, sb + BAR_G + 8 * (c % 3));
    }
    n++;
  }
  if (spin >= SPIN_TOT) g_err = 16;
}

__global__ void __launch_bounds__(512, 1)
k_work(const __grid_constant__ CUtensorMap tmWo, const __grid_constant__ CUtensorMap tmBo, const bf16* __restrict__ wqkv, bf16* __restrict__ out) {
  using namespace W;
  extern __shared__ __align__(1024) uint8_t smem[];
  const uint32_t sb = smem_u32(smem);
  const int tid = threadIdx.x, w = blockIdx.x;
  const int wg = __shfl_sync(0xffffffffu, tid >> 7, 0);
  if (tid == 0) {
    if (sb != SB0) g_err = 101;
    for (int i = 0; i < 5; i++) { mbar_init(sb + BAR_F + 8 * i, 1); mbar_init(sb + BAR_E + 8 * i, 8); mbar_init(sb + BAR_G + 8 * i, 1); mbar_init(sb + BAR_H + 8 * i, 4); }
    mbar_init(sb + BAR_W, 1); mbar_init(sb + BAR_W + 8, 1);
    for (int p = 0; p < 16; p++) sts32(sb + OFF_SAFE + 4 * p, 0);
    asm volatile("fence.mbarrier_init.release.cluster;" ::: "memory");
  }
  if (tid < 8 * COL / 16) sts128(sb + OFF_H + tid * 16, make_uint4(0, 0, 0, 0));
  fence_async();
  __syncthreads();

  if (w < NP) {
    if (wg == 0) work_p<0>(tmWo, sb, w, keep(tid));
    else if (wg == 1) work_p<1>(tmWo, sb, w, keep(tid));
    else {
      asm volatile("setmaxnreg.dec.sync.aligned.u32 48;");
      const int aw = (tid >> 5) - 8;
      if (aw < 2) {
        if ((tid & 31) == 0) work_p_producer(sb, w, aw);
      } else {
        const int id = (aw - 2) * NP + w;
        if (id < 128) work_ln(id & 3, id >> 2, tid & 31, out);
      }
    }
  } else {
    const int bc = w - NP;
    if (wg == 0) work_b<0>(wqkv, sb, bc, keep(tid));
    else if (wg == 1) work_b<1>(wqkv, sb, bc, keep(tid));
    else if (wg == 2) {
      asm volatile("setmaxnreg.dec.sync.aligned.u32 48;");
      work_wo(tmBo, sb, bc, keep(tid));
    } else {
      asm volatile("setmaxnreg.dec.sync.aligned.u32 24;");
      if (tid < 416) {
        if (tid == 384) work_x_producer(sb, bc);
      } else if (tid < 448) {
        if (bc < 10) {
          WBAR_SYNC(NB_PV, 160);
          if (tid == 416) work_g_producer(sb, bc);
        }
      } else if (tid < 480) {
        for (int k = 0; k < NSTEP; k++) {
          WBAR_SYNC(NB_TD, 288);
          WBAR_SYNC(NB_AS, 288);
          if (tid == 448 && k < NSEG) csignal_t(CN_A + k, 5);
          __syncwarp();
          WBAR_SYNC(NB_AS + 1, 288);
          if (tid == 448 && k >= LAG) csignal_t(CN_A + 64 + k - LAG, 4);
          __syncwarp();
        }
      } else if (bc < 10) {
        FOR_SEGS(l, s)
          WBAR_SYNC(NB_SG, 160);
          if (tid == 480) csignal_t(CN_W + l * 64 + s, 6);
          __syncwarp();
        }
      }
    }
  }
  __syncthreads();
  asm volatile("griddepcontrol.wait;" ::: "memory");
}

typedef CUresult (*EncodeFn)(CUtensorMap*, CUtensorMapDataType, cuuint32_t, void*, const cuuint64_t*, const cuuint64_t*,
                             const cuuint32_t*, const cuuint32_t*, CUtensorMapInterleave, CUtensorMapSwizzle,
                             CUtensorMapL2promotion, CUtensorMapFloatOOBfill);

static void make_map(EncodeFn enc, CUtensorMap* tm, const void* ptr, uint64_t cols, uint64_t rows, uint32_t boxc, uint32_t boxr) {
  cuuint64_t dims[2] = {cols, rows};
  cuuint64_t strides[1] = {cols * 2};
  cuuint32_t box[2] = {boxc, boxr};
  cuuint32_t es[2] = {1, 1};
  enc(tm, CU_TENSOR_MAP_DATA_TYPE_BFLOAT16, 2, const_cast<void*>(ptr), dims, strides, box, es, CU_TENSOR_MAP_INTERLEAVE_NONE,
      CU_TENSOR_MAP_SWIZZLE_128B, CU_TENSOR_MAP_L2_PROMOTION_L2_256B, CU_TENSOR_MAP_FLOAT_OOB_FILL_NONE);
}

extern "C" void kernel_launch(void* const* d_in, const int* in_sizes, int n_in, void* d_out, int out_size) {
  const bf16* x0 = (const bf16*)d_in[0];
  const bf16* mem0 = (const bf16*)d_in[1];
  const bf16* Wq = (const bf16*)d_in[2];
  const bf16* Wk = (const bf16*)d_in[3];
  const bf16* Wv = (const bf16*)d_in[4];
  const bf16* Wo = (const bf16*)d_in[5];
  const bf16* Bqkv = (const bf16*)d_in[8];
  const bf16* Bwo = (const bf16*)d_in[9];
  bf16* out = (bf16*)d_out;

  static EncodeFn enc = nullptr;
  if (!enc) {
    void* fn = nullptr;
    cudaDriverEntryPointQueryResult qr;
    cudaGetDriverEntryPoint("cuTensorMapEncodeTiled", &fn, cudaEnableDefault, &qr);
    enc = (EncodeFn)fn;
    cudaFuncSetAttribute(k_chain, cudaFuncAttributeMaxDynamicSharedMemorySize, C::SMEM);
    cudaFuncSetAttribute(k_work, cudaFuncAttributeMaxDynamicSharedMemorySize, W::SMEM);
  }
  CUtensorMap tmWq, tmWk, tmWv, tmWo, tmWp, tmBo;
  make_map(enc, &tmWq, Wq, NH * DH, DM, 64, 128);
  make_map(enc, &tmWk, Wk, NH * DH, DM, 64, 128);
  make_map(enc, &tmWv, Wv, NH * DH, DM, 64, 128);
  make_map(enc, &tmWo, Wo, DM, NH * DH, 64, 64);
  make_map(enc, &tmWp, Wo, DM, NH * DH, 64, 16);
  make_map(enc, &tmBo, Bwo, DM, DM, 64, 64);

  cudaStream_t st = cudaStreamPerThread;
  k_pre<<<256, 256, 0, st>>>(x0, mem0);
  cudaLaunchAttribute at[1];
  at[0].id = cudaLaunchAttributeProgrammaticStreamSerialization; at[0].val.programmaticStreamSerializationAllowed = 1;
  {
    cudaLaunchConfig_t cfg = {};
    cfg.gridDim = dim3(96); cfg.blockDim = dim3(384); cfg.dynamicSmemBytes = C::SMEM; cfg.stream = st;
    cfg.attrs = at; cfg.numAttrs = 0;
    cudaLaunchKernelEx(&cfg, k_chain, tmWq, tmWk, tmWv, tmWo);
  }
  cudaLaunchConfig_t cfg = {};
  cfg.gridDim = dim3(W::NW); cfg.blockDim = dim3(512); cfg.dynamicSmemBytes = W::SMEM; cfg.stream = st;
  cfg.attrs = at; cfg.numAttrs = NOWORK == 2 ? 0 : 1;
  cudaLaunchKernelEx(&cfg, k_work, tmWp, tmBo, Bqkv, out);
}
```

```cpp
#include <cuda_runtime.h>
#include <cuda_bf16.h>
#include <cuda.h>
#include <stdint.h>

typedef __nv_bfloat16 bf16;

constexpr int SEQ = 2048, DM = 640, NH = 32, DH = 192, NSEG = 64;
#define LAG 7
constexpr int NSTEP = NSEG + LAG;
constexpr uint32_t SENT = 0xFFFFFFFFu;

constexpr int MAIL9 = 288 * 2048, MAIL_BYTES = MAIL9 + 64 * 3072;
__device__ __align__(1024) uint8_t g_xn[2][NSEG * 40960];
__device__ __align__(1024) uint8_t g_xnb[NSTEP][81920];
__device__ __align__(1024) uint8_t g_ob[2][NSEG * 40960];
#define ORING 8
static_assert(ORING > LAG, "a slot is free again LAG + 1 steps later");
__device__ __align__(1024) uint8_t g_o[ORING][96][8192];
__device__ __align__(1024) float g_x[SEQ * DM];
constexpr int EX_MAIL = 0;
constexpr int EX_M = 2 << 20;
constexpr int EX_FLAG = EX_M + NSTEP * 20480;
__host__ __device__ constexpr int m_kstep(int j) {
  return j < 24 ? (3 * ((j % 12) / 4) + j / 12) * 4 + j % 4 : j < 26 ? 12 + j : j < 38 ? (3 * ((j - 26) / 4) + 2) * 4 + (j - 26) % 4 : j;
}
__host__ __device__ constexpr int m_wave(int u) { return u == 0 ? 0 : u == 1 ? 12 : u == 2 ? 26 : 40; }
static_assert(EX_FLAG + NSTEP * 3072 <= (4 << 20), "");
__device__ __align__(1024) uint8_t g_ex[8 << 20];
__host__ __device__ __forceinline__ uint8_t* ex_window(uint8_t* p) { return reinterpret_cast<uint8_t*>((reinterpret_cast<uint64_t>(p) + (4 << 20) - 1) & ~(uint64_t)((4 << 20) - 1)); }
enum { CN_P = 0, CN_L = 128, CN_A = 256, CN_W = 384, CN_X = 512, CN_O = 576, CN_NUM = CN_O + 5 * NSTEP };
__device__ __align__(128) uint32_t g_cnt[CN_NUM][32];
__device__ int g_err;
#define TS(jj, i)
#define TS1(jj, i)
#define PTS(i)
#define TSB(jj, i)
#define TSV(jj, i, v)
#define TS_FLUSH(jj)
#define WTS(b, k)
#define WTS1(b, k)
#define WW -1

__device__ __forceinline__ uint32_t smem_u32(const void* p) { return (uint32_t)__cvta_generic_to_shared(p); }
__device__ __forceinline__ uint32_t clk32() { uint32_t t; asm volatile("mov.u32 %0, %%clock;" : "=r"(t)::"memory"); return t; }
__device__ __forceinline__ uint32_t mapa(uint32_t a, uint32_t r) { uint32_t o; asm("mapa.shared::cluster.u32 %0,%1,%2;" : "=r"(o) : "r"(a), "r"(r)); return o; }
__device__ __forceinline__ void mbar_init(uint32_t bar, uint32_t cnt) { asm volatile("mbarrier.init.shared::cta.b64 [%0],%1;" ::"r"(bar), "r"(cnt) : "memory"); }
__device__ __forceinline__ void mbar_expect_tx(uint32_t bar, uint32_t bytes) { asm volatile("mbarrier.arrive.expect_tx.shared::cta.b64 _,[%0],%1;" ::"r"(bar), "r"(bytes) : "memory"); }
__device__ __forceinline__ void mbar_arrive(uint32_t bar) { asm volatile("mbarrier.arrive.shared::cta.b64 _,[%0];" ::"r"(bar) : "memory"); }
__device__ __forceinline__ void mbar_arrive_cluster(uint32_t bar) { asm volatile("mbarrier.arrive.shared::cluster.b64 _,[%0];" ::"r"(bar) : "memory"); }
__device__ __forceinline__ bool mbar_try(uint32_t bar, uint32_t ph) {
  uint32_t ok;
  asm volatile("{.reg .pred p; mbarrier.try_wait.parity.shared::cta.b64 p,[%1],%2; selp.u32 %0,1,0,p;}" : "=r"(ok) : "r"(bar), "r"(ph) : "memory");
  return ok;
}
__device__ __forceinline__ bool mbar_test(uint32_t bar, uint32_t ph) {
  uint32_t ok;
  asm volatile("{.reg .pred p; mbarrier.test_wait.parity.shared::cta.b64 p,[%1],%2; selp.u32 %0,1,0,p;}" : "=r"(ok) : "r"(bar), "r"(ph) : "memory");
  return ok;
}
__device__ __forceinline__ int fresh(int x) { asm volatile("" : "+r"(x)); return x; }
#define PHASE_IDS const int tid = fresh(tid0), lane = tid & 31, w = tid >> 5, g = lane >> 2, t = lane & 3; (void)w; (void)g; (void)t
__device__ __forceinline__ void bar_sync(int id, int n) { asm volatile("bar.sync %0,%1;" ::"r"(id), "r"(n) : "memory"); }
__device__ __forceinline__ void bar_arrive(int id, int n) { asm volatile("bar.arrive %0,%1;" ::"r"(id), "r"(n) : "memory"); }
__device__ __forceinline__ bool bar_red_or(int id, int n, bool v) {
  uint32_t r;
  asm volatile("{\n .reg .pred p, q;\n setp.ne.u32 q, %3, 0;\n barrier.cta.red.or.pred p, %1, %2, q;\n selp.u32 %0, 1, 0, p;\n}" : "=r"(r) : "r"(id), "r"(n), "r"((uint32_t)v) : "memory");
  return r != 0;
}
__device__ __forceinline__ void fence_async() { asm volatile("fence.proxy.async.shared::cta;" ::: "memory"); }
__device__ __forceinline__ void bulk_g2s(uint32_t dst, const void* src, uint32_t bytes, uint32_t bar) {
  asm volatile("cp.async.bulk.shared::cluster.global.mbarrier::complete_tx::bytes [%0],[%1],%2,[%3];" ::"r"(dst), "l"(src), "r"(bytes), "r"(bar) : "memory");
}
__device__ __forceinline__ void bulk_g2s_mc(uint32_t dst, const void* src, uint32_t bytes, uint32_t bar) {
  asm volatile("cp.async.bulk.shared::cluster.global.mbarrier::complete_tx::bytes.multicast::cluster [%0],[%1],%2,[%3],%4;"
               ::"r"(dst), "l"(src), "r"(bytes), "r"(bar), "h"((uint16_t)7) : "memory");
}
__device__ __forceinline__ void bulk_s2g(void* dst, uint32_t src, uint32_t bytes) {
  asm volatile("cp.async.bulk.global.shared::cta.bulk_group [%0],[%1],%2;" ::"l"(dst), "r"(src), "r"(bytes) : "memory");
}
__device__ __forceinline__ void bulk_s2c(uint32_t dst, uint32_t src, uint32_t bytes, uint32_t bar) {
  asm volatile("cp.async.bulk.shared::cluster.shared::cta.mbarrier::complete_tx::bytes [%0],[%1],%2,[%3];" ::"r"(dst), "r"(src), "r"(bytes), "r"(bar) : "memory");
}
__device__ __forceinline__ void tma2d(uint32_t dst, const CUtensorMap* tm, int c0, int c1, uint32_t bar) {
  asm volatile("cp.async.bulk.tensor.2d.shared::cluster.global.mbarrier::complete_tx::bytes [%0],[%1,{%3,%4}],[%2];"
               ::"r"(dst), "l"(tm), "r"(bar), "r"(c0), "r"(c1) : "memory");
}
__device__ __forceinline__ void tma2d_prefetch(const CUtensorMap* tm, int c0, int c1) {
  asm volatile("cp.async.bulk.prefetch.tensor.2d.L2.global.tile [%0,{%1,%2}];" ::"l"(tm), "r"(c0), "r"(c1) : "memory");
}
__device__ __forceinline__ uint32_t pack_bf16(float lo, float hi) {
  uint32_t r; asm("cvt.rn.bf16x2.f32 %0,%1,%2;" : "=r"(r) : "f"(hi), "f"(lo)); return r;
}
__device__ __forceinline__ float bf_lo(uint32_t x) { return __uint_as_float(x << 16); }
__device__ __forceinline__ float bf_hi(uint32_t x) { return __uint_as_float(x & 0xFFFF0000u); }
__device__ __forceinline__ float ex2(float x) { float y; asm("ex2.approx.ftz.f32 %0,%1;" : "=f"(y) : "f"(x)); return y; }
__device__ __forceinline__ void ldsm4(uint32_t (&r)[4], uint32_t a) {
  asm volatile("ldmatrix.sync.aligned.m8n8.x4.shared.b16 {%0,%1,%2,%3},[%4];" : "=r"(r[0]), "=r"(r[1]), "=r"(r[2]), "=r"(r[3]) : "r"(a) : "memory");
}
__device__ __forceinline__ void ldsm4t(uint32_t (&r)[4], uint32_t a) {
  asm volatile("ldmatrix.sync.aligned.m8n8.x4.trans.shared.b16 {%0,%1,%2,%3},[%4];" : "=r"(r[0]), "=r"(r[1]), "=r"(r[2]), "=r"(r[3]) : "r"(a) : "memory");
}
__device__ __forceinline__ void ldsm2(uint32_t& r0, uint32_t& r1, uint32_t a) {
  asm volatile("ldmatrix.sync.aligned.m8n8.x2.shared.b16 {%0,%1},[%2];" : "=r"(r0), "=r"(r1) : "r"(a) : "memory");
}
__device__ __forceinline__ void ldsm2t(uint32_t& r0, uint32_t& r1, uint32_t a) {
  asm volatile("ldmatrix.sync.aligned.m8n8.x2.trans.shared.b16 {%0,%1},[%2];" : "=r"(r0), "=r"(r1) : "r"(a) : "memory");
}
__device__ __forceinline__ void ldsm1(uint32_t& r0, uint32_t a) {
  asm volatile("ldmatrix.sync.aligned.m8n8.x1.shared.b16 {%0},[%1];" : "=r"(r0) : "r"(a) : "memory");
}
__device__ __forceinline__ void mma16816(float (&d)[4], uint32_t a0, uint32_t a1, uint32_t a2, uint32_t a3, uint32_t b0, uint32_t b1) {
  asm volatile("mma.sync.aligned.m16n8k16.row.col.f32.bf16.bf16.f32 {%0,%1,%2,%3},{%4,%5,%6,%7},{%8,%9},{%0,%1,%2,%3};"
               : "+f"(d[0]), "+f"(d[1]), "+f"(d[2]), "+f"(d[3]) : "r"(a0), "r"(a1), "r"(a2), "r"(a3), "r"(b0), "r"(b1));
}
__device__ __forceinline__ void mma1688(float (&d)[4], uint32_t a0, uint32_t a1, uint32_t b0) {
  asm volatile("mma.sync.aligned.m16n8k8.row.col.f32.bf16.bf16.f32 {%0,%1,%2,%3},{%4,%5},{%6},{%0,%1,%2,%3};"
               : "+f"(d[0]), "+f"(d[1]), "+f"(d[2]), "+f"(d[3]) : "r"(a0), "r"(a1), "r"(b0));
}
__device__ __forceinline__ void sts32(uint32_t a, uint32_t v) { asm volatile("st.shared.b32 [%0],%1;" ::"r"(a), "r"(v) : "memory"); }
__device__ __forceinline__ void sts64f(uint32_t a, float x, float y) { asm volatile("st.shared.v2.f32 [%0],{%1,%2};" ::"r"(a), "f"(x), "f"(y) : "memory"); }
__device__ __forceinline__ void sts128(uint32_t a, uint4 v) { asm volatile("st.shared.v4.b32 [%0],{%1,%2,%3,%4};" ::"r"(a), "r"(v.x), "r"(v.y), "r"(v.z), "r"(v.w) : "memory"); }
__device__ __forceinline__ float lds32f(uint32_t a) { float v; asm volatile("ld.shared.f32 %0,[%1];" : "=f"(v) : "r"(a) : "memory"); return v; }
__device__ __forceinline__ float2 lds64f(uint32_t a) { float2 v; asm volatile("ld.shared.v2.f32 {%0,%1},[%2];" : "=f"(v.x), "=f"(v.y) : "r"(a) : "memory"); return v; }
__device__ __forceinline__ uint4 lds128(uint32_t a) { uint4 v; asm volatile("ld.shared.v4.b32 {%0,%1,%2,%3},[%4];" : "=r"(v.x), "=r"(v.y), "=r"(v.z), "=r"(v.w) : "r"(a) : "memory"); return v; }
__device__ __forceinline__ float4 lds128f(uint32_t a) { float4 v; asm volatile("ld.shared.v4.f32 {%0,%1,%2,%3},[%4];" : "=f"(v.x), "=f"(v.y), "=f"(v.z), "=f"(v.w) : "r"(a) : "memory"); return v; }
__device__ __forceinline__ void st_async2(uint32_t a, float x, float y, uint32_t bar) {
  asm volatile("st.async.weak.shared::cluster.mbarrier::complete_tx::bytes.v2.f32 [%0],{%1,%2},[%3];" ::"r"(a), "f"(x), "f"(y), "r"(bar) : "memory");
}
__device__ __forceinline__ void st_async4(uint32_t a, const float (&v)[4], uint32_t bar) {
  asm volatile("st.async.weak.shared::cluster.mbarrier::complete_tx::bytes.v4.f32 [%0],{%1,%2,%3,%4},[%5];" ::"r"(a), "f"(v[0]), "f"(v[1]), "f"(v[2]), "f"(v[3]), "r"(bar) : "memory");
}
__device__ __forceinline__ void st_async4v(uint32_t a, float x, float y, float z, float w, uint32_t bar) {
  asm volatile("st.async.weak.shared::cluster.mbarrier::complete_tx::bytes.v4.f32 [%0],{%1,%2,%3,%4},[%5];" ::"r"(a), "f"(x), "f"(y), "f"(z), "f"(w), "r"(bar) : "memory");
}
__device__ __forceinline__ void st_async4u(uint32_t a, const uint4& v, uint32_t bar) {
  asm volatile("st.async.weak.shared::cluster.mbarrier::complete_tx::bytes.v4.b32 [%0],{%1,%2,%3,%4},[%5];" ::"r"(a), "r"(v.x), "r"(v.y), "r"(v.z), "r"(v.w), "r"(bar) : "memory");
}
__device__ __forceinline__ uint4 ld_relaxed4(const void* p) {
  uint4 v; asm volatile("ld.relaxed.gpu.global.v4.u32 {%0,%1,%2,%3},[%4];" : "=r"(v.x), "=r"(v.y), "=r"(v.z), "=r"(v.w) : "l"(p) : "memory"); return v;
}
__device__ __forceinline__ uint32_t ld_relaxed(const void* p) {
  uint32_t v; asm volatile("ld.relaxed.gpu.global.u32 %0,[%1];" : "=r"(v) : "l"(p) : "memory"); return v;
}
__device__ __forceinline__ void st_relaxed(void* p, uint32_t v) { asm volatile("st.relaxed.gpu.global.b32 [%0],%1;" ::"l"(p), "r"(v) : "memory"); }
__device__ __forceinline__ void st_relaxed4(void* p, uint32_t v) { asm volatile("st.relaxed.gpu.global.v4.b32 [%0],{%1,%1,%1,%1};" ::"l"(p), "r"(v) : "memory"); }

__device__ __forceinline__ uint32_t ld_acquire(const void* p) {
  uint32_t v; asm volatile("ld.acquire.gpu.global.u32 %0,[%1];" : "=r"(v) : "l"(p) : "memory"); return v;
}
__device__ __forceinline__ float4 ld_relaxed4f(const void* p) {
  float4 v; asm volatile("ld.relaxed.gpu.global.v4.f32 {%0,%1,%2,%3},[%4];" : "=f"(v.x), "=f"(v.y), "=f"(v.z), "=f"(v.w) : "l"(p) : "memory"); return v;
}
__device__ __forceinline__ float2 ld_relaxed2f(const void* p) {
  float2 v; asm volatile("ld.relaxed.gpu.global.v2.f32 {%0,%1},[%2];" : "=f"(v.x), "=f"(v.y) : "l"(p) : "memory"); return v;
}
__device__ __forceinline__ void prefetch_l2(const void* p) { asm volatile("prefetch.global.L2 [%0];" ::"l"(p)); }
__device__ __forceinline__ void fence_gpu() { asm volatile("fence.acq_rel.gpu;" ::: "memory"); }
__device__ __forceinline__ void fence_async_all() { asm volatile("fence.proxy.async.global;" ::: "memory"); }
constexpr int SPIN_TOT = 1 << 22;
__device__ __forceinline__ void csignal(int idx) { asm volatile("red.release.gpu.global.add.u32 [%0],1;" ::"l"(&g_cnt[idx][0]) : "memory"); }
#define csignal_t(idx, role) csignal(idx)
__device__ __forceinline__ void cwait(int idx, uint32_t target, int& spin) {
  while (ld_acquire(&g_cnt[idx][0]) < target && spin < SPIN_TOT) spin += 16;
}

__device__ __forceinline__ uint64_t mkdesc(uint32_t addr, uint32_t lbo, uint32_t sbo) {
  return (uint64_t)((addr & 0x3FFFF) >> 4) | ((uint64_t)(lbo >> 4) << 16) | ((uint64_t)(sbo >> 4) << 32) | ((uint64_t)1 << 62);
}
__device__ __forceinline__ uint64_t mkdesc_ns(uint32_t addr, uint32_t lbo, uint32_t sbo) {
  return (uint64_t)((addr & 0x3FFFF) >> 4) | ((uint64_t)(lbo >> 4) << 16) | ((uint64_t)(sbo >> 4) << 32);
}
__device__ __forceinline__ void wg_fence() { asm volatile("wgmma.fence.sync.aligned;" ::: "memory"); }
__device__ __forceinline__ void wg_commit() { asm volatile("wgmma.commit_group.sync.aligned;" ::: "memory"); }
template <int N> __device__ __forceinline__ void wg_wait() { asm volatile("wgmma.wait_group.sync.aligned %0;" ::"n"(N) : "memory"); }

__device__ __forceinline__ void wgmma_rs16(float (&d)[8], const uint32_t (&a)[4], uint64_t db, int sc) {
  asm volatile("{.reg .pred p; setp.ne.b32 p,%13,0; wgmma.mma_async.sync.aligned.m64n16k16.f32.bf16.bf16 "
               "{%0,%1,%2,%3,%4,%5,%6,%7},{%8,%9,%10,%11},%12,p,1,1,0;}"
               : "+f"(d[0]), "+f"(d[1]), "+f"(d[2]), "+f"(d[3]), "+f"(d[4]), "+f"(d[5]), "+f"(d[6]), "+f"(d[7])
               : "r"(a[0]), "r"(a[1]), "r"(a[2]), "r"(a[3]), "l"(db), "r"(sc));
}
__device__ __forceinline__ void wgmma_rs64(float (&d)[32], const uint32_t (&a)[4], uint64_t db, int sc) {
  asm volatile("{.reg .pred p; setp.ne.b32 p,%37,0; wgmma.mma_async.sync.aligned.m64n64k16.f32.bf16.bf16 "
               "{%0,%1,%2,%3,%4,%5,%6,%7,%8,%9,%10,%11,%12,%13,%14,%15,%16,%17,%18,%19,%20,%21,%22,%23,%24,%25,%26,%27,%28,%29,%30,%31},{%32,%33,%34,%35},%36,p,1,1,0;}"
               : "+f"(d[0]), "+f"(d[1]), "+f"(d[2]), "+f"(d[3]), "+f"(d[4]), "+f"(d[5]), "+f"(d[6]), "+f"(d[7]), "+f"(d[8]), "+f"(d[9]), "+f"(d[10]), "+f"(d[11]), "+f"(d[12]), "+f"(d[13]), "+f"(d[14]), "+f"(d[15]), "+f"(d[16]), "+f"(d[17]), "+f"(d[18]), "+f"(d[19]), "+f"(d[20]), "+f"(d[21]), "+f"(d[22]), "+f"(d[23]), "+f"(d[24]), "+f"(d[25]), "+f"(d[26]), "+f"(d[27]), "+f"(d[28]), "+f"(d[29]), "+f"(d[30]), "+f"(d[31])
               : "r"(a[0]), "r"(a[1]), "r"(a[2]), "r"(a[3]), "l"(db), "r"(sc));
}
__device__ __forceinline__ void wgmma_rt16(float (&d)[8], const uint32_t (&a)[4], uint64_t db, int sc) {
  asm volatile("{.reg .pred p; setp.ne.b32 p,%13,0; wgmma.mma_async.sync.aligned.m64n16k16.f32.bf16.bf16 "
               "{%0,%1,%2,%3,%4,%5,%6,%7},{%8,%9,%10,%11},%12,p,1,1,1;}"
               : "+f"(d[0]), "+f"(d[1]), "+f"(d[2]), "+f"(d[3]), "+f"(d[4]), "+f"(d[5]), "+f"(d[6]), "+f"(d[7])
               : "r"(a[0]), "r"(a[1]), "r"(a[2]), "r"(a[3]), "l"(db), "r"(sc));
}
__device__ __forceinline__ void wgmma_rt80(float (&d)[40], const uint32_t (&a)[4], uint64_t db, int sc) {
  asm volatile("{.reg .pred p; setp.ne.b32 p,%45,0; wgmma.mma_async.sync.aligned.m64n80k16.f32.bf16.bf16 "
               "{%0,%1,%2,%3,%4,%5,%6,%7,%8,%9,%10,%11,%12,%13,%14,%15,%16,%17,%18,%19,%20,%21,%22,%23,%24,%25,%26,%27,%28,%29,%30,%31,%32,%33,%34,%35,%36,%37,%38,%39},{%40,%41,%42,%43},%44,p,1,1,1;}"
               : "+f"(d[0]), "+f"(d[1]), "+f"(d[2]), "+f"(d[3]), "+f"(d[4]), "+f"(d[5]), "+f"(d[6]), "+f"(d[7]), "+f"(d[8]), "+f"(d[9]), "+f"(d[10]), "+f"(d[11]), "+f"(d[12]), "+f"(d[13]), "+f"(d[14]), "+f"(d[15]), "+f"(d[16]), "+f"(d[17]), "+f"(d[18]), "+f"(d[19]), "+f"(d[20]), "+f"(d[21]), "+f"(d[22]), "+f"(d[23]), "+f"(d[24]), "+f"(d[25]), "+f"(d[26]), "+f"(d[27]), "+f"(d[28]), "+f"(d[29]), "+f"(d[30]), "+f"(d[31]), "+f"(d[32]), "+f"(d[33]), "+f"(d[34]), "+f"(d[35]), "+f"(d[36]), "+f"(d[37]), "+f"(d[38]), "+f"(d[39])
               : "r"(a[0]), "r"(a[1]), "r"(a[2]), "r"(a[3]), "l"(db), "r"(sc));
}
__device__ __forceinline__ void wgmma_rs32(float (&d)[16], const uint32_t (&a)[4], uint64_t db, int sc) {
  asm volatile("{.reg .pred p; setp.ne.b32 p,%21,0; wgmma.mma_async.sync.aligned.m64n32k16.f32.bf16.bf16 "
               "{%0,%1,%2,%3,%4,%5,%6,%7,%8,%9,%10,%11,%12,%13,%14,%15},{%16,%17,%18,%19},%20,p,1,1,0;}"
               : "+f"(d[0]), "+f"(d[1]), "+f"(d[2]), "+f"(d[3]), "+f"(d[4]), "+f"(d[5]), "+f"(d[6]), "+f"(d[7]), "+f"(d[8]), "+f"(d[9]), "+f"(d[10]), "+f"(d[11]), "+f"(d[12]), "+f"(d[13]), "+f"(d[14]), "+f"(d[15])
               : "r"(a[0]), "r"(a[1]), "r"(a[2]), "r"(a[3]), "l"(db), "r"(sc));
}
__device__ __forceinline__ void wgmma_ts32(float (&d)[16], uint64_t da, uint64_t db, int sc) {
  asm volatile("{.reg .pred p; setp.ne.b32 p,%18,0; wgmma.mma_async.sync.aligned.m64n32k16.f32.bf16.bf16 "
               "{%0,%1,%2,%3,%4,%5,%6,%7,%8,%9,%10,%11,%12,%13,%14,%15},%16,%17,p,1,1,1,0;}"
               : "+f"(d[0]), "+f"(d[1]), "+f"(d[2]), "+f"(d[3]), "+f"(d[4]), "+f"(d[5]), "+f"(d[6]), "+f"(d[7]), "+f"(d[8]), "+f"(d[9]), "+f"(d[10]), "+f"(d[11]), "+f"(d[12]), "+f"(d[13]), "+f"(d[14]), "+f"(d[15])
               : "l"(da), "l"(db), "r"(sc));
}
__device__ __forceinline__ void wgmma_ts16(float (&d)[8], uint64_t da, uint64_t db, int sc) {
  asm volatile("{.reg .pred p; setp.ne.b32 p,%10,0; wgmma.mma_async.sync.aligned.m64n16k16.f32.bf16.bf16 "
               "{%0,%1,%2,%3,%4,%5,%6,%7},%8,%9,p,1,1,1,0;}"
               : "+f"(d[0]), "+f"(d[1]), "+f"(d[2]), "+f"(d[3]), "+f"(d[4]), "+f"(d[5]), "+f"(d[6]), "+f"(d[7])
               : "l"(da), "l"(db), "r"(sc));
}
__device__ __forceinline__ void wgmma_ts64(float (&d)[32], uint64_t da, uint64_t db, int sc) {
  asm volatile("{.reg .pred p; setp.ne.b32 p,%34,0; wgmma.mma_async.sync.aligned.m64n64k16.f32.bf16.bf16 "
               "{%0,%1,%2,%3,%4,%5,%6,%7,%8,%9,%10,%11,%12,%13,%14,%15,%16,%17,%18,%19,%20,%21,%22,%23,%24,%25,%26,%27,%28,%29,%30,%31},%32,%33,p,1,1,1,0;}"
               : "+f"(d[0]), "+f"(d[1]), "+f"(d[2]), "+f"(d[3]), "+f"(d[4]), "+f"(d[5]), "+f"(d[6]), "+f"(d[7]), "+f"(d[8]), "+f"(d[9]), "+f"(d[10]), "+f"(d[11]), "+f"(d[12]), "+f"(d[13]), "+f"(d[14]), "+f"(d[15]), "+f"(d[16]), "+f"(d[17]), "+f"(d[18]), "+f"(d[19]), "+f"(d[20]), "+f"(d[21]), "+f"(d[22]), "+f"(d[23]), "+f"(d[24]), "+f"(d[25]), "+f"(d[26]), "+f"(d[27]), "+f"(d[28]), "+f"(d[29]), "+f"(d[30]), "+f"(d[31])
               : "l"(da), "l"(db), "r"(sc));
}
__device__ __forceinline__ void wgmma_tt16(float (&d)[8], uint64_t da, uint64_t db, int sc) {
  asm volatile("{.reg .pred p; setp.ne.b32 p,%10,0; wgmma.mma_async.sync.aligned.m64n16k16.f32.bf16.bf16 "
               "{%0,%1,%2,%3,%4,%5,%6,%7},%8,%9,p,1,1,1,1;}"
               : "+f"(d[0]), "+f"(d[1]), "+f"(d[2]), "+f"(d[3]), "+f"(d[4]), "+f"(d[5]), "+f"(d[6]), "+f"(d[7])
               : "l"(da), "l"(db), "r"(sc));
}
__device__ __forceinline__ void wgmma_tt40(float (&d)[20], uint64_t da, uint64_t db, int sc) {
  asm volatile("{.reg .pred p; setp.ne.b32 p,%22,0; wgmma.mma_async.sync.aligned.m64n40k16.f32.bf16.bf16 "
               "{%0,%1,%2,%3,%4,%5,%6,%7,%8,%9,%10,%11,%12,%13,%14,%15,%16,%17,%18,%19},%20,%21,p,1,1,1,1;}"
               : "+f"(d[0]), "+f"(d[1]), "+f"(d[2]), "+f"(d[3]), "+f"(d[4]), "+f"(d[5]), "+f"(d[6]), "+f"(d[7]), "+f"(d[8]), "+f"(d[9]), "+f"(d[10]), "+f"(d[11]), "+f"(d[12]), "+f"(d[13]), "+f"(d[14]), "+f"(d[15]), "+f"(d[16]), "+f"(d[17]), "+f"(d[18]), "+f"(d[19])
               : "l"(da), "l"(db), "r"(sc));
}
__device__ __forceinline__ void wgmma_ss8(float (&d)[4], uint64_t da, uint64_t db, int sc) {
  asm volatile("{.reg .pred p; setp.ne.b32 p,%6,0; wgmma.mma_async.sync.aligned.m64n8k16.f32.bf16.bf16 "
               "{%0,%1,%2,%3},%4,%5,p,1,1,0,0;}"
               : "+f"(d[0]), "+f"(d[1]), "+f"(d[2]), "+f"(d[3])
               : "l"(da), "l"(db), "r"(sc));
}
__device__ __forceinline__ void wgmma_ss32(float (&d)[16], uint64_t da, uint64_t db, int sc) {
  asm volatile("{.reg .pred p; setp.ne.b32 p,%18,0; wgmma.mma_async.sync.aligned.m64n32k16.f32.bf16.bf16 "
               "{%0,%1,%2,%3,%4,%5,%6,%7,%8,%9,%10,%11,%12,%13,%14,%15},%16,%17,p,1,1,0,0;}"
               : "+f"(d[0]), "+f"(d[1]), "+f"(d[2]), "+f"(d[3]), "+f"(d[4]), "+f"(d[5]), "+f"(d[6]), "+f"(d[7]), "+f"(d[8]), "+f"(d[9]), "+f"(d[10]), "+f"(d[11]), "+f"(d[12]), "+f"(d[13]), "+f"(d[14]), "+f"(d[15])
               : "l"(da), "l"(db), "r"(sc));
}
__device__ __forceinline__ void wgmma_st64(float (&d)[32], uint64_t da, uint64_t db, int sc) {
  asm volatile("{.reg .pred p; setp.ne.b32 p,%34,0; wgmma.mma_async.sync.aligned.m64n64k16.f32.bf16.bf16 "
               "{%0,%1,%2,%3,%4,%5,%6,%7,%8,%9,%10,%11,%12,%13,%14,%15,%16,%17,%18,%19,%20,%21,%22,%23,%24,%25,%26,%27,%28,%29,%30,%31},%32,%33,p,1,1,0,1;}"
               : "+f"(d[0]), "+f"(d[1]), "+f"(d[2]), "+f"(d[3]), "+f"(d[4]), "+f"(d[5]), "+f"(d[6]), "+f"(d[7]), "+f"(d[8]), "+f"(d[9]), "+f"(d[10]), "+f"(d[11]), "+f"(d[12]), "+f"(d[13]), "+f"(d[14]), "+f"(d[15]), "+f"(d[16]), "+f"(d[17]), "+f"(d[18]), "+f"(d[19]), "+f"(d[20]), "+f"(d[21]), "+f"(d[22]), "+f"(d[23]), "+f"(d[24]), "+f"(d[25]), "+f"(d[26]), "+f"(d[27]), "+f"(d[28]), "+f"(d[29]), "+f"(d[30]), "+f"(d[31])
               : "l"(da), "l"(db), "r"(sc));
}
__device__ __forceinline__ void wgmma_st128(float (&d)[64], uint64_t da, uint64_t db, int sc) {
  asm volatile("{.reg .pred p; setp.ne.b32 p,%66,0; wgmma.mma_async.sync.aligned.m64n128k16.f32.bf16.bf16 "
               "{%0,%1,%2,%3,%4,%5,%6,%7,%8,%9,%10,%11,%12,%13,%14,%15,%16,%17,%18,%19,%20,%21,%22,%23,%24,%25,%26,%27,%28,%29,%30,%31,%32,%33,%34,%35,%36,%37,%38,%39,%40,%41,%42,%43,%44,%45,%46,%47,%48,%49,%50,%51,%52,%53,%54,%55,%56,%57,%58,%59,%60,%61,%62,%63},%64,%65,p,1,1,0,1;}"
               : "+f"(d[0]), "+f"(d[1]), "+f"(d[2]), "+f"(d[3]), "+f"(d[4]), "+f"(d[5]), "+f"(d[6]), "+f"(d[7]), "+f"(d[8]), "+f"(d[9]), "+f"(d[10]), "+f"(d[11]), "+f"(d[12]), "+f"(d[13]), "+f"(d[14]), "+f"(d[15]), "+f"(d[16]), "+f"(d[17]), "+f"(d[18]), "+f"(d[19]), "+f"(d[20]), "+f"(d[21]), "+f"(d[22]), "+f"(d[23]), "+f"(d[24]), "+f"(d[25]), "+f"(d[26]), "+f"(d[27]), "+f"(d[28]), "+f"(d[29]), "+f"(d[30]), "+f"(d[31]), "+f"(d[32]), "+f"(d[33]), "+f"(d[34]), "+f"(d[35]), "+f"(d[36]), "+f"(d[37]), "+f"(d[38]), "+f"(d[39]), "+f"(d[40]), "+f"(d[41]), "+f"(d[42]), "+f"(d[43]), "+f"(d[44]), "+f"(d[45]), "+f"(d[46]), "+f"(d[47]), "+f"(d[48]), "+f"(d[49]), "+f"(d[50]), "+f"(d[51]), "+f"(d[52]), "+f"(d[53]), "+f"(d[54]), "+f"(d[55]), "+f"(d[56]), "+f"(d[57]), "+f"(d[58]), "+f"(d[59]), "+f"(d[60]), "+f"(d[61]), "+f"(d[62]), "+f"(d[63])
               : "l"(da), "l"(db), "r"(sc));
}

__device__ __forceinline__ void stsm4(uint32_t a, uint32_t r0, uint32_t r1, uint32_t r2, uint32_t r3) {
  asm volatile("stmatrix.sync.aligned.m8n8.x4.shared.b16 [%0],{%1,%2,%3,%4};" ::"r"(a), "r"(r0), "r"(r1), "r"(r2), "r"(r3) : "memory");
}
__device__ __forceinline__ void stsm4t(uint32_t a, uint32_t r0, uint32_t r1, uint32_t r2, uint32_t r3) {
  asm volatile("stmatrix.sync.aligned.m8n8.x4.trans.shared.b16 [%0],{%1,%2,%3,%4};" ::"r"(a), "r"(r0), "r"(r1), "r"(r2), "r"(r3) : "memory");
}
__device__ __forceinline__ void sts64(uint32_t a, uint32_t x, uint32_t y) { asm volatile("st.shared.v2.b32 [%0],{%1,%2};" ::"r"(a), "r"(x), "r"(y) : "memory"); }
__device__ __forceinline__ void st_async2u(uint32_t a, uint32_t x, uint32_t y, uint32_t bar) {
  asm volatile("st.async.weak.shared::cluster.mbarrier::complete_tx::bytes.v2.b32 [%0],{%1,%2},[%3];" ::"r"(a), "r"(x), "r"(y), "r"(bar) : "memory");
}
__device__ __forceinline__ void st_relaxed128(void* p, uint32_t x, uint32_t y, uint32_t z, uint32_t w) {
  asm volatile("{.reg .b128 v; mov.b128 v,{%1,%2,%3,%4}; st.relaxed.gpu.global.b128 [%0],v;}" ::"l"(p), "r"(x), "r"(y), "r"(z), "r"(w) : "memory");
}
__device__ __forceinline__ void st_relaxed64(void* p, uint32_t x, uint32_t y) {
  asm volatile("{.reg .b64 v; mov.b64 v,{%1,%2}; st.relaxed.gpu.global.b64 [%0],v;}" ::"l"(p), "r"(x), "r"(y) : "memory");
}
__device__ __forceinline__ uint4 ld_relaxed128(const void* p) {
  uint4 v;
  asm volatile("{.reg .b128 v; .reg .b64 lo, hi; ld.relaxed.gpu.global.b128 v,[%4]; mov.b128 {lo,hi},v; mov.b64 {%0,%1},lo; mov.b64 {%2,%3},hi;}" : "=r"(v.x), "=r"(v.y), "=r"(v.z), "=r"(v.w) : "l"(p) : "memory");
  return v;
}

__device__ __forceinline__ uint32_t pack_h2(float lo, float hi) {
  uint32_t r; asm("cvt.rn.satfinite.f16x2.f32 %0,%1,%2;" : "=r"(r) : "f"(hi), "f"(lo)); return r;
}
__device__ __forceinline__ void add_h2(float& lo, float& hi, uint32_t u, uint32_t v) {
  float a, b;
  asm("{.reg .b16 l, h; .reg .b32 s; add.rn.f16x2 s,%2,%3; mov.b32 {l,h},s; cvt.f32.f16 %0,l; cvt.f32.f16 %1,h;}" : "=f"(a), "=f"(b) : "r"(u), "r"(v));
  lo += a; hi += b;
}
__device__ __forceinline__ void mwait(uint32_t bar, uint32_t ph, int& spin) {
  asm volatile("{.reg .pred p, q;\nWAIT_LOOP:\n add.s32 %0,%0,1;\n setp.lt.s32 q,%0,%3;\n mbarrier.try_wait.parity.shared::cta.b64 p,[%1],%2;\n not.pred p,p;\n and.pred q,q,p;\n @q bra.uni WAIT_LOOP;\n}"
               : "+&r"(spin) : "r"(bar), "r"(ph), "n"(SPIN_TOT) : "memory");
}
__device__ __forceinline__ int keep(int x) { return __shfl_sync(0xffffffffu, x, threadIdx.x & 31); }
__device__ __forceinline__ uint32_t pin(uint32_t x) { asm volatile("" : "+r"(x)); return x; }
template <typename T> __device__ __forceinline__ T* pinp(T* x) { asm volatile("" : "+l"(x)); return x; }
__device__ __forceinline__ void st_async1u(uint32_t a, uint32_t x, uint32_t bar) {
  asm volatile("st.async.weak.shared::cluster.mbarrier::complete_tx::bytes.b32 [%0],%1,[%2];" ::"r"(a), "r"(x), "r"(bar) : "memory");
}
__device__ __forceinline__ uint32_t lds32(uint32_t a) { uint32_t v; asm volatile("ld.shared.b32 %0,[%1];" : "=r"(v) : "r"(a) : "memory"); return v; }
__device__ __forceinline__ uint2 lds64(uint32_t a) { uint2 v; asm volatile("ld.shared.v2.b32 {%0,%1},[%2];" : "=r"(v.x), "=r"(v.y) : "r"(a) : "memory"); return v; }

__device__ __forceinline__ void permute_cols(uint32_t tile, int tid, int n) {
  for (int it = tid; it < n; it += 128) {
    const int row = it >> 2, q = it & 3;
    const uint32_t a0 = tile + row * 128 + (((2 * q) ^ (row & 7)) << 4), a1 = tile + row * 128 + (((2 * q + 1) ^ (row & 7)) << 4);
    const uint4 u = lds128(a0), v = lds128(a1);
    sts128(a0, make_uint4(__byte_perm(u.x, u.y, 0x5410), __byte_perm(u.z, u.w, 0x5410), __byte_perm(v.x, v.y, 0x5410), __byte_perm(v.z, v.w, 0x5410)));
    sts128(a1, make_uint4(__byte_perm(u.x, u.y, 0x7632), __byte_perm(u.z, u.w, 0x7632), __byte_perm(v.x, v.y, 0x7632), __byte_perm(v.z, v.w, 0x7632)));
  }
}

__device__ __forceinline__ uint8_t* mkptr(uint32_t lo, uint32_t hi) { uint8_t* p; asm("mov.b64 %0,{%1,%2};" : "=l"(p) : "r"(lo), "r"(hi)); return p; }
__device__ __forceinline__ int uni(int x) { return __shfl_sync(0xffffffffu, x, 0); }

__device__ __forceinline__ void ln_row_to_image(const bf16* __restrict__ x, uint8_t* __restrict__ img, int row, int lane) {
  const uint4* src = reinterpret_cast<const uint4*>(x + (size_t)row * DM);
  uint4 v[3];
  v[0] = src[lane]; v[1] = src[lane + 32];
  v[2] = lane < 16 ? src[lane + 64] : make_uint4(0, 0, 0, 0);
  float s = 0.f;
#pragma unroll
  for (int i = 0; i < 3; i++) {
    s += bf_lo(v[i].x) + bf_hi(v[i].x) + bf_lo(v[i].y) + bf_hi(v[i].y) + bf_lo(v[i].z) + bf_hi(v[i].z) + bf_lo(v[i].w) + bf_hi(v[i].w);
  }
#pragma unroll
  for (int o = 16; o > 0; o >>= 1) s += __shfl_xor_sync(0xffffffffu, s, o);
  const float mean = s * (1.f / DM);
  float q = 0.f;
#pragma unroll
  for (int i = 0; i < 3; i++) {
    if (i < 2 || lane < 16) {
      const uint32_t w[4] = {v[i].x, v[i].y, v[i].z, v[i].w};
#pragma unroll
      for (int j = 0; j < 4; j++) { float a = bf_lo(w[j]) - mean, b = bf_hi(w[j]) - mean; q += a * a + b * b; }
    }
  }
#pragma unroll
  for (int o = 16; o > 0; o >>= 1) q += __shfl_xor_sync(0xffffffffu, q, o);
  const float rstd = rsqrtf(q * (1.f / DM) + 1e-5f);
#pragma unroll
  for (int i = 0; i < 3; i++) {
    if (i < 2 || lane < 16) {
      const int c = lane + 32 * i;
      uint4 o;
      o.x = pack_bf16((bf_lo(v[i].x) - mean) * rstd, (bf_hi(v[i].x) - mean) * rstd);
      o.y = pack_bf16((bf_lo(v[i].y) - mean) * rstd, (bf_hi(v[i].y) - mean) * rstd);
      o.z = pack_bf16((bf_lo(v[i].z) - mean) * rstd, (bf_hi(v[i].z) - mean) * rstd);
      o.w = pack_bf16((bf_lo(v[i].w) - mean) * rstd, (bf_hi(v[i].w) - mean) * rstd);
      const size_t off = (size_t)(row >> 5) * 40960 + (c >> 4) * 8192 + ((row >> 3) & 3) * 2048 + ((c >> 3) & 1) * 1024 + (row & 7) * 128 + (((c & 7) ^ (row & 7)) << 4);
      *reinterpret_cast<uint4*>(img + off) = o;
      float4* xf = reinterpret_cast<float4*>(g_x + (size_t)row * DM + c * 8);
      xf[0] = make_float4(bf_lo(v[i].x), bf_hi(v[i].x), bf_lo(v[i].y), bf_hi(v[i].y));
      xf[1] = make_float4(bf_lo(v[i].z), bf_hi(v[i].z), bf_lo(v[i].w), bf_hi(v[i].w));
    }
  }
}

__global__ void __launch_bounds__(256) k_pre(const bf16* __restrict__ x, const bf16* __restrict__ mem0) {
  const int row = blockIdx.x * 8 + (threadIdx.x >> 5);
  ln_row_to_image(x, g_xn[0], row, threadIdx.x & 31);
  const int gt = blockIdx.x * 256 + threadIdx.x;
  const uint4 sent = make_uint4(SENT, SENT, SENT, SENT);
  uint8_t* ex = ex_window(g_ex);
  if (gt < MAIL_BYTES / 16) {
    reinterpret_cast<uint4*>(ex + EX_MAIL)[gt] = sent;
    reinterpret_cast<uint4*>(ex + EX_MAIL + (1 << 20))[gt] = sent;
  }
  uint4* mb = reinterpret_cast<uint4*>(ex + EX_M);
  for (int i = gt; i < NSTEP * 1280; i += 65536) {
    const int p = i % 1280, st = i / 1280;
    uint4 v = sent;
    if (st == 0 || (st == LAG && (p & 8))) v = *reinterpret_cast<const uint4*>(mem0 + (p & 7) * DM + m_kstep(p >> 5) * 16 + (p & 16) / 2);
    mb[i] = v;
  }
  if (gt < NSTEP * 192) reinterpret_cast<uint4*>(ex + EX_FLAG)[gt] = gt < 192 ? make_uint4(0, 0, 0, 0) : sent;
  if (gt < CN_NUM) g_cnt[gt][0] = 0;
}

namespace C {
constexpr int NKR = 37;
constexpr int OFF_WQ = 0, OFF_WK = 81920;
constexpr int OFF_YO = 163840, OFF_YV = OFF_YO + 6144;
constexpr int OFF_M = 176128;
__host__ __device__ constexpr int og_off(int c) { return c ? OFF_M + 14336 + c * 2048 : 229376; }
constexpr int OFF_KT = 196608;
constexpr int OFF_XT = OFF_KT + 10240;
constexpr int OFF_VT = OFF_XT + 7168;
constexpr int OFF_XM = OFF_VT + 11392;
constexpr int OFF_PT = OFF_XM + 2560;
constexpr int KS = 1280, VS = 1408;
__host__ __device__ constexpr int slot_off(int p) { return p == 2 ? OFF_M : OFF_KT + (p % 3) * 16384; }
constexpr int OFF_BAR = 231552;
constexpr int OFF_SAFE = OFF_BAR + 176;
constexpr int OFF_TS = OFF_BAR + 256;
constexpr int SMEM = 232448;
constexpr uint32_t SB0 = 1024;
constexpr int BAR_F = OFF_BAR, BAR_E = OFF_BAR + 40, BAR_MOK = OFF_BAR + 88, BAR_XM = OFF_BAR + 96, BAR_XF = OFF_BAR + 104,
              BAR_XT = OFF_BAR + 112, BAR_MF = OFF_BAR + 120, BAR_OG = OFF_BAR + 128, BAR_W = OFF_BAR + 136, FLG_REDO = OFF_BAR + 80, BAR_M = OFF_BAR + 144;
constexpr int NB_PRO = 1, NB_RD = 2, NB_MR = 3, NB_QK = 4, NB_SM = 5, NB_VA = 6, NB_VQ = 7, NB_A = 8, NB_Q = 9, NB_C = 10, NB_WQ = 11, NB_QI = 12, NB_SI = 13, NB_WV = 14;
#define B1 300
#define B1D 100
#define B2 250
#define FLP 1
#define OSG 2
#define QIE 4
#define SIE 2
#define WOE 1
#define OGF 0
#define VSP 8
#define RFK 5
#define PFD 3
#define WOL 0
#define NOWORK 0
constexpr float SCL = 1.f / 2048, SCE = 0.07216878364870322f * 1.4426950408889634f * 2048;
}

#define CBAR_SYNC(id, n) bar_sync(id, n)
#define CBAR_ARRIVE(id, n) bar_arrive(id, n)

__device__ __forceinline__ uint64_t wdesc(int off) { return mkdesc(C::SB0 + off, 8192, 1024); }
__device__ __forceinline__ uint64_t mdesc(int k) { return mkdesc_ns(C::SB0 + C::OFF_M + k * 512, 256, 128); }
__device__ __forceinline__ uint64_t tdesc(int k) { return mkdesc(C::SB0 + C::slot_off(k >> 3) + ((k >> 2) & 1) * 1024 + (k & 3) * 32, 16, 2048); }

__device__ __forceinline__ int dh_row(int n) { return (n & ~63) + (n & 32) + ((n >> 1) & 3) * 8 + ((n >> 3) & 3) * 2 + (n & 1); }
template <bool PERM>
__device__ __forceinline__ void load_weights_rs(uint32_t (&wf)[C::NKR][4], uint32_t sb, int stage, int yoff, int tid0) {
  using namespace C;
  const int i = (tid0 >> 3) & 3, n0 = (tid0 & 7) + (i >> 1) * 8;
  const int chunk = 2 * ((tid0 >> 5) & 3) + (i & 1);
  const int r0 = PERM ? dh_row(n0) : n0, r1 = PERM ? dh_row(n0 + 16) : n0 + 16;
  const uint32_t a0 = sb + stage + r0 * 128 + ((chunk ^ (r0 & 7)) << 4), a1 = sb + stage + r1 * 128 + ((chunk ^ (r1 & 7)) << 4);
#pragma unroll
  for (int k = 0; k < NKR; k++) ldsm4t(wf[k], ((k & 1) ? a1 : a0) + (k >> 1) * 4096);
#pragma unroll
  for (int k = 0; k < 40 - NKR; k++) {
    const int n = (NKR + k) * 16 + ((tid0 & 127) >> 3), r = PERM ? dh_row(n) : n, c = tid0 & 7;
    sts128(sb + yoff + (n - NKR * 16) * 128 + ((c ^ (n & 7)) << 4), lds128(sb + stage + r * 128 + ((c ^ (r & 7)) << 4)));
  }
  fence_async();
  CBAR_SYNC(NB_PRO, 384);
}
template <int STRIDE>
__device__ __forceinline__ void store_mem(const float (&d)[8], uint32_t base, int tid) {
  const int m = (tid >> 3) & 3;
  stsm4(base + (((tid >> 5) & 3) * 2 + (m & 1)) * STRIDE + (m >> 1) * 640 + (tid & 7) * 16, pack_bf16(d[0], d[1]), pack_bf16(d[2], d[3]),
        pack_bf16(d[4], d[5]), pack_bf16(d[6], d[7]));
}

__device__ __forceinline__ void load_pair(uint32_t sb, int i, int p, uint32_t slot, uint32_t bar, uint32_t ph, int& spin) {
  using namespace C;
  const uint8_t* s0 = g_xn[0] + (size_t)i * 40960 + p * 8192;
  const uint8_t* s1 = g_xn[NOWORK ? 0 : 1] + (size_t)(i - LAG) * 40960 + p * 8192;
  const uint8_t* sa = pinp(i < NSEG ? s0 : s1);
  const uint8_t* sc = pinp(i >= LAG ? s1 : s0);
  const uint32_t dst = pin(sb + slot), fb = pin(sb + BAR_F + 8 * p);
  mwait(bar, ph, spin);
  bulk_g2s_mc(dst, sa, 8192, fb);
  bulk_g2s_mc(dst + 8192, sc, 8192, fb);
}
__device__ __forceinline__ void first_fill(uint32_t sb, int i, int rank, bool seen, int& spin) {
  using namespace C;
  const int s1 = i - LAG;
  if (!NOWORK && s1 >= 0 && !seen) { cwait(CN_X + s1, 32, spin); fence_async_all(); }
  load_pair(sb, i, rank, rank == 2 ? OFF_M : OFF_KT + rank * 16384, sb + BAR_E + 8 * rank, (i - 1) & 1, spin);
}
__device__ __forceinline__ void release_round(uint32_t sb, int p, int tid) {
  using namespace C;
  const int lane = tid & 31;
  if (p < 2) { if (lane == 0) mbar_arrive_cluster(mapa(sb, p) + BAR_E + 8 * (3 + p)); }
  else if (lane < 3) mbar_arrive_cluster(mapa(sb, lane) + BAR_MOK);
}

template <int K0, int K1>
__device__ __forceinline__ void v_mem_pass(float (&d)[8], const uint32_t (&wf)[C::NKR][4]) {
  using namespace C;
  wg_fence();
#pragma unroll
  for (int j = K0; j < K1; j++) {
    const int k = m_kstep(j);
    if (k < NKR) wgmma_rs16(d, wf[k < NKR ? k : 0], mdesc(j), j != 32);
    else wgmma_ts16(d, wdesc(OFF_YV + (k - NKR) * 2048), mdesc(j), 1);
  }
  wg_commit();
}
__device__ __forceinline__ void chain_v(const uint32_t sb, const int tid0, const int cta, const int rank) {
  using namespace C;
  asm volatile("setmaxnreg.inc.sync.aligned.u32 208;");
  int spin = 0;
  uint32_t wf[NKR][4];
  if (tid0 == 256) first_fill(sb, 0, rank, false, spin);
  __syncwarp();
  mwait(sb + BAR_W, 0, spin);
  for (int it = tid0 & 127; it < 1280; it += 128) {
    const uint32_t base = sb + OFF_WK + (it >> 1) * 128;
    const int sw = ((it >> 1) & 7) ^ ((it & 1) * 4);
    const uint4 u0 = lds128(base + (sw << 4)), u1 = lds128(base + ((sw ^ 1) << 4)), u2 = lds128(base + ((sw ^ 2) << 4)), u3 = lds128(base + ((sw ^ 3) << 4));
    sts128(base + (sw << 4), make_uint4(u0.x, u1.x, u2.x, u3.x)); sts128(base + ((sw ^ 1) << 4), make_uint4(u0.y, u1.y, u2.y, u3.y));
    sts128(base + ((sw ^ 2) << 4), make_uint4(u0.z, u1.z, u2.z, u3.z)); sts128(base + ((sw ^ 3) << 4), make_uint4(u0.w, u1.w, u2.w, u3.w));
  }
  bar_sync(NB_RD, 128);
  load_weights_rs<false>(wf, sb, OFF_WK, OFF_YV, tid0);
#pragma unroll 1
  for (int i = 0; i < NSTEP; i++) {
    {
      float d[32];
      if (i > 0) CBAR_SYNC(NB_WV, 256);
#pragma unroll
      for (int p = 0; p < 5; p++) {
        mwait(sb + BAR_F + 8 * p, i & 1, spin);
        TS(i, 25 + p);
        wg_fence();
#pragma unroll
        for (int k = 8 * p; k < 8 * p + 8; k++) {
          if (k < NKR) wgmma_rs64(d, wf[k < NKR ? k : 0], tdesc(k), k);
          else wgmma_ts64(d, wdesc(OFF_YV + (k - NKR) * 2048), tdesc(k), 1);
          if (k == 8 * p + 1 && p >= 1 && p <= 3) {
            wg_commit(); wg_wait<1>();
            release_round(sb, p - 1, fresh(tid0));
            wg_fence();
          }
          if (k == 8 * p + RFK && (p == 1 || p == 2)) {
            wg_commit();
            if (rank == p - 1 && tid0 == 256) load_pair(sb, i, p + 2, slot_off(p + 2), sb + BAR_E + 8 * (p + 2), i & 1, spin);
            __syncwarp();
            wg_fence();
          }
        }
        wg_commit();
      }
      wg_wait<0>();
      TS(i, 23);
      CBAR_SYNC(NB_RD, 256);
      const int tid = fresh(tid0) & 127, m = (tid >> 3) & 3;
      if (tid >= 96) {
        if (tid < 101) { if (i + 1 < NSTEP) mbar_expect_tx(sb + BAR_F + 8 * (tid - 96), 16384); }
        else if (tid == 101) mbar_expect_tx(sb + BAR_XM, 2560);
        else if (tid == 102) mbar_expect_tx(sb + BAR_XT, 7168);
        else if (tid == 103) mbar_expect_tx(sb + BAR_OG, 4096);
        else if (tid < 106) mbar_arrive_cluster(mapa(sb, (rank + tid - 103) % 3) + BAR_XF);
        __syncwarp();
      }
      const uint32_t a = sb + OFF_VT + 256 + ((tid >> 5) * 2 + (m & 1)) * VS + (m >> 1) * 128 + (tid & 7) * 16;
#pragma unroll
      for (int s = 0; s < 4; s++)
        stsm4(a + (s & 1) * 256 + (s >> 1) * 640, pack_bf16(d[8 * s], d[8 * s + 1]), pack_bf16(d[8 * s + 2], d[8 * s + 3]),
              pack_bf16(d[8 * s + 4], d[8 * s + 5]), pack_bf16(d[8 * s + 6], d[8 * s + 7]));
      if (tid < 80) sts128(sb + (tid < 72 ? OFF_VT + (tid >> 3) * VS : OFF_PT + 1280) + (tid & 7) * 16, make_uint4(0, 0, 0, 0));
      fence_async();
    }
    mwait(sb + BAR_XF, i & 1, spin);
    CBAR_ARRIVE(NB_QK, 384);
    bool seen = false;
    if (!NOWORK && tid0 == 256 && i + 1 >= LAG && i + 1 < NSTEP) { seen = ld_acquire(&g_cnt[CN_X + i + 1 - LAG][0]) >= 32; fence_async_all(); }
    __syncwarp();
    CBAR_SYNC(NB_QI, 256);
    float d[8];
    v_mem_pass<32, 40>(d, wf);
    CBAR_SYNC(NB_SM, 256);
    wg_wait<0>();
    if (__builtin_expect(lds32(sb + FLG_REDO), 0)) { v_mem_pass<32, 40>(d, wf); wg_wait<0>(); }
    if ((tid0 & 31) < 2) mbar_arrive_cluster(mapa(sb, (rank + 1 + (tid0 & 1)) % 3) + BAR_MF);
    v_mem_pass<0, 32>(d, wf);
    wg_wait<0>();
    TS(i, 24);
    const int tid = fresh(tid0);
    if ((tid & 31) == 0) mbar_arrive_cluster(mapa(sb, 2) + BAR_E + 16);
    store_mem<VS>(d, sb + OFF_VT + 128, tid);
    fence_async();
    CBAR_ARRIVE(NB_VA, 256);
    CBAR_ARRIVE(NB_VQ, 256);
    if (tid == 256) {
      if (i + 1 < NSTEP) { first_fill(sb, i + 1, rank, seen, spin); TS1(i + 1, 37); }
    } else if (tid >= 288 && tid < 295) {
      const int lane = tid & 31, ip = i + PFD;
      if (cta < 80 && ip < NSTEP) {
        if (lane < 2) prefetch_l2(ex_window(g_ex) + EX_M + ip * 20480 + (cta * 2 + lane) * 128);
        else if (lane == 6) { if (cta < 24) prefetch_l2(ex_window(g_ex) + EX_FLAG + ip * 3072 + cta * 128); }
        else if (ip < NSEG) prefetch_l2(g_xn[0] + (size_t)ip * 40960 + (cta * 4 + lane - 2) * 128);
      }
    }
    TS_FLUSH(i - 1);
    __syncwarp();
  }
  CBAR_ARRIVE(NB_WV, 256);
  if (spin >= SPIN_TOT) g_err = 3;
}

__device__ __forceinline__ float quad_max(float x) {
  const float a = __shfl_xor_sync(0xffffffffu, x, 1), b = __shfl_xor_sync(0xffffffffu, x, 2), c = __shfl_xor_sync(0xffffffffu, x, 3);
  return fmaxf(fmaxf(x, a), fmaxf(b, c));
}
__device__ __forceinline__ float quad_sum(float x) {
  const float a = __shfl_xor_sync(0xffffffffu, x, 1), b = __shfl_xor_sync(0xffffffffu, x, 2), c = __shfl_xor_sync(0xffffffffu, x, 3);
  return (x + a) + (b + c);
}
__device__ __forceinline__ float max10(const float (&y)[10]) {
  return fmaxf(fmaxf(fmaxf(fmaxf(y[0], y[1]), fmaxf(y[2], y[3])), fmaxf(fmaxf(y[4], y[5]), fmaxf(y[6], y[7]))), fmaxf(y[8], y[9]));
}
__device__ __forceinline__ float sum10(const float (&y)[10]) {
  return (((y[0] + y[1]) + (y[2] + y[3])) + ((y[4] + y[5]) + (y[6] + y[7]))) + (y[8] + y[9]);
}
__device__ __forceinline__ float rcp(float x) { float y; asm("rcp.approx.ftz.f32 %0,%1;" : "=f"(y) : "f"(x)); return y; }

__device__ __forceinline__ void signal_o(int i, int cta) { csignal(CN_O + i * 5 + min(cta / 19, 4)); }

__device__ __forceinline__ void chain_q(const CUtensorMap& tmWq, const CUtensorMap& tmWk, const uint32_t sb, const int tid0, const int cta, const int rank) {
  using namespace C;
  asm volatile("setmaxnreg.dec.sync.aligned.u32 96;");
  int spin = 0;
  CBAR_SYNC(NB_PRO, 384);
  PTS(5);
  if (tid0 == 128) {
    const int col = (cta / 3) * DH + rank * 64;
    mbar_expect_tx(sb + BAR_W, 163840);
    for (int i = 0; i < 5; i++) {
      tma2d(sb + OFF_WQ + i * 16384, &tmWq, col, i * 128, sb + BAR_W);
      tma2d(sb + OFF_WK + i * 16384, &tmWk, col, i * 128, sb + BAR_W);
    }
  }
  __syncwarp();
  mwait(sb + BAR_W, 1, spin);
  PTS(6);
#pragma unroll 1
  for (int i = 0; i < NSTEP; i++) {
    const int ph = i & 1;
    uint32_t qf[4][4];
    {
      float d[64];
#pragma unroll
      for (int p = 0; p < 5; p++) {
        mwait(sb + BAR_F + 8 * p, ph, spin);
        if (p == 0) TS(i, 0);
        wg_fence();
#pragma unroll
        for (int k = 8 * p; k < 8 * p + 8; k++) {
          wgmma_st128(d, tdesc(k), mkdesc(SB0 + OFF_WQ + k * 2048, OFF_WK - OFF_WQ, 1024), k);
          if (k == 8 * p + 1 && p >= 1 && p <= 3) {
            wg_commit(); wg_wait<1>();
            release_round(sb, p - 1, fresh(tid0));
            wg_fence();
          }
        }
        wg_commit();
      }
      wg_wait<0>();
      TS(i, 1);
      CBAR_SYNC(NB_RD, 256);
      TSB(i, 2);
      const int tid = fresh(tid0), w = (tid >> 5) & 3, m = (tid >> 3) & 3;
      const uint32_t a = sb + OFF_KT + (m >> 1) * KS + (1 + 5 * (w >> 1) + 2 * (w & 1) + (m & 1)) * 128 + (tid & 7) * 16;
#pragma unroll
      for (int s = 0; s < 4; s++)
        stsm4t(a + s * 2 * KS, pack_bf16(d[32 + 8 * s], d[33 + 8 * s]), pack_bf16(d[34 + 8 * s], d[35 + 8 * s]),
               pack_bf16(d[36 + 8 * s], d[37 + 8 * s]), pack_bf16(d[38 + 8 * s], d[39 + 8 * s]));
      fence_async();
      CBAR_ARRIVE(NB_QK, 384);
      if (OSG == 0) { if (tid == 224 && i > 0) signal_o(i - 1, cta); __syncwarp(); }
#pragma unroll
      for (int kk = 0; kk < 4; kk++)
#pragma unroll
        for (int j = 0; j < 4; j++) asm volatile("cvt.rn.bf16x2.f32 %0,%1,%2;" : "=r"(qf[kk][j]) : "f"(d[8 * kk + 2 * j + 1] * SCL), "f"(d[8 * kk + 2 * j] * SCL));
    }
    CBAR_SYNC(NB_SI, 256);
    uint32_t pf[5][4];
    float s0, s1;
    {
      float y0[10], y1[10];
      const int tid = fresh(tid0), lane = tid & 31, u = (tid >> 5) & 1;
      const bool c1 = tid & 64;
      {
        float x[40];
        wg_fence();
#pragma unroll
        for (int kk = 0; kk < 4; kk++) wgmma_rt80(x, qf[kk], mkdesc_ns(SB0 + OFF_KT + kk * 2 * KS, KS, 128), kk);
        wg_commit();
        wg_wait<0>();
#pragma unroll
        for (int j = 0; j < 5; j++) {
          y0[2 * j] = (c1 ? x[20 + 4 * j] : x[4 * j]); y0[2 * j + 1] = (c1 ? x[21 + 4 * j] : x[4 * j + 1]);
          y1[2 * j] = (c1 ? x[22 + 4 * j] : x[4 * j + 2]); y1[2 * j + 1] = (c1 ? x[23 + 4 * j] : x[4 * j + 3]);
        }
      }
      TS(i, 17);
      const uint32_t xo = OFF_XT + (c1 ? 1792 : 0) + u * 640 + lane * 16, x2 = xo + u * 512 + 512 - lane * 12;
      {
        const uint4 h0 = make_uint4(pack_h2(y0[0], y0[1]), pack_h2(y0[2], y0[3]), pack_h2(y1[0], y1[1]), pack_h2(y1[2], y1[3]));
        const uint4 h1 = make_uint4(pack_h2(y0[4], y0[5]), pack_h2(y0[6], y0[7]), pack_h2(y1[4], y1[5]), pack_h2(y1[6], y1[7]));
        const uint32_t h2 = u ? pack_h2(y1[8], y1[9]) : h1.z;
#pragma unroll
        for (int dd = 0; dd < 2; dd++) {
          const uint32_t rb = mapa(sb, (rank + 1 + dd) % 3), ro = rb + (1 - dd) * 3584;
          st_async4u(ro + xo, h0, rb + BAR_XT);
          if (u) st_async4u(ro + xo + 512, h1, rb + BAR_XT);
          st_async1u(ro + x2, h2, rb + BAR_XT);
        }
      }
      TS(i, 18);
      const int lim = 16 * u + (lane >> 2) + 8 - 2 * (lane & 3);
#pragma unroll
      for (int j = 1; j < 5; j++) {
        if (8 * j > lim) y0[2 * j] = -INFINITY;
        if (8 * j + 1 > lim) y0[2 * j + 1] = -INFINITY;
        if (8 * j - 8 > lim) y1[2 * j] = -INFINITY;
        if (8 * j - 7 > lim) y1[2 * j + 1] = -INFINITY;
      }
      mwait(sb + BAR_XT, ph, spin);
      TS(i, 19);
      {
        const uint4 u0 = lds128(sb + xo), v0 = lds128(sb + xo + 3584);
        const uint32_t u2 = lds32(sb + x2), v2 = lds32(sb + x2 + 3584);
        uint4 u1 = make_uint4(0, 0, u2, 0), v1 = make_uint4(0, 0, v2, 0);
        if (u) { u1 = lds128(sb + xo + 512); v1 = lds128(sb + xo + 512 + 3584); }
        __syncwarp();
        if (lane == 0) mbar_arrive_cluster(mapa(sb, 0) + BAR_E);
        add_h2(y0[0], y0[1], u0.x, v0.x); add_h2(y0[2], y0[3], u0.y, v0.y); add_h2(y1[0], y1[1], u0.z, v0.z); add_h2(y1[2], y1[3], u0.w, v0.w);
        add_h2(y0[4], y0[5], u1.x, v1.x); add_h2(y0[6], y0[7], u1.y, v1.y); add_h2(y1[4], y1[5], u1.z, v1.z); add_h2(y1[6], y1[7], u1.w, v1.w);
        add_h2(y1[8], y1[9], u2, v2);
      }
      y0[8] = y0[0]; y0[9] = y0[1];
      const float m0 = quad_max(max10(y0)) * -SCE, m1 = quad_max(max10(y1)) * -SCE;
      s0 = 0.f; s1 = 0.f;
#pragma unroll
      for (int j = 0; j < 5; j++) {
        const uint32_t p0 = j < 4 ? pack_bf16(ex2(fmaf(y0[2 * j], SCE, m0)), ex2(fmaf(y0[2 * j + 1], SCE, m0))) : 0u;
        const uint32_t p1 = pack_bf16(ex2(fmaf(y1[2 * j], SCE, m1)), ex2(fmaf(y1[2 * j + 1], SCE, m1)));
        s0 += bf_lo(p0) + bf_hi(p0); s1 += bf_lo(p1) + bf_hi(p1);
        pf[j >> 1][2 * (j & 1)] = c1 ? 0u : p0; pf[j >> 1][2 * (j & 1) + 1] = c1 ? 0u : p1;
        pf[(j + 5) >> 1][2 * ((j + 5) & 1)] = c1 ? p0 : 0u; pf[(j + 5) >> 1][2 * ((j + 5) & 1) + 1] = c1 ? p1 : 0u;
      }
    }
    CBAR_SYNC(NB_VQ, 256);
    TSB(i, 20);
    {
      float o[32];
      wg_fence();
#pragma unroll
      for (int q = 0; q < 5; q++) wgmma_rs64(o, pf[q], mkdesc_ns(SB0 + OFF_VT + 128 + q * 256, 128, VS), q);
      wg_commit();
      s0 = rcp(quad_sum(s0)); s1 = rcp(quad_sum(s1));
      const int tid = fresh(tid0), g = (tid >> 2) & 7, c = (tid >> 6) & 1, sg = i - c * LAG;
      uint8_t* op = pinp(&g_o[i % ORING][cta][(((tid >> 5) & 3) * 16 + g) * 128]);
      const uint32_t o0 = pin(((tid & 3) ^ g) << 4), live = pin(sg >= 0 && sg < NSEG);
      wg_wait<0>();
      TS(i, 21);
      if ((tid & 31) == 0) mbar_arrive_cluster(mapa(sb, 1) + BAR_E + 8);
      uint4 ov[4];
#pragma unroll
      for (int h = 0; h < 2; h++) {
        const float* x = o + 16 * h;
        ov[2 * h] = make_uint4(pin(pack_bf16(x[0] * s0, x[1] * s0)), pin(pack_bf16(x[4] * s0, x[5] * s0)), pin(pack_bf16(x[8] * s0, x[9] * s0)), pin(pack_bf16(x[12] * s0, x[13] * s0)));
        ov[2 * h + 1] = make_uint4(pin(pack_bf16(x[2] * s1, x[3] * s1)), pin(pack_bf16(x[6] * s1, x[7] * s1)), pin(pack_bf16(x[10] * s1, x[11] * s1)), pin(pack_bf16(x[14] * s1, x[15] * s1)));
      }
      TS(i, 22);
      if (i + 1 < NSTEP) CBAR_SYNC(NB_WQ, 256); else CBAR_ARRIVE(NB_WQ, 256);
      if (live) {
#pragma unroll
        for (int h = 0; h < 4; h++) *reinterpret_cast<uint4*>(op + (h & 1) * 1024 + (o0 ^ ((h >> 1) * 64))) = ov[h];
      }
      if (OSG && i + 1 < NSTEP) CBAR_ARRIVE(NB_MR, 160);
    }
  }
  CBAR_SYNC(NB_Q, 128);
  if (tid0 == 224) signal_o(NSTEP - 1, cta);
  if (spin >= SPIN_TOT) g_err = 2;
}

template <int NL>
__device__ __forceinline__ void poll_add(const uint8_t* mb, uint32_t tag, float (&f)[8], uint8_t* flag, bool lead, int osig, int& n, int& spin) {
  uint4 x[NL];
#pragma unroll
  for (int i = 0; i < NL; i++) x[i] = ld_relaxed128(mb + i * 512);
  if (OSG == 1 && osig >= 0) csignal(osig);
  while (true) {
    uint32_t any = 0;
#pragma unroll
    for (int i = 0; i < NL; i++) any |= (x[i].x ^ tag) | (NL == 6 ? x[i].z ^ tag : 0u);
    n++;
    if (!__any_sync(0xffffffffu, (any & 1) && spin < SPIN_TOT)) break;
    spin += 16;
#pragma unroll
    for (int i = 0; i < NL; i++)
      if (((pin(x[i].x) ^ tag) | (NL == 6 ? x[i].z ^ tag : 0u)) & 1) x[i] = ld_relaxed128(mb + i * 512);
  }
  if (FLP == 0 && lead) st_relaxed(flag, 0);
#pragma unroll
  for (int i = 0; i < NL; i++) {
    const uint32_t u[4] = {x[i].x, x[i].y, x[i].z, x[i].w};
#pragma unroll
    for (int j = 0; j < 4; j++) {
      if (i == 0) { f[2 * j] = bf_lo(u[j]); f[2 * j + 1] = bf_hi(u[j]); }
      else { f[2 * j] += bf_lo(u[j]); f[2 * j + 1] += bf_hi(u[j]); }
    }
  }
}

template <int B, int SLOT>
__device__ __forceinline__ void wo_block(float (&acc)[8], const uint32_t (&wf)[C::NKR][4]) {
  using namespace C;
#pragma unroll
  for (int kk = 0; kk < 4; kk++) {
    const int k = 4 * B + kk;
    const uint64_t db = mkdesc_ns(SB0 + og_off(SLOT) + kk * 512, 256, 128);
    if (k < NKR) wgmma_rt16(acc, wf[k < NKR ? k : 0], db, SLOT | kk);
    else wgmma_tt16(acc, wdesc(OFF_YO + (k - NKR) * 2048), db, 1);
  }
}

__device__ __forceinline__ void chain_a(const uint32_t sb, const int tid0, const int cta, const int rank) {
  using namespace C;
  asm volatile("setmaxnreg.inc.sync.aligned.u32 200;");
  int spin = 0;
  uint32_t wf[NKR][4];
  mwait(sb + BAR_W, 0, spin);
  permute_cols(sb + OFF_WQ, tid0, 2560);
  CBAR_SYNC(NB_A, 128);
  load_weights_rs<true>(wf, sb, OFF_WQ, OFF_YO, tid0);
  const int wu = uni(tid0 >> 5);
  const int head = cta / 3;
  const bool t9 = head >= 24 && rank > 0;
  const uint64_t exa = reinterpret_cast<uint64_t>(ex_window(g_ex));
  const uint32_t ehi = (uint32_t)(exa >> 32), elo = (uint32_t)exa;

#pragma unroll 1
  for (int i = -1; i < NSTEP; i++) {
    const int ph = i & 1;
    if (i >= 0) {
      const int tid = fresh(tid0);
      const uint32_t mo = __shfl_xor_sync(0xffffffffu, elo + (ph << 20) + ((rank * 8 + (tid >> 4)) * 4 + (tid & 3)) * 2048 + head * 64 + (tid & 12) * 4, 0);
      const uint32_t m9 = __shfl_xor_sync(0xffffffffu, elo + (ph << 20) + MAIL9 + (((tid >> 4) * 2 + (tid & 1)) * 4 + (tid & 2)) * 3072 + cta * 32 + (tid & 12) * 2, 0);
      const uint32_t oo = __shfl_xor_sync(0xffffffffu, (tid >> 5) * 512 + (tid & 2) * 64 + (tid & 28) * 4 + (tid & 1) * 8, 0);
      if (i == 0) mwait(sb + BAR_W, 1, spin);
      mwait(sb + BAR_M, ph, spin);
      TS(i, 3);
      {
        float x[20];
        int redo = 0;
      retry:
        bool bad;
        {
          float dq[8], dk[8];
          const bool w1 = mbar_test(sb + BAR_M + 8, ph), w2 = mbar_test(sb + BAR_M + 16, ph);
          wg_fence();
#pragma unroll
          for (int j = 0; j < 40; j++) {
            if (j == m_wave(1) || j == m_wave(2)) {
              wg_commit();
              if (!(j == m_wave(1) ? w1 : w2)) mwait(sb + BAR_M + (j == m_wave(1) ? 8 : 16), ph, spin);
            }
            if (j == 40 - QIE / 2 && !redo) CBAR_ARRIVE(NB_QI, 256);
            wgmma_ts16(dq, wdesc(OFF_WQ + m_kstep(j) * 2048), mdesc(j), j);
            wgmma_ts16(dk, wdesc(OFF_WK + m_kstep(j) * 2048), mdesc(j), j);
          }
          wg_commit();
          const int m = (tid >> 3) & 3, dg = (tid >> 5) * 2 + (m & 1);
          const uint32_t ka = sb + OFF_KT + dg * KS + (m >> 1) * 640 + (tid & 7) * 16;
          if (!redo) CBAR_SYNC(NB_QK, 384);
          sts32(sb + FLG_REDO, redo);
          wg_wait<0>();
          TS(i, 4);
          stsm4(ka, pack_bf16(dk[0], dk[1]), pack_bf16(dk[2], dk[3]), pack_bf16(dk[4], dk[5]), pack_bf16(dk[6], dk[7]));
          stsm4(ka + dg * (VS - KS) + (OFF_VT + 128 - OFF_KT), pack_bf16(dq[0] * SCL, dq[1] * SCL), pack_bf16(dq[2] * SCL, dq[3] * SCL),
                pack_bf16(dq[4] * SCL, dq[5] * SCL), pack_bf16(dq[6] * SCL, dq[7] * SCL));
          const float chk = (dq[0] + dq[1]) + (dq[4] + dq[5]);
          fence_async();
          bad = bar_red_or(NB_C, 128, chk != chk && !redo);
        }
        TSB(i, 5);
        wg_fence();
#pragma unroll
        for (int kk = 0; kk < 4; kk++) wgmma_tt40(x, mkdesc_ns(SB0 + OFF_VT + 128 + kk * 2 * VS, VS, 640), mkdesc_ns(SB0 + OFF_KT + kk * 2 * KS, KS, 128), kk);
#pragma unroll
        for (int kk = 0; kk < 4; kk++) {
          if (SIE && kk == 4 - SIE && !bad) CBAR_ARRIVE(NB_SI, 256);
          wgmma_tt40(x, mkdesc_ns(SB0 + OFF_VT + kk * 2 * VS, VS, 384), mkdesc_ns(SB0 + OFF_KT + 640 + kk * 2 * KS, KS, 128), 1);
        }
        wg_commit();
        if (!SIE && !bad) CBAR_ARRIVE(NB_SI, 256);
        if (__builtin_expect(__any_sync(0xffffffffu, bad), 0)) {
          wg_wait<0>();
#pragma unroll 1
          for (int k = 0; k < 10; k++) {
            uint4 v = lds128(sb + OFF_M + tid * 16 + k * 2048);
            if (v.x == SENT || v.y == SENT || v.z == SENT || v.w == SENT) {
              do { v = ld_relaxed4(mkptr(elo + EX_M + i * 20480 + tid * 16 + k * 2048, ehi)); spin += 16; } while ((v.x == SENT || v.y == SENT || v.z == SENT || v.w == SENT) && spin < SPIN_TOT);
              sts128(sb + OFF_M + tid * 16 + k * 2048, v);
            }
          }
          fence_async();
          bar_sync(NB_C, 128);
          redo = fresh(1);
          goto retry;
        }
        TSV(i, 36, redo);
        const uint32_t rb1 = mapa(sb, (rank + 1) % 3), rb2 = mapa(sb, (rank + 2) % 3);
        wg_wait<0>();
        TS(i, 6);
        if (wu < 2) {
          float y[10];
#pragma unroll
          for (int j = 0; j < 5; j++) { y[2 * j] = x[4 * j]; y[2 * j + 1] = x[4 * j + 1]; }
          const uint4 h0 = make_uint4(pack_h2(y[0], y[1]), pack_h2(y[2], y[3]), pack_h2(y[4], y[5]), pack_h2(y[6], y[7]));
          const uint32_t h1 = pack_h2(y[8], y[9]);
          st_async4u(rb1 + OFF_XM + 1024 + tid * 16, h0, rb1 + BAR_XM);
          st_async4u(rb2 + OFF_XM + tid * 16, h0, rb2 + BAR_XM);
          st_async1u(rb1 + OFF_XM + 2304 + tid * 4, h1, rb1 + BAR_XM);
          st_async1u(rb2 + OFF_XM + 2048 + tid * 4, h1, rb2 + BAR_XM);
          CBAR_ARRIVE(NB_SM, 256);
          if ((tid & 31) == 0) mbar_arrive_cluster(mapa(sb, 0) + BAR_E);
          TS(i, 7);
          const uint32_t sw = (tid & 7) * 4 + (tid & 8) * 8 + (tid & 16) * 2;
          mwait(sb + BAR_XM, ph, spin);
          TS(i, 8);
          const uint4 u0 = lds128(sb + OFF_XM + tid * 16), v0 = lds128(sb + OFF_XM + 1024 + tid * 16);
          const uint32_t u1 = lds32(sb + OFF_XM + 2048 + tid * 4), v1 = lds32(sb + OFF_XM + 2304 + tid * 4);
          add_h2(y[0], y[1], u0.x, v0.x); add_h2(y[2], y[3], u0.y, v0.y); add_h2(y[4], y[5], u0.z, v0.z); add_h2(y[6], y[7], u0.w, v0.w);
          add_h2(y[8], y[9], u1, v1);
          const float mx = quad_max(max10(y)) * -SCE;
#pragma unroll
          for (int j = 0; j < 5; j++) {
            y[2 * j] = ex2(fmaf(y[2 * j], SCE, mx)); y[2 * j + 1] = ex2(fmaf(y[2 * j + 1], SCE, mx));
            sts32(sb + OFF_PT + wu * 640 + sw + j * 128, pack_bf16(y[2 * j], y[2 * j + 1]));
          }
          sts32(sb + OFF_XM + 2048 + wu * 128 + sw, __float_as_uint(sum10(y)));
          fence_async();
          TS(i, 9);
        } else {
          CBAR_ARRIVE(NB_SM, 256);
          if ((tid & 31) == 0) mbar_arrive_cluster(mapa(sb, 0) + BAR_E);
          mwait(sb + BAR_MF, ph, spin);
        }
      }
      CBAR_SYNC(NB_VA, 256);
      TSB(i, 10);
      {
        float o[2][4];
        wg_fence();
#pragma unroll
        for (int c = 0; c < 2; c++)
#pragma unroll
          for (int q = 0; q < 3; q++)
            wgmma_ss8(o[c], mkdesc_ns(SB0 + OFF_VT + 128 + c * 640 + q * 256, 128, VS), mkdesc_ns(SB0 + OFF_PT + c * 640 + q * 256, q == 2 && c == 0 ? 768 : 128, 128), q);
        wg_commit();
        const float4 e = lds128f(sb + OFF_XM + 2048 + (tid & 15) * 16);
        const uint32_t rb1 = mapa(sb, (rank + 1) % 3), rb2 = mapa(sb, (rank + 2) % 3);
        const float inv = rcp((e.x + e.y) + (e.z + e.w));
        const int sl = (tid & 3) * 2;
        const float i0 = __shfl_sync(0xffffffffu, inv, sl), i1 = __shfl_sync(0xffffffffu, inv, sl + 1);
        const float i2 = __shfl_sync(0xffffffffu, inv, sl + 8), i3 = __shfl_sync(0xffffffffu, inv, sl + 9);
        wg_wait<0>();
        TS(i, 11);
        const uint32_t p0 = pack_bf16(o[0][0] * i0, o[0][1] * i1), p1 = pack_bf16(o[1][0] * i2, o[1][1] * i3);
        const uint32_t p2 = pack_bf16(o[0][2] * i0, o[0][3] * i1), p3 = pack_bf16(o[1][2] * i2, o[1][3] * i3);
        if (OGF) { sts64(sb + oo + og_off(0), p0, p1); sts64(sb + oo + og_off(0) + 256, p2, p3); fence_async(); }
        st_async2u(rb1 + oo + og_off(2), p0, p1, rb1 + BAR_OG);
        st_async2u(rb2 + oo + og_off(1), p0, p1, rb2 + BAR_OG);
        st_async2u(rb1 + oo + og_off(2) + 256, p2, p3, rb1 + BAR_OG);
        st_async2u(rb2 + oo + og_off(1) + 256, p2, p3, rb2 + BAR_OG);
        if (!OGF) { sts64(sb + oo + og_off(0), p0, p1); sts64(sb + oo + og_off(0) + 256, p2, p3); fence_async(); }
      }
      CBAR_SYNC(NB_A, 128);
      TSB(i, 12);
      {
        float acc[3][8];
        wg_fence();
        wo_block<0, 0>(acc[2], wf);
        wg_commit();
        wo_block<1, 0>(acc[0], wf);
        wo_block<4, 0>(acc[1], wf);
        wg_commit();
        const bool og = mbar_try(sb + BAR_OG, ph);
        const uint32_t tag = (i >> 1) & 1;
#define TAGGED(LO, HI) ((pack_bf16(LO, HI) & ~1u) | tag)
#define SEND(OFF, U) st_relaxed128(mkptr(mo, ehi) + (OFF), TAGGED(acc[U][0], acc[U][2]), pack_bf16(acc[U][1], acc[U][3]), pack_bf16(acc[U][4], acc[U][6]), pack_bf16(acc[U][5], acc[U][7]))
        wg_wait<1>();
        const uint32_t n0 = pin(TAGGED(acc[2][0], acc[2][2])), n1 = pin(pack_bf16(acc[2][1], acc[2][3]));
        const uint32_t n2 = pin(TAGGED(acc[2][4], acc[2][6])), n3 = pin(pack_bf16(acc[2][5], acc[2][7]));
        if (__builtin_expect(!og, 0)) mwait(sb + BAR_OG, ph, spin);
        asm volatile("fence.proxy.async::generic.acquire.sync_restrict::shared::cluster.cluster;" ::: "memory");
        TS(i, 13);
        wg_fence();
        wo_block<2, 1>(acc[0], wf); wo_block<3, 2>(acc[0], wf);
        wg_commit();
        st_relaxed64(mkptr(m9, ehi), n0, n1);
        st_relaxed64(mkptr(m9, ehi) + 3072, n2, n3);
        if ((tid & 31) == 0) mbar_arrive_cluster(mapa(sb, 1) + BAR_E + 8);
        wo_block<5, 1>(acc[1], wf); wo_block<6, 2>(acc[1], wf);
        wg_commit();
        wo_block<7, 0>(acc[2], wf);
        wg_commit();
        wg_wait<2>(); SEND(0, 0);
        wo_block<8, 1>(acc[2], wf); wo_block<9, 2>(acc[2], wf);
        wg_commit();
        if (WOE == 0) { CBAR_ARRIVE(NB_WV, 256); CBAR_ARRIVE(NB_WQ, 256); }
        wg_wait<2>(); SEND(24 * 8192, 1);
        if (WOE == 1) CBAR_ARRIVE(NB_WV, 256);
        wg_wait<0>(); SEND(48 * 8192, 2);
        if (WOE == 2) CBAR_ARRIVE(NB_WV, 256);
        if (WOE >= 1) CBAR_ARRIVE(NB_WQ, 256);
#undef SEND
#undef TAGGED
      }
      TS(i, 14);
      if (i + 1 >= NSTEP) break;
    }
    uint32_t t1 = clk32();
    if (i >= 0) {
      const int lane = fresh(tid0) & 31, j = lane >> 3;
      const uint8_t* mb = mkptr(elo + (ph << 20) + (t9 ? MAIL9 + (rank * 8 + head - 32) * 12288 + wu * 3072 : (rank * 24 + head % 24) * 8192 + wu * 2048) + lane * 16, ehi);
      const uint32_t tag = (i >> 1) & 1;
      const bool pub = (lane & (t9 ? 6 : 4)) == 0 && !(((t9 ? head : wu) & 1) && i + 1 == LAG) && (t9 || head < 24);
      const uint32_t dst = pin(elo + EX_M + (i + 1) * 20480 + (rank * 7168 - (rank ? 1024 : 0)) +
                               (t9 ? (head + 24) * 128 + wu * 32 + (j & 1) * 16 + (lane & 1) * 8 + (j >> 1) * 4
                                   : head * 256 + (wu & 1) * 128 + (wu >> 1) * 64 + j * 16 + (lane & 3) * 4));
      uint8_t* flag = mkptr(elo + EX_FLAG + (i + 1) * 3072 + (rank * 32 + head) * 32 + wu * 4, ehi);
      const int osig = OSG == 1 && tid0 == 96 ? CN_O + i * 5 + min(cta / 19, 4) : -1;
      if (OSG && wu == 3) CBAR_SYNC(NB_MR, 160);
      while (clk32() - t1 < B1 - (2 - rank) * B1D) {}
      TS(i + 1, 30);
      float f[8];
      int n = 0;
      if (!t9) poll_add<4>(mb, tag, f, flag, lane == 0, osig, n, spin);
      else poll_add<6>(mb, tag, f, flag, lane == 0, osig, n, spin);
      if (FLP == 1 && lane == 0) st_relaxed(flag, __float_as_uint(f[0] + f[7]) >> 1);
      t1 = clk32();
      TS(i + 1, 31); TSV(i + 1, 32, n);
      const bool h = lane & 16, q = lane & 8;
#pragma unroll
      for (int j = 0; j < 4; j++) f[j] = (h ? f[4 + j] : f[j]) + __shfl_xor_sync(0xffffffffu, h ? f[j] : f[4 + j], 16);
#pragma unroll
      for (int j = 0; j < 2; j++) f[j] = (q ? f[2 + j] : f[j]) + __shfl_xor_sync(0xffffffffu, q ? f[j] : f[2 + j], 8);
      f[0] += __shfl_xor_sync(0xffffffffu, f[0], 4); f[1] += __shfl_xor_sync(0xffffffffu, f[1], 4);
      if (t9) { f[0] += __shfl_xor_sync(0xffffffffu, f[0], 2); f[1] += __shfl_xor_sync(0xffffffffu, f[1], 2); }
      if (pub) st_relaxed(mkptr(dst, ehi), pack_bf16(f[0], f[1]));
      if (FLP == 2 && lane == 0) st_relaxed(flag, 0);
      if (OSG == 2 && tid0 == 96) { TS1(i + 1, 38); signal_o(i, cta); TS1(i + 1, 39); }
      if (OSG == 4 && tid0 == 96) asm volatile("red.relaxed.gpu.global.add.u32 [%0],1;" ::"l"(&g_cnt[CN_O + i * 5 + min(cta / 19, 4)][0]) : "memory");
      TS(i + 1, 15);
    }
    if (wu == 0) {
      const int tid = fresh(tid0);
      const uint8_t* pp = mkptr(elo + EX_FLAG + (i + 1) * 3072 + (rank * 32 + (tid < 24 || rank ? tid : 0)) * 32, ehi);
      while (clk32() - t1 < B2) {}
      TS(i + 1, 16);
      int n = 1;
      uint4 x = ld_relaxed4(pp);
      if (tid < 3) mbar_expect_tx(sb + BAR_M + 8 * tid, tid ? 7168 : 6144);
      bool mok = mbar_test(sb + BAR_MOK, ph ^ 1);
      while (__any_sync(0xffffffffu, (int)(x.x | x.y | x.z | x.w) < 0 && spin < SPIN_TOT)) { x = ld_relaxed4(pp); mok = mbar_test(sb + BAR_MOK, ph ^ 1); n++; spin += 16; }
      if (!mok) mwait(sb + BAR_MOK, ph ^ 1, spin);
      TSV(i + 1, 35, n);
      TS(i + 1, 34);
      if (tid0 == 0) {
        const int o = rank * 7168 - (rank ? 1024 : 0);
        bulk_g2s_mc(sb + OFF_M + o, mkptr(elo + EX_M + (i + 1) * 20480 + o, ehi), rank ? 7168 : 6144, sb + BAR_M + 8 * rank);
      }
      TS(i + 1, 33);
      __syncwarp();
    }
  }
  if (spin >= SPIN_TOT) g_err = 1;
}

__global__ void __cluster_dims__(3, 1, 1) __launch_bounds__(384, 1)
k_chain(const __grid_constant__ CUtensorMap tmWq, const __grid_constant__ CUtensorMap tmWk,
        const __grid_constant__ CUtensorMap tmWv, const __grid_constant__ CUtensorMap tmWo) {
  using namespace C;
  extern __shared__ __align__(1024) uint8_t smem[];
  const uint32_t sb = smem_u32(smem);
  const int tid = threadIdx.x;
  const int wg = __shfl_sync(0xffffffffu, tid >> 7, 0);
  const int cta = uni(blockIdx.x), rank = uni(blockIdx.x % 3);

  asm volatile("griddepcontrol.launch_dependents;");
  if (tid == 0) {
    if ((sb & 0xFFFFFF) != SB0) g_err = 100;
    for (int p = 0; p < 5; p++) { mbar_init(sb + BAR_F + 8 * p, 1); mbar_init(sb + BAR_E + 8 * p, p == 2 ? 12 : 24); }
    mbar_init(sb + BAR_M, 1); mbar_init(sb + BAR_M + 8, 1); mbar_init(sb + BAR_M + 16, 1); mbar_init(sb + BAR_MOK, 24); mbar_init(sb + BAR_XM, 1); mbar_init(sb + BAR_XF, 2);
    mbar_init(sb + BAR_XT, 1); mbar_init(sb + BAR_MF, 8); mbar_init(sb + BAR_OG, 1); mbar_init(sb + BAR_W, 1);
    for (int p = 0; p < 5; p++) mbar_expect_tx(sb + BAR_F + 8 * p, 16384);
    for (int p = 0; p < 16; p++) sts32(sb + OFF_SAFE + 4 * p, 0);
    asm volatile("fence.mbarrier_init.release.cluster;" ::: "memory");
    fence_async();
    mbar_expect_tx(sb + BAR_W, 163840);
    const int head = cta / 3, col = head * DH + rank * 64;
    tma2d(sb + OFF_WQ, &tmWo, 576, col, sb + BAR_W);
    for (int i = 0; i < 9; i++) tma2d(sb + OFF_WQ + (i + 1) * 8192, &tmWo, (3 * rank + i / 3) * 64, head * DH + ((rank + i) % 3) * 64, sb + BAR_W);
    for (int i = 0; i < 5; i++) tma2d(sb + OFF_WK + i * 16384, &tmWv, col, i * 128, sb + BAR_W);
  }
  __syncthreads();
  asm volatile("barrier.cluster.arrive.release.aligned;" ::: "memory");
  asm volatile("barrier.cluster.wait.acquire.aligned;" ::: "memory");

  if (wg == 0) chain_a(sb, keep(tid), cta, rank);
  else if (wg == 1) chain_q(tmWq, tmWk, sb, keep(tid), cta, rank);
  else chain_v(sb, keep(tid), cta, rank);
  asm volatile("barrier.cluster.arrive.release.aligned;" ::: "memory");
  asm volatile("barrier.cluster.wait.acquire.aligned;" ::: "memory");
}

namespace W {
constexpr int NP = 25, NBC = 11, NW = NP + NBC;
constexpr int PRS = 37, PW = 43 * 2048;
constexpr int OFF_W = 0;
constexpr int OFF_R = 2 * PW;
constexpr int QRS = 35, KRS = 37;
constexpr int OFF_WV = 0, OFF_YQ = 81920, OFF_YK = OFF_YQ + (40 - QRS) * 2048, OFF_WO = OFF_YK + (40 - KRS) * 2048;
constexpr int OFF_G = OFF_WO + 39 * 2048;
constexpr int OFF_X = OFF_G + 12288;
constexpr int COL = 976;
constexpr int OFF_T = OFF_X + 8192;
constexpr int OFF_H = OFF_X + 32768;
constexpr int OFF_BAR = OFF_H + 8 * COL;
constexpr int OFF_SAFE = OFF_BAR + 192;
constexpr int SMEM = 232448;
static_assert(OFF_SAFE + 64 <= SMEM && OFF_R + 40960 <= OFF_BAR, "");
constexpr uint32_t SB0 = 1024;
constexpr int BAR_F = OFF_BAR, BAR_E = OFF_BAR + 40, BAR_G = OFF_BAR + 80, BAR_H = OFF_BAR + 120, BAR_W = OFF_BAR + 160;
constexpr int NB_G0 = 1, NB_SG = 4, NB_B = 5, NB_AS = 6, NB_PK = 8, NB_PV = 9, NB_TD = 10;
}
#define WOP 0
#define WBAR_SYNC(id, n) bar_sync(id, n)
#define WBAR_ARRIVE(id, n) bar_arrive(id, n)

__device__ __forceinline__ uint64_t rdesc(int off, int kk) { return mkdesc(W::SB0 + off + kk * 32, 16, 1024); }
__device__ __forceinline__ uint32_t frag_addr(uint32_t base, int tid) {
  const int i = (tid >> 3) & 3, r = tid & 7;
  return base + (r + (i >> 1) * 8) * 128 + (((2 * ((tid >> 5) & 3) + (i & 1)) ^ r) << 4);
}
template <int NK>
__device__ __forceinline__ void load_frags(uint32_t (&wf)[NK][4], uint32_t base, int tid) {
  const uint32_t a0 = frag_addr(base, tid);
#pragma unroll
  for (int k = 0; k < NK; k++) ldsm4t(wf[k], a0 + k * 2048);
}
__device__ __forceinline__ void red_tile(const float* d, int seg, int col0, int tid) {
  float* p = g_x + (size_t)(seg * 32 + 2 * (tid & 3)) * DM + col0 + ((tid >> 5) & 3) * 16 + ((tid >> 2) & 7) * 2;
#pragma unroll
  for (int j = 0; j < 8; j++)
    asm volatile("red.relaxed.gpu.global.add.v2.f32 [%0],{%1,%2};" ::"l"(p + ((j >> 1) * 8 + (j & 1)) * DM), "f"(d[4 * (j >> 1) + (j & 1)]), "f"(d[4 * (j >> 1) + 2 + (j & 1)]) : "memory");
}
#define FOR_SEGS(l, s)                                            \
  for (int j_ = 0; j_ < 2 * NSTEP; j_++) {                        \
    const int l = j_ & 1, s = (j_ >> 1) - l * LAG;                \
    if (s < 0 || s >= NSEG) continue;

template <int WG>
__device__ __forceinline__ void work_p(const CUtensorMap& tmWo, uint32_t sb, int pc, int tid0) {
  using namespace W;
  asm volatile("setmaxnreg.inc.sync.aligned.u32 208;");
  int spin = 0;
  const int ks = pc / 5, col0 = (pc % 5) * 128 + WG * 64;
  const uint32_t wb = sb + OFF_W + WG * PW;
  uint32_t wf[PRS][4];
#pragma unroll 1
  for (int hf = 0; hf < 2; hf++) {
    const int nk = hf ? 80 - PRS : PRS;
    if ((tid0 & 127) == 0) {
      mbar_expect_tx(sb + BAR_W + 8 * WG, nk * 2048);
      for (int i = 0; i < nk; i++) tma2d(wb + i * 2048, &tmWo, col0, ks * 19 * 64 + (i < PRS ? 2 * i + hf : PRS + i) * 16, sb + BAR_W + 8 * WG);
    }
    __syncwarp();
    mwait(sb + BAR_W + 8 * WG, hf, spin);
    permute_cols(wb, tid0 & 127, nk * 64);
    if (hf == 1 && ks < 4) for (int it = 39 * 64 + (tid0 & 127) - 64; it < 43 * 64; it += 128) {
      const uint32_t a = wb + (it >> 2) * 128 + (((2 * (it & 3)) ^ ((it >> 2) & 6)) << 4);
      if (it >= 39 * 64) { sts128(a, make_uint4(0, 0, 0, 0)); sts128(a + 16, make_uint4(0, 0, 0, 0)); }
    }
    fence_async();
    WBAR_SYNC(NB_G0 + WG, 128);
    if (hf == 0) {
      load_frags<PRS>(wf, wb, tid0);
      fence_async();
      WBAR_SYNC(NB_G0 + WG, 128);
    }
  }
#pragma unroll 1
  for (int k = 0; k < NSTEP; k++) {
    float d[32];
#pragma unroll
    for (int f = 0; f < 20; f++) {
      mwait(sb + BAR_F + 8 * (f % 5), (f / 5) & 1, spin);
      if (f == 0 && WG == 0 && pc == WW) WTS(k, 1);
      wg_fence();
#pragma unroll
      for (int kk = 0; kk < 4; kk++) {
        const int q = 4 * f + kk;
        if (q < 2 * PRS && !(q & 1)) wgmma_rs64(d, wf[q < 2 * PRS ? q >> 1 : 0], rdesc(OFF_R + (f % 5) * 8192, kk), q);
        else wgmma_ts64(d, mkdesc(SB0 + OFF_W + WG * PW + (q < 2 * PRS ? q >> 1 : q - PRS) * 2048, 8192, 1024), rdesc(OFF_R + (f % 5) * 8192, kk), 1);
        if (kk == 0 && f > 0) {
          wg_commit();
          wg_wait<1>();
          if ((tid0 & 31) == 0) mbar_arrive(sb + BAR_E + 8 * ((f - 1) % 5));
        }
      }
      wg_commit();
    }
    wg_wait<0>();
    if ((tid0 & 31) == 0) mbar_arrive(sb + BAR_E + 32);
    if (WG == 0 && pc == WW) WTS(k, 2);
    if (k < NSEG) red_tile(d, k, col0, tid0);
    if (k >= LAG) red_tile(d + 16, k - LAG, col0, tid0);
    if (WG == 0 && pc == WW) WTS(k, 13);
    WBAR_SYNC(NB_SG, 256);
    if (WG == 0) { if (tid0 == 0) csignal_t(CN_P + k, 3); __syncwarp(); }
  }
  if (spin >= SPIN_TOT) g_err = 11;
}
__device__ __forceinline__ void work_p_producer(uint32_t sb, int pc, int odd) {
  using namespace W;
  int spin = 0;
  const int ks = pc / 5;
#pragma unroll 1
  for (int k = 0; k < NSTEP; k++) {
    const uint32_t lo = k < NSEG ? 0 : 4096, len = k < LAG || k >= NSEG ? 4096 : 8192;
    const uint8_t* src = &g_o[k % ORING][ks * 19 + odd][lo];
    cwait(CN_O + k * 5 + ks, ks == 4 ? 20 : 19, spin);
    fence_async_all();
    if (pc == WW && !odd) WTS1(k, 0);
#pragma unroll
    for (int u = 0; u < 10; u++) {
      const int st = odd ? (2 * u + 1) % 5 : (2 * u) % 5, ph = odd ? ((2 * u + 1) / 5) & 1 : ((2 * u) / 5) & 1;
      mwait(sb + BAR_E + 8 * st, ph ^ 1, spin);
      if (u == 9 && odd && ks < 4) mbar_arrive(sb + BAR_F + 8 * st);
      else {
        mbar_expect_tx(sb + BAR_F + 8 * st, len);
        bulk_g2s(sb + OFF_R + st * 8192 + lo, src + u * 16384, len, sb + BAR_F + 8 * st);
      }
    }
  }
  if (spin >= SPIN_TOT) g_err = 12;
}
__device__ __forceinline__ float warp_sum(float x) {
  x = quad_sum(x);
  const float a = __shfl_xor_sync(0xffffffffu, x, 4), b = __shfl_xor_sync(0xffffffffu, x, 8), c = __shfl_xor_sync(0xffffffffu, x, 12);
  x = (x + a) + (b + c);
  return x + __shfl_xor_sync(0xffffffffu, x, 16);
}
__device__ __forceinline__ void work_ln(int kind, int r, int lane, bf16* out) {
  int spin = 0;
  const int l = kind & 1;
  const int rp = kind < 2 ? (r & 1) * 16 + (r >> 1) : r;
  const uint32_t sw = ((((lane >> 1) & 7) ^ (rp & 7)) << 4) + (lane & 1) * 8;
  uint8_t* dst = kind < 2 ? g_xnb[l * LAG] + (lane >> 4) * 8192 + l * 4096 + rp * 128 + sw
               : kind == 2 ? g_xn[1] + (r >> 3) * 2048 + (lane >> 4) * 1024 + (r & 7) * 128 + sw
                           : reinterpret_cast<uint8_t*>(out) + r * 1280 + lane * 8;
  const int dm = kind < 2 ? 16384 : kind == 2 ? 8192 : 256, ds = kind < 2 ? 81920 : 40960;
#pragma unroll 1
  for (int s = 0; s < NSEG; s++) {
    const float* xr = g_x + (size_t)(s * 32 + r) * DM;
    if (kind == 0 && lane < 20 && s + 3 < NSEG) prefetch_l2(xr + 96 * DM + lane * 32);
    if (lane == 0) cwait(kind < 2 ? CN_P + s + l * LAG : CN_W + l * 64 + s, kind < 2 ? W::NP : 10, spin);
    __syncwarp();
    if (r == 0 && lane == 0 && (l == 0 || s + LAG >= NSEG)) WTS1(s + l * LAG, kind < 2 ? 3 : 11);
    float4 v[5];
#pragma unroll
    for (int m = 0; m < 5; m++) v[m] = ld_relaxed4f(xr + m * 128 + lane * 4);
    if (kind < 3) {
      float t = 0.f;
#pragma unroll
      for (int m = 0; m < 5; m++) t += (v[m].x + v[m].y) + (v[m].z + v[m].w);
      const float mean = warp_sum(t) * (1.f / DM);
      float q0 = 0.f, q1 = 0.f;
#pragma unroll
      for (int m = 0; m < 5; m++) {
        v[m].x -= mean; v[m].y -= mean; v[m].z -= mean; v[m].w -= mean;
        q0 += v[m].x * v[m].x + v[m].y * v[m].y; q1 += v[m].z * v[m].z + v[m].w * v[m].w;
      }
      const float rs = rsqrtf(warp_sum(q0 + q1) * (1.f / DM) + 1e-5f);
#pragma unroll
      for (int m = 0; m < 5; m++) { v[m].x *= rs; v[m].y *= rs; v[m].z *= rs; v[m].w *= rs; }
    }
#pragma unroll
    for (int m = 0; m < 5; m++) *reinterpret_cast<uint2*>(dst + (size_t)s * ds + m * dm) = make_uint2(pack_bf16(v[m].x, v[m].y), pack_bf16(v[m].z, v[m].w));
    __syncwarp();
    if (r == 0 && lane == 0 && (l == 0 || s + LAG >= NSEG)) WTS1(s + l * LAG, kind < 2 ? 4 : 12);
    if (lane == 0 && kind < 3) csignal_t(kind < 2 ? CN_L + s + l * LAG : CN_X + s, kind);
  }
  if (spin >= SPIN_TOT) g_err = 13;
}

__device__ __forceinline__ void stage_qkv(const bf16* wqkv, uint32_t base, int T, int bc, int tid) {
  const int q = tid & 15;
  const bool ok = q < 15 && bc * 60 + 4 * q < DM;
  const bf16* src = wqkv + T * DM + bc * 60 + 4 * q;
#pragma unroll 1
  for (int k0 = tid >> 4; k0 < 640; k0 += 80) {
    uint2 v[10];
#pragma unroll
    for (int u = 0; u < 10; u++) v[u] = ok ? *reinterpret_cast<const uint2*>(src + (size_t)(k0 + 8 * u) * 1920) : make_uint2(0, 0);
#pragma unroll
    for (int u = 0; u < 10; u++) sts64(base + (k0 + 8 * u) * 128 + (((q >> 1) ^ (k0 & 7)) << 4) + (q & 1) * 8, v[u].x, v[u].y);
  }
}
__device__ __forceinline__ void attend(uint32_t sb, int bc, int l, int s, int p, int tid) {
  using namespace W;
  const int r = tid & 7, m = (tid >> 3) & 3, hh = (tid >> 5) & 3, g = (tid >> 2) & 7, t = tid & 3;
  const int f2 = r < 4 ? 20 * hh + 16 + r : 60;
  const uint32_t tb = sb + OFF_T + (l * 4 + 2 * p) * COL, hb = sb + OFF_H + (l * 2 + p) * COL;
  const uint32_t ko = (m < 2 ? 20 * hh + 8 * m + r : f2) * 16, vo = (m < 2 ? 20 * hh + 4 * (r >> 1) + 2 * m + (r & 1) : f2) * 16;
  const float scl = 0.22360679774997896f * 1.4426950408889634f;
  float sc[3][4];
  {
    uint32_t q[4], q8a, q8b, k[3][4];
    ldsm4t(q, tb + (m & 1) * COL + (20 * hh + (m >> 1) * 8 + r) * 16);
    ldsm2t(q8a, q8b, tb + (m & 1) * COL + f2 * 16);
    ldsm4t(k[0], hb + ko); ldsm4t(k[1], tb + 8 * COL + ko); ldsm4t(k[2], tb + 9 * COL + ko);
#pragma unroll
    for (int c = 0; c < 3; c++) { sc[c][0] = sc[c][1] = sc[c][2] = sc[c][3] = 0.f; mma16816(sc[c], q[0], q[1], q[2], q[3], k[c][0], k[c][1]); }
#pragma unroll
    for (int c = 0; c < 3; c++) mma1688(sc[c], q8a, q8b, k[c][2]);
  }
  uint32_t v[3][4];
  ldsm4(v[0], hb + 4 * COL + vo); ldsm4(v[1], tb + 16 * COL + vo); ldsm4(v[2], tb + 17 * COL + vo);
  const bool lo0 = 2 * t > g, lo1 = 2 * t + 1 > g;
  uint32_t pw[2];
  float inv[2];
#pragma unroll
  for (int h = 0; h < 2; h++) {
    float y0 = lo0 ? sc[h][2 * h] : sc[h + 1][2 * h], y1 = lo1 ? sc[h][2 * h + 1] : sc[h + 1][2 * h + 1];
    if (h == 0 && s == 0) { y0 = lo0 ? -INFINITY : y0; y1 = lo1 ? -INFINITY : y1; }
    const float mx = quad_max(fmaxf(y0, y1)) * -scl;
    pw[h] = pack_bf16(ex2(fmaf(y0, scl, mx)), ex2(fmaf(y1, scl, mx)));
    inv[h] = bf_lo(pw[h]) + bf_hi(pw[h]);
  }
  const uint32_t ml = (lo0 ? 0xFFFFu : 0u) | (lo1 ? 0xFFFF0000u : 0u);
  float o[3][4];
#pragma unroll
  for (int j = 0; j < 3; j++) { o[j][0] = o[j][1] = o[j][2] = o[j][3] = 0.f; mma16816(o[j], pw[0] & ml, 0u, pw[0] & ~ml, pw[1] & ml, v[0][j], v[1][j]); }
#pragma unroll
  for (int j = 0; j < 3; j++) mma1688(o[j], 0u, pw[1] & ~ml, v[2][j]);
  inv[0] = rcp(quad_sum(inv[0])); inv[1] = rcp(quad_sum(inv[1]));
  const uint32_t ca = (bc * 3 + hh) * 20 + 4 * t, cb = ca + 16 - 2 * t, row = 2 * g + p;
  uint8_t* img = g_ob[l] + (size_t)s * 40960 + row * 128;
  const uint32_t oa = (ca >> 6) * 4096 + (((ca >> 3) ^ row) & 7) * 16 + (ca & 4) * 2, ob = (cb >> 6) * 4096 + (((cb >> 3) ^ row) & 7) * 16 + (cb & 6) * 2;
#pragma unroll
  for (int h = 0; h < 2; h++) {
    *reinterpret_cast<uint2*>(img + oa + h * 2048) = make_uint2(pack_bf16(o[0][2 * h] * inv[h], o[0][2 * h + 1] * inv[h]), pack_bf16(o[1][2 * h] * inv[h], o[1][2 * h + 1] * inv[h]));
    if (t < 2) *reinterpret_cast<uint32_t*>(img + ob + h * 2048) = pack_bf16(o[2][2 * h] * inv[h], o[2][2 * h + 1] * inv[h]);
  }
}
template <int WG>
__device__ __forceinline__ void work_b(const bf16* wqkv, uint32_t sb, int bc, int tid0) {
  using namespace W;
  if (WG == 0) asm volatile("setmaxnreg.inc.sync.aligned.u32 232;");
  else asm volatile("setmaxnreg.inc.sync.aligned.u32 208;");
  constexpr int NR = WG ? KRS : QRS, OFF_Y = WG ? OFF_YK : OFF_YQ;
  int spin = 0;
  const uint32_t wb = sb + (WG ? OFF_WO : OFF_WV);
  uint32_t wf[NR][4];
  stage_qkv(wqkv, wb, WG, bc, tid0 & 127);
  WBAR_SYNC(NB_G0 + WG, 128);
  load_frags<NR>(wf, wb, tid0);
#pragma unroll
  for (int k = NR; k < 40; k++) sts128(sb + OFF_Y + (k - NR) * 2048 + (tid0 & 127) * 16, lds128(wb + k * 2048 + (tid0 & 127) * 16));
  fence_async();
  if (WG == 1) WBAR_ARRIVE(NB_PK, 256);
  WBAR_SYNC(NB_G0 + WG, 128);
  if (WG == 0) {
    stage_qkv(wqkv, wb, 2, bc, tid0);
    fence_async();
    WBAR_SYNC(NB_G0, 128);
  }
#pragma unroll 1
  for (int k = 0; k < NSTEP; k++) {
    uint32_t hist[8];
    {
      float d[32], e[32];
#pragma unroll
      for (int c = 0; c < 10; c++) {
        mwait(sb + BAR_F + 8 * (c % 4), ((c % 4 < 2 ? k : 0) + c / 4) & 1, spin);
        if (c == 0 && bc == 0) WTS(k, WG ? 15 : 6);
        wg_fence();
#pragma unroll
        for (int kk = 0; kk < 4; kk++) {
          const int q = 4 * c + kk;
          const uint64_t db = rdesc(OFF_X + (c % 4) * 8192, kk);
          if (q < NR) wgmma_rs64(d, wf[q < NR ? q : 0], db, q);
          else wgmma_ts64(d, mkdesc(SB0 + OFF_Y + (q - NR) * 2048, 8192, 1024), db, 1);
          if (WG == 0) wgmma_ts64(e, mkdesc(SB0 + OFF_WV + q * 2048, 8192, 1024), db, q);
          if (kk == 0 && c > 0 && (c <= 6 || c == 9)) {
            wg_commit();
            wg_wait<1>();
            if ((tid0 & 31) == 0) mbar_arrive(sb + BAR_E + 8 * ((c - 1) % 4));
          }
        }
        wg_commit();
      }
      wg_wait<0>();
      if (bc == 0) WTS(k, 16 + WG);
      WBAR_SYNC(NB_B, 256);
      const int tid = fresh(tid0), m = (tid >> 3) & 3;
      const uint32_t a = sb + OFF_T + min(((tid >> 5) & 3) * 16 + (m & 1) * 8 + (tid & 7), 60) * 16 + (m >> 1) * COL;
      const float (&x)[32] = WG ? d : e;
#pragma unroll
      for (int p = 0; p < 4; p++) {
        hist[2 * p] = pack_bf16(x[8 * p + 4], x[8 * p + 5]); hist[2 * p + 1] = pack_bf16(x[8 * p + 6], x[8 * p + 7]);
        stsm4(a + (16 - 8 * WG + 2 * p) * COL, pack_bf16(x[8 * p], x[8 * p + 1]), pack_bf16(x[8 * p + 2], x[8 * p + 3]), hist[2 * p], hist[2 * p + 1]);
        if (WG == 0)
          stsm4(a + 2 * p * COL, pack_bf16(d[8 * p], d[8 * p + 1]), pack_bf16(d[8 * p + 2], d[8 * p + 3]), pack_bf16(d[8 * p + 4], d[8 * p + 5]), pack_bf16(d[8 * p + 6], d[8 * p + 7]));
      }
    }
    WBAR_SYNC(NB_TD, 288);
    if (bc == 0 && WG == 0) WTS(k, 7);
#pragma unroll 1
    for (int l = 0; l < 2; l++) {
      const int tid = fresh(tid0), hh = uni((tid >> 5) & 3), s = k - l * LAG;
      if (hh < 3 && bc * 3 + hh < NH && s >= 0 && s < NSEG) attend(sb, bc, l, s, WG, tid);
      if (bc == 0 && WG == 0) WTS(k, l == 0 || k >= NSEG ? 8 : 25);
      if (l == 0) WBAR_ARRIVE(NB_AS, 288); else WBAR_ARRIVE(NB_AS + 1, 288);
    }
    WBAR_SYNC(NB_B, 256);
    {
      const int tid = fresh(tid0), m = (tid >> 3) & 3;
      const uint32_t a = sb + OFF_H + min(((tid >> 5) & 3) * 16 + (m & 1) * 8 + (tid & 7), 60) * 16 + (4 - 4 * WG + (m >> 1)) * COL;
      stsm4(a, hist[0], hist[1], hist[2], hist[3]);
      if (k >= LAG) stsm4(a + 2 * COL, hist[4], hist[5], hist[6], hist[7]);
      fence_async();
      if ((tid & 31) < 3) mbar_arrive(sb + BAR_E + 8 + 8 * (tid & 3));
    }
  }
  if (spin >= SPIN_TOT) g_err = 14;
}
__device__ __forceinline__ void work_wo(const CUtensorMap& tmBo, uint32_t sb, int bc, int tid0) {
  using namespace W;
  int spin = 0;
  WBAR_SYNC(NB_PK, 256);
  if (bc == 10) return;
  if ((tid0 & 127) == 0) {
    mbar_expect_tx(sb + BAR_W, 81920);
    for (int i = 0; i < 10; i++) tma2d(sb + OFF_WO + i * 8192, &tmBo, bc * 64, i * 64, sb + BAR_W);
  }
  __syncwarp();
  mwait(sb + BAR_W, 0, spin);
  permute_cols(sb + OFF_WO, tid0 & 127, 2560);
  WBAR_SYNC(NB_G0 + 2, 128);
  uint32_t wl[4];
  ldsm4t(wl, frag_addr(sb + OFF_WO + 39 * 2048, tid0));
  fence_async();
  WBAR_SYNC(NB_PV, 160);
  uint32_t n = 0;
  FOR_SEGS(l, s)
    float d[16];
#pragma unroll
    for (int c = 0; c < 10; c++) {
      mwait(sb + BAR_G + 8 * (c % 3), ((c % 3 ? n : 0) + c / 3) & 1, spin);
      if (c == 0 && bc == 0) WTS(s + l * LAG, l == 0 || s + LAG >= NSEG ? 20 : 23);
      wg_fence();
#pragma unroll
      for (int kk = 0; kk < 4; kk++) {
        if (c == 9 && kk == 3) wgmma_rs32(d, wl, rdesc(OFF_G + (c % 3) * 4096, kk), 1);
        else wgmma_ts32(d, mkdesc(SB0 + OFF_WO + (4 * c + kk) * 2048, 8192, 1024), rdesc(OFF_G + (c % 3) * 4096, kk), c | kk);
      }
      wg_commit();
      if (c == 9 || !WOP) wg_wait<0>();
      else if (c > 0) wg_wait<1>();
      if ((tid0 & 31) == 0) {
        if (WOP && c > 0) mbar_arrive(sb + BAR_H + 8 * ((c - 1) % 3));
        if (c == 9 || !WOP) mbar_arrive(sb + BAR_H + 8 * (c % 3));
      }
    }
    if (bc == 0) WTS(s + l * LAG, l == 0 || s + LAG >= NSEG ? 10 : 24);
    red_tile(d, s, bc * 64, tid0);
    WBAR_SYNC(NB_SG, 160);
    n++;
  }
  if (spin >= SPIN_TOT) g_err = 17;
}
__device__ __forceinline__ void work_x_producer(uint32_t sb, int bc) {
  using namespace W;
  int spin = 0;
#pragma unroll 1
  for (int k = 0; k < NSTEP; k++) {
    const uint32_t lo = k < NSEG ? 0 : 4096, len = k < LAG || k >= NSEG ? 4096 : 8192;
    const uint8_t* src = g_xnb[k] + lo;
    cwait(CN_L + k, len >> 7, spin);
    fence_async_all();
    if (bc == 0) WTS1(k, 5);
#pragma unroll
    for (int c = 0; c < 10; c++) {
      mwait(sb + BAR_E + 8 * (c % 4), (((c % 4 < 2 ? k : 0) + c / 4) & 1) ^ 1, spin);
      mbar_expect_tx(sb + BAR_F + 8 * (c % 4), len);
      bulk_g2s(sb + OFF_X + (c % 4) * 8192 + lo, src + c * 8192, len, sb + BAR_F + 8 * (c % 4));
    }
  }
  if (spin >= SPIN_TOT) g_err = 15;
}
__device__ __forceinline__ void work_g_producer(uint32_t sb, int bc) {
  using namespace W;
  int spin = 0;
  uint32_t n = 0;
  FOR_SEGS(l, s)
    const uint8_t* src = g_ob[l] + (size_t)s * 40960;
    cwait(CN_A + l * 64 + s, NBC, spin);
    fence_async_all();
    if (bc == 0) WTS1(s + l * LAG, l == 0 || s + LAG >= NSEG ? 9 : 22);
#pragma unroll
    for (int c = 0; c < 10; c++) {
      mwait(sb + BAR_H + 8 * (c % 3), (((c % 3 ? n : 0) + c / 3) & 1) ^ 1, spin);
      mbar_expect_tx(sb + BAR_G + 8 * (c % 3), 4096);
      bulk_g2s(sb + OFF_G + (c % 3) * 4096, src + c * 4096, 4096, sb + BAR_G + 8 * (c % 3));
    }
    n++;
  }
  if (spin >= SPIN_TOT) g_err = 16;
}

__global__ void __launch_bounds__(512, 1)
k_work(const __grid_constant__ CUtensorMap tmWo, const __grid_constant__ CUtensorMap tmBo, const bf16* __restrict__ wqkv, bf16* __restrict__ out) {
  using namespace W;
  extern __shared__ __align__(1024) uint8_t smem[];
  const uint32_t sb = smem_u32(smem);
  const int tid = threadIdx.x, w = blockIdx.x;
  const int wg = __shfl_sync(0xffffffffu, tid >> 7, 0);
  if (tid == 0) {
    if (sb != SB0) g_err = 101;
    for (int i = 0; i < 5; i++) { mbar_init(sb + BAR_F + 8 * i, 1); mbar_init(sb + BAR_E + 8 * i, 8); mbar_init(sb + BAR_G + 8 * i, 1); mbar_init(sb + BAR_H + 8 * i, 4); }
    mbar_init(sb + BAR_W, 1); mbar_init(sb + BAR_W + 8, 1);
    for (int p = 0; p < 16; p++) sts32(sb + OFF_SAFE + 4 * p, 0);
    asm volatile("fence.mbarrier_init.release.cluster;" ::: "memory");
  }
  if (tid < 8 * COL / 16) sts128(sb + OFF_H + tid * 16, make_uint4(0, 0, 0, 0));
  fence_async();
  __syncthreads();

  if (w < NP) {
    if (wg == 0) work_p<0>(tmWo, sb, w, keep(tid));
    else if (wg == 1) work_p<1>(tmWo, sb, w, keep(tid));
    else {
      asm volatile("setmaxnreg.dec.sync.aligned.u32 48;");
      const int aw = (tid >> 5) - 8;
      if (aw < 2) {
        if ((tid & 31) == 0) work_p_producer(sb, w, aw);
      } else {
        const int id = (aw - 2) * NP + w;
        if (id < 128) work_ln(id & 3, id >> 2, tid & 31, out);
      }
    }
  } else {
    const int bc = w - NP;
    if (wg == 0) work_b<0>(wqkv, sb, bc, keep(tid));
    else if (wg == 1) work_b<1>(wqkv, sb, bc, keep(tid));
    else if (wg == 2) {
      asm volatile("setmaxnreg.dec.sync.aligned.u32 48;");
      work_wo(tmBo, sb, bc, keep(tid));
    } else {
      asm volatile("setmaxnreg.dec.sync.aligned.u32 24;");
      if (tid < 416) {
        if (tid == 384) work_x_producer(sb, bc);
      } else if (tid < 448) {
        if (bc < 10) {
          WBAR_SYNC(NB_PV, 160);
          if (tid == 416) work_g_producer(sb, bc);
        }
      } else if (tid < 480) {
        for (int k = 0; k < NSTEP; k++) {
          WBAR_SYNC(NB_TD, 288);
          WBAR_SYNC(NB_AS, 288);
          if (tid == 448 && k < NSEG) csignal_t(CN_A + k, 5);
          __syncwarp();
          WBAR_SYNC(NB_AS + 1, 288);
          if (tid == 448 && k >= LAG) csignal_t(CN_A + 64 + k - LAG, 4);
          __syncwarp();
        }
      } else if (bc < 10) {
        FOR_SEGS(l, s)
          WBAR_SYNC(NB_SG, 160);
          if (tid == 480) csignal_t(CN_W + l * 64 + s, 6);
          __syncwarp();
        }
      }
    }
  }
  __syncthreads();
  asm volatile("griddepcontrol.wait;" ::: "memory");
}

typedef CUresult (*EncodeFn)(CUtensorMap*, CUtensorMapDataType, cuuint32_t, void*, const cuuint64_t*, const cuuint64_t*,
                             const cuuint32_t*, const cuuint32_t*, CUtensorMapInterleave, CUtensorMapSwizzle,
                             CUtensorMapL2promotion, CUtensorMapFloatOOBfill);

static void make_map(EncodeFn enc, CUtensorMap* tm, const void* ptr, uint64_t cols, uint64_t rows, uint32_t boxc, uint32_t boxr) {
  cuuint64_t dims[2] = {cols, rows};
  cuuint64_t strides[1] = {cols * 2};
  cuuint32_t box[2] = {boxc, boxr};
  cuuint32_t es[2] = {1, 1};
  enc(tm, CU_TENSOR_MAP_DATA_TYPE_BFLOAT16, 2, const_cast<void*>(ptr), dims, strides, box, es, CU_TENSOR_MAP_INTERLEAVE_NONE,
      CU_TENSOR_MAP_SWIZZLE_128B, CU_TENSOR_MAP_L2_PROMOTION_L2_256B, CU_TENSOR_MAP_FLOAT_OOB_FILL_NONE);
}

extern "C" void kernel_launch(void* const* d_in, const int* in_sizes, int n_in, void* d_out, int out_size) {
  const bf16* x0 = (const bf16*)d_in[0];
  const bf16* mem0 = (const bf16*)d_in[1];
  const bf16* Wq = (const bf16*)d_in[2];
  const bf16* Wk = (const bf16*)d_in[3];
  const bf16* Wv = (const bf16*)d_in[4];
  const bf16* Wo = (const bf16*)d_in[5];
  const bf16* Bqkv = (const bf16*)d_in[8];
  const bf16* Bwo = (const bf16*)d_in[9];
  bf16* out = (bf16*)d_out;

  static EncodeFn enc = nullptr;
  if (!enc) {
    void* fn = nullptr;
    cudaDriverEntryPointQueryResult qr;
    cudaGetDriverEntryPoint("cuTensorMapEncodeTiled", &fn, cudaEnableDefault, &qr);
    enc = (EncodeFn)fn;
    cudaFuncSetAttribute(k_chain, cudaFuncAttributeMaxDynamicSharedMemorySize, C::SMEM);
    cudaFuncSetAttribute(k_work, cudaFuncAttributeMaxDynamicSharedMemorySize, W::SMEM);
  }
  CUtensorMap tmWq, tmWk, tmWv, tmWo, tmWp, tmBo;
  make_map(enc, &tmWq, Wq, NH * DH, DM, 64, 128);
  make_map(enc, &tmWk, Wk, NH * DH, DM, 64, 128);
  make_map(enc, &tmWv, Wv, NH * DH, DM, 64, 128);
  make_map(enc, &tmWo, Wo, DM, NH * DH, 64, 64);
  make_map(enc, &tmWp, Wo, DM, NH * DH, 64, 16);
  make_map(enc, &tmBo, Bwo, DM, DM, 64, 64);

  cudaStream_t st = cudaStreamPerThread;
  k_pre<<<256, 256, 0, st>>>(x0, mem0);
  cudaLaunchAttribute at[1];
  at[0].id = cudaLaunchAttributeProgrammaticStreamSerialization; at[0].val.programmaticStreamSerializationAllowed = 1;
  {
    cudaLaunchConfig_t cfg = {};
    cfg.gridDim = dim3(96); cfg.blockDim = dim3(384); cfg.dynamicSmemBytes = C::SMEM; cfg.stream = st;
    cfg.attrs = at; cfg.numAttrs = 0;
    cudaLaunchKernelEx(&cfg, k_chain, tmWq, tmWk, tmWv, tmWo);
  }
  cudaLaunchConfig_t cfg = {};
  cfg.gridDim = dim3(W::NW); cfg.blockDim = dim3(512); cfg.dynamicSmemBytes = W::SMEM; cfg.stream = st;
  cfg.attrs = at; cfg.numAttrs = NOWORK == 2 ? 0 : 1;
  cudaLaunchKernelEx(&cfg, k_work, tmWp, tmBo, Bqkv, out);
}
```

```cpp
#include <cuda_runtime.h>
#include <cuda_bf16.h>
#include <cuda.h>
#include <stdint.h>

typedef __nv_bfloat16 bf16;

constexpr int SEQ = 2048, DM = 640, NH = 32, DH = 192, NSEG = 64;
#define LAG 7
constexpr int NSTEP = NSEG + LAG;
constexpr uint32_t SENT = 0xFFFFFFFFu;

constexpr int MAIL9 = 288 * 2048, MAIL_BYTES = MAIL9 + 64 * 3072;
__device__ __align__(1024) uint8_t g_xn[NSTEP][81920];
__device__ __align__(1024) uint8_t g_xnb[NSTEP][81920];
__device__ __align__(1024) uint8_t g_ob[2][NSEG * 40960];
#define ORING 8
static_assert(ORING > LAG, "a slot is free again LAG + 1 steps later");
__device__ __align__(1024) uint8_t g_o[ORING][96][8192];
__device__ __align__(1024) float g_x[SEQ * DM];
constexpr int EX_MAIL = 0;
constexpr int EX_M = 2 << 20;
constexpr int EX_FLAG = EX_M + NSTEP * 20480;
static_assert(EX_FLAG + NSTEP * 3072 <= (4 << 20), "");
__device__ __align__(1024) uint8_t g_ex[8 << 20];
__host__ __device__ __forceinline__ uint8_t* ex_window(uint8_t* p) { return reinterpret_cast<uint8_t*>((reinterpret_cast<uint64_t>(p) + (4 << 20) - 1) & ~(uint64_t)((4 << 20) - 1)); }
enum { CN_P = 0, CN_L = 128, CN_A = 256, CN_W = 384, CN_X = 512, CN_O = 576, CN_NUM = CN_O + 5 * NSTEP };
__device__ __align__(128) uint32_t g_cnt[CN_NUM][32];
__device__ int g_err;
#define TS(jj, i)
#define TS1(jj, i)
#define PTS(i)
#define TSB(jj, i)
#define TSV(jj, i, v)
#define TS_FLUSH(jj)
#define WTS(b, k)
#define WTS1(b, k)
#define WW -1

__device__ __forceinline__ uint32_t smem_u32(const void* p) { return (uint32_t)__cvta_generic_to_shared(p); }
__device__ __forceinline__ uint32_t clk32() { uint32_t t; asm volatile("mov.u32 %0, %%clock;" : "=r"(t)::"memory"); return t; }
__device__ __forceinline__ uint32_t mapa(uint32_t a, uint32_t r) { uint32_t o; asm("mapa.shared::cluster.u32 %0,%1,%2;" : "=r"(o) : "r"(a), "r"(r)); return o; }
__device__ __forceinline__ void mbar_init(uint32_t bar, uint32_t cnt) { asm volatile("mbarrier.init.shared::cta.b64 [%0],%1;" ::"r"(bar), "r"(cnt) : "memory"); }
__device__ __forceinline__ void mbar_expect_tx(uint32_t bar, uint32_t bytes) { asm volatile("mbarrier.arrive.expect_tx.shared::cta.b64 _,[%0],%1;" ::"r"(bar), "r"(bytes) : "memory"); }
__device__ __forceinline__ void mbar_arrive(uint32_t bar) { asm volatile("mbarrier.arrive.shared::cta.b64 _,[%0];" ::"r"(bar) : "memory"); }
__device__ __forceinline__ void mbar_arrive_cluster(uint32_t bar) { asm volatile("mbarrier.arrive.shared::cluster.b64 _,[%0];" ::"r"(bar) : "memory"); }
__device__ __forceinline__ bool mbar_try(uint32_t bar, uint32_t ph) {
  uint32_t ok;
  asm volatile("{.reg .pred p; mbarrier.try_wait.parity.shared::cta.b64 p,[%1],%2; selp.u32 %0,1,0,p;}" : "=r"(ok) : "r"(bar), "r"(ph) : "memory");
  return ok;
}
__device__ __forceinline__ bool mbar_test(uint32_t bar, uint32_t ph) {
  uint32_t ok;
  asm volatile("{.reg .pred p; mbarrier.test_wait.parity.shared::cta.b64 p,[%1],%2; selp.u32 %0,1,0,p;}" : "=r"(ok) : "r"(bar), "r"(ph) : "memory");
  return ok;
}
__device__ __forceinline__ int fresh(int x) { asm volatile("" : "+r"(x)); return x; }
#define PHASE_IDS const int tid = fresh(tid0), lane = tid & 31, w = tid >> 5, g = lane >> 2, t = lane & 3; (void)w; (void)g; (void)t
__device__ __forceinline__ void bar_sync(int id, int n) { asm volatile("bar.sync %0,%1;" ::"r"(id), "r"(n) : "memory"); }
__device__ __forceinline__ void bar_arrive(int id, int n) { asm volatile("bar.arrive %0,%1;" ::"r"(id), "r"(n) : "memory"); }
__device__ __forceinline__ bool bar_red_or(int id, int n, bool v) {
  uint32_t r;
  asm volatile("{\n .reg .pred p, q;\n setp.ne.u32 q, %3, 0;\n barrier.cta.red.or.pred p, %1, %2, q;\n selp.u32 %0, 1, 0, p;\n}" : "=r"(r) : "r"(id), "r"(n), "r"((uint32_t)v) : "memory");
  return r != 0;
}
__device__ __forceinline__ void fence_async() { asm volatile("fence.proxy.async.shared::cta;" ::: "memory"); }
__device__ __forceinline__ void bulk_g2s(uint32_t dst, const void* src, uint32_t bytes, uint32_t bar) {
  asm volatile("cp.async.bulk.shared::cluster.global.mbarrier::complete_tx::bytes [%0],[%1],%2,[%3];" ::"r"(dst), "l"(src), "r"(bytes), "r"(bar) : "memory");
}
__device__ __forceinline__ void bulk_g2s_mc(uint32_t dst, const void* src, uint32_t bytes, uint32_t bar) {
  asm volatile("cp.async.bulk.shared::cluster.global.mbarrier::complete_tx::bytes.multicast::cluster [%0],[%1],%2,[%3],%4;"
               ::"r"(dst), "l"(src), "r"(bytes), "r"(bar), "h"((uint16_t)7) : "memory");
}
__device__ __forceinline__ void bulk_s2g(void* dst, uint32_t src, uint32_t bytes) {
  asm volatile("cp.async.bulk.global.shared::cta.bulk_group [%0],[%1],%2;" ::"l"(dst), "r"(src), "r"(bytes) : "memory");
}
__device__ __forceinline__ void bulk_s2c(uint32_t dst, uint32_t src, uint32_t bytes, uint32_t bar) {
  asm volatile("cp.async.bulk.shared::cluster.shared::cta.mbarrier::complete_tx::bytes [%0],[%1],%2,[%3];" ::"r"(dst), "r"(src), "r"(bytes), "r"(bar) : "memory");
}
__device__ __forceinline__ void tma2d(uint32_t dst, const CUtensorMap* tm, int c0, int c1, uint32_t bar) {
  asm volatile("cp.async.bulk.tensor.2d.shared::cluster.global.mbarrier::complete_tx::bytes [%0],[%1,{%3,%4}],[%2];"
               ::"r"(dst), "l"(tm), "r"(bar), "r"(c0), "r"(c1) : "memory");
}
__device__ __forceinline__ void tma2d_prefetch(const CUtensorMap* tm, int c0, int c1) {
  asm volatile("cp.async.bulk.prefetch.tensor.2d.L2.global.tile [%0,{%1,%2}];" ::"l"(tm), "r"(c0), "r"(c1) : "memory");
}
__device__ __forceinline__ uint32_t pack_bf16(float lo, float hi) {
  uint32_t r; asm("cvt.rn.bf16x2.f32 %0,%1,%2;" : "=r"(r) : "f"(hi), "f"(lo)); return r;
}
__device__ __forceinline__ float bf_lo(uint32_t x) { return __uint_as_float(x << 16); }
__device__ __forceinline__ float bf_hi(uint32_t x) { return __uint_as_float(x & 0xFFFF0000u); }
__device__ __forceinline__ float ex2(float x) { float y; asm("ex2.approx.ftz.f32 %0,%1;" : "=f"(y) : "f"(x)); return y; }
__device__ __forceinline__ void ldsm4(uint32_t (&r)[4], uint32_t a) {
  asm volatile("ldmatrix.sync.aligned.m8n8.x4.shared.b16 {%0,%1,%2,%3},[%4];" : "=r"(r[0]), "=r"(r[1]), "=r"(r[2]), "=r"(r[3]) : "r"(a) : "memory");
}
__device__ __forceinline__ void ldsm4t(uint32_t (&r)[4], uint32_t a) {
  asm volatile("ldmatrix.sync.aligned.m8n8.x4.trans.shared.b16 {%0,%1,%2,%3},[%4];" : "=r"(r[0]), "=r"(r[1]), "=r"(r[2]), "=r"(r[3]) : "r"(a) : "memory");
}
__device__ __forceinline__ void ldsm2(uint32_t& r0, uint32_t& r1, uint32_t a) {
  asm volatile("ldmatrix.sync.aligned.m8n8.x2.shared.b16 {%0,%1},[%2];" : "=r"(r0), "=r"(r1) : "r"(a) : "memory");
}
__device__ __forceinline__ void ldsm2t(uint32_t& r0, uint32_t& r1, uint32_t a) {
  asm volatile("ldmatrix.sync.aligned.m8n8.x2.trans.shared.b16 {%0,%1},[%2];" : "=r"(r0), "=r"(r1) : "r"(a) : "memory");
}
__device__ __forceinline__ void ldsm1(uint32_t& r0, uint32_t a) {
  asm volatile("ldmatrix.sync.aligned.m8n8.x1.shared.b16 {%0},[%1];" : "=r"(r0) : "r"(a) : "memory");
}
__device__ __forceinline__ void mma16816(float (&d)[4], uint32_t a0, uint32_t a1, uint32_t a2, uint32_t a3, uint32_t b0, uint32_t b1) {
  asm volatile("mma.sync.aligned.m16n8k16.row.col.f32.bf16.bf16.f32 {%0,%1,%2,%3},{%4,%5,%6,%7},{%8,%9},{%0,%1,%2,%3};"
               : "+f"(d[0]), "+f"(d[1]), "+f"(d[2]), "+f"(d[3]) : "r"(a0), "r"(a1), "r"(a2), "r"(a3), "r"(b0), "r"(b1));
}
__device__ __forceinline__ void mma1688(float (&d)[4], uint32_t a0, uint32_t a1, uint32_t b0) {
  asm volatile("mma.sync.aligned.m16n8k8.row.col.f32.bf16.bf16.f32 {%0,%1,%2,%3},{%4,%5},{%6},{%0,%1,%2,%3};"
               : "+f"(d[0]), "+f"(d[1]), "+f"(d[2]), "+f"(d[3]) : "r"(a0), "r"(a1), "r"(b0));
}
__device__ __forceinline__ void sts32(uint32_t a, uint32_t v) { asm volatile("st.shared.b32 [%0],%1;" ::"r"(a), "r"(v) : "memory"); }
__device__ __forceinline__ void sts64f(uint32_t a, float x, float y) { asm volatile("st.shared.v2.f32 [%0],{%1,%2};" ::"r"(a), "f"(x), "f"(y) : "memory"); }
__device__ __forceinline__ void sts128(uint32_t a, uint4 v) { asm volatile("st.shared.v4.b32 [%0],{%1,%2,%3,%4};" ::"r"(a), "r"(v.x), "r"(v.y), "r"(v.z), "r"(v.w) : "memory"); }
__device__ __forceinline__ float lds32f(uint32_t a) { float v; asm volatile("ld.shared.f32 %0,[%1];" : "=f"(v) : "r"(a) : "memory"); return v; }
__device__ __forceinline__ float2 lds64f(uint32_t a) { float2 v; asm volatile("ld.shared.v2.f32 {%0,%1},[%2];" : "=f"(v.x), "=f"(v.y) : "r"(a) : "memory"); return v; }
__device__ __forceinline__ uint4 lds128(uint32_t a) { uint4 v; asm volatile("ld.shared.v4.b32 {%0,%1,%2,%3},[%4];" : "=r"(v.x), "=r"(v.y), "=r"(v.z), "=r"(v.w) : "r"(a) : "memory"); return v; }
__device__ __forceinline__ float4 lds128f(uint32_t a) { float4 v; asm volatile("ld.shared.v4.f32 {%0,%1,%2,%3},[%4];" : "=f"(v.x), "=f"(v.y), "=f"(v.z), "=f"(v.w) : "r"(a) : "memory"); return v; }
__device__ __forceinline__ void st_async2(uint32_t a, float x, float y, uint32_t bar) {
  asm volatile("st.async.weak.shared::cluster.mbarrier::complete_tx::bytes.v2.f32 [%0],{%1,%2},[%3];" ::"r"(a), "f"(x), "f"(y), "r"(bar) : "memory");
}
__device__ __forceinline__ void st_async4(uint32_t a, const float (&v)[4], uint32_t bar) {
  asm volatile("st.async.weak.shared::cluster.mbarrier::complete_tx::bytes.v4.f32 [%0],{%1,%2,%3,%4},[%5];" ::"r"(a), "f"(v[0]), "f"(v[1]), "f"(v[2]), "f"(v[3]), "r"(bar) : "memory");
}
__device__ __forceinline__ void st_async4v(uint32_t a, float x, float y, float z, float w, uint32_t bar) {
  asm volatile("st.async.weak.shared::cluster.mbarrier::complete_tx::bytes.v4.f32 [%0],{%1,%2,%3,%4},[%5];" ::"r"(a), "f"(x), "f"(y), "f"(z), "f"(w), "r"(bar) : "memory");
}
__device__ __forceinline__ void st_async4u(uint32_t a, const uint4& v, uint32_t bar) {
  asm volatile("st.async.weak.shared::cluster.mbarrier::complete_tx::bytes.v4.b32 [%0],{%1,%2,%3,%4},[%5];" ::"r"(a), "r"(v.x), "r"(v.y), "r"(v.z), "r"(v.w), "r"(bar) : "memory");
}
__device__ __forceinline__ uint4 ld_relaxed4(const void* p) {
  uint4 v; asm volatile("ld.relaxed.gpu.global.v4.u32 {%0,%1,%2,%3},[%4];" : "=r"(v.x), "=r"(v.y), "=r"(v.z), "=r"(v.w) : "l"(p) : "memory"); return v;
}
__device__ __forceinline__ uint32_t ld_relaxed(const void* p) {
  uint32_t v; asm volatile("ld.relaxed.gpu.global.u32 %0,[%1];" : "=r"(v) : "l"(p) : "memory"); return v;
}
__device__ __forceinline__ void st_relaxed(void* p, uint32_t v) { asm volatile("st.relaxed.gpu.global.b32 [%0],%1;" ::"l"(p), "r"(v) : "memory"); }
__device__ __forceinline__ void st_relaxed4(void* p, uint32_t v) { asm volatile("st.relaxed.gpu.global.v4.b32 [%0],{%1,%1,%1,%1};" ::"l"(p), "r"(v) : "memory"); }

__device__ __forceinline__ uint32_t ld_acquire(const void* p) {
  uint32_t v; asm volatile("ld.acquire.gpu.global.u32 %0,[%1];" : "=r"(v) : "l"(p) : "memory"); return v;
}
__device__ __forceinline__ float4 ld_relaxed4f(const void* p) {
  float4 v; asm volatile("ld.relaxed.gpu.global.v4.f32 {%0,%1,%2,%3},[%4];" : "=f"(v.x), "=f"(v.y), "=f"(v.z), "=f"(v.w) : "l"(p) : "memory"); return v;
}
__device__ __forceinline__ float2 ld_relaxed2f(const void* p) {
  float2 v; asm volatile("ld.relaxed.gpu.global.v2.f32 {%0,%1},[%2];" : "=f"(v.x), "=f"(v.y) : "l"(p) : "memory"); return v;
}
__device__ __forceinline__ void prefetch_l2(const void* p) { asm volatile("prefetch.global.L2 [%0];" ::"l"(p)); }
__device__ __forceinline__ void fence_gpu() { asm volatile("fence.acq_rel.gpu;" ::: "memory"); }
__device__ __forceinline__ void fence_async_all() { asm volatile("fence.proxy.async.global;" ::: "memory"); }
constexpr int SPIN_TOT = 1 << 22;
__device__ __forceinline__ void csignal(int idx) { asm volatile("red.release.gpu.global.add.u32 [%0],1;" ::"l"(&g_cnt[idx][0]) : "memory"); }
#define csignal_t(idx, role) csignal(idx)
__device__ __forceinline__ void cwait(int idx, uint32_t target, int& spin) {
  while (ld_acquire(&g_cnt[idx][0]) < target && spin < SPIN_TOT) spin += 16;
}

__device__ __forceinline__ uint64_t mkdesc(uint32_t addr, uint32_t lbo, uint32_t sbo) {
  return (uint64_t)((addr & 0x3FFFF) >> 4) | ((uint64_t)(lbo >> 4) << 16) | ((uint64_t)(sbo >> 4) << 32) | ((uint64_t)1 << 62);
}
__device__ __forceinline__ uint64_t mkdesc_ns(uint32_t addr, uint32_t lbo, uint32_t sbo) {
  return (uint64_t)((addr & 0x3FFFF) >> 4) | ((uint64_t)(lbo >> 4) << 16) | ((uint64_t)(sbo >> 4) << 32);
}
__device__ __forceinline__ void wg_fence() { asm volatile("wgmma.fence.sync.aligned;" ::: "memory"); }
__device__ __forceinline__ void wg_commit() { asm volatile("wgmma.commit_group.sync.aligned;" ::: "memory"); }
template <int N> __device__ __forceinline__ void wg_wait() { asm volatile("wgmma.wait_group.sync.aligned %0;" ::"n"(N) : "memory"); }

__device__ __forceinline__ void wgmma_rs16(float (&d)[8], const uint32_t (&a)[4], uint64_t db, int sc) {
  asm volatile("{.reg .pred p; setp.ne.b32 p,%13,0; wgmma.mma_async.sync.aligned.m64n16k16.f32.bf16.bf16 "
               "{%0,%1,%2,%3,%4,%5,%6,%7},{%8,%9,%10,%11},%12,p,1,1,0;}"
               : "+f"(d[0]), "+f"(d[1]), "+f"(d[2]), "+f"(d[3]), "+f"(d[4]), "+f"(d[5]), "+f"(d[6]), "+f"(d[7])
               : "r"(a[0]), "r"(a[1]), "r"(a[2]), "r"(a[3]), "l"(db), "r"(sc));
}
__device__ __forceinline__ void wgmma_rs64(float (&d)[32], const uint32_t (&a)[4], uint64_t db, int sc) {
  asm volatile("{.reg .pred p; setp.ne.b32 p,%37,0; wgmma.mma_async.sync.aligned.m64n64k16.f32.bf16.bf16 "
               "{%0,%1,%2,%3,%4,%5,%6,%7,%8,%9,%10,%11,%12,%13,%14,%15,%16,%17,%18,%19,%20,%21,%22,%23,%24,%25,%26,%27,%28,%29,%30,%31},{%32,%33,%34,%35},%36,p,1,1,0;}"
               : "+f"(d[0]), "+f"(d[1]), "+f"(d[2]), "+f"(d[3]), "+f"(d[4]), "+f"(d[5]), "+f"(d[6]), "+f"(d[7]), "+f"(d[8]), "+f"(d[9]), "+f"(d[10]), "+f"(d[11]), "+f"(d[12]), "+f"(d[13]), "+f"(d[14]), "+f"(d[15]), "+f"(d[16]), "+f"(d[17]), "+f"(d[18]), "+f"(d[19]), "+f"(d[20]), "+f"(d[21]), "+f"(d[22]), "+f"(d[23]), "+f"(d[24]), "+f"(d[25]), "+f"(d[26]), "+f"(d[27]), "+f"(d[28]), "+f"(d[29]), "+f"(d[30]), "+f"(d[31])
               : "r"(a[0]), "r"(a[1]), "r"(a[2]), "r"(a[3]), "l"(db), "r"(sc));
}
__device__ __forceinline__ void wgmma_rt16(float (&d)[8], const uint32_t (&a)[4], uint64_t db, int sc) {
  asm volatile("{.reg .pred p; setp.ne.b32 p,%13,0; wgmma.mma_async.sync.aligned.m64n16k16.f32.bf16.bf16 "
               "{%0,%1,%2,%3,%4,%5,%6,%7},{%8,%9,%10,%11},%12,p,1,1,1;}"
               : "+f"(d[0]), "+f"(d[1]), "+f"(d[2]), "+f"(d[3]), "+f"(d[4]), "+f"(d[5]), "+f"(d[6]), "+f"(d[7])
               : "r"(a[0]), "r"(a[1]), "r"(a[2]), "r"(a[3]), "l"(db), "r"(sc));
}
__device__ __forceinline__ void wgmma_rt80(float (&d)[40], const uint32_t (&a)[4], uint64_t db, int sc) {
  asm volatile("{.reg .pred p; setp.ne.b32 p,%45,0; wgmma.mma_async.sync.aligned.m64n80k16.f32.bf16.bf16 "
               "{%0,%1,%2,%3,%4,%5,%6,%7,%8,%9,%10,%11,%12,%13,%14,%15,%16,%17,%18,%19,%20,%21,%22,%23,%24,%25,%26,%27,%28,%29,%30,%31,%32,%33,%34,%35,%36,%37,%38,%39},{%40,%41,%42,%43},%44,p,1,1,1;}"
               : "+f"(d[0]), "+f"(d[1]), "+f"(d[2]), "+f"(d[3]), "+f"(d[4]), "+f"(d[5]), "+f"(d[6]), "+f"(d[7]), "+f"(d[8]), "+f"(d[9]), "+f"(d[10]), "+f"(d[11]), "+f"(d[12]), "+f"(d[13]), "+f"(d[14]), "+f"(d[15]), "+f"(d[16]), "+f"(d[17]), "+f"(d[18]), "+f"(d[19]), "+f"(d[20]), "+f"(d[21]), "+f"(d[22]), "+f"(d[23]), "+f"(d[24]), "+f"(d[25]), "+f"(d[26]), "+f"(d[27]), "+f"(d[28]), "+f"(d[29]), "+f"(d[30]), "+f"(d[31]), "+f"(d[32]), "+f"(d[33]), "+f"(d[34]), "+f"(d[35]), "+f"(d[36]), "+f"(d[37]), "+f"(d[38]), "+f"(d[39])
               : "r"(a[0]), "r"(a[1]), "r"(a[2]), "r"(a[3]), "l"(db), "r"(sc));
}
__device__ __forceinline__ void wgmma_rs32(float (&d)[16], const uint32_t (&a)[4], uint64_t db, int sc) {
  asm volatile("{.reg .pred p; setp.ne.b32 p,%21,0; wgmma.mma_async.sync.aligned.m64n32k16.f32.bf16.bf16 "
               "{%0,%1,%2,%3,%4,%5,%6,%7,%8,%9,%10,%11,%12,%13,%14,%15},{%16,%17,%18,%19},%20,p,1,1,0;}"
               : "+f"(d[0]), "+f"(d[1]), "+f"(d[2]), "+f"(d[3]), "+f"(d[4]), "+f"(d[5]), "+f"(d[6]), "+f"(d[7]), "+f"(d[8]), "+f"(d[9]), "+f"(d[10]), "+f"(d[11]), "+f"(d[12]), "+f"(d[13]), "+f"(d[14]), "+f"(d[15])
               : "r"(a[0]), "r"(a[1]), "r"(a[2]), "r"(a[3]), "l"(db), "r"(sc));
}
__device__ __forceinline__ void wgmma_ts32(float (&d)[16], uint64_t da, uint64_t db, int sc) {
  asm volatile("{.reg .pred p; setp.ne.b32 p,%18,0; wgmma.mma_async.sync.aligned.m64n32k16.f32.bf16.bf16 "
               "{%0,%1,%2,%3,%4,%5,%6,%7,%8,%9,%10,%11,%12,%13,%14,%15},%16,%17,p,1,1,1,0;}"
               : "+f"(d[0]), "+f"(d[1]), "+f"(d[2]), "+f"(d[3]), "+f"(d[4]), "+f"(d[5]), "+f"(d[6]), "+f"(d[7]), "+f"(d[8]), "+f"(d[9]), "+f"(d[10]), "+f"(d[11]), "+f"(d[12]), "+f"(d[13]), "+f"(d[14]), "+f"(d[15])
               : "l"(da), "l"(db), "r"(sc));
}
__device__ __forceinline__ void wgmma_rs8(float (&d)[4], const uint32_t (&a)[4], uint64_t db, int sc) {
  asm volatile("{.reg .pred p; setp.ne.b32 p,%9,0; wgmma.mma_async.sync.aligned.m64n8k16.f32.bf16.bf16 "
               "{%0,%1,%2,%3},{%4,%5,%6,%7},%8,p,1,1,0;}"
               : "+f"(d[0]), "+f"(d[1]), "+f"(d[2]), "+f"(d[3])
               : "r"(a[0]), "r"(a[1]), "r"(a[2]), "r"(a[3]), "l"(db), "r"(sc));
}
__device__ __forceinline__ void wgmma_ts16(float (&d)[8], uint64_t da, uint64_t db, int sc) {
  asm volatile("{.reg .pred p; setp.ne.b32 p,%10,0; wgmma.mma_async.sync.aligned.m64n16k16.f32.bf16.bf16 "
               "{%0,%1,%2,%3,%4,%5,%6,%7},%8,%9,p,1,1,1,0;}"
               : "+f"(d[0]), "+f"(d[1]), "+f"(d[2]), "+f"(d[3]), "+f"(d[4]), "+f"(d[5]), "+f"(d[6]), "+f"(d[7])
               : "l"(da), "l"(db), "r"(sc));
}
__device__ __forceinline__ void wgmma_ts64(float (&d)[32], uint64_t da, uint64_t db, int sc) {
  asm volatile("{.reg .pred p; setp.ne.b32 p,%34,0; wgmma.mma_async.sync.aligned.m64n64k16.f32.bf16.bf16 "
               "{%0,%1,%2,%3,%4,%5,%6,%7,%8,%9,%10,%11,%12,%13,%14,%15,%16,%17,%18,%19,%20,%21,%22,%23,%24,%25,%26,%27,%28,%29,%30,%31},%32,%33,p,1,1,1,0;}"
               : "+f"(d[0]), "+f"(d[1]), "+f"(d[2]), "+f"(d[3]), "+f"(d[4]), "+f"(d[5]), "+f"(d[6]), "+f"(d[7]), "+f"(d[8]), "+f"(d[9]), "+f"(d[10]), "+f"(d[11]), "+f"(d[12]), "+f"(d[13]), "+f"(d[14]), "+f"(d[15]), "+f"(d[16]), "+f"(d[17]), "+f"(d[18]), "+f"(d[19]), "+f"(d[20]), "+f"(d[21]), "+f"(d[22]), "+f"(d[23]), "+f"(d[24]), "+f"(d[25]), "+f"(d[26]), "+f"(d[27]), "+f"(d[28]), "+f"(d[29]), "+f"(d[30]), "+f"(d[31])
               : "l"(da), "l"(db), "r"(sc));
}
__device__ __forceinline__ void wgmma_tt16(float (&d)[8], uint64_t da, uint64_t db, int sc) {
  asm volatile("{.reg .pred p; setp.ne.b32 p,%10,0; wgmma.mma_async.sync.aligned.m64n16k16.f32.bf16.bf16 "
               "{%0,%1,%2,%3,%4,%5,%6,%7},%8,%9,p,1,1,1,1;}"
               : "+f"(d[0]), "+f"(d[1]), "+f"(d[2]), "+f"(d[3]), "+f"(d[4]), "+f"(d[5]), "+f"(d[6]), "+f"(d[7])
               : "l"(da), "l"(db), "r"(sc));
}
__device__ __forceinline__ void wgmma_tt40(float (&d)[20], uint64_t da, uint64_t db, int sc) {
  asm volatile("{.reg .pred p; setp.ne.b32 p,%22,0; wgmma.mma_async.sync.aligned.m64n40k16.f32.bf16.bf16 "
               "{%0,%1,%2,%3,%4,%5,%6,%7,%8,%9,%10,%11,%12,%13,%14,%15,%16,%17,%18,%19},%20,%21,p,1,1,1,1;}"
               : "+f"(d[0]), "+f"(d[1]), "+f"(d[2]), "+f"(d[3]), "+f"(d[4]), "+f"(d[5]), "+f"(d[6]), "+f"(d[7]), "+f"(d[8]), "+f"(d[9]), "+f"(d[10]), "+f"(d[11]), "+f"(d[12]), "+f"(d[13]), "+f"(d[14]), "+f"(d[15]), "+f"(d[16]), "+f"(d[17]), "+f"(d[18]), "+f"(d[19])
               : "l"(da), "l"(db), "r"(sc));
}
__device__ __forceinline__ void wgmma_ss8(float (&d)[4], uint64_t da, uint64_t db, int sc) {
  asm volatile("{.reg .pred p; setp.ne.b32 p,%6,0; wgmma.mma_async.sync.aligned.m64n8k16.f32.bf16.bf16 "
               "{%0,%1,%2,%3},%4,%5,p,1,1,0,0;}"
               : "+f"(d[0]), "+f"(d[1]), "+f"(d[2]), "+f"(d[3])
               : "l"(da), "l"(db), "r"(sc));
}
__device__ __forceinline__ void wgmma_ss32(float (&d)[16], uint64_t da, uint64_t db, int sc) {
  asm volatile("{.reg .pred p; setp.ne.b32 p,%18,0; wgmma.mma_async.sync.aligned.m64n32k16.f32.bf16.bf16 "
               "{%0,%1,%2,%3,%4,%5,%6,%7,%8,%9,%10,%11,%12,%13,%14,%15},%16,%17,p,1,1,0,0;}"
               : "+f"(d[0]), "+f"(d[1]), "+f"(d[2]), "+f"(d[3]), "+f"(d[4]), "+f"(d[5]), "+f"(d[6]), "+f"(d[7]), "+f"(d[8]), "+f"(d[9]), "+f"(d[10]), "+f"(d[11]), "+f"(d[12]), "+f"(d[13]), "+f"(d[14]), "+f"(d[15])
               : "l"(da), "l"(db), "r"(sc));
}
__device__ __forceinline__ void wgmma_st64(float (&d)[32], uint64_t da, uint64_t db, int sc) {
  asm volatile("{.reg .pred p; setp.ne.b32 p,%34,0; wgmma.mma_async.sync.aligned.m64n64k16.f32.bf16.bf16 "
               "{%0,%1,%2,%3,%4,%5,%6,%7,%8,%9,%10,%11,%12,%13,%14,%15,%16,%17,%18,%19,%20,%21,%22,%23,%24,%25,%26,%27,%28,%29,%30,%31},%32,%33,p,1,1,0,1;}"
               : "+f"(d[0]), "+f"(d[1]), "+f"(d[2]), "+f"(d[3]), "+f"(d[4]), "+f"(d[5]), "+f"(d[6]), "+f"(d[7]), "+f"(d[8]), "+f"(d[9]), "+f"(d[10]), "+f"(d[11]), "+f"(d[12]), "+f"(d[13]), "+f"(d[14]), "+f"(d[15]), "+f"(d[16]), "+f"(d[17]), "+f"(d[18]), "+f"(d[19]), "+f"(d[20]), "+f"(d[21]), "+f"(d[22]), "+f"(d[23]), "+f"(d[24]), "+f"(d[25]), "+f"(d[26]), "+f"(d[27]), "+f"(d[28]), "+f"(d[29]), "+f"(d[30]), "+f"(d[31])
               : "l"(da), "l"(db), "r"(sc));
}
__device__ __forceinline__ void wgmma_st128(float (&d)[64], uint64_t da, uint64_t db, int sc) {
  asm volatile("{.reg .pred p; setp.ne.b32 p,%66,0; wgmma.mma_async.sync.aligned.m64n128k16.f32.bf16.bf16 "
               "{%0,%1,%2,%3,%4,%5,%6,%7,%8,%9,%10,%11,%12,%13,%14,%15,%16,%17,%18,%19,%20,%21,%22,%23,%24,%25,%26,%27,%28,%29,%30,%31,%32,%33,%34,%35,%36,%37,%38,%39,%40,%41,%42,%43,%44,%45,%46,%47,%48,%49,%50,%51,%52,%53,%54,%55,%56,%57,%58,%59,%60,%61,%62,%63},%64,%65,p,1,1,0,1;}"
               : "+f"(d[0]), "+f"(d[1]), "+f"(d[2]), "+f"(d[3]), "+f"(d[4]), "+f"(d[5]), "+f"(d[6]), "+f"(d[7]), "+f"(d[8]), "+f"(d[9]), "+f"(d[10]), "+f"(d[11]), "+f"(d[12]), "+f"(d[13]), "+f"(d[14]), "+f"(d[15]), "+f"(d[16]), "+f"(d[17]), "+f"(d[18]), "+f"(d[19]), "+f"(d[20]), "+f"(d[21]), "+f"(d[22]), "+f"(d[23]), "+f"(d[24]), "+f"(d[25]), "+f"(d[26]), "+f"(d[27]), "+f"(d[28]), "+f"(d[29]), "+f"(d[30]), "+f"(d[31]), "+f"(d[32]), "+f"(d[33]), "+f"(d[34]), "+f"(d[35]), "+f"(d[36]), "+f"(d[37]), "+f"(d[38]), "+f"(d[39]), "+f"(d[40]), "+f"(d[41]), "+f"(d[42]), "+f"(d[43]), "+f"(d[44]), "+f"(d[45]), "+f"(d[46]), "+f"(d[47]), "+f"(d[48]), "+f"(d[49]), "+f"(d[50]), "+f"(d[51]), "+f"(d[52]), "+f"(d[53]), "+f"(d[54]), "+f"(d[55]), "+f"(d[56]), "+f"(d[57]), "+f"(d[58]), "+f"(d[59]), "+f"(d[60]), "+f"(d[61]), "+f"(d[62]), "+f"(d[63])
               : "l"(da), "l"(db), "r"(sc));
}

__device__ __forceinline__ void stsm4(uint32_t a, uint32_t r0, uint32_t r1, uint32_t r2, uint32_t r3) {
  asm volatile("stmatrix.sync.aligned.m8n8.x4.shared.b16 [%0],{%1,%2,%3,%4};" ::"r"(a), "r"(r0), "r"(r1), "r"(r2), "r"(r3) : "memory");
}
__device__ __forceinline__ void stsm4t(uint32_t a, uint32_t r0, uint32_t r1, uint32_t r2, uint32_t r3) {
  asm volatile("stmatrix.sync.aligned.m8n8.x4.trans.shared.b16 [%0],{%1,%2,%3,%4};" ::"r"(a), "r"(r0), "r"(r1), "r"(r2), "r"(r3) : "memory");
}
__device__ __forceinline__ void sts64(uint32_t a, uint32_t x, uint32_t y) { asm volatile("st.shared.v2.b32 [%0],{%1,%2};" ::"r"(a), "r"(x), "r"(y) : "memory"); }
__device__ __forceinline__ void st_async2u(uint32_t a, uint32_t x, uint32_t y, uint32_t bar) {
  asm volatile("st.async.weak.shared::cluster.mbarrier::complete_tx::bytes.v2.b32 [%0],{%1,%2},[%3];" ::"r"(a), "r"(x), "r"(y), "r"(bar) : "memory");
}
__device__ __forceinline__ void st_relaxed128(void* p, uint32_t x, uint32_t y, uint32_t z, uint32_t w) {
  asm volatile("{.reg .b128 v; mov.b128 v,{%1,%2,%3,%4}; st.relaxed.gpu.global.b128 [%0],v;}" ::"l"(p), "r"(x), "r"(y), "r"(z), "r"(w) : "memory");
}
__device__ __forceinline__ void st_relaxed64(void* p, uint32_t x, uint32_t y) {
  asm volatile("{.reg .b64 v; mov.b64 v,{%1,%2}; st.relaxed.gpu.global.b64 [%0],v;}" ::"l"(p), "r"(x), "r"(y) : "memory");
}
__device__ __forceinline__ uint4 ld_relaxed128(const void* p) {
  uint4 v;
  asm volatile("{.reg .b128 v; .reg .b64 lo, hi; ld.relaxed.gpu.global.b128 v,[%4]; mov.b128 {lo,hi},v; mov.b64 {%0,%1},lo; mov.b64 {%2,%3},hi;}" : "=r"(v.x), "=r"(v.y), "=r"(v.z), "=r"(v.w) : "l"(p) : "memory");
  return v;
}

__device__ __forceinline__ uint32_t pack_h2(float lo, float hi) {
  uint32_t r; asm("cvt.rn.satfinite.f16x2.f32 %0,%1,%2;" : "=r"(r) : "f"(hi), "f"(lo)); return r;
}
__device__ __forceinline__ void add_h2(float& lo, float& hi, uint32_t u, uint32_t v) {
  float a, b;
  asm("{.reg .b16 l, h; .reg .b32 s; add.rn.f16x2 s,%2,%3; mov.b32 {l,h},s; cvt.f32.f16 %0,l; cvt.f32.f16 %1,h;}" : "=f"(a), "=f"(b) : "r"(u), "r"(v));
  lo += a; hi += b;
}
__device__ __forceinline__ void mwait(uint32_t bar, uint32_t ph, int& spin) {
  asm volatile("{.reg .pred p, q;\nWAIT_LOOP:\n add.s32 %0,%0,1;\n setp.lt.s32 q,%0,%3;\n mbarrier.try_wait.parity.shared::cta.b64 p,[%1],%2;\n not.pred p,p;\n and.pred q,q,p;\n @q bra.uni WAIT_LOOP;\n}"
               : "+&r"(spin) : "r"(bar), "r"(ph), "n"(SPIN_TOT) : "memory");
}
__device__ __forceinline__ int keep(int x) { return __shfl_sync(0xffffffffu, x, threadIdx.x & 31); }
__device__ __forceinline__ uint32_t pin(uint32_t x) { asm volatile("" : "+r"(x)); return x; }
template <typename T> __device__ __forceinline__ T* pinp(T* x) { asm volatile("" : "+l"(x)); return x; }
__device__ __forceinline__ void st_async1u(uint32_t a, uint32_t x, uint32_t bar) {
  asm volatile("st.async.weak.shared::cluster.mbarrier::complete_tx::bytes.b32 [%0],%1,[%2];" ::"r"(a), "r"(x), "r"(bar) : "memory");
}
__device__ __forceinline__ uint32_t lds32(uint32_t a) { uint32_t v; asm volatile("ld.shared.b32 %0,[%1];" : "=r"(v) : "r"(a) : "memory"); return v; }
__device__ __forceinline__ uint2 lds64(uint32_t a) { uint2 v; asm volatile("ld.shared.v2.b32 {%0,%1},[%2];" : "=r"(v.x), "=r"(v.y) : "r"(a) : "memory"); return v; }

__device__ __forceinline__ void permute_cols(uint32_t tile, int tid, int n) {
  for (int it = tid; it < n; it += 128) {
    const int row = it >> 2, q = it & 3;
    const uint32_t a0 = tile + row * 128 + (((2 * q) ^ (row & 7)) << 4), a1 = tile + row * 128 + (((2 * q + 1) ^ (row & 7)) << 4);
    const uint4 u = lds128(a0), v = lds128(a1);
    sts128(a0, make_uint4(__byte_perm(u.x, u.y, 0x5410), __byte_perm(u.z, u.w, 0x5410), __byte_perm(v.x, v.y, 0x5410), __byte_perm(v.z, v.w, 0x5410)));
    sts128(a1, make_uint4(__byte_perm(u.x, u.y, 0x7632), __byte_perm(u.z, u.w, 0x7632), __byte_perm(v.x, v.y, 0x7632), __byte_perm(v.z, v.w, 0x7632)));
  }
}

__device__ __forceinline__ uint8_t* mkptr(uint32_t lo, uint32_t hi) { uint8_t* p; asm("mov.b64 %0,{%1,%2};" : "=l"(p) : "r"(lo), "r"(hi)); return p; }
__device__ __forceinline__ int uni(int x) { return __shfl_sync(0xffffffffu, x, 0); }

__device__ __forceinline__ bool elect_one() {
  uint32_t p; asm volatile("{.reg .pred q; elect.sync _|q, 0xffffffff; selp.u32 %0,1,0,q;}" : "=r"(p)); return p;
}
__device__ __forceinline__ uint64_t desc_at(uint64_t d, uint32_t off) {
  uint64_t r; asm("mov.b64 %0,{%1,%2};" : "=l"(r) : "r"((uint32_t)d + (off >> 4)), "r"((uint32_t)(d >> 32))); return r;
}
__device__ __forceinline__ uint32_t scale_bf16x2(uint32_t x, uint32_t s) { uint32_t r; asm("mul.rn.bf16x2 %0,%1,%2;" : "=r"(r) : "r"(x), "r"(s)); return r; }

__device__ __forceinline__ void ln_row_to_image(const bf16* __restrict__ x, uint8_t* __restrict__ img, int row, int lane) {
  const uint4* src = reinterpret_cast<const uint4*>(x + (size_t)row * DM);
  uint4 v[3];
  v[0] = src[lane]; v[1] = src[lane + 32];
  v[2] = lane < 16 ? src[lane + 64] : make_uint4(0, 0, 0, 0);
  float s = 0.f;
#pragma unroll
  for (int i = 0; i < 3; i++) {
    s += bf_lo(v[i].x) + bf_hi(v[i].x) + bf_lo(v[i].y) + bf_hi(v[i].y) + bf_lo(v[i].z) + bf_hi(v[i].z) + bf_lo(v[i].w) + bf_hi(v[i].w);
  }
#pragma unroll
  for (int o = 16; o > 0; o >>= 1) s += __shfl_xor_sync(0xffffffffu, s, o);
  const float mean = s * (1.f / DM);
  float q = 0.f;
#pragma unroll
  for (int i = 0; i < 3; i++) {
    if (i < 2 || lane < 16) {
      const uint32_t w[4] = {v[i].x, v[i].y, v[i].z, v[i].w};
#pragma unroll
      for (int j = 0; j < 4; j++) { float a = bf_lo(w[j]) - mean, b = bf_hi(w[j]) - mean; q += a * a + b * b; }
    }
  }
#pragma unroll
  for (int o = 16; o > 0; o >>= 1) q += __shfl_xor_sync(0xffffffffu, q, o);
  const float rstd = rsqrtf(q * (1.f / DM) + 1e-5f);
#pragma unroll
  for (int i = 0; i < 3; i++) {
    if (i < 2 || lane < 16) {
      const int c = lane + 32 * i;
      uint4 o;
      o.x = pack_bf16((bf_lo(v[i].x) - mean) * rstd, (bf_hi(v[i].x) - mean) * rstd);
      o.y = pack_bf16((bf_lo(v[i].y) - mean) * rstd, (bf_hi(v[i].y) - mean) * rstd);
      o.z = pack_bf16((bf_lo(v[i].z) - mean) * rstd, (bf_hi(v[i].z) - mean) * rstd);
      o.w = pack_bf16((bf_lo(v[i].w) - mean) * rstd, (bf_hi(v[i].w) - mean) * rstd);
      const size_t off = (size_t)(row >> 5) * 81920 + (c >> 4) * 16384 + ((row >> 3) & 3) * 4096 + ((c >> 3) & 1) * 1024 + (row & 7) * 128 + (((c & 7) ^ (row & 7)) << 4);
      *reinterpret_cast<uint4*>(img + off) = o;
      float4* xf = reinterpret_cast<float4*>(g_x + (size_t)row * DM + c * 8);
      xf[0] = make_float4(bf_lo(v[i].x), bf_hi(v[i].x), bf_lo(v[i].y), bf_hi(v[i].y));
      xf[1] = make_float4(bf_lo(v[i].z), bf_hi(v[i].z), bf_lo(v[i].w), bf_hi(v[i].w));
    }
  }
}

#define NOWORK 0
__global__ void __launch_bounds__(256) k_pre(const bf16* __restrict__ x, const bf16* __restrict__ mem0) {
  const int row = blockIdx.x * 8 + (threadIdx.x >> 5);
  ln_row_to_image(x, g_xn[0], row, threadIdx.x & 31);
  const int gt = blockIdx.x * 256 + threadIdx.x;
  const uint4 sent = make_uint4(SENT, SENT, SENT, SENT);
  uint8_t* ex = ex_window(g_ex);
  if (gt < MAIL_BYTES / 16) {
    reinterpret_cast<uint4*>(ex + EX_MAIL)[gt] = sent;
    reinterpret_cast<uint4*>(ex + EX_MAIL + (1 << 20))[gt] = sent;
  }
  uint4* mb = reinterpret_cast<uint4*>(ex + EX_M);
  for (int i = gt; i < NSTEP * 1280; i += 65536) {
    const int p = i % 1280, st = i / 1280;
    uint4 v = sent;
    if (st == 0 || (st == LAG && (p & 8))) v = *reinterpret_cast<const uint4*>(mem0 + (p & 7) * DM + (p >> 4) * 8);
    mb[i] = v;
  }
  if (gt < NSTEP * 192) reinterpret_cast<uint4*>(ex + EX_FLAG)[gt] = gt < 192 ? make_uint4(0, 0, 0, 0) : sent;
  for (int i = gt; i < (NOWORK ? NSTEP + LAG : 2 * LAG) * 2560; i += 65536) {
    const int st = i / 2560, p = i % 2560;
    *reinterpret_cast<uint4*>(g_xn[st < LAG ? st + NSEG : st - LAG] + (p >> 7) * 4096 + (st < LAG ? 0 : 2048) + (p & 127) * 16) = make_uint4(0, 0, 0, 0);
  }
  if (gt < CN_NUM) g_cnt[gt][0] = 0;
}

namespace C {
constexpr int NKR = 37;
constexpr int OFF_WQ = 0, OFF_WK = 81920;
constexpr int OFF_YO = 163840, OFF_YV = OFF_YO + 6144;
constexpr int OFF_M = 176128;
__host__ __device__ constexpr int og_off(int c) { return c ? OFF_M + 14336 + c * 2048 : 229376; }
constexpr int OFF_KT = 196608;
constexpr int OFF_XT = OFF_KT + 10240;
constexpr int OFF_VT = OFF_XT + 7168;
constexpr int OFF_XM = OFF_VT + 11392;
constexpr int OFF_PT = OFF_XM + 2560;
constexpr int KS = 1280, VS = 1408;
__host__ __device__ constexpr int slot_off(int p) { return p == 2 ? OFF_M : OFF_KT + (p % 3) * 16384; }
constexpr int OFF_ONE = 231424;
constexpr int OFF_BAR = 231552;
constexpr int OFF_SAFE = OFF_BAR + 160;
constexpr int OFF_TS = OFF_BAR + 256;
constexpr int SMEM = 232448;
constexpr uint32_t SB0 = 1024;
constexpr int BAR_F = OFF_BAR, BAR_XM = BAR_F + 40, BAR_XT = BAR_F + 48, BAR_OG = BAR_F + 56, BAR_E = OFF_BAR + 64, BAR_MOK = BAR_E + 40,
              BAR_M = OFF_BAR + 112, BAR_XF = OFF_BAR + 120, BAR_MF = OFF_BAR + 128, BAR_W = OFF_BAR + 136, FLG_REDO = OFF_BAR + 144;
constexpr int NB_PRO = 1, NB_RD = 2, NB_MR = 3, NB_QK = 4, NB_SM = 5, NB_VA = 6, NB_VQ = 7, NB_A = 8, NB_Q = 9, NB_C = 10, NB_WQ = 11, NB_QI = 12, NB_SI = 13, NB_WV = 14;
#define B1 300
#define B2 250
#define FLP 1
#define OSG 2
#define P1U 10
#define QIE 4
#define SIE 2
#define WOE 1
#define OGF 0
#define VSP 8
#define RFK 5
#define PFD 3
#define WOL 0
constexpr uint32_t SCQ = 0x3A003A00;
constexpr float SCE = 0.07216878364870322f * 1.4426950408889634f * 2048;
}

#define CBAR_SYNC(id, n) bar_sync(id, n)
#define CBAR_ARRIVE(id, n) bar_arrive(id, n)

__device__ __forceinline__ uint64_t wdesc(int off) { return mkdesc(C::SB0 + off, 8192, 1024); }
__device__ __forceinline__ uint64_t mdesc(int k) { return mkdesc_ns(C::SB0 + C::OFF_M + k * 512, 256, 128); }
__device__ __forceinline__ uint64_t tdesc(int k) { return mkdesc(C::SB0 + C::slot_off(k >> 3) + ((k >> 2) & 1) * 1024 + (k & 3) * 32, 16, 2048); }

__device__ __forceinline__ int dh_row(int n) { return (n & ~63) + (n & 32) + ((n >> 1) & 3) * 8 + ((n >> 3) & 3) * 2 + (n & 1); }
template <bool PERM>
__device__ __forceinline__ void load_weights_rs(uint32_t (&wf)[C::NKR][4], uint32_t sb, int stage, int yoff, int tid0) {
  using namespace C;
  const int i = (tid0 >> 3) & 3, n0 = (tid0 & 7) + (i >> 1) * 8;
  const int chunk = 2 * ((tid0 >> 5) & 3) + (i & 1);
  const int r0 = PERM ? dh_row(n0) : n0, r1 = PERM ? dh_row(n0 + 16) : n0 + 16;
  const uint32_t a0 = sb + stage + r0 * 128 + ((chunk ^ (r0 & 7)) << 4), a1 = sb + stage + r1 * 128 + ((chunk ^ (r1 & 7)) << 4);
#pragma unroll
  for (int k = 0; k < NKR; k++) ldsm4t(wf[k], ((k & 1) ? a1 : a0) + (k >> 1) * 4096);
#pragma unroll
  for (int k = 0; k < 40 - NKR; k++) {
    const int n = (NKR + k) * 16 + ((tid0 & 127) >> 3), r = PERM ? dh_row(n) : n, c = tid0 & 7;
    sts128(sb + yoff + (n - NKR * 16) * 128 + ((c ^ (n & 7)) << 4), lds128(sb + stage + r * 128 + ((c ^ (r & 7)) << 4)));
  }
  fence_async();
  CBAR_SYNC(NB_PRO, 384);
}
template <int STRIDE>
__device__ __forceinline__ void store_mem(const float (&d)[8], uint32_t base, int tid) {
  const int m = (tid >> 3) & 3;
  stsm4(base + (((tid >> 5) & 3) * 2 + (m & 1)) * STRIDE + (m >> 1) * 640 + (tid & 7) * 16, pack_bf16(d[0], d[1]), pack_bf16(d[2], d[3]),
        pack_bf16(d[4], d[5]), pack_bf16(d[6], d[7]));
}

__device__ __forceinline__ void load_pair(uint32_t sb, int i, int p, uint32_t slot, uint32_t ph, int& spin) {
  using namespace C;
  mwait(sb + BAR_E + 8 * p, ph, spin);
  if (elect_one()) bulk_g2s_mc(sb + slot, g_xn[i] + p * 16384, 16384, sb + BAR_F + 8 * p);
}
__device__ __forceinline__ void release_round(uint32_t sb, int p, int lane) {
  if (lane < (p == 2 ? 3 : 1)) mbar_arrive_cluster(mapa(sb, p == 2 ? lane : p) + C::BAR_E + 8 * (3 + p));
}

template <int K0, int K1>
__device__ __forceinline__ void v_mem_pass(float (&d)[8], const uint32_t (&wf)[C::NKR][4]) {
  using namespace C;
  wg_fence();
#pragma unroll
  for (int k = K0; k < K1; k++) {
    if (k < NKR) wgmma_rs16(d, wf[k < NKR ? k : 0], mdesc(k), k != 32);
    else wgmma_ts16(d, wdesc(OFF_YV + (k - NKR) * 2048), mdesc(k), 1);
  }
  wg_commit();
}
__device__ __forceinline__ void chain_v(const uint32_t sb, const int tid0, const int cta, const int rank) {
  using namespace C;
  asm volatile("setmaxnreg.inc.sync.aligned.u32 208;");
  int spin = 0;
  uint32_t wf[NKR][4];
  const int wu = uni((tid0 >> 5) & 3);
  const uint32_t slot = rank == 2 ? OFF_M : OFF_KT + rank * 16384;
  if (wu == 0) load_pair(sb, 0, rank, slot, 1, spin);
  mwait(sb + BAR_W, 0, spin);
  for (int it = tid0 & 127; it < 1280; it += 128) {
    const uint32_t base = sb + OFF_WK + (it >> 1) * 128;
    const int sw = ((it >> 1) & 7) ^ ((it & 1) * 4);
    const uint4 u0 = lds128(base + (sw << 4)), u1 = lds128(base + ((sw ^ 1) << 4)), u2 = lds128(base + ((sw ^ 2) << 4)), u3 = lds128(base + ((sw ^ 3) << 4));
    sts128(base + (sw << 4), make_uint4(u0.x, u1.x, u2.x, u3.x)); sts128(base + ((sw ^ 1) << 4), make_uint4(u0.y, u1.y, u2.y, u3.y));
    sts128(base + ((sw ^ 2) << 4), make_uint4(u0.z, u1.z, u2.z, u3.z)); sts128(base + ((sw ^ 3) << 4), make_uint4(u0.w, u1.w, u2.w, u3.w));
  }
  bar_sync(NB_RD, 128);
  load_weights_rs<false>(wf, sb, OFF_WK, OFF_YV, tid0);
#pragma unroll 1
  for (int i = 0; i < NSTEP; i++) {
    {
      float d[32];
      if (i > 0) CBAR_SYNC(NB_WV, 256);
#pragma unroll
      for (int p = 0; p < 5; p++) {
        mwait(sb + BAR_F + 8 * p, i & 1, spin);
        TS(i, 25 + p);
        wg_fence();
#pragma unroll
        for (int k = 8 * p; k < 8 * p + 8; k++) {
          if (k < NKR) wgmma_rs64(d, wf[k < NKR ? k : 0], tdesc(k), k);
          else wgmma_ts64(d, wdesc(OFF_YV + (k - NKR) * 2048), tdesc(k), 1);
          if (k == 8 * p + 1 && p >= 1 && p <= 3) {
            wg_commit(); wg_wait<1>();
            release_round(sb, p - 1, tid0 & 31);
          }
          if (k == 8 * p + RFK && (p == 1 || p == 2)) {
            wg_commit();
            if (rank == p - 1 && wu == 0) load_pair(sb, i, p + 2, slot_off(p + 2), i & 1, spin);
            wg_fence();
          }
        }
        wg_commit();
      }
      wg_wait<0>();
      TS(i, 23);
      CBAR_SYNC(NB_RD, 256);
      const int tid = fresh(tid0) & 127, m = (tid >> 3) & 3;
      if (tid < 8) mbar_expect_tx(sb + BAR_F + 8 * tid, tid < 5 ? 16384 : tid == 5 ? 2560 : tid == 6 ? 7168 : 4096);
      if (tid < 3 && tid != rank) mbar_arrive_cluster(mapa(sb, tid) + BAR_XF);
      const uint32_t a = sb + OFF_VT + 256 + ((tid >> 5) * 2 + (m & 1)) * VS + (m >> 1) * 640 + (tid & 7) * 16;
#pragma unroll
      for (int s = 0; s < 4; s++)
        stsm4(a + s * 128, pack_bf16(d[8 * s], d[8 * s + 1]), pack_bf16(d[8 * s + 2], d[8 * s + 3]),
              pack_bf16(d[8 * s + 4], d[8 * s + 5]), pack_bf16(d[8 * s + 6], d[8 * s + 7]));
      if (tid < 80) sts128(sb + (tid < 72 ? OFF_VT + (tid >> 3) * VS : OFF_PT + 1280) + (tid & 7) * 16, make_uint4(0, 0, 0, 0));
      fence_async();
    }
    mwait(sb + BAR_XF, i & 1, spin);
    CBAR_ARRIVE(NB_QK, 384);
    const uint32_t* xc = &g_cnt[CN_X + i + 1 - LAG][0];
    bool seen = NOWORK || i + 1 < LAG;
    if (wu == 0 && !seen) { seen = ld_acquire(xc) >= 32; fence_async_all(); }
    CBAR_SYNC(NB_QI, 256);
    float d[8];
    v_mem_pass<32, 40>(d, wf);
    CBAR_SYNC(NB_SM, 256);
    wg_wait<0>();
    if (__builtin_expect(lds32(sb + FLG_REDO), 0)) { v_mem_pass<32, 40>(d, wf); wg_wait<0>(); }
    if ((tid0 & 31) < 3 && (tid0 & 31) != rank) mbar_arrive_cluster(mapa(sb, tid0 & 31) + BAR_MF);
    v_mem_pass<0, 32>(d, wf);
    wg_wait<0>();
    TS(i, 24);
    const int tid = fresh(tid0);
    if ((tid & 31) == 0) mbar_arrive_cluster(mapa(sb, 2) + BAR_E + 16);
    store_mem<VS>(d, sb + OFF_VT + 128, tid);
    fence_async();
    CBAR_ARRIVE(NB_VA, 256);
    CBAR_ARRIVE(NB_VQ, 256);
    if (wu == 0 && i + 1 < NSTEP) {
      if (__builtin_expect(!seen, 0)) { while (ld_acquire(xc) < 32 && spin < SPIN_TOT) spin += 16; fence_async_all(); }
      load_pair(sb, i + 1, rank, slot, i & 1, spin);
      TS(i + 1, 37);
    }
    TS_FLUSH(i - 1);
    __syncwarp();
  }
  CBAR_ARRIVE(NB_WV, 256);
  if (spin >= SPIN_TOT) g_err = 3;
}

__device__ __forceinline__ float quad_max(float x) {
  const float a = __shfl_xor_sync(0xffffffffu, x, 1), b = __shfl_xor_sync(0xffffffffu, x, 2), c = __shfl_xor_sync(0xffffffffu, x, 3);
  return fmaxf(fmaxf(x, a), fmaxf(b, c));
}
__device__ __forceinline__ float quad_sum(float x) {
  const float a = __shfl_xor_sync(0xffffffffu, x, 1), b = __shfl_xor_sync(0xffffffffu, x, 2), c = __shfl_xor_sync(0xffffffffu, x, 3);
  return (x + a) + (b + c);
}
__device__ __forceinline__ float max10(const float (&y)[10]) {
  return fmaxf(fmaxf(fmaxf(fmaxf(y[0], y[1]), fmaxf(y[2], y[3])), fmaxf(fmaxf(y[4], y[5]), fmaxf(y[6], y[7]))), fmaxf(y[8], y[9]));
}
__device__ __forceinline__ float sum10(const float (&y)[10]) {
  return (((y[0] + y[1]) + (y[2] + y[3])) + ((y[4] + y[5]) + (y[6] + y[7]))) + (y[8] + y[9]);
}
__device__ __forceinline__ float rcp(float x) { float y; asm("rcp.approx.ftz.f32 %0,%1;" : "=f"(y) : "f"(x)); return y; }

__device__ __forceinline__ void signal_o(int i, int cta) { csignal(CN_O + i * 5 + min(cta / 19, 4)); }

__device__ __forceinline__ void chain_q(const CUtensorMap& tmWq, const CUtensorMap& tmWk, const uint32_t sb, const int tid0, const int cta, const int rank) {
  using namespace C;
  asm volatile("setmaxnreg.dec.sync.aligned.u32 96;");
  int spin = 0;
  CBAR_SYNC(NB_PRO, 384);
  PTS(5);
  if (tid0 == 128) {
    const int col = (cta / 3) * DH + rank * 64;
    mbar_expect_tx(sb + BAR_W, 163840);
    for (int i = 0; i < 5; i++) {
      tma2d(sb + OFF_WQ + i * 16384, &tmWq, col, i * 128, sb + BAR_W);
      tma2d(sb + OFF_WK + i * 16384, &tmWk, col, i * 128, sb + BAR_W);
    }
  }
  __syncwarp();
  mwait(sb + BAR_W, 1, spin);
  PTS(6);
  const int wu = uni((tid0 >> 5) & 3);
#pragma unroll 1
  for (int i = 0; i < NSTEP; i++) {
    const int ph = i & 1;
    uint32_t qf[4][4];
    {
      float d[64];
#pragma unroll
      for (int k = 0; k < 64; k++) d[k] = 0.f;
#pragma unroll 1
      for (int p = 0; p < 5; p++) {
        const uint32_t so = p == 2 ? OFF_M : OFF_KT + (p == 1 || p == 4 ? 16384 : 0);
        mwait(sb + BAR_F + 8 * p, ph, spin);
        if (p == 0) TS(i, 0);
        wg_fence();
#pragma unroll
        for (int k = 0; k < 8; k++) {
          wgmma_st128(d, desc_at(mkdesc(SB0 + (k >> 2) * 1024 + (k & 3) * 32, 16, 2048), so),
                      desc_at(mkdesc(SB0 + OFF_WQ + k * 2048, OFF_WK - OFF_WQ, 1024), p * 16384), 1);
          if (k == 1) {
            wg_commit(); wg_wait<1>();
            release_round(sb, p - 1, (p & 3) ? tid0 & 31 : 32);
          }
        }
        wg_commit();
      }
      wg_wait<0>();
      TS(i, 1);
      CBAR_SYNC(NB_RD, 256);
      TSB(i, 2);
      const int tid = fresh(tid0), w = (tid >> 5) & 3, m = (tid >> 3) & 3;
      const uint32_t a = sb + OFF_KT + (m >> 1) * KS + (1 + w + 5 * (m & 1)) * 128 + (tid & 7) * 16;
#pragma unroll
      for (int s = 0; s < 4; s++)
        stsm4t(a + s * 2 * KS, pack_bf16(d[32 + 8 * s], d[33 + 8 * s]), pack_bf16(d[34 + 8 * s], d[35 + 8 * s]),
               pack_bf16(d[36 + 8 * s], d[37 + 8 * s]), pack_bf16(d[38 + 8 * s], d[39 + 8 * s]));
      fence_async();
      CBAR_ARRIVE(NB_QK, 384);
      if (OSG == 0) { if (tid == 224 && i > 0) signal_o(i - 1, cta); __syncwarp(); }
#pragma unroll
      for (int kk = 0; kk < 4; kk++)
#pragma unroll
        for (int j = 0; j < 4; j++) asm volatile("{.reg .b32 t; cvt.rn.bf16x2.f32 t,%1,%2; mul.rn.bf16x2 %0,t,%3;}" : "=r"(qf[kk][j]) : "f"(d[8 * kk + 2 * j + 1]), "f"(d[8 * kk + 2 * j]), "r"(SCQ));
    }
    CBAR_SYNC(NB_SI, 256);
    uint32_t pf[5][4];
    {
      float y0[10], y1[10];
      const int tidf = fresh(tid0), lane = tidf & 31;
      {
        float x[40];
        wg_fence();
#pragma unroll
        for (int kk = 0; kk < 4; kk++) wgmma_rt80(x, qf[kk], mkdesc_ns(SB0 + OFF_KT + kk * 2 * KS, KS, 128), kk);
        wg_commit();
        wg_wait<0>();
#pragma unroll
        for (int j = 0; j < 5; j++) { y0[2 * j] = x[4 * j]; y0[2 * j + 1] = x[4 * j + 1]; y1[2 * j] = x[22 + 4 * j]; y1[2 * j + 1] = x[23 + 4 * j]; }
      }
      TS(i, 17);
      const uint32_t xo = OFF_XT + (wu * (wu + 3) / 2) * 256 + lane * 16, x2 = xo + (wu >> 1) * 512 + 512 - lane * 8;
      {
        const uint4 h0 = make_uint4(pack_h2(y0[0], y0[1]), pack_h2(y1[0], y1[1]), pack_h2(y0[2], y0[3]), pack_h2(y1[2], y1[3]));
        const uint4 h1 = make_uint4(pack_h2(y0[4], y0[5]), pack_h2(y1[4], y1[5]), pack_h2(y0[6], y0[7]), pack_h2(y1[6], y1[7]));
        const uint32_t h2 = wu == 1 ? h1.x : pack_h2(y0[8], y0[9]), h3 = wu == 1 ? h1.y : pack_h2(y1[8], y1[9]);
        const uint32_t rb1 = mapa(sb, (rank + 1) % 3), rb2 = mapa(sb, (rank + 2) % 3);
        st_async4u(rb1 + xo + 3584, h0, rb1 + BAR_XT);
        st_async4u(rb2 + xo, h0, rb2 + BAR_XT);
        if (wu >= 2) { st_async4u(rb1 + xo + 4096, h1, rb1 + BAR_XT); st_async4u(rb2 + xo + 512, h1, rb2 + BAR_XT); }
        if (wu & 1) { st_async2u(rb1 + x2 + 3584, h2, h3, rb1 + BAR_XT); st_async2u(rb2 + x2, h2, h3, rb2 + BAR_XT); }
      }
      TS(i, 18);
      const int lim = 8 * wu + (lane >> 2) + 8 - 2 * (lane & 3);
#pragma unroll
      for (int j = 2; j < 10; j++)
        if (8 * (j >> 1) + (j & 1) > lim) { y0[j] = -INFINITY; y1[j] = -INFINITY; }
      mwait(sb + BAR_XT, ph, spin);
      TS(i, 19);
      {
        const uint4 u0 = lds128(sb + xo), v0 = lds128(sb + xo + 3584);
        uint2 u2 = make_uint2(0, 0), v2 = u2;
        if (wu & 1) { u2 = lds64(sb + x2); v2 = lds64(sb + x2 + 3584); }
        uint4 u1 = make_uint4(u2.x, u2.y, 0, 0), v1 = make_uint4(v2.x, v2.y, 0, 0);
        if (wu >= 2) { u1 = lds128(sb + xo + 512); v1 = lds128(sb + xo + 4096); }
        __syncwarp();
        if (lane == 0) mbar_arrive_cluster(mapa(sb, 0) + BAR_E);
        add_h2(y0[0], y0[1], u0.x, v0.x); add_h2(y1[0], y1[1], u0.y, v0.y); add_h2(y0[2], y0[3], u0.z, v0.z); add_h2(y1[2], y1[3], u0.w, v0.w);
        add_h2(y0[4], y0[5], u1.x, v1.x); add_h2(y1[4], y1[5], u1.y, v1.y); add_h2(y0[6], y0[7], u1.z, v1.z); add_h2(y1[6], y1[7], u1.w, v1.w);
        add_h2(y0[8], y0[9], u2.x, v2.x); add_h2(y1[8], y1[9], u2.y, v2.y);
      }
      const float m0 = quad_max(max10(y0)) * -SCE, m1 = quad_max(max10(y1)) * -SCE;
#pragma unroll
      for (int j = 0; j < 5; j++) {
        pf[j >> 1][2 * (j & 1)] = pack_bf16(ex2(fmaf(y0[2 * j], SCE, m0)), ex2(fmaf(y0[2 * j + 1], SCE, m0)));
        pf[j >> 1][2 * (j & 1) + 1] = tidf >> (10 + j);
        pf[(j + 5) >> 1][2 * ((j + 5) & 1)] = tidf >> (20 + j);
        pf[(j + 5) >> 1][2 * ((j + 5) & 1) + 1] = pack_bf16(ex2(fmaf(y1[2 * j], SCE, m1)), ex2(fmaf(y1[2 * j + 1], SCE, m1)));
      }
    }
#pragma unroll
    for (int q = 0; q < 20; q++) pf[q >> 2][q & 3] = pin(pf[q >> 2][q & 3]);
    CBAR_SYNC(NB_VQ, 256);
    TSB(i, 20);
    {
      float o[32], sm[4];
      wg_fence();
#pragma unroll
      for (int q = 0; q < 5; q++) wgmma_rs8(sm, pf[q], mkdesc_ns(SB0 + OFF_ONE, 0, 0), q);
#pragma unroll
      for (int q = 0; q < 5; q++) wgmma_rs64(o, pf[q], mkdesc_ns(SB0 + OFF_VT + 128 + q * 256, 128, VS), q);
      wg_commit();
      const int tid = fresh(tid0), g = (tid >> 2) & 7;
      uint8_t* op = pinp(&g_o[i % ORING][cta][(tid & 124) * 32]);
      const uint32_t o0 = pin(((tid & 3) ^ g) << 4);
      wg_wait<0>();
      TS(i, 21);
      if ((tid & 31) == 0) mbar_arrive_cluster(mapa(sb, 1) + BAR_E + 8);
      const float s0 = rcp(sm[0]), s1 = rcp(sm[2]);
      uint4 ov[4];
#pragma unroll
      for (int h = 0; h < 2; h++) {
        const float* x = o + 16 * h;
        ov[2 * h] = make_uint4(pin(pack_bf16(x[0] * s0, x[1] * s0)), pin(pack_bf16(x[4] * s0, x[5] * s0)), pin(pack_bf16(x[8] * s0, x[9] * s0)), pin(pack_bf16(x[12] * s0, x[13] * s0)));
        ov[2 * h + 1] = make_uint4(pin(pack_bf16(x[2] * s1, x[3] * s1)), pin(pack_bf16(x[6] * s1, x[7] * s1)), pin(pack_bf16(x[10] * s1, x[11] * s1)), pin(pack_bf16(x[14] * s1, x[15] * s1)));
      }
      TS(i, 22);
      if (i + 1 < NSTEP) CBAR_SYNC(NB_WQ, 256); else CBAR_ARRIVE(NB_WQ, 256);
#pragma unroll
      for (int h = 0; h < 4; h++) *reinterpret_cast<uint4*>(op + (h & 1) * 4096 + (o0 ^ ((h >> 1) * 64))) = ov[h];
      if (OSG && i + 1 < NSTEP) CBAR_ARRIVE(NB_MR, 160);
    }
  }
  CBAR_SYNC(NB_Q, 128);
  if (tid0 == 224) signal_o(NSTEP - 1, cta);
  if (spin >= SPIN_TOT) g_err = 2;
}

template <int NL>
__device__ __forceinline__ void poll_add(const uint8_t* mb, uint32_t tag, float (&f)[8], uint8_t* flag, bool lead, int osig, int& n, int& spin) {
  uint4 x[NL];
#pragma unroll
  for (int i = 0; i < NL; i++) x[i] = ld_relaxed128(mb + i * 512);
  if (OSG == 1 && osig >= 0) csignal(osig);
  while (true) {
    uint32_t any = 0;
#pragma unroll
    for (int i = 0; i < NL; i++) any |= (x[i].x ^ tag) | (NL == 6 ? x[i].z ^ tag : 0u);
    n++;
    if (!__any_sync(0xffffffffu, (any & 1) && spin < SPIN_TOT)) break;
    spin += 16;
#pragma unroll
    for (int i = 0; i < NL; i++)
      if (((pin(x[i].x) ^ tag) | (NL == 6 ? x[i].z ^ tag : 0u)) & 1) x[i] = ld_relaxed128(mb + i * 512);
  }
  if (FLP == 0 && lead) st_relaxed(flag, 0);
#pragma unroll
  for (int i = 0; i < NL; i++) {
    const uint32_t u[4] = {x[i].x, x[i].y, x[i].z, x[i].w};
#pragma unroll
    for (int j = 0; j < 4; j++) {
      if (i == 0) { f[2 * j] = bf_lo(u[j]); f[2 * j + 1] = bf_hi(u[j]); }
      else { f[2 * j] += bf_lo(u[j]); f[2 * j + 1] += bf_hi(u[j]); }
    }
  }
}

template <int B, int SLOT>
__device__ __forceinline__ void wo_block(float (&acc)[8], const uint32_t (&wf)[C::NKR][4]) {
  using namespace C;
#pragma unroll
  for (int kk = 0; kk < 4; kk++) {
    const int k = 4 * B + kk;
    const uint64_t db = mkdesc_ns(SB0 + og_off(SLOT) + kk * 512, 256, 128);
    if (k < NKR) wgmma_rt16(acc, wf[k < NKR ? k : 0], db, SLOT | kk);
    else wgmma_tt16(acc, wdesc(OFF_YO + (k - NKR) * 2048), db, 1);
  }
}

__device__ __forceinline__ void chain_a(const uint32_t sb, const int tid0, const int cta, const int rank) {
  using namespace C;
  asm volatile("setmaxnreg.inc.sync.aligned.u32 200;");
  int spin = 0;
  uint32_t wf[NKR][4];
  mwait(sb + BAR_W, 0, spin);
  permute_cols(sb + OFF_WQ, tid0, 2560);
  CBAR_SYNC(NB_A, 128);
  load_weights_rs<true>(wf, sb, OFF_WQ, OFF_YO, tid0);
  const int wu = uni(tid0 >> 5);
  const bool t9 = cta >= 72 && cta < 88;
  const uint64_t exa = reinterpret_cast<uint64_t>(ex_window(g_ex));
  const uint32_t ehi = (uint32_t)(exa >> 32), elo = (uint32_t)exa;

#pragma unroll 1
  for (int i = -1; i < NSTEP; i++) {
    const int ph = i & 1;
    if (i >= 0) {
      const int tid = fresh(tid0);
      const uint32_t mo = __shfl_xor_sync(0xffffffffu, elo + (ph << 20) + ((rank * 24 + (tid >> 4)) * 4 + (tid & 3)) * 2048 + (cta / 3) * 64 + (tid & 12) * 4, 0);
      const uint32_t m9 = __shfl_xor_sync(0xffffffffu, elo + (ph << 20) + MAIL9 + (((tid >> 4) * 2 + (tid & 1)) * 4 + (tid & 2)) * 3072 + cta * 32 + (tid & 12) * 2, 0);
      const uint32_t oo = __shfl_xor_sync(0xffffffffu, (tid >> 5) * 512 + (tid & 2) * 64 + (tid & 28) * 4 + (tid & 1) * 8, 0);
      if (i == 0) mwait(sb + BAR_W, 1, spin);
      mwait(sb + BAR_M, ph, spin);
      TS(i, 3);
      {
        float x[20];
        int redo = 0;
      retry:
        bool bad;
        {
          float dq[8] = {}, dk[8] = {};
#pragma unroll 1
          for (int k0 = 0; k0 < 40; k0 += P1U) {
            wg_fence();
#pragma unroll
            for (int k = 0; k < P1U; k++) {
              if (k == P1U - QIE / 2 && k0 == 40 - P1U && !redo) CBAR_ARRIVE(NB_QI, 256);
              const uint64_t db = desc_at(mdesc(k), k0 * 512);
              wgmma_ts16(dq, desc_at(wdesc(OFF_WQ + k * 2048), k0 * 2048), db, 1);
              wgmma_ts16(dk, desc_at(wdesc(OFF_WK + k * 2048), k0 * 2048), db, 1);
            }
            wg_commit();
          }
          const int m = (tid >> 3) & 3, dg = (tid >> 5) * 2 + (m & 1);
          const uint32_t ka = sb + OFF_KT + dg * KS + (m >> 1) * 640 + (tid & 7) * 16;
          if (!redo) CBAR_SYNC(NB_QK, 384);
          sts32(sb + FLG_REDO, redo);
          wg_wait<0>();
          TS(i, 4);
          stsm4(ka, pack_bf16(dk[0], dk[1]), pack_bf16(dk[2], dk[3]), pack_bf16(dk[4], dk[5]), pack_bf16(dk[6], dk[7]));
          stsm4(ka + dg * (VS - KS) + (OFF_VT + 128 - OFF_KT), scale_bf16x2(pack_bf16(dq[0], dq[1]), SCQ), scale_bf16x2(pack_bf16(dq[2], dq[3]), SCQ),
                scale_bf16x2(pack_bf16(dq[4], dq[5]), SCQ), scale_bf16x2(pack_bf16(dq[6], dq[7]), SCQ));
          const float chk = (dq[0] + dq[1]) + (dq[4] + dq[5]);
          fence_async();
          bad = bar_red_or(NB_C, 128, chk != chk && !redo);
        }
        TSB(i, 5);
        wg_fence();
#pragma unroll
        for (int kk = 0; kk < 4; kk++) wgmma_tt40(x, mkdesc_ns(SB0 + OFF_VT + 128 + kk * 2 * VS, VS, 640), mkdesc_ns(SB0 + OFF_KT + kk * 2 * KS, KS, 128), kk);
#pragma unroll
        for (int kk = 0; kk < 4; kk++) {
          if (SIE && kk == 4 - SIE && !bad) CBAR_ARRIVE(NB_SI, 256);
          wgmma_tt40(x, mkdesc_ns(SB0 + OFF_VT + kk * 2 * VS, VS, 384), mkdesc_ns(SB0 + OFF_KT + 640 + kk * 2 * KS, KS, 128), 1);
        }
        wg_commit();
        if (!SIE && !bad) CBAR_ARRIVE(NB_SI, 256);
        if (__builtin_expect(__any_sync(0xffffffffu, bad), 0)) {
          wg_wait<0>();
#pragma unroll 1
          for (int k = 0; k < 10; k++) {
            uint4 v = lds128(sb + OFF_M + tid * 16 + k * 2048);
            if (v.x == SENT || v.y == SENT || v.z == SENT || v.w == SENT) {
              do { v = ld_relaxed4(mkptr(elo + EX_M + i * 20480 + tid * 16 + k * 2048, ehi)); spin += 16; } while ((v.x == SENT || v.y == SENT || v.z == SENT || v.w == SENT) && spin < SPIN_TOT);
              sts128(sb + OFF_M + tid * 16 + k * 2048, v);
            }
          }
          fence_async();
          bar_sync(NB_C, 128);
          redo = fresh(1);
          goto retry;
        }
        TSV(i, 36, redo);
        const uint32_t rb1 = mapa(sb, (rank + 1) % 3), rb2 = mapa(sb, (rank + 2) % 3);
        wg_wait<0>();
        TS(i, 6);
        if (wu < 2) {
          float y[10];
#pragma unroll
          for (int j = 0; j < 5; j++) { y[2 * j] = x[4 * j]; y[2 * j + 1] = x[4 * j + 1]; }
          const uint4 h0 = make_uint4(pack_h2(y[0], y[1]), pack_h2(y[2], y[3]), pack_h2(y[4], y[5]), pack_h2(y[6], y[7]));
          const uint32_t h1 = pack_h2(y[8], y[9]);
          st_async4u(rb1 + OFF_XM + 1024 + tid * 16, h0, rb1 + BAR_XM);
          st_async4u(rb2 + OFF_XM + tid * 16, h0, rb2 + BAR_XM);
          st_async1u(rb1 + OFF_XM + 2304 + tid * 4, h1, rb1 + BAR_XM);
          st_async1u(rb2 + OFF_XM + 2048 + tid * 4, h1, rb2 + BAR_XM);
          CBAR_ARRIVE(NB_SM, 256);
          if ((tid & 31) == 0) mbar_arrive_cluster(mapa(sb, 0) + BAR_E);
          TS(i, 7);
          const uint32_t sw = (tid & 7) * 4 + (tid & 8) * 8 + (tid & 16) * 2;
          mwait(sb + BAR_XM, ph, spin);
          TS(i, 8);
          const uint4 u0 = lds128(sb + OFF_XM + tid * 16), v0 = lds128(sb + OFF_XM + 1024 + tid * 16);
          const uint32_t u1 = lds32(sb + OFF_XM + 2048 + tid * 4), v1 = lds32(sb + OFF_XM + 2304 + tid * 4);
          add_h2(y[0], y[1], u0.x, v0.x); add_h2(y[2], y[3], u0.y, v0.y); add_h2(y[4], y[5], u0.z, v0.z); add_h2(y[6], y[7], u0.w, v0.w);
          add_h2(y[8], y[9], u1, v1);
          const float mx = quad_max(max10(y)) * -SCE;
#pragma unroll
          for (int j = 0; j < 5; j++) {
            y[2 * j] = ex2(fmaf(y[2 * j], SCE, mx)); y[2 * j + 1] = ex2(fmaf(y[2 * j + 1], SCE, mx));
            sts32(sb + OFF_PT + wu * 640 + sw + j * 128, pack_bf16(y[2 * j], y[2 * j + 1]));
          }
          sts32(sb + OFF_XM + 2048 + wu * 128 + sw, __float_as_uint(sum10(y)));
          fence_async();
          TS(i, 9);
        } else {
          CBAR_ARRIVE(NB_SM, 256);
          if ((tid & 31) == 0) mbar_arrive_cluster(mapa(sb, 0) + BAR_E);
          mwait(sb + BAR_MF, ph, spin);
        }
      }
      CBAR_SYNC(NB_VA, 256);
      TSB(i, 10);
      {
        float o[2][4];
        wg_fence();
#pragma unroll
        for (int c = 0; c < 2; c++)
#pragma unroll
          for (int q = 0; q < 3; q++)
            wgmma_ss8(o[c], mkdesc_ns(SB0 + OFF_VT + 128 + c * 640 + q * 256, 128, VS), mkdesc_ns(SB0 + OFF_PT + c * 640 + q * 256, q == 2 && c == 0 ? 768 : 128, 128), q);
        wg_commit();
        const float4 e = lds128f(sb + OFF_XM + 2048 + (tid & 15) * 16);
        const uint32_t rb1 = mapa(sb, (rank + 1) % 3), rb2 = mapa(sb, (rank + 2) % 3);
        const float inv = rcp((e.x + e.y) + (e.z + e.w));
        const int sl = (tid & 3) * 2;
        const float i0 = __shfl_sync(0xffffffffu, inv, sl), i1 = __shfl_sync(0xffffffffu, inv, sl + 1);
        const float i2 = __shfl_sync(0xffffffffu, inv, sl + 8), i3 = __shfl_sync(0xffffffffu, inv, sl + 9);
        wg_wait<0>();
        TS(i, 11);
        const uint32_t p0 = pack_bf16(o[0][0] * i0, o[0][1] * i1), p1 = pack_bf16(o[1][0] * i2, o[1][1] * i3);
        const uint32_t p2 = pack_bf16(o[0][2] * i0, o[0][3] * i1), p3 = pack_bf16(o[1][2] * i2, o[1][3] * i3);
        if (OGF) { sts64(sb + oo + og_off(0), p0, p1); sts64(sb + oo + og_off(0) + 256, p2, p3); fence_async(); }
        st_async2u(rb1 + oo + og_off(2), p0, p1, rb1 + BAR_OG);
        st_async2u(rb2 + oo + og_off(1), p0, p1, rb2 + BAR_OG);
        st_async2u(rb1 + oo + og_off(2) + 256, p2, p3, rb1 + BAR_OG);
        st_async2u(rb2 + oo + og_off(1) + 256, p2, p3, rb2 + BAR_OG);
        if (!OGF) { sts64(sb + oo + og_off(0), p0, p1); sts64(sb + oo + og_off(0) + 256, p2, p3); fence_async(); }
      }
      CBAR_SYNC(NB_A, 128);
      TSB(i, 12);
      {
        float acc[3][8];
        wg_fence();
        wo_block<0, 0>(acc[2], wf);
        wg_commit();
        wo_block<1, 0>(acc[0], wf);
        wo_block<4, 0>(acc[1], wf);
        wg_commit();
        const bool og = mbar_try(sb + BAR_OG, ph);
        const uint32_t tag = (i >> 1) & 1;
#define TAGGED(LO, HI) ((pack_bf16(LO, HI) & ~1u) | tag)
#define SEND(OFF, U) st_relaxed128(mkptr(mo, ehi) + (OFF), TAGGED(acc[U][0], acc[U][2]), pack_bf16(acc[U][1], acc[U][3]), pack_bf16(acc[U][4], acc[U][6]), pack_bf16(acc[U][5], acc[U][7]))
        wg_wait<1>();
        const uint32_t n0 = pin(TAGGED(acc[2][0], acc[2][2])), n1 = pin(pack_bf16(acc[2][1], acc[2][3]));
        const uint32_t n2 = pin(TAGGED(acc[2][4], acc[2][6])), n3 = pin(pack_bf16(acc[2][5], acc[2][7]));
        if (__builtin_expect(!og, 0)) mwait(sb + BAR_OG, ph, spin);
        asm volatile("fence.proxy.async::generic.acquire.sync_restrict::shared::cluster.cluster;" ::: "memory");
        TS(i, 13);
        wg_fence();
        wo_block<2, 1>(acc[0], wf); wo_block<3, 2>(acc[0], wf);
        wg_commit();
        st_relaxed64(mkptr(m9, ehi), n0, n1);
        st_relaxed64(mkptr(m9, ehi) + 3072, n2, n3);
        if ((tid & 31) == 0) mbar_arrive_cluster(mapa(sb, 1) + BAR_E + 8);
        wo_block<5, 1>(acc[1], wf); wo_block<6, 2>(acc[1], wf);
        wg_commit();
        wo_block<7, 0>(acc[2], wf);
        wg_commit();
        wg_wait<2>(); SEND(0, 0);
        wo_block<8, 1>(acc[2], wf); wo_block<9, 2>(acc[2], wf);
        wg_commit();
        if (WOE == 0) { CBAR_ARRIVE(NB_WV, 256); CBAR_ARRIVE(NB_WQ, 256); }
        wg_wait<2>(); SEND(32 * 2048, 1);
        if (WOE == 1) CBAR_ARRIVE(NB_WV, 256);
        wg_wait<0>(); SEND(64 * 2048, 2);
        if (WOE == 2) CBAR_ARRIVE(NB_WV, 256);
        if (WOE >= 1) CBAR_ARRIVE(NB_WQ, 256);
#undef SEND
#undef TAGGED
      }
      TS(i, 14);
      if (i + 1 >= NSTEP) break;
    }
    uint32_t t1 = clk32();
    if (i >= 0) {
      const int lane = fresh(tid0) & 31, j = lane >> 3;
      const uint8_t* mb = mkptr(elo + (ph << 20) + (t9 ? MAIL9 + (cta - 72) * 12288 + wu * 3072 : (cta < 72 ? cta : cta - 24) * 8192 + wu * 2048) + lane * 16, ehi);
      const uint32_t tag = (i >> 1) & 1;
      const bool pub = (lane & (t9 ? 6 : 4)) == 0 && !(((t9 ? cta : wu) & 1) && i + 1 == LAG) && cta < 88;
      const uint32_t dst = pin(elo + EX_M + (i + 1) * 20480 + (t9 ? (cta + 72) * 128 + wu * 32 + (j & 1) * 16 + (lane & 1) * 8 + (j >> 1) * 4
                                                                   : cta * 256 + (wu & 1) * 128 + (wu >> 1) * 64 + j * 16 + (lane & 3) * 4));
      uint8_t* flag = mkptr(elo + EX_FLAG + (i + 1) * 3072 + cta * 32 + wu * 4, ehi);
      const int osig = OSG == 1 && tid0 == 96 ? CN_O + i * 5 + min(cta / 19, 4) : -1;
      if (OSG && wu == 3) CBAR_SYNC(NB_MR, 160);
      while (clk32() - t1 < B1) {}
      TS(i + 1, 30);
      float f[8];
      int n = 0;
      if (!t9) poll_add<4>(mb, tag, f, flag, lane == 0, osig, n, spin);
      else poll_add<6>(mb, tag, f, flag, lane == 0, osig, n, spin);
      if (FLP == 1 && lane == 0) st_relaxed(flag, __float_as_uint(f[0] + f[7]) >> 1);
      t1 = clk32();
      TS(i + 1, 31); TSV(i + 1, 32, n);
      const bool h = lane & 16, q = lane & 8;
#pragma unroll
      for (int j = 0; j < 4; j++) f[j] = (h ? f[4 + j] : f[j]) + __shfl_xor_sync(0xffffffffu, h ? f[j] : f[4 + j], 16);
#pragma unroll
      for (int j = 0; j < 2; j++) f[j] = (q ? f[2 + j] : f[j]) + __shfl_xor_sync(0xffffffffu, q ? f[j] : f[2 + j], 8);
      f[0] += __shfl_xor_sync(0xffffffffu, f[0], 4); f[1] += __shfl_xor_sync(0xffffffffu, f[1], 4);
      if (t9) { f[0] += __shfl_xor_sync(0xffffffffu, f[0], 2); f[1] += __shfl_xor_sync(0xffffffffu, f[1], 2); }
      if (pub) st_relaxed(mkptr(dst, ehi), pack_bf16(f[0], f[1]));
      if (FLP == 2 && lane == 0) st_relaxed(flag, 0);
      if (OSG == 2 && tid0 == 96) { TS1(i + 1, 38); signal_o(i, cta); TS1(i + 1, 39); }
      if (OSG == 4 && tid0 == 96) asm volatile("red.relaxed.gpu.global.add.u32 [%0],1;" ::"l"(&g_cnt[CN_O + i * 5 + min(cta / 19, 4)][0]) : "memory");
      TS(i + 1, 15);
    }
    if (wu == 0) {
      const int tid = fresh(tid0);
      const uint8_t* pp = mkptr(elo + EX_FLAG + (i + 1) * 3072 + (rank * 28 + (tid < 28 || rank == 2 ? tid : 0)) * 32, ehi);
      while (clk32() - t1 < B2) {}
      TS(i + 1, 16);
      int n = 1;
      uint4 x = ld_relaxed4(pp);
      if (tid0 == 0) mbar_expect_tx(sb + BAR_M, 20480);
      bool mok = mbar_test(sb + BAR_MOK, ph ^ 1);
      while (__any_sync(0xffffffffu, (int)(x.x | x.y | x.z | x.w) < 0 && spin < SPIN_TOT)) { x = ld_relaxed4(pp); mok = mbar_test(sb + BAR_MOK, ph ^ 1); n++; spin += 16; }
      if (!mok) mwait(sb + BAR_MOK, ph ^ 1, spin);
      TSV(i + 1, 35, n);
      TS(i + 1, 34);
      if (elect_one()) bulk_g2s_mc(sb + OFF_M + rank * 7168, mkptr(elo + EX_M + (i + 1) * 20480 + rank * 7168, ehi), rank == 2 ? 6144 : 7168, sb + BAR_M);
      TS(i + 1, 33);
      __syncwarp();
    }
  }
  if (spin >= SPIN_TOT) g_err = 1;
}

__global__ void __cluster_dims__(3, 1, 1) __launch_bounds__(384, 1)
k_chain(const __grid_constant__ CUtensorMap tmWq, const __grid_constant__ CUtensorMap tmWk,
        const __grid_constant__ CUtensorMap tmWv, const __grid_constant__ CUtensorMap tmWo) {
  using namespace C;
  extern __shared__ __align__(1024) uint8_t smem[];
  const uint32_t sb = smem_u32(smem);
  const int tid = threadIdx.x;
  const int wg = __shfl_sync(0xffffffffu, tid >> 7, 0);
  const int cta = uni(blockIdx.x), rank = uni(blockIdx.x % 3);

  asm volatile("griddepcontrol.launch_dependents;");
  if (tid == 0) {
    if ((sb & 0xFFFFFF) != SB0) g_err = 100;
    for (int p = 0; p < 5; p++) { mbar_init(sb + BAR_F + 8 * p, 1); mbar_init(sb + BAR_E + 8 * p, p == 2 ? 12 : 24); }
    mbar_init(sb + BAR_M, 1); mbar_init(sb + BAR_MOK, 24); mbar_init(sb + BAR_XM, 1); mbar_init(sb + BAR_XF, 2);
    mbar_init(sb + BAR_XT, 1); mbar_init(sb + BAR_MF, 8); mbar_init(sb + BAR_OG, 1); mbar_init(sb + BAR_W, 1);
    for (int p = 0; p < 5; p++) mbar_expect_tx(sb + BAR_F + 8 * p, 16384);
    for (int p = 0; p < 16; p++) sts32(sb + OFF_SAFE + 4 * p, 0);
    for (int p = 0; p < 32; p++) sts32(sb + OFF_ONE + 4 * p, 0x3F803F80);
    asm volatile("fence.mbarrier_init.release.cluster;" ::: "memory");
    fence_async();
    mbar_expect_tx(sb + BAR_W, 163840);
    const int head = cta / 3, col = head * DH + rank * 64;
    tma2d(sb + OFF_WQ, &tmWo, 576, col, sb + BAR_W);
    for (int i = 0; i < 9; i++) tma2d(sb + OFF_WQ + (i + 1) * 8192, &tmWo, (3 * rank + i / 3) * 64, head * DH + ((rank + i) % 3) * 64, sb + BAR_W);
    for (int i = 0; i < 5; i++) tma2d(sb + OFF_WK + i * 16384, &tmWv, col, i * 128, sb + BAR_W);
  }
  __syncthreads();
  asm volatile("barrier.cluster.arrive.release.aligned;" ::: "memory");
  asm volatile("barrier.cluster.wait.acquire.aligned;" ::: "memory");

  if (wg == 0) chain_a(sb, keep(tid), cta, rank);
  else if (wg == 1) chain_q(tmWq, tmWk, sb, keep(tid), cta, rank);
  else chain_v(sb, keep(tid), cta, rank);
  asm volatile("barrier.cluster.arrive.release.aligned;" ::: "memory");
  asm volatile("barrier.cluster.wait.acquire.aligned;" ::: "memory");
}

namespace W {
constexpr int NP = 25, NBC = 11, NW = NP + NBC;
constexpr int PRS = 37, PW = 43 * 2048;
constexpr int OFF_W = 0;
constexpr int OFF_R = 2 * PW;
constexpr int QRS = 35, KRS = 37;
constexpr int OFF_WV = 0, OFF_YQ = 81920, OFF_YK = OFF_YQ + (40 - QRS) * 2048, OFF_WO = OFF_YK + (40 - KRS) * 2048;
constexpr int OFF_G = OFF_WO + 39 * 2048;
constexpr int OFF_X = OFF_G + 12288;
constexpr int COL = 976;
constexpr int OFF_T = OFF_X + 8192;
constexpr int OFF_H = OFF_X + 32768;
constexpr int OFF_BAR = OFF_H + 8 * COL;
constexpr int OFF_SAFE = OFF_BAR + 192;
constexpr int SMEM = 232448;
static_assert(OFF_SAFE + 64 <= SMEM && OFF_R + 40960 <= OFF_BAR, "");
constexpr uint32_t SB0 = 1024;
constexpr int BAR_F = OFF_BAR, BAR_E = OFF_BAR + 40, BAR_G = OFF_BAR + 80, BAR_H = OFF_BAR + 120, BAR_W = OFF_BAR + 160;
constexpr int NB_G0 = 1, NB_SG = 4, NB_B = 5, NB_AS = 6, NB_PK = 8, NB_PV = 9, NB_TD = 10;
}
#define PFW 1
#define WOP 0
#define WBAR_SYNC(id, n) bar_sync(id, n)
#define WBAR_ARRIVE(id, n) bar_arrive(id, n)

__device__ __forceinline__ uint64_t rdesc(int off, int kk) { return mkdesc(W::SB0 + off + kk * 32, 16, 1024); }
__device__ __forceinline__ uint32_t frag_addr(uint32_t base, int tid) {
  const int i = (tid >> 3) & 3, r = tid & 7;
  return base + (r + (i >> 1) * 8) * 128 + (((2 * ((tid >> 5) & 3) + (i & 1)) ^ r) << 4);
}
template <int NK>
__device__ __forceinline__ void load_frags(uint32_t (&wf)[NK][4], uint32_t base, int tid) {
  const uint32_t a0 = frag_addr(base, tid);
#pragma unroll
  for (int k = 0; k < NK; k++) ldsm4t(wf[k], a0 + k * 2048);
}
__device__ __forceinline__ void red_tile(const float* d, int seg, int col0, int tid) {
  float* p = g_x + (size_t)(seg * 32 + 2 * (tid & 3)) * DM + col0 + ((tid >> 5) & 3) * 16 + ((tid >> 2) & 7) * 2;
#pragma unroll
  for (int j = 0; j < 8; j++)
    asm volatile("red.relaxed.gpu.global.add.v2.f32 [%0],{%1,%2};" ::"l"(p + ((j >> 1) * 8 + (j & 1)) * DM), "f"(d[4 * (j >> 1) + (j & 1)]), "f"(d[4 * (j >> 1) + 2 + (j & 1)]) : "memory");
}
#define FOR_SEGS(l, s)                                            \
  for (int j_ = 0; j_ < 2 * NSTEP; j_++) {                        \
    const int l = j_ & 1, s = (j_ >> 1) - l * LAG;                \
    if (s < 0 || s >= NSEG) continue;

template <int WG>
__device__ __forceinline__ void work_p(const CUtensorMap& tmWo, uint32_t sb, int pc, int tid0) {
  using namespace W;
  asm volatile("setmaxnreg.inc.sync.aligned.u32 208;");
  int spin = 0;
  const int ks = pc / 5, col0 = (pc % 5) * 128 + WG * 64;
  const uint32_t wb = sb + OFF_W + WG * PW;
  uint32_t wf[PRS][4];
#pragma unroll 1
  for (int hf = 0; hf < 2; hf++) {
    const int nk = hf ? 80 - PRS : PRS;
    if ((tid0 & 127) == 0) {
      mbar_expect_tx(sb + BAR_W + 8 * WG, nk * 2048);
      for (int i = 0; i < nk; i++) tma2d(wb + i * 2048, &tmWo, col0, ks * 19 * 64 + (i < PRS ? 2 * i + hf : PRS + i) * 16, sb + BAR_W + 8 * WG);
    }
    __syncwarp();
    mwait(sb + BAR_W + 8 * WG, hf, spin);
    permute_cols(wb, tid0 & 127, nk * 64);
    if (hf == 1 && ks < 4) for (int it = 39 * 64 + (tid0 & 127) - 64; it < 43 * 64; it += 128) {
      const uint32_t a = wb + (it >> 2) * 128 + (((2 * (it & 3)) ^ ((it >> 2) & 6)) << 4);
      if (it >= 39 * 64) { sts128(a, make_uint4(0, 0, 0, 0)); sts128(a + 16, make_uint4(0, 0, 0, 0)); }
    }
    fence_async();
    WBAR_SYNC(NB_G0 + WG, 128);
    if (hf == 0) {
      load_frags<PRS>(wf, wb, tid0);
      fence_async();
      WBAR_SYNC(NB_G0 + WG, 128);
    }
  }
#pragma unroll 1
  for (int k = 0; k < NSTEP; k++) {
    float d[32];
#pragma unroll
    for (int f = 0; f < 20; f++) {
      mwait(sb + BAR_F + 8 * (f % 5), (f / 5) & 1, spin);
      if (f == 0 && WG == 0 && pc == WW) WTS(k, 1);
      wg_fence();
#pragma unroll
      for (int kk = 0; kk < 4; kk++) {
        const int q = 4 * f + kk;
        if (q < 2 * PRS && !(q & 1)) wgmma_rs64(d, wf[q < 2 * PRS ? q >> 1 : 0], rdesc(OFF_R + (f % 5) * 8192, kk), q);
        else wgmma_ts64(d, mkdesc(SB0 + OFF_W + WG * PW + (q < 2 * PRS ? q >> 1 : q - PRS) * 2048, 8192, 1024), rdesc(OFF_R + (f % 5) * 8192, kk), 1);
        if (kk == 0 && f > 0) {
          wg_commit();
          wg_wait<1>();
          if ((tid0 & 31) == 0) mbar_arrive(sb + BAR_E + 8 * ((f - 1) % 5));
        }
      }
      wg_commit();
    }
    wg_wait<0>();
    if ((tid0 & 31) == 0) mbar_arrive(sb + BAR_E + 32);
    if (WG == 0 && pc == WW) WTS(k, 2);
    if (k < NSEG) red_tile(d, k, col0, tid0);
    if (k >= LAG) red_tile(d + 16, k - LAG, col0, tid0);
    if (WG == 0 && pc == WW) WTS(k, 13);
    WBAR_SYNC(NB_SG, 256);
    if (WG == 0) { if (tid0 == 0) csignal_t(CN_P + k, 3); __syncwarp(); }
  }
  if (spin >= SPIN_TOT) g_err = 11;
}
__device__ __forceinline__ void work_p_producer(uint32_t sb, int pc, int odd) {
  using namespace W;
  int spin = 0;
  const int ks = pc / 5;
#pragma unroll 1
  for (int k = 0; k < NSTEP; k++) {
    const uint32_t lo = k < NSEG ? 0 : 4096, len = k < LAG || k >= NSEG ? 4096 : 8192;
    const uint8_t* src = &g_o[k % ORING][ks * 19 + odd][lo];
    cwait(CN_O + k * 5 + ks, ks == 4 ? 20 : 19, spin);
    fence_async_all();
    if (pc == WW && !odd) WTS1(k, 0);
#pragma unroll
    for (int u = 0; u < 10; u++) {
      const int st = odd ? (2 * u + 1) % 5 : (2 * u) % 5, ph = odd ? ((2 * u + 1) / 5) & 1 : ((2 * u) / 5) & 1;
      mwait(sb + BAR_E + 8 * st, ph ^ 1, spin);
      if (u == 9 && odd && ks < 4) mbar_arrive(sb + BAR_F + 8 * st);
      else {
        mbar_expect_tx(sb + BAR_F + 8 * st, len);
        bulk_g2s(sb + OFF_R + st * 8192 + lo, src + u * 16384, len, sb + BAR_F + 8 * st);
      }
    }
  }
  if (spin >= SPIN_TOT) g_err = 12;
}
__device__ __forceinline__ float warp_sum(float x) {
  x = quad_sum(x);
  const float a = __shfl_xor_sync(0xffffffffu, x, 4), b = __shfl_xor_sync(0xffffffffu, x, 8), c = __shfl_xor_sync(0xffffffffu, x, 12);
  x = (x + a) + (b + c);
  return x + __shfl_xor_sync(0xffffffffu, x, 16);
}
__device__ __forceinline__ void work_ln(int kind, int r, int lane, bf16* out) {
  int spin = 0;
  const int l = kind & 1;
  const int rp = kind < 2 ? (r & 1) * 16 + (r >> 1) : r;
  const uint32_t sw = ((((lane >> 1) & 7) ^ (rp & 7)) << 4) + (lane & 1) * 8;
  uint8_t* dst = kind < 2 ? g_xnb[l * LAG] + (lane >> 4) * 8192 + l * 4096 + rp * 128 + sw
               : kind == 2 ? g_xn[LAG] + (r >> 3) * 4096 + 2048 + (lane >> 4) * 1024 + (r & 7) * 128 + sw
                           : reinterpret_cast<uint8_t*>(out) + r * 1280 + lane * 8;
  const int dm = kind < 3 ? 16384 : 256, ds = kind < 3 ? 81920 : 40960;
#pragma unroll 1
  for (int s = 0; s < NSEG; s++) {
    const float* xr = g_x + (size_t)(s * 32 + r) * DM;
    if (lane == 0) cwait(kind < 2 ? CN_P + s + l * LAG : CN_W + l * 64 + s, kind < 2 ? W::NP : 10, spin);
    __syncwarp();
    if (r == 0 && lane == 0 && (l == 0 || s + LAG >= NSEG)) WTS1(s + l * LAG, kind < 2 ? 3 : 11);
    float4 v[5];
#pragma unroll
    for (int m = 0; m < 5; m++) v[m] = ld_relaxed4f(xr + m * 128 + lane * 4);
    if (kind < 3) {
      float t = 0.f;
#pragma unroll
      for (int m = 0; m < 5; m++) t += (v[m].x + v[m].y) + (v[m].z + v[m].w);
      const float mean = warp_sum(t) * (1.f / DM);
      float q0 = 0.f, q1 = 0.f;
#pragma unroll
      for (int m = 0; m < 5; m++) {
        v[m].x -= mean; v[m].y -= mean; v[m].z -= mean; v[m].w -= mean;
        q0 += v[m].x * v[m].x + v[m].y * v[m].y; q1 += v[m].z * v[m].z + v[m].w * v[m].w;
      }
      const float rs = rsqrtf(warp_sum(q0 + q1) * (1.f / DM) + 1e-5f);
#pragma unroll
      for (int m = 0; m < 5; m++) { v[m].x *= rs; v[m].y *= rs; v[m].z *= rs; v[m].w *= rs; }
    }
#pragma unroll
    for (int m = 0; m < 5; m++) *reinterpret_cast<uint2*>(dst + (size_t)s * ds + m * dm) = make_uint2(pack_bf16(v[m].x, v[m].y), pack_bf16(v[m].z, v[m].w));
    __syncwarp();
    if (r == 0 && lane == 0 && (l == 0 || s + LAG >= NSEG)) WTS1(s + l * LAG, kind < 2 ? 4 : 12);
    if (lane == 0 && kind < 3) csignal_t(kind < 2 ? CN_L + s + l * LAG : CN_X + s, kind);
  }
  if (spin >= SPIN_TOT) g_err = 13;
}

__device__ __forceinline__ void work_prefetch(int t) {
  int spin = 0;
#pragma unroll 1
  for (int k = 0; k + 4 < NSTEP; k++) {
    if ((t & 31) == 0) cwait(CN_O + k * 5, 1, spin);
    __syncwarp();
    if (k + 2 < NSEG) { prefetch_l2(g_x + (size_t)(k + 2) * 32 * DM + t * 64); prefetch_l2(g_x + (size_t)(k + 2) * 32 * DM + t * 64 + 32); }
    prefetch_l2(g_xn[k + 4] + (t >> 4) * 4096 + (t & 15) * 128);
    if (t < 184) prefetch_l2(ex_window(g_ex) + (t < 160 ? EX_M + (k + 4) * 20480 + t * 128 : EX_FLAG + (k + 4) * 3072 + (t - 160) * 128));
  }
}

__device__ __forceinline__ void stage_qkv(const bf16* wqkv, uint32_t base, int T, int bc, int tid) {
  const int q = tid & 15;
  const bool ok = q < 15 && bc * 60 + 4 * q < DM;
  const bf16* src = wqkv + T * DM + bc * 60 + 4 * q;
#pragma unroll 1
  for (int k0 = tid >> 4; k0 < 640; k0 += 80) {
    uint2 v[10];
#pragma unroll
    for (int u = 0; u < 10; u++) v[u] = ok ? *reinterpret_cast<const uint2*>(src + (size_t)(k0 + 8 * u) * 1920) : make_uint2(0, 0);
#pragma unroll
    for (int u = 0; u < 10; u++) sts64(base + (k0 + 8 * u) * 128 + (((q >> 1) ^ (k0 & 7)) << 4) + (q & 1) * 8, v[u].x, v[u].y);
  }
}
__device__ __forceinline__ void attend(uint32_t sb, int bc, int l, int s, int p, int tid) {
  using namespace W;
  const int r = tid & 7, m = (tid >> 3) & 3, hh = (tid >> 5) & 3, g = (tid >> 2) & 7, t = tid & 3;
  const int f2 = r < 4 ? 20 * hh + 16 + r : 60;
  const uint32_t tb = sb + OFF_T + (l * 4 + 2 * p) * COL, hb = sb + OFF_H + (l * 2 + p) * COL;
  const uint32_t ko = (m < 2 ? 20 * hh + 8 * m + r : f2) * 16, vo = (m < 2 ? 20 * hh + 4 * (r >> 1) + 2 * m + (r & 1) : f2) * 16;
  const float scl = 0.22360679774997896f * 1.4426950408889634f;
  float sc[3][4];
  {
    uint32_t q[4], q8a, q8b, k[3][4];
    ldsm4t(q, tb + (m & 1) * COL + (20 * hh + (m >> 1) * 8 + r) * 16);
    ldsm2t(q8a, q8b, tb + (m & 1) * COL + f2 * 16);
    ldsm4t(k[0], hb + ko); ldsm4t(k[1], tb + 8 * COL + ko); ldsm4t(k[2], tb + 9 * COL + ko);
#pragma unroll
    for (int c = 0; c < 3; c++) { sc[c][0] = sc[c][1] = sc[c][2] = sc[c][3] = 0.f; mma16816(sc[c], q[0], q[1], q[2], q[3], k[c][0], k[c][1]); }
#pragma unroll
    for (int c = 0; c < 3; c++) mma1688(sc[c], q8a, q8b, k[c][2]);
  }
  uint32_t v[3][4];
  ldsm4(v[0], hb + 4 * COL + vo); ldsm4(v[1], tb + 16 * COL + vo); ldsm4(v[2], tb + 17 * COL + vo);
  const bool lo0 = 2 * t > g, lo1 = 2 * t + 1 > g;
  uint32_t pw[2];
  float inv[2];
#pragma unroll
  for (int h = 0; h < 2; h++) {
    float y0 = lo0 ? sc[h][2 * h] : sc[h + 1][2 * h], y1 = lo1 ? sc[h][2 * h + 1] : sc[h + 1][2 * h + 1];
    if (h == 0 && s == 0) { y0 = lo0 ? -INFINITY : y0; y1 = lo1 ? -INFINITY : y1; }
    const float mx = quad_max(fmaxf(y0, y1)) * -scl;
    pw[h] = pack_bf16(ex2(fmaf(y0, scl, mx)), ex2(fmaf(y1, scl, mx)));
    inv[h] = bf_lo(pw[h]) + bf_hi(pw[h]);
  }
  const uint32_t ml = (lo0 ? 0xFFFFu : 0u) | (lo1 ? 0xFFFF0000u : 0u);
  float o[3][4];
#pragma unroll
  for (int j = 0; j < 3; j++) { o[j][0] = o[j][1] = o[j][2] = o[j][3] = 0.f; mma16816(o[j], pw[0] & ml, 0u, pw[0] & ~ml, pw[1] & ml, v[0][j], v[1][j]); }
#pragma unroll
  for (int j = 0; j < 3; j++) mma1688(o[j], 0u, pw[1] & ~ml, v[2][j]);
  inv[0] = rcp(quad_sum(inv[0])); inv[1] = rcp(quad_sum(inv[1]));
  const uint32_t ca = (bc * 3 + hh) * 20 + 4 * t, cb = ca + 16 - 2 * t, row = 2 * g + p;
  uint8_t* img = g_ob[l] + (size_t)s * 40960 + row * 128;
  const uint32_t oa = (ca >> 6) * 4096 + (((ca >> 3) ^ row) & 7) * 16 + (ca & 4) * 2, ob = (cb >> 6) * 4096 + (((cb >> 3) ^ row) & 7) * 16 + (cb & 6) * 2;
#pragma unroll
  for (int h = 0; h < 2; h++) {
    *reinterpret_cast<uint2*>(img + oa + h * 2048) = make_uint2(pack_bf16(o[0][2 * h] * inv[h], o[0][2 * h + 1] * inv[h]), pack_bf16(o[1][2 * h] * inv[h], o[1][2 * h + 1] * inv[h]));
    if (t < 2) *reinterpret_cast<uint32_t*>(img + ob + h * 2048) = pack_bf16(o[2][2 * h] * inv[h], o[2][2 * h + 1] * inv[h]);
  }
}
template <int WG>
__device__ __forceinline__ void work_b(const bf16* wqkv, uint32_t sb, int bc, int tid0) {
  using namespace W;
  if (WG == 0) asm volatile("setmaxnreg.inc.sync.aligned.u32 232;");
  else asm volatile("setmaxnreg.inc.sync.aligned.u32 208;");
  constexpr int NR = WG ? KRS : QRS, OFF_Y = WG ? OFF_YK : OFF_YQ;
  int spin = 0;
  const uint32_t wb = sb + (WG ? OFF_WO : OFF_WV);
  uint32_t wf[NR][4];
  stage_qkv(wqkv, wb, WG, bc, tid0 & 127);
  WBAR_SYNC(NB_G0 + WG, 128);
  load_frags<NR>(wf, wb, tid0);
#pragma unroll
  for (int k = NR; k < 40; k++) sts128(sb + OFF_Y + (k - NR) * 2048 + (tid0 & 127) * 16, lds128(wb + k * 2048 + (tid0 & 127) * 16));
  fence_async();
  if (WG == 1) WBAR_ARRIVE(NB_PK, 256);
  WBAR_SYNC(NB_G0 + WG, 128);
  if (WG == 0) {
    stage_qkv(wqkv, wb, 2, bc, tid0);
    fence_async();
    WBAR_SYNC(NB_G0, 128);
  }
#pragma unroll 1
  for (int k = 0; k < NSTEP; k++) {
    uint32_t hist[8];
    {
      float d[32], e[32];
#pragma unroll
      for (int c = 0; c < 10; c++) {
        mwait(sb + BAR_F + 8 * (c % 4), ((c % 4 < 2 ? k : 0) + c / 4) & 1, spin);
        if (c == 0 && bc == 0) WTS(k, WG ? 15 : 6);
        wg_fence();
#pragma unroll
        for (int kk = 0; kk < 4; kk++) {
          const int q = 4 * c + kk;
          const uint64_t db = rdesc(OFF_X + (c % 4) * 8192, kk);
          if (q < NR) wgmma_rs64(d, wf[q < NR ? q : 0], db, q);
          else wgmma_ts64(d, mkdesc(SB0 + OFF_Y + (q - NR) * 2048, 8192, 1024), db, 1);
          if (WG == 0) wgmma_ts64(e, mkdesc(SB0 + OFF_WV + q * 2048, 8192, 1024), db, q);
          if (kk == 0 && c > 0 && (c <= 6 || c == 9)) {
            wg_commit();
            wg_wait<1>();
            if ((tid0 & 31) == 0) mbar_arrive(sb + BAR_E + 8 * ((c - 1) % 4));
          }
        }
        wg_commit();
      }
      wg_wait<0>();
      if (bc == 0) WTS(k, 16 + WG);
      WBAR_SYNC(NB_B, 256);
      const int tid = fresh(tid0), m = (tid >> 3) & 3;
      const uint32_t a = sb + OFF_T + min(((tid >> 5) & 3) * 16 + (m & 1) * 8 + (tid & 7), 60) * 16 + (m >> 1) * COL;
      const float (&x)[32] = WG ? d : e;
#pragma unroll
      for (int p = 0; p < 4; p++) {
        hist[2 * p] = pack_bf16(x[8 * p + 4], x[8 * p + 5]); hist[2 * p + 1] = pack_bf16(x[8 * p + 6], x[8 * p + 7]);
        stsm4(a + (16 - 8 * WG + 2 * p) * COL, pack_bf16(x[8 * p], x[8 * p + 1]), pack_bf16(x[8 * p + 2], x[8 * p + 3]), hist[2 * p], hist[2 * p + 1]);
        if (WG == 0)
          stsm4(a + 2 * p * COL, pack_bf16(d[8 * p], d[8 * p + 1]), pack_bf16(d[8 * p + 2], d[8 * p + 3]), pack_bf16(d[8 * p + 4], d[8 * p + 5]), pack_bf16(d[8 * p + 6], d[8 * p + 7]));
      }
    }
    WBAR_SYNC(NB_TD, 288);
    if (bc == 0 && WG == 0) WTS(k, 7);
#pragma unroll 1
    for (int l = 0; l < 2; l++) {
      const int tid = fresh(tid0), hh = uni((tid >> 5) & 3), s = k - l * LAG;
      if (hh < 3 && bc * 3 + hh < NH && s >= 0 && s < NSEG) attend(sb, bc, l, s, WG, tid);
      if (bc == 0 && WG == 0) WTS(k, l == 0 || k >= NSEG ? 8 : 25);
      if (l == 0) WBAR_ARRIVE(NB_AS, 288); else WBAR_ARRIVE(NB_AS + 1, 288);
    }
    WBAR_SYNC(NB_B, 256);
    {
      const int tid = fresh(tid0), m = (tid >> 3) & 3;
      const uint32_t a = sb + OFF_H + min(((tid >> 5) & 3) * 16 + (m & 1) * 8 + (tid & 7), 60) * 16 + (4 - 4 * WG + (m >> 1)) * COL;
      stsm4(a, hist[0], hist[1], hist[2], hist[3]);
      if (k >= LAG) stsm4(a + 2 * COL, hist[4], hist[5], hist[6], hist[7]);
      fence_async();
      if ((tid & 31) < 3) mbar_arrive(sb + BAR_E + 8 + 8 * (tid & 3));
    }
  }
  if (spin >= SPIN_TOT) g_err = 14;
}
__device__ __forceinline__ void work_wo(const CUtensorMap& tmBo, uint32_t sb, int bc, int tid0) {
  using namespace W;
  int spin = 0;
  WBAR_SYNC(NB_PK, 256);
  if (bc == 10) return;
  if ((tid0 & 127) == 0) {
    mbar_expect_tx(sb + BAR_W, 81920);
    for (int i = 0; i < 10; i++) tma2d(sb + OFF_WO + i * 8192, &tmBo, bc * 64, i * 64, sb + BAR_W);
  }
  __syncwarp();
  mwait(sb + BAR_W, 0, spin);
  permute_cols(sb + OFF_WO, tid0 & 127, 2560);
  WBAR_SYNC(NB_G0 + 2, 128);
  uint32_t wl[4];
  ldsm4t(wl, frag_addr(sb + OFF_WO + 39 * 2048, tid0));
  fence_async();
  WBAR_SYNC(NB_PV, 160);
  uint32_t n = 0;
  FOR_SEGS(l, s)
    float d[16];
#pragma unroll
    for (int c = 0; c < 10; c++) {
      mwait(sb + BAR_G + 8 * (c % 3), ((c % 3 ? n : 0) + c / 3) & 1, spin);
      if (c == 0 && bc == 0) WTS(s + l * LAG, l == 0 || s + LAG >= NSEG ? 20 : 23);
      wg_fence();
#pragma unroll
      for (int kk = 0; kk < 4; kk++) {
        if (c == 9 && kk == 3) wgmma_rs32(d, wl, rdesc(OFF_G + (c % 3) * 4096, kk), 1);
        else wgmma_ts32(d, mkdesc(SB0 + OFF_WO + (4 * c + kk) * 2048, 8192, 1024), rdesc(OFF_G + (c % 3) * 4096, kk), c | kk);
      }
      wg_commit();
      if (c == 9 || !WOP) wg_wait<0>();
      else if (c > 0) wg_wait<1>();
      if ((tid0 & 31) == 0) {
        if (WOP && c > 0) mbar_arrive(sb + BAR_H + 8 * ((c - 1) % 3));
        if (c == 9 || !WOP) mbar_arrive(sb + BAR_H + 8 * (c % 3));
      }
    }
    if (bc == 0) WTS(s + l * LAG, l == 0 || s + LAG >= NSEG ? 10 : 24);
    red_tile(d, s, bc * 64, tid0);
    WBAR_SYNC(NB_SG, 160);
    n++;
  }
  if (spin >= SPIN_TOT) g_err = 17;
}
__device__ __forceinline__ void work_x_producer(uint32_t sb, int bc) {
  using namespace W;
  int spin = 0;
#pragma unroll 1
  for (int k = 0; k < NSTEP; k++) {
    const uint32_t lo = k < NSEG ? 0 : 4096, len = k < LAG || k >= NSEG ? 4096 : 8192;
    const uint8_t* src = g_xnb[k] + lo;
    cwait(CN_L + k, len >> 7, spin);
    fence_async_all();
    if (bc == 0) WTS1(k, 5);
#pragma unroll
    for (int c = 0; c < 10; c++) {
      mwait(sb + BAR_E + 8 * (c % 4), (((c % 4 < 2 ? k : 0) + c / 4) & 1) ^ 1, spin);
      mbar_expect_tx(sb + BAR_F + 8 * (c % 4), len);
      bulk_g2s(sb + OFF_X + (c % 4) * 8192 + lo, src + c * 8192, len, sb + BAR_F + 8 * (c % 4));
    }
  }
  if (spin >= SPIN_TOT) g_err = 15;
}
__device__ __forceinline__ void work_g_producer(uint32_t sb, int bc) {
  using namespace W;
  int spin = 0;
  uint32_t n = 0;
  FOR_SEGS(l, s)
    const uint8_t* src = g_ob[l] + (size_t)s * 40960;
    cwait(CN_A + l * 64 + s, NBC, spin);
    fence_async_all();
    if (bc == 0) WTS1(s + l * LAG, l == 0 || s + LAG >= NSEG ? 9 : 22);
#pragma unroll
    for (int c = 0; c < 10; c++) {
      mwait(sb + BAR_H + 8 * (c % 3), (((c % 3 ? n : 0) + c / 3) & 1) ^ 1, spin);
      mbar_expect_tx(sb + BAR_G + 8 * (c % 3), 4096);
      bulk_g2s(sb + OFF_G + (c % 3) * 4096, src + c * 4096, 4096, sb + BAR_G + 8 * (c % 3));
    }
    n++;
  }
  if (spin >= SPIN_TOT) g_err = 16;
}

__global__ void __launch_bounds__(512, 1)
k_work(const __grid_constant__ CUtensorMap tmWo, const __grid_constant__ CUtensorMap tmBo, const bf16* __restrict__ wqkv, bf16* __restrict__ out) {
  using namespace W;
  extern __shared__ __align__(1024) uint8_t smem[];
  const uint32_t sb = smem_u32(smem);
  const int tid = threadIdx.x, w = blockIdx.x;
  const int wg = __shfl_sync(0xffffffffu, tid >> 7, 0);
  if (tid == 0) {
    if (sb != SB0) g_err = 101;
    for (int i = 0; i < 5; i++) { mbar_init(sb + BAR_F + 8 * i, 1); mbar_init(sb + BAR_E + 8 * i, 8); mbar_init(sb + BAR_G + 8 * i, 1); mbar_init(sb + BAR_H + 8 * i, 4); }
    mbar_init(sb + BAR_W, 1); mbar_init(sb + BAR_W + 8, 1);
    for (int p = 0; p < 16; p++) sts32(sb + OFF_SAFE + 4 * p, 0);
    asm volatile("fence.mbarrier_init.release.cluster;" ::: "memory");
  }
  if (tid < 8 * COL / 16) sts128(sb + OFF_H + tid * 16, make_uint4(0, 0, 0, 0));
  fence_async();
  __syncthreads();

  if (w < NP) {
    if (wg == 0) work_p<0>(tmWo, sb, w, keep(tid));
    else if (wg == 1) work_p<1>(tmWo, sb, w, keep(tid));
    else {
      asm volatile("setmaxnreg.dec.sync.aligned.u32 48;");
      const int aw = (tid >> 5) - 8;
      if (aw < 2) {
        if ((tid & 31) == 0) work_p_producer(sb, w, aw);
      } else {
        const int id = (aw - 2) * NP + w;
        if (id < 128) work_ln(id & 3, id >> 2, tid & 31, out);
        else if (PFW && id < 138) work_prefetch((id - 128) * 32 + (tid & 31));
      }
    }
  } else {
    const int bc = w - NP;
    if (wg == 0) work_b<0>(wqkv, sb, bc, keep(tid));
    else if (wg == 1) work_b<1>(wqkv, sb, bc, keep(tid));
    else if (wg == 2) {
      asm volatile("setmaxnreg.dec.sync.aligned.u32 48;");
      work_wo(tmBo, sb, bc, keep(tid));
    } else {
      asm volatile("setmaxnreg.dec.sync.aligned.u32 24;");
      if (tid < 416) {
        if (tid == 384) work_x_producer(sb, bc);
      } else if (tid < 448) {
        if (bc < 10) {
          WBAR_SYNC(NB_PV, 160);
          if (tid == 416) work_g_producer(sb, bc);
        }
      } else if (tid < 480) {
        for (int k = 0; k < NSTEP; k++) {
          WBAR_SYNC(NB_TD, 288);
          WBAR_SYNC(NB_AS, 288);
          if (tid == 448 && k < NSEG) csignal_t(CN_A + k, 5);
          __syncwarp();
          WBAR_SYNC(NB_AS + 1, 288);
          if (tid == 448 && k >= LAG) csignal_t(CN_A + 64 + k - LAG, 4);
          __syncwarp();
        }
      } else if (bc < 10) {
        FOR_SEGS(l, s)
          WBAR_SYNC(NB_SG, 160);
          if (tid == 480) csignal_t(CN_W + l * 64 + s, 6);
          __syncwarp();
        }
      }
    }
  }
  __syncthreads();
  asm volatile("griddepcontrol.wait;" ::: "memory");
}

typedef CUresult (*EncodeFn)(CUtensorMap*, CUtensorMapDataType, cuuint32_t, void*, const cuuint64_t*, const cuuint64_t*,
                             const cuuint32_t*, const cuuint32_t*, CUtensorMapInterleave, CUtensorMapSwizzle,
                             CUtensorMapL2promotion, CUtensorMapFloatOOBfill);

static void make_map(EncodeFn enc, CUtensorMap* tm, const void* ptr, uint64_t cols, uint64_t rows, uint32_t boxc, uint32_t boxr) {
  cuuint64_t dims[2] = {cols, rows};
  cuuint64_t strides[1] = {cols * 2};
  cuuint32_t box[2] = {boxc, boxr};
  cuuint32_t es[2] = {1, 1};
  enc(tm, CU_TENSOR_MAP_DATA_TYPE_BFLOAT16, 2, const_cast<void*>(ptr), dims, strides, box, es, CU_TENSOR_MAP_INTERLEAVE_NONE,
      CU_TENSOR_MAP_SWIZZLE_128B, CU_TENSOR_MAP_L2_PROMOTION_L2_256B, CU_TENSOR_MAP_FLOAT_OOB_FILL_NONE);
}

extern "C" void kernel_launch(void* const* d_in, const int* in_sizes, int n_in, void* d_out, int out_size) {
  const bf16* x0 = (const bf16*)d_in[0];
  const bf16* mem0 = (const bf16*)d_in[1];
  const bf16* Wq = (const bf16*)d_in[2];
  const bf16* Wk = (const bf16*)d_in[3];
  const bf16* Wv = (const bf16*)d_in[4];
  const bf16* Wo = (const bf16*)d_in[5];
  const bf16* Bqkv = (const bf16*)d_in[8];
  const bf16* Bwo = (const bf16*)d_in[9];
  bf16* out = (bf16*)d_out;

  static EncodeFn enc = nullptr;
  if (!enc) {
    void* fn = nullptr;
    cudaDriverEntryPointQueryResult qr;
    cudaGetDriverEntryPoint("cuTensorMapEncodeTiled", &fn, cudaEnableDefault, &qr);
    enc = (EncodeFn)fn;
    cudaFuncSetAttribute(k_chain, cudaFuncAttributeMaxDynamicSharedMemorySize, C::SMEM);
    cudaFuncSetAttribute(k_work, cudaFuncAttributeMaxDynamicSharedMemorySize, W::SMEM);
  }
  CUtensorMap tmWq, tmWk, tmWv, tmWo, tmWp, tmBo;
  make_map(enc, &tmWq, Wq, NH * DH, DM, 64, 128);
  make_map(enc, &tmWk, Wk, NH * DH, DM, 64, 128);
  make_map(enc, &tmWv, Wv, NH * DH, DM, 64, 128);
  make_map(enc, &tmWo, Wo, DM, NH * DH, 64, 64);
  make_map(enc, &tmWp, Wo, DM, NH * DH, 64, 16);
  make_map(enc, &tmBo, Bwo, DM, DM, 64, 64);

  cudaStream_t st = cudaStreamPerThread;
  k_pre<<<256, 256, 0, st>>>(x0, mem0);
  cudaLaunchAttribute at[1];
  at[0].id = cudaLaunchAttributeProgrammaticStreamSerialization; at[0].val.programmaticStreamSerializationAllowed = 1;
  {
    cudaLaunchConfig_t cfg = {};
    cfg.gridDim = dim3(96); cfg.blockDim = dim3(384); cfg.dynamicSmemBytes = C::SMEM; cfg.stream = st;
    cfg.attrs = at; cfg.numAttrs = 0;
    cudaLaunchKernelEx(&cfg, k_chain, tmWq, tmWk, tmWv, tmWo);
  }
  cudaLaunchConfig_t cfg = {};
  cfg.gridDim = dim3(W::NW); cfg.blockDim = dim3(512); cfg.dynamicSmemBytes = W::SMEM; cfg.stream = st;
  cfg.attrs = at; cfg.numAttrs = NOWORK == 2 ? 0 : 1;
  cudaLaunchKernelEx(&cfg, k_work, tmWp, tmBo, Bqkv, out);
}
```

```cpp
#include <cuda_runtime.h>
#include <cuda_bf16.h>
#include <cuda.h>
#include <stdint.h>

typedef __nv_bfloat16 bf16;

constexpr int SEQ = 2048, DM = 640, NH = 32, DH = 192, NSEG = 64;
#define LAG 7
constexpr int NSTEP = NSEG + LAG;
constexpr uint32_t SENT = 0xFFFFFFFFu;

constexpr int MAIL9 = 288 * 2048, MAIL_BYTES = MAIL9 + 64 * 3072;
__device__ __align__(1024) uint8_t g_xn[NSTEP][81920];
__device__ __align__(1024) uint8_t g_xnb[NSTEP][81920];
__device__ __align__(1024) uint8_t g_ob[2][NSEG * 40960];
#define ORING 8
static_assert(ORING > LAG, "a slot is free again LAG + 1 steps later");
__device__ __align__(1024) uint8_t g_o[ORING][96][8192];
__device__ __align__(1024) float g_x[SEQ * DM];
constexpr int EX_MAIL = 0;
constexpr int EX_M = 2 << 20;
constexpr int EX_FLAG = EX_M + NSTEP * 20480;
static_assert(EX_FLAG + NSTEP * 3072 <= (4 << 20), "");
__device__ __align__(1024) uint8_t g_ex[8 << 20];
__host__ __device__ __forceinline__ uint8_t* ex_window(uint8_t* p) { return reinterpret_cast<uint8_t*>((reinterpret_cast<uint64_t>(p) + (4 << 20) - 1) & ~(uint64_t)((4 << 20) - 1)); }
enum { CN_P = 0, CN_L = 128, CN_A = 256, CN_W = 384, CN_X = 512, CN_O = 576, CN_NUM = CN_O + 5 * NSTEP };
__device__ __align__(128) uint32_t g_cnt[CN_NUM][32];
__device__ int g_err;
#define TS(jj, i)
#define TS1(jj, i)
#define PTS(i)
#define TSB(jj, i)
#define TSV(jj, i, v)
#define TS_FLUSH(jj)
#define WTS(b, k)
#define WTS1(b, k)
#define WW -1

__device__ __forceinline__ uint32_t smem_u32(const void* p) { return (uint32_t)__cvta_generic_to_shared(p); }
__device__ __forceinline__ uint32_t clk32() { uint32_t t; asm volatile("mov.u32 %0, %%clock;" : "=r"(t)::"memory"); return t; }
__device__ __forceinline__ uint32_t mapa(uint32_t a, uint32_t r) { uint32_t o; asm("mapa.shared::cluster.u32 %0,%1,%2;" : "=r"(o) : "r"(a), "r"(r)); return o; }
__device__ __forceinline__ void mbar_init(uint32_t bar, uint32_t cnt) { asm volatile("mbarrier.init.shared::cta.b64 [%0],%1;" ::"r"(bar), "r"(cnt) : "memory"); }
__device__ __forceinline__ void mbar_expect_tx(uint32_t bar, uint32_t bytes) { asm volatile("mbarrier.arrive.expect_tx.shared::cta.b64 _,[%0],%1;" ::"r"(bar), "r"(bytes) : "memory"); }
__device__ __forceinline__ void mbar_arrive(uint32_t bar) { asm volatile("mbarrier.arrive.shared::cta.b64 _,[%0];" ::"r"(bar) : "memory"); }
__device__ __forceinline__ void mbar_arrive_cluster(uint32_t bar) { asm volatile("mbarrier.arrive.shared::cluster.b64 _,[%0];" ::"r"(bar) : "memory"); }
__device__ __forceinline__ bool mbar_try(uint32_t bar, uint32_t ph) {
  uint32_t ok;
  asm volatile("{.reg .pred p; mbarrier.try_wait.parity.shared::cta.b64 p,[%1],%2; selp.u32 %0,1,0,p;}" : "=r"(ok) : "r"(bar), "r"(ph) : "memory");
  return ok;
}
__device__ __forceinline__ bool mbar_test(uint32_t bar, uint32_t ph) {
  uint32_t ok;
  asm volatile("{.reg .pred p; mbarrier.test_wait.parity.shared::cta.b64 p,[%1],%2; selp.u32 %0,1,0,p;}" : "=r"(ok) : "r"(bar), "r"(ph) : "memory");
  return ok;
}
__device__ __forceinline__ int fresh(int x) { asm volatile("" : "+r"(x)); return x; }
#define PHASE_IDS const int tid = fresh(tid0), lane = tid & 31, w = tid >> 5, g = lane >> 2, t = lane & 3; (void)w; (void)g; (void)t
__device__ __forceinline__ void bar_sync(int id, int n) { asm volatile("bar.sync %0,%1;" ::"r"(id), "r"(n) : "memory"); }
__device__ __forceinline__ void bar_arrive(int id, int n) { asm volatile("bar.arrive %0,%1;" ::"r"(id), "r"(n) : "memory"); }
__device__ __forceinline__ bool bar_red_or(int id, int n, bool v) {
  uint32_t r;
  asm volatile("{\n .reg .pred p, q;\n setp.ne.u32 q, %3, 0;\n barrier.cta.red.or.pred p, %1, %2, q;\n selp.u32 %0, 1, 0, p;\n}" : "=r"(r) : "r"(id), "r"(n), "r"((uint32_t)v) : "memory");
  return r != 0;
}
__device__ __forceinline__ void fence_async() { asm volatile("fence.proxy.async.shared::cta;" ::: "memory"); }
__device__ __forceinline__ void bulk_g2s(uint32_t dst, const void* src, uint32_t bytes, uint32_t bar) {
  asm volatile("cp.async.bulk.shared::cluster.global.mbarrier::complete_tx::bytes [%0],[%1],%2,[%3];" ::"r"(dst), "l"(src), "r"(bytes), "r"(bar) : "memory");
}
__device__ __forceinline__ void bulk_g2s_mc(uint32_t dst, const void* src, uint32_t bytes, uint32_t bar) {
  asm volatile("cp.async.bulk.shared::cluster.global.mbarrier::complete_tx::bytes.multicast::cluster [%0],[%1],%2,[%3],%4;"
               ::"r"(dst), "l"(src), "r"(bytes), "r"(bar), "h"((uint16_t)7) : "memory");
}
__device__ __forceinline__ void bulk_s2g(void* dst, uint32_t src, uint32_t bytes) {
  asm volatile("cp.async.bulk.global.shared::cta.bulk_group [%0],[%1],%2;" ::"l"(dst), "r"(src), "r"(bytes) : "memory");
}
__device__ __forceinline__ void bulk_s2c(uint32_t dst, uint32_t src, uint32_t bytes, uint32_t bar) {
  asm volatile("cp.async.bulk.shared::cluster.shared::cta.mbarrier::complete_tx::bytes [%0],[%1],%2,[%3];" ::"r"(dst), "r"(src), "r"(bytes), "r"(bar) : "memory");
}
__device__ __forceinline__ void tma2d(uint32_t dst, const CUtensorMap* tm, int c0, int c1, uint32_t bar) {
  asm volatile("cp.async.bulk.tensor.2d.shared::cluster.global.mbarrier::complete_tx::bytes [%0],[%1,{%3,%4}],[%2];"
               ::"r"(dst), "l"(tm), "r"(bar), "r"(c0), "r"(c1) : "memory");
}
__device__ __forceinline__ void tma2d_prefetch(const CUtensorMap* tm, int c0, int c1) {
  asm volatile("cp.async.bulk.prefetch.tensor.2d.L2.global.tile [%0,{%1,%2}];" ::"l"(tm), "r"(c0), "r"(c1) : "memory");
}
__device__ __forceinline__ uint32_t pack_bf16(float lo, float hi) {
  uint32_t r; asm("cvt.rn.bf16x2.f32 %0,%1,%2;" : "=r"(r) : "f"(hi), "f"(lo)); return r;
}
__device__ __forceinline__ float bf_lo(uint32_t x) { return __uint_as_float(x << 16); }
__device__ __forceinline__ float bf_hi(uint32_t x) { return __uint_as_float(x & 0xFFFF0000u); }
__device__ __forceinline__ float ex2(float x) { float y; asm("ex2.approx.ftz.f32 %0,%1;" : "=f"(y) : "f"(x)); return y; }
__device__ __forceinline__ void ldsm4(uint32_t (&r)[4], uint32_t a) {
  asm volatile("ldmatrix.sync.aligned.m8n8.x4.shared.b16 {%0,%1,%2,%3},[%4];" : "=r"(r[0]), "=r"(r[1]), "=r"(r[2]), "=r"(r[3]) : "r"(a) : "memory");
}
__device__ __forceinline__ void ldsm4t(uint32_t (&r)[4], uint32_t a) {
  asm volatile("ldmatrix.sync.aligned.m8n8.x4.trans.shared.b16 {%0,%1,%2,%3},[%4];" : "=r"(r[0]), "=r"(r[1]), "=r"(r[2]), "=r"(r[3]) : "r"(a) : "memory");
}
__device__ __forceinline__ void ldsm2(uint32_t& r0, uint32_t& r1, uint32_t a) {
  asm volatile("ldmatrix.sync.aligned.m8n8.x2.shared.b16 {%0,%1},[%2];" : "=r"(r0), "=r"(r1) : "r"(a) : "memory");
}
__device__ __forceinline__ void ldsm2t(uint32_t& r0, uint32_t& r1, uint32_t a) {
  asm volatile("ldmatrix.sync.aligned.m8n8.x2.trans.shared.b16 {%0,%1},[%2];" : "=r"(r0), "=r"(r1) : "r"(a) : "memory");
}
__device__ __forceinline__ void ldsm1(uint32_t& r0, uint32_t a) {
  asm volatile("ldmatrix.sync.aligned.m8n8.x1.shared.b16 {%0},[%1];" : "=r"(r0) : "r"(a) : "memory");
}
__device__ __forceinline__ void mma16816(float (&d)[4], uint32_t a0, uint32_t a1, uint32_t a2, uint32_t a3, uint32_t b0, uint32_t b1) {
  asm volatile("mma.sync.aligned.m16n8k16.row.col.f32.bf16.bf16.f32 {%0,%1,%2,%3},{%4,%5,%6,%7},{%8,%9},{%0,%1,%2,%3};"
               : "+f"(d[0]), "+f"(d[1]), "+f"(d[2]), "+f"(d[3]) : "r"(a0), "r"(a1), "r"(a2), "r"(a3), "r"(b0), "r"(b1));
}
__device__ __forceinline__ void mma1688(float (&d)[4], uint32_t a0, uint32_t a1, uint32_t b0) {
  asm volatile("mma.sync.aligned.m16n8k8.row.col.f32.bf16.bf16.f32 {%0,%1,%2,%3},{%4,%5},{%6},{%0,%1,%2,%3};"
               : "+f"(d[0]), "+f"(d[1]), "+f"(d[2]), "+f"(d[3]) : "r"(a0), "r"(a1), "r"(b0));
}
__device__ __forceinline__ void sts32(uint32_t a, uint32_t v) { asm volatile("st.shared.b32 [%0],%1;" ::"r"(a), "r"(v) : "memory"); }
__device__ __forceinline__ void sts64f(uint32_t a, float x, float y) { asm volatile("st.shared.v2.f32 [%0],{%1,%2};" ::"r"(a), "f"(x), "f"(y) : "memory"); }
__device__ __forceinline__ void sts128(uint32_t a, uint4 v) { asm volatile("st.shared.v4.b32 [%0],{%1,%2,%3,%4};" ::"r"(a), "r"(v.x), "r"(v.y), "r"(v.z), "r"(v.w) : "memory"); }
__device__ __forceinline__ float lds32f(uint32_t a) { float v; asm volatile("ld.shared.f32 %0,[%1];" : "=f"(v) : "r"(a) : "memory"); return v; }
__device__ __forceinline__ float2 lds64f(uint32_t a) { float2 v; asm volatile("ld.shared.v2.f32 {%0,%1},[%2];" : "=f"(v.x), "=f"(v.y) : "r"(a) : "memory"); return v; }
__device__ __forceinline__ uint4 lds128(uint32_t a) { uint4 v; asm volatile("ld.shared.v4.b32 {%0,%1,%2,%3},[%4];" : "=r"(v.x), "=r"(v.y), "=r"(v.z), "=r"(v.w) : "r"(a) : "memory"); return v; }
__device__ __forceinline__ float4 lds128f(uint32_t a) { float4 v; asm volatile("ld.shared.v4.f32 {%0,%1,%2,%3},[%4];" : "=f"(v.x), "=f"(v.y), "=f"(v.z), "=f"(v.w) : "r"(a) : "memory"); return v; }
__device__ __forceinline__ void st_async2(uint32_t a, float x, float y, uint32_t bar) {
  asm volatile("st.async.weak.shared::cluster.mbarrier::complete_tx::bytes.v2.f32 [%0],{%1,%2},[%3];" ::"r"(a), "f"(x), "f"(y), "r"(bar) : "memory");
}
__device__ __forceinline__ void st_async4(uint32_t a, const float (&v)[4], uint32_t bar) {
  asm volatile("st.async.weak.shared::cluster.mbarrier::complete_tx::bytes.v4.f32 [%0],{%1,%2,%3,%4},[%5];" ::"r"(a), "f"(v[0]), "f"(v[1]), "f"(v[2]), "f"(v[3]), "r"(bar) : "memory");
}
__device__ __forceinline__ void st_async4v(uint32_t a, float x, float y, float z, float w, uint32_t bar) {
  asm volatile("st.async.weak.shared::cluster.mbarrier::complete_tx::bytes.v4.f32 [%0],{%1,%2,%3,%4},[%5];" ::"r"(a), "f"(x), "f"(y), "f"(z), "f"(w), "r"(bar) : "memory");
}
__device__ __forceinline__ void st_async4u(uint32_t a, const uint4& v, uint32_t bar) {
  asm volatile("st.async.weak.shared::cluster.mbarrier::complete_tx::bytes.v4.b32 [%0],{%1,%2,%3,%4},[%5];" ::"r"(a), "r"(v.x), "r"(v.y), "r"(v.z), "r"(v.w), "r"(bar) : "memory");
}
__device__ __forceinline__ uint4 ld_relaxed4(const void* p) {
  uint4 v; asm volatile("ld.relaxed.gpu.global.v4.u32 {%0,%1,%2,%3},[%4];" : "=r"(v.x), "=r"(v.y), "=r"(v.z), "=r"(v.w) : "l"(p) : "memory"); return v;
}
__device__ __forceinline__ uint32_t ld_relaxed(const void* p) {
  uint32_t v; asm volatile("ld.relaxed.gpu.global.u32 %0,[%1];" : "=r"(v) : "l"(p) : "memory"); return v;
}
__device__ __forceinline__ void st_relaxed(void* p, uint32_t v) { asm volatile("st.relaxed.gpu.global.b32 [%0],%1;" ::"l"(p), "r"(v) : "memory"); }
__device__ __forceinline__ void st_relaxed4(void* p, uint32_t v) { asm volatile("st.relaxed.gpu.global.v4.b32 [%0],{%1,%1,%1,%1};" ::"l"(p), "r"(v) : "memory"); }

__device__ __forceinline__ uint32_t ld_acquire(const void* p) {
  uint32_t v; asm volatile("ld.acquire.gpu.global.u32 %0,[%1];" : "=r"(v) : "l"(p) : "memory"); return v;
}
__device__ __forceinline__ float4 ld_relaxed4f(const void* p) {
  float4 v; asm volatile("ld.relaxed.gpu.global.v4.f32 {%0,%1,%2,%3},[%4];" : "=f"(v.x), "=f"(v.y), "=f"(v.z), "=f"(v.w) : "l"(p) : "memory"); return v;
}
__device__ __forceinline__ float2 ld_relaxed2f(const void* p) {
  float2 v; asm volatile("ld.relaxed.gpu.global.v2.f32 {%0,%1},[%2];" : "=f"(v.x), "=f"(v.y) : "l"(p) : "memory"); return v;
}
__device__ __forceinline__ void prefetch_l2(const void* p) { asm volatile("prefetch.global.L2 [%0];" ::"l"(p)); }
__device__ __forceinline__ void fence_gpu() { asm volatile("fence.acq_rel.gpu;" ::: "memory"); }
__device__ __forceinline__ void fence_async_all() { asm volatile("fence.proxy.async.global;" ::: "memory"); }
constexpr int SPIN_TOT = 1 << 22;
__device__ __forceinline__ void csignal(int idx) { asm volatile("red.release.gpu.global.add.u32 [%0],1;" ::"l"(&g_cnt[idx][0]) : "memory"); }
#define csignal_t(idx, role) csignal(idx)
__device__ __forceinline__ void cwait(int idx, uint32_t target, int& spin) {
  while (ld_acquire(&g_cnt[idx][0]) < target && spin < SPIN_TOT) spin += 16;
}

__device__ __forceinline__ uint64_t mkdesc(uint32_t addr, uint32_t lbo, uint32_t sbo) {
  return (uint64_t)((addr & 0x3FFFF) >> 4) | ((uint64_t)(lbo >> 4) << 16) | ((uint64_t)(sbo >> 4) << 32) | ((uint64_t)1 << 62);
}
__device__ __forceinline__ uint64_t mkdesc_ns(uint32_t addr, uint32_t lbo, uint32_t sbo) {
  return (uint64_t)((addr & 0x3FFFF) >> 4) | ((uint64_t)(lbo >> 4) << 16) | ((uint64_t)(sbo >> 4) << 32);
}
__device__ __forceinline__ void wg_fence() { asm volatile("wgmma.fence.sync.aligned;" ::: "memory"); }
__device__ __forceinline__ void wg_commit() { asm volatile("wgmma.commit_group.sync.aligned;" ::: "memory"); }
template <int N> __device__ __forceinline__ void wg_wait() { asm volatile("wgmma.wait_group.sync.aligned %0;" ::"n"(N) : "memory"); }

__device__ __forceinline__ void wgmma_rs16(float (&d)[8], const uint32_t (&a)[4], uint64_t db, int sc) {
  asm volatile("{.reg .pred p; setp.ne.b32 p,%13,0; wgmma.mma_async.sync.aligned.m64n16k16.f32.bf16.bf16 "
               "{%0,%1,%2,%3,%4,%5,%6,%7},{%8,%9,%10,%11},%12,p,1,1,0;}"
               : "+f"(d[0]), "+f"(d[1]), "+f"(d[2]), "+f"(d[3]), "+f"(d[4]), "+f"(d[5]), "+f"(d[6]), "+f"(d[7])
               : "r"(a[0]), "r"(a[1]), "r"(a[2]), "r"(a[3]), "l"(db), "r"(sc));
}
__device__ __forceinline__ void wgmma_rs64(float (&d)[32], const uint32_t (&a)[4], uint64_t db, int sc) {
  asm volatile("{.reg .pred p; setp.ne.b32 p,%37,0; wgmma.mma_async.sync.aligned.m64n64k16.f32.bf16.bf16 "
               "{%0,%1,%2,%3,%4,%5,%6,%7,%8,%9,%10,%11,%12,%13,%14,%15,%16,%17,%18,%19,%20,%21,%22,%23,%24,%25,%26,%27,%28,%29,%30,%31},{%32,%33,%34,%35},%36,p,1,1,0;}"
               : "+f"(d[0]), "+f"(d[1]), "+f"(d[2]), "+f"(d[3]), "+f"(d[4]), "+f"(d[5]), "+f"(d[6]), "+f"(d[7]), "+f"(d[8]), "+f"(d[9]), "+f"(d[10]), "+f"(d[11]), "+f"(d[12]), "+f"(d[13]), "+f"(d[14]), "+f"(d[15]), "+f"(d[16]), "+f"(d[17]), "+f"(d[18]), "+f"(d[19]), "+f"(d[20]), "+f"(d[21]), "+f"(d[22]), "+f"(d[23]), "+f"(d[24]), "+f"(d[25]), "+f"(d[26]), "+f"(d[27]), "+f"(d[28]), "+f"(d[29]), "+f"(d[30]), "+f"(d[31])
               : "r"(a[0]), "r"(a[1]), "r"(a[2]), "r"(a[3]), "l"(db), "r"(sc));
}
__device__ __forceinline__ void wgmma_rt16(float (&d)[8], const uint32_t (&a)[4], uint64_t db, int sc) {
  asm volatile("{.reg .pred p; setp.ne.b32 p,%13,0; wgmma.mma_async.sync.aligned.m64n16k16.f32.bf16.bf16 "
               "{%0,%1,%2,%3,%4,%5,%6,%7},{%8,%9,%10,%11},%12,p,1,1,1;}"
               : "+f"(d[0]), "+f"(d[1]), "+f"(d[2]), "+f"(d[3]), "+f"(d[4]), "+f"(d[5]), "+f"(d[6]), "+f"(d[7])
               : "r"(a[0]), "r"(a[1]), "r"(a[2]), "r"(a[3]), "l"(db), "r"(sc));
}
__device__ __forceinline__ void wgmma_rt80(float (&d)[40], const uint32_t (&a)[4], uint64_t db, int sc) {
  asm volatile("{.reg .pred p; setp.ne.b32 p,%45,0; wgmma.mma_async.sync.aligned.m64n80k16.f32.bf16.bf16 "
               "{%0,%1,%2,%3,%4,%5,%6,%7,%8,%9,%10,%11,%12,%13,%14,%15,%16,%17,%18,%19,%20,%21,%22,%23,%24,%25,%26,%27,%28,%29,%30,%31,%32,%33,%34,%35,%36,%37,%38,%39},{%40,%41,%42,%43},%44,p,1,1,1;}"
               : "+f"(d[0]), "+f"(d[1]), "+f"(d[2]), "+f"(d[3]), "+f"(d[4]), "+f"(d[5]), "+f"(d[6]), "+f"(d[7]), "+f"(d[8]), "+f"(d[9]), "+f"(d[10]), "+f"(d[11]), "+f"(d[12]), "+f"(d[13]), "+f"(d[14]), "+f"(d[15]), "+f"(d[16]), "+f"(d[17]), "+f"(d[18]), "+f"(d[19]), "+f"(d[20]), "+f"(d[21]), "+f"(d[22]), "+f"(d[23]), "+f"(d[24]), "+f"(d[25]), "+f"(d[26]), "+f"(d[27]), "+f"(d[28]), "+f"(d[29]), "+f"(d[30]), "+f"(d[31]), "+f"(d[32]), "+f"(d[33]), "+f"(d[34]), "+f"(d[35]), "+f"(d[36]), "+f"(d[37]), "+f"(d[38]), "+f"(d[39])
               : "r"(a[0]), "r"(a[1]), "r"(a[2]), "r"(a[3]), "l"(db), "r"(sc));
}
__device__ __forceinline__ void wgmma_rs32(float (&d)[16], const uint32_t (&a)[4], uint64_t db, int sc) {
  asm volatile("{.reg .pred p; setp.ne.b32 p,%21,0; wgmma.mma_async.sync.aligned.m64n32k16.f32.bf16.bf16 "
               "{%0,%1,%2,%3,%4,%5,%6,%7,%8,%9,%10,%11,%12,%13,%14,%15},{%16,%17,%18,%19},%20,p,1,1,0;}"
               : "+f"(d[0]), "+f"(d[1]), "+f"(d[2]), "+f"(d[3]), "+f"(d[4]), "+f"(d[5]), "+f"(d[6]), "+f"(d[7]), "+f"(d[8]), "+f"(d[9]), "+f"(d[10]), "+f"(d[11]), "+f"(d[12]), "+f"(d[13]), "+f"(d[14]), "+f"(d[15])
               : "r"(a[0]), "r"(a[1]), "r"(a[2]), "r"(a[3]), "l"(db), "r"(sc));
}
__device__ __forceinline__ void wgmma_ts32(float (&d)[16], uint64_t da, uint64_t db, int sc) {
  asm volatile("{.reg .pred p; setp.ne.b32 p,%18,0; wgmma.mma_async.sync.aligned.m64n32k16.f32.bf16.bf16 "
               "{%0,%1,%2,%3,%4,%5,%6,%7,%8,%9,%10,%11,%12,%13,%14,%15},%16,%17,p,1,1,1,0;}"
               : "+f"(d[0]), "+f"(d[1]), "+f"(d[2]), "+f"(d[3]), "+f"(d[4]), "+f"(d[5]), "+f"(d[6]), "+f"(d[7]), "+f"(d[8]), "+f"(d[9]), "+f"(d[10]), "+f"(d[11]), "+f"(d[12]), "+f"(d[13]), "+f"(d[14]), "+f"(d[15])
               : "l"(da), "l"(db), "r"(sc));
}
__device__ __forceinline__ void wgmma_rs8(float (&d)[4], const uint32_t (&a)[4], uint64_t db, int sc) {
  asm volatile("{.reg .pred p; setp.ne.b32 p,%9,0; wgmma.mma_async.sync.aligned.m64n8k16.f32.bf16.bf16 "
               "{%0,%1,%2,%3},{%4,%5,%6,%7},%8,p,1,1,0;}"
               : "+f"(d[0]), "+f"(d[1]), "+f"(d[2]), "+f"(d[3])
               : "r"(a[0]), "r"(a[1]), "r"(a[2]), "r"(a[3]), "l"(db), "r"(sc));
}
__device__ __forceinline__ void wgmma_ts16(float (&d)[8], uint64_t da, uint64_t db, int sc) {
  asm volatile("{.reg .pred p; setp.ne.b32 p,%10,0; wgmma.mma_async.sync.aligned.m64n16k16.f32.bf16.bf16 "
               "{%0,%1,%2,%3,%4,%5,%6,%7},%8,%9,p,1,1,1,0;}"
               : "+f"(d[0]), "+f"(d[1]), "+f"(d[2]), "+f"(d[3]), "+f"(d[4]), "+f"(d[5]), "+f"(d[6]), "+f"(d[7])
               : "l"(da), "l"(db), "r"(sc));
}
__device__ __forceinline__ void wgmma_ts64(float (&d)[32], uint64_t da, uint64_t db, int sc) {
  asm volatile("{.reg .pred p; setp.ne.b32 p,%34,0; wgmma.mma_async.sync.aligned.m64n64k16.f32.bf16.bf16 "
               "{%0,%1,%2,%3,%4,%5,%6,%7,%8,%9,%10,%11,%12,%13,%14,%15,%16,%17,%18,%19,%20,%21,%22,%23,%24,%25,%26,%27,%28,%29,%30,%31},%32,%33,p,1,1,1,0;}"
               : "+f"(d[0]), "+f"(d[1]), "+f"(d[2]), "+f"(d[3]), "+f"(d[4]), "+f"(d[5]), "+f"(d[6]), "+f"(d[7]), "+f"(d[8]), "+f"(d[9]), "+f"(d[10]), "+f"(d[11]), "+f"(d[12]), "+f"(d[13]), "+f"(d[14]), "+f"(d[15]), "+f"(d[16]), "+f"(d[17]), "+f"(d[18]), "+f"(d[19]), "+f"(d[20]), "+f"(d[21]), "+f"(d[22]), "+f"(d[23]), "+f"(d[24]), "+f"(d[25]), "+f"(d[26]), "+f"(d[27]), "+f"(d[28]), "+f"(d[29]), "+f"(d[30]), "+f"(d[31])
               : "l"(da), "l"(db), "r"(sc));
}
__device__ __forceinline__ void wgmma_tt16(float (&d)[8], uint64_t da, uint64_t db, int sc) {
  asm volatile("{.reg .pred p; setp.ne.b32 p,%10,0; wgmma.mma_async.sync.aligned.m64n16k16.f32.bf16.bf16 "
               "{%0,%1,%2,%3,%4,%5,%6,%7},%8,%9,p,1,1,1,1;}"
               : "+f"(d[0]), "+f"(d[1]), "+f"(d[2]), "+f"(d[3]), "+f"(d[4]), "+f"(d[5]), "+f"(d[6]), "+f"(d[7])
               : "l"(da), "l"(db), "r"(sc));
}
__device__ __forceinline__ void wgmma_tt40(float (&d)[20], uint64_t da, uint64_t db, int sc) {
  asm volatile("{.reg .pred p; setp.ne.b32 p,%22,0; wgmma.mma_async.sync.aligned.m64n40k16.f32.bf16.bf16 "
               "{%0,%1,%2,%3,%4,%5,%6,%7,%8,%9,%10,%11,%12,%13,%14,%15,%16,%17,%18,%19},%20,%21,p,1,1,1,1;}"
               : "+f"(d[0]), "+f"(d[1]), "+f"(d[2]), "+f"(d[3]), "+f"(d[4]), "+f"(d[5]), "+f"(d[6]), "+f"(d[7]), "+f"(d[8]), "+f"(d[9]), "+f"(d[10]), "+f"(d[11]), "+f"(d[12]), "+f"(d[13]), "+f"(d[14]), "+f"(d[15]), "+f"(d[16]), "+f"(d[17]), "+f"(d[18]), "+f"(d[19])
               : "l"(da), "l"(db), "r"(sc));
}
__device__ __forceinline__ void wgmma_ss8(float (&d)[4], uint64_t da, uint64_t db, int sc) {
  asm volatile("{.reg .pred p; setp.ne.b32 p,%6,0; wgmma.mma_async.sync.aligned.m64n8k16.f32.bf16.bf16 "
               "{%0,%1,%2,%3},%4,%5,p,1,1,0,0;}"
               : "+f"(d[0]), "+f"(d[1]), "+f"(d[2]), "+f"(d[3])
               : "l"(da), "l"(db), "r"(sc));
}
__device__ __forceinline__ void wgmma_ss32(float (&d)[16], uint64_t da, uint64_t db, int sc) {
  asm volatile("{.reg .pred p; setp.ne.b32 p,%18,0; wgmma.mma_async.sync.aligned.m64n32k16.f32.bf16.bf16 "
               "{%0,%1,%2,%3,%4,%5,%6,%7,%8,%9,%10,%11,%12,%13,%14,%15},%16,%17,p,1,1,0,0;}"
               : "+f"(d[0]), "+f"(d[1]), "+f"(d[2]), "+f"(d[3]), "+f"(d[4]), "+f"(d[5]), "+f"(d[6]), "+f"(d[7]), "+f"(d[8]), "+f"(d[9]), "+f"(d[10]), "+f"(d[11]), "+f"(d[12]), "+f"(d[13]), "+f"(d[14]), "+f"(d[15])
               : "l"(da), "l"(db), "r"(sc));
}
__device__ __forceinline__ void wgmma_st64(float (&d)[32], uint64_t da, uint64_t db, int sc) {
  asm volatile("{.reg .pred p; setp.ne.b32 p,%34,0; wgmma.mma_async.sync.aligned.m64n64k16.f32.bf16.bf16 "
               "{%0,%1,%2,%3,%4,%5,%6,%7,%8,%9,%10,%11,%12,%13,%14,%15,%16,%17,%18,%19,%20,%21,%22,%23,%24,%25,%26,%27,%28,%29,%30,%31},%32,%33,p,1,1,0,1;}"
               : "+f"(d[0]), "+f"(d[1]), "+f"(d[2]), "+f"(d[3]), "+f"(d[4]), "+f"(d[5]), "+f"(d[6]), "+f"(d[7]), "+f"(d[8]), "+f"(d[9]), "+f"(d[10]), "+f"(d[11]), "+f"(d[12]), "+f"(d[13]), "+f"(d[14]), "+f"(d[15]), "+f"(d[16]), "+f"(d[17]), "+f"(d[18]), "+f"(d[19]), "+f"(d[20]), "+f"(d[21]), "+f"(d[22]), "+f"(d[23]), "+f"(d[24]), "+f"(d[25]), "+f"(d[26]), "+f"(d[27]), "+f"(d[28]), "+f"(d[29]), "+f"(d[30]), "+f"(d[31])
               : "l"(da), "l"(db), "r"(sc));
}
__device__ __forceinline__ void wgmma_st128(float (&d)[64], uint64_t da, uint64_t db, int sc) {
  asm volatile("{.reg .pred p; setp.ne.b32 p,%66,0; wgmma.mma_async.sync.aligned.m64n128k16.f32.bf16.bf16 "
               "{%0,%1,%2,%3,%4,%5,%6,%7,%8,%9,%10,%11,%12,%13,%14,%15,%16,%17,%18,%19,%20,%21,%22,%23,%24,%25,%26,%27,%28,%29,%30,%31,%32,%33,%34,%35,%36,%37,%38,%39,%40,%41,%42,%43,%44,%45,%46,%47,%48,%49,%50,%51,%52,%53,%54,%55,%56,%57,%58,%59,%60,%61,%62,%63},%64,%65,p,1,1,0,1;}"
               : "+f"(d[0]), "+f"(d[1]), "+f"(d[2]), "+f"(d[3]), "+f"(d[4]), "+f"(d[5]), "+f"(d[6]), "+f"(d[7]), "+f"(d[8]), "+f"(d[9]), "+f"(d[10]), "+f"(d[11]), "+f"(d[12]), "+f"(d[13]), "+f"(d[14]), "+f"(d[15]), "+f"(d[16]), "+f"(d[17]), "+f"(d[18]), "+f"(d[19]), "+f"(d[20]), "+f"(d[21]), "+f"(d[22]), "+f"(d[23]), "+f"(d[24]), "+f"(d[25]), "+f"(d[26]), "+f"(d[27]), "+f"(d[28]), "+f"(d[29]), "+f"(d[30]), "+f"(d[31]), "+f"(d[32]), "+f"(d[33]), "+f"(d[34]), "+f"(d[35]), "+f"(d[36]), "+f"(d[37]), "+f"(d[38]), "+f"(d[39]), "+f"(d[40]), "+f"(d[41]), "+f"(d[42]), "+f"(d[43]), "+f"(d[44]), "+f"(d[45]), "+f"(d[46]), "+f"(d[47]), "+f"(d[48]), "+f"(d[49]), "+f"(d[50]), "+f"(d[51]), "+f"(d[52]), "+f"(d[53]), "+f"(d[54]), "+f"(d[55]), "+f"(d[56]), "+f"(d[57]), "+f"(d[58]), "+f"(d[59]), "+f"(d[60]), "+f"(d[61]), "+f"(d[62]), "+f"(d[63])
               : "l"(da), "l"(db), "r"(sc));
}

__device__ __forceinline__ void stsm4(uint32_t a, uint32_t r0, uint32_t r1, uint32_t r2, uint32_t r3) {
  asm volatile("stmatrix.sync.aligned.m8n8.x4.shared.b16 [%0],{%1,%2,%3,%4};" ::"r"(a), "r"(r0), "r"(r1), "r"(r2), "r"(r3) : "memory");
}
__device__ __forceinline__ void stsm4t(uint32_t a, uint32_t r0, uint32_t r1, uint32_t r2, uint32_t r3) {
  asm volatile("stmatrix.sync.aligned.m8n8.x4.trans.shared.b16 [%0],{%1,%2,%3,%4};" ::"r"(a), "r"(r0), "r"(r1), "r"(r2), "r"(r3) : "memory");
}
__device__ __forceinline__ void sts64(uint32_t a, uint32_t x, uint32_t y) { asm volatile("st.shared.v2.b32 [%0],{%1,%2};" ::"r"(a), "r"(x), "r"(y) : "memory"); }
__device__ __forceinline__ void st_async2u(uint32_t a, uint32_t x, uint32_t y, uint32_t bar) {
  asm volatile("st.async.weak.shared::cluster.mbarrier::complete_tx::bytes.v2.b32 [%0],{%1,%2},[%3];" ::"r"(a), "r"(x), "r"(y), "r"(bar) : "memory");
}
__device__ __forceinline__ void st_relaxed128(void* p, uint32_t x, uint32_t y, uint32_t z, uint32_t w) {
  asm volatile("{.reg .b128 v; mov.b128 v,{%1,%2,%3,%4}; st.relaxed.gpu.global.b128 [%0],v;}" ::"l"(p), "r"(x), "r"(y), "r"(z), "r"(w) : "memory");
}
__device__ __forceinline__ void st_relaxed64(void* p, uint32_t x, uint32_t y) {
  asm volatile("{.reg .b64 v; mov.b64 v,{%1,%2}; st.relaxed.gpu.global.b64 [%0],v;}" ::"l"(p), "r"(x), "r"(y) : "memory");
}
__device__ __forceinline__ uint4 ld_relaxed128(const void* p) {
  uint4 v;
  asm volatile("{.reg .b128 v; .reg .b64 lo, hi; ld.relaxed.gpu.global.b128 v,[%4]; mov.b128 {lo,hi},v; mov.b64 {%0,%1},lo; mov.b64 {%2,%3},hi;}" : "=r"(v.x), "=r"(v.y), "=r"(v.z), "=r"(v.w) : "l"(p) : "memory");
  return v;
}

__device__ __forceinline__ uint32_t pack_h2(float lo, float hi) {
  uint32_t r; asm("cvt.rn.satfinite.f16x2.f32 %0,%1,%2;" : "=r"(r) : "f"(hi), "f"(lo)); return r;
}
__device__ __forceinline__ void add_h2(float& lo, float& hi, uint32_t u, uint32_t v) {
  float a, b;
  asm("{.reg .b16 l, h; .reg .b32 s; add.rn.f16x2 s,%2,%3; mov.b32 {l,h},s; cvt.f32.f16 %0,l; cvt.f32.f16 %1,h;}" : "=f"(a), "=f"(b) : "r"(u), "r"(v));
  lo += a; hi += b;
}
__device__ __forceinline__ void mwait(uint32_t bar, uint32_t ph, int& spin) {
  asm volatile("{.reg .pred p, q;\nWAIT_LOOP:\n add.s32 %0,%0,1;\n setp.lt.s32 q,%0,%3;\n mbarrier.try_wait.parity.shared::cta.b64 p,[%1],%2;\n not.pred p,p;\n and.pred q,q,p;\n @q bra.uni WAIT_LOOP;\n}"
               : "+&r"(spin) : "r"(bar), "r"(ph), "n"(SPIN_TOT) : "memory");
}
__device__ __forceinline__ int keep(int x) { return __shfl_sync(0xffffffffu, x, threadIdx.x & 31); }
__device__ __forceinline__ uint32_t pin(uint32_t x) { asm volatile("" : "+r"(x)); return x; }
template <typename T> __device__ __forceinline__ T* pinp(T* x) { asm volatile("" : "+l"(x)); return x; }
__device__ __forceinline__ void st_async1u(uint32_t a, uint32_t x, uint32_t bar) {
  asm volatile("st.async.weak.shared::cluster.mbarrier::complete_tx::bytes.b32 [%0],%1,[%2];" ::"r"(a), "r"(x), "r"(bar) : "memory");
}
__device__ __forceinline__ uint32_t lds32(uint32_t a) { uint32_t v; asm volatile("ld.shared.b32 %0,[%1];" : "=r"(v) : "r"(a) : "memory"); return v; }
__device__ __forceinline__ uint2 lds64(uint32_t a) { uint2 v; asm volatile("ld.shared.v2.b32 {%0,%1},[%2];" : "=r"(v.x), "=r"(v.y) : "r"(a) : "memory"); return v; }

__device__ __forceinline__ void permute_cols(uint32_t tile, int tid, int n) {
  for (int it = tid; it < n; it += 128) {
    const int row = it >> 2, q = it & 3;
    const uint32_t a0 = tile + row * 128 + (((2 * q) ^ (row & 7)) << 4), a1 = tile + row * 128 + (((2 * q + 1) ^ (row & 7)) << 4);
    const uint4 u = lds128(a0), v = lds128(a1);
    sts128(a0, make_uint4(__byte_perm(u.x, u.y, 0x5410), __byte_perm(u.z, u.w, 0x5410), __byte_perm(v.x, v.y, 0x5410), __byte_perm(v.z, v.w, 0x5410)));
    sts128(a1, make_uint4(__byte_perm(u.x, u.y, 0x7632), __byte_perm(u.z, u.w, 0x7632), __byte_perm(v.x, v.y, 0x7632), __byte_perm(v.z, v.w, 0x7632)));
  }
}

__device__ __forceinline__ uint8_t* mkptr(uint32_t lo, uint32_t hi) { uint8_t* p; asm("mov.b64 %0,{%1,%2};" : "=l"(p) : "r"(lo), "r"(hi)); return p; }
__device__ __forceinline__ int uni(int x) { return __shfl_sync(0xffffffffu, x, 0); }

__device__ __forceinline__ bool elect_one() {
  uint32_t p; asm volatile("{.reg .pred q; elect.sync _|q, 0xffffffff; selp.u32 %0,1,0,q;}" : "=r"(p)); return p;
}
__device__ __forceinline__ uint64_t desc_at(uint64_t d, uint32_t off) {
  uint64_t r; asm("mov.b64 %0,{%1,%2};" : "=l"(r) : "r"((uint32_t)d + (off >> 4)), "r"((uint32_t)(d >> 32))); return r;
}
__device__ __forceinline__ uint32_t scale_bf16x2(uint32_t x, uint32_t s) { uint32_t r; asm("mul.rn.bf16x2 %0,%1,%2;" : "=r"(r) : "r"(x), "r"(s)); return r; }

__device__ __forceinline__ void stg128(void* p, const uint4& v) { asm volatile("st.global.v4.b32 [%0],{%1,%2,%3,%4};" ::"l"(p), "r"(v.x), "r"(v.y), "r"(v.z), "r"(v.w) : "memory"); }

__device__ __forceinline__ void ln_row_to_image(const bf16* __restrict__ x, uint8_t* __restrict__ img, int row, int lane) {
  const uint4* src = reinterpret_cast<const uint4*>(x + (size_t)row * DM);
  uint4 v[3];
  v[0] = src[lane]; v[1] = src[lane + 32];
  v[2] = lane < 16 ? src[lane + 64] : make_uint4(0, 0, 0, 0);
  float s = 0.f;
#pragma unroll
  for (int i = 0; i < 3; i++) {
    s += bf_lo(v[i].x) + bf_hi(v[i].x) + bf_lo(v[i].y) + bf_hi(v[i].y) + bf_lo(v[i].z) + bf_hi(v[i].z) + bf_lo(v[i].w) + bf_hi(v[i].w);
  }
#pragma unroll
  for (int o = 16; o > 0; o >>= 1) s += __shfl_xor_sync(0xffffffffu, s, o);
  const float mean = s * (1.f / DM);
  float q = 0.f;
#pragma unroll
  for (int i = 0; i < 3; i++) {
    if (i < 2 || lane < 16) {
      const uint32_t w[4] = {v[i].x, v[i].y, v[i].z, v[i].w};
#pragma unroll
      for (int j = 0; j < 4; j++) { float a = bf_lo(w[j]) - mean, b = bf_hi(w[j]) - mean; q += a * a + b * b; }
    }
  }
#pragma unroll
  for (int o = 16; o > 0; o >>= 1) q += __shfl_xor_sync(0xffffffffu, q, o);
  const float rstd = rsqrtf(q * (1.f / DM) + 1e-5f);
#pragma unroll
  for (int i = 0; i < 3; i++) {
    if (i < 2 || lane < 16) {
      const int c = lane + 32 * i;
      uint4 o;
      o.x = pack_bf16((bf_lo(v[i].x) - mean) * rstd, (bf_hi(v[i].x) - mean) * rstd);
      o.y = pack_bf16((bf_lo(v[i].y) - mean) * rstd, (bf_hi(v[i].y) - mean) * rstd);
      o.z = pack_bf16((bf_lo(v[i].z) - mean) * rstd, (bf_hi(v[i].z) - mean) * rstd);
      o.w = pack_bf16((bf_lo(v[i].w) - mean) * rstd, (bf_hi(v[i].w) - mean) * rstd);
      const size_t off = (size_t)(row >> 5) * 81920 + (c >> 4) * 16384 + ((row >> 3) & 3) * 4096 + ((c >> 3) & 1) * 1024 + (row & 7) * 128 + (((c & 7) ^ (row & 7)) << 4);
      *reinterpret_cast<uint4*>(img + off) = o;
      float4* xf = reinterpret_cast<float4*>(g_x + (size_t)row * DM + c * 8);
      xf[0] = make_float4(bf_lo(v[i].x), bf_hi(v[i].x), bf_lo(v[i].y), bf_hi(v[i].y));
      xf[1] = make_float4(bf_lo(v[i].z), bf_hi(v[i].z), bf_lo(v[i].w), bf_hi(v[i].w));
    }
  }
}

#define NOWORK 0
__global__ void __launch_bounds__(256) k_pre(const bf16* __restrict__ x, const bf16* __restrict__ mem0) {
  const int row = blockIdx.x * 8 + (threadIdx.x >> 5);
  ln_row_to_image(x, g_xn[0], row, threadIdx.x & 31);
  const int gt = blockIdx.x * 256 + threadIdx.x;
  const uint4 sent = make_uint4(SENT, SENT, SENT, SENT);
  uint8_t* ex = ex_window(g_ex);
  if (gt < MAIL_BYTES / 16) {
    reinterpret_cast<uint4*>(ex + EX_MAIL)[gt] = sent;
    reinterpret_cast<uint4*>(ex + EX_MAIL + (1 << 20))[gt] = sent;
  }
  uint4* mb = reinterpret_cast<uint4*>(ex + EX_M);
  for (int i = gt; i < NSTEP * 1280; i += 65536) {
    const int p = i % 1280, st = i / 1280;
    uint4 v = sent;
    if (st == 0 || (st == LAG && (p & 8))) v = *reinterpret_cast<const uint4*>(mem0 + (p & 7) * DM + (p >> 4) * 8);
    mb[i] = v;
  }
  if (gt < NSTEP * 192) reinterpret_cast<uint4*>(ex + EX_FLAG)[gt] = gt < 192 ? make_uint4(0, 0, 0, 0) : sent;
  for (int i = gt; i < (NOWORK ? NSTEP + LAG : 2 * LAG) * 2560; i += 65536) {
    const int st = i / 2560, p = i % 2560;
    *reinterpret_cast<uint4*>(g_xn[st < LAG ? st + NSEG : st - LAG] + (p >> 7) * 4096 + (st < LAG ? 0 : 2048) + (p & 127) * 16) = make_uint4(0, 0, 0, 0);
  }
  if (gt < CN_NUM) g_cnt[gt][0] = 0;
}

namespace C {
constexpr int NKR = 37;
constexpr int OFF_WQ = 0, OFF_WK = 81920;
constexpr int OFF_YO = 163840, OFF_YV = OFF_YO + 6144;
constexpr int OFF_M = 176128;
__host__ __device__ constexpr int og_off(int c) { return c ? OFF_M + 14336 + c * 2048 : 229376; }
constexpr int OFF_KT = 196608;
constexpr int OFF_XT = OFF_KT + 10240;
constexpr int OFF_VT = OFF_XT + 7168;
constexpr int OFF_XM = OFF_VT + 11392;
constexpr int OFF_PT = OFF_XM + 2560;
constexpr int KS = 1280, VS = 1408;
__host__ __device__ constexpr int slot_off(int p) { return p == 2 ? OFF_M : OFF_KT + (p % 3) * 16384; }
constexpr int OFF_ONE = 231424;
constexpr int OFF_BAR = 231552;
constexpr int OFF_SAFE = OFF_BAR + 160;
constexpr int OFF_TS = OFF_BAR + 256;
constexpr int SMEM = 232448;
constexpr uint32_t SB0 = 1024;
constexpr int BAR_F = OFF_BAR, BAR_XM = BAR_F + 40, BAR_XT = BAR_F + 48, BAR_OG = BAR_F + 56, BAR_E = OFF_BAR + 64, BAR_MOK = BAR_E + 40,
              BAR_M = OFF_BAR + 112, BAR_XF = OFF_BAR + 120, BAR_MF = OFF_BAR + 128, BAR_W = OFF_BAR + 136, FLG_REDO = OFF_BAR + 144;
constexpr int NB_PRO = 1, NB_RD = 2, NB_MR = 3, NB_QK = 4, NB_SM = 5, NB_VA = 6, NB_VQ = 7, NB_A = 8, NB_Q = 9, NB_C = 10, NB_WQ = 11, NB_QI = 12, NB_SI = 13, NB_WV = 14;
#define B1 200
#define B2 250
#define FLP 1
#define OSG 2
#define OST 7
#define P1U 4
#define QIE 4
#define SIE 2
#define WOE 1
#define OGF 0
#define VSP 8
#define RFK 5
#define PFD 3
#define WOL 0
constexpr uint32_t SCQ = 0x3A003A00;
constexpr float SCE = 0.07216878364870322f * 1.4426950408889634f * 2048;
}

#define CBAR_SYNC(id, n) bar_sync(id, n)
#define CBAR_ARRIVE(id, n) bar_arrive(id, n)

__device__ __forceinline__ uint64_t wdesc(int off) { return mkdesc(C::SB0 + off, 8192, 1024); }
__device__ __forceinline__ uint64_t mdesc(int k) { return mkdesc_ns(C::SB0 + C::OFF_M + k * 512, 256, 128); }
__device__ __forceinline__ uint64_t tdesc(int k) { return mkdesc(C::SB0 + C::slot_off(k >> 3) + ((k >> 2) & 1) * 1024 + (k & 3) * 32, 16, 2048); }

__device__ __forceinline__ int dh_row(int n) { return (n & ~63) + (n & 32) + ((n >> 1) & 3) * 8 + ((n >> 3) & 3) * 2 + (n & 1); }
template <bool PERM>
__device__ __forceinline__ void load_weights_rs(uint32_t (&wf)[C::NKR][4], uint32_t sb, int stage, int yoff, int tid0) {
  using namespace C;
  const int i = (tid0 >> 3) & 3, n0 = (tid0 & 7) + (i >> 1) * 8;
  const int chunk = 2 * ((tid0 >> 5) & 3) + (i & 1);
  const int r0 = PERM ? dh_row(n0) : n0, r1 = PERM ? dh_row(n0 + 16) : n0 + 16;
  const uint32_t a0 = sb + stage + r0 * 128 + ((chunk ^ (r0 & 7)) << 4), a1 = sb + stage + r1 * 128 + ((chunk ^ (r1 & 7)) << 4);
#pragma unroll
  for (int k = 0; k < NKR; k++) ldsm4t(wf[k], ((k & 1) ? a1 : a0) + (k >> 1) * 4096);
#pragma unroll
  for (int k = 0; k < 40 - NKR; k++) {
    const int n = (NKR + k) * 16 + ((tid0 & 127) >> 3), r = PERM ? dh_row(n) : n, c = tid0 & 7;
    sts128(sb + yoff + (n - NKR * 16) * 128 + ((c ^ (n & 7)) << 4), lds128(sb + stage + r * 128 + ((c ^ (r & 7)) << 4)));
  }
  fence_async();
  CBAR_SYNC(NB_PRO, 384);
}
template <int STRIDE>
__device__ __forceinline__ void store_mem(const float (&d)[8], uint32_t base, int tid) {
  const int m = (tid >> 3) & 3;
  stsm4(base + (((tid >> 5) & 3) * 2 + (m & 1)) * STRIDE + (m >> 1) * 640 + (tid & 7) * 16, pack_bf16(d[0], d[1]), pack_bf16(d[2], d[3]),
        pack_bf16(d[4], d[5]), pack_bf16(d[6], d[7]));
}

__device__ __forceinline__ void load_pair(uint32_t sb, int i, int p, uint32_t slot, uint32_t ph, int& spin) {
  using namespace C;
  mwait(sb + BAR_E + 8 * p, ph, spin);
  if (elect_one()) bulk_g2s_mc(sb + slot, g_xn[i] + p * 16384, 16384, sb + BAR_F + 8 * p);
}
__device__ __forceinline__ void release_round(uint32_t sb, int p, int lane) {
  if (lane < (p == 2 ? 3 : 1)) mbar_arrive_cluster(mapa(sb, p == 2 ? lane : p) + C::BAR_E + 8 * (3 + p));
}

template <int K0, int K1>
__device__ __forceinline__ void v_mem_pass(float (&d)[8], const uint32_t (&wf)[C::NKR][4]) {
  using namespace C;
  wg_fence();
#pragma unroll
  for (int k = K0; k < K1; k++) {
    if (k < NKR) wgmma_rs16(d, wf[k < NKR ? k : 0], mdesc(k), k != 32);
    else wgmma_ts16(d, wdesc(OFF_YV + (k - NKR) * 2048), mdesc(k), 1);
  }
  wg_commit();
}
__device__ __forceinline__ void chain_v(const uint32_t sb, const int tid0, const int cta, const int rank) {
  using namespace C;
  asm volatile("setmaxnreg.inc.sync.aligned.u32 208;");
  int spin = 0;
  uint32_t wf[NKR][4];
  const int wu = uni((tid0 >> 5) & 3);
  const uint32_t slot = rank == 2 ? OFF_M : OFF_KT + rank * 16384;
  if (wu == 0) load_pair(sb, 0, rank, slot, 1, spin);
  mwait(sb + BAR_W, 0, spin);
  for (int it = tid0 & 127; it < 1280; it += 128) {
    const uint32_t base = sb + OFF_WK + (it >> 1) * 128;
    const int sw = ((it >> 1) & 7) ^ ((it & 1) * 4);
    const uint4 u0 = lds128(base + (sw << 4)), u1 = lds128(base + ((sw ^ 1) << 4)), u2 = lds128(base + ((sw ^ 2) << 4)), u3 = lds128(base + ((sw ^ 3) << 4));
    sts128(base + (sw << 4), make_uint4(u0.x, u1.x, u2.x, u3.x)); sts128(base + ((sw ^ 1) << 4), make_uint4(u0.y, u1.y, u2.y, u3.y));
    sts128(base + ((sw ^ 2) << 4), make_uint4(u0.z, u1.z, u2.z, u3.z)); sts128(base + ((sw ^ 3) << 4), make_uint4(u0.w, u1.w, u2.w, u3.w));
  }
  bar_sync(NB_RD, 128);
  load_weights_rs<false>(wf, sb, OFF_WK, OFF_YV, tid0);
#pragma unroll 1
  for (int i = 0; i < NSTEP; i++) {
    {
      float d[32];
      if (i > 0) CBAR_SYNC(NB_WV, 256);
#pragma unroll
      for (int p = 0; p < 5; p++) {
        mwait(sb + BAR_F + 8 * p, i & 1, spin);
        TS(i, 25 + p);
        wg_fence();
#pragma unroll
        for (int k = 8 * p; k < 8 * p + 8; k++) {
          if (k < NKR) wgmma_rs64(d, wf[k < NKR ? k : 0], tdesc(k), k);
          else wgmma_ts64(d, wdesc(OFF_YV + (k - NKR) * 2048), tdesc(k), 1);
          if (k == 8 * p + 1 && p >= 1 && p <= 3) {
            wg_commit(); wg_wait<1>();
            release_round(sb, p - 1, tid0 & 31);
          }
          if (k == 8 * p + RFK && (p == 1 || p == 2)) {
            wg_commit();
            if (rank == p - 1 && wu == 0) load_pair(sb, i, p + 2, slot_off(p + 2), i & 1, spin);
            wg_fence();
          }
        }
        wg_commit();
      }
      wg_wait<0>();
      TS(i, 23);
      CBAR_SYNC(NB_RD, 256);
      const int tid = fresh(tid0) & 127, m = (tid >> 3) & 3;
      if (tid < 8) mbar_expect_tx(sb + BAR_F + 8 * tid, tid < 5 ? 16384 : tid == 5 ? 2560 : tid == 6 ? 7168 : 4096);
      if (tid < 3 && tid != rank) mbar_arrive_cluster(mapa(sb, tid) + BAR_XF);
      const uint32_t a = sb + OFF_VT + 256 + ((tid >> 5) * 2 + (m & 1)) * VS + (m >> 1) * 640 + (tid & 7) * 16;
#pragma unroll
      for (int s = 0; s < 4; s++)
        stsm4(a + s * 128, pack_bf16(d[8 * s], d[8 * s + 1]), pack_bf16(d[8 * s + 2], d[8 * s + 3]),
              pack_bf16(d[8 * s + 4], d[8 * s + 5]), pack_bf16(d[8 * s + 6], d[8 * s + 7]));
      if (tid < 80) sts128(sb + (tid < 72 ? OFF_VT + (tid >> 3) * VS : OFF_PT + 1280) + (tid & 7) * 16, make_uint4(0, 0, 0, 0));
      fence_async();
    }
    mwait(sb + BAR_XF, i & 1, spin);
    CBAR_ARRIVE(NB_QK, 384);
    const uint32_t* xc = &g_cnt[CN_X + i + 1 - LAG][0];
    bool seen = NOWORK || i + 1 < LAG;
    if (wu == 0 && !seen) { seen = ld_acquire(xc) >= 32; fence_async_all(); }
    CBAR_SYNC(NB_QI, 256);
    float d[8];
    v_mem_pass<32, 40>(d, wf);
    CBAR_SYNC(NB_SM, 256);
    wg_wait<0>();
    if (__builtin_expect(lds32(sb + FLG_REDO), 0)) { v_mem_pass<32, 40>(d, wf); wg_wait<0>(); }
    if ((tid0 & 31) < 3 && (tid0 & 31) != rank) mbar_arrive_cluster(mapa(sb, tid0 & 31) + BAR_MF);
    v_mem_pass<0, 32>(d, wf);
    wg_wait<0>();
    TS(i, 24);
    const int tid = fresh(tid0);
    if ((tid & 31) == 0) mbar_arrive_cluster(mapa(sb, 2) + BAR_E + 16);
    store_mem<VS>(d, sb + OFF_VT + 128, tid);
    fence_async();
    CBAR_ARRIVE(NB_VA, 256);
    CBAR_ARRIVE(NB_VQ, 256);
    if (wu == 0 && i + 1 < NSTEP) {
      if (__builtin_expect(!seen, 0)) { while (ld_acquire(xc) < 32 && spin < SPIN_TOT) spin += 16; fence_async_all(); }
      load_pair(sb, i + 1, rank, slot, i & 1, spin);
      TS(i + 1, 37);
    }
    TS_FLUSH(i - 1);
    __syncwarp();
  }
  CBAR_ARRIVE(NB_WV, 256);
  if (spin >= SPIN_TOT) g_err = 3;
}

__device__ __forceinline__ float quad_max(float x) {
  const float a = __shfl_xor_sync(0xffffffffu, x, 1), b = __shfl_xor_sync(0xffffffffu, x, 2), c = __shfl_xor_sync(0xffffffffu, x, 3);
  return fmaxf(fmaxf(x, a), fmaxf(b, c));
}
__device__ __forceinline__ float quad_sum(float x) {
  const float a = __shfl_xor_sync(0xffffffffu, x, 1), b = __shfl_xor_sync(0xffffffffu, x, 2), c = __shfl_xor_sync(0xffffffffu, x, 3);
  return (x + a) + (b + c);
}
__device__ __forceinline__ float max10(const float (&y)[10]) {
  return fmaxf(fmaxf(fmaxf(fmaxf(y[0], y[1]), fmaxf(y[2], y[3])), fmaxf(fmaxf(y[4], y[5]), fmaxf(y[6], y[7]))), fmaxf(y[8], y[9]));
}
__device__ __forceinline__ float sum10(const float (&y)[10]) {
  return (((y[0] + y[1]) + (y[2] + y[3])) + ((y[4] + y[5]) + (y[6] + y[7]))) + (y[8] + y[9]);
}
__device__ __forceinline__ float rcp(float x) { float y; asm("rcp.approx.ftz.f32 %0,%1;" : "=f"(y) : "f"(x)); return y; }

__device__ __forceinline__ void signal_o(int i, int cta) { csignal(CN_O + i * 5 + min(cta / 19, 4)); }

__device__ __forceinline__ void chain_q(const CUtensorMap& tmWq, const CUtensorMap& tmWk, const uint32_t sb, const int tid0, const int cta, const int rank) {
  using namespace C;
  asm volatile("setmaxnreg.dec.sync.aligned.u32 96;");
  int spin = 0;
  CBAR_SYNC(NB_PRO, 384);
  PTS(5);
  if (tid0 == 128) {
    const int col = (cta / 3) * DH + rank * 64;
    mbar_expect_tx(sb + BAR_W, 163840);
    for (int i = 0; i < 5; i++) {
      tma2d(sb + OFF_WQ + i * 16384, &tmWq, col, i * 128, sb + BAR_W);
      tma2d(sb + OFF_WK + i * 16384, &tmWk, col, i * 128, sb + BAR_W);
    }
  }
  __syncwarp();
  mwait(sb + BAR_W, 1, spin);
  PTS(6);
  const int wu = uni((tid0 >> 5) & 3);
  uint4 ov[4] = {};
  uint8_t* op = &g_o[ORING - 1][cta][(tid0 & 124) * 32];
  const uint32_t o0 = ((tid0 ^ (tid0 >> 2)) & 3) * 16 + (tid0 & 16) * 4;
#pragma unroll 1
  for (int i = 0; i < NSTEP; i++) {
    const int ph = i & 1;
    uint32_t qf[4][4];
    {
      float d[64];
#define QK_STEP(K, SC) wgmma_st128(d, desc_at(mkdesc(SB0 + ((K) >> 2) * 1024 + ((K) & 3) * 32, 16, 2048), so), \
                                   desc_at(mkdesc(SB0 + OFF_WQ + (K) * 2048, OFF_WK - OFF_WQ, 1024), p * 16384), SC)
      int p = 0;
      uint32_t so = OFF_KT;
      mwait(sb + BAR_F, ph, spin);
      TS(i, 0);
      wg_fence();
#pragma unroll
      for (int k = 0; k < 8; k++) {
        QK_STEP(k, k);
        if (k == OST) {
          wg_commit();
          mwait(sb + BAR_F, ph, spin);
#pragma unroll
          for (int h = 0; h < 4; h++) stg128(op + (h & 1) * 4096 + (o0 ^ ((h >> 1) * 64)), ov[h]);
          if (i > 0) CBAR_ARRIVE(NB_MR, 160);
          if (k < 7) wg_fence();
        }
      }
      if (OST < 7) wg_commit();
#pragma unroll 1
      for (p = 1; p < 5; p++) {
        static_assert(OFF_KT - OFF_M == 5 << 12, "");
        so = OFF_M + (((0x95095u >> (4 * p)) & 15) << 12);
        mwait(sb + BAR_F + 8 * p, ph, spin);
        wg_fence();
#pragma unroll
        for (int k = 0; k < 8; k++) {
          QK_STEP(k, 1);
          if (k == 1) {
            wg_commit(); wg_wait<1>();
            release_round(sb, p - 1, p < 4 ? tid0 & 31 : 32);
          }
        }
        wg_commit();
      }
#undef QK_STEP
      wg_wait<0>();
      TS(i, 1);
      CBAR_SYNC(NB_RD, 256);
      TSB(i, 2);
      const int tid = fresh(tid0), w = (tid >> 5) & 3, m = (tid >> 3) & 3;
      const uint32_t a = sb + OFF_KT + (m >> 1) * KS + (1 + w + 5 * (m & 1)) * 128 + (tid & 7) * 16;
#pragma unroll
      for (int s = 0; s < 4; s++)
        stsm4t(a + s * 2 * KS, pack_bf16(d[32 + 8 * s], d[33 + 8 * s]), pack_bf16(d[34 + 8 * s], d[35 + 8 * s]),
               pack_bf16(d[36 + 8 * s], d[37 + 8 * s]), pack_bf16(d[38 + 8 * s], d[39 + 8 * s]));
      fence_async();
      CBAR_ARRIVE(NB_QK, 384);
#pragma unroll
      for (int kk = 0; kk < 4; kk++)
#pragma unroll
        for (int j = 0; j < 4; j++) asm volatile("{.reg .b32 t; cvt.rn.bf16x2.f32 t,%1,%2; mul.rn.bf16x2 %0,t,%3;}" : "=r"(qf[kk][j]) : "f"(d[8 * kk + 2 * j + 1]), "f"(d[8 * kk + 2 * j]), "r"(SCQ));
    }
    CBAR_SYNC(NB_SI, 256);
    uint32_t pf[5][4];
    {
      float y0[10], y1[10];
      const int tidf = fresh(tid0), lane = tidf & 31;
      {
        float x[40];
        wg_fence();
#pragma unroll
        for (int kk = 0; kk < 4; kk++) wgmma_rt80(x, qf[kk], mkdesc_ns(SB0 + OFF_KT + kk * 2 * KS, KS, 128), kk);
        wg_commit();
        wg_wait<0>();
#pragma unroll
        for (int j = 0; j < 5; j++) { y0[2 * j] = x[4 * j]; y0[2 * j + 1] = x[4 * j + 1]; y1[2 * j] = x[22 + 4 * j]; y1[2 * j + 1] = x[23 + 4 * j]; }
      }
      TS(i, 17);
      const uint32_t xo = OFF_XT + (wu * (wu + 3) / 2) * 256 + lane * 16, x2 = xo + (wu >> 1) * 512 + 512 - lane * 8;
      {
        const uint4 h0 = make_uint4(pack_h2(y0[0], y0[1]), pack_h2(y1[0], y1[1]), pack_h2(y0[2], y0[3]), pack_h2(y1[2], y1[3]));
        const uint4 h1 = make_uint4(pack_h2(y0[4], y0[5]), pack_h2(y1[4], y1[5]), pack_h2(y0[6], y0[7]), pack_h2(y1[6], y1[7]));
        const uint32_t h2 = wu == 1 ? h1.x : pack_h2(y0[8], y0[9]), h3 = wu == 1 ? h1.y : pack_h2(y1[8], y1[9]);
        const uint32_t rb1 = mapa(sb, (rank + 1) % 3), rb2 = mapa(sb, (rank + 2) % 3);
        st_async4u(rb1 + xo + 3584, h0, rb1 + BAR_XT);
        st_async4u(rb2 + xo, h0, rb2 + BAR_XT);
        if (wu >= 2) { st_async4u(rb1 + xo + 4096, h1, rb1 + BAR_XT); st_async4u(rb2 + xo + 512, h1, rb2 + BAR_XT); }
        if (wu & 1) { st_async2u(rb1 + x2 + 3584, h2, h3, rb1 + BAR_XT); st_async2u(rb2 + x2, h2, h3, rb2 + BAR_XT); }
      }
      TS(i, 18);
      const int lim = 8 * wu + (lane >> 2) + 8 - 2 * (lane & 3);
#pragma unroll
      for (int j = 2; j < 10; j++)
        if (8 * (j >> 1) + (j & 1) > lim) { y0[j] = -INFINITY; y1[j] = -INFINITY; }
      mwait(sb + BAR_XT, ph, spin);
      TS(i, 19);
      {
        const uint4 u0 = lds128(sb + xo), v0 = lds128(sb + xo + 3584);
        uint2 u2 = make_uint2(0, 0), v2 = u2;
        if (wu & 1) { u2 = lds64(sb + x2); v2 = lds64(sb + x2 + 3584); }
        uint4 u1 = make_uint4(u2.x, u2.y, 0, 0), v1 = make_uint4(v2.x, v2.y, 0, 0);
        if (wu >= 2) { u1 = lds128(sb + xo + 512); v1 = lds128(sb + xo + 4096); }
        __syncwarp();
        if (lane == 0) mbar_arrive_cluster(mapa(sb, 0) + BAR_E);
        add_h2(y0[0], y0[1], u0.x, v0.x); add_h2(y1[0], y1[1], u0.y, v0.y); add_h2(y0[2], y0[3], u0.z, v0.z); add_h2(y1[2], y1[3], u0.w, v0.w);
        add_h2(y0[4], y0[5], u1.x, v1.x); add_h2(y1[4], y1[5], u1.y, v1.y); add_h2(y0[6], y0[7], u1.z, v1.z); add_h2(y1[6], y1[7], u1.w, v1.w);
        add_h2(y0[8], y0[9], u2.x, v2.x); add_h2(y1[8], y1[9], u2.y, v2.y);
      }
      const float m0 = quad_max(max10(y0)) * -SCE, m1 = quad_max(max10(y1)) * -SCE;
#pragma unroll
      for (int j = 0; j < 5; j++) {
        pf[j >> 1][2 * (j & 1)] = pack_bf16(ex2(fmaf(y0[2 * j], SCE, m0)), ex2(fmaf(y0[2 * j + 1], SCE, m0)));
        pf[j >> 1][2 * (j & 1) + 1] = tidf >> (10 + j);
        pf[(j + 5) >> 1][2 * ((j + 5) & 1)] = tidf >> (20 + j);
        pf[(j + 5) >> 1][2 * ((j + 5) & 1) + 1] = pack_bf16(ex2(fmaf(y1[2 * j], SCE, m1)), ex2(fmaf(y1[2 * j + 1], SCE, m1)));
      }
    }
#pragma unroll
    for (int q = 0; q < 20; q++) pf[q >> 2][q & 3] = pin(pf[q >> 2][q & 3]);
    CBAR_SYNC(NB_VQ, 256);
    TSB(i, 20);
    {
      float o[32], sm[4];
      wg_fence();
#pragma unroll
      for (int q = 0; q < 5; q++) wgmma_rs8(sm, pf[q], mkdesc_ns(SB0 + OFF_ONE, 0, 0), q);
#pragma unroll
      for (int q = 0; q < 5; q++) wgmma_rs64(o, pf[q], mkdesc_ns(SB0 + OFF_VT + 128 + q * 256, 128, VS), q);
      wg_commit();
      const int tid = fresh(tid0);
      op = &g_o[i % ORING][cta][(tid & 124) * 32];
      wg_wait<0>();
      TS(i, 21);
      if ((tid & 31) == 0) mbar_arrive_cluster(mapa(sb, 1) + BAR_E + 8);
      const float s0 = rcp(sm[0]), s1 = rcp(sm[2]);
#pragma unroll
      for (int h = 0; h < 2; h++) {
        const float* x = o + 16 * h;
        ov[2 * h] = make_uint4(pin(pack_bf16(x[0] * s0, x[1] * s0)), pin(pack_bf16(x[4] * s0, x[5] * s0)), pin(pack_bf16(x[8] * s0, x[9] * s0)), pin(pack_bf16(x[12] * s0, x[13] * s0)));
        ov[2 * h + 1] = make_uint4(pin(pack_bf16(x[2] * s1, x[3] * s1)), pin(pack_bf16(x[6] * s1, x[7] * s1)), pin(pack_bf16(x[10] * s1, x[11] * s1)), pin(pack_bf16(x[14] * s1, x[15] * s1)));
      }
      TS(i, 22);
      if (i + 1 < NSTEP) CBAR_SYNC(NB_WQ, 256); else CBAR_ARRIVE(NB_WQ, 256);
    }
  }
#pragma unroll
  for (int h = 0; h < 4; h++) stg128(op + (h & 1) * 4096 + (o0 ^ ((h >> 1) * 64)), ov[h]);
  CBAR_SYNC(NB_Q, 128);
  if (tid0 == 224) signal_o(NSTEP - 1, cta);
  if (spin >= SPIN_TOT) g_err = 2;
}

template <int NL> __device__ __forceinline__ void poll(uint4 (&x)[NL], const uint8_t* mb, uint32_t tag, int& spin);
template <> __device__ __forceinline__ void poll<4>(uint4 (&x)[4], const uint8_t* mb, uint32_t tag, int& spin) {
  asm volatile("{.reg .pred p<6>, q; .reg .b128 v; .reg .b32 t;\n"
               " ld.relaxed.gpu.global.b128 v,[%17+0]; mov.b128 {%0,%1,%2,%3},v;\n"
               " ld.relaxed.gpu.global.b128 v,[%17+512]; mov.b128 {%4,%5,%6,%7},v;\n"
               " ld.relaxed.gpu.global.b128 v,[%17+1024]; mov.b128 {%8,%9,%10,%11},v;\n"
               " ld.relaxed.gpu.global.b128 v,[%17+1536]; mov.b128 {%12,%13,%14,%15},v;\n"
               "POLL_LOOP:\n add.s32 %16,%16,16;\n"
               " lop3.b32 t,%0,%18,1,0x28; setp.ne.b32 p0,t,0;\n"
               " lop3.b32 t,%4,%18,1,0x28; setp.ne.b32 p1,t,0;\n"
               " lop3.b32 t,%8,%18,1,0x28; setp.ne.b32 p2,t,0;\n"
               " lop3.b32 t,%12,%18,1,0x28; setp.ne.b32 p3,t,0;\n"
               " or.pred q,p0,p1; or.pred q,q,p2; or.pred q,q,p3; setp.lt.and.s32 q,%16,%19,q; vote.sync.any.pred q,q,0xffffffff;\n"
               " mov.b128 v,{%0,%1,%2,%3}; @p0 ld.relaxed.gpu.global.b128 v,[%17+0]; mov.b128 {%0,%1,%2,%3},v;\n"
               " mov.b128 v,{%4,%5,%6,%7}; @p1 ld.relaxed.gpu.global.b128 v,[%17+512]; mov.b128 {%4,%5,%6,%7},v;\n"
               " mov.b128 v,{%8,%9,%10,%11}; @p2 ld.relaxed.gpu.global.b128 v,[%17+1024]; mov.b128 {%8,%9,%10,%11},v;\n"
               " mov.b128 v,{%12,%13,%14,%15}; @p3 ld.relaxed.gpu.global.b128 v,[%17+1536]; mov.b128 {%12,%13,%14,%15},v;\n"
               " @q bra.uni POLL_LOOP;\n}"
               : "=&r"(x[0].x), "=&r"(x[0].y), "=&r"(x[0].z), "=&r"(x[0].w), "=&r"(x[1].x), "=&r"(x[1].y), "=&r"(x[1].z), "=&r"(x[1].w), "=&r"(x[2].x), "=&r"(x[2].y), "=&r"(x[2].z), "=&r"(x[2].w), "=&r"(x[3].x), "=&r"(x[3].y), "=&r"(x[3].z), "=&r"(x[3].w), "+&r"(spin)
               : "l"(mb), "r"(tag), "n"(SPIN_TOT) : "memory");
}
template <> __device__ __forceinline__ void poll<6>(uint4 (&x)[6], const uint8_t* mb, uint32_t tag, int& spin) {
  asm volatile("{.reg .pred p<6>, q; .reg .b128 v; .reg .b32 t;\n"
               " ld.relaxed.gpu.global.b128 v,[%25+0]; mov.b128 {%0,%1,%2,%3},v;\n"
               " ld.relaxed.gpu.global.b128 v,[%25+512]; mov.b128 {%4,%5,%6,%7},v;\n"
               " ld.relaxed.gpu.global.b128 v,[%25+1024]; mov.b128 {%8,%9,%10,%11},v;\n"
               " ld.relaxed.gpu.global.b128 v,[%25+1536]; mov.b128 {%12,%13,%14,%15},v;\n"
               " ld.relaxed.gpu.global.b128 v,[%25+2048]; mov.b128 {%16,%17,%18,%19},v;\n"
               " ld.relaxed.gpu.global.b128 v,[%25+2560]; mov.b128 {%20,%21,%22,%23},v;\n"
               "POLL_LOOP:\n add.s32 %24,%24,16;\n"
               " lop3.b32 t,%0,%2,%26,0x7e; and.b32 t,t,1; setp.ne.b32 p0,t,0;\n"
               " lop3.b32 t,%4,%6,%26,0x7e; and.b32 t,t,1; setp.ne.b32 p1,t,0;\n"
               " lop3.b32 t,%8,%10,%26,0x7e; and.b32 t,t,1; setp.ne.b32 p2,t,0;\n"
               " lop3.b32 t,%12,%14,%26,0x7e; and.b32 t,t,1; setp.ne.b32 p3,t,0;\n"
               " lop3.b32 t,%16,%18,%26,0x7e; and.b32 t,t,1; setp.ne.b32 p4,t,0;\n"
               " lop3.b32 t,%20,%22,%26,0x7e; and.b32 t,t,1; setp.ne.b32 p5,t,0;\n"
               " or.pred q,p0,p1; or.pred q,q,p2; or.pred q,q,p3; or.pred q,q,p4; or.pred q,q,p5; setp.lt.and.s32 q,%24,%27,q; vote.sync.any.pred q,q,0xffffffff;\n"
               " mov.b128 v,{%0,%1,%2,%3}; @p0 ld.relaxed.gpu.global.b128 v,[%25+0]; mov.b128 {%0,%1,%2,%3},v;\n"
               " mov.b128 v,{%4,%5,%6,%7}; @p1 ld.relaxed.gpu.global.b128 v,[%25+512]; mov.b128 {%4,%5,%6,%7},v;\n"
               " mov.b128 v,{%8,%9,%10,%11}; @p2 ld.relaxed.gpu.global.b128 v,[%25+1024]; mov.b128 {%8,%9,%10,%11},v;\n"
               " mov.b128 v,{%12,%13,%14,%15}; @p3 ld.relaxed.gpu.global.b128 v,[%25+1536]; mov.b128 {%12,%13,%14,%15},v;\n"
               " mov.b128 v,{%16,%17,%18,%19}; @p4 ld.relaxed.gpu.global.b128 v,[%25+2048]; mov.b128 {%16,%17,%18,%19},v;\n"
               " mov.b128 v,{%20,%21,%22,%23}; @p5 ld.relaxed.gpu.global.b128 v,[%25+2560]; mov.b128 {%20,%21,%22,%23},v;\n"
               " @q bra.uni POLL_LOOP;\n}"
               : "=&r"(x[0].x), "=&r"(x[0].y), "=&r"(x[0].z), "=&r"(x[0].w), "=&r"(x[1].x), "=&r"(x[1].y), "=&r"(x[1].z), "=&r"(x[1].w), "=&r"(x[2].x), "=&r"(x[2].y), "=&r"(x[2].z), "=&r"(x[2].w), "=&r"(x[3].x), "=&r"(x[3].y), "=&r"(x[3].z), "=&r"(x[3].w), "=&r"(x[4].x), "=&r"(x[4].y), "=&r"(x[4].z), "=&r"(x[4].w), "=&r"(x[5].x), "=&r"(x[5].y), "=&r"(x[5].z), "=&r"(x[5].w), "+&r"(spin)
               : "l"(mb), "r"(tag), "n"(SPIN_TOT) : "memory");
}
template <int NL>
__device__ __forceinline__ void poll_add(const uint8_t* mb, uint32_t tag, float (&f)[8], uint8_t* flag, bool lead, int& spin) {
  uint4 x[NL];
  poll<NL>(x, mb, tag, spin);
  if (FLP == 0 && lead) st_relaxed(flag, 0);
#pragma unroll
  for (int i = 0; i < NL; i++) {
    const uint32_t u[4] = {x[i].x, x[i].y, x[i].z, x[i].w};
#pragma unroll
    for (int j = 0; j < 4; j++) {
      if (i == 0) { f[2 * j] = bf_lo(u[j]); f[2 * j + 1] = bf_hi(u[j]); }
      else { f[2 * j] += bf_lo(u[j]); f[2 * j + 1] += bf_hi(u[j]); }
    }
  }
}

template <int B, int SLOT>
__device__ __forceinline__ void wo_step(float (&acc)[8], const uint32_t (&wf)[C::NKR][4], int kk) {
  using namespace C;
  const int k = 4 * B + kk;
  const uint64_t db = mkdesc_ns(SB0 + og_off(SLOT) + kk * 512, 256, 128);
  if (k < NKR) wgmma_rt16(acc, wf[k < NKR ? k : 0], db, SLOT | kk);
  else wgmma_tt16(acc, wdesc(OFF_YO + (k - NKR) * 2048), db, 1);
}
template <int B, int SLOT>
__device__ __forceinline__ void wo_block(float (&acc)[8], const uint32_t (&wf)[C::NKR][4]) {
#pragma unroll
  for (int kk = 0; kk < 4; kk++) wo_step<B, SLOT>(acc, wf, kk);
}
template <int B, int SLOT>
__device__ __forceinline__ void wo_block2(float (&acc0)[8], float (&acc1)[8], const uint32_t (&wf)[C::NKR][4]) {
#pragma unroll
  for (int kk = 0; kk < 4; kk++) { wo_step<B, SLOT>(acc0, wf, kk); wo_step<B + 3, SLOT>(acc1, wf, kk); }
}

__device__ __forceinline__ void chain_a(const uint32_t sb, const int tid0, const int cta, const int rank) {
  using namespace C;
  asm volatile("setmaxnreg.inc.sync.aligned.u32 200;");
  int spin = 0;
  uint32_t wf[NKR][4];
  mwait(sb + BAR_W, 0, spin);
  permute_cols(sb + OFF_WQ, tid0, 2560);
  CBAR_SYNC(NB_A, 128);
  load_weights_rs<true>(wf, sb, OFF_WQ, OFF_YO, tid0);
  const int wu = uni(tid0 >> 5);
  const bool t9 = cta >= 72 && cta < 88;
  const uint64_t exa = reinterpret_cast<uint64_t>(ex_window(g_ex));
  const uint32_t ehi = (uint32_t)(exa >> 32), elo = (uint32_t)exa;

#pragma unroll 1
  for (int i = -1; i < NSTEP; i++) {
    const int ph = i & 1;
    if (i >= 0) {
      const int tid = fresh(tid0);
      const uint32_t mo = __shfl_xor_sync(0xffffffffu, elo + (ph << 20) + ((rank * 24 + (tid >> 4)) * 4 + (tid & 3)) * 2048 + (cta / 3) * 64 + (tid & 12) * 4, 0);
      const uint32_t m9 = __shfl_xor_sync(0xffffffffu, elo + (ph << 20) + MAIL9 + (((tid >> 4) * 2 + (tid & 1)) * 4 + (tid & 2)) * 3072 + cta * 32 + (tid & 12) * 2, 0);
      const uint32_t oo = __shfl_xor_sync(0xffffffffu, (tid >> 5) * 512 + (tid & 2) * 64 + (tid & 28) * 4 + (tid & 1) * 8, 0);
      if (i == 0) mwait(sb + BAR_W, 1, spin);
      mwait(sb + BAR_M, ph, spin);
      TS(i, 3);
      {
        float x[20];
        int redo = 0;
      retry:
        bool bad;
        {
          float dq[8] = {}, dk[8] = {};
#pragma unroll 1
          for (int k0 = 0; k0 < 40; k0 += P1U) {
            wg_fence();
#pragma unroll
            for (int k = 0; k < P1U; k++) {
              if (k == P1U - QIE / 2 && k0 == 40 - P1U && !redo) CBAR_ARRIVE(NB_QI, 256);
              const uint64_t db = desc_at(mdesc(k), k0 * 512);
              wgmma_ts16(dq, desc_at(wdesc(OFF_WQ + k * 2048), k0 * 2048), db, 1);
              wgmma_ts16(dk, desc_at(wdesc(OFF_WK + k * 2048), k0 * 2048), db, 1);
            }
            wg_commit();
          }
          const int m = (tid >> 3) & 3, dg = (tid >> 5) * 2 + (m & 1);
          const uint32_t ka = sb + OFF_KT + dg * KS + (m >> 1) * 640 + (tid & 7) * 16;
          if (!redo) CBAR_SYNC(NB_QK, 384);
          sts32(sb + FLG_REDO, redo);
          wg_wait<0>();
          TS(i, 4);
          stsm4(ka, pack_bf16(dk[0], dk[1]), pack_bf16(dk[2], dk[3]), pack_bf16(dk[4], dk[5]), pack_bf16(dk[6], dk[7]));
          stsm4(ka + dg * (VS - KS) + (OFF_VT + 128 - OFF_KT), scale_bf16x2(pack_bf16(dq[0], dq[1]), SCQ), scale_bf16x2(pack_bf16(dq[2], dq[3]), SCQ),
                scale_bf16x2(pack_bf16(dq[4], dq[5]), SCQ), scale_bf16x2(pack_bf16(dq[6], dq[7]), SCQ));
          const float chk = (dq[0] + dq[1]) + (dq[4] + dq[5]);
          fence_async();
          bad = bar_red_or(NB_C, 128, chk != chk && !redo);
        }
        TSB(i, 5);
        wg_fence();
#pragma unroll
        for (int kk = 0; kk < 4; kk++) wgmma_tt40(x, mkdesc_ns(SB0 + OFF_VT + 128 + kk * 2 * VS, VS, 640), mkdesc_ns(SB0 + OFF_KT + kk * 2 * KS, KS, 128), kk);
#pragma unroll
        for (int kk = 0; kk < 4; kk++) {
          if (SIE && kk == 4 - SIE && !bad) CBAR_ARRIVE(NB_SI, 256);
          wgmma_tt40(x, mkdesc_ns(SB0 + OFF_VT + kk * 2 * VS, VS, 384), mkdesc_ns(SB0 + OFF_KT + 640 + kk * 2 * KS, KS, 128), 1);
        }
        wg_commit();
        if (!SIE && !bad) CBAR_ARRIVE(NB_SI, 256);
        if (__builtin_expect(__any_sync(0xffffffffu, bad), 0)) {
          wg_wait<0>();
#pragma unroll 1
          for (int k = 0; k < 10; k++) {
            uint4 v = lds128(sb + OFF_M + tid * 16 + k * 2048);
            if (v.x == SENT || v.y == SENT || v.z == SENT || v.w == SENT) {
              do { v = ld_relaxed4(mkptr(elo + EX_M + i * 20480 + tid * 16 + k * 2048, ehi)); spin += 16; } while ((v.x == SENT || v.y == SENT || v.z == SENT || v.w == SENT) && spin < SPIN_TOT);
              sts128(sb + OFF_M + tid * 16 + k * 2048, v);
            }
          }
          fence_async();
          bar_sync(NB_C, 128);
          redo = fresh(1);
          goto retry;
        }
        TSV(i, 36, redo);
        const uint32_t rb1 = mapa(sb, (rank + 1) % 3), rb2 = mapa(sb, (rank + 2) % 3);
        wg_wait<0>();
        TS(i, 6);
        if (wu < 2) {
          float y[10];
#pragma unroll
          for (int j = 0; j < 5; j++) { y[2 * j] = x[4 * j]; y[2 * j + 1] = x[4 * j + 1]; }
          const uint4 h0 = make_uint4(pack_h2(y[0], y[1]), pack_h2(y[2], y[3]), pack_h2(y[4], y[5]), pack_h2(y[6], y[7]));
          const uint32_t h1 = pack_h2(y[8], y[9]);
          st_async4u(rb1 + OFF_XM + 1024 + tid * 16, h0, rb1 + BAR_XM);
          st_async4u(rb2 + OFF_XM + tid * 16, h0, rb2 + BAR_XM);
          st_async1u(rb1 + OFF_XM + 2304 + tid * 4, h1, rb1 + BAR_XM);
          st_async1u(rb2 + OFF_XM + 2048 + tid * 4, h1, rb2 + BAR_XM);
          CBAR_ARRIVE(NB_SM, 256);
          if ((tid & 31) == 0) mbar_arrive_cluster(mapa(sb, 0) + BAR_E);
          TS(i, 7);
          const uint32_t sw = (tid & 7) * 4 + (tid & 8) * 8 + (tid & 16) * 2;
          mwait(sb + BAR_XM, ph, spin);
          TS(i, 8);
          const uint4 u0 = lds128(sb + OFF_XM + tid * 16), v0 = lds128(sb + OFF_XM + 1024 + tid * 16);
          const uint32_t u1 = lds32(sb + OFF_XM + 2048 + tid * 4), v1 = lds32(sb + OFF_XM + 2304 + tid * 4);
          add_h2(y[0], y[1], u0.x, v0.x); add_h2(y[2], y[3], u0.y, v0.y); add_h2(y[4], y[5], u0.z, v0.z); add_h2(y[6], y[7], u0.w, v0.w);
          add_h2(y[8], y[9], u1, v1);
          const float mx = quad_max(max10(y)) * -SCE;
#pragma unroll
          for (int j = 0; j < 5; j++) {
            y[2 * j] = ex2(fmaf(y[2 * j], SCE, mx)); y[2 * j + 1] = ex2(fmaf(y[2 * j + 1], SCE, mx));
            sts32(sb + OFF_PT + wu * 640 + sw + j * 128, pack_bf16(y[2 * j], y[2 * j + 1]));
          }
          sts32(sb + OFF_XM + 2048 + wu * 128 + sw, __float_as_uint(sum10(y)));
          fence_async();
          TS(i, 9);
        } else {
          CBAR_ARRIVE(NB_SM, 256);
          if ((tid & 31) == 0) mbar_arrive_cluster(mapa(sb, 0) + BAR_E);
          mwait(sb + BAR_MF, ph, spin);
        }
      }
      CBAR_SYNC(NB_VA, 256);
      TSB(i, 10);
      {
        float o[2][4];
        wg_fence();
#pragma unroll
        for (int c = 0; c < 2; c++)
#pragma unroll
          for (int q = 0; q < 3; q++)
            wgmma_ss8(o[c], mkdesc_ns(SB0 + OFF_VT + 128 + c * 640 + q * 256, 128, VS), mkdesc_ns(SB0 + OFF_PT + c * 640 + q * 256, q == 2 && c == 0 ? 768 : 128, 128), q);
        wg_commit();
        const float4 e = lds128f(sb + OFF_XM + 2048 + (tid & 15) * 16);
        const uint32_t rb1 = mapa(sb, (rank + 1) % 3), rb2 = mapa(sb, (rank + 2) % 3);
        const float inv = rcp((e.x + e.y) + (e.z + e.w));
        const int sl = (tid & 3) * 2;
        const float i0 = __shfl_sync(0xffffffffu, inv, sl), i1 = __shfl_sync(0xffffffffu, inv, sl + 1);
        const float i2 = __shfl_sync(0xffffffffu, inv, sl + 8), i3 = __shfl_sync(0xffffffffu, inv, sl + 9);
        wg_wait<0>();
        TS(i, 11);
        const uint32_t p0 = pack_bf16(o[0][0] * i0, o[0][1] * i1), p1 = pack_bf16(o[1][0] * i2, o[1][1] * i3);
        const uint32_t p2 = pack_bf16(o[0][2] * i0, o[0][3] * i1), p3 = pack_bf16(o[1][2] * i2, o[1][3] * i3);
        if (OGF) { sts64(sb + oo + og_off(0), p0, p1); sts64(sb + oo + og_off(0) + 256, p2, p3); fence_async(); }
        st_async2u(rb1 + oo + og_off(2), p0, p1, rb1 + BAR_OG);
        st_async2u(rb2 + oo + og_off(1), p0, p1, rb2 + BAR_OG);
        st_async2u(rb1 + oo + og_off(2) + 256, p2, p3, rb1 + BAR_OG);
        st_async2u(rb2 + oo + og_off(1) + 256, p2, p3, rb2 + BAR_OG);
        if (!OGF) { sts64(sb + oo + og_off(0), p0, p1); sts64(sb + oo + og_off(0) + 256, p2, p3); fence_async(); }
      }
      CBAR_SYNC(NB_A, 128);
      TSB(i, 12);
      {
        float acc[3][8];
        wg_fence();
        wo_block<0, 0>(acc[2], wf);
        wg_commit();
        if (tid == 0) mbar_arrive_cluster(mapa(sb, 1) + BAR_E + 8);
        wo_block2<1, 0>(acc[0], acc[1], wf);
        wg_commit();
        const bool og = mbar_try(sb + BAR_OG, ph);
        const uint32_t tag = (i >> 1) & 1;
#define TAGGED(LO, HI) ((pack_bf16(LO, HI) & ~1u) | tag)
#define SEND(OFF, U) st_relaxed128(mkptr(mo, ehi) + (OFF), TAGGED(acc[U][0], acc[U][2]), pack_bf16(acc[U][1], acc[U][3]), pack_bf16(acc[U][4], acc[U][6]), pack_bf16(acc[U][5], acc[U][7]))
        wg_wait<1>();
        const uint32_t n0 = pin(TAGGED(acc[2][0], acc[2][2])), n1 = pin(pack_bf16(acc[2][1], acc[2][3]));
        const uint32_t n2 = pin(TAGGED(acc[2][4], acc[2][6])), n3 = pin(pack_bf16(acc[2][5], acc[2][7]));
        if (__builtin_expect(!og, 0)) mwait(sb + BAR_OG, ph, spin);
        asm volatile("fence.proxy.async::generic.acquire.sync_restrict::shared::cluster.cluster;" ::: "memory");
        TS(i, 13);
        wg_fence();
        wo_block2<2, 1>(acc[0], acc[1], wf);
        st_relaxed64(mkptr(m9, ehi), n0, n1);
        st_relaxed64(mkptr(m9, ehi) + 3072, n2, n3);
        wo_block2<3, 2>(acc[0], acc[1], wf);
        wg_commit();
        wo_block<7, 0>(acc[2], wf);
        wg_commit();
        wg_wait<1>(); SEND(0, 0);
        wo_block<8, 1>(acc[2], wf);
        SEND(32 * 2048, 1);
        wo_block<9, 2>(acc[2], wf);
        wg_commit();
        if (WOE == 0) { CBAR_ARRIVE(NB_WV, 256); CBAR_ARRIVE(NB_WQ, 256); }
        if (WOE == 1) CBAR_ARRIVE(NB_WV, 256);
        wg_wait<0>(); SEND(64 * 2048, 2);
        if (WOE == 2) CBAR_ARRIVE(NB_WV, 256);
        if (WOE >= 1) CBAR_ARRIVE(NB_WQ, 256);
#undef SEND
#undef TAGGED
      }
      TS(i, 14);
      if (i + 1 >= NSTEP) break;
    }
    uint32_t t1 = clk32();
    if (i >= 0) {
      const int lane = fresh(tid0) & 31, j = lane >> 3;
      const uint8_t* mb = mkptr(elo + (ph << 20) + (t9 ? MAIL9 + (cta - 72) * 12288 + wu * 3072 : (cta < 72 ? cta : cta - 24) * 8192 + wu * 2048) + lane * 16, ehi);
      const uint32_t tag = (i >> 1) & 1;
      const bool pub = (lane & (t9 ? 6 : 4)) == 0 && !(((t9 ? cta : wu) & 1) && i + 1 == LAG) && cta < 88;
      const uint32_t dst = pin(elo + EX_M + (i + 1) * 20480 + (t9 ? (cta + 72) * 128 + wu * 32 + (j & 1) * 16 + (lane & 1) * 8 + (j >> 1) * 4
                                                                   : cta * 256 + (wu & 1) * 128 + (wu >> 1) * 64 + j * 16 + (lane & 3) * 4));
      uint8_t* flag = mkptr(elo + EX_FLAG + (i + 1) * 3072 + cta * 32 + wu * 4, ehi);
      while (clk32() - t1 < B1) {}
      TS(i + 1, 30);
      float f[8];
      const int n0 = spin;
      if (!t9) poll_add<4>(mb, tag, f, flag, lane == 0, spin);
      else poll_add<6>(mb, tag, f, flag, lane == 0, spin);
      if (FLP == 1 && lane == 0) st_relaxed(flag, __float_as_uint(f[0] + f[7]) >> 1);
      t1 = clk32();
      TS(i + 1, 31); TSV(i + 1, 32, (spin - n0) >> 4);
      const bool h = lane & 16, q = lane & 8;
#pragma unroll
      for (int j = 0; j < 4; j++) f[j] = (h ? f[4 + j] : f[j]) + __shfl_xor_sync(0xffffffffu, h ? f[j] : f[4 + j], 16);
#pragma unroll
      for (int j = 0; j < 2; j++) f[j] = (q ? f[2 + j] : f[j]) + __shfl_xor_sync(0xffffffffu, q ? f[j] : f[2 + j], 8);
      f[0] += __shfl_xor_sync(0xffffffffu, f[0], 4); f[1] += __shfl_xor_sync(0xffffffffu, f[1], 4);
      if (t9) { f[0] += __shfl_xor_sync(0xffffffffu, f[0], 2); f[1] += __shfl_xor_sync(0xffffffffu, f[1], 2); }
      if (pub) st_relaxed(mkptr(dst, ehi), pack_bf16(f[0], f[1]));
      if (FLP == 2 && lane == 0) st_relaxed(flag, 0);
      if (wu == 3) {
        CBAR_SYNC(NB_MR, 160);
        if (elect_one()) signal_o(i, cta);
      }
      TS(i + 1, 15);
    }
    if (wu == 0) {
      const int tid = fresh(tid0);
      const uint8_t* pp = mkptr(elo + EX_FLAG + (i + 1) * 3072 + (rank * 28 + (tid < 28 || rank == 2 ? tid : 0)) * 32, ehi);
      while (clk32() - t1 < B2) {}
      TS(i + 1, 16);
      int n = 1;
      uint4 x = ld_relaxed4(pp);
      if (tid0 == 0) mbar_expect_tx(sb + BAR_M, 20480);
      bool mok = mbar_test(sb + BAR_MOK, ph ^ 1);
      while (__any_sync(0xffffffffu, (int)(x.x | x.y | x.z | x.w) < 0 && spin < SPIN_TOT)) { x = ld_relaxed4(pp); mok = mbar_test(sb + BAR_MOK, ph ^ 1); n++; spin += 16; }
      if (!mok) mwait(sb + BAR_MOK, ph ^ 1, spin);
      TSV(i + 1, 35, n);
      TS(i + 1, 34);
      if (elect_one()) bulk_g2s_mc(sb + OFF_M + rank * 7168, mkptr(elo + EX_M + (i + 1) * 20480 + rank * 7168, ehi), rank == 2 ? 6144 : 7168, sb + BAR_M);
      TS(i + 1, 33);
      __syncwarp();
    }
  }
  if (spin >= SPIN_TOT) g_err = 1;
}

__global__ void __cluster_dims__(3, 1, 1) __launch_bounds__(384, 1)
k_chain(const __grid_constant__ CUtensorMap tmWq, const __grid_constant__ CUtensorMap tmWk,
        const __grid_constant__ CUtensorMap tmWv, const __grid_constant__ CUtensorMap tmWo) {
  using namespace C;
  extern __shared__ __align__(1024) uint8_t smem[];
  const uint32_t sb = smem_u32(smem);
  const int tid = threadIdx.x;
  const int wg = __shfl_sync(0xffffffffu, tid >> 7, 0);
  const int cta = uni(blockIdx.x), rank = uni(blockIdx.x % 3);

  asm volatile("griddepcontrol.launch_dependents;");
  if (tid == 0) {
    if ((sb & 0xFFFFFF) != SB0) g_err = 100;
    for (int p = 0; p < 5; p++) { mbar_init(sb + BAR_F + 8 * p, 1); mbar_init(sb + BAR_E + 8 * p, p == 2 ? 12 : p == 1 ? 15 : 24); }
    mbar_init(sb + BAR_M, 1); mbar_init(sb + BAR_MOK, 24); mbar_init(sb + BAR_XM, 1); mbar_init(sb + BAR_XF, 2);
    mbar_init(sb + BAR_XT, 1); mbar_init(sb + BAR_MF, 8); mbar_init(sb + BAR_OG, 1); mbar_init(sb + BAR_W, 1);
    for (int p = 0; p < 5; p++) mbar_expect_tx(sb + BAR_F + 8 * p, 16384);
    for (int p = 0; p < 16; p++) sts32(sb + OFF_SAFE + 4 * p, 0);
    for (int p = 0; p < 32; p++) sts32(sb + OFF_ONE + 4 * p, 0x3F803F80);
    asm volatile("fence.mbarrier_init.release.cluster;" ::: "memory");
    fence_async();
    mbar_expect_tx(sb + BAR_W, 163840);
    const int head = cta / 3, col = head * DH + rank * 64;
    tma2d(sb + OFF_WQ, &tmWo, 576, col, sb + BAR_W);
    for (int i = 0; i < 9; i++) tma2d(sb + OFF_WQ + (i + 1) * 8192, &tmWo, (3 * rank + i / 3) * 64, head * DH + ((rank + i) % 3) * 64, sb + BAR_W);
    for (int i = 0; i < 5; i++) tma2d(sb + OFF_WK + i * 16384, &tmWv, col, i * 128, sb + BAR_W);
  }
  __syncthreads();
  asm volatile("barrier.cluster.arrive.release.aligned;" ::: "memory");
  asm volatile("barrier.cluster.wait.acquire.aligned;" ::: "memory");

  if (wg == 0) chain_a(sb, keep(tid), cta, rank);
  else if (wg == 1) chain_q(tmWq, tmWk, sb, keep(tid), cta, rank);
  else chain_v(sb, keep(tid), cta, rank);
  asm volatile("barrier.cluster.arrive.release.aligned;" ::: "memory");
  asm volatile("barrier.cluster.wait.acquire.aligned;" ::: "memory");
}

namespace W {
constexpr int NP = 25, NBC = 11, NW = NP + NBC;
constexpr int PRS = 37, PW = 43 * 2048;
constexpr int OFF_W = 0;
constexpr int OFF_R = 2 * PW;
constexpr int QRS = 35, KRS = 37;
constexpr int OFF_WV = 0, OFF_YQ = 81920, OFF_YK = OFF_YQ + (40 - QRS) * 2048, OFF_WO = OFF_YK + (40 - KRS) * 2048;
constexpr int OFF_G = OFF_WO + 39 * 2048;
constexpr int OFF_X = OFF_G + 12288;
constexpr int COL = 976;
constexpr int OFF_T = OFF_X + 8192;
constexpr int OFF_H = OFF_X + 32768;
constexpr int OFF_BAR = OFF_H + 8 * COL;
constexpr int OFF_SAFE = OFF_BAR + 192;
constexpr int SMEM = 232448;
static_assert(OFF_SAFE + 64 <= SMEM && OFF_R + 40960 <= OFF_BAR, "");
constexpr uint32_t SB0 = 1024;
constexpr int BAR_F = OFF_BAR, BAR_E = OFF_BAR + 40, BAR_G = OFF_BAR + 80, BAR_H = OFF_BAR + 120, BAR_W = OFF_BAR + 160;
constexpr int NB_G0 = 1, NB_SG = 4, NB_B = 5, NB_AS = 6, NB_PK = 8, NB_PV = 9, NB_TD = 10;
}
#define PFW 1
#define WOP 0
#define WBAR_SYNC(id, n) bar_sync(id, n)
#define WBAR_ARRIVE(id, n) bar_arrive(id, n)

__device__ __forceinline__ uint64_t rdesc(int off, int kk) { return mkdesc(W::SB0 + off + kk * 32, 16, 1024); }
__device__ __forceinline__ uint32_t frag_addr(uint32_t base, int tid) {
  const int i = (tid >> 3) & 3, r = tid & 7;
  return base + (r + (i >> 1) * 8) * 128 + (((2 * ((tid >> 5) & 3) + (i & 1)) ^ r) << 4);
}
template <int NK>
__device__ __forceinline__ void load_frags(uint32_t (&wf)[NK][4], uint32_t base, int tid) {
  const uint32_t a0 = frag_addr(base, tid);
#pragma unroll
  for (int k = 0; k < NK; k++) ldsm4t(wf[k], a0 + k * 2048);
}
__device__ __forceinline__ void red_tile(const float* d, int seg, int col0, int tid) {
  float* p = g_x + (size_t)(seg * 32 + 2 * (tid & 3)) * DM + col0 + ((tid >> 5) & 3) * 16 + ((tid >> 2) & 7) * 2;
#pragma unroll
  for (int j = 0; j < 8; j++)
    asm volatile("red.relaxed.gpu.global.add.v2.f32 [%0],{%1,%2};" ::"l"(p + ((j >> 1) * 8 + (j & 1)) * DM), "f"(d[4 * (j >> 1) + (j & 1)]), "f"(d[4 * (j >> 1) + 2 + (j & 1)]) : "memory");
}
#define FOR_SEGS(l, s)                                            \
  for (int j_ = 0; j_ < 2 * NSTEP; j_++) {                        \
    const int l = j_ & 1, s = (j_ >> 1) - l * LAG;                \
    if (s < 0 || s >= NSEG) continue;

template <int WG>
__device__ __forceinline__ void work_p(const CUtensorMap& tmWo, uint32_t sb, int pc, int tid0) {
  using namespace W;
  asm volatile("setmaxnreg.inc.sync.aligned.u32 208;");
  int spin = 0;
  const int ks = pc / 5, col0 = (pc % 5) * 128 + WG * 64;
  const uint32_t wb = sb + OFF_W + WG * PW;
  uint32_t wf[PRS][4];
#pragma unroll 1
  for (int hf = 0; hf < 2; hf++) {
    const int nk = hf ? 80 - PRS : PRS;
    if ((tid0 & 127) == 0) {
      mbar_expect_tx(sb + BAR_W + 8 * WG, nk * 2048);
      for (int i = 0; i < nk; i++) tma2d(wb + i * 2048, &tmWo, col0, ks * 19 * 64 + (i < PRS ? 2 * i + hf : PRS + i) * 16, sb + BAR_W + 8 * WG);
    }
    __syncwarp();
    mwait(sb + BAR_W + 8 * WG, hf, spin);
    permute_cols(wb, tid0 & 127, nk * 64);
    if (hf == 1 && ks < 4) for (int it = 39 * 64 + (tid0 & 127) - 64; it < 43 * 64; it += 128) {
      const uint32_t a = wb + (it >> 2) * 128 + (((2 * (it & 3)) ^ ((it >> 2) & 6)) << 4);
      if (it >= 39 * 64) { sts128(a, make_uint4(0, 0, 0, 0)); sts128(a + 16, make_uint4(0, 0, 0, 0)); }
    }
    fence_async();
    WBAR_SYNC(NB_G0 + WG, 128);
    if (hf == 0) {
      load_frags<PRS>(wf, wb, tid0);
      fence_async();
      WBAR_SYNC(NB_G0 + WG, 128);
    }
  }
#pragma unroll 1
  for (int k = 0; k < NSTEP; k++) {
    float d[32];
#pragma unroll
    for (int f = 0; f < 20; f++) {
      mwait(sb + BAR_F + 8 * (f % 5), (f / 5) & 1, spin);
      if (f == 0 && WG == 0 && pc == WW) WTS(k, 1);
      wg_fence();
#pragma unroll
      for (int kk = 0; kk < 4; kk++) {
        const int q = 4 * f + kk;
        if (q < 2 * PRS && !(q & 1)) wgmma_rs64(d, wf[q < 2 * PRS ? q >> 1 : 0], rdesc(OFF_R + (f % 5) * 8192, kk), q);
        else wgmma_ts64(d, mkdesc(SB0 + OFF_W + WG * PW + (q < 2 * PRS ? q >> 1 : q - PRS) * 2048, 8192, 1024), rdesc(OFF_R + (f % 5) * 8192, kk), 1);
        if (kk == 0 && f > 0) {
          wg_commit();
          wg_wait<1>();
          if ((tid0 & 31) == 0) mbar_arrive(sb + BAR_E + 8 * ((f - 1) % 5));
        }
      }
      wg_commit();
    }
    wg_wait<0>();
    if ((tid0 & 31) == 0) mbar_arrive(sb + BAR_E + 32);
    if (WG == 0 && pc == WW) WTS(k, 2);
    if (k < NSEG) red_tile(d, k, col0, tid0);
    if (k >= LAG) red_tile(d + 16, k - LAG, col0, tid0);
    if (WG == 0 && pc == WW) WTS(k, 13);
    WBAR_SYNC(NB_SG, 256);
    if (WG == 0) { if (tid0 == 0) csignal_t(CN_P + k, 3); __syncwarp(); }
  }
  if (spin >= SPIN_TOT) g_err = 11;
}
__device__ __forceinline__ void work_p_producer(uint32_t sb, int pc, int odd) {
  using namespace W;
  int spin = 0;
  const int ks = pc / 5;
#pragma unroll 1
  for (int k = 0; k < NSTEP; k++) {
    const uint32_t lo = k < NSEG ? 0 : 4096, len = k < LAG || k >= NSEG ? 4096 : 8192;
    const uint8_t* src = &g_o[k % ORING][ks * 19 + odd][lo];
    cwait(CN_O + k * 5 + ks, ks == 4 ? 20 : 19, spin);
    fence_async_all();
    if (pc == WW && !odd) WTS1(k, 0);
#pragma unroll
    for (int u = 0; u < 10; u++) {
      const int st = odd ? (2 * u + 1) % 5 : (2 * u) % 5, ph = odd ? ((2 * u + 1) / 5) & 1 : ((2 * u) / 5) & 1;
      mwait(sb + BAR_E + 8 * st, ph ^ 1, spin);
      if (u == 9 && odd && ks < 4) mbar_arrive(sb + BAR_F + 8 * st);
      else {
        mbar_expect_tx(sb + BAR_F + 8 * st, len);
        bulk_g2s(sb + OFF_R + st * 8192 + lo, src + u * 16384, len, sb + BAR_F + 8 * st);
      }
    }
  }
  if (spin >= SPIN_TOT) g_err = 12;
}
__device__ __forceinline__ float warp_sum(float x) {
  x = quad_sum(x);
  const float a = __shfl_xor_sync(0xffffffffu, x, 4), b = __shfl_xor_sync(0xffffffffu, x, 8), c = __shfl_xor_sync(0xffffffffu, x, 12);
  x = (x + a) + (b + c);
  return x + __shfl_xor_sync(0xffffffffu, x, 16);
}
__device__ __forceinline__ void work_ln(int kind, int r, int lane, bf16* out) {
  int spin = 0;
  const int l = kind & 1;
  const int rp = kind < 2 ? (r & 1) * 16 + (r >> 1) : r;
  const uint32_t sw = ((((lane >> 1) & 7) ^ (rp & 7)) << 4) + (lane & 1) * 8;
  uint8_t* dst = kind < 2 ? g_xnb[l * LAG] + (lane >> 4) * 8192 + l * 4096 + rp * 128 + sw
               : kind == 2 ? g_xn[LAG] + (r >> 3) * 4096 + 2048 + (lane >> 4) * 1024 + (r & 7) * 128 + sw
                           : reinterpret_cast<uint8_t*>(out) + r * 1280 + lane * 8;
  const int dm = kind < 3 ? 16384 : 256, ds = kind < 3 ? 81920 : 40960;
#pragma unroll 1
  for (int s = 0; s < NSEG; s++) {
    const float* xr = g_x + (size_t)(s * 32 + r) * DM;
    if (lane == 0) cwait(kind < 2 ? CN_P + s + l * LAG : CN_W + l * 64 + s, kind < 2 ? W::NP : 10, spin);
    __syncwarp();
    if (r == 0 && lane == 0 && (l == 0 || s + LAG >= NSEG)) WTS1(s + l * LAG, kind < 2 ? 3 : 11);
    float4 v[5];
#pragma unroll
    for (int m = 0; m < 5; m++) v[m] = ld_relaxed4f(xr + m * 128 + lane * 4);
    if (kind < 3) {
      float t = 0.f;
#pragma unroll
      for (int m = 0; m < 5; m++) t += (v[m].x + v[m].y) + (v[m].z + v[m].w);
      const float mean = warp_sum(t) * (1.f / DM);
      float q0 = 0.f, q1 = 0.f;
#pragma unroll
      for (int m = 0; m < 5; m++) {
        v[m].x -= mean; v[m].y -= mean; v[m].z -= mean; v[m].w -= mean;
        q0 += v[m].x * v[m].x + v[m].y * v[m].y; q1 += v[m].z * v[m].z + v[m].w * v[m].w;
      }
      const float rs = rsqrtf(warp_sum(q0 + q1) * (1.f / DM) + 1e-5f);
#pragma unroll
      for (int m = 0; m < 5; m++) { v[m].x *= rs; v[m].y *= rs; v[m].z *= rs; v[m].w *= rs; }
    }
#pragma unroll
    for (int m = 0; m < 5; m++) *reinterpret_cast<uint2*>(dst + (size_t)s * ds + m * dm) = make_uint2(pack_bf16(v[m].x, v[m].y), pack_bf16(v[m].z, v[m].w));
    __syncwarp();
    if (r == 0 && lane == 0 && (l == 0 || s + LAG >= NSEG)) WTS1(s + l * LAG, kind < 2 ? 4 : 12);
    if (lane == 0 && kind < 3) csignal_t(kind < 2 ? CN_L + s + l * LAG : CN_X + s, kind);
  }
  if (spin >= SPIN_TOT) g_err = 13;
}

__device__ __forceinline__ void work_prefetch(int t) {
  int spin = 0;
#pragma unroll 1
  for (int k = 0; k + 4 < NSTEP; k++) {
    if ((t & 31) == 0) cwait(CN_O + k * 5, 1, spin);
    __syncwarp();
    if (k + 2 < NSEG) { prefetch_l2(g_x + (size_t)(k + 2) * 32 * DM + t * 64); prefetch_l2(g_x + (size_t)(k + 2) * 32 * DM + t * 64 + 32); }
    prefetch_l2(g_xn[k + 4] + (t >> 4) * 4096 + (t & 15) * 128);
    if (t < 184) prefetch_l2(ex_window(g_ex) + (t < 160 ? EX_M + (k + 4) * 20480 + t * 128 : EX_FLAG + (k + 4) * 3072 + (t - 160) * 128));
  }
}

__device__ __forceinline__ void stage_qkv(const bf16* wqkv, uint32_t base, int T, int bc, int tid) {
  const int q = tid & 15;
  const bool ok = q < 15 && bc * 60 + 4 * q < DM;
  const bf16* src = wqkv + T * DM + bc * 60 + 4 * q;
#pragma unroll 1
  for (int k0 = tid >> 4; k0 < 640; k0 += 80) {
    uint2 v[10];
#pragma unroll
    for (int u = 0; u < 10; u++) v[u] = ok ? *reinterpret_cast<const uint2*>(src + (size_t)(k0 + 8 * u) * 1920) : make_uint2(0, 0);
#pragma unroll
    for (int u = 0; u < 10; u++) sts64(base + (k0 + 8 * u) * 128 + (((q >> 1) ^ (k0 & 7)) << 4) + (q & 1) * 8, v[u].x, v[u].y);
  }
}
__device__ __forceinline__ void attend(uint32_t sb, int bc, int l, int s, int p, int tid) {
  using namespace W;
  const int r = tid & 7, m = (tid >> 3) & 3, hh = (tid >> 5) & 3, g = (tid >> 2) & 7, t = tid & 3;
  const int f2 = r < 4 ? 20 * hh + 16 + r : 60;
  const uint32_t tb = sb + OFF_T + (l * 4 + 2 * p) * COL, hb = sb + OFF_H + (l * 2 + p) * COL;
  const uint32_t ko = (m < 2 ? 20 * hh + 8 * m + r : f2) * 16, vo = (m < 2 ? 20 * hh + 4 * (r >> 1) + 2 * m + (r & 1) : f2) * 16;
  const float scl = 0.22360679774997896f * 1.4426950408889634f;
  float sc[3][4];
  {
    uint32_t q[4], q8a, q8b, k[3][4];
    ldsm4t(q, tb + (m & 1) * COL + (20 * hh + (m >> 1) * 8 + r) * 16);
    ldsm2t(q8a, q8b, tb + (m & 1) * COL + f2 * 16);
    ldsm4t(k[0], hb + ko); ldsm4t(k[1], tb + 8 * COL + ko); ldsm4t(k[2], tb + 9 * COL + ko);
#pragma unroll
    for (int c = 0; c < 3; c++) { sc[c][0] = sc[c][1] = sc[c][2] = sc[c][3] = 0.f; mma16816(sc[c], q[0], q[1], q[2], q[3], k[c][0], k[c][1]); }
#pragma unroll
    for (int c = 0; c < 3; c++) mma1688(sc[c], q8a, q8b, k[c][2]);
  }
  uint32_t v[3][4];
  ldsm4(v[0], hb + 4 * COL + vo); ldsm4(v[1], tb + 16 * COL + vo); ldsm4(v[2], tb + 17 * COL + vo);
  const bool lo0 = 2 * t > g, lo1 = 2 * t + 1 > g;
  uint32_t pw[2];
  float inv[2];
#pragma unroll
  for (int h = 0; h < 2; h++) {
    float y0 = lo0 ? sc[h][2 * h] : sc[h + 1][2 * h], y1 = lo1 ? sc[h][2 * h + 1] : sc[h + 1][2 * h + 1];
    if (h == 0 && s == 0) { y0 = lo0 ? -INFINITY : y0; y1 = lo1 ? -INFINITY : y1; }
    const float mx = quad_max(fmaxf(y0, y1)) * -scl;
    pw[h] = pack_bf16(ex2(fmaf(y0, scl, mx)), ex2(fmaf(y1, scl, mx)));
    inv[h] = bf_lo(pw[h]) + bf_hi(pw[h]);
  }
  const uint32_t ml = (lo0 ? 0xFFFFu : 0u) | (lo1 ? 0xFFFF0000u : 0u);
  float o[3][4];
#pragma unroll
  for (int j = 0; j < 3; j++) { o[j][0] = o[j][1] = o[j][2] = o[j][3] = 0.f; mma16816(o[j], pw[0] & ml, 0u, pw[0] & ~ml, pw[1] & ml, v[0][j], v[1][j]); }
#pragma unroll
  for (int j = 0; j < 3; j++) mma1688(o[j], 0u, pw[1] & ~ml, v[2][j]);
  inv[0] = rcp(quad_sum(inv[0])); inv[1] = rcp(quad_sum(inv[1]));
  const uint32_t ca = (bc * 3 + hh) * 20 + 4 * t, cb = ca + 16 - 2 * t, row = 2 * g + p;
  uint8_t* img = g_ob[l] + (size_t)s * 40960 + row * 128;
  const uint32_t oa = (ca >> 6) * 4096 + (((ca >> 3) ^ row) & 7) * 16 + (ca & 4) * 2, ob = (cb >> 6) * 4096 + (((cb >> 3) ^ row) & 7) * 16 + (cb & 6) * 2;
#pragma unroll
  for (int h = 0; h < 2; h++) {
    *reinterpret_cast<uint2*>(img + oa + h * 2048) = make_uint2(pack_bf16(o[0][2 * h] * inv[h], o[0][2 * h + 1] * inv[h]), pack_bf16(o[1][2 * h] * inv[h], o[1][2 * h + 1] * inv[h]));
    if (t < 2) *reinterpret_cast<uint32_t*>(img + ob + h * 2048) = pack_bf16(o[2][2 * h] * inv[h], o[2][2 * h + 1] * inv[h]);
  }
}
template <int WG>
__device__ __forceinline__ void work_b(const bf16* wqkv, uint32_t sb, int bc, int tid0) {
  using namespace W;
  if (WG == 0) asm volatile("setmaxnreg.inc.sync.aligned.u32 232;");
  else asm volatile("setmaxnreg.inc.sync.aligned.u32 208;");
  constexpr int NR = WG ? KRS : QRS, OFF_Y = WG ? OFF_YK : OFF_YQ;
  int spin = 0;
  const uint32_t wb = sb + (WG ? OFF_WO : OFF_WV);
  uint32_t wf[NR][4];
  stage_qkv(wqkv, wb, WG, bc, tid0 & 127);
  WBAR_SYNC(NB_G0 + WG, 128);
  load_frags<NR>(wf, wb, tid0);
#pragma unroll
  for (int k = NR; k < 40; k++) sts128(sb + OFF_Y + (k - NR) * 2048 + (tid0 & 127) * 16, lds128(wb + k * 2048 + (tid0 & 127) * 16));
  fence_async();
  if (WG == 1) WBAR_ARRIVE(NB_PK, 256);
  WBAR_SYNC(NB_G0 + WG, 128);
  if (WG == 0) {
    stage_qkv(wqkv, wb, 2, bc, tid0);
    fence_async();
    WBAR_SYNC(NB_G0, 128);
  }
#pragma unroll 1
  for (int k = 0; k < NSTEP; k++) {
    uint32_t hist[8];
    {
      float d[32], e[32];
#pragma unroll
      for (int c = 0; c < 10; c++) {
        mwait(sb + BAR_F + 8 * (c % 4), ((c % 4 < 2 ? k : 0) + c / 4) & 1, spin);
        if (c == 0 && bc == 0) WTS(k, WG ? 15 : 6);
        wg_fence();
#pragma unroll
        for (int kk = 0; kk < 4; kk++) {
          const int q = 4 * c + kk;
          const uint64_t db = rdesc(OFF_X + (c % 4) * 8192, kk);
          if (q < NR) wgmma_rs64(d, wf[q < NR ? q : 0], db, q);
          else wgmma_ts64(d, mkdesc(SB0 + OFF_Y + (q - NR) * 2048, 8192, 1024), db, 1);
          if (WG == 0) wgmma_ts64(e, mkdesc(SB0 + OFF_WV + q * 2048, 8192, 1024), db, q);
          if (kk == 0 && c > 0 && (c <= 6 || c == 9)) {
            wg_commit();
            wg_wait<1>();
            if ((tid0 & 31) == 0) mbar_arrive(sb + BAR_E + 8 * ((c - 1) % 4));
          }
        }
        wg_commit();
      }
      wg_wait<0>();
      if (bc == 0) WTS(k, 16 + WG);
      WBAR_SYNC(NB_B, 256);
      const int tid = fresh(tid0), m = (tid >> 3) & 3;
      const uint32_t a = sb + OFF_T + min(((tid >> 5) & 3) * 16 + (m & 1) * 8 + (tid & 7), 60) * 16 + (m >> 1) * COL;
      const float (&x)[32] = WG ? d : e;
#pragma unroll
      for (int p = 0; p < 4; p++) {
        hist[2 * p] = pack_bf16(x[8 * p + 4], x[8 * p + 5]); hist[2 * p + 1] = pack_bf16(x[8 * p + 6], x[8 * p + 7]);
        stsm4(a + (16 - 8 * WG + 2 * p) * COL, pack_bf16(x[8 * p], x[8 * p + 1]), pack_bf16(x[8 * p + 2], x[8 * p + 3]), hist[2 * p], hist[2 * p + 1]);
        if (WG == 0)
          stsm4(a + 2 * p * COL, pack_bf16(d[8 * p], d[8 * p + 1]), pack_bf16(d[8 * p + 2], d[8 * p + 3]), pack_bf16(d[8 * p + 4], d[8 * p + 5]), pack_bf16(d[8 * p + 6], d[8 * p + 7]));
      }
    }
    WBAR_SYNC(NB_TD, 288);
    if (bc == 0 && WG == 0) WTS(k, 7);
#pragma unroll 1
    for (int l = 0; l < 2; l++) {
      const int tid = fresh(tid0), hh = uni((tid >> 5) & 3), s = k - l * LAG;
      if (hh < 3 && bc * 3 + hh < NH && s >= 0 && s < NSEG) attend(sb, bc, l, s, WG, tid);
      if (bc == 0 && WG == 0) WTS(k, l == 0 || k >= NSEG ? 8 : 25);
      if (l == 0) WBAR_ARRIVE(NB_AS, 288); else WBAR_ARRIVE(NB_AS + 1, 288);
    }
    WBAR_SYNC(NB_B, 256);
    {
      const int tid = fresh(tid0), m = (tid >> 3) & 3;
      const uint32_t a = sb + OFF_H + min(((tid >> 5) & 3) * 16 + (m & 1) * 8 + (tid & 7), 60) * 16 + (4 - 4 * WG + (m >> 1)) * COL;
      stsm4(a, hist[0], hist[1], hist[2], hist[3]);
      if (k >= LAG) stsm4(a + 2 * COL, hist[4], hist[5], hist[6], hist[7]);
      fence_async();
      if ((tid & 31) < 3) mbar_arrive(sb + BAR_E + 8 + 8 * (tid & 3));
    }
  }
  if (spin >= SPIN_TOT) g_err = 14;
}
__device__ __forceinline__ void work_wo(const CUtensorMap& tmBo, uint32_t sb, int bc, int tid0) {
  using namespace W;
  int spin = 0;
  WBAR_SYNC(NB_PK, 256);
  if (bc == 10) return;
  if ((tid0 & 127) == 0) {
    mbar_expect_tx(sb + BAR_W, 81920);
    for (int i = 0; i < 10; i++) tma2d(sb + OFF_WO + i * 8192, &tmBo, bc * 64, i * 64, sb + BAR_W);
  }
  __syncwarp();
  mwait(sb + BAR_W, 0, spin);
  permute_cols(sb + OFF_WO, tid0 & 127, 2560);
  WBAR_SYNC(NB_G0 + 2, 128);
  uint32_t wl[4];
  ldsm4t(wl, frag_addr(sb + OFF_WO + 39 * 2048, tid0));
  fence_async();
  WBAR_SYNC(NB_PV, 160);
  uint32_t n = 0;
  FOR_SEGS(l, s)
    float d[16];
#pragma unroll
    for (int c = 0; c < 10; c++) {
      mwait(sb + BAR_G + 8 * (c % 3), ((c % 3 ? n : 0) + c / 3) & 1, spin);
      if (c == 0 && bc == 0) WTS(s + l * LAG, l == 0 || s + LAG >= NSEG ? 20 : 23);
      wg_fence();
#pragma unroll
      for (int kk = 0; kk < 4; kk++) {
        if (c == 9 && kk == 3) wgmma_rs32(d, wl, rdesc(OFF_G + (c % 3) * 4096, kk), 1);
        else wgmma_ts32(d, mkdesc(SB0 + OFF_WO + (4 * c + kk) * 2048, 8192, 1024), rdesc(OFF_G + (c % 3) * 4096, kk), c | kk);
      }
      wg_commit();
      if (c == 9 || !WOP) wg_wait<0>();
      else if (c > 0) wg_wait<1>();
      if ((tid0 & 31) == 0) {
        if (WOP && c > 0) mbar_arrive(sb + BAR_H + 8 * ((c - 1) % 3));
        if (c == 9 || !WOP) mbar_arrive(sb + BAR_H + 8 * (c % 3));
      }
    }
    if (bc == 0) WTS(s + l * LAG, l == 0 || s + LAG >= NSEG ? 10 : 24);
    red_tile(d, s, bc * 64, tid0);
    WBAR_SYNC(NB_SG, 160);
    n++;
  }
  if (spin >= SPIN_TOT) g_err = 17;
}
__device__ __forceinline__ void work_x_producer(uint32_t sb, int bc) {
  using namespace W;
  int spin = 0;
#pragma unroll 1
  for (int k = 0; k < NSTEP; k++) {
    const uint32_t lo = k < NSEG ? 0 : 4096, len = k < LAG || k >= NSEG ? 4096 : 8192;
    const uint8_t* src = g_xnb[k] + lo;
    cwait(CN_L + k, len >> 7, spin);
    fence_async_all();
    if (bc == 0) WTS1(k, 5);
#pragma unroll
    for (int c = 0; c < 10; c++) {
      mwait(sb + BAR_E + 8 * (c % 4), (((c % 4 < 2 ? k : 0) + c / 4) & 1) ^ 1, spin);
      mbar_expect_tx(sb + BAR_F + 8 * (c % 4), len);
      bulk_g2s(sb + OFF_X + (c % 4) * 8192 + lo, src + c * 8192, len, sb + BAR_F + 8 * (c % 4));
    }
  }
  if (spin >= SPIN_TOT) g_err = 15;
}
__device__ __forceinline__ void work_g_producer(uint32_t sb, int bc) {
  using namespace W;
  int spin = 0;
  uint32_t n = 0;
  FOR_SEGS(l, s)
    const uint8_t* src = g_ob[l] + (size_t)s * 40960;
    cwait(CN_A + l * 64 + s, NBC, spin);
    fence_async_all();
    if (bc == 0) WTS1(s + l * LAG, l == 0 || s + LAG >= NSEG ? 9 : 22);
#pragma unroll
    for (int c = 0; c < 10; c++) {
      mwait(sb + BAR_H + 8 * (c % 3), (((c % 3 ? n : 0) + c / 3) & 1) ^ 1, spin);
      mbar_expect_tx(sb + BAR_G + 8 * (c % 3), 4096);
      bulk_g2s(sb + OFF_G + (c % 3) * 4096, src + c * 4096, 4096, sb + BAR_G + 8 * (c % 3));
    }
    n++;
  }
  if (spin >= SPIN_TOT) g_err = 16;
}

__global__ void __launch_bounds__(512, 1)
k_work(const __grid_constant__ CUtensorMap tmWo, const __grid_constant__ CUtensorMap tmBo, const bf16* __restrict__ wqkv, bf16* __restrict__ out) {
  using namespace W;
  extern __shared__ __align__(1024) uint8_t smem[];
  const uint32_t sb = smem_u32(smem);
  const int tid = threadIdx.x, w = blockIdx.x;
  const int wg = __shfl_sync(0xffffffffu, tid >> 7, 0);
  if (tid == 0) {
    if (sb != SB0) g_err = 101;
    for (int i = 0; i < 5; i++) { mbar_init(sb + BAR_F + 8 * i, 1); mbar_init(sb + BAR_E + 8 * i, 8); mbar_init(sb + BAR_G + 8 * i, 1); mbar_init(sb + BAR_H + 8 * i, 4); }
    mbar_init(sb + BAR_W, 1); mbar_init(sb + BAR_W + 8, 1);
    for (int p = 0; p < 16; p++) sts32(sb + OFF_SAFE + 4 * p, 0);
    asm volatile("fence.mbarrier_init.release.cluster;" ::: "memory");
  }
  if (tid < 8 * COL / 16) sts128(sb + OFF_H + tid * 16, make_uint4(0, 0, 0, 0));
  fence_async();
  __syncthreads();

  if (w < NP) {
    if (wg == 0) work_p<0>(tmWo, sb, w, keep(tid));
    else if (wg == 1) work_p<1>(tmWo, sb, w, keep(tid));
    else {
      asm volatile("setmaxnreg.dec.sync.aligned.u32 48;");
      const int aw = (tid >> 5) - 8;
      if (aw < 2) {
        if ((tid & 31) == 0) work_p_producer(sb, w, aw);
      } else {
        const int id = (aw - 2) * NP + w;
        if (id < 128) work_ln(id & 3, id >> 2, tid & 31, out);
        else if (PFW && id < 138) work_prefetch((id - 128) * 32 + (tid & 31));
      }
    }
  } else {
    const int bc = w - NP;
    if (wg == 0) work_b<0>(wqkv, sb, bc, keep(tid));
    else if (wg == 1) work_b<1>(wqkv, sb, bc, keep(tid));
    else if (wg == 2) {
      asm volatile("setmaxnreg.dec.sync.aligned.u32 48;");
      work_wo(tmBo, sb, bc, keep(tid));
    } else {
      asm volatile("setmaxnreg.dec.sync.aligned.u32 24;");
      if (tid < 416) {
        if (tid == 384) work_x_producer(sb, bc);
      } else if (tid < 448) {
        if (bc < 10) {
          WBAR_SYNC(NB_PV, 160);
          if (tid == 416) work_g_producer(sb, bc);
        }
      } else if (tid < 480) {
        for (int k = 0; k < NSTEP; k++) {
          WBAR_SYNC(NB_TD, 288);
          WBAR_SYNC(NB_AS, 288);
          if (tid == 448 && k < NSEG) csignal_t(CN_A + k, 5);
          __syncwarp();
          WBAR_SYNC(NB_AS + 1, 288);
          if (tid == 448 && k >= LAG) csignal_t(CN_A + 64 + k - LAG, 4);
          __syncwarp();
        }
      } else if (bc < 10) {
        FOR_SEGS(l, s)
          WBAR_SYNC(NB_SG, 160);
          if (tid == 480) csignal_t(CN_W + l * 64 + s, 6);
          __syncwarp();
        }
      }
    }
  }
  __syncthreads();
  asm volatile("griddepcontrol.wait;" ::: "memory");
}

typedef CUresult (*EncodeFn)(CUtensorMap*, CUtensorMapDataType, cuuint32_t, void*, const cuuint64_t*, const cuuint64_t*,
                             const cuuint32_t*, const cuuint32_t*, CUtensorMapInterleave, CUtensorMapSwizzle,
                             CUtensorMapL2promotion, CUtensorMapFloatOOBfill);

static void make_map(EncodeFn enc, CUtensorMap* tm, const void* ptr, uint64_t cols, uint64_t rows, uint32_t boxc, uint32_t boxr) {
  cuuint64_t dims[2] = {cols, rows};
  cuuint64_t strides[1] = {cols * 2};
  cuuint32_t box[2] = {boxc, boxr};
  cuuint32_t es[2] = {1, 1};
  enc(tm, CU_TENSOR_MAP_DATA_TYPE_BFLOAT16, 2, const_cast<void*>(ptr), dims, strides, box, es, CU_TENSOR_MAP_INTERLEAVE_NONE,
      CU_TENSOR_MAP_SWIZZLE_128B, CU_TENSOR_MAP_L2_PROMOTION_L2_256B, CU_TENSOR_MAP_FLOAT_OOB_FILL_NONE);
}

extern "C" void kernel_launch(void* const* d_in, const int* in_sizes, int n_in, void* d_out, int out_size) {
  const bf16* x0 = (const bf16*)d_in[0];
  const bf16* mem0 = (const bf16*)d_in[1];
  const bf16* Wq = (const bf16*)d_in[2];
  const bf16* Wk = (const bf16*)d_in[3];
  const bf16* Wv = (const bf16*)d_in[4];
  const bf16* Wo = (const bf16*)d_in[5];
  const bf16* Bqkv = (const bf16*)d_in[8];
  const bf16* Bwo = (const bf16*)d_in[9];
  bf16* out = (bf16*)d_out;

  static EncodeFn enc = nullptr;
  if (!enc) {
    void* fn = nullptr;
    cudaDriverEntryPointQueryResult qr;
    cudaGetDriverEntryPoint("cuTensorMapEncodeTiled", &fn, cudaEnableDefault, &qr);
    enc = (EncodeFn)fn;
    cudaFuncSetAttribute(k_chain, cudaFuncAttributeMaxDynamicSharedMemorySize, C::SMEM);
    cudaFuncSetAttribute(k_work, cudaFuncAttributeMaxDynamicSharedMemorySize, W::SMEM);
  }
  CUtensorMap tmWq, tmWk, tmWv, tmWo, tmWp, tmBo;
  make_map(enc, &tmWq, Wq, NH * DH, DM, 64, 128);
  make_map(enc, &tmWk, Wk, NH * DH, DM, 64, 128);
  make_map(enc, &tmWv, Wv, NH * DH, DM, 64, 128);
  make_map(enc, &tmWo, Wo, DM, NH * DH, 64, 64);
  make_map(enc, &tmWp, Wo, DM, NH * DH, 64, 16);
  make_map(enc, &tmBo, Bwo, DM, DM, 64, 64);

  cudaStream_t st = cudaStreamPerThread;
  k_pre<<<256, 256, 0, st>>>(x0, mem0);
  cudaLaunchAttribute at[1];
  at[0].id = cudaLaunchAttributeProgrammaticStreamSerialization; at[0].val.programmaticStreamSerializationAllowed = 1;
  {
    cudaLaunchConfig_t cfg = {};
    cfg.gridDim = dim3(96); cfg.blockDim = dim3(384); cfg.dynamicSmemBytes = C::SMEM; cfg.stream = st;
    cfg.attrs = at; cfg.numAttrs = 0;
    cudaLaunchKernelEx(&cfg, k_chain, tmWq, tmWk, tmWv, tmWo);
  }
  cudaLaunchConfig_t cfg = {};
  cfg.gridDim = dim3(W::NW); cfg.blockDim = dim3(512); cfg.dynamicSmemBytes = W::SMEM; cfg.stream = st;
  cfg.attrs = at; cfg.numAttrs = NOWORK == 2 ? 0 : 1;
  cudaLaunchKernelEx(&cfg, k_work, tmWp, tmBo, Bqkv, out);
}
```

```cpp
#include <cuda_runtime.h>
#include <cuda_bf16.h>
#include <cuda.h>
#include <stdint.h>

typedef __nv_bfloat16 bf16;

constexpr int SEQ = 2048, DM = 640, NH = 32, DH = 192, NSEG = 64;
#define LAG 7
constexpr int NSTEP = NSEG + LAG;
constexpr uint32_t SENT = 0xFFFFFFFFu;

constexpr int MAIL9 = 288 * 2048, MAIL_BYTES = MAIL9 + 64 * 3072;
__device__ __align__(1024) uint8_t g_xn[NSTEP][81920];
__device__ __align__(1024) uint8_t g_xnb[NSTEP][81920];
__device__ __align__(1024) uint8_t g_ob[2][NSEG * 40960];
#define ORING 8
static_assert(ORING > LAG, "a slot is free again LAG + 1 steps later");
__device__ __align__(1024) uint8_t g_o[ORING][96][8192];
__device__ __align__(1024) float g_x[SEQ * DM];
constexpr int EX_MAIL = 0;
constexpr int EX_M = 2 << 20;
constexpr int EX_FLAG = EX_M + NSTEP * 20480;
static_assert(EX_FLAG + NSTEP * 3072 <= (4 << 20), "");
__device__ __align__(1024) uint8_t g_ex[8 << 20];
__host__ __device__ __forceinline__ uint8_t* ex_window(uint8_t* p) { return reinterpret_cast<uint8_t*>((reinterpret_cast<uint64_t>(p) + (4 << 20) - 1) & ~(uint64_t)((4 << 20) - 1)); }
enum { CN_P = 0, CN_L = 128, CN_A = 256, CN_W = 384, CN_X = 512, CN_O = 576, CN_NUM = CN_O + 5 * NSTEP };
__device__ __align__(128) uint32_t g_cnt[CN_NUM][32];
__device__ int g_err;
#define TS(jj, i)
#define TS1(jj, i)
#define PTS(i)
#define TSB(jj, i)
#define TSV(jj, i, v)
#define TS_FLUSH(jj)
#define WTS(b, k)
#define WTS1(b, k)
#define WW -1

__device__ __forceinline__ uint32_t smem_u32(const void* p) { return (uint32_t)__cvta_generic_to_shared(p); }
__device__ __forceinline__ uint32_t clk32() { uint32_t t; asm volatile("mov.u32 %0, %%clock;" : "=r"(t)::"memory"); return t; }
__device__ __forceinline__ uint32_t mapa(uint32_t a, uint32_t r) { uint32_t o; asm("mapa.shared::cluster.u32 %0,%1,%2;" : "=r"(o) : "r"(a), "r"(r)); return o; }
__device__ __forceinline__ void mbar_init(uint32_t bar, uint32_t cnt) { asm volatile("mbarrier.init.shared::cta.b64 [%0],%1;" ::"r"(bar), "r"(cnt) : "memory"); }
__device__ __forceinline__ void mbar_expect_tx(uint32_t bar, uint32_t bytes) { asm volatile("mbarrier.arrive.expect_tx.shared::cta.b64 _,[%0],%1;" ::"r"(bar), "r"(bytes) : "memory"); }
__device__ __forceinline__ void mbar_arrive(uint32_t bar) { asm volatile("mbarrier.arrive.shared::cta.b64 _,[%0];" ::"r"(bar) : "memory"); }
__device__ __forceinline__ void mbar_arrive_cluster(uint32_t bar) { asm volatile("mbarrier.arrive.shared::cluster.b64 _,[%0];" ::"r"(bar) : "memory"); }
__device__ __forceinline__ bool mbar_try(uint32_t bar, uint32_t ph) {
  uint32_t ok;
  asm volatile("{.reg .pred p; mbarrier.try_wait.parity.shared::cta.b64 p,[%1],%2; selp.u32 %0,1,0,p;}" : "=r"(ok) : "r"(bar), "r"(ph) : "memory");
  return ok;
}
__device__ __forceinline__ bool mbar_test(uint32_t bar, uint32_t ph) {
  uint32_t ok;
  asm volatile("{.reg .pred p; mbarrier.test_wait.parity.shared::cta.b64 p,[%1],%2; selp.u32 %0,1,0,p;}" : "=r"(ok) : "r"(bar), "r"(ph) : "memory");
  return ok;
}
__device__ __forceinline__ int fresh(int x) { asm volatile("" : "+r"(x)); return x; }
#define PHASE_IDS const int tid = fresh(tid0), lane = tid & 31, w = tid >> 5, g = lane >> 2, t = lane & 3; (void)w; (void)g; (void)t
__device__ __forceinline__ void bar_sync(int id, int n) { asm volatile("bar.sync %0,%1;" ::"r"(id), "r"(n) : "memory"); }
__device__ __forceinline__ void bar_arrive(int id, int n) { asm volatile("bar.arrive %0,%1;" ::"r"(id), "r"(n) : "memory"); }
__device__ __forceinline__ bool bar_red_or(int id, int n, bool v) {
  uint32_t r;
  asm volatile("{\n .reg .pred p, q;\n setp.ne.u32 q, %3, 0;\n barrier.cta.red.or.pred p, %1, %2, q;\n selp.u32 %0, 1, 0, p;\n}" : "=r"(r) : "r"(id), "r"(n), "r"((uint32_t)v) : "memory");
  return r != 0;
}
__device__ __forceinline__ void fence_async() { asm volatile("fence.proxy.async.shared::cta;" ::: "memory"); }
__device__ __forceinline__ void bulk_g2s(uint32_t dst, const void* src, uint32_t bytes, uint32_t bar) {
  asm volatile("cp.async.bulk.shared::cluster.global.mbarrier::complete_tx::bytes [%0],[%1],%2,[%3];" ::"r"(dst), "l"(src), "r"(bytes), "r"(bar) : "memory");
}
__device__ __forceinline__ void bulk_g2s_mc(uint32_t dst, const void* src, uint32_t bytes, uint32_t bar) {
  asm volatile("cp.async.bulk.shared::cluster.global.mbarrier::complete_tx::bytes.multicast::cluster [%0],[%1],%2,[%3],%4;"
               ::"r"(dst), "l"(src), "r"(bytes), "r"(bar), "h"((uint16_t)7) : "memory");
}
__device__ __forceinline__ void bulk_s2g(void* dst, uint32_t src, uint32_t bytes) {
  asm volatile("cp.async.bulk.global.shared::cta.bulk_group [%0],[%1],%2;" ::"l"(dst), "r"(src), "r"(bytes) : "memory");
}
__device__ __forceinline__ void bulk_s2c(uint32_t dst, uint32_t src, uint32_t bytes, uint32_t bar) {
  asm volatile("cp.async.bulk.shared::cluster.shared::cta.mbarrier::complete_tx::bytes [%0],[%1],%2,[%3];" ::"r"(dst), "r"(src), "r"(bytes), "r"(bar) : "memory");
}
__device__ __forceinline__ void tma2d(uint32_t dst, const CUtensorMap* tm, int c0, int c1, uint32_t bar) {
  asm volatile("cp.async.bulk.tensor.2d.shared::cluster.global.mbarrier::complete_tx::bytes [%0],[%1,{%3,%4}],[%2];"
               ::"r"(dst), "l"(tm), "r"(bar), "r"(c0), "r"(c1) : "memory");
}
__device__ __forceinline__ void tma2d_prefetch(const CUtensorMap* tm, int c0, int c1) {
  asm volatile("cp.async.bulk.prefetch.tensor.2d.L2.global.tile [%0,{%1,%2}];" ::"l"(tm), "r"(c0), "r"(c1) : "memory");
}
__device__ __forceinline__ uint32_t pack_bf16(float lo, float hi) {
  uint32_t r; asm("cvt.rn.bf16x2.f32 %0,%1,%2;" : "=r"(r) : "f"(hi), "f"(lo)); return r;
}
__device__ __forceinline__ float bf_lo(uint32_t x) { return __uint_as_float(x << 16); }
__device__ __forceinline__ float bf_hi(uint32_t x) { return __uint_as_float(x & 0xFFFF0000u); }
__device__ __forceinline__ float ex2(float x) { float y; asm("ex2.approx.ftz.f32 %0,%1;" : "=f"(y) : "f"(x)); return y; }
__device__ __forceinline__ void ldsm4(uint32_t (&r)[4], uint32_t a) {
  asm volatile("ldmatrix.sync.aligned.m8n8.x4.shared.b16 {%0,%1,%2,%3},[%4];" : "=r"(r[0]), "=r"(r[1]), "=r"(r[2]), "=r"(r[3]) : "r"(a) : "memory");
}
__device__ __forceinline__ void ldsm4t(uint32_t (&r)[4], uint32_t a) {
  asm volatile("ldmatrix.sync.aligned.m8n8.x4.trans.shared.b16 {%0,%1,%2,%3},[%4];" : "=r"(r[0]), "=r"(r[1]), "=r"(r[2]), "=r"(r[3]) : "r"(a) : "memory");
}
__device__ __forceinline__ void ldsm2(uint32_t& r0, uint32_t& r1, uint32_t a) {
  asm volatile("ldmatrix.sync.aligned.m8n8.x2.shared.b16 {%0,%1},[%2];" : "=r"(r0), "=r"(r1) : "r"(a) : "memory");
}
__device__ __forceinline__ void ldsm2t(uint32_t& r0, uint32_t& r1, uint32_t a) {
  asm volatile("ldmatrix.sync.aligned.m8n8.x2.trans.shared.b16 {%0,%1},[%2];" : "=r"(r0), "=r"(r1) : "r"(a) : "memory");
}
__device__ __forceinline__ void ldsm1(uint32_t& r0, uint32_t a) {
  asm volatile("ldmatrix.sync.aligned.m8n8.x1.shared.b16 {%0},[%1];" : "=r"(r0) : "r"(a) : "memory");
}
__device__ __forceinline__ void mma16816(float (&d)[4], uint32_t a0, uint32_t a1, uint32_t a2, uint32_t a3, uint32_t b0, uint32_t b1) {
  asm volatile("mma.sync.aligned.m16n8k16.row.col.f32.bf16.bf16.f32 {%0,%1,%2,%3},{%4,%5,%6,%7},{%8,%9},{%0,%1,%2,%3};"
               : "+f"(d[0]), "+f"(d[1]), "+f"(d[2]), "+f"(d[3]) : "r"(a0), "r"(a1), "r"(a2), "r"(a3), "r"(b0), "r"(b1));
}
__device__ __forceinline__ void mma1688(float (&d)[4], uint32_t a0, uint32_t a1, uint32_t b0) {
  asm volatile("mma.sync.aligned.m16n8k8.row.col.f32.bf16.bf16.f32 {%0,%1,%2,%3},{%4,%5},{%6},{%0,%1,%2,%3};"
               : "+f"(d[0]), "+f"(d[1]), "+f"(d[2]), "+f"(d[3]) : "r"(a0), "r"(a1), "r"(b0));
}
__device__ __forceinline__ void sts32(uint32_t a, uint32_t v) { asm volatile("st.shared.b32 [%0],%1;" ::"r"(a), "r"(v) : "memory"); }
__device__ __forceinline__ void sts64f(uint32_t a, float x, float y) { asm volatile("st.shared.v2.f32 [%0],{%1,%2};" ::"r"(a), "f"(x), "f"(y) : "memory"); }
__device__ __forceinline__ void sts128(uint32_t a, uint4 v) { asm volatile("st.shared.v4.b32 [%0],{%1,%2,%3,%4};" ::"r"(a), "r"(v.x), "r"(v.y), "r"(v.z), "r"(v.w) : "memory"); }
__device__ __forceinline__ float lds32f(uint32_t a) { float v; asm volatile("ld.shared.f32 %0,[%1];" : "=f"(v) : "r"(a) : "memory"); return v; }
__device__ __forceinline__ float2 lds64f(uint32_t a) { float2 v; asm volatile("ld.shared.v2.f32 {%0,%1},[%2];" : "=f"(v.x), "=f"(v.y) : "r"(a) : "memory"); return v; }
__device__ __forceinline__ uint4 lds128(uint32_t a) { uint4 v; asm volatile("ld.shared.v4.b32 {%0,%1,%2,%3},[%4];" : "=r"(v.x), "=r"(v.y), "=r"(v.z), "=r"(v.w) : "r"(a) : "memory"); return v; }
__device__ __forceinline__ float4 lds128f(uint32_t a) { float4 v; asm volatile("ld.shared.v4.f32 {%0,%1,%2,%3},[%4];" : "=f"(v.x), "=f"(v.y), "=f"(v.z), "=f"(v.w) : "r"(a) : "memory"); return v; }
__device__ __forceinline__ void st_async2(uint32_t a, float x, float y, uint32_t bar) {
  asm volatile("st.async.weak.shared::cluster.mbarrier::complete_tx::bytes.v2.f32 [%0],{%1,%2},[%3];" ::"r"(a), "f"(x), "f"(y), "r"(bar) : "memory");
}
__device__ __forceinline__ void st_async4(uint32_t a, const float (&v)[4], uint32_t bar) {
  asm volatile("st.async.weak.shared::cluster.mbarrier::complete_tx::bytes.v4.f32 [%0],{%1,%2,%3,%4},[%5];" ::"r"(a), "f"(v[0]), "f"(v[1]), "f"(v[2]), "f"(v[3]), "r"(bar) : "memory");
}
__device__ __forceinline__ void st_async4v(uint32_t a, float x, float y, float z, float w, uint32_t bar) {
  asm volatile("st.async.weak.shared::cluster.mbarrier::complete_tx::bytes.v4.f32 [%0],{%1,%2,%3,%4},[%5];" ::"r"(a), "f"(x), "f"(y), "f"(z), "f"(w), "r"(bar) : "memory");
}
__device__ __forceinline__ void st_async4u(uint32_t a, const uint4& v, uint32_t bar) {
  asm volatile("st.async.weak.shared::cluster.mbarrier::complete_tx::bytes.v4.b32 [%0],{%1,%2,%3,%4},[%5];" ::"r"(a), "r"(v.x), "r"(v.y), "r"(v.z), "r"(v.w), "r"(bar) : "memory");
}
__device__ __forceinline__ uint4 ld_relaxed4(const void* p) {
  uint4 v; asm volatile("ld.relaxed.gpu.global.v4.u32 {%0,%1,%2,%3},[%4];" : "=r"(v.x), "=r"(v.y), "=r"(v.z), "=r"(v.w) : "l"(p) : "memory"); return v;
}
__device__ __forceinline__ uint32_t ld_relaxed(const void* p) {
  uint32_t v; asm volatile("ld.relaxed.gpu.global.u32 %0,[%1];" : "=r"(v) : "l"(p) : "memory"); return v;
}
__device__ __forceinline__ void st_relaxed(void* p, uint32_t v) { asm volatile("st.relaxed.gpu.global.b32 [%0],%1;" ::"l"(p), "r"(v) : "memory"); }
__device__ __forceinline__ void st_relaxed4(void* p, uint32_t v) { asm volatile("st.relaxed.gpu.global.v4.b32 [%0],{%1,%1,%1,%1};" ::"l"(p), "r"(v) : "memory"); }

__device__ __forceinline__ uint32_t ld_acquire(const void* p) {
  uint32_t v; asm volatile("ld.acquire.gpu.global.u32 %0,[%1];" : "=r"(v) : "l"(p) : "memory"); return v;
}
__device__ __forceinline__ float4 ld_relaxed4f(const void* p) {
  float4 v; asm volatile("ld.relaxed.gpu.global.v4.f32 {%0,%1,%2,%3},[%4];" : "=f"(v.x), "=f"(v.y), "=f"(v.z), "=f"(v.w) : "l"(p) : "memory"); return v;
}
__device__ __forceinline__ float2 ld_relaxed2f(const void* p) {
  float2 v; asm volatile("ld.relaxed.gpu.global.v2.f32 {%0,%1},[%2];" : "=f"(v.x), "=f"(v.y) : "l"(p) : "memory"); return v;
}
__device__ __forceinline__ void prefetch_l2(const void* p) { asm volatile("prefetch.global.L2 [%0];" ::"l"(p)); }
__device__ __forceinline__ void fence_gpu() { asm volatile("fence.acq_rel.gpu;" ::: "memory"); }
__device__ __forceinline__ void fence_async_all() { asm volatile("fence.proxy.async.global;" ::: "memory"); }
constexpr int SPIN_TOT = 1 << 22;
__device__ __forceinline__ void csignal(int idx) { asm volatile("red.release.gpu.global.add.u32 [%0],1;" ::"l"(&g_cnt[idx][0]) : "memory"); }
#define csignal_t(idx, role) csignal(idx)
__device__ __forceinline__ void cwait(int idx, uint32_t target, int& spin) {
  while (ld_acquire(&g_cnt[idx][0]) < target && spin < SPIN_TOT) spin += 16;
}

__device__ __forceinline__ uint64_t mkdesc(uint32_t addr, uint32_t lbo, uint32_t sbo) {
  return (uint64_t)((addr & 0x3FFFF) >> 4) | ((uint64_t)(lbo >> 4) << 16) | ((uint64_t)(sbo >> 4) << 32) | ((uint64_t)1 << 62);
}
__device__ __forceinline__ uint64_t mkdesc_ns(uint32_t addr, uint32_t lbo, uint32_t sbo) {
  return (uint64_t)((addr & 0x3FFFF) >> 4) | ((uint64_t)(lbo >> 4) << 16) | ((uint64_t)(sbo >> 4) << 32);
}
__device__ __forceinline__ void wg_fence() { asm volatile("wgmma.fence.sync.aligned;" ::: "memory"); }
__device__ __forceinline__ void wg_commit() { asm volatile("wgmma.commit_group.sync.aligned;" ::: "memory"); }
template <int N> __device__ __forceinline__ void wg_wait() { asm volatile("wgmma.wait_group.sync.aligned %0;" ::"n"(N) : "memory"); }

__device__ __forceinline__ void wgmma_rs16(float (&d)[8], const uint32_t (&a)[4], uint64_t db, int sc) {
  asm volatile("{.reg .pred p; setp.ne.b32 p,%13,0; wgmma.mma_async.sync.aligned.m64n16k16.f32.bf16.bf16 "
               "{%0,%1,%2,%3,%4,%5,%6,%7},{%8,%9,%10,%11},%12,p,1,1,0;}"
               : "+f"(d[0]), "+f"(d[1]), "+f"(d[2]), "+f"(d[3]), "+f"(d[4]), "+f"(d[5]), "+f"(d[6]), "+f"(d[7])
               : "r"(a[0]), "r"(a[1]), "r"(a[2]), "r"(a[3]), "l"(db), "r"(sc));
}
__device__ __forceinline__ void wgmma_rs64(float (&d)[32], const uint32_t (&a)[4], uint64_t db, int sc) {
  asm volatile("{.reg .pred p; setp.ne.b32 p,%37,0; wgmma.mma_async.sync.aligned.m64n64k16.f32.bf16.bf16 "
               "{%0,%1,%2,%3,%4,%5,%6,%7,%8,%9,%10,%11,%12,%13,%14,%15,%16,%17,%18,%19,%20,%21,%22,%23,%24,%25,%26,%27,%28,%29,%30,%31},{%32,%33,%34,%35},%36,p,1,1,0;}"
               : "+f"(d[0]), "+f"(d[1]), "+f"(d[2]), "+f"(d[3]), "+f"(d[4]), "+f"(d[5]), "+f"(d[6]), "+f"(d[7]), "+f"(d[8]), "+f"(d[9]), "+f"(d[10]), "+f"(d[11]), "+f"(d[12]), "+f"(d[13]), "+f"(d[14]), "+f"(d[15]), "+f"(d[16]), "+f"(d[17]), "+f"(d[18]), "+f"(d[19]), "+f"(d[20]), "+f"(d[21]), "+f"(d[22]), "+f"(d[23]), "+f"(d[24]), "+f"(d[25]), "+f"(d[26]), "+f"(d[27]), "+f"(d[28]), "+f"(d[29]), "+f"(d[30]), "+f"(d[31])
               : "r"(a[0]), "r"(a[1]), "r"(a[2]), "r"(a[3]), "l"(db), "r"(sc));
}
__device__ __forceinline__ void wgmma_rt16(float (&d)[8], const uint32_t (&a)[4], uint64_t db, int sc) {
  asm volatile("{.reg .pred p; setp.ne.b32 p,%13,0; wgmma.mma_async.sync.aligned.m64n16k16.f32.bf16.bf16 "
               "{%0,%1,%2,%3,%4,%5,%6,%7},{%8,%9,%10,%11},%12,p,1,1,1;}"
               : "+f"(d[0]), "+f"(d[1]), "+f"(d[2]), "+f"(d[3]), "+f"(d[4]), "+f"(d[5]), "+f"(d[6]), "+f"(d[7])
               : "r"(a[0]), "r"(a[1]), "r"(a[2]), "r"(a[3]), "l"(db), "r"(sc));
}
__device__ __forceinline__ void wgmma_rt80(float (&d)[40], const uint32_t (&a)[4], uint64_t db, int sc) {
  asm volatile("{.reg .pred p; setp.ne.b32 p,%45,0; wgmma.mma_async.sync.aligned.m64n80k16.f32.bf16.bf16 "
               "{%0,%1,%2,%3,%4,%5,%6,%7,%8,%9,%10,%11,%12,%13,%14,%15,%16,%17,%18,%19,%20,%21,%22,%23,%24,%25,%26,%27,%28,%29,%30,%31,%32,%33,%34,%35,%36,%37,%38,%39},{%40,%41,%42,%43},%44,p,1,1,1;}"
               : "+f"(d[0]), "+f"(d[1]), "+f"(d[2]), "+f"(d[3]), "+f"(d[4]), "+f"(d[5]), "+f"(d[6]), "+f"(d[7]), "+f"(d[8]), "+f"(d[9]), "+f"(d[10]), "+f"(d[11]), "+f"(d[12]), "+f"(d[13]), "+f"(d[14]), "+f"(d[15]), "+f"(d[16]), "+f"(d[17]), "+f"(d[18]), "+f"(d[19]), "+f"(d[20]), "+f"(d[21]), "+f"(d[22]), "+f"(d[23]), "+f"(d[24]), "+f"(d[25]), "+f"(d[26]), "+f"(d[27]), "+f"(d[28]), "+f"(d[29]), "+f"(d[30]), "+f"(d[31]), "+f"(d[32]), "+f"(d[33]), "+f"(d[34]), "+f"(d[35]), "+f"(d[36]), "+f"(d[37]), "+f"(d[38]), "+f"(d[39])
               : "r"(a[0]), "r"(a[1]), "r"(a[2]), "r"(a[3]), "l"(db), "r"(sc));
}
__device__ __forceinline__ void wgmma_rs32(float (&d)[16], const uint32_t (&a)[4], uint64_t db, int sc) {
  asm volatile("{.reg .pred p; setp.ne.b32 p,%21,0; wgmma.mma_async.sync.aligned.m64n32k16.f32.bf16.bf16 "
               "{%0,%1,%2,%3,%4,%5,%6,%7,%8,%9,%10,%11,%12,%13,%14,%15},{%16,%17,%18,%19},%20,p,1,1,0;}"
               : "+f"(d[0]), "+f"(d[1]), "+f"(d[2]), "+f"(d[3]), "+f"(d[4]), "+f"(d[5]), "+f"(d[6]), "+f"(d[7]), "+f"(d[8]), "+f"(d[9]), "+f"(d[10]), "+f"(d[11]), "+f"(d[12]), "+f"(d[13]), "+f"(d[14]), "+f"(d[15])
               : "r"(a[0]), "r"(a[1]), "r"(a[2]), "r"(a[3]), "l"(db), "r"(sc));
}
__device__ __forceinline__ void wgmma_ts32(float (&d)[16], uint64_t da, uint64_t db, int sc) {
  asm volatile("{.reg .pred p; setp.ne.b32 p,%18,0; wgmma.mma_async.sync.aligned.m64n32k16.f32.bf16.bf16 "
               "{%0,%1,%2,%3,%4,%5,%6,%7,%8,%9,%10,%11,%12,%13,%14,%15},%16,%17,p,1,1,1,0;}"
               : "+f"(d[0]), "+f"(d[1]), "+f"(d[2]), "+f"(d[3]), "+f"(d[4]), "+f"(d[5]), "+f"(d[6]), "+f"(d[7]), "+f"(d[8]), "+f"(d[9]), "+f"(d[10]), "+f"(d[11]), "+f"(d[12]), "+f"(d[13]), "+f"(d[14]), "+f"(d[15])
               : "l"(da), "l"(db), "r"(sc));
}
__device__ __forceinline__ void wgmma_rs8(float (&d)[4], const uint32_t (&a)[4], uint64_t db, int sc) {
  asm volatile("{.reg .pred p; setp.ne.b32 p,%9,0; wgmma.mma_async.sync.aligned.m64n8k16.f32.bf16.bf16 "
               "{%0,%1,%2,%3},{%4,%5,%6,%7},%8,p,1,1,0;}"
               : "+f"(d[0]), "+f"(d[1]), "+f"(d[2]), "+f"(d[3])
               : "r"(a[0]), "r"(a[1]), "r"(a[2]), "r"(a[3]), "l"(db), "r"(sc));
}
__device__ __forceinline__ void wgmma_ts16(float (&d)[8], uint64_t da, uint64_t db, int sc) {
  asm volatile("{.reg .pred p; setp.ne.b32 p,%10,0; wgmma.mma_async.sync.aligned.m64n16k16.f32.bf16.bf16 "
               "{%0,%1,%2,%3,%4,%5,%6,%7},%8,%9,p,1,1,1,0;}"
               : "+f"(d[0]), "+f"(d[1]), "+f"(d[2]), "+f"(d[3]), "+f"(d[4]), "+f"(d[5]), "+f"(d[6]), "+f"(d[7])
               : "l"(da), "l"(db), "r"(sc));
}
__device__ __forceinline__ void wgmma_ts64(float (&d)[32], uint64_t da, uint64_t db, int sc) {
  asm volatile("{.reg .pred p; setp.ne.b32 p,%34,0; wgmma.mma_async.sync.aligned.m64n64k16.f32.bf16.bf16 "
               "{%0,%1,%2,%3,%4,%5,%6,%7,%8,%9,%10,%11,%12,%13,%14,%15,%16,%17,%18,%19,%20,%21,%22,%23,%24,%25,%26,%27,%28,%29,%30,%31},%32,%33,p,1,1,1,0;}"
               : "+f"(d[0]), "+f"(d[1]), "+f"(d[2]), "+f"(d[3]), "+f"(d[4]), "+f"(d[5]), "+f"(d[6]), "+f"(d[7]), "+f"(d[8]), "+f"(d[9]), "+f"(d[10]), "+f"(d[11]), "+f"(d[12]), "+f"(d[13]), "+f"(d[14]), "+f"(d[15]), "+f"(d[16]), "+f"(d[17]), "+f"(d[18]), "+f"(d[19]), "+f"(d[20]), "+f"(d[21]), "+f"(d[22]), "+f"(d[23]), "+f"(d[24]), "+f"(d[25]), "+f"(d[26]), "+f"(d[27]), "+f"(d[28]), "+f"(d[29]), "+f"(d[30]), "+f"(d[31])
               : "l"(da), "l"(db), "r"(sc));
}
__device__ __forceinline__ void wgmma_tt16(float (&d)[8], uint64_t da, uint64_t db, int sc) {
  asm volatile("{.reg .pred p; setp.ne.b32 p,%10,0; wgmma.mma_async.sync.aligned.m64n16k16.f32.bf16.bf16 "
               "{%0,%1,%2,%3,%4,%5,%6,%7},%8,%9,p,1,1,1,1;}"
               : "+f"(d[0]), "+f"(d[1]), "+f"(d[2]), "+f"(d[3]), "+f"(d[4]), "+f"(d[5]), "+f"(d[6]), "+f"(d[7])
               : "l"(da), "l"(db), "r"(sc));
}
__device__ __forceinline__ void wgmma_tt40(float (&d)[20], uint64_t da, uint64_t db, int sc) {
  asm volatile("{.reg .pred p; setp.ne.b32 p,%22,0; wgmma.mma_async.sync.aligned.m64n40k16.f32.bf16.bf16 "
               "{%0,%1,%2,%3,%4,%5,%6,%7,%8,%9,%10,%11,%12,%13,%14,%15,%16,%17,%18,%19},%20,%21,p,1,1,1,1;}"
               : "+f"(d[0]), "+f"(d[1]), "+f"(d[2]), "+f"(d[3]), "+f"(d[4]), "+f"(d[5]), "+f"(d[6]), "+f"(d[7]), "+f"(d[8]), "+f"(d[9]), "+f"(d[10]), "+f"(d[11]), "+f"(d[12]), "+f"(d[13]), "+f"(d[14]), "+f"(d[15]), "+f"(d[16]), "+f"(d[17]), "+f"(d[18]), "+f"(d[19])
               : "l"(da), "l"(db), "r"(sc));
}
__device__ __forceinline__ void wgmma_ss8(float (&d)[4], uint64_t da, uint64_t db, int sc) {
  asm volatile("{.reg .pred p; setp.ne.b32 p,%6,0; wgmma.mma_async.sync.aligned.m64n8k16.f32.bf16.bf16 "
               "{%0,%1,%2,%3},%4,%5,p,1,1,0,0;}"
               : "+f"(d[0]), "+f"(d[1]), "+f"(d[2]), "+f"(d[3])
               : "l"(da), "l"(db), "r"(sc));
}
__device__ __forceinline__ void wgmma_ss32(float (&d)[16], uint64_t da, uint64_t db, int sc) {
  asm volatile("{.reg .pred p; setp.ne.b32 p,%18,0; wgmma.mma_async.sync.aligned.m64n32k16.f32.bf16.bf16 "
               "{%0,%1,%2,%3,%4,%5,%6,%7,%8,%9,%10,%11,%12,%13,%14,%15},%16,%17,p,1,1,0,0;}"
               : "+f"(d[0]), "+f"(d[1]), "+f"(d[2]), "+f"(d[3]), "+f"(d[4]), "+f"(d[5]), "+f"(d[6]), "+f"(d[7]), "+f"(d[8]), "+f"(d[9]), "+f"(d[10]), "+f"(d[11]), "+f"(d[12]), "+f"(d[13]), "+f"(d[14]), "+f"(d[15])
               : "l"(da), "l"(db), "r"(sc));
}
__device__ __forceinline__ void wgmma_st64(float (&d)[32], uint64_t da, uint64_t db, int sc) {
  asm volatile("{.reg .pred p; setp.ne.b32 p,%34,0; wgmma.mma_async.sync.aligned.m64n64k16.f32.bf16.bf16 "
               "{%0,%1,%2,%3,%4,%5,%6,%7,%8,%9,%10,%11,%12,%13,%14,%15,%16,%17,%18,%19,%20,%21,%22,%23,%24,%25,%26,%27,%28,%29,%30,%31},%32,%33,p,1,1,0,1;}"
               : "+f"(d[0]), "+f"(d[1]), "+f"(d[2]), "+f"(d[3]), "+f"(d[4]), "+f"(d[5]), "+f"(d[6]), "+f"(d[7]), "+f"(d[8]), "+f"(d[9]), "+f"(d[10]), "+f"(d[11]), "+f"(d[12]), "+f"(d[13]), "+f"(d[14]), "+f"(d[15]), "+f"(d[16]), "+f"(d[17]), "+f"(d[18]), "+f"(d[19]), "+f"(d[20]), "+f"(d[21]), "+f"(d[22]), "+f"(d[23]), "+f"(d[24]), "+f"(d[25]), "+f"(d[26]), "+f"(d[27]), "+f"(d[28]), "+f"(d[29]), "+f"(d[30]), "+f"(d[31])
               : "l"(da), "l"(db), "r"(sc));
}
__device__ __forceinline__ void wgmma_st128(float (&d)[64], uint64_t da, uint64_t db, int sc) {
  asm volatile("{.reg .pred p; setp.ne.b32 p,%66,0; wgmma.mma_async.sync.aligned.m64n128k16.f32.bf16.bf16 "
               "{%0,%1,%2,%3,%4,%5,%6,%7,%8,%9,%10,%11,%12,%13,%14,%15,%16,%17,%18,%19,%20,%21,%22,%23,%24,%25,%26,%27,%28,%29,%30,%31,%32,%33,%34,%35,%36,%37,%38,%39,%40,%41,%42,%43,%44,%45,%46,%47,%48,%49,%50,%51,%52,%53,%54,%55,%56,%57,%58,%59,%60,%61,%62,%63},%64,%65,p,1,1,0,1;}"
               : "+f"(d[0]), "+f"(d[1]), "+f"(d[2]), "+f"(d[3]), "+f"(d[4]), "+f"(d[5]), "+f"(d[6]), "+f"(d[7]), "+f"(d[8]), "+f"(d[9]), "+f"(d[10]), "+f"(d[11]), "+f"(d[12]), "+f"(d[13]), "+f"(d[14]), "+f"(d[15]), "+f"(d[16]), "+f"(d[17]), "+f"(d[18]), "+f"(d[19]), "+f"(d[20]), "+f"(d[21]), "+f"(d[22]), "+f"(d[23]), "+f"(d[24]), "+f"(d[25]), "+f"(d[26]), "+f"(d[27]), "+f"(d[28]), "+f"(d[29]), "+f"(d[30]), "+f"(d[31]), "+f"(d[32]), "+f"(d[33]), "+f"(d[34]), "+f"(d[35]), "+f"(d[36]), "+f"(d[37]), "+f"(d[38]), "+f"(d[39]), "+f"(d[40]), "+f"(d[41]), "+f"(d[42]), "+f"(d[43]), "+f"(d[44]), "+f"(d[45]), "+f"(d[46]), "+f"(d[47]), "+f"(d[48]), "+f"(d[49]), "+f"(d[50]), "+f"(d[51]), "+f"(d[52]), "+f"(d[53]), "+f"(d[54]), "+f"(d[55]), "+f"(d[56]), "+f"(d[57]), "+f"(d[58]), "+f"(d[59]), "+f"(d[60]), "+f"(d[61]), "+f"(d[62]), "+f"(d[63])
               : "l"(da), "l"(db), "r"(sc));
}

__device__ __forceinline__ void stsm4(uint32_t a, uint32_t r0, uint32_t r1, uint32_t r2, uint32_t r3) {
  asm volatile("stmatrix.sync.aligned.m8n8.x4.shared.b16 [%0],{%1,%2,%3,%4};" ::"r"(a), "r"(r0), "r"(r1), "r"(r2), "r"(r3) : "memory");
}
__device__ __forceinline__ void stsm4t(uint32_t a, uint32_t r0, uint32_t r1, uint32_t r2, uint32_t r3) {
  asm volatile("stmatrix.sync.aligned.m8n8.x4.trans.shared.b16 [%0],{%1,%2,%3,%4};" ::"r"(a), "r"(r0), "r"(r1), "r"(r2), "r"(r3) : "memory");
}
__device__ __forceinline__ void sts64(uint32_t a, uint32_t x, uint32_t y) { asm volatile("st.shared.v2.b32 [%0],{%1,%2};" ::"r"(a), "r"(x), "r"(y) : "memory"); }
__device__ __forceinline__ void st_async2u(uint32_t a, uint32_t x, uint32_t y, uint32_t bar) {
  asm volatile("st.async.weak.shared::cluster.mbarrier::complete_tx::bytes.v2.b32 [%0],{%1,%2},[%3];" ::"r"(a), "r"(x), "r"(y), "r"(bar) : "memory");
}
__device__ __forceinline__ void st_relaxed128(void* p, uint32_t x, uint32_t y, uint32_t z, uint32_t w) {
  asm volatile("{.reg .b128 v; mov.b128 v,{%1,%2,%3,%4}; st.relaxed.gpu.global.b128 [%0],v;}" ::"l"(p), "r"(x), "r"(y), "r"(z), "r"(w) : "memory");
}
__device__ __forceinline__ void st_relaxed64(void* p, uint32_t x, uint32_t y) {
  asm volatile("{.reg .b64 v; mov.b64 v,{%1,%2}; st.relaxed.gpu.global.b64 [%0],v;}" ::"l"(p), "r"(x), "r"(y) : "memory");
}
__device__ __forceinline__ uint4 ld_relaxed128(const void* p) {
  uint4 v;
  asm volatile("{.reg .b128 v; .reg .b64 lo, hi; ld.relaxed.gpu.global.b128 v,[%4]; mov.b128 {lo,hi},v; mov.b64 {%0,%1},lo; mov.b64 {%2,%3},hi;}" : "=r"(v.x), "=r"(v.y), "=r"(v.z), "=r"(v.w) : "l"(p) : "memory");
  return v;
}

__device__ __forceinline__ uint32_t pack_h2(float lo, float hi) {
  uint32_t r; asm("cvt.rn.satfinite.f16x2.f32 %0,%1,%2;" : "=r"(r) : "f"(hi), "f"(lo)); return r;
}
__device__ __forceinline__ void add_h2(float& lo, float& hi, uint32_t u, uint32_t v) {
  float a, b;
  asm("{.reg .b16 l, h; .reg .b32 s; add.rn.f16x2 s,%2,%3; mov.b32 {l,h},s; cvt.f32.f16 %0,l; cvt.f32.f16 %1,h;}" : "=f"(a), "=f"(b) : "r"(u), "r"(v));
  lo += a; hi += b;
}
__device__ __forceinline__ void mwait(uint32_t bar, uint32_t ph, int& spin) {
  asm volatile("{.reg .pred p, q;\nWAIT_LOOP:\n add.s32 %0,%0,1;\n setp.lt.s32 q,%0,%3;\n mbarrier.try_wait.parity.shared::cta.b64 p,[%1],%2;\n not.pred p,p;\n and.pred q,q,p;\n @q bra.uni WAIT_LOOP;\n}"
               : "+&r"(spin) : "r"(bar), "r"(ph), "n"(SPIN_TOT) : "memory");
}
__device__ __forceinline__ int keep(int x) { return __shfl_sync(0xffffffffu, x, threadIdx.x & 31); }
__device__ __forceinline__ uint32_t pin(uint32_t x) { asm volatile("" : "+r"(x)); return x; }
template <typename T> __device__ __forceinline__ T* pinp(T* x) { asm volatile("" : "+l"(x)); return x; }
__device__ __forceinline__ void st_async1u(uint32_t a, uint32_t x, uint32_t bar) {
  asm volatile("st.async.weak.shared::cluster.mbarrier::complete_tx::bytes.b32 [%0],%1,[%2];" ::"r"(a), "r"(x), "r"(bar) : "memory");
}
__device__ __forceinline__ uint32_t lds32(uint32_t a) { uint32_t v; asm volatile("ld.shared.b32 %0,[%1];" : "=r"(v) : "r"(a) : "memory"); return v; }
__device__ __forceinline__ uint2 lds64(uint32_t a) { uint2 v; asm volatile("ld.shared.v2.b32 {%0,%1},[%2];" : "=r"(v.x), "=r"(v.y) : "r"(a) : "memory"); return v; }

__device__ __forceinline__ void permute_cols(uint32_t tile, int tid, int n) {
  for (int it = tid; it < n; it += 128) {
    const int row = it >> 2, q = it & 3;
    const uint32_t a0 = tile + row * 128 + (((2 * q) ^ (row & 7)) << 4), a1 = tile + row * 128 + (((2 * q + 1) ^ (row & 7)) << 4);
    const uint4 u = lds128(a0), v = lds128(a1);
    sts128(a0, make_uint4(__byte_perm(u.x, u.y, 0x5410), __byte_perm(u.z, u.w, 0x5410), __byte_perm(v.x, v.y, 0x5410), __byte_perm(v.z, v.w, 0x5410)));
    sts128(a1, make_uint4(__byte_perm(u.x, u.y, 0x7632), __byte_perm(u.z, u.w, 0x7632), __byte_perm(v.x, v.y, 0x7632), __byte_perm(v.z, v.w, 0x7632)));
  }
}

__device__ __forceinline__ uint8_t* mkptr(uint32_t lo, uint32_t hi) { uint8_t* p; asm("mov.b64 %0,{%1,%2};" : "=l"(p) : "r"(lo), "r"(hi)); return p; }
__device__ __forceinline__ int uni(int x) { return __shfl_sync(0xffffffffu, x, 0); }

__device__ __forceinline__ bool elect_one() {
  uint32_t p; asm volatile("{.reg .pred q; elect.sync _|q, 0xffffffff; selp.u32 %0,1,0,q;}" : "=r"(p)); return p;
}
__device__ __forceinline__ uint64_t desc_at(uint64_t d, uint32_t off) {
  uint64_t r; asm("mov.b64 %0,{%1,%2};" : "=l"(r) : "r"((uint32_t)d + (off >> 4)), "r"((uint32_t)(d >> 32))); return r;
}
__device__ __forceinline__ uint32_t scale_bf16x2(uint32_t x, uint32_t s) { uint32_t r; asm("mul.rn.bf16x2 %0,%1,%2;" : "=r"(r) : "r"(x), "r"(s)); return r; }

__device__ __forceinline__ void stg128(void* p, const uint4& v) { asm volatile("st.global.v4.b32 [%0],{%1,%2,%3,%4};" ::"l"(p), "r"(v.x), "r"(v.y), "r"(v.z), "r"(v.w) : "memory"); }

__device__ __forceinline__ void ln_row_to_image(const bf16* __restrict__ x, uint8_t* __restrict__ img, int row, int lane) {
  const uint4* src = reinterpret_cast<const uint4*>(x + (size_t)row * DM);
  uint4 v[3];
  v[0] = src[lane]; v[1] = src[lane + 32];
  v[2] = lane < 16 ? src[lane + 64] : make_uint4(0, 0, 0, 0);
  float s = 0.f;
#pragma unroll
  for (int i = 0; i < 3; i++) {
    s += bf_lo(v[i].x) + bf_hi(v[i].x) + bf_lo(v[i].y) + bf_hi(v[i].y) + bf_lo(v[i].z) + bf_hi(v[i].z) + bf_lo(v[i].w) + bf_hi(v[i].w);
  }
#pragma unroll
  for (int o = 16; o > 0; o >>= 1) s += __shfl_xor_sync(0xffffffffu, s, o);
  const float mean = s * (1.f / DM);
  float q = 0.f;
#pragma unroll
  for (int i = 0; i < 3; i++) {
    if (i < 2 || lane < 16) {
      const uint32_t w[4] = {v[i].x, v[i].y, v[i].z, v[i].w};
#pragma unroll
      for (int j = 0; j < 4; j++) { float a = bf_lo(w[j]) - mean, b = bf_hi(w[j]) - mean; q += a * a + b * b; }
    }
  }
#pragma unroll
  for (int o = 16; o > 0; o >>= 1) q += __shfl_xor_sync(0xffffffffu, q, o);
  const float rstd = rsqrtf(q * (1.f / DM) + 1e-5f);
#pragma unroll
  for (int i = 0; i < 3; i++) {
    if (i < 2 || lane < 16) {
      const int c = lane + 32 * i;
      uint4 o;
      o.x = pack_bf16((bf_lo(v[i].x) - mean) * rstd, (bf_hi(v[i].x) - mean) * rstd);
      o.y = pack_bf16((bf_lo(v[i].y) - mean) * rstd, (bf_hi(v[i].y) - mean) * rstd);
      o.z = pack_bf16((bf_lo(v[i].z) - mean) * rstd, (bf_hi(v[i].z) - mean) * rstd);
      o.w = pack_bf16((bf_lo(v[i].w) - mean) * rstd, (bf_hi(v[i].w) - mean) * rstd);
      const size_t off = (size_t)(row >> 5) * 81920 + (c >> 4) * 16384 + ((row >> 3) & 3) * 4096 + ((c >> 3) & 1) * 1024 + (row & 7) * 128 + (((c & 7) ^ (row & 7)) << 4);
      *reinterpret_cast<uint4*>(img + off) = o;
      float4* xf = reinterpret_cast<float4*>(g_x + (size_t)row * DM + c * 8);
      xf[0] = make_float4(bf_lo(v[i].x), bf_hi(v[i].x), bf_lo(v[i].y), bf_hi(v[i].y));
      xf[1] = make_float4(bf_lo(v[i].z), bf_hi(v[i].z), bf_lo(v[i].w), bf_hi(v[i].w));
    }
  }
}

#define NOWORK 0
__global__ void __launch_bounds__(256) k_pre(const bf16* __restrict__ x, const bf16* __restrict__ mem0) {
  const int row = blockIdx.x * 8 + (threadIdx.x >> 5);
  ln_row_to_image(x, g_xn[0], row, threadIdx.x & 31);
  const int gt = blockIdx.x * 256 + threadIdx.x;
  const uint4 sent = make_uint4(SENT, SENT, SENT, SENT);
  uint8_t* ex = ex_window(g_ex);
  if (gt < MAIL_BYTES / 16) {
    reinterpret_cast<uint4*>(ex + EX_MAIL)[gt] = sent;
    reinterpret_cast<uint4*>(ex + EX_MAIL + (1 << 20))[gt] = sent;
  }
  uint4* mb = reinterpret_cast<uint4*>(ex + EX_M);
  for (int i = gt; i < NSTEP * 1280; i += 65536) {
    const int p = i % 1280, st = i / 1280;
    uint4 v = sent;
    if (st == 0 || (st == LAG && (p & 8))) v = *reinterpret_cast<const uint4*>(mem0 + (p & 7) * DM + (p >> 4) * 8);
    mb[i] = v;
  }
  if (gt < NSTEP * 192) reinterpret_cast<uint4*>(ex + EX_FLAG)[gt] = gt < 192 ? make_uint4(0, 0, 0, 0) : sent;
  for (int i = gt; i < (NOWORK ? NSTEP + LAG : 2 * LAG) * 2560; i += 65536) {
    const int st = i / 2560, p = i % 2560;
    *reinterpret_cast<uint4*>(g_xn[st < LAG ? st + NSEG : st - LAG] + (p >> 7) * 4096 + (st < LAG ? 0 : 2048) + (p & 127) * 16) = make_uint4(0, 0, 0, 0);
  }
  if (gt < CN_NUM) g_cnt[gt][0] = 0;
}

namespace C {
constexpr int NKR = 37;
constexpr int OFF_WQ = 0, OFF_WK = 81920;
constexpr int OFF_YO = 163840, OFF_YV = OFF_YO + 6144;
constexpr int OFF_M = 176128;
__host__ __device__ constexpr int og_off(int c) { return c ? OFF_M + 14336 + c * 2048 : 229376; }
constexpr int OFF_KT = 196608;
constexpr int OFF_XT = OFF_KT + 10240;
constexpr int OFF_VT = OFF_XT + 7168;
constexpr int OFF_XM = OFF_VT + 11392;
constexpr int OFF_PT = OFF_XM + 2560;
constexpr int KS = 1280, VS = 1408;
__host__ __device__ constexpr int slot_off(int p) { return p == 2 ? OFF_M : OFF_KT + (p % 3) * 16384; }
constexpr int OFF_ONE = 231424;
constexpr int OFF_BAR = 231552;
constexpr int OFF_SAFE = OFF_BAR + 160;
constexpr int OFF_TS = OFF_BAR + 256;
constexpr int SMEM = 232448;
constexpr uint32_t SB0 = 1024;
constexpr int BAR_F = OFF_BAR, BAR_XM = BAR_F + 40, BAR_XT = BAR_F + 48, BAR_OG = BAR_F + 56, BAR_E = OFF_BAR + 64, BAR_MOK = BAR_E + 40,
              BAR_M = OFF_BAR + 112, BAR_XF = OFF_BAR + 120, BAR_MF = OFF_BAR + 128, BAR_W = OFF_BAR + 136, FLG_REDO = OFF_BAR + 144;
constexpr int NB_PRO = 1, NB_RD = 2, NB_MR = 3, NB_QK = 4, NB_SM = 5, NB_VA = 6, NB_VQ = 7, NB_A = 8, NB_Q = 9, NB_C = 10, NB_WQ = 11, NB_QI = 12, NB_SI = 13, NB_WV = 14;
#define B1 600
#define AD0 16
#define AD1 128
#define AD2 16
#define AD3 128
#define BMX 1200
#define B2 800
#define FLP 1
#define OSG 2
#define OST 7
#define P1U 4
#define QIE 4
#define SIE 2
#define WOE 1
#define OGF 0
#define VSP 8
#define RFK 5
#define PFD 3
#define WOL 0
constexpr uint32_t SCQ = 0x3A003A00;
constexpr float SCE = 0.07216878364870322f * 1.4426950408889634f * 2048;
}

#define CBAR_SYNC(id, n) bar_sync(id, n)
#define CBAR_ARRIVE(id, n) bar_arrive(id, n)

__device__ __forceinline__ uint64_t wdesc(int off) { return mkdesc(C::SB0 + off, 8192, 1024); }
__device__ __forceinline__ uint64_t mdesc(int k) { return mkdesc_ns(C::SB0 + C::OFF_M + k * 512, 256, 128); }
__device__ __forceinline__ uint64_t tdesc(int k) { return mkdesc(C::SB0 + C::slot_off(k >> 3) + ((k >> 2) & 1) * 1024 + (k & 3) * 32, 16, 2048); }

__device__ __forceinline__ int dh_row(int n) { return (n & ~63) + (n & 32) + ((n >> 1) & 3) * 8 + ((n >> 3) & 3) * 2 + (n & 1); }
template <bool PERM>
__device__ __forceinline__ void load_weights_rs(uint32_t (&wf)[C::NKR][4], uint32_t sb, int stage, int yoff, int tid0) {
  using namespace C;
  const int i = (tid0 >> 3) & 3, n0 = (tid0 & 7) + (i >> 1) * 8;
  const int chunk = 2 * ((tid0 >> 5) & 3) + (i & 1);
  const int r0 = PERM ? dh_row(n0) : n0, r1 = PERM ? dh_row(n0 + 16) : n0 + 16;
  const uint32_t a0 = sb + stage + r0 * 128 + ((chunk ^ (r0 & 7)) << 4), a1 = sb + stage + r1 * 128 + ((chunk ^ (r1 & 7)) << 4);
#pragma unroll
  for (int k = 0; k < NKR; k++) ldsm4t(wf[k], ((k & 1) ? a1 : a0) + (k >> 1) * 4096);
#pragma unroll
  for (int k = 0; k < 40 - NKR; k++) {
    const int n = (NKR + k) * 16 + ((tid0 & 127) >> 3), r = PERM ? dh_row(n) : n, c = tid0 & 7;
    sts128(sb + yoff + (n - NKR * 16) * 128 + ((c ^ (n & 7)) << 4), lds128(sb + stage + r * 128 + ((c ^ (r & 7)) << 4)));
  }
  fence_async();
  CBAR_SYNC(NB_PRO, 384);
}
template <int STRIDE>
__device__ __forceinline__ void store_mem(const float (&d)[8], uint32_t base, int tid) {
  const int m = (tid >> 3) & 3;
  stsm4(base + (((tid >> 5) & 3) * 2 + (m & 1)) * STRIDE + (m >> 1) * 640 + (tid & 7) * 16, pack_bf16(d[0], d[1]), pack_bf16(d[2], d[3]),
        pack_bf16(d[4], d[5]), pack_bf16(d[6], d[7]));
}

__device__ __forceinline__ void load_pair(uint32_t sb, int i, int p, uint32_t slot, uint32_t ph, int& spin) {
  using namespace C;
  mwait(sb + BAR_E + 8 * p, ph, spin);
  if (elect_one()) bulk_g2s_mc(sb + slot, g_xn[i] + p * 16384, 16384, sb + BAR_F + 8 * p);
}
__device__ __forceinline__ void release_round(uint32_t sb, int p, int lane) {
  if (lane < (p == 2 ? 3 : 1)) mbar_arrive_cluster(mapa(sb, p == 2 ? lane : p) + C::BAR_E + 8 * (3 + p));
}

template <int K0, int K1>
__device__ __forceinline__ void v_mem_pass(float (&d)[8], const uint32_t (&wf)[C::NKR][4]) {
  using namespace C;
  wg_fence();
#pragma unroll
  for (int k = K0; k < K1; k++) {
    if (k < NKR) wgmma_rs16(d, wf[k < NKR ? k : 0], mdesc(k), k != 32);
    else wgmma_ts16(d, wdesc(OFF_YV + (k - NKR) * 2048), mdesc(k), 1);
  }
  wg_commit();
}
__device__ __forceinline__ void chain_v(const uint32_t sb, const int tid0, const int cta, const int rank) {
  using namespace C;
  asm volatile("setmaxnreg.inc.sync.aligned.u32 208;");
  int spin = 0;
  uint32_t wf[NKR][4];
  const int wu = uni((tid0 >> 5) & 3);
  const uint32_t slot = rank == 2 ? OFF_M : OFF_KT + rank * 16384;
  if (wu == 0) load_pair(sb, 0, rank, slot, 1, spin);
  mwait(sb + BAR_W, 0, spin);
  for (int it = tid0 & 127; it < 1280; it += 128) {
    const uint32_t base = sb + OFF_WK + (it >> 1) * 128;
    const int sw = ((it >> 1) & 7) ^ ((it & 1) * 4);
    const uint4 u0 = lds128(base + (sw << 4)), u1 = lds128(base + ((sw ^ 1) << 4)), u2 = lds128(base + ((sw ^ 2) << 4)), u3 = lds128(base + ((sw ^ 3) << 4));
    sts128(base + (sw << 4), make_uint4(u0.x, u1.x, u2.x, u3.x)); sts128(base + ((sw ^ 1) << 4), make_uint4(u0.y, u1.y, u2.y, u3.y));
    sts128(base + ((sw ^ 2) << 4), make_uint4(u0.z, u1.z, u2.z, u3.z)); sts128(base + ((sw ^ 3) << 4), make_uint4(u0.w, u1.w, u2.w, u3.w));
  }
  bar_sync(NB_RD, 128);
  load_weights_rs<false>(wf, sb, OFF_WK, OFF_YV, tid0);
#pragma unroll 1
  for (int i = 0; i < NSTEP; i++) {
    {
      float d[32];
      if (i > 0) CBAR_SYNC(NB_WV, 256);
#pragma unroll
      for (int p = 0; p < 5; p++) {
        mwait(sb + BAR_F + 8 * p, i & 1, spin);
        TS(i, 25 + p);
        wg_fence();
#pragma unroll
        for (int k = 8 * p; k < 8 * p + 8; k++) {
          if (k < NKR) wgmma_rs64(d, wf[k < NKR ? k : 0], tdesc(k), k);
          else wgmma_ts64(d, wdesc(OFF_YV + (k - NKR) * 2048), tdesc(k), 1);
          if (k == 8 * p + 1 && p >= 1 && p <= 3) {
            wg_commit(); wg_wait<1>();
            release_round(sb, p - 1, tid0 & 31);
          }
          if (k == 8 * p + RFK && (p == 1 || p == 2)) {
            wg_commit();
            if (rank == p - 1 && wu == 0) load_pair(sb, i, p + 2, slot_off(p + 2), i & 1, spin);
            wg_fence();
          }
        }
        wg_commit();
      }
      wg_wait<0>();
      TS(i, 23);
      CBAR_SYNC(NB_RD, 256);
      const int tid = fresh(tid0) & 127, m = (tid >> 3) & 3;
      if (tid < 8) mbar_expect_tx(sb + BAR_F + 8 * tid, tid < 5 ? 16384 : tid == 5 ? 2560 : tid == 6 ? 7168 : 4096);
      if (tid < 3 && tid != rank) mbar_arrive_cluster(mapa(sb, tid) + BAR_XF);
      const uint32_t a = sb + OFF_VT + 256 + ((tid >> 5) * 2 + (m & 1)) * VS + (m >> 1) * 640 + (tid & 7) * 16;
#pragma unroll
      for (int s = 0; s < 4; s++)
        stsm4(a + s * 128, pack_bf16(d[8 * s], d[8 * s + 1]), pack_bf16(d[8 * s + 2], d[8 * s + 3]),
              pack_bf16(d[8 * s + 4], d[8 * s + 5]), pack_bf16(d[8 * s + 6], d[8 * s + 7]));
      if (tid < 80) sts128(sb + (tid < 72 ? OFF_VT + (tid >> 3) * VS : OFF_PT + 1280) + (tid & 7) * 16, make_uint4(0, 0, 0, 0));
      fence_async();
    }
    mwait(sb + BAR_XF, i & 1, spin);
    CBAR_ARRIVE(NB_QK, 384);
    const uint32_t* xc = &g_cnt[CN_X + i + 1 - LAG][0];
    bool seen = NOWORK || i + 1 < LAG;
    if (wu == 0 && !seen) { seen = ld_acquire(xc) >= 32; fence_async_all(); }
    CBAR_SYNC(NB_QI, 256);
    float d[8];
    v_mem_pass<32, 40>(d, wf);
    CBAR_SYNC(NB_SM, 256);
    wg_wait<0>();
    if (__builtin_expect(lds32(sb + FLG_REDO), 0)) { v_mem_pass<32, 40>(d, wf); wg_wait<0>(); }
    if ((tid0 & 31) < 3 && (tid0 & 31) != rank) mbar_arrive_cluster(mapa(sb, tid0 & 31) + BAR_MF);
    v_mem_pass<0, 32>(d, wf);
    wg_wait<0>();
    TS(i, 24);
    const int tid = fresh(tid0);
    if ((tid & 31) == 0) mbar_arrive_cluster(mapa(sb, 2) + BAR_E + 16);
    store_mem<VS>(d, sb + OFF_VT + 128, tid);
    fence_async();
    CBAR_ARRIVE(NB_VA, 256);
    CBAR_ARRIVE(NB_VQ, 256);
    if (wu == 0 && i + 1 < NSTEP) {
      if (__builtin_expect(!seen, 0)) { while (ld_acquire(xc) < 32 && spin < SPIN_TOT) spin += 16; fence_async_all(); }
      load_pair(sb, i + 1, rank, slot, i & 1, spin);
      TS(i + 1, 37);
    }
    TS_FLUSH(i - 1);
    __syncwarp();
  }
  CBAR_ARRIVE(NB_WV, 256);
  if (spin >= SPIN_TOT) g_err = 3;
}

__device__ __forceinline__ float quad_max(float x) {
  const float a = __shfl_xor_sync(0xffffffffu, x, 1), b = __shfl_xor_sync(0xffffffffu, x, 2), c = __shfl_xor_sync(0xffffffffu, x, 3);
  return fmaxf(fmaxf(x, a), fmaxf(b, c));
}
__device__ __forceinline__ float quad_sum(float x) {
  const float a = __shfl_xor_sync(0xffffffffu, x, 1), b = __shfl_xor_sync(0xffffffffu, x, 2), c = __shfl_xor_sync(0xffffffffu, x, 3);
  return (x + a) + (b + c);
}
__device__ __forceinline__ float max10(const float (&y)[10]) {
  return fmaxf(fmaxf(fmaxf(fmaxf(y[0], y[1]), fmaxf(y[2], y[3])), fmaxf(fmaxf(y[4], y[5]), fmaxf(y[6], y[7]))), fmaxf(y[8], y[9]));
}
__device__ __forceinline__ float sum10(const float (&y)[10]) {
  return (((y[0] + y[1]) + (y[2] + y[3])) + ((y[4] + y[5]) + (y[6] + y[7]))) + (y[8] + y[9]);
}
__device__ __forceinline__ float rcp(float x) { float y; asm("rcp.approx.ftz.f32 %0,%1;" : "=f"(y) : "f"(x)); return y; }

__device__ __forceinline__ void signal_o(int i, int cta) { csignal(CN_O + i * 5 + min(cta / 19, 4)); }

__device__ __forceinline__ void chain_q(const CUtensorMap& tmWq, const CUtensorMap& tmWk, const uint32_t sb, const int tid0, const int cta, const int rank) {
  using namespace C;
  asm volatile("setmaxnreg.dec.sync.aligned.u32 96;");
  int spin = 0;
  CBAR_SYNC(NB_PRO, 384);
  PTS(5);
  if (tid0 == 128) {
    const int col = (cta / 3) * DH + rank * 64;
    mbar_expect_tx(sb + BAR_W, 163840);
    for (int i = 0; i < 5; i++) {
      tma2d(sb + OFF_WQ + i * 16384, &tmWq, col, i * 128, sb + BAR_W);
      tma2d(sb + OFF_WK + i * 16384, &tmWk, col, i * 128, sb + BAR_W);
    }
  }
  __syncwarp();
  mwait(sb + BAR_W, 1, spin);
  PTS(6);
  const int wu = uni((tid0 >> 5) & 3);
  uint4 ov[4] = {};
  uint8_t* op = &g_o[ORING - 1][cta][(tid0 & 124) * 32];
  const uint32_t o0 = ((tid0 ^ (tid0 >> 2)) & 3) * 16 + (tid0 & 16) * 4;
#pragma unroll 1
  for (int i = 0; i < NSTEP; i++) {
    const int ph = i & 1;
    uint32_t qf[4][4];
    {
      float d[64];
#define QK_STEP(K, SC) wgmma_st128(d, desc_at(mkdesc(SB0 + ((K) >> 2) * 1024 + ((K) & 3) * 32, 16, 2048), so), \
                                   desc_at(mkdesc(SB0 + OFF_WQ + (K) * 2048, OFF_WK - OFF_WQ, 1024), p * 16384), SC)
      int p = 0;
      uint32_t so = OFF_KT;
      mwait(sb + BAR_F, ph, spin);
      TS(i, 0);
      wg_fence();
#pragma unroll
      for (int k = 0; k < 8; k++) {
        QK_STEP(k, k);
        if (k == OST) {
          wg_commit();
          mwait(sb + BAR_F, ph, spin);
#pragma unroll
          for (int h = 0; h < 4; h++) stg128(op + (h & 1) * 4096 + (o0 ^ ((h >> 1) * 64)), ov[h]);
          if (i > 0) CBAR_ARRIVE(NB_MR, 160);
          if (k < 7) wg_fence();
        }
      }
      if (OST < 7) wg_commit();
#pragma unroll 1
      for (p = 1; p < 5; p++) {
        static_assert(OFF_KT - OFF_M == 5 << 12, "");
        so = OFF_M + (((0x95095u >> (4 * p)) & 15) << 12);
        mwait(sb + BAR_F + 8 * p, ph, spin);
        wg_fence();
#pragma unroll
        for (int k = 0; k < 8; k++) {
          QK_STEP(k, 1);
          if (k == 1) {
            wg_commit(); wg_wait<1>();
            release_round(sb, p - 1, p < 4 ? tid0 & 31 : 32);
          }
        }
        wg_commit();
      }
#undef QK_STEP
      wg_wait<0>();
      TS(i, 1);
      CBAR_SYNC(NB_RD, 256);
      TSB(i, 2);
      const int tid = fresh(tid0), w = (tid >> 5) & 3, m = (tid >> 3) & 3;
      const uint32_t a = sb + OFF_KT + (m >> 1) * KS + (1 + w + 5 * (m & 1)) * 128 + (tid & 7) * 16;
#pragma unroll
      for (int s = 0; s < 4; s++)
        stsm4t(a + s * 2 * KS, pack_bf16(d[32 + 8 * s], d[33 + 8 * s]), pack_bf16(d[34 + 8 * s], d[35 + 8 * s]),
               pack_bf16(d[36 + 8 * s], d[37 + 8 * s]), pack_bf16(d[38 + 8 * s], d[39 + 8 * s]));
      fence_async();
      CBAR_ARRIVE(NB_QK, 384);
#pragma unroll
      for (int kk = 0; kk < 4; kk++)
#pragma unroll
        for (int j = 0; j < 4; j++) asm volatile("{.reg .b32 t; cvt.rn.bf16x2.f32 t,%1,%2; mul.rn.bf16x2 %0,t,%3;}" : "=r"(qf[kk][j]) : "f"(d[8 * kk + 2 * j + 1]), "f"(d[8 * kk + 2 * j]), "r"(SCQ));
    }
    CBAR_SYNC(NB_SI, 256);
    uint32_t pf[5][4];
    {
      float y0[10], y1[10];
      const int tidf = fresh(tid0), lane = tidf & 31;
      {
        float x[40];
        wg_fence();
#pragma unroll
        for (int kk = 0; kk < 4; kk++) wgmma_rt80(x, qf[kk], mkdesc_ns(SB0 + OFF_KT + kk * 2 * KS, KS, 128), kk);
        wg_commit();
        wg_wait<0>();
#pragma unroll
        for (int j = 0; j < 5; j++) { y0[2 * j] = x[4 * j]; y0[2 * j + 1] = x[4 * j + 1]; y1[2 * j] = x[22 + 4 * j]; y1[2 * j + 1] = x[23 + 4 * j]; }
      }
      TS(i, 17);
      const uint32_t xo = OFF_XT + (wu * (wu + 3) / 2) * 256 + lane * 16, x2 = xo + (wu >> 1) * 512 + 512 - lane * 8;
      {
        const uint4 h0 = make_uint4(pack_h2(y0[0], y0[1]), pack_h2(y1[0], y1[1]), pack_h2(y0[2], y0[3]), pack_h2(y1[2], y1[3]));
        const uint4 h1 = make_uint4(pack_h2(y0[4], y0[5]), pack_h2(y1[4], y1[5]), pack_h2(y0[6], y0[7]), pack_h2(y1[6], y1[7]));
        const uint32_t h2 = wu == 1 ? h1.x : pack_h2(y0[8], y0[9]), h3 = wu == 1 ? h1.y : pack_h2(y1[8], y1[9]);
        const uint32_t rb1 = mapa(sb, (rank + 1) % 3), rb2 = mapa(sb, (rank + 2) % 3);
        st_async4u(rb1 + xo + 3584, h0, rb1 + BAR_XT);
        st_async4u(rb2 + xo, h0, rb2 + BAR_XT);
        if (wu >= 2) { st_async4u(rb1 + xo + 4096, h1, rb1 + BAR_XT); st_async4u(rb2 + xo + 512, h1, rb2 + BAR_XT); }
        if (wu & 1) { st_async2u(rb1 + x2 + 3584, h2, h3, rb1 + BAR_XT); st_async2u(rb2 + x2, h2, h3, rb2 + BAR_XT); }
      }
      TS(i, 18);
      const int lim = 8 * wu + (lane >> 2) + 8 - 2 * (lane & 3);
#pragma unroll
      for (int j = 2; j < 10; j++)
        if (8 * (j >> 1) + (j & 1) > lim) { y0[j] = -INFINITY; y1[j] = -INFINITY; }
      mwait(sb + BAR_XT, ph, spin);
      TS(i, 19);
      {
        const uint4 u0 = lds128(sb + xo), v0 = lds128(sb + xo + 3584);
        uint2 u2 = make_uint2(0, 0), v2 = u2;
        if (wu & 1) { u2 = lds64(sb + x2); v2 = lds64(sb + x2 + 3584); }
        uint4 u1 = make_uint4(u2.x, u2.y, 0, 0), v1 = make_uint4(v2.x, v2.y, 0, 0);
        if (wu >= 2) { u1 = lds128(sb + xo + 512); v1 = lds128(sb + xo + 4096); }
        __syncwarp();
        if (lane == 0) mbar_arrive_cluster(mapa(sb, 0) + BAR_E);
        add_h2(y0[0], y0[1], u0.x, v0.x); add_h2(y1[0], y1[1], u0.y, v0.y); add_h2(y0[2], y0[3], u0.z, v0.z); add_h2(y1[2], y1[3], u0.w, v0.w);
        add_h2(y0[4], y0[5], u1.x, v1.x); add_h2(y1[4], y1[5], u1.y, v1.y); add_h2(y0[6], y0[7], u1.z, v1.z); add_h2(y1[6], y1[7], u1.w, v1.w);
        add_h2(y0[8], y0[9], u2.x, v2.x); add_h2(y1[8], y1[9], u2.y, v2.y);
      }
      const float m0 = quad_max(max10(y0)) * -SCE, m1 = quad_max(max10(y1)) * -SCE;
#pragma unroll
      for (int j = 0; j < 5; j++) {
        pf[j >> 1][2 * (j & 1)] = pack_bf16(ex2(fmaf(y0[2 * j], SCE, m0)), ex2(fmaf(y0[2 * j + 1], SCE, m0)));
        pf[j >> 1][2 * (j & 1) + 1] = tidf >> (10 + j);
        pf[(j + 5) >> 1][2 * ((j + 5) & 1)] = tidf >> (20 + j);
        pf[(j + 5) >> 1][2 * ((j + 5) & 1) + 1] = pack_bf16(ex2(fmaf(y1[2 * j], SCE, m1)), ex2(fmaf(y1[2 * j + 1], SCE, m1)));
      }
    }
#pragma unroll
    for (int q = 0; q < 20; q++) pf[q >> 2][q & 3] = pin(pf[q >> 2][q & 3]);
    CBAR_SYNC(NB_VQ, 256);
    TSB(i, 20);
    {
      float o[32], sm[4];
      wg_fence();
#pragma unroll
      for (int q = 0; q < 5; q++) wgmma_rs8(sm, pf[q], mkdesc_ns(SB0 + OFF_ONE, 0, 0), q);
#pragma unroll
      for (int q = 0; q < 5; q++) wgmma_rs64(o, pf[q], mkdesc_ns(SB0 + OFF_VT + 128 + q * 256, 128, VS), q);
      wg_commit();
      const int tid = fresh(tid0);
      op = &g_o[i % ORING][cta][(tid & 124) * 32];
      wg_wait<0>();
      TS(i, 21);
      if ((tid & 31) == 0) mbar_arrive_cluster(mapa(sb, 1) + BAR_E + 8);
      const float s0 = rcp(sm[0]), s1 = rcp(sm[2]);
#pragma unroll
      for (int h = 0; h < 2; h++) {
        const float* x = o + 16 * h;
        ov[2 * h] = make_uint4(pin(pack_bf16(x[0] * s0, x[1] * s0)), pin(pack_bf16(x[4] * s0, x[5] * s0)), pin(pack_bf16(x[8] * s0, x[9] * s0)), pin(pack_bf16(x[12] * s0, x[13] * s0)));
        ov[2 * h + 1] = make_uint4(pin(pack_bf16(x[2] * s1, x[3] * s1)), pin(pack_bf16(x[6] * s1, x[7] * s1)), pin(pack_bf16(x[10] * s1, x[11] * s1)), pin(pack_bf16(x[14] * s1, x[15] * s1)));
      }
      TS(i, 22);
      if (i + 1 < NSTEP) CBAR_SYNC(NB_WQ, 256); else CBAR_ARRIVE(NB_WQ, 256);
    }
  }
#pragma unroll
  for (int h = 0; h < 4; h++) stg128(op + (h & 1) * 4096 + (o0 ^ ((h >> 1) * 64)), ov[h]);
  CBAR_SYNC(NB_Q, 128);
  if (tid0 == 224) signal_o(NSTEP - 1, cta);
  if (spin >= SPIN_TOT) g_err = 2;
}

template <int NL> __device__ __forceinline__ void poll(uint4 (&x)[NL], const uint8_t* mb, uint32_t tag, int& spin);
template <> __device__ __forceinline__ void poll<4>(uint4 (&x)[4], const uint8_t* mb, uint32_t tag, int& spin) {
  asm volatile("{.reg .pred p<6>, q; .reg .b128 v; .reg .b32 t;\n"
               " ld.relaxed.gpu.global.b128 v,[%17+0]; mov.b128 {%0,%1,%2,%3},v;\n"
               " ld.relaxed.gpu.global.b128 v,[%17+512]; mov.b128 {%4,%5,%6,%7},v;\n"
               " ld.relaxed.gpu.global.b128 v,[%17+1024]; mov.b128 {%8,%9,%10,%11},v;\n"
               " ld.relaxed.gpu.global.b128 v,[%17+1536]; mov.b128 {%12,%13,%14,%15},v;\n"
               "POLL_LOOP:\n add.s32 %16,%16,16;\n"
               " lop3.b32 t,%0,%18,1,0x28; setp.ne.b32 p0,t,0;\n"
               " lop3.b32 t,%4,%18,1,0x28; setp.ne.b32 p1,t,0;\n"
               " lop3.b32 t,%8,%18,1,0x28; setp.ne.b32 p2,t,0;\n"
               " lop3.b32 t,%12,%18,1,0x28; setp.ne.b32 p3,t,0;\n"
               " or.pred q,p0,p1; or.pred q,q,p2; or.pred q,q,p3; setp.lt.and.s32 q,%16,%19,q; vote.sync.any.pred q,q,0xffffffff;\n"
               " mov.b128 v,{%0,%1,%2,%3}; @p0 ld.relaxed.gpu.global.b128 v,[%17+0]; mov.b128 {%0,%1,%2,%3},v;\n"
               " mov.b128 v,{%4,%5,%6,%7}; @p1 ld.relaxed.gpu.global.b128 v,[%17+512]; mov.b128 {%4,%5,%6,%7},v;\n"
               " mov.b128 v,{%8,%9,%10,%11}; @p2 ld.relaxed.gpu.global.b128 v,[%17+1024]; mov.b128 {%8,%9,%10,%11},v;\n"
               " mov.b128 v,{%12,%13,%14,%15}; @p3 ld.relaxed.gpu.global.b128 v,[%17+1536]; mov.b128 {%12,%13,%14,%15},v;\n"
               " @q bra.uni POLL_LOOP;\n}"
               : "=&r"(x[0].x), "=&r"(x[0].y), "=&r"(x[0].z), "=&r"(x[0].w), "=&r"(x[1].x), "=&r"(x[1].y), "=&r"(x[1].z), "=&r"(x[1].w), "=&r"(x[2].x), "=&r"(x[2].y), "=&r"(x[2].z), "=&r"(x[2].w), "=&r"(x[3].x), "=&r"(x[3].y), "=&r"(x[3].z), "=&r"(x[3].w), "+&r"(spin)
               : "l"(mb), "r"(tag), "n"(SPIN_TOT) : "memory");
}
template <> __device__ __forceinline__ void poll<6>(uint4 (&x)[6], const uint8_t* mb, uint32_t tag, int& spin) {
  asm volatile("{.reg .pred p<6>, q; .reg .b128 v; .reg .b32 t;\n"
               " ld.relaxed.gpu.global.b128 v,[%25+0]; mov.b128 {%0,%1,%2,%3},v;\n"
               " ld.relaxed.gpu.global.b128 v,[%25+512]; mov.b128 {%4,%5,%6,%7},v;\n"
               " ld.relaxed.gpu.global.b128 v,[%25+1024]; mov.b128 {%8,%9,%10,%11},v;\n"
               " ld.relaxed.gpu.global.b128 v,[%25+1536]; mov.b128 {%12,%13,%14,%15},v;\n"
               " ld.relaxed.gpu.global.b128 v,[%25+2048]; mov.b128 {%16,%17,%18,%19},v;\n"
               " ld.relaxed.gpu.global.b128 v,[%25+2560]; mov.b128 {%20,%21,%22,%23},v;\n"
               "POLL_LOOP:\n add.s32 %24,%24,16;\n"
               " lop3.b32 t,%0,%2,%26,0x7e; and.b32 t,t,1; setp.ne.b32 p0,t,0;\n"
               " lop3.b32 t,%4,%6,%26,0x7e; and.b32 t,t,1; setp.ne.b32 p1,t,0;\n"
               " lop3.b32 t,%8,%10,%26,0x7e; and.b32 t,t,1; setp.ne.b32 p2,t,0;\n"
               " lop3.b32 t,%12,%14,%26,0x7e; and.b32 t,t,1; setp.ne.b32 p3,t,0;\n"
               " lop3.b32 t,%16,%18,%26,0x7e; and.b32 t,t,1; setp.ne.b32 p4,t,0;\n"
               " lop3.b32 t,%20,%22,%26,0x7e; and.b32 t,t,1; setp.ne.b32 p5,t,0;\n"
               " or.pred q,p0,p1; or.pred q,q,p2; or.pred q,q,p3; or.pred q,q,p4; or.pred q,q,p5; setp.lt.and.s32 q,%24,%27,q; vote.sync.any.pred q,q,0xffffffff;\n"
               " mov.b128 v,{%0,%1,%2,%3}; @p0 ld.relaxed.gpu.global.b128 v,[%25+0]; mov.b128 {%0,%1,%2,%3},v;\n"
               " mov.b128 v,{%4,%5,%6,%7}; @p1 ld.relaxed.gpu.global.b128 v,[%25+512]; mov.b128 {%4,%5,%6,%7},v;\n"
               " mov.b128 v,{%8,%9,%10,%11}; @p2 ld.relaxed.gpu.global.b128 v,[%25+1024]; mov.b128 {%8,%9,%10,%11},v;\n"
               " mov.b128 v,{%12,%13,%14,%15}; @p3 ld.relaxed.gpu.global.b128 v,[%25+1536]; mov.b128 {%12,%13,%14,%15},v;\n"
               " mov.b128 v,{%16,%17,%18,%19}; @p4 ld.relaxed.gpu.global.b128 v,[%25+2048]; mov.b128 {%16,%17,%18,%19},v;\n"
               " mov.b128 v,{%20,%21,%22,%23}; @p5 ld.relaxed.gpu.global.b128 v,[%25+2560]; mov.b128 {%20,%21,%22,%23},v;\n"
               " @q bra.uni POLL_LOOP;\n}"
               : "=&r"(x[0].x), "=&r"(x[0].y), "=&r"(x[0].z), "=&r"(x[0].w), "=&r"(x[1].x), "=&r"(x[1].y), "=&r"(x[1].z), "=&r"(x[1].w), "=&r"(x[2].x), "=&r"(x[2].y), "=&r"(x[2].z), "=&r"(x[2].w), "=&r"(x[3].x), "=&r"(x[3].y), "=&r"(x[3].z), "=&r"(x[3].w), "=&r"(x[4].x), "=&r"(x[4].y), "=&r"(x[4].z), "=&r"(x[4].w), "=&r"(x[5].x), "=&r"(x[5].y), "=&r"(x[5].z), "=&r"(x[5].w), "+&r"(spin)
               : "l"(mb), "r"(tag), "n"(SPIN_TOT) : "memory");
}
template <int NL>
__device__ __forceinline__ void poll_add(const uint8_t* mb, uint32_t tag, float (&f)[8], uint8_t* flag, bool lead, int& spin) {
  uint4 x[NL];
  poll<NL>(x, mb, tag, spin);
  if (FLP == 0 && lead) st_relaxed(flag, 0);
#pragma unroll
  for (int i = 0; i < NL; i++) {
    const uint32_t u[4] = {x[i].x, x[i].y, x[i].z, x[i].w};
#pragma unroll
    for (int j = 0; j < 4; j++) {
      if (i == 0) { f[2 * j] = bf_lo(u[j]); f[2 * j + 1] = bf_hi(u[j]); }
      else { f[2 * j] += bf_lo(u[j]); f[2 * j + 1] += bf_hi(u[j]); }
    }
  }
}

template <int B, int SLOT>
__device__ __forceinline__ void wo_step(float (&acc)[8], const uint32_t (&wf)[C::NKR][4], int kk) {
  using namespace C;
  const int k = 4 * B + kk;
  const uint64_t db = mkdesc_ns(SB0 + og_off(SLOT) + kk * 512, 256, 128);
  if (k < NKR) wgmma_rt16(acc, wf[k < NKR ? k : 0], db, SLOT | kk);
  else wgmma_tt16(acc, wdesc(OFF_YO + (k - NKR) * 2048), db, 1);
}
template <int B, int SLOT>
__device__ __forceinline__ void wo_block(float (&acc)[8], const uint32_t (&wf)[C::NKR][4]) {
#pragma unroll
  for (int kk = 0; kk < 4; kk++) wo_step<B, SLOT>(acc, wf, kk);
}

__device__ __forceinline__ void chain_a(const uint32_t sb, const int tid0, const int cta, const int rank) {
  using namespace C;
  asm volatile("setmaxnreg.inc.sync.aligned.u32 200;");
  int spin = 0;
  uint32_t wf[NKR][4];
  mwait(sb + BAR_W, 0, spin);
  permute_cols(sb + OFF_WQ, tid0, 2560);
  CBAR_SYNC(NB_A, 128);
  load_weights_rs<true>(wf, sb, OFF_WQ, OFF_YO, tid0);
  const int wu = uni(tid0 >> 5);
  const bool t9 = cta >= 72 && cta < 88;
  const uint64_t exa = reinterpret_cast<uint64_t>(ex_window(g_ex));
  const uint32_t ehi = (uint32_t)(exa >> 32), elo = (uint32_t)exa;

  int b1 = B1, b2 = B2;
#pragma unroll 1
  for (int i = -1; i < NSTEP; i++) {
    const int ph = i & 1;
    if (i >= 0) {
      const int tid = fresh(tid0);
      const uint32_t mo = __shfl_xor_sync(0xffffffffu, elo + (ph << 20) + ((rank * 24 + (tid >> 4)) * 4 + (tid & 3)) * 2048 + (cta / 3) * 64 + (tid & 12) * 4, 0);
      const uint32_t m9 = __shfl_xor_sync(0xffffffffu, elo + (ph << 20) + MAIL9 + (((tid >> 4) * 2 + (tid & 1)) * 4 + (tid & 2)) * 3072 + cta * 32 + (tid & 12) * 2, 0);
      const uint32_t oo = __shfl_xor_sync(0xffffffffu, (tid >> 5) * 512 + (tid & 2) * 64 + (tid & 28) * 4 + (tid & 1) * 8, 0);
      if (i == 0) mwait(sb + BAR_W, 1, spin);
      mwait(sb + BAR_M, ph, spin);
      TS(i, 3);
      {
        float x[20];
        int redo = 0;
      retry:
        bool bad;
        {
          float dq[8] = {}, dk[8] = {};
#pragma unroll 1
          for (int k0 = 0; k0 < 40; k0 += P1U) {
            wg_fence();
#pragma unroll
            for (int k = 0; k < P1U; k++) {
              if (k == P1U - QIE / 2 && k0 == 40 - P1U && !redo) CBAR_ARRIVE(NB_QI, 256);
              const uint64_t db = desc_at(mdesc(k), k0 * 512);
              wgmma_ts16(dq, desc_at(wdesc(OFF_WQ + k * 2048), k0 * 2048), db, 1);
              wgmma_ts16(dk, desc_at(wdesc(OFF_WK + k * 2048), k0 * 2048), db, 1);
            }
            wg_commit();
          }
          const int m = (tid >> 3) & 3, dg = (tid >> 5) * 2 + (m & 1);
          const uint32_t ka = sb + OFF_KT + dg * KS + (m >> 1) * 640 + (tid & 7) * 16;
          if (!redo) CBAR_SYNC(NB_QK, 384);
          sts32(sb + FLG_REDO, redo);
          wg_wait<0>();
          TS(i, 4);
          stsm4(ka, pack_bf16(dk[0], dk[1]), pack_bf16(dk[2], dk[3]), pack_bf16(dk[4], dk[5]), pack_bf16(dk[6], dk[7]));
          stsm4(ka + dg * (VS - KS) + (OFF_VT + 128 - OFF_KT), scale_bf16x2(pack_bf16(dq[0], dq[1]), SCQ), scale_bf16x2(pack_bf16(dq[2], dq[3]), SCQ),
                scale_bf16x2(pack_bf16(dq[4], dq[5]), SCQ), scale_bf16x2(pack_bf16(dq[6], dq[7]), SCQ));
          const float chk = (dq[0] + dq[1]) + (dq[4] + dq[5]);
          fence_async();
          bad = bar_red_or(NB_C, 128, chk != chk && !redo);
        }
        TSB(i, 5);
        wg_fence();
#pragma unroll
        for (int kk = 0; kk < 4; kk++) wgmma_tt40(x, mkdesc_ns(SB0 + OFF_VT + 128 + kk * 2 * VS, VS, 640), mkdesc_ns(SB0 + OFF_KT + kk * 2 * KS, KS, 128), kk);
#pragma unroll
        for (int kk = 0; kk < 4; kk++) {
          if (SIE && kk == 4 - SIE && !bad) CBAR_ARRIVE(NB_SI, 256);
          wgmma_tt40(x, mkdesc_ns(SB0 + OFF_VT + kk * 2 * VS, VS, 384), mkdesc_ns(SB0 + OFF_KT + 640 + kk * 2 * KS, KS, 128), 1);
        }
        wg_commit();
        if (!SIE && !bad) CBAR_ARRIVE(NB_SI, 256);
        if (__builtin_expect(__any_sync(0xffffffffu, bad), 0)) {
          wg_wait<0>();
#pragma unroll 1
          for (int k = 0; k < 10; k++) {
            uint4 v = lds128(sb + OFF_M + tid * 16 + k * 2048);
            if (v.x == SENT || v.y == SENT || v.z == SENT || v.w == SENT) {
              do { v = ld_relaxed4(mkptr(elo + EX_M + i * 20480 + tid * 16 + k * 2048, ehi)); spin += 16; } while ((v.x == SENT || v.y == SENT || v.z == SENT || v.w == SENT) && spin < SPIN_TOT);
              sts128(sb + OFF_M + tid * 16 + k * 2048, v);
            }
          }
          fence_async();
          bar_sync(NB_C, 128);
          redo = fresh(1);
          goto retry;
        }
        TSV(i, 36, redo);
        const uint32_t rb1 = mapa(sb, (rank + 1) % 3), rb2 = mapa(sb, (rank + 2) % 3);
        wg_wait<0>();
        TS(i, 6);
        if (wu < 2) {
          float y[10];
#pragma unroll
          for (int j = 0; j < 5; j++) { y[2 * j] = x[4 * j]; y[2 * j + 1] = x[4 * j + 1]; }
          const uint4 h0 = make_uint4(pack_h2(y[0], y[1]), pack_h2(y[2], y[3]), pack_h2(y[4], y[5]), pack_h2(y[6], y[7]));
          const uint32_t h1 = pack_h2(y[8], y[9]);
          st_async4u(rb1 + OFF_XM + 1024 + tid * 16, h0, rb1 + BAR_XM);
          st_async4u(rb2 + OFF_XM + tid * 16, h0, rb2 + BAR_XM);
          st_async1u(rb1 + OFF_XM + 2304 + tid * 4, h1, rb1 + BAR_XM);
          st_async1u(rb2 + OFF_XM + 2048 + tid * 4, h1, rb2 + BAR_XM);
          CBAR_ARRIVE(NB_SM, 256);
          if ((tid & 31) == 0) mbar_arrive_cluster(mapa(sb, 0) + BAR_E);
          TS(i, 7);
          const uint32_t sw = (tid & 7) * 4 + (tid & 8) * 8 + (tid & 16) * 2;
          mwait(sb + BAR_XM, ph, spin);
          TS(i, 8);
          const uint4 u0 = lds128(sb + OFF_XM + tid * 16), v0 = lds128(sb + OFF_XM + 1024 + tid * 16);
          const uint32_t u1 = lds32(sb + OFF_XM + 2048 + tid * 4), v1 = lds32(sb + OFF_XM + 2304 + tid * 4);
          add_h2(y[0], y[1], u0.x, v0.x); add_h2(y[2], y[3], u0.y, v0.y); add_h2(y[4], y[5], u0.z, v0.z); add_h2(y[6], y[7], u0.w, v0.w);
          add_h2(y[8], y[9], u1, v1);
          const float mx = quad_max(max10(y)) * -SCE;
#pragma unroll
          for (int j = 0; j < 5; j++) {
            y[2 * j] = ex2(fmaf(y[2 * j], SCE, mx)); y[2 * j + 1] = ex2(fmaf(y[2 * j + 1], SCE, mx));
            sts32(sb + OFF_PT + wu * 640 + sw + j * 128, pack_bf16(y[2 * j], y[2 * j + 1]));
          }
          sts32(sb + OFF_XM + 2048 + wu * 128 + sw, __float_as_uint(sum10(y)));
          fence_async();
          TS(i, 9);
        } else {
          CBAR_ARRIVE(NB_SM, 256);
          if ((tid & 31) == 0) mbar_arrive_cluster(mapa(sb, 0) + BAR_E);
          mwait(sb + BAR_MF, ph, spin);
        }
      }
      CBAR_SYNC(NB_VA, 256);
      TSB(i, 10);
      {
        float o[2][4];
        wg_fence();
#pragma unroll
        for (int c = 0; c < 2; c++)
#pragma unroll
          for (int q = 0; q < 3; q++)
            wgmma_ss8(o[c], mkdesc_ns(SB0 + OFF_VT + 128 + c * 640 + q * 256, 128, VS), mkdesc_ns(SB0 + OFF_PT + c * 640 + q * 256, q == 2 && c == 0 ? 768 : 128, 128), q);
        wg_commit();
        const float4 e = lds128f(sb + OFF_XM + 2048 + (tid & 15) * 16);
        const uint32_t rb1 = mapa(sb, (rank + 1) % 3), rb2 = mapa(sb, (rank + 2) % 3);
        const float inv = rcp((e.x + e.y) + (e.z + e.w));
        const int sl = (tid & 3) * 2;
        const float i0 = __shfl_sync(0xffffffffu, inv, sl), i1 = __shfl_sync(0xffffffffu, inv, sl + 1);
        const float i2 = __shfl_sync(0xffffffffu, inv, sl + 8), i3 = __shfl_sync(0xffffffffu, inv, sl + 9);
        wg_wait<0>();
        TS(i, 11);
        const uint32_t p0 = pack_bf16(o[0][0] * i0, o[0][1] * i1), p1 = pack_bf16(o[1][0] * i2, o[1][1] * i3);
        const uint32_t p2 = pack_bf16(o[0][2] * i0, o[0][3] * i1), p3 = pack_bf16(o[1][2] * i2, o[1][3] * i3);
        if (OGF) { sts64(sb + oo + og_off(0), p0, p1); sts64(sb + oo + og_off(0) + 256, p2, p3); fence_async(); }
        st_async2u(rb1 + oo + og_off(2), p0, p1, rb1 + BAR_OG);
        st_async2u(rb2 + oo + og_off(1), p0, p1, rb2 + BAR_OG);
        st_async2u(rb1 + oo + og_off(2) + 256, p2, p3, rb1 + BAR_OG);
        st_async2u(rb2 + oo + og_off(1) + 256, p2, p3, rb2 + BAR_OG);
        if (!OGF) { sts64(sb + oo + og_off(0), p0, p1); sts64(sb + oo + og_off(0) + 256, p2, p3); fence_async(); }
      }
      CBAR_SYNC(NB_A, 128);
      TSB(i, 12);
      {
        float acc[3][8];
        wg_fence();
        wo_block<0, 0>(acc[2], wf);
        wg_commit();
        if (tid == 0) mbar_arrive_cluster(mapa(sb, 1) + BAR_E + 8);
        wo_block<1, 0>(acc[0], wf);
        wo_block<4, 0>(acc[1], wf);
        wg_commit();
        const uint32_t tag = (i >> 1) & 1;
#define TAGGED(LO, HI) ((pack_bf16(LO, HI) & ~1u) | tag)
#define SEND(OFF, U) st_relaxed128(mkptr(mo, ehi) + (OFF), TAGGED(acc[U][0], acc[U][2]), pack_bf16(acc[U][1], acc[U][3]), pack_bf16(acc[U][4], acc[U][6]), pack_bf16(acc[U][5], acc[U][7]))
        wg_wait<1>();
        const uint32_t n0 = pin(TAGGED(acc[2][0], acc[2][2])), n1 = pin(pack_bf16(acc[2][1], acc[2][3]));
        const uint32_t n2 = pin(TAGGED(acc[2][4], acc[2][6])), n3 = pin(pack_bf16(acc[2][5], acc[2][7]));
        wg_fence();
        wo_block<7, 0>(acc[2], wf);
        wg_commit();
        st_relaxed64(mkptr(m9, ehi), n0, n1);
        st_relaxed64(mkptr(m9, ehi) + 3072, n2, n3);
        mwait(sb + BAR_OG, ph, spin);
        asm volatile("fence.proxy.async::generic.acquire.sync_restrict::shared::cluster.cluster;" ::: "memory");
        TS(i, 13);
        wg_fence();
        wo_block<2, 1>(acc[0], wf); wo_block<3, 2>(acc[0], wf);
        wg_commit();
        wo_block<5, 1>(acc[1], wf); wo_block<6, 2>(acc[1], wf);
        wg_commit();
        wg_wait<1>(); SEND(0, 0);
        wo_block<8, 1>(acc[2], wf); wo_block<9, 2>(acc[2], wf);
        wg_commit();
        if (WOE == 0) { CBAR_ARRIVE(NB_WV, 256); CBAR_ARRIVE(NB_WQ, 256); }
        wg_wait<1>(); SEND(32 * 2048, 1);
        if (WOE == 1) CBAR_ARRIVE(NB_WV, 256);
        wg_wait<0>(); SEND(64 * 2048, 2);
        if (WOE == 2) CBAR_ARRIVE(NB_WV, 256);
        if (WOE >= 1) CBAR_ARRIVE(NB_WQ, 256);
#undef SEND
#undef TAGGED
      }
      TS(i, 14);
      if (i + 1 >= NSTEP) break;
    }
    uint32_t t1 = clk32();
    if (i >= 0) {
      const int lane = fresh(tid0) & 31, j = lane >> 3;
      const uint8_t* mb = mkptr(elo + (ph << 20) + (t9 ? MAIL9 + (cta - 72) * 12288 + wu * 3072 : (cta < 72 ? cta : cta - 24) * 8192 + wu * 2048) + lane * 16, ehi);
      const uint32_t tag = (i >> 1) & 1;
      const bool pub = (lane & (t9 ? 6 : 4)) == 0 && !(((t9 ? cta : wu) & 1) && i + 1 == LAG) && cta < 88;
      const uint32_t dst = pin(elo + EX_M + (i + 1) * 20480 + (t9 ? (cta + 72) * 128 + wu * 32 + (j & 1) * 16 + (lane & 1) * 8 + (j >> 1) * 4
                                                                   : cta * 256 + (wu & 1) * 128 + (wu >> 1) * 64 + j * 16 + (lane & 3) * 4));
      uint8_t* flag = mkptr(elo + EX_FLAG + (i + 1) * 3072 + cta * 32 + wu * 4, ehi);
      while (clk32() - t1 < b1) {}
      TS(i + 1, 30);
      float f[8];
      const int n0 = spin;
      if (!t9) poll_add<4>(mb, tag, f, flag, lane == 0, spin);
      else poll_add<6>(mb, tag, f, flag, lane == 0, spin);
      if (FLP == 1 && lane == 0) st_relaxed(flag, __float_as_uint(f[0] + f[7]) >> 1);
      t1 = clk32();
      b1 = __any_sync(0xffffffffu, spin - n0 > 16) ? min(b1 + AD1, BMX) : max(b1 - AD0, 0);
      TSV(i + 1, 38, b1);
      TS(i + 1, 31); TSV(i + 1, 32, (spin - n0) >> 4);
      const bool h = lane & 16, q = lane & 8;
#pragma unroll
      for (int j = 0; j < 4; j++) f[j] = (h ? f[4 + j] : f[j]) + __shfl_xor_sync(0xffffffffu, h ? f[j] : f[4 + j], 16);
#pragma unroll
      for (int j = 0; j < 2; j++) f[j] = (q ? f[2 + j] : f[j]) + __shfl_xor_sync(0xffffffffu, q ? f[j] : f[2 + j], 8);
      f[0] += __shfl_xor_sync(0xffffffffu, f[0], 4); f[1] += __shfl_xor_sync(0xffffffffu, f[1], 4);
      if (t9) { f[0] += __shfl_xor_sync(0xffffffffu, f[0], 2); f[1] += __shfl_xor_sync(0xffffffffu, f[1], 2); }
      if (pub) st_relaxed(mkptr(dst, ehi), pack_bf16(f[0], f[1]));
      if (FLP == 2 && lane == 0) st_relaxed(flag, 0);
      if (wu == 3) {
        CBAR_SYNC(NB_MR, 160);
        if (elect_one()) signal_o(i, cta);
      }
      TS(i + 1, 15);
    }
    if (wu == 0) {
      const int tid = fresh(tid0);
      const uint8_t* pp = mkptr(elo + EX_FLAG + (i + 1) * 3072 + (rank * 28 + (tid < 28 || rank == 2 ? tid : 0)) * 32, ehi);
      while (clk32() - t1 < b2) {}
      TS(i + 1, 16);
      int n = 1;
      uint4 x = ld_relaxed4(pp);
      if (tid0 == 0) mbar_expect_tx(sb + BAR_M, 20480);
      bool mok = mbar_test(sb + BAR_MOK, ph ^ 1);
      while (__any_sync(0xffffffffu, (int)(x.x | x.y | x.z | x.w) < 0 && spin < SPIN_TOT)) { x = ld_relaxed4(pp); mok = mbar_test(sb + BAR_MOK, ph ^ 1); n++; spin += 16; }
      if (!mok) mwait(sb + BAR_MOK, ph ^ 1, spin);
      b2 = n > 1 ? min(b2 + AD3, BMX) : max(b2 - AD2, 0);
      TSV(i + 1, 35, n); TSV(i + 1, 39, b2);
      TS(i + 1, 34);
      if (elect_one()) bulk_g2s_mc(sb + OFF_M + rank * 7168, mkptr(elo + EX_M + (i + 1) * 20480 + rank * 7168, ehi), rank == 2 ? 6144 : 7168, sb + BAR_M);
      TS(i + 1, 33);
      __syncwarp();
    }
  }
  if (spin >= SPIN_TOT) g_err = 1;
}

__global__ void __cluster_dims__(3, 1, 1) __launch_bounds__(384, 1)
k_chain(const __grid_constant__ CUtensorMap tmWq, const __grid_constant__ CUtensorMap tmWk,
        const __grid_constant__ CUtensorMap tmWv, const __grid_constant__ CUtensorMap tmWo) {
  using namespace C;
  extern __shared__ __align__(1024) uint8_t smem[];
  const uint32_t sb = smem_u32(smem);
  const int tid = threadIdx.x;
  const int wg = __shfl_sync(0xffffffffu, tid >> 7, 0);
  const int cta = uni(blockIdx.x), rank = uni(blockIdx.x % 3);

  asm volatile("griddepcontrol.launch_dependents;");
  if (tid == 0) {
    if ((sb & 0xFFFFFF) != SB0) g_err = 100;
    for (int p = 0; p < 5; p++) { mbar_init(sb + BAR_F + 8 * p, 1); mbar_init(sb + BAR_E + 8 * p, p == 2 ? 12 : p == 1 ? 15 : 24); }
    mbar_init(sb + BAR_M, 1); mbar_init(sb + BAR_MOK, 24); mbar_init(sb + BAR_XM, 1); mbar_init(sb + BAR_XF, 2);
    mbar_init(sb + BAR_XT, 1); mbar_init(sb + BAR_MF, 8); mbar_init(sb + BAR_OG, 1); mbar_init(sb + BAR_W, 1);
    for (int p = 0; p < 5; p++) mbar_expect_tx(sb + BAR_F + 8 * p, 16384);
    for (int p = 0; p < 16; p++) sts32(sb + OFF_SAFE + 4 * p, 0);
    for (int p = 0; p < 32; p++) sts32(sb + OFF_ONE + 4 * p, 0x3F803F80);
    asm volatile("fence.mbarrier_init.release.cluster;" ::: "memory");
    fence_async();
    mbar_expect_tx(sb + BAR_W, 163840);
    const int head = cta / 3, col = head * DH + rank * 64;
    tma2d(sb + OFF_WQ, &tmWo, 576, col, sb + BAR_W);
    for (int i = 0; i < 9; i++) tma2d(sb + OFF_WQ + (i + 1) * 8192, &tmWo, (3 * rank + i / 3) * 64, head * DH + ((rank + i) % 3) * 64, sb + BAR_W);
    for (int i = 0; i < 5; i++) tma2d(sb + OFF_WK + i * 16384, &tmWv, col, i * 128, sb + BAR_W);
  }
  __syncthreads();
  asm volatile("barrier.cluster.arrive.release.aligned;" ::: "memory");
  asm volatile("barrier.cluster.wait.acquire.aligned;" ::: "memory");

  if (wg == 0) chain_a(sb, keep(tid), cta, rank);
  else if (wg == 1) chain_q(tmWq, tmWk, sb, keep(tid), cta, rank);
  else chain_v(sb, keep(tid), cta, rank);
  asm volatile("barrier.cluster.arrive.release.aligned;" ::: "memory");
  asm volatile("barrier.cluster.wait.acquire.aligned;" ::: "memory");
}

namespace W {
constexpr int NP = 25, NBC = 11, NW = NP + NBC;
constexpr int PRS = 37, PW = 43 * 2048;
constexpr int OFF_W = 0;
constexpr int OFF_R = 2 * PW;
constexpr int QRS = 35, KRS = 37;
constexpr int OFF_WV = 0, OFF_YQ = 81920, OFF_YK = OFF_YQ + (40 - QRS) * 2048, OFF_WO = OFF_YK + (40 - KRS) * 2048;
constexpr int OFF_G = OFF_WO + 39 * 2048;
constexpr int OFF_X = OFF_G + 12288;
constexpr int COL = 976;
constexpr int OFF_T = OFF_X + 8192;
constexpr int OFF_H = OFF_X + 32768;
constexpr int OFF_BAR = OFF_H + 8 * COL;
constexpr int OFF_SAFE = OFF_BAR + 192;
constexpr int SMEM = 232448;
static_assert(OFF_SAFE + 64 <= SMEM && OFF_R + 40960 <= OFF_BAR, "");
constexpr uint32_t SB0 = 1024;
constexpr int BAR_F = OFF_BAR, BAR_E = OFF_BAR + 40, BAR_G = OFF_BAR + 80, BAR_H = OFF_BAR + 120, BAR_W = OFF_BAR + 160;
constexpr int NB_G0 = 1, NB_SG = 4, NB_B = 5, NB_AS = 6, NB_PK = 8, NB_PV = 9, NB_TD = 10;
}
#define PFW 1
#define WOP 0
#define WBAR_SYNC(id, n) bar_sync(id, n)
#define WBAR_ARRIVE(id, n) bar_arrive(id, n)

__device__ __forceinline__ uint64_t rdesc(int off, int kk) { return mkdesc(W::SB0 + off + kk * 32, 16, 1024); }
__device__ __forceinline__ uint32_t frag_addr(uint32_t base, int tid) {
  const int i = (tid >> 3) & 3, r = tid & 7;
  return base + (r + (i >> 1) * 8) * 128 + (((2 * ((tid >> 5) & 3) + (i & 1)) ^ r) << 4);
}
template <int NK>
__device__ __forceinline__ void load_frags(uint32_t (&wf)[NK][4], uint32_t base, int tid) {
  const uint32_t a0 = frag_addr(base, tid);
#pragma unroll
  for (int k = 0; k < NK; k++) ldsm4t(wf[k], a0 + k * 2048);
}
__device__ __forceinline__ void red_tile(const float* d, int seg, int col0, int tid) {
  float* p = g_x + (size_t)(seg * 32 + 2 * (tid & 3)) * DM + col0 + ((tid >> 5) & 3) * 16 + ((tid >> 2) & 7) * 2;
#pragma unroll
  for (int j = 0; j < 8; j++)
    asm volatile("red.relaxed.gpu.global.add.v2.f32 [%0],{%1,%2};" ::"l"(p + ((j >> 1) * 8 + (j & 1)) * DM), "f"(d[4 * (j >> 1) + (j & 1)]), "f"(d[4 * (j >> 1) + 2 + (j & 1)]) : "memory");
}
#define FOR_SEGS(l, s)                                            \
  for (int j_ = 0; j_ < 2 * NSTEP; j_++) {                        \
    const int l = j_ & 1, s = (j_ >> 1) - l * LAG;                \
    if (s < 0 || s >= NSEG) continue;

template <int WG>
__device__ __forceinline__ void work_p(const CUtensorMap& tmWo, uint32_t sb, int pc, int tid0) {
  using namespace W;
  asm volatile("setmaxnreg.inc.sync.aligned.u32 208;");
  int spin = 0;
  const int ks = pc / 5, col0 = (pc % 5) * 128 + WG * 64;
  const uint32_t wb = sb + OFF_W + WG * PW;
  uint32_t wf[PRS][4];
#pragma unroll 1
  for (int hf = 0; hf < 2; hf++) {
    const int nk = hf ? 80 - PRS : PRS;
    if ((tid0 & 127) == 0) {
      mbar_expect_tx(sb + BAR_W + 8 * WG, nk * 2048);
      for (int i = 0; i < nk; i++) tma2d(wb + i * 2048, &tmWo, col0, ks * 19 * 64 + (i < PRS ? 2 * i + hf : PRS + i) * 16, sb + BAR_W + 8 * WG);
    }
    __syncwarp();
    mwait(sb + BAR_W + 8 * WG, hf, spin);
    permute_cols(wb, tid0 & 127, nk * 64);
    if (hf == 1 && ks < 4) for (int it = 39 * 64 + (tid0 & 127) - 64; it < 43 * 64; it += 128) {
      const uint32_t a = wb + (it >> 2) * 128 + (((2 * (it & 3)) ^ ((it >> 2) & 6)) << 4);
      if (it >= 39 * 64) { sts128(a, make_uint4(0, 0, 0, 0)); sts128(a + 16, make_uint4(0, 0, 0, 0)); }
    }
    fence_async();
    WBAR_SYNC(NB_G0 + WG, 128);
    if (hf == 0) {
      load_frags<PRS>(wf, wb, tid0);
      fence_async();
      WBAR_SYNC(NB_G0 + WG, 128);
    }
  }
#pragma unroll 1
  for (int k = 0; k < NSTEP; k++) {
    float d[32];
#pragma unroll
    for (int f = 0; f < 20; f++) {
      mwait(sb + BAR_F + 8 * (f % 5), (f / 5) & 1, spin);
      if (f == 0 && WG == 0 && pc == WW) WTS(k, 1);
      wg_fence();
#pragma unroll
      for (int kk = 0; kk < 4; kk++) {
        const int q = 4 * f + kk;
        if (q < 2 * PRS && !(q & 1)) wgmma_rs64(d, wf[q < 2 * PRS ? q >> 1 : 0], rdesc(OFF_R + (f % 5) * 8192, kk), q);
        else wgmma_ts64(d, mkdesc(SB0 + OFF_W + WG * PW + (q < 2 * PRS ? q >> 1 : q - PRS) * 2048, 8192, 1024), rdesc(OFF_R + (f % 5) * 8192, kk), 1);
        if (kk == 0 && f > 0) {
          wg_commit();
          wg_wait<1>();
          if ((tid0 & 31) == 0) mbar_arrive(sb + BAR_E + 8 * ((f - 1) % 5));
        }
      }
      wg_commit();
    }
    wg_wait<0>();
    if ((tid0 & 31) == 0) mbar_arrive(sb + BAR_E + 32);
    if (WG == 0 && pc == WW) WTS(k, 2);
    if (k < NSEG) red_tile(d, k, col0, tid0);
    if (k >= LAG) red_tile(d + 16, k - LAG, col0, tid0);
    if (WG == 0 && pc == WW) WTS(k, 13);
    WBAR_SYNC(NB_SG, 256);
    if (WG == 0) { if (tid0 == 0) csignal_t(CN_P + k, 3); __syncwarp(); }
  }
  if (spin >= SPIN_TOT) g_err = 11;
}
__device__ __forceinline__ void work_p_producer(uint32_t sb, int pc, int odd) {
  using namespace W;
  int spin = 0;
  const int ks = pc / 5;
#pragma unroll 1
  for (int k = 0; k < NSTEP; k++) {
    const uint32_t lo = k < NSEG ? 0 : 4096, len = k < LAG || k >= NSEG ? 4096 : 8192;
    const uint8_t* src = &g_o[k % ORING][ks * 19 + odd][lo];
    cwait(CN_O + k * 5 + ks, ks == 4 ? 20 : 19, spin);
    fence_async_all();
    if (pc == WW && !odd) WTS1(k, 0);
#pragma unroll
    for (int u = 0; u < 10; u++) {
      const int st = odd ? (2 * u + 1) % 5 : (2 * u) % 5, ph = odd ? ((2 * u + 1) / 5) & 1 : ((2 * u) / 5) & 1;
      mwait(sb + BAR_E + 8 * st, ph ^ 1, spin);
      if (u == 9 && odd && ks < 4) mbar_arrive(sb + BAR_F + 8 * st);
      else {
        mbar_expect_tx(sb + BAR_F + 8 * st, len);
        bulk_g2s(sb + OFF_R + st * 8192 + lo, src + u * 16384, len, sb + BAR_F + 8 * st);
      }
    }
  }
  if (spin >= SPIN_TOT) g_err = 12;
}
__device__ __forceinline__ float warp_sum(float x) {
  x = quad_sum(x);
  const float a = __shfl_xor_sync(0xffffffffu, x, 4), b = __shfl_xor_sync(0xffffffffu, x, 8), c = __shfl_xor_sync(0xffffffffu, x, 12);
  x = (x + a) + (b + c);
  return x + __shfl_xor_sync(0xffffffffu, x, 16);
}
__device__ __forceinline__ void work_ln(int kind, int r, int lane, bf16* out) {
  int spin = 0;
  const int l = kind & 1;
  const int rp = kind < 2 ? (r & 1) * 16 + (r >> 1) : r;
  const uint32_t sw = ((((lane >> 1) & 7) ^ (rp & 7)) << 4) + (lane & 1) * 8;
  uint8_t* dst = kind < 2 ? g_xnb[l * LAG] + (lane >> 4) * 8192 + l * 4096 + rp * 128 + sw
               : kind == 2 ? g_xn[LAG] + (r >> 3) * 4096 + 2048 + (lane >> 4) * 1024 + (r & 7) * 128 + sw
                           : reinterpret_cast<uint8_t*>(out) + r * 1280 + lane * 8;
  const int dm = kind < 3 ? 16384 : 256, ds = kind < 3 ? 81920 : 40960;
#pragma unroll 1
  for (int s = 0; s < NSEG; s++) {
    const float* xr = g_x + (size_t)(s * 32 + r) * DM;
    if (lane == 0) cwait(kind < 2 ? CN_P + s + l * LAG : CN_W + l * 64 + s, kind < 2 ? W::NP : 10, spin);
    __syncwarp();
    if (r == 0 && lane == 0 && (l == 0 || s + LAG >= NSEG)) WTS1(s + l * LAG, kind < 2 ? 3 : 11);
    float4 v[5];
#pragma unroll
    for (int m = 0; m < 5; m++) v[m] = ld_relaxed4f(xr + m * 128 + lane * 4);
    if (kind < 3) {
      float t = 0.f;
#pragma unroll
      for (int m = 0; m < 5; m++) t += (v[m].x + v[m].y) + (v[m].z + v[m].w);
      const float mean = warp_sum(t) * (1.f / DM);
      float q0 = 0.f, q1 = 0.f;
#pragma unroll
      for (int m = 0; m < 5; m++) {
        v[m].x -= mean; v[m].y -= mean; v[m].z -= mean; v[m].w -= mean;
        q0 += v[m].x * v[m].x + v[m].y * v[m].y; q1 += v[m].z * v[m].z + v[m].w * v[m].w;
      }
      const float rs = rsqrtf(warp_sum(q0 + q1) * (1.f / DM) + 1e-5f);
#pragma unroll
      for (int m = 0; m < 5; m++) { v[m].x *= rs; v[m].y *= rs; v[m].z *= rs; v[m].w *= rs; }
    }
#pragma unroll
    for (int m = 0; m < 5; m++) *reinterpret_cast<uint2*>(dst + (size_t)s * ds + m * dm) = make_uint2(pack_bf16(v[m].x, v[m].y), pack_bf16(v[m].z, v[m].w));
    __syncwarp();
    if (r == 0 && lane == 0 && (l == 0 || s + LAG >= NSEG)) WTS1(s + l * LAG, kind < 2 ? 4 : 12);
    if (lane == 0 && kind < 3) csignal_t(kind < 2 ? CN_L + s + l * LAG : CN_X + s, kind);
  }
  if (spin >= SPIN_TOT) g_err = 13;
}

__device__ __forceinline__ void work_prefetch(int t) {
  int spin = 0;
#pragma unroll 1
  for (int k = 0; k + 4 < NSTEP; k++) {
    if ((t & 31) == 0) cwait(CN_O + k * 5, 1, spin);
    __syncwarp();
    if (k + 2 < NSEG) { prefetch_l2(g_x + (size_t)(k + 2) * 32 * DM + t * 64); prefetch_l2(g_x + (size_t)(k + 2) * 32 * DM + t * 64 + 32); }
    prefetch_l2(g_xn[k + 4] + (t >> 4) * 4096 + (t & 15) * 128);
    if (t < 184) prefetch_l2(ex_window(g_ex) + (t < 160 ? EX_M + (k + 4) * 20480 + t * 128 : EX_FLAG + (k + 4) * 3072 + (t - 160) * 128));
  }
}

__device__ __forceinline__ void stage_qkv(const bf16* wqkv, uint32_t base, int T, int bc, int tid) {
  const int q = tid & 15;
  const bool ok = q < 15 && bc * 60 + 4 * q < DM;
  const bf16* src = wqkv + T * DM + bc * 60 + 4 * q;
#pragma unroll 1
  for (int k0 = tid >> 4; k0 < 640; k0 += 80) {
    uint2 v[10];
#pragma unroll
    for (int u = 0; u < 10; u++) v[u] = ok ? *reinterpret_cast<const uint2*>(src + (size_t)(k0 + 8 * u) * 1920) : make_uint2(0, 0);
#pragma unroll
    for (int u = 0; u < 10; u++) sts64(base + (k0 + 8 * u) * 128 + (((q >> 1) ^ (k0 & 7)) << 4) + (q & 1) * 8, v[u].x, v[u].y);
  }
}
__device__ __forceinline__ void attend(uint32_t sb, int bc, int l, int s, int p, int tid) {
  using namespace W;
  const int r = tid & 7, m = (tid >> 3) & 3, hh = (tid >> 5) & 3, g = (tid >> 2) & 7, t = tid & 3;
  const int f2 = r < 4 ? 20 * hh + 16 + r : 60;
  const uint32_t tb = sb + OFF_T + (l * 4 + 2 * p) * COL, hb = sb + OFF_H + (l * 2 + p) * COL;
  const uint32_t ko = (m < 2 ? 20 * hh + 8 * m + r : f2) * 16, vo = (m < 2 ? 20 * hh + 4 * (r >> 1) + 2 * m + (r & 1) : f2) * 16;
  const float scl = 0.22360679774997896f * 1.4426950408889634f;
  float sc[3][4];
  {
    uint32_t q[4], q8a, q8b, k[3][4];
    ldsm4t(q, tb + (m & 1) * COL + (20 * hh + (m >> 1) * 8 + r) * 16);
    ldsm2t(q8a, q8b, tb + (m & 1) * COL + f2 * 16);
    ldsm4t(k[0], hb + ko); ldsm4t(k[1], tb + 8 * COL + ko); ldsm4t(k[2], tb + 9 * COL + ko);
#pragma unroll
    for (int c = 0; c < 3; c++) { sc[c][0] = sc[c][1] = sc[c][2] = sc[c][3] = 0.f; mma16816(sc[c], q[0], q[1], q[2], q[3], k[c][0], k[c][1]); }
#pragma unroll
    for (int c = 0; c < 3; c++) mma1688(sc[c], q8a, q8b, k[c][2]);
  }
  uint32_t v[3][4];
  ldsm4(v[0], hb + 4 * COL + vo); ldsm4(v[1], tb + 16 * COL + vo); ldsm4(v[2], tb + 17 * COL + vo);
  const bool lo0 = 2 * t > g, lo1 = 2 * t + 1 > g;
  uint32_t pw[2];
  float inv[2];
#pragma unroll
  for (int h = 0; h < 2; h++) {
    float y0 = lo0 ? sc[h][2 * h] : sc[h + 1][2 * h], y1 = lo1 ? sc[h][2 * h + 1] : sc[h + 1][2 * h + 1];
    if (h == 0 && s == 0) { y0 = lo0 ? -INFINITY : y0; y1 = lo1 ? -INFINITY : y1; }
    const float mx = quad_max(fmaxf(y0, y1)) * -scl;
    pw[h] = pack_bf16(ex2(fmaf(y0, scl, mx)), ex2(fmaf(y1, scl, mx)));
    inv[h] = bf_lo(pw[h]) + bf_hi(pw[h]);
  }
  const uint32_t ml = (lo0 ? 0xFFFFu : 0u) | (lo1 ? 0xFFFF0000u : 0u);
  float o[3][4];
#pragma unroll
  for (int j = 0; j < 3; j++) { o[j][0] = o[j][1] = o[j][2] = o[j][3] = 0.f; mma16816(o[j], pw[0] & ml, 0u, pw[0] & ~ml, pw[1] & ml, v[0][j], v[1][j]); }
#pragma unroll
  for (int j = 0; j < 3; j++) mma1688(o[j], 0u, pw[1] & ~ml, v[2][j]);
  inv[0] = rcp(quad_sum(inv[0])); inv[1] = rcp(quad_sum(inv[1]));
  const uint32_t ca = (bc * 3 + hh) * 20 + 4 * t, cb = ca + 16 - 2 * t, row = 2 * g + p;
  uint8_t* img = g_ob[l] + (size_t)s * 40960 + row * 128;
  const uint32_t oa = (ca >> 6) * 4096 + (((ca >> 3) ^ row) & 7) * 16 + (ca & 4) * 2, ob = (cb >> 6) * 4096 + (((cb >> 3) ^ row) & 7) * 16 + (cb & 6) * 2;
#pragma unroll
  for (int h = 0; h < 2; h++) {
    *reinterpret_cast<uint2*>(img + oa + h * 2048) = make_uint2(pack_bf16(o[0][2 * h] * inv[h], o[0][2 * h + 1] * inv[h]), pack_bf16(o[1][2 * h] * inv[h], o[1][2 * h + 1] * inv[h]));
    if (t < 2) *reinterpret_cast<uint32_t*>(img + ob + h * 2048) = pack_bf16(o[2][2 * h] * inv[h], o[2][2 * h + 1] * inv[h]);
  }
}
template <int WG>
__device__ __forceinline__ void work_b(const bf16* wqkv, uint32_t sb, int bc, int tid0) {
  using namespace W;
  if (WG == 0) asm volatile("setmaxnreg.inc.sync.aligned.u32 232;");
  else asm volatile("setmaxnreg.inc.sync.aligned.u32 208;");
  constexpr int NR = WG ? KRS : QRS, OFF_Y = WG ? OFF_YK : OFF_YQ;
  int spin = 0;
  const uint32_t wb = sb + (WG ? OFF_WO : OFF_WV);
  uint32_t wf[NR][4];
  stage_qkv(wqkv, wb, WG, bc, tid0 & 127);
  WBAR_SYNC(NB_G0 + WG, 128);
  load_frags<NR>(wf, wb, tid0);
#pragma unroll
  for (int k = NR; k < 40; k++) sts128(sb + OFF_Y + (k - NR) * 2048 + (tid0 & 127) * 16, lds128(wb + k * 2048 + (tid0 & 127) * 16));
  fence_async();
  if (WG == 1) WBAR_ARRIVE(NB_PK, 256);
  WBAR_SYNC(NB_G0 + WG, 128);
  if (WG == 0) {
    stage_qkv(wqkv, wb, 2, bc, tid0);
    fence_async();
    WBAR_SYNC(NB_G0, 128);
  }
#pragma unroll 1
  for (int k = 0; k < NSTEP; k++) {
    uint32_t hist[8];
    {
      float d[32], e[32];
#pragma unroll
      for (int c = 0; c < 10; c++) {
        mwait(sb + BAR_F + 8 * (c % 4), ((c % 4 < 2 ? k : 0) + c / 4) & 1, spin);
        if (c == 0 && bc == 0) WTS(k, WG ? 15 : 6);
        wg_fence();
#pragma unroll
        for (int kk = 0; kk < 4; kk++) {
          const int q = 4 * c + kk;
          const uint64_t db = rdesc(OFF_X + (c % 4) * 8192, kk);
          if (q < NR) wgmma_rs64(d, wf[q < NR ? q : 0], db, q);
          else wgmma_ts64(d, mkdesc(SB0 + OFF_Y + (q - NR) * 2048, 8192, 1024), db, 1);
          if (WG == 0) wgmma_ts64(e, mkdesc(SB0 + OFF_WV + q * 2048, 8192, 1024), db, q);
          if (kk == 0 && c > 0 && (c <= 6 || c == 9)) {
            wg_commit();
            wg_wait<1>();
            if ((tid0 & 31) == 0) mbar_arrive(sb + BAR_E + 8 * ((c - 1) % 4));
          }
        }
        wg_commit();
      }
      wg_wait<0>();
      if (bc == 0) WTS(k, 16 + WG);
      WBAR_SYNC(NB_B, 256);
      const int tid = fresh(tid0), m = (tid >> 3) & 3;
      const uint32_t a = sb + OFF_T + min(((tid >> 5) & 3) * 16 + (m & 1) * 8 + (tid & 7), 60) * 16 + (m >> 1) * COL;
      const float (&x)[32] = WG ? d : e;
#pragma unroll
      for (int p = 0; p < 4; p++) {
        hist[2 * p] = pack_bf16(x[8 * p + 4], x[8 * p + 5]); hist[2 * p + 1] = pack_bf16(x[8 * p + 6], x[8 * p + 7]);
        stsm4(a + (16 - 8 * WG + 2 * p) * COL, pack_bf16(x[8 * p], x[8 * p + 1]), pack_bf16(x[8 * p + 2], x[8 * p + 3]), hist[2 * p], hist[2 * p + 1]);
        if (WG == 0)
          stsm4(a + 2 * p * COL, pack_bf16(d[8 * p], d[8 * p + 1]), pack_bf16(d[8 * p + 2], d[8 * p + 3]), pack_bf16(d[8 * p + 4], d[8 * p + 5]), pack_bf16(d[8 * p + 6], d[8 * p + 7]));
      }
    }
    WBAR_SYNC(NB_TD, 288);
    if (bc == 0 && WG == 0) WTS(k, 7);
#pragma unroll 1
    for (int l = 0; l < 2; l++) {
      const int tid = fresh(tid0), hh = uni((tid >> 5) & 3), s = k - l * LAG;
      if (hh < 3 && bc * 3 + hh < NH && s >= 0 && s < NSEG) attend(sb, bc, l, s, WG, tid);
      if (bc == 0 && WG == 0) WTS(k, l == 0 || k >= NSEG ? 8 : 25);
      if (l == 0) WBAR_ARRIVE(NB_AS, 288); else WBAR_ARRIVE(NB_AS + 1, 288);
    }
    WBAR_SYNC(NB_B, 256);
    {
      const int tid = fresh(tid0), m = (tid >> 3) & 3;
      const uint32_t a = sb + OFF_H + min(((tid >> 5) & 3) * 16 + (m & 1) * 8 + (tid & 7), 60) * 16 + (4 - 4 * WG + (m >> 1)) * COL;
      stsm4(a, hist[0], hist[1], hist[2], hist[3]);
      if (k >= LAG) stsm4(a + 2 * COL, hist[4], hist[5], hist[6], hist[7]);
      fence_async();
      if ((tid & 31) < 3) mbar_arrive(sb + BAR_E + 8 + 8 * (tid & 3));
    }
  }
  if (spin >= SPIN_TOT) g_err = 14;
}
__device__ __forceinline__ void work_wo(const CUtensorMap& tmBo, uint32_t sb, int bc, int tid0) {
  using namespace W;
  int spin = 0;
  WBAR_SYNC(NB_PK, 256);
  if (bc == 10) return;
  if ((tid0 & 127) == 0) {
    mbar_expect_tx(sb + BAR_W, 81920);
    for (int i = 0; i < 10; i++) tma2d(sb + OFF_WO + i * 8192, &tmBo, bc * 64, i * 64, sb + BAR_W);
  }
  __syncwarp();
  mwait(sb + BAR_W, 0, spin);
  permute_cols(sb + OFF_WO, tid0 & 127, 2560);
  WBAR_SYNC(NB_G0 + 2, 128);
  uint32_t wl[4];
  ldsm4t(wl, frag_addr(sb + OFF_WO + 39 * 2048, tid0));
  fence_async();
  WBAR_SYNC(NB_PV, 160);
  uint32_t n = 0;
  FOR_SEGS(l, s)
    float d[16];
#pragma unroll
    for (int c = 0; c < 10; c++) {
      mwait(sb + BAR_G + 8 * (c % 3), ((c % 3 ? n : 0) + c / 3) & 1, spin);
      if (c == 0 && bc == 0) WTS(s + l * LAG, l == 0 || s + LAG >= NSEG ? 20 : 23);
      wg_fence();
#pragma unroll
      for (int kk = 0; kk < 4; kk++) {
        if (c == 9 && kk == 3) wgmma_rs32(d, wl, rdesc(OFF_G + (c % 3) * 4096, kk), 1);
        else wgmma_ts32(d, mkdesc(SB0 + OFF_WO + (4 * c + kk) * 2048, 8192, 1024), rdesc(OFF_G + (c % 3) * 4096, kk), c | kk);
      }
      wg_commit();
      if (c == 9 || !WOP) wg_wait<0>();
      else if (c > 0) wg_wait<1>();
      if ((tid0 & 31) == 0) {
        if (WOP && c > 0) mbar_arrive(sb + BAR_H + 8 * ((c - 1) % 3));
        if (c == 9 || !WOP) mbar_arrive(sb + BAR_H + 8 * (c % 3));
      }
    }
    if (bc == 0) WTS(s + l * LAG, l == 0 || s + LAG >= NSEG ? 10 : 24);
    red_tile(d, s, bc * 64, tid0);
    WBAR_SYNC(NB_SG, 160);
    n++;
  }
  if (spin >= SPIN_TOT) g_err = 17;
}
__device__ __forceinline__ void work_x_producer(uint32_t sb, int bc) {
  using namespace W;
  int spin = 0;
#pragma unroll 1
  for (int k = 0; k < NSTEP; k++) {
    const uint32_t lo = k < NSEG ? 0 : 4096, len = k < LAG || k >= NSEG ? 4096 : 8192;
    const uint8_t* src = g_xnb[k] + lo;
    cwait(CN_L + k, len >> 7, spin);
    fence_async_all();
    if (bc == 0) WTS1(k, 5);
#pragma unroll
    for (int c = 0; c < 10; c++) {
      mwait(sb + BAR_E + 8 * (c % 4), (((c % 4 < 2 ? k : 0) + c / 4) & 1) ^ 1, spin);
      mbar_expect_tx(sb + BAR_F + 8 * (c % 4), len);
      bulk_g2s(sb + OFF_X + (c % 4) * 8192 + lo, src + c * 8192, len, sb + BAR_F + 8 * (c % 4));
    }
  }
  if (spin >= SPIN_TOT) g_err = 15;
}
__device__ __forceinline__ void work_g_producer(uint32_t sb, int bc) {
  using namespace W;
  int spin = 0;
  uint32_t n = 0;
  FOR_SEGS(l, s)
    const uint8_t* src = g_ob[l] + (size_t)s * 40960;
    cwait(CN_A + l * 64 + s, NBC, spin);
    fence_async_all();
    if (bc == 0) WTS1(s + l * LAG, l == 0 || s + LAG >= NSEG ? 9 : 22);
#pragma unroll
    for (int c = 0; c < 10; c++) {
      mwait(sb + BAR_H + 8 * (c % 3), (((c % 3 ? n : 0) + c / 3) & 1) ^ 1, spin);
      mbar_expect_tx(sb + BAR_G + 8 * (c % 3), 4096);
      bulk_g2s(sb + OFF_G + (c % 3) * 4096, src + c * 4096, 4096, sb + BAR_G + 8 * (c % 3));
    }
    n++;
  }
  if (spin >= SPIN_TOT) g_err = 16;
}

__global__ void __launch_bounds__(512, 1)
k_work(const __grid_constant__ CUtensorMap tmWo, const __grid_constant__ CUtensorMap tmBo, const bf16* __restrict__ wqkv, bf16* __restrict__ out) {
  using namespace W;
  extern __shared__ __align__(1024) uint8_t smem[];
  const uint32_t sb = smem_u32(smem);
  const int tid = threadIdx.x, w = blockIdx.x;
  const int wg = __shfl_sync(0xffffffffu, tid >> 7, 0);
  if (tid == 0) {
    if (sb != SB0) g_err = 101;
    for (int i = 0; i < 5; i++) { mbar_init(sb + BAR_F + 8 * i, 1); mbar_init(sb + BAR_E + 8 * i, 8); mbar_init(sb + BAR_G + 8 * i, 1); mbar_init(sb + BAR_H + 8 * i, 4); }
    mbar_init(sb + BAR_W, 1); mbar_init(sb + BAR_W + 8, 1);
    for (int p = 0; p < 16; p++) sts32(sb + OFF_SAFE + 4 * p, 0);
    asm volatile("fence.mbarrier_init.release.cluster;" ::: "memory");
  }
  if (tid < 8 * COL / 16) sts128(sb + OFF_H + tid * 16, make_uint4(0, 0, 0, 0));
  fence_async();
  __syncthreads();

  if (w < NP) {
    if (wg == 0) work_p<0>(tmWo, sb, w, keep(tid));
    else if (wg == 1) work_p<1>(tmWo, sb, w, keep(tid));
    else {
      asm volatile("setmaxnreg.dec.sync.aligned.u32 48;");
      const int aw = (tid >> 5) - 8;
      if (aw < 2) {
        if ((tid & 31) == 0) work_p_producer(sb, w, aw);
      } else {
        const int id = (aw - 2) * NP + w;
        if (id < 128) work_ln(id & 3, id >> 2, tid & 31, out);
        else if (PFW && id < 138) work_prefetch((id - 128) * 32 + (tid & 31));
      }
    }
  } else {
    const int bc = w - NP;
    if (wg == 0) work_b<0>(wqkv, sb, bc, keep(tid));
    else if (wg == 1) work_b<1>(wqkv, sb, bc, keep(tid));
    else if (wg == 2) {
      asm volatile("setmaxnreg.dec.sync.aligned.u32 48;");
      work_wo(tmBo, sb, bc, keep(tid));
    } else {
      asm volatile("setmaxnreg.dec.sync.aligned.u32 24;");
      if (tid < 416) {
        if (tid == 384) work_x_producer(sb, bc);
      } else if (tid < 448) {
        if (bc < 10) {
          WBAR_SYNC(NB_PV, 160);
          if (tid == 416) work_g_producer(sb, bc);
        }
      } else if (tid < 480) {
        for (int k = 0; k < NSTEP; k++) {
          WBAR_SYNC(NB_TD, 288);
          WBAR_SYNC(NB_AS, 288);
          if (tid == 448 && k < NSEG) csignal_t(CN_A + k, 5);
          __syncwarp();
          WBAR_SYNC(NB_AS + 1, 288);
          if (tid == 448 && k >= LAG) csignal_t(CN_A + 64 + k - LAG, 4);
          __syncwarp();
        }
      } else if (bc < 10) {
        FOR_SEGS(l, s)
          WBAR_SYNC(NB_SG, 160);
          if (tid == 480) csignal_t(CN_W + l * 64 + s, 6);
          __syncwarp();
        }
      }
    }
  }
  __syncthreads();
  asm volatile("griddepcontrol.wait;" ::: "memory");
}

typedef CUresult (*EncodeFn)(CUtensorMap*, CUtensorMapDataType, cuuint32_t, void*, const cuuint64_t*, const cuuint64_t*,
                             const cuuint32_t*, const cuuint32_t*, CUtensorMapInterleave, CUtensorMapSwizzle,
                             CUtensorMapL2promotion, CUtensorMapFloatOOBfill);

static void make_map(EncodeFn enc, CUtensorMap* tm, const void* ptr, uint64_t cols, uint64_t rows, uint32_t boxc, uint32_t boxr) {
  cuuint64_t dims[2] = {cols, rows};
  cuuint64_t strides[1] = {cols * 2};
  cuuint32_t box[2] = {boxc, boxr};
  cuuint32_t es[2] = {1, 1};
  enc(tm, CU_TENSOR_MAP_DATA_TYPE_BFLOAT16, 2, const_cast<void*>(ptr), dims, strides, box, es, CU_TENSOR_MAP_INTERLEAVE_NONE,
      CU_TENSOR_MAP_SWIZZLE_128B, CU_TENSOR_MAP_L2_PROMOTION_L2_256B, CU_TENSOR_MAP_FLOAT_OOB_FILL_NONE);
}

extern "C" void kernel_launch(void* const* d_in, const int* in_sizes, int n_in, void* d_out, int out_size) {
  const bf16* x0 = (const bf16*)d_in[0];
  const bf16* mem0 = (const bf16*)d_in[1];
  const bf16* Wq = (const bf16*)d_in[2];
  const bf16* Wk = (const bf16*)d_in[3];
  const bf16* Wv = (const bf16*)d_in[4];
  const bf16* Wo = (const bf16*)d_in[5];
  const bf16* Bqkv = (const bf16*)d_in[8];
  const bf16* Bwo = (const bf16*)d_in[9];
  bf16* out = (bf16*)d_out;

  static EncodeFn enc = nullptr;
  if (!enc) {
    void* fn = nullptr;
    cudaDriverEntryPointQueryResult qr;
    cudaGetDriverEntryPoint("cuTensorMapEncodeTiled", &fn, cudaEnableDefault, &qr);
    enc = (EncodeFn)fn;
    cudaFuncSetAttribute(k_chain, cudaFuncAttributeMaxDynamicSharedMemorySize, C::SMEM);
    cudaFuncSetAttribute(k_work, cudaFuncAttributeMaxDynamicSharedMemorySize, W::SMEM);
  }
  CUtensorMap tmWq, tmWk, tmWv, tmWo, tmWp, tmBo;
  make_map(enc, &tmWq, Wq, NH * DH, DM, 64, 128);
  make_map(enc, &tmWk, Wk, NH * DH, DM, 64, 128);
  make_map(enc, &tmWv, Wv, NH * DH, DM, 64, 128);
  make_map(enc, &tmWo, Wo, DM, NH * DH, 64, 64);
  make_map(enc, &tmWp, Wo, DM, NH * DH, 64, 16);
  make_map(enc, &tmBo, Bwo, DM, DM, 64, 64);

  cudaStream_t st = cudaStreamPerThread;
  k_pre<<<256, 256, 0, st>>>(x0, mem0);
  cudaLaunchAttribute at[1];
  at[0].id = cudaLaunchAttributeProgrammaticStreamSerialization; at[0].val.programmaticStreamSerializationAllowed = 1;
  {
    cudaLaunchConfig_t cfg = {};
    cfg.gridDim = dim3(96); cfg.blockDim = dim3(384); cfg.dynamicSmemBytes = C::SMEM; cfg.stream = st;
    cfg.attrs = at; cfg.numAttrs = 0;
    cudaLaunchKernelEx(&cfg, k_chain, tmWq, tmWk, tmWv, tmWo);
  }
  cudaLaunchConfig_t cfg = {};
  cfg.gridDim = dim3(W::NW); cfg.blockDim = dim3(512); cfg.dynamicSmemBytes = W::SMEM; cfg.stream = st;
  cfg.attrs = at; cfg.numAttrs = NOWORK == 2 ? 0 : 1;
  cudaLaunchKernelEx(&cfg, k_work, tmWp, tmBo, Bqkv, out);
}
```

```cpp
#include <cuda_runtime.h>
#include <cuda_bf16.h>
#include <cuda.h>
#include <stdint.h>

typedef __nv_bfloat16 bf16;

constexpr int SEQ = 2048, DM = 640, NH = 32, DH = 192, NSEG = 64;
#define LAG 6
constexpr int NSTEP = NSEG + LAG;
constexpr uint32_t SENT = 0xFFFFFFFFu;

constexpr int MAIL9 = 288 * 2048, MAIL_BYTES = MAIL9 + 64 * 3072;
__device__ __align__(1024) uint8_t g_xn[NSTEP][81920];
__device__ __align__(1024) uint8_t g_xnb[NSTEP][81920];
__device__ __align__(1024) uint8_t g_ob[2][NSEG * 40960];
#define ORING 8
static_assert(ORING > LAG, "a slot is free again LAG + 1 steps later");
__device__ __align__(1024) uint8_t g_o[ORING][96][8192];
__device__ __align__(1024) float g_x[SEQ * DM];
constexpr int EX_MAIL = 0;
constexpr int EX_M = 2 << 20;
constexpr int EX_FLAG = EX_M + NSTEP * 20480;
static_assert(EX_FLAG + NSTEP * 3072 <= (4 << 20), "");
__device__ __align__(1024) uint8_t g_ex[8 << 20];
__host__ __device__ __forceinline__ uint8_t* ex_window(uint8_t* p) { return reinterpret_cast<uint8_t*>((reinterpret_cast<uint64_t>(p) + (4 << 20) - 1) & ~(uint64_t)((4 << 20) - 1)); }
enum { CN_P = 0, CN_L = 128, CN_A = 256, CN_W = 384, CN_X = 512, CN_O = 576, CN_NUM = CN_O + 5 * NSTEP };
__device__ __align__(128) uint32_t g_cnt[CN_NUM][32];
__device__ int g_err;
#define TS(jj, i)
#define TS1(jj, i)
#define PTS(i)
#define TSB(jj, i)
#define TSV(jj, i, v)
#define TS_FLUSH(jj)
#define WTS(b, k)
#define WTS1(b, k)
#define WW -1

__device__ __forceinline__ uint32_t smem_u32(const void* p) { return (uint32_t)__cvta_generic_to_shared(p); }
__device__ __forceinline__ uint32_t clk32() { uint32_t t; asm volatile("mov.u32 %0, %%clock;" : "=r"(t)::"memory"); return t; }
__device__ __forceinline__ uint32_t mapa(uint32_t a, uint32_t r) { uint32_t o; asm("mapa.shared::cluster.u32 %0,%1,%2;" : "=r"(o) : "r"(a), "r"(r)); return o; }
__device__ __forceinline__ void mbar_init(uint32_t bar, uint32_t cnt) { asm volatile("mbarrier.init.shared::cta.b64 [%0],%1;" ::"r"(bar), "r"(cnt) : "memory"); }
__device__ __forceinline__ void mbar_expect_tx(uint32_t bar, uint32_t bytes) { asm volatile("mbarrier.arrive.expect_tx.shared::cta.b64 _,[%0],%1;" ::"r"(bar), "r"(bytes) : "memory"); }
__device__ __forceinline__ void mbar_arrive(uint32_t bar) { asm volatile("mbarrier.arrive.shared::cta.b64 _,[%0];" ::"r"(bar) : "memory"); }
__device__ __forceinline__ void mbar_arrive_cluster(uint32_t bar) { asm volatile("mbarrier.arrive.shared::cluster.b64 _,[%0];" ::"r"(bar) : "memory"); }
__device__ __forceinline__ bool mbar_try(uint32_t bar, uint32_t ph) {
  uint32_t ok;
  asm volatile("{.reg .pred p; mbarrier.try_wait.parity.shared::cta.b64 p,[%1],%2; selp.u32 %0,1,0,p;}" : "=r"(ok) : "r"(bar), "r"(ph) : "memory");
  return ok;
}
__device__ __forceinline__ bool mbar_test(uint32_t bar, uint32_t ph) {
  uint32_t ok;
  asm volatile("{.reg .pred p; mbarrier.test_wait.parity.shared::cta.b64 p,[%1],%2; selp.u32 %0,1,0,p;}" : "=r"(ok) : "r"(bar), "r"(ph) : "memory");
  return ok;
}
__device__ __forceinline__ int fresh(int x) { asm volatile("" : "+r"(x)); return x; }
#define PHASE_IDS const int tid = fresh(tid0), lane = tid & 31, w = tid >> 5, g = lane >> 2, t = lane & 3; (void)w; (void)g; (void)t
__device__ __forceinline__ void bar_sync(int id, int n) { asm volatile("bar.sync %0,%1;" ::"r"(id), "r"(n) : "memory"); }
__device__ __forceinline__ void bar_arrive(int id, int n) { asm volatile("bar.arrive %0,%1;" ::"r"(id), "r"(n) : "memory"); }
__device__ __forceinline__ bool bar_red_or(int id, int n, bool v) {
  uint32_t r;
  asm volatile("{\n .reg .pred p, q;\n setp.ne.u32 q, %3, 0;\n barrier.cta.red.or.pred p, %1, %2, q;\n selp.u32 %0, 1, 0, p;\n}" : "=r"(r) : "r"(id), "r"(n), "r"((uint32_t)v) : "memory");
  return r != 0;
}
__device__ __forceinline__ void fence_async() { asm volatile("fence.proxy.async.shared::cta;" ::: "memory"); }
__device__ __forceinline__ void bulk_g2s(uint32_t dst, const void* src, uint32_t bytes, uint32_t bar) {
  asm volatile("cp.async.bulk.shared::cluster.global.mbarrier::complete_tx::bytes [%0],[%1],%2,[%3];" ::"r"(dst), "l"(src), "r"(bytes), "r"(bar) : "memory");
}
__device__ __forceinline__ void bulk_g2s_mc(uint32_t dst, const void* src, uint32_t bytes, uint32_t bar) {
  asm volatile("cp.async.bulk.shared::cluster.global.mbarrier::complete_tx::bytes.multicast::cluster [%0],[%1],%2,[%3],%4;"
               ::"r"(dst), "l"(src), "r"(bytes), "r"(bar), "h"((uint16_t)7) : "memory");
}
__device__ __forceinline__ void bulk_s2g(void* dst, uint32_t src, uint32_t bytes) {
  asm volatile("cp.async.bulk.global.shared::cta.bulk_group [%0],[%1],%2;" ::"l"(dst), "r"(src), "r"(bytes) : "memory");
}
__device__ __forceinline__ void bulk_s2c(uint32_t dst, uint32_t src, uint32_t bytes, uint32_t bar) {
  asm volatile("cp.async.bulk.shared::cluster.shared::cta.mbarrier::complete_tx::bytes [%0],[%1],%2,[%3];" ::"r"(dst), "r"(src), "r"(bytes), "r"(bar) : "memory");
}
__device__ __forceinline__ void tma2d(uint32_t dst, const CUtensorMap* tm, int c0, int c1, uint32_t bar) {
  asm volatile("cp.async.bulk.tensor.2d.shared::cluster.global.mbarrier::complete_tx::bytes [%0],[%1,{%3,%4}],[%2];"
               ::"r"(dst), "l"(tm), "r"(bar), "r"(c0), "r"(c1) : "memory");
}
__device__ __forceinline__ void tma2d_prefetch(const CUtensorMap* tm, int c0, int c1) {
  asm volatile("cp.async.bulk.prefetch.tensor.2d.L2.global.tile [%0,{%1,%2}];" ::"l"(tm), "r"(c0), "r"(c1) : "memory");
}
__device__ __forceinline__ uint32_t pack_bf16(float lo, float hi) {
  uint32_t r; asm("cvt.rn.bf16x2.f32 %0,%1,%2;" : "=r"(r) : "f"(hi), "f"(lo)); return r;
}
__device__ __forceinline__ float bf_lo(uint32_t x) { return __uint_as_float(x << 16); }
__device__ __forceinline__ float bf_hi(uint32_t x) { return __uint_as_float(x & 0xFFFF0000u); }
__device__ __forceinline__ float ex2(float x) { float y; asm("ex2.approx.ftz.f32 %0,%1;" : "=f"(y) : "f"(x)); return y; }
__device__ __forceinline__ void ldsm4(uint32_t (&r)[4], uint32_t a) {
  asm volatile("ldmatrix.sync.aligned.m8n8.x4.shared.b16 {%0,%1,%2,%3},[%4];" : "=r"(r[0]), "=r"(r[1]), "=r"(r[2]), "=r"(r[3]) : "r"(a) : "memory");
}
__device__ __forceinline__ void ldsm4t(uint32_t (&r)[4], uint32_t a) {
  asm volatile("ldmatrix.sync.aligned.m8n8.x4.trans.shared.b16 {%0,%1,%2,%3},[%4];" : "=r"(r[0]), "=r"(r[1]), "=r"(r[2]), "=r"(r[3]) : "r"(a) : "memory");
}
__device__ __forceinline__ void ldsm2(uint32_t& r0, uint32_t& r1, uint32_t a) {
  asm volatile("ldmatrix.sync.aligned.m8n8.x2.shared.b16 {%0,%1},[%2];" : "=r"(r0), "=r"(r1) : "r"(a) : "memory");
}
__device__ __forceinline__ void ldsm2t(uint32_t& r0, uint32_t& r1, uint32_t a) {
  asm volatile("ldmatrix.sync.aligned.m8n8.x2.trans.shared.b16 {%0,%1},[%2];" : "=r"(r0), "=r"(r1) : "r"(a) : "memory");
}
__device__ __forceinline__ void ldsm1(uint32_t& r0, uint32_t a) {
  asm volatile("ldmatrix.sync.aligned.m8n8.x1.shared.b16 {%0},[%1];" : "=r"(r0) : "r"(a) : "memory");
}
__device__ __forceinline__ void mma16816(float (&d)[4], uint32_t a0, uint32_t a1, uint32_t a2, uint32_t a3, uint32_t b0, uint32_t b1) {
  asm volatile("mma.sync.aligned.m16n8k16.row.col.f32.bf16.bf16.f32 {%0,%1,%2,%3},{%4,%5,%6,%7},{%8,%9},{%0,%1,%2,%3};"
               : "+f"(d[0]), "+f"(d[1]), "+f"(d[2]), "+f"(d[3]) : "r"(a0), "r"(a1), "r"(a2), "r"(a3), "r"(b0), "r"(b1));
}
__device__ __forceinline__ void mma1688(float (&d)[4], uint32_t a0, uint32_t a1, uint32_t b0) {
  asm volatile("mma.sync.aligned.m16n8k8.row.col.f32.bf16.bf16.f32 {%0,%1,%2,%3},{%4,%5},{%6},{%0,%1,%2,%3};"
               : "+f"(d[0]), "+f"(d[1]), "+f"(d[2]), "+f"(d[3]) : "r"(a0), "r"(a1), "r"(b0));
}
__device__ __forceinline__ void sts32(uint32_t a, uint32_t v) { asm volatile("st.shared.b32 [%0],%1;" ::"r"(a), "r"(v) : "memory"); }
__device__ __forceinline__ void sts64f(uint32_t a, float x, float y) { asm volatile("st.shared.v2.f32 [%0],{%1,%2};" ::"r"(a), "f"(x), "f"(y) : "memory"); }
__device__ __forceinline__ void sts128(uint32_t a, uint4 v) { asm volatile("st.shared.v4.b32 [%0],{%1,%2,%3,%4};" ::"r"(a), "r"(v.x), "r"(v.y), "r"(v.z), "r"(v.w) : "memory"); }
__device__ __forceinline__ float lds32f(uint32_t a) { float v; asm volatile("ld.shared.f32 %0,[%1];" : "=f"(v) : "r"(a) : "memory"); return v; }
__device__ __forceinline__ float2 lds64f(uint32_t a) { float2 v; asm volatile("ld.shared.v2.f32 {%0,%1},[%2];" : "=f"(v.x), "=f"(v.y) : "r"(a) : "memory"); return v; }
__device__ __forceinline__ uint4 lds128(uint32_t a) { uint4 v; asm volatile("ld.shared.v4.b32 {%0,%1,%2,%3},[%4];" : "=r"(v.x), "=r"(v.y), "=r"(v.z), "=r"(v.w) : "r"(a) : "memory"); return v; }
__device__ __forceinline__ float4 lds128f(uint32_t a) { float4 v; asm volatile("ld.shared.v4.f32 {%0,%1,%2,%3},[%4];" : "=f"(v.x), "=f"(v.y), "=f"(v.z), "=f"(v.w) : "r"(a) : "memory"); return v; }
__device__ __forceinline__ void st_async2(uint32_t a, float x, float y, uint32_t bar) {
  asm volatile("st.async.weak.shared::cluster.mbarrier::complete_tx::bytes.v2.f32 [%0],{%1,%2},[%3];" ::"r"(a), "f"(x), "f"(y), "r"(bar) : "memory");
}
__device__ __forceinline__ void st_async4(uint32_t a, const float (&v)[4], uint32_t bar) {
  asm volatile("st.async.weak.shared::cluster.mbarrier::complete_tx::bytes.v4.f32 [%0],{%1,%2,%3,%4},[%5];" ::"r"(a), "f"(v[0]), "f"(v[1]), "f"(v[2]), "f"(v[3]), "r"(bar) : "memory");
}
__device__ __forceinline__ void st_async4v(uint32_t a, float x, float y, float z, float w, uint32_t bar) {
  asm volatile("st.async.weak.shared::cluster.mbarrier::complete_tx::bytes.v4.f32 [%0],{%1,%2,%3,%4},[%5];" ::"r"(a), "f"(x), "f"(y), "f"(z), "f"(w), "r"(bar) : "memory");
}
__device__ __forceinline__ void st_async4u(uint32_t a, const uint4& v, uint32_t bar) {
  asm volatile("st.async.weak.shared::cluster.mbarrier::complete_tx::bytes.v4.b32 [%0],{%1,%2,%3,%4},[%5];" ::"r"(a), "r"(v.x), "r"(v.y), "r"(v.z), "r"(v.w), "r"(bar) : "memory");
}
__device__ __forceinline__ uint4 ld_relaxed4(const void* p) {
  uint4 v; asm volatile("ld.relaxed.gpu.global.v4.u32 {%0,%1,%2,%3},[%4];" : "=r"(v.x), "=r"(v.y), "=r"(v.z), "=r"(v.w) : "l"(p) : "memory"); return v;
}
__device__ __forceinline__ uint32_t ld_relaxed(const void* p) {
  uint32_t v; asm volatile("ld.relaxed.gpu.global.u32 %0,[%1];" : "=r"(v) : "l"(p) : "memory"); return v;
}
__device__ __forceinline__ void st_relaxed(void* p, uint32_t v) { asm volatile("st.relaxed.gpu.global.b32 [%0],%1;" ::"l"(p), "r"(v) : "memory"); }
__device__ __forceinline__ void st_relaxed4(void* p, uint32_t v) { asm volatile("st.relaxed.gpu.global.v4.b32 [%0],{%1,%1,%1,%1};" ::"l"(p), "r"(v) : "memory"); }

__device__ __forceinline__ uint32_t ld_acquire(const void* p) {
  uint32_t v; asm volatile("ld.acquire.gpu.global.u32 %0,[%1];" : "=r"(v) : "l"(p) : "memory"); return v;
}
__device__ __forceinline__ float4 ld_relaxed4f(const void* p) {
  float4 v; asm volatile("ld.relaxed.gpu.global.v4.f32 {%0,%1,%2,%3},[%4];" : "=f"(v.x), "=f"(v.y), "=f"(v.z), "=f"(v.w) : "l"(p) : "memory"); return v;
}
__device__ __forceinline__ float2 ld_relaxed2f(const void* p) {
  float2 v; asm volatile("ld.relaxed.gpu.global.v2.f32 {%0,%1},[%2];" : "=f"(v.x), "=f"(v.y) : "l"(p) : "memory"); return v;
}
__device__ __forceinline__ void prefetch_l2(const void* p) { asm volatile("prefetch.global.L2 [%0];" ::"l"(p)); }
__device__ __forceinline__ void fence_gpu() { asm volatile("fence.acq_rel.gpu;" ::: "memory"); }
__device__ __forceinline__ void fence_async_all() { asm volatile("fence.proxy.async.global;" ::: "memory"); }
constexpr int SPIN_TOT = 1 << 22;
__device__ __forceinline__ void csignal(int idx) { asm volatile("red.release.gpu.global.add.u32 [%0],1;" ::"l"(&g_cnt[idx][0]) : "memory"); }
#define RLX 0
#define csignal_t(idx, role) csignal(idx)
__device__ __forceinline__ void cwait(int idx, uint32_t target, int& spin) {
  while (ld_acquire(&g_cnt[idx][0]) < target && spin < SPIN_TOT) spin += 16;
}

__device__ __forceinline__ uint64_t mkdesc(uint32_t addr, uint32_t lbo, uint32_t sbo) {
  return (uint64_t)((addr & 0x3FFFF) >> 4) | ((uint64_t)(lbo >> 4) << 16) | ((uint64_t)(sbo >> 4) << 32) | ((uint64_t)1 << 62);
}
__device__ __forceinline__ uint64_t mkdesc_ns(uint32_t addr, uint32_t lbo, uint32_t sbo) {
  return (uint64_t)((addr & 0x3FFFF) >> 4) | ((uint64_t)(lbo >> 4) << 16) | ((uint64_t)(sbo >> 4) << 32);
}
__device__ __forceinline__ void wg_fence() { asm volatile("wgmma.fence.sync.aligned;" ::: "memory"); }
__device__ __forceinline__ void wg_commit() { asm volatile("wgmma.commit_group.sync.aligned;" ::: "memory"); }
template <int N> __device__ __forceinline__ void wg_wait() { asm volatile("wgmma.wait_group.sync.aligned %0;" ::"n"(N) : "memory"); }

__device__ __forceinline__ void wgmma_rs16(float (&d)[8], const uint32_t (&a)[4], uint64_t db, int sc) {
  asm volatile("{.reg .pred p; setp.ne.b32 p,%13,0; wgmma.mma_async.sync.aligned.m64n16k16.f32.bf16.bf16 "
               "{%0,%1,%2,%3,%4,%5,%6,%7},{%8,%9,%10,%11},%12,p,1,1,0;}"
               : "+f"(d[0]), "+f"(d[1]), "+f"(d[2]), "+f"(d[3]), "+f"(d[4]), "+f"(d[5]), "+f"(d[6]), "+f"(d[7])
               : "r"(a[0]), "r"(a[1]), "r"(a[2]), "r"(a[3]), "l"(db), "r"(sc));
}
__device__ __forceinline__ void wgmma_rs64(float (&d)[32], const uint32_t (&a)[4], uint64_t db, int sc) {
  asm volatile("{.reg .pred p; setp.ne.b32 p,%37,0; wgmma.mma_async.sync.aligned.m64n64k16.f32.bf16.bf16 "
               "{%0,%1,%2,%3,%4,%5,%6,%7,%8,%9,%10,%11,%12,%13,%14,%15,%16,%17,%18,%19,%20,%21,%22,%23,%24,%25,%26,%27,%28,%29,%30,%31},{%32,%33,%34,%35},%36,p,1,1,0;}"
               : "+f"(d[0]), "+f"(d[1]), "+f"(d[2]), "+f"(d[3]), "+f"(d[4]), "+f"(d[5]), "+f"(d[6]), "+f"(d[7]), "+f"(d[8]), "+f"(d[9]), "+f"(d[10]), "+f"(d[11]), "+f"(d[12]), "+f"(d[13]), "+f"(d[14]), "+f"(d[15]), "+f"(d[16]), "+f"(d[17]), "+f"(d[18]), "+f"(d[19]), "+f"(d[20]), "+f"(d[21]), "+f"(d[22]), "+f"(d[23]), "+f"(d[24]), "+f"(d[25]), "+f"(d[26]), "+f"(d[27]), "+f"(d[28]), "+f"(d[29]), "+f"(d[30]), "+f"(d[31])
               : "r"(a[0]), "r"(a[1]), "r"(a[2]), "r"(a[3]), "l"(db), "r"(sc));
}
__device__ __forceinline__ void wgmma_rt16(float (&d)[8], const uint32_t (&a)[4], uint64_t db, int sc) {
  asm volatile("{.reg .pred p; setp.ne.b32 p,%13,0; wgmma.mma_async.sync.aligned.m64n16k16.f32.bf16.bf16 "
               "{%0,%1,%2,%3,%4,%5,%6,%7},{%8,%9,%10,%11},%12,p,1,1,1;}"
               : "+f"(d[0]), "+f"(d[1]), "+f"(d[2]), "+f"(d[3]), "+f"(d[4]), "+f"(d[5]), "+f"(d[6]), "+f"(d[7])
               : "r"(a[0]), "r"(a[1]), "r"(a[2]), "r"(a[3]), "l"(db), "r"(sc));
}
__device__ __forceinline__ void wgmma_rt80(float (&d)[40], const uint32_t (&a)[4], uint64_t db, int sc) {
  asm volatile("{.reg .pred p; setp.ne.b32 p,%45,0; wgmma.mma_async.sync.aligned.m64n80k16.f32.bf16.bf16 "
               "{%0,%1,%2,%3,%4,%5,%6,%7,%8,%9,%10,%11,%12,%13,%14,%15,%16,%17,%18,%19,%20,%21,%22,%23,%24,%25,%26,%27,%28,%29,%30,%31,%32,%33,%34,%35,%36,%37,%38,%39},{%40,%41,%42,%43},%44,p,1,1,1;}"
               : "+f"(d[0]), "+f"(d[1]), "+f"(d[2]), "+f"(d[3]), "+f"(d[4]), "+f"(d[5]), "+f"(d[6]), "+f"(d[7]), "+f"(d[8]), "+f"(d[9]), "+f"(d[10]), "+f"(d[11]), "+f"(d[12]), "+f"(d[13]), "+f"(d[14]), "+f"(d[15]), "+f"(d[16]), "+f"(d[17]), "+f"(d[18]), "+f"(d[19]), "+f"(d[20]), "+f"(d[21]), "+f"(d[22]), "+f"(d[23]), "+f"(d[24]), "+f"(d[25]), "+f"(d[26]), "+f"(d[27]), "+f"(d[28]), "+f"(d[29]), "+f"(d[30]), "+f"(d[31]), "+f"(d[32]), "+f"(d[33]), "+f"(d[34]), "+f"(d[35]), "+f"(d[36]), "+f"(d[37]), "+f"(d[38]), "+f"(d[39])
               : "r"(a[0]), "r"(a[1]), "r"(a[2]), "r"(a[3]), "l"(db), "r"(sc));
}
__device__ __forceinline__ void wgmma_rs32(float (&d)[16], const uint32_t (&a)[4], uint64_t db, int sc) {
  asm volatile("{.reg .pred p; setp.ne.b32 p,%21,0; wgmma.mma_async.sync.aligned.m64n32k16.f32.bf16.bf16 "
               "{%0,%1,%2,%3,%4,%5,%6,%7,%8,%9,%10,%11,%12,%13,%14,%15},{%16,%17,%18,%19},%20,p,1,1,0;}"
               : "+f"(d[0]), "+f"(d[1]), "+f"(d[2]), "+f"(d[3]), "+f"(d[4]), "+f"(d[5]), "+f"(d[6]), "+f"(d[7]), "+f"(d[8]), "+f"(d[9]), "+f"(d[10]), "+f"(d[11]), "+f"(d[12]), "+f"(d[13]), "+f"(d[14]), "+f"(d[15])
               : "r"(a[0]), "r"(a[1]), "r"(a[2]), "r"(a[3]), "l"(db), "r"(sc));
}
__device__ __forceinline__ void wgmma_ts32(float (&d)[16], uint64_t da, uint64_t db, int sc) {
  asm volatile("{.reg .pred p; setp.ne.b32 p,%18,0; wgmma.mma_async.sync.aligned.m64n32k16.f32.bf16.bf16 "
               "{%0,%1,%2,%3,%4,%5,%6,%7,%8,%9,%10,%11,%12,%13,%14,%15},%16,%17,p,1,1,1,0;}"
               : "+f"(d[0]), "+f"(d[1]), "+f"(d[2]), "+f"(d[3]), "+f"(d[4]), "+f"(d[5]), "+f"(d[6]), "+f"(d[7]), "+f"(d[8]), "+f"(d[9]), "+f"(d[10]), "+f"(d[11]), "+f"(d[12]), "+f"(d[13]), "+f"(d[14]), "+f"(d[15])
               : "l"(da), "l"(db), "r"(sc));
}
__device__ __forceinline__ void wgmma_rs8(float (&d)[4], const uint32_t (&a)[4], uint64_t db, int sc) {
  asm volatile("{.reg .pred p; setp.ne.b32 p,%9,0; wgmma.mma_async.sync.aligned.m64n8k16.f32.bf16.bf16 "
               "{%0,%1,%2,%3},{%4,%5,%6,%7},%8,p,1,1,0;}"
               : "+f"(d[0]), "+f"(d[1]), "+f"(d[2]), "+f"(d[3])
               : "r"(a[0]), "r"(a[1]), "r"(a[2]), "r"(a[3]), "l"(db), "r"(sc));
}
__device__ __forceinline__ void wgmma_ts16(float (&d)[8], uint64_t da, uint64_t db, int sc) {
  asm volatile("{.reg .pred p; setp.ne.b32 p,%10,0; wgmma.mma_async.sync.aligned.m64n16k16.f32.bf16.bf16 "
               "{%0,%1,%2,%3,%4,%5,%6,%7},%8,%9,p,1,1,1,0;}"
               : "+f"(d[0]), "+f"(d[1]), "+f"(d[2]), "+f"(d[3]), "+f"(d[4]), "+f"(d[5]), "+f"(d[6]), "+f"(d[7])
               : "l"(da), "l"(db), "r"(sc));
}
__device__ __forceinline__ void wgmma_ts64(float (&d)[32], uint64_t da, uint64_t db, int sc) {
  asm volatile("{.reg .pred p; setp.ne.b32 p,%34,0; wgmma.mma_async.sync.aligned.m64n64k16.f32.bf16.bf16 "
               "{%0,%1,%2,%3,%4,%5,%6,%7,%8,%9,%10,%11,%12,%13,%14,%15,%16,%17,%18,%19,%20,%21,%22,%23,%24,%25,%26,%27,%28,%29,%30,%31},%32,%33,p,1,1,1,0;}"
               : "+f"(d[0]), "+f"(d[1]), "+f"(d[2]), "+f"(d[3]), "+f"(d[4]), "+f"(d[5]), "+f"(d[6]), "+f"(d[7]), "+f"(d[8]), "+f"(d[9]), "+f"(d[10]), "+f"(d[11]), "+f"(d[12]), "+f"(d[13]), "+f"(d[14]), "+f"(d[15]), "+f"(d[16]), "+f"(d[17]), "+f"(d[18]), "+f"(d[19]), "+f"(d[20]), "+f"(d[21]), "+f"(d[22]), "+f"(d[23]), "+f"(d[24]), "+f"(d[25]), "+f"(d[26]), "+f"(d[27]), "+f"(d[28]), "+f"(d[29]), "+f"(d[30]), "+f"(d[31])
               : "l"(da), "l"(db), "r"(sc));
}
__device__ __forceinline__ void wgmma_tt16(float (&d)[8], uint64_t da, uint64_t db, int sc) {
  asm volatile("{.reg .pred p; setp.ne.b32 p,%10,0; wgmma.mma_async.sync.aligned.m64n16k16.f32.bf16.bf16 "
               "{%0,%1,%2,%3,%4,%5,%6,%7},%8,%9,p,1,1,1,1;}"
               : "+f"(d[0]), "+f"(d[1]), "+f"(d[2]), "+f"(d[3]), "+f"(d[4]), "+f"(d[5]), "+f"(d[6]), "+f"(d[7])
               : "l"(da), "l"(db), "r"(sc));
}
__device__ __forceinline__ void wgmma_tt40(float (&d)[20], uint64_t da, uint64_t db, int sc) {
  asm volatile("{.reg .pred p; setp.ne.b32 p,%22,0; wgmma.mma_async.sync.aligned.m64n40k16.f32.bf16.bf16 "
               "{%0,%1,%2,%3,%4,%5,%6,%7,%8,%9,%10,%11,%12,%13,%14,%15,%16,%17,%18,%19},%20,%21,p,1,1,1,1;}"
               : "+f"(d[0]), "+f"(d[1]), "+f"(d[2]), "+f"(d[3]), "+f"(d[4]), "+f"(d[5]), "+f"(d[6]), "+f"(d[7]), "+f"(d[8]), "+f"(d[9]), "+f"(d[10]), "+f"(d[11]), "+f"(d[12]), "+f"(d[13]), "+f"(d[14]), "+f"(d[15]), "+f"(d[16]), "+f"(d[17]), "+f"(d[18]), "+f"(d[19])
               : "l"(da), "l"(db), "r"(sc));
}
__device__ __forceinline__ void wgmma_ss8(float (&d)[4], uint64_t da, uint64_t db, int sc) {
  asm volatile("{.reg .pred p; setp.ne.b32 p,%6,0; wgmma.mma_async.sync.aligned.m64n8k16.f32.bf16.bf16 "
               "{%0,%1,%2,%3},%4,%5,p,1,1,0,0;}"
               : "+f"(d[0]), "+f"(d[1]), "+f"(d[2]), "+f"(d[3])
               : "l"(da), "l"(db), "r"(sc));
}
__device__ __forceinline__ void wgmma_ss32(float (&d)[16], uint64_t da, uint64_t db, int sc) {
  asm volatile("{.reg .pred p; setp.ne.b32 p,%18,0; wgmma.mma_async.sync.aligned.m64n32k16.f32.bf16.bf16 "
               "{%0,%1,%2,%3,%4,%5,%6,%7,%8,%9,%10,%11,%12,%13,%14,%15},%16,%17,p,1,1,0,0;}"
               : "+f"(d[0]), "+f"(d[1]), "+f"(d[2]), "+f"(d[3]), "+f"(d[4]), "+f"(d[5]), "+f"(d[6]), "+f"(d[7]), "+f"(d[8]), "+f"(d[9]), "+f"(d[10]), "+f"(d[11]), "+f"(d[12]), "+f"(d[13]), "+f"(d[14]), "+f"(d[15])
               : "l"(da), "l"(db), "r"(sc));
}
__device__ __forceinline__ void wgmma_st64(float (&d)[32], uint64_t da, uint64_t db, int sc) {
  asm volatile("{.reg .pred p; setp.ne.b32 p,%34,0; wgmma.mma_async.sync.aligned.m64n64k16.f32.bf16.bf16 "
               "{%0,%1,%2,%3,%4,%5,%6,%7,%8,%9,%10,%11,%12,%13,%14,%15,%16,%17,%18,%19,%20,%21,%22,%23,%24,%25,%26,%27,%28,%29,%30,%31},%32,%33,p,1,1,0,1;}"
               : "+f"(d[0]), "+f"(d[1]), "+f"(d[2]), "+f"(d[3]), "+f"(d[4]), "+f"(d[5]), "+f"(d[6]), "+f"(d[7]), "+f"(d[8]), "+f"(d[9]), "+f"(d[10]), "+f"(d[11]), "+f"(d[12]), "+f"(d[13]), "+f"(d[14]), "+f"(d[15]), "+f"(d[16]), "+f"(d[17]), "+f"(d[18]), "+f"(d[19]), "+f"(d[20]), "+f"(d[21]), "+f"(d[22]), "+f"(d[23]), "+f"(d[24]), "+f"(d[25]), "+f"(d[26]), "+f"(d[27]), "+f"(d[28]), "+f"(d[29]), "+f"(d[30]), "+f"(d[31])
               : "l"(da), "l"(db), "r"(sc));
}
__device__ __forceinline__ void wgmma_st128(float (&d)[64], uint64_t da, uint64_t db, int sc) {
  asm volatile("{.reg .pred p; setp.ne.b32 p,%66,0; wgmma.mma_async.sync.aligned.m64n128k16.f32.bf16.bf16 "
               "{%0,%1,%2,%3,%4,%5,%6,%7,%8,%9,%10,%11,%12,%13,%14,%15,%16,%17,%18,%19,%20,%21,%22,%23,%24,%25,%26,%27,%28,%29,%30,%31,%32,%33,%34,%35,%36,%37,%38,%39,%40,%41,%42,%43,%44,%45,%46,%47,%48,%49,%50,%51,%52,%53,%54,%55,%56,%57,%58,%59,%60,%61,%62,%63},%64,%65,p,1,1,0,1;}"
               : "+f"(d[0]), "+f"(d[1]), "+f"(d[2]), "+f"(d[3]), "+f"(d[4]), "+f"(d[5]), "+f"(d[6]), "+f"(d[7]), "+f"(d[8]), "+f"(d[9]), "+f"(d[10]), "+f"(d[11]), "+f"(d[12]), "+f"(d[13]), "+f"(d[14]), "+f"(d[15]), "+f"(d[16]), "+f"(d[17]), "+f"(d[18]), "+f"(d[19]), "+f"(d[20]), "+f"(d[21]), "+f"(d[22]), "+f"(d[23]), "+f"(d[24]), "+f"(d[25]), "+f"(d[26]), "+f"(d[27]), "+f"(d[28]), "+f"(d[29]), "+f"(d[30]), "+f"(d[31]), "+f"(d[32]), "+f"(d[33]), "+f"(d[34]), "+f"(d[35]), "+f"(d[36]), "+f"(d[37]), "+f"(d[38]), "+f"(d[39]), "+f"(d[40]), "+f"(d[41]), "+f"(d[42]), "+f"(d[43]), "+f"(d[44]), "+f"(d[45]), "+f"(d[46]), "+f"(d[47]), "+f"(d[48]), "+f"(d[49]), "+f"(d[50]), "+f"(d[51]), "+f"(d[52]), "+f"(d[53]), "+f"(d[54]), "+f"(d[55]), "+f"(d[56]), "+f"(d[57]), "+f"(d[58]), "+f"(d[59]), "+f"(d[60]), "+f"(d[61]), "+f"(d[62]), "+f"(d[63])
               : "l"(da), "l"(db), "r"(sc));
}

__device__ __forceinline__ void stsm4(uint32_t a, uint32_t r0, uint32_t r1, uint32_t r2, uint32_t r3) {
  asm volatile("stmatrix.sync.aligned.m8n8.x4.shared.b16 [%0],{%1,%2,%3,%4};" ::"r"(a), "r"(r0), "r"(r1), "r"(r2), "r"(r3) : "memory");
}
__device__ __forceinline__ void stsm4t(uint32_t a, uint32_t r0, uint32_t r1, uint32_t r2, uint32_t r3) {
  asm volatile("stmatrix.sync.aligned.m8n8.x4.trans.shared.b16 [%0],{%1,%2,%3,%4};" ::"r"(a), "r"(r0), "r"(r1), "r"(r2), "r"(r3) : "memory");
}
__device__ __forceinline__ void sts64(uint32_t a, uint32_t x, uint32_t y) { asm volatile("st.shared.v2.b32 [%0],{%1,%2};" ::"r"(a), "r"(x), "r"(y) : "memory"); }
__device__ __forceinline__ void st_async2u(uint32_t a, uint32_t x, uint32_t y, uint32_t bar) {
  asm volatile("st.async.weak.shared::cluster.mbarrier::complete_tx::bytes.v2.b32 [%0],{%1,%2},[%3];" ::"r"(a), "r"(x), "r"(y), "r"(bar) : "memory");
}
__device__ __forceinline__ void st_relaxed128(void* p, uint32_t x, uint32_t y, uint32_t z, uint32_t w) {
  asm volatile("{.reg .b128 v; mov.b128 v,{%1,%2,%3,%4}; st.relaxed.gpu.global.b128 [%0],v;}" ::"l"(p), "r"(x), "r"(y), "r"(z), "r"(w) : "memory");
}
__device__ __forceinline__ void st_relaxed64(void* p, uint32_t x, uint32_t y) {
  asm volatile("{.reg .b64 v; mov.b64 v,{%1,%2}; st.relaxed.gpu.global.b64 [%0],v;}" ::"l"(p), "r"(x), "r"(y) : "memory");
}
__device__ __forceinline__ uint4 ld_relaxed128(const void* p) {
  uint4 v;
  asm volatile("{.reg .b128 v; .reg .b64 lo, hi; ld.relaxed.gpu.global.b128 v,[%4]; mov.b128 {lo,hi},v; mov.b64 {%0,%1},lo; mov.b64 {%2,%3},hi;}" : "=r"(v.x), "=r"(v.y), "=r"(v.z), "=r"(v.w) : "l"(p) : "memory");
  return v;
}

__device__ __forceinline__ uint32_t pack_h2(float lo, float hi) {
  uint32_t r; asm("cvt.rn.satfinite.f16x2.f32 %0,%1,%2;" : "=r"(r) : "f"(hi), "f"(lo)); return r;
}
__device__ __forceinline__ void add_h2(float& lo, float& hi, uint32_t u, uint32_t v) {
  float a, b;
  asm("{.reg .b16 l, h; .reg .b32 s; add.rn.f16x2 s,%2,%3; mov.b32 {l,h},s; cvt.f32.f16 %0,l; cvt.f32.f16 %1,h;}" : "=f"(a), "=f"(b) : "r"(u), "r"(v));
  lo += a; hi += b;
}
__device__ __forceinline__ void mwait(uint32_t bar, uint32_t ph, int& spin) {
  asm volatile("{.reg .pred p, q;\nWAIT_LOOP:\n add.s32 %0,%0,1;\n setp.lt.s32 q,%0,%3;\n mbarrier.try_wait.parity.shared::cta.b64 p,[%1],%2;\n not.pred p,p;\n and.pred q,q,p;\n @q bra.uni WAIT_LOOP;\n}"
               : "+&r"(spin) : "r"(bar), "r"(ph), "n"(SPIN_TOT) : "memory");
}
__device__ __forceinline__ int keep(int x) { return __shfl_sync(0xffffffffu, x, threadIdx.x & 31); }
__device__ __forceinline__ uint32_t pin(uint32_t x) { asm volatile("" : "+r"(x)); return x; }
template <typename T> __device__ __forceinline__ T* pinp(T* x) { asm volatile("" : "+l"(x)); return x; }
__device__ __forceinline__ void st_async1u(uint32_t a, uint32_t x, uint32_t bar) {
  asm volatile("st.async.weak.shared::cluster.mbarrier::complete_tx::bytes.b32 [%0],%1,[%2];" ::"r"(a), "r"(x), "r"(bar) : "memory");
}
__device__ __forceinline__ uint32_t lds32(uint32_t a) { uint32_t v; asm volatile("ld.shared.b32 %0,[%1];" : "=r"(v) : "r"(a) : "memory"); return v; }
__device__ __forceinline__ uint2 lds64(uint32_t a) { uint2 v; asm volatile("ld.shared.v2.b32 {%0,%1},[%2];" : "=r"(v.x), "=r"(v.y) : "r"(a) : "memory"); return v; }

__device__ __forceinline__ void permute_cols(uint32_t tile, int tid, int n) {
  for (int it = tid; it < n; it += 128) {
    const int row = it >> 2, q = it & 3;
    const uint32_t a0 = tile + row * 128 + (((2 * q) ^ (row & 7)) << 4), a1 = tile + row * 128 + (((2 * q + 1) ^ (row & 7)) << 4);
    const uint4 u = lds128(a0), v = lds128(a1);
    sts128(a0, make_uint4(__byte_perm(u.x, u.y, 0x5410), __byte_perm(u.z, u.w, 0x5410), __byte_perm(v.x, v.y, 0x5410), __byte_perm(v.z, v.w, 0x5410)));
    sts128(a1, make_uint4(__byte_perm(u.x, u.y, 0x7632), __byte_perm(u.z, u.w, 0x7632), __byte_perm(v.x, v.y, 0x7632), __byte_perm(v.z, v.w, 0x7632)));
  }
}

__device__ __forceinline__ uint8_t* mkptr(uint32_t lo, uint32_t hi) { uint8_t* p; asm("mov.b64 %0,{%1,%2};" : "=l"(p) : "r"(lo), "r"(hi)); return p; }
__device__ __forceinline__ int uni(int x) { return __shfl_sync(0xffffffffu, x, 0); }

__device__ __forceinline__ bool elect_one() {
  uint32_t p; asm volatile("{.reg .pred q; elect.sync _|q, 0xffffffff; selp.u32 %0,1,0,q;}" : "=r"(p)); return p;
}
__device__ __forceinline__ uint64_t desc_at(uint64_t d, uint32_t off) {
  uint64_t r; asm("mov.b64 %0,{%1,%2};" : "=l"(r) : "r"((uint32_t)d + (off >> 4)), "r"((uint32_t)(d >> 32))); return r;
}
__device__ __forceinline__ uint32_t scale_bf16x2(uint32_t x, uint32_t s) { uint32_t r; asm("mul.rn.bf16x2 %0,%1,%2;" : "=r"(r) : "r"(x), "r"(s)); return r; }

__device__ __forceinline__ void stg128(void* p, const uint4& v) { asm volatile("st.global.v4.b32 [%0],{%1,%2,%3,%4};" ::"l"(p), "r"(v.x), "r"(v.y), "r"(v.z), "r"(v.w) : "memory"); }

__device__ __forceinline__ void ln_row_to_image(const bf16* __restrict__ x, uint8_t* __restrict__ img, int row, int lane) {
  const uint4* src = reinterpret_cast<const uint4*>(x + (size_t)row * DM);
  uint4 v[3];
  v[0] = src[lane]; v[1] = src[lane + 32];
  v[2] = lane < 16 ? src[lane + 64] : make_uint4(0, 0, 0, 0);
  float s = 0.f;
#pragma unroll
  for (int i = 0; i < 3; i++) {
    s += bf_lo(v[i].x) + bf_hi(v[i].x) + bf_lo(v[i].y) + bf_hi(v[i].y) + bf_lo(v[i].z) + bf_hi(v[i].z) + bf_lo(v[i].w) + bf_hi(v[i].w);
  }
#pragma unroll
  for (int o = 16; o > 0; o >>= 1) s += __shfl_xor_sync(0xffffffffu, s, o);
  const float mean = s * (1.f / DM);
  float q = 0.f;
#pragma unroll
  for (int i = 0; i < 3; i++) {
    if (i < 2 || lane < 16) {
      const uint32_t w[4] = {v[i].x, v[i].y, v[i].z, v[i].w};
#pragma unroll
      for (int j = 0; j < 4; j++) { float a = bf_lo(w[j]) - mean, b = bf_hi(w[j]) - mean; q += a * a + b * b; }
    }
  }
#pragma unroll
  for (int o = 16; o > 0; o >>= 1) q += __shfl_xor_sync(0xffffffffu, q, o);
  const float rstd = rsqrtf(q * (1.f / DM) + 1e-5f);
#pragma unroll
  for (int i = 0; i < 3; i++) {
    if (i < 2 || lane < 16) {
      const int c = lane + 32 * i;
      uint4 o;
      o.x = pack_bf16((bf_lo(v[i].x) - mean) * rstd, (bf_hi(v[i].x) - mean) * rstd);
      o.y = pack_bf16((bf_lo(v[i].y) - mean) * rstd, (bf_hi(v[i].y) - mean) * rstd);
      o.z = pack_bf16((bf_lo(v[i].z) - mean) * rstd, (bf_hi(v[i].z) - mean) * rstd);
      o.w = pack_bf16((bf_lo(v[i].w) - mean) * rstd, (bf_hi(v[i].w) - mean) * rstd);
      const size_t off = (size_t)(row >> 5) * 81920 + (c >> 4) * 16384 + ((row >> 3) & 3) * 4096 + ((c >> 3) & 1) * 1024 + (row & 7) * 128 + (((c & 7) ^ (row & 7)) << 4);
      *reinterpret_cast<uint4*>(img + off) = o;
      float4* xf = reinterpret_cast<float4*>(g_x + (size_t)row * DM + c * 8);
      xf[0] = make_float4(bf_lo(v[i].x), bf_hi(v[i].x), bf_lo(v[i].y), bf_hi(v[i].y));
      xf[1] = make_float4(bf_lo(v[i].z), bf_hi(v[i].z), bf_lo(v[i].w), bf_hi(v[i].w));
    }
  }
}

#define NOWORK 0
__global__ void __launch_bounds__(256) k_pre(const bf16* __restrict__ x, const bf16* __restrict__ mem0) {
  const int row = blockIdx.x * 8 + (threadIdx.x >> 5);
  ln_row_to_image(x, g_xn[0], row, threadIdx.x & 31);
  const int gt = blockIdx.x * 256 + threadIdx.x;
  const uint4 sent = make_uint4(SENT, SENT, SENT, SENT);
  uint8_t* ex = ex_window(g_ex);
  if (gt < MAIL_BYTES / 16) {
    reinterpret_cast<uint4*>(ex + EX_MAIL)[gt] = sent;
    reinterpret_cast<uint4*>(ex + EX_MAIL + (1 << 20))[gt] = sent;
  }
  uint4* mb = reinterpret_cast<uint4*>(ex + EX_M);
  for (int i = gt; i < NSTEP * 1280; i += 65536) {
    const int p = i % 1280, st = i / 1280;
    uint4 v = sent;
    if (st == 0 || (st == LAG && (p & 8))) v = *reinterpret_cast<const uint4*>(mem0 + (p & 7) * DM + (p >> 4) * 8);
    mb[i] = v;
  }
  if (gt < NSTEP * 192) reinterpret_cast<uint4*>(ex + EX_FLAG)[gt] = gt < 192 ? make_uint4(0, 0, 0, 0) : sent;
  for (int i = gt; i < (NOWORK ? NSTEP + LAG : 2 * LAG) * 2560; i += 65536) {
    const int st = i / 2560, p = i % 2560;
    *reinterpret_cast<uint4*>(g_xn[st < LAG ? st + NSEG : st - LAG] + (p >> 7) * 4096 + (st < LAG ? 0 : 2048) + (p & 127) * 16) = make_uint4(0, 0, 0, 0);
  }
  if (gt < CN_NUM) g_cnt[gt][0] = 0;
}

namespace C {
constexpr int NKR = 37;
constexpr int OFF_WQ = 0, OFF_WK = 81920;
constexpr int OFF_YO = 163840, OFF_YV = OFF_YO + 6144;
constexpr int OFF_M = 176128;
__host__ __device__ constexpr int og_off(int c) { return c ? OFF_M + 14336 + c * 2048 : 229376; }
constexpr int OFF_KT = 196608;
constexpr int OFF_XT = OFF_KT + 10240;
constexpr int OFF_VT = OFF_XT + 7168;
constexpr int OFF_XM = OFF_VT + 11392;
constexpr int OFF_PT = OFF_XM + 2560;
constexpr int KS = 1280, VS = 1408;
__host__ __device__ constexpr int slot_off(int p) { return p == 2 ? OFF_M : OFF_KT + (p % 3) * 16384; }
constexpr int OFF_ONE = 231424;
constexpr int OFF_BAR = 231552;
constexpr int OFF_SAFE = OFF_BAR + 160;
constexpr int OFF_TS = OFF_BAR + 256;
constexpr int SMEM = 232448;
constexpr uint32_t SB0 = 1024;
constexpr int BAR_F = OFF_BAR, BAR_XM = BAR_F + 40, BAR_XT = BAR_F + 48, BAR_OG = BAR_F + 56, BAR_E = OFF_BAR + 64, BAR_MOK = BAR_E + 40,
              BAR_M = OFF_BAR + 112, BAR_XF = OFF_BAR + 120, BAR_MF = OFF_BAR + 128, BAR_W = OFF_BAR + 136, FLG_REDO = OFF_BAR + 144;
constexpr int NB_PRO = 1, NB_RD = 2, NB_MR = 3, NB_QK = 4, NB_SM = 5, NB_VA = 6, NB_VQ = 7, NB_A = 8, NB_Q = 9, NB_C = 10, NB_WQ = 11, NB_QI = 12, NB_SI = 13, NB_WV = 14;
#define B1 600
#define AD0 16
#define AD1 128
#define AD2 16
#define AD3 128
#define BMX 1200
#define B2 800
#define FLP 1
#define OSG 2
#define OST 7
#define P1U 4
#define QIE 4
#define SIE 2
#define WOE 1
#define OGF 0
#define VSP 8
#define RFK 5
#define PFD 3
#define WOL 0
constexpr uint32_t SCQ = 0x3A003A00;
constexpr float SCE = 0.07216878364870322f * 1.4426950408889634f * 2048;
}

#define CBAR_SYNC(id, n) bar_sync(id, n)
#define CBAR_ARRIVE(id, n) bar_arrive(id, n)

__device__ __forceinline__ uint64_t wdesc(int off) { return mkdesc(C::SB0 + off, 8192, 1024); }
__device__ __forceinline__ uint64_t mdesc(int k) { return mkdesc_ns(C::SB0 + C::OFF_M + k * 512, 256, 128); }
__device__ __forceinline__ uint64_t tdesc(int k) { return mkdesc(C::SB0 + C::slot_off(k >> 3) + ((k >> 2) & 1) * 1024 + (k & 3) * 32, 16, 2048); }

__device__ __forceinline__ int dh_row(int n) { return (n & ~63) + (n & 32) + ((n >> 1) & 3) * 8 + ((n >> 3) & 3) * 2 + (n & 1); }
template <bool PERM>
__device__ __forceinline__ void load_weights_rs(uint32_t (&wf)[C::NKR][4], uint32_t sb, int stage, int yoff, int tid0) {
  using namespace C;
  const int i = (tid0 >> 3) & 3, n0 = (tid0 & 7) + (i >> 1) * 8;
  const int chunk = 2 * ((tid0 >> 5) & 3) + (i & 1);
  const int r0 = PERM ? dh_row(n0) : n0, r1 = PERM ? dh_row(n0 + 16) : n0 + 16;
  const uint32_t a0 = sb + stage + r0 * 128 + ((chunk ^ (r0 & 7)) << 4), a1 = sb + stage + r1 * 128 + ((chunk ^ (r1 & 7)) << 4);
#pragma unroll
  for (int k = 0; k < NKR; k++) ldsm4t(wf[k], ((k & 1) ? a1 : a0) + (k >> 1) * 4096);
#pragma unroll
  for (int k = 0; k < 40 - NKR; k++) {
    const int n = (NKR + k) * 16 + ((tid0 & 127) >> 3), r = PERM ? dh_row(n) : n, c = tid0 & 7;
    sts128(sb + yoff + (n - NKR * 16) * 128 + ((c ^ (n & 7)) << 4), lds128(sb + stage + r * 128 + ((c ^ (r & 7)) << 4)));
  }
  fence_async();
  CBAR_SYNC(NB_PRO, 384);
}
template <int STRIDE>
__device__ __forceinline__ void store_mem(const float (&d)[8], uint32_t base, int tid) {
  const int m = (tid >> 3) & 3;
  stsm4(base + (((tid >> 5) & 3) * 2 + (m & 1)) * STRIDE + (m >> 1) * 640 + (tid & 7) * 16, pack_bf16(d[0], d[1]), pack_bf16(d[2], d[3]),
        pack_bf16(d[4], d[5]), pack_bf16(d[6], d[7]));
}

__device__ __forceinline__ void load_pair(uint32_t sb, int i, int p, uint32_t slot, uint32_t ph, int& spin) {
  using namespace C;
  mwait(sb + BAR_E + 8 * p, ph, spin);
  if (elect_one()) bulk_g2s_mc(sb + slot, g_xn[i] + p * 16384, 16384, sb + BAR_F + 8 * p);
}
__device__ __forceinline__ void release_round(uint32_t sb, int p, int lane) {
  if (lane < (p == 2 ? 3 : 1)) mbar_arrive_cluster(mapa(sb, p == 2 ? lane : p) + C::BAR_E + 8 * (3 + p));
}

template <int K0, int K1>
__device__ __forceinline__ void v_mem_pass(float (&d)[8], const uint32_t (&wf)[C::NKR][4]) {
  using namespace C;
  wg_fence();
#pragma unroll
  for (int k = K0; k < K1; k++) {
    if (k < NKR) wgmma_rs16(d, wf[k < NKR ? k : 0], mdesc(k), k != 32);
    else wgmma_ts16(d, wdesc(OFF_YV + (k - NKR) * 2048), mdesc(k), 1);
  }
  wg_commit();
}
__device__ __forceinline__ void chain_v(const uint32_t sb, const int tid0, const int cta, const int rank) {
  using namespace C;
  asm volatile("setmaxnreg.inc.sync.aligned.u32 208;");
  int spin = 0;
  uint32_t wf[NKR][4];
  const int wu = uni((tid0 >> 5) & 3);
  const uint32_t slot = rank == 2 ? OFF_M : OFF_KT + rank * 16384;
  if (wu == 0) load_pair(sb, 0, rank, slot, 1, spin);
  mwait(sb + BAR_W, 0, spin);
  for (int it = tid0 & 127; it < 1280; it += 128) {
    const uint32_t base = sb + OFF_WK + (it >> 1) * 128;
    const int sw = ((it >> 1) & 7) ^ ((it & 1) * 4);
    const uint4 u0 = lds128(base + (sw << 4)), u1 = lds128(base + ((sw ^ 1) << 4)), u2 = lds128(base + ((sw ^ 2) << 4)), u3 = lds128(base + ((sw ^ 3) << 4));
    sts128(base + (sw << 4), make_uint4(u0.x, u1.x, u2.x, u3.x)); sts128(base + ((sw ^ 1) << 4), make_uint4(u0.y, u1.y, u2.y, u3.y));
    sts128(base + ((sw ^ 2) << 4), make_uint4(u0.z, u1.z, u2.z, u3.z)); sts128(base + ((sw ^ 3) << 4), make_uint4(u0.w, u1.w, u2.w, u3.w));
  }
  bar_sync(NB_RD, 128);
  load_weights_rs<false>(wf, sb, OFF_WK, OFF_YV, tid0);
#pragma unroll 1
  for (int i = 0; i < NSTEP; i++) {
    {
      float d[32];
      if (i > 0) CBAR_SYNC(NB_WV, 256);
#pragma unroll
      for (int p = 0; p < 5; p++) {
        mwait(sb + BAR_F + 8 * p, i & 1, spin);
        TS(i, 25 + p);
        wg_fence();
#pragma unroll
        for (int k = 8 * p; k < 8 * p + 8; k++) {
          if (k < NKR) wgmma_rs64(d, wf[k < NKR ? k : 0], tdesc(k), k);
          else wgmma_ts64(d, wdesc(OFF_YV + (k - NKR) * 2048), tdesc(k), 1);
          if (k == 8 * p + 1 && p >= 1 && p <= 3) {
            wg_commit(); wg_wait<1>();
            release_round(sb, p - 1, tid0 & 31);
          }
          if (k == 8 * p + RFK && (p == 1 || p == 2)) {
            wg_commit();
            if (rank == p - 1 && wu == 0) load_pair(sb, i, p + 2, slot_off(p + 2), i & 1, spin);
            wg_fence();
          }
        }
        wg_commit();
      }
      wg_wait<0>();
      TS(i, 23);
      CBAR_SYNC(NB_RD, 256);
      const int tid = fresh(tid0) & 127, m = (tid >> 3) & 3;
      if (tid < 8) mbar_expect_tx(sb + BAR_F + 8 * tid, tid < 5 ? 16384 : tid == 5 ? 2560 : tid == 6 ? 7168 : 4096);
      if (tid < 3 && tid != rank) mbar_arrive_cluster(mapa(sb, tid) + BAR_XF);
      const uint32_t a = sb + OFF_VT + 256 + ((tid >> 5) * 2 + (m & 1)) * VS + (m >> 1) * 640 + (tid & 7) * 16;
#pragma unroll
      for (int s = 0; s < 4; s++)
        stsm4(a + s * 128, pack_bf16(d[8 * s], d[8 * s + 1]), pack_bf16(d[8 * s + 2], d[8 * s + 3]),
              pack_bf16(d[8 * s + 4], d[8 * s + 5]), pack_bf16(d[8 * s + 6], d[8 * s + 7]));
      if (tid < 80) sts128(sb + (tid < 72 ? OFF_VT + (tid >> 3) * VS : OFF_PT + 1280) + (tid & 7) * 16, make_uint4(0, 0, 0, 0));
      fence_async();
    }
    mwait(sb + BAR_XF, i & 1, spin);
    CBAR_ARRIVE(NB_QK, 384);
    const uint32_t* xc = &g_cnt[CN_X + i + 1 - LAG][0];
    bool seen = NOWORK || i + 1 < LAG;
    if (wu == 0 && !seen) { seen = ld_acquire(xc) >= 32; fence_async_all(); }
    CBAR_SYNC(NB_QI, 256);
    float d[8];
    v_mem_pass<32, 40>(d, wf);
    CBAR_SYNC(NB_SM, 256);
    wg_wait<0>();
    if (__builtin_expect(lds32(sb + FLG_REDO), 0)) { v_mem_pass<32, 40>(d, wf); wg_wait<0>(); }
    if ((tid0 & 31) < 3 && (tid0 & 31) != rank) mbar_arrive_cluster(mapa(sb, tid0 & 31) + BAR_MF);
    v_mem_pass<0, 32>(d, wf);
    wg_wait<0>();
    TS(i, 24);
    const int tid = fresh(tid0);
    if ((tid & 31) == 0) mbar_arrive_cluster(mapa(sb, 2) + BAR_E + 16);
    store_mem<VS>(d, sb + OFF_VT + 128, tid);
    fence_async();
    CBAR_ARRIVE(NB_VA, 256);
    CBAR_ARRIVE(NB_VQ, 256);
    if (wu == 0 && i + 1 < NSTEP) {
      if (__builtin_expect(!seen, 0)) { while (ld_acquire(xc) < 32 && spin < SPIN_TOT) spin += 16; fence_async_all(); }
      load_pair(sb, i + 1, rank, slot, i & 1, spin);
      TS(i + 1, 37);
    }
    TS_FLUSH(i - 1);
    __syncwarp();
  }
  CBAR_ARRIVE(NB_WV, 256);
  if (spin >= SPIN_TOT) g_err = 3;
}

__device__ __forceinline__ float quad_max(float x) {
  const float a = __shfl_xor_sync(0xffffffffu, x, 1), b = __shfl_xor_sync(0xffffffffu, x, 2), c = __shfl_xor_sync(0xffffffffu, x, 3);
  return fmaxf(fmaxf(x, a), fmaxf(b, c));
}
__device__ __forceinline__ float quad_sum(float x) {
  const float a = __shfl_xor_sync(0xffffffffu, x, 1), b = __shfl_xor_sync(0xffffffffu, x, 2), c = __shfl_xor_sync(0xffffffffu, x, 3);
  return (x + a) + (b + c);
}
__device__ __forceinline__ float max10(const float (&y)[10]) {
  return fmaxf(fmaxf(fmaxf(fmaxf(y[0], y[1]), fmaxf(y[2], y[3])), fmaxf(fmaxf(y[4], y[5]), fmaxf(y[6], y[7]))), fmaxf(y[8], y[9]));
}
__device__ __forceinline__ float sum10(const float (&y)[10]) {
  return (((y[0] + y[1]) + (y[2] + y[3])) + ((y[4] + y[5]) + (y[6] + y[7]))) + (y[8] + y[9]);
}
__device__ __forceinline__ float rcp(float x) { float y; asm("rcp.approx.ftz.f32 %0,%1;" : "=f"(y) : "f"(x)); return y; }

__device__ __forceinline__ void signal_o(int i, int cta) { csignal(CN_O + i * 5 + min(cta / 19, 4)); }

__device__ __forceinline__ void chain_q(const CUtensorMap& tmWq, const CUtensorMap& tmWk, const uint32_t sb, const int tid0, const int cta, const int rank) {
  using namespace C;
  asm volatile("setmaxnreg.dec.sync.aligned.u32 96;");
  int spin = 0;
  CBAR_SYNC(NB_PRO, 384);
  PTS(5);
  if (tid0 == 128) {
    const int col = (cta / 3) * DH + rank * 64;
    mbar_expect_tx(sb + BAR_W, 163840);
    for (int i = 0; i < 5; i++) {
      tma2d(sb + OFF_WQ + i * 16384, &tmWq, col, i * 128, sb + BAR_W);
      tma2d(sb + OFF_WK + i * 16384, &tmWk, col, i * 128, sb + BAR_W);
    }
  }
  __syncwarp();
  mwait(sb + BAR_W, 1, spin);
  PTS(6);
  const int wu = uni((tid0 >> 5) & 3);
  uint4 ov[4] = {};
  uint8_t* op = &g_o[ORING - 1][cta][(tid0 & 124) * 32];
  const uint32_t o0 = ((tid0 ^ (tid0 >> 2)) & 3) * 16 + (tid0 & 16) * 4;
#pragma unroll 1
  for (int i = 0; i < NSTEP; i++) {
    const int ph = i & 1;
    uint32_t qf[4][4];
    {
      float d[64];
#define QK_STEP(K, SC) wgmma_st128(d, desc_at(mkdesc(SB0 + ((K) >> 2) * 1024 + ((K) & 3) * 32, 16, 2048), so), \
                                   desc_at(mkdesc(SB0 + OFF_WQ + (K) * 2048, OFF_WK - OFF_WQ, 1024), p * 16384), SC)
      int p = 0;
      uint32_t so = OFF_KT;
      mwait(sb + BAR_F, ph, spin);
      TS(i, 0);
      wg_fence();
#pragma unroll
      for (int k = 0; k < 8; k++) {
        QK_STEP(k, k);
        if (k == OST) {
          wg_commit();
          mwait(sb + BAR_F, ph, spin);
#pragma unroll
          for (int h = 0; h < 4; h++) stg128(op + (h & 1) * 4096 + (o0 ^ ((h >> 1) * 64)), ov[h]);
          if (i > 0) CBAR_ARRIVE(NB_MR, 160);
          if (k < 7) wg_fence();
        }
      }
      if (OST < 7) wg_commit();
#pragma unroll 1
      for (p = 1; p < 5; p++) {
        static_assert(OFF_KT - OFF_M == 5 << 12, "");
        so = OFF_M + (((0x95095u >> (4 * p)) & 15) << 12);
        mwait(sb + BAR_F + 8 * p, ph, spin);
        wg_fence();
#pragma unroll
        for (int k = 0; k < 8; k++) {
          QK_STEP(k, 1);
          if (k == 1) {
            wg_commit(); wg_wait<1>();
            release_round(sb, p - 1, p < 4 ? tid0 & 31 : 32);
          }
        }
        wg_commit();
      }
#undef QK_STEP
      wg_wait<0>();
      TS(i, 1);
      CBAR_SYNC(NB_RD, 256);
      TSB(i, 2);
      const int tid = fresh(tid0), w = (tid >> 5) & 3, m = (tid >> 3) & 3;
      const uint32_t a = sb + OFF_KT + (m >> 1) * KS + (1 + w + 5 * (m & 1)) * 128 + (tid & 7) * 16;
#pragma unroll
      for (int s = 0; s < 4; s++)
        stsm4t(a + s * 2 * KS, pack_bf16(d[32 + 8 * s], d[33 + 8 * s]), pack_bf16(d[34 + 8 * s], d[35 + 8 * s]),
               pack_bf16(d[36 + 8 * s], d[37 + 8 * s]), pack_bf16(d[38 + 8 * s], d[39 + 8 * s]));
      fence_async();
      CBAR_ARRIVE(NB_QK, 384);
#pragma unroll
      for (int kk = 0; kk < 4; kk++)
#pragma unroll
        for (int j = 0; j < 4; j++) asm volatile("{.reg .b32 t; cvt.rn.bf16x2.f32 t,%1,%2; mul.rn.bf16x2 %0,t,%3;}" : "=r"(qf[kk][j]) : "f"(d[8 * kk + 2 * j + 1]), "f"(d[8 * kk + 2 * j]), "r"(SCQ));
    }
    CBAR_SYNC(NB_SI, 256);
    uint32_t pf[5][4];
    {
      float y0[10], y1[10];
      const int tidf = fresh(tid0), lane = tidf & 31;
      {
        float x[40];
        wg_fence();
#pragma unroll
        for (int kk = 0; kk < 4; kk++) wgmma_rt80(x, qf[kk], mkdesc_ns(SB0 + OFF_KT + kk * 2 * KS, KS, 128), kk);
        wg_commit();
        wg_wait<0>();
#pragma unroll
        for (int j = 0; j < 5; j++) { y0[2 * j] = x[4 * j]; y0[2 * j + 1] = x[4 * j + 1]; y1[2 * j] = x[22 + 4 * j]; y1[2 * j + 1] = x[23 + 4 * j]; }
      }
      TS(i, 17);
      const uint32_t xo = OFF_XT + (wu * (wu + 3) / 2) * 256 + lane * 16, x2 = xo + (wu >> 1) * 512 + 512 - lane * 8;
      {
        const uint4 h0 = make_uint4(pack_h2(y0[0], y0[1]), pack_h2(y1[0], y1[1]), pack_h2(y0[2], y0[3]), pack_h2(y1[2], y1[3]));
        const uint4 h1 = make_uint4(pack_h2(y0[4], y0[5]), pack_h2(y1[4], y1[5]), pack_h2(y0[6], y0[7]), pack_h2(y1[6], y1[7]));
        const uint32_t h2 = wu == 1 ? h1.x : pack_h2(y0[8], y0[9]), h3 = wu == 1 ? h1.y : pack_h2(y1[8], y1[9]);
        const uint32_t rb1 = mapa(sb, (rank + 1) % 3), rb2 = mapa(sb, (rank + 2) % 3);
        st_async4u(rb1 + xo + 3584, h0, rb1 + BAR_XT);
        st_async4u(rb2 + xo, h0, rb2 + BAR_XT);
        if (wu >= 2) { st_async4u(rb1 + xo + 4096, h1, rb1 + BAR_XT); st_async4u(rb2 + xo + 512, h1, rb2 + BAR_XT); }
        if (wu & 1) { st_async2u(rb1 + x2 + 3584, h2, h3, rb1 + BAR_XT); st_async2u(rb2 + x2, h2, h3, rb2 + BAR_XT); }
      }
      TS(i, 18);
      const int lim = 8 * wu + (lane >> 2) + 8 - 2 * (lane & 3);
#pragma unroll
      for (int j = 2; j < 10; j++)
        if (8 * (j >> 1) + (j & 1) > lim) { y0[j] = -INFINITY; y1[j] = -INFINITY; }
      mwait(sb + BAR_XT, ph, spin);
      TS(i, 19);
      {
        const uint4 u0 = lds128(sb + xo), v0 = lds128(sb + xo + 3584);
        uint2 u2 = make_uint2(0, 0), v2 = u2;
        if (wu & 1) { u2 = lds64(sb + x2); v2 = lds64(sb + x2 + 3584); }
        uint4 u1 = make_uint4(u2.x, u2.y, 0, 0), v1 = make_uint4(v2.x, v2.y, 0, 0);
        if (wu >= 2) { u1 = lds128(sb + xo + 512); v1 = lds128(sb + xo + 4096); }
        __syncwarp();
        if (lane == 0) mbar_arrive_cluster(mapa(sb, 0) + BAR_E);
        add_h2(y0[0], y0[1], u0.x, v0.x); add_h2(y1[0], y1[1], u0.y, v0.y); add_h2(y0[2], y0[3], u0.z, v0.z); add_h2(y1[2], y1[3], u0.w, v0.w);
        add_h2(y0[4], y0[5], u1.x, v1.x); add_h2(y1[4], y1[5], u1.y, v1.y); add_h2(y0[6], y0[7], u1.z, v1.z); add_h2(y1[6], y1[7], u1.w, v1.w);
        add_h2(y0[8], y0[9], u2.x, v2.x); add_h2(y1[8], y1[9], u2.y, v2.y);
      }
      const float m0 = quad_max(max10(y0)) * -SCE, m1 = quad_max(max10(y1)) * -SCE;
#pragma unroll
      for (int j = 0; j < 5; j++) {
        pf[j >> 1][2 * (j & 1)] = pack_bf16(ex2(fmaf(y0[2 * j], SCE, m0)), ex2(fmaf(y0[2 * j + 1], SCE, m0)));
        pf[j >> 1][2 * (j & 1) + 1] = tidf >> (10 + j);
        pf[(j + 5) >> 1][2 * ((j + 5) & 1)] = tidf >> (20 + j);
        pf[(j + 5) >> 1][2 * ((j + 5) & 1) + 1] = pack_bf16(ex2(fmaf(y1[2 * j], SCE, m1)), ex2(fmaf(y1[2 * j + 1], SCE, m1)));
      }
    }
#pragma unroll
    for (int q = 0; q < 20; q++) pf[q >> 2][q & 3] = pin(pf[q >> 2][q & 3]);
    CBAR_SYNC(NB_VQ, 256);
    TSB(i, 20);
    {
      float o[32], sm[4];
      wg_fence();
#pragma unroll
      for (int q = 0; q < 5; q++) wgmma_rs8(sm, pf[q], mkdesc_ns(SB0 + OFF_ONE, 0, 0), q);
#pragma unroll
      for (int q = 0; q < 5; q++) wgmma_rs64(o, pf[q], mkdesc_ns(SB0 + OFF_VT + 128 + q * 256, 128, VS), q);
      wg_commit();
      const int tid = fresh(tid0);
      op = &g_o[i % ORING][cta][(tid & 124) * 32];
      wg_wait<0>();
      TS(i, 21);
      if ((tid & 31) == 0) mbar_arrive_cluster(mapa(sb, 1) + BAR_E + 8);
      const float s0 = rcp(sm[0]), s1 = rcp(sm[2]);
#pragma unroll
      for (int h = 0; h < 2; h++) {
        const float* x = o + 16 * h;
        ov[2 * h] = make_uint4(pin(pack_bf16(x[0] * s0, x[1] * s0)), pin(pack_bf16(x[4] * s0, x[5] * s0)), pin(pack_bf16(x[8] * s0, x[9] * s0)), pin(pack_bf16(x[12] * s0, x[13] * s0)));
        ov[2 * h + 1] = make_uint4(pin(pack_bf16(x[2] * s1, x[3] * s1)), pin(pack_bf16(x[6] * s1, x[7] * s1)), pin(pack_bf16(x[10] * s1, x[11] * s1)), pin(pack_bf16(x[14] * s1, x[15] * s1)));
      }
      TS(i, 22);
      if (i + 1 < NSTEP) CBAR_SYNC(NB_WQ, 256); else CBAR_ARRIVE(NB_WQ, 256);
    }
  }
#pragma unroll
  for (int h = 0; h < 4; h++) stg128(op + (h & 1) * 4096 + (o0 ^ ((h >> 1) * 64)), ov[h]);
  CBAR_SYNC(NB_Q, 128);
  if (tid0 == 224) signal_o(NSTEP - 1, cta);
  if (spin >= SPIN_TOT) g_err = 2;
}

template <int NL> __device__ __forceinline__ void poll(uint4 (&x)[NL], const uint8_t* mb, uint32_t tag, int& spin);
template <> __device__ __forceinline__ void poll<4>(uint4 (&x)[4], const uint8_t* mb, uint32_t tag, int& spin) {
  asm volatile("{.reg .pred p<6>, q; .reg .b128 v; .reg .b32 t;\n"
               " ld.relaxed.gpu.global.b128 v,[%17+0]; mov.b128 {%0,%1,%2,%3},v;\n"
               " ld.relaxed.gpu.global.b128 v,[%17+512]; mov.b128 {%4,%5,%6,%7},v;\n"
               " ld.relaxed.gpu.global.b128 v,[%17+1024]; mov.b128 {%8,%9,%10,%11},v;\n"
               " ld.relaxed.gpu.global.b128 v,[%17+1536]; mov.b128 {%12,%13,%14,%15},v;\n"
               "POLL_LOOP:\n add.s32 %16,%16,16;\n"
               " lop3.b32 t,%0,%18,1,0x28; setp.ne.b32 p0,t,0;\n"
               " lop3.b32 t,%4,%18,1,0x28; setp.ne.b32 p1,t,0;\n"
               " lop3.b32 t,%8,%18,1,0x28; setp.ne.b32 p2,t,0;\n"
               " lop3.b32 t,%12,%18,1,0x28; setp.ne.b32 p3,t,0;\n"
               " or.pred q,p0,p1; or.pred q,q,p2; or.pred q,q,p3; setp.lt.and.s32 q,%16,%19,q; vote.sync.any.pred q,q,0xffffffff;\n"
               " mov.b128 v,{%0,%1,%2,%3}; @p0 ld.relaxed.gpu.global.b128 v,[%17+0]; mov.b128 {%0,%1,%2,%3},v;\n"
               " mov.b128 v,{%4,%5,%6,%7}; @p1 ld.relaxed.gpu.global.b128 v,[%17+512]; mov.b128 {%4,%5,%6,%7},v;\n"
               " mov.b128 v,{%8,%9,%10,%11}; @p2 ld.relaxed.gpu.global.b128 v,[%17+1024]; mov.b128 {%8,%9,%10,%11},v;\n"
               " mov.b128 v,{%12,%13,%14,%15}; @p3 ld.relaxed.gpu.global.b128 v,[%17+1536]; mov.b128 {%12,%13,%14,%15},v;\n"
               " @q bra.uni POLL_LOOP;\n}"
               : "=&r"(x[0].x), "=&r"(x[0].y), "=&r"(x[0].z), "=&r"(x[0].w), "=&r"(x[1].x), "=&r"(x[1].y), "=&r"(x[1].z), "=&r"(x[1].w), "=&r"(x[2].x), "=&r"(x[2].y), "=&r"(x[2].z), "=&r"(x[2].w), "=&r"(x[3].x), "=&r"(x[3].y), "=&r"(x[3].z), "=&r"(x[3].w), "+&r"(spin)
               : "l"(mb), "r"(tag), "n"(SPIN_TOT) : "memory");
}
template <> __device__ __forceinline__ void poll<6>(uint4 (&x)[6], const uint8_t* mb, uint32_t tag, int& spin) {
  asm volatile("{.reg .pred p<6>, q; .reg .b128 v; .reg .b32 t;\n"
               " ld.relaxed.gpu.global.b128 v,[%25+0]; mov.b128 {%0,%1,%2,%3},v;\n"
               " ld.relaxed.gpu.global.b128 v,[%25+512]; mov.b128 {%4,%5,%6,%7},v;\n"
               " ld.relaxed.gpu.global.b128 v,[%25+1024]; mov.b128 {%8,%9,%10,%11},v;\n"
               " ld.relaxed.gpu.global.b128 v,[%25+1536]; mov.b128 {%12,%13,%14,%15},v;\n"
               " ld.relaxed.gpu.global.b128 v,[%25+2048]; mov.b128 {%16,%17,%18,%19},v;\n"
               " ld.relaxed.gpu.global.b128 v,[%25+2560]; mov.b128 {%20,%21,%22,%23},v;\n"
               "POLL_LOOP:\n add.s32 %24,%24,16;\n"
               " lop3.b32 t,%0,%2,%26,0x7e; and.b32 t,t,1; setp.ne.b32 p0,t,0;\n"
               " lop3.b32 t,%4,%6,%26,0x7e; and.b32 t,t,1; setp.ne.b32 p1,t,0;\n"
               " lop3.b32 t,%8,%10,%26,0x7e; and.b32 t,t,1; setp.ne.b32 p2,t,0;\n"
               " lop3.b32 t,%12,%14,%26,0x7e; and.b32 t,t,1; setp.ne.b32 p3,t,0;\n"
               " lop3.b32 t,%16,%18,%26,0x7e; and.b32 t,t,1; setp.ne.b32 p4,t,0;\n"
               " lop3.b32 t,%20,%22,%26,0x7e; and.b32 t,t,1; setp.ne.b32 p5,t,0;\n"
               " or.pred q,p0,p1; or.pred q,q,p2; or.pred q,q,p3; or.pred q,q,p4; or.pred q,q,p5; setp.lt.and.s32 q,%24,%27,q; vote.sync.any.pred q,q,0xffffffff;\n"
               " mov.b128 v,{%0,%1,%2,%3}; @p0 ld.relaxed.gpu.global.b128 v,[%25+0]; mov.b128 {%0,%1,%2,%3},v;\n"
               " mov.b128 v,{%4,%5,%6,%7}; @p1 ld.relaxed.gpu.global.b128 v,[%25+512]; mov.b128 {%4,%5,%6,%7},v;\n"
               " mov.b128 v,{%8,%9,%10,%11}; @p2 ld.relaxed.gpu.global.b128 v,[%25+1024]; mov.b128 {%8,%9,%10,%11},v;\n"
               " mov.b128 v,{%12,%13,%14,%15}; @p3 ld.relaxed.gpu.global.b128 v,[%25+1536]; mov.b128 {%12,%13,%14,%15},v;\n"
               " mov.b128 v,{%16,%17,%18,%19}; @p4 ld.relaxed.gpu.global.b128 v,[%25+2048]; mov.b128 {%16,%17,%18,%19},v;\n"
               " mov.b128 v,{%20,%21,%22,%23}; @p5 ld.relaxed.gpu.global.b128 v,[%25+2560]; mov.b128 {%20,%21,%22,%23},v;\n"
               " @q bra.uni POLL_LOOP;\n}"
               : "=&r"(x[0].x), "=&r"(x[0].y), "=&r"(x[0].z), "=&r"(x[0].w), "=&r"(x[1].x), "=&r"(x[1].y), "=&r"(x[1].z), "=&r"(x[1].w), "=&r"(x[2].x), "=&r"(x[2].y), "=&r"(x[2].z), "=&r"(x[2].w), "=&r"(x[3].x), "=&r"(x[3].y), "=&r"(x[3].z), "=&r"(x[3].w), "=&r"(x[4].x), "=&r"(x[4].y), "=&r"(x[4].z), "=&r"(x[4].w), "=&r"(x[5].x), "=&r"(x[5].y), "=&r"(x[5].z), "=&r"(x[5].w), "+&r"(spin)
               : "l"(mb), "r"(tag), "n"(SPIN_TOT) : "memory");
}
template <int NL>
__device__ __forceinline__ void poll_add(const uint8_t* mb, uint32_t tag, float (&f)[8], uint8_t* flag, bool lead, int& spin) {
  uint4 x[NL];
  poll<NL>(x, mb, tag, spin);
  if (FLP == 0 && lead) st_relaxed(flag, 0);
#pragma unroll
  for (int i = 0; i < NL; i++) {
    const uint32_t u[4] = {x[i].x, x[i].y, x[i].z, x[i].w};
#pragma unroll
    for (int j = 0; j < 4; j++) {
      if (i == 0) { f[2 * j] = bf_lo(u[j]); f[2 * j + 1] = bf_hi(u[j]); }
      else { f[2 * j] += bf_lo(u[j]); f[2 * j + 1] += bf_hi(u[j]); }
    }
  }
}

template <int B, int SLOT>
__device__ __forceinline__ void wo_step(float (&acc)[8], const uint32_t (&wf)[C::NKR][4], int kk) {
  using namespace C;
  const int k = 4 * B + kk;
  const uint64_t db = mkdesc_ns(SB0 + og_off(SLOT) + kk * 512, 256, 128);
  if (k < NKR) wgmma_rt16(acc, wf[k < NKR ? k : 0], db, SLOT | kk);
  else wgmma_tt16(acc, wdesc(OFF_YO + (k - NKR) * 2048), db, 1);
}
template <int B, int SLOT>
__device__ __forceinline__ void wo_block(float (&acc)[8], const uint32_t (&wf)[C::NKR][4]) {
#pragma unroll
  for (int kk = 0; kk < 4; kk++) wo_step<B, SLOT>(acc, wf, kk);
}

__device__ __forceinline__ void chain_a(const uint32_t sb, const int tid0, const int cta, const int rank) {
  using namespace C;
  asm volatile("setmaxnreg.inc.sync.aligned.u32 200;");
  int spin = 0;
  uint32_t wf[NKR][4];
  mwait(sb + BAR_W, 0, spin);
  permute_cols(sb + OFF_WQ, tid0, 2560);
  CBAR_SYNC(NB_A, 128);
  load_weights_rs<true>(wf, sb, OFF_WQ, OFF_YO, tid0);
  const int wu = uni(tid0 >> 5);
  const bool t9 = cta >= 72 && cta < 88;
  const uint64_t exa = reinterpret_cast<uint64_t>(ex_window(g_ex));
  const uint32_t ehi = (uint32_t)(exa >> 32), elo = (uint32_t)exa;

  int b1 = B1, b2 = B2;
#pragma unroll 1
  for (int i = -1; i < NSTEP; i++) {
    const int ph = i & 1;
    if (i >= 0) {
      const int tid = fresh(tid0);
      const uint32_t mo = __shfl_xor_sync(0xffffffffu, elo + (ph << 20) + ((rank * 24 + (tid >> 4)) * 4 + (tid & 3)) * 2048 + (cta / 3) * 64 + (tid & 12) * 4, 0);
      const uint32_t m9 = __shfl_xor_sync(0xffffffffu, elo + (ph << 20) + MAIL9 + (((tid >> 4) * 2 + (tid & 1)) * 4 + (tid & 2)) * 3072 + cta * 32 + (tid & 12) * 2, 0);
      const uint32_t oo = __shfl_xor_sync(0xffffffffu, (tid >> 5) * 512 + (tid & 2) * 64 + (tid & 28) * 4 + (tid & 1) * 8, 0);
      if (i == 0) mwait(sb + BAR_W, 1, spin);
      mwait(sb + BAR_M, ph, spin);
      TS(i, 3);
      {
        float x[20];
        int redo = 0;
      retry:
        bool bad;
        {
          float dq[8] = {}, dk[8] = {};
#pragma unroll 1
          for (int k0 = 0; k0 < 40; k0 += P1U) {
            wg_fence();
#pragma unroll
            for (int k = 0; k < P1U; k++) {
              if (k == P1U - QIE / 2 && k0 == 40 - P1U && !redo) CBAR_ARRIVE(NB_QI, 256);
              const uint64_t db = desc_at(mdesc(k), k0 * 512);
              wgmma_ts16(dq, desc_at(wdesc(OFF_WQ + k * 2048), k0 * 2048), db, 1);
              wgmma_ts16(dk, desc_at(wdesc(OFF_WK + k * 2048), k0 * 2048), db, 1);
            }
            wg_commit();
          }
          const int m = (tid >> 3) & 3, dg = (tid >> 5) * 2 + (m & 1);
          const uint32_t ka = sb + OFF_KT + dg * KS + (m >> 1) * 640 + (tid & 7) * 16;
          if (!redo) CBAR_SYNC(NB_QK, 384);
          sts32(sb + FLG_REDO, redo);
          wg_wait<0>();
          TS(i, 4);
          stsm4(ka, pack_bf16(dk[0], dk[1]), pack_bf16(dk[2], dk[3]), pack_bf16(dk[4], dk[5]), pack_bf16(dk[6], dk[7]));
          stsm4(ka + dg * (VS - KS) + (OFF_VT + 128 - OFF_KT), scale_bf16x2(pack_bf16(dq[0], dq[1]), SCQ), scale_bf16x2(pack_bf16(dq[2], dq[3]), SCQ),
                scale_bf16x2(pack_bf16(dq[4], dq[5]), SCQ), scale_bf16x2(pack_bf16(dq[6], dq[7]), SCQ));
          const float chk = (dq[0] + dq[1]) + (dq[4] + dq[5]);
          fence_async();
          bad = bar_red_or(NB_C, 128, chk != chk && !redo);
        }
        TSB(i, 5);
        wg_fence();
#pragma unroll
        for (int kk = 0; kk < 4; kk++) wgmma_tt40(x, mkdesc_ns(SB0 + OFF_VT + 128 + kk * 2 * VS, VS, 640), mkdesc_ns(SB0 + OFF_KT + kk * 2 * KS, KS, 128), kk);
#pragma unroll
        for (int kk = 0; kk < 4; kk++) {
          if (SIE && kk == 4 - SIE && !bad) CBAR_ARRIVE(NB_SI, 256);
          wgmma_tt40(x, mkdesc_ns(SB0 + OFF_VT + kk * 2 * VS, VS, 384), mkdesc_ns(SB0 + OFF_KT + 640 + kk * 2 * KS, KS, 128), 1);
        }
        wg_commit();
        if (!SIE && !bad) CBAR_ARRIVE(NB_SI, 256);
        if (__builtin_expect(__any_sync(0xffffffffu, bad), 0)) {
          wg_wait<0>();
#pragma unroll 1
          for (int k = 0; k < 10; k++) {
            uint4 v = lds128(sb + OFF_M + tid * 16 + k * 2048);
            if (v.x == SENT || v.y == SENT || v.z == SENT || v.w == SENT) {
              do { v = ld_relaxed4(mkptr(elo + EX_M + i * 20480 + tid * 16 + k * 2048, ehi)); spin += 16; } while ((v.x == SENT || v.y == SENT || v.z == SENT || v.w == SENT) && spin < SPIN_TOT);
              sts128(sb + OFF_M + tid * 16 + k * 2048, v);
            }
          }
          fence_async();
          bar_sync(NB_C, 128);
          redo = fresh(1);
          goto retry;
        }
        TSV(i, 36, redo);
        const uint32_t rb1 = mapa(sb, (rank + 1) % 3), rb2 = mapa(sb, (rank + 2) % 3);
        wg_wait<0>();
        TS(i, 6);
        if (wu < 2) {
          float y[10];
#pragma unroll
          for (int j = 0; j < 5; j++) { y[2 * j] = x[4 * j]; y[2 * j + 1] = x[4 * j + 1]; }
          const uint4 h0 = make_uint4(pack_h2(y[0], y[1]), pack_h2(y[2], y[3]), pack_h2(y[4], y[5]), pack_h2(y[6], y[7]));
          const uint32_t h1 = pack_h2(y[8], y[9]);
          st_async4u(rb1 + OFF_XM + 1024 + tid * 16, h0, rb1 + BAR_XM);
          st_async4u(rb2 + OFF_XM + tid * 16, h0, rb2 + BAR_XM);
          st_async1u(rb1 + OFF_XM + 2304 + tid * 4, h1, rb1 + BAR_XM);
          st_async1u(rb2 + OFF_XM + 2048 + tid * 4, h1, rb2 + BAR_XM);
          CBAR_ARRIVE(NB_SM, 256);
          if ((tid & 31) == 0) mbar_arrive_cluster(mapa(sb, 0) + BAR_E);
          TS(i, 7);
          const uint32_t sw = (tid & 7) * 4 + (tid & 8) * 8 + (tid & 16) * 2;
          mwait(sb + BAR_XM, ph, spin);
          TS(i, 8);
          const uint4 u0 = lds128(sb + OFF_XM + tid * 16), v0 = lds128(sb + OFF_XM + 1024 + tid * 16);
          const uint32_t u1 = lds32(sb + OFF_XM + 2048 + tid * 4), v1 = lds32(sb + OFF_XM + 2304 + tid * 4);
          add_h2(y[0], y[1], u0.x, v0.x); add_h2(y[2], y[3], u0.y, v0.y); add_h2(y[4], y[5], u0.z, v0.z); add_h2(y[6], y[7], u0.w, v0.w);
          add_h2(y[8], y[9], u1, v1);
          const float mx = quad_max(max10(y)) * -SCE;
#pragma unroll
          for (int j = 0; j < 5; j++) {
            y[2 * j] = ex2(fmaf(y[2 * j], SCE, mx)); y[2 * j + 1] = ex2(fmaf(y[2 * j + 1], SCE, mx));
            sts32(sb + OFF_PT + wu * 640 + sw + j * 128, pack_bf16(y[2 * j], y[2 * j + 1]));
          }
          sts32(sb + OFF_XM + 2048 + wu * 128 + sw, __float_as_uint(sum10(y)));
          fence_async();
          TS(i, 9);
        } else {
          CBAR_ARRIVE(NB_SM, 256);
          if ((tid & 31) == 0) mbar_arrive_cluster(mapa(sb, 0) + BAR_E);
          mwait(sb + BAR_MF, ph, spin);
        }
      }
      CBAR_SYNC(NB_VA, 256);
      TSB(i, 10);
      {
        float o[2][4];
        wg_fence();
#pragma unroll
        for (int c = 0; c < 2; c++)
#pragma unroll
          for (int q = 0; q < 3; q++)
            wgmma_ss8(o[c], mkdesc_ns(SB0 + OFF_VT + 128 + c * 640 + q * 256, 128, VS), mkdesc_ns(SB0 + OFF_PT + c * 640 + q * 256, q == 2 && c == 0 ? 768 : 128, 128), q);
        wg_commit();
        const float4 e = lds128f(sb + OFF_XM + 2048 + (tid & 15) * 16);
        const uint32_t rb1 = mapa(sb, (rank + 1) % 3), rb2 = mapa(sb, (rank + 2) % 3);
        const float inv = rcp((e.x + e.y) + (e.z + e.w));
        const int sl = (tid & 3) * 2;
        const float i0 = __shfl_sync(0xffffffffu, inv, sl), i1 = __shfl_sync(0xffffffffu, inv, sl + 1);
        const float i2 = __shfl_sync(0xffffffffu, inv, sl + 8), i3 = __shfl_sync(0xffffffffu, inv, sl + 9);
        wg_wait<0>();
        TS(i, 11);
        const uint32_t p0 = pack_bf16(o[0][0] * i0, o[0][1] * i1), p1 = pack_bf16(o[1][0] * i2, o[1][1] * i3);
        const uint32_t p2 = pack_bf16(o[0][2] * i0, o[0][3] * i1), p3 = pack_bf16(o[1][2] * i2, o[1][3] * i3);
        if (OGF) { sts64(sb + oo + og_off(0), p0, p1); sts64(sb + oo + og_off(0) + 256, p2, p3); fence_async(); }
        st_async2u(rb1 + oo + og_off(2), p0, p1, rb1 + BAR_OG);
        st_async2u(rb2 + oo + og_off(1), p0, p1, rb2 + BAR_OG);
        st_async2u(rb1 + oo + og_off(2) + 256, p2, p3, rb1 + BAR_OG);
        st_async2u(rb2 + oo + og_off(1) + 256, p2, p3, rb2 + BAR_OG);
        if (!OGF) { sts64(sb + oo + og_off(0), p0, p1); sts64(sb + oo + og_off(0) + 256, p2, p3); fence_async(); }
      }
      CBAR_SYNC(NB_A, 128);
      TSB(i, 12);
      {
        float acc[3][8];
        wg_fence();
        wo_block<0, 0>(acc[2], wf);
        wg_commit();
        if (tid == 0) mbar_arrive_cluster(mapa(sb, 1) + BAR_E + 8);
        wo_block<1, 0>(acc[0], wf);
        wo_block<4, 0>(acc[1], wf);
        wg_commit();
        const uint32_t tag = (i >> 1) & 1;
#define TAGGED(LO, HI) ((pack_bf16(LO, HI) & ~1u) | tag)
#define SEND(OFF, U) st_relaxed128(mkptr(mo, ehi) + (OFF), TAGGED(acc[U][0], acc[U][2]), pack_bf16(acc[U][1], acc[U][3]), pack_bf16(acc[U][4], acc[U][6]), pack_bf16(acc[U][5], acc[U][7]))
        wg_wait<1>();
        const uint32_t n0 = pin(TAGGED(acc[2][0], acc[2][2])), n1 = pin(pack_bf16(acc[2][1], acc[2][3]));
        const uint32_t n2 = pin(TAGGED(acc[2][4], acc[2][6])), n3 = pin(pack_bf16(acc[2][5], acc[2][7]));
        wg_fence();
        wo_block<7, 0>(acc[2], wf);
        wg_commit();
        st_relaxed64(mkptr(m9, ehi), n0, n1);
        st_relaxed64(mkptr(m9, ehi) + 3072, n2, n3);
        mwait(sb + BAR_OG, ph, spin);
        asm volatile("fence.proxy.async::generic.acquire.sync_restrict::shared::cluster.cluster;" ::: "memory");
        TS(i, 13);
        wg_fence();
        wo_block<2, 1>(acc[0], wf); wo_block<3, 2>(acc[0], wf);
        wg_commit();
        wo_block<5, 1>(acc[1], wf); wo_block<6, 2>(acc[1], wf);
        wg_commit();
        wg_wait<1>(); SEND(0, 0);
        wo_block<8, 1>(acc[2], wf); wo_block<9, 2>(acc[2], wf);
        wg_commit();
        if (WOE == 0) { CBAR_ARRIVE(NB_WV, 256); CBAR_ARRIVE(NB_WQ, 256); }
        wg_wait<1>(); SEND(32 * 2048, 1);
        if (WOE == 1) CBAR_ARRIVE(NB_WV, 256);
        wg_wait<0>(); SEND(64 * 2048, 2);
        if (WOE == 2) CBAR_ARRIVE(NB_WV, 256);
        if (WOE >= 1) CBAR_ARRIVE(NB_WQ, 256);
#undef SEND
#undef TAGGED
      }
      TS(i, 14);
      if (i + 1 >= NSTEP) break;
    }
    uint32_t t1 = clk32();
    if (i >= 0) {
      const int lane = fresh(tid0) & 31, j = lane >> 3;
      const uint8_t* mb = mkptr(elo + (ph << 20) + (t9 ? MAIL9 + (cta - 72) * 12288 + wu * 3072 : (cta < 72 ? cta : cta - 24) * 8192 + wu * 2048) + lane * 16, ehi);
      const uint32_t tag = (i >> 1) & 1;
      const bool pub = (lane & (t9 ? 6 : 4)) == 0 && !(((t9 ? cta : wu) & 1) && i + 1 == LAG) && cta < 88;
      const uint32_t dst = pin(elo + EX_M + (i + 1) * 20480 + (t9 ? (cta + 72) * 128 + wu * 32 + (j & 1) * 16 + (lane & 1) * 8 + (j >> 1) * 4
                                                                   : cta * 256 + (wu & 1) * 128 + (wu >> 1) * 64 + j * 16 + (lane & 3) * 4));
      uint8_t* flag = mkptr(elo + EX_FLAG + (i + 1) * 3072 + cta * 32 + wu * 4, ehi);
      while (clk32() - t1 < b1) {}
      TS(i + 1, 30);
      float f[8];
      const int n0 = spin;
      if (!t9) poll_add<4>(mb, tag, f, flag, lane == 0, spin);
      else poll_add<6>(mb, tag, f, flag, lane == 0, spin);
      if (FLP == 1 && lane == 0) st_relaxed(flag, __float_as_uint(f[0] + f[7]) >> 1);
      t1 = clk32();
      b1 = __any_sync(0xffffffffu, spin - n0 > 16) ? min(b1 + AD1, BMX) : max(b1 - AD0, 0);
      TSV(i + 1, 38, b1);
      TS(i + 1, 31); TSV(i + 1, 32, (spin - n0) >> 4);
      const bool h = lane & 16, q = lane & 8;
#pragma unroll
      for (int j = 0; j < 4; j++) f[j] = (h ? f[4 + j] : f[j]) + __shfl_xor_sync(0xffffffffu, h ? f[j] : f[4 + j], 16);
#pragma unroll
      for (int j = 0; j < 2; j++) f[j] = (q ? f[2 + j] : f[j]) + __shfl_xor_sync(0xffffffffu, q ? f[j] : f[2 + j], 8);
      f[0] += __shfl_xor_sync(0xffffffffu, f[0], 4); f[1] += __shfl_xor_sync(0xffffffffu, f[1], 4);
      if (t9) { f[0] += __shfl_xor_sync(0xffffffffu, f[0], 2); f[1] += __shfl_xor_sync(0xffffffffu, f[1], 2); }
      if (pub) st_relaxed(mkptr(dst, ehi), pack_bf16(f[0], f[1]));
      if (FLP == 2 && lane == 0) st_relaxed(flag, 0);
      if (wu == 3) {
        CBAR_SYNC(NB_MR, 160);
        if (elect_one()) signal_o(i, cta);
      }
      TS(i + 1, 15);
    }
    if (wu == 0) {
      const int tid = fresh(tid0);
      const uint8_t* pp = mkptr(elo + EX_FLAG + (i + 1) * 3072 + (rank * 28 + (tid < 28 || rank == 2 ? tid : 0)) * 32, ehi);
      while (clk32() - t1 < b2) {}
      TS(i + 1, 16);
      int n = 1;
      uint4 x = ld_relaxed4(pp);
      if (tid0 == 0) mbar_expect_tx(sb + BAR_M, 20480);
      bool mok = mbar_test(sb + BAR_MOK, ph ^ 1);
      while (__any_sync(0xffffffffu, (int)(x.x | x.y | x.z | x.w) < 0 && spin < SPIN_TOT)) { x = ld_relaxed4(pp); mok = mbar_test(sb + BAR_MOK, ph ^ 1); n++; spin += 16; }
      if (!mok) mwait(sb + BAR_MOK, ph ^ 1, spin);
      b2 = n > 1 ? min(b2 + AD3, BMX) : max(b2 - AD2, 0);
      TSV(i + 1, 35, n); TSV(i + 1, 39, b2);
      TS(i + 1, 34);
      if (elect_one()) bulk_g2s_mc(sb + OFF_M + rank * 7168, mkptr(elo + EX_M + (i + 1) * 20480 + rank * 7168, ehi), rank == 2 ? 6144 : 7168, sb + BAR_M);
      TS(i + 1, 33);
      __syncwarp();
    }
  }
  if (spin >= SPIN_TOT) g_err = 1;
}

__global__ void __cluster_dims__(3, 1, 1) __launch_bounds__(384, 1)
k_chain(const __grid_constant__ CUtensorMap tmWq, const __grid_constant__ CUtensorMap tmWk,
        const __grid_constant__ CUtensorMap tmWv, const __grid_constant__ CUtensorMap tmWo) {
  using namespace C;
  extern __shared__ __align__(1024) uint8_t smem[];
  const uint32_t sb = smem_u32(smem);
  const int tid = threadIdx.x;
  const int wg = __shfl_sync(0xffffffffu, tid >> 7, 0);
  const int cta = uni(blockIdx.x), rank = uni(blockIdx.x % 3);

  asm volatile("griddepcontrol.launch_dependents;");
  if (tid == 0) {
    if ((sb & 0xFFFFFF) != SB0) g_err = 100;
    for (int p = 0; p < 5; p++) { mbar_init(sb + BAR_F + 8 * p, 1); mbar_init(sb + BAR_E + 8 * p, p == 2 ? 12 : p == 1 ? 15 : 24); }
    mbar_init(sb + BAR_M, 1); mbar_init(sb + BAR_MOK, 24); mbar_init(sb + BAR_XM, 1); mbar_init(sb + BAR_XF, 2);
    mbar_init(sb + BAR_XT, 1); mbar_init(sb + BAR_MF, 8); mbar_init(sb + BAR_OG, 1); mbar_init(sb + BAR_W, 1);
    for (int p = 0; p < 5; p++) mbar_expect_tx(sb + BAR_F + 8 * p, 16384);
    for (int p = 0; p < 16; p++) sts32(sb + OFF_SAFE + 4 * p, 0);
    for (int p = 0; p < 32; p++) sts32(sb + OFF_ONE + 4 * p, 0x3F803F80);
    asm volatile("fence.mbarrier_init.release.cluster;" ::: "memory");
    fence_async();
    mbar_expect_tx(sb + BAR_W, 163840);
    const int head = cta / 3, col = head * DH + rank * 64;
    tma2d(sb + OFF_WQ, &tmWo, 576, col, sb + BAR_W);
    for (int i = 0; i < 9; i++) tma2d(sb + OFF_WQ + (i + 1) * 8192, &tmWo, (3 * rank + i / 3) * 64, head * DH + ((rank + i) % 3) * 64, sb + BAR_W);
    for (int i = 0; i < 5; i++) tma2d(sb + OFF_WK + i * 16384, &tmWv, col, i * 128, sb + BAR_W);
  }
  __syncthreads();
  asm volatile("barrier.cluster.arrive.release.aligned;" ::: "memory");
  asm volatile("barrier.cluster.wait.acquire.aligned;" ::: "memory");

  if (wg == 0) chain_a(sb, keep(tid), cta, rank);
  else if (wg == 1) chain_q(tmWq, tmWk, sb, keep(tid), cta, rank);
  else chain_v(sb, keep(tid), cta, rank);
  asm volatile("barrier.cluster.arrive.release.aligned;" ::: "memory");
  asm volatile("barrier.cluster.wait.acquire.aligned;" ::: "memory");
}

namespace W {
constexpr int NP = 25, NBC = 11, NW = NP + NBC;
constexpr int PRS = 37, PW = 43 * 2048;
constexpr int OFF_W = 0;
constexpr int OFF_R = 2 * PW;
constexpr int QRS = 35, KRS = 37;
constexpr int OFF_WV = 0, OFF_YQ = 81920, OFF_YK = OFF_YQ + (40 - QRS) * 2048, OFF_WO = OFF_YK + (40 - KRS) * 2048;
constexpr int OFF_G = OFF_WO + 39 * 2048;
constexpr int OFF_X = OFF_G + 20480;
constexpr int COL = 976;
constexpr int OFF_T = OFF_X;
constexpr int OFF_H = OFF_X + 24576;
constexpr int OFF_BAR = OFF_H + 8 * COL;
constexpr int OFF_SAFE = OFF_BAR + 192;
constexpr int SMEM = 232448;
static_assert(OFF_SAFE + 64 <= SMEM && OFF_R + 40960 <= OFF_BAR, "");
constexpr uint32_t SB0 = 1024;
constexpr int BAR_F = OFF_BAR, BAR_E = OFF_BAR + 40, BAR_G = OFF_BAR + 80, BAR_H = OFF_BAR + 120, BAR_W = OFF_BAR + 160;
constexpr int NB_G0 = 1, NB_SG = 4, NB_B = 5, NB_AS = 6, NB_PK = 8, NB_PV = 9, NB_TD = 10;
}
#define PFW 1
#define OBP 1
#define GLA 0
#define WOP 0
#define WBAR_SYNC(id, n) bar_sync(id, n)
#define WBAR_ARRIVE(id, n) bar_arrive(id, n)

__device__ __forceinline__ uint64_t rdesc(int off, int kk) { return mkdesc(W::SB0 + off + kk * 32, 16, 1024); }
__device__ __forceinline__ uint32_t frag_addr(uint32_t base, int tid) {
  const int i = (tid >> 3) & 3, r = tid & 7;
  return base + (r + (i >> 1) * 8) * 128 + (((2 * ((tid >> 5) & 3) + (i & 1)) ^ r) << 4);
}
template <int NK>
__device__ __forceinline__ void load_frags(uint32_t (&wf)[NK][4], uint32_t base, int tid) {
  const uint32_t a0 = frag_addr(base, tid);
#pragma unroll
  for (int k = 0; k < NK; k++) ldsm4t(wf[k], a0 + k * 2048);
}
__device__ __forceinline__ void red_tile(const float* d, int seg, int col0, int tid) {
  float* p = g_x + (size_t)(seg * 32 + 2 * (tid & 3)) * DM + col0 + ((tid >> 5) & 3) * 16 + ((tid >> 2) & 7) * 2;
#pragma unroll
  for (int j = 0; j < 8; j++)
    asm volatile("red.relaxed.gpu.global.add.v2.f32 [%0],{%1,%2};" ::"l"(p + ((j >> 1) * 8 + (j & 1)) * DM), "f"(d[4 * (j >> 1) + (j & 1)]), "f"(d[4 * (j >> 1) + 2 + (j & 1)]) : "memory");
}
#define FOR_SEGS(l, s)                                            \
  for (int j_ = 0; j_ < 2 * NSTEP; j_++) {                        \
    const int l = j_ & 1, s = (j_ >> 1) - l * LAG;                \
    if (s < 0 || s >= NSEG) continue;

template <int WG>
__device__ __forceinline__ void work_p(const CUtensorMap& tmWo, uint32_t sb, int pc, int tid0) {
  using namespace W;
  asm volatile("setmaxnreg.inc.sync.aligned.u32 208;");
  int spin = 0;
  const int ks = pc / 5, col0 = (pc % 5) * 128 + WG * 64;
  const uint32_t wb = sb + OFF_W + WG * PW;
  uint32_t wf[PRS][4];
#pragma unroll 1
  for (int hf = 0; hf < 2; hf++) {
    const int nk = hf ? 80 - PRS : PRS;
    if ((tid0 & 127) == 0) {
      mbar_expect_tx(sb + BAR_W + 8 * WG, nk * 2048);
      for (int i = 0; i < nk; i++) tma2d(wb + i * 2048, &tmWo, col0, ks * 19 * 64 + (i < PRS ? 2 * i + hf : PRS + i) * 16, sb + BAR_W + 8 * WG);
    }
    __syncwarp();
    mwait(sb + BAR_W + 8 * WG, hf, spin);
    permute_cols(wb, tid0 & 127, nk * 64);
    if (hf == 1 && ks < 4) for (int it = 39 * 64 + (tid0 & 127) - 64; it < 43 * 64; it += 128) {
      const uint32_t a = wb + (it >> 2) * 128 + (((2 * (it & 3)) ^ ((it >> 2) & 6)) << 4);
      if (it >= 39 * 64) { sts128(a, make_uint4(0, 0, 0, 0)); sts128(a + 16, make_uint4(0, 0, 0, 0)); }
    }
    fence_async();
    WBAR_SYNC(NB_G0 + WG, 128);
    if (hf == 0) {
      load_frags<PRS>(wf, wb, tid0);
      fence_async();
      WBAR_SYNC(NB_G0 + WG, 128);
    }
  }
#pragma unroll 1
  for (int k = 0; k < NSTEP; k++) {
    float d[32];
#pragma unroll
    for (int f = 0; f < 20; f++) {
      mwait(sb + BAR_F + 8 * (f % 5), (f / 5) & 1, spin);
      if (f == 0 && WG == 0 && pc == WW) WTS(k, 1);
      wg_fence();
#pragma unroll
      for (int kk = 0; kk < 4; kk++) {
        const int q = 4 * f + kk;
        if (q < 2 * PRS && !(q & 1)) wgmma_rs64(d, wf[q < 2 * PRS ? q >> 1 : 0], rdesc(OFF_R + (f % 5) * 8192, kk), q);
        else wgmma_ts64(d, mkdesc(SB0 + OFF_W + WG * PW + (q < 2 * PRS ? q >> 1 : q - PRS) * 2048, 8192, 1024), rdesc(OFF_R + (f % 5) * 8192, kk), 1);
        if (kk == 0 && f > 0) {
          wg_commit();
          wg_wait<1>();
          if ((tid0 & 31) == 0) mbar_arrive(sb + BAR_E + 8 * ((f - 1) % 5));
        }
      }
      wg_commit();
    }
    wg_wait<0>();
    if ((tid0 & 31) == 0) mbar_arrive(sb + BAR_E + 32);
    if (WG == 0 && pc == WW) WTS(k, 2);
    if (k < NSEG) red_tile(d, k, col0, tid0);
    if (k >= LAG) red_tile(d + 16, k - LAG, col0, tid0);
    if (WG == 0 && pc == WW) WTS(k, 13);
    WBAR_SYNC(NB_SG, 256);
    if (WG == 0) { if (tid0 == 0) csignal_t(CN_P + k, 3); __syncwarp(); }
  }
  if (spin >= SPIN_TOT) g_err = 11;
}
__device__ __forceinline__ void work_p_producer(uint32_t sb, int pc, int odd) {
  using namespace W;
  int spin = 0;
  const int ks = pc / 5;
#pragma unroll 1
  for (int k = 0; k < NSTEP; k++) {
    const uint32_t lo = k < NSEG ? 0 : 4096, len = k < LAG || k >= NSEG ? 4096 : 8192;
    const uint8_t* src = &g_o[k % ORING][ks * 19 + odd][lo];
    cwait(CN_O + k * 5 + ks, ks == 4 ? 20 : 19, spin);
    fence_async_all();
    if (pc == WW && !odd) WTS1(k, 0);
#pragma unroll
    for (int u = 0; u < 10; u++) {
      const int st = odd ? (2 * u + 1) % 5 : (2 * u) % 5, ph = odd ? ((2 * u + 1) / 5) & 1 : ((2 * u) / 5) & 1;
      mwait(sb + BAR_E + 8 * st, ph ^ 1, spin);
      if (elect_one()) {
        if (u == 9 && odd && ks < 4) mbar_arrive(sb + BAR_F + 8 * st);
        else {
          mbar_expect_tx(sb + BAR_F + 8 * st, len);
          bulk_g2s(sb + OFF_R + st * 8192 + lo, src + u * 16384, len, sb + BAR_F + 8 * st);
        }
      }
    }
  }
  if (spin >= SPIN_TOT) g_err = 12;
}
__device__ __forceinline__ float warp_sum(float x) {
  x = quad_sum(x);
  const float a = __shfl_xor_sync(0xffffffffu, x, 4), b = __shfl_xor_sync(0xffffffffu, x, 8), c = __shfl_xor_sync(0xffffffffu, x, 12);
  x = (x + a) + (b + c);
  return x + __shfl_xor_sync(0xffffffffu, x, 16);
}
__device__ __forceinline__ void work_ln(int kind, int r, int lane, bf16* out) {
  int spin = 0;
  const int l = kind & 1;
  const int rp = kind < 2 ? (r & 1) * 16 + (r >> 1) : r;
  const uint32_t sw = ((((lane >> 1) & 7) ^ (rp & 7)) << 4) + (lane & 1) * 8;
  uint8_t* dst = kind < 2 ? g_xnb[l * LAG] + (lane >> 4) * 8192 + l * 4096 + rp * 128 + sw
               : kind == 2 ? g_xn[LAG] + (r >> 3) * 4096 + 2048 + (lane >> 4) * 1024 + (r & 7) * 128 + sw
                           : reinterpret_cast<uint8_t*>(out) + r * 1280 + lane * 8;
  const int dm = kind < 3 ? 16384 : 256, ds = kind < 3 ? 81920 : 40960;
#pragma unroll 1
  for (int s = 0; s < NSEG; s++) {
    const float* xr = g_x + (size_t)(s * 32 + r) * DM;
    if (OBP && kind < 2) {
      uint8_t* ob = g_ob[l] + (size_t)s * 40960 + r * 1280 + lane * 16;
      stg128(ob, make_uint4(0, 0, 0, 0)); stg128(ob + 512, make_uint4(0, 0, 0, 0));
      if (lane < 16) stg128(ob + 1024, make_uint4(0, 0, 0, 0));
    }
    if (lane == 0) cwait(kind < 2 ? CN_P + s + l * LAG : CN_W + l * 64 + s, kind < 2 ? W::NP : 10, spin);
    __syncwarp();
    if (r == 0 && lane == 0 && (l == 0 || s + LAG >= NSEG)) WTS1(s + l * LAG, kind < 2 ? 3 : 11);
    float4 v[5];
#pragma unroll
    for (int m = 0; m < 5; m++) v[m] = ld_relaxed4f(xr + m * 128 + lane * 4);
    if (kind < 3) {
      float t = 0.f;
#pragma unroll
      for (int m = 0; m < 5; m++) t += (v[m].x + v[m].y) + (v[m].z + v[m].w);
      const float mean = warp_sum(t) * (1.f / DM);
      float q0 = 0.f, q1 = 0.f;
#pragma unroll
      for (int m = 0; m < 5; m++) {
        v[m].x -= mean; v[m].y -= mean; v[m].z -= mean; v[m].w -= mean;
        q0 += v[m].x * v[m].x + v[m].y * v[m].y; q1 += v[m].z * v[m].z + v[m].w * v[m].w;
      }
      const float rs = rsqrtf(warp_sum(q0 + q1) * (1.f / DM) + 1e-5f);
#pragma unroll
      for (int m = 0; m < 5; m++) { v[m].x *= rs; v[m].y *= rs; v[m].z *= rs; v[m].w *= rs; }
    }
#pragma unroll
    for (int m = 0; m < 5; m++) *reinterpret_cast<uint2*>(dst + (size_t)s * ds + m * dm) = make_uint2(pack_bf16(v[m].x, v[m].y), pack_bf16(v[m].z, v[m].w));
    __syncwarp();
    if (r == 0 && lane == 0 && (l == 0 || s + LAG >= NSEG)) WTS1(s + l * LAG, kind < 2 ? 4 : 12);
    if (lane == 0 && kind < 3) csignal_t(kind < 2 ? CN_L + s + l * LAG : CN_X + s, kind);
  }
  if (spin >= SPIN_TOT) g_err = 13;
}

__device__ __forceinline__ void work_prefetch(int t) {
  int spin = 0;
#pragma unroll 1
  for (int k = 0; k + 4 < NSTEP; k++) {
    if ((t & 31) == 0) cwait(CN_O + k * 5, 1, spin);
    __syncwarp();
    if (k + 2 < NSEG) { prefetch_l2(g_x + (size_t)(k + 2) * 32 * DM + t * 64); prefetch_l2(g_x + (size_t)(k + 2) * 32 * DM + t * 64 + 32); }
    prefetch_l2(g_xn[k + 4] + (t >> 4) * 4096 + (t & 15) * 128);
    if (t < 184) prefetch_l2(ex_window(g_ex) + (t < 160 ? EX_M + (k + 4) * 20480 + t * 128 : EX_FLAG + (k + 4) * 3072 + (t - 160) * 128));
  }
}

__device__ __forceinline__ void stage_qkv(const bf16* wqkv, uint32_t base, int T, int bc, int tid) {
  const int q = tid & 15;
  const bool ok = q < 15 && bc * 60 + 4 * q < DM;
  const bf16* src = wqkv + T * DM + bc * 60 + 4 * q;
#pragma unroll 1
  for (int k0 = tid >> 4; k0 < 640; k0 += 80) {
    uint2 v[10];
#pragma unroll
    for (int u = 0; u < 10; u++) v[u] = ok ? *reinterpret_cast<const uint2*>(src + (size_t)(k0 + 8 * u) * 1920) : make_uint2(0, 0);
#pragma unroll
    for (int u = 0; u < 10; u++) sts64(base + (k0 + 8 * u) * 128 + (((q >> 1) ^ (k0 & 7)) << 4) + (q & 1) * 8, v[u].x, v[u].y);
  }
}
__device__ __forceinline__ void attend(uint32_t sb, int bc, int l, int s, int p, int tid) {
  using namespace W;
  const int r = tid & 7, m = (tid >> 3) & 3, hh = (tid >> 5) & 3, g = (tid >> 2) & 7, t = tid & 3;
  const int f2 = r < 4 ? 20 * hh + 16 + r : 60;
  const uint32_t tb = sb + OFF_T + (l * 4 + 2 * p) * COL, hb = sb + OFF_H + (l * 2 + p) * COL;
  const uint32_t ko = (m < 2 ? 20 * hh + 8 * m + r : f2) * 16, vo = (m < 2 ? 20 * hh + 4 * (r >> 1) + 2 * m + (r & 1) : f2) * 16;
  const float scl = 0.22360679774997896f * 1.4426950408889634f;
  float sc[3][4];
  {
    uint32_t q[4], q8a, q8b, k[3][4];
    ldsm4t(q, tb + (m & 1) * COL + (20 * hh + (m >> 1) * 8 + r) * 16);
    ldsm2t(q8a, q8b, tb + (m & 1) * COL + f2 * 16);
    ldsm4t(k[0], hb + ko); ldsm4t(k[1], tb + 8 * COL + ko); ldsm4t(k[2], tb + 9 * COL + ko);
#pragma unroll
    for (int c = 0; c < 3; c++) { sc[c][0] = sc[c][1] = sc[c][2] = sc[c][3] = 0.f; mma16816(sc[c], q[0], q[1], q[2], q[3], k[c][0], k[c][1]); }
#pragma unroll
    for (int c = 0; c < 3; c++) mma1688(sc[c], q8a, q8b, k[c][2]);
  }
  uint32_t v[3][4];
  ldsm4(v[0], hb + 4 * COL + vo); ldsm4(v[1], tb + 16 * COL + vo); ldsm4(v[2], tb + 17 * COL + vo);
  const bool lo0 = 2 * t > g, lo1 = 2 * t + 1 > g;
  uint32_t pw[2];
  float inv[2];
#pragma unroll
  for (int h = 0; h < 2; h++) {
    float y0 = lo0 ? sc[h][2 * h] : sc[h + 1][2 * h], y1 = lo1 ? sc[h][2 * h + 1] : sc[h + 1][2 * h + 1];
    if (h == 0 && s == 0) { y0 = lo0 ? -INFINITY : y0; y1 = lo1 ? -INFINITY : y1; }
    const float mx = quad_max(fmaxf(y0, y1)) * -scl;
    pw[h] = pack_bf16(ex2(fmaf(y0, scl, mx)), ex2(fmaf(y1, scl, mx)));
    inv[h] = bf_lo(pw[h]) + bf_hi(pw[h]);
  }
  const uint32_t ml = (lo0 ? 0xFFFFu : 0u) | (lo1 ? 0xFFFF0000u : 0u);
  float o[3][4];
#pragma unroll
  for (int j = 0; j < 3; j++) { o[j][0] = o[j][1] = o[j][2] = o[j][3] = 0.f; mma16816(o[j], pw[0] & ml, 0u, pw[0] & ~ml, pw[1] & ml, v[0][j], v[1][j]); }
#pragma unroll
  for (int j = 0; j < 3; j++) mma1688(o[j], 0u, pw[1] & ~ml, v[2][j]);
  inv[0] = rcp(quad_sum(inv[0])); inv[1] = rcp(quad_sum(inv[1]));
  const uint32_t ca = (bc * 3 + hh) * 20 + 4 * t, cb = ca + 16 - 2 * t, row = 2 * g + p;
  uint8_t* img = g_ob[l] + (size_t)s * 40960 + row * 128;
  const uint32_t oa = (ca >> 6) * 4096 + (((ca >> 3) ^ row) & 7) * 16 + (ca & 4) * 2, ob = (cb >> 6) * 4096 + (((cb >> 3) ^ row) & 7) * 16 + (cb & 6) * 2;
#pragma unroll
  for (int h = 0; h < 2; h++) {
    *reinterpret_cast<uint2*>(img + oa + h * 2048) = make_uint2(pack_bf16(o[0][2 * h] * inv[h], o[0][2 * h + 1] * inv[h]), pack_bf16(o[1][2 * h] * inv[h], o[1][2 * h + 1] * inv[h]));
    if (t < 2) *reinterpret_cast<uint32_t*>(img + ob + h * 2048) = pack_bf16(o[2][2 * h] * inv[h], o[2][2 * h + 1] * inv[h]);
  }
}
template <int WG>
__device__ __forceinline__ void work_b(const bf16* wqkv, uint32_t sb, int bc, int tid0) {
  using namespace W;
  if (WG == 0) asm volatile("setmaxnreg.inc.sync.aligned.u32 232;");
  else asm volatile("setmaxnreg.inc.sync.aligned.u32 208;");
  constexpr int NR = WG ? KRS : QRS, OFF_Y = WG ? OFF_YK : OFF_YQ;
  int spin = 0;
  const uint32_t wb = sb + (WG ? OFF_WO : OFF_WV);
  uint32_t wf[NR][4];
  stage_qkv(wqkv, wb, WG, bc, tid0 & 127);
  WBAR_SYNC(NB_G0 + WG, 128);
  load_frags<NR>(wf, wb, tid0);
#pragma unroll
  for (int k = NR; k < 40; k++) sts128(sb + OFF_Y + (k - NR) * 2048 + (tid0 & 127) * 16, lds128(wb + k * 2048 + (tid0 & 127) * 16));
  fence_async();
  if (WG == 1) WBAR_ARRIVE(NB_PK, 256);
  WBAR_SYNC(NB_G0 + WG, 128);
  if (WG == 0) {
    stage_qkv(wqkv, wb, 2, bc, tid0);
    fence_async();
    WBAR_SYNC(NB_G0, 128);
  }
#pragma unroll 1
  for (int k = 0; k < NSTEP; k++) {
    uint32_t hist[8];
    {
      float d[32], e[32];
#pragma unroll
      for (int c = 0; c < 10; c++) {
        mwait(sb + BAR_F + 8 * (c % 3), ((c % 3 ? k : 0) + c / 3) & 1, spin);
        if (c == 0 && bc == 0) WTS(k, WG ? 15 : 6);
        wg_fence();
#pragma unroll
        for (int kk = 0; kk < 4; kk++) {
          const int q = 4 * c + kk;
          const uint64_t db = rdesc(OFF_X + (c % 3) * 8192, kk);
          if (q < NR) wgmma_rs64(d, wf[q < NR ? q : 0], db, q);
          else wgmma_ts64(d, mkdesc(SB0 + OFF_Y + (q - NR) * 2048, 8192, 1024), db, 1);
          if (WG == 0) wgmma_ts64(e, mkdesc(SB0 + OFF_WV + q * 2048, 8192, 1024), db, q);
          if (kk == 0 && c > 0 && c <= 7) {
            wg_commit();
            wg_wait<1>();
            if ((tid0 & 31) == 0) mbar_arrive(sb + BAR_E + 8 * ((c - 1) % 3));
          }
        }
        wg_commit();
      }
      wg_wait<0>();
      if (bc == 0) WTS(k, 16 + WG);
      WBAR_SYNC(NB_B, 256);
      const int tid = fresh(tid0), m = (tid >> 3) & 3;
      const uint32_t a = sb + OFF_T + min(((tid >> 5) & 3) * 16 + (m & 1) * 8 + (tid & 7), 60) * 16 + (m >> 1) * COL;
      const float (&x)[32] = WG ? d : e;
#pragma unroll
      for (int p = 0; p < 4; p++) {
        hist[2 * p] = pack_bf16(x[8 * p + 4], x[8 * p + 5]); hist[2 * p + 1] = pack_bf16(x[8 * p + 6], x[8 * p + 7]);
        stsm4(a + (16 - 8 * WG + 2 * p) * COL, pack_bf16(x[8 * p], x[8 * p + 1]), pack_bf16(x[8 * p + 2], x[8 * p + 3]), hist[2 * p], hist[2 * p + 1]);
        if (WG == 0)
          stsm4(a + 2 * p * COL, pack_bf16(d[8 * p], d[8 * p + 1]), pack_bf16(d[8 * p + 2], d[8 * p + 3]), pack_bf16(d[8 * p + 4], d[8 * p + 5]), pack_bf16(d[8 * p + 6], d[8 * p + 7]));
      }
    }
    WBAR_SYNC(NB_TD, 288);
    if (bc == 0 && WG == 0) WTS(k, 7);
#pragma unroll 1
    for (int l = 0; l < 2; l++) {
      const int tid = fresh(tid0), hh = uni((tid >> 5) & 3), s = k - l * LAG;
      if (hh < 3 && bc * 3 + hh < NH && s >= 0 && s < NSEG) attend(sb, bc, l, s, WG, tid);
      if (bc == 0 && WG == 0) WTS(k, l == 0 || k >= NSEG ? 8 : 25);
      if (l == 0) WBAR_ARRIVE(NB_AS, 288); else WBAR_ARRIVE(NB_AS + 1, 288);
    }
    WBAR_SYNC(NB_B, 256);
    {
      const int tid = fresh(tid0), m = (tid >> 3) & 3;
      const uint32_t a = sb + OFF_H + min(((tid >> 5) & 3) * 16 + (m & 1) * 8 + (tid & 7), 60) * 16 + (4 - 4 * WG + (m >> 1)) * COL;
      stsm4(a, hist[0], hist[1], hist[2], hist[3]);
      if (k >= LAG) stsm4(a + 2 * COL, hist[4], hist[5], hist[6], hist[7]);
      fence_async();
      if ((tid & 31) < 3) mbar_arrive(sb + BAR_E + 8 * (tid & 3));
    }
  }
  if (spin >= SPIN_TOT) g_err = 14;
}
__device__ __forceinline__ void work_wo(const CUtensorMap& tmBo, uint32_t sb, int bc, int tid0) {
  using namespace W;
  int spin = 0;
  WBAR_SYNC(NB_PK, 256);
  if (bc == 10) return;
  if ((tid0 & 127) == 0) {
    mbar_expect_tx(sb + BAR_W, 81920);
    for (int i = 0; i < 10; i++) tma2d(sb + OFF_WO + i * 8192, &tmBo, bc * 64, i * 64, sb + BAR_W);
  }
  __syncwarp();
  mwait(sb + BAR_W, 0, spin);
  permute_cols(sb + OFF_WO, tid0 & 127, 2560);
  WBAR_SYNC(NB_G0 + 2, 128);
  uint32_t wl[4];
  ldsm4t(wl, frag_addr(sb + OFF_WO + 39 * 2048, tid0));
  fence_async();
  WBAR_SYNC(NB_PV, 160);
  FOR_SEGS(l, s)
    float d[16];
#pragma unroll
    for (int c = 0; c < 10; c++) {
      mwait(sb + BAR_G + 8 * (c % 5), c / 5, spin);
      if (c == 0 && bc == 0) WTS(s + l * LAG, l == 0 || s + LAG >= NSEG ? 20 : 23);
      wg_fence();
#pragma unroll
      for (int kk = 0; kk < 4; kk++) {
        if (c == 9 && kk == 3) wgmma_rs32(d, wl, rdesc(OFF_G + (c % 5) * 4096, kk), 1);
        else wgmma_ts32(d, mkdesc(SB0 + OFF_WO + (4 * c + kk) * 2048, 8192, 1024), rdesc(OFF_G + (c % 5) * 4096, kk), c | kk);
      }
      wg_commit();
      if (c % 5) {
        wg_wait<1>();
        if ((tid0 & 31) == 0) mbar_arrive(sb + BAR_H + 8 * ((c - 1) % 5));
      }
      if (c % 5 == 4) {
        wg_wait<0>();
        if ((tid0 & 31) == 0) mbar_arrive(sb + BAR_H + 32);
      }
    }
    if (bc == 0) WTS(s + l * LAG, l == 0 || s + LAG >= NSEG ? 10 : 24);
    red_tile(d, s, bc * 64, tid0);
    WBAR_SYNC(NB_SG, 160);
  }
  if (spin >= SPIN_TOT) g_err = 17;
}
__device__ __forceinline__ void work_x_producer(uint32_t sb, int bc) {
  using namespace W;
  int spin = 0;
#pragma unroll 1
  for (int k = 0; k < NSTEP; k++) {
    const uint32_t lo = k < NSEG ? 0 : 4096, len = k < LAG || k >= NSEG ? 4096 : 8192;
    const uint8_t* src = g_xnb[k] + lo;
    cwait(CN_L + k, len >> 7, spin);
    fence_async_all();
    if (bc == 0) WTS1(k, 5);
#pragma unroll
    for (int c = 0; c < 10; c++) {
      mwait(sb + BAR_E + 8 * (c % 3), (((c % 3 ? k : 0) + c / 3) & 1) ^ 1, spin);
      if (elect_one()) {
        mbar_expect_tx(sb + BAR_F + 8 * (c % 3), len);
        bulk_g2s(sb + OFF_X + (c % 3) * 8192 + lo, src + c * 8192, len, sb + BAR_F + 8 * (c % 3));
      }
    }
  }
  if (spin >= SPIN_TOT) g_err = 15;
}
__device__ __forceinline__ void work_g_producer(uint32_t sb, int bc) {
  using namespace W;
  int spin = 0;
  uint32_t seen = 0;
  FOR_SEGS(l, s)
    const uint8_t* src = g_ob[l] + (size_t)s * 40960;
    if (seen < NBC) { cwait(CN_A + l * 64 + s, NBC, spin); fence_async_all(); }
    if (bc == 0) WTS1(s + l * LAG, l == 0 || s + LAG >= NSEG ? 9 : 22);
    seen = 0;
#pragma unroll
    for (int c = 0; c < 10; c++) {
      if (GLA && c == GLA && l == 0 && s >= LAG) { seen = ld_acquire(&g_cnt[CN_A + 64 + s - LAG][0]); fence_async_all(); }
      mwait(sb + BAR_H + 8 * (c % 5), c < 5, spin);
      if (elect_one()) {
        mbar_expect_tx(sb + BAR_G + 8 * (c % 5), 4096);
        bulk_g2s(sb + OFF_G + (c % 5) * 4096, src + c * 4096, 4096, sb + BAR_G + 8 * (c % 5));
      }
    }
  }
  if (spin >= SPIN_TOT) g_err = 16;
}

__global__ void __launch_bounds__(512, 1)
k_work(const __grid_constant__ CUtensorMap tmWo, const __grid_constant__ CUtensorMap tmBo, const bf16* __restrict__ wqkv, bf16* __restrict__ out) {
  using namespace W;
  extern __shared__ __align__(1024) uint8_t smem[];
  const uint32_t sb = smem_u32(smem);
  const int tid = threadIdx.x, w = blockIdx.x;
  const int wg = __shfl_sync(0xffffffffu, tid >> 7, 0);
  if (tid == 0) {
    if (sb != SB0) g_err = 101;
    for (int i = 0; i < 5; i++) { mbar_init(sb + BAR_F + 8 * i, 1); mbar_init(sb + BAR_E + 8 * i, 8); mbar_init(sb + BAR_G + 8 * i, 1); mbar_init(sb + BAR_H + 8 * i, 4); }
    mbar_init(sb + BAR_W, 1); mbar_init(sb + BAR_W + 8, 1);
    for (int p = 0; p < 16; p++) sts32(sb + OFF_SAFE + 4 * p, 0);
    asm volatile("fence.mbarrier_init.release.cluster;" ::: "memory");
  }
  if (tid < 8 * COL / 16) sts128(sb + OFF_H + tid * 16, make_uint4(0, 0, 0, 0));
  fence_async();
  __syncthreads();

  if (w < NP) {
    if (wg == 0) work_p<0>(tmWo, sb, w, keep(tid));
    else if (wg == 1) work_p<1>(tmWo, sb, w, keep(tid));
    else {
      asm volatile("setmaxnreg.dec.sync.aligned.u32 48;");
      const int aw = uni(tid >> 5) - 8;
      if (aw < 2) {
        work_p_producer(sb, w, aw);
      } else {
        const int id = (aw - 2) * NP + w;
        if (id < 128) work_ln(id & 3, id >> 2, tid & 31, out);
        else if (PFW && id < 138) work_prefetch((id - 128) * 32 + (tid & 31));
      }
    }
  } else {
    const int bc = w - NP;
    if (wg == 0) work_b<0>(wqkv, sb, bc, keep(tid));
    else if (wg == 1) work_b<1>(wqkv, sb, bc, keep(tid));
    else if (wg == 2) {
      asm volatile("setmaxnreg.dec.sync.aligned.u32 48;");
      work_wo(tmBo, sb, bc, keep(tid));
    } else {
      asm volatile("setmaxnreg.dec.sync.aligned.u32 24;");
      const int aw = uni(tid >> 5) - 12;
      if (aw == 0) work_x_producer(sb, bc);
      else if (aw == 1) {
        if (bc < 10) {
          WBAR_SYNC(NB_PV, 160);
          work_g_producer(sb, bc);
        }
      } else if (aw == 2) {
        for (int k = 0; k < NSTEP; k++) {
          WBAR_SYNC(NB_TD, 288);
          WBAR_SYNC(NB_AS, 288);
          if (tid == 448 && k < NSEG) csignal_t(CN_A + k, 5);
          __syncwarp();
          WBAR_SYNC(NB_AS + 1, 288);
          if (tid == 448 && k >= LAG) csignal_t(CN_A + 64 + k - LAG, 4);
          __syncwarp();
        }
      } else if (bc < 10) {
        FOR_SEGS(l, s)
          WBAR_SYNC(NB_SG, 160);
          if (tid == 480) csignal_t(CN_W + l * 64 + s, 6);
          __syncwarp();
        }
      }
    }
  }
  __syncthreads();
  asm volatile("griddepcontrol.wait;" ::: "memory");
}

typedef CUresult (*EncodeFn)(CUtensorMap*, CUtensorMapDataType, cuuint32_t, void*, const cuuint64_t*, const cuuint64_t*,
                             const cuuint32_t*, const cuuint32_t*, CUtensorMapInterleave, CUtensorMapSwizzle,
                             CUtensorMapL2promotion, CUtensorMapFloatOOBfill);

static void make_map(EncodeFn enc, CUtensorMap* tm, const void* ptr, uint64_t cols, uint64_t rows, uint32_t boxc, uint32_t boxr) {
  cuuint64_t dims[2] = {cols, rows};
  cuuint64_t strides[1] = {cols * 2};
  cuuint32_t box[2] = {boxc, boxr};
  cuuint32_t es[2] = {1, 1};
  enc(tm, CU_TENSOR_MAP_DATA_TYPE_BFLOAT16, 2, const_cast<void*>(ptr), dims, strides, box, es, CU_TENSOR_MAP_INTERLEAVE_NONE,
      CU_TENSOR_MAP_SWIZZLE_128B, CU_TENSOR_MAP_L2_PROMOTION_L2_256B, CU_TENSOR_MAP_FLOAT_OOB_FILL_NONE);
}

extern "C" void kernel_launch(void* const* d_in, const int* in_sizes, int n_in, void* d_out, int out_size) {
  const bf16* x0 = (const bf16*)d_in[0];
  const bf16* mem0 = (const bf16*)d_in[1];
  const bf16* Wq = (const bf16*)d_in[2];
  const bf16* Wk = (const bf16*)d_in[3];
  const bf16* Wv = (const bf16*)d_in[4];
  const bf16* Wo = (const bf16*)d_in[5];
  const bf16* Bqkv = (const bf16*)d_in[8];
  const bf16* Bwo = (const bf16*)d_in[9];
  bf16* out = (bf16*)d_out;

  static EncodeFn enc = nullptr;
  if (!enc) {
    void* fn = nullptr;
    cudaDriverEntryPointQueryResult qr;
    cudaGetDriverEntryPoint("cuTensorMapEncodeTiled", &fn, cudaEnableDefault, &qr);
    enc = (EncodeFn)fn;
    cudaFuncSetAttribute(k_chain, cudaFuncAttributeMaxDynamicSharedMemorySize, C::SMEM);
    cudaFuncSetAttribute(k_work, cudaFuncAttributeMaxDynamicSharedMemorySize, W::SMEM);
  }
  CUtensorMap tmWq, tmWk, tmWv, tmWo, tmWp, tmBo;
  make_map(enc, &tmWq, Wq, NH * DH, DM, 64, 128);
  make_map(enc, &tmWk, Wk, NH * DH, DM, 64, 128);
  make_map(enc, &tmWv, Wv, NH * DH, DM, 64, 128);
  make_map(enc, &tmWo, Wo, DM, NH * DH, 64, 64);
  make_map(enc, &tmWp, Wo, DM, NH * DH, 64, 16);
  make_map(enc, &tmBo, Bwo, DM, DM, 64, 64);

  cudaStream_t st = cudaStreamPerThread;
  k_pre<<<256, 256, 0, st>>>(x0, mem0);
  cudaLaunchAttribute at[1];
  at[0].id = cudaLaunchAttributeProgrammaticStreamSerialization; at[0].val.programmaticStreamSerializationAllowed = 1;
  {
    cudaLaunchConfig_t cfg = {};
    cfg.gridDim = dim3(96); cfg.blockDim = dim3(384); cfg.dynamicSmemBytes = C::SMEM; cfg.stream = st;
    cfg.attrs = at; cfg.numAttrs = 0;
    cudaLaunchKernelEx(&cfg, k_chain, tmWq, tmWk, tmWv, tmWo);
  }
  cudaLaunchConfig_t cfg = {};
  cfg.gridDim = dim3(W::NW); cfg.blockDim = dim3(512); cfg.dynamicSmemBytes = W::SMEM; cfg.stream = st;
  cfg.attrs = at; cfg.numAttrs = NOWORK == 2 ? 0 : 1;
  cudaLaunchKernelEx(&cfg, k_work, tmWp, tmBo, Bqkv, out);
}
```

```cpp
#include <cuda_runtime.h>
#include <cuda_bf16.h>
#include <cuda.h>
#include <stdint.h>

typedef __nv_bfloat16 bf16;

constexpr int SEQ = 2048, DM = 640, NH = 32, DH = 192, NSEG = 64;
#define LAG 6
constexpr int NSTEP = NSEG + LAG;
constexpr int NPRE = 4;
constexpr uint32_t SENT = 0xFFFFFFFFu;

constexpr int MAIL9 = 288 * 2048, MAIL_BYTES = MAIL9 + 64 * 3072;
__device__ __align__(1024) uint8_t g_xn[NSTEP][81920];
__device__ __align__(1024) uint8_t g_xnb[NSTEP][81920];
__device__ __align__(1024) uint8_t g_ob[2][NSEG * 40960];
#define ORING 8
static_assert(ORING > LAG, "a slot is free again LAG + 1 steps later");
__device__ __align__(1024) uint8_t g_o[ORING][96][8192];
__device__ __align__(1024) float g_x[SEQ * DM];
constexpr int EX_MAIL = 0;
constexpr int EX_M = 2 << 20;
constexpr int EX_FLAG = EX_M + NSTEP * 20480;
static_assert(EX_FLAG + NSTEP * 3072 <= (4 << 20), "");
__device__ __align__(1024) uint8_t g_ex[8 << 20];
__host__ __device__ __forceinline__ uint8_t* ex_window(uint8_t* p) { return reinterpret_cast<uint8_t*>((reinterpret_cast<uint64_t>(p) + (4 << 20) - 1) & ~(uint64_t)((4 << 20) - 1)); }
enum { CN_P = 0, CN_L = 128, CN_A = 256, CN_W = 384, CN_X = 512, CN_O = 640, CN_NUM = CN_O + 5 * NSTEP };
__device__ __align__(128) uint32_t g_cnt[CN_NUM][32];
__device__ __align__(128) uint32_t g_ticket[2][32];
__device__ int g_err;
#define TS(jj, i)
#define TS1(jj, i)
#define PTS(i)
#define TSB(jj, i)
#define TSV(jj, i, v)
#define TS_FLUSH(jj)
#define WTS(b, k)
#define WTS1(b, k)
#define WW -1

__device__ __forceinline__ uint32_t smem_u32(const void* p) { return (uint32_t)__cvta_generic_to_shared(p); }
__device__ __forceinline__ uint32_t clk32() { uint32_t t; asm volatile("mov.u32 %0, %%clock;" : "=r"(t)::"memory"); return t; }
__device__ __forceinline__ uint32_t mapa(uint32_t a, uint32_t r) { uint32_t o; asm("mapa.shared::cluster.u32 %0,%1,%2;" : "=r"(o) : "r"(a), "r"(r)); return o; }
__device__ __forceinline__ void mbar_init(uint32_t bar, uint32_t cnt) { asm volatile("mbarrier.init.shared::cta.b64 [%0],%1;" ::"r"(bar), "r"(cnt) : "memory"); }
__device__ __forceinline__ void mbar_expect_tx(uint32_t bar, uint32_t bytes) { asm volatile("mbarrier.arrive.expect_tx.shared::cta.b64 _,[%0],%1;" ::"r"(bar), "r"(bytes) : "memory"); }
__device__ __forceinline__ void mbar_arrive(uint32_t bar) { asm volatile("mbarrier.arrive.shared::cta.b64 _,[%0];" ::"r"(bar) : "memory"); }
__device__ __forceinline__ void mbar_arrive_cluster(uint32_t bar) { asm volatile("mbarrier.arrive.shared::cluster.b64 _,[%0];" ::"r"(bar) : "memory"); }
__device__ __forceinline__ bool mbar_try(uint32_t bar, uint32_t ph) {
  uint32_t ok;
  asm volatile("{.reg .pred p; mbarrier.try_wait.parity.shared::cta.b64 p,[%1],%2; selp.u32 %0,1,0,p;}" : "=r"(ok) : "r"(bar), "r"(ph) : "memory");
  return ok;
}
__device__ __forceinline__ bool mbar_test(uint32_t bar, uint32_t ph) {
  uint32_t ok;
  asm volatile("{.reg .pred p; mbarrier.test_wait.parity.shared::cta.b64 p,[%1],%2; selp.u32 %0,1,0,p;}" : "=r"(ok) : "r"(bar), "r"(ph) : "memory");
  return ok;
}
__device__ __forceinline__ int fresh(int x) { asm volatile("" : "+r"(x)); return x; }
#define PHASE_IDS const int tid = fresh(tid0), lane = tid & 31, w = tid >> 5, g = lane >> 2, t = lane & 3; (void)w; (void)g; (void)t
__device__ __forceinline__ void bar_sync(int id, int n) { asm volatile("bar.sync %0,%1;" ::"r"(id), "r"(n) : "memory"); }
__device__ __forceinline__ void bar_arrive(int id, int n) { asm volatile("bar.arrive %0,%1;" ::"r"(id), "r"(n) : "memory"); }
__device__ __forceinline__ bool bar_red_or(int id, int n, bool v) {
  uint32_t r;
  asm volatile("{\n .reg .pred p, q;\n setp.ne.u32 q, %3, 0;\n barrier.cta.red.or.pred p, %1, %2, q;\n selp.u32 %0, 1, 0, p;\n}" : "=r"(r) : "r"(id), "r"(n), "r"((uint32_t)v) : "memory");
  return r != 0;
}
__device__ __forceinline__ void fence_async() { asm volatile("fence.proxy.async.shared::cta;" ::: "memory"); }
__device__ __forceinline__ void bulk_g2s(uint32_t dst, const void* src, uint32_t bytes, uint32_t bar) {
  asm volatile("cp.async.bulk.shared::cluster.global.mbarrier::complete_tx::bytes [%0],[%1],%2,[%3];" ::"r"(dst), "l"(src), "r"(bytes), "r"(bar) : "memory");
}
__device__ __forceinline__ void bulk_g2s_mc(uint32_t dst, const void* src, uint32_t bytes, uint32_t bar) {
  asm volatile("cp.async.bulk.shared::cluster.global.mbarrier::complete_tx::bytes.multicast::cluster [%0],[%1],%2,[%3],%4;"
               ::"r"(dst), "l"(src), "r"(bytes), "r"(bar), "h"((uint16_t)7) : "memory");
}
__device__ __forceinline__ void bulk_s2g(void* dst, uint32_t src, uint32_t bytes) {
  asm volatile("cp.async.bulk.global.shared::cta.bulk_group [%0],[%1],%2;" ::"l"(dst), "r"(src), "r"(bytes) : "memory");
}
__device__ __forceinline__ void bulk_s2c(uint32_t dst, uint32_t src, uint32_t bytes, uint32_t bar) {
  asm volatile("cp.async.bulk.shared::cluster.shared::cta.mbarrier::complete_tx::bytes [%0],[%1],%2,[%3];" ::"r"(dst), "r"(src), "r"(bytes), "r"(bar) : "memory");
}
__device__ __forceinline__ void tma2d(uint32_t dst, const CUtensorMap* tm, int c0, int c1, uint32_t bar) {
  asm volatile("cp.async.bulk.tensor.2d.shared::cluster.global.mbarrier::complete_tx::bytes [%0],[%1,{%3,%4}],[%2];"
               ::"r"(dst), "l"(tm), "r"(bar), "r"(c0), "r"(c1) : "memory");
}
__device__ __forceinline__ void tma2d_prefetch(const CUtensorMap* tm, int c0, int c1) {
  asm volatile("cp.async.bulk.prefetch.tensor.2d.L2.global.tile [%0,{%1,%2}];" ::"l"(tm), "r"(c0), "r"(c1) : "memory");
}
__device__ __forceinline__ uint32_t pack_bf16(float lo, float hi) {
  uint32_t r; asm("cvt.rn.bf16x2.f32 %0,%1,%2;" : "=r"(r) : "f"(hi), "f"(lo)); return r;
}
__device__ __forceinline__ float bf_lo(uint32_t x) { return __uint_as_float(x << 16); }
__device__ __forceinline__ float bf_hi(uint32_t x) { return __uint_as_float(x & 0xFFFF0000u); }
__device__ __forceinline__ float ex2(float x) { float y; asm("ex2.approx.ftz.f32 %0,%1;" : "=f"(y) : "f"(x)); return y; }
__device__ __forceinline__ void ldsm4(uint32_t (&r)[4], uint32_t a) {
  asm volatile("ldmatrix.sync.aligned.m8n8.x4.shared.b16 {%0,%1,%2,%3},[%4];" : "=r"(r[0]), "=r"(r[1]), "=r"(r[2]), "=r"(r[3]) : "r"(a) : "memory");
}
__device__ __forceinline__ void ldsm4t(uint32_t (&r)[4], uint32_t a) {
  asm volatile("ldmatrix.sync.aligned.m8n8.x4.trans.shared.b16 {%0,%1,%2,%3},[%4];" : "=r"(r[0]), "=r"(r[1]), "=r"(r[2]), "=r"(r[3]) : "r"(a) : "memory");
}
__device__ __forceinline__ void ldsm2(uint32_t& r0, uint32_t& r1, uint32_t a) {
  asm volatile("ldmatrix.sync.aligned.m8n8.x2.shared.b16 {%0,%1},[%2];" : "=r"(r0), "=r"(r1) : "r"(a) : "memory");
}
__device__ __forceinline__ void ldsm2t(uint32_t& r0, uint32_t& r1, uint32_t a) {
  asm volatile("ldmatrix.sync.aligned.m8n8.x2.trans.shared.b16 {%0,%1},[%2];" : "=r"(r0), "=r"(r1) : "r"(a) : "memory");
}
__device__ __forceinline__ void ldsm1(uint32_t& r0, uint32_t a) {
  asm volatile("ldmatrix.sync.aligned.m8n8.x1.shared.b16 {%0},[%1];" : "=r"(r0) : "r"(a) : "memory");
}
__device__ __forceinline__ void mma16816(float (&d)[4], uint32_t a0, uint32_t a1, uint32_t a2, uint32_t a3, uint32_t b0, uint32_t b1) {
  asm volatile("mma.sync.aligned.m16n8k16.row.col.f32.bf16.bf16.f32 {%0,%1,%2,%3},{%4,%5,%6,%7},{%8,%9},{%0,%1,%2,%3};"
               : "+f"(d[0]), "+f"(d[1]), "+f"(d[2]), "+f"(d[3]) : "r"(a0), "r"(a1), "r"(a2), "r"(a3), "r"(b0), "r"(b1));
}
__device__ __forceinline__ void mma1688(float (&d)[4], uint32_t a0, uint32_t a1, uint32_t b0) {
  asm volatile("mma.sync.aligned.m16n8k8.row.col.f32.bf16.bf16.f32 {%0,%1,%2,%3},{%4,%5},{%6},{%0,%1,%2,%3};"
               : "+f"(d[0]), "+f"(d[1]), "+f"(d[2]), "+f"(d[3]) : "r"(a0), "r"(a1), "r"(b0));
}
__device__ __forceinline__ void sts32(uint32_t a, uint32_t v) { asm volatile("st.shared.b32 [%0],%1;" ::"r"(a), "r"(v) : "memory"); }
__device__ __forceinline__ void sts64f(uint32_t a, float x, float y) { asm volatile("st.shared.v2.f32 [%0],{%1,%2};" ::"r"(a), "f"(x), "f"(y) : "memory"); }
__device__ __forceinline__ void sts128(uint32_t a, uint4 v) { asm volatile("st.shared.v4.b32 [%0],{%1,%2,%3,%4};" ::"r"(a), "r"(v.x), "r"(v.y), "r"(v.z), "r"(v.w) : "memory"); }
__device__ __forceinline__ float lds32f(uint32_t a) { float v; asm volatile("ld.shared.f32 %0,[%1];" : "=f"(v) : "r"(a) : "memory"); return v; }
__device__ __forceinline__ float2 lds64f(uint32_t a) { float2 v; asm volatile("ld.shared.v2.f32 {%0,%1},[%2];" : "=f"(v.x), "=f"(v.y) : "r"(a) : "memory"); return v; }
__device__ __forceinline__ uint4 lds128(uint32_t a) { uint4 v; asm volatile("ld.shared.v4.b32 {%0,%1,%2,%3},[%4];" : "=r"(v.x), "=r"(v.y), "=r"(v.z), "=r"(v.w) : "r"(a) : "memory"); return v; }
__device__ __forceinline__ float4 lds128f(uint32_t a) { float4 v; asm volatile("ld.shared.v4.f32 {%0,%1,%2,%3},[%4];" : "=f"(v.x), "=f"(v.y), "=f"(v.z), "=f"(v.w) : "r"(a) : "memory"); return v; }
__device__ __forceinline__ void st_async2(uint32_t a, float x, float y, uint32_t bar) {
  asm volatile("st.async.weak.shared::cluster.mbarrier::complete_tx::bytes.v2.f32 [%0],{%1,%2},[%3];" ::"r"(a), "f"(x), "f"(y), "r"(bar) : "memory");
}
__device__ __forceinline__ void st_async4(uint32_t a, const float (&v)[4], uint32_t bar) {
  asm volatile("st.async.weak.shared::cluster.mbarrier::complete_tx::bytes.v4.f32 [%0],{%1,%2,%3,%4},[%5];" ::"r"(a), "f"(v[0]), "f"(v[1]), "f"(v[2]), "f"(v[3]), "r"(bar) : "memory");
}
__device__ __forceinline__ void st_async4v(uint32_t a, float x, float y, float z, float w, uint32_t bar) {
  asm volatile("st.async.weak.shared::cluster.mbarrier::complete_tx::bytes.v4.f32 [%0],{%1,%2,%3,%4},[%5];" ::"r"(a), "f"(x), "f"(y), "f"(z), "f"(w), "r"(bar) : "memory");
}
__device__ __forceinline__ void st_async4u(uint32_t a, const uint4& v, uint32_t bar) {
  asm volatile("st.async.weak.shared::cluster.mbarrier::complete_tx::bytes.v4.b32 [%0],{%1,%2,%3,%4},[%5];" ::"r"(a), "r"(v.x), "r"(v.y), "r"(v.z), "r"(v.w), "r"(bar) : "memory");
}
__device__ __forceinline__ uint4 ld_relaxed4(const void* p) {
  uint4 v; asm volatile("ld.relaxed.gpu.global.v4.u32 {%0,%1,%2,%3},[%4];" : "=r"(v.x), "=r"(v.y), "=r"(v.z), "=r"(v.w) : "l"(p) : "memory"); return v;
}
__device__ __forceinline__ uint32_t ld_relaxed(const void* p) {
  uint32_t v; asm volatile("ld.relaxed.gpu.global.u32 %0,[%1];" : "=r"(v) : "l"(p) : "memory"); return v;
}
__device__ __forceinline__ void st_relaxed(void* p, uint32_t v) { asm volatile("st.relaxed.gpu.global.b32 [%0],%1;" ::"l"(p), "r"(v) : "memory"); }
__device__ __forceinline__ void st_relaxed4(void* p, uint32_t v) { asm volatile("st.relaxed.gpu.global.v4.b32 [%0],{%1,%1,%1,%1};" ::"l"(p), "r"(v) : "memory"); }

__device__ __forceinline__ uint32_t ld_acquire(const void* p) {
  uint32_t v; asm volatile("ld.acquire.gpu.global.u32 %0,[%1];" : "=r"(v) : "l"(p) : "memory"); return v;
}
__device__ __forceinline__ float4 ld_relaxed4f(const void* p) {
  float4 v; asm volatile("ld.relaxed.gpu.global.v4.f32 {%0,%1,%2,%3},[%4];" : "=f"(v.x), "=f"(v.y), "=f"(v.z), "=f"(v.w) : "l"(p) : "memory"); return v;
}
__device__ __forceinline__ float2 ld_relaxed2f(const void* p) {
  float2 v; asm volatile("ld.relaxed.gpu.global.v2.f32 {%0,%1},[%2];" : "=f"(v.x), "=f"(v.y) : "l"(p) : "memory"); return v;
}
__device__ __forceinline__ void prefetch_l2(const void* p) { asm volatile("prefetch.global.L2 [%0];" ::"l"(p)); }
__device__ __forceinline__ void fence_gpu() { asm volatile("fence.acq_rel.gpu;" ::: "memory"); }
__device__ __forceinline__ void fence_async_all() { asm volatile("fence.proxy.async.global;" ::: "memory"); }
constexpr int SPIN_TOT = 1 << 22;
__device__ __forceinline__ void csignal(int idx) { asm volatile("red.release.gpu.global.add.u32 [%0],1;" ::"l"(&g_cnt[idx][0]) : "memory"); }
#define RLX 0
#define csignal_t(idx, role) csignal(idx)
__device__ __forceinline__ void cwait(int idx, uint32_t target, int& spin) {
  while (ld_acquire(&g_cnt[idx][0]) < target && spin < SPIN_TOT) spin += 16;
}

__device__ __forceinline__ uint64_t mkdesc(uint32_t addr, uint32_t lbo, uint32_t sbo) {
  return (uint64_t)((addr & 0x3FFFF) >> 4) | ((uint64_t)(lbo >> 4) << 16) | ((uint64_t)(sbo >> 4) << 32) | ((uint64_t)1 << 62);
}
__device__ __forceinline__ uint64_t mkdesc_ns(uint32_t addr, uint32_t lbo, uint32_t sbo) {
  return (uint64_t)((addr & 0x3FFFF) >> 4) | ((uint64_t)(lbo >> 4) << 16) | ((uint64_t)(sbo >> 4) << 32);
}
__device__ __forceinline__ void wg_fence() { asm volatile("wgmma.fence.sync.aligned;" ::: "memory"); }
__device__ __forceinline__ void wg_commit() { asm volatile("wgmma.commit_group.sync.aligned;" ::: "memory"); }
template <int N> __device__ __forceinline__ void wg_wait() { asm volatile("wgmma.wait_group.sync.aligned %0;" ::"n"(N) : "memory"); }

__device__ __forceinline__ void wgmma_rs16(float (&d)[8], const uint32_t (&a)[4], uint64_t db, int sc) {
  asm volatile("{.reg .pred p; setp.ne.b32 p,%13,0; wgmma.mma_async.sync.aligned.m64n16k16.f32.bf16.bf16 "
               "{%0,%1,%2,%3,%4,%5,%6,%7},{%8,%9,%10,%11},%12,p,1,1,0;}"
               : "+f"(d[0]), "+f"(d[1]), "+f"(d[2]), "+f"(d[3]), "+f"(d[4]), "+f"(d[5]), "+f"(d[6]), "+f"(d[7])
               : "r"(a[0]), "r"(a[1]), "r"(a[2]), "r"(a[3]), "l"(db), "r"(sc));
}
__device__ __forceinline__ void wgmma_rs64(float (&d)[32], const uint32_t (&a)[4], uint64_t db, int sc) {
  asm volatile("{.reg .pred p; setp.ne.b32 p,%37,0; wgmma.mma_async.sync.aligned.m64n64k16.f32.bf16.bf16 "
               "{%0,%1,%2,%3,%4,%5,%6,%7,%8,%9,%10,%11,%12,%13,%14,%15,%16,%17,%18,%19,%20,%21,%22,%23,%24,%25,%26,%27,%28,%29,%30,%31},{%32,%33,%34,%35},%36,p,1,1,0;}"
               : "+f"(d[0]), "+f"(d[1]), "+f"(d[2]), "+f"(d[3]), "+f"(d[4]), "+f"(d[5]), "+f"(d[6]), "+f"(d[7]), "+f"(d[8]), "+f"(d[9]), "+f"(d[10]), "+f"(d[11]), "+f"(d[12]), "+f"(d[13]), "+f"(d[14]), "+f"(d[15]), "+f"(d[16]), "+f"(d[17]), "+f"(d[18]), "+f"(d[19]), "+f"(d[20]), "+f"(d[21]), "+f"(d[22]), "+f"(d[23]), "+f"(d[24]), "+f"(d[25]), "+f"(d[26]), "+f"(d[27]), "+f"(d[28]), "+f"(d[29]), "+f"(d[30]), "+f"(d[31])
               : "r"(a[0]), "r"(a[1]), "r"(a[2]), "r"(a[3]), "l"(db), "r"(sc));
}
__device__ __forceinline__ void wgmma_rt16(float (&d)[8], const uint32_t (&a)[4], uint64_t db, int sc) {
  asm volatile("{.reg .pred p; setp.ne.b32 p,%13,0; wgmma.mma_async.sync.aligned.m64n16k16.f32.bf16.bf16 "
               "{%0,%1,%2,%3,%4,%5,%6,%7},{%8,%9,%10,%11},%12,p,1,1,1;}"
               : "+f"(d[0]), "+f"(d[1]), "+f"(d[2]), "+f"(d[3]), "+f"(d[4]), "+f"(d[5]), "+f"(d[6]), "+f"(d[7])
               : "r"(a[0]), "r"(a[1]), "r"(a[2]), "r"(a[3]), "l"(db), "r"(sc));
}
__device__ __forceinline__ void wgmma_rt80(float (&d)[40], const uint32_t (&a)[4], uint64_t db, int sc) {
  asm volatile("{.reg .pred p; setp.ne.b32 p,%45,0; wgmma.mma_async.sync.aligned.m64n80k16.f32.bf16.bf16 "
               "{%0,%1,%2,%3,%4,%5,%6,%7,%8,%9,%10,%11,%12,%13,%14,%15,%16,%17,%18,%19,%20,%21,%22,%23,%24,%25,%26,%27,%28,%29,%30,%31,%32,%33,%34,%35,%36,%37,%38,%39},{%40,%41,%42,%43},%44,p,1,1,1;}"
               : "+f"(d[0]), "+f"(d[1]), "+f"(d[2]), "+f"(d[3]), "+f"(d[4]), "+f"(d[5]), "+f"(d[6]), "+f"(d[7]), "+f"(d[8]), "+f"(d[9]), "+f"(d[10]), "+f"(d[11]), "+f"(d[12]), "+f"(d[13]), "+f"(d[14]), "+f"(d[15]), "+f"(d[16]), "+f"(d[17]), "+f"(d[18]), "+f"(d[19]), "+f"(d[20]), "+f"(d[21]), "+f"(d[22]), "+f"(d[23]), "+f"(d[24]), "+f"(d[25]), "+f"(d[26]), "+f"(d[27]), "+f"(d[28]), "+f"(d[29]), "+f"(d[30]), "+f"(d[31]), "+f"(d[32]), "+f"(d[33]), "+f"(d[34]), "+f"(d[35]), "+f"(d[36]), "+f"(d[37]), "+f"(d[38]), "+f"(d[39])
               : "r"(a[0]), "r"(a[1]), "r"(a[2]), "r"(a[3]), "l"(db), "r"(sc));
}
__device__ __forceinline__ void wgmma_rs32(float (&d)[16], const uint32_t (&a)[4], uint64_t db, int sc) {
  asm volatile("{.reg .pred p; setp.ne.b32 p,%21,0; wgmma.mma_async.sync.aligned.m64n32k16.f32.bf16.bf16 "
               "{%0,%1,%2,%3,%4,%5,%6,%7,%8,%9,%10,%11,%12,%13,%14,%15},{%16,%17,%18,%19},%20,p,1,1,0;}"
               : "+f"(d[0]), "+f"(d[1]), "+f"(d[2]), "+f"(d[3]), "+f"(d[4]), "+f"(d[5]), "+f"(d[6]), "+f"(d[7]), "+f"(d[8]), "+f"(d[9]), "+f"(d[10]), "+f"(d[11]), "+f"(d[12]), "+f"(d[13]), "+f"(d[14]), "+f"(d[15])
               : "r"(a[0]), "r"(a[1]), "r"(a[2]), "r"(a[3]), "l"(db), "r"(sc));
}
__device__ __forceinline__ void wgmma_ts32(float (&d)[16], uint64_t da, uint64_t db, int sc) {
  asm volatile("{.reg .pred p; setp.ne.b32 p,%18,0; wgmma.mma_async.sync.aligned.m64n32k16.f32.bf16.bf16 "
               "{%0,%1,%2,%3,%4,%5,%6,%7,%8,%9,%10,%11,%12,%13,%14,%15},%16,%17,p,1,1,1,0;}"
               : "+f"(d[0]), "+f"(d[1]), "+f"(d[2]), "+f"(d[3]), "+f"(d[4]), "+f"(d[5]), "+f"(d[6]), "+f"(d[7]), "+f"(d[8]), "+f"(d[9]), "+f"(d[10]), "+f"(d[11]), "+f"(d[12]), "+f"(d[13]), "+f"(d[14]), "+f"(d[15])
               : "l"(da), "l"(db), "r"(sc));
}
__device__ __forceinline__ void wgmma_rs8(float (&d)[4], const uint32_t (&a)[4], uint64_t db, int sc) {
  asm volatile("{.reg .pred p; setp.ne.b32 p,%9,0; wgmma.mma_async.sync.aligned.m64n8k16.f32.bf16.bf16 "
               "{%0,%1,%2,%3},{%4,%5,%6,%7},%8,p,1,1,0;}"
               : "+f"(d[0]), "+f"(d[1]), "+f"(d[2]), "+f"(d[3])
               : "r"(a[0]), "r"(a[1]), "r"(a[2]), "r"(a[3]), "l"(db), "r"(sc));
}
__device__ __forceinline__ void wgmma_ts16(float (&d)[8], uint64_t da, uint64_t db, int sc) {
  asm volatile("{.reg .pred p; setp.ne.b32 p,%10,0; wgmma.mma_async.sync.aligned.m64n16k16.f32.bf16.bf16 "
               "{%0,%1,%2,%3,%4,%5,%6,%7},%8,%9,p,1,1,1,0;}"
               : "+f"(d[0]), "+f"(d[1]), "+f"(d[2]), "+f"(d[3]), "+f"(d[4]), "+f"(d[5]), "+f"(d[6]), "+f"(d[7])
               : "l"(da), "l"(db), "r"(sc));
}
__device__ __forceinline__ void wgmma_ts64(float (&d)[32], uint64_t da, uint64_t db, int sc) {
  asm volatile("{.reg .pred p; setp.ne.b32 p,%34,0; wgmma.mma_async.sync.aligned.m64n64k16.f32.bf16.bf16 "
               "{%0,%1,%2,%3,%4,%5,%6,%7,%8,%9,%10,%11,%12,%13,%14,%15,%16,%17,%18,%19,%20,%21,%22,%23,%24,%25,%26,%27,%28,%29,%30,%31},%32,%33,p,1,1,1,0;}"
               : "+f"(d[0]), "+f"(d[1]), "+f"(d[2]), "+f"(d[3]), "+f"(d[4]), "+f"(d[5]), "+f"(d[6]), "+f"(d[7]), "+f"(d[8]), "+f"(d[9]), "+f"(d[10]), "+f"(d[11]), "+f"(d[12]), "+f"(d[13]), "+f"(d[14]), "+f"(d[15]), "+f"(d[16]), "+f"(d[17]), "+f"(d[18]), "+f"(d[19]), "+f"(d[20]), "+f"(d[21]), "+f"(d[22]), "+f"(d[23]), "+f"(d[24]), "+f"(d[25]), "+f"(d[26]), "+f"(d[27]), "+f"(d[28]), "+f"(d[29]), "+f"(d[30]), "+f"(d[31])
               : "l"(da), "l"(db), "r"(sc));
}
__device__ __forceinline__ void wgmma_tt16(float (&d)[8], uint64_t da, uint64_t db, int sc) {
  asm volatile("{.reg .pred p; setp.ne.b32 p,%10,0; wgmma.mma_async.sync.aligned.m64n16k16.f32.bf16.bf16 "
               "{%0,%1,%2,%3,%4,%5,%6,%7},%8,%9,p,1,1,1,1;}"
               : "+f"(d[0]), "+f"(d[1]), "+f"(d[2]), "+f"(d[3]), "+f"(d[4]), "+f"(d[5]), "+f"(d[6]), "+f"(d[7])
               : "l"(da), "l"(db), "r"(sc));
}
__device__ __forceinline__ void wgmma_tt40(float (&d)[20], uint64_t da, uint64_t db, int sc) {
  asm volatile("{.reg .pred p; setp.ne.b32 p,%22,0; wgmma.mma_async.sync.aligned.m64n40k16.f32.bf16.bf16 "
               "{%0,%1,%2,%3,%4,%5,%6,%7,%8,%9,%10,%11,%12,%13,%14,%15,%16,%17,%18,%19},%20,%21,p,1,1,1,1;}"
               : "+f"(d[0]), "+f"(d[1]), "+f"(d[2]), "+f"(d[3]), "+f"(d[4]), "+f"(d[5]), "+f"(d[6]), "+f"(d[7]), "+f"(d[8]), "+f"(d[9]), "+f"(d[10]), "+f"(d[11]), "+f"(d[12]), "+f"(d[13]), "+f"(d[14]), "+f"(d[15]), "+f"(d[16]), "+f"(d[17]), "+f"(d[18]), "+f"(d[19])
               : "l"(da), "l"(db), "r"(sc));
}
__device__ __forceinline__ void wgmma_ss8(float (&d)[4], uint64_t da, uint64_t db, int sc) {
  asm volatile("{.reg .pred p; setp.ne.b32 p,%6,0; wgmma.mma_async.sync.aligned.m64n8k16.f32.bf16.bf16 "
               "{%0,%1,%2,%3},%4,%5,p,1,1,0,0;}"
               : "+f"(d[0]), "+f"(d[1]), "+f"(d[2]), "+f"(d[3])
               : "l"(da), "l"(db), "r"(sc));
}
__device__ __forceinline__ void wgmma_ss32(float (&d)[16], uint64_t da, uint64_t db, int sc) {
  asm volatile("{.reg .pred p; setp.ne.b32 p,%18,0; wgmma.mma_async.sync.aligned.m64n32k16.f32.bf16.bf16 "
               "{%0,%1,%2,%3,%4,%5,%6,%7,%8,%9,%10,%11,%12,%13,%14,%15},%16,%17,p,1,1,0,0;}"
               : "+f"(d[0]), "+f"(d[1]), "+f"(d[2]), "+f"(d[3]), "+f"(d[4]), "+f"(d[5]), "+f"(d[6]), "+f"(d[7]), "+f"(d[8]), "+f"(d[9]), "+f"(d[10]), "+f"(d[11]), "+f"(d[12]), "+f"(d[13]), "+f"(d[14]), "+f"(d[15])
               : "l"(da), "l"(db), "r"(sc));
}
__device__ __forceinline__ void wgmma_st64(float (&d)[32], uint64_t da, uint64_t db, int sc) {
  asm volatile("{.reg .pred p; setp.ne.b32 p,%34,0; wgmma.mma_async.sync.aligned.m64n64k16.f32.bf16.bf16 "
               "{%0,%1,%2,%3,%4,%5,%6,%7,%8,%9,%10,%11,%12,%13,%14,%15,%16,%17,%18,%19,%20,%21,%22,%23,%24,%25,%26,%27,%28,%29,%30,%31},%32,%33,p,1,1,0,1;}"
               : "+f"(d[0]), "+f"(d[1]), "+f"(d[2]), "+f"(d[3]), "+f"(d[4]), "+f"(d[5]), "+f"(d[6]), "+f"(d[7]), "+f"(d[8]), "+f"(d[9]), "+f"(d[10]), "+f"(d[11]), "+f"(d[12]), "+f"(d[13]), "+f"(d[14]), "+f"(d[15]), "+f"(d[16]), "+f"(d[17]), "+f"(d[18]), "+f"(d[19]), "+f"(d[20]), "+f"(d[21]), "+f"(d[22]), "+f"(d[23]), "+f"(d[24]), "+f"(d[25]), "+f"(d[26]), "+f"(d[27]), "+f"(d[28]), "+f"(d[29]), "+f"(d[30]), "+f"(d[31])
               : "l"(da), "l"(db), "r"(sc));
}
__device__ __forceinline__ void wgmma_st128(float (&d)[64], uint64_t da, uint64_t db, int sc) {
  asm volatile("{.reg .pred p; setp.ne.b32 p,%66,0; wgmma.mma_async.sync.aligned.m64n128k16.f32.bf16.bf16 "
               "{%0,%1,%2,%3,%4,%5,%6,%7,%8,%9,%10,%11,%12,%13,%14,%15,%16,%17,%18,%19,%20,%21,%22,%23,%24,%25,%26,%27,%28,%29,%30,%31,%32,%33,%34,%35,%36,%37,%38,%39,%40,%41,%42,%43,%44,%45,%46,%47,%48,%49,%50,%51,%52,%53,%54,%55,%56,%57,%58,%59,%60,%61,%62,%63},%64,%65,p,1,1,0,1;}"
               : "+f"(d[0]), "+f"(d[1]), "+f"(d[2]), "+f"(d[3]), "+f"(d[4]), "+f"(d[5]), "+f"(d[6]), "+f"(d[7]), "+f"(d[8]), "+f"(d[9]), "+f"(d[10]), "+f"(d[11]), "+f"(d[12]), "+f"(d[13]), "+f"(d[14]), "+f"(d[15]), "+f"(d[16]), "+f"(d[17]), "+f"(d[18]), "+f"(d[19]), "+f"(d[20]), "+f"(d[21]), "+f"(d[22]), "+f"(d[23]), "+f"(d[24]), "+f"(d[25]), "+f"(d[26]), "+f"(d[27]), "+f"(d[28]), "+f"(d[29]), "+f"(d[30]), "+f"(d[31]), "+f"(d[32]), "+f"(d[33]), "+f"(d[34]), "+f"(d[35]), "+f"(d[36]), "+f"(d[37]), "+f"(d[38]), "+f"(d[39]), "+f"(d[40]), "+f"(d[41]), "+f"(d[42]), "+f"(d[43]), "+f"(d[44]), "+f"(d[45]), "+f"(d[46]), "+f"(d[47]), "+f"(d[48]), "+f"(d[49]), "+f"(d[50]), "+f"(d[51]), "+f"(d[52]), "+f"(d[53]), "+f"(d[54]), "+f"(d[55]), "+f"(d[56]), "+f"(d[57]), "+f"(d[58]), "+f"(d[59]), "+f"(d[60]), "+f"(d[61]), "+f"(d[62]), "+f"(d[63])
               : "l"(da), "l"(db), "r"(sc));
}

__device__ __forceinline__ void stsm4(uint32_t a, uint32_t r0, uint32_t r1, uint32_t r2, uint32_t r3) {
  asm volatile("stmatrix.sync.aligned.m8n8.x4.shared.b16 [%0],{%1,%2,%3,%4};" ::"r"(a), "r"(r0), "r"(r1), "r"(r2), "r"(r3) : "memory");
}
__device__ __forceinline__ void stsm4t(uint32_t a, uint32_t r0, uint32_t r1, uint32_t r2, uint32_t r3) {
  asm volatile("stmatrix.sync.aligned.m8n8.x4.trans.shared.b16 [%0],{%1,%2,%3,%4};" ::"r"(a), "r"(r0), "r"(r1), "r"(r2), "r"(r3) : "memory");
}
__device__ __forceinline__ void sts64(uint32_t a, uint32_t x, uint32_t y) { asm volatile("st.shared.v2.b32 [%0],{%1,%2};" ::"r"(a), "r"(x), "r"(y) : "memory"); }
__device__ __forceinline__ void st_async2u(uint32_t a, uint32_t x, uint32_t y, uint32_t bar) {
  asm volatile("st.async.weak.shared::cluster.mbarrier::complete_tx::bytes.v2.b32 [%0],{%1,%2},[%3];" ::"r"(a), "r"(x), "r"(y), "r"(bar) : "memory");
}
__device__ __forceinline__ void st_relaxed128(void* p, uint32_t x, uint32_t y, uint32_t z, uint32_t w) {
  asm volatile("{.reg .b128 v; mov.b128 v,{%1,%2,%3,%4}; st.relaxed.gpu.global.b128 [%0],v;}" ::"l"(p), "r"(x), "r"(y), "r"(z), "r"(w) : "memory");
}
__device__ __forceinline__ void st_relaxed64(void* p, uint32_t x, uint32_t y) {
  asm volatile("{.reg .b64 v; mov.b64 v,{%1,%2}; st.relaxed.gpu.global.b64 [%0],v;}" ::"l"(p), "r"(x), "r"(y) : "memory");
}
__device__ __forceinline__ uint4 ld_relaxed128(const void* p) {
  uint4 v;
  asm volatile("{.reg .b128 v; .reg .b64 lo, hi; ld.relaxed.gpu.global.b128 v,[%4]; mov.b128 {lo,hi},v; mov.b64 {%0,%1},lo; mov.b64 {%2,%3},hi;}" : "=r"(v.x), "=r"(v.y), "=r"(v.z), "=r"(v.w) : "l"(p) : "memory");
  return v;
}

__device__ __forceinline__ uint32_t pack_h2(float lo, float hi) {
  uint32_t r; asm("cvt.rn.satfinite.f16x2.f32 %0,%1,%2;" : "=r"(r) : "f"(hi), "f"(lo)); return r;
}
__device__ __forceinline__ void add_h2(float& lo, float& hi, uint32_t u, uint32_t v) {
  float a, b;
  asm("{.reg .b16 l, h; .reg .b32 s; add.rn.f16x2 s,%2,%3; mov.b32 {l,h},s; cvt.f32.f16 %0,l; cvt.f32.f16 %1,h;}" : "=f"(a), "=f"(b) : "r"(u), "r"(v));
  lo += a; hi += b;
}
__device__ __forceinline__ void mwait(uint32_t bar, uint32_t ph, int& spin) {
  asm volatile("{.reg .pred p, q;\nWAIT_LOOP:\n add.s32 %0,%0,1;\n setp.lt.s32 q,%0,%3;\n mbarrier.try_wait.parity.shared::cta.b64 p,[%1],%2;\n not.pred p,p;\n and.pred q,q,p;\n @q bra.uni WAIT_LOOP;\n}"
               : "+&r"(spin) : "r"(bar), "r"(ph), "n"(SPIN_TOT) : "memory");
}
__device__ __forceinline__ int keep(int x) { return __shfl_sync(0xffffffffu, x, threadIdx.x & 31); }
__device__ __forceinline__ uint32_t pin(uint32_t x) { asm volatile("" : "+r"(x)); return x; }
template <typename T> __device__ __forceinline__ T* pinp(T* x) { asm volatile("" : "+l"(x)); return x; }
__device__ __forceinline__ void st_async1u(uint32_t a, uint32_t x, uint32_t bar) {
  asm volatile("st.async.weak.shared::cluster.mbarrier::complete_tx::bytes.b32 [%0],%1,[%2];" ::"r"(a), "r"(x), "r"(bar) : "memory");
}
__device__ __forceinline__ uint32_t lds32(uint32_t a) { uint32_t v; asm volatile("ld.shared.b32 %0,[%1];" : "=r"(v) : "r"(a) : "memory"); return v; }
__device__ __forceinline__ uint2 lds64(uint32_t a) { uint2 v; asm volatile("ld.shared.v2.b32 {%0,%1},[%2];" : "=r"(v.x), "=r"(v.y) : "r"(a) : "memory"); return v; }

__device__ __forceinline__ void permute_cols(uint32_t tile, int tid, int n) {
#pragma unroll 2
  for (int it = tid; it < n; it += 128) {
    const int row = it >> 2, q = it & 3;
    const uint32_t a0 = tile + row * 128 + (((2 * q) ^ (row & 7)) << 4), a1 = tile + row * 128 + (((2 * q + 1) ^ (row & 7)) << 4);
    const uint4 u = lds128(a0), v = lds128(a1);
    sts128(a0, make_uint4(__byte_perm(u.x, u.y, 0x5410), __byte_perm(u.z, u.w, 0x5410), __byte_perm(v.x, v.y, 0x5410), __byte_perm(v.z, v.w, 0x5410)));
    sts128(a1, make_uint4(__byte_perm(u.x, u.y, 0x7632), __byte_perm(u.z, u.w, 0x7632), __byte_perm(v.x, v.y, 0x7632), __byte_perm(v.z, v.w, 0x7632)));
  }
}

__device__ __forceinline__ uint8_t* mkptr(uint32_t lo, uint32_t hi) { uint8_t* p; asm("mov.b64 %0,{%1,%2};" : "=l"(p) : "r"(lo), "r"(hi)); return p; }
__device__ __forceinline__ int uni(int x) { return __shfl_sync(0xffffffffu, x, 0); }

__device__ __forceinline__ bool elect_one() {
  uint32_t p; asm volatile("{.reg .pred q; elect.sync _|q, 0xffffffff; selp.u32 %0,1,0,q;}" : "=r"(p)); return p;
}
__device__ __forceinline__ uint64_t desc_at(uint64_t d, uint32_t off) {
  uint64_t r; asm("mov.b64 %0,{%1,%2};" : "=l"(r) : "r"((uint32_t)d + (off >> 4)), "r"((uint32_t)(d >> 32))); return r;
}
__device__ __forceinline__ uint32_t scale_bf16x2(uint32_t x, uint32_t s) { uint32_t r; asm("mul.rn.bf16x2 %0,%1,%2;" : "=r"(r) : "r"(x), "r"(s)); return r; }

__device__ __forceinline__ void stg128(void* p, const uint4& v) { asm volatile("st.global.v4.b32 [%0],{%1,%2,%3,%4};" ::"l"(p), "r"(v.x), "r"(v.y), "r"(v.z), "r"(v.w) : "memory"); }

__device__ __forceinline__ float quad_sum(float x) {
  const float a = __shfl_xor_sync(0xffffffffu, x, 1), b = __shfl_xor_sync(0xffffffffu, x, 2), c = __shfl_xor_sync(0xffffffffu, x, 3);
  return (x + a) + (b + c);
}
__device__ __forceinline__ float warp_sum(float x) {
  x = quad_sum(x);
  const float a = __shfl_xor_sync(0xffffffffu, x, 4), b = __shfl_xor_sync(0xffffffffu, x, 8), c = __shfl_xor_sync(0xffffffffu, x, 12);
  x = (x + a) + (b + c);
  return x + __shfl_xor_sync(0xffffffffu, x, 16);
}
__device__ __forceinline__ void ln_row(float4 (&v)[5]) {
  float t = 0.f;
#pragma unroll
  for (int m = 0; m < 5; m++) t += (v[m].x + v[m].y) + (v[m].z + v[m].w);
  const float mean = warp_sum(t) * (1.f / DM);
  float q0 = 0.f, q1 = 0.f;
#pragma unroll
  for (int m = 0; m < 5; m++) {
    v[m].x -= mean; v[m].y -= mean; v[m].z -= mean; v[m].w -= mean;
    q0 += v[m].x * v[m].x + v[m].y * v[m].y; q1 += v[m].z * v[m].z + v[m].w * v[m].w;
  }
  const float rs = rsqrtf(warp_sum(q0 + q1) * (1.f / DM) + 1e-5f);
#pragma unroll
  for (int m = 0; m < 5; m++) { v[m].x *= rs; v[m].y *= rs; v[m].z *= rs; v[m].w *= rs; }
}
__device__ __forceinline__ void ln0_load(const bf16* __restrict__ x, uint2 (&u)[5], int row, int lane) {
#pragma unroll
  for (int m = 0; m < 5; m++) u[m] = *reinterpret_cast<const uint2*>(x + (size_t)row * DM + m * 128 + lane * 4);
}
__device__ __forceinline__ void ln0_copy(const uint2 (&u)[5], int row, int lane) {
#pragma unroll
  for (int m = 0; m < 5; m++) stg128(g_x + (size_t)row * DM + m * 128 + lane * 4, make_uint4(u[m].x << 16, u[m].x & 0xFFFF0000u, u[m].y << 16, u[m].y & 0xFFFF0000u));
}
__device__ __forceinline__ void ln0_row(const uint2 (&u)[5], int row, int lane) {
  float4 v[5];
#pragma unroll
  for (int m = 0; m < 5; m++) v[m] = make_float4(bf_lo(u[m].x), bf_hi(u[m].x), bf_lo(u[m].y), bf_hi(u[m].y));
  ln_row(v);
  uint8_t* dst = g_xn[row >> 5] + ((row >> 3) & 3) * 4096 + (lane >> 4) * 1024 + (row & 7) * 128 + ((((lane >> 1) ^ row) & 7) << 4) + (lane & 1) * 8;
#pragma unroll
  for (int m = 0; m < 5; m++) *reinterpret_cast<uint2*>(dst + m * 16384) = make_uint2(pack_bf16(v[m].x, v[m].y), pack_bf16(v[m].z, v[m].w));
}

#define NOWORK 0
__device__ __forceinline__ void prep_row(const uint2 (&u)[5], const bf16* __restrict__ mem0, int k, int r, int lane) {
  const uint4 sent = make_uint4(SENT, SENT, SENT, SENT);
  if (k + 1 < NSTEP) {
    uint8_t* ex = ex_window(g_ex);
#pragma unroll
    for (int h = 0; h < 2; h++) {
      const int p = r * 40 + h * 32 + lane;
      if (h == 0 || lane < 8) {
        uint4 v = sent;
        if (k + 1 == LAG && (p & 8)) v = *reinterpret_cast<const uint4*>(mem0 + (p & 7) * DM + (p >> 4) * 8);
        stg128(ex + EX_M + (k + 1) * 20480 + p * 16, v);
      } else if (lane < 14) stg128(ex + EX_FLAG + (k + 1) * 3072 + (r * 6 + lane - 8) * 16, sent);
    }
  }
  if (k < LAG || k >= NSEG || NOWORK) {
    uint8_t* z = g_xn[k] + (r >> 3) * 4096 + (k < NSEG ? 2048 : 0) + (lane >> 4) * 1024 + (r & 7) * 128 + (lane & 15) * 8;
#pragma unroll
    for (int m = 0; m < 5; m++) *reinterpret_cast<uint2*>(z + m * 16384) = make_uint2(0, 0);
  }
  if (k < NSEG) {
    ln0_copy(u, k * 32 + r, lane);
    ln0_row(u, k * 32 + r, lane);
  }
}
__device__ __forceinline__ void pre_work(const bf16* __restrict__ x, const bf16* __restrict__ mem0, int cta, int tid) {
  constexpr int NT = 96 * 128;
  const int gt = cta * 128 + tid;
  uint8_t* ex = ex_window(g_ex);
#pragma unroll 1
  for (int row = cta + 96 * (tid >> 5); row < (NOWORK == 2 ? NSTEP : NPRE) * 32; row += 384) {
    uint2 u[5];
    ln0_load(x, u, min(row, SEQ - 1), tid & 31);
    prep_row(u, mem0, row >> 5, row & 31, tid & 31);
  }
#pragma unroll 1
  for (int i = gt; i < MAIL_BYTES / 16; i += NT) {
    stg128(ex + EX_MAIL + i * 16, make_uint4(SENT, SENT, SENT, SENT));
    stg128(ex + EX_MAIL + (1 << 20) + i * 16, make_uint4(SENT, SENT, SENT, SENT));
  }
  const int p = NT - 1 - gt;
  if (p < 1280) stg128(ex + EX_M + p * 16, *reinterpret_cast<const uint4*>(mem0 + (p & 7) * DM + (p >> 4) * 8));
  if (p < 192) stg128(ex + EX_FLAG + p * 16, make_uint4(0, 0, 0, 0));
  if (gt < 8 * CN_NUM) stg128(&g_cnt[0][0] + gt * 4, make_uint4(0, 0, 0, 0));
}
__device__ __forceinline__ void pre_wait(int which, uint32_t n, int& spin) {
  uint32_t old;
  asm volatile("atom.acq_rel.gpu.global.add.u32 %0,[%1],1;" : "=r"(old) : "l"(&g_ticket[which][0]) : "memory");
  const uint32_t target = (old / n + 1) * 96;
  while ((int)(ld_acquire(&g_ticket[0][0]) - target) < 0 && spin < SPIN_TOT) spin += 16;
  fence_async_all();
}

namespace C {
constexpr int NKR = 37;
constexpr int OFF_WQ = 0, OFF_WK = 81920;
constexpr int OFF_YO = 163840, OFF_YV = OFF_YO + 6144;
constexpr int OFF_M = 176128;
__host__ __device__ constexpr int og_off(int c) { return c ? OFF_M + 14336 + c * 2048 : 229376; }
constexpr int OFF_KT = 196608;
constexpr int OFF_XT = OFF_KT + 10240;
constexpr int OFF_VT = OFF_XT + 7168;
constexpr int OFF_XM = OFF_VT + 11392;
constexpr int OFF_PT = OFF_XM + 2560;
constexpr int KS = 1280, VS = 1408;
__host__ __device__ constexpr int slot_off(int p) { return p == 2 ? OFF_M : OFF_KT + (p % 3) * 16384; }
constexpr int OFF_ONE = 231424;
constexpr int OFF_BAR = 231552;
constexpr int OFF_SAFE = OFF_BAR + 144;
constexpr int OFF_TS = OFF_BAR + 256;
constexpr int SMEM = 232448;
constexpr uint32_t SB0 = 1024;
constexpr int BAR_F = OFF_BAR, BAR_XM = BAR_F + 40, BAR_XT = BAR_F + 48, BAR_OG = BAR_F + 56, BAR_E = OFF_BAR + 64, BAR_MOK = BAR_E + 40,
              BAR_M = OFF_BAR + 112, BAR_XF = OFF_BAR + 120, BAR_MF = OFF_BAR + 128, FLG_REDO = OFF_BAR + 136, BAR_W = OFF_BAR + 208;
constexpr int NB_PRO = 1, NB_RD = 2, NB_MR = 3, NB_QK = 4, NB_SM = 5, NB_VA = 6, NB_VQ = 7, NB_A = 8, NB_Q = 9, NB_C = 10, NB_WQ = 11, NB_QI = 12, NB_SI = 13, NB_WV = 14, NB_V = 15;
#define B1 600
#define AD0 16
#define AD1 128
#define AD2 16
#define AD3 128
#define BMX 1200
#define B2 800
#define FLP 1
#define OSG 2
#define OST 7
#define NBX 1
#define P1U 4
#define QIE 4
#define SIE 2
#define WOE 1
#define OGF 0
#define VSP 8
#define RFK 5
#define PFD 3
#define WOL 0
constexpr uint32_t SCQ = 0x3A003A00;
constexpr float SCE = 0.07216878364870322f * 1.4426950408889634f * 2048;
}

#define CBAR_SYNC(id, n) bar_sync(id, n)
#define CBAR_ARRIVE(id, n) bar_arrive(id, n)

__device__ __forceinline__ uint64_t wdesc(int off) { return mkdesc(C::SB0 + off, 8192, 1024); }
__device__ __forceinline__ uint64_t mdesc(int k) { return mkdesc_ns(C::SB0 + C::OFF_M + k * 512, 256, 128); }
__device__ __forceinline__ uint64_t tdesc(int k) { return mkdesc(C::SB0 + C::slot_off(k >> 3) + ((k >> 2) & 1) * 1024 + (k & 3) * 32, 16, 2048); }

__device__ __forceinline__ int dh_row(int n) { return (n & ~63) + (n & 32) + ((n >> 1) & 3) * 8 + ((n >> 3) & 3) * 2 + (n & 1); }
template <bool IS_O>
__device__ __forceinline__ void stage_box(const CUtensorMap& tm, uint32_t sb, int p, int cta, int rank) {
  using namespace C;
  const uint32_t bar = sb + BAR_W + 8 * p;
  const int head = cta / 3, col = head * DH + rank * 64;
  mbar_expect_tx(bar, 16384);
  if (!IS_O) tma2d(sb + OFF_WK + p * 16384, &tm, col, p * 128, bar);
  else for (int b = 2 * p - 1; b <= 2 * p; b++)
    tma2d(sb + OFF_WQ + (b + 1) * 8192, &tm, b < 0 ? 576 : (3 * rank + b / 3) * 64, b < 0 ? col : head * DH + ((rank + b) % 3) * 64, bar);
}
template <bool IS_O>
__device__ __forceinline__ void load_weights_rs(uint32_t (&wf)[C::NKR][4], const CUtensorMap& tms, const CUtensorMap& tm, int cta, int rank, uint32_t sb, int tid0, int& spin) {
  using namespace C;
  constexpr int STAGE = IS_O ? OFF_WQ : OFF_WK, YOFF = IS_O ? OFF_YO : OFF_YV, NB = IS_O ? NB_C : NB_V;
  const int i = (tid0 >> 3) & 3, n0 = (tid0 & 7) + (i >> 1) * 8;
  const int chunk = 2 * ((tid0 >> 5) & 3) + (i & 1);
  const int r0 = IS_O ? dh_row(n0) : n0, r1 = IS_O ? dh_row(n0 + 16) : n0 + 16;
  const uint32_t a0 = sb + STAGE + r0 * 128 + ((chunk ^ (r0 & 7)) << 4), a1 = sb + STAGE + r1 * 128 + ((chunk ^ (r1 & 7)) << 4);
#pragma unroll
  for (int p = 0; p < 5; p++) {
    mwait(sb + BAR_W + 8 * p, 0, spin);
    if (IS_O) PTS(8 + p);
    if (p + NBX < 5) { if ((tid0 & 127) == 96) stage_box<IS_O>(tms, sb, p + NBX, cta, rank); __syncwarp(); }
    if (IS_O) permute_cols(sb + STAGE + p * 16384, tid0, 512);
    else {
#pragma unroll 1
      for (int it = tid0 & 127; it < 256; it += 128) {
        const uint32_t base = sb + STAGE + p * 16384 + (it >> 1) * 128;
        const int sw = ((it >> 1) & 7) ^ ((it & 1) * 4);
        const uint4 u0 = lds128(base + (sw << 4)), u1 = lds128(base + ((sw ^ 1) << 4)), u2 = lds128(base + ((sw ^ 2) << 4)), u3 = lds128(base + ((sw ^ 3) << 4));
        sts128(base + (sw << 4), make_uint4(u0.x, u1.x, u2.x, u3.x)); sts128(base + ((sw ^ 1) << 4), make_uint4(u0.y, u1.y, u2.y, u3.y));
        sts128(base + ((sw ^ 2) << 4), make_uint4(u0.z, u1.z, u2.z, u3.z)); sts128(base + ((sw ^ 3) << 4), make_uint4(u0.w, u1.w, u2.w, u3.w));
      }
    }
    bar_sync(NB, 128);
#pragma unroll
    for (int k = 8 * p; k < 8 * p + 8; k++) {
      if (k < NKR) ldsm4t(wf[k < NKR ? k : 0], ((k & 1) ? a1 : a0) + (k >> 1) * 4096);
      else {
        const int n = k * 16 + ((tid0 & 127) >> 3), r = IS_O ? dh_row(n) : n, c = tid0 & 7;
        sts128(sb + YOFF + (n - NKR * 16) * 128 + ((c ^ (n & 7)) << 4), lds128(sb + STAGE + r * 128 + ((c ^ (r & 7)) << 4)));
      }
    }
    fence_async();
    bar_sync(NB, 128);
    if ((tid0 & 127) == 0) {
      mbar_expect_tx(sb + BAR_W + 8 * p, 16384);
      tma2d(sb + STAGE + p * 16384, &tm, (cta / 3) * DH + rank * 64, p * 128, sb + BAR_W + 8 * p);
    }
    __syncwarp();
  }
  PTS(IS_O ? 13 : 14);
  CBAR_SYNC(NB_PRO, 384);
}
template <int STRIDE>
__device__ __forceinline__ void store_mem(const float (&d)[8], uint32_t base, int tid) {
  const int m = (tid >> 3) & 3;
  stsm4(base + (((tid >> 5) & 3) * 2 + (m & 1)) * STRIDE + (m >> 1) * 640 + (tid & 7) * 16, pack_bf16(d[0], d[1]), pack_bf16(d[2], d[3]),
        pack_bf16(d[4], d[5]), pack_bf16(d[6], d[7]));
}

__device__ __forceinline__ void load_pair(uint32_t sb, int i, int p, uint32_t slot, uint32_t ph, int& spin) {
  using namespace C;
  mwait(sb + BAR_E + 8 * p, ph, spin);
  if (elect_one()) bulk_g2s_mc(sb + slot, g_xn[i] + p * 16384, 16384, sb + BAR_F + 8 * p);
}
__device__ __forceinline__ void release_round(uint32_t sb, int p, int lane) {
  if (lane < (p == 2 ? 3 : 1)) mbar_arrive_cluster(mapa(sb, p == 2 ? lane : p) + C::BAR_E + 8 * (3 + p));
}

template <int K0, int K1>
__device__ __forceinline__ void v_mem_pass(float (&d)[8], const uint32_t (&wf)[C::NKR][4]) {
  using namespace C;
  wg_fence();
#pragma unroll
  for (int k = K0; k < K1; k++) {
    if (k < NKR) wgmma_rs16(d, wf[k < NKR ? k : 0], mdesc(k), k != 32);
    else wgmma_ts16(d, wdesc(OFF_YV + (k - NKR) * 2048), mdesc(k), 1);
  }
  wg_commit();
}
__device__ __forceinline__ void chain_v(const CUtensorMap& tmWv, const CUtensorMap& tmWk, const uint32_t sb, const int tid0, const int cta, const int rank) {
  using namespace C;
  asm volatile("setmaxnreg.inc.sync.aligned.u32 208;");
  int spin = 0;
  uint32_t wf[NKR][4];
  const int wu = uni((tid0 >> 5) & 3);
  const uint32_t slot = rank == 2 ? OFF_M : OFF_KT + rank * 16384;
  load_weights_rs<false>(wf, tmWv, tmWk, cta, rank, sb, tid0, spin);
  PTS(5);
#pragma unroll 1
  for (int i = 0; i < NSTEP; i++) {
    {
      float d[32];
      if (i > 0) CBAR_SYNC(NB_WV, 256);
#pragma unroll
      for (int p = 0; p < 5; p++) {
        mwait(sb + BAR_F + 8 * p, i & 1, spin);
        TS(i, 25 + p);
        wg_fence();
#pragma unroll
        for (int k = 8 * p; k < 8 * p + 8; k++) {
          if (k < NKR) wgmma_rs64(d, wf[k < NKR ? k : 0], tdesc(k), k);
          else wgmma_ts64(d, wdesc(OFF_YV + (k - NKR) * 2048), tdesc(k), 1);
          if (k == 8 * p + 1 && p >= 1 && p <= 3) {
            wg_commit(); wg_wait<1>();
            release_round(sb, p - 1, tid0 & 31);
          }
          if (k == 8 * p + RFK && (p == 1 || p == 2)) {
            wg_commit();
            if (rank == p - 1 && wu == 0) load_pair(sb, i, p + 2, slot_off(p + 2), i & 1, spin);
            wg_fence();
          }
        }
        wg_commit();
      }
      wg_wait<0>();
      TS(i, 23);
      CBAR_SYNC(NB_RD, 256);
      const int tid = fresh(tid0) & 127, m = (tid >> 3) & 3;
      if (tid < 8) mbar_expect_tx(sb + BAR_F + 8 * tid, tid < 5 ? 16384 : tid == 5 ? 2560 : tid == 6 ? 7168 : 4096);
      if (tid < 3 && tid != rank) mbar_arrive_cluster(mapa(sb, tid) + BAR_XF);
      const uint32_t a = sb + OFF_VT + 256 + ((tid >> 5) * 2 + (m & 1)) * VS + (m >> 1) * 640 + (tid & 7) * 16;
#pragma unroll
      for (int s = 0; s < 4; s++)
        stsm4(a + s * 128, pack_bf16(d[8 * s], d[8 * s + 1]), pack_bf16(d[8 * s + 2], d[8 * s + 3]),
              pack_bf16(d[8 * s + 4], d[8 * s + 5]), pack_bf16(d[8 * s + 6], d[8 * s + 7]));
      if (tid < 80) sts128(sb + (tid < 72 ? OFF_VT + (tid >> 3) * VS : OFF_PT + 1280) + (tid & 7) * 16, make_uint4(0, 0, 0, 0));
      fence_async();
    }
    mwait(sb + BAR_XF, i & 1, spin);
    CBAR_ARRIVE(NB_QK, 384);
    const uint32_t* xc = &g_cnt[CN_X + i + 1][0];
    const uint32_t xn = i + 1 < LAG || NOWORK ? 16 : 48;
    bool seen = NOWORK == 2 || i + 1 < NPRE;
    if (wu == 0 && !seen) { seen = ld_acquire(xc) >= xn; fence_async_all(); }
    CBAR_SYNC(NB_QI, 256);
    float d[8];
    v_mem_pass<32, 40>(d, wf);
    CBAR_SYNC(NB_SM, 256);
    wg_wait<0>();
    if (__builtin_expect(lds32(sb + FLG_REDO), 0)) { v_mem_pass<32, 40>(d, wf); wg_wait<0>(); }
    if ((tid0 & 31) < 3 && (tid0 & 31) != rank) mbar_arrive_cluster(mapa(sb, tid0 & 31) + BAR_MF);
    v_mem_pass<0, 32>(d, wf);
    wg_wait<0>();
    TS(i, 24);
    const int tid = fresh(tid0);
    if ((tid & 31) == 0) mbar_arrive_cluster(mapa(sb, 2) + BAR_E + 16);
    store_mem<VS>(d, sb + OFF_VT + 128, tid);
    fence_async();
    CBAR_ARRIVE(NB_VA, 256);
    CBAR_ARRIVE(NB_VQ, 256);
    if (wu == 0 && i + 1 < NSTEP) {
      if (__builtin_expect(!seen, 0)) { while (ld_acquire(xc) < xn && spin < SPIN_TOT) spin += 16; fence_async_all(); }
      load_pair(sb, i + 1, rank, slot, i & 1, spin);
      TS(i + 1, 37);
    }
    TS_FLUSH(i - 1);
    __syncwarp();
  }
  CBAR_ARRIVE(NB_WV, 256);
  if (spin >= SPIN_TOT) g_err = 3;
}

__device__ __forceinline__ float quad_max(float x) {
  const float a = __shfl_xor_sync(0xffffffffu, x, 1), b = __shfl_xor_sync(0xffffffffu, x, 2), c = __shfl_xor_sync(0xffffffffu, x, 3);
  return fmaxf(fmaxf(x, a), fmaxf(b, c));
}
__device__ __forceinline__ float max10(const float (&y)[10]) {
  return fmaxf(fmaxf(fmaxf(fmaxf(y[0], y[1]), fmaxf(y[2], y[3])), fmaxf(fmaxf(y[4], y[5]), fmaxf(y[6], y[7]))), fmaxf(y[8], y[9]));
}
__device__ __forceinline__ float sum10(const float (&y)[10]) {
  return (((y[0] + y[1]) + (y[2] + y[3])) + ((y[4] + y[5]) + (y[6] + y[7]))) + (y[8] + y[9]);
}
__device__ __forceinline__ float rcp(float x) { float y; asm("rcp.approx.ftz.f32 %0,%1;" : "=f"(y) : "f"(x)); return y; }

__device__ __forceinline__ void signal_o(int i, int cta) { csignal(CN_O + i * 5 + min(cta / 19, 4)); }

__device__ __forceinline__ void chain_q(const bf16* x0, const bf16* mem0, const uint32_t sb, const int tid0, const int cta, const int rank) {
  using namespace C;
  asm volatile("setmaxnreg.dec.sync.aligned.u32 96;");
  int spin = 0;
  PTS(0);
  pre_work(x0, mem0, cta, tid0 & 127);
  PTS(3);
  CBAR_SYNC(NB_Q, 128);
  PTS(2);
  if (tid0 < 160) {
    if (tid0 == 128) pre_wait(0, 96, spin);
    __syncwarp();
    load_pair(sb, 0, rank, rank == 2 ? OFF_M : OFF_KT + rank * 16384, 1, spin);
  }
  PTS(4);
  CBAR_SYNC(NB_PRO, 384);
  mwait(sb + BAR_W, 1, spin);
  PTS(6);
  const int wu = uni((tid0 >> 5) & 3);
  uint4 ov[4] = {};
  uint8_t* op = &g_o[ORING - 1][cta][(tid0 & 124) * 32];
  const uint32_t o0 = ((tid0 ^ (tid0 >> 2)) & 3) * 16 + (tid0 & 16) * 4;
#pragma unroll 1
  for (int i = 0; i < NSTEP; i++) {
    const int ph = i & 1;
    uint32_t qf[4][4];
    {
      float d[64];
#define QK_STEP(K, SC) wgmma_st128(d, desc_at(mkdesc(SB0 + ((K) >> 2) * 1024 + ((K) & 3) * 32, 16, 2048), so), \
                                   desc_at(mkdesc(SB0 + OFF_WQ + (K) * 2048, OFF_WK - OFF_WQ, 1024), p * 16384), SC)
      int p = 0;
      uint32_t so = OFF_KT;
      mwait(sb + BAR_F, ph, spin);
      TS(i, 0);
      wg_fence();
#pragma unroll
      for (int k = 0; k < 8; k++) {
        QK_STEP(k, k);
        if (k == OST) {
          wg_commit();
          mwait(sb + BAR_F, ph, spin);
#pragma unroll
          for (int h = 0; h < 4; h++) stg128(op + (h & 1) * 4096 + (o0 ^ ((h >> 1) * 64)), ov[h]);
          if (i > 0) CBAR_ARRIVE(NB_MR, 160);
          if (k < 7) wg_fence();
        }
      }
      if (OST < 7) wg_commit();
#pragma unroll 1
      for (p = 1; p < 5; p++) {
        static_assert(OFF_KT - OFF_M == 5 << 12, "");
        so = OFF_M + (((0x95095u >> (4 * p)) & 15) << 12);
        if (i == 0) { mwait(sb + BAR_W + 8 * p, 1, spin); PTS(14 + p); }
        mwait(sb + BAR_F + 8 * p, ph, spin);
        wg_fence();
#pragma unroll
        for (int k = 0; k < 8; k++) {
          QK_STEP(k, 1);
          if (k == 1) {
            wg_commit(); wg_wait<1>();
            release_round(sb, p - 1, p < 4 ? tid0 & 31 : 32);
          }
        }
        wg_commit();
      }
#undef QK_STEP
      wg_wait<0>();
      TS(i, 1);
      CBAR_SYNC(NB_RD, 256);
      TSB(i, 2);
      const int tid = fresh(tid0), w = (tid >> 5) & 3, m = (tid >> 3) & 3;
      const uint32_t a = sb + OFF_KT + (m >> 1) * KS + (1 + w + 5 * (m & 1)) * 128 + (tid & 7) * 16;
#pragma unroll
      for (int s = 0; s < 4; s++)
        stsm4t(a + s * 2 * KS, pack_bf16(d[32 + 8 * s], d[33 + 8 * s]), pack_bf16(d[34 + 8 * s], d[35 + 8 * s]),
               pack_bf16(d[36 + 8 * s], d[37 + 8 * s]), pack_bf16(d[38 + 8 * s], d[39 + 8 * s]));
      fence_async();
      CBAR_ARRIVE(NB_QK, 384);
#pragma unroll
      for (int kk = 0; kk < 4; kk++)
#pragma unroll
        for (int j = 0; j < 4; j++) asm volatile("{.reg .b32 t; cvt.rn.bf16x2.f32 t,%1,%2; mul.rn.bf16x2 %0,t,%3;}" : "=r"(qf[kk][j]) : "f"(d[8 * kk + 2 * j + 1]), "f"(d[8 * kk + 2 * j]), "r"(SCQ));
    }
    CBAR_SYNC(NB_SI, 256);
    uint32_t pf[5][4];
    {
      float y0[10], y1[10];
      const int tidf = fresh(tid0), lane = tidf & 31;
      {
        float x[40];
        wg_fence();
#pragma unroll
        for (int kk = 0; kk < 4; kk++) wgmma_rt80(x, qf[kk], mkdesc_ns(SB0 + OFF_KT + kk * 2 * KS, KS, 128), kk);
        wg_commit();
        wg_wait<0>();
#pragma unroll
        for (int j = 0; j < 5; j++) { y0[2 * j] = x[4 * j]; y0[2 * j + 1] = x[4 * j + 1]; y1[2 * j] = x[22 + 4 * j]; y1[2 * j + 1] = x[23 + 4 * j]; }
      }
      TS(i, 17);
      const uint32_t xo = OFF_XT + (wu * (wu + 3) / 2) * 256 + lane * 16, x2 = xo + (wu >> 1) * 512 + 512 - lane * 8;
      {
        const uint4 h0 = make_uint4(pack_h2(y0[0], y0[1]), pack_h2(y1[0], y1[1]), pack_h2(y0[2], y0[3]), pack_h2(y1[2], y1[3]));
        const uint4 h1 = make_uint4(pack_h2(y0[4], y0[5]), pack_h2(y1[4], y1[5]), pack_h2(y0[6], y0[7]), pack_h2(y1[6], y1[7]));
        const uint32_t h2 = wu == 1 ? h1.x : pack_h2(y0[8], y0[9]), h3 = wu == 1 ? h1.y : pack_h2(y1[8], y1[9]);
        const uint32_t rb1 = mapa(sb, (rank + 1) % 3), rb2 = mapa(sb, (rank + 2) % 3);
        st_async4u(rb1 + xo + 3584, h0, rb1 + BAR_XT);
        st_async4u(rb2 + xo, h0, rb2 + BAR_XT);
        if (wu >= 2) { st_async4u(rb1 + xo + 4096, h1, rb1 + BAR_XT); st_async4u(rb2 + xo + 512, h1, rb2 + BAR_XT); }
        if (wu & 1) { st_async2u(rb1 + x2 + 3584, h2, h3, rb1 + BAR_XT); st_async2u(rb2 + x2, h2, h3, rb2 + BAR_XT); }
      }
      TS(i, 18);
      const int lim = 8 * wu + (lane >> 2) + 8 - 2 * (lane & 3);
#pragma unroll
      for (int j = 2; j < 10; j++)
        if (8 * (j >> 1) + (j & 1) > lim) { y0[j] = -INFINITY; y1[j] = -INFINITY; }
      mwait(sb + BAR_XT, ph, spin);
      TS(i, 19);
      {
        const uint4 u0 = lds128(sb + xo), v0 = lds128(sb + xo + 3584);
        uint2 u2 = make_uint2(0, 0), v2 = u2;
        if (wu & 1) { u2 = lds64(sb + x2); v2 = lds64(sb + x2 + 3584); }
        uint4 u1 = make_uint4(u2.x, u2.y, 0, 0), v1 = make_uint4(v2.x, v2.y, 0, 0);
        if (wu >= 2) { u1 = lds128(sb + xo + 512); v1 = lds128(sb + xo + 4096); }
        __syncwarp();
        if (lane == 0) mbar_arrive_cluster(mapa(sb, 0) + BAR_E);
        add_h2(y0[0], y0[1], u0.x, v0.x); add_h2(y1[0], y1[1], u0.y, v0.y); add_h2(y0[2], y0[3], u0.z, v0.z); add_h2(y1[2], y1[3], u0.w, v0.w);
        add_h2(y0[4], y0[5], u1.x, v1.x); add_h2(y1[4], y1[5], u1.y, v1.y); add_h2(y0[6], y0[7], u1.z, v1.z); add_h2(y1[6], y1[7], u1.w, v1.w);
        add_h2(y0[8], y0[9], u2.x, v2.x); add_h2(y1[8], y1[9], u2.y, v2.y);
      }
      const float m0 = quad_max(max10(y0)) * -SCE, m1 = quad_max(max10(y1)) * -SCE;
#pragma unroll
      for (int j = 0; j < 5; j++) {
        pf[j >> 1][2 * (j & 1)] = pack_bf16(ex2(fmaf(y0[2 * j], SCE, m0)), ex2(fmaf(y0[2 * j + 1], SCE, m0)));
        pf[j >> 1][2 * (j & 1) + 1] = tidf >> (10 + j);
        pf[(j + 5) >> 1][2 * ((j + 5) & 1)] = tidf >> (20 + j);
        pf[(j + 5) >> 1][2 * ((j + 5) & 1) + 1] = pack_bf16(ex2(fmaf(y1[2 * j], SCE, m1)), ex2(fmaf(y1[2 * j + 1], SCE, m1)));
      }
    }
#pragma unroll
    for (int q = 0; q < 20; q++) pf[q >> 2][q & 3] = pin(pf[q >> 2][q & 3]);
    CBAR_SYNC(NB_VQ, 256);
    TSB(i, 20);
    {
      float o[32], sm[4];
      wg_fence();
#pragma unroll
      for (int q = 0; q < 5; q++) wgmma_rs8(sm, pf[q], mkdesc_ns(SB0 + OFF_ONE, 0, 0), q);
#pragma unroll
      for (int q = 0; q < 5; q++) wgmma_rs64(o, pf[q], mkdesc_ns(SB0 + OFF_VT + 128 + q * 256, 128, VS), q);
      wg_commit();
      const int tid = fresh(tid0);
      op = &g_o[i % ORING][cta][(tid & 124) * 32];
      wg_wait<0>();
      TS(i, 21);
      if ((tid & 31) == 0) mbar_arrive_cluster(mapa(sb, 1) + BAR_E + 8);
      const float s0 = rcp(sm[0]), s1 = rcp(sm[2]);
#pragma unroll
      for (int h = 0; h < 2; h++) {
        const float* x = o + 16 * h;
        ov[2 * h] = make_uint4(pin(pack_bf16(x[0] * s0, x[1] * s0)), pin(pack_bf16(x[4] * s0, x[5] * s0)), pin(pack_bf16(x[8] * s0, x[9] * s0)), pin(pack_bf16(x[12] * s0, x[13] * s0)));
        ov[2 * h + 1] = make_uint4(pin(pack_bf16(x[2] * s1, x[3] * s1)), pin(pack_bf16(x[6] * s1, x[7] * s1)), pin(pack_bf16(x[10] * s1, x[11] * s1)), pin(pack_bf16(x[14] * s1, x[15] * s1)));
      }
      TS(i, 22);
      if (i + 1 < NSTEP) CBAR_SYNC(NB_WQ, 256); else CBAR_ARRIVE(NB_WQ, 256);
    }
  }
#pragma unroll
  for (int h = 0; h < 4; h++) stg128(op + (h & 1) * 4096 + (o0 ^ ((h >> 1) * 64)), ov[h]);
  CBAR_SYNC(NB_Q, 128);
  if (tid0 == 224) signal_o(NSTEP - 1, cta);
  if (spin >= SPIN_TOT) g_err = 2;
}

template <int NL> __device__ __forceinline__ void poll(uint4 (&x)[NL], const uint8_t* mb, uint32_t tag, int& spin);
template <> __device__ __forceinline__ void poll<4>(uint4 (&x)[4], const uint8_t* mb, uint32_t tag, int& spin) {
  asm volatile("{.reg .pred p<6>, q; .reg .b128 v; .reg .b32 t;\n"
               " ld.relaxed.gpu.global.b128 v,[%17+0]; mov.b128 {%0,%1,%2,%3},v;\n"
               " ld.relaxed.gpu.global.b128 v,[%17+512]; mov.b128 {%4,%5,%6,%7},v;\n"
               " ld.relaxed.gpu.global.b128 v,[%17+1024]; mov.b128 {%8,%9,%10,%11},v;\n"
               " ld.relaxed.gpu.global.b128 v,[%17+1536]; mov.b128 {%12,%13,%14,%15},v;\n"
               "POLL_LOOP:\n add.s32 %16,%16,16;\n"
               " lop3.b32 t,%0,%18,1,0x28; setp.ne.b32 p0,t,0;\n"
               " lop3.b32 t,%4,%18,1,0x28; setp.ne.b32 p1,t,0;\n"
               " lop3.b32 t,%8,%18,1,0x28; setp.ne.b32 p2,t,0;\n"
               " lop3.b32 t,%12,%18,1,0x28; setp.ne.b32 p3,t,0;\n"
               " or.pred q,p0,p1; or.pred q,q,p2; or.pred q,q,p3; setp.lt.and.s32 q,%16,%19,q; vote.sync.any.pred q,q,0xffffffff;\n"
               " mov.b128 v,{%0,%1,%2,%3}; @p0 ld.relaxed.gpu.global.b128 v,[%17+0]; mov.b128 {%0,%1,%2,%3},v;\n"
               " mov.b128 v,{%4,%5,%6,%7}; @p1 ld.relaxed.gpu.global.b128 v,[%17+512]; mov.b128 {%4,%5,%6,%7},v;\n"
               " mov.b128 v,{%8,%9,%10,%11}; @p2 ld.relaxed.gpu.global.b128 v,[%17+1024]; mov.b128 {%8,%9,%10,%11},v;\n"
               " mov.b128 v,{%12,%13,%14,%15}; @p3 ld.relaxed.gpu.global.b128 v,[%17+1536]; mov.b128 {%12,%13,%14,%15},v;\n"
               " @q bra.uni POLL_LOOP;\n}"
               : "=&r"(x[0].x), "=&r"(x[0].y), "=&r"(x[0].z), "=&r"(x[0].w), "=&r"(x[1].x), "=&r"(x[1].y), "=&r"(x[1].z), "=&r"(x[1].w), "=&r"(x[2].x), "=&r"(x[2].y), "=&r"(x[2].z), "=&r"(x[2].w), "=&r"(x[3].x), "=&r"(x[3].y), "=&r"(x[3].z), "=&r"(x[3].w), "+&r"(spin)
               : "l"(mb), "r"(tag), "n"(SPIN_TOT) : "memory");
}
template <> __device__ __forceinline__ void poll<6>(uint4 (&x)[6], const uint8_t* mb, uint32_t tag, int& spin) {
  asm volatile("{.reg .pred p<6>, q; .reg .b128 v; .reg .b32 t;\n"
               " ld.relaxed.gpu.global.b128 v,[%25+0]; mov.b128 {%0,%1,%2,%3},v;\n"
               " ld.relaxed.gpu.global.b128 v,[%25+512]; mov.b128 {%4,%5,%6,%7},v;\n"
               " ld.relaxed.gpu.global.b128 v,[%25+1024]; mov.b128 {%8,%9,%10,%11},v;\n"
               " ld.relaxed.gpu.global.b128 v,[%25+1536]; mov.b128 {%12,%13,%14,%15},v;\n"
               " ld.relaxed.gpu.global.b128 v,[%25+2048]; mov.b128 {%16,%17,%18,%19},v;\n"
               " ld.relaxed.gpu.global.b128 v,[%25+2560]; mov.b128 {%20,%21,%22,%23},v;\n"
               "POLL_LOOP:\n add.s32 %24,%24,16;\n"
               " lop3.b32 t,%0,%2,%26,0x7e; and.b32 t,t,1; setp.ne.b32 p0,t,0;\n"
               " lop3.b32 t,%4,%6,%26,0x7e; and.b32 t,t,1; setp.ne.b32 p1,t,0;\n"
               " lop3.b32 t,%8,%10,%26,0x7e; and.b32 t,t,1; setp.ne.b32 p2,t,0;\n"
               " lop3.b32 t,%12,%14,%26,0x7e; and.b32 t,t,1; setp.ne.b32 p3,t,0;\n"
               " lop3.b32 t,%16,%18,%26,0x7e; and.b32 t,t,1; setp.ne.b32 p4,t,0;\n"
               " lop3.b32 t,%20,%22,%26,0x7e; and.b32 t,t,1; setp.ne.b32 p5,t,0;\n"
               " or.pred q,p0,p1; or.pred q,q,p2; or.pred q,q,p3; or.pred q,q,p4; or.pred q,q,p5; setp.lt.and.s32 q,%24,%27,q; vote.sync.any.pred q,q,0xffffffff;\n"
               " mov.b128 v,{%0,%1,%2,%3}; @p0 ld.relaxed.gpu.global.b128 v,[%25+0]; mov.b128 {%0,%1,%2,%3},v;\n"
               " mov.b128 v,{%4,%5,%6,%7}; @p1 ld.relaxed.gpu.global.b128 v,[%25+512]; mov.b128 {%4,%5,%6,%7},v;\n"
               " mov.b128 v,{%8,%9,%10,%11}; @p2 ld.relaxed.gpu.global.b128 v,[%25+1024]; mov.b128 {%8,%9,%10,%11},v;\n"
               " mov.b128 v,{%12,%13,%14,%15}; @p3 ld.relaxed.gpu.global.b128 v,[%25+1536]; mov.b128 {%12,%13,%14,%15},v;\n"
               " mov.b128 v,{%16,%17,%18,%19}; @p4 ld.relaxed.gpu.global.b128 v,[%25+2048]; mov.b128 {%16,%17,%18,%19},v;\n"
               " mov.b128 v,{%20,%21,%22,%23}; @p5 ld.relaxed.gpu.global.b128 v,[%25+2560]; mov.b128 {%20,%21,%22,%23},v;\n"
               " @q bra.uni POLL_LOOP;\n}"
               : "=&r"(x[0].x), "=&r"(x[0].y), "=&r"(x[0].z), "=&r"(x[0].w), "=&r"(x[1].x), "=&r"(x[1].y), "=&r"(x[1].z), "=&r"(x[1].w), "=&r"(x[2].x), "=&r"(x[2].y), "=&r"(x[2].z), "=&r"(x[2].w), "=&r"(x[3].x), "=&r"(x[3].y), "=&r"(x[3].z), "=&r"(x[3].w), "=&r"(x[4].x), "=&r"(x[4].y), "=&r"(x[4].z), "=&r"(x[4].w), "=&r"(x[5].x), "=&r"(x[5].y), "=&r"(x[5].z), "=&r"(x[5].w), "+&r"(spin)
               : "l"(mb), "r"(tag), "n"(SPIN_TOT) : "memory");
}
template <int NL>
__device__ __forceinline__ void poll_add(const uint8_t* mb, uint32_t tag, float (&f)[8], uint8_t* flag, bool lead, int& spin) {
  uint4 x[NL];
  poll<NL>(x, mb, tag, spin);
  if (FLP == 0 && lead) st_relaxed(flag, 0);
#pragma unroll
  for (int i = 0; i < NL; i++) {
    const uint32_t u[4] = {x[i].x, x[i].y, x[i].z, x[i].w};
#pragma unroll
    for (int j = 0; j < 4; j++) {
      if (i == 0) { f[2 * j] = bf_lo(u[j]); f[2 * j + 1] = bf_hi(u[j]); }
      else { f[2 * j] += bf_lo(u[j]); f[2 * j + 1] += bf_hi(u[j]); }
    }
  }
}

template <int B, int SLOT>
__device__ __forceinline__ void wo_step(float (&acc)[8], const uint32_t (&wf)[C::NKR][4], int kk) {
  using namespace C;
  const int k = 4 * B + kk;
  const uint64_t db = mkdesc_ns(SB0 + og_off(SLOT) + kk * 512, 256, 128);
  if (k < NKR) wgmma_rt16(acc, wf[k < NKR ? k : 0], db, SLOT | kk);
  else wgmma_tt16(acc, wdesc(OFF_YO + (k - NKR) * 2048), db, 1);
}
template <int B, int SLOT>
__device__ __forceinline__ void wo_block(float (&acc)[8], const uint32_t (&wf)[C::NKR][4]) {
#pragma unroll
  for (int kk = 0; kk < 4; kk++) wo_step<B, SLOT>(acc, wf, kk);
}

__device__ __forceinline__ void chain_a(const CUtensorMap& tmWo, const CUtensorMap& tmWq, const uint32_t sb, const int tid0, const int cta, const int rank) {
  using namespace C;
  asm volatile("setmaxnreg.inc.sync.aligned.u32 200;");
  int spin = 0;
  uint32_t wf[NKR][4];
  load_weights_rs<true>(wf, tmWo, tmWq, cta, rank, sb, tid0, spin);
  const int wu = uni(tid0 >> 5);
  const bool t9 = cta >= 72 && cta < 88;
  const uint64_t exa = reinterpret_cast<uint64_t>(ex_window(g_ex));
  const uint32_t ehi = (uint32_t)(exa >> 32), elo = (uint32_t)exa;

  int b1 = B1, b2 = B2;
#pragma unroll 1
  for (int i = -1; i < NSTEP; i++) {
    const int ph = i & 1;
    if (i >= 0) {
      const int tid = fresh(tid0);
      const uint32_t mo = __shfl_xor_sync(0xffffffffu, elo + (ph << 20) + ((rank * 24 + (tid >> 4)) * 4 + (tid & 3)) * 2048 + (cta / 3) * 64 + (tid & 12) * 4, 0);
      const uint32_t m9 = __shfl_xor_sync(0xffffffffu, elo + (ph << 20) + MAIL9 + (((tid >> 4) * 2 + (tid & 1)) * 4 + (tid & 2)) * 3072 + cta * 32 + (tid & 12) * 2, 0);
      const uint32_t oo = __shfl_xor_sync(0xffffffffu, (tid >> 5) * 512 + (tid & 2) * 64 + (tid & 28) * 4 + (tid & 1) * 8, 0);
      if (i == 0) { mwait(sb + BAR_W + 24, 1, spin); mwait(sb + BAR_W + 32, 1, spin); PTS(7); }
      mwait(sb + BAR_M, ph, spin);
      TS(i, 3);
      {
        float x[20];
        int redo = 0;
      retry:
        bool bad;
        {
          float dq[8] = {}, dk[8] = {};
#pragma unroll 1
          for (int k0 = 0; k0 < 40; k0 += P1U) {
            wg_fence();
#pragma unroll
            for (int k = 0; k < P1U; k++) {
              if (k == P1U - QIE / 2 && k0 == 40 - P1U && !redo) CBAR_ARRIVE(NB_QI, 256);
              const uint64_t db = desc_at(mdesc(k), k0 * 512);
              wgmma_ts16(dq, desc_at(wdesc(OFF_WQ + k * 2048), k0 * 2048), db, 1);
              wgmma_ts16(dk, desc_at(wdesc(OFF_WK + k * 2048), k0 * 2048), db, 1);
            }
            wg_commit();
          }
          const int m = (tid >> 3) & 3, dg = (tid >> 5) * 2 + (m & 1);
          const uint32_t ka = sb + OFF_KT + dg * KS + (m >> 1) * 640 + (tid & 7) * 16;
          if (!redo) CBAR_SYNC(NB_QK, 384);
          sts32(sb + FLG_REDO, redo);
          wg_wait<0>();
          TS(i, 4);
          stsm4(ka, pack_bf16(dk[0], dk[1]), pack_bf16(dk[2], dk[3]), pack_bf16(dk[4], dk[5]), pack_bf16(dk[6], dk[7]));
          stsm4(ka + dg * (VS - KS) + (OFF_VT + 128 - OFF_KT), scale_bf16x2(pack_bf16(dq[0], dq[1]), SCQ), scale_bf16x2(pack_bf16(dq[2], dq[3]), SCQ),
                scale_bf16x2(pack_bf16(dq[4], dq[5]), SCQ), scale_bf16x2(pack_bf16(dq[6], dq[7]), SCQ));
          const float chk = (dq[0] + dq[1]) + (dq[4] + dq[5]);
          fence_async();
          bad = bar_red_or(NB_C, 128, chk != chk && !redo);
        }
        TSB(i, 5);
        wg_fence();
#pragma unroll
        for (int kk = 0; kk < 4; kk++) wgmma_tt40(x, mkdesc_ns(SB0 + OFF_VT + 128 + kk * 2 * VS, VS, 640), mkdesc_ns(SB0 + OFF_KT + kk * 2 * KS, KS, 128), kk);
#pragma unroll
        for (int kk = 0; kk < 4; kk++) {
          if (SIE && kk == 4 - SIE && !bad) CBAR_ARRIVE(NB_SI, 256);
          wgmma_tt40(x, mkdesc_ns(SB0 + OFF_VT + kk * 2 * VS, VS, 384), mkdesc_ns(SB0 + OFF_KT + 640 + kk * 2 * KS, KS, 128), 1);
        }
        wg_commit();
        if (!SIE && !bad) CBAR_ARRIVE(NB_SI, 256);
        if (__builtin_expect(__any_sync(0xffffffffu, bad), 0)) {
          wg_wait<0>();
#pragma unroll 1
          for (int k = 0; k < 10; k++) {
            uint4 v = lds128(sb + OFF_M + tid * 16 + k * 2048);
            if (v.x == SENT || v.y == SENT || v.z == SENT || v.w == SENT) {
              do { v = ld_relaxed4(mkptr(elo + EX_M + i * 20480 + tid * 16 + k * 2048, ehi)); spin += 16; } while ((v.x == SENT || v.y == SENT || v.z == SENT || v.w == SENT) && spin < SPIN_TOT);
              sts128(sb + OFF_M + tid * 16 + k * 2048, v);
            }
          }
          fence_async();
          bar_sync(NB_C, 128);
          redo = fresh(1);
          goto retry;
        }
        TSV(i, 36, redo);
        const uint32_t rb1 = mapa(sb, (rank + 1) % 3), rb2 = mapa(sb, (rank + 2) % 3);
        wg_wait<0>();
        TS(i, 6);
        if (wu < 2) {
          float y[10];
#pragma unroll
          for (int j = 0; j < 5; j++) { y[2 * j] = x[4 * j]; y[2 * j + 1] = x[4 * j + 1]; }
          const uint4 h0 = make_uint4(pack_h2(y[0], y[1]), pack_h2(y[2], y[3]), pack_h2(y[4], y[5]), pack_h2(y[6], y[7]));
          const uint32_t h1 = pack_h2(y[8], y[9]);
          st_async4u(rb1 + OFF_XM + 1024 + tid * 16, h0, rb1 + BAR_XM);
          st_async4u(rb2 + OFF_XM + tid * 16, h0, rb2 + BAR_XM);
          st_async1u(rb1 + OFF_XM + 2304 + tid * 4, h1, rb1 + BAR_XM);
          st_async1u(rb2 + OFF_XM + 2048 + tid * 4, h1, rb2 + BAR_XM);
          CBAR_ARRIVE(NB_SM, 256);
          if ((tid & 31) == 0) mbar_arrive_cluster(mapa(sb, 0) + BAR_E);
          TS(i, 7);
          const uint32_t sw = (tid & 7) * 4 + (tid & 8) * 8 + (tid & 16) * 2;
          mwait(sb + BAR_XM, ph, spin);
          TS(i, 8);
          const uint4 u0 = lds128(sb + OFF_XM + tid * 16), v0 = lds128(sb + OFF_XM + 1024 + tid * 16);
          const uint32_t u1 = lds32(sb + OFF_XM + 2048 + tid * 4), v1 = lds32(sb + OFF_XM + 2304 + tid * 4);
          add_h2(y[0], y[1], u0.x, v0.x); add_h2(y[2], y[3], u0.y, v0.y); add_h2(y[4], y[5], u0.z, v0.z); add_h2(y[6], y[7], u0.w, v0.w);
          add_h2(y[8], y[9], u1, v1);
          const float mx = quad_max(max10(y)) * -SCE;
#pragma unroll
          for (int j = 0; j < 5; j++) {
            y[2 * j] = ex2(fmaf(y[2 * j], SCE, mx)); y[2 * j + 1] = ex2(fmaf(y[2 * j + 1], SCE, mx));
            sts32(sb + OFF_PT + wu * 640 + sw + j * 128, pack_bf16(y[2 * j], y[2 * j + 1]));
          }
          sts32(sb + OFF_XM + 2048 + wu * 128 + sw, __float_as_uint(sum10(y)));
          fence_async();
          TS(i, 9);
        } else {
          CBAR_ARRIVE(NB_SM, 256);
          if ((tid & 31) == 0) mbar_arrive_cluster(mapa(sb, 0) + BAR_E);
          mwait(sb + BAR_MF, ph, spin);
        }
      }
      CBAR_SYNC(NB_VA, 256);
      TSB(i, 10);
      {
        float o[2][4];
        wg_fence();
#pragma unroll
        for (int c = 0; c < 2; c++)
#pragma unroll
          for (int q = 0; q < 3; q++)
            wgmma_ss8(o[c], mkdesc_ns(SB0 + OFF_VT + 128 + c * 640 + q * 256, 128, VS), mkdesc_ns(SB0 + OFF_PT + c * 640 + q * 256, q == 2 && c == 0 ? 768 : 128, 128), q);
        wg_commit();
        const float4 e = lds128f(sb + OFF_XM + 2048 + (tid & 15) * 16);
        const uint32_t rb1 = mapa(sb, (rank + 1) % 3), rb2 = mapa(sb, (rank + 2) % 3);
        const float inv = rcp((e.x + e.y) + (e.z + e.w));
        const int sl = (tid & 3) * 2;
        const float i0 = __shfl_sync(0xffffffffu, inv, sl), i1 = __shfl_sync(0xffffffffu, inv, sl + 1);
        const float i2 = __shfl_sync(0xffffffffu, inv, sl + 8), i3 = __shfl_sync(0xffffffffu, inv, sl + 9);
        wg_wait<0>();
        TS(i, 11);
        const uint32_t p0 = pack_bf16(o[0][0] * i0, o[0][1] * i1), p1 = pack_bf16(o[1][0] * i2, o[1][1] * i3);
        const uint32_t p2 = pack_bf16(o[0][2] * i0, o[0][3] * i1), p3 = pack_bf16(o[1][2] * i2, o[1][3] * i3);
        if (OGF) { sts64(sb + oo + og_off(0), p0, p1); sts64(sb + oo + og_off(0) + 256, p2, p3); fence_async(); }
        st_async2u(rb1 + oo + og_off(2), p0, p1, rb1 + BAR_OG);
        st_async2u(rb2 + oo + og_off(1), p0, p1, rb2 + BAR_OG);
        st_async2u(rb1 + oo + og_off(2) + 256, p2, p3, rb1 + BAR_OG);
        st_async2u(rb2 + oo + og_off(1) + 256, p2, p3, rb2 + BAR_OG);
        if (!OGF) { sts64(sb + oo + og_off(0), p0, p1); sts64(sb + oo + og_off(0) + 256, p2, p3); fence_async(); }
      }
      CBAR_SYNC(NB_A, 128);
      TSB(i, 12);
      {
        float acc[3][8];
        wg_fence();
        wo_block<0, 0>(acc[2], wf);
        wg_commit();
        if (tid == 0) mbar_arrive_cluster(mapa(sb, 1) + BAR_E + 8);
        wo_block<1, 0>(acc[0], wf);
        wo_block<4, 0>(acc[1], wf);
        wg_commit();
        const uint32_t tag = (i >> 1) & 1;
#define TAGGED(LO, HI) ((pack_bf16(LO, HI) & ~1u) | tag)
#define SEND(OFF, U) st_relaxed128(mkptr(mo, ehi) + (OFF), TAGGED(acc[U][0], acc[U][2]), pack_bf16(acc[U][1], acc[U][3]), pack_bf16(acc[U][4], acc[U][6]), pack_bf16(acc[U][5], acc[U][7]))
        wg_wait<1>();
        const uint32_t n0 = pin(TAGGED(acc[2][0], acc[2][2])), n1 = pin(pack_bf16(acc[2][1], acc[2][3]));
        const uint32_t n2 = pin(TAGGED(acc[2][4], acc[2][6])), n3 = pin(pack_bf16(acc[2][5], acc[2][7]));
        wg_fence();
        wo_block<7, 0>(acc[2], wf);
        wg_commit();
        st_relaxed64(mkptr(m9, ehi), n0, n1);
        st_relaxed64(mkptr(m9, ehi) + 3072, n2, n3);
        mwait(sb + BAR_OG, ph, spin);
        asm volatile("fence.proxy.async::generic.acquire.sync_restrict::shared::cluster.cluster;" ::: "memory");
        TS(i, 13);
        wg_fence();
        wo_block<2, 1>(acc[0], wf); wo_block<3, 2>(acc[0], wf);
        wg_commit();
        wo_block<5, 1>(acc[1], wf); wo_block<6, 2>(acc[1], wf);
        wg_commit();
        wg_wait<1>(); SEND(0, 0);
        wo_block<8, 1>(acc[2], wf); wo_block<9, 2>(acc[2], wf);
        wg_commit();
        if (WOE == 0) { CBAR_ARRIVE(NB_WV, 256); CBAR_ARRIVE(NB_WQ, 256); }
        wg_wait<1>(); SEND(32 * 2048, 1);
        if (WOE == 1) CBAR_ARRIVE(NB_WV, 256);
        wg_wait<0>(); SEND(64 * 2048, 2);
        if (WOE == 2) CBAR_ARRIVE(NB_WV, 256);
        if (WOE >= 1) CBAR_ARRIVE(NB_WQ, 256);
#undef SEND
#undef TAGGED
      }
      TS(i, 14);
      if (i < 2) PTS(19 + i);
      if (i + 1 >= NSTEP) break;
    }
    uint32_t t1 = clk32();
    if (i >= 0) {
      const int lane = fresh(tid0) & 31, j = lane >> 3;
      const uint8_t* mb = mkptr(elo + (ph << 20) + (t9 ? MAIL9 + (cta - 72) * 12288 + wu * 3072 : (cta < 72 ? cta : cta - 24) * 8192 + wu * 2048) + lane * 16, ehi);
      const uint32_t tag = (i >> 1) & 1;
      const bool pub = (lane & (t9 ? 6 : 4)) == 0 && !(((t9 ? cta : wu) & 1) && i + 1 == LAG) && cta < 88;
      const uint32_t dst = pin(elo + EX_M + (i + 1) * 20480 + (t9 ? (cta + 72) * 128 + wu * 32 + (j & 1) * 16 + (lane & 1) * 8 + (j >> 1) * 4
                                                                   : cta * 256 + (wu & 1) * 128 + (wu >> 1) * 64 + j * 16 + (lane & 3) * 4));
      uint8_t* flag = mkptr(elo + EX_FLAG + (i + 1) * 3072 + cta * 32 + wu * 4, ehi);
      while (clk32() - t1 < b1) {}
      TS(i + 1, 30);
      float f[8];
      const int n0 = spin;
      if (!t9) poll_add<4>(mb, tag, f, flag, lane == 0, spin);
      else poll_add<6>(mb, tag, f, flag, lane == 0, spin);
      if (FLP == 1 && lane == 0) st_relaxed(flag, __float_as_uint(f[0] + f[7]) >> 1);
      t1 = clk32();
      b1 = __any_sync(0xffffffffu, spin - n0 > 16) ? min(b1 + AD1, BMX) : max(b1 - AD0, 0);
      TSV(i + 1, 38, b1);
      TS(i + 1, 31); TSV(i + 1, 32, (spin - n0) >> 4);
      const bool h = lane & 16, q = lane & 8;
#pragma unroll
      for (int j = 0; j < 4; j++) f[j] = (h ? f[4 + j] : f[j]) + __shfl_xor_sync(0xffffffffu, h ? f[j] : f[4 + j], 16);
#pragma unroll
      for (int j = 0; j < 2; j++) f[j] = (q ? f[2 + j] : f[j]) + __shfl_xor_sync(0xffffffffu, q ? f[j] : f[2 + j], 8);
      f[0] += __shfl_xor_sync(0xffffffffu, f[0], 4); f[1] += __shfl_xor_sync(0xffffffffu, f[1], 4);
      if (t9) { f[0] += __shfl_xor_sync(0xffffffffu, f[0], 2); f[1] += __shfl_xor_sync(0xffffffffu, f[1], 2); }
      if (pub) st_relaxed(mkptr(dst, ehi), pack_bf16(f[0], f[1]));
      if (FLP == 2 && lane == 0) st_relaxed(flag, 0);
      if (wu == 3) {
        CBAR_SYNC(NB_MR, 160);
        if (elect_one()) signal_o(i, cta);
      }
      TS(i + 1, 15);
    }
    if (wu == 0) {
      const int tid = fresh(tid0);
      const uint8_t* pp = mkptr(elo + EX_FLAG + (i + 1) * 3072 + (rank * 28 + (tid < 28 || rank == 2 ? tid : 0)) * 32, ehi);
      while (clk32() - t1 < b2) {}
      TS(i + 1, 16);
      int n = 1;
      uint4 x = ld_relaxed4(pp);
      if (tid0 == 0) mbar_expect_tx(sb + BAR_M, 20480);
      bool mok = mbar_test(sb + BAR_MOK, ph ^ 1);
      while (__any_sync(0xffffffffu, (int)(x.x | x.y | x.z | x.w) < 0 && spin < SPIN_TOT)) { x = ld_relaxed4(pp); mok = mbar_test(sb + BAR_MOK, ph ^ 1); n++; spin += 16; }
      if (!mok) mwait(sb + BAR_MOK, ph ^ 1, spin);
      b2 = n > 1 ? min(b2 + AD3, BMX) : max(b2 - AD2, 0);
      TSV(i + 1, 35, n); TSV(i + 1, 39, b2);
      TS(i + 1, 34);
      if (elect_one()) bulk_g2s_mc(sb + OFF_M + rank * 7168, mkptr(elo + EX_M + (i + 1) * 20480 + rank * 7168, ehi), rank == 2 ? 6144 : 7168, sb + BAR_M);
      TS(i + 1, 33);
      __syncwarp();
    }
  }
  if (spin >= SPIN_TOT) g_err = 1;
}

__global__ void __cluster_dims__(3, 1, 1) __launch_bounds__(384, 1)
k_chain(const __grid_constant__ CUtensorMap tmWq, const __grid_constant__ CUtensorMap tmWk,
        const __grid_constant__ CUtensorMap tmWv, const __grid_constant__ CUtensorMap tmWo, const bf16* __restrict__ x0, const bf16* __restrict__ mem0) {
  using namespace C;
  extern __shared__ __align__(1024) uint8_t smem[];
  const uint32_t sb = smem_u32(smem);
  const int tid = threadIdx.x;
  const int wg = __shfl_sync(0xffffffffu, tid >> 7, 0);
  const int cta = uni(blockIdx.x), rank = uni(blockIdx.x % 3);

  asm volatile("griddepcontrol.launch_dependents;");
  if (cta < 4) prefetch_l2(tid < 320 ? x0 + (cta * 320 + tid) * 64 : mem0 + (cta * 20 + tid % 20) * 64);
  if (tid == 32) {
    for (int p = 0; p < 5; p++) mbar_init(sb + BAR_W + 8 * p, 2);
    fence_async();
    for (int p = 0; p < NBX; p++) { stage_box<false>(tmWv, sb, p, cta, rank); stage_box<true>(tmWo, sb, p, cta, rank); }
  }
  if (tid == 0) {
    if ((sb & 0xFFFFFF) != SB0) g_err = 100;
    for (int p = 0; p < 5; p++) { mbar_init(sb + BAR_F + 8 * p, 1); mbar_init(sb + BAR_E + 8 * p, p == 2 ? 12 : p == 1 ? 15 : 24); }
    mbar_init(sb + BAR_M, 1); mbar_init(sb + BAR_MOK, 24); mbar_init(sb + BAR_XM, 1); mbar_init(sb + BAR_XF, 2);
    mbar_init(sb + BAR_XT, 1); mbar_init(sb + BAR_MF, 8); mbar_init(sb + BAR_OG, 1);
    for (int p = 0; p < 5; p++) mbar_expect_tx(sb + BAR_F + 8 * p, 16384);
    for (int p = 0; p < 16; p++) sts32(sb + OFF_SAFE + 4 * p, 0);
    for (int p = 0; p < 32; p++) sts32(sb + OFF_ONE + 4 * p, 0x3F803F80);
    asm volatile("fence.mbarrier_init.release.cluster;" ::: "memory");
    fence_async();
  }
  __syncthreads();
  asm volatile("barrier.cluster.arrive.relaxed.aligned;" ::: "memory");
  asm volatile("barrier.cluster.wait.aligned;" ::: "memory");

  if (wg == 0) chain_a(tmWo, tmWq, sb, keep(tid), cta, rank);
  else if (wg == 1) chain_q(x0, mem0, sb, keep(tid), cta, rank);
  else chain_v(tmWv, tmWk, sb, keep(tid), cta, rank);
  asm volatile("barrier.cluster.arrive.release.aligned;" ::: "memory");
  asm volatile("barrier.cluster.wait.acquire.aligned;" ::: "memory");
}

namespace W {
constexpr int NP = 25, NBC = 11, NW = NP + NBC;
constexpr int PRS = 37, PW = 43 * 2048;
constexpr int OFF_W = 0;
constexpr int OFF_R = 2 * PW;
constexpr int QRS = 35, KRS = 37;
constexpr int OFF_WV = 0, OFF_YQ = 81920, OFF_YK = OFF_YQ + (40 - QRS) * 2048, OFF_WO = OFF_YK + (40 - KRS) * 2048;
constexpr int OFF_G = OFF_WO + 39 * 2048;
constexpr int OFF_X = OFF_G + 20480;
constexpr int COL = 976;
constexpr int OFF_T = OFF_X;
constexpr int OFF_H = OFF_X + 24576;
constexpr int OFF_BAR = OFF_H + 8 * COL;
constexpr int OFF_SAFE = OFF_BAR + 192;
constexpr int SMEM = 232448;
static_assert(OFF_SAFE + 64 <= SMEM && OFF_R + 40960 <= OFF_BAR, "");
constexpr uint32_t SB0 = 1024;
constexpr int BAR_F = OFF_BAR, BAR_E = OFF_BAR + 40, BAR_G = OFF_BAR + 80, BAR_H = OFF_BAR + 120, BAR_W = OFF_BAR + 160;
constexpr int NB_G0 = 1, NB_SG = 4, NB_B = 5, NB_AS = 6, NB_PK = 8, NB_PV = 9, NB_TD = 10;
}
#define OBP 1
#define GLA 0
#define WOP 0
#define WBAR_SYNC(id, n) bar_sync(id, n)
#define WBAR_ARRIVE(id, n) bar_arrive(id, n)

__device__ __forceinline__ uint64_t rdesc(int off, int kk) { return mkdesc(W::SB0 + off + kk * 32, 16, 1024); }
__device__ __forceinline__ uint32_t frag_addr(uint32_t base, int tid) {
  const int i = (tid >> 3) & 3, r = tid & 7;
  return base + (r + (i >> 1) * 8) * 128 + (((2 * ((tid >> 5) & 3) + (i & 1)) ^ r) << 4);
}
template <int NK>
__device__ __forceinline__ void load_frags(uint32_t (&wf)[NK][4], uint32_t base, int tid) {
  const uint32_t a0 = frag_addr(base, tid);
#pragma unroll
  for (int k = 0; k < NK; k++) ldsm4t(wf[k], a0 + k * 2048);
}
__device__ __forceinline__ void red_tile(const float* d, int seg, int col0, int tid) {
  float* p = g_x + (size_t)(seg * 32 + 2 * (tid & 3)) * DM + col0 + ((tid >> 5) & 3) * 16 + ((tid >> 2) & 7) * 2;
#pragma unroll
  for (int j = 0; j < 8; j++)
    asm volatile("red.relaxed.gpu.global.add.v2.f32 [%0],{%1,%2};" ::"l"(p + ((j >> 1) * 8 + (j & 1)) * DM), "f"(d[4 * (j >> 1) + (j & 1)]), "f"(d[4 * (j >> 1) + 2 + (j & 1)]) : "memory");
}
#define FOR_SEGS(l, s)                                            \
  for (int j_ = 0; j_ < 2 * NSTEP; j_++) {                        \
    const int l = j_ & 1, s = (j_ >> 1) - l * LAG;                \
    if (s < 0 || s >= NSEG) continue;

template <int WG>
__device__ __forceinline__ void work_p(const CUtensorMap& tmWo, uint32_t sb, int pc, int tid0) {
  using namespace W;
  asm volatile("setmaxnreg.inc.sync.aligned.u32 208;");
  int spin = 0;
  const int ks = pc / 5, col0 = (pc % 5) * 128 + WG * 64;
  const uint32_t wb = sb + OFF_W + WG * PW;
  uint32_t wf[PRS][4];
#pragma unroll 1
  for (int hf = 0; hf < 2; hf++) {
    const int nk = hf ? 80 - PRS : PRS;
    if ((tid0 & 127) == 0) {
      mbar_expect_tx(sb + BAR_W + 8 * WG, nk * 2048);
      for (int i = 0; i < nk; i++) tma2d(wb + i * 2048, &tmWo, col0, ks * 19 * 64 + (i < PRS ? 2 * i + hf : PRS + i) * 16, sb + BAR_W + 8 * WG);
    }
    __syncwarp();
    mwait(sb + BAR_W + 8 * WG, hf, spin);
    permute_cols(wb, tid0 & 127, nk * 64);
    if (hf == 1 && ks < 4) for (int it = 39 * 64 + (tid0 & 127) - 64; it < 43 * 64; it += 128) {
      const uint32_t a = wb + (it >> 2) * 128 + (((2 * (it & 3)) ^ ((it >> 2) & 6)) << 4);
      if (it >= 39 * 64) { sts128(a, make_uint4(0, 0, 0, 0)); sts128(a + 16, make_uint4(0, 0, 0, 0)); }
    }
    fence_async();
    WBAR_SYNC(NB_G0 + WG, 128);
    if (hf == 0) {
      load_frags<PRS>(wf, wb, tid0);
      fence_async();
      WBAR_SYNC(NB_G0 + WG, 128);
    }
  }
#pragma unroll 1
  for (int k = 0; k < NSTEP; k++) {
    float d[32];
#pragma unroll
    for (int f = 0; f < 20; f++) {
      mwait(sb + BAR_F + 8 * (f % 5), (f / 5) & 1, spin);
      if (f == 0 && WG == 0 && pc == WW) WTS(k, 1);
      wg_fence();
#pragma unroll
      for (int kk = 0; kk < 4; kk++) {
        const int q = 4 * f + kk;
        if (q < 2 * PRS && !(q & 1)) wgmma_rs64(d, wf[q < 2 * PRS ? q >> 1 : 0], rdesc(OFF_R + (f % 5) * 8192, kk), q);
        else wgmma_ts64(d, mkdesc(SB0 + OFF_W + WG * PW + (q < 2 * PRS ? q >> 1 : q - PRS) * 2048, 8192, 1024), rdesc(OFF_R + (f % 5) * 8192, kk), 1);
        if (kk == 0 && f > 0) {
          wg_commit();
          wg_wait<1>();
          if ((tid0 & 31) == 0) mbar_arrive(sb + BAR_E + 8 * ((f - 1) % 5));
        }
      }
      wg_commit();
    }
    wg_wait<0>();
    if ((tid0 & 31) == 0) mbar_arrive(sb + BAR_E + 32);
    if (WG == 0 && pc == WW) WTS(k, 2);
    if (k < NSEG) red_tile(d, k, col0, tid0);
    if (k >= LAG) red_tile(d + 16, k - LAG, col0, tid0);
    if (WG == 0 && pc == WW) WTS(k, 13);
    WBAR_SYNC(NB_SG, 256);
    if (WG == 0) { if (tid0 == 0) csignal_t(CN_P + k, 3); __syncwarp(); }
  }
  if (spin >= SPIN_TOT) g_err = 11;
}
__device__ __forceinline__ void work_p_producer(uint32_t sb, int pc, int odd) {
  using namespace W;
  int spin = 0;
  const int ks = pc / 5;
#pragma unroll 1
  for (int k = 0; k < NSTEP; k++) {
    const uint32_t lo = k < NSEG ? 0 : 4096, len = k < LAG || k >= NSEG ? 4096 : 8192;
    const uint8_t* src = &g_o[k % ORING][ks * 19 + odd][lo];
    cwait(CN_O + k * 5 + ks, ks == 4 ? 20 : 19, spin);
    fence_async_all();
    if (pc == WW && !odd) WTS1(k, 0);
#pragma unroll
    for (int u = 0; u < 10; u++) {
      const int st = odd ? (2 * u + 1) % 5 : (2 * u) % 5, ph = odd ? ((2 * u + 1) / 5) & 1 : ((2 * u) / 5) & 1;
      mwait(sb + BAR_E + 8 * st, ph ^ 1, spin);
      if (elect_one()) {
        if (u == 9 && odd && ks < 4) mbar_arrive(sb + BAR_F + 8 * st);
        else {
          mbar_expect_tx(sb + BAR_F + 8 * st, len);
          bulk_g2s(sb + OFF_R + st * 8192 + lo, src + u * 16384, len, sb + BAR_F + 8 * st);
        }
      }
    }
  }
  if (spin >= SPIN_TOT) g_err = 12;
}
__device__ __forceinline__ void work_ln(int kind, int r, int lane, bf16* out) {
  int spin = 0;
  const int l = kind & 1;
  const int rp = kind < 2 ? (r & 1) * 16 + (r >> 1) : r;
  const uint32_t sw = ((((lane >> 1) & 7) ^ (rp & 7)) << 4) + (lane & 1) * 8;
  uint8_t* dst = kind < 2 ? g_xnb[l * LAG] + (lane >> 4) * 8192 + l * 4096 + rp * 128 + sw
               : kind == 2 ? g_xn[LAG] + (r >> 3) * 4096 + 2048 + (lane >> 4) * 1024 + (r & 7) * 128 + sw
                           : reinterpret_cast<uint8_t*>(out) + r * 1280 + lane * 8;
  const int dm = kind < 3 ? 16384 : 256, ds = kind < 3 ? 81920 : 40960;
#pragma unroll 1
  for (int s = 0; s < NSEG; s++) {
    const float* xr = g_x + (size_t)(s * 32 + r) * DM;
    if (OBP && kind < 2) {
      uint8_t* ob = g_ob[l] + (size_t)s * 40960 + r * 1280 + lane * 16;
      stg128(ob, make_uint4(0, 0, 0, 0)); stg128(ob + 512, make_uint4(0, 0, 0, 0));
      if (lane < 16) stg128(ob + 1024, make_uint4(0, 0, 0, 0));
    }
    if (lane == 0) cwait(kind < 2 ? CN_P + s + l * LAG : CN_W + l * 64 + s, kind < 2 ? W::NP : 10, spin);
    __syncwarp();
    if (r == 0 && lane == 0 && (l == 0 || s + LAG >= NSEG)) WTS1(s + l * LAG, kind < 2 ? 3 : 11);
    float4 v[5];
#pragma unroll
    for (int m = 0; m < 5; m++) v[m] = ld_relaxed4f(xr + m * 128 + lane * 4);
    if (kind < 3) ln_row(v);
#pragma unroll
    for (int m = 0; m < 5; m++) *reinterpret_cast<uint2*>(dst + (size_t)s * ds + m * dm) = make_uint2(pack_bf16(v[m].x, v[m].y), pack_bf16(v[m].z, v[m].w));
    __syncwarp();
    if (r == 0 && lane == 0 && (l == 0 || s + LAG >= NSEG)) WTS1(s + l * LAG, kind < 2 ? 4 : 12);
    if (lane == 0 && kind < (NOWORK ? 2 : 3)) csignal_t(kind < 2 ? CN_L + s + l * LAG : CN_X + s + LAG, kind);
  }
  if (spin >= SPIN_TOT) g_err = 13;
}

__device__ __forceinline__ void work_prep(const bf16* x0, const bf16* mem0, int r, int lane) {
  int spin = 0;
#pragma unroll 1
  for (int k = NPRE; k < NSTEP; k++) {
    uint2 u[5], v[5];
    ln0_load(x0, u, min(k * 32 + r, SEQ - 1), lane);
    ln0_load(x0, v, min(k * 32 + r + 16, SEQ - 1), lane);
    if (lane == 0) cwait(CN_O + (k - NPRE) * 5, 1, spin);
    __syncwarp();
#pragma unroll 1
    for (int h = 0; h < 2; h++) {
      prep_row(u, mem0, k, r + 16 * h, lane);
#pragma unroll
      for (int m = 0; m < 5; m++) u[m] = v[m];
    }
    __syncwarp();
    if (lane == 0) csignal(CN_X + k);
  }
  if (spin >= SPIN_TOT) g_err = 19;
}

__device__ __forceinline__ void stage_qkv(const bf16* wqkv, uint32_t base, int T, int bc, int tid) {
  const int q = tid & 15;
  const bool ok = q < 15 && bc * 60 + 4 * q < DM;
  const bf16* src = wqkv + T * DM + bc * 60 + 4 * q;
#pragma unroll 1
  for (int k0 = tid >> 4; k0 < 640; k0 += 80) {
    uint2 v[10];
#pragma unroll
    for (int u = 0; u < 10; u++) v[u] = ok ? *reinterpret_cast<const uint2*>(src + (size_t)(k0 + 8 * u) * 1920) : make_uint2(0, 0);
#pragma unroll
    for (int u = 0; u < 10; u++) sts64(base + (k0 + 8 * u) * 128 + (((q >> 1) ^ (k0 & 7)) << 4) + (q & 1) * 8, v[u].x, v[u].y);
  }
}
__device__ __forceinline__ void attend(uint32_t sb, int bc, int l, int s, int p, int tid) {
  using namespace W;
  const int r = tid & 7, m = (tid >> 3) & 3, hh = (tid >> 5) & 3, g = (tid >> 2) & 7, t = tid & 3;
  const int f2 = r < 4 ? 20 * hh + 16 + r : 60;
  const uint32_t tb = sb + OFF_T + (l * 4 + 2 * p) * COL, hb = sb + OFF_H + (l * 2 + p) * COL;
  const uint32_t ko = (m < 2 ? 20 * hh + 8 * m + r : f2) * 16, vo = (m < 2 ? 20 * hh + 4 * (r >> 1) + 2 * m + (r & 1) : f2) * 16;
  const float scl = 0.22360679774997896f * 1.4426950408889634f;
  float sc[3][4];
  {
    uint32_t q[4], q8a, q8b, k[3][4];
    ldsm4t(q, tb + (m & 1) * COL + (20 * hh + (m >> 1) * 8 + r) * 16);
    ldsm2t(q8a, q8b, tb + (m & 1) * COL + f2 * 16);
    ldsm4t(k[0], hb + ko); ldsm4t(k[1], tb + 8 * COL + ko); ldsm4t(k[2], tb + 9 * COL + ko);
#pragma unroll
    for (int c = 0; c < 3; c++) { sc[c][0] = sc[c][1] = sc[c][2] = sc[c][3] = 0.f; mma16816(sc[c], q[0], q[1], q[2], q[3], k[c][0], k[c][1]); }
#pragma unroll
    for (int c = 0; c < 3; c++) mma1688(sc[c], q8a, q8b, k[c][2]);
  }
  uint32_t v[3][4];
  ldsm4(v[0], hb + 4 * COL + vo); ldsm4(v[1], tb + 16 * COL + vo); ldsm4(v[2], tb + 17 * COL + vo);
  const bool lo0 = 2 * t > g, lo1 = 2 * t + 1 > g;
  uint32_t pw[2];
  float inv[2];
#pragma unroll
  for (int h = 0; h < 2; h++) {
    float y0 = lo0 ? sc[h][2 * h] : sc[h + 1][2 * h], y1 = lo1 ? sc[h][2 * h + 1] : sc[h + 1][2 * h + 1];
    if (h == 0 && s == 0) { y0 = lo0 ? -INFINITY : y0; y1 = lo1 ? -INFINITY : y1; }
    const float mx = quad_max(fmaxf(y0, y1)) * -scl;
    pw[h] = pack_bf16(ex2(fmaf(y0, scl, mx)), ex2(fmaf(y1, scl, mx)));
    inv[h] = bf_lo(pw[h]) + bf_hi(pw[h]);
  }
  const uint32_t ml = (lo0 ? 0xFFFFu : 0u) | (lo1 ? 0xFFFF0000u : 0u);
  float o[3][4];
#pragma unroll
  for (int j = 0; j < 3; j++) { o[j][0] = o[j][1] = o[j][2] = o[j][3] = 0.f; mma16816(o[j], pw[0] & ml, 0u, pw[0] & ~ml, pw[1] & ml, v[0][j], v[1][j]); }
#pragma unroll
  for (int j = 0; j < 3; j++) mma1688(o[j], 0u, pw[1] & ~ml, v[2][j]);
  inv[0] = rcp(quad_sum(inv[0])); inv[1] = rcp(quad_sum(inv[1]));
  const uint32_t ca = (bc * 3 + hh) * 20 + 4 * t, cb = ca + 16 - 2 * t, row = 2 * g + p;
  uint8_t* img = g_ob[l] + (size_t)s * 40960 + row * 128;
  const uint32_t oa = (ca >> 6) * 4096 + (((ca >> 3) ^ row) & 7) * 16 + (ca & 4) * 2, ob = (cb >> 6) * 4096 + (((cb >> 3) ^ row) & 7) * 16 + (cb & 6) * 2;
#pragma unroll
  for (int h = 0; h < 2; h++) {
    *reinterpret_cast<uint2*>(img + oa + h * 2048) = make_uint2(pack_bf16(o[0][2 * h] * inv[h], o[0][2 * h + 1] * inv[h]), pack_bf16(o[1][2 * h] * inv[h], o[1][2 * h + 1] * inv[h]));
    if (t < 2) *reinterpret_cast<uint32_t*>(img + ob + h * 2048) = pack_bf16(o[2][2 * h] * inv[h], o[2][2 * h + 1] * inv[h]);
  }
}
template <int WG>
__device__ __forceinline__ void work_b(const bf16* wqkv, uint32_t sb, int bc, int tid0) {
  using namespace W;
  if (WG == 0) asm volatile("setmaxnreg.inc.sync.aligned.u32 232;");
  else asm volatile("setmaxnreg.inc.sync.aligned.u32 208;");
  constexpr int NR = WG ? KRS : QRS, OFF_Y = WG ? OFF_YK : OFF_YQ;
  int spin = 0;
  const uint32_t wb = sb + (WG ? OFF_WO : OFF_WV);
  uint32_t wf[NR][4];
  stage_qkv(wqkv, wb, WG, bc, tid0 & 127);
  WBAR_SYNC(NB_G0 + WG, 128);
  load_frags<NR>(wf, wb, tid0);
#pragma unroll
  for (int k = NR; k < 40; k++) sts128(sb + OFF_Y + (k - NR) * 2048 + (tid0 & 127) * 16, lds128(wb + k * 2048 + (tid0 & 127) * 16));
  fence_async();
  if (WG == 1) WBAR_ARRIVE(NB_PK, 256);
  WBAR_SYNC(NB_G0 + WG, 128);
  if (WG == 0) {
    stage_qkv(wqkv, wb, 2, bc, tid0);
    fence_async();
    WBAR_SYNC(NB_G0, 128);
  }
#pragma unroll 1
  for (int k = 0; k < NSTEP; k++) {
    uint32_t hist[8];
    {
      float d[32], e[32];
#pragma unroll
      for (int c = 0; c < 10; c++) {
        mwait(sb + BAR_F + 8 * (c % 3), ((c % 3 ? k : 0) + c / 3) & 1, spin);
        if (c == 0 && bc == 0) WTS(k, WG ? 15 : 6);
        wg_fence();
#pragma unroll
        for (int kk = 0; kk < 4; kk++) {
          const int q = 4 * c + kk;
          const uint64_t db = rdesc(OFF_X + (c % 3) * 8192, kk);
          if (q < NR) wgmma_rs64(d, wf[q < NR ? q : 0], db, q);
          else wgmma_ts64(d, mkdesc(SB0 + OFF_Y + (q - NR) * 2048, 8192, 1024), db, 1);
          if (WG == 0) wgmma_ts64(e, mkdesc(SB0 + OFF_WV + q * 2048, 8192, 1024), db, q);
          if (kk == 0 && c > 0 && c <= 7) {
            wg_commit();
            wg_wait<1>();
            if ((tid0 & 31) == 0) mbar_arrive(sb + BAR_E + 8 * ((c - 1) % 3));
          }
        }
        wg_commit();
      }
      wg_wait<0>();
      if (bc == 0) WTS(k, 16 + WG);
      WBAR_SYNC(NB_B, 256);
      const int tid = fresh(tid0), m = (tid >> 3) & 3;
      const uint32_t a = sb + OFF_T + min(((tid >> 5) & 3) * 16 + (m & 1) * 8 + (tid & 7), 60) * 16 + (m >> 1) * COL;
      const float (&x)[32] = WG ? d : e;
#pragma unroll
      for (int p = 0; p < 4; p++) {
        hist[2 * p] = pack_bf16(x[8 * p + 4], x[8 * p + 5]); hist[2 * p + 1] = pack_bf16(x[8 * p + 6], x[8 * p + 7]);
        stsm4(a + (16 - 8 * WG + 2 * p) * COL, pack_bf16(x[8 * p], x[8 * p + 1]), pack_bf16(x[8 * p + 2], x[8 * p + 3]), hist[2 * p], hist[2 * p + 1]);
        if (WG == 0)
          stsm4(a + 2 * p * COL, pack_bf16(d[8 * p], d[8 * p + 1]), pack_bf16(d[8 * p + 2], d[8 * p + 3]), pack_bf16(d[8 * p + 4], d[8 * p + 5]), pack_bf16(d[8 * p + 6], d[8 * p + 7]));
      }
    }
    WBAR_SYNC(NB_TD, 288);
    if (bc == 0 && WG == 0) WTS(k, 7);
#pragma unroll 1
    for (int l = 0; l < 2; l++) {
      const int tid = fresh(tid0), hh = uni((tid >> 5) & 3), s = k - l * LAG;
      if (hh < 3 && bc * 3 + hh < NH && s >= 0 && s < NSEG) attend(sb, bc, l, s, WG, tid);
      if (bc == 0 && WG == 0) WTS(k, l == 0 || k >= NSEG ? 8 : 25);
      if (l == 0) WBAR_ARRIVE(NB_AS, 288); else WBAR_ARRIVE(NB_AS + 1, 288);
    }
    WBAR_SYNC(NB_B, 256);
    {
      const int tid = fresh(tid0), m = (tid >> 3) & 3;
      const uint32_t a = sb + OFF_H + min(((tid >> 5) & 3) * 16 + (m & 1) * 8 + (tid & 7), 60) * 16 + (4 - 4 * WG + (m >> 1)) * COL;
      stsm4(a, hist[0], hist[1], hist[2], hist[3]);
      if (k >= LAG) stsm4(a + 2 * COL, hist[4], hist[5], hist[6], hist[7]);
      fence_async();
      if ((tid & 31) < 3) mbar_arrive(sb + BAR_E + 8 * (tid & 3));
    }
  }
  if (spin >= SPIN_TOT) g_err = 14;
}
__device__ __forceinline__ void work_wo(const CUtensorMap& tmBo, uint32_t sb, int bc, int tid0) {
  using namespace W;
  int spin = 0;
  WBAR_SYNC(NB_PK, 256);
  if (bc == 10) return;
  if ((tid0 & 127) == 0) {
    mbar_expect_tx(sb + BAR_W, 81920);
    for (int i = 0; i < 10; i++) tma2d(sb + OFF_WO + i * 8192, &tmBo, bc * 64, i * 64, sb + BAR_W);
  }
  __syncwarp();
  mwait(sb + BAR_W, 0, spin);
  permute_cols(sb + OFF_WO, tid0 & 127, 2560);
  WBAR_SYNC(NB_G0 + 2, 128);
  uint32_t wl[4];
  ldsm4t(wl, frag_addr(sb + OFF_WO + 39 * 2048, tid0));
  fence_async();
  WBAR_SYNC(NB_PV, 160);
  FOR_SEGS(l, s)
    float d[16];
#pragma unroll
    for (int c = 0; c < 10; c++) {
      mwait(sb + BAR_G + 8 * (c % 5), c / 5, spin);
      if (c == 0 && bc == 0) WTS(s + l * LAG, l == 0 || s + LAG >= NSEG ? 20 : 23);
      wg_fence();
#pragma unroll
      for (int kk = 0; kk < 4; kk++) {
        if (c == 9 && kk == 3) wgmma_rs32(d, wl, rdesc(OFF_G + (c % 5) * 4096, kk), 1);
        else wgmma_ts32(d, mkdesc(SB0 + OFF_WO + (4 * c + kk) * 2048, 8192, 1024), rdesc(OFF_G + (c % 5) * 4096, kk), c | kk);
      }
      wg_commit();
      if (c % 5) {
        wg_wait<1>();
        if ((tid0 & 31) == 0) mbar_arrive(sb + BAR_H + 8 * ((c - 1) % 5));
      }
      if (c % 5 == 4) {
        wg_wait<0>();
        if ((tid0 & 31) == 0) mbar_arrive(sb + BAR_H + 32);
      }
    }
    if (bc == 0) WTS(s + l * LAG, l == 0 || s + LAG >= NSEG ? 10 : 24);
    red_tile(d, s, bc * 64, tid0);
    WBAR_SYNC(NB_SG, 160);
  }
  if (spin >= SPIN_TOT) g_err = 17;
}
__device__ __forceinline__ void work_x_producer(uint32_t sb, int bc) {
  using namespace W;
  int spin = 0;
#pragma unroll 1
  for (int k = 0; k < NSTEP; k++) {
    const uint32_t lo = k < NSEG ? 0 : 4096, len = k < LAG || k >= NSEG ? 4096 : 8192;
    const uint8_t* src = g_xnb[k] + lo;
    cwait(CN_L + k, len >> 7, spin);
    fence_async_all();
    if (bc == 0) WTS1(k, 5);
#pragma unroll
    for (int c = 0; c < 10; c++) {
      mwait(sb + BAR_E + 8 * (c % 3), (((c % 3 ? k : 0) + c / 3) & 1) ^ 1, spin);
      if (elect_one()) {
        mbar_expect_tx(sb + BAR_F + 8 * (c % 3), len);
        bulk_g2s(sb + OFF_X + (c % 3) * 8192 + lo, src + c * 8192, len, sb + BAR_F + 8 * (c % 3));
      }
    }
  }
  if (spin >= SPIN_TOT) g_err = 15;
}
__device__ __forceinline__ void work_g_producer(uint32_t sb, int bc) {
  using namespace W;
  int spin = 0;
  uint32_t seen = 0;
  FOR_SEGS(l, s)
    const uint8_t* src = g_ob[l] + (size_t)s * 40960;
    if (seen < NBC) { cwait(CN_A + l * 64 + s, NBC, spin); fence_async_all(); }
    if (bc == 0) WTS1(s + l * LAG, l == 0 || s + LAG >= NSEG ? 9 : 22);
    seen = 0;
#pragma unroll
    for (int c = 0; c < 10; c++) {
      if (GLA && c == GLA && l == 0 && s >= LAG) { seen = ld_acquire(&g_cnt[CN_A + 64 + s - LAG][0]); fence_async_all(); }
      mwait(sb + BAR_H + 8 * (c % 5), c < 5, spin);
      if (elect_one()) {
        mbar_expect_tx(sb + BAR_G + 8 * (c % 5), 4096);
        bulk_g2s(sb + OFF_G + (c % 5) * 4096, src + c * 4096, 4096, sb + BAR_G + 8 * (c % 5));
      }
    }
  }
  if (spin >= SPIN_TOT) g_err = 16;
}

__global__ void __launch_bounds__(512, 1)
k_work(const __grid_constant__ CUtensorMap tmWo, const __grid_constant__ CUtensorMap tmBo, const bf16* __restrict__ wqkv, bf16* __restrict__ out,
       const bf16* __restrict__ x0, const bf16* __restrict__ mem0) {
  using namespace W;
  extern __shared__ __align__(1024) uint8_t smem[];
  const uint32_t sb = smem_u32(smem);
  const int tid = threadIdx.x, w = blockIdx.x;
  const int wg = __shfl_sync(0xffffffffu, tid >> 7, 0);
  if (tid == 0) {
    if (sb != SB0) g_err = 101;
    for (int i = 0; i < 5; i++) { mbar_init(sb + BAR_F + 8 * i, 1); mbar_init(sb + BAR_E + 8 * i, 8); mbar_init(sb + BAR_G + 8 * i, 1); mbar_init(sb + BAR_H + 8 * i, 4); }
    mbar_init(sb + BAR_W, 1); mbar_init(sb + BAR_W + 8, 1);
    for (int p = 0; p < 16; p++) sts32(sb + OFF_SAFE + 4 * p, 0);
    asm volatile("fence.mbarrier_init.release.cluster;" ::: "memory");
    int spin = 0;
    pre_wait(1, NW, spin);
    if (spin >= SPIN_TOT) g_err = 18;
  }
  if (tid < 8 * COL / 16) sts128(sb + OFF_H + tid * 16, make_uint4(0, 0, 0, 0));
  fence_async();
  __syncthreads();

  if (w < NP) {
    if (wg == 0) work_p<0>(tmWo, sb, w, keep(tid));
    else if (wg == 1) work_p<1>(tmWo, sb, w, keep(tid));
    else {
      asm volatile("setmaxnreg.dec.sync.aligned.u32 48;");
      const int aw = uni(tid >> 5) - 8;
      if (aw < 2) {
        work_p_producer(sb, w, aw);
      } else {
        const int id = (aw - 2) * NP + w;
        if (id < 128) work_ln(id & 3, id >> 2, tid & 31, out);
        else if (id < 144 && NOWORK != 2) work_prep(x0, mem0, id - 128, tid & 31);
      }
    }
  } else {
    const int bc = w - NP;
    if (wg == 0) work_b<0>(wqkv, sb, bc, keep(tid));
    else if (wg == 1) work_b<1>(wqkv, sb, bc, keep(tid));
    else if (wg == 2) {
      asm volatile("setmaxnreg.dec.sync.aligned.u32 48;");
      work_wo(tmBo, sb, bc, keep(tid));
    } else {
      asm volatile("setmaxnreg.dec.sync.aligned.u32 24;");
      const int aw = uni(tid >> 5) - 12;
      if (aw == 0) work_x_producer(sb, bc);
      else if (aw == 1) {
        if (bc < 10) {
          WBAR_SYNC(NB_PV, 160);
          work_g_producer(sb, bc);
        }
      } else if (aw == 2) {
        for (int k = 0; k < NSTEP; k++) {
          WBAR_SYNC(NB_TD, 288);
          WBAR_SYNC(NB_AS, 288);
          if (tid == 448 && k < NSEG) csignal_t(CN_A + k, 5);
          __syncwarp();
          WBAR_SYNC(NB_AS + 1, 288);
          if (tid == 448 && k >= LAG) csignal_t(CN_A + 64 + k - LAG, 4);
          __syncwarp();
        }
      } else if (bc < 10) {
        FOR_SEGS(l, s)
          WBAR_SYNC(NB_SG, 160);
          if (tid == 480) csignal_t(CN_W + l * 64 + s, 6);
          __syncwarp();
        }
      }
    }
  }
  __syncthreads();
  asm volatile("griddepcontrol.wait;" ::: "memory");
}

typedef CUresult (*EncodeFn)(CUtensorMap*, CUtensorMapDataType, cuuint32_t, void*, const cuuint64_t*, const cuuint64_t*,
                             const cuuint32_t*, const cuuint32_t*, CUtensorMapInterleave, CUtensorMapSwizzle,
                             CUtensorMapL2promotion, CUtensorMapFloatOOBfill);

static void make_map(EncodeFn enc, CUtensorMap* tm, const void* ptr, uint64_t cols, uint64_t rows, uint32_t boxc, uint32_t boxr) {
  cuuint64_t dims[2] = {cols, rows};
  cuuint64_t strides[1] = {cols * 2};
  cuuint32_t box[2] = {boxc, boxr};
  cuuint32_t es[2] = {1, 1};
  enc(tm, CU_TENSOR_MAP_DATA_TYPE_BFLOAT16, 2, const_cast<void*>(ptr), dims, strides, box, es, CU_TENSOR_MAP_INTERLEAVE_NONE,
      CU_TENSOR_MAP_SWIZZLE_128B, CU_TENSOR_MAP_L2_PROMOTION_L2_256B, CU_TENSOR_MAP_FLOAT_OOB_FILL_NONE);
}

extern "C" void kernel_launch(void* const* d_in, const int* in_sizes, int n_in, void* d_out, int out_size) {
  const bf16* x0 = (const bf16*)d_in[0];
  const bf16* mem0 = (const bf16*)d_in[1];
  const bf16* Wq = (const bf16*)d_in[2];
  const bf16* Wk = (const bf16*)d_in[3];
  const bf16* Wv = (const bf16*)d_in[4];
  const bf16* Wo = (const bf16*)d_in[5];
  const bf16* Bqkv = (const bf16*)d_in[8];
  const bf16* Bwo = (const bf16*)d_in[9];
  bf16* out = (bf16*)d_out;

  static EncodeFn enc = nullptr;
  if (!enc) {
    void* fn = nullptr;
    cudaDriverEntryPointQueryResult qr;
    cudaGetDriverEntryPoint("cuTensorMapEncodeTiled", &fn, cudaEnableDefault, &qr);
    enc = (EncodeFn)fn;
    cudaFuncSetAttribute(k_chain, cudaFuncAttributeMaxDynamicSharedMemorySize, C::SMEM);
    cudaFuncSetAttribute(k_work, cudaFuncAttributeMaxDynamicSharedMemorySize, W::SMEM);
  }
  CUtensorMap tmWq, tmWk, tmWv, tmWo, tmWp, tmBo;
  make_map(enc, &tmWq, Wq, NH * DH, DM, 64, 128);
  make_map(enc, &tmWk, Wk, NH * DH, DM, 64, 128);
  make_map(enc, &tmWv, Wv, NH * DH, DM, 64, 128);
  make_map(enc, &tmWo, Wo, DM, NH * DH, 64, 64);
  make_map(enc, &tmWp, Wo, DM, NH * DH, 64, 16);
  make_map(enc, &tmBo, Bwo, DM, DM, 64, 64);

  cudaStream_t st = cudaStreamPerThread;
  cudaLaunchAttribute at[1];
  at[0].id = cudaLaunchAttributeProgrammaticStreamSerialization; at[0].val.programmaticStreamSerializationAllowed = 1;
  {
    cudaLaunchConfig_t cfg = {};
    cfg.gridDim = dim3(96); cfg.blockDim = dim3(384); cfg.dynamicSmemBytes = C::SMEM; cfg.stream = st;
    cfg.attrs = at; cfg.numAttrs = 0;
    cudaLaunchKernelEx(&cfg, k_chain, tmWq, tmWk, tmWv, tmWo, x0, mem0);
  }
  cudaLaunchConfig_t cfg = {};
  cfg.gridDim = dim3(W::NW); cfg.blockDim = dim3(512); cfg.dynamicSmemBytes = W::SMEM; cfg.stream = st;
  cfg.attrs = at; cfg.numAttrs = NOWORK == 2 ? 0 : 1;
  cudaLaunchKernelEx(&cfg, k_work, tmWp, tmBo, Bqkv, out, x0, mem0);
}
```

```cpp
#include <cuda_runtime.h>
#include <cuda_bf16.h>
#include <cuda.h>
#include <stdint.h>

typedef __nv_bfloat16 bf16;

constexpr int SEQ = 2048, DM = 640, NH = 32, DH = 192, NSEG = 64;
#define LAG 6
constexpr int NSTEP = NSEG + LAG;
constexpr int NPRE = 4;
constexpr uint32_t SENT = 0xFFFFFFFFu;

constexpr int MAIL9 = 288 * 2048, MAIL_BYTES = MAIL9 + 64 * 3072;
__device__ __align__(1024) uint8_t g_xn[NSTEP][81920];
__device__ __align__(1024) uint8_t g_xnb[NSTEP][81920];
__device__ __align__(1024) uint8_t g_ob[2][NSEG * 40960];
#define ORING 8
static_assert(ORING > LAG, "a slot is free again LAG + 1 steps later");
__device__ __align__(1024) uint8_t g_o[ORING][96][8192];
__device__ __align__(1024) float g_x[SEQ * DM];
constexpr int EX_MAIL = 0;
constexpr int EX_M = 2 << 20;
constexpr int EX_FLAG = EX_M + NSTEP * 20480;
static_assert(EX_FLAG + NSTEP * 3072 <= (4 << 20), "");
__device__ __align__(1024) uint8_t g_ex[8 << 20];
__host__ __device__ __forceinline__ uint8_t* ex_window(uint8_t* p) { return reinterpret_cast<uint8_t*>((reinterpret_cast<uint64_t>(p) + (4 << 20) - 1) & ~(uint64_t)((4 << 20) - 1)); }
enum { CN_P = 0, CN_L = 128, CN_A = 256, CN_W = 384, CN_X = 512, CN_O = 640, CN_NUM = CN_O + 5 * NSTEP };
__device__ __align__(128) uint32_t g_cnt[CN_NUM][32];
__device__ __align__(128) uint32_t g_ticket[2][32];
__device__ int g_err;
#define TS(jj, i)
#define TS1(jj, i)
#define PTS(i)
#define TSB(jj, i)
#define TSV(jj, i, v)
#define TS_FLUSH(jj)
#define WTS(b, k)
#define WTS1(b, k)
#define WW -1

__device__ __forceinline__ uint32_t smem_u32(const void* p) { return (uint32_t)__cvta_generic_to_shared(p); }
__device__ __forceinline__ uint32_t clk32() { uint32_t t; asm volatile("mov.u32 %0, %%clock;" : "=r"(t)::"memory"); return t; }
__device__ __forceinline__ uint32_t mapa(uint32_t a, uint32_t r) { uint32_t o; asm("mapa.shared::cluster.u32 %0,%1,%2;" : "=r"(o) : "r"(a), "r"(r)); return o; }
__device__ __forceinline__ void mbar_init(uint32_t bar, uint32_t cnt) { asm volatile("mbarrier.init.shared::cta.b64 [%0],%1;" ::"r"(bar), "r"(cnt) : "memory"); }
__device__ __forceinline__ void mbar_expect_tx(uint32_t bar, uint32_t bytes) { asm volatile("mbarrier.arrive.expect_tx.shared::cta.b64 _,[%0],%1;" ::"r"(bar), "r"(bytes) : "memory"); }
__device__ __forceinline__ void mbar_arrive(uint32_t bar) { asm volatile("mbarrier.arrive.shared::cta.b64 _,[%0];" ::"r"(bar) : "memory"); }
__device__ __forceinline__ void mbar_arrive_cluster(uint32_t bar) { asm volatile("mbarrier.arrive.shared::cluster.b64 _,[%0];" ::"r"(bar) : "memory"); }
__device__ __forceinline__ bool mbar_try(uint32_t bar, uint32_t ph) {
  uint32_t ok;
  asm volatile("{.reg .pred p; mbarrier.try_wait.parity.shared::cta.b64 p,[%1],%2; selp.u32 %0,1,0,p;}" : "=r"(ok) : "r"(bar), "r"(ph) : "memory");
  return ok;
}
__device__ __forceinline__ bool mbar_test(uint32_t bar, uint32_t ph) {
  uint32_t ok;
  asm volatile("{.reg .pred p; mbarrier.test_wait.parity.shared::cta.b64 p,[%1],%2; selp.u32 %0,1,0,p;}" : "=r"(ok) : "r"(bar), "r"(ph) : "memory");
  return ok;
}
__device__ __forceinline__ int fresh(int x) { asm volatile("" : "+r"(x)); return x; }
#define PHASE_IDS const int tid = fresh(tid0), lane = tid & 31, w = tid >> 5, g = lane >> 2, t = lane & 3; (void)w; (void)g; (void)t
__device__ __forceinline__ void bar_sync(int id, int n) { asm volatile("bar.sync %0,%1;" ::"r"(id), "r"(n) : "memory"); }
__device__ __forceinline__ void bar_arrive(int id, int n) { asm volatile("bar.arrive %0,%1;" ::"r"(id), "r"(n) : "memory"); }
__device__ __forceinline__ bool bar_red_or(int id, int n, bool v) {
  uint32_t r;
  asm volatile("{\n .reg .pred p, q;\n setp.ne.u32 q, %3, 0;\n barrier.cta.red.or.pred p, %1, %2, q;\n selp.u32 %0, 1, 0, p;\n}" : "=r"(r) : "r"(id), "r"(n), "r"((uint32_t)v) : "memory");
  return r != 0;
}
__device__ __forceinline__ void fence_async() { asm volatile("fence.proxy.async.shared::cta;" ::: "memory"); }
__device__ __forceinline__ void bulk_g2s(uint32_t dst, const void* src, uint32_t bytes, uint32_t bar) {
  asm volatile("cp.async.bulk.shared::cluster.global.mbarrier::complete_tx::bytes [%0],[%1],%2,[%3];" ::"r"(dst), "l"(src), "r"(bytes), "r"(bar) : "memory");
}
__device__ __forceinline__ void bulk_g2s_mc(uint32_t dst, const void* src, uint32_t bytes, uint32_t bar) {
  asm volatile("cp.async.bulk.shared::cluster.global.mbarrier::complete_tx::bytes.multicast::cluster [%0],[%1],%2,[%3],%4;"
               ::"r"(dst), "l"(src), "r"(bytes), "r"(bar), "h"((uint16_t)7) : "memory");
}
__device__ __forceinline__ void bulk_s2g(void* dst, uint32_t src, uint32_t bytes) {
  asm volatile("cp.async.bulk.global.shared::cta.bulk_group [%0],[%1],%2;" ::"l"(dst), "r"(src), "r"(bytes) : "memory");
}
__device__ __forceinline__ void bulk_s2c(uint32_t dst, uint32_t src, uint32_t bytes, uint32_t bar) {
  asm volatile("cp.async.bulk.shared::cluster.shared::cta.mbarrier::complete_tx::bytes [%0],[%1],%2,[%3];" ::"r"(dst), "r"(src), "r"(bytes), "r"(bar) : "memory");
}
__device__ __forceinline__ void tma2d(uint32_t dst, const CUtensorMap* tm, int c0, int c1, uint32_t bar) {
  asm volatile("cp.async.bulk.tensor.2d.shared::cluster.global.mbarrier::complete_tx::bytes [%0],[%1,{%3,%4}],[%2];"
               ::"r"(dst), "l"(tm), "r"(bar), "r"(c0), "r"(c1) : "memory");
}
__device__ __forceinline__ void tma2d_prefetch(const CUtensorMap* tm, int c0, int c1) {
  asm volatile("cp.async.bulk.prefetch.tensor.2d.L2.global.tile [%0,{%1,%2}];" ::"l"(tm), "r"(c0), "r"(c1) : "memory");
}
__device__ __forceinline__ uint32_t pack_bf16(float lo, float hi) {
  uint32_t r; asm("cvt.rn.bf16x2.f32 %0,%1,%2;" : "=r"(r) : "f"(hi), "f"(lo)); return r;
}
__device__ __forceinline__ float bf_lo(uint32_t x) { return __uint_as_float(x << 16); }
__device__ __forceinline__ float bf_hi(uint32_t x) { return __uint_as_float(x & 0xFFFF0000u); }
__device__ __forceinline__ float ex2(float x) { float y; asm("ex2.approx.ftz.f32 %0,%1;" : "=f"(y) : "f"(x)); return y; }
__device__ __forceinline__ void ldsm4(uint32_t (&r)[4], uint32_t a) {
  asm volatile("ldmatrix.sync.aligned.m8n8.x4.shared.b16 {%0,%1,%2,%3},[%4];" : "=r"(r[0]), "=r"(r[1]), "=r"(r[2]), "=r"(r[3]) : "r"(a) : "memory");
}
__device__ __forceinline__ void ldsm4t(uint32_t (&r)[4], uint32_t a) {
  asm volatile("ldmatrix.sync.aligned.m8n8.x4.trans.shared.b16 {%0,%1,%2,%3},[%4];" : "=r"(r[0]), "=r"(r[1]), "=r"(r[2]), "=r"(r[3]) : "r"(a) : "memory");
}
__device__ __forceinline__ void ldsm2(uint32_t& r0, uint32_t& r1, uint32_t a) {
  asm volatile("ldmatrix.sync.aligned.m8n8.x2.shared.b16 {%0,%1},[%2];" : "=r"(r0), "=r"(r1) : "r"(a) : "memory");
}
__device__ __forceinline__ void ldsm2t(uint32_t& r0, uint32_t& r1, uint32_t a) {
  asm volatile("ldmatrix.sync.aligned.m8n8.x2.trans.shared.b16 {%0,%1},[%2];" : "=r"(r0), "=r"(r1) : "r"(a) : "memory");
}
__device__ __forceinline__ void ldsm1(uint32_t& r0, uint32_t a) {
  asm volatile("ldmatrix.sync.aligned.m8n8.x1.shared.b16 {%0},[%1];" : "=r"(r0) : "r"(a) : "memory");
}
__device__ __forceinline__ void mma16816(float (&d)[4], uint32_t a0, uint32_t a1, uint32_t a2, uint32_t a3, uint32_t b0, uint32_t b1) {
  asm volatile("mma.sync.aligned.m16n8k16.row.col.f32.bf16.bf16.f32 {%0,%1,%2,%3},{%4,%5,%6,%7},{%8,%9},{%0,%1,%2,%3};"
               : "+f"(d[0]), "+f"(d[1]), "+f"(d[2]), "+f"(d[3]) : "r"(a0), "r"(a1), "r"(a2), "r"(a3), "r"(b0), "r"(b1));
}
__device__ __forceinline__ void mma1688(float (&d)[4], uint32_t a0, uint32_t a1, uint32_t b0) {
  asm volatile("mma.sync.aligned.m16n8k8.row.col.f32.bf16.bf16.f32 {%0,%1,%2,%3},{%4,%5},{%6},{%0,%1,%2,%3};"
               : "+f"(d[0]), "+f"(d[1]), "+f"(d[2]), "+f"(d[3]) : "r"(a0), "r"(a1), "r"(b0));
}
__device__ __forceinline__ void sts32(uint32_t a, uint32_t v) { asm volatile("st.shared.b32 [%0],%1;" ::"r"(a), "r"(v) : "memory"); }
__device__ __forceinline__ void sts64f(uint32_t a, float x, float y) { asm volatile("st.shared.v2.f32 [%0],{%1,%2};" ::"r"(a), "f"(x), "f"(y) : "memory"); }
__device__ __forceinline__ void sts128(uint32_t a, uint4 v) { asm volatile("st.shared.v4.b32 [%0],{%1,%2,%3,%4};" ::"r"(a), "r"(v.x), "r"(v.y), "r"(v.z), "r"(v.w) : "memory"); }
__device__ __forceinline__ float lds32f(uint32_t a) { float v; asm volatile("ld.shared.f32 %0,[%1];" : "=f"(v) : "r"(a) : "memory"); return v; }
__device__ __forceinline__ float2 lds64f(uint32_t a) { float2 v; asm volatile("ld.shared.v2.f32 {%0,%1},[%2];" : "=f"(v.x), "=f"(v.y) : "r"(a) : "memory"); return v; }
__device__ __forceinline__ uint4 lds128(uint32_t a) { uint4 v; asm volatile("ld.shared.v4.b32 {%0,%1,%2,%3},[%4];" : "=r"(v.x), "=r"(v.y), "=r"(v.z), "=r"(v.w) : "r"(a) : "memory"); return v; }
__device__ __forceinline__ float4 lds128f(uint32_t a) { float4 v; asm volatile("ld.shared.v4.f32 {%0,%1,%2,%3},[%4];" : "=f"(v.x), "=f"(v.y), "=f"(v.z), "=f"(v.w) : "r"(a) : "memory"); return v; }
__device__ __forceinline__ void st_async2(uint32_t a, float x, float y, uint32_t bar) {
  asm volatile("st.async.weak.shared::cluster.mbarrier::complete_tx::bytes.v2.f32 [%0],{%1,%2},[%3];" ::"r"(a), "f"(x), "f"(y), "r"(bar) : "memory");
}
__device__ __forceinline__ void st_async4(uint32_t a, const float (&v)[4], uint32_t bar) {
  asm volatile("st.async.weak.shared::cluster.mbarrier::complete_tx::bytes.v4.f32 [%0],{%1,%2,%3,%4},[%5];" ::"r"(a), "f"(v[0]), "f"(v[1]), "f"(v[2]), "f"(v[3]), "r"(bar) : "memory");
}
__device__ __forceinline__ void st_async4v(uint32_t a, float x, float y, float z, float w, uint32_t bar) {
  asm volatile("st.async.weak.shared::cluster.mbarrier::complete_tx::bytes.v4.f32 [%0],{%1,%2,%3,%4},[%5];" ::"r"(a), "f"(x), "f"(y), "f"(z), "f"(w), "r"(bar) : "memory");
}
__device__ __forceinline__ void st_async4u(uint32_t a, const uint4& v, uint32_t bar) {
  asm volatile("st.async.weak.shared::cluster.mbarrier::complete_tx::bytes.v4.b32 [%0],{%1,%2,%3,%4},[%5];" ::"r"(a), "r"(v.x), "r"(v.y), "r"(v.z), "r"(v.w), "r"(bar) : "memory");
}
__device__ __forceinline__ uint4 ld_relaxed4(const void* p) {
  uint4 v; asm volatile("ld.relaxed.gpu.global.v4.u32 {%0,%1,%2,%3},[%4];" : "=r"(v.x), "=r"(v.y), "=r"(v.z), "=r"(v.w) : "l"(p) : "memory"); return v;
}
__device__ __forceinline__ uint32_t ld_relaxed(const void* p) {
  uint32_t v; asm volatile("ld.relaxed.gpu.global.u32 %0,[%1];" : "=r"(v) : "l"(p) : "memory"); return v;
}
__device__ __forceinline__ void st_relaxed(void* p, uint32_t v) { asm volatile("st.relaxed.gpu.global.b32 [%0],%1;" ::"l"(p), "r"(v) : "memory"); }
__device__ __forceinline__ void st_relaxed4(void* p, uint32_t v) { asm volatile("st.relaxed.gpu.global.v4.b32 [%0],{%1,%1,%1,%1};" ::"l"(p), "r"(v) : "memory"); }

__device__ __forceinline__ uint32_t ld_acquire(const void* p) {
  uint32_t v; asm volatile("ld.acquire.gpu.global.u32 %0,[%1];" : "=r"(v) : "l"(p) : "memory"); return v;
}
__device__ __forceinline__ float4 ld_relaxed4f(const void* p) {
  float4 v; asm volatile("ld.relaxed.gpu.global.v4.f32 {%0,%1,%2,%3},[%4];" : "=f"(v.x), "=f"(v.y), "=f"(v.z), "=f"(v.w) : "l"(p) : "memory"); return v;
}
__device__ __forceinline__ float2 ld_relaxed2f(const void* p) {
  float2 v; asm volatile("ld.relaxed.gpu.global.v2.f32 {%0,%1},[%2];" : "=f"(v.x), "=f"(v.y) : "l"(p) : "memory"); return v;
}
__device__ __forceinline__ void prefetch_l2(const void* p) { asm volatile("prefetch.global.L2 [%0];" ::"l"(p)); }
__device__ __forceinline__ void fence_gpu() { asm volatile("fence.acq_rel.gpu;" ::: "memory"); }
__device__ __forceinline__ void fence_async_all() { asm volatile("fence.proxy.async.global;" ::: "memory"); }
constexpr int SPIN_TOT = 1 << 22;
__device__ __forceinline__ void csignal(int idx) { asm volatile("red.release.gpu.global.add.u32 [%0],1;" ::"l"(&g_cnt[idx][0]) : "memory"); }
#define RLX 0
#define csignal_t(idx, role) csignal(idx)
__device__ __forceinline__ void cwait(int idx, uint32_t target, int& spin) {
  while (ld_acquire(&g_cnt[idx][0]) < target && spin < SPIN_TOT) spin += 16;
}

__device__ __forceinline__ uint64_t mkdesc(uint32_t addr, uint32_t lbo, uint32_t sbo) {
  return (uint64_t)((addr & 0x3FFFF) >> 4) | ((uint64_t)(lbo >> 4) << 16) | ((uint64_t)(sbo >> 4) << 32) | ((uint64_t)1 << 62);
}
__device__ __forceinline__ uint64_t mkdesc_ns(uint32_t addr, uint32_t lbo, uint32_t sbo) {
  return (uint64_t)((addr & 0x3FFFF) >> 4) | ((uint64_t)(lbo >> 4) << 16) | ((uint64_t)(sbo >> 4) << 32);
}
__device__ __forceinline__ void wg_fence() { asm volatile("wgmma.fence.sync.aligned;" ::: "memory"); }
__device__ __forceinline__ void wg_commit() { asm volatile("wgmma.commit_group.sync.aligned;" ::: "memory"); }
template <int N> __device__ __forceinline__ void wg_wait() { asm volatile("wgmma.wait_group.sync.aligned %0;" ::"n"(N) : "memory"); }

__device__ __forceinline__ void wgmma_rs16(float (&d)[8], const uint32_t (&a)[4], uint64_t db, int sc) {
  asm volatile("{.reg .pred p; setp.ne.b32 p,%13,0; wgmma.mma_async.sync.aligned.m64n16k16.f32.bf16.bf16 "
               "{%0,%1,%2,%3,%4,%5,%6,%7},{%8,%9,%10,%11},%12,p,1,1,0;}"
               : "+f"(d[0]), "+f"(d[1]), "+f"(d[2]), "+f"(d[3]), "+f"(d[4]), "+f"(d[5]), "+f"(d[6]), "+f"(d[7])
               : "r"(a[0]), "r"(a[1]), "r"(a[2]), "r"(a[3]), "l"(db), "r"(sc));
}
__device__ __forceinline__ void wgmma_rs64(float (&d)[32], const uint32_t (&a)[4], uint64_t db, int sc) {
  asm volatile("{.reg .pred p; setp.ne.b32 p,%37,0; wgmma.mma_async.sync.aligned.m64n64k16.f32.bf16.bf16 "
               "{%0,%1,%2,%3,%4,%5,%6,%7,%8,%9,%10,%11,%12,%13,%14,%15,%16,%17,%18,%19,%20,%21,%22,%23,%24,%25,%26,%27,%28,%29,%30,%31},{%32,%33,%34,%35},%36,p,1,1,0;}"
               : "+f"(d[0]), "+f"(d[1]), "+f"(d[2]), "+f"(d[3]), "+f"(d[4]), "+f"(d[5]), "+f"(d[6]), "+f"(d[7]), "+f"(d[8]), "+f"(d[9]), "+f"(d[10]), "+f"(d[11]), "+f"(d[12]), "+f"(d[13]), "+f"(d[14]), "+f"(d[15]), "+f"(d[16]), "+f"(d[17]), "+f"(d[18]), "+f"(d[19]), "+f"(d[20]), "+f"(d[21]), "+f"(d[22]), "+f"(d[23]), "+f"(d[24]), "+f"(d[25]), "+f"(d[26]), "+f"(d[27]), "+f"(d[28]), "+f"(d[29]), "+f"(d[30]), "+f"(d[31])
               : "r"(a[0]), "r"(a[1]), "r"(a[2]), "r"(a[3]), "l"(db), "r"(sc));
}
__device__ __forceinline__ void wgmma_rt16(float (&d)[8], const uint32_t (&a)[4], uint64_t db, int sc) {
  asm volatile("{.reg .pred p; setp.ne.b32 p,%13,0; wgmma.mma_async.sync.aligned.m64n16k16.f32.bf16.bf16 "
               "{%0,%1,%2,%3,%4,%5,%6,%7},{%8,%9,%10,%11},%12,p,1,1,1;}"
               : "+f"(d[0]), "+f"(d[1]), "+f"(d[2]), "+f"(d[3]), "+f"(d[4]), "+f"(d[5]), "+f"(d[6]), "+f"(d[7])
               : "r"(a[0]), "r"(a[1]), "r"(a[2]), "r"(a[3]), "l"(db), "r"(sc));
}
__device__ __forceinline__ void wgmma_rt80(float (&d)[40], const uint32_t (&a)[4], uint64_t db, int sc) {
  asm volatile("{.reg .pred p; setp.ne.b32 p,%45,0; wgmma.mma_async.sync.aligned.m64n80k16.f32.bf16.bf16 "
               "{%0,%1,%2,%3,%4,%5,%6,%7,%8,%9,%10,%11,%12,%13,%14,%15,%16,%17,%18,%19,%20,%21,%22,%23,%24,%25,%26,%27,%28,%29,%30,%31,%32,%33,%34,%35,%36,%37,%38,%39},{%40,%41,%42,%43},%44,p,1,1,1;}"
               : "+f"(d[0]), "+f"(d[1]), "+f"(d[2]), "+f"(d[3]), "+f"(d[4]), "+f"(d[5]), "+f"(d[6]), "+f"(d[7]), "+f"(d[8]), "+f"(d[9]), "+f"(d[10]), "+f"(d[11]), "+f"(d[12]), "+f"(d[13]), "+f"(d[14]), "+f"(d[15]), "+f"(d[16]), "+f"(d[17]), "+f"(d[18]), "+f"(d[19]), "+f"(d[20]), "+f"(d[21]), "+f"(d[22]), "+f"(d[23]), "+f"(d[24]), "+f"(d[25]), "+f"(d[26]), "+f"(d[27]), "+f"(d[28]), "+f"(d[29]), "+f"(d[30]), "+f"(d[31]), "+f"(d[32]), "+f"(d[33]), "+f"(d[34]), "+f"(d[35]), "+f"(d[36]), "+f"(d[37]), "+f"(d[38]), "+f"(d[39])
               : "r"(a[0]), "r"(a[1]), "r"(a[2]), "r"(a[3]), "l"(db), "r"(sc));
}
__device__ __forceinline__ void wgmma_rs32(float (&d)[16], const uint32_t (&a)[4], uint64_t db, int sc) {
  asm volatile("{.reg .pred p; setp.ne.b32 p,%21,0; wgmma.mma_async.sync.aligned.m64n32k16.f32.bf16.bf16 "
               "{%0,%1,%2,%3,%4,%5,%6,%7,%8,%9,%10,%11,%12,%13,%14,%15},{%16,%17,%18,%19},%20,p,1,1,0;}"
               : "+f"(d[0]), "+f"(d[1]), "+f"(d[2]), "+f"(d[3]), "+f"(d[4]), "+f"(d[5]), "+f"(d[6]), "+f"(d[7]), "+f"(d[8]), "+f"(d[9]), "+f"(d[10]), "+f"(d[11]), "+f"(d[12]), "+f"(d[13]), "+f"(d[14]), "+f"(d[15])
               : "r"(a[0]), "r"(a[1]), "r"(a[2]), "r"(a[3]), "l"(db), "r"(sc));
}
__device__ __forceinline__ void wgmma_ts32(float (&d)[16], uint64_t da, uint64_t db, int sc) {
  asm volatile("{.reg .pred p; setp.ne.b32 p,%18,0; wgmma.mma_async.sync.aligned.m64n32k16.f32.bf16.bf16 "
               "{%0,%1,%2,%3,%4,%5,%6,%7,%8,%9,%10,%11,%12,%13,%14,%15},%16,%17,p,1,1,1,0;}"
               : "+f"(d[0]), "+f"(d[1]), "+f"(d[2]), "+f"(d[3]), "+f"(d[4]), "+f"(d[5]), "+f"(d[6]), "+f"(d[7]), "+f"(d[8]), "+f"(d[9]), "+f"(d[10]), "+f"(d[11]), "+f"(d[12]), "+f"(d[13]), "+f"(d[14]), "+f"(d[15])
               : "l"(da), "l"(db), "r"(sc));
}
__device__ __forceinline__ void wgmma_rs8(float (&d)[4], const uint32_t (&a)[4], uint64_t db, int sc) {
  asm volatile("{.reg .pred p; setp.ne.b32 p,%9,0; wgmma.mma_async.sync.aligned.m64n8k16.f32.bf16.bf16 "
               "{%0,%1,%2,%3},{%4,%5,%6,%7},%8,p,1,1,0;}"
               : "+f"(d[0]), "+f"(d[1]), "+f"(d[2]), "+f"(d[3])
               : "r"(a[0]), "r"(a[1]), "r"(a[2]), "r"(a[3]), "l"(db), "r"(sc));
}
__device__ __forceinline__ void wgmma_ts16(float (&d)[8], uint64_t da, uint64_t db, int sc) {
  asm volatile("{.reg .pred p; setp.ne.b32 p,%10,0; wgmma.mma_async.sync.aligned.m64n16k16.f32.bf16.bf16 "
               "{%0,%1,%2,%3,%4,%5,%6,%7},%8,%9,p,1,1,1,0;}"
               : "+f"(d[0]), "+f"(d[1]), "+f"(d[2]), "+f"(d[3]), "+f"(d[4]), "+f"(d[5]), "+f"(d[6]), "+f"(d[7])
               : "l"(da), "l"(db), "r"(sc));
}
__device__ __forceinline__ void wgmma_ts64(float (&d)[32], uint64_t da, uint64_t db, int sc) {
  asm volatile("{.reg .pred p; setp.ne.b32 p,%34,0; wgmma.mma_async.sync.aligned.m64n64k16.f32.bf16.bf16 "
               "{%0,%1,%2,%3,%4,%5,%6,%7,%8,%9,%10,%11,%12,%13,%14,%15,%16,%17,%18,%19,%20,%21,%22,%23,%24,%25,%26,%27,%28,%29,%30,%31},%32,%33,p,1,1,1,0;}"
               : "+f"(d[0]), "+f"(d[1]), "+f"(d[2]), "+f"(d[3]), "+f"(d[4]), "+f"(d[5]), "+f"(d[6]), "+f"(d[7]), "+f"(d[8]), "+f"(d[9]), "+f"(d[10]), "+f"(d[11]), "+f"(d[12]), "+f"(d[13]), "+f"(d[14]), "+f"(d[15]), "+f"(d[16]), "+f"(d[17]), "+f"(d[18]), "+f"(d[19]), "+f"(d[20]), "+f"(d[21]), "+f"(d[22]), "+f"(d[23]), "+f"(d[24]), "+f"(d[25]), "+f"(d[26]), "+f"(d[27]), "+f"(d[28]), "+f"(d[29]), "+f"(d[30]), "+f"(d[31])
               : "l"(da), "l"(db), "r"(sc));
}
__device__ __forceinline__ void wgmma_tt16(float (&d)[8], uint64_t da, uint64_t db, int sc) {
  asm volatile("{.reg .pred p; setp.ne.b32 p,%10,0; wgmma.mma_async.sync.aligned.m64n16k16.f32.bf16.bf16 "
               "{%0,%1,%2,%3,%4,%5,%6,%7},%8,%9,p,1,1,1,1;}"
               : "+f"(d[0]), "+f"(d[1]), "+f"(d[2]), "+f"(d[3]), "+f"(d[4]), "+f"(d[5]), "+f"(d[6]), "+f"(d[7])
               : "l"(da), "l"(db), "r"(sc));
}
__device__ __forceinline__ void wgmma_tt40(float (&d)[20], uint64_t da, uint64_t db, int sc) {
  asm volatile("{.reg .pred p; setp.ne.b32 p,%22,0; wgmma.mma_async.sync.aligned.m64n40k16.f32.bf16.bf16 "
               "{%0,%1,%2,%3,%4,%5,%6,%7,%8,%9,%10,%11,%12,%13,%14,%15,%16,%17,%18,%19},%20,%21,p,1,1,1,1;}"
               : "+f"(d[0]), "+f"(d[1]), "+f"(d[2]), "+f"(d[3]), "+f"(d[4]), "+f"(d[5]), "+f"(d[6]), "+f"(d[7]), "+f"(d[8]), "+f"(d[9]), "+f"(d[10]), "+f"(d[11]), "+f"(d[12]), "+f"(d[13]), "+f"(d[14]), "+f"(d[15]), "+f"(d[16]), "+f"(d[17]), "+f"(d[18]), "+f"(d[19])
               : "l"(da), "l"(db), "r"(sc));
}
__device__ __forceinline__ void wgmma_ss8(float (&d)[4], uint64_t da, uint64_t db, int sc) {
  asm volatile("{.reg .pred p; setp.ne.b32 p,%6,0; wgmma.mma_async.sync.aligned.m64n8k16.f32.bf16.bf16 "
               "{%0,%1,%2,%3},%4,%5,p,1,1,0,0;}"
               : "+f"(d[0]), "+f"(d[1]), "+f"(d[2]), "+f"(d[3])
               : "l"(da), "l"(db), "r"(sc));
}
__device__ __forceinline__ void wgmma_ss32(float (&d)[16], uint64_t da, uint64_t db, int sc) {
  asm volatile("{.reg .pred p; setp.ne.b32 p,%18,0; wgmma.mma_async.sync.aligned.m64n32k16.f32.bf16.bf16 "
               "{%0,%1,%2,%3,%4,%5,%6,%7,%8,%9,%10,%11,%12,%13,%14,%15},%16,%17,p,1,1,0,0;}"
               : "+f"(d[0]), "+f"(d[1]), "+f"(d[2]), "+f"(d[3]), "+f"(d[4]), "+f"(d[5]), "+f"(d[6]), "+f"(d[7]), "+f"(d[8]), "+f"(d[9]), "+f"(d[10]), "+f"(d[11]), "+f"(d[12]), "+f"(d[13]), "+f"(d[14]), "+f"(d[15])
               : "l"(da), "l"(db), "r"(sc));
}
__device__ __forceinline__ void wgmma_st64(float (&d)[32], uint64_t da, uint64_t db, int sc) {
  asm volatile("{.reg .pred p; setp.ne.b32 p,%34,0; wgmma.mma_async.sync.aligned.m64n64k16.f32.bf16.bf16 "
               "{%0,%1,%2,%3,%4,%5,%6,%7,%8,%9,%10,%11,%12,%13,%14,%15,%16,%17,%18,%19,%20,%21,%22,%23,%24,%25,%26,%27,%28,%29,%30,%31},%32,%33,p,1,1,0,1;}"
               : "+f"(d[0]), "+f"(d[1]), "+f"(d[2]), "+f"(d[3]), "+f"(d[4]), "+f"(d[5]), "+f"(d[6]), "+f"(d[7]), "+f"(d[8]), "+f"(d[9]), "+f"(d[10]), "+f"(d[11]), "+f"(d[12]), "+f"(d[13]), "+f"(d[14]), "+f"(d[15]), "+f"(d[16]), "+f"(d[17]), "+f"(d[18]), "+f"(d[19]), "+f"(d[20]), "+f"(d[21]), "+f"(d[22]), "+f"(d[23]), "+f"(d[24]), "+f"(d[25]), "+f"(d[26]), "+f"(d[27]), "+f"(d[28]), "+f"(d[29]), "+f"(d[30]), "+f"(d[31])
               : "l"(da), "l"(db), "r"(sc));
}
__device__ __forceinline__ void wgmma_st128(float (&d)[64], uint64_t da, uint64_t db, int sc) {
  asm volatile("{.reg .pred p; setp.ne.b32 p,%66,0; wgmma.mma_async.sync.aligned.m64n128k16.f32.bf16.bf16 "
               "{%0,%1,%2,%3,%4,%5,%6,%7,%8,%9,%10,%11,%12,%13,%14,%15,%16,%17,%18,%19,%20,%21,%22,%23,%24,%25,%26,%27,%28,%29,%30,%31,%32,%33,%34,%35,%36,%37,%38,%39,%40,%41,%42,%43,%44,%45,%46,%47,%48,%49,%50,%51,%52,%53,%54,%55,%56,%57,%58,%59,%60,%61,%62,%63},%64,%65,p,1,1,0,1;}"
               : "+f"(d[0]), "+f"(d[1]), "+f"(d[2]), "+f"(d[3]), "+f"(d[4]), "+f"(d[5]), "+f"(d[6]), "+f"(d[7]), "+f"(d[8]), "+f"(d[9]), "+f"(d[10]), "+f"(d[11]), "+f"(d[12]), "+f"(d[13]), "+f"(d[14]), "+f"(d[15]), "+f"(d[16]), "+f"(d[17]), "+f"(d[18]), "+f"(d[19]), "+f"(d[20]), "+f"(d[21]), "+f"(d[22]), "+f"(d[23]), "+f"(d[24]), "+f"(d[25]), "+f"(d[26]), "+f"(d[27]), "+f"(d[28]), "+f"(d[29]), "+f"(d[30]), "+f"(d[31]), "+f"(d[32]), "+f"(d[33]), "+f"(d[34]), "+f"(d[35]), "+f"(d[36]), "+f"(d[37]), "+f"(d[38]), "+f"(d[39]), "+f"(d[40]), "+f"(d[41]), "+f"(d[42]), "+f"(d[43]), "+f"(d[44]), "+f"(d[45]), "+f"(d[46]), "+f"(d[47]), "+f"(d[48]), "+f"(d[49]), "+f"(d[50]), "+f"(d[51]), "+f"(d[52]), "+f"(d[53]), "+f"(d[54]), "+f"(d[55]), "+f"(d[56]), "+f"(d[57]), "+f"(d[58]), "+f"(d[59]), "+f"(d[60]), "+f"(d[61]), "+f"(d[62]), "+f"(d[63])
               : "l"(da), "l"(db), "r"(sc));
}

__device__ __forceinline__ void stsm4(uint32_t a, uint32_t r0, uint32_t r1, uint32_t r2, uint32_t r3) {
  asm volatile("stmatrix.sync.aligned.m8n8.x4.shared.b16 [%0],{%1,%2,%3,%4};" ::"r"(a), "r"(r0), "r"(r1), "r"(r2), "r"(r3) : "memory");
}
__device__ __forceinline__ void stsm4t(uint32_t a, uint32_t r0, uint32_t r1, uint32_t r2, uint32_t r3) {
  asm volatile("stmatrix.sync.aligned.m8n8.x4.trans.shared.b16 [%0],{%1,%2,%3,%4};" ::"r"(a), "r"(r0), "r"(r1), "r"(r2), "r"(r3) : "memory");
}
__device__ __forceinline__ void sts64(uint32_t a, uint32_t x, uint32_t y) { asm volatile("st.shared.v2.b32 [%0],{%1,%2};" ::"r"(a), "r"(x), "r"(y) : "memory"); }
__device__ __forceinline__ void st_async2u(uint32_t a, uint32_t x, uint32_t y, uint32_t bar) {
  asm volatile("st.async.weak.shared::cluster.mbarrier::complete_tx::bytes.v2.b32 [%0],{%1,%2},[%3];" ::"r"(a), "r"(x), "r"(y), "r"(bar) : "memory");
}
__device__ __forceinline__ void st_relaxed128(void* p, uint32_t x, uint32_t y, uint32_t z, uint32_t w) {
  asm volatile("{.reg .b128 v; mov.b128 v,{%1,%2,%3,%4}; st.relaxed.gpu.global.b128 [%0],v;}" ::"l"(p), "r"(x), "r"(y), "r"(z), "r"(w) : "memory");
}
__device__ __forceinline__ void st_relaxed64(void* p, uint32_t x, uint32_t y) {
  asm volatile("{.reg .b64 v; mov.b64 v,{%1,%2}; st.relaxed.gpu.global.b64 [%0],v;}" ::"l"(p), "r"(x), "r"(y) : "memory");
}
__device__ __forceinline__ uint4 ld_relaxed128(const void* p) {
  uint4 v;
  asm volatile("{.reg .b128 v; .reg .b64 lo, hi; ld.relaxed.gpu.global.b128 v,[%4]; mov.b128 {lo,hi},v; mov.b64 {%0,%1},lo; mov.b64 {%2,%3},hi;}" : "=r"(v.x), "=r"(v.y), "=r"(v.z), "=r"(v.w) : "l"(p) : "memory");
  return v;
}

__device__ __forceinline__ uint32_t pack_h2(float lo, float hi) {
  uint32_t r; asm("cvt.rn.satfinite.f16x2.f32 %0,%1,%2;" : "=r"(r) : "f"(hi), "f"(lo)); return r;
}
__device__ __forceinline__ void add_h2(float& lo, float& hi, uint32_t u, uint32_t v) {
  float a, b;
  asm("{.reg .b16 l, h; .reg .b32 s; add.rn.f16x2 s,%2,%3; mov.b32 {l,h},s; cvt.f32.f16 %0,l; cvt.f32.f16 %1,h;}" : "=f"(a), "=f"(b) : "r"(u), "r"(v));
  lo += a; hi += b;
}
__device__ __forceinline__ void mwait(uint32_t bar, uint32_t ph, int& spin) {
  asm volatile("{.reg .pred p, q;\nWAIT_LOOP:\n add.s32 %0,%0,1;\n setp.lt.s32 q,%0,%3;\n mbarrier.try_wait.parity.shared::cta.b64 p,[%1],%2;\n not.pred p,p;\n and.pred q,q,p;\n @q bra.uni WAIT_LOOP;\n}"
               : "+&r"(spin) : "r"(bar), "r"(ph), "n"(SPIN_TOT) : "memory");
}
__device__ __forceinline__ int keep(int x) { return __shfl_sync(0xffffffffu, x, threadIdx.x & 31); }
__device__ __forceinline__ uint32_t pin(uint32_t x) { asm volatile("" : "+r"(x)); return x; }
template <typename T> __device__ __forceinline__ T* pinp(T* x) { asm volatile("" : "+l"(x)); return x; }
__device__ __forceinline__ void st_async1u(uint32_t a, uint32_t x, uint32_t bar) {
  asm volatile("st.async.weak.shared::cluster.mbarrier::complete_tx::bytes.b32 [%0],%1,[%2];" ::"r"(a), "r"(x), "r"(bar) : "memory");
}
__device__ __forceinline__ uint32_t lds32(uint32_t a) { uint32_t v; asm volatile("ld.shared.b32 %0,[%1];" : "=r"(v) : "r"(a) : "memory"); return v; }
__device__ __forceinline__ uint2 lds64(uint32_t a) { uint2 v; asm volatile("ld.shared.v2.b32 {%0,%1},[%2];" : "=r"(v.x), "=r"(v.y) : "r"(a) : "memory"); return v; }

__device__ __forceinline__ void permute_cols(uint32_t tile, int tid, int n) {
#pragma unroll 2
  for (int it = tid; it < n; it += 128) {
    const int row = it >> 2, q = it & 3;
    const uint32_t a0 = tile + row * 128 + (((2 * q) ^ (row & 7)) << 4), a1 = tile + row * 128 + (((2 * q + 1) ^ (row & 7)) << 4);
    const uint4 u = lds128(a0), v = lds128(a1);
    sts128(a0, make_uint4(__byte_perm(u.x, u.y, 0x5410), __byte_perm(u.z, u.w, 0x5410), __byte_perm(v.x, v.y, 0x5410), __byte_perm(v.z, v.w, 0x5410)));
    sts128(a1, make_uint4(__byte_perm(u.x, u.y, 0x7632), __byte_perm(u.z, u.w, 0x7632), __byte_perm(v.x, v.y, 0x7632), __byte_perm(v.z, v.w, 0x7632)));
  }
}

__device__ __forceinline__ uint8_t* mkptr(uint32_t lo, uint32_t hi) { uint8_t* p; asm("mov.b64 %0,{%1,%2};" : "=l"(p) : "r"(lo), "r"(hi)); return p; }
__device__ __forceinline__ int uni(int x) { return __shfl_sync(0xffffffffu, x, 0); }

__device__ __forceinline__ bool elect_one() {
  uint32_t p; asm volatile("{.reg .pred q; elect.sync _|q, 0xffffffff; selp.u32 %0,1,0,q;}" : "=r"(p)); return p;
}
__device__ __forceinline__ uint64_t desc_at(uint64_t d, uint32_t off) {
  uint64_t r; asm("mov.b64 %0,{%1,%2};" : "=l"(r) : "r"((uint32_t)d + (off >> 4)), "r"((uint32_t)(d >> 32))); return r;
}
__device__ __forceinline__ uint32_t scale_bf16x2(uint32_t x, uint32_t s) { uint32_t r; asm("mul.rn.bf16x2 %0,%1,%2;" : "=r"(r) : "r"(x), "r"(s)); return r; }

__device__ __forceinline__ void stg128(void* p, const uint4& v) { asm volatile("st.global.v4.b32 [%0],{%1,%2,%3,%4};" ::"l"(p), "r"(v.x), "r"(v.y), "r"(v.z), "r"(v.w) : "memory"); }

__device__ __forceinline__ float quad_sum(float x) {
  const float a = __shfl_xor_sync(0xffffffffu, x, 1), b = __shfl_xor_sync(0xffffffffu, x, 2), c = __shfl_xor_sync(0xffffffffu, x, 3);
  return (x + a) + (b + c);
}
__device__ __forceinline__ float warp_sum(float x) {
  x = quad_sum(x);
  const float a = __shfl_xor_sync(0xffffffffu, x, 4), b = __shfl_xor_sync(0xffffffffu, x, 8), c = __shfl_xor_sync(0xffffffffu, x, 12);
  x = (x + a) + (b + c);
  return x + __shfl_xor_sync(0xffffffffu, x, 16);
}
__device__ __forceinline__ void ln_row(float4 (&v)[5]) {
  float t = 0.f;
#pragma unroll
  for (int m = 0; m < 5; m++) t += (v[m].x + v[m].y) + (v[m].z + v[m].w);
  const float mean = warp_sum(t) * (1.f / DM);
  float q0 = 0.f, q1 = 0.f;
#pragma unroll
  for (int m = 0; m < 5; m++) {
    v[m].x -= mean; v[m].y -= mean; v[m].z -= mean; v[m].w -= mean;
    q0 += v[m].x * v[m].x + v[m].y * v[m].y; q1 += v[m].z * v[m].z + v[m].w * v[m].w;
  }
  const float rs = rsqrtf(warp_sum(q0 + q1) * (1.f / DM) + 1e-5f);
#pragma unroll
  for (int m = 0; m < 5; m++) { v[m].x *= rs; v[m].y *= rs; v[m].z *= rs; v[m].w *= rs; }
}
__device__ __forceinline__ void ln0_load(const bf16* __restrict__ x, uint2 (&u)[5], int row, int lane) {
#pragma unroll
  for (int m = 0; m < 5; m++) u[m] = *reinterpret_cast<const uint2*>(x + (size_t)row * DM + m * 128 + lane * 4);
}
__device__ __forceinline__ void ln0_copy(const uint2 (&u)[5], int row, int lane) {
#pragma unroll
  for (int m = 0; m < 5; m++) stg128(g_x + (size_t)row * DM + m * 128 + lane * 4, make_uint4(u[m].x << 16, u[m].x & 0xFFFF0000u, u[m].y << 16, u[m].y & 0xFFFF0000u));
}
__device__ __forceinline__ void ln0_row(const uint2 (&u)[5], int row, int lane) {
  float4 v[5];
#pragma unroll
  for (int m = 0; m < 5; m++) v[m] = make_float4(bf_lo(u[m].x), bf_hi(u[m].x), bf_lo(u[m].y), bf_hi(u[m].y));
  ln_row(v);
  uint8_t* dst = g_xn[row >> 5] + ((row >> 3) & 3) * 4096 + (lane >> 4) * 1024 + (row & 7) * 128 + ((((lane >> 1) ^ row) & 7) << 4) + (lane & 1) * 8;
#pragma unroll
  for (int m = 0; m < 5; m++) *reinterpret_cast<uint2*>(dst + m * 16384) = make_uint2(pack_bf16(v[m].x, v[m].y), pack_bf16(v[m].z, v[m].w));
}

#define NOWORK 0
__device__ __forceinline__ void prep_row(const uint2 (&u)[5], const bf16* __restrict__ mem0, int k, int r, int lane) {
  const uint4 sent = make_uint4(SENT, SENT, SENT, SENT);
  if (k + 1 < NSTEP) {
    uint8_t* ex = ex_window(g_ex);
#pragma unroll
    for (int h = 0; h < 2; h++) {
      const int p = r * 40 + h * 32 + lane;
      if (h == 0 || lane < 8) {
        uint4 v = sent;
        if (k + 1 == LAG && (p & 8)) v = *reinterpret_cast<const uint4*>(mem0 + (p & 7) * DM + (p >> 4) * 8);
        stg128(ex + EX_M + (k + 1) * 20480 + p * 16, v);
      } else if (lane < 14) stg128(ex + EX_FLAG + (k + 1) * 3072 + (r * 6 + lane - 8) * 16, sent);
    }
  }
  if (k < LAG || k >= NSEG || NOWORK) {
    uint8_t* z = g_xn[k] + (r >> 3) * 4096 + (k < NSEG ? 2048 : 0) + (lane >> 4) * 1024 + (r & 7) * 128 + (lane & 15) * 8;
#pragma unroll
    for (int m = 0; m < 5; m++) *reinterpret_cast<uint2*>(z + m * 16384) = make_uint2(0, 0);
  }
  if (k < NSEG) {
    ln0_copy(u, k * 32 + r, lane);
    ln0_row(u, k * 32 + r, lane);
  }
}
__device__ __forceinline__ void pre_work(const bf16* __restrict__ x, const bf16* __restrict__ mem0, int cta, int tid) {
  constexpr int NT = 96 * 128;
  const int gt = cta * 128 + tid;
  uint8_t* ex = ex_window(g_ex);
#pragma unroll 1
  for (int row = cta + 96 * (tid >> 5); row < (NOWORK == 2 ? NSTEP : NPRE) * 32; row += 384) {
    uint2 u[5];
    ln0_load(x, u, min(row, SEQ - 1), tid & 31);
    prep_row(u, mem0, row >> 5, row & 31, tid & 31);
  }
#pragma unroll 1
  for (int i = gt; i < MAIL_BYTES / 16; i += NT) {
    stg128(ex + EX_MAIL + i * 16, make_uint4(SENT, SENT, SENT, SENT));
    stg128(ex + EX_MAIL + (1 << 20) + i * 16, make_uint4(SENT, SENT, SENT, SENT));
  }
  const int p = NT - 1 - gt;
  if (p < 1280) stg128(ex + EX_M + p * 16, *reinterpret_cast<const uint4*>(mem0 + (p & 7) * DM + (p >> 4) * 8));
  if (p < 192) stg128(ex + EX_FLAG + p * 16, make_uint4(0, 0, 0, 0));
  if (gt < 8 * CN_NUM) stg128(&g_cnt[0][0] + gt * 4, make_uint4(0, 0, 0, 0));
}
__device__ __forceinline__ void pre_wait(int which, uint32_t n, int& spin) {
  uint32_t old;
  asm volatile("atom.acq_rel.gpu.global.add.u32 %0,[%1],1;" : "=r"(old) : "l"(&g_ticket[which][0]) : "memory");
  const uint32_t target = (old / n + 1) * 96;
  while ((int)(ld_acquire(&g_ticket[0][0]) - target) < 0 && spin < SPIN_TOT) spin += 16;
  fence_async_all();
}

namespace C {
constexpr int NKR = 37;
constexpr int OFF_WQ = 0, OFF_WK = 81920;
constexpr int OFF_YO = 163840, OFF_YV = OFF_YO + 6144;
constexpr int OFF_M = 176128;
__host__ __device__ constexpr int og_off(int c) { return c ? OFF_M + 14336 + c * 2048 : 229376; }
constexpr int OFF_KT = 196608;
constexpr int OFF_XT = OFF_KT + 10240;
constexpr int OFF_VT = OFF_XT + 7168;
constexpr int OFF_XM = OFF_VT + 11392;
constexpr int OFF_PT = OFF_XM + 2560;
constexpr int KS = 1280, VS = 1408;
__host__ __device__ constexpr int slot_off(int p) { return p == 2 ? OFF_M : OFF_KT + (p % 3) * 16384; }
constexpr int OFF_ONE = 231424;
constexpr int OFF_BAR = 231552;
constexpr int OFF_SAFE = OFF_BAR + 144;
constexpr int OFF_TS = OFF_BAR + 256;
constexpr int SMEM = 232448;
constexpr uint32_t SB0 = 1024;
constexpr int BAR_F = OFF_BAR, BAR_XM = BAR_F + 40, BAR_XT = BAR_F + 48, BAR_OG = BAR_F + 56, BAR_E = OFF_BAR + 64, BAR_MOK = BAR_E + 40,
              BAR_M = OFF_BAR + 112, BAR_XF = OFF_BAR + 120, BAR_MF = OFF_BAR + 128, FLG_REDO = OFF_BAR + 136, BAR_W = OFF_BAR + 208;
constexpr int NB_PRO = 1, NB_RD = 2, NB_MR = 3, NB_QK = 4, NB_SM = 5, NB_VA = 6, NB_VQ = 7, NB_A = 8, NB_Q = 9, NB_C = 10, NB_WQ = 11, NB_QI = 12, NB_SI = 13, NB_WV = 14, NB_V = 15;
#define B1 600
#define AD0 16
#define AD1 128
#define AD2 16
#define AD3 128
#define BMX 1200
#define B2 800
#define FLP 1
#define OSG 2
#define OST 7
#define NBX 1
#define P1U 4
#define QIE 4
#define SIE 2
#define WOE 1
#define OGF 0
#define VSP 8
#define RFK 5
#define PFD 3
#define WOL 0
constexpr uint32_t SCQ = 0x3A003A00;
constexpr float SCE = 0.07216878364870322f * 1.4426950408889634f * 2048;
}

#define CBAR_SYNC(id, n) bar_sync(id, n)
#define CBAR_ARRIVE(id, n) bar_arrive(id, n)

__device__ __forceinline__ uint64_t wdesc(int off) { return mkdesc(C::SB0 + off, 8192, 1024); }
__device__ __forceinline__ uint64_t mdesc(int k) { return mkdesc_ns(C::SB0 + C::OFF_M + k * 512, 256, 128); }
__device__ __forceinline__ uint64_t tdesc(int k) { return mkdesc(C::SB0 + C::slot_off(k >> 3) + ((k >> 2) & 1) * 1024 + (k & 3) * 32, 16, 2048); }

__device__ __forceinline__ int dh_row(int n) { return (n & ~63) + (n & 32) + ((n >> 1) & 3) * 8 + ((n >> 3) & 3) * 2 + (n & 1); }
template <bool IS_O>
__device__ __forceinline__ void stage_box(const CUtensorMap& tm, uint32_t sb, int p, int cta, int rank) {
  using namespace C;
  const uint32_t bar = sb + BAR_W + 8 * p;
  const int head = cta / 3, col = head * DH + rank * 64;
  mbar_expect_tx(bar, 16384);
  if (!IS_O) tma2d(sb + OFF_WK + p * 16384, &tm, col, p * 128, bar);
  else for (int b = 2 * p - 1; b <= 2 * p; b++)
    tma2d(sb + OFF_WQ + (b + 1) * 8192, &tm, b < 0 ? 576 : (3 * rank + b / 3) * 64, b < 0 ? col : head * DH + ((rank + b) % 3) * 64, bar);
}
template <bool IS_O>
__device__ __forceinline__ void load_weights_rs(uint32_t (&wf)[C::NKR][4], const CUtensorMap& tms, const CUtensorMap& tm, int cta, int rank, uint32_t sb, int tid0, int& spin) {
  using namespace C;
  constexpr int STAGE = IS_O ? OFF_WQ : OFF_WK, YOFF = IS_O ? OFF_YO : OFF_YV, NB = IS_O ? NB_C : NB_V;
  const int i = (tid0 >> 3) & 3, n0 = (tid0 & 7) + (i >> 1) * 8;
  const int chunk = 2 * ((tid0 >> 5) & 3) + (i & 1);
  const int r0 = IS_O ? dh_row(n0) : n0, r1 = IS_O ? dh_row(n0 + 16) : n0 + 16;
  const uint32_t a0 = sb + STAGE + r0 * 128 + ((chunk ^ (r0 & 7)) << 4), a1 = sb + STAGE + r1 * 128 + ((chunk ^ (r1 & 7)) << 4);
#pragma unroll
  for (int p = 0; p < 5; p++) {
    mwait(sb + BAR_W + 8 * p, 0, spin);
    if (IS_O) PTS(8 + p);
    if (p + NBX < 5) { if ((tid0 & 127) == 96) stage_box<IS_O>(tms, sb, p + NBX, cta, rank); __syncwarp(); }
    if (IS_O) permute_cols(sb + STAGE + p * 16384, tid0, 512);
    else {
#pragma unroll 1
      for (int it = tid0 & 127; it < 256; it += 128) {
        const uint32_t base = sb + STAGE + p * 16384 + (it >> 1) * 128;
        const int sw = ((it >> 1) & 7) ^ ((it & 1) * 4);
        const uint4 u0 = lds128(base + (sw << 4)), u1 = lds128(base + ((sw ^ 1) << 4)), u2 = lds128(base + ((sw ^ 2) << 4)), u3 = lds128(base + ((sw ^ 3) << 4));
        sts128(base + (sw << 4), make_uint4(u0.x, u1.x, u2.x, u3.x)); sts128(base + ((sw ^ 1) << 4), make_uint4(u0.y, u1.y, u2.y, u3.y));
        sts128(base + ((sw ^ 2) << 4), make_uint4(u0.z, u1.z, u2.z, u3.z)); sts128(base + ((sw ^ 3) << 4), make_uint4(u0.w, u1.w, u2.w, u3.w));
      }
    }
    bar_sync(NB, 128);
#pragma unroll
    for (int k = 8 * p; k < 8 * p + 8; k++) {
      if (k < NKR) ldsm4t(wf[k < NKR ? k : 0], ((k & 1) ? a1 : a0) + (k >> 1) * 4096);
      else {
        const int n = k * 16 + ((tid0 & 127) >> 3), r = IS_O ? dh_row(n) : n, c = tid0 & 7;
        sts128(sb + YOFF + (n - NKR * 16) * 128 + ((c ^ (n & 7)) << 4), lds128(sb + STAGE + r * 128 + ((c ^ (r & 7)) << 4)));
      }
    }
    fence_async();
    bar_sync(NB, 128);
    if ((tid0 & 127) == 0) {
      mbar_expect_tx(sb + BAR_W + 8 * p, 16384);
      tma2d(sb + STAGE + p * 16384, &tm, (cta / 3) * DH + rank * 64, p * 128, sb + BAR_W + 8 * p);
    }
    __syncwarp();
  }
  PTS(IS_O ? 13 : 14);
  CBAR_SYNC(NB_PRO, 384);
}
template <int STRIDE>
__device__ __forceinline__ void store_mem(const float (&d)[8], uint32_t base, int tid) {
  const int m = (tid >> 3) & 3;
  stsm4(base + (((tid >> 5) & 3) * 2 + (m & 1)) * STRIDE + (m >> 1) * 640 + (tid & 7) * 16, pack_bf16(d[0], d[1]), pack_bf16(d[2], d[3]),
        pack_bf16(d[4], d[5]), pack_bf16(d[6], d[7]));
}

__device__ __forceinline__ void load_pair(uint32_t sb, int i, int p, uint32_t slot, uint32_t ph, int& spin) {
  using namespace C;
  mwait(sb + BAR_E + 8 * p, ph, spin);
  if (elect_one()) bulk_g2s_mc(sb + slot, g_xn[i] + p * 16384, 16384, sb + BAR_F + 8 * p);
}
__device__ __forceinline__ void release_round(uint32_t sb, int p, int lane) {
  if (lane < (p == 2 ? 3 : 1)) mbar_arrive_cluster(mapa(sb, p == 2 ? lane : p) + C::BAR_E + 8 * (3 + p));
}

template <int K0, int K1>
__device__ __forceinline__ void v_mem_pass(float (&d)[8], const uint32_t (&wf)[C::NKR][4]) {
  using namespace C;
  wg_fence();
#pragma unroll
  for (int k = K0; k < K1; k++) {
    if (k < NKR) wgmma_rs16(d, wf[k < NKR ? k : 0], mdesc(k), k != 32);
    else wgmma_ts16(d, wdesc(OFF_YV + (k - NKR) * 2048), mdesc(k), 1);
  }
  wg_commit();
}
__device__ __forceinline__ void chain_v(const CUtensorMap& tmWv, const CUtensorMap& tmWk, const uint32_t sb, const int tid0, const int cta, const int rank) {
  using namespace C;
  asm volatile("setmaxnreg.inc.sync.aligned.u32 208;");
  int spin = 0;
  uint32_t wf[NKR][4];
  const int wu = uni((tid0 >> 5) & 3);
  const uint32_t slot = rank == 2 ? OFF_M : OFF_KT + rank * 16384;
  load_weights_rs<false>(wf, tmWv, tmWk, cta, rank, sb, tid0, spin);
  PTS(5);
#pragma unroll 1
  for (int i = 0; i < NSTEP; i++) {
    {
      float d[32];
      if (i > 0) CBAR_SYNC(NB_WV, 256);
#pragma unroll
      for (int p = 0; p < 5; p++) {
        mwait(sb + BAR_F + 8 * p, i & 1, spin);
        TS(i, 25 + p);
        wg_fence();
#pragma unroll
        for (int k = 8 * p; k < 8 * p + 8; k++) {
          if (k < NKR) wgmma_rs64(d, wf[k < NKR ? k : 0], tdesc(k), k);
          else wgmma_ts64(d, wdesc(OFF_YV + (k - NKR) * 2048), tdesc(k), 1);
          if (k == 8 * p + 1 && p >= 1 && p <= 3) {
            wg_commit(); wg_wait<1>();
            release_round(sb, p - 1, tid0 & 31);
          }
          if (k == 8 * p + RFK && (p == 1 || p == 2)) {
            wg_commit();
            if (rank == p - 1 && wu == 0) load_pair(sb, i, p + 2, slot_off(p + 2), i & 1, spin);
            wg_fence();
          }
        }
        wg_commit();
      }
      wg_wait<0>();
      TS(i, 23);
      CBAR_SYNC(NB_RD, 256);
      const int tid = fresh(tid0) & 127, m = (tid >> 3) & 3;
      if (tid < 8) mbar_expect_tx(sb + BAR_F + 8 * tid, tid < 5 ? 16384 : tid == 5 ? 2560 : tid == 6 ? 7168 : 4096);
      if (tid < 3 && tid != rank) mbar_arrive_cluster(mapa(sb, tid) + BAR_XF);
      const uint32_t a = sb + OFF_VT + 256 + ((tid >> 5) * 2 + (m & 1)) * VS + (m >> 1) * 640 + (tid & 7) * 16;
#pragma unroll
      for (int s = 0; s < 4; s++)
        stsm4(a + s * 128, pack_bf16(d[8 * s], d[8 * s + 1]), pack_bf16(d[8 * s + 2], d[8 * s + 3]),
              pack_bf16(d[8 * s + 4], d[8 * s + 5]), pack_bf16(d[8 * s + 6], d[8 * s + 7]));
      if (tid < 80) sts128(sb + (tid < 72 ? OFF_VT + (tid >> 3) * VS : OFF_PT + 1280) + (tid & 7) * 16, make_uint4(0, 0, 0, 0));
      fence_async();
    }
    mwait(sb + BAR_XF, i & 1, spin);
    CBAR_ARRIVE(NB_QK, 384);
    const uint32_t* xc = &g_cnt[CN_X + i + 1][0];
    const uint32_t xn = i + 1 < LAG || NOWORK ? 16 : 48;
    bool seen = NOWORK == 2 || i + 1 < NPRE;
    if (wu == 0 && !seen) { seen = ld_acquire(xc) >= xn; fence_async_all(); }
    CBAR_SYNC(NB_QI, 256);
    float d[8];
    v_mem_pass<32, 40>(d, wf);
    CBAR_SYNC(NB_SM, 256);
    wg_wait<0>();
    if (__builtin_expect(lds32(sb + FLG_REDO), 0)) { v_mem_pass<32, 40>(d, wf); wg_wait<0>(); }
    if ((tid0 & 31) < 3 && (tid0 & 31) != rank) mbar_arrive_cluster(mapa(sb, tid0 & 31) + BAR_MF);
    v_mem_pass<0, 32>(d, wf);
    wg_wait<0>();
    TS(i, 24);
    const int tid = fresh(tid0);
    if ((tid & 31) == 0) mbar_arrive_cluster(mapa(sb, 2) + BAR_E + 16);
    store_mem<VS>(d, sb + OFF_VT + 128, tid);
    fence_async();
    CBAR_ARRIVE(NB_VA, 256);
    CBAR_ARRIVE(NB_VQ, 256);
    if (wu == 0 && i + 1 < NSTEP) {
      if (__builtin_expect(!seen, 0)) { while (ld_acquire(xc) < xn && spin < SPIN_TOT) spin += 16; fence_async_all(); }
      load_pair(sb, i + 1, rank, slot, i & 1, spin);
      TS(i + 1, 37);
    }
    TS_FLUSH(i - 1);
    __syncwarp();
  }
  CBAR_ARRIVE(NB_WV, 256);
  if (spin >= SPIN_TOT) g_err = 3;
}

__device__ __forceinline__ float quad_max(float x) {
  const float a = __shfl_xor_sync(0xffffffffu, x, 1), b = __shfl_xor_sync(0xffffffffu, x, 2), c = __shfl_xor_sync(0xffffffffu, x, 3);
  return fmaxf(fmaxf(x, a), fmaxf(b, c));
}
__device__ __forceinline__ float max10(const float (&y)[10]) {
  return fmaxf(fmaxf(fmaxf(fmaxf(y[0], y[1]), fmaxf(y[2], y[3])), fmaxf(fmaxf(y[4], y[5]), fmaxf(y[6], y[7]))), fmaxf(y[8], y[9]));
}
__device__ __forceinline__ float sum10(const float (&y)[10]) {
  return (((y[0] + y[1]) + (y[2] + y[3])) + ((y[4] + y[5]) + (y[6] + y[7]))) + (y[8] + y[9]);
}
__device__ __forceinline__ float rcp(float x) { float y; asm("rcp.approx.ftz.f32 %0,%1;" : "=f"(y) : "f"(x)); return y; }

__device__ __forceinline__ void signal_o(int i, int cta) { csignal(CN_O + i * 5 + min(cta / 19, 4)); }

__device__ __forceinline__ void chain_q(const bf16* x0, const bf16* mem0, const uint32_t sb, const int tid0, const int cta, const int rank) {
  using namespace C;
  asm volatile("setmaxnreg.dec.sync.aligned.u32 96;");
  int spin = 0;
  PTS(0);
  pre_work(x0, mem0, cta, tid0 & 127);
  PTS(3);
  CBAR_SYNC(NB_Q, 128);
  PTS(2);
  if (tid0 < 160) {
    if (tid0 == 128) pre_wait(0, 96, spin);
    __syncwarp();
    load_pair(sb, 0, rank, rank == 2 ? OFF_M : OFF_KT + rank * 16384, 1, spin);
  }
  PTS(4);
  CBAR_SYNC(NB_PRO, 384);
  mwait(sb + BAR_W, 1, spin);
  PTS(6);
  const int wu = uni((tid0 >> 5) & 3);
  uint4 ov[4] = {};
  uint8_t* op = &g_o[ORING - 1][cta][(tid0 & 124) * 32];
  const uint32_t o0 = ((tid0 ^ (tid0 >> 2)) & 3) * 16 + (tid0 & 16) * 4;
#pragma unroll 1
  for (int i = 0; i < NSTEP; i++) {
    const int ph = i & 1;
    uint32_t qf[4][4];
    {
      float d[64];
#define QK_STEP(K, SC) wgmma_st128(d, desc_at(mkdesc(SB0 + ((K) >> 2) * 1024 + ((K) & 3) * 32, 16, 2048), so), \
                                   desc_at(mkdesc(SB0 + OFF_WQ + (K) * 2048, OFF_WK - OFF_WQ, 1024), p * 16384), SC)
      int p = 0;
      uint32_t so = OFF_KT;
      mwait(sb + BAR_F, ph, spin);
      TS(i, 0);
      wg_fence();
#pragma unroll
      for (int k = 0; k < 8; k++) {
        QK_STEP(k, k);
        if (k == OST) {
          wg_commit();
          mwait(sb + BAR_F, ph, spin);
#pragma unroll
          for (int h = 0; h < 4; h++) stg128(op + (h & 1) * 4096 + (o0 ^ ((h >> 1) * 64)), ov[h]);
          if (i > 0) CBAR_ARRIVE(NB_MR, 160);
          if (k < 7) wg_fence();
        }
      }
      if (OST < 7) wg_commit();
#pragma unroll 1
      for (p = 1; p < 5; p++) {
        static_assert(OFF_KT - OFF_M == 5 << 12, "");
        so = OFF_M + (((0x95095u >> (4 * p)) & 15) << 12);
        if (i == 0) { mwait(sb + BAR_W + 8 * p, 1, spin); PTS(14 + p); }
        mwait(sb + BAR_F + 8 * p, ph, spin);
        wg_fence();
#pragma unroll
        for (int k = 0; k < 8; k++) {
          QK_STEP(k, 1);
          if (k == 1) {
            wg_commit(); wg_wait<1>();
            release_round(sb, p - 1, p < 4 ? tid0 & 31 : 32);
          }
        }
        wg_commit();
      }
#undef QK_STEP
      wg_wait<0>();
      TS(i, 1);
      CBAR_SYNC(NB_RD, 256);
      TSB(i, 2);
      const int tid = fresh(tid0), w = (tid >> 5) & 3, m = (tid >> 3) & 3;
      const uint32_t a = sb + OFF_KT + (m >> 1) * KS + (1 + w + 5 * (m & 1)) * 128 + (tid & 7) * 16;
#pragma unroll
      for (int s = 0; s < 4; s++)
        stsm4t(a + s * 2 * KS, pack_bf16(d[32 + 8 * s], d[33 + 8 * s]), pack_bf16(d[34 + 8 * s], d[35 + 8 * s]),
               pack_bf16(d[36 + 8 * s], d[37 + 8 * s]), pack_bf16(d[38 + 8 * s], d[39 + 8 * s]));
      fence_async();
      CBAR_ARRIVE(NB_QK, 384);
#pragma unroll
      for (int kk = 0; kk < 4; kk++)
#pragma unroll
        for (int j = 0; j < 4; j++) asm volatile("{.reg .b32 t; cvt.rn.bf16x2.f32 t,%1,%2; mul.rn.bf16x2 %0,t,%3;}" : "=r"(qf[kk][j]) : "f"(d[8 * kk + 2 * j + 1]), "f"(d[8 * kk + 2 * j]), "r"(SCQ));
    }
    CBAR_SYNC(NB_SI, 256);
    uint32_t pf[5][4];
    {
      float y0[10], y1[10];
      const int tidf = fresh(tid0), lane = tidf & 31;
      {
        float x[40];
        wg_fence();
#pragma unroll
        for (int kk = 0; kk < 4; kk++) wgmma_rt80(x, qf[kk], mkdesc_ns(SB0 + OFF_KT + kk * 2 * KS, KS, 128), kk);
        wg_commit();
        wg_wait<0>();
#pragma unroll
        for (int j = 0; j < 5; j++) { y0[2 * j] = x[4 * j]; y0[2 * j + 1] = x[4 * j + 1]; y1[2 * j] = x[22 + 4 * j]; y1[2 * j + 1] = x[23 + 4 * j]; }
      }
      TS(i, 17);
      const uint32_t xo = OFF_XT + (wu * (wu + 3) / 2) * 256 + lane * 16, x2 = xo + (wu >> 1) * 512 + 512 - lane * 8;
      {
        const uint4 h0 = make_uint4(pack_h2(y0[0], y0[1]), pack_h2(y1[0], y1[1]), pack_h2(y0[2], y0[3]), pack_h2(y1[2], y1[3]));
        const uint4 h1 = make_uint4(pack_h2(y0[4], y0[5]), pack_h2(y1[4], y1[5]), pack_h2(y0[6], y0[7]), pack_h2(y1[6], y1[7]));
        const uint32_t h2 = wu == 1 ? h1.x : pack_h2(y0[8], y0[9]), h3 = wu == 1 ? h1.y : pack_h2(y1[8], y1[9]);
        const uint32_t rb1 = mapa(sb, (rank + 1) % 3), rb2 = mapa(sb, (rank + 2) % 3);
        st_async4u(rb1 + xo + 3584, h0, rb1 + BAR_XT);
        st_async4u(rb2 + xo, h0, rb2 + BAR_XT);
        if (wu >= 2) { st_async4u(rb1 + xo + 4096, h1, rb1 + BAR_XT); st_async4u(rb2 + xo + 512, h1, rb2 + BAR_XT); }
        if (wu & 1) { st_async2u(rb1 + x2 + 3584, h2, h3, rb1 + BAR_XT); st_async2u(rb2 + x2, h2, h3, rb2 + BAR_XT); }
      }
      TS(i, 18);
      const int lim = 8 * wu + (lane >> 2) + 8 - 2 * (lane & 3);
#pragma unroll
      for (int j = 2; j < 10; j++)
        if (8 * (j >> 1) + (j & 1) > lim) { y0[j] = -INFINITY; y1[j] = -INFINITY; }
      mwait(sb + BAR_XT, ph, spin);
      TS(i, 19);
      {
        const uint4 u0 = lds128(sb + xo), v0 = lds128(sb + xo + 3584);
        uint2 u2 = make_uint2(0, 0), v2 = u2;
        if (wu & 1) { u2 = lds64(sb + x2); v2 = lds64(sb + x2 + 3584); }
        uint4 u1 = make_uint4(u2.x, u2.y, 0, 0), v1 = make_uint4(v2.x, v2.y, 0, 0);
        if (wu >= 2) { u1 = lds128(sb + xo + 512); v1 = lds128(sb + xo + 4096); }
        __syncwarp();
        if (lane == 0) mbar_arrive_cluster(mapa(sb, 0) + BAR_E);
        add_h2(y0[0], y0[1], u0.x, v0.x); add_h2(y1[0], y1[1], u0.y, v0.y); add_h2(y0[2], y0[3], u0.z, v0.z); add_h2(y1[2], y1[3], u0.w, v0.w);
        add_h2(y0[4], y0[5], u1.x, v1.x); add_h2(y1[4], y1[5], u1.y, v1.y); add_h2(y0[6], y0[7], u1.z, v1.z); add_h2(y1[6], y1[7], u1.w, v1.w);
        add_h2(y0[8], y0[9], u2.x, v2.x); add_h2(y1[8], y1[9], u2.y, v2.y);
      }
      const float m0 = quad_max(max10(y0)) * -SCE, m1 = quad_max(max10(y1)) * -SCE;
#pragma unroll
      for (int j = 0; j < 5; j++) {
        pf[j >> 1][2 * (j & 1)] = pack_bf16(ex2(fmaf(y0[2 * j], SCE, m0)), ex2(fmaf(y0[2 * j + 1], SCE, m0)));
        pf[j >> 1][2 * (j & 1) + 1] = tidf >> (10 + j);
        pf[(j + 5) >> 1][2 * ((j + 5) & 1)] = tidf >> (20 + j);
        pf[(j + 5) >> 1][2 * ((j + 5) & 1) + 1] = pack_bf16(ex2(fmaf(y1[2 * j], SCE, m1)), ex2(fmaf(y1[2 * j + 1], SCE, m1)));
      }
    }
#pragma unroll
    for (int q = 0; q < 20; q++) pf[q >> 2][q & 3] = pin(pf[q >> 2][q & 3]);
    CBAR_SYNC(NB_VQ, 256);
    TSB(i, 20);
    {
      float o[32], sm[4];
      wg_fence();
#pragma unroll
      for (int q = 0; q < 5; q++) wgmma_rs8(sm, pf[q], mkdesc_ns(SB0 + OFF_ONE, 0, 0), q);
#pragma unroll
      for (int q = 0; q < 5; q++) wgmma_rs64(o, pf[q], mkdesc_ns(SB0 + OFF_VT + 128 + q * 256, 128, VS), q);
      wg_commit();
      const int tid = fresh(tid0);
      op = &g_o[i % ORING][cta][(tid & 124) * 32];
      wg_wait<0>();
      TS(i, 21);
      if ((tid & 31) == 0) mbar_arrive_cluster(mapa(sb, 1) + BAR_E + 8);
      const float s0 = rcp(sm[0]), s1 = rcp(sm[2]);
#pragma unroll
      for (int h = 0; h < 2; h++) {
        const float* x = o + 16 * h;
        ov[2 * h] = make_uint4(pin(pack_bf16(x[0] * s0, x[1] * s0)), pin(pack_bf16(x[4] * s0, x[5] * s0)), pin(pack_bf16(x[8] * s0, x[9] * s0)), pin(pack_bf16(x[12] * s0, x[13] * s0)));
        ov[2 * h + 1] = make_uint4(pin(pack_bf16(x[2] * s1, x[3] * s1)), pin(pack_bf16(x[6] * s1, x[7] * s1)), pin(pack_bf16(x[10] * s1, x[11] * s1)), pin(pack_bf16(x[14] * s1, x[15] * s1)));
      }
      TS(i, 22);
      if (i + 1 < NSTEP) CBAR_SYNC(NB_WQ, 256); else CBAR_ARRIVE(NB_WQ, 256);
    }
  }
#pragma unroll
  for (int h = 0; h < 4; h++) stg128(op + (h & 1) * 4096 + (o0 ^ ((h >> 1) * 64)), ov[h]);
  CBAR_SYNC(NB_Q, 128);
  if (tid0 == 224) signal_o(NSTEP - 1, cta);
  if (spin >= SPIN_TOT) g_err = 2;
}

template <int NL> __device__ __forceinline__ void poll(uint4 (&x)[NL], const uint8_t* mb, uint32_t tag, int& spin);
template <> __device__ __forceinline__ void poll<4>(uint4 (&x)[4], const uint8_t* mb, uint32_t tag, int& spin) {
  asm volatile("{.reg .pred p<6>, q; .reg .b128 v; .reg .b32 t;\n"
               " ld.relaxed.gpu.global.b128 v,[%17+0]; mov.b128 {%0,%1,%2,%3},v;\n"
               " ld.relaxed.gpu.global.b128 v,[%17+512]; mov.b128 {%4,%5,%6,%7},v;\n"
               " ld.relaxed.gpu.global.b128 v,[%17+1024]; mov.b128 {%8,%9,%10,%11},v;\n"
               " ld.relaxed.gpu.global.b128 v,[%17+1536]; mov.b128 {%12,%13,%14,%15},v;\n"
               "POLL_LOOP:\n add.s32 %16,%16,16;\n"
               " lop3.b32 t,%0,%18,1,0x28; setp.ne.b32 p0,t,0;\n"
               " lop3.b32 t,%4,%18,1,0x28; setp.ne.b32 p1,t,0;\n"
               " lop3.b32 t,%8,%18,1,0x28; setp.ne.b32 p2,t,0;\n"
               " lop3.b32 t,%12,%18,1,0x28; setp.ne.b32 p3,t,0;\n"
               " or.pred q,p0,p1; or.pred q,q,p2; or.pred q,q,p3; setp.lt.and.s32 q,%16,%19,q; vote.sync.any.pred q,q,0xffffffff;\n"
               " mov.b128 v,{%0,%1,%2,%3}; @p0 ld.relaxed.gpu.global.b128 v,[%17+0]; mov.b128 {%0,%1,%2,%3},v;\n"
               " mov.b128 v,{%4,%5,%6,%7}; @p1 ld.relaxed.gpu.global.b128 v,[%17+512]; mov.b128 {%4,%5,%6,%7},v;\n"
               " mov.b128 v,{%8,%9,%10,%11}; @p2 ld.relaxed.gpu.global.b128 v,[%17+1024]; mov.b128 {%8,%9,%10,%11},v;\n"
               " mov.b128 v,{%12,%13,%14,%15}; @p3 ld.relaxed.gpu.global.b128 v,[%17+1536]; mov.b128 {%12,%13,%14,%15},v;\n"
               " @q bra.uni POLL_LOOP;\n}"
               : "=&r"(x[0].x), "=&r"(x[0].y), "=&r"(x[0].z), "=&r"(x[0].w), "=&r"(x[1].x), "=&r"(x[1].y), "=&r"(x[1].z), "=&r"(x[1].w), "=&r"(x[2].x), "=&r"(x[2].y), "=&r"(x[2].z), "=&r"(x[2].w), "=&r"(x[3].x), "=&r"(x[3].y), "=&r"(x[3].z), "=&r"(x[3].w), "+&r"(spin)
               : "l"(mb), "r"(tag), "n"(SPIN_TOT) : "memory");
}
template <> __device__ __forceinline__ void poll<6>(uint4 (&x)[6], const uint8_t* mb, uint32_t tag, int& spin) {
  asm volatile("{.reg .pred p<6>, q; .reg .b128 v; .reg .b32 t;\n"
               " ld.relaxed.gpu.global.b128 v,[%25+0]; mov.b128 {%0,%1,%2,%3},v;\n"
               " ld.relaxed.gpu.global.b128 v,[%25+512]; mov.b128 {%4,%5,%6,%7},v;\n"
               " ld.relaxed.gpu.global.b128 v,[%25+1024]; mov.b128 {%8,%9,%10,%11},v;\n"
               " ld.relaxed.gpu.global.b128 v,[%25+1536]; mov.b128 {%12,%13,%14,%15},v;\n"
               " ld.relaxed.gpu.global.b128 v,[%25+2048]; mov.b128 {%16,%17,%18,%19},v;\n"
               " ld.relaxed.gpu.global.b128 v,[%25+2560]; mov.b128 {%20,%21,%22,%23},v;\n"
               "POLL_LOOP:\n add.s32 %24,%24,16;\n"
               " lop3.b32 t,%0,%2,%26,0x7e; and.b32 t,t,1; setp.ne.b32 p0,t,0;\n"
               " lop3.b32 t,%4,%6,%26,0x7e; and.b32 t,t,1; setp.ne.b32 p1,t,0;\n"
               " lop3.b32 t,%8,%10,%26,0x7e; and.b32 t,t,1; setp.ne.b32 p2,t,0;\n"
               " lop3.b32 t,%12,%14,%26,0x7e; and.b32 t,t,1; setp.ne.b32 p3,t,0;\n"
               " lop3.b32 t,%16,%18,%26,0x7e; and.b32 t,t,1; setp.ne.b32 p4,t,0;\n"
               " lop3.b32 t,%20,%22,%26,0x7e; and.b32 t,t,1; setp.ne.b32 p5,t,0;\n"
               " or.pred q,p0,p1; or.pred q,q,p2; or.pred q,q,p3; or.pred q,q,p4; or.pred q,q,p5; setp.lt.and.s32 q,%24,%27,q; vote.sync.any.pred q,q,0xffffffff;\n"
               " mov.b128 v,{%0,%1,%2,%3}; @p0 ld.relaxed.gpu.global.b128 v,[%25+0]; mov.b128 {%0,%1,%2,%3},v;\n"
               " mov.b128 v,{%4,%5,%6,%7}; @p1 ld.relaxed.gpu.global.b128 v,[%25+512]; mov.b128 {%4,%5,%6,%7},v;\n"
               " mov.b128 v,{%8,%9,%10,%11}; @p2 ld.relaxed.gpu.global.b128 v,[%25+1024]; mov.b128 {%8,%9,%10,%11},v;\n"
               " mov.b128 v,{%12,%13,%14,%15}; @p3 ld.relaxed.gpu.global.b128 v,[%25+1536]; mov.b128 {%12,%13,%14,%15},v;\n"
               " mov.b128 v,{%16,%17,%18,%19}; @p4 ld.relaxed.gpu.global.b128 v,[%25+2048]; mov.b128 {%16,%17,%18,%19},v;\n"
               " mov.b128 v,{%20,%21,%22,%23}; @p5 ld.relaxed.gpu.global.b128 v,[%25+2560]; mov.b128 {%20,%21,%22,%23},v;\n"
               " @q bra.uni POLL_LOOP;\n}"
               : "=&r"(x[0].x), "=&r"(x[0].y), "=&r"(x[0].z), "=&r"(x[0].w), "=&r"(x[1].x), "=&r"(x[1].y), "=&r"(x[1].z), "=&r"(x[1].w), "=&r"(x[2].x), "=&r"(x[2].y), "=&r"(x[2].z), "=&r"(x[2].w), "=&r"(x[3].x), "=&r"(x[3].y), "=&r"(x[3].z), "=&r"(x[3].w), "=&r"(x[4].x), "=&r"(x[4].y), "=&r"(x[4].z), "=&r"(x[4].w), "=&r"(x[5].x), "=&r"(x[5].y), "=&r"(x[5].z), "=&r"(x[5].w), "+&r"(spin)
               : "l"(mb), "r"(tag), "n"(SPIN_TOT) : "memory");
}
template <int NL>
__device__ __forceinline__ void poll_add(const uint8_t* mb, uint32_t tag, float (&f)[8], uint8_t* flag, bool lead, int& spin) {
  uint4 x[NL];
  poll<NL>(x, mb, tag, spin);
  if (FLP == 0 && lead) st_relaxed(flag, 0);
#pragma unroll
  for (int i = 0; i < NL; i++) {
    const uint32_t u[4] = {x[i].x, x[i].y, x[i].z, x[i].w};
#pragma unroll
    for (int j = 0; j < 4; j++) {
      if (i == 0) { f[2 * j] = bf_lo(u[j]); f[2 * j + 1] = bf_hi(u[j]); }
      else { f[2 * j] += bf_lo(u[j]); f[2 * j + 1] += bf_hi(u[j]); }
    }
  }
}

template <int B, int SLOT>
__device__ __forceinline__ void wo_step(float (&acc)[8], const uint32_t (&wf)[C::NKR][4], int kk) {
  using namespace C;
  const int k = 4 * B + kk;
  const uint64_t db = mkdesc_ns(SB0 + og_off(SLOT) + kk * 512, 256, 128);
  if (k < NKR) wgmma_rt16(acc, wf[k < NKR ? k : 0], db, SLOT | kk);
  else wgmma_tt16(acc, wdesc(OFF_YO + (k - NKR) * 2048), db, 1);
}
template <int B, int SLOT>
__device__ __forceinline__ void wo_block(float (&acc)[8], const uint32_t (&wf)[C::NKR][4]) {
#pragma unroll
  for (int kk = 0; kk < 4; kk++) wo_step<B, SLOT>(acc, wf, kk);
}

__device__ __forceinline__ void chain_a(const CUtensorMap& tmWo, const CUtensorMap& tmWq, const uint32_t sb, const int tid0, const int cta, const int rank) {
  using namespace C;
  asm volatile("setmaxnreg.inc.sync.aligned.u32 200;");
  int spin = 0;
  uint32_t wf[NKR][4];
  load_weights_rs<true>(wf, tmWo, tmWq, cta, rank, sb, tid0, spin);
  const int wu = uni(tid0 >> 5);
  const bool t9 = cta >= 72 && cta < 88;
  const uint64_t exa = reinterpret_cast<uint64_t>(ex_window(g_ex));
  const uint32_t ehi = (uint32_t)(exa >> 32), elo = (uint32_t)exa;

  int b1 = B1, b2 = B2;
#pragma unroll 1
  for (int i = -1; i < NSTEP; i++) {
    const int ph = i & 1;
    if (i >= 0) {
      const int tid = fresh(tid0);
      const uint32_t mo = __shfl_xor_sync(0xffffffffu, elo + (ph << 20) + ((rank * 24 + (tid >> 4)) * 4 + (tid & 3)) * 2048 + (cta / 3) * 64 + (tid & 12) * 4, 0);
      const uint32_t m9 = __shfl_xor_sync(0xffffffffu, elo + (ph << 20) + MAIL9 + (((tid >> 4) * 2 + (tid & 1)) * 4 + (tid & 2)) * 3072 + cta * 32 + (tid & 12) * 2, 0);
      const uint32_t oo = __shfl_xor_sync(0xffffffffu, (tid >> 5) * 512 + (tid & 2) * 64 + (tid & 28) * 4 + (tid & 1) * 8, 0);
      if (i == 0) { mwait(sb + BAR_W + 24, 1, spin); mwait(sb + BAR_W + 32, 1, spin); PTS(7); }
      mwait(sb + BAR_M, ph, spin);
      TS(i, 3);
      {
        float x[20];
        int redo = 0;
      retry:
        bool bad;
        {
          float dq[8] = {}, dk[8] = {};
#pragma unroll 1
          for (int k0 = 0; k0 < 40; k0 += P1U) {
            wg_fence();
#pragma unroll
            for (int k = 0; k < P1U; k++) {
              if (k == P1U - QIE / 2 && k0 == 40 - P1U && !redo) CBAR_ARRIVE(NB_QI, 256);
              const uint64_t db = desc_at(mdesc(k), k0 * 512);
              wgmma_ts16(dq, desc_at(wdesc(OFF_WQ + k * 2048), k0 * 2048), db, 1);
              wgmma_ts16(dk, desc_at(wdesc(OFF_WK + k * 2048), k0 * 2048), db, 1);
            }
            wg_commit();
          }
          const int m = (tid >> 3) & 3, dg = (tid >> 5) * 2 + (m & 1);
          const uint32_t ka = sb + OFF_KT + dg * KS + (m >> 1) * 640 + (tid & 7) * 16;
          if (!redo) CBAR_SYNC(NB_QK, 384);
          sts32(sb + FLG_REDO, redo);
          wg_wait<0>();
          TS(i, 4);
          stsm4(ka, pack_bf16(dk[0], dk[1]), pack_bf16(dk[2], dk[3]), pack_bf16(dk[4], dk[5]), pack_bf16(dk[6], dk[7]));
          stsm4(ka + dg * (VS - KS) + (OFF_VT + 128 - OFF_KT), scale_bf16x2(pack_bf16(dq[0], dq[1]), SCQ), scale_bf16x2(pack_bf16(dq[2], dq[3]), SCQ),
                scale_bf16x2(pack_bf16(dq[4], dq[5]), SCQ), scale_bf16x2(pack_bf16(dq[6], dq[7]), SCQ));
          const float chk = (dq[0] + dq[1]) + (dq[4] + dq[5]);
          fence_async();
          bad = bar_red_or(NB_C, 128, chk != chk && !redo);
        }
        TSB(i, 5);
        wg_fence();
#pragma unroll
        for (int kk = 0; kk < 4; kk++) wgmma_tt40(x, mkdesc_ns(SB0 + OFF_VT + 128 + kk * 2 * VS, VS, 640), mkdesc_ns(SB0 + OFF_KT + kk * 2 * KS, KS, 128), kk);
#pragma unroll
        for (int kk = 0; kk < 4; kk++) {
          if (SIE && kk == 4 - SIE && !bad) CBAR_ARRIVE(NB_SI, 256);
          wgmma_tt40(x, mkdesc_ns(SB0 + OFF_VT + kk * 2 * VS, VS, 384), mkdesc_ns(SB0 + OFF_KT + 640 + kk * 2 * KS, KS, 128), 1);
        }
        wg_commit();
        if (!SIE && !bad) CBAR_ARRIVE(NB_SI, 256);
        if (__builtin_expect(__any_sync(0xffffffffu, bad), 0)) {
          wg_wait<0>();
#pragma unroll 1
          for (int k = 0; k < 10; k++) {
            uint4 v = lds128(sb + OFF_M + tid * 16 + k * 2048);
            if (v.x == SENT || v.y == SENT || v.z == SENT || v.w == SENT) {
              do { v = ld_relaxed4(mkptr(elo + EX_M + i * 20480 + tid * 16 + k * 2048, ehi)); spin += 16; } while ((v.x == SENT || v.y == SENT || v.z == SENT || v.w == SENT) && spin < SPIN_TOT);
              sts128(sb + OFF_M + tid * 16 + k * 2048, v);
            }
          }
          fence_async();
          bar_sync(NB_C, 128);
          redo = fresh(1);
          goto retry;
        }
        TSV(i, 36, redo);
        const uint32_t rb1 = mapa(sb, (rank + 1) % 3), rb2 = mapa(sb, (rank + 2) % 3);
        wg_wait<0>();
        TS(i, 6);
        if (wu < 2) {
          float y[10];
#pragma unroll
          for (int j = 0; j < 5; j++) { y[2 * j] = x[4 * j]; y[2 * j + 1] = x[4 * j + 1]; }
          const uint4 h0 = make_uint4(pack_h2(y[0], y[1]), pack_h2(y[2], y[3]), pack_h2(y[4], y[5]), pack_h2(y[6], y[7]));
          const uint32_t h1 = pack_h2(y[8], y[9]);
          st_async4u(rb1 + OFF_XM + 1024 + tid * 16, h0, rb1 + BAR_XM);
          st_async4u(rb2 + OFF_XM + tid * 16, h0, rb2 + BAR_XM);
          st_async1u(rb1 + OFF_XM + 2304 + tid * 4, h1, rb1 + BAR_XM);
          st_async1u(rb2 + OFF_XM + 2048 + tid * 4, h1, rb2 + BAR_XM);
          CBAR_ARRIVE(NB_SM, 256);
          if ((tid & 31) == 0) mbar_arrive_cluster(mapa(sb, 0) + BAR_E);
          TS(i, 7);
          const uint32_t sw = (tid & 7) * 4 + (tid & 8) * 8 + (tid & 16) * 2;
          mwait(sb + BAR_XM, ph, spin);
          TS(i, 8);
          const uint4 u0 = lds128(sb + OFF_XM + tid * 16), v0 = lds128(sb + OFF_XM + 1024 + tid * 16);
          const uint32_t u1 = lds32(sb + OFF_XM + 2048 + tid * 4), v1 = lds32(sb + OFF_XM + 2304 + tid * 4);
          add_h2(y[0], y[1], u0.x, v0.x); add_h2(y[2], y[3], u0.y, v0.y); add_h2(y[4], y[5], u0.z, v0.z); add_h2(y[6], y[7], u0.w, v0.w);
          add_h2(y[8], y[9], u1, v1);
          const float mx = quad_max(max10(y)) * -SCE;
#pragma unroll
          for (int j = 0; j < 5; j++) {
            y[2 * j] = ex2(fmaf(y[2 * j], SCE, mx)); y[2 * j + 1] = ex2(fmaf(y[2 * j + 1], SCE, mx));
            sts32(sb + OFF_PT + wu * 640 + sw + j * 128, pack_bf16(y[2 * j], y[2 * j + 1]));
          }
          sts32(sb + OFF_XM + 2048 + wu * 128 + sw, __float_as_uint(sum10(y)));
          fence_async();
          TS(i, 9);
        } else {
          CBAR_ARRIVE(NB_SM, 256);
          if ((tid & 31) == 0) mbar_arrive_cluster(mapa(sb, 0) + BAR_E);
          mwait(sb + BAR_MF, ph, spin);
        }
      }
      CBAR_SYNC(NB_VA, 256);
      TSB(i, 10);
      {
        float o[2][4];
        wg_fence();
#pragma unroll
        for (int c = 0; c < 2; c++)
#pragma unroll
          for (int q = 0; q < 3; q++)
            wgmma_ss8(o[c], mkdesc_ns(SB0 + OFF_VT + 128 + c * 640 + q * 256, 128, VS), mkdesc_ns(SB0 + OFF_PT + c * 640 + q * 256, q == 2 && c == 0 ? 768 : 128, 128), q);
        wg_commit();
        const float4 e = lds128f(sb + OFF_XM + 2048 + (tid & 15) * 16);
        const uint32_t rb1 = mapa(sb, (rank + 1) % 3), rb2 = mapa(sb, (rank + 2) % 3);
        const float inv = rcp((e.x + e.y) + (e.z + e.w));
        const int sl = (tid & 3) * 2;
        const float i0 = __shfl_sync(0xffffffffu, inv, sl), i1 = __shfl_sync(0xffffffffu, inv, sl + 1);
        const float i2 = __shfl_sync(0xffffffffu, inv, sl + 8), i3 = __shfl_sync(0xffffffffu, inv, sl + 9);
        wg_wait<0>();
        TS(i, 11);
        const uint32_t p0 = pack_bf16(o[0][0] * i0, o[0][1] * i1), p1 = pack_bf16(o[1][0] * i2, o[1][1] * i3);
        const uint32_t p2 = pack_bf16(o[0][2] * i0, o[0][3] * i1), p3 = pack_bf16(o[1][2] * i2, o[1][3] * i3);
        if (OGF) { sts64(sb + oo + og_off(0), p0, p1); sts64(sb + oo + og_off(0) + 256, p2, p3); fence_async(); }
        st_async2u(rb1 + oo + og_off(2), p0, p1, rb1 + BAR_OG);
        st_async2u(rb2 + oo + og_off(1), p0, p1, rb2 + BAR_OG);
        st_async2u(rb1 + oo + og_off(2) + 256, p2, p3, rb1 + BAR_OG);
        st_async2u(rb2 + oo + og_off(1) + 256, p2, p3, rb2 + BAR_OG);
        if (!OGF) { sts64(sb + oo + og_off(0), p0, p1); sts64(sb + oo + og_off(0) + 256, p2, p3); fence_async(); }
      }
      CBAR_SYNC(NB_A, 128);
      TSB(i, 12);
      {
        float acc[3][8];
        wg_fence();
        wo_block<0, 0>(acc[2], wf);
        wg_commit();
        if (tid == 0) mbar_arrive_cluster(mapa(sb, 1) + BAR_E + 8);
        wo_block<1, 0>(acc[0], wf);
        wo_block<4, 0>(acc[1], wf);
        wg_commit();
        const uint32_t tag = (i >> 1) & 1;
#define TAGGED(LO, HI) ((pack_bf16(LO, HI) & ~1u) | tag)
#define SEND(OFF, U) st_relaxed128(mkptr(mo, ehi) + (OFF), TAGGED(acc[U][0], acc[U][2]), pack_bf16(acc[U][1], acc[U][3]), pack_bf16(acc[U][4], acc[U][6]), pack_bf16(acc[U][5], acc[U][7]))
        wg_wait<1>();
        const uint32_t n0 = pin(TAGGED(acc[2][0], acc[2][2])), n1 = pin(pack_bf16(acc[2][1], acc[2][3]));
        const uint32_t n2 = pin(TAGGED(acc[2][4], acc[2][6])), n3 = pin(pack_bf16(acc[2][5], acc[2][7]));
        wg_fence();
        wo_block<7, 0>(acc[2], wf);
        wg_commit();
        st_relaxed64(mkptr(m9, ehi), n0, n1);
        st_relaxed64(mkptr(m9, ehi) + 3072, n2, n3);
        mwait(sb + BAR_OG, ph, spin);
        asm volatile("fence.proxy.async::generic.acquire.sync_restrict::shared::cluster.cluster;" ::: "memory");
        TS(i, 13);
        wg_fence();
        wo_block<2, 1>(acc[0], wf); wo_block<3, 2>(acc[0], wf);
        wg_commit();
        wo_block<5, 1>(acc[1], wf); wo_block<6, 2>(acc[1], wf);
        wg_commit();
        wg_wait<1>(); SEND(0, 0);
        wo_block<8, 1>(acc[2], wf); wo_block<9, 2>(acc[2], wf);
        wg_commit();
        if (WOE == 0) { CBAR_ARRIVE(NB_WV, 256); CBAR_ARRIVE(NB_WQ, 256); }
        wg_wait<1>(); SEND(32 * 2048, 1);
        if (WOE == 1) CBAR_ARRIVE(NB_WV, 256);
        wg_wait<0>(); SEND(64 * 2048, 2);
        if (WOE == 2) CBAR_ARRIVE(NB_WV, 256);
        if (WOE >= 1) CBAR_ARRIVE(NB_WQ, 256);
#undef SEND
#undef TAGGED
      }
      TS(i, 14);
      if (i < 2) PTS(19 + i);
      if (i + 1 >= NSTEP) break;
    }
    uint32_t t1 = clk32();
    if (i >= 0) {
      const int lane = fresh(tid0) & 31, j = lane >> 3;
      const uint8_t* mb = mkptr(elo + (ph << 20) + (t9 ? MAIL9 + (cta - 72) * 12288 + wu * 3072 : (cta < 72 ? cta : cta - 24) * 8192 + wu * 2048) + lane * 16, ehi);
      const uint32_t tag = (i >> 1) & 1;
      const bool pub = (lane & (t9 ? 6 : 4)) == 0 && !(((t9 ? cta : wu) & 1) && i + 1 == LAG) && cta < 88;
      const uint32_t dst = pin(elo + EX_M + (i + 1) * 20480 + (t9 ? (cta + 72) * 128 + wu * 32 + (j & 1) * 16 + (lane & 1) * 8 + (j >> 1) * 4
                                                                   : cta * 256 + (wu & 1) * 128 + (wu >> 1) * 64 + j * 16 + (lane & 3) * 4));
      uint8_t* flag = mkptr(elo + EX_FLAG + (i + 1) * 3072 + cta * 32 + wu * 4, ehi);
      while (clk32() - t1 < b1) {}
      TS(i + 1, 30);
      float f[8];
      const int n0 = spin;
      if (!t9) poll_add<4>(mb, tag, f, flag, lane == 0, spin);
      else poll_add<6>(mb, tag, f, flag, lane == 0, spin);
      if (FLP == 1 && lane == 0) st_relaxed(flag, __float_as_uint(f[0] + f[7]) >> 1);
      t1 = clk32();
      b1 = __any_sync(0xffffffffu, spin - n0 > 16) ? min(b1 + AD1, BMX) : max(b1 - AD0, 0);
      TSV(i + 1, 38, b1);
      TS(i + 1, 31); TSV(i + 1, 32, (spin - n0) >> 4);
      const bool h = lane & 16, q = lane & 8;
#pragma unroll
      for (int j = 0; j < 4; j++) f[j] = (h ? f[4 + j] : f[j]) + __shfl_xor_sync(0xffffffffu, h ? f[j] : f[4 + j], 16);
#pragma unroll
      for (int j = 0; j < 2; j++) f[j] = (q ? f[2 + j] : f[j]) + __shfl_xor_sync(0xffffffffu, q ? f[j] : f[2 + j], 8);
      f[0] += __shfl_xor_sync(0xffffffffu, f[0], 4); f[1] += __shfl_xor_sync(0xffffffffu, f[1], 4);
      if (t9) { f[0] += __shfl_xor_sync(0xffffffffu, f[0], 2); f[1] += __shfl_xor_sync(0xffffffffu, f[1], 2); }
      if (pub) st_relaxed(mkptr(dst, ehi), pack_bf16(f[0], f[1]));
      if (FLP == 2 && lane == 0) st_relaxed(flag, 0);
      if (wu == 3) {
        CBAR_SYNC(NB_MR, 160);
        if (elect_one()) signal_o(i, cta);
      }
      TS(i + 1, 15);
    }
    if (wu == 0) {
      const int tid = fresh(tid0);
      const uint8_t* pp = mkptr(elo + EX_FLAG + (i + 1) * 3072 + (rank * 28 + (tid < 28 || rank == 2 ? tid : 0)) * 32, ehi);
      while (clk32() - t1 < b2) {}
      TS(i + 1, 16);
      int n = 1;
      uint4 x = ld_relaxed4(pp);
      if (tid0 == 0) mbar_expect_tx(sb + BAR_M, 20480);
      bool mok = mbar_test(sb + BAR_MOK, ph ^ 1);
      while (__any_sync(0xffffffffu, (int)(x.x | x.y | x.z | x.w) < 0 && spin < SPIN_TOT)) { x = ld_relaxed4(pp); mok = mbar_test(sb + BAR_MOK, ph ^ 1); n++; spin += 16; }
      if (!mok) mwait(sb + BAR_MOK, ph ^ 1, spin);
      b2 = n > 1 ? min(b2 + AD3, BMX) : max(b2 - AD2, 0);
      TSV(i + 1, 35, n); TSV(i + 1, 39, b2);
      TS(i + 1, 34);
      if (elect_one()) bulk_g2s_mc(sb + OFF_M + rank * 7168, mkptr(elo + EX_M + (i + 1) * 20480 + rank * 7168, ehi), rank == 2 ? 6144 : 7168, sb + BAR_M);
      TS(i + 1, 33);
      __syncwarp();
    }
  }
  if (spin >= SPIN_TOT) g_err = 1;
}

__global__ void __cluster_dims__(3, 1, 1) __launch_bounds__(384, 1)
k_chain(const __grid_constant__ CUtensorMap tmWq, const __grid_constant__ CUtensorMap tmWk,
        const __grid_constant__ CUtensorMap tmWv, const __grid_constant__ CUtensorMap tmWo, const bf16* __restrict__ x0, const bf16* __restrict__ mem0) {
  using namespace C;
  extern __shared__ __align__(1024) uint8_t smem[];
  const uint32_t sb = smem_u32(smem);
  const int tid = threadIdx.x;
  const int wg = __shfl_sync(0xffffffffu, tid >> 7, 0);
  const int cta = uni(blockIdx.x), rank = uni(blockIdx.x % 3);

  asm volatile("griddepcontrol.launch_dependents;");
  if (cta < 4) prefetch_l2(tid < 320 ? x0 + (cta * 320 + tid) * 64 : mem0 + (cta * 20 + tid % 20) * 64);
  if (tid == 32) {
    for (int p = 0; p < 5; p++) mbar_init(sb + BAR_W + 8 * p, 2);
    fence_async();
    for (int p = 0; p < NBX; p++) { stage_box<false>(tmWv, sb, p, cta, rank); stage_box<true>(tmWo, sb, p, cta, rank); }
  }
  if (tid == 0) {
    if ((sb & 0xFFFFFF) != SB0) g_err = 100;
    for (int p = 0; p < 5; p++) { mbar_init(sb + BAR_F + 8 * p, 1); mbar_init(sb + BAR_E + 8 * p, p == 2 ? 12 : p == 1 ? 15 : 24); }
    mbar_init(sb + BAR_M, 1); mbar_init(sb + BAR_MOK, 24); mbar_init(sb + BAR_XM, 1); mbar_init(sb + BAR_XF, 2);
    mbar_init(sb + BAR_XT, 1); mbar_init(sb + BAR_MF, 8); mbar_init(sb + BAR_OG, 1);
    for (int p = 0; p < 5; p++) mbar_expect_tx(sb + BAR_F + 8 * p, 16384);
    for (int p = 0; p < 16; p++) sts32(sb + OFF_SAFE + 4 * p, 0);
    for (int p = 0; p < 32; p++) sts32(sb + OFF_ONE + 4 * p, 0x3F803F80);
    asm volatile("fence.mbarrier_init.release.cluster;" ::: "memory");
    fence_async();
  }
  __syncthreads();
  asm volatile("barrier.cluster.arrive.relaxed.aligned;" ::: "memory");
  asm volatile("barrier.cluster.wait.aligned;" ::: "memory");

  if (wg == 0) chain_a(tmWo, tmWq, sb, keep(tid), cta, rank);
  else if (wg == 1) chain_q(x0, mem0, sb, keep(tid), cta, rank);
  else chain_v(tmWv, tmWk, sb, keep(tid), cta, rank);
  asm volatile("barrier.cluster.arrive.release.aligned;" ::: "memory");
  asm volatile("barrier.cluster.wait.acquire.aligned;" ::: "memory");
}

namespace W {
constexpr int NP = 25, NBC = 11, NW = NP + NBC;
constexpr int PRS = 37, PW = 43 * 2048;
constexpr int OFF_W = 0;
constexpr int OFF_R = 2 * PW;
constexpr int QRS = 35, KRS = 37;
constexpr int OFF_WV = 0, OFF_YQ = 81920, OFF_YK = OFF_YQ + (40 - QRS) * 2048, OFF_WO = OFF_YK + (40 - KRS) * 2048;
constexpr int OFF_G = OFF_WO + 39 * 2048;
constexpr int OFF_X = OFF_G + 20480;
constexpr int COL = 976;
constexpr int OFF_T = OFF_X;
constexpr int OFF_H = OFF_X + 24576;
constexpr int OFF_BAR = OFF_H + 8 * COL;
constexpr int OFF_SAFE = OFF_BAR + 192;
constexpr int SMEM = 232448;
static_assert(OFF_SAFE + 64 <= SMEM && OFF_R + 40960 <= OFF_BAR, "");
constexpr uint32_t SB0 = 1024;
constexpr int BAR_F = OFF_BAR, BAR_E = OFF_BAR + 40, BAR_G = OFF_BAR + 80, BAR_H = OFF_BAR + 120, BAR_W = OFF_BAR + 160, BAR_GO = OFF_BAR + 176;
constexpr int NB_G0 = 1, NB_SG = 4, NB_B = 5, NB_AS = 6, NB_PK = 8, NB_PV = 9, NB_TD = 10;
}
#define OBP 1
#define GLA 0
#define HOLD 2
#define WBAR_SYNC(id, n) bar_sync(id, n)
#define WBAR_ARRIVE(id, n) bar_arrive(id, n)

__device__ __forceinline__ uint64_t rdesc(int off, int kk) { return mkdesc(W::SB0 + off + kk * 32, 16, 1024); }
__device__ __forceinline__ uint32_t frag_addr(uint32_t base, int tid) {
  const int i = (tid >> 3) & 3, r = tid & 7;
  return base + (r + (i >> 1) * 8) * 128 + (((2 * ((tid >> 5) & 3) + (i & 1)) ^ r) << 4);
}
template <int NK>
__device__ __forceinline__ void load_frags(uint32_t (&wf)[NK][4], uint32_t base, int tid) {
  const uint32_t a0 = frag_addr(base, tid);
#pragma unroll
  for (int k = 0; k < NK; k++) ldsm4t(wf[k], a0 + k * 2048);
}
__device__ __forceinline__ void red_tile(const float* d, int seg, int col0, int tid) {
  float* p = g_x + (size_t)(seg * 32 + 2 * (tid & 3)) * DM + col0 + ((tid >> 5) & 3) * 16 + ((tid >> 2) & 7) * 2;
#pragma unroll
  for (int j = 0; j < 8; j++)
    asm volatile("red.relaxed.gpu.global.add.v2.f32 [%0],{%1,%2};" ::"l"(p + ((j >> 1) * 8 + (j & 1)) * DM), "f"(d[4 * (j >> 1) + (j & 1)]), "f"(d[4 * (j >> 1) + 2 + (j & 1)]) : "memory");
}
#define FOR_SEGS(l, s)                                            \
  for (int j_ = 0; j_ < 2 * NSTEP; j_++) {                        \
    const int l = j_ & 1, s = (j_ >> 1) - l * LAG;                \
    if (s < 0 || s >= NSEG) continue;

template <int WG>
__device__ __forceinline__ void work_p(const CUtensorMap& tmWo, uint32_t sb, int pc, int tid0) {
  using namespace W;
  asm volatile("setmaxnreg.inc.sync.aligned.u32 208;");
  int spin = 0;
  const int ks = pc / 5, col0 = (pc % 5) * 128 + WG * 64;
  const uint32_t wb = sb + OFF_W + WG * PW;
  uint32_t wf[PRS][4];
#pragma unroll 1
  for (int hf = 0; hf < 2; hf++) {
    const int nk = hf ? 80 - PRS : PRS;
    if ((tid0 & 127) == 0) {
      mbar_expect_tx(sb + BAR_W + 8 * WG, nk * 2048);
      for (int i = 0; i < nk; i++) tma2d(wb + i * 2048, &tmWo, col0, ks * 19 * 64 + (i < PRS ? 2 * i + hf : PRS + i) * 16, sb + BAR_W + 8 * WG);
    }
    __syncwarp();
    mwait(sb + BAR_W + 8 * WG, hf, spin);
    permute_cols(wb, tid0 & 127, nk * 64);
    if (hf == 1 && ks < 4) for (int it = 39 * 64 + (tid0 & 127) - 64; it < 43 * 64; it += 128) {
      const uint32_t a = wb + (it >> 2) * 128 + (((2 * (it & 3)) ^ ((it >> 2) & 6)) << 4);
      if (it >= 39 * 64) { sts128(a, make_uint4(0, 0, 0, 0)); sts128(a + 16, make_uint4(0, 0, 0, 0)); }
    }
    fence_async();
    WBAR_SYNC(NB_G0 + WG, 128);
    if (hf == 0) {
      load_frags<PRS>(wf, wb, tid0);
      fence_async();
      WBAR_SYNC(NB_G0 + WG, 128);
    }
  }
#pragma unroll 1
  for (int k = 0; k < NSTEP; k++) {
    float d[32];
#pragma unroll
    for (int f = 0; f < 20; f++) {
      mwait(sb + BAR_F + 8 * (f % 5), (f / 5) & 1, spin);
      if (f == 0 && WG == 0 && pc == WW) WTS(k, 1);
      wg_fence();
#pragma unroll
      for (int kk = 0; kk < 4; kk++) {
        const int q = 4 * f + kk;
        if (q < 2 * PRS && !(q & 1)) wgmma_rs64(d, wf[q < 2 * PRS ? q >> 1 : 0], rdesc(OFF_R + (f % 5) * 8192, kk), q);
        else wgmma_ts64(d, mkdesc(SB0 + OFF_W + WG * PW + (q < 2 * PRS ? q >> 1 : q - PRS) * 2048, 8192, 1024), rdesc(OFF_R + (f % 5) * 8192, kk), 1);
        if (kk == 0 && f > 0) {
          wg_commit();
          wg_wait<1>();
          if ((tid0 & 31) == 0) mbar_arrive(sb + BAR_E + 8 * ((f - 1) % 5));
        }
      }
      wg_commit();
    }
    wg_wait<0>();
    if ((tid0 & 31) == 0) mbar_arrive(sb + BAR_E + 32);
    if (WG == 0 && pc == WW) WTS(k, 2);
    if (k < NSEG) red_tile(d, k, col0, tid0);
    if (k >= LAG) red_tile(d + 16, k - LAG, col0, tid0);
    if (WG == 0 && pc == WW) WTS(k, 13);
    WBAR_SYNC(NB_SG, 256);
    if (WG == 0) { if (tid0 == 0) csignal_t(CN_P + k, 3); __syncwarp(); }
  }
  if (spin >= SPIN_TOT) g_err = 11;
}
__device__ __forceinline__ void work_p_producer(uint32_t sb, int pc, int odd) {
  using namespace W;
  int spin = 0;
  const int ks = pc / 5;
#pragma unroll 1
  for (int k = 0; k < NSTEP; k++) {
    const uint32_t lo = k < NSEG ? 0 : 4096, len = k < LAG || k >= NSEG ? 4096 : 8192;
    const uint8_t* src = &g_o[k % ORING][ks * 19 + odd][lo];
    cwait(CN_O + k * 5 + ks, ks == 4 ? 20 : 19, spin);
    fence_async_all();
    if (pc == WW && !odd) WTS1(k, 0);
#pragma unroll
    for (int u = 0; u < 10; u++) {
      const int st = odd ? (2 * u + 1) % 5 : (2 * u) % 5, ph = odd ? ((2 * u + 1) / 5) & 1 : ((2 * u) / 5) & 1;
      mwait(sb + BAR_E + 8 * st, ph ^ 1, spin);
      if (elect_one()) {
        if (u == 9 && odd && ks < 4) mbar_arrive(sb + BAR_F + 8 * st);
        else {
          mbar_expect_tx(sb + BAR_F + 8 * st, len);
          bulk_g2s(sb + OFF_R + st * 8192 + lo, src + u * 16384, len, sb + BAR_F + 8 * st);
        }
      }
    }
  }
  if (spin >= SPIN_TOT) g_err = 12;
}
__device__ __forceinline__ void work_ln(int kind, int r, int lane, bf16* out) {
  int spin = 0;
  const int l = kind & 1;
  const int rp = kind < 2 ? (r & 1) * 16 + (r >> 1) : r;
  const uint32_t sw = ((((lane >> 1) & 7) ^ (rp & 7)) << 4) + (lane & 1) * 8;
  uint8_t* dst = kind < 2 ? g_xnb[l * LAG] + (lane >> 4) * 8192 + l * 4096 + rp * 128 + sw
               : kind == 2 ? g_xn[LAG] + (r >> 3) * 4096 + 2048 + (lane >> 4) * 1024 + (r & 7) * 128 + sw
                           : reinterpret_cast<uint8_t*>(out) + r * 1280 + lane * 8;
  const int dm = kind < 3 ? 16384 : 256, ds = kind < 3 ? 81920 : 40960;
#pragma unroll 1
  for (int s = 0; s < NSEG; s++) {
    const float* xr = g_x + (size_t)(s * 32 + r) * DM;
    if (OBP && kind < 2) {
      uint8_t* ob = g_ob[l] + (size_t)s * 40960 + r * 1280 + lane * 16;
      stg128(ob, make_uint4(0, 0, 0, 0)); stg128(ob + 512, make_uint4(0, 0, 0, 0));
      if (lane < 16) stg128(ob + 1024, make_uint4(0, 0, 0, 0));
    }
    if (lane == 0) cwait(kind < 2 ? CN_P + s + l * LAG : CN_W + l * 64 + s, kind < 2 ? W::NP : 10, spin);
    __syncwarp();
    if (r == 0 && lane == 0 && (l == 0 || s + LAG >= NSEG)) WTS1(s + l * LAG, kind < 2 ? 3 : 11);
    float4 v[5];
#pragma unroll
    for (int m = 0; m < 5; m++) v[m] = ld_relaxed4f(xr + m * 128 + lane * 4);
    if (kind < 3) ln_row(v);
#pragma unroll
    for (int m = 0; m < 5; m++) *reinterpret_cast<uint2*>(dst + (size_t)s * ds + m * dm) = make_uint2(pack_bf16(v[m].x, v[m].y), pack_bf16(v[m].z, v[m].w));
    __syncwarp();
    if (r == 0 && lane == 0 && (l == 0 || s + LAG >= NSEG)) WTS1(s + l * LAG, kind < 2 ? 4 : 12);
    if (lane == 0 && kind < (NOWORK ? 2 : 3)) csignal_t(kind < 2 ? CN_L + s + l * LAG : CN_X + s + LAG, kind);
  }
  if (spin >= SPIN_TOT) g_err = 13;
}

__device__ __forceinline__ void work_prep(const bf16* x0, const bf16* mem0, int r, int lane) {
  int spin = 0;
#pragma unroll 1
  for (int k = NPRE; k < NSTEP; k++) {
    uint2 u[5], v[5];
    ln0_load(x0, u, min(k * 32 + r, SEQ - 1), lane);
    ln0_load(x0, v, min(k * 32 + r + 16, SEQ - 1), lane);
    if (lane == 0) cwait(CN_O + (k - NPRE) * 5, 1, spin);
    __syncwarp();
#pragma unroll 1
    for (int h = 0; h < 2; h++) {
      prep_row(u, mem0, k, r + 16 * h, lane);
#pragma unroll
      for (int m = 0; m < 5; m++) u[m] = v[m];
    }
    __syncwarp();
    if (lane == 0) csignal(CN_X + k);
  }
  if (spin >= SPIN_TOT) g_err = 19;
}

__device__ __forceinline__ void stage_qkv(const bf16* wqkv, uint32_t base, int T, int bc, int tid) {
  const int q = tid & 15;
  const bool ok = q < 15 && bc * 60 + 4 * q < DM;
  const bf16* src = wqkv + T * DM + bc * 60 + 4 * q;
#pragma unroll 1
  for (int k0 = tid >> 4; k0 < 640; k0 += 80) {
    uint2 v[10];
#pragma unroll
    for (int u = 0; u < 10; u++) v[u] = ok ? *reinterpret_cast<const uint2*>(src + (size_t)(k0 + 8 * u) * 1920) : make_uint2(0, 0);
#pragma unroll
    for (int u = 0; u < 10; u++) sts64(base + (k0 + 8 * u) * 128 + (((q >> 1) ^ (k0 & 7)) << 4) + (q & 1) * 8, v[u].x, v[u].y);
  }
}
__device__ __forceinline__ void attend(uint32_t sb, int bc, int l, int s, int p, int tid) {
  using namespace W;
  const int r = tid & 7, m = (tid >> 3) & 3, hh = (tid >> 5) & 3, g = (tid >> 2) & 7, t = tid & 3;
  const int f2 = r < 4 ? 20 * hh + 16 + r : 60;
  const uint32_t tb = sb + OFF_T + (l * 4 + 2 * p) * COL, hb = sb + OFF_H + (l * 2 + p) * COL;
  const uint32_t ko = (m < 2 ? 20 * hh + 8 * m + r : f2) * 16, vo = (m < 2 ? 20 * hh + 4 * (r >> 1) + 2 * m + (r & 1) : f2) * 16;
  const float scl = 0.22360679774997896f * 1.4426950408889634f;
  float sc[3][4];
  {
    uint32_t q[4], q8a, q8b, k[3][4];
    ldsm4t(q, tb + (m & 1) * COL + (20 * hh + (m >> 1) * 8 + r) * 16);
    ldsm2t(q8a, q8b, tb + (m & 1) * COL + f2 * 16);
    ldsm4t(k[0], hb + ko); ldsm4t(k[1], tb + 8 * COL + ko); ldsm4t(k[2], tb + 9 * COL + ko);
#pragma unroll
    for (int c = 0; c < 3; c++) { sc[c][0] = sc[c][1] = sc[c][2] = sc[c][3] = 0.f; mma16816(sc[c], q[0], q[1], q[2], q[3], k[c][0], k[c][1]); }
#pragma unroll
    for (int c = 0; c < 3; c++) mma1688(sc[c], q8a, q8b, k[c][2]);
  }
  uint32_t v[3][4];
  ldsm4(v[0], hb + 4 * COL + vo); ldsm4(v[1], tb + 16 * COL + vo); ldsm4(v[2], tb + 17 * COL + vo);
  const bool lo0 = 2 * t > g, lo1 = 2 * t + 1 > g;
  uint32_t pw[2];
  float inv[2];
#pragma unroll
  for (int h = 0; h < 2; h++) {
    float y0 = lo0 ? sc[h][2 * h] : sc[h + 1][2 * h], y1 = lo1 ? sc[h][2 * h + 1] : sc[h + 1][2 * h + 1];
    if (h == 0 && s == 0) { y0 = lo0 ? -INFINITY : y0; y1 = lo1 ? -INFINITY : y1; }
    const float mx = quad_max(fmaxf(y0, y1)) * -scl;
    pw[h] = pack_bf16(ex2(fmaf(y0, scl, mx)), ex2(fmaf(y1, scl, mx)));
    inv[h] = bf_lo(pw[h]) + bf_hi(pw[h]);
  }
  const uint32_t ml = (lo0 ? 0xFFFFu : 0u) | (lo1 ? 0xFFFF0000u : 0u);
  float o[3][4];
#pragma unroll
  for (int j = 0; j < 3; j++) { o[j][0] = o[j][1] = o[j][2] = o[j][3] = 0.f; mma16816(o[j], pw[0] & ml, 0u, pw[0] & ~ml, pw[1] & ml, v[0][j], v[1][j]); }
#pragma unroll
  for (int j = 0; j < 3; j++) mma1688(o[j], 0u, pw[1] & ~ml, v[2][j]);
  inv[0] = rcp(quad_sum(inv[0])); inv[1] = rcp(quad_sum(inv[1]));
  const int tid2 = __shfl_xor_sync(0xffffffffu, tid, 0);
  const uint32_t ca = (bc * 3 + ((tid2 >> 5) & 3)) * 20 + 4 * (tid2 & 3), cb = ca + 16 - 2 * (tid2 & 3), row = ((tid2 >> 1) & 14) + p;
  uint8_t* img = g_ob[l] + (size_t)s * 40960 + row * 128;
  const uint32_t oa = (ca >> 6) * 4096 + (((ca >> 3) ^ row) & 7) * 16 + (ca & 4) * 2, ob = (cb >> 6) * 4096 + (((cb >> 3) ^ row) & 7) * 16 + (cb & 6) * 2;
#pragma unroll
  for (int h = 0; h < 2; h++) {
    *reinterpret_cast<uint2*>(img + oa + h * 2048) = make_uint2(pack_bf16(o[0][2 * h] * inv[h], o[0][2 * h + 1] * inv[h]), pack_bf16(o[1][2 * h] * inv[h], o[1][2 * h + 1] * inv[h]));
    if (t < 2) *reinterpret_cast<uint32_t*>(img + ob + h * 2048) = pack_bf16(o[2][2 * h] * inv[h], o[2][2 * h + 1] * inv[h]);
  }
}
template <int WG>
__device__ __forceinline__ void work_b(const bf16* wqkv, uint32_t sb, int bc, int tid0) {
  using namespace W;
  if (WG == 0) asm volatile("setmaxnreg.inc.sync.aligned.u32 232;");
  else asm volatile("setmaxnreg.inc.sync.aligned.u32 208;");
  constexpr int NR = WG ? KRS : QRS, OFF_Y = WG ? OFF_YK : OFF_YQ;
  int spin = 0;
  const uint32_t wb = sb + (WG ? OFF_WO : OFF_WV);
  uint32_t wf[NR][4];
  stage_qkv(wqkv, wb, WG, bc, tid0 & 127);
  WBAR_SYNC(NB_G0 + WG, 128);
  load_frags<NR>(wf, wb, tid0);
#pragma unroll
  for (int k = NR; k < 40; k++) sts128(sb + OFF_Y + (k - NR) * 2048 + (tid0 & 127) * 16, lds128(wb + k * 2048 + (tid0 & 127) * 16));
  fence_async();
  if (WG == 1) WBAR_ARRIVE(NB_PK, 256);
  WBAR_SYNC(NB_G0 + WG, 128);
  if (WG == 0) {
    stage_qkv(wqkv, wb, 2, bc, tid0);
    fence_async();
    WBAR_SYNC(NB_G0, 128);
  }
#pragma unroll 1
  for (int k = 0; k < NSTEP; k++) {
    uint32_t hist[8];
    {
      float d[32], e[32];
#pragma unroll
      for (int c = 0; c < 10; c++) {
        mwait(sb + BAR_F + 8 * (c % 3), ((c % 3 ? k : 0) + c / 3) & 1, spin);
        if (c == 0 && bc == 0) WTS(k, WG ? 15 : 6);
        if (HOLD && c == 9 && WG == 0 && tid0 == 0) mbar_arrive(sb + BAR_GO);
        wg_fence();
#pragma unroll
        for (int kk = 0; kk < 4; kk++) {
          const int q = 4 * c + kk;
          const uint64_t db = rdesc(OFF_X + (c % 3) * 8192, kk);
          if (q < NR) wgmma_rs64(d, wf[q < NR ? q : 0], db, q);
          else wgmma_ts64(d, mkdesc(SB0 + OFF_Y + (q - NR) * 2048, 8192, 1024), db, 1);
          if (WG == 0) wgmma_ts64(e, mkdesc(SB0 + OFF_WV + q * 2048, 8192, 1024), db, q);
          if (kk == 0 && c > 0 && c <= 7) {
            wg_commit();
            wg_wait<1>();
            if ((tid0 & 31) == 0) mbar_arrive(sb + BAR_E + 8 * ((c - 1) % 3));
          }
        }
        wg_commit();
      }
      wg_wait<0>();
      if (bc == 0) WTS(k, 16 + WG);
      WBAR_SYNC(NB_B, 256);
      const int tid = fresh(tid0), m = (tid >> 3) & 3;
      const uint32_t a = sb + OFF_T + min(((tid >> 5) & 3) * 16 + (m & 1) * 8 + (tid & 7), 60) * 16 + (m >> 1) * COL;
      const float (&x)[32] = WG ? d : e;
#pragma unroll
      for (int p = 0; p < 4; p++) {
        hist[2 * p] = pack_bf16(x[8 * p + 4], x[8 * p + 5]); hist[2 * p + 1] = pack_bf16(x[8 * p + 6], x[8 * p + 7]);
        stsm4(a + (16 - 8 * WG + 2 * p) * COL, pack_bf16(x[8 * p], x[8 * p + 1]), pack_bf16(x[8 * p + 2], x[8 * p + 3]), hist[2 * p], hist[2 * p + 1]);
        if (WG == 0)
          stsm4(a + 2 * p * COL, pack_bf16(d[8 * p], d[8 * p + 1]), pack_bf16(d[8 * p + 2], d[8 * p + 3]), pack_bf16(d[8 * p + 4], d[8 * p + 5]), pack_bf16(d[8 * p + 6], d[8 * p + 7]));
      }
    }
    WBAR_SYNC(NB_TD, 288);
    if (bc == 0 && WG == 0) WTS(k, 7);
#pragma unroll 1
    for (int l = 0; l < 2; l++) {
      const int tid = fresh(tid0), hh = uni((tid >> 5) & 3), s = k - l * LAG;
      if (hh < 3 && bc * 3 + hh < NH && s >= 0 && s < NSEG) attend(sb, bc, l, s, WG, tid);
      if (bc == 0 && WG == 0) WTS(k, l == 0 || k >= NSEG ? 8 : 25);
      if (l == 0) WBAR_ARRIVE(NB_AS, 288); else WBAR_ARRIVE(NB_AS + 1, 288);
    }
    WBAR_SYNC(NB_B, 256);
    {
      if (HOLD && WG == 0 && tid0 == 0) mbar_arrive(sb + BAR_GO);
      const int tid = fresh(tid0), m = (tid >> 3) & 3;
      const uint32_t a = sb + OFF_H + min(((tid >> 5) & 3) * 16 + (m & 1) * 8 + (tid & 7), 60) * 16 + (4 - 4 * WG + (m >> 1)) * COL;
      stsm4(a, hist[0], hist[1], hist[2], hist[3]);
      if (k >= LAG) stsm4(a + 2 * COL, hist[4], hist[5], hist[6], hist[7]);
      fence_async();
      if ((tid & 31) < 3) mbar_arrive(sb + BAR_E + 8 * (tid & 3));
    }
  }
  if (spin >= SPIN_TOT) g_err = 14;
}
__device__ __forceinline__ void work_wo(const CUtensorMap& tmBo, uint32_t sb, int bc, int tid0) {
  using namespace W;
  int spin = 0;
  WBAR_SYNC(NB_PK, 256);
  if (bc == 10) return;
  if ((tid0 & 127) == 0) {
    mbar_expect_tx(sb + BAR_W, 81920);
    for (int i = 0; i < 10; i++) tma2d(sb + OFF_WO + i * 8192, &tmBo, bc * 64, i * 64, sb + BAR_W);
  }
  __syncwarp();
  mwait(sb + BAR_W, 0, spin);
  permute_cols(sb + OFF_WO, tid0 & 127, 2560);
  WBAR_SYNC(NB_G0 + 2, 128);
  uint32_t wl[4];
  ldsm4t(wl, frag_addr(sb + OFF_WO + 39 * 2048, tid0));
  fence_async();
  WBAR_SYNC(NB_PV, 160);
  FOR_SEGS(l, s)
    float d[16];
#pragma unroll
    for (int c = 0; c < 10; c++) {
      mwait(sb + BAR_G + 8 * (c % 5), c / 5, spin);
      if (HOLD && c % HOLD == 0) mwait(sb + BAR_GO, 1, spin);
      if (c == 0 && bc == 0) WTS(s + l * LAG, l == 0 || s + LAG >= NSEG ? 20 : 23);
      wg_fence();
#pragma unroll
      for (int kk = 0; kk < 4; kk++) {
        if (c == 9 && kk == 3) wgmma_rs32(d, wl, rdesc(OFF_G + (c % 5) * 4096, kk), 1);
        else wgmma_ts32(d, mkdesc(SB0 + OFF_WO + (4 * c + kk) * 2048, 8192, 1024), rdesc(OFF_G + (c % 5) * 4096, kk), c | kk);
      }
      wg_commit();
      if (c % 5) {
        wg_wait<1>();
        if ((tid0 & 31) == 0) mbar_arrive(sb + BAR_H + 8 * ((c - 1) % 5));
      }
      if (c % 5 == 4) {
        wg_wait<0>();
        if ((tid0 & 31) == 0) mbar_arrive(sb + BAR_H + 32);
      }
    }
    if (bc == 0) WTS(s + l * LAG, l == 0 || s + LAG >= NSEG ? 10 : 24);
    red_tile(d, s, bc * 64, tid0);
    WBAR_SYNC(NB_SG, 160);
  }
  if (spin >= SPIN_TOT) g_err = 17;
}
__device__ __forceinline__ void work_x_producer(uint32_t sb, int bc) {
  using namespace W;
  int spin = 0;
#pragma unroll 1
  for (int k = 0; k < NSTEP; k++) {
    const uint32_t lo = k < NSEG ? 0 : 4096, len = k < LAG || k >= NSEG ? 4096 : 8192;
    const uint8_t* src = g_xnb[k] + lo;
    cwait(CN_L + k, len >> 7, spin);
    fence_async_all();
    if (bc == 0) WTS1(k, 5);
#pragma unroll
    for (int c = 0; c < 10; c++) {
      mwait(sb + BAR_E + 8 * (c % 3), (((c % 3 ? k : 0) + c / 3) & 1) ^ 1, spin);
      if (elect_one()) {
        mbar_expect_tx(sb + BAR_F + 8 * (c % 3), len);
        bulk_g2s(sb + OFF_X + (c % 3) * 8192 + lo, src + c * 8192, len, sb + BAR_F + 8 * (c % 3));
      }
    }
  }
  if (spin >= SPIN_TOT) g_err = 15;
}
__device__ __forceinline__ void work_g_producer(uint32_t sb, int bc) {
  using namespace W;
  int spin = 0;
  uint32_t seen = 0;
  FOR_SEGS(l, s)
    const uint8_t* src = g_ob[l] + (size_t)s * 40960;
    if (seen < NBC) { cwait(CN_A + l * 64 + s, NBC, spin); fence_async_all(); }
    if (bc == 0) WTS1(s + l * LAG, l == 0 || s + LAG >= NSEG ? 9 : 22);
    seen = 0;
#pragma unroll
    for (int c = 0; c < 10; c++) {
      if (GLA && c == GLA && l == 0 && s >= LAG) { seen = ld_acquire(&g_cnt[CN_A + 64 + s - LAG][0]); fence_async_all(); }
      mwait(sb + BAR_H + 8 * (c % 5), c < 5, spin);
      if (elect_one()) {
        mbar_expect_tx(sb + BAR_G + 8 * (c % 5), 4096);
        bulk_g2s(sb + OFF_G + (c % 5) * 4096, src + c * 4096, 4096, sb + BAR_G + 8 * (c % 5));
      }
    }
  }
  if (spin >= SPIN_TOT) g_err = 16;
}

__global__ void __launch_bounds__(512, 1)
k_work(const __grid_constant__ CUtensorMap tmWo, const __grid_constant__ CUtensorMap tmBo, const bf16* __restrict__ wqkv, bf16* __restrict__ out,
       const bf16* __restrict__ x0, const bf16* __restrict__ mem0) {
  using namespace W;
  extern __shared__ __align__(1024) uint8_t smem[];
  const uint32_t sb = smem_u32(smem);
  const int tid = threadIdx.x, w = blockIdx.x;
  const int wg = __shfl_sync(0xffffffffu, tid >> 7, 0);
  if (tid == 0) {
    if (sb != SB0) g_err = 101;
    for (int i = 0; i < 5; i++) { mbar_init(sb + BAR_F + 8 * i, 1); mbar_init(sb + BAR_E + 8 * i, 8); mbar_init(sb + BAR_G + 8 * i, 1); mbar_init(sb + BAR_H + 8 * i, 4); }
    mbar_init(sb + BAR_W, 1); mbar_init(sb + BAR_W + 8, 1); mbar_init(sb + BAR_GO, 1);
    for (int p = 0; p < 16; p++) sts32(sb + OFF_SAFE + 4 * p, 0);
    asm volatile("fence.mbarrier_init.release.cluster;" ::: "memory");
    int spin = 0;
    pre_wait(1, NW, spin);
    if (spin >= SPIN_TOT) g_err = 18;
  }
  if (tid < 8 * COL / 16) sts128(sb + OFF_H + tid * 16, make_uint4(0, 0, 0, 0));
  fence_async();
  __syncthreads();

  if (w < NP) {
    if (wg == 0) work_p<0>(tmWo, sb, w, keep(tid));
    else if (wg == 1) work_p<1>(tmWo, sb, w, keep(tid));
    else {
      asm volatile("setmaxnreg.dec.sync.aligned.u32 48;");
      const int aw = uni(tid >> 5) - 8;
      if (aw < 2) {
        work_p_producer(sb, w, aw);
      } else {
        const int id = (aw - 2) * NP + w;
        if (id < 128) work_ln(id & 3, id >> 2, tid & 31, out);
        else if (id < 144 && NOWORK != 2) work_prep(x0, mem0, id - 128, tid & 31);
      }
    }
  } else {
    const int bc = w - NP;
    if (wg == 0) work_b<0>(wqkv, sb, bc, keep(tid));
    else if (wg == 1) work_b<1>(wqkv, sb, bc, keep(tid));
    else if (wg == 2) {
      asm volatile("setmaxnreg.dec.sync.aligned.u32 48;");
      work_wo(tmBo, sb, bc, keep(tid));
    } else {
      asm volatile("setmaxnreg.dec.sync.aligned.u32 24;");
      const int aw = uni(tid >> 5) - 12;
      if (aw == 0) work_x_producer(sb, bc);
      else if (aw == 1) {
        if (bc < 10) {
          WBAR_SYNC(NB_PV, 160);
          work_g_producer(sb, bc);
        }
      } else if (aw == 2) {
        for (int k = 0; k < NSTEP; k++) {
          WBAR_SYNC(NB_TD, 288);
          WBAR_SYNC(NB_AS, 288);
          if (tid == 448 && k < NSEG) csignal_t(CN_A + k, 5);
          __syncwarp();
          WBAR_SYNC(NB_AS + 1, 288);
          if (tid == 448 && k >= LAG) csignal_t(CN_A + 64 + k - LAG, 4);
          __syncwarp();
        }
      } else if (bc < 10) {
        FOR_SEGS(l, s)
          WBAR_SYNC(NB_SG, 160);
          if (tid == 480) csignal_t(CN_W + l * 64 + s, 6);
          __syncwarp();
        }
      }
    }
  }
  __syncthreads();
  asm volatile("griddepcontrol.wait;" ::: "memory");
}

typedef CUresult (*EncodeFn)(CUtensorMap*, CUtensorMapDataType, cuuint32_t, void*, const cuuint64_t*, const cuuint64_t*,
                             const cuuint32_t*, const cuuint32_t*, CUtensorMapInterleave, CUtensorMapSwizzle,
                             CUtensorMapL2promotion, CUtensorMapFloatOOBfill);

static void make_map(EncodeFn enc, CUtensorMap* tm, const void* ptr, uint64_t cols, uint64_t rows, uint32_t boxc, uint32_t boxr) {
  cuuint64_t dims[2] = {cols, rows};
  cuuint64_t strides[1] = {cols * 2};
  cuuint32_t box[2] = {boxc, boxr};
  cuuint32_t es[2] = {1, 1};
  enc(tm, CU_TENSOR_MAP_DATA_TYPE_BFLOAT16, 2, const_cast<void*>(ptr), dims, strides, box, es, CU_TENSOR_MAP_INTERLEAVE_NONE,
      CU_TENSOR_MAP_SWIZZLE_128B, CU_TENSOR_MAP_L2_PROMOTION_L2_256B, CU_TENSOR_MAP_FLOAT_OOB_FILL_NONE);
}

extern "C" void kernel_launch(void* const* d_in, const int* in_sizes, int n_in, void* d_out, int out_size) {
  const bf16* x0 = (const bf16*)d_in[0];
  const bf16* mem0 = (const bf16*)d_in[1];
  const bf16* Wq = (const bf16*)d_in[2];
  const bf16* Wk = (const bf16*)d_in[3];
  const bf16* Wv = (const bf16*)d_in[4];
  const bf16* Wo = (const bf16*)d_in[5];
  const bf16* Bqkv = (const bf16*)d_in[8];
  const bf16* Bwo = (const bf16*)d_in[9];
  bf16* out = (bf16*)d_out;

  static EncodeFn enc = nullptr;
  if (!enc) {
    void* fn = nullptr;
    cudaDriverEntryPointQueryResult qr;
    cudaGetDriverEntryPoint("cuTensorMapEncodeTiled", &fn, cudaEnableDefault, &qr);
    enc = (EncodeFn)fn;
    cudaFuncSetAttribute(k_chain, cudaFuncAttributeMaxDynamicSharedMemorySize, C::SMEM);
    cudaFuncSetAttribute(k_work, cudaFuncAttributeMaxDynamicSharedMemorySize, W::SMEM);
  }
  CUtensorMap tmWq, tmWk, tmWv, tmWo, tmWp, tmBo;
  make_map(enc, &tmWq, Wq, NH * DH, DM, 64, 128);
  make_map(enc, &tmWk, Wk, NH * DH, DM, 64, 128);
  make_map(enc, &tmWv, Wv, NH * DH, DM, 64, 128);
  make_map(enc, &tmWo, Wo, DM, NH * DH, 64, 64);
  make_map(enc, &tmWp, Wo, DM, NH * DH, 64, 16);
  make_map(enc, &tmBo, Bwo, DM, DM, 64, 64);

  cudaStream_t st = cudaStreamPerThread;
  cudaLaunchAttribute at[1];
  at[0].id = cudaLaunchAttributeProgrammaticStreamSerialization; at[0].val.programmaticStreamSerializationAllowed = 1;
  {
    cudaLaunchConfig_t cfg = {};
    cfg.gridDim = dim3(96); cfg.blockDim = dim3(384); cfg.dynamicSmemBytes = C::SMEM; cfg.stream = st;
    cfg.attrs = at; cfg.numAttrs = 0;
    cudaLaunchKernelEx(&cfg, k_chain, tmWq, tmWk, tmWv, tmWo, x0, mem0);
  }
  cudaLaunchConfig_t cfg = {};
  cfg.gridDim = dim3(W::NW); cfg.blockDim = dim3(512); cfg.dynamicSmemBytes = W::SMEM; cfg.stream = st;
  cfg.attrs = at; cfg.numAttrs = NOWORK == 2 ? 0 : 1;
  cudaLaunchKernelEx(&cfg, k_work, tmWp, tmBo, Bqkv, out, x0, mem0);
}
```

```cpp
#include <cuda_runtime.h>
#include <cuda_bf16.h>
#include <cuda.h>
#include <stdint.h>

typedef __nv_bfloat16 bf16;

constexpr int SEQ = 2048, DM = 640, NH = 32, DH = 192, NSEG = 64;
#define LAG 6
constexpr int NSTEP = NSEG + LAG;
constexpr int NPRE = 4;
constexpr uint32_t SENT = 0xFFFFFFFFu;

constexpr int MAIL9 = 288 * 2048, MAIL_BYTES = MAIL9 + 64 * 3072;
__device__ __align__(1024) uint8_t g_xn[NSTEP][81920];
__device__ __align__(1024) uint8_t g_xnb[NSTEP][81920];
__device__ __align__(1024) uint8_t g_ob[NSTEP][81920];
#define ORING 8
static_assert(ORING > LAG, "a slot is free again LAG + 1 steps later");
__device__ __align__(1024) uint8_t g_o[ORING][96][8192];
__device__ __align__(1024) float g_x[SEQ * DM];
constexpr int EX_MAIL = 0;
constexpr int EX_M = 2 << 20;
constexpr int EX_FLAG = EX_M + NSTEP * 20480;
static_assert(EX_FLAG + NSTEP * 3072 <= (4 << 20), "");
__device__ __align__(1024) uint8_t g_ex[8 << 20];
__host__ __device__ __forceinline__ uint8_t* ex_window(uint8_t* p) { return reinterpret_cast<uint8_t*>((reinterpret_cast<uint64_t>(p) + (4 << 20) - 1) & ~(uint64_t)((4 << 20) - 1)); }
enum { CN_P = 0, CN_L = 128, CN_A = 256, CN_W = 384, CN_X = 512, CN_F = 640, CN_O = 768, CN_NUM = CN_O + 5 * NSTEP };
__device__ __align__(128) uint32_t g_cnt[CN_NUM][32];
__device__ __align__(128) uint32_t g_ticket[2][32];
__device__ int g_err;
#define TS(jj, i)
#define TS1(jj, i)
#define PTS(i)
#define TSB(jj, i)
#define TSV(jj, i, v)
#define TS_FLUSH(jj)
#define WTS(b, k)
#define WTS1(b, k)
#define WW -1

__device__ __forceinline__ uint32_t smem_u32(const void* p) { return (uint32_t)__cvta_generic_to_shared(p); }
__device__ __forceinline__ uint32_t clk32() { uint32_t t; asm volatile("mov.u32 %0, %%clock;" : "=r"(t)::"memory"); return t; }
__device__ __forceinline__ uint32_t mapa(uint32_t a, uint32_t r) { uint32_t o; asm("mapa.shared::cluster.u32 %0,%1,%2;" : "=r"(o) : "r"(a), "r"(r)); return o; }
__device__ __forceinline__ void mbar_init(uint32_t bar, uint32_t cnt) { asm volatile("mbarrier.init.shared::cta.b64 [%0],%1;" ::"r"(bar), "r"(cnt) : "memory"); }
__device__ __forceinline__ void mbar_expect_tx(uint32_t bar, uint32_t bytes) { asm volatile("mbarrier.arrive.expect_tx.shared::cta.b64 _,[%0],%1;" ::"r"(bar), "r"(bytes) : "memory"); }
__device__ __forceinline__ void mbar_arrive(uint32_t bar) { asm volatile("mbarrier.arrive.shared::cta.b64 _,[%0];" ::"r"(bar) : "memory"); }
__device__ __forceinline__ void mbar_arrive_cluster(uint32_t bar) { asm volatile("mbarrier.arrive.shared::cluster.b64 _,[%0];" ::"r"(bar) : "memory"); }
__device__ __forceinline__ bool mbar_try(uint32_t bar, uint32_t ph) {
  uint32_t ok;
  asm volatile("{.reg .pred p; mbarrier.try_wait.parity.shared::cta.b64 p,[%1],%2; selp.u32 %0,1,0,p;}" : "=r"(ok) : "r"(bar), "r"(ph) : "memory");
  return ok;
}
__device__ __forceinline__ bool mbar_test(uint32_t bar, uint32_t ph) {
  uint32_t ok;
  asm volatile("{.reg .pred p; mbarrier.test_wait.parity.shared::cta.b64 p,[%1],%2; selp.u32 %0,1,0,p;}" : "=r"(ok) : "r"(bar), "r"(ph) : "memory");
  return ok;
}
__device__ __forceinline__ int fresh(int x) { asm volatile("" : "+r"(x)); return x; }
#define PHASE_IDS const int tid = fresh(tid0), lane = tid & 31, w = tid >> 5, g = lane >> 2, t = lane & 3; (void)w; (void)g; (void)t
__device__ __forceinline__ void bar_sync(int id, int n) { asm volatile("bar.sync %0,%1;" ::"r"(id), "r"(n) : "memory"); }
__device__ __forceinline__ void bar_arrive(int id, int n) { asm volatile("bar.arrive %0,%1;" ::"r"(id), "r"(n) : "memory"); }
__device__ __forceinline__ bool bar_red_or(int id, int n, bool v) {
  uint32_t r;
  asm volatile("{\n .reg .pred p, q;\n setp.ne.u32 q, %3, 0;\n barrier.cta.red.or.pred p, %1, %2, q;\n selp.u32 %0, 1, 0, p;\n}" : "=r"(r) : "r"(id), "r"(n), "r"((uint32_t)v) : "memory");
  return r != 0;
}
__device__ __forceinline__ void fence_async() { asm volatile("fence.proxy.async.shared::cta;" ::: "memory"); }
__device__ __forceinline__ void bulk_g2s(uint32_t dst, const void* src, uint32_t bytes, uint32_t bar) {
  asm volatile("cp.async.bulk.shared::cluster.global.mbarrier::complete_tx::bytes [%0],[%1],%2,[%3];" ::"r"(dst), "l"(src), "r"(bytes), "r"(bar) : "memory");
}
__device__ __forceinline__ void bulk_g2s_mc(uint32_t dst, const void* src, uint32_t bytes, uint32_t bar) {
  asm volatile("cp.async.bulk.shared::cluster.global.mbarrier::complete_tx::bytes.multicast::cluster [%0],[%1],%2,[%3],%4;"
               ::"r"(dst), "l"(src), "r"(bytes), "r"(bar), "h"((uint16_t)7) : "memory");
}
__device__ __forceinline__ void bulk_s2g(void* dst, uint32_t src, uint32_t bytes) {
  asm volatile("cp.async.bulk.global.shared::cta.bulk_group [%0],[%1],%2;" ::"l"(dst), "r"(src), "r"(bytes) : "memory");
}
__device__ __forceinline__ void bulk_s2c(uint32_t dst, uint32_t src, uint32_t bytes, uint32_t bar) {
  asm volatile("cp.async.bulk.shared::cluster.shared::cta.mbarrier::complete_tx::bytes [%0],[%1],%2,[%3];" ::"r"(dst), "r"(src), "r"(bytes), "r"(bar) : "memory");
}
__device__ __forceinline__ void tma2d(uint32_t dst, const CUtensorMap* tm, int c0, int c1, uint32_t bar) {
  asm volatile("cp.async.bulk.tensor.2d.shared::cluster.global.mbarrier::complete_tx::bytes [%0],[%1,{%3,%4}],[%2];"
               ::"r"(dst), "l"(tm), "r"(bar), "r"(c0), "r"(c1) : "memory");
}
__device__ __forceinline__ void tma2d_prefetch(const CUtensorMap* tm, int c0, int c1) {
  asm volatile("cp.async.bulk.prefetch.tensor.2d.L2.global.tile [%0,{%1,%2}];" ::"l"(tm), "r"(c0), "r"(c1) : "memory");
}
__device__ __forceinline__ uint32_t pack_bf16(float lo, float hi) {
  uint32_t r; asm("cvt.rn.bf16x2.f32 %0,%1,%2;" : "=r"(r) : "f"(hi), "f"(lo)); return r;
}
__device__ __forceinline__ float bf_lo(uint32_t x) { return __uint_as_float(x << 16); }
__device__ __forceinline__ float bf_hi(uint32_t x) { return __uint_as_float(x & 0xFFFF0000u); }
__device__ __forceinline__ float ex2(float x) { float y; asm("ex2.approx.ftz.f32 %0,%1;" : "=f"(y) : "f"(x)); return y; }
__device__ __forceinline__ void ldsm4(uint32_t (&r)[4], uint32_t a) {
  asm volatile("ldmatrix.sync.aligned.m8n8.x4.shared.b16 {%0,%1,%2,%3},[%4];" : "=r"(r[0]), "=r"(r[1]), "=r"(r[2]), "=r"(r[3]) : "r"(a) : "memory");
}
__device__ __forceinline__ void ldsm4t(uint32_t (&r)[4], uint32_t a) {
  asm volatile("ldmatrix.sync.aligned.m8n8.x4.trans.shared.b16 {%0,%1,%2,%3},[%4];" : "=r"(r[0]), "=r"(r[1]), "=r"(r[2]), "=r"(r[3]) : "r"(a) : "memory");
}
__device__ __forceinline__ void ldsm2(uint32_t& r0, uint32_t& r1, uint32_t a) {
  asm volatile("ldmatrix.sync.aligned.m8n8.x2.shared.b16 {%0,%1},[%2];" : "=r"(r0), "=r"(r1) : "r"(a) : "memory");
}
__device__ __forceinline__ void ldsm2t(uint32_t& r0, uint32_t& r1, uint32_t a) {
  asm volatile("ldmatrix.sync.aligned.m8n8.x2.trans.shared.b16 {%0,%1},[%2];" : "=r"(r0), "=r"(r1) : "r"(a) : "memory");
}
__device__ __forceinline__ void ldsm1(uint32_t& r0, uint32_t a) {
  asm volatile("ldmatrix.sync.aligned.m8n8.x1.shared.b16 {%0},[%1];" : "=r"(r0) : "r"(a) : "memory");
}
__device__ __forceinline__ void mma16816(float (&d)[4], uint32_t a0, uint32_t a1, uint32_t a2, uint32_t a3, uint32_t b0, uint32_t b1) {
  asm volatile("mma.sync.aligned.m16n8k16.row.col.f32.bf16.bf16.f32 {%0,%1,%2,%3},{%4,%5,%6,%7},{%8,%9},{%0,%1,%2,%3};"
               : "+f"(d[0]), "+f"(d[1]), "+f"(d[2]), "+f"(d[3]) : "r"(a0), "r"(a1), "r"(a2), "r"(a3), "r"(b0), "r"(b1));
}
__device__ __forceinline__ void mma1688(float (&d)[4], uint32_t a0, uint32_t a1, uint32_t b0) {
  asm volatile("mma.sync.aligned.m16n8k8.row.col.f32.bf16.bf16.f32 {%0,%1,%2,%3},{%4,%5},{%6},{%0,%1,%2,%3};"
               : "+f"(d[0]), "+f"(d[1]), "+f"(d[2]), "+f"(d[3]) : "r"(a0), "r"(a1), "r"(b0));
}
__device__ __forceinline__ void sts32(uint32_t a, uint32_t v) { asm volatile("st.shared.b32 [%0],%1;" ::"r"(a), "r"(v) : "memory"); }
__device__ __forceinline__ void sts64f(uint32_t a, float x, float y) { asm volatile("st.shared.v2.f32 [%0],{%1,%2};" ::"r"(a), "f"(x), "f"(y) : "memory"); }
__device__ __forceinline__ void sts128(uint32_t a, uint4 v) { asm volatile("st.shared.v4.b32 [%0],{%1,%2,%3,%4};" ::"r"(a), "r"(v.x), "r"(v.y), "r"(v.z), "r"(v.w) : "memory"); }
__device__ __forceinline__ float lds32f(uint32_t a) { float v; asm volatile("ld.shared.f32 %0,[%1];" : "=f"(v) : "r"(a) : "memory"); return v; }
__device__ __forceinline__ float2 lds64f(uint32_t a) { float2 v; asm volatile("ld.shared.v2.f32 {%0,%1},[%2];" : "=f"(v.x), "=f"(v.y) : "r"(a) : "memory"); return v; }
__device__ __forceinline__ uint4 lds128(uint32_t a) { uint4 v; asm volatile("ld.shared.v4.b32 {%0,%1,%2,%3},[%4];" : "=r"(v.x), "=r"(v.y), "=r"(v.z), "=r"(v.w) : "r"(a) : "memory"); return v; }
__device__ __forceinline__ float4 lds128f(uint32_t a) { float4 v; asm volatile("ld.shared.v4.f32 {%0,%1,%2,%3},[%4];" : "=f"(v.x), "=f"(v.y), "=f"(v.z), "=f"(v.w) : "r"(a) : "memory"); return v; }
__device__ __forceinline__ void st_async2(uint32_t a, float x, float y, uint32_t bar) {
  asm volatile("st.async.weak.shared::cluster.mbarrier::complete_tx::bytes.v2.f32 [%0],{%1,%2},[%3];" ::"r"(a), "f"(x), "f"(y), "r"(bar) : "memory");
}
__device__ __forceinline__ void st_async4(uint32_t a, const float (&v)[4], uint32_t bar) {
  asm volatile("st.async.weak.shared::cluster.mbarrier::complete_tx::bytes.v4.f32 [%0],{%1,%2,%3,%4},[%5];" ::"r"(a), "f"(v[0]), "f"(v[1]), "f"(v[2]), "f"(v[3]), "r"(bar) : "memory");
}
__device__ __forceinline__ void st_async4v(uint32_t a, float x, float y, float z, float w, uint32_t bar) {
  asm volatile("st.async.weak.shared::cluster.mbarrier::complete_tx::bytes.v4.f32 [%0],{%1,%2,%3,%4},[%5];" ::"r"(a), "f"(x), "f"(y), "f"(z), "f"(w), "r"(bar) : "memory");
}
__device__ __forceinline__ void st_async4u(uint32_t a, const uint4& v, uint32_t bar) {
  asm volatile("st.async.weak.shared::cluster.mbarrier::complete_tx::bytes.v4.b32 [%0],{%1,%2,%3,%4},[%5];" ::"r"(a), "r"(v.x), "r"(v.y), "r"(v.z), "r"(v.w), "r"(bar) : "memory");
}
__device__ __forceinline__ uint4 ld_relaxed4(const void* p) {
  uint4 v; asm volatile("ld.relaxed.gpu.global.v4.u32 {%0,%1,%2,%3},[%4];" : "=r"(v.x), "=r"(v.y), "=r"(v.z), "=r"(v.w) : "l"(p) : "memory"); return v;
}
__device__ __forceinline__ uint32_t ld_relaxed(const void* p) {
  uint32_t v; asm volatile("ld.relaxed.gpu.global.u32 %0,[%1];" : "=r"(v) : "l"(p) : "memory"); return v;
}
__device__ __forceinline__ void st_relaxed(void* p, uint32_t v) { asm volatile("st.relaxed.gpu.global.b32 [%0],%1;" ::"l"(p), "r"(v) : "memory"); }
__device__ __forceinline__ void st_relaxed4(void* p, uint32_t v) { asm volatile("st.relaxed.gpu.global.v4.b32 [%0],{%1,%1,%1,%1};" ::"l"(p), "r"(v) : "memory"); }

__device__ __forceinline__ uint32_t ld_acquire(const void* p) {
  uint32_t v; asm volatile("ld.acquire.gpu.global.u32 %0,[%1];" : "=r"(v) : "l"(p) : "memory"); return v;
}
__device__ __forceinline__ float4 ld_relaxed4f(const void* p) {
  float4 v; asm volatile("ld.relaxed.gpu.global.v4.f32 {%0,%1,%2,%3},[%4];" : "=f"(v.x), "=f"(v.y), "=f"(v.z), "=f"(v.w) : "l"(p) : "memory"); return v;
}
__device__ __forceinline__ float2 ld_relaxed2f(const void* p) {
  float2 v; asm volatile("ld.relaxed.gpu.global.v2.f32 {%0,%1},[%2];" : "=f"(v.x), "=f"(v.y) : "l"(p) : "memory"); return v;
}
__device__ __forceinline__ void prefetch_l2(const void* p) { asm volatile("prefetch.global.L2 [%0];" ::"l"(p)); }
__device__ __forceinline__ void fence_gpu() { asm volatile("fence.acq_rel.gpu;" ::: "memory"); }
__device__ __forceinline__ void fence_async_all() { asm volatile("fence.proxy.async.global;" ::: "memory"); }
constexpr int SPIN_TOT = 1 << 22;
__device__ __forceinline__ void csignal(int idx) { asm volatile("red.release.gpu.global.add.u32 [%0],1;" ::"l"(&g_cnt[idx][0]) : "memory"); }
__device__ __forceinline__ void csignal_fast(int idx) { asm volatile("red.relaxed.gpu.global.add.u32 [%0],1;" ::"l"(&g_cnt[idx][0]) : "memory"); }
#define UNS 0
#define RLX 0
#define csignal_t(idx, role) csignal(idx)
__device__ __forceinline__ void cwait(int idx, uint32_t target, int& spin) {
  while (ld_acquire(&g_cnt[idx][0]) < target && spin < SPIN_TOT) spin += 16;
}

__device__ __forceinline__ uint64_t mkdesc(uint32_t addr, uint32_t lbo, uint32_t sbo) {
  return (uint64_t)((addr & 0x3FFFF) >> 4) | ((uint64_t)(lbo >> 4) << 16) | ((uint64_t)(sbo >> 4) << 32) | ((uint64_t)1 << 62);
}
__device__ __forceinline__ uint64_t mkdesc_ns(uint32_t addr, uint32_t lbo, uint32_t sbo) {
  return (uint64_t)((addr & 0x3FFFF) >> 4) | ((uint64_t)(lbo >> 4) << 16) | ((uint64_t)(sbo >> 4) << 32);
}
__device__ __forceinline__ void wg_fence() { asm volatile("wgmma.fence.sync.aligned;" ::: "memory"); }
__device__ __forceinline__ void wg_commit() { asm volatile("wgmma.commit_group.sync.aligned;" ::: "memory"); }
template <int N> __device__ __forceinline__ void wg_wait() { asm volatile("wgmma.wait_group.sync.aligned %0;" ::"n"(N) : "memory"); }

__device__ __forceinline__ void wgmma_rs16(float (&d)[8], const uint32_t (&a)[4], uint64_t db, int sc) {
  asm volatile("{.reg .pred p; setp.ne.b32 p,%13,0; wgmma.mma_async.sync.aligned.m64n16k16.f32.bf16.bf16 "
               "{%0,%1,%2,%3,%4,%5,%6,%7},{%8,%9,%10,%11},%12,p,1,1,0;}"
               : "+f"(d[0]), "+f"(d[1]), "+f"(d[2]), "+f"(d[3]), "+f"(d[4]), "+f"(d[5]), "+f"(d[6]), "+f"(d[7])
               : "r"(a[0]), "r"(a[1]), "r"(a[2]), "r"(a[3]), "l"(db), "r"(sc));
}
__device__ __forceinline__ void wgmma_rs64(float (&d)[32], const uint32_t (&a)[4], uint64_t db, int sc) {
  asm volatile("{.reg .pred p; setp.ne.b32 p,%37,0; wgmma.mma_async.sync.aligned.m64n64k16.f32.bf16.bf16 "
               "{%0,%1,%2,%3,%4,%5,%6,%7,%8,%9,%10,%11,%12,%13,%14,%15,%16,%17,%18,%19,%20,%21,%22,%23,%24,%25,%26,%27,%28,%29,%30,%31},{%32,%33,%34,%35},%36,p,1,1,0;}"
               : "+f"(d[0]), "+f"(d[1]), "+f"(d[2]), "+f"(d[3]), "+f"(d[4]), "+f"(d[5]), "+f"(d[6]), "+f"(d[7]), "+f"(d[8]), "+f"(d[9]), "+f"(d[10]), "+f"(d[11]), "+f"(d[12]), "+f"(d[13]), "+f"(d[14]), "+f"(d[15]), "+f"(d[16]), "+f"(d[17]), "+f"(d[18]), "+f"(d[19]), "+f"(d[20]), "+f"(d[21]), "+f"(d[22]), "+f"(d[23]), "+f"(d[24]), "+f"(d[25]), "+f"(d[26]), "+f"(d[27]), "+f"(d[28]), "+f"(d[29]), "+f"(d[30]), "+f"(d[31])
               : "r"(a[0]), "r"(a[1]), "r"(a[2]), "r"(a[3]), "l"(db), "r"(sc));
}
__device__ __forceinline__ void wgmma_rt16(float (&d)[8], const uint32_t (&a)[4], uint64_t db, int sc) {
  asm volatile("{.reg .pred p; setp.ne.b32 p,%13,0; wgmma.mma_async.sync.aligned.m64n16k16.f32.bf16.bf16 "
               "{%0,%1,%2,%3,%4,%5,%6,%7},{%8,%9,%10,%11},%12,p,1,1,1;}"
               : "+f"(d[0]), "+f"(d[1]), "+f"(d[2]), "+f"(d[3]), "+f"(d[4]), "+f"(d[5]), "+f"(d[6]), "+f"(d[7])
               : "r"(a[0]), "r"(a[1]), "r"(a[2]), "r"(a[3]), "l"(db), "r"(sc));
}
__device__ __forceinline__ void wgmma_rt80(float (&d)[40], const uint32_t (&a)[4], uint64_t db, int sc) {
  asm volatile("{.reg .pred p; setp.ne.b32 p,%45,0; wgmma.mma_async.sync.aligned.m64n80k16.f32.bf16.bf16 "
               "{%0,%1,%2,%3,%4,%5,%6,%7,%8,%9,%10,%11,%12,%13,%14,%15,%16,%17,%18,%19,%20,%21,%22,%23,%24,%25,%26,%27,%28,%29,%30,%31,%32,%33,%34,%35,%36,%37,%38,%39},{%40,%41,%42,%43},%44,p,1,1,1;}"
               : "+f"(d[0]), "+f"(d[1]), "+f"(d[2]), "+f"(d[3]), "+f"(d[4]), "+f"(d[5]), "+f"(d[6]), "+f"(d[7]), "+f"(d[8]), "+f"(d[9]), "+f"(d[10]), "+f"(d[11]), "+f"(d[12]), "+f"(d[13]), "+f"(d[14]), "+f"(d[15]), "+f"(d[16]), "+f"(d[17]), "+f"(d[18]), "+f"(d[19]), "+f"(d[20]), "+f"(d[21]), "+f"(d[22]), "+f"(d[23]), "+f"(d[24]), "+f"(d[25]), "+f"(d[26]), "+f"(d[27]), "+f"(d[28]), "+f"(d[29]), "+f"(d[30]), "+f"(d[31]), "+f"(d[32]), "+f"(d[33]), "+f"(d[34]), "+f"(d[35]), "+f"(d[36]), "+f"(d[37]), "+f"(d[38]), "+f"(d[39])
               : "r"(a[0]), "r"(a[1]), "r"(a[2]), "r"(a[3]), "l"(db), "r"(sc));
}
__device__ __forceinline__ void wgmma_rs32(float (&d)[16], const uint32_t (&a)[4], uint64_t db, int sc) {
  asm volatile("{.reg .pred p; setp.ne.b32 p,%21,0; wgmma.mma_async.sync.aligned.m64n32k16.f32.bf16.bf16 "
               "{%0,%1,%2,%3,%4,%5,%6,%7,%8,%9,%10,%11,%12,%13,%14,%15},{%16,%17,%18,%19},%20,p,1,1,0;}"
               : "+f"(d[0]), "+f"(d[1]), "+f"(d[2]), "+f"(d[3]), "+f"(d[4]), "+f"(d[5]), "+f"(d[6]), "+f"(d[7]), "+f"(d[8]), "+f"(d[9]), "+f"(d[10]), "+f"(d[11]), "+f"(d[12]), "+f"(d[13]), "+f"(d[14]), "+f"(d[15])
               : "r"(a[0]), "r"(a[1]), "r"(a[2]), "r"(a[3]), "l"(db), "r"(sc));
}
__device__ __forceinline__ void wgmma_ts32(float (&d)[16], uint64_t da, uint64_t db, int sc) {
  asm volatile("{.reg .pred p; setp.ne.b32 p,%18,0; wgmma.mma_async.sync.aligned.m64n32k16.f32.bf16.bf16 "
               "{%0,%1,%2,%3,%4,%5,%6,%7,%8,%9,%10,%11,%12,%13,%14,%15},%16,%17,p,1,1,1,0;}"
               : "+f"(d[0]), "+f"(d[1]), "+f"(d[2]), "+f"(d[3]), "+f"(d[4]), "+f"(d[5]), "+f"(d[6]), "+f"(d[7]), "+f"(d[8]), "+f"(d[9]), "+f"(d[10]), "+f"(d[11]), "+f"(d[12]), "+f"(d[13]), "+f"(d[14]), "+f"(d[15])
               : "l"(da), "l"(db), "r"(sc));
}
__device__ __forceinline__ void wgmma_rs8(float (&d)[4], const uint32_t (&a)[4], uint64_t db, int sc) {
  asm volatile("{.reg .pred p; setp.ne.b32 p,%9,0; wgmma.mma_async.sync.aligned.m64n8k16.f32.bf16.bf16 "
               "{%0,%1,%2,%3},{%4,%5,%6,%7},%8,p,1,1,0;}"
               : "+f"(d[0]), "+f"(d[1]), "+f"(d[2]), "+f"(d[3])
               : "r"(a[0]), "r"(a[1]), "r"(a[2]), "r"(a[3]), "l"(db), "r"(sc));
}
__device__ __forceinline__ void wgmma_tt32(float (&d)[16], uint64_t da, uint64_t db, int sc) {
  asm volatile("{.reg .pred p; setp.ne.b32 p,%18,0; wgmma.mma_async.sync.aligned.m64n32k16.f32.bf16.bf16 "
               "{%0,%1,%2,%3,%4,%5,%6,%7,%8,%9,%10,%11,%12,%13,%14,%15},%16,%17,p,1,1,1,1;}"
               : "+f"(d[0]), "+f"(d[1]), "+f"(d[2]), "+f"(d[3]), "+f"(d[4]), "+f"(d[5]), "+f"(d[6]), "+f"(d[7]), "+f"(d[8]), "+f"(d[9]), "+f"(d[10]), "+f"(d[11]), "+f"(d[12]), "+f"(d[13]), "+f"(d[14]), "+f"(d[15])
               : "l"(da), "l"(db), "r"(sc));
}
__device__ __forceinline__ void wgmma_ts16(float (&d)[8], uint64_t da, uint64_t db, int sc) {
  asm volatile("{.reg .pred p; setp.ne.b32 p,%10,0; wgmma.mma_async.sync.aligned.m64n16k16.f32.bf16.bf16 "
               "{%0,%1,%2,%3,%4,%5,%6,%7},%8,%9,p,1,1,1,0;}"
               : "+f"(d[0]), "+f"(d[1]), "+f"(d[2]), "+f"(d[3]), "+f"(d[4]), "+f"(d[5]), "+f"(d[6]), "+f"(d[7])
               : "l"(da), "l"(db), "r"(sc));
}
__device__ __forceinline__ void wgmma_ts64(float (&d)[32], uint64_t da, uint64_t db, int sc) {
  asm volatile("{.reg .pred p; setp.ne.b32 p,%34,0; wgmma.mma_async.sync.aligned.m64n64k16.f32.bf16.bf16 "
               "{%0,%1,%2,%3,%4,%5,%6,%7,%8,%9,%10,%11,%12,%13,%14,%15,%16,%17,%18,%19,%20,%21,%22,%23,%24,%25,%26,%27,%28,%29,%30,%31},%32,%33,p,1,1,1,0;}"
               : "+f"(d[0]), "+f"(d[1]), "+f"(d[2]), "+f"(d[3]), "+f"(d[4]), "+f"(d[5]), "+f"(d[6]), "+f"(d[7]), "+f"(d[8]), "+f"(d[9]), "+f"(d[10]), "+f"(d[11]), "+f"(d[12]), "+f"(d[13]), "+f"(d[14]), "+f"(d[15]), "+f"(d[16]), "+f"(d[17]), "+f"(d[18]), "+f"(d[19]), "+f"(d[20]), "+f"(d[21]), "+f"(d[22]), "+f"(d[23]), "+f"(d[24]), "+f"(d[25]), "+f"(d[26]), "+f"(d[27]), "+f"(d[28]), "+f"(d[29]), "+f"(d[30]), "+f"(d[31])
               : "l"(da), "l"(db), "r"(sc));
}
__device__ __forceinline__ void wgmma_tt16(float (&d)[8], uint64_t da, uint64_t db, int sc) {
  asm volatile("{.reg .pred p; setp.ne.b32 p,%10,0; wgmma.mma_async.sync.aligned.m64n16k16.f32.bf16.bf16 "
               "{%0,%1,%2,%3,%4,%5,%6,%7},%8,%9,p,1,1,1,1;}"
               : "+f"(d[0]), "+f"(d[1]), "+f"(d[2]), "+f"(d[3]), "+f"(d[4]), "+f"(d[5]), "+f"(d[6]), "+f"(d[7])
               : "l"(da), "l"(db), "r"(sc));
}
__device__ __forceinline__ void wgmma_tt40(float (&d)[20], uint64_t da, uint64_t db, int sc) {
  asm volatile("{.reg .pred p; setp.ne.b32 p,%22,0; wgmma.mma_async.sync.aligned.m64n40k16.f32.bf16.bf16 "
               "{%0,%1,%2,%3,%4,%5,%6,%7,%8,%9,%10,%11,%12,%13,%14,%15,%16,%17,%18,%19},%20,%21,p,1,1,1,1;}"
               : "+f"(d[0]), "+f"(d[1]), "+f"(d[2]), "+f"(d[3]), "+f"(d[4]), "+f"(d[5]), "+f"(d[6]), "+f"(d[7]), "+f"(d[8]), "+f"(d[9]), "+f"(d[10]), "+f"(d[11]), "+f"(d[12]), "+f"(d[13]), "+f"(d[14]), "+f"(d[15]), "+f"(d[16]), "+f"(d[17]), "+f"(d[18]), "+f"(d[19])
               : "l"(da), "l"(db), "r"(sc));
}
__device__ __forceinline__ void wgmma_ss8(float (&d)[4], uint64_t da, uint64_t db, int sc) {
  asm volatile("{.reg .pred p; setp.ne.b32 p,%6,0; wgmma.mma_async.sync.aligned.m64n8k16.f32.bf16.bf16 "
               "{%0,%1,%2,%3},%4,%5,p,1,1,0,0;}"
               : "+f"(d[0]), "+f"(d[1]), "+f"(d[2]), "+f"(d[3])
               : "l"(da), "l"(db), "r"(sc));
}
__device__ __forceinline__ void wgmma_ss32(float (&d)[16], uint64_t da, uint64_t db, int sc) {
  asm volatile("{.reg .pred p; setp.ne.b32 p,%18,0; wgmma.mma_async.sync.aligned.m64n32k16.f32.bf16.bf16 "
               "{%0,%1,%2,%3,%4,%5,%6,%7,%8,%9,%10,%11,%12,%13,%14,%15},%16,%17,p,1,1,0,0;}"
               : "+f"(d[0]), "+f"(d[1]), "+f"(d[2]), "+f"(d[3]), "+f"(d[4]), "+f"(d[5]), "+f"(d[6]), "+f"(d[7]), "+f"(d[8]), "+f"(d[9]), "+f"(d[10]), "+f"(d[11]), "+f"(d[12]), "+f"(d[13]), "+f"(d[14]), "+f"(d[15])
               : "l"(da), "l"(db), "r"(sc));
}
__device__ __forceinline__ void wgmma_st64(float (&d)[32], uint64_t da, uint64_t db, int sc) {
  asm volatile("{.reg .pred p; setp.ne.b32 p,%34,0; wgmma.mma_async.sync.aligned.m64n64k16.f32.bf16.bf16 "
               "{%0,%1,%2,%3,%4,%5,%6,%7,%8,%9,%10,%11,%12,%13,%14,%15,%16,%17,%18,%19,%20,%21,%22,%23,%24,%25,%26,%27,%28,%29,%30,%31},%32,%33,p,1,1,0,1;}"
               : "+f"(d[0]), "+f"(d[1]), "+f"(d[2]), "+f"(d[3]), "+f"(d[4]), "+f"(d[5]), "+f"(d[6]), "+f"(d[7]), "+f"(d[8]), "+f"(d[9]), "+f"(d[10]), "+f"(d[11]), "+f"(d[12]), "+f"(d[13]), "+f"(d[14]), "+f"(d[15]), "+f"(d[16]), "+f"(d[17]), "+f"(d[18]), "+f"(d[19]), "+f"(d[20]), "+f"(d[21]), "+f"(d[22]), "+f"(d[23]), "+f"(d[24]), "+f"(d[25]), "+f"(d[26]), "+f"(d[27]), "+f"(d[28]), "+f"(d[29]), "+f"(d[30]), "+f"(d[31])
               : "l"(da), "l"(db), "r"(sc));
}
__device__ __forceinline__ void wgmma_st128(float (&d)[64], uint64_t da, uint64_t db, int sc) {
  asm volatile("{.reg .pred p; setp.ne.b32 p,%66,0; wgmma.mma_async.sync.aligned.m64n128k16.f32.bf16.bf16 "
               "{%0,%1,%2,%3,%4,%5,%6,%7,%8,%9,%10,%11,%12,%13,%14,%15,%16,%17,%18,%19,%20,%21,%22,%23,%24,%25,%26,%27,%28,%29,%30,%31,%32,%33,%34,%35,%36,%37,%38,%39,%40,%41,%42,%43,%44,%45,%46,%47,%48,%49,%50,%51,%52,%53,%54,%55,%56,%57,%58,%59,%60,%61,%62,%63},%64,%65,p,1,1,0,1;}"
               : "+f"(d[0]), "+f"(d[1]), "+f"(d[2]), "+f"(d[3]), "+f"(d[4]), "+f"(d[5]), "+f"(d[6]), "+f"(d[7]), "+f"(d[8]), "+f"(d[9]), "+f"(d[10]), "+f"(d[11]), "+f"(d[12]), "+f"(d[13]), "+f"(d[14]), "+f"(d[15]), "+f"(d[16]), "+f"(d[17]), "+f"(d[18]), "+f"(d[19]), "+f"(d[20]), "+f"(d[21]), "+f"(d[22]), "+f"(d[23]), "+f"(d[24]), "+f"(d[25]), "+f"(d[26]), "+f"(d[27]), "+f"(d[28]), "+f"(d[29]), "+f"(d[30]), "+f"(d[31]), "+f"(d[32]), "+f"(d[33]), "+f"(d[34]), "+f"(d[35]), "+f"(d[36]), "+f"(d[37]), "+f"(d[38]), "+f"(d[39]), "+f"(d[40]), "+f"(d[41]), "+f"(d[42]), "+f"(d[43]), "+f"(d[44]), "+f"(d[45]), "+f"(d[46]), "+f"(d[47]), "+f"(d[48]), "+f"(d[49]), "+f"(d[50]), "+f"(d[51]), "+f"(d[52]), "+f"(d[53]), "+f"(d[54]), "+f"(d[55]), "+f"(d[56]), "+f"(d[57]), "+f"(d[58]), "+f"(d[59]), "+f"(d[60]), "+f"(d[61]), "+f"(d[62]), "+f"(d[63])
               : "l"(da), "l"(db), "r"(sc));
}

__device__ __forceinline__ void stsm4(uint32_t a, uint32_t r0, uint32_t r1, uint32_t r2, uint32_t r3) {
  asm volatile("stmatrix.sync.aligned.m8n8.x4.shared.b16 [%0],{%1,%2,%3,%4};" ::"r"(a), "r"(r0), "r"(r1), "r"(r2), "r"(r3) : "memory");
}
__device__ __forceinline__ void stsm4t(uint32_t a, uint32_t r0, uint32_t r1, uint32_t r2, uint32_t r3) {
  asm volatile("stmatrix.sync.aligned.m8n8.x4.trans.shared.b16 [%0],{%1,%2,%3,%4};" ::"r"(a), "r"(r0), "r"(r1), "r"(r2), "r"(r3) : "memory");
}
__device__ __forceinline__ void stsm2t(uint32_t a, uint32_t r0, uint32_t r1) {
  asm volatile("stmatrix.sync.aligned.m8n8.x2.trans.shared.b16 [%0],{%1,%2};" ::"r"(a), "r"(r0), "r"(r1) : "memory");
}
__device__ __forceinline__ void sts64(uint32_t a, uint32_t x, uint32_t y) { asm volatile("st.shared.v2.b32 [%0],{%1,%2};" ::"r"(a), "r"(x), "r"(y) : "memory"); }
__device__ __forceinline__ void st_async2u(uint32_t a, uint32_t x, uint32_t y, uint32_t bar) {
  asm volatile("st.async.weak.shared::cluster.mbarrier::complete_tx::bytes.v2.b32 [%0],{%1,%2},[%3];" ::"r"(a), "r"(x), "r"(y), "r"(bar) : "memory");
}
__device__ __forceinline__ void st_relaxed128(void* p, uint32_t x, uint32_t y, uint32_t z, uint32_t w) {
  asm volatile("{.reg .b128 v; mov.b128 v,{%1,%2,%3,%4}; st.relaxed.gpu.global.b128 [%0],v;}" ::"l"(p), "r"(x), "r"(y), "r"(z), "r"(w) : "memory");
}
__device__ __forceinline__ void st_relaxed64(void* p, uint32_t x, uint32_t y) {
  asm volatile("{.reg .b64 v; mov.b64 v,{%1,%2}; st.relaxed.gpu.global.b64 [%0],v;}" ::"l"(p), "r"(x), "r"(y) : "memory");
}
__device__ __forceinline__ uint4 ld_relaxed128(const void* p) {
  uint4 v;
  asm volatile("{.reg .b128 v; .reg .b64 lo, hi; ld.relaxed.gpu.global.b128 v,[%4]; mov.b128 {lo,hi},v; mov.b64 {%0,%1},lo; mov.b64 {%2,%3},hi;}" : "=r"(v.x), "=r"(v.y), "=r"(v.z), "=r"(v.w) : "l"(p) : "memory");
  return v;
}

__device__ __forceinline__ uint32_t pack_h2(float lo, float hi) {
  uint32_t r; asm("cvt.rn.satfinite.f16x2.f32 %0,%1,%2;" : "=r"(r) : "f"(hi), "f"(lo)); return r;
}
__device__ __forceinline__ void add_h2(float& lo, float& hi, uint32_t u, uint32_t v) {
  float a, b;
  asm("{.reg .b16 l, h; .reg .b32 s; add.rn.f16x2 s,%2,%3; mov.b32 {l,h},s; cvt.f32.f16 %0,l; cvt.f32.f16 %1,h;}" : "=f"(a), "=f"(b) : "r"(u), "r"(v));
  lo += a; hi += b;
}
__device__ __forceinline__ void mwait(uint32_t bar, uint32_t ph, int& spin) {
  asm volatile("{.reg .pred p, q;\nWAIT_LOOP:\n add.s32 %0,%0,1;\n setp.lt.s32 q,%0,%3;\n mbarrier.try_wait.parity.shared::cta.b64 p,[%1],%2;\n not.pred p,p;\n and.pred q,q,p;\n @q bra.uni WAIT_LOOP;\n}"
               : "+&r"(spin) : "r"(bar), "r"(ph), "n"(SPIN_TOT) : "memory");
}
__device__ __forceinline__ int keep(int x) { return __shfl_sync(0xffffffffu, x, threadIdx.x & 31); }
__device__ __forceinline__ uint32_t pin(uint32_t x) { asm volatile("" : "+r"(x)); return x; }
template <typename T> __device__ __forceinline__ T* pinp(T* x) { asm volatile("" : "+l"(x)); return x; }
__device__ __forceinline__ void st_async1u(uint32_t a, uint32_t x, uint32_t bar) {
  asm volatile("st.async.weak.shared::cluster.mbarrier::complete_tx::bytes.b32 [%0],%1,[%2];" ::"r"(a), "r"(x), "r"(bar) : "memory");
}
__device__ __forceinline__ uint32_t lds32(uint32_t a) { uint32_t v; asm volatile("ld.shared.b32 %0,[%1];" : "=r"(v) : "r"(a) : "memory"); return v; }
__device__ __forceinline__ uint2 lds64(uint32_t a) { uint2 v; asm volatile("ld.shared.v2.b32 {%0,%1},[%2];" : "=r"(v.x), "=r"(v.y) : "r"(a) : "memory"); return v; }

__device__ __forceinline__ void permute_cols(uint32_t tile, int tid, int n) {
#pragma unroll 2
  for (int it = tid; it < n; it += 128) {
    const int row = it >> 2, q = it & 3;
    const uint32_t a0 = tile + row * 128 + (((2 * q) ^ (row & 7)) << 4), a1 = tile + row * 128 + (((2 * q + 1) ^ (row & 7)) << 4);
    const uint4 u = lds128(a0), v = lds128(a1);
    sts128(a0, make_uint4(__byte_perm(u.x, u.y, 0x5410), __byte_perm(u.z, u.w, 0x5410), __byte_perm(v.x, v.y, 0x5410), __byte_perm(v.z, v.w, 0x5410)));
    sts128(a1, make_uint4(__byte_perm(u.x, u.y, 0x7632), __byte_perm(u.z, u.w, 0x7632), __byte_perm(v.x, v.y, 0x7632), __byte_perm(v.z, v.w, 0x7632)));
  }
}

__device__ __forceinline__ uint8_t* mkptr(uint32_t lo, uint32_t hi) { uint8_t* p; asm("mov.b64 %0,{%1,%2};" : "=l"(p) : "r"(lo), "r"(hi)); return p; }
__device__ __forceinline__ int uni(int x) { return __shfl_sync(0xffffffffu, x, 0); }

__device__ __forceinline__ bool elect_one() {
  uint32_t p; asm volatile("{.reg .pred q; elect.sync _|q, 0xffffffff; selp.u32 %0,1,0,q;}" : "=r"(p)); return p;
}
__device__ __forceinline__ uint64_t desc_at(uint64_t d, uint32_t off) {
  uint64_t r; asm("mov.b64 %0,{%1,%2};" : "=l"(r) : "r"((uint32_t)d + (off >> 4)), "r"((uint32_t)(d >> 32))); return r;
}
__device__ __forceinline__ uint32_t scale_bf16x2(uint32_t x, uint32_t s) { uint32_t r; asm("mul.rn.bf16x2 %0,%1,%2;" : "=r"(r) : "r"(x), "r"(s)); return r; }

__device__ __forceinline__ void stg128(void* p, const uint4& v) { asm volatile("st.global.v4.b32 [%0],{%1,%2,%3,%4};" ::"l"(p), "r"(v.x), "r"(v.y), "r"(v.z), "r"(v.w) : "memory"); }

__device__ __forceinline__ float quad_sum(float x) {
  const float a = __shfl_xor_sync(0xffffffffu, x, 1), b = __shfl_xor_sync(0xffffffffu, x, 2), c = __shfl_xor_sync(0xffffffffu, x, 3);
  return (x + a) + (b + c);
}
__device__ __forceinline__ float warp_sum(float x) {
  x = quad_sum(x);
  const float a = __shfl_xor_sync(0xffffffffu, x, 4), b = __shfl_xor_sync(0xffffffffu, x, 8), c = __shfl_xor_sync(0xffffffffu, x, 12);
  x = (x + a) + (b + c);
  return x + __shfl_xor_sync(0xffffffffu, x, 16);
}
__device__ __forceinline__ void ln_row(float4 (&v)[5]) {
  float t = 0.f;
#pragma unroll
  for (int m = 0; m < 5; m++) t += (v[m].x + v[m].y) + (v[m].z + v[m].w);
  const float mean = warp_sum(t) * (1.f / DM);
  float q0 = 0.f, q1 = 0.f;
#pragma unroll
  for (int m = 0; m < 5; m++) {
    v[m].x -= mean; v[m].y -= mean; v[m].z -= mean; v[m].w -= mean;
    q0 += v[m].x * v[m].x + v[m].y * v[m].y; q1 += v[m].z * v[m].z + v[m].w * v[m].w;
  }
  const float rs = rsqrtf(warp_sum(q0 + q1) * (1.f / DM) + 1e-5f);
#pragma unroll
  for (int m = 0; m < 5; m++) { v[m].x *= rs; v[m].y *= rs; v[m].z *= rs; v[m].w *= rs; }
}
__device__ __forceinline__ void ln0_load(const bf16* __restrict__ x, uint2 (&u)[5], int row, int lane) {
#pragma unroll
  for (int m = 0; m < 5; m++) u[m] = *reinterpret_cast<const uint2*>(x + (size_t)row * DM + m * 128 + lane * 4);
}
__device__ __forceinline__ void ln0_copy(const uint2 (&u)[5], int row, int lane) {
#pragma unroll
  for (int m = 0; m < 5; m++) stg128(g_x + (size_t)row * DM + m * 128 + lane * 4, make_uint4(u[m].x << 16, u[m].x & 0xFFFF0000u, u[m].y << 16, u[m].y & 0xFFFF0000u));
}
__device__ __forceinline__ void ln0_row(const uint2 (&u)[5], int row, int lane) {
  float4 v[5];
#pragma unroll
  for (int m = 0; m < 5; m++) v[m] = make_float4(bf_lo(u[m].x), bf_hi(u[m].x), bf_lo(u[m].y), bf_hi(u[m].y));
  ln_row(v);
  uint8_t* dst = g_xn[row >> 5] + ((row >> 3) & 3) * 4096 + (lane >> 4) * 1024 + (row & 7) * 128 + ((((lane >> 1) ^ row) & 7) << 4) + (lane & 1) * 8;
#pragma unroll
  for (int m = 0; m < 5; m++) *reinterpret_cast<uint2*>(dst + m * 16384) = make_uint2(pack_bf16(v[m].x, v[m].y), pack_bf16(v[m].z, v[m].w));
}

#define NOWORK 0
__device__ __forceinline__ void prep_row(const uint2 (&u)[5], const bf16* __restrict__ mem0, int k, int r, int lane) {
  const uint4 sent = make_uint4(SENT, SENT, SENT, SENT);
  if (k + 1 < NSTEP) {
    uint8_t* ex = ex_window(g_ex);
#pragma unroll
    for (int h = 0; h < 2; h++) {
      const int p = r * 40 + h * 32 + lane;
      if (h == 0 || lane < 8) {
        uint4 v = sent;
        if (k + 1 == LAG && (p & 8)) v = *reinterpret_cast<const uint4*>(mem0 + (p & 7) * DM + (p >> 4) * 8);
        stg128(ex + EX_M + (k + 1) * 20480 + p * 16, v);
      } else if (lane < 14) stg128(ex + EX_FLAG + (k + 1) * 3072 + (r * 6 + lane - 8) * 16, sent);
    }
  }
  if (k < LAG || k >= NSEG || NOWORK) {
    uint8_t* z = g_xn[k] + (r >> 3) * 4096 + (k < NSEG ? 2048 : 0) + (lane >> 4) * 1024 + (r & 7) * 128 + (lane & 15) * 8;
#pragma unroll
    for (int m = 0; m < 5; m++) *reinterpret_cast<uint2*>(z + m * 16384) = make_uint2(0, 0);
  }
  if (k < NSEG) {
    ln0_copy(u, k * 32 + r, lane);
    ln0_row(u, k * 32 + r, lane);
  }
}
__device__ __forceinline__ void pre_work(const bf16* __restrict__ x, const bf16* __restrict__ mem0, int cta, int tid) {
  constexpr int NT = 96 * 128;
  const int gt = cta * 128 + tid;
  uint8_t* ex = ex_window(g_ex);
#pragma unroll 1
  for (int row = cta + 96 * (tid >> 5); row < (NOWORK == 2 ? NSTEP : NPRE) * 32; row += 384) {
    uint2 u[5];
    ln0_load(x, u, min(row, SEQ - 1), tid & 31);
    prep_row(u, mem0, row >> 5, row & 31, tid & 31);
  }
#pragma unroll 1
  for (int i = gt; i < MAIL_BYTES / 16; i += NT) {
    stg128(ex + EX_MAIL + i * 16, make_uint4(SENT, SENT, SENT, SENT));
    stg128(ex + EX_MAIL + (1 << 20) + i * 16, make_uint4(SENT, SENT, SENT, SENT));
  }
  const int p = NT - 1 - gt;
  if (p < 1280) stg128(ex + EX_M + p * 16, *reinterpret_cast<const uint4*>(mem0 + (p & 7) * DM + (p >> 4) * 8));
  if (p < 192) stg128(ex + EX_FLAG + p * 16, make_uint4(0, 0, 0, 0));
  if (gt < 8 * CN_NUM) stg128(&g_cnt[0][0] + gt * 4, make_uint4(0, 0, 0, 0));
}
__device__ __forceinline__ void pre_wait(int which, uint32_t n, int& spin) {
  uint32_t old;
  asm volatile("atom.acq_rel.gpu.global.add.u32 %0,[%1],1;" : "=r"(old) : "l"(&g_ticket[which][0]) : "memory");
  const uint32_t target = (old / n + 1) * 96;
  while ((int)(ld_acquire(&g_ticket[0][0]) - target) < 0 && spin < SPIN_TOT) spin += 16;
  fence_async_all();
}

namespace C {
constexpr int NKR = 37;
constexpr int OFF_WQ = 0, OFF_WK = 81920;
constexpr int OFF_YO = 163840, OFF_YV = OFF_YO + 6144;
constexpr int OFF_M = 176128;
__host__ __device__ constexpr int og_off(int c) { return c ? OFF_M + 14336 + c * 2048 : 229376; }
constexpr int OFF_KT = 196608;
constexpr int OFF_XT = OFF_KT + 10240;
constexpr int OFF_VT = OFF_XT + 7168;
constexpr int OFF_XM = OFF_VT + 11392;
constexpr int OFF_PT = OFF_XM + 2560;
constexpr int KS = 1280, VS = 1408;
__host__ __device__ constexpr int slot_off(int p) { return p == 2 ? OFF_M : OFF_KT + (p % 3) * 16384; }
constexpr int OFF_ONE = 231424;
constexpr int OFF_BAR = 231552;
constexpr int OFF_SAFE = OFF_BAR + 144;
constexpr int OFF_TS = OFF_BAR + 256;
constexpr int SMEM = 232448;
constexpr uint32_t SB0 = 1024;
constexpr int BAR_F = OFF_BAR, BAR_XM = BAR_F + 40, BAR_XT = BAR_F + 48, BAR_OG = BAR_F + 56, BAR_E = OFF_BAR + 64, BAR_MOK = BAR_E + 40,
              BAR_M = OFF_BAR + 112, BAR_XF = OFF_BAR + 120, BAR_MF = OFF_BAR + 128, FLG_REDO = OFF_BAR + 136, BAR_W = OFF_BAR + 208;
constexpr int NB_PRO = 1, NB_RD = 2, NB_MR = 3, NB_QK = 4, NB_SM = 5, NB_VA = 6, NB_VQ = 7, NB_A = 8, NB_Q = 9, NB_C = 10, NB_WQ = 11, NB_QI = 12, NB_SI = 13, NB_WV = 14, NB_V = 15;
#define B1 600
#define AD0 16
#define AD1 128
#define AD2 16
#define AD3 128
#define BMX 1200
#define B2 800
#define FLP 1
#define OSG 2
#define OST 7
#define NBX 1
#define P1U 4
#define QIE 4
#define SIE 2
#define WOE 1
#define OGF 0
#define VSP 8
#define RFK 5
#define PFD 3
#define WOL 0
constexpr uint32_t SCQ = 0x3A003A00;
constexpr float SCE = 0.07216878364870322f * 1.4426950408889634f * 2048;
}

#define CBAR_SYNC(id, n) bar_sync(id, n)
#define CBAR_ARRIVE(id, n) bar_arrive(id, n)

__device__ __forceinline__ uint64_t wdesc(int off) { return mkdesc(C::SB0 + off, 8192, 1024); }
__device__ __forceinline__ uint64_t mdesc(int k) { return mkdesc_ns(C::SB0 + C::OFF_M + k * 512, 256, 128); }
__device__ __forceinline__ uint64_t tdesc(int k) { return mkdesc(C::SB0 + C::slot_off(k >> 3) + ((k >> 2) & 1) * 1024 + (k & 3) * 32, 16, 2048); }

__device__ __forceinline__ int dh_row(int n) { return (n & ~63) + (n & 32) + ((n >> 1) & 3) * 8 + ((n >> 3) & 3) * 2 + (n & 1); }
template <bool IS_O>
__device__ __forceinline__ void stage_box(const CUtensorMap& tm, uint32_t sb, int p, int cta, int rank) {
  using namespace C;
  const uint32_t bar = sb + BAR_W + 8 * p;
  const int head = cta / 3, col = head * DH + rank * 64;
  mbar_expect_tx(bar, 16384);
  if (!IS_O) tma2d(sb + OFF_WK + p * 16384, &tm, col, p * 128, bar);
  else for (int b = 2 * p - 1; b <= 2 * p; b++)
    tma2d(sb + OFF_WQ + (b + 1) * 8192, &tm, b < 0 ? 576 : (3 * rank + b / 3) * 64, b < 0 ? col : head * DH + ((rank + b) % 3) * 64, bar);
}
template <bool IS_O>
__device__ __forceinline__ void load_weights_rs(uint32_t (&wf)[C::NKR][4], const CUtensorMap& tms, const CUtensorMap& tm, int cta, int rank, uint32_t sb, int tid0, int& spin) {
  using namespace C;
  constexpr int STAGE = IS_O ? OFF_WQ : OFF_WK, YOFF = IS_O ? OFF_YO : OFF_YV, NB = IS_O ? NB_C : NB_V;
  const int i = (tid0 >> 3) & 3, n0 = (tid0 & 7) + (i >> 1) * 8;
  const int chunk = 2 * ((tid0 >> 5) & 3) + (i & 1);
  const int r0 = IS_O ? dh_row(n0) : n0, r1 = IS_O ? dh_row(n0 + 16) : n0 + 16;
  const uint32_t a0 = sb + STAGE + r0 * 128 + ((chunk ^ (r0 & 7)) << 4), a1 = sb + STAGE + r1 * 128 + ((chunk ^ (r1 & 7)) << 4);
#pragma unroll
  for (int p = 0; p < 5; p++) {
    mwait(sb + BAR_W + 8 * p, 0, spin);
    if (IS_O) PTS(8 + p);
    if (p + NBX < 5) { if ((tid0 & 127) == 96) stage_box<IS_O>(tms, sb, p + NBX, cta, rank); __syncwarp(); }
    if (IS_O) permute_cols(sb + STAGE + p * 16384, tid0, 512);
    else {
#pragma unroll 1
      for (int it = tid0 & 127; it < 256; it += 128) {
        const uint32_t base = sb + STAGE + p * 16384 + (it >> 1) * 128;
        const int sw = ((it >> 1) & 7) ^ ((it & 1) * 4);
        const uint4 u0 = lds128(base + (sw << 4)), u1 = lds128(base + ((sw ^ 1) << 4)), u2 = lds128(base + ((sw ^ 2) << 4)), u3 = lds128(base + ((sw ^ 3) << 4));
        sts128(base + (sw << 4), make_uint4(u0.x, u1.x, u2.x, u3.x)); sts128(base + ((sw ^ 1) << 4), make_uint4(u0.y, u1.y, u2.y, u3.y));
        sts128(base + ((sw ^ 2) << 4), make_uint4(u0.z, u1.z, u2.z, u3.z)); sts128(base + ((sw ^ 3) << 4), make_uint4(u0.w, u1.w, u2.w, u3.w));
      }
    }
    bar_sync(NB, 128);
#pragma unroll
    for (int k = 8 * p; k < 8 * p + 8; k++) {
      if (k < NKR) ldsm4t(wf[k < NKR ? k : 0], ((k & 1) ? a1 : a0) + (k >> 1) * 4096);
      else {
        const int n = k * 16 + ((tid0 & 127) >> 3), r = IS_O ? dh_row(n) : n, c = tid0 & 7;
        sts128(sb + YOFF + (n - NKR * 16) * 128 + ((c ^ (n & 7)) << 4), lds128(sb + STAGE + r * 128 + ((c ^ (r & 7)) << 4)));
      }
    }
    fence_async();
    bar_sync(NB, 128);
    if ((tid0 & 127) == 0) {
      mbar_expect_tx(sb + BAR_W + 8 * p, 16384);
      tma2d(sb + STAGE + p * 16384, &tm, (cta / 3) * DH + rank * 64, p * 128, sb + BAR_W + 8 * p);
    }
    __syncwarp();
  }
  PTS(IS_O ? 13 : 14);
  CBAR_SYNC(NB_PRO, 384);
}
template <int STRIDE>
__device__ __forceinline__ void store_mem(const float (&d)[8], uint32_t base, int tid) {
  const int m = (tid >> 3) & 3;
  stsm4(base + (((tid >> 5) & 3) * 2 + (m & 1)) * STRIDE + (m >> 1) * 640 + (tid & 7) * 16, pack_bf16(d[0], d[1]), pack_bf16(d[2], d[3]),
        pack_bf16(d[4], d[5]), pack_bf16(d[6], d[7]));
}

__device__ __forceinline__ void load_pair(uint32_t sb, int i, int p, uint32_t slot, uint32_t ph, int& spin) {
  using namespace C;
  mwait(sb + BAR_E + 8 * p, ph, spin);
  if (elect_one()) bulk_g2s_mc(sb + slot, g_xn[i] + p * 16384, 16384, sb + BAR_F + 8 * p);
}
__device__ __forceinline__ void release_round(uint32_t sb, int p, int lane) {
  if (lane < (p == 2 ? 3 : 1)) mbar_arrive_cluster(mapa(sb, p == 2 ? lane : p) + C::BAR_E + 8 * (3 + p));
}

template <int K0, int K1>
__device__ __forceinline__ void v_mem_pass(float (&d)[8], const uint32_t (&wf)[C::NKR][4]) {
  using namespace C;
  wg_fence();
#pragma unroll
  for (int k = K0; k < K1; k++) {
    if (k < NKR) wgmma_rs16(d, wf[k < NKR ? k : 0], mdesc(k), k != 32);
    else wgmma_ts16(d, wdesc(OFF_YV + (k - NKR) * 2048), mdesc(k), 1);
  }
  wg_commit();
}
__device__ __forceinline__ void chain_v(const CUtensorMap& tmWv, const CUtensorMap& tmWk, const uint32_t sb, const int tid0, const int cta, const int rank) {
  using namespace C;
  asm volatile("setmaxnreg.inc.sync.aligned.u32 208;");
  int spin = 0;
  uint32_t wf[NKR][4];
  const int wu = uni((tid0 >> 5) & 3);
  const uint32_t slot = rank == 2 ? OFF_M : OFF_KT + rank * 16384;
  load_weights_rs<false>(wf, tmWv, tmWk, cta, rank, sb, tid0, spin);
  PTS(5);
#pragma unroll 1
  for (int i = 0; i < NSTEP; i++) {
    {
      float d[32];
      if (i > 0) CBAR_SYNC(NB_WV, 256);
#pragma unroll
      for (int p = 0; p < 5; p++) {
        mwait(sb + BAR_F + 8 * p, i & 1, spin);
        TS(i, 25 + p);
        wg_fence();
#pragma unroll
        for (int k = 8 * p; k < 8 * p + 8; k++) {
          if (k < NKR) wgmma_rs64(d, wf[k < NKR ? k : 0], tdesc(k), k);
          else wgmma_ts64(d, wdesc(OFF_YV + (k - NKR) * 2048), tdesc(k), 1);
          if (k == 8 * p + 1 && p >= 1 && p <= 3) {
            wg_commit(); wg_wait<1>();
            release_round(sb, p - 1, tid0 & 31);
          }
          if (k == 8 * p + RFK && (p == 1 || p == 2)) {
            wg_commit();
            if (rank == p - 1 && wu == 0) load_pair(sb, i, p + 2, slot_off(p + 2), i & 1, spin);
            wg_fence();
          }
        }
        wg_commit();
      }
      wg_wait<0>();
      TS(i, 23);
      CBAR_SYNC(NB_RD, 256);
      const int tid = fresh(tid0) & 127, m = (tid >> 3) & 3;
      if (tid < 8) mbar_expect_tx(sb + BAR_F + 8 * tid, tid < 5 ? 16384 : tid == 5 ? 2560 : tid == 6 ? 7168 : 4096);
      if (tid < 3 && tid != rank) mbar_arrive_cluster(mapa(sb, tid) + BAR_XF);
      const uint32_t a = sb + OFF_VT + 256 + ((tid >> 5) * 2 + (m & 1)) * VS + (m >> 1) * 640 + (tid & 7) * 16;
#pragma unroll
      for (int s = 0; s < 4; s++)
        stsm4(a + s * 128, pack_bf16(d[8 * s], d[8 * s + 1]), pack_bf16(d[8 * s + 2], d[8 * s + 3]),
              pack_bf16(d[8 * s + 4], d[8 * s + 5]), pack_bf16(d[8 * s + 6], d[8 * s + 7]));
      if (tid < 80) sts128(sb + (tid < 72 ? OFF_VT + (tid >> 3) * VS : OFF_PT + 1280) + (tid & 7) * 16, make_uint4(0, 0, 0, 0));
      fence_async();
    }
    mwait(sb + BAR_XF, i & 1, spin);
    CBAR_ARRIVE(NB_QK, 384);
    const uint32_t* xc = &g_cnt[CN_X + i + 1][0];
    const uint32_t xn = i + 1 < LAG || NOWORK ? 16 : 48;
    bool seen = NOWORK == 2 || i + 1 < NPRE;
    if (wu == 0 && !seen) { seen = ld_acquire(xc) >= xn; fence_async_all(); }
    CBAR_SYNC(NB_QI, 256);
    float d[8];
    v_mem_pass<32, 40>(d, wf);
    CBAR_SYNC(NB_SM, 256);
    wg_wait<0>();
    if (__builtin_expect(lds32(sb + FLG_REDO), 0)) { v_mem_pass<32, 40>(d, wf); wg_wait<0>(); }
    if ((tid0 & 31) < 3 && (tid0 & 31) != rank) mbar_arrive_cluster(mapa(sb, tid0 & 31) + BAR_MF);
    v_mem_pass<0, 32>(d, wf);
    wg_wait<0>();
    TS(i, 24);
    const int tid = fresh(tid0);
    if ((tid & 31) == 0) mbar_arrive_cluster(mapa(sb, 2) + BAR_E + 16);
    store_mem<VS>(d, sb + OFF_VT + 128, tid);
    fence_async();
    CBAR_ARRIVE(NB_VA, 256);
    CBAR_ARRIVE(NB_VQ, 256);
    if (wu == 0 && i + 1 < NSTEP) {
      if (__builtin_expect(!seen, 0)) { while (ld_acquire(xc) < xn && spin < SPIN_TOT) spin += 16; fence_async_all(); }
      load_pair(sb, i + 1, rank, slot, i & 1, spin);
      TS(i + 1, 37);
    }
    TS_FLUSH(i - 1);
    __syncwarp();
  }
  CBAR_ARRIVE(NB_WV, 256);
  if (spin >= SPIN_TOT) g_err = 3;
}

__device__ __forceinline__ float quad_max(float x) {
  const float a = __shfl_xor_sync(0xffffffffu, x, 1), b = __shfl_xor_sync(0xffffffffu, x, 2), c = __shfl_xor_sync(0xffffffffu, x, 3);
  return fmaxf(fmaxf(x, a), fmaxf(b, c));
}
__device__ __forceinline__ float max10(const float (&y)[10]) {
  return fmaxf(fmaxf(fmaxf(fmaxf(y[0], y[1]), fmaxf(y[2], y[3])), fmaxf(fmaxf(y[4], y[5]), fmaxf(y[6], y[7]))), fmaxf(y[8], y[9]));
}
__device__ __forceinline__ float sum10(const float (&y)[10]) {
  return (((y[0] + y[1]) + (y[2] + y[3])) + ((y[4] + y[5]) + (y[6] + y[7]))) + (y[8] + y[9]);
}
__device__ __forceinline__ float rcp(float x) { float y; asm("rcp.approx.ftz.f32 %0,%1;" : "=f"(y) : "f"(x)); return y; }

__device__ __forceinline__ void signal_o(int i, int cta) { csignal(CN_O + i * 5 + min(cta / 19, 4)); }

__device__ __forceinline__ void chain_q(const bf16* x0, const bf16* mem0, const uint32_t sb, const int tid0, const int cta, const int rank) {
  using namespace C;
  asm volatile("setmaxnreg.dec.sync.aligned.u32 96;");
  int spin = 0;
  PTS(0);
  pre_work(x0, mem0, cta, tid0 & 127);
  PTS(3);
  CBAR_SYNC(NB_Q, 128);
  PTS(2);
  if (tid0 < 160) {
    if (tid0 == 128) pre_wait(0, 96, spin);
    __syncwarp();
    load_pair(sb, 0, rank, rank == 2 ? OFF_M : OFF_KT + rank * 16384, 1, spin);
  }
  PTS(4);
  CBAR_SYNC(NB_PRO, 384);
  mwait(sb + BAR_W, 1, spin);
  PTS(6);
  const int wu = uni((tid0 >> 5) & 3);
  uint4 ov[4] = {};
  uint8_t* op = &g_o[ORING - 1][cta][(tid0 & 124) * 32];
  const uint32_t o0 = ((tid0 ^ (tid0 >> 2)) & 3) * 16 + (tid0 & 16) * 4;
#pragma unroll 1
  for (int i = 0; i < NSTEP; i++) {
    const int ph = i & 1;
    uint32_t qf[4][4];
    {
      float d[64];
#define QK_STEP(K, SC) wgmma_st128(d, desc_at(mkdesc(SB0 + ((K) >> 2) * 1024 + ((K) & 3) * 32, 16, 2048), so), \
                                   desc_at(mkdesc(SB0 + OFF_WQ + (K) * 2048, OFF_WK - OFF_WQ, 1024), p * 16384), SC)
      int p = 0;
      uint32_t so = OFF_KT;
      mwait(sb + BAR_F, ph, spin);
      TS(i, 0);
      wg_fence();
#pragma unroll
      for (int k = 0; k < 8; k++) {
        QK_STEP(k, k);
        if (k == OST) {
          wg_commit();
          mwait(sb + BAR_F, ph, spin);
#pragma unroll
          for (int h = 0; h < 4; h++) stg128(op + (h & 1) * 4096 + (o0 ^ ((h >> 1) * 64)), ov[h]);
          if (i > 0) CBAR_ARRIVE(NB_MR, 160);
          if (k < 7) wg_fence();
        }
      }
      if (OST < 7) wg_commit();
#pragma unroll 1
      for (p = 1; p < 5; p++) {
        static_assert(OFF_KT - OFF_M == 5 << 12, "");
        so = OFF_M + (((0x95095u >> (4 * p)) & 15) << 12);
        if (i == 0) { mwait(sb + BAR_W + 8 * p, 1, spin); PTS(14 + p); }
        mwait(sb + BAR_F + 8 * p, ph, spin);
        wg_fence();
#pragma unroll
        for (int k = 0; k < 8; k++) {
          QK_STEP(k, 1);
          if (k == 1) {
            wg_commit(); wg_wait<1>();
            release_round(sb, p - 1, p < 4 ? tid0 & 31 : 32);
          }
        }
        wg_commit();
      }
#undef QK_STEP
      wg_wait<0>();
      TS(i, 1);
      CBAR_SYNC(NB_RD, 256);
      TSB(i, 2);
      const int tid = fresh(tid0), w = (tid >> 5) & 3, m = (tid >> 3) & 3;
      const uint32_t a = sb + OFF_KT + (m >> 1) * KS + (1 + w + 5 * (m & 1)) * 128 + (tid & 7) * 16;
#pragma unroll
      for (int s = 0; s < 4; s++)
        stsm4t(a + s * 2 * KS, pack_bf16(d[32 + 8 * s], d[33 + 8 * s]), pack_bf16(d[34 + 8 * s], d[35 + 8 * s]),
               pack_bf16(d[36 + 8 * s], d[37 + 8 * s]), pack_bf16(d[38 + 8 * s], d[39 + 8 * s]));
      fence_async();
      CBAR_ARRIVE(NB_QK, 384);
#pragma unroll
      for (int kk = 0; kk < 4; kk++)
#pragma unroll
        for (int j = 0; j < 4; j++) asm volatile("{.reg .b32 t; cvt.rn.bf16x2.f32 t,%1,%2; mul.rn.bf16x2 %0,t,%3;}" : "=r"(qf[kk][j]) : "f"(d[8 * kk + 2 * j + 1]), "f"(d[8 * kk + 2 * j]), "r"(SCQ));
    }
    CBAR_SYNC(NB_SI, 256);
    uint32_t pf[5][4];
    {
      float y0[10], y1[10];
      const int tidf = fresh(tid0), lane = tidf & 31;
      {
        float x[40];
        wg_fence();
#pragma unroll
        for (int kk = 0; kk < 4; kk++) wgmma_rt80(x, qf[kk], mkdesc_ns(SB0 + OFF_KT + kk * 2 * KS, KS, 128), kk);
        wg_commit();
        wg_wait<0>();
#pragma unroll
        for (int j = 0; j < 5; j++) { y0[2 * j] = x[4 * j]; y0[2 * j + 1] = x[4 * j + 1]; y1[2 * j] = x[22 + 4 * j]; y1[2 * j + 1] = x[23 + 4 * j]; }
      }
      TS(i, 17);
      const uint32_t xo = OFF_XT + (wu * (wu + 3) / 2) * 256 + lane * 16, x2 = xo + (wu >> 1) * 512 + 512 - lane * 8;
      {
        const uint4 h0 = make_uint4(pack_h2(y0[0], y0[1]), pack_h2(y1[0], y1[1]), pack_h2(y0[2], y0[3]), pack_h2(y1[2], y1[3]));
        const uint4 h1 = make_uint4(pack_h2(y0[4], y0[5]), pack_h2(y1[4], y1[5]), pack_h2(y0[6], y0[7]), pack_h2(y1[6], y1[7]));
        const uint32_t h2 = wu == 1 ? h1.x : pack_h2(y0[8], y0[9]), h3 = wu == 1 ? h1.y : pack_h2(y1[8], y1[9]);
        const uint32_t rb1 = mapa(sb, (rank + 1) % 3), rb2 = mapa(sb, (rank + 2) % 3);
        st_async4u(rb1 + xo + 3584, h0, rb1 + BAR_XT);
        st_async4u(rb2 + xo, h0, rb2 + BAR_XT);
        if (wu >= 2) { st_async4u(rb1 + xo + 4096, h1, rb1 + BAR_XT); st_async4u(rb2 + xo + 512, h1, rb2 + BAR_XT); }
        if (wu & 1) { st_async2u(rb1 + x2 + 3584, h2, h3, rb1 + BAR_XT); st_async2u(rb2 + x2, h2, h3, rb2 + BAR_XT); }
      }
      TS(i, 18);
      const int lim = 8 * wu + (lane >> 2) + 8 - 2 * (lane & 3);
#pragma unroll
      for (int j = 2; j < 10; j++)
        if (8 * (j >> 1) + (j & 1) > lim) { y0[j] = -INFINITY; y1[j] = -INFINITY; }
      mwait(sb + BAR_XT, ph, spin);
      TS(i, 19);
      {
        const uint4 u0 = lds128(sb + xo), v0 = lds128(sb + xo + 3584);
        uint2 u2 = make_uint2(0, 0), v2 = u2;
        if (wu & 1) { u2 = lds64(sb + x2); v2 = lds64(sb + x2 + 3584); }
        uint4 u1 = make_uint4(u2.x, u2.y, 0, 0), v1 = make_uint4(v2.x, v2.y, 0, 0);
        if (wu >= 2) { u1 = lds128(sb + xo + 512); v1 = lds128(sb + xo + 4096); }
        __syncwarp();
        if (lane == 0) mbar_arrive_cluster(mapa(sb, 0) + BAR_E);
        add_h2(y0[0], y0[1], u0.x, v0.x); add_h2(y1[0], y1[1], u0.y, v0.y); add_h2(y0[2], y0[3], u0.z, v0.z); add_h2(y1[2], y1[3], u0.w, v0.w);
        add_h2(y0[4], y0[5], u1.x, v1.x); add_h2(y1[4], y1[5], u1.y, v1.y); add_h2(y0[6], y0[7], u1.z, v1.z); add_h2(y1[6], y1[7], u1.w, v1.w);
        add_h2(y0[8], y0[9], u2.x, v2.x); add_h2(y1[8], y1[9], u2.y, v2.y);
      }
      const float m0 = quad_max(max10(y0)) * -SCE, m1 = quad_max(max10(y1)) * -SCE;
#pragma unroll
      for (int j = 0; j < 5; j++) {
        pf[j >> 1][2 * (j & 1)] = pack_bf16(ex2(fmaf(y0[2 * j], SCE, m0)), ex2(fmaf(y0[2 * j + 1], SCE, m0)));
        pf[j >> 1][2 * (j & 1) + 1] = tidf >> (10 + j);
        pf[(j + 5) >> 1][2 * ((j + 5) & 1)] = tidf >> (20 + j);
        pf[(j + 5) >> 1][2 * ((j + 5) & 1) + 1] = pack_bf16(ex2(fmaf(y1[2 * j], SCE, m1)), ex2(fmaf(y1[2 * j + 1], SCE, m1)));
      }
    }
#pragma unroll
    for (int q = 0; q < 20; q++) pf[q >> 2][q & 3] = pin(pf[q >> 2][q & 3]);
    CBAR_SYNC(NB_VQ, 256);
    TSB(i, 20);
    {
      float o[32], sm[4];
      wg_fence();
#pragma unroll
      for (int q = 0; q < 5; q++) wgmma_rs8(sm, pf[q], mkdesc_ns(SB0 + OFF_ONE, 0, 0), q);
#pragma unroll
      for (int q = 0; q < 5; q++) wgmma_rs64(o, pf[q], mkdesc_ns(SB0 + OFF_VT + 128 + q * 256, 128, VS), q);
      wg_commit();
      const int tid = fresh(tid0);
      op = &g_o[i % ORING][cta][(tid & 124) * 32];
      wg_wait<0>();
      TS(i, 21);
      if ((tid & 31) == 0) mbar_arrive_cluster(mapa(sb, 1) + BAR_E + 8);
      const float s0 = rcp(sm[0]), s1 = rcp(sm[2]);
#pragma unroll
      for (int h = 0; h < 2; h++) {
        const float* x = o + 16 * h;
        ov[2 * h] = make_uint4(pin(pack_bf16(x[0] * s0, x[1] * s0)), pin(pack_bf16(x[4] * s0, x[5] * s0)), pin(pack_bf16(x[8] * s0, x[9] * s0)), pin(pack_bf16(x[12] * s0, x[13] * s0)));
        ov[2 * h + 1] = make_uint4(pin(pack_bf16(x[2] * s1, x[3] * s1)), pin(pack_bf16(x[6] * s1, x[7] * s1)), pin(pack_bf16(x[10] * s1, x[11] * s1)), pin(pack_bf16(x[14] * s1, x[15] * s1)));
      }
      TS(i, 22);
      if (i + 1 < NSTEP) CBAR_SYNC(NB_WQ, 256); else CBAR_ARRIVE(NB_WQ, 256);
    }
  }
#pragma unroll
  for (int h = 0; h < 4; h++) stg128(op + (h & 1) * 4096 + (o0 ^ ((h >> 1) * 64)), ov[h]);
  CBAR_SYNC(NB_Q, 128);
  if (tid0 == 224) signal_o(NSTEP - 1, cta);
  if (spin >= SPIN_TOT) g_err = 2;
}

template <int NL> __device__ __forceinline__ void poll(uint4 (&x)[NL], const uint8_t* mb, uint32_t tag, int& spin);
template <> __device__ __forceinline__ void poll<4>(uint4 (&x)[4], const uint8_t* mb, uint32_t tag, int& spin) {
  asm volatile("{.reg .pred p<6>, q; .reg .b128 v; .reg .b32 t;\n"
               " ld.relaxed.gpu.global.b128 v,[%17+0]; mov.b128 {%0,%1,%2,%3},v;\n"
               " ld.relaxed.gpu.global.b128 v,[%17+512]; mov.b128 {%4,%5,%6,%7},v;\n"
               " ld.relaxed.gpu.global.b128 v,[%17+1024]; mov.b128 {%8,%9,%10,%11},v;\n"
               " ld.relaxed.gpu.global.b128 v,[%17+1536]; mov.b128 {%12,%13,%14,%15},v;\n"
               "POLL_LOOP:\n add.s32 %16,%16,16;\n"
               " lop3.b32 t,%0,%18,1,0x28; setp.ne.b32 p0,t,0;\n"
               " lop3.b32 t,%4,%18,1,0x28; setp.ne.b32 p1,t,0;\n"
               " lop3.b32 t,%8,%18,1,0x28; setp.ne.b32 p2,t,0;\n"
               " lop3.b32 t,%12,%18,1,0x28; setp.ne.b32 p3,t,0;\n"
               " or.pred q,p0,p1; or.pred q,q,p2; or.pred q,q,p3; setp.lt.and.s32 q,%16,%19,q; vote.sync.any.pred q,q,0xffffffff;\n"
               " mov.b128 v,{%0,%1,%2,%3}; @p0 ld.relaxed.gpu.global.b128 v,[%17+0]; mov.b128 {%0,%1,%2,%3},v;\n"
               " mov.b128 v,{%4,%5,%6,%7}; @p1 ld.relaxed.gpu.global.b128 v,[%17+512]; mov.b128 {%4,%5,%6,%7},v;\n"
               " mov.b128 v,{%8,%9,%10,%11}; @p2 ld.relaxed.gpu.global.b128 v,[%17+1024]; mov.b128 {%8,%9,%10,%11},v;\n"
               " mov.b128 v,{%12,%13,%14,%15}; @p3 ld.relaxed.gpu.global.b128 v,[%17+1536]; mov.b128 {%12,%13,%14,%15},v;\n"
               " @q bra.uni POLL_LOOP;\n}"
               : "=&r"(x[0].x), "=&r"(x[0].y), "=&r"(x[0].z), "=&r"(x[0].w), "=&r"(x[1].x), "=&r"(x[1].y), "=&r"(x[1].z), "=&r"(x[1].w), "=&r"(x[2].x), "=&r"(x[2].y), "=&r"(x[2].z), "=&r"(x[2].w), "=&r"(x[3].x), "=&r"(x[3].y), "=&r"(x[3].z), "=&r"(x[3].w), "+&r"(spin)
               : "l"(mb), "r"(tag), "n"(SPIN_TOT) : "memory");
}
template <> __device__ __forceinline__ void poll<6>(uint4 (&x)[6], const uint8_t* mb, uint32_t tag, int& spin) {
  asm volatile("{.reg .pred p<6>, q; .reg .b128 v; .reg .b32 t;\n"
               " ld.relaxed.gpu.global.b128 v,[%25+0]; mov.b128 {%0,%1,%2,%3},v;\n"
               " ld.relaxed.gpu.global.b128 v,[%25+512]; mov.b128 {%4,%5,%6,%7},v;\n"
               " ld.relaxed.gpu.global.b128 v,[%25+1024]; mov.b128 {%8,%9,%10,%11},v;\n"
               " ld.relaxed.gpu.global.b128 v,[%25+1536]; mov.b128 {%12,%13,%14,%15},v;\n"
               " ld.relaxed.gpu.global.b128 v,[%25+2048]; mov.b128 {%16,%17,%18,%19},v;\n"
               " ld.relaxed.gpu.global.b128 v,[%25+2560]; mov.b128 {%20,%21,%22,%23},v;\n"
               "POLL_LOOP:\n add.s32 %24,%24,16;\n"
               " lop3.b32 t,%0,%2,%26,0x7e; and.b32 t,t,1; setp.ne.b32 p0,t,0;\n"
               " lop3.b32 t,%4,%6,%26,0x7e; and.b32 t,t,1; setp.ne.b32 p1,t,0;\n"
               " lop3.b32 t,%8,%10,%26,0x7e; and.b32 t,t,1; setp.ne.b32 p2,t,0;\n"
               " lop3.b32 t,%12,%14,%26,0x7e; and.b32 t,t,1; setp.ne.b32 p3,t,0;\n"
               " lop3.b32 t,%16,%18,%26,0x7e; and.b32 t,t,1; setp.ne.b32 p4,t,0;\n"
               " lop3.b32 t,%20,%22,%26,0x7e; and.b32 t,t,1; setp.ne.b32 p5,t,0;\n"
               " or.pred q,p0,p1; or.pred q,q,p2; or.pred q,q,p3; or.pred q,q,p4; or.pred q,q,p5; setp.lt.and.s32 q,%24,%27,q; vote.sync.any.pred q,q,0xffffffff;\n"
               " mov.b128 v,{%0,%1,%2,%3}; @p0 ld.relaxed.gpu.global.b128 v,[%25+0]; mov.b128 {%0,%1,%2,%3},v;\n"
               " mov.b128 v,{%4,%5,%6,%7}; @p1 ld.relaxed.gpu.global.b128 v,[%25+512]; mov.b128 {%4,%5,%6,%7},v;\n"
               " mov.b128 v,{%8,%9,%10,%11}; @p2 ld.relaxed.gpu.global.b128 v,[%25+1024]; mov.b128 {%8,%9,%10,%11},v;\n"
               " mov.b128 v,{%12,%13,%14,%15}; @p3 ld.relaxed.gpu.global.b128 v,[%25+1536]; mov.b128 {%12,%13,%14,%15},v;\n"
               " mov.b128 v,{%16,%17,%18,%19}; @p4 ld.relaxed.gpu.global.b128 v,[%25+2048]; mov.b128 {%16,%17,%18,%19},v;\n"
               " mov.b128 v,{%20,%21,%22,%23}; @p5 ld.relaxed.gpu.global.b128 v,[%25+2560]; mov.b128 {%20,%21,%22,%23},v;\n"
               " @q bra.uni POLL_LOOP;\n}"
               : "=&r"(x[0].x), "=&r"(x[0].y), "=&r"(x[0].z), "=&r"(x[0].w), "=&r"(x[1].x), "=&r"(x[1].y), "=&r"(x[1].z), "=&r"(x[1].w), "=&r"(x[2].x), "=&r"(x[2].y), "=&r"(x[2].z), "=&r"(x[2].w), "=&r"(x[3].x), "=&r"(x[3].y), "=&r"(x[3].z), "=&r"(x[3].w), "=&r"(x[4].x), "=&r"(x[4].y), "=&r"(x[4].z), "=&r"(x[4].w), "=&r"(x[5].x), "=&r"(x[5].y), "=&r"(x[5].z), "=&r"(x[5].w), "+&r"(spin)
               : "l"(mb), "r"(tag), "n"(SPIN_TOT) : "memory");
}
template <int NL>
__device__ __forceinline__ void poll_add(const uint8_t* mb, uint32_t tag, float (&f)[8], uint8_t* flag, bool lead, int& spin) {
  uint4 x[NL];
  poll<NL>(x, mb, tag, spin);
  if (FLP == 0 && lead) st_relaxed(flag, 0);
#pragma unroll
  for (int i = 0; i < NL; i++) {
    const uint32_t u[4] = {x[i].x, x[i].y, x[i].z, x[i].w};
#pragma unroll
    for (int j = 0; j < 4; j++) {
      if (i == 0) { f[2 * j] = bf_lo(u[j]); f[2 * j + 1] = bf_hi(u[j]); }
      else { f[2 * j] += bf_lo(u[j]); f[2 * j + 1] += bf_hi(u[j]); }
    }
  }
}

template <int B, int SLOT>
__device__ __forceinline__ void wo_step(float (&acc)[8], const uint32_t (&wf)[C::NKR][4], int kk) {
  using namespace C;
  const int k = 4 * B + kk;
  const uint64_t db = mkdesc_ns(SB0 + og_off(SLOT) + kk * 512, 256, 128);
  if (k < NKR) wgmma_rt16(acc, wf[k < NKR ? k : 0], db, SLOT | kk);
  else wgmma_tt16(acc, wdesc(OFF_YO + (k - NKR) * 2048), db, 1);
}
template <int B, int SLOT>
__device__ __forceinline__ void wo_block(float (&acc)[8], const uint32_t (&wf)[C::NKR][4]) {
#pragma unroll
  for (int kk = 0; kk < 4; kk++) wo_step<B, SLOT>(acc, wf, kk);
}

__device__ __forceinline__ void chain_a(const CUtensorMap& tmWo, const CUtensorMap& tmWq, const uint32_t sb, const int tid0, const int cta, const int rank) {
  using namespace C;
  asm volatile("setmaxnreg.inc.sync.aligned.u32 200;");
  int spin = 0;
  uint32_t wf[NKR][4];
  load_weights_rs<true>(wf, tmWo, tmWq, cta, rank, sb, tid0, spin);
  const int wu = uni(tid0 >> 5);
  const bool t9 = cta >= 72 && cta < 88;
  const uint64_t exa = reinterpret_cast<uint64_t>(ex_window(g_ex));
  const uint32_t ehi = (uint32_t)(exa >> 32), elo = (uint32_t)exa;

  int b1 = B1, b2 = B2;
#pragma unroll 1
  for (int i = -1; i < NSTEP; i++) {
    const int ph = i & 1;
    if (i >= 0) {
      const int tid = fresh(tid0);
      const uint32_t mo = __shfl_xor_sync(0xffffffffu, elo + (ph << 20) + ((rank * 24 + (tid >> 4)) * 4 + (tid & 3)) * 2048 + (cta / 3) * 64 + (tid & 12) * 4, 0);
      const uint32_t m9 = __shfl_xor_sync(0xffffffffu, elo + (ph << 20) + MAIL9 + (((tid >> 4) * 2 + (tid & 1)) * 4 + (tid & 2)) * 3072 + cta * 32 + (tid & 12) * 2, 0);
      const uint32_t oo = __shfl_xor_sync(0xffffffffu, (tid >> 5) * 512 + (tid & 2) * 64 + (tid & 28) * 4 + (tid & 1) * 8, 0);
      if (i == 0) { mwait(sb + BAR_W + 24, 1, spin); mwait(sb + BAR_W + 32, 1, spin); PTS(7); }
      mwait(sb + BAR_M, ph, spin);
      TS(i, 3);
      {
        float x[20];
        int redo = 0;
      retry:
        bool bad;
        {
          float dq[8] = {}, dk[8] = {};
#pragma unroll 1
          for (int k0 = 0; k0 < 40; k0 += P1U) {
            wg_fence();
#pragma unroll
            for (int k = 0; k < P1U; k++) {
              if (k == P1U - QIE / 2 && k0 == 40 - P1U && !redo) CBAR_ARRIVE(NB_QI, 256);
              const uint64_t db = desc_at(mdesc(k), k0 * 512);
              wgmma_ts16(dq, desc_at(wdesc(OFF_WQ + k * 2048), k0 * 2048), db, 1);
              wgmma_ts16(dk, desc_at(wdesc(OFF_WK + k * 2048), k0 * 2048), db, 1);
            }
            wg_commit();
          }
          const int m = (tid >> 3) & 3, dg = (tid >> 5) * 2 + (m & 1);
          const uint32_t ka = sb + OFF_KT + dg * KS + (m >> 1) * 640 + (tid & 7) * 16;
          if (!redo) CBAR_SYNC(NB_QK, 384);
          sts32(sb + FLG_REDO, redo);
          wg_wait<0>();
          TS(i, 4);
          stsm4(ka, pack_bf16(dk[0], dk[1]), pack_bf16(dk[2], dk[3]), pack_bf16(dk[4], dk[5]), pack_bf16(dk[6], dk[7]));
          stsm4(ka + dg * (VS - KS) + (OFF_VT + 128 - OFF_KT), scale_bf16x2(pack_bf16(dq[0], dq[1]), SCQ), scale_bf16x2(pack_bf16(dq[2], dq[3]), SCQ),
                scale_bf16x2(pack_bf16(dq[4], dq[5]), SCQ), scale_bf16x2(pack_bf16(dq[6], dq[7]), SCQ));
          const float chk = (dq[0] + dq[1]) + (dq[4] + dq[5]);
          fence_async();
          bad = bar_red_or(NB_C, 128, chk != chk && !redo);
        }
        TSB(i, 5);
        wg_fence();
#pragma unroll
        for (int kk = 0; kk < 4; kk++) wgmma_tt40(x, mkdesc_ns(SB0 + OFF_VT + 128 + kk * 2 * VS, VS, 640), mkdesc_ns(SB0 + OFF_KT + kk * 2 * KS, KS, 128), kk);
#pragma unroll
        for (int kk = 0; kk < 4; kk++) {
          if (SIE && kk == 4 - SIE && !bad) CBAR_ARRIVE(NB_SI, 256);
          wgmma_tt40(x, mkdesc_ns(SB0 + OFF_VT + kk * 2 * VS, VS, 384), mkdesc_ns(SB0 + OFF_KT + 640 + kk * 2 * KS, KS, 128), 1);
        }
        wg_commit();
        if (!SIE && !bad) CBAR_ARRIVE(NB_SI, 256);
        if (__builtin_expect(__any_sync(0xffffffffu, bad), 0)) {
          wg_wait<0>();
#pragma unroll 1
          for (int k = 0; k < 10; k++) {
            uint4 v = lds128(sb + OFF_M + tid * 16 + k * 2048);
            if (v.x == SENT || v.y == SENT || v.z == SENT || v.w == SENT) {
              do { v = ld_relaxed4(mkptr(elo + EX_M + i * 20480 + tid * 16 + k * 2048, ehi)); spin += 16; } while ((v.x == SENT || v.y == SENT || v.z == SENT || v.w == SENT) && spin < SPIN_TOT);
              sts128(sb + OFF_M + tid * 16 + k * 2048, v);
            }
          }
          fence_async();
          bar_sync(NB_C, 128);
          redo = fresh(1);
          goto retry;
        }
        TSV(i, 36, redo);
        const uint32_t rb1 = mapa(sb, (rank + 1) % 3), rb2 = mapa(sb, (rank + 2) % 3);
        wg_wait<0>();
        TS(i, 6);
        if (wu < 2) {
          float y[10];
#pragma unroll
          for (int j = 0; j < 5; j++) { y[2 * j] = x[4 * j]; y[2 * j + 1] = x[4 * j + 1]; }
          const uint4 h0 = make_uint4(pack_h2(y[0], y[1]), pack_h2(y[2], y[3]), pack_h2(y[4], y[5]), pack_h2(y[6], y[7]));
          const uint32_t h1 = pack_h2(y[8], y[9]);
          st_async4u(rb1 + OFF_XM + 1024 + tid * 16, h0, rb1 + BAR_XM);
          st_async4u(rb2 + OFF_XM + tid * 16, h0, rb2 + BAR_XM);
          st_async1u(rb1 + OFF_XM + 2304 + tid * 4, h1, rb1 + BAR_XM);
          st_async1u(rb2 + OFF_XM + 2048 + tid * 4, h1, rb2 + BAR_XM);
          CBAR_ARRIVE(NB_SM, 256);
          if ((tid & 31) == 0) mbar_arrive_cluster(mapa(sb, 0) + BAR_E);
          TS(i, 7);
          const uint32_t sw = (tid & 7) * 4 + (tid & 8) * 8 + (tid & 16) * 2;
          mwait(sb + BAR_XM, ph, spin);
          TS(i, 8);
          const uint4 u0 = lds128(sb + OFF_XM + tid * 16), v0 = lds128(sb + OFF_XM + 1024 + tid * 16);
          const uint32_t u1 = lds32(sb + OFF_XM + 2048 + tid * 4), v1 = lds32(sb + OFF_XM + 2304 + tid * 4);
          add_h2(y[0], y[1], u0.x, v0.x); add_h2(y[2], y[3], u0.y, v0.y); add_h2(y[4], y[5], u0.z, v0.z); add_h2(y[6], y[7], u0.w, v0.w);
          add_h2(y[8], y[9], u1, v1);
          const float mx = quad_max(max10(y)) * -SCE;
#pragma unroll
          for (int j = 0; j < 5; j++) {
            y[2 * j] = ex2(fmaf(y[2 * j], SCE, mx)); y[2 * j + 1] = ex2(fmaf(y[2 * j + 1], SCE, mx));
            sts32(sb + OFF_PT + wu * 640 + sw + j * 128, pack_bf16(y[2 * j], y[2 * j + 1]));
          }
          sts32(sb + OFF_XM + 2048 + wu * 128 + sw, __float_as_uint(sum10(y)));
          fence_async();
          TS(i, 9);
        } else {
          CBAR_ARRIVE(NB_SM, 256);
          if ((tid & 31) == 0) mbar_arrive_cluster(mapa(sb, 0) + BAR_E);
          mwait(sb + BAR_MF, ph, spin);
        }
      }
      CBAR_SYNC(NB_VA, 256);
      TSB(i, 10);
      {
        float o[2][4];
        wg_fence();
#pragma unroll
        for (int c = 0; c < 2; c++)
#pragma unroll
          for (int q = 0; q < 3; q++)
            wgmma_ss8(o[c], mkdesc_ns(SB0 + OFF_VT + 128 + c * 640 + q * 256, 128, VS), mkdesc_ns(SB0 + OFF_PT + c * 640 + q * 256, q == 2 && c == 0 ? 768 : 128, 128), q);
        wg_commit();
        const float4 e = lds128f(sb + OFF_XM + 2048 + (tid & 15) * 16);
        const uint32_t rb1 = mapa(sb, (rank + 1) % 3), rb2 = mapa(sb, (rank + 2) % 3);
        const float inv = rcp((e.x + e.y) + (e.z + e.w));
        const int sl = (tid & 3) * 2;
        const float i0 = __shfl_sync(0xffffffffu, inv, sl), i1 = __shfl_sync(0xffffffffu, inv, sl + 1);
        const float i2 = __shfl_sync(0xffffffffu, inv, sl + 8), i3 = __shfl_sync(0xffffffffu, inv, sl + 9);
        wg_wait<0>();
        TS(i, 11);
        const uint32_t p0 = pack_bf16(o[0][0] * i0, o[0][1] * i1), p1 = pack_bf16(o[1][0] * i2, o[1][1] * i3);
        const uint32_t p2 = pack_bf16(o[0][2] * i0, o[0][3] * i1), p3 = pack_bf16(o[1][2] * i2, o[1][3] * i3);
        if (OGF) { sts64(sb + oo + og_off(0), p0, p1); sts64(sb + oo + og_off(0) + 256, p2, p3); fence_async(); }
        st_async2u(rb1 + oo + og_off(2), p0, p1, rb1 + BAR_OG);
        st_async2u(rb2 + oo + og_off(1), p0, p1, rb2 + BAR_OG);
        st_async2u(rb1 + oo + og_off(2) + 256, p2, p3, rb1 + BAR_OG);
        st_async2u(rb2 + oo + og_off(1) + 256, p2, p3, rb2 + BAR_OG);
        if (!OGF) { sts64(sb + oo + og_off(0), p0, p1); sts64(sb + oo + og_off(0) + 256, p2, p3); fence_async(); }
      }
      CBAR_SYNC(NB_A, 128);
      TSB(i, 12);
      {
        float acc[3][8];
        wg_fence();
        wo_block<0, 0>(acc[2], wf);
        wg_commit();
        if (tid == 0) mbar_arrive_cluster(mapa(sb, 1) + BAR_E + 8);
        wo_block<1, 0>(acc[0], wf);
        wo_block<4, 0>(acc[1], wf);
        wg_commit();
        const uint32_t tag = (i >> 1) & 1;
#define TAGGED(LO, HI) ((pack_bf16(LO, HI) & ~1u) | tag)
#define SEND(OFF, U) st_relaxed128(mkptr(mo, ehi) + (OFF), TAGGED(acc[U][0], acc[U][2]), pack_bf16(acc[U][1], acc[U][3]), pack_bf16(acc[U][4], acc[U][6]), pack_bf16(acc[U][5], acc[U][7]))
        wg_wait<1>();
        const uint32_t n0 = pin(TAGGED(acc[2][0], acc[2][2])), n1 = pin(pack_bf16(acc[2][1], acc[2][3]));
        const uint32_t n2 = pin(TAGGED(acc[2][4], acc[2][6])), n3 = pin(pack_bf16(acc[2][5], acc[2][7]));
        wg_fence();
        wo_block<7, 0>(acc[2], wf);
        wg_commit();
        st_relaxed64(mkptr(m9, ehi), n0, n1);
        st_relaxed64(mkptr(m9, ehi) + 3072, n2, n3);
        mwait(sb + BAR_OG, ph, spin);
        asm volatile("fence.proxy.async::generic.acquire.sync_restrict::shared::cluster.cluster;" ::: "memory");
        TS(i, 13);
        wg_fence();
        wo_block<2, 1>(acc[0], wf); wo_block<3, 2>(acc[0], wf);
        wg_commit();
        wo_block<5, 1>(acc[1], wf); wo_block<6, 2>(acc[1], wf);
        wg_commit();
        wg_wait<1>(); SEND(0, 0);
        wo_block<8, 1>(acc[2], wf); wo_block<9, 2>(acc[2], wf);
        wg_commit();
        if (WOE == 0) { CBAR_ARRIVE(NB_WV, 256); CBAR_ARRIVE(NB_WQ, 256); }
        wg_wait<1>(); SEND(32 * 2048, 1);
        if (WOE == 1) CBAR_ARRIVE(NB_WV, 256);
        wg_wait<0>(); SEND(64 * 2048, 2);
        if (WOE == 2) CBAR_ARRIVE(NB_WV, 256);
        if (WOE >= 1) CBAR_ARRIVE(NB_WQ, 256);
#undef SEND
#undef TAGGED
      }
      TS(i, 14);
      if (i < 2) PTS(19 + i);
      if (i + 1 >= NSTEP) break;
    }
    uint32_t t1 = clk32();
    if (i >= 0) {
      const int lane = fresh(tid0) & 31, j = lane >> 3;
      const uint8_t* mb = mkptr(elo + (ph << 20) + (t9 ? MAIL9 + (cta - 72) * 12288 + wu * 3072 : (cta < 72 ? cta : cta - 24) * 8192 + wu * 2048) + lane * 16, ehi);
      const uint32_t tag = (i >> 1) & 1;
      const bool pub = (lane & (t9 ? 6 : 4)) == 0 && !(((t9 ? cta : wu) & 1) && i + 1 == LAG) && cta < 88;
      const uint32_t dst = pin(elo + EX_M + (i + 1) * 20480 + (t9 ? (cta + 72) * 128 + wu * 32 + (j & 1) * 16 + (lane & 1) * 8 + (j >> 1) * 4
                                                                   : cta * 256 + (wu & 1) * 128 + (wu >> 1) * 64 + j * 16 + (lane & 3) * 4));
      uint8_t* flag = mkptr(elo + EX_FLAG + (i + 1) * 3072 + cta * 32 + wu * 4, ehi);
      while (clk32() - t1 < b1) {}
      TS(i + 1, 30);
      float f[8];
      const int n0 = spin;
      if (!t9) poll_add<4>(mb, tag, f, flag, lane == 0, spin);
      else poll_add<6>(mb, tag, f, flag, lane == 0, spin);
      if (FLP == 1 && lane == 0) st_relaxed(flag, __float_as_uint(f[0] + f[7]) >> 1);
      t1 = clk32();
      b1 = __any_sync(0xffffffffu, spin - n0 > 16) ? min(b1 + AD1, BMX) : max(b1 - AD0, 0);
      TSV(i + 1, 38, b1);
      TS(i + 1, 31); TSV(i + 1, 32, (spin - n0) >> 4);
      const bool h = lane & 16, q = lane & 8;
#pragma unroll
      for (int j = 0; j < 4; j++) f[j] = (h ? f[4 + j] : f[j]) + __shfl_xor_sync(0xffffffffu, h ? f[j] : f[4 + j], 16);
#pragma unroll
      for (int j = 0; j < 2; j++) f[j] = (q ? f[2 + j] : f[j]) + __shfl_xor_sync(0xffffffffu, q ? f[j] : f[2 + j], 8);
      f[0] += __shfl_xor_sync(0xffffffffu, f[0], 4); f[1] += __shfl_xor_sync(0xffffffffu, f[1], 4);
      if (t9) { f[0] += __shfl_xor_sync(0xffffffffu, f[0], 2); f[1] += __shfl_xor_sync(0xffffffffu, f[1], 2); }
      if (pub) st_relaxed(mkptr(dst, ehi), pack_bf16(f[0], f[1]));
      if (FLP == 2 && lane == 0) st_relaxed(flag, 0);
      if (wu == 3) {
        CBAR_SYNC(NB_MR, 160);
        if (elect_one()) signal_o(i, cta);
      }
      TS(i + 1, 15);
    }
    if (wu == 0) {
      const int tid = fresh(tid0);
      const uint8_t* pp = mkptr(elo + EX_FLAG + (i + 1) * 3072 + (rank * 28 + (tid < 28 || rank == 2 ? tid : 0)) * 32, ehi);
      while (clk32() - t1 < b2) {}
      TS(i + 1, 16);
      int n = 1;
      uint4 x = ld_relaxed4(pp);
      if (tid0 == 0) mbar_expect_tx(sb + BAR_M, 20480);
      bool mok = mbar_test(sb + BAR_MOK, ph ^ 1);
      while (__any_sync(0xffffffffu, (int)(x.x | x.y | x.z | x.w) < 0 && spin < SPIN_TOT)) { x = ld_relaxed4(pp); mok = mbar_test(sb + BAR_MOK, ph ^ 1); n++; spin += 16; }
      if (!mok) mwait(sb + BAR_MOK, ph ^ 1, spin);
      b2 = n > 1 ? min(b2 + AD3, BMX) : max(b2 - AD2, 0);
      TSV(i + 1, 35, n); TSV(i + 1, 39, b2);
      TS(i + 1, 34);
      if (elect_one()) bulk_g2s_mc(sb + OFF_M + rank * 7168, mkptr(elo + EX_M + (i + 1) * 20480 + rank * 7168, ehi), rank == 2 ? 6144 : 7168, sb + BAR_M);
      TS(i + 1, 33);
      __syncwarp();
    }
  }
  if (spin >= SPIN_TOT) g_err = 1;
}

__global__ void __cluster_dims__(3, 1, 1) __launch_bounds__(384, 1)
k_chain(const __grid_constant__ CUtensorMap tmWq, const __grid_constant__ CUtensorMap tmWk,
        const __grid_constant__ CUtensorMap tmWv, const __grid_constant__ CUtensorMap tmWo, const bf16* __restrict__ x0, const bf16* __restrict__ mem0) {
  using namespace C;
  extern __shared__ __align__(1024) uint8_t smem[];
  const uint32_t sb = smem_u32(smem);
  const int tid = threadIdx.x;
  const int wg = __shfl_sync(0xffffffffu, tid >> 7, 0);
  const int cta = uni(blockIdx.x), rank = uni(blockIdx.x % 3);

  asm volatile("griddepcontrol.launch_dependents;");
  if (cta < 4) prefetch_l2(tid < 320 ? x0 + (cta * 320 + tid) * 64 : mem0 + (cta * 20 + tid % 20) * 64);
  if (tid == 32) {
    for (int p = 0; p < 5; p++) mbar_init(sb + BAR_W + 8 * p, 2);
    fence_async();
    for (int p = 0; p < NBX; p++) { stage_box<false>(tmWv, sb, p, cta, rank); stage_box<true>(tmWo, sb, p, cta, rank); }
  }
  if (tid == 0) {
    if ((sb & 0xFFFFFF) != SB0) g_err = 100;
    for (int p = 0; p < 5; p++) { mbar_init(sb + BAR_F + 8 * p, 1); mbar_init(sb + BAR_E + 8 * p, p == 2 ? 12 : p == 1 ? 15 : 24); }
    mbar_init(sb + BAR_M, 1); mbar_init(sb + BAR_MOK, 24); mbar_init(sb + BAR_XM, 1); mbar_init(sb + BAR_XF, 2);
    mbar_init(sb + BAR_XT, 1); mbar_init(sb + BAR_MF, 8); mbar_init(sb + BAR_OG, 1);
    for (int p = 0; p < 5; p++) mbar_expect_tx(sb + BAR_F + 8 * p, 16384);
    for (int p = 0; p < 16; p++) sts32(sb + OFF_SAFE + 4 * p, 0);
    for (int p = 0; p < 32; p++) sts32(sb + OFF_ONE + 4 * p, 0x3F803F80);
    asm volatile("fence.mbarrier_init.release.cluster;" ::: "memory");
    fence_async();
  }
  __syncthreads();
  asm volatile("barrier.cluster.arrive.relaxed.aligned;" ::: "memory");
  asm volatile("barrier.cluster.wait.aligned;" ::: "memory");

  if (wg == 0) chain_a(tmWo, tmWq, sb, keep(tid), cta, rank);
  else if (wg == 1) chain_q(x0, mem0, sb, keep(tid), cta, rank);
  else chain_v(tmWv, tmWk, sb, keep(tid), cta, rank);
  asm volatile("barrier.cluster.arrive.release.aligned;" ::: "memory");
  asm volatile("barrier.cluster.wait.acquire.aligned;" ::: "memory");
}

namespace W {
constexpr int NP = 25, NBC = 11, NW = NP + NBC;
constexpr int PRS = 37, PW = 43 * 2048;
constexpr int OFF_W = 0;
constexpr int OFF_R = 2 * PW;
constexpr int BRS = 36, VSS = 37;
constexpr int OFF_WO = 0, OFF_Y = 81920;
constexpr int OFF_X = OFF_Y + 2 * (40 - BRS) * 2048;
constexpr int OFF_WV = OFF_X + 40960;
constexpr int OFF_S = OFF_WV + VSS * 2048;
constexpr int COL = 976;
constexpr int OFF_T = OFF_X + 16384;
constexpr int OFF_H = OFF_S + 7696;
constexpr int OFF_BAR = OFF_H + 8 * COL;
constexpr int OFF_SAFE = OFF_BAR + 256;
constexpr int SMEM = 232448;
static_assert(OFF_SAFE + 64 <= SMEM && OFF_R + 40960 <= OFF_BAR, "");
constexpr uint32_t SB0 = 1024;
constexpr int BAR_F = OFF_BAR, BAR_E = OFF_BAR + 40, BAR_G = OFF_BAR + 80, BAR_W = OFF_BAR + 160, BAR_R = OFF_BAR + 176;
constexpr int NB_G0 = 1, NB_SG = 4, NB_B = 5, NB_AS = 6, NB_SG1 = 7, NB_RED = 8, NB_R = 9;
}
#define FSA 1
#define WBAR_SYNC(id, n) bar_sync(id, n)
#define WBAR_ARRIVE(id, n) bar_arrive(id, n)

__device__ __forceinline__ uint64_t rdesc(int off, int kk) { return mkdesc(W::SB0 + off + kk * 32, 16, 1024); }
__device__ __forceinline__ uint64_t gdesc(int off, int kk) { return mkdesc_ns(W::SB0 + off + kk * 1024, 512, 512) | ((uint64_t)2 << 62); }
__device__ __forceinline__ uint32_t frag_addr(uint32_t base, int tid) {
  const int i = (tid >> 3) & 3, r = tid & 7;
  return base + (r + (i >> 1) * 8) * 128 + (((2 * ((tid >> 5) & 3) + (i & 1)) ^ r) << 4);
}
template <int NK>
__device__ __forceinline__ void load_frags(uint32_t (&wf)[NK][4], uint32_t base, int tid) {
  const uint32_t a0 = frag_addr(base, tid);
#pragma unroll
  for (int k = 0; k < NK; k++) ldsm4t(wf[k], a0 + k * 2048);
}
template <bool SORTED>
__device__ __forceinline__ void red_tile(const float* d, int seg, int col0, int tid) {
  float* p = g_x + (size_t)(seg * 32 + (SORTED ? 4 : 2) * (tid & 3)) * DM + col0 + ((tid >> 5) & 3) * 16 + ((tid >> 2) & 7) * 2;
#pragma unroll
  for (int j = 0; j < 8; j++)
    asm volatile("red.relaxed.gpu.global.add.v2.f32 [%0],{%1,%2};" ::"l"(p + (SORTED ? (j & 2) * 8 + (j & 1) * 2 + (j >> 2) : (j >> 1) * 8 + (j & 1)) * DM),
                 "f"(d[4 * (j >> 1) + (j & 1)]), "f"(d[4 * (j >> 1) + 2 + (j & 1)]) : "memory");
}

__device__ __forceinline__ void work_p(const CUtensorMap& tmWo, uint32_t sb, int pc, const int WG, int tid0) {
  using namespace W;
  asm volatile("setmaxnreg.inc.sync.aligned.u32 208;");
  int spin = 0;
  const int ks = pc / 5, col0 = (pc % 5) * 128 + WG * 64;
  const uint32_t wb = sb + OFF_W + WG * PW;
  uint32_t wf[PRS][4];
#pragma unroll 1
  for (int hf = 0; hf < 2; hf++) {
    const int nk = hf ? 80 - PRS : PRS;
    if ((tid0 & 127) == 0) {
      mbar_expect_tx(sb + BAR_W + 8 * WG, nk * 2048);
      for (int i = 0; i < nk; i++) tma2d(wb + i * 2048, &tmWo, col0, ks * 19 * 64 + (i < PRS ? 2 * i + hf : PRS + i) * 16, sb + BAR_W + 8 * WG);
    }
    __syncwarp();
    mwait(sb + BAR_W + 8 * WG, hf, spin);
    permute_cols(wb, tid0 & 127, nk * 64);
    if (hf == 1 && ks < 4) for (int it = 39 * 64 + (tid0 & 127) - 64; it < 43 * 64; it += 128) {
      const uint32_t a = wb + (it >> 2) * 128 + (((2 * (it & 3)) ^ ((it >> 2) & 6)) << 4);
      if (it >= 39 * 64) { sts128(a, make_uint4(0, 0, 0, 0)); sts128(a + 16, make_uint4(0, 0, 0, 0)); }
    }
    fence_async();
    WBAR_SYNC(NB_G0 + WG, 128);
    if (hf == 0) {
      load_frags<PRS>(wf, wb, tid0);
      fence_async();
      WBAR_SYNC(NB_G0 + WG, 128);
    }
  }
#pragma unroll 1
  for (int k = 0; k < NSTEP; k++) {
    float d[32];
#pragma unroll
    for (int f = 0; f < 20; f++) {
      mwait(sb + BAR_F + 8 * (f % 5), (f / 5) & 1, spin);
      if (f == 0 && WG == 0 && pc == WW) WTS(k, 1);
      wg_fence();
#pragma unroll
      for (int kk = 0; kk < 4; kk++) {
        const int q = 4 * f + kk;
        if (q < 2 * PRS && !(q & 1)) wgmma_rs64(d, wf[q < 2 * PRS ? q >> 1 : 0], rdesc(OFF_R + (f % 5) * 8192, kk), q);
        else wgmma_ts64(d, desc_at(mkdesc(SB0 + OFF_W + (q < 2 * PRS ? q >> 1 : q - PRS) * 2048, 8192, 1024), WG * PW), rdesc(OFF_R + (f % 5) * 8192, kk), 1);
        if (kk == 0 && f > 0) {
          wg_commit();
          wg_wait<1>();
          if ((tid0 & 31) == 0) mbar_arrive(sb + BAR_E + 8 * ((f - 1) % 5));
        }
      }
      wg_commit();
    }
    wg_wait<0>();
    if ((tid0 & 31) == 0) mbar_arrive(sb + BAR_E + 32);
    if (WG == 0 && pc == WW) WTS(k, 2);
    if (k < NSEG) red_tile<false>(d, k, col0, tid0);
    if (k >= LAG) red_tile<false>(d + 16, k - LAG, col0, tid0);
    if (WG == 0 && pc == WW) WTS(k, 13);
    WBAR_SYNC(NB_SG, 256);
    if (WG == 0) { if (tid0 == 0) { if (UNS & 8) csignal_fast(CN_P + k); else csignal_t(CN_P + k, 3); } __syncwarp(); }
  }
  if (spin >= SPIN_TOT) g_err = 11;
}
__device__ __forceinline__ void work_p_producer(uint32_t sb, int pc, int odd) {
  using namespace W;
  int spin = 0;
  const int ks = pc / 5;
#pragma unroll 1
  for (int k = 0; k < NSTEP; k++) {
    const uint32_t lo = k < NSEG ? 0 : 4096, len = k < LAG || k >= NSEG ? 4096 : 8192;
    const uint8_t* src = &g_o[k % ORING][ks * 19 + odd][lo];
    cwait(CN_O + k * 5 + ks, ks == 4 ? 20 : 19, spin);
    fence_async_all();
    if (pc == WW && !odd) WTS1(k, 0);
#pragma unroll
    for (int u = 0; u < 10; u++) {
      const int st = odd ? (2 * u + 1) % 5 : (2 * u) % 5, ph = odd ? ((2 * u + 1) / 5) & 1 : ((2 * u) / 5) & 1;
      mwait(sb + BAR_E + 8 * st, ph ^ 1, spin);
      if (elect_one()) {
        if (u == 9 && odd && ks < 4) mbar_arrive(sb + BAR_F + 8 * st);
        else {
          mbar_expect_tx(sb + BAR_F + 8 * st, len);
          bulk_g2s(sb + OFF_R + st * 8192 + lo, src + u * 16384, len, sb + BAR_F + 8 * st);
        }
      }
    }
  }
  if (spin >= SPIN_TOT) g_err = 12;
}
__device__ __forceinline__ void work_ln(int kind, int r, int lane, bf16* out) {
  int spin = 0;
  const int l = kind & 1;
  const int rp = kind < 2 ? (r & 1) * 16 + (r >> 1) : r;
  const uint32_t sw = ((((lane >> 1) & 7) ^ (rp & 7)) << 4) + (lane & 1) * 8;
  uint8_t* dst = kind < 2 ? g_xnb[l * LAG] + (lane >> 4) * 8192 + l * 4096 + rp * 128 + sw
               : kind == 2 ? g_xn[LAG] + (r >> 3) * 4096 + 2048 + (lane >> 4) * 1024 + (r & 7) * 128 + sw
                           : reinterpret_cast<uint8_t*>(out) + r * 1280 + lane * 8;
  const int dm = kind < 3 ? 16384 : 256, ds = kind < 3 ? 81920 : 40960;
#pragma unroll 1
  for (int s = 0; s < NSEG; s++) {
    const float* xr = g_x + (size_t)(s * 32 + r) * DM;
    if (kind < 2) {
      uint8_t* ob = g_ob[s + l * LAG] + (l * 32 + r) * 1280 + lane * 16;
      stg128(ob, make_uint4(SENT, SENT, SENT, SENT)); stg128(ob + 512, make_uint4(SENT, SENT, SENT, SENT));
      if (lane < 16) stg128(ob + 1024, make_uint4(SENT, SENT, SENT, SENT));
    }
    if (lane == 0) cwait(kind < 2 ? CN_P + s + l * LAG : CN_W + l * 64 + s, kind < 2 ? W::NP : 10, spin);
    __syncwarp();
    if (r == 0 && lane == 0 && (l == 0 || s + LAG >= NSEG)) WTS1(s + l * LAG, kind < 2 ? 3 : 11);
    float4 v[5];
#pragma unroll
    for (int m = 0; m < 5; m++) v[m] = ld_relaxed4f(xr + m * 128 + lane * 4);
    if (kind < 3) ln_row(v);
#pragma unroll
    for (int m = 0; m < 5; m++) *reinterpret_cast<uint2*>(dst + (size_t)s * ds + m * dm) = make_uint2(pack_bf16(v[m].x, v[m].y), pack_bf16(v[m].z, v[m].w));
    __syncwarp();
    if (r == 0 && lane == 0 && (l == 0 || s + LAG >= NSEG)) WTS1(s + l * LAG, kind < 2 ? 4 : 12);
    if (lane == 0 && kind < (NOWORK ? 2 : 3)) { if ((UNS >> (kind < 2 ? 1 : 2)) & 1) csignal_fast(kind < 2 ? CN_L + s + l * LAG : CN_X + s + LAG); else csignal_t(kind < 2 ? CN_L + s + l * LAG : CN_X + s + LAG, kind); }
  }
  if (spin >= SPIN_TOT) g_err = 13;
}

__device__ __forceinline__ void work_prep(const bf16* x0, const bf16* mem0, int r, int lane) {
  int spin = 0;
#pragma unroll 1
  for (int k = NPRE; k < NSTEP; k++) {
    uint2 u[5], v[5];
    ln0_load(x0, u, min(k * 32 + r, SEQ - 1), lane);
    ln0_load(x0, v, min(k * 32 + r + 16, SEQ - 1), lane);
    if (lane == 0) cwait(CN_O + (k - NPRE) * 5, 1, spin);
    __syncwarp();
#pragma unroll 1
    for (int h = 0; h < 2; h++) {
      prep_row(u, mem0, k, r + 16 * h, lane);
#pragma unroll
      for (int m = 0; m < 5; m++) u[m] = v[m];
    }
    __syncwarp();
    if (lane == 0) csignal(CN_X + k);
  }
  if (spin >= SPIN_TOT) g_err = 19;
}

__device__ __forceinline__ void stage_qkv(const bf16* wqkv, uint32_t base, int T, int bc, int tid) {
  const int q = tid & 15;
  const bool ok = q < 15 && bc * 60 + 4 * q < DM;
  const bf16* src = wqkv + T * DM + bc * 60 + 4 * q;
#pragma unroll 1
  for (int k0 = tid >> 4; k0 < 640; k0 += 80) {
    uint2 v[10];
#pragma unroll
    for (int u = 0; u < 10; u++) v[u] = ok ? *reinterpret_cast<const uint2*>(src + (size_t)(k0 + 8 * u) * 1920) : make_uint2(0, 0);
#pragma unroll
    for (int u = 0; u < 10; u++) sts64(base + (k0 + 8 * u) * 128 + (((q >> 1) ^ (k0 & 7)) << 4) + (q & 1) * 8, v[u].x, v[u].y);
  }
}
struct AttAddr { uint32_t qa, qb, ka, oa, ob, ml; };
__device__ __forceinline__ AttAddr att_addr(uint32_t sb, int bc, int hh, int tid) {
  using namespace W;
  const int r = tid & 7, m = (tid >> 3) & 3, g = (tid >> 2) & 7, t = tid & 3, lp = (tid >> 5) & 3;
  const int f2 = r < 4 ? 20 * hh + 16 + r : 60;
  const uint32_t tb = sb + OFF_T + 2 * lp * COL;
  const int fa = 20 * hh + (m >> 1) * 8 + r, pc = 2 * (lp & 1) + (m & 1);
  const uint32_t o0 = sb + OFF_S + (lp >> 1) * 3840;
  AttAddr x;
  x.qa = keep(tb + (m & 1) * COL + (20 * hh + (m >> 1) * 8 + r) * 16);
  x.qb = keep(tb + (m & 1) * COL + f2 * 16);
  x.ka = keep(tb + (m < 2 ? 20 * hh + 8 * m + r : f2) * 16);
  x.oa = keep(o0 + fa * 64 + ((pc ^ ((bc * 60 + fa) >> 1)) & 3) * 16);
  x.ob = keep(r < 4 ? o0 + f2 * 64 + ((pc ^ ((bc * 60 + f2) >> 1)) & 3) * 16 : sb + OFF_S + 7680);
  x.ml = keep((2 * t > g ? 0xFFFFu : 0u) | (2 * t + 1 > g ? 0xFFFF0000u : 0u));
  return x;
}
__device__ __forceinline__ void release_tiles(uint32_t sb, int tid) {
  fence_async();
  __syncwarp();
  if ((tid & 31) < 3) mbar_arrive(sb + W::BAR_E + 16 + 8 * (tid & 3));
}
__device__ __forceinline__ void attend(uint32_t sb, const AttAddr& x, int k0, int lp, int tid) {
  using namespace W;
  const uint32_t hd = OFF_H - OFF_T - lp * COL;
  const float scl = 0.22360679774997896f * 1.4426950408889634f;
  float sc[3][4];
  uint32_t v[3][4];
  {
    uint32_t q[4], q8a, q8b, k[3][4];
    ldsm4t(q, x.qa);
    ldsm4t(k[0], x.ka + hd); ldsm4t(k[1], x.ka + 8 * COL); ldsm4t(k[2], x.ka + 9 * COL);
    ldsm2t(q8a, q8b, x.qb);
#pragma unroll
    for (int c = 0; c < 3; c++) { sc[c][0] = sc[c][1] = sc[c][2] = sc[c][3] = 0.f; mma16816(sc[c], q[0], q[1], q[2], q[3], k[c][0], k[c][1]); }
#pragma unroll
    for (int c = 0; c < 3; c++) mma1688(sc[c], q8a, q8b, k[c][2]);
    stsm4t(x.ka + hd, k[2][0], k[2][1], k[2][2], k[2][3]);
  }
  ldsm4(v[0], x.ka + hd + 4 * COL); ldsm4(v[1], x.ka + 16 * COL); ldsm4(v[2], x.ka + 17 * COL);
  stsm4(x.ka + hd + 4 * COL, v[2][0], v[2][1], v[2][2], v[2][3]);
  release_tiles(sb, tid);
  const bool lo0 = x.ml & 1, lo1 = (int)x.ml < 0, first = k0 == (lp >> 1) * LAG;
  uint32_t pw[2];
  float inv[2];
#pragma unroll
  for (int h = 0; h < 2; h++) {
    float y0 = lo0 ? sc[h][2 * h] : sc[h + 1][2 * h], y1 = lo1 ? sc[h][2 * h + 1] : sc[h + 1][2 * h + 1];
    if (h == 0 && first) { y0 = lo0 ? -INFINITY : y0; y1 = lo1 ? -INFINITY : y1; }
    const float mx = quad_max(fmaxf(y0, y1)) * -scl;
    y0 = ex2(fmaf(y0, scl, mx)); y1 = ex2(fmaf(y1, scl, mx));
    pw[h] = pack_bf16(y0, y1);
    inv[h] = y0 + y1;
  }
  float o[3][4];
  const uint32_t a0 = pw[0] & x.ml, a2 = pw[0] & ~x.ml, a3 = pw[1] & x.ml, a5 = pw[1] & ~x.ml, z0 = tid >> 10, z1 = tid >> 11;
#pragma unroll
  for (int j = 0; j < 3; j++) { o[j][0] = o[j][1] = o[j][2] = o[j][3] = 0.f; mma16816(o[j], a0, z0, a2, a3, v[0][j], v[1][j]); }
#pragma unroll
  for (int j = 0; j < 3; j++) mma1688(o[j], z1, a5, v[2][j]);
  inv[0] = rcp(quad_sum(inv[0])); inv[1] = rcp(quad_sum(inv[1]));
  stsm4t(x.oa, pack_bf16(o[0][0] * inv[0], o[0][1] * inv[0]), pack_bf16(o[0][2] * inv[1], o[0][3] * inv[1]),
         pack_bf16(o[1][0] * inv[0], o[1][1] * inv[0]), pack_bf16(o[1][2] * inv[1], o[1][3] * inv[1]));
  stsm2t(x.ob, pack_bf16(o[2][0] * inv[0], o[2][1] * inv[0]), pack_bf16(o[2][2] * inv[1], o[2][3] * inv[1]));
  fence_async();
}
template <bool IS_V>
__device__ __forceinline__ void work_b(const CUtensorMap& tmBo, const bf16* wqkv, uint32_t sb, int bc, const int wg, int tid0) {
  using namespace W;
  if (!IS_V) asm volatile("setmaxnreg.inc.sync.aligned.u32 208;");
  else asm volatile("setmaxnreg.dec.sync.aligned.u32 72;");
  constexpr int NR = IS_V ? 40 - VSS : BRS;
  const int WG = IS_V ? 2 : wg;
  const uint32_t yo = WG * (40 - BRS) * 2048;
  int spin = 0;
  uint32_t wf[NR][4];
  if (!IS_V) {
    const uint32_t wb = sb + (WG ? OFF_WO : OFF_WV);
    stage_qkv(wqkv, wb, WG, bc, tid0 & 127);
    WBAR_SYNC(NB_G0 + WG, 128);
    load_frags<NR>(wf, wb, tid0);
#pragma unroll
    for (int k = NR; k < 40; k++) sts128(sb + OFF_Y + yo + (k - NR) * 2048 + (tid0 & 127) * 16, lds128(wb + k * 2048 + (tid0 & 127) * 16));
    fence_async();
  }
  WBAR_SYNC(NB_B, 384);
  if (WG == 1 && bc < 10) {
    if ((tid0 & 127) == 0) {
      mbar_expect_tx(sb + BAR_W, 81920);
      for (int i = 0; i < 10; i++) tma2d(sb + OFF_WO + i * 8192, &tmBo, bc * 64, i * 64, sb + BAR_W);
    }
    __syncwarp();
    mwait(sb + BAR_W, 0, spin);
    permute_cols(sb + OFF_WO, tid0 & 127, 2560);
  }
  if (IS_V) {
    stage_qkv(wqkv, sb + OFF_WV, 2, bc, tid0 & 127);
    WBAR_SYNC(NB_G0 + 2, 128);
    load_frags<NR>(wf, sb + OFF_WV + VSS * 2048, tid0);
  }
  fence_async();
  WBAR_SYNC(NB_B, 384);
  const int wu = uni((tid0 >> 5) & 3);
  uint32_t nredo = 0;
  const AttAddr aa = att_addr(sb, bc, WG, tid0);
#pragma unroll 1
  for (int k = 0; k < NSTEP + (WG == 0); k++) {
    if (WG || k < NSTEP) {
    {
      float d[32];
#pragma unroll
      for (int c = 0; c < 10; c++) {
        mwait(sb + BAR_F + 8 * (c % 5), c / 5, spin);
        if (c == 0 && bc == 0 && WG != 1) WTS(k, WG ? 15 : 6);
        wg_fence();
#pragma unroll
        for (int kk = 0; kk < 4; kk++) {
          const int q = 4 * c + kk;
          const uint64_t db = rdesc(OFF_X + (c % 5) * 8192, kk);
          if (IS_V ? q >= VSS : q < NR) wgmma_rs64(d, wf[IS_V ? (q >= VSS ? q - VSS : 0) : (q < NR ? q : 0)], db, q);
          else if (IS_V) wgmma_ts64(d, mkdesc(SB0 + OFF_WV + q * 2048, 8192, 1024), db, q);
          else wgmma_ts64(d, desc_at(mkdesc(SB0 + OFF_Y + (q - NR) * 2048, 8192, 1024), yo), db, 1);
        }
        wg_commit();
        if (c > 0 && c <= 7) {
          wg_wait<1>();
          if ((tid0 & 31) == 0) mbar_arrive(sb + BAR_E + 8 * ((c - 1) % 5));
        }
      }
      wg_wait<0>();
      if (bc == 0 && WG != 1) WTS(k, 16 + WG / 2);
      WBAR_SYNC(NB_B, 384);
      const int tid = fresh(tid0), m = (tid >> 3) & 3;
      const uint32_t a = sb + OFF_T + min(wu * 16 + (m & 1) * 8 + (tid & 7), 60) * 16 + (8 * WG + (m >> 1)) * COL;
#pragma unroll
      for (int p = 0; p < 4; p++) {
        stsm4(a + 2 * p * COL, pack_bf16(d[8 * p], d[8 * p + 1]), pack_bf16(d[8 * p + 2], d[8 * p + 3]), pack_bf16(d[8 * p + 4], d[8 * p + 5]), pack_bf16(d[8 * p + 6], d[8 * p + 7]));
      }
    }
    WBAR_SYNC(NB_B, 384);
    if (bc == 0 && WG == 0) WTS(k, 7);
    if (bc * 3 + WG < NH && (wu < 2 ? k < NSEG : k >= LAG)) attend(sb, aa, k, wu, fresh(tid0));
    else release_tiles(sb, tid0);
    if (bc == 0 && WG == 0) WTS(k, 8);
    WBAR_SYNC(NB_AS, 416);
    }
    const int s = k - (1 - WG) * (LAG + 1);
    if (!IS_V && bc < 10 && s >= 0 && s < NSEG) {
      float d[16];
#pragma unroll
      for (int f = 0; f < 5; f++) {
        mwait(sb + BAR_G + 40 * WG + 8 * f, s & 1, spin);
        if (f == 0 && bc == 0) WTS(k - 1 + WG, WG || k > NSEG ? 20 : 23);
        wg_fence();
#pragma unroll
        for (int kk = 0; kk < 8; kk++) {
          wgmma_tt32(d, mkdesc(SB0 + OFF_WO + (8 * f + kk) * 2048, 8192, 1024), gdesc(OFF_X + f * 8192, kk), f | kk);
          if (kk == 1 && f > 0) {
            wg_commit();
            wg_wait<1>();
            if ((tid0 & 31) < 3) mbar_arrive(sb + BAR_E + 8 * (f - 1));
          }
        }
        wg_commit();
      }
      wg_wait<0>();
      if (WG == 1 && FSA) {
        const float chk = ((d[0] + d[1]) + (d[4] + d[5])) + ((d[8] + d[9]) + (d[12] + d[13]));
        if (__builtin_expect(bar_red_or(NB_RED, 128, chk != chk), 0)) {
          if (wu == 0) { cwait(CN_A + k, NBC, spin); fence_async_all(); }
#pragma unroll
          for (int q = 0; q < 16; q++) d[q] = 0.f;
#pragma unroll 1
          for (int f = 0; f < 5; f++) {
            if (wu == 0 && elect_one()) { mbar_expect_tx(sb + BAR_W + 8, 8192); bulk_g2s(sb + OFF_X + 32768, g_ob[k] + f * 8192, 8192, sb + BAR_W + 8); }
            __syncwarp();
            mwait(sb + BAR_W + 8, nredo & 1, spin);
            nredo++;
            wg_fence();
#pragma unroll
            for (int kk = 0; kk < 8; kk++)
              wgmma_tt32(d, desc_at(mkdesc(SB0 + OFF_WO + kk * 2048, 8192, 1024), f * 16384), gdesc(OFF_X + 32768, kk), 1);
            wg_commit();
            wg_wait<0>();
            bar_sync(NB_RED, 128);
          }
        }
      }
      if ((tid0 & 31) < 3) mbar_arrive(sb + BAR_E + 32);
      if (bc == 0) WTS(k - 1 + WG, WG || k > NSEG ? 10 : 24);
      red_tile<true>(d, s, bc * 64, fresh(tid0));
      WBAR_SYNC(WG ? NB_SG : NB_SG1, 160);
    }
  }
  if (spin >= SPIN_TOT) g_err = 14;
}
__device__ __forceinline__ bool b_job(int k, int u, int bc) { return u < 2 ? k < NSTEP : bc < 10 && (u == 2 ? k > LAG : k < NSEG); }
__device__ __forceinline__ void work_b_watch(uint32_t sb, int bc) {
  using namespace W;
  int spin = 0;
#pragma unroll 1
  for (int j = 0; j < 4 * NSTEP + 3; j++) {
    const int k = j >> 2, u = j & 3;
    if (u == 1 || !b_job(k, u, bc)) continue;
    cwait(u == 0 ? CN_L + k : u == 2 ? CN_A + k - 1 : (FSA ? CN_F : CN_A) + k, u ? NBC : k < LAG || k >= NSEG ? 32 : 64, spin);
    fence_async_all();
    if (bc == 0 && (u != 2 || k > NSEG)) WTS1(k + (u ? u - 3 : 0), u ? 9 : 5);
    if (elect_one()) mbar_arrive(sb + BAR_R + 8 * u);
    __syncwarp();
    if (u == 0) WBAR_SYNC(NB_R, 64);
  }
  if (spin >= SPIN_TOT) g_err = 16;
}
__device__ __forceinline__ void work_b_producer(uint32_t sb, int bc) {
  using namespace W;
  int spin = 0;
  uint32_t pe = 1;
#pragma unroll 1
  for (int j = 0; j < 4 * NSTEP + 3; j++) {
    const int k = j >> 2, u = j & 3;
    if (!b_job(k, u, bc)) continue;
    const uint32_t half = u < 2 && (k < LAG || k >= NSEG), lo = half && k >= NSEG ? 4096 : 0, len = half ? 4096 : 8192, fb = sb + (u < 2 ? BAR_F : BAR_G + 40 * (u - 2));
    const uint8_t* src = (u < 2 ? g_xnb[k] + u * 40960 : u == 2 ? g_ob[k - 1] + 40960 : g_ob[k]) + lo;
    if (u != 1) mwait(sb + BAR_R + 8 * u, (u == 2 ? k - LAG - 1 : k) & 1, spin);
#pragma unroll
    for (int f = 0; f < 5; f++) {
      mwait(sb + BAR_E + 8 * f, pe, spin);
      if (elect_one()) {
        mbar_expect_tx(fb + 8 * f, len);
        bulk_g2s(sb + OFF_X + f * 8192 + lo, src + f * 8192, len, fb + 8 * f);
      }
    }
    if (u == 0) WBAR_SYNC(NB_R, 64);
    pe ^= 1;
  }
  if (spin >= SPIN_TOT) g_err = 15;
}

__global__ void __launch_bounds__(512, 1)
k_work(const __grid_constant__ CUtensorMap tmWo, const __grid_constant__ CUtensorMap tmBo, const bf16* __restrict__ wqkv, bf16* __restrict__ out,
       const bf16* __restrict__ x0, const bf16* __restrict__ mem0) {
  using namespace W;
  extern __shared__ __align__(1024) uint8_t smem[];
  const uint32_t sb = smem_u32(smem);
  const int tid = threadIdx.x, w = blockIdx.x;
  const int wg = __shfl_sync(0xffffffffu, tid >> 7, 0);
  if (tid == 0) {
    if (sb != SB0) g_err = 101;
    for (int i = 0; i < 5; i++) { mbar_init(sb + BAR_F + 8 * i, 1); mbar_init(sb + BAR_E + 8 * i, w < NP ? 8 : 12); }
    for (int i = 0; i < 16; i++) mbar_init(sb + BAR_G + 8 * i, 1);
    for (int p = 0; p < 16; p++) sts32(sb + OFF_SAFE + 4 * p, 0);
    asm volatile("fence.mbarrier_init.release.cluster;" ::: "memory");
    int spin = 0;
    pre_wait(1, NW, spin);
    if (spin >= SPIN_TOT) g_err = 18;
  }
  if (tid < 8 * COL / 16) sts128(sb + OFF_H + tid * 16, make_uint4(0, 0, 0, 0));
  fence_async();
  __syncthreads();

  if (w < NP) {
    if (wg < 2) work_p(tmWo, sb, w, wg, keep(tid));
    else {
      asm volatile("setmaxnreg.dec.sync.aligned.u32 48;");
      const int aw = uni(tid >> 5) - 8;
      if (aw < 2) {
        work_p_producer(sb, w, aw);
      } else {
        const int id = (aw - 2) * NP + w;
        if (id < 128) work_ln(id & 3, id >> 2, tid & 31, out);
        else if (id < 144 && NOWORK != 2) work_prep(x0, mem0, id - 128, tid & 31);
      }
    }
  } else {
    const int bc = w - NP;
    if (wg < 2) work_b<false>(tmBo, wqkv, sb, bc, wg, keep(tid));
    else if (wg == 2) work_b<true>(tmBo, wqkv, sb, bc, wg, keep(tid));
    else {
      asm volatile("setmaxnreg.dec.sync.aligned.u32 24;");
      const int aw = uni(tid >> 5) - 12;
      if (aw == 0) work_b_producer(sb, bc);
      else if (aw == 1) work_b_watch(sb, bc);
      else if (aw == 2) {
#pragma unroll 1
        for (int k = 0; k <= NSTEP; k++) {
          if (k < NSTEP) {
            WBAR_SYNC(NB_AS, 416);
            if (elect_one()) {
              const uint32_t len = bc < 10 ? 3840 : 2560;
              if (k < NSEG) bulk_s2g(g_ob[k] + bc * 3840, sb + OFF_S, len);
              if (k >= LAG) bulk_s2g(g_ob[k] + 40960 + bc * 3840, sb + OFF_S + 3840, len);
              asm volatile("cp.async.bulk.commit_group;" ::: "memory");
              asm volatile("cp.async.bulk.wait_group 0;" ::: "memory");
              if (FSA) csignal_fast(CN_F + k);
              fence_async_all();
              csignal_t(CN_A + k, 5);
            }
            __syncwarp();
          }
          if (b_job(k, 2, bc)) {
            WBAR_SYNC(NB_SG1, 160);
            if ((tid & 31) == 0) csignal_t(CN_W + 64 + k - LAG - 1, 4);
            __syncwarp();
          }
        }
      } else if (bc < 10) {
#pragma unroll 1
        for (int k = 0; k < NSEG; k++) {
          WBAR_SYNC(NB_SG, 160);
          if ((tid & 31) == 0) csignal_t(CN_W + k, 6);
          __syncwarp();
        }
      }
    }
  }
  __syncthreads();
  asm volatile("griddepcontrol.wait;" ::: "memory");
}

typedef CUresult (*EncodeFn)(CUtensorMap*, CUtensorMapDataType, cuuint32_t, void*, const cuuint64_t*, const cuuint64_t*,
                             const cuuint32_t*, const cuuint32_t*, CUtensorMapInterleave, CUtensorMapSwizzle,
                             CUtensorMapL2promotion, CUtensorMapFloatOOBfill);

static void make_map(EncodeFn enc, CUtensorMap* tm, const void* ptr, uint64_t cols, uint64_t rows, uint32_t boxc, uint32_t boxr) {
  cuuint64_t dims[2] = {cols, rows};
  cuuint64_t strides[1] = {cols * 2};
  cuuint32_t box[2] = {boxc, boxr};
  cuuint32_t es[2] = {1, 1};
  enc(tm, CU_TENSOR_MAP_DATA_TYPE_BFLOAT16, 2, const_cast<void*>(ptr), dims, strides, box, es, CU_TENSOR_MAP_INTERLEAVE_NONE,
      CU_TENSOR_MAP_SWIZZLE_128B, CU_TENSOR_MAP_L2_PROMOTION_L2_256B, CU_TENSOR_MAP_FLOAT_OOB_FILL_NONE);
}

extern "C" void kernel_launch(void* const* d_in, const int* in_sizes, int n_in, void* d_out, int out_size) {
  const bf16* x0 = (const bf16*)d_in[0];
  const bf16* mem0 = (const bf16*)d_in[1];
  const bf16* Wq = (const bf16*)d_in[2];
  const bf16* Wk = (const bf16*)d_in[3];
  const bf16* Wv = (const bf16*)d_in[4];
  const bf16* Wo = (const bf16*)d_in[5];
  const bf16* Bqkv = (const bf16*)d_in[8];
  const bf16* Bwo = (const bf16*)d_in[9];
  bf16* out = (bf16*)d_out;

  static EncodeFn enc = nullptr;
  if (!enc) {
    void* fn = nullptr;
    cudaDriverEntryPointQueryResult qr;
    cudaGetDriverEntryPoint("cuTensorMapEncodeTiled", &fn, cudaEnableDefault, &qr);
    enc = (EncodeFn)fn;
    cudaFuncSetAttribute(k_chain, cudaFuncAttributeMaxDynamicSharedMemorySize, C::SMEM);
    cudaFuncSetAttribute(k_work, cudaFuncAttributeMaxDynamicSharedMemorySize, W::SMEM);
  }
  CUtensorMap tmWq, tmWk, tmWv, tmWo, tmWp, tmBo;
  make_map(enc, &tmWq, Wq, NH * DH, DM, 64, 128);
  make_map(enc, &tmWk, Wk, NH * DH, DM, 64, 128);
  make_map(enc, &tmWv, Wv, NH * DH, DM, 64, 128);
  make_map(enc, &tmWo, Wo, DM, NH * DH, 64, 64);
  make_map(enc, &tmWp, Wo, DM, NH * DH, 64, 16);
  make_map(enc, &tmBo, Bwo, DM, DM, 64, 64);

  cudaStream_t st = cudaStreamPerThread;
  cudaLaunchAttribute at[1];
  at[0].id = cudaLaunchAttributeProgrammaticStreamSerialization; at[0].val.programmaticStreamSerializationAllowed = 1;
  {
    cudaLaunchConfig_t cfg = {};
    cfg.gridDim = dim3(96); cfg.blockDim = dim3(384); cfg.dynamicSmemBytes = C::SMEM; cfg.stream = st;
    cfg.attrs = at; cfg.numAttrs = 0;
    cudaLaunchKernelEx(&cfg, k_chain, tmWq, tmWk, tmWv, tmWo, x0, mem0);
  }
  cudaLaunchConfig_t cfg = {};
  cfg.gridDim = dim3(W::NW); cfg.blockDim = dim3(512); cfg.dynamicSmemBytes = W::SMEM; cfg.stream = st;
  cfg.attrs = at; cfg.numAttrs = NOWORK == 2 ? 0 : 1;
  cudaLaunchKernelEx(&cfg, k_work, tmWp, tmBo, Bqkv, out, x0, mem0);
}
```

```cpp
#include <cuda_runtime.h>
#include <cuda_bf16.h>
#include <cuda.h>
#include <stdint.h>

typedef __nv_bfloat16 bf16;

constexpr int SEQ = 2048, DM = 640, NH = 32, DH = 192, NSEG = 64;
#define LAG 6
constexpr int NSTEP = NSEG + LAG;
constexpr int NPRE = 4;
constexpr uint32_t SENT = 0xFFFFFFFFu;

constexpr int MAIL9 = 288 * 2048, MAIL_BYTES = MAIL9 + 64 * 3072;
__device__ __align__(1024) uint8_t g_xn[NSTEP][81920];
__device__ __align__(1024) uint8_t g_xnb[NSTEP][81920];
__device__ __align__(1024) uint8_t g_ob[NSTEP][81920];
__device__ __align__(1024) uint8_t g_y[2][NSEG * 40960];
#define ORING 8
static_assert(ORING > LAG, "a slot is free again LAG + 1 steps later");
__device__ __align__(1024) uint8_t g_o[ORING][96][8192];
__device__ __align__(1024) float g_x[SEQ * DM];
constexpr int EX_MAIL = 0;
constexpr int EX_M = 2 << 20;
constexpr int EX_FLAG = EX_M + NSTEP * 20480;
static_assert(EX_FLAG + NSTEP * 3072 <= (4 << 20), "");
__device__ __align__(1024) uint8_t g_ex[8 << 20];
__host__ __device__ __forceinline__ uint8_t* ex_window(uint8_t* p) { return reinterpret_cast<uint8_t*>((reinterpret_cast<uint64_t>(p) + (4 << 20) - 1) & ~(uint64_t)((4 << 20) - 1)); }
enum { CN_P = 0, CN_L = 128, CN_A = 256, CN_W = 384, CN_X = 512, CN_F = 640, CN_O = 768, CN_NUM = CN_O + 5 * NSTEP };
__device__ __align__(128) uint32_t g_cnt[CN_NUM][32];
__device__ __align__(128) uint32_t g_ticket[2][32];
__device__ int g_err;
#define TS(jj, i)
#define TS1(jj, i)
#define PTS(i)
#define TSB(jj, i)
#define TSV(jj, i, v)
#define TS_FLUSH(jj)
#define WTS(b, k)
#define WTS1(b, k)
#define WW -1

__device__ __forceinline__ uint32_t smem_u32(const void* p) { return (uint32_t)__cvta_generic_to_shared(p); }
__device__ __forceinline__ uint32_t clk32() { uint32_t t; asm volatile("mov.u32 %0, %%clock;" : "=r"(t)::"memory"); return t; }
__device__ __forceinline__ uint32_t mapa(uint32_t a, uint32_t r) { uint32_t o; asm("mapa.shared::cluster.u32 %0,%1,%2;" : "=r"(o) : "r"(a), "r"(r)); return o; }
__device__ __forceinline__ void mbar_init(uint32_t bar, uint32_t cnt) { asm volatile("mbarrier.init.shared::cta.b64 [%0],%1;" ::"r"(bar), "r"(cnt) : "memory"); }
__device__ __forceinline__ void mbar_expect_tx(uint32_t bar, uint32_t bytes) { asm volatile("mbarrier.arrive.expect_tx.shared::cta.b64 _,[%0],%1;" ::"r"(bar), "r"(bytes) : "memory"); }
__device__ __forceinline__ void mbar_arrive(uint32_t bar) { asm volatile("mbarrier.arrive.shared::cta.b64 _,[%0];" ::"r"(bar) : "memory"); }
__device__ __forceinline__ void mbar_arrive_cluster(uint32_t bar) { asm volatile("mbarrier.arrive.shared::cluster.b64 _,[%0];" ::"r"(bar) : "memory"); }
__device__ __forceinline__ bool mbar_try(uint32_t bar, uint32_t ph) {
  uint32_t ok;
  asm volatile("{.reg .pred p; mbarrier.try_wait.parity.shared::cta.b64 p,[%1],%2; selp.u32 %0,1,0,p;}" : "=r"(ok) : "r"(bar), "r"(ph) : "memory");
  return ok;
}
__device__ __forceinline__ bool mbar_test(uint32_t bar, uint32_t ph) {
  uint32_t ok;
  asm volatile("{.reg .pred p; mbarrier.test_wait.parity.shared::cta.b64 p,[%1],%2; selp.u32 %0,1,0,p;}" : "=r"(ok) : "r"(bar), "r"(ph) : "memory");
  return ok;
}
__device__ __forceinline__ int fresh(int x) { asm volatile("" : "+r"(x)); return x; }
#define PHASE_IDS const int tid = fresh(tid0), lane = tid & 31, w = tid >> 5, g = lane >> 2, t = lane & 3; (void)w; (void)g; (void)t
__device__ __forceinline__ void bar_sync(int id, int n) { asm volatile("bar.sync %0,%1;" ::"r"(id), "r"(n) : "memory"); }
__device__ __forceinline__ void bar_arrive(int id, int n) { asm volatile("bar.arrive %0,%1;" ::"r"(id), "r"(n) : "memory"); }
__device__ __forceinline__ bool bar_red_or(int id, int n, bool v) {
  uint32_t r;
  asm volatile("{\n .reg .pred p, q;\n setp.ne.u32 q, %3, 0;\n barrier.cta.red.or.pred p, %1, %2, q;\n selp.u32 %0, 1, 0, p;\n}" : "=r"(r) : "r"(id), "r"(n), "r"((uint32_t)v) : "memory");
  return r != 0;
}
__device__ __forceinline__ void fence_async() { asm volatile("fence.proxy.async.shared::cta;" ::: "memory"); }
__device__ __forceinline__ void bulk_g2s(uint32_t dst, const void* src, uint32_t bytes, uint32_t bar) {
  asm volatile("cp.async.bulk.shared::cluster.global.mbarrier::complete_tx::bytes [%0],[%1],%2,[%3];" ::"r"(dst), "l"(src), "r"(bytes), "r"(bar) : "memory");
}
__device__ __forceinline__ void bulk_g2s_mc(uint32_t dst, const void* src, uint32_t bytes, uint32_t bar) {
  asm volatile("cp.async.bulk.shared::cluster.global.mbarrier::complete_tx::bytes.multicast::cluster [%0],[%1],%2,[%3],%4;"
               ::"r"(dst), "l"(src), "r"(bytes), "r"(bar), "h"((uint16_t)7) : "memory");
}
__device__ __forceinline__ void bulk_s2g(void* dst, uint32_t src, uint32_t bytes) {
  asm volatile("cp.async.bulk.global.shared::cta.bulk_group [%0],[%1],%2;" ::"l"(dst), "r"(src), "r"(bytes) : "memory");
}
__device__ __forceinline__ void bulk_s2c(uint32_t dst, uint32_t src, uint32_t bytes, uint32_t bar) {
  asm volatile("cp.async.bulk.shared::cluster.shared::cta.mbarrier::complete_tx::bytes [%0],[%1],%2,[%3];" ::"r"(dst), "r"(src), "r"(bytes), "r"(bar) : "memory");
}
__device__ __forceinline__ void tma2d(uint32_t dst, const CUtensorMap* tm, int c0, int c1, uint32_t bar) {
  asm volatile("cp.async.bulk.tensor.2d.shared::cluster.global.mbarrier::complete_tx::bytes [%0],[%1,{%3,%4}],[%2];"
               ::"r"(dst), "l"(tm), "r"(bar), "r"(c0), "r"(c1) : "memory");
}
__device__ __forceinline__ void tma2d_prefetch(const CUtensorMap* tm, int c0, int c1) {
  asm volatile("cp.async.bulk.prefetch.tensor.2d.L2.global.tile [%0,{%1,%2}];" ::"l"(tm), "r"(c0), "r"(c1) : "memory");
}
__device__ __forceinline__ uint32_t pack_bf16(float lo, float hi) {
  uint32_t r; asm("cvt.rn.bf16x2.f32 %0,%1,%2;" : "=r"(r) : "f"(hi), "f"(lo)); return r;
}
__device__ __forceinline__ float bf_lo(uint32_t x) { return __uint_as_float(x << 16); }
__device__ __forceinline__ float bf_hi(uint32_t x) { return __uint_as_float(x & 0xFFFF0000u); }
__device__ __forceinline__ float ex2(float x) { float y; asm("ex2.approx.ftz.f32 %0,%1;" : "=f"(y) : "f"(x)); return y; }
__device__ __forceinline__ void ldsm4(uint32_t (&r)[4], uint32_t a) {
  asm volatile("ldmatrix.sync.aligned.m8n8.x4.shared.b16 {%0,%1,%2,%3},[%4];" : "=r"(r[0]), "=r"(r[1]), "=r"(r[2]), "=r"(r[3]) : "r"(a) : "memory");
}
__device__ __forceinline__ void ldsm4t(uint32_t (&r)[4], uint32_t a) {
  asm volatile("ldmatrix.sync.aligned.m8n8.x4.trans.shared.b16 {%0,%1,%2,%3},[%4];" : "=r"(r[0]), "=r"(r[1]), "=r"(r[2]), "=r"(r[3]) : "r"(a) : "memory");
}
__device__ __forceinline__ void ldsm2(uint32_t& r0, uint32_t& r1, uint32_t a) {
  asm volatile("ldmatrix.sync.aligned.m8n8.x2.shared.b16 {%0,%1},[%2];" : "=r"(r0), "=r"(r1) : "r"(a) : "memory");
}
__device__ __forceinline__ void ldsm2t(uint32_t& r0, uint32_t& r1, uint32_t a) {
  asm volatile("ldmatrix.sync.aligned.m8n8.x2.trans.shared.b16 {%0,%1},[%2];" : "=r"(r0), "=r"(r1) : "r"(a) : "memory");
}
__device__ __forceinline__ void ldsm1(uint32_t& r0, uint32_t a) {
  asm volatile("ldmatrix.sync.aligned.m8n8.x1.shared.b16 {%0},[%1];" : "=r"(r0) : "r"(a) : "memory");
}
__device__ __forceinline__ void mma16816(float (&d)[4], uint32_t a0, uint32_t a1, uint32_t a2, uint32_t a3, uint32_t b0, uint32_t b1) {
  asm volatile("mma.sync.aligned.m16n8k16.row.col.f32.bf16.bf16.f32 {%0,%1,%2,%3},{%4,%5,%6,%7},{%8,%9},{%0,%1,%2,%3};"
               : "+f"(d[0]), "+f"(d[1]), "+f"(d[2]), "+f"(d[3]) : "r"(a0), "r"(a1), "r"(a2), "r"(a3), "r"(b0), "r"(b1));
}
__device__ __forceinline__ void mma1688(float (&d)[4], uint32_t a0, uint32_t a1, uint32_t b0) {
  asm volatile("mma.sync.aligned.m16n8k8.row.col.f32.bf16.bf16.f32 {%0,%1,%2,%3},{%4,%5},{%6},{%0,%1,%2,%3};"
               : "+f"(d[0]), "+f"(d[1]), "+f"(d[2]), "+f"(d[3]) : "r"(a0), "r"(a1), "r"(b0));
}
__device__ __forceinline__ void sts32(uint32_t a, uint32_t v) { asm volatile("st.shared.b32 [%0],%1;" ::"r"(a), "r"(v) : "memory"); }
__device__ __forceinline__ void sts64f(uint32_t a, float x, float y) { asm volatile("st.shared.v2.f32 [%0],{%1,%2};" ::"r"(a), "f"(x), "f"(y) : "memory"); }
__device__ __forceinline__ void sts128(uint32_t a, uint4 v) { asm volatile("st.shared.v4.b32 [%0],{%1,%2,%3,%4};" ::"r"(a), "r"(v.x), "r"(v.y), "r"(v.z), "r"(v.w) : "memory"); }
__device__ __forceinline__ float lds32f(uint32_t a) { float v; asm volatile("ld.shared.f32 %0,[%1];" : "=f"(v) : "r"(a) : "memory"); return v; }
__device__ __forceinline__ float2 lds64f(uint32_t a) { float2 v; asm volatile("ld.shared.v2.f32 {%0,%1},[%2];" : "=f"(v.x), "=f"(v.y) : "r"(a) : "memory"); return v; }
__device__ __forceinline__ uint4 lds128(uint32_t a) { uint4 v; asm volatile("ld.shared.v4.b32 {%0,%1,%2,%3},[%4];" : "=r"(v.x), "=r"(v.y), "=r"(v.z), "=r"(v.w) : "r"(a) : "memory"); return v; }
__device__ __forceinline__ float4 lds128f(uint32_t a) { float4 v; asm volatile("ld.shared.v4.f32 {%0,%1,%2,%3},[%4];" : "=f"(v.x), "=f"(v.y), "=f"(v.z), "=f"(v.w) : "r"(a) : "memory"); return v; }
__device__ __forceinline__ void st_async2(uint32_t a, float x, float y, uint32_t bar) {
  asm volatile("st.async.weak.shared::cluster.mbarrier::complete_tx::bytes.v2.f32 [%0],{%1,%2},[%3];" ::"r"(a), "f"(x), "f"(y), "r"(bar) : "memory");
}
__device__ __forceinline__ void st_async4(uint32_t a, const float (&v)[4], uint32_t bar) {
  asm volatile("st.async.weak.shared::cluster.mbarrier::complete_tx::bytes.v4.f32 [%0],{%1,%2,%3,%4},[%5];" ::"r"(a), "f"(v[0]), "f"(v[1]), "f"(v[2]), "f"(v[3]), "r"(bar) : "memory");
}
__device__ __forceinline__ void st_async4v(uint32_t a, float x, float y, float z, float w, uint32_t bar) {
  asm volatile("st.async.weak.shared::cluster.mbarrier::complete_tx::bytes.v4.f32 [%0],{%1,%2,%3,%4},[%5];" ::"r"(a), "f"(x), "f"(y), "f"(z), "f"(w), "r"(bar) : "memory");
}
__device__ __forceinline__ void st_async4u(uint32_t a, const uint4& v, uint32_t bar) {
  asm volatile("st.async.weak.shared::cluster.mbarrier::complete_tx::bytes.v4.b32 [%0],{%1,%2,%3,%4},[%5];" ::"r"(a), "r"(v.x), "r"(v.y), "r"(v.z), "r"(v.w), "r"(bar) : "memory");
}
__device__ __forceinline__ uint4 ld_relaxed4(const void* p) {
  uint4 v; asm volatile("ld.relaxed.gpu.global.v4.u32 {%0,%1,%2,%3},[%4];" : "=r"(v.x), "=r"(v.y), "=r"(v.z), "=r"(v.w) : "l"(p) : "memory"); return v;
}
__device__ __forceinline__ uint32_t ld_relaxed(const void* p) {
  uint32_t v; asm volatile("ld.relaxed.gpu.global.u32 %0,[%1];" : "=r"(v) : "l"(p) : "memory"); return v;
}
__device__ __forceinline__ void st_relaxed(void* p, uint32_t v) { asm volatile("st.relaxed.gpu.global.b32 [%0],%1;" ::"l"(p), "r"(v) : "memory"); }
__device__ __forceinline__ void st_relaxed4(void* p, uint32_t v) { asm volatile("st.relaxed.gpu.global.v4.b32 [%0],{%1,%1,%1,%1};" ::"l"(p), "r"(v) : "memory"); }

__device__ __forceinline__ uint32_t ld_acquire(const void* p) {
  uint32_t v; asm volatile("ld.acquire.gpu.global.u32 %0,[%1];" : "=r"(v) : "l"(p) : "memory"); return v;
}
__device__ __forceinline__ float4 ld_relaxed4f(const void* p) {
  float4 v; asm volatile("ld.relaxed.gpu.global.v4.f32 {%0,%1,%2,%3},[%4];" : "=f"(v.x), "=f"(v.y), "=f"(v.z), "=f"(v.w) : "l"(p) : "memory"); return v;
}
__device__ __forceinline__ float2 ld_relaxed2f(const void* p) {
  float2 v; asm volatile("ld.relaxed.gpu.global.v2.f32 {%0,%1},[%2];" : "=f"(v.x), "=f"(v.y) : "l"(p) : "memory"); return v;
}
__device__ __forceinline__ void prefetch_l2(const void* p) { asm volatile("prefetch.global.L2 [%0];" ::"l"(p)); }
__device__ __forceinline__ void fence_gpu() { asm volatile("fence.acq_rel.gpu;" ::: "memory"); }
__device__ __forceinline__ void fence_async_all() { asm volatile("fence.proxy.async.global;" ::: "memory"); }
constexpr int SPIN_TOT = 1 << 22;
__device__ __forceinline__ void csignal(int idx) { asm volatile("red.release.gpu.global.add.u32 [%0],1;" ::"l"(&g_cnt[idx][0]) : "memory"); }
__device__ __forceinline__ void csignal_fast(int idx) { asm volatile("red.relaxed.gpu.global.add.u32 [%0],1;" ::"l"(&g_cnt[idx][0]) : "memory"); }
#define UNS 0
#define RLX 0
#define csignal_t(idx, role) csignal(idx)
__device__ __forceinline__ void cwait(int idx, uint32_t target, int& spin) {
  while (ld_acquire(&g_cnt[idx][0]) < target && spin < SPIN_TOT) spin += 16;
}

__device__ __forceinline__ uint64_t mkdesc(uint32_t addr, uint32_t lbo, uint32_t sbo) {
  return (uint64_t)((addr & 0x3FFFF) >> 4) | ((uint64_t)(lbo >> 4) << 16) | ((uint64_t)(sbo >> 4) << 32) | ((uint64_t)1 << 62);
}
__device__ __forceinline__ uint64_t mkdesc_ns(uint32_t addr, uint32_t lbo, uint32_t sbo) {
  return (uint64_t)((addr & 0x3FFFF) >> 4) | ((uint64_t)(lbo >> 4) << 16) | ((uint64_t)(sbo >> 4) << 32);
}
__device__ __forceinline__ void wg_fence() { asm volatile("wgmma.fence.sync.aligned;" ::: "memory"); }
__device__ __forceinline__ void wg_commit() { asm volatile("wgmma.commit_group.sync.aligned;" ::: "memory"); }
template <int N> __device__ __forceinline__ void wg_wait() { asm volatile("wgmma.wait_group.sync.aligned %0;" ::"n"(N) : "memory"); }

__device__ __forceinline__ void wgmma_rs16(float (&d)[8], const uint32_t (&a)[4], uint64_t db, int sc) {
  asm volatile("{.reg .pred p; setp.ne.b32 p,%13,0; wgmma.mma_async.sync.aligned.m64n16k16.f32.bf16.bf16 "
               "{%0,%1,%2,%3,%4,%5,%6,%7},{%8,%9,%10,%11},%12,p,1,1,0;}"
               : "+f"(d[0]), "+f"(d[1]), "+f"(d[2]), "+f"(d[3]), "+f"(d[4]), "+f"(d[5]), "+f"(d[6]), "+f"(d[7])
               : "r"(a[0]), "r"(a[1]), "r"(a[2]), "r"(a[3]), "l"(db), "r"(sc));
}
__device__ __forceinline__ void wgmma_rs64(float (&d)[32], const uint32_t (&a)[4], uint64_t db, int sc) {
  asm volatile("{.reg .pred p; setp.ne.b32 p,%37,0; wgmma.mma_async.sync.aligned.m64n64k16.f32.bf16.bf16 "
               "{%0,%1,%2,%3,%4,%5,%6,%7,%8,%9,%10,%11,%12,%13,%14,%15,%16,%17,%18,%19,%20,%21,%22,%23,%24,%25,%26,%27,%28,%29,%30,%31},{%32,%33,%34,%35},%36,p,1,1,0;}"
               : "+f"(d[0]), "+f"(d[1]), "+f"(d[2]), "+f"(d[3]), "+f"(d[4]), "+f"(d[5]), "+f"(d[6]), "+f"(d[7]), "+f"(d[8]), "+f"(d[9]), "+f"(d[10]), "+f"(d[11]), "+f"(d[12]), "+f"(d[13]), "+f"(d[14]), "+f"(d[15]), "+f"(d[16]), "+f"(d[17]), "+f"(d[18]), "+f"(d[19]), "+f"(d[20]), "+f"(d[21]), "+f"(d[22]), "+f"(d[23]), "+f"(d[24]), "+f"(d[25]), "+f"(d[26]), "+f"(d[27]), "+f"(d[28]), "+f"(d[29]), "+f"(d[30]), "+f"(d[31])
               : "r"(a[0]), "r"(a[1]), "r"(a[2]), "r"(a[3]), "l"(db), "r"(sc));
}
__device__ __forceinline__ void wgmma_rt16(float (&d)[8], const uint32_t (&a)[4], uint64_t db, int sc) {
  asm volatile("{.reg .pred p; setp.ne.b32 p,%13,0; wgmma.mma_async.sync.aligned.m64n16k16.f32.bf16.bf16 "
               "{%0,%1,%2,%3,%4,%5,%6,%7},{%8,%9,%10,%11},%12,p,1,1,1;}"
               : "+f"(d[0]), "+f"(d[1]), "+f"(d[2]), "+f"(d[3]), "+f"(d[4]), "+f"(d[5]), "+f"(d[6]), "+f"(d[7])
               : "r"(a[0]), "r"(a[1]), "r"(a[2]), "r"(a[3]), "l"(db), "r"(sc));
}
__device__ __forceinline__ void wgmma_rt80(float (&d)[40], const uint32_t (&a)[4], uint64_t db, int sc) {
  asm volatile("{.reg .pred p; setp.ne.b32 p,%45,0; wgmma.mma_async.sync.aligned.m64n80k16.f32.bf16.bf16 "
               "{%0,%1,%2,%3,%4,%5,%6,%7,%8,%9,%10,%11,%12,%13,%14,%15,%16,%17,%18,%19,%20,%21,%22,%23,%24,%25,%26,%27,%28,%29,%30,%31,%32,%33,%34,%35,%36,%37,%38,%39},{%40,%41,%42,%43},%44,p,1,1,1;}"
               : "+f"(d[0]), "+f"(d[1]), "+f"(d[2]), "+f"(d[3]), "+f"(d[4]), "+f"(d[5]), "+f"(d[6]), "+f"(d[7]), "+f"(d[8]), "+f"(d[9]), "+f"(d[10]), "+f"(d[11]), "+f"(d[12]), "+f"(d[13]), "+f"(d[14]), "+f"(d[15]), "+f"(d[16]), "+f"(d[17]), "+f"(d[18]), "+f"(d[19]), "+f"(d[20]), "+f"(d[21]), "+f"(d[22]), "+f"(d[23]), "+f"(d[24]), "+f"(d[25]), "+f"(d[26]), "+f"(d[27]), "+f"(d[28]), "+f"(d[29]), "+f"(d[30]), "+f"(d[31]), "+f"(d[32]), "+f"(d[33]), "+f"(d[34]), "+f"(d[35]), "+f"(d[36]), "+f"(d[37]), "+f"(d[38]), "+f"(d[39])
               : "r"(a[0]), "r"(a[1]), "r"(a[2]), "r"(a[3]), "l"(db), "r"(sc));
}
__device__ __forceinline__ void wgmma_rs32(float (&d)[16], const uint32_t (&a)[4], uint64_t db, int sc) {
  asm volatile("{.reg .pred p; setp.ne.b32 p,%21,0; wgmma.mma_async.sync.aligned.m64n32k16.f32.bf16.bf16 "
               "{%0,%1,%2,%3,%4,%5,%6,%7,%8,%9,%10,%11,%12,%13,%14,%15},{%16,%17,%18,%19},%20,p,1,1,0;}"
               : "+f"(d[0]), "+f"(d[1]), "+f"(d[2]), "+f"(d[3]), "+f"(d[4]), "+f"(d[5]), "+f"(d[6]), "+f"(d[7]), "+f"(d[8]), "+f"(d[9]), "+f"(d[10]), "+f"(d[11]), "+f"(d[12]), "+f"(d[13]), "+f"(d[14]), "+f"(d[15])
               : "r"(a[0]), "r"(a[1]), "r"(a[2]), "r"(a[3]), "l"(db), "r"(sc));
}
__device__ __forceinline__ void wgmma_ts32(float (&d)[16], uint64_t da, uint64_t db, int sc) {
  asm volatile("{.reg .pred p; setp.ne.b32 p,%18,0; wgmma.mma_async.sync.aligned.m64n32k16.f32.bf16.bf16 "
               "{%0,%1,%2,%3,%4,%5,%6,%7,%8,%9,%10,%11,%12,%13,%14,%15},%16,%17,p,1,1,1,0;}"
               : "+f"(d[0]), "+f"(d[1]), "+f"(d[2]), "+f"(d[3]), "+f"(d[4]), "+f"(d[5]), "+f"(d[6]), "+f"(d[7]), "+f"(d[8]), "+f"(d[9]), "+f"(d[10]), "+f"(d[11]), "+f"(d[12]), "+f"(d[13]), "+f"(d[14]), "+f"(d[15])
               : "l"(da), "l"(db), "r"(sc));
}
__device__ __forceinline__ void wgmma_rs8(float (&d)[4], const uint32_t (&a)[4], uint64_t db, int sc) {
  asm volatile("{.reg .pred p; setp.ne.b32 p,%9,0; wgmma.mma_async.sync.aligned.m64n8k16.f32.bf16.bf16 "
               "{%0,%1,%2,%3},{%4,%5,%6,%7},%8,p,1,1,0;}"
               : "+f"(d[0]), "+f"(d[1]), "+f"(d[2]), "+f"(d[3])
               : "r"(a[0]), "r"(a[1]), "r"(a[2]), "r"(a[3]), "l"(db), "r"(sc));
}
__device__ __forceinline__ void wgmma_tt32(float (&d)[16], uint64_t da, uint64_t db, int sc) {
  asm volatile("{.reg .pred p; setp.ne.b32 p,%18,0; wgmma.mma_async.sync.aligned.m64n32k16.f32.bf16.bf16 "
               "{%0,%1,%2,%3,%4,%5,%6,%7,%8,%9,%10,%11,%12,%13,%14,%15},%16,%17,p,1,1,1,1;}"
               : "+f"(d[0]), "+f"(d[1]), "+f"(d[2]), "+f"(d[3]), "+f"(d[4]), "+f"(d[5]), "+f"(d[6]), "+f"(d[7]), "+f"(d[8]), "+f"(d[9]), "+f"(d[10]), "+f"(d[11]), "+f"(d[12]), "+f"(d[13]), "+f"(d[14]), "+f"(d[15])
               : "l"(da), "l"(db), "r"(sc));
}
__device__ __forceinline__ void wgmma_ts16(float (&d)[8], uint64_t da, uint64_t db, int sc) {
  asm volatile("{.reg .pred p; setp.ne.b32 p,%10,0; wgmma.mma_async.sync.aligned.m64n16k16.f32.bf16.bf16 "
               "{%0,%1,%2,%3,%4,%5,%6,%7},%8,%9,p,1,1,1,0;}"
               : "+f"(d[0]), "+f"(d[1]), "+f"(d[2]), "+f"(d[3]), "+f"(d[4]), "+f"(d[5]), "+f"(d[6]), "+f"(d[7])
               : "l"(da), "l"(db), "r"(sc));
}
__device__ __forceinline__ void wgmma_ts64(float (&d)[32], uint64_t da, uint64_t db, int sc) {
  asm volatile("{.reg .pred p; setp.ne.b32 p,%34,0; wgmma.mma_async.sync.aligned.m64n64k16.f32.bf16.bf16 "
               "{%0,%1,%2,%3,%4,%5,%6,%7,%8,%9,%10,%11,%12,%13,%14,%15,%16,%17,%18,%19,%20,%21,%22,%23,%24,%25,%26,%27,%28,%29,%30,%31},%32,%33,p,1,1,1,0;}"
               : "+f"(d[0]), "+f"(d[1]), "+f"(d[2]), "+f"(d[3]), "+f"(d[4]), "+f"(d[5]), "+f"(d[6]), "+f"(d[7]), "+f"(d[8]), "+f"(d[9]), "+f"(d[10]), "+f"(d[11]), "+f"(d[12]), "+f"(d[13]), "+f"(d[14]), "+f"(d[15]), "+f"(d[16]), "+f"(d[17]), "+f"(d[18]), "+f"(d[19]), "+f"(d[20]), "+f"(d[21]), "+f"(d[22]), "+f"(d[23]), "+f"(d[24]), "+f"(d[25]), "+f"(d[26]), "+f"(d[27]), "+f"(d[28]), "+f"(d[29]), "+f"(d[30]), "+f"(d[31])
               : "l"(da), "l"(db), "r"(sc));
}
__device__ __forceinline__ void wgmma_tt16(float (&d)[8], uint64_t da, uint64_t db, int sc) {
  asm volatile("{.reg .pred p; setp.ne.b32 p,%10,0; wgmma.mma_async.sync.aligned.m64n16k16.f32.bf16.bf16 "
               "{%0,%1,%2,%3,%4,%5,%6,%7},%8,%9,p,1,1,1,1;}"
               : "+f"(d[0]), "+f"(d[1]), "+f"(d[2]), "+f"(d[3]), "+f"(d[4]), "+f"(d[5]), "+f"(d[6]), "+f"(d[7])
               : "l"(da), "l"(db), "r"(sc));
}
__device__ __forceinline__ void wgmma_tt40(float (&d)[20], uint64_t da, uint64_t db, int sc) {
  asm volatile("{.reg .pred p; setp.ne.b32 p,%22,0; wgmma.mma_async.sync.aligned.m64n40k16.f32.bf16.bf16 "
               "{%0,%1,%2,%3,%4,%5,%6,%7,%8,%9,%10,%11,%12,%13,%14,%15,%16,%17,%18,%19},%20,%21,p,1,1,1,1;}"
               : "+f"(d[0]), "+f"(d[1]), "+f"(d[2]), "+f"(d[3]), "+f"(d[4]), "+f"(d[5]), "+f"(d[6]), "+f"(d[7]), "+f"(d[8]), "+f"(d[9]), "+f"(d[10]), "+f"(d[11]), "+f"(d[12]), "+f"(d[13]), "+f"(d[14]), "+f"(d[15]), "+f"(d[16]), "+f"(d[17]), "+f"(d[18]), "+f"(d[19])
               : "l"(da), "l"(db), "r"(sc));
}
__device__ __forceinline__ void wgmma_ss8(float (&d)[4], uint64_t da, uint64_t db, int sc) {
  asm volatile("{.reg .pred p; setp.ne.b32 p,%6,0; wgmma.mma_async.sync.aligned.m64n8k16.f32.bf16.bf16 "
               "{%0,%1,%2,%3},%4,%5,p,1,1,0,0;}"
               : "+f"(d[0]), "+f"(d[1]), "+f"(d[2]), "+f"(d[3])
               : "l"(da), "l"(db), "r"(sc));
}
__device__ __forceinline__ void wgmma_ss32(float (&d)[16], uint64_t da, uint64_t db, int sc) {
  asm volatile("{.reg .pred p; setp.ne.b32 p,%18,0; wgmma.mma_async.sync.aligned.m64n32k16.f32.bf16.bf16 "
               "{%0,%1,%2,%3,%4,%5,%6,%7,%8,%9,%10,%11,%12,%13,%14,%15},%16,%17,p,1,1,0,0;}"
               : "+f"(d[0]), "+f"(d[1]), "+f"(d[2]), "+f"(d[3]), "+f"(d[4]), "+f"(d[5]), "+f"(d[6]), "+f"(d[7]), "+f"(d[8]), "+f"(d[9]), "+f"(d[10]), "+f"(d[11]), "+f"(d[12]), "+f"(d[13]), "+f"(d[14]), "+f"(d[15])
               : "l"(da), "l"(db), "r"(sc));
}
__device__ __forceinline__ void wgmma_st64(float (&d)[32], uint64_t da, uint64_t db, int sc) {
  asm volatile("{.reg .pred p; setp.ne.b32 p,%34,0; wgmma.mma_async.sync.aligned.m64n64k16.f32.bf16.bf16 "
               "{%0,%1,%2,%3,%4,%5,%6,%7,%8,%9,%10,%11,%12,%13,%14,%15,%16,%17,%18,%19,%20,%21,%22,%23,%24,%25,%26,%27,%28,%29,%30,%31},%32,%33,p,1,1,0,1;}"
               : "+f"(d[0]), "+f"(d[1]), "+f"(d[2]), "+f"(d[3]), "+f"(d[4]), "+f"(d[5]), "+f"(d[6]), "+f"(d[7]), "+f"(d[8]), "+f"(d[9]), "+f"(d[10]), "+f"(d[11]), "+f"(d[12]), "+f"(d[13]), "+f"(d[14]), "+f"(d[15]), "+f"(d[16]), "+f"(d[17]), "+f"(d[18]), "+f"(d[19]), "+f"(d[20]), "+f"(d[21]), "+f"(d[22]), "+f"(d[23]), "+f"(d[24]), "+f"(d[25]), "+f"(d[26]), "+f"(d[27]), "+f"(d[28]), "+f"(d[29]), "+f"(d[30]), "+f"(d[31])
               : "l"(da), "l"(db), "r"(sc));
}
__device__ __forceinline__ void wgmma_st128(float (&d)[64], uint64_t da, uint64_t db, int sc) {
  asm volatile("{.reg .pred p; setp.ne.b32 p,%66,0; wgmma.mma_async.sync.aligned.m64n128k16.f32.bf16.bf16 "
               "{%0,%1,%2,%3,%4,%5,%6,%7,%8,%9,%10,%11,%12,%13,%14,%15,%16,%17,%18,%19,%20,%21,%22,%23,%24,%25,%26,%27,%28,%29,%30,%31,%32,%33,%34,%35,%36,%37,%38,%39,%40,%41,%42,%43,%44,%45,%46,%47,%48,%49,%50,%51,%52,%53,%54,%55,%56,%57,%58,%59,%60,%61,%62,%63},%64,%65,p,1,1,0,1;}"
               : "+f"(d[0]), "+f"(d[1]), "+f"(d[2]), "+f"(d[3]), "+f"(d[4]), "+f"(d[5]), "+f"(d[6]), "+f"(d[7]), "+f"(d[8]), "+f"(d[9]), "+f"(d[10]), "+f"(d[11]), "+f"(d[12]), "+f"(d[13]), "+f"(d[14]), "+f"(d[15]), "+f"(d[16]), "+f"(d[17]), "+f"(d[18]), "+f"(d[19]), "+f"(d[20]), "+f"(d[21]), "+f"(d[22]), "+f"(d[23]), "+f"(d[24]), "+f"(d[25]), "+f"(d[26]), "+f"(d[27]), "+f"(d[28]), "+f"(d[29]), "+f"(d[30]), "+f"(d[31]), "+f"(d[32]), "+f"(d[33]), "+f"(d[34]), "+f"(d[35]), "+f"(d[36]), "+f"(d[37]), "+f"(d[38]), "+f"(d[39]), "+f"(d[40]), "+f"(d[41]), "+f"(d[42]), "+f"(d[43]), "+f"(d[44]), "+f"(d[45]), "+f"(d[46]), "+f"(d[47]), "+f"(d[48]), "+f"(d[49]), "+f"(d[50]), "+f"(d[51]), "+f"(d[52]), "+f"(d[53]), "+f"(d[54]), "+f"(d[55]), "+f"(d[56]), "+f"(d[57]), "+f"(d[58]), "+f"(d[59]), "+f"(d[60]), "+f"(d[61]), "+f"(d[62]), "+f"(d[63])
               : "l"(da), "l"(db), "r"(sc));
}

__device__ __forceinline__ void stsm4(uint32_t a, uint32_t r0, uint32_t r1, uint32_t r2, uint32_t r3) {
  asm volatile("stmatrix.sync.aligned.m8n8.x4.shared.b16 [%0],{%1,%2,%3,%4};" ::"r"(a), "r"(r0), "r"(r1), "r"(r2), "r"(r3) : "memory");
}
__device__ __forceinline__ void stsm4t(uint32_t a, uint32_t r0, uint32_t r1, uint32_t r2, uint32_t r3) {
  asm volatile("stmatrix.sync.aligned.m8n8.x4.trans.shared.b16 [%0],{%1,%2,%3,%4};" ::"r"(a), "r"(r0), "r"(r1), "r"(r2), "r"(r3) : "memory");
}
__device__ __forceinline__ void stsm2t(uint32_t a, uint32_t r0, uint32_t r1) {
  asm volatile("stmatrix.sync.aligned.m8n8.x2.trans.shared.b16 [%0],{%1,%2};" ::"r"(a), "r"(r0), "r"(r1) : "memory");
}
__device__ __forceinline__ void sts64(uint32_t a, uint32_t x, uint32_t y) { asm volatile("st.shared.v2.b32 [%0],{%1,%2};" ::"r"(a), "r"(x), "r"(y) : "memory"); }
__device__ __forceinline__ void st_async2u(uint32_t a, uint32_t x, uint32_t y, uint32_t bar) {
  asm volatile("st.async.weak.shared::cluster.mbarrier::complete_tx::bytes.v2.b32 [%0],{%1,%2},[%3];" ::"r"(a), "r"(x), "r"(y), "r"(bar) : "memory");
}
__device__ __forceinline__ void st_relaxed128(void* p, uint32_t x, uint32_t y, uint32_t z, uint32_t w) {
  asm volatile("{.reg .b128 v; mov.b128 v,{%1,%2,%3,%4}; st.relaxed.gpu.global.b128 [%0],v;}" ::"l"(p), "r"(x), "r"(y), "r"(z), "r"(w) : "memory");
}
__device__ __forceinline__ void st_relaxed64(void* p, uint32_t x, uint32_t y) {
  asm volatile("{.reg .b64 v; mov.b64 v,{%1,%2}; st.relaxed.gpu.global.b64 [%0],v;}" ::"l"(p), "r"(x), "r"(y) : "memory");
}
__device__ __forceinline__ uint4 ld_relaxed128(const void* p) {
  uint4 v;
  asm volatile("{.reg .b128 v; .reg .b64 lo, hi; ld.relaxed.gpu.global.b128 v,[%4]; mov.b128 {lo,hi},v; mov.b64 {%0,%1},lo; mov.b64 {%2,%3},hi;}" : "=r"(v.x), "=r"(v.y), "=r"(v.z), "=r"(v.w) : "l"(p) : "memory");
  return v;
}

__device__ __forceinline__ uint32_t pack_h2(float lo, float hi) {
  uint32_t r; asm("cvt.rn.satfinite.f16x2.f32 %0,%1,%2;" : "=r"(r) : "f"(hi), "f"(lo)); return r;
}
__device__ __forceinline__ void add_h2(float& lo, float& hi, uint32_t u, uint32_t v) {
  float a, b;
  asm("{.reg .b16 l, h; .reg .b32 s; add.rn.f16x2 s,%2,%3; mov.b32 {l,h},s; cvt.f32.f16 %0,l; cvt.f32.f16 %1,h;}" : "=f"(a), "=f"(b) : "r"(u), "r"(v));
  lo += a; hi += b;
}
__device__ __forceinline__ void mwait(uint32_t bar, uint32_t ph, int& spin) {
  asm volatile("{.reg .pred p, q;\nWAIT_LOOP:\n add.s32 %0,%0,1;\n setp.lt.s32 q,%0,%3;\n mbarrier.try_wait.parity.shared::cta.b64 p,[%1],%2;\n not.pred p,p;\n and.pred q,q,p;\n @q bra.uni WAIT_LOOP;\n}"
               : "+&r"(spin) : "r"(bar), "r"(ph), "n"(SPIN_TOT) : "memory");
}
__device__ __forceinline__ int keep(int x) { return __shfl_sync(0xffffffffu, x, threadIdx.x & 31); }
__device__ __forceinline__ uint32_t pin(uint32_t x) { asm volatile("" : "+r"(x)); return x; }
template <typename T> __device__ __forceinline__ T* pinp(T* x) { asm volatile("" : "+l"(x)); return x; }
__device__ __forceinline__ void st_async1u(uint32_t a, uint32_t x, uint32_t bar) {
  asm volatile("st.async.weak.shared::cluster.mbarrier::complete_tx::bytes.b32 [%0],%1,[%2];" ::"r"(a), "r"(x), "r"(bar) : "memory");
}
__device__ __forceinline__ uint32_t lds32(uint32_t a) { uint32_t v; asm volatile("ld.shared.b32 %0,[%1];" : "=r"(v) : "r"(a) : "memory"); return v; }
__device__ __forceinline__ uint2 lds64(uint32_t a) { uint2 v; asm volatile("ld.shared.v2.b32 {%0,%1},[%2];" : "=r"(v.x), "=r"(v.y) : "r"(a) : "memory"); return v; }

__device__ __forceinline__ void permute_cols(uint32_t tile, int tid, int n) {
#pragma unroll 2
  for (int it = tid; it < n; it += 128) {
    const int row = it >> 2, q = it & 3;
    const uint32_t a0 = tile + row * 128 + (((2 * q) ^ (row & 7)) << 4), a1 = tile + row * 128 + (((2 * q + 1) ^ (row & 7)) << 4);
    const uint4 u = lds128(a0), v = lds128(a1);
    sts128(a0, make_uint4(__byte_perm(u.x, u.y, 0x5410), __byte_perm(u.z, u.w, 0x5410), __byte_perm(v.x, v.y, 0x5410), __byte_perm(v.z, v.w, 0x5410)));
    sts128(a1, make_uint4(__byte_perm(u.x, u.y, 0x7632), __byte_perm(u.z, u.w, 0x7632), __byte_perm(v.x, v.y, 0x7632), __byte_perm(v.z, v.w, 0x7632)));
  }
}

__device__ __forceinline__ uint8_t* mkptr(uint32_t lo, uint32_t hi) { uint8_t* p; asm("mov.b64 %0,{%1,%2};" : "=l"(p) : "r"(lo), "r"(hi)); return p; }
__device__ __forceinline__ int uni(int x) { return __shfl_sync(0xffffffffu, x, 0); }

__device__ __forceinline__ bool elect_one() {
  uint32_t p; asm volatile("{.reg .pred q; elect.sync _|q, 0xffffffff; selp.u32 %0,1,0,q;}" : "=r"(p)); return p;
}
__device__ __forceinline__ uint64_t desc_at(uint64_t d, uint32_t off) {
  uint64_t r; asm("mov.b64 %0,{%1,%2};" : "=l"(r) : "r"((uint32_t)d + (off >> 4)), "r"((uint32_t)(d >> 32))); return r;
}
__device__ __forceinline__ uint32_t scale_bf16x2(uint32_t x, uint32_t s) { uint32_t r; asm("mul.rn.bf16x2 %0,%1,%2;" : "=r"(r) : "r"(x), "r"(s)); return r; }

__device__ __forceinline__ void stg128(void* p, const uint4& v) { asm volatile("st.global.v4.b32 [%0],{%1,%2,%3,%4};" ::"l"(p), "r"(v.x), "r"(v.y), "r"(v.z), "r"(v.w) : "memory"); }

__device__ __forceinline__ float quad_sum(float x) {
  const float a = __shfl_xor_sync(0xffffffffu, x, 1), b = __shfl_xor_sync(0xffffffffu, x, 2), c = __shfl_xor_sync(0xffffffffu, x, 3);
  return (x + a) + (b + c);
}
__device__ __forceinline__ float warp_sum(float x) {
  x = quad_sum(x);
  const float a = __shfl_xor_sync(0xffffffffu, x, 4), b = __shfl_xor_sync(0xffffffffu, x, 8), c = __shfl_xor_sync(0xffffffffu, x, 12);
  x = (x + a) + (b + c);
  return x + __shfl_xor_sync(0xffffffffu, x, 16);
}
__device__ __forceinline__ void ln_row(float4 (&v)[5]) {
  float t = 0.f;
#pragma unroll
  for (int m = 0; m < 5; m++) t += (v[m].x + v[m].y) + (v[m].z + v[m].w);
  const float lm = t * (1.f / 20);
  const float p = __shfl_sync(0xffffffffu, lm, 0);
  float q0 = 0.f, q1 = 0.f;
#pragma unroll
  for (int m = 0; m < 5; m++) {
    v[m].x -= lm; v[m].y -= lm; v[m].z -= lm; v[m].w -= lm;
    q0 += v[m].x * v[m].x + v[m].y * v[m].y; q1 += v[m].z * v[m].z + v[m].w * v[m].w;
  }
  const float d = lm - p;
  const float md = warp_sum(d) * (1.f / 32), q = warp_sum(fmaf(20.f * d, d, q0 + q1));
  const float rs = rsqrtf(fmaxf(q * (1.f / DM) - md * md, 0.f) + 1e-5f), sh = (d - md) * rs;
#pragma unroll
  for (int m = 0; m < 5; m++) { v[m].x = fmaf(v[m].x, rs, sh); v[m].y = fmaf(v[m].y, rs, sh); v[m].z = fmaf(v[m].z, rs, sh); v[m].w = fmaf(v[m].w, rs, sh); }
}
__device__ __forceinline__ void ln0_load(const bf16* __restrict__ x, uint2 (&u)[5], int row, int lane) {
#pragma unroll
  for (int m = 0; m < 5; m++) u[m] = *reinterpret_cast<const uint2*>(x + (size_t)row * DM + m * 128 + lane * 4);
}
__device__ __forceinline__ void ln0_copy(const uint2 (&u)[5], int row, int lane) {
#pragma unroll
  for (int m = 0; m < 5; m++) stg128(g_x + (size_t)row * DM + m * 128 + lane * 4, make_uint4(u[m].x << 16, u[m].x & 0xFFFF0000u, u[m].y << 16, u[m].y & 0xFFFF0000u));
}
__device__ __forceinline__ void ln0_row(const uint2 (&u)[5], int row, int lane) {
  float4 v[5];
#pragma unroll
  for (int m = 0; m < 5; m++) v[m] = make_float4(bf_lo(u[m].x), bf_hi(u[m].x), bf_lo(u[m].y), bf_hi(u[m].y));
  ln_row(v);
  uint8_t* dst = g_xn[row >> 5] + ((row >> 3) & 3) * 4096 + (lane >> 4) * 1024 + (row & 7) * 128 + ((((lane >> 1) ^ row) & 7) << 4) + (lane & 1) * 8;
#pragma unroll
  for (int m = 0; m < 5; m++) *reinterpret_cast<uint2*>(dst + m * 16384) = make_uint2(pack_bf16(v[m].x, v[m].y), pack_bf16(v[m].z, v[m].w));
}

#define NOWORK 0
__device__ __forceinline__ void prep_row(const uint2 (&u)[5], const bf16* __restrict__ mem0, int k, int r, int lane) {
  const uint4 sent = make_uint4(SENT, SENT, SENT, SENT);
  if (k + 1 < NSTEP) {
    uint8_t* ex = ex_window(g_ex);
#pragma unroll
    for (int h = 0; h < 2; h++) {
      const int p = r * 40 + h * 32 + lane;
      if (h == 0 || lane < 8) {
        uint4 v = sent;
        if (k + 1 == LAG && (p & 8)) v = *reinterpret_cast<const uint4*>(mem0 + (p & 7) * DM + (p >> 4) * 8);
        stg128(ex + EX_M + (k + 1) * 20480 + p * 16, v);
      } else if (lane < 14) stg128(ex + EX_FLAG + (k + 1) * 3072 + (r * 6 + lane - 8) * 16, sent);
    }
  }
  if (k < LAG || k >= NSEG || NOWORK) {
    uint8_t* z = g_xn[k] + (r >> 3) * 4096 + (k < NSEG ? 2048 : 0) + (lane >> 4) * 1024 + (r & 7) * 128 + (lane & 15) * 8;
#pragma unroll
    for (int m = 0; m < 5; m++) *reinterpret_cast<uint2*>(z + m * 16384) = make_uint2(0, 0);
  }
  if (k < NSEG) {
    ln0_copy(u, k * 32 + r, lane);
    ln0_row(u, k * 32 + r, lane);
  }
}
__device__ __forceinline__ void pre_work(const bf16* __restrict__ x, const bf16* __restrict__ mem0, int cta, int tid) {
  constexpr int NT = 96 * 128;
  const int gt = cta * 128 + tid;
  uint8_t* ex = ex_window(g_ex);
#pragma unroll 1
  for (int row = cta + 96 * (tid >> 5); row < (NOWORK == 2 ? NSTEP : NPRE) * 32; row += 384) {
    uint2 u[5];
    ln0_load(x, u, min(row, SEQ - 1), tid & 31);
    prep_row(u, mem0, row >> 5, row & 31, tid & 31);
  }
#pragma unroll 1
  for (int i = gt; i < MAIL_BYTES / 16; i += NT) {
    stg128(ex + EX_MAIL + i * 16, make_uint4(SENT, SENT, SENT, SENT));
    stg128(ex + EX_MAIL + (1 << 20) + i * 16, make_uint4(SENT, SENT, SENT, SENT));
  }
  const int p = NT - 1 - gt;
  if (p < 1280) stg128(ex + EX_M + p * 16, *reinterpret_cast<const uint4*>(mem0 + (p & 7) * DM + (p >> 4) * 8));
  if (p < 192) stg128(ex + EX_FLAG + p * 16, make_uint4(0, 0, 0, 0));
  if (gt < 8 * CN_NUM) stg128(&g_cnt[0][0] + gt * 4, make_uint4(0, 0, 0, 0));
}
__device__ __forceinline__ void pre_wait(int which, uint32_t n, int& spin) {
  uint32_t old;
  asm volatile("atom.acq_rel.gpu.global.add.u32 %0,[%1],1;" : "=r"(old) : "l"(&g_ticket[which][0]) : "memory");
  const uint32_t target = (old / n + 1) * 96;
  while ((int)(ld_acquire(&g_ticket[0][0]) - target) < 0 && spin < SPIN_TOT) spin += 16;
  fence_async_all();
}

namespace C {
constexpr int NKR = 37;
constexpr int OFF_WQ = 0, OFF_WK = 81920;
constexpr int OFF_YO = 163840, OFF_YV = OFF_YO + 6144;
constexpr int OFF_M = 176128;
__host__ __device__ constexpr int og_off(int c) { return c ? OFF_M + 14336 + c * 2048 : 229376; }
constexpr int OFF_KT = 196608;
constexpr int OFF_XT = OFF_KT + 10240;
constexpr int OFF_VT = OFF_XT + 7168;
constexpr int OFF_XM = OFF_VT + 11392;
constexpr int OFF_PT = OFF_XM + 2560;
constexpr int KS = 1280, VS = 1408;
__host__ __device__ constexpr int slot_off(int p) { return p == 2 ? OFF_M : OFF_KT + (p % 3) * 16384; }
constexpr int OFF_ONE = 231424;
constexpr int OFF_BAR = 231552;
constexpr int OFF_SAFE = OFF_BAR + 144;
constexpr int OFF_TS = OFF_BAR + 256;
constexpr int SMEM = 232448;
constexpr uint32_t SB0 = 1024;
constexpr int BAR_F = OFF_BAR, BAR_XM = BAR_F + 40, BAR_XT = BAR_F + 48, BAR_OG = BAR_F + 56, BAR_E = OFF_BAR + 64, BAR_MOK = BAR_E + 40,
              BAR_M = OFF_BAR + 112, BAR_XF = OFF_BAR + 120, BAR_MF = OFF_BAR + 128, FLG_REDO = OFF_BAR + 136, BAR_W = OFF_BAR + 208;
constexpr int NB_PRO = 1, NB_RD = 2, NB_MR = 3, NB_QK = 4, NB_SM = 5, NB_VA = 6, NB_VQ = 7, NB_A = 8, NB_Q = 9, NB_C = 10, NB_WQ = 11, NB_QI = 12, NB_SI = 13, NB_WV = 14, NB_V = 15;
#define B1 600
#define AD0 16
#define AD1 128
#define AD2 16
#define AD3 128
#define BMX 1200
#define B2 800
#define FLP 1
#define OSG 2
#define OST 7
#define NBX 1
#define P1U 4
#define QIE 4
#define SIE 2
#define WOE 1
#define OGF 0
#define VSP 8
#define RFK 5
#define PFD 3
#define WOL 0
constexpr uint32_t SCQ = 0x3A003A00;
constexpr float SCE = 0.07216878364870322f * 1.4426950408889634f * 2048;
}

#define CBAR_SYNC(id, n) bar_sync(id, n)
#define CBAR_ARRIVE(id, n) bar_arrive(id, n)

__device__ __forceinline__ uint64_t wdesc(int off) { return mkdesc(C::SB0 + off, 8192, 1024); }
__device__ __forceinline__ uint64_t mdesc(int k) { return mkdesc_ns(C::SB0 + C::OFF_M + k * 512, 256, 128); }
__device__ __forceinline__ uint64_t tdesc(int k) { return mkdesc(C::SB0 + C::slot_off(k >> 3) + ((k >> 2) & 1) * 1024 + (k & 3) * 32, 16, 2048); }

__device__ __forceinline__ int dh_row(int n) { return (n & ~63) + (n & 32) + ((n >> 1) & 3) * 8 + ((n >> 3) & 3) * 2 + (n & 1); }
template <bool IS_O>
__device__ __forceinline__ void stage_box(const CUtensorMap& tm, uint32_t sb, int p, int cta, int rank) {
  using namespace C;
  const uint32_t bar = sb + BAR_W + 8 * p;
  const int head = cta / 3, col = head * DH + rank * 64;
  mbar_expect_tx(bar, 16384);
  if (!IS_O) tma2d(sb + OFF_WK + p * 16384, &tm, col, p * 128, bar);
  else for (int b = 2 * p - 1; b <= 2 * p; b++)
    tma2d(sb + OFF_WQ + (b + 1) * 8192, &tm, b < 0 ? 576 : (3 * rank + b / 3) * 64, b < 0 ? col : head * DH + ((rank + b) % 3) * 64, bar);
}
template <bool IS_O>
__device__ __forceinline__ void load_weights_rs(uint32_t (&wf)[C::NKR][4], const CUtensorMap& tms, const CUtensorMap& tm, int cta, int rank, uint32_t sb, int tid0, int& spin) {
  using namespace C;
  constexpr int STAGE = IS_O ? OFF_WQ : OFF_WK, YOFF = IS_O ? OFF_YO : OFF_YV, NB = IS_O ? NB_C : NB_V;
  const int i = (tid0 >> 3) & 3, n0 = (tid0 & 7) + (i >> 1) * 8;
  const int chunk = 2 * ((tid0 >> 5) & 3) + (i & 1);
  const int r0 = IS_O ? dh_row(n0) : n0, r1 = IS_O ? dh_row(n0 + 16) : n0 + 16;
  const uint32_t a0 = sb + STAGE + r0 * 128 + ((chunk ^ (r0 & 7)) << 4), a1 = sb + STAGE + r1 * 128 + ((chunk ^ (r1 & 7)) << 4);
#pragma unroll
  for (int p = 0; p < 5; p++) {
    mwait(sb + BAR_W + 8 * p, 0, spin);
    if (IS_O) PTS(8 + p);
    if (p + NBX < 5) { if ((tid0 & 127) == 96) stage_box<IS_O>(tms, sb, p + NBX, cta, rank); __syncwarp(); }
    if (IS_O) permute_cols(sb + STAGE + p * 16384, tid0, 512);
    else {
#pragma unroll 1
      for (int it = tid0 & 127; it < 256; it += 128) {
        const uint32_t base = sb + STAGE + p * 16384 + (it >> 1) * 128;
        const int sw = ((it >> 1) & 7) ^ ((it & 1) * 4);
        const uint4 u0 = lds128(base + (sw << 4)), u1 = lds128(base + ((sw ^ 1) << 4)), u2 = lds128(base + ((sw ^ 2) << 4)), u3 = lds128(base + ((sw ^ 3) << 4));
        sts128(base + (sw << 4), make_uint4(u0.x, u1.x, u2.x, u3.x)); sts128(base + ((sw ^ 1) << 4), make_uint4(u0.y, u1.y, u2.y, u3.y));
        sts128(base + ((sw ^ 2) << 4), make_uint4(u0.z, u1.z, u2.z, u3.z)); sts128(base + ((sw ^ 3) << 4), make_uint4(u0.w, u1.w, u2.w, u3.w));
      }
    }
    bar_sync(NB, 128);
#pragma unroll
    for (int k = 8 * p; k < 8 * p + 8; k++) {
      if (k < NKR) ldsm4t(wf[k < NKR ? k : 0], ((k & 1) ? a1 : a0) + (k >> 1) * 4096);
      else {
        const int n = k * 16 + ((tid0 & 127) >> 3), r = IS_O ? dh_row(n) : n, c = tid0 & 7;
        sts128(sb + YOFF + (n - NKR * 16) * 128 + ((c ^ (n & 7)) << 4), lds128(sb + STAGE + r * 128 + ((c ^ (r & 7)) << 4)));
      }
    }
    fence_async();
    bar_sync(NB, 128);
    if ((tid0 & 127) == 0) {
      mbar_expect_tx(sb + BAR_W + 8 * p, 16384);
      tma2d(sb + STAGE + p * 16384, &tm, (cta / 3) * DH + rank * 64, p * 128, sb + BAR_W + 8 * p);
    }
    __syncwarp();
  }
  PTS(IS_O ? 13 : 14);
  CBAR_SYNC(NB_PRO, 384);
}
template <int STRIDE>
__device__ __forceinline__ void store_mem(const float (&d)[8], uint32_t base, int tid) {
  const int m = (tid >> 3) & 3;
  stsm4(base + (((tid >> 5) & 3) * 2 + (m & 1)) * STRIDE + (m >> 1) * 640 + (tid & 7) * 16, pack_bf16(d[0], d[1]), pack_bf16(d[2], d[3]),
        pack_bf16(d[4], d[5]), pack_bf16(d[6], d[7]));
}

__device__ __forceinline__ void load_pair(uint32_t sb, int i, int p, uint32_t slot, uint32_t ph, int& spin) {
  using namespace C;
  mwait(sb + BAR_E + 8 * p, ph, spin);
  if (elect_one()) bulk_g2s_mc(sb + slot, g_xn[i] + p * 16384, 16384, sb + BAR_F + 8 * p);
}
__device__ __forceinline__ void release_round(uint32_t sb, int p, int lane) {
  if (lane < (p == 2 ? 3 : 1)) mbar_arrive_cluster(mapa(sb, p == 2 ? lane : p) + C::BAR_E + 8 * (3 + p));
}

template <int K0, int K1>
__device__ __forceinline__ void v_mem_pass(float (&d)[8], const uint32_t (&wf)[C::NKR][4]) {
  using namespace C;
  wg_fence();
#pragma unroll
  for (int k = K0; k < K1; k++) {
    if (k < NKR) wgmma_rs16(d, wf[k < NKR ? k : 0], mdesc(k), k != 32);
    else wgmma_ts16(d, wdesc(OFF_YV + (k - NKR) * 2048), mdesc(k), 1);
  }
  wg_commit();
}
__device__ __forceinline__ void chain_v(const CUtensorMap& tmWv, const CUtensorMap& tmWk, const uint32_t sb, const int tid0, const int cta, const int rank) {
  using namespace C;
  asm volatile("setmaxnreg.inc.sync.aligned.u32 208;");
  int spin = 0;
  uint32_t wf[NKR][4];
  const int wu = uni((tid0 >> 5) & 3);
  const uint32_t slot = rank == 2 ? OFF_M : OFF_KT + rank * 16384;
  load_weights_rs<false>(wf, tmWv, tmWk, cta, rank, sb, tid0, spin);
  PTS(5);
#pragma unroll 1
  for (int i = 0; i < NSTEP; i++) {
    {
      float d[32];
      if (i > 0) CBAR_SYNC(NB_WV, 256);
#pragma unroll
      for (int p = 0; p < 5; p++) {
        mwait(sb + BAR_F + 8 * p, i & 1, spin);
        TS(i, 25 + p);
        wg_fence();
#pragma unroll
        for (int k = 8 * p; k < 8 * p + 8; k++) {
          if (k < NKR) wgmma_rs64(d, wf[k < NKR ? k : 0], tdesc(k), k);
          else wgmma_ts64(d, wdesc(OFF_YV + (k - NKR) * 2048), tdesc(k), 1);
          if (k == 8 * p + 1 && p >= 1 && p <= 3) {
            wg_commit(); wg_wait<1>();
            release_round(sb, p - 1, tid0 & 31);
          }
          if (k == 8 * p + RFK && (p == 1 || p == 2)) {
            wg_commit();
            if (rank == p - 1 && wu == 0) load_pair(sb, i, p + 2, slot_off(p + 2), i & 1, spin);
            wg_fence();
          }
        }
        wg_commit();
      }
      wg_wait<0>();
      TS(i, 23);
      CBAR_SYNC(NB_RD, 256);
      const int tid = fresh(tid0) & 127, m = (tid >> 3) & 3;
      if (tid < 8) mbar_expect_tx(sb + BAR_F + 8 * tid, tid < 5 ? 16384 : tid == 5 ? 2560 : tid == 6 ? 7168 : 4096);
      if (tid < 3 && tid != rank) mbar_arrive_cluster(mapa(sb, tid) + BAR_XF);
      const uint32_t a = sb + OFF_VT + 256 + ((tid >> 5) * 2 + (m & 1)) * VS + (m >> 1) * 640 + (tid & 7) * 16;
#pragma unroll
      for (int s = 0; s < 4; s++)
        stsm4(a + s * 128, pack_bf16(d[8 * s], d[8 * s + 1]), pack_bf16(d[8 * s + 2], d[8 * s + 3]),
              pack_bf16(d[8 * s + 4], d[8 * s + 5]), pack_bf16(d[8 * s + 6], d[8 * s + 7]));
      if (tid < 80) sts128(sb + (tid < 72 ? OFF_VT + (tid >> 3) * VS : OFF_PT + 1280) + (tid & 7) * 16, make_uint4(0, 0, 0, 0));
      fence_async();
    }
    mwait(sb + BAR_XF, i & 1, spin);
    CBAR_ARRIVE(NB_QK, 384);
    const uint32_t* xc = &g_cnt[CN_X + i + 1][0];
    const uint32_t xn = i + 1 < LAG || NOWORK ? 16 : 48;
    bool seen = NOWORK == 2 || i + 1 < NPRE;
    if (wu == 0 && !seen) { seen = ld_acquire(xc) >= xn; fence_async_all(); }
    CBAR_SYNC(NB_QI, 256);
    float d[8];
    v_mem_pass<32, 40>(d, wf);
    CBAR_SYNC(NB_SM, 256);
    wg_wait<0>();
    if (__builtin_expect(lds32(sb + FLG_REDO), 0)) { v_mem_pass<32, 40>(d, wf); wg_wait<0>(); }
    if ((tid0 & 31) < 3 && (tid0 & 31) != rank) mbar_arrive_cluster(mapa(sb, tid0 & 31) + BAR_MF);
    v_mem_pass<0, 32>(d, wf);
    wg_wait<0>();
    TS(i, 24);
    const int tid = fresh(tid0);
    if ((tid & 31) == 0) mbar_arrive_cluster(mapa(sb, 2) + BAR_E + 16);
    store_mem<VS>(d, sb + OFF_VT + 128, tid);
    fence_async();
    CBAR_ARRIVE(NB_VA, 256);
    CBAR_ARRIVE(NB_VQ, 256);
    if (wu == 0 && i + 1 < NSTEP) {
      if (__builtin_expect(!seen, 0)) { while (ld_acquire(xc) < xn && spin < SPIN_TOT) spin += 16; fence_async_all(); }
      load_pair(sb, i + 1, rank, slot, i & 1, spin);
      TS(i + 1, 37);
    }
    TS_FLUSH(i - 1);
    __syncwarp();
  }
  CBAR_ARRIVE(NB_WV, 256);
  if (spin >= SPIN_TOT) g_err = 3;
}

__device__ __forceinline__ float quad_max(float x) {
  const float a = __shfl_xor_sync(0xffffffffu, x, 1), b = __shfl_xor_sync(0xffffffffu, x, 2), c = __shfl_xor_sync(0xffffffffu, x, 3);
  return fmaxf(fmaxf(x, a), fmaxf(b, c));
}
__device__ __forceinline__ float max10(const float (&y)[10]) {
  return fmaxf(fmaxf(fmaxf(fmaxf(y[0], y[1]), fmaxf(y[2], y[3])), fmaxf(fmaxf(y[4], y[5]), fmaxf(y[6], y[7]))), fmaxf(y[8], y[9]));
}
__device__ __forceinline__ float sum10(const float (&y)[10]) {
  return (((y[0] + y[1]) + (y[2] + y[3])) + ((y[4] + y[5]) + (y[6] + y[7]))) + (y[8] + y[9]);
}
__device__ __forceinline__ float rcp(float x) { float y; asm("rcp.approx.ftz.f32 %0,%1;" : "=f"(y) : "f"(x)); return y; }

__device__ __forceinline__ void signal_o(int i, int cta) { csignal(CN_O + i * 5 + min(cta / 19, 4)); }

__device__ __forceinline__ void chain_q(const bf16* x0, const bf16* mem0, const uint32_t sb, const int tid0, const int cta, const int rank) {
  using namespace C;
  asm volatile("setmaxnreg.dec.sync.aligned.u32 96;");
  int spin = 0;
  PTS(0);
  pre_work(x0, mem0, cta, tid0 & 127);
  PTS(3);
  CBAR_SYNC(NB_Q, 128);
  PTS(2);
  if (tid0 < 160) {
    if (tid0 == 128) pre_wait(0, 96, spin);
    __syncwarp();
    load_pair(sb, 0, rank, rank == 2 ? OFF_M : OFF_KT + rank * 16384, 1, spin);
  }
  PTS(4);
  CBAR_SYNC(NB_PRO, 384);
  mwait(sb + BAR_W, 1, spin);
  PTS(6);
  const int wu = uni((tid0 >> 5) & 3);
  uint4 ov[4] = {};
  uint8_t* op = &g_o[ORING - 1][cta][(tid0 & 124) * 32];
  const uint32_t o0 = ((tid0 ^ (tid0 >> 2)) & 3) * 16 + (tid0 & 16) * 4;
#pragma unroll 1
  for (int i = 0; i < NSTEP; i++) {
    const int ph = i & 1;
    uint32_t qf[4][4];
    {
      float d[64];
#define QK_STEP(K, SC) wgmma_st128(d, desc_at(mkdesc(SB0 + ((K) >> 2) * 1024 + ((K) & 3) * 32, 16, 2048), so), \
                                   desc_at(mkdesc(SB0 + OFF_WQ + (K) * 2048, OFF_WK - OFF_WQ, 1024), p * 16384), SC)
      int p = 0;
      uint32_t so = OFF_KT;
      mwait(sb + BAR_F, ph, spin);
      TS(i, 0);
      wg_fence();
#pragma unroll
      for (int k = 0; k < 8; k++) {
        QK_STEP(k, k);
        if (k == OST) {
          wg_commit();
          mwait(sb + BAR_F, ph, spin);
#pragma unroll
          for (int h = 0; h < 4; h++) stg128(op + (h & 1) * 4096 + (o0 ^ ((h >> 1) * 64)), ov[h]);
          if (i > 0) CBAR_ARRIVE(NB_MR, 160);
          if (k < 7) wg_fence();
        }
      }
      if (OST < 7) wg_commit();
#pragma unroll 1
      for (p = 1; p < 5; p++) {
        static_assert(OFF_KT - OFF_M == 5 << 12, "");
        so = OFF_M + (((0x95095u >> (4 * p)) & 15) << 12);
        if (i == 0) { mwait(sb + BAR_W + 8 * p, 1, spin); PTS(14 + p); }
        mwait(sb + BAR_F + 8 * p, ph, spin);
        wg_fence();
#pragma unroll
        for (int k = 0; k < 8; k++) {
          QK_STEP(k, 1);
          if (k == 1) {
            wg_commit(); wg_wait<1>();
            release_round(sb, p - 1, p < 4 ? tid0 & 31 : 32);
          }
        }
        wg_commit();
      }
#undef QK_STEP
      wg_wait<0>();
      TS(i, 1);
      CBAR_SYNC(NB_RD, 256);
      TSB(i, 2);
      const int tid = fresh(tid0), w = (tid >> 5) & 3, m = (tid >> 3) & 3;
      const uint32_t a = sb + OFF_KT + (m >> 1) * KS + (1 + w + 5 * (m & 1)) * 128 + (tid & 7) * 16;
#pragma unroll
      for (int s = 0; s < 4; s++)
        stsm4t(a + s * 2 * KS, pack_bf16(d[32 + 8 * s], d[33 + 8 * s]), pack_bf16(d[34 + 8 * s], d[35 + 8 * s]),
               pack_bf16(d[36 + 8 * s], d[37 + 8 * s]), pack_bf16(d[38 + 8 * s], d[39 + 8 * s]));
      fence_async();
      CBAR_ARRIVE(NB_QK, 384);
#pragma unroll
      for (int kk = 0; kk < 4; kk++)
#pragma unroll
        for (int j = 0; j < 4; j++) asm volatile("{.reg .b32 t; cvt.rn.bf16x2.f32 t,%1,%2; mul.rn.bf16x2 %0,t,%3;}" : "=r"(qf[kk][j]) : "f"(d[8 * kk + 2 * j + 1]), "f"(d[8 * kk + 2 * j]), "r"(SCQ));
    }
    CBAR_SYNC(NB_SI, 256);
    uint32_t pf[5][4];
    {
      float y0[10], y1[10];
      const int tidf = fresh(tid0), lane = tidf & 31;
      {
        float x[40];
        wg_fence();
#pragma unroll
        for (int kk = 0; kk < 4; kk++) wgmma_rt80(x, qf[kk], mkdesc_ns(SB0 + OFF_KT + kk * 2 * KS, KS, 128), kk);
        wg_commit();
        wg_wait<0>();
#pragma unroll
        for (int j = 0; j < 5; j++) { y0[2 * j] = x[4 * j]; y0[2 * j + 1] = x[4 * j + 1]; y1[2 * j] = x[22 + 4 * j]; y1[2 * j + 1] = x[23 + 4 * j]; }
      }
      TS(i, 17);
      const uint32_t xo = OFF_XT + (wu * (wu + 3) / 2) * 256 + lane * 16, x2 = xo + (wu >> 1) * 512 + 512 - lane * 8;
      {
        const uint4 h0 = make_uint4(pack_h2(y0[0], y0[1]), pack_h2(y1[0], y1[1]), pack_h2(y0[2], y0[3]), pack_h2(y1[2], y1[3]));
        const uint4 h1 = make_uint4(pack_h2(y0[4], y0[5]), pack_h2(y1[4], y1[5]), pack_h2(y0[6], y0[7]), pack_h2(y1[6], y1[7]));
        const uint32_t h2 = wu == 1 ? h1.x : pack_h2(y0[8], y0[9]), h3 = wu == 1 ? h1.y : pack_h2(y1[8], y1[9]);
        const uint32_t rb1 = mapa(sb, (rank + 1) % 3), rb2 = mapa(sb, (rank + 2) % 3);
        st_async4u(rb1 + xo + 3584, h0, rb1 + BAR_XT);
        st_async4u(rb2 + xo, h0, rb2 + BAR_XT);
        if (wu >= 2) { st_async4u(rb1 + xo + 4096, h1, rb1 + BAR_XT); st_async4u(rb2 + xo + 512, h1, rb2 + BAR_XT); }
        if (wu & 1) { st_async2u(rb1 + x2 + 3584, h2, h3, rb1 + BAR_XT); st_async2u(rb2 + x2, h2, h3, rb2 + BAR_XT); }
      }
      TS(i, 18);
      const int lim = 8 * wu + (lane >> 2) + 8 - 2 * (lane & 3);
#pragma unroll
      for (int j = 2; j < 10; j++)
        if (8 * (j >> 1) + (j & 1) > lim) { y0[j] = -INFINITY; y1[j] = -INFINITY; }
      mwait(sb + BAR_XT, ph, spin);
      TS(i, 19);
      {
        const uint4 u0 = lds128(sb + xo), v0 = lds128(sb + xo + 3584);
        uint2 u2 = make_uint2(0, 0), v2 = u2;
        if (wu & 1) { u2 = lds64(sb + x2); v2 = lds64(sb + x2 + 3584); }
        uint4 u1 = make_uint4(u2.x, u2.y, 0, 0), v1 = make_uint4(v2.x, v2.y, 0, 0);
        if (wu >= 2) { u1 = lds128(sb + xo + 512); v1 = lds128(sb + xo + 4096); }
        __syncwarp();
        if (lane == 0) mbar_arrive_cluster(mapa(sb, 0) + BAR_E);
        add_h2(y0[0], y0[1], u0.x, v0.x); add_h2(y1[0], y1[1], u0.y, v0.y); add_h2(y0[2], y0[3], u0.z, v0.z); add_h2(y1[2], y1[3], u0.w, v0.w);
        add_h2(y0[4], y0[5], u1.x, v1.x); add_h2(y1[4], y1[5], u1.y, v1.y); add_h2(y0[6], y0[7], u1.z, v1.z); add_h2(y1[6], y1[7], u1.w, v1.w);
        add_h2(y0[8], y0[9], u2.x, v2.x); add_h2(y1[8], y1[9], u2.y, v2.y);
      }
      const float m0 = quad_max(max10(y0)) * -SCE, m1 = quad_max(max10(y1)) * -SCE;
#pragma unroll
      for (int j = 0; j < 5; j++) {
        pf[j >> 1][2 * (j & 1)] = pack_bf16(ex2(fmaf(y0[2 * j], SCE, m0)), ex2(fmaf(y0[2 * j + 1], SCE, m0)));
        pf[j >> 1][2 * (j & 1) + 1] = tidf >> (10 + j);
        pf[(j + 5) >> 1][2 * ((j + 5) & 1)] = tidf >> (20 + j);
        pf[(j + 5) >> 1][2 * ((j + 5) & 1) + 1] = pack_bf16(ex2(fmaf(y1[2 * j], SCE, m1)), ex2(fmaf(y1[2 * j + 1], SCE, m1)));
      }
    }
#pragma unroll
    for (int q = 0; q < 20; q++) pf[q >> 2][q & 3] = pin(pf[q >> 2][q & 3]);
    CBAR_SYNC(NB_VQ, 256);
    TSB(i, 20);
    {
      float o[32], sm[4];
      wg_fence();
#pragma unroll
      for (int q = 0; q < 5; q++) wgmma_rs8(sm, pf[q], mkdesc_ns(SB0 + OFF_ONE, 0, 0), q);
#pragma unroll
      for (int q = 0; q < 5; q++) wgmma_rs64(o, pf[q], mkdesc_ns(SB0 + OFF_VT + 128 + q * 256, 128, VS), q);
      wg_commit();
      const int tid = fresh(tid0);
      op = &g_o[i % ORING][cta][(tid & 124) * 32];
      wg_wait<0>();
      TS(i, 21);
      if ((tid & 31) == 0) mbar_arrive_cluster(mapa(sb, 1) + BAR_E + 8);
      const float s0 = rcp(sm[0]), s1 = rcp(sm[2]);
#pragma unroll
      for (int h = 0; h < 2; h++) {
        const float* x = o + 16 * h;
        ov[2 * h] = make_uint4(pin(pack_bf16(x[0] * s0, x[1] * s0)), pin(pack_bf16(x[4] * s0, x[5] * s0)), pin(pack_bf16(x[8] * s0, x[9] * s0)), pin(pack_bf16(x[12] * s0, x[13] * s0)));
        ov[2 * h + 1] = make_uint4(pin(pack_bf16(x[2] * s1, x[3] * s1)), pin(pack_bf16(x[6] * s1, x[7] * s1)), pin(pack_bf16(x[10] * s1, x[11] * s1)), pin(pack_bf16(x[14] * s1, x[15] * s1)));
      }
      TS(i, 22);
      if (i + 1 < NSTEP) CBAR_SYNC(NB_WQ, 256); else CBAR_ARRIVE(NB_WQ, 256);
    }
  }
#pragma unroll
  for (int h = 0; h < 4; h++) stg128(op + (h & 1) * 4096 + (o0 ^ ((h >> 1) * 64)), ov[h]);
  CBAR_SYNC(NB_Q, 128);
  if (tid0 == 224) signal_o(NSTEP - 1, cta);
  if (spin >= SPIN_TOT) g_err = 2;
}

template <int NL> __device__ __forceinline__ void poll(uint4 (&x)[NL], const uint8_t* mb, uint32_t tag, int& spin);
template <> __device__ __forceinline__ void poll<4>(uint4 (&x)[4], const uint8_t* mb, uint32_t tag, int& spin) {
  asm volatile("{.reg .pred p<6>, q; .reg .b128 v; .reg .b32 t;\n"
               " ld.relaxed.gpu.global.b128 v,[%17+0]; mov.b128 {%0,%1,%2,%3},v;\n"
               " ld.relaxed.gpu.global.b128 v,[%17+512]; mov.b128 {%4,%5,%6,%7},v;\n"
               " ld.relaxed.gpu.global.b128 v,[%17+1024]; mov.b128 {%8,%9,%10,%11},v;\n"
               " ld.relaxed.gpu.global.b128 v,[%17+1536]; mov.b128 {%12,%13,%14,%15},v;\n"
               "POLL_LOOP:\n add.s32 %16,%16,16;\n"
               " lop3.b32 t,%0,%18,1,0x28; setp.ne.b32 p0,t,0;\n"
               " lop3.b32 t,%4,%18,1,0x28; setp.ne.b32 p1,t,0;\n"
               " lop3.b32 t,%8,%18,1,0x28; setp.ne.b32 p2,t,0;\n"
               " lop3.b32 t,%12,%18,1,0x28; setp.ne.b32 p3,t,0;\n"
               " or.pred q,p0,p1; or.pred q,q,p2; or.pred q,q,p3; setp.lt.and.s32 q,%16,%19,q; vote.sync.any.pred q,q,0xffffffff;\n"
               " mov.b128 v,{%0,%1,%2,%3}; @p0 ld.relaxed.gpu.global.b128 v,[%17+0]; mov.b128 {%0,%1,%2,%3},v;\n"
               " mov.b128 v,{%4,%5,%6,%7}; @p1 ld.relaxed.gpu.global.b128 v,[%17+512]; mov.b128 {%4,%5,%6,%7},v;\n"
               " mov.b128 v,{%8,%9,%10,%11}; @p2 ld.relaxed.gpu.global.b128 v,[%17+1024]; mov.b128 {%8,%9,%10,%11},v;\n"
               " mov.b128 v,{%12,%13,%14,%15}; @p3 ld.relaxed.gpu.global.b128 v,[%17+1536]; mov.b128 {%12,%13,%14,%15},v;\n"
               " @q bra.uni POLL_LOOP;\n}"
               : "=&r"(x[0].x), "=&r"(x[0].y), "=&r"(x[0].z), "=&r"(x[0].w), "=&r"(x[1].x), "=&r"(x[1].y), "=&r"(x[1].z), "=&r"(x[1].w), "=&r"(x[2].x), "=&r"(x[2].y), "=&r"(x[2].z), "=&r"(x[2].w), "=&r"(x[3].x), "=&r"(x[3].y), "=&r"(x[3].z), "=&r"(x[3].w), "+&r"(spin)
               : "l"(mb), "r"(tag), "n"(SPIN_TOT) : "memory");
}
template <> __device__ __forceinline__ void poll<6>(uint4 (&x)[6], const uint8_t* mb, uint32_t tag, int& spin) {
  asm volatile("{.reg .pred p<6>, q; .reg .b128 v; .reg .b32 t;\n"
               " ld.relaxed.gpu.global.b128 v,[%25+0]; mov.b128 {%0,%1,%2,%3},v;\n"
               " ld.relaxed.gpu.global.b128 v,[%25+512]; mov.b128 {%4,%5,%6,%7},v;\n"
               " ld.relaxed.gpu.global.b128 v,[%25+1024]; mov.b128 {%8,%9,%10,%11},v;\n"
               " ld.relaxed.gpu.global.b128 v,[%25+1536]; mov.b128 {%12,%13,%14,%15},v;\n"
               " ld.relaxed.gpu.global.b128 v,[%25+2048]; mov.b128 {%16,%17,%18,%19},v;\n"
               " ld.relaxed.gpu.global.b128 v,[%25+2560]; mov.b128 {%20,%21,%22,%23},v;\n"
               "POLL_LOOP:\n add.s32 %24,%24,16;\n"
               " lop3.b32 t,%0,%2,%26,0x7e; and.b32 t,t,1; setp.ne.b32 p0,t,0;\n"
               " lop3.b32 t,%4,%6,%26,0x7e; and.b32 t,t,1; setp.ne.b32 p1,t,0;\n"
               " lop3.b32 t,%8,%10,%26,0x7e; and.b32 t,t,1; setp.ne.b32 p2,t,0;\n"
               " lop3.b32 t,%12,%14,%26,0x7e; and.b32 t,t,1; setp.ne.b32 p3,t,0;\n"
               " lop3.b32 t,%16,%18,%26,0x7e; and.b32 t,t,1; setp.ne.b32 p4,t,0;\n"
               " lop3.b32 t,%20,%22,%26,0x7e; and.b32 t,t,1; setp.ne.b32 p5,t,0;\n"
               " or.pred q,p0,p1; or.pred q,q,p2; or.pred q,q,p3; or.pred q,q,p4; or.pred q,q,p5; setp.lt.and.s32 q,%24,%27,q; vote.sync.any.pred q,q,0xffffffff;\n"
               " mov.b128 v,{%0,%1,%2,%3}; @p0 ld.relaxed.gpu.global.b128 v,[%25+0]; mov.b128 {%0,%1,%2,%3},v;\n"
               " mov.b128 v,{%4,%5,%6,%7}; @p1 ld.relaxed.gpu.global.b128 v,[%25+512]; mov.b128 {%4,%5,%6,%7},v;\n"
               " mov.b128 v,{%8,%9,%10,%11}; @p2 ld.relaxed.gpu.global.b128 v,[%25+1024]; mov.b128 {%8,%9,%10,%11},v;\n"
               " mov.b128 v,{%12,%13,%14,%15}; @p3 ld.relaxed.gpu.global.b128 v,[%25+1536]; mov.b128 {%12,%13,%14,%15},v;\n"
               " mov.b128 v,{%16,%17,%18,%19}; @p4 ld.relaxed.gpu.global.b128 v,[%25+2048]; mov.b128 {%16,%17,%18,%19},v;\n"
               " mov.b128 v,{%20,%21,%22,%23}; @p5 ld.relaxed.gpu.global.b128 v,[%25+2560]; mov.b128 {%20,%21,%22,%23},v;\n"
               " @q bra.uni POLL_LOOP;\n}"
               : "=&r"(x[0].x), "=&r"(x[0].y), "=&r"(x[0].z), "=&r"(x[0].w), "=&r"(x[1].x), "=&r"(x[1].y), "=&r"(x[1].z), "=&r"(x[1].w), "=&r"(x[2].x), "=&r"(x[2].y), "=&r"(x[2].z), "=&r"(x[2].w), "=&r"(x[3].x), "=&r"(x[3].y), "=&r"(x[3].z), "=&r"(x[3].w), "=&r"(x[4].x), "=&r"(x[4].y), "=&r"(x[4].z), "=&r"(x[4].w), "=&r"(x[5].x), "=&r"(x[5].y), "=&r"(x[5].z), "=&r"(x[5].w), "+&r"(spin)
               : "l"(mb), "r"(tag), "n"(SPIN_TOT) : "memory");
}
template <int NL>
__device__ __forceinline__ void poll_add(const uint8_t* mb, uint32_t tag, float (&f)[8], uint8_t* flag, bool lead, int& spin) {
  uint4 x[NL];
  poll<NL>(x, mb, tag, spin);
  if (FLP == 0 && lead) st_relaxed(flag, 0);
#pragma unroll
  for (int i = 0; i < NL; i++) {
    const uint32_t u[4] = {x[i].x, x[i].y, x[i].z, x[i].w};
#pragma unroll
    for (int j = 0; j < 4; j++) {
      if (i == 0) { f[2 * j] = bf_lo(u[j]); f[2 * j + 1] = bf_hi(u[j]); }
      else { f[2 * j] += bf_lo(u[j]); f[2 * j + 1] += bf_hi(u[j]); }
    }
  }
}

template <int B, int SLOT>
__device__ __forceinline__ void wo_step(float (&acc)[8], const uint32_t (&wf)[C::NKR][4], int kk) {
  using namespace C;
  const int k = 4 * B + kk;
  const uint64_t db = mkdesc_ns(SB0 + og_off(SLOT) + kk * 512, 256, 128);
  if (k < NKR) wgmma_rt16(acc, wf[k < NKR ? k : 0], db, SLOT | kk);
  else wgmma_tt16(acc, wdesc(OFF_YO + (k - NKR) * 2048), db, 1);
}
template <int B, int SLOT>
__device__ __forceinline__ void wo_block(float (&acc)[8], const uint32_t (&wf)[C::NKR][4]) {
#pragma unroll
  for (int kk = 0; kk < 4; kk++) wo_step<B, SLOT>(acc, wf, kk);
}

__device__ __forceinline__ void chain_a(const CUtensorMap& tmWo, const CUtensorMap& tmWq, const uint32_t sb, const int tid0, const int cta, const int rank) {
  using namespace C;
  asm volatile("setmaxnreg.inc.sync.aligned.u32 200;");
  int spin = 0;
  uint32_t wf[NKR][4];
  load_weights_rs<true>(wf, tmWo, tmWq, cta, rank, sb, tid0, spin);
  const int wu = uni(tid0 >> 5);
  const bool t9 = cta >= 72 && cta < 88;
  const uint64_t exa = reinterpret_cast<uint64_t>(ex_window(g_ex));
  const uint32_t ehi = (uint32_t)(exa >> 32), elo = (uint32_t)exa;

  int b1 = B1, b2 = B2;
#pragma unroll 1
  for (int i = -1; i < NSTEP; i++) {
    const int ph = i & 1;
    if (i >= 0) {
      const int tid = fresh(tid0);
      const uint32_t mo = __shfl_xor_sync(0xffffffffu, elo + (ph << 20) + ((rank * 24 + (tid >> 4)) * 4 + (tid & 3)) * 2048 + (cta / 3) * 64 + (tid & 12) * 4, 0);
      const uint32_t m9 = __shfl_xor_sync(0xffffffffu, elo + (ph << 20) + MAIL9 + (((tid >> 4) * 2 + (tid & 1)) * 4 + (tid & 2)) * 3072 + cta * 32 + (tid & 12) * 2, 0);
      const uint32_t oo = __shfl_xor_sync(0xffffffffu, (tid >> 5) * 512 + (tid & 2) * 64 + (tid & 28) * 4 + (tid & 1) * 8, 0);
      if (i == 0) { mwait(sb + BAR_W + 24, 1, spin); mwait(sb + BAR_W + 32, 1, spin); PTS(7); }
      mwait(sb + BAR_M, ph, spin);
      TS(i, 3);
      {
        float x[20];
        int redo = 0;
      retry:
        bool bad;
        {
          float dq[8] = {}, dk[8] = {};
#pragma unroll 1
          for (int k0 = 0; k0 < 40; k0 += P1U) {
            wg_fence();
#pragma unroll
            for (int k = 0; k < P1U; k++) {
              if (k == P1U - QIE / 2 && k0 == 40 - P1U && !redo) CBAR_ARRIVE(NB_QI, 256);
              const uint64_t db = desc_at(mdesc(k), k0 * 512);
              wgmma_ts16(dq, desc_at(wdesc(OFF_WQ + k * 2048), k0 * 2048), db, 1);
              wgmma_ts16(dk, desc_at(wdesc(OFF_WK + k * 2048), k0 * 2048), db, 1);
            }
            wg_commit();
          }
          const int m = (tid >> 3) & 3, dg = (tid >> 5) * 2 + (m & 1);
          const uint32_t ka = sb + OFF_KT + dg * KS + (m >> 1) * 640 + (tid & 7) * 16;
          if (!redo) CBAR_SYNC(NB_QK, 384);
          sts32(sb + FLG_REDO, redo);
          wg_wait<0>();
          TS(i, 4);
          stsm4(ka, pack_bf16(dk[0], dk[1]), pack_bf16(dk[2], dk[3]), pack_bf16(dk[4], dk[5]), pack_bf16(dk[6], dk[7]));
          stsm4(ka + dg * (VS - KS) + (OFF_VT + 128 - OFF_KT), scale_bf16x2(pack_bf16(dq[0], dq[1]), SCQ), scale_bf16x2(pack_bf16(dq[2], dq[3]), SCQ),
                scale_bf16x2(pack_bf16(dq[4], dq[5]), SCQ), scale_bf16x2(pack_bf16(dq[6], dq[7]), SCQ));
          const float chk = (dq[0] + dq[1]) + (dq[4] + dq[5]);
          fence_async();
          bad = bar_red_or(NB_C, 128, chk != chk && !redo);
        }
        TSB(i, 5);
        wg_fence();
#pragma unroll
        for (int kk = 0; kk < 4; kk++) wgmma_tt40(x, mkdesc_ns(SB0 + OFF_VT + 128 + kk * 2 * VS, VS, 640), mkdesc_ns(SB0 + OFF_KT + kk * 2 * KS, KS, 128), kk);
#pragma unroll
        for (int kk = 0; kk < 4; kk++) {
          if (SIE && kk == 4 - SIE && !bad) CBAR_ARRIVE(NB_SI, 256);
          wgmma_tt40(x, mkdesc_ns(SB0 + OFF_VT + kk * 2 * VS, VS, 384), mkdesc_ns(SB0 + OFF_KT + 640 + kk * 2 * KS, KS, 128), 1);
        }
        wg_commit();
        if (!SIE && !bad) CBAR_ARRIVE(NB_SI, 256);
        if (__builtin_expect(__any_sync(0xffffffffu, bad), 0)) {
          wg_wait<0>();
#pragma unroll 1
          for (int k = 0; k < 10; k++) {
            uint4 v = lds128(sb + OFF_M + tid * 16 + k * 2048);
            if (v.x == SENT || v.y == SENT || v.z == SENT || v.w == SENT) {
              do { v = ld_relaxed4(mkptr(elo + EX_M + i * 20480 + tid * 16 + k * 2048, ehi)); spin += 16; } while ((v.x == SENT || v.y == SENT || v.z == SENT || v.w == SENT) && spin < SPIN_TOT);
              sts128(sb + OFF_M + tid * 16 + k * 2048, v);
            }
          }
          fence_async();
          bar_sync(NB_C, 128);
          redo = fresh(1);
          goto retry;
        }
        TSV(i, 36, redo);
        const uint32_t rb1 = mapa(sb, (rank + 1) % 3), rb2 = mapa(sb, (rank + 2) % 3);
        wg_wait<0>();
        TS(i, 6);
        if (wu < 2) {
          float y[10];
#pragma unroll
          for (int j = 0; j < 5; j++) { y[2 * j] = x[4 * j]; y[2 * j + 1] = x[4 * j + 1]; }
          const uint4 h0 = make_uint4(pack_h2(y[0], y[1]), pack_h2(y[2], y[3]), pack_h2(y[4], y[5]), pack_h2(y[6], y[7]));
          const uint32_t h1 = pack_h2(y[8], y[9]);
          st_async4u(rb1 + OFF_XM + 1024 + tid * 16, h0, rb1 + BAR_XM);
          st_async4u(rb2 + OFF_XM + tid * 16, h0, rb2 + BAR_XM);
          st_async1u(rb1 + OFF_XM + 2304 + tid * 4, h1, rb1 + BAR_XM);
          st_async1u(rb2 + OFF_XM + 2048 + tid * 4, h1, rb2 + BAR_XM);
          CBAR_ARRIVE(NB_SM, 256);
          if ((tid & 31) == 0) mbar_arrive_cluster(mapa(sb, 0) + BAR_E);
          TS(i, 7);
          const uint32_t sw = (tid & 7) * 4 + (tid & 8) * 8 + (tid & 16) * 2;
          mwait(sb + BAR_XM, ph, spin);
          TS(i, 8);
          const uint4 u0 = lds128(sb + OFF_XM + tid * 16), v0 = lds128(sb + OFF_XM + 1024 + tid * 16);
          const uint32_t u1 = lds32(sb + OFF_XM + 2048 + tid * 4), v1 = lds32(sb + OFF_XM + 2304 + tid * 4);
          add_h2(y[0], y[1], u0.x, v0.x); add_h2(y[2], y[3], u0.y, v0.y); add_h2(y[4], y[5], u0.z, v0.z); add_h2(y[6], y[7], u0.w, v0.w);
          add_h2(y[8], y[9], u1, v1);
          const float mx = quad_max(max10(y)) * -SCE;
#pragma unroll
          for (int j = 0; j < 5; j++) {
            y[2 * j] = ex2(fmaf(y[2 * j], SCE, mx)); y[2 * j + 1] = ex2(fmaf(y[2 * j + 1], SCE, mx));
            sts32(sb + OFF_PT + wu * 640 + sw + j * 128, pack_bf16(y[2 * j], y[2 * j + 1]));
          }
          sts32(sb + OFF_XM + 2048 + wu * 128 + sw, __float_as_uint(sum10(y)));
          fence_async();
          TS(i, 9);
        } else {
          CBAR_ARRIVE(NB_SM, 256);
          if ((tid & 31) == 0) mbar_arrive_cluster(mapa(sb, 0) + BAR_E);
          mwait(sb + BAR_MF, ph, spin);
        }
      }
      CBAR_SYNC(NB_VA, 256);
      TSB(i, 10);
      {
        float o[2][4];
        wg_fence();
#pragma unroll
        for (int c = 0; c < 2; c++)
#pragma unroll
          for (int q = 0; q < 3; q++)
            wgmma_ss8(o[c], mkdesc_ns(SB0 + OFF_VT + 128 + c * 640 + q * 256, 128, VS), mkdesc_ns(SB0 + OFF_PT + c * 640 + q * 256, q == 2 && c == 0 ? 768 : 128, 128), q);
        wg_commit();
        const float4 e = lds128f(sb + OFF_XM + 2048 + (tid & 15) * 16);
        const uint32_t rb1 = mapa(sb, (rank + 1) % 3), rb2 = mapa(sb, (rank + 2) % 3);
        const float inv = rcp((e.x + e.y) + (e.z + e.w));
        const int sl = (tid & 3) * 2;
        const float i0 = __shfl_sync(0xffffffffu, inv, sl), i1 = __shfl_sync(0xffffffffu, inv, sl + 1);
        const float i2 = __shfl_sync(0xffffffffu, inv, sl + 8), i3 = __shfl_sync(0xffffffffu, inv, sl + 9);
        wg_wait<0>();
        TS(i, 11);
        const uint32_t p0 = pack_bf16(o[0][0] * i0, o[0][1] * i1), p1 = pack_bf16(o[1][0] * i2, o[1][1] * i3);
        const uint32_t p2 = pack_bf16(o[0][2] * i0, o[0][3] * i1), p3 = pack_bf16(o[1][2] * i2, o[1][3] * i3);
        if (OGF) { sts64(sb + oo + og_off(0), p0, p1); sts64(sb + oo + og_off(0) + 256, p2, p3); fence_async(); }
        st_async2u(rb1 + oo + og_off(2), p0, p1, rb1 + BAR_OG);
        st_async2u(rb2 + oo + og_off(1), p0, p1, rb2 + BAR_OG);
        st_async2u(rb1 + oo + og_off(2) + 256, p2, p3, rb1 + BAR_OG);
        st_async2u(rb2 + oo + og_off(1) + 256, p2, p3, rb2 + BAR_OG);
        if (!OGF) { sts64(sb + oo + og_off(0), p0, p1); sts64(sb + oo + og_off(0) + 256, p2, p3); fence_async(); }
      }
      CBAR_SYNC(NB_A, 128);
      TSB(i, 12);
      {
        float acc[3][8];
        wg_fence();
        wo_block<0, 0>(acc[2], wf);
        wg_commit();
        if (tid == 0) mbar_arrive_cluster(mapa(sb, 1) + BAR_E + 8);
        wo_block<1, 0>(acc[0], wf);
        wo_block<4, 0>(acc[1], wf);
        wg_commit();
        const uint32_t tag = (i >> 1) & 1;
#define TAGGED(LO, HI) ((pack_bf16(LO, HI) & ~1u) | tag)
#define SEND(OFF, U) st_relaxed128(mkptr(mo, ehi) + (OFF), TAGGED(acc[U][0], acc[U][2]), pack_bf16(acc[U][1], acc[U][3]), pack_bf16(acc[U][4], acc[U][6]), pack_bf16(acc[U][5], acc[U][7]))
        wg_wait<1>();
        const uint32_t n0 = pin(TAGGED(acc[2][0], acc[2][2])), n1 = pin(pack_bf16(acc[2][1], acc[2][3]));
        const uint32_t n2 = pin(TAGGED(acc[2][4], acc[2][6])), n3 = pin(pack_bf16(acc[2][5], acc[2][7]));
        wg_fence();
        wo_block<7, 0>(acc[2], wf);
        wg_commit();
        st_relaxed64(mkptr(m9, ehi), n0, n1);
        st_relaxed64(mkptr(m9, ehi) + 3072, n2, n3);
        mwait(sb + BAR_OG, ph, spin);
        asm volatile("fence.proxy.async::generic.acquire.sync_restrict::shared::cluster.cluster;" ::: "memory");
        TS(i, 13);
        wg_fence();
        wo_block<2, 1>(acc[0], wf); wo_block<3, 2>(acc[0], wf);
        wg_commit();
        wo_block<5, 1>(acc[1], wf); wo_block<6, 2>(acc[1], wf);
        wg_commit();
        wg_wait<1>(); SEND(0, 0);
        wo_block<8, 1>(acc[2], wf); wo_block<9, 2>(acc[2], wf);
        wg_commit();
        if (WOE == 0) { CBAR_ARRIVE(NB_WV, 256); CBAR_ARRIVE(NB_WQ, 256); }
        wg_wait<1>(); SEND(32 * 2048, 1);
        if (WOE == 1) CBAR_ARRIVE(NB_WV, 256);
        wg_wait<0>(); SEND(64 * 2048, 2);
        if (WOE == 2) CBAR_ARRIVE(NB_WV, 256);
        if (WOE >= 1) CBAR_ARRIVE(NB_WQ, 256);
#undef SEND
#undef TAGGED
      }
      TS(i, 14);
      if (i < 2) PTS(19 + i);
      if (i + 1 >= NSTEP) break;
    }
    uint32_t t1 = clk32();
    if (i >= 0) {
      const int lane = fresh(tid0) & 31, j = lane >> 3;
      const uint8_t* mb = mkptr(elo + (ph << 20) + (t9 ? MAIL9 + (cta - 72) * 12288 + wu * 3072 : (cta < 72 ? cta : cta - 24) * 8192 + wu * 2048) + lane * 16, ehi);
      const uint32_t tag = (i >> 1) & 1;
      const bool pub = (lane & (t9 ? 6 : 4)) == 0 && !(((t9 ? cta : wu) & 1) && i + 1 == LAG) && cta < 88;
      const uint32_t dst = pin(elo + EX_M + (i + 1) * 20480 + (t9 ? (cta + 72) * 128 + wu * 32 + (j & 1) * 16 + (lane & 1) * 8 + (j >> 1) * 4
                                                                   : cta * 256 + (wu & 1) * 128 + (wu >> 1) * 64 + j * 16 + (lane & 3) * 4));
      uint8_t* flag = mkptr(elo + EX_FLAG + (i + 1) * 3072 + cta * 32 + wu * 4, ehi);
      while (clk32() - t1 < b1) {}
      TS(i + 1, 30);
      float f[8];
      const int n0 = spin;
      if (!t9) poll_add<4>(mb, tag, f, flag, lane == 0, spin);
      else poll_add<6>(mb, tag, f, flag, lane == 0, spin);
      if (FLP == 1 && lane == 0) st_relaxed(flag, __float_as_uint(f[0] + f[7]) >> 1);
      t1 = clk32();
      b1 = __any_sync(0xffffffffu, spin - n0 > 16) ? min(b1 + AD1, BMX) : max(b1 - AD0, 0);
      TSV(i + 1, 38, b1);
      TS(i + 1, 31); TSV(i + 1, 32, (spin - n0) >> 4);
      const bool h = lane & 16, q = lane & 8;
#pragma unroll
      for (int j = 0; j < 4; j++) f[j] = (h ? f[4 + j] : f[j]) + __shfl_xor_sync(0xffffffffu, h ? f[j] : f[4 + j], 16);
#pragma unroll
      for (int j = 0; j < 2; j++) f[j] = (q ? f[2 + j] : f[j]) + __shfl_xor_sync(0xffffffffu, q ? f[j] : f[2 + j], 8);
      f[0] += __shfl_xor_sync(0xffffffffu, f[0], 4); f[1] += __shfl_xor_sync(0xffffffffu, f[1], 4);
      if (t9) { f[0] += __shfl_xor_sync(0xffffffffu, f[0], 2); f[1] += __shfl_xor_sync(0xffffffffu, f[1], 2); }
      if (pub) st_relaxed(mkptr(dst, ehi), pack_bf16(f[0], f[1]));
      if (FLP == 2 && lane == 0) st_relaxed(flag, 0);
      if (wu == 3) {
        CBAR_SYNC(NB_MR, 160);
        if (elect_one()) signal_o(i, cta);
      }
      TS(i + 1, 15);
    }
    if (wu == 0) {
      const int tid = fresh(tid0);
      const uint8_t* pp = mkptr(elo + EX_FLAG + (i + 1) * 3072 + (rank * 28 + (tid < 28 || rank == 2 ? tid : 0)) * 32, ehi);
      while (clk32() - t1 < b2) {}
      TS(i + 1, 16);
      int n = 1;
      uint4 x = ld_relaxed4(pp);
      if (tid0 == 0) mbar_expect_tx(sb + BAR_M, 20480);
      bool mok = mbar_test(sb + BAR_MOK, ph ^ 1);
      while (__any_sync(0xffffffffu, (int)(x.x | x.y | x.z | x.w) < 0 && spin < SPIN_TOT)) { x = ld_relaxed4(pp); mok = mbar_test(sb + BAR_MOK, ph ^ 1); n++; spin += 16; }
      if (!mok) mwait(sb + BAR_MOK, ph ^ 1, spin);
      b2 = n > 1 ? min(b2 + AD3, BMX) : max(b2 - AD2, 0);
      TSV(i + 1, 35, n); TSV(i + 1, 39, b2);
      TS(i + 1, 34);
      if (elect_one()) bulk_g2s_mc(sb + OFF_M + rank * 7168, mkptr(elo + EX_M + (i + 1) * 20480 + rank * 7168, ehi), rank == 2 ? 6144 : 7168, sb + BAR_M);
      TS(i + 1, 33);
      __syncwarp();
    }
  }
  if (spin >= SPIN_TOT) g_err = 1;
}

__global__ void __cluster_dims__(3, 1, 1) __launch_bounds__(384, 1)
k_chain(const __grid_constant__ CUtensorMap tmWq, const __grid_constant__ CUtensorMap tmWk,
        const __grid_constant__ CUtensorMap tmWv, const __grid_constant__ CUtensorMap tmWo, const bf16* __restrict__ x0, const bf16* __restrict__ mem0) {
  using namespace C;
  extern __shared__ __align__(1024) uint8_t smem[];
  const uint32_t sb = smem_u32(smem);
  const int tid = threadIdx.x;
  const int wg = __shfl_sync(0xffffffffu, tid >> 7, 0);
  const int cta = uni(blockIdx.x), rank = uni(blockIdx.x % 3);

  asm volatile("griddepcontrol.launch_dependents;");
  if (cta < 4) prefetch_l2(tid < 320 ? x0 + (cta * 320 + tid) * 64 : mem0 + (cta * 20 + tid % 20) * 64);
  if (tid == 32) {
    for (int p = 0; p < 5; p++) mbar_init(sb + BAR_W + 8 * p, 2);
    fence_async();
    for (int p = 0; p < NBX; p++) { stage_box<false>(tmWv, sb, p, cta, rank); stage_box<true>(tmWo, sb, p, cta, rank); }
  }
  if (tid == 0) {
    if ((sb & 0xFFFFFF) != SB0) g_err = 100;
    for (int p = 0; p < 5; p++) { mbar_init(sb + BAR_F + 8 * p, 1); mbar_init(sb + BAR_E + 8 * p, p == 2 ? 12 : p == 1 ? 15 : 24); }
    mbar_init(sb + BAR_M, 1); mbar_init(sb + BAR_MOK, 24); mbar_init(sb + BAR_XM, 1); mbar_init(sb + BAR_XF, 2);
    mbar_init(sb + BAR_XT, 1); mbar_init(sb + BAR_MF, 8); mbar_init(sb + BAR_OG, 1);
    for (int p = 0; p < 5; p++) mbar_expect_tx(sb + BAR_F + 8 * p, 16384);
    for (int p = 0; p < 16; p++) sts32(sb + OFF_SAFE + 4 * p, 0);
    for (int p = 0; p < 32; p++) sts32(sb + OFF_ONE + 4 * p, 0x3F803F80);
    asm volatile("fence.mbarrier_init.release.cluster;" ::: "memory");
    fence_async();
  }
  __syncthreads();
  asm volatile("barrier.cluster.arrive.relaxed.aligned;" ::: "memory");
  asm volatile("barrier.cluster.wait.aligned;" ::: "memory");

  if (wg == 0) chain_a(tmWo, tmWq, sb, keep(tid), cta, rank);
  else if (wg == 1) chain_q(x0, mem0, sb, keep(tid), cta, rank);
  else chain_v(tmWv, tmWk, sb, keep(tid), cta, rank);
  asm volatile("barrier.cluster.arrive.release.aligned;" ::: "memory");
  asm volatile("barrier.cluster.wait.acquire.aligned;" ::: "memory");
}

namespace W {
constexpr int NP = 25, NBC = 11, NW = NP + NBC;
constexpr int PRS = 37, PW = 43 * 2048;
constexpr int OFF_W = 0;
constexpr int OFF_R = 2 * PW;
constexpr int BRS = 36, VSS = 37;
constexpr int OFF_WO = 0, OFF_Y = 81920;
constexpr int OFF_X = OFF_Y + 2 * (40 - BRS) * 2048;
constexpr int OFF_WV = OFF_X + 40960;
constexpr int OFF_S = OFF_WV + VSS * 2048;
constexpr int COL = 976;
constexpr int OFF_T = OFF_X + 16384;
constexpr int OFF_H = OFF_S + 7696;
constexpr int OFF_BAR = OFF_H + 8 * COL;
constexpr int OFF_SAFE = OFF_BAR + 256;
constexpr int SMEM = 232448;
static_assert(OFF_SAFE + 64 <= SMEM && OFF_R + 40960 <= OFF_BAR, "");
constexpr uint32_t SB0 = 1024;
constexpr int BAR_F = OFF_BAR, BAR_E = OFF_BAR + 40, BAR_G = OFF_BAR + 80, BAR_W = OFF_BAR + 160, BAR_R = OFF_BAR + 176;
constexpr int NB_G0 = 1, NB_SG = 4, NB_B = 5, NB_AS = 6, NB_SG1 = 7, NB_RED = 8, NB_R = 11, NB_TD = 12;
}
#define FSA 1
#define WBAR_SYNC(id, n) bar_sync(id, n)
#define WBAR_ARRIVE(id, n) bar_arrive(id, n)

__device__ __forceinline__ uint64_t rdesc(int off, int kk) { return mkdesc(W::SB0 + off + kk * 32, 16, 1024); }
__device__ __forceinline__ uint64_t gdesc(int off, int kk) { return mkdesc_ns(W::SB0 + off + kk * 1024, 512, 512) | ((uint64_t)2 << 62); }
__device__ __forceinline__ uint32_t frag_addr(uint32_t base, int tid) {
  const int i = (tid >> 3) & 3, r = tid & 7;
  return base + (r + (i >> 1) * 8) * 128 + (((2 * ((tid >> 5) & 3) + (i & 1)) ^ r) << 4);
}
template <int NK>
__device__ __forceinline__ void load_frags(uint32_t (&wf)[NK][4], uint32_t base, int tid) {
  const uint32_t a0 = frag_addr(base, tid);
#pragma unroll
  for (int k = 0; k < NK; k++) ldsm4t(wf[k], a0 + k * 2048);
}
__device__ __forceinline__ void red_tile(const float* d, int seg, int col0, int tid) {
  float* p = g_x + (size_t)(seg * 32 + 2 * (tid & 3)) * DM + col0 + ((tid >> 5) & 3) * 16 + ((tid >> 2) & 7) * 2;
#pragma unroll
  for (int j = 0; j < 8; j++)
    asm volatile("red.relaxed.gpu.global.add.v2.f32 [%0],{%1,%2};" ::"l"(p + ((j >> 1) * 8 + (j & 1)) * DM), "f"(d[4 * (j >> 1) + (j & 1)]), "f"(d[4 * (j >> 1) + 2 + (j & 1)]) : "memory");
}

__device__ __forceinline__ void work_p(const CUtensorMap& tmWo, uint32_t sb, int pc, const int WG, int tid0) {
  using namespace W;
  asm volatile("setmaxnreg.inc.sync.aligned.u32 208;");
  int spin = 0;
  const int ks = pc / 5, col0 = (pc % 5) * 128 + WG * 64;
  const uint32_t wb = sb + OFF_W + WG * PW;
  uint32_t wf[PRS][4];
#pragma unroll 1
  for (int hf = 0; hf < 2; hf++) {
    const int nk = hf ? 80 - PRS : PRS;
    if ((tid0 & 127) == 0) {
      mbar_expect_tx(sb + BAR_W + 8 * WG, nk * 2048);
      for (int i = 0; i < nk; i++) tma2d(wb + i * 2048, &tmWo, col0, ks * 19 * 64 + (i < PRS ? 2 * i + hf : PRS + i) * 16, sb + BAR_W + 8 * WG);
    }
    __syncwarp();
    mwait(sb + BAR_W + 8 * WG, hf, spin);
    permute_cols(wb, tid0 & 127, nk * 64);
    if (hf == 1 && ks < 4) for (int it = 39 * 64 + (tid0 & 127) - 64; it < 43 * 64; it += 128) {
      const uint32_t a = wb + (it >> 2) * 128 + (((2 * (it & 3)) ^ ((it >> 2) & 6)) << 4);
      if (it >= 39 * 64) { sts128(a, make_uint4(0, 0, 0, 0)); sts128(a + 16, make_uint4(0, 0, 0, 0)); }
    }
    fence_async();
    WBAR_SYNC(NB_G0 + WG, 128);
    if (hf == 0) {
      load_frags<PRS>(wf, wb, tid0);
      fence_async();
      WBAR_SYNC(NB_G0 + WG, 128);
    }
  }
#pragma unroll 1
  for (int k = 0; k < NSTEP; k++) {
    float d[32];
#pragma unroll
    for (int f = 0; f < 20; f++) {
      mwait(sb + BAR_F + 8 * (f % 5), (f / 5) & 1, spin);
      if (f == 0 && WG == 0 && pc == WW) WTS(k, 1);
      wg_fence();
#pragma unroll
      for (int kk = 0; kk < 4; kk++) {
        const int q = 4 * f + kk;
        if (q < 2 * PRS && !(q & 1)) wgmma_rs64(d, wf[q < 2 * PRS ? q >> 1 : 0], rdesc(OFF_R + (f % 5) * 8192, kk), q);
        else wgmma_ts64(d, desc_at(mkdesc(SB0 + OFF_W + (q < 2 * PRS ? q >> 1 : q - PRS) * 2048, 8192, 1024), WG * PW), rdesc(OFF_R + (f % 5) * 8192, kk), 1);
        if (kk == 0 && f > 0) {
          wg_commit();
          wg_wait<1>();
          if ((tid0 & 31) == 0) mbar_arrive(sb + BAR_E + 8 * ((f - 1) % 5));
        }
      }
      wg_commit();
    }
    wg_wait<0>();
    if ((tid0 & 31) == 0) mbar_arrive(sb + BAR_E + 32);
    if (WG == 0 && pc == WW) WTS(k, 2);
    if (k < NSEG) red_tile(d, k, col0, tid0);
    if (k >= LAG) red_tile(d + 16, k - LAG, col0, tid0);
    if (WG == 0 && pc == WW) WTS(k, 13);
    WBAR_SYNC(NB_SG, 256);
    if (WG == 0) { if (tid0 == 0) { if (UNS & 8) csignal_fast(CN_P + k); else csignal_t(CN_P + k, 3); } __syncwarp(); }
  }
  if (spin >= SPIN_TOT) g_err = 11;
}
__device__ __forceinline__ void work_p_producer(uint32_t sb, int pc, int odd) {
  using namespace W;
  int spin = 0;
  const int ks = pc / 5;
#pragma unroll 1
  for (int k = 0; k < NSTEP; k++) {
    const uint32_t lo = k < NSEG ? 0 : 4096, len = k < LAG || k >= NSEG ? 4096 : 8192;
    const uint8_t* src = &g_o[k % ORING][ks * 19 + odd][lo];
    cwait(CN_O + k * 5 + ks, ks == 4 ? 20 : 19, spin);
    fence_async_all();
    if (pc == WW && !odd) WTS1(k, 0);
#pragma unroll
    for (int u = 0; u < 10; u++) {
      const int st = odd ? (2 * u + 1) % 5 : (2 * u) % 5, ph = odd ? ((2 * u + 1) / 5) & 1 : ((2 * u) / 5) & 1;
      mwait(sb + BAR_E + 8 * st, ph ^ 1, spin);
      if (elect_one()) {
        if (u == 9 && odd && ks < 4) mbar_arrive(sb + BAR_F + 8 * st);
        else {
          mbar_expect_tx(sb + BAR_F + 8 * st, len);
          bulk_g2s(sb + OFF_R + st * 8192 + lo, src + u * 16384, len, sb + BAR_F + 8 * st);
        }
      }
    }
  }
  if (spin >= SPIN_TOT) g_err = 12;
}
__device__ __forceinline__ void work_ln(int kind, int r, int lane, bf16* out) {
  int spin = 0;
  const int l = kind & 1;
  const int rp = kind < 2 ? (r & 1) * 16 + (r >> 1) : r;
  const uint32_t sw = ((((lane >> 1) & 7) ^ (rp & 7)) << 4) + (lane & 1) * 8;
  uint8_t* dst = kind < 2 ? g_xnb[l * LAG] + (lane >> 4) * 8192 + l * 4096 + rp * 128 + sw
               : kind == 2 ? g_xn[LAG] + (r >> 3) * 4096 + 2048 + (lane >> 4) * 1024 + (r & 7) * 128 + sw
                           : reinterpret_cast<uint8_t*>(out) + r * 1280 + lane * 8;
  const int dm = kind < 3 ? 16384 : 256, ds = kind < 3 ? 81920 : 40960;
#pragma unroll 1
  for (int s = 0; s < NSEG; s++) {
    float* xr = g_x + (size_t)(s * 32 + r) * DM;
    float4 v[5];
    if (kind < 2) {
#pragma unroll
      for (int u = 0; u < 5; u++) {
        const int p = u * 32 + lane;
        stg128((p < 80 ? g_ob[s + l * LAG] + (l * 32 + r) * 1280 : g_y[l] + (size_t)s * 40960 + (r - 1) * 1280) + p * 16, make_uint4(SENT, SENT, SENT, SENT));
      }
      if (lane == 0) cwait(CN_P + s + l * LAG, W::NP, spin);
      __syncwarp();
      if (r == 0 && lane == 0 && (l == 0 || s + LAG >= NSEG)) WTS1(s + l * LAG, 3);
#pragma unroll
      for (int m = 0; m < 5; m++) v[m] = ld_relaxed4f(xr + m * 128 + lane * 4);
    } else {
      if (lane == 0) cwait(CN_L + s + l * LAG, s + l * LAG < LAG || s + l * LAG >= NSEG ? 32 : 64, spin);
      __syncwarp();
#pragma unroll
      for (int m = 0; m < 5; m++) v[m] = ld_relaxed4f(xr + m * 128 + lane * 4);
      if (lane == 0) cwait(CN_W + l * 64 + s, 10, spin);
      __syncwarp();
      if (r == 0 && lane == 0 && (l == 0 || s + LAG >= NSEG)) WTS1(s + l * LAG, 11);
      const uint8_t* yp = g_y[l] + (size_t)s * 40960 + (lane >> 4) * 4096 + r * 128 + sw;
      float2 y[5];
      bool bad;
      do {
        bad = false;
#pragma unroll
        for (int m = 0; m < 5; m++) y[m] = ld_relaxed2f(yp + m * 8192);
#pragma unroll
        for (int m = 0; m < 5; m++) bad |= __float_as_uint(y[m].x) == SENT || __float_as_uint(y[m].y) == SENT;
        spin += 16;
      } while (__any_sync(0xffffffffu, bad && spin < SPIN_TOT));
#pragma unroll
      for (int m = 0; m < 5; m++) {
        v[m].x += bf_lo(__float_as_uint(y[m].x)); v[m].y += bf_hi(__float_as_uint(y[m].x));
        v[m].z += bf_lo(__float_as_uint(y[m].y)); v[m].w += bf_hi(__float_as_uint(y[m].y));
        if (kind == 2) *reinterpret_cast<float4*>(xr + m * 128 + lane * 4) = v[m];
      }
    }
    if (kind < 3) ln_row(v);
#pragma unroll
    for (int m = 0; m < 5; m++) *reinterpret_cast<uint2*>(dst + (size_t)s * ds + m * dm) = make_uint2(pack_bf16(v[m].x, v[m].y), pack_bf16(v[m].z, v[m].w));
    __syncwarp();
    if (r == 0 && lane == 0 && (l == 0 || s + LAG >= NSEG)) WTS1(s + l * LAG, kind < 2 ? 4 : 12);
    if (lane == 0 && kind < (NOWORK ? 2 : 3)) { if ((UNS >> (kind < 2 ? 1 : 2)) & 1) csignal_fast(kind < 2 ? CN_L + s + l * LAG : CN_X + s + LAG); else csignal_t(kind < 2 ? CN_L + s + l * LAG : CN_X + s + LAG, kind); }
  }
  if (spin >= SPIN_TOT) g_err = 13;
}

__device__ __forceinline__ void work_prep(const bf16* x0, const bf16* mem0, int r, int lane) {
  int spin = 0;
#pragma unroll 1
  for (int k = NPRE; k < NSTEP; k++) {
    uint2 u[5], v[5];
    ln0_load(x0, u, min(k * 32 + r, SEQ - 1), lane);
    ln0_load(x0, v, min(k * 32 + r + 16, SEQ - 1), lane);
    if (lane == 0) cwait(CN_O + (k - NPRE) * 5, 1, spin);
    __syncwarp();
#pragma unroll 1
    for (int h = 0; h < 2; h++) {
      prep_row(u, mem0, k, r + 16 * h, lane);
#pragma unroll
      for (int m = 0; m < 5; m++) u[m] = v[m];
    }
    __syncwarp();
    if (lane == 0) csignal(CN_X + k);
  }
  if (spin >= SPIN_TOT) g_err = 19;
}

__device__ __forceinline__ void stage_qkv(const bf16* wqkv, uint32_t base, int T, int bc, int tid) {
  const int q = tid & 15;
  const bool ok = q < 15 && bc * 60 + 4 * q < DM;
  const bf16* src = wqkv + T * DM + bc * 60 + 4 * q;
#pragma unroll 1
  for (int k0 = tid >> 4; k0 < 640; k0 += 80) {
    uint2 v[10];
#pragma unroll
    for (int u = 0; u < 10; u++) v[u] = ok ? *reinterpret_cast<const uint2*>(src + (size_t)(k0 + 8 * u) * 1920) : make_uint2(0, 0);
#pragma unroll
    for (int u = 0; u < 10; u++) sts64(base + (k0 + 8 * u) * 128 + (((q >> 1) ^ (k0 & 7)) << 4) + (q & 1) * 8, v[u].x, v[u].y);
  }
}
struct AttAddr { uint32_t qa, qb, ka, oa, ob, ml; };
__device__ __forceinline__ AttAddr att_addr(uint32_t sb, int bc, int hh, int tid) {
  using namespace W;
  const int r = tid & 7, m = (tid >> 3) & 3, g = (tid >> 2) & 7, t = tid & 3, lp = (tid >> 5) & 3;
  const int f2 = r < 4 ? 20 * hh + 16 + r : 60;
  const uint32_t tb = sb + OFF_T + 2 * lp * COL;
  const int fa = 20 * hh + (m >> 1) * 8 + r, pc = 2 * (lp & 1) + (m & 1);
  const uint32_t o0 = sb + OFF_S + (lp >> 1) * 3840;
  AttAddr x;
  x.qa = keep(tb + (m & 1) * COL + (20 * hh + (m >> 1) * 8 + r) * 16);
  x.qb = keep(tb + (m & 1) * COL + f2 * 16);
  x.ka = keep(tb + (m < 2 ? 20 * hh + 8 * m + r : f2) * 16);
  x.oa = keep(o0 + fa * 64 + ((pc ^ ((bc * 60 + fa) >> 1)) & 3) * 16);
  x.ob = keep(r < 4 ? o0 + f2 * 64 + ((pc ^ ((bc * 60 + f2) >> 1)) & 3) * 16 : sb + OFF_S + 7680);
  x.ml = keep((2 * t > g ? 0xFFFFu : 0u) | (2 * t + 1 > g ? 0xFFFF0000u : 0u));
  return x;
}
__device__ __forceinline__ void release_tiles(uint32_t sb, int tid) {
  fence_async();
  __syncwarp();
  if ((tid & 31) < 3) mbar_arrive(sb + W::BAR_E + 16 + 8 * (tid & 3));
}
__device__ __forceinline__ void attend(uint32_t sb, const AttAddr& x, int k0, int lp, int tid) {
  using namespace W;
  const uint32_t hd = OFF_H - OFF_T - lp * COL;
  const float scl = 0.22360679774997896f * 1.4426950408889634f;
  float sc[3][4];
  uint32_t v[3][4];
  {
    uint32_t q[4], q8a, q8b, k[3][4];
    ldsm4t(q, x.qa);
    ldsm4t(k[0], x.ka + hd); ldsm4t(k[1], x.ka + 8 * COL); ldsm4t(k[2], x.ka + 9 * COL);
    ldsm2t(q8a, q8b, x.qb);
#pragma unroll
    for (int c = 0; c < 3; c++) { sc[c][0] = sc[c][1] = sc[c][2] = sc[c][3] = 0.f; mma16816(sc[c], q[0], q[1], q[2], q[3], k[c][0], k[c][1]); }
#pragma unroll
    for (int c = 0; c < 3; c++) mma1688(sc[c], q8a, q8b, k[c][2]);
    stsm4t(x.ka + hd, k[2][0], k[2][1], k[2][2], k[2][3]);
  }
  ldsm4(v[0], x.ka + hd + 4 * COL); ldsm4(v[1], x.ka + 16 * COL); ldsm4(v[2], x.ka + 17 * COL);
  stsm4(x.ka + hd + 4 * COL, v[2][0], v[2][1], v[2][2], v[2][3]);
  release_tiles(sb, tid);
  const bool lo0 = x.ml & 1, lo1 = (int)x.ml < 0, first = k0 == (lp >> 1) * LAG;
  uint32_t pw[2];
  float inv[2];
#pragma unroll
  for (int h = 0; h < 2; h++) {
    float y0 = lo0 ? sc[h][2 * h] : sc[h + 1][2 * h], y1 = lo1 ? sc[h][2 * h + 1] : sc[h + 1][2 * h + 1];
    if (h == 0 && first) { y0 = lo0 ? -INFINITY : y0; y1 = lo1 ? -INFINITY : y1; }
    const float mx = quad_max(fmaxf(y0, y1)) * -scl;
    y0 = ex2(fmaf(y0, scl, mx)); y1 = ex2(fmaf(y1, scl, mx));
    pw[h] = pack_bf16(y0, y1);
    inv[h] = y0 + y1;
  }
  float o[3][4];
  const uint32_t a0 = pw[0] & x.ml, a2 = pw[0] & ~x.ml, a3 = pw[1] & x.ml, a5 = pw[1] & ~x.ml, z0 = tid >> 10, z1 = tid >> 11;
#pragma unroll
  for (int j = 0; j < 3; j++) { o[j][0] = o[j][1] = o[j][2] = o[j][3] = 0.f; mma16816(o[j], a0, z0, a2, a3, v[0][j], v[1][j]); }
#pragma unroll
  for (int j = 0; j < 3; j++) mma1688(o[j], z1, a5, v[2][j]);
  inv[0] = rcp(quad_sum(inv[0])); inv[1] = rcp(quad_sum(inv[1]));
  stsm4t(x.oa, pack_bf16(o[0][0] * inv[0], o[0][1] * inv[0]), pack_bf16(o[0][2] * inv[1], o[0][3] * inv[1]),
         pack_bf16(o[1][0] * inv[0], o[1][1] * inv[0]), pack_bf16(o[1][2] * inv[1], o[1][3] * inv[1]));
  stsm2t(x.ob, pack_bf16(o[2][0] * inv[0], o[2][1] * inv[0]), pack_bf16(o[2][2] * inv[1], o[2][3] * inv[1]));
  fence_async();
}
template <bool IS_V>
__device__ __forceinline__ void work_b(const CUtensorMap& tmBo, const bf16* wqkv, uint32_t sb, int bc, const int wg, int tid0) {
  using namespace W;
  if (!IS_V) asm volatile("setmaxnreg.inc.sync.aligned.u32 208;");
  else asm volatile("setmaxnreg.dec.sync.aligned.u32 72;");
  constexpr int NR = IS_V ? 40 - VSS : BRS;
  const int WG = IS_V ? 2 : wg;
  const uint32_t yo = WG * (40 - BRS) * 2048;
  int spin = 0;
  uint32_t wf[NR][4];
  if (!IS_V) {
    const uint32_t wb = sb + (WG ? OFF_WO : OFF_WV);
    stage_qkv(wqkv, wb, WG, bc, tid0 & 127);
    WBAR_SYNC(NB_G0 + WG, 128);
    load_frags<NR>(wf, wb, tid0);
#pragma unroll
    for (int k = NR; k < 40; k++) sts128(sb + OFF_Y + yo + (k - NR) * 2048 + (tid0 & 127) * 16, lds128(wb + k * 2048 + (tid0 & 127) * 16));
    fence_async();
  }
  WBAR_SYNC(NB_B, 384);
  if (WG == 1 && bc < 10) {
    if ((tid0 & 127) == 0) {
      mbar_expect_tx(sb + BAR_W, 81920);
      for (int i = 0; i < 10; i++) tma2d(sb + OFF_WO + i * 8192, &tmBo, bc * 64, i * 64, sb + BAR_W);
    }
    __syncwarp();
    mwait(sb + BAR_W, 0, spin);
  }
  if (IS_V) {
    stage_qkv(wqkv, sb + OFF_WV, 2, bc, tid0 & 127);
    WBAR_SYNC(NB_G0 + 2, 128);
    load_frags<NR>(wf, sb + OFF_WV + VSS * 2048, tid0);
  }
  fence_async();
  WBAR_SYNC(NB_B, 384);
  const int wu = uni((tid0 >> 5) & 3);
  uint32_t nredo = 0;
  const AttAddr aa = att_addr(sb, bc, WG, tid0);
#pragma unroll 1
  for (int k = 0; k < NSTEP + (WG == 0); k++) {
    if (WG || k < NSTEP) {
    {
      float d[32];
#pragma unroll
      for (int c = 0; c < 10; c++) {
        mwait(sb + BAR_F + 8 * (c % 5), c / 5, spin);
        if (c == 0 && bc == 0 && WG != 1) WTS(k, WG ? 15 : 6);
        wg_fence();
#pragma unroll
        for (int kk = 0; kk < 4; kk++) {
          const int q = 4 * c + kk;
          const uint64_t db = rdesc(OFF_X + (c % 5) * 8192, kk);
          if (IS_V ? q >= VSS : q < NR) wgmma_rs64(d, wf[IS_V ? (q >= VSS ? q - VSS : 0) : (q < NR ? q : 0)], db, q);
          else if (IS_V) wgmma_ts64(d, mkdesc(SB0 + OFF_WV + q * 2048, 8192, 1024), db, q);
          else wgmma_ts64(d, desc_at(mkdesc(SB0 + OFF_Y + (q - NR) * 2048, 8192, 1024), yo), db, 1);
        }
        wg_commit();
        if (c > 0 && c <= 7) {
          wg_wait<1>();
          if ((tid0 & 31) == 0) mbar_arrive(sb + BAR_E + 8 * ((c - 1) % 5));
        }
      }
      wg_wait<0>();
      if (bc == 0 && WG != 1) WTS(k, 16 + WG / 2);
      WBAR_SYNC(NB_B, 384);
      const int tid = fresh(tid0), m = (tid >> 3) & 3;
      const uint32_t a = sb + OFF_T + min(wu * 16 + (m & 1) * 8 + (tid & 7), 60) * 16 + (8 * WG + (m >> 1)) * COL;
#pragma unroll
      for (int p = 0; p < 4; p++) {
        stsm4(a + 2 * p * COL, pack_bf16(d[8 * p], d[8 * p + 1]), pack_bf16(d[8 * p + 2], d[8 * p + 3]), pack_bf16(d[8 * p + 4], d[8 * p + 5]), pack_bf16(d[8 * p + 6], d[8 * p + 7]));
      }
    }
    WBAR_SYNC(NB_TD, 416);
    if (bc == 0 && WG == 0) WTS(k, 7);
    if (bc * 3 + WG < NH && (wu < 2 ? k < NSEG : k >= LAG)) attend(sb, aa, k, wu, fresh(tid0));
    else release_tiles(sb, tid0);
    if (bc == 0 && WG == 0) WTS(k, 8);
    WBAR_SYNC(NB_AS, 416);
    }
    const int s = k - (1 - WG) * (LAG + 1);
    if (!IS_V && bc < 10 && s >= 0 && s < NSEG) {
      float d[16];
#pragma unroll
      for (int f = 0; f < 5; f++) {
        mwait(sb + BAR_G + 40 * WG + 8 * f, s & 1, spin);
        if (f == 0 && bc == 0) WTS(k - 1 + WG, WG || k > NSEG ? 20 : 23);
        wg_fence();
#pragma unroll
        for (int kk = 0; kk < 8; kk++) {
          wgmma_tt32(d, mkdesc(SB0 + OFF_WO + (8 * f + kk) * 2048, 8192, 1024), gdesc(OFF_X + f * 8192, kk), f | kk);
          if (kk == 1 && f > 0) {
            wg_commit();
            wg_wait<1>();
            if ((tid0 & 31) < 3) mbar_arrive(sb + BAR_E + 8 * (f - 1));
          }
        }
        wg_commit();
      }
      wg_wait<0>();
      if (WG == 1 && FSA) {
        const float chk = ((d[0] + d[1]) + (d[4] + d[5])) + ((d[8] + d[9]) + (d[12] + d[13]));
        if (__builtin_expect(bar_red_or(NB_RED, 128, chk != chk), 0)) {
          if (wu == 0) { cwait(CN_A + k, NBC, spin); fence_async_all(); }
#pragma unroll
          for (int q = 0; q < 16; q++) d[q] = 0.f;
#pragma unroll 1
          for (int f = 0; f < 5; f++) {
            if (wu == 0 && elect_one()) { mbar_expect_tx(sb + BAR_W + 8, 8192); bulk_g2s(sb + OFF_X + 32768, g_ob[k] + f * 8192, 8192, sb + BAR_W + 8); }
            __syncwarp();
            mwait(sb + BAR_W + 8, nredo & 1, spin);
            nredo++;
            wg_fence();
#pragma unroll
            for (int kk = 0; kk < 8; kk++)
              wgmma_tt32(d, desc_at(mkdesc(SB0 + OFF_WO + kk * 2048, 8192, 1024), f * 16384), gdesc(OFF_X + 32768, kk), 1);
            wg_commit();
            wg_wait<0>();
            bar_sync(NB_RED, 128);
          }
        }
      }
      else bar_sync(NB_RED + 2 - WG, 128);
      if (bc == 0) WTS(k - 1 + WG, WG || k > NSEG ? 10 : 24);
      const int tid = fresh(tid0), m = (tid >> 3) & 3, row = (m >> 1) * 16 + 2 * (tid & 7);
      const uint32_t a = sb + OFF_X + 32768 + row * 128 + (((2 * wu + (m & 1)) ^ row) & 7) * 16;
#pragma unroll
      for (int p = 0; p < 2; p++)
        stsm4t(a ^ (p * 144), pack_bf16(d[8 * p], d[8 * p + 1]), pack_bf16(d[8 * p + 2], d[8 * p + 3]), pack_bf16(d[8 * p + 4], d[8 * p + 5]), pack_bf16(d[8 * p + 6], d[8 * p + 7]));
      fence_async();
      WBAR_SYNC(WG ? NB_SG : NB_SG1, 160);
    }
  }
  if (spin >= SPIN_TOT) g_err = 14;
}
__device__ __forceinline__ bool b_job(int k, int u, int bc) { return u < 2 ? k < NSTEP : bc < 10 && (u == 2 ? k > LAG : k < NSEG); }
__device__ __forceinline__ void work_b_watch(uint32_t sb, int bc) {
  using namespace W;
  int spin = 0;
#pragma unroll 1
  for (int j = 0; j < 4 * NSTEP + 3; j++) {
    const int k = j >> 2, u = j & 3;
    if (u == 1 || !b_job(k, u, bc)) continue;
    cwait(u == 0 ? CN_L + k : u == 2 ? CN_A + k - 1 : (FSA ? CN_F : CN_A) + k, u ? NBC : k < LAG || k >= NSEG ? 32 : 64, spin);
    fence_async_all();
    if (bc == 0 && (u != 2 || k > NSEG)) WTS1(k + (u ? u - 3 : 0), u ? 9 : 5);
    if (elect_one()) mbar_arrive(sb + BAR_R + 8 * u);
    __syncwarp();
    if (u == 0) WBAR_SYNC(NB_R, 64);
  }
  if (spin >= SPIN_TOT) g_err = 16;
}
__device__ __forceinline__ void work_b_producer(uint32_t sb, int bc) {
  using namespace W;
  int spin = 0;
  uint32_t pe = 1;
#pragma unroll 1
  for (int j = 0; j < 4 * NSTEP + 3; j++) {
    const int k = j >> 2, u = j & 3;
    if (!b_job(k, u, bc)) continue;
    const uint32_t half = u < 2 && (k < LAG || k >= NSEG), lo = half && k >= NSEG ? 4096 : 0, len = half ? 4096 : 8192, fb = sb + (u < 2 ? BAR_F : BAR_G + 40 * (u - 2));
    const uint8_t* src = (u < 2 ? g_xnb[k] + u * 40960 : u == 2 ? g_ob[k - 1] + 40960 : g_ob[k]) + lo;
    if (u != 1) mwait(sb + BAR_R + 8 * u, (u == 2 ? k - LAG - 1 : k) & 1, spin);
#pragma unroll
    for (int f = 0; f < 5; f++) {
      mwait(sb + BAR_E + 8 * f, pe, spin);
      if (elect_one()) {
        mbar_expect_tx(fb + 8 * f, len);
        bulk_g2s(sb + OFF_X + f * 8192 + lo, src + f * 8192, len, fb + 8 * f);
      }
    }
    if (u == 0) WBAR_SYNC(NB_R, 64);
    pe ^= 1;
  }
  if (spin >= SPIN_TOT) g_err = 15;
}

__global__ void __launch_bounds__(512, 1)
k_work(const __grid_constant__ CUtensorMap tmWo, const __grid_constant__ CUtensorMap tmBo, const bf16* __restrict__ wqkv, bf16* __restrict__ out,
       const bf16* __restrict__ x0, const bf16* __restrict__ mem0) {
  using namespace W;
  extern __shared__ __align__(1024) uint8_t smem[];
  const uint32_t sb = smem_u32(smem);
  const int tid = threadIdx.x, w = blockIdx.x;
  const int wg = __shfl_sync(0xffffffffu, tid >> 7, 0);
  if (tid == 0) {
    if (sb != SB0) g_err = 101;
    for (int i = 0; i < 5; i++) { mbar_init(sb + BAR_F + 8 * i, 1); mbar_init(sb + BAR_E + 8 * i, w < NP ? 8 : 12); }
    for (int i = 0; i < 16; i++) mbar_init(sb + BAR_G + 8 * i, 1);
    for (int p = 0; p < 16; p++) sts32(sb + OFF_SAFE + 4 * p, 0);
    asm volatile("fence.mbarrier_init.release.cluster;" ::: "memory");
    int spin = 0;
    pre_wait(1, NW, spin);
    if (spin >= SPIN_TOT) g_err = 18;
  }
  if (tid < 8 * COL / 16) sts128(sb + OFF_H + tid * 16, make_uint4(0, 0, 0, 0));
  fence_async();
  __syncthreads();

  if (w < NP) {
    if (wg < 2) work_p(tmWo, sb, w, wg, keep(tid));
    else {
      asm volatile("setmaxnreg.dec.sync.aligned.u32 48;");
      const int aw = uni(tid >> 5) - 8;
      if (aw < 2) {
        work_p_producer(sb, w, aw);
      } else {
        const int id = (aw - 2) * NP + w;
        if (id < 128) work_ln(id & 3, id >> 2, tid & 31, out);
        else if (id < 144 && NOWORK != 2) work_prep(x0, mem0, id - 128, tid & 31);
      }
    }
  } else {
    const int bc = w - NP;
    if (wg < 2) work_b<false>(tmBo, wqkv, sb, bc, wg, keep(tid));
    else if (wg == 2) work_b<true>(tmBo, wqkv, sb, bc, wg, keep(tid));
    else {
      asm volatile("setmaxnreg.dec.sync.aligned.u32 24;");
      const int aw = uni(tid >> 5) - 12;
      if (aw == 0) work_b_producer(sb, bc);
      else if (aw == 1) work_b_watch(sb, bc);
      else if (aw == 2) {
#pragma unroll 1
        for (int k = 0; k < NSTEP; k++) {
          WBAR_ARRIVE(NB_TD, 416);
          WBAR_SYNC(NB_AS, 416);
          if (elect_one()) {
            const uint32_t len = bc < 10 ? 3840 : 2560;
            if (k < NSEG) bulk_s2g(g_ob[k] + bc * 3840, sb + OFF_S, len);
            if (k >= LAG) bulk_s2g(g_ob[k] + 40960 + bc * 3840, sb + OFF_S + 3840, len);
            asm volatile("cp.async.bulk.commit_group;" ::: "memory");
            asm volatile("cp.async.bulk.wait_group 0;" ::: "memory");
            if (FSA) csignal_fast(CN_F + k);
            fence_async_all();
            csignal_t(CN_A + k, 5);
          }
          __syncwarp();
        }
      } else if (bc < 10) {
#pragma unroll 1
        for (int j = 0; j < 2 * NSTEP + 1; j++) {
          const int l = (j & 1) ^ 1, s = (j >> 1) - l * (LAG + 1);
          if (s < 0 || s >= NSEG) continue;
          WBAR_SYNC(l ? NB_SG1 : NB_SG, 160);
          if (elect_one()) {
            bulk_s2g(g_y[l] + (size_t)s * 40960 + bc * 4096, sb + OFF_X + 32768, 4096);
            asm volatile("cp.async.bulk.commit_group;" ::: "memory");
            asm volatile("cp.async.bulk.wait_group 0;" ::: "memory");
            asm volatile("mbarrier.arrive.shared::cta.b64 _,[%0],12;" ::"r"(sb + BAR_E + 32) : "memory");
            csignal_fast(CN_W + l * 64 + s);
          }
          __syncwarp();
        }
      }
    }
  }
  __syncthreads();
  asm volatile("griddepcontrol.wait;" ::: "memory");
}

typedef CUresult (*EncodeFn)(CUtensorMap*, CUtensorMapDataType, cuuint32_t, void*, const cuuint64_t*, const cuuint64_t*,
                             const cuuint32_t*, const cuuint32_t*, CUtensorMapInterleave, CUtensorMapSwizzle,
                             CUtensorMapL2promotion, CUtensorMapFloatOOBfill);

static void make_map(EncodeFn enc, CUtensorMap* tm, const void* ptr, uint64_t cols, uint64_t rows, uint32_t boxc, uint32_t boxr) {
  cuuint64_t dims[2] = {cols, rows};
  cuuint64_t strides[1] = {cols * 2};
  cuuint32_t box[2] = {boxc, boxr};
  cuuint32_t es[2] = {1, 1};
  enc(tm, CU_TENSOR_MAP_DATA_TYPE_BFLOAT16, 2, const_cast<void*>(ptr), dims, strides, box, es, CU_TENSOR_MAP_INTERLEAVE_NONE,
      CU_TENSOR_MAP_SWIZZLE_128B, CU_TENSOR_MAP_L2_PROMOTION_L2_256B, CU_TENSOR_MAP_FLOAT_OOB_FILL_NONE);
}

extern "C" void kernel_launch(void* const* d_in, const int* in_sizes, int n_in, void* d_out, int out_size) {
  const bf16* x0 = (const bf16*)d_in[0];
  const bf16* mem0 = (const bf16*)d_in[1];
  const bf16* Wq = (const bf16*)d_in[2];
  const bf16* Wk = (const bf16*)d_in[3];
  const bf16* Wv = (const bf16*)d_in[4];
  const bf16* Wo = (const bf16*)d_in[5];
  const bf16* Bqkv = (const bf16*)d_in[8];
  const bf16* Bwo = (const bf16*)d_in[9];
  bf16* out = (bf16*)d_out;

  static EncodeFn enc = nullptr;
  if (!enc) {
    void* fn = nullptr;
    cudaDriverEntryPointQueryResult qr;
    cudaGetDriverEntryPoint("cuTensorMapEncodeTiled", &fn, cudaEnableDefault, &qr);
    enc = (EncodeFn)fn;
    cudaFuncSetAttribute(k_chain, cudaFuncAttributeMaxDynamicSharedMemorySize, C::SMEM);
    cudaFuncSetAttribute(k_work, cudaFuncAttributeMaxDynamicSharedMemorySize, W::SMEM);
  }
  CUtensorMap tmWq, tmWk, tmWv, tmWo, tmWp, tmBo;
  make_map(enc, &tmWq, Wq, NH * DH, DM, 64, 128);
  make_map(enc, &tmWk, Wk, NH * DH, DM, 64, 128);
  make_map(enc, &tmWv, Wv, NH * DH, DM, 64, 128);
  make_map(enc, &tmWo, Wo, DM, NH * DH, 64, 64);
  make_map(enc, &tmWp, Wo, DM, NH * DH, 64, 16);
  make_map(enc, &tmBo, Bwo, DM, DM, 64, 64);

  cudaStream_t st = cudaStreamPerThread;
  cudaLaunchAttribute at[1];
  at[0].id = cudaLaunchAttributeProgrammaticStreamSerialization; at[0].val.programmaticStreamSerializationAllowed = 1;
  {
    cudaLaunchConfig_t cfg = {};
    cfg.gridDim = dim3(96); cfg.blockDim = dim3(384); cfg.dynamicSmemBytes = C::SMEM; cfg.stream = st;
    cfg.attrs = at; cfg.numAttrs = 0;
    cudaLaunchKernelEx(&cfg, k_chain, tmWq, tmWk, tmWv, tmWo, x0, mem0);
  }
  cudaLaunchConfig_t cfg = {};
  cfg.gridDim = dim3(W::NW); cfg.blockDim = dim3(512); cfg.dynamicSmemBytes = W::SMEM; cfg.stream = st;
  cfg.attrs = at; cfg.numAttrs = NOWORK == 2 ? 0 : 1;
  cudaLaunchKernelEx(&cfg, k_work, tmWp, tmBo, Bqkv, out, x0, mem0);
}
```

```cpp
#include <cuda_runtime.h>
#include <cuda_bf16.h>
#include <cuda.h>
#include <stdint.h>

typedef __nv_bfloat16 bf16;

constexpr int SEQ = 2048, DM = 640, NH = 32, DH = 192, NSEG = 64;
#define LAG 5
constexpr int NSTEP = NSEG + LAG;
constexpr int NPRE = 4;
constexpr uint32_t SENT = 0xFFFFFFFFu;

constexpr int MAIL9 = 288 * 2048, MAIL_BYTES = MAIL9 + 64 * 3072;
__device__ __align__(1024) uint8_t g_xn[NSTEP][81920];
__device__ __align__(1024) uint8_t g_xnb[NSTEP][81920];
__device__ __align__(1024) uint8_t g_ob[NSTEP][81920];
__device__ __align__(1024) uint8_t g_y[2][NSEG * 40960];
#define ORING 8
static_assert(ORING > LAG, "a slot is free again LAG + 1 steps later");
__device__ __align__(1024) uint8_t g_o[ORING][96][8192];
__device__ __align__(1024) float g_x[SEQ * DM];
constexpr int EX_MAIL = 0;
constexpr int EX_M = 2 << 20;
constexpr int EX_FLAG = EX_M + NSTEP * 20480;
static_assert(EX_FLAG + NSTEP * 3072 <= (4 << 20), "");
__device__ __align__(1024) uint8_t g_ex[8 << 20];
__host__ __device__ __forceinline__ uint8_t* ex_window(uint8_t* p) { return reinterpret_cast<uint8_t*>((reinterpret_cast<uint64_t>(p) + (4 << 20) - 1) & ~(uint64_t)((4 << 20) - 1)); }
enum { CN_P = 0, CN_L = 128, CN_A = 256, CN_W = 384, CN_X = 512, CN_F = 640, CN_O = 768, CN_NUM = CN_O + 5 * NSTEP };
__device__ __align__(128) uint32_t g_cnt[CN_NUM][32];
__device__ __align__(128) uint32_t g_ticket[2][32];
__device__ int g_err;
#define TS(jj, i)
#define TS1(jj, i)
#define PTS(i)
#define TSB(jj, i)
#define TSV(jj, i, v)
#define TS_FLUSH(jj)
#define WTS(b, k)
#define WTS1(b, k)
#define WW -1

__device__ __forceinline__ uint32_t smem_u32(const void* p) { return (uint32_t)__cvta_generic_to_shared(p); }
__device__ __forceinline__ uint32_t clk32() { uint32_t t; asm volatile("mov.u32 %0, %%clock;" : "=r"(t)::"memory"); return t; }
__device__ __forceinline__ uint32_t mapa(uint32_t a, uint32_t r) { uint32_t o; asm("mapa.shared::cluster.u32 %0,%1,%2;" : "=r"(o) : "r"(a), "r"(r)); return o; }
__device__ __forceinline__ void mbar_init(uint32_t bar, uint32_t cnt) { asm volatile("mbarrier.init.shared::cta.b64 [%0],%1;" ::"r"(bar), "r"(cnt) : "memory"); }
__device__ __forceinline__ void mbar_expect_tx(uint32_t bar, uint32_t bytes) { asm volatile("mbarrier.arrive.expect_tx.shared::cta.b64 _,[%0],%1;" ::"r"(bar), "r"(bytes) : "memory"); }
__device__ __forceinline__ void mbar_arrive(uint32_t bar) { asm volatile("mbarrier.arrive.shared::cta.b64 _,[%0];" ::"r"(bar) : "memory"); }
__device__ __forceinline__ void mbar_arrive_cluster(uint32_t bar) { asm volatile("mbarrier.arrive.shared::cluster.b64 _,[%0];" ::"r"(bar) : "memory"); }
__device__ __forceinline__ bool mbar_try(uint32_t bar, uint32_t ph) {
  uint32_t ok;
  asm volatile("{.reg .pred p; mbarrier.try_wait.parity.shared::cta.b64 p,[%1],%2; selp.u32 %0,1,0,p;}" : "=r"(ok) : "r"(bar), "r"(ph) : "memory");
  return ok;
}
__device__ __forceinline__ bool mbar_test(uint32_t bar, uint32_t ph) {
  uint32_t ok;
  asm volatile("{.reg .pred p; mbarrier.test_wait.parity.shared::cta.b64 p,[%1],%2; selp.u32 %0,1,0,p;}" : "=r"(ok) : "r"(bar), "r"(ph) : "memory");
  return ok;
}
__device__ __forceinline__ int fresh(int x) { asm volatile("" : "+r"(x)); return x; }
#define PHASE_IDS const int tid = fresh(tid0), lane = tid & 31, w = tid >> 5, g = lane >> 2, t = lane & 3; (void)w; (void)g; (void)t
__device__ __forceinline__ void bar_sync(int id, int n) { asm volatile("bar.sync %0,%1;" ::"r"(id), "r"(n) : "memory"); }
__device__ __forceinline__ void bar_arrive(int id, int n) { asm volatile("bar.arrive %0,%1;" ::"r"(id), "r"(n) : "memory"); }
__device__ __forceinline__ bool bar_red_or(int id, int n, bool v) {
  uint32_t r;
  asm volatile("{\n .reg .pred p, q;\n setp.ne.u32 q, %3, 0;\n barrier.cta.red.or.pred p, %1, %2, q;\n selp.u32 %0, 1, 0, p;\n}" : "=r"(r) : "r"(id), "r"(n), "r"((uint32_t)v) : "memory");
  return r != 0;
}
__device__ __forceinline__ void fence_async() { asm volatile("fence.proxy.async.shared::cta;" ::: "memory"); }
__device__ __forceinline__ void bulk_g2s(uint32_t dst, const void* src, uint32_t bytes, uint32_t bar) {
  asm volatile("cp.async.bulk.shared::cluster.global.mbarrier::complete_tx::bytes [%0],[%1],%2,[%3];" ::"r"(dst), "l"(src), "r"(bytes), "r"(bar) : "memory");
}
__device__ __forceinline__ void bulk_g2s_mc(uint32_t dst, const void* src, uint32_t bytes, uint32_t bar) {
  asm volatile("cp.async.bulk.shared::cluster.global.mbarrier::complete_tx::bytes.multicast::cluster [%0],[%1],%2,[%3],%4;"
               ::"r"(dst), "l"(src), "r"(bytes), "r"(bar), "h"((uint16_t)7) : "memory");
}
__device__ __forceinline__ void bulk_s2g(void* dst, uint32_t src, uint32_t bytes) {
  asm volatile("cp.async.bulk.global.shared::cta.bulk_group [%0],[%1],%2;" ::"l"(dst), "r"(src), "r"(bytes) : "memory");
}
__device__ __forceinline__ void bulk_s2c(uint32_t dst, uint32_t src, uint32_t bytes, uint32_t bar) {
  asm volatile("cp.async.bulk.shared::cluster.shared::cta.mbarrier::complete_tx::bytes [%0],[%1],%2,[%3];" ::"r"(dst), "r"(src), "r"(bytes), "r"(bar) : "memory");
}
__device__ __forceinline__ void tma2d(uint32_t dst, const CUtensorMap* tm, int c0, int c1, uint32_t bar) {
  asm volatile("cp.async.bulk.tensor.2d.shared::cluster.global.mbarrier::complete_tx::bytes [%0],[%1,{%3,%4}],[%2];"
               ::"r"(dst), "l"(tm), "r"(bar), "r"(c0), "r"(c1) : "memory");
}
__device__ __forceinline__ void tma2d_prefetch(const CUtensorMap* tm, int c0, int c1) {
  asm volatile("cp.async.bulk.prefetch.tensor.2d.L2.global.tile [%0,{%1,%2}];" ::"l"(tm), "r"(c0), "r"(c1) : "memory");
}
__device__ __forceinline__ uint32_t pack_bf16(float lo, float hi) {
  uint32_t r; asm("cvt.rn.bf16x2.f32 %0,%1,%2;" : "=r"(r) : "f"(hi), "f"(lo)); return r;
}
__device__ __forceinline__ float bf_lo(uint32_t x) { return __uint_as_float(x << 16); }
__device__ __forceinline__ float bf_hi(uint32_t x) { return __uint_as_float(x & 0xFFFF0000u); }
__device__ __forceinline__ float ex2(float x) { float y; asm("ex2.approx.ftz.f32 %0,%1;" : "=f"(y) : "f"(x)); return y; }
__device__ __forceinline__ void ldsm4(uint32_t (&r)[4], uint32_t a) {
  asm volatile("ldmatrix.sync.aligned.m8n8.x4.shared.b16 {%0,%1,%2,%3},[%4];" : "=r"(r[0]), "=r"(r[1]), "=r"(r[2]), "=r"(r[3]) : "r"(a) : "memory");
}
__device__ __forceinline__ void ldsm4t(uint32_t (&r)[4], uint32_t a) {
  asm volatile("ldmatrix.sync.aligned.m8n8.x4.trans.shared.b16 {%0,%1,%2,%3},[%4];" : "=r"(r[0]), "=r"(r[1]), "=r"(r[2]), "=r"(r[3]) : "r"(a) : "memory");
}
__device__ __forceinline__ void ldsm2(uint32_t& r0, uint32_t& r1, uint32_t a) {
  asm volatile("ldmatrix.sync.aligned.m8n8.x2.shared.b16 {%0,%1},[%2];" : "=r"(r0), "=r"(r1) : "r"(a) : "memory");
}
__device__ __forceinline__ void ldsm2t(uint32_t& r0, uint32_t& r1, uint32_t a) {
  asm volatile("ldmatrix.sync.aligned.m8n8.x2.trans.shared.b16 {%0,%1},[%2];" : "=r"(r0), "=r"(r1) : "r"(a) : "memory");
}
__device__ __forceinline__ void ldsm1(uint32_t& r0, uint32_t a) {
  asm volatile("ldmatrix.sync.aligned.m8n8.x1.shared.b16 {%0},[%1];" : "=r"(r0) : "r"(a) : "memory");
}
__device__ __forceinline__ void mma16816(float (&d)[4], uint32_t a0, uint32_t a1, uint32_t a2, uint32_t a3, uint32_t b0, uint32_t b1) {
  asm volatile("mma.sync.aligned.m16n8k16.row.col.f32.bf16.bf16.f32 {%0,%1,%2,%3},{%4,%5,%6,%7},{%8,%9},{%0,%1,%2,%3};"
               : "+f"(d[0]), "+f"(d[1]), "+f"(d[2]), "+f"(d[3]) : "r"(a0), "r"(a1), "r"(a2), "r"(a3), "r"(b0), "r"(b1));
}
__device__ __forceinline__ void mma1688(float (&d)[4], uint32_t a0, uint32_t a1, uint32_t b0) {
  asm volatile("mma.sync.aligned.m16n8k8.row.col.f32.bf16.bf16.f32 {%0,%1,%2,%3},{%4,%5},{%6},{%0,%1,%2,%3};"
               : "+f"(d[0]), "+f"(d[1]), "+f"(d[2]), "+f"(d[3]) : "r"(a0), "r"(a1), "r"(b0));
}
__device__ __forceinline__ void sts32(uint32_t a, uint32_t v) { asm volatile("st.shared.b32 [%0],%1;" ::"r"(a), "r"(v) : "memory"); }
__device__ __forceinline__ void sts64f(uint32_t a, float x, float y) { asm volatile("st.shared.v2.f32 [%0],{%1,%2};" ::"r"(a), "f"(x), "f"(y) : "memory"); }
__device__ __forceinline__ void sts128(uint32_t a, uint4 v) { asm volatile("st.shared.v4.b32 [%0],{%1,%2,%3,%4};" ::"r"(a), "r"(v.x), "r"(v.y), "r"(v.z), "r"(v.w) : "memory"); }
__device__ __forceinline__ float lds32f(uint32_t a) { float v; asm volatile("ld.shared.f32 %0,[%1];" : "=f"(v) : "r"(a) : "memory"); return v; }
__device__ __forceinline__ float2 lds64f(uint32_t a) { float2 v; asm volatile("ld.shared.v2.f32 {%0,%1},[%2];" : "=f"(v.x), "=f"(v.y) : "r"(a) : "memory"); return v; }
__device__ __forceinline__ uint4 lds128(uint32_t a) { uint4 v; asm volatile("ld.shared.v4.b32 {%0,%1,%2,%3},[%4];" : "=r"(v.x), "=r"(v.y), "=r"(v.z), "=r"(v.w) : "r"(a) : "memory"); return v; }
__device__ __forceinline__ float4 lds128f(uint32_t a) { float4 v; asm volatile("ld.shared.v4.f32 {%0,%1,%2,%3},[%4];" : "=f"(v.x), "=f"(v.y), "=f"(v.z), "=f"(v.w) : "r"(a) : "memory"); return v; }
__device__ __forceinline__ void st_async2(uint32_t a, float x, float y, uint32_t bar) {
  asm volatile("st.async.weak.shared::cluster.mbarrier::complete_tx::bytes.v2.f32 [%0],{%1,%2},[%3];" ::"r"(a), "f"(x), "f"(y), "r"(bar) : "memory");
}
__device__ __forceinline__ void st_async4(uint32_t a, const float (&v)[4], uint32_t bar) {
  asm volatile("st.async.weak.shared::cluster.mbarrier::complete_tx::bytes.v4.f32 [%0],{%1,%2,%3,%4},[%5];" ::"r"(a), "f"(v[0]), "f"(v[1]), "f"(v[2]), "f"(v[3]), "r"(bar) : "memory");
}
__device__ __forceinline__ void st_async4v(uint32_t a, float x, float y, float z, float w, uint32_t bar) {
  asm volatile("st.async.weak.shared::cluster.mbarrier::complete_tx::bytes.v4.f32 [%0],{%1,%2,%3,%4},[%5];" ::"r"(a), "f"(x), "f"(y), "f"(z), "f"(w), "r"(bar) : "memory");
}
__device__ __forceinline__ void st_async4u(uint32_t a, const uint4& v, uint32_t bar) {
  asm volatile("st.async.weak.shared::cluster.mbarrier::complete_tx::bytes.v4.b32 [%0],{%1,%2,%3,%4},[%5];" ::"r"(a), "r"(v.x), "r"(v.y), "r"(v.z), "r"(v.w), "r"(bar) : "memory");
}
__device__ __forceinline__ uint4 ld_relaxed4(const void* p) {
  uint4 v; asm volatile("ld.relaxed.gpu.global.v4.u32 {%0,%1,%2,%3},[%4];" : "=r"(v.x), "=r"(v.y), "=r"(v.z), "=r"(v.w) : "l"(p) : "memory"); return v;
}
__device__ __forceinline__ uint32_t ld_relaxed(const void* p) {
  uint32_t v; asm volatile("ld.relaxed.gpu.global.u32 %0,[%1];" : "=r"(v) : "l"(p) : "memory"); return v;
}
__device__ __forceinline__ void st_relaxed(void* p, uint32_t v) { asm volatile("st.relaxed.gpu.global.b32 [%0],%1;" ::"l"(p), "r"(v) : "memory"); }
__device__ __forceinline__ void st_relaxed4(void* p, uint32_t v) { asm volatile("st.relaxed.gpu.global.v4.b32 [%0],{%1,%1,%1,%1};" ::"l"(p), "r"(v) : "memory"); }

__device__ __forceinline__ uint32_t ld_acquire(const void* p) {
  uint32_t v; asm volatile("ld.acquire.gpu.global.u32 %0,[%1];" : "=r"(v) : "l"(p) : "memory"); return v;
}
__device__ __forceinline__ float4 ld_relaxed4f(const void* p) {
  float4 v; asm volatile("ld.relaxed.gpu.global.v4.f32 {%0,%1,%2,%3},[%4];" : "=f"(v.x), "=f"(v.y), "=f"(v.z), "=f"(v.w) : "l"(p) : "memory"); return v;
}
__device__ __forceinline__ float2 ld_relaxed2f(const void* p) {
  float2 v; asm volatile("ld.relaxed.gpu.global.v2.f32 {%0,%1},[%2];" : "=f"(v.x), "=f"(v.y) : "l"(p) : "memory"); return v;
}
__device__ __forceinline__ void prefetch_l2(const void* p) { asm volatile("prefetch.global.L2 [%0];" ::"l"(p)); }
__device__ __forceinline__ void fence_gpu() { asm volatile("fence.acq_rel.gpu;" ::: "memory"); }
__device__ __forceinline__ void fence_async_all() { asm volatile("fence.proxy.async.global;" ::: "memory"); }
constexpr int SPIN_TOT = 1 << 22;
__device__ __forceinline__ void csignal(int idx) { asm volatile("red.release.gpu.global.add.u32 [%0],1;" ::"l"(&g_cnt[idx][0]) : "memory"); }
__device__ __forceinline__ void csignal_fast(int idx) { asm volatile("red.relaxed.gpu.global.add.u32 [%0],1;" ::"l"(&g_cnt[idx][0]) : "memory"); }
#define UNS 0
#define RLX 1
#define csignal_t(idx, role) csignal(idx)
__device__ __forceinline__ void cwait(int idx, uint32_t target, int& spin) {
  while (ld_relaxed(&g_cnt[idx][0]) < target && spin < SPIN_TOT) spin += 16;
}

__device__ __forceinline__ uint64_t mkdesc(uint32_t addr, uint32_t lbo, uint32_t sbo) {
  return (uint64_t)((addr & 0x3FFFF) >> 4) | ((uint64_t)(lbo >> 4) << 16) | ((uint64_t)(sbo >> 4) << 32) | ((uint64_t)1 << 62);
}
__device__ __forceinline__ uint64_t mkdesc_ns(uint32_t addr, uint32_t lbo, uint32_t sbo) {
  return (uint64_t)((addr & 0x3FFFF) >> 4) | ((uint64_t)(lbo >> 4) << 16) | ((uint64_t)(sbo >> 4) << 32);
}
__device__ __forceinline__ void wg_fence() { asm volatile("wgmma.fence.sync.aligned;" ::: "memory"); }
__device__ __forceinline__ void wg_commit() { asm volatile("wgmma.commit_group.sync.aligned;" ::: "memory"); }
template <int N> __device__ __forceinline__ void wg_wait() { asm volatile("wgmma.wait_group.sync.aligned %0;" ::"n"(N) : "memory"); }

__device__ __forceinline__ void wgmma_rs16(float (&d)[8], const uint32_t (&a)[4], uint64_t db, int sc) {
  asm volatile("{.reg .pred p; setp.ne.b32 p,%13,0; wgmma.mma_async.sync.aligned.m64n16k16.f32.bf16.bf16 "
               "{%0,%1,%2,%3,%4,%5,%6,%7},{%8,%9,%10,%11},%12,p,1,1,0;}"
               : "+f"(d[0]), "+f"(d[1]), "+f"(d[2]), "+f"(d[3]), "+f"(d[4]), "+f"(d[5]), "+f"(d[6]), "+f"(d[7])
               : "r"(a[0]), "r"(a[1]), "r"(a[2]), "r"(a[3]), "l"(db), "r"(sc));
}
__device__ __forceinline__ void wgmma_rs64(float (&d)[32], const uint32_t (&a)[4], uint64_t db, int sc) {
  asm volatile("{.reg .pred p; setp.ne.b32 p,%37,0; wgmma.mma_async.sync.aligned.m64n64k16.f32.bf16.bf16 "
               "{%0,%1,%2,%3,%4,%5,%6,%7,%8,%9,%10,%11,%12,%13,%14,%15,%16,%17,%18,%19,%20,%21,%22,%23,%24,%25,%26,%27,%28,%29,%30,%31},{%32,%33,%34,%35},%36,p,1,1,0;}"
               : "+f"(d[0]), "+f"(d[1]), "+f"(d[2]), "+f"(d[3]), "+f"(d[4]), "+f"(d[5]), "+f"(d[6]), "+f"(d[7]), "+f"(d[8]), "+f"(d[9]), "+f"(d[10]), "+f"(d[11]), "+f"(d[12]), "+f"(d[13]), "+f"(d[14]), "+f"(d[15]), "+f"(d[16]), "+f"(d[17]), "+f"(d[18]), "+f"(d[19]), "+f"(d[20]), "+f"(d[21]), "+f"(d[22]), "+f"(d[23]), "+f"(d[24]), "+f"(d[25]), "+f"(d[26]), "+f"(d[27]), "+f"(d[28]), "+f"(d[29]), "+f"(d[30]), "+f"(d[31])
               : "r"(a[0]), "r"(a[1]), "r"(a[2]), "r"(a[3]), "l"(db), "r"(sc));
}
__device__ __forceinline__ void wgmma_rt16(float (&d)[8], const uint32_t (&a)[4], uint64_t db, int sc) {
  asm volatile("{.reg .pred p; setp.ne.b32 p,%13,0; wgmma.mma_async.sync.aligned.m64n16k16.f32.bf16.bf16 "
               "{%0,%1,%2,%3,%4,%5,%6,%7},{%8,%9,%10,%11},%12,p,1,1,1;}"
               : "+f"(d[0]), "+f"(d[1]), "+f"(d[2]), "+f"(d[3]), "+f"(d[4]), "+f"(d[5]), "+f"(d[6]), "+f"(d[7])
               : "r"(a[0]), "r"(a[1]), "r"(a[2]), "r"(a[3]), "l"(db), "r"(sc));
}
__device__ __forceinline__ void wgmma_rt80(float (&d)[40], const uint32_t (&a)[4], uint64_t db, int sc) {
  asm volatile("{.reg .pred p; setp.ne.b32 p,%45,0; wgmma.mma_async.sync.aligned.m64n80k16.f32.bf16.bf16 "
               "{%0,%1,%2,%3,%4,%5,%6,%7,%8,%9,%10,%11,%12,%13,%14,%15,%16,%17,%18,%19,%20,%21,%22,%23,%24,%25,%26,%27,%28,%29,%30,%31,%32,%33,%34,%35,%36,%37,%38,%39},{%40,%41,%42,%43},%44,p,1,1,1;}"
               : "+f"(d[0]), "+f"(d[1]), "+f"(d[2]), "+f"(d[3]), "+f"(d[4]), "+f"(d[5]), "+f"(d[6]), "+f"(d[7]), "+f"(d[8]), "+f"(d[9]), "+f"(d[10]), "+f"(d[11]), "+f"(d[12]), "+f"(d[13]), "+f"(d[14]), "+f"(d[15]), "+f"(d[16]), "+f"(d[17]), "+f"(d[18]), "+f"(d[19]), "+f"(d[20]), "+f"(d[21]), "+f"(d[22]), "+f"(d[23]), "+f"(d[24]), "+f"(d[25]), "+f"(d[26]), "+f"(d[27]), "+f"(d[28]), "+f"(d[29]), "+f"(d[30]), "+f"(d[31]), "+f"(d[32]), "+f"(d[33]), "+f"(d[34]), "+f"(d[35]), "+f"(d[36]), "+f"(d[37]), "+f"(d[38]), "+f"(d[39])
               : "r"(a[0]), "r"(a[1]), "r"(a[2]), "r"(a[3]), "l"(db), "r"(sc));
}
__device__ __forceinline__ void wgmma_rs32(float (&d)[16], const uint32_t (&a)[4], uint64_t db, int sc) {
  asm volatile("{.reg .pred p; setp.ne.b32 p,%21,0; wgmma.mma_async.sync.aligned.m64n32k16.f32.bf16.bf16 "
               "{%0,%1,%2,%3,%4,%5,%6,%7,%8,%9,%10,%11,%12,%13,%14,%15},{%16,%17,%18,%19},%20,p,1,1,0;}"
               : "+f"(d[0]), "+f"(d[1]), "+f"(d[2]), "+f"(d[3]), "+f"(d[4]), "+f"(d[5]), "+f"(d[6]), "+f"(d[7]), "+f"(d[8]), "+f"(d[9]), "+f"(d[10]), "+f"(d[11]), "+f"(d[12]), "+f"(d[13]), "+f"(d[14]), "+f"(d[15])
               : "r"(a[0]), "r"(a[1]), "r"(a[2]), "r"(a[3]), "l"(db), "r"(sc));
}
__device__ __forceinline__ void wgmma_ts32(float (&d)[16], uint64_t da, uint64_t db, int sc) {
  asm volatile("{.reg .pred p; setp.ne.b32 p,%18,0; wgmma.mma_async.sync.aligned.m64n32k16.f32.bf16.bf16 "
               "{%0,%1,%2,%3,%4,%5,%6,%7,%8,%9,%10,%11,%12,%13,%14,%15},%16,%17,p,1,1,1,0;}"
               : "+f"(d[0]), "+f"(d[1]), "+f"(d[2]), "+f"(d[3]), "+f"(d[4]), "+f"(d[5]), "+f"(d[6]), "+f"(d[7]), "+f"(d[8]), "+f"(d[9]), "+f"(d[10]), "+f"(d[11]), "+f"(d[12]), "+f"(d[13]), "+f"(d[14]), "+f"(d[15])
               : "l"(da), "l"(db), "r"(sc));
}
__device__ __forceinline__ void wgmma_rs8(float (&d)[4], const uint32_t (&a)[4], uint64_t db, int sc) {
  asm volatile("{.reg .pred p; setp.ne.b32 p,%9,0; wgmma.mma_async.sync.aligned.m64n8k16.f32.bf16.bf16 "
               "{%0,%1,%2,%3},{%4,%5,%6,%7},%8,p,1,1,0;}"
               : "+f"(d[0]), "+f"(d[1]), "+f"(d[2]), "+f"(d[3])
               : "r"(a[0]), "r"(a[1]), "r"(a[2]), "r"(a[3]), "l"(db), "r"(sc));
}
__device__ __forceinline__ void wgmma_tt32(float (&d)[16], uint64_t da, uint64_t db, int sc) {
  asm volatile("{.reg .pred p; setp.ne.b32 p,%18,0; wgmma.mma_async.sync.aligned.m64n32k16.f32.bf16.bf16 "
               "{%0,%1,%2,%3,%4,%5,%6,%7,%8,%9,%10,%11,%12,%13,%14,%15},%16,%17,p,1,1,1,1;}"
               : "+f"(d[0]), "+f"(d[1]), "+f"(d[2]), "+f"(d[3]), "+f"(d[4]), "+f"(d[5]), "+f"(d[6]), "+f"(d[7]), "+f"(d[8]), "+f"(d[9]), "+f"(d[10]), "+f"(d[11]), "+f"(d[12]), "+f"(d[13]), "+f"(d[14]), "+f"(d[15])
               : "l"(da), "l"(db), "r"(sc));
}
__device__ __forceinline__ void wgmma_ts16(float (&d)[8], uint64_t da, uint64_t db, int sc) {
  asm volatile("{.reg .pred p; setp.ne.b32 p,%10,0; wgmma.mma_async.sync.aligned.m64n16k16.f32.bf16.bf16 "
               "{%0,%1,%2,%3,%4,%5,%6,%7},%8,%9,p,1,1,1,0;}"
               : "+f"(d[0]), "+f"(d[1]), "+f"(d[2]), "+f"(d[3]), "+f"(d[4]), "+f"(d[5]), "+f"(d[6]), "+f"(d[7])
               : "l"(da), "l"(db), "r"(sc));
}
__device__ __forceinline__ void wgmma_ts64(float (&d)[32], uint64_t da, uint64_t db, int sc) {
  asm volatile("{.reg .pred p; setp.ne.b32 p,%34,0; wgmma.mma_async.sync.aligned.m64n64k16.f32.bf16.bf16 "
               "{%0,%1,%2,%3,%4,%5,%6,%7,%8,%9,%10,%11,%12,%13,%14,%15,%16,%17,%18,%19,%20,%21,%22,%23,%24,%25,%26,%27,%28,%29,%30,%31},%32,%33,p,1,1,1,0;}"
               : "+f"(d[0]), "+f"(d[1]), "+f"(d[2]), "+f"(d[3]), "+f"(d[4]), "+f"(d[5]), "+f"(d[6]), "+f"(d[7]), "+f"(d[8]), "+f"(d[9]), "+f"(d[10]), "+f"(d[11]), "+f"(d[12]), "+f"(d[13]), "+f"(d[14]), "+f"(d[15]), "+f"(d[16]), "+f"(d[17]), "+f"(d[18]), "+f"(d[19]), "+f"(d[20]), "+f"(d[21]), "+f"(d[22]), "+f"(d[23]), "+f"(d[24]), "+f"(d[25]), "+f"(d[26]), "+f"(d[27]), "+f"(d[28]), "+f"(d[29]), "+f"(d[30]), "+f"(d[31])
               : "l"(da), "l"(db), "r"(sc));
}
__device__ __forceinline__ void wgmma_tt16(float (&d)[8], uint64_t da, uint64_t db, int sc) {
  asm volatile("{.reg .pred p; setp.ne.b32 p,%10,0; wgmma.mma_async.sync.aligned.m64n16k16.f32.bf16.bf16 "
               "{%0,%1,%2,%3,%4,%5,%6,%7},%8,%9,p,1,1,1,1;}"
               : "+f"(d[0]), "+f"(d[1]), "+f"(d[2]), "+f"(d[3]), "+f"(d[4]), "+f"(d[5]), "+f"(d[6]), "+f"(d[7])
               : "l"(da), "l"(db), "r"(sc));
}
__device__ __forceinline__ void wgmma_tt40(float (&d)[20], uint64_t da, uint64_t db, int sc) {
  asm volatile("{.reg .pred p; setp.ne.b32 p,%22,0; wgmma.mma_async.sync.aligned.m64n40k16.f32.bf16.bf16 "
               "{%0,%1,%2,%3,%4,%5,%6,%7,%8,%9,%10,%11,%12,%13,%14,%15,%16,%17,%18,%19},%20,%21,p,1,1,1,1;}"
               : "+f"(d[0]), "+f"(d[1]), "+f"(d[2]), "+f"(d[3]), "+f"(d[4]), "+f"(d[5]), "+f"(d[6]), "+f"(d[7]), "+f"(d[8]), "+f"(d[9]), "+f"(d[10]), "+f"(d[11]), "+f"(d[12]), "+f"(d[13]), "+f"(d[14]), "+f"(d[15]), "+f"(d[16]), "+f"(d[17]), "+f"(d[18]), "+f"(d[19])
               : "l"(da), "l"(db), "r"(sc));
}
__device__ __forceinline__ void wgmma_ss8(float (&d)[4], uint64_t da, uint64_t db, int sc) {
  asm volatile("{.reg .pred p; setp.ne.b32 p,%6,0; wgmma.mma_async.sync.aligned.m64n8k16.f32.bf16.bf16 "
               "{%0,%1,%2,%3},%4,%5,p,1,1,0,0;}"
               : "+f"(d[0]), "+f"(d[1]), "+f"(d[2]), "+f"(d[3])
               : "l"(da), "l"(db), "r"(sc));
}
__device__ __forceinline__ void wgmma_ss32(float (&d)[16], uint64_t da, uint64_t db, int sc) {
  asm volatile("{.reg .pred p; setp.ne.b32 p,%18,0; wgmma.mma_async.sync.aligned.m64n32k16.f32.bf16.bf16 "
               "{%0,%1,%2,%3,%4,%5,%6,%7,%8,%9,%10,%11,%12,%13,%14,%15},%16,%17,p,1,1,0,0;}"
               : "+f"(d[0]), "+f"(d[1]), "+f"(d[2]), "+f"(d[3]), "+f"(d[4]), "+f"(d[5]), "+f"(d[6]), "+f"(d[7]), "+f"(d[8]), "+f"(d[9]), "+f"(d[10]), "+f"(d[11]), "+f"(d[12]), "+f"(d[13]), "+f"(d[14]), "+f"(d[15])
               : "l"(da), "l"(db), "r"(sc));
}
__device__ __forceinline__ void wgmma_st64(float (&d)[32], uint64_t da, uint64_t db, int sc) {
  asm volatile("{.reg .pred p; setp.ne.b32 p,%34,0; wgmma.mma_async.sync.aligned.m64n64k16.f32.bf16.bf16 "
               "{%0,%1,%2,%3,%4,%5,%6,%7,%8,%9,%10,%11,%12,%13,%14,%15,%16,%17,%18,%19,%20,%21,%22,%23,%24,%25,%26,%27,%28,%29,%30,%31},%32,%33,p,1,1,0,1;}"
               : "+f"(d[0]), "+f"(d[1]), "+f"(d[2]), "+f"(d[3]), "+f"(d[4]), "+f"(d[5]), "+f"(d[6]), "+f"(d[7]), "+f"(d[8]), "+f"(d[9]), "+f"(d[10]), "+f"(d[11]), "+f"(d[12]), "+f"(d[13]), "+f"(d[14]), "+f"(d[15]), "+f"(d[16]), "+f"(d[17]), "+f"(d[18]), "+f"(d[19]), "+f"(d[20]), "+f"(d[21]), "+f"(d[22]), "+f"(d[23]), "+f"(d[24]), "+f"(d[25]), "+f"(d[26]), "+f"(d[27]), "+f"(d[28]), "+f"(d[29]), "+f"(d[30]), "+f"(d[31])
               : "l"(da), "l"(db), "r"(sc));
}
__device__ __forceinline__ void wgmma_st128(float (&d)[64], uint64_t da, uint64_t db, int sc) {
  asm volatile("{.reg .pred p; setp.ne.b32 p,%66,0; wgmma.mma_async.sync.aligned.m64n128k16.f32.bf16.bf16 "
               "{%0,%1,%2,%3,%4,%5,%6,%7,%8,%9,%10,%11,%12,%13,%14,%15,%16,%17,%18,%19,%20,%21,%22,%23,%24,%25,%26,%27,%28,%29,%30,%31,%32,%33,%34,%35,%36,%37,%38,%39,%40,%41,%42,%43,%44,%45,%46,%47,%48,%49,%50,%51,%52,%53,%54,%55,%56,%57,%58,%59,%60,%61,%62,%63},%64,%65,p,1,1,0,1;}"
               : "+f"(d[0]), "+f"(d[1]), "+f"(d[2]), "+f"(d[3]), "+f"(d[4]), "+f"(d[5]), "+f"(d[6]), "+f"(d[7]), "+f"(d[8]), "+f"(d[9]), "+f"(d[10]), "+f"(d[11]), "+f"(d[12]), "+f"(d[13]), "+f"(d[14]), "+f"(d[15]), "+f"(d[16]), "+f"(d[17]), "+f"(d[18]), "+f"(d[19]), "+f"(d[20]), "+f"(d[21]), "+f"(d[22]), "+f"(d[23]), "+f"(d[24]), "+f"(d[25]), "+f"(d[26]), "+f"(d[27]), "+f"(d[28]), "+f"(d[29]), "+f"(d[30]), "+f"(d[31]), "+f"(d[32]), "+f"(d[33]), "+f"(d[34]), "+f"(d[35]), "+f"(d[36]), "+f"(d[37]), "+f"(d[38]), "+f"(d[39]), "+f"(d[40]), "+f"(d[41]), "+f"(d[42]), "+f"(d[43]), "+f"(d[44]), "+f"(d[45]), "+f"(d[46]), "+f"(d[47]), "+f"(d[48]), "+f"(d[49]), "+f"(d[50]), "+f"(d[51]), "+f"(d[52]), "+f"(d[53]), "+f"(d[54]), "+f"(d[55]), "+f"(d[56]), "+f"(d[57]), "+f"(d[58]), "+f"(d[59]), "+f"(d[60]), "+f"(d[61]), "+f"(d[62]), "+f"(d[63])
               : "l"(da), "l"(db), "r"(sc));
}

__device__ __forceinline__ void stsm4(uint32_t a, uint32_t r0, uint32_t r1, uint32_t r2, uint32_t r3) {
  asm volatile("stmatrix.sync.aligned.m8n8.x4.shared.b16 [%0],{%1,%2,%3,%4};" ::"r"(a), "r"(r0), "r"(r1), "r"(r2), "r"(r3) : "memory");
}
__device__ __forceinline__ void stsm4t(uint32_t a, uint32_t r0, uint32_t r1, uint32_t r2, uint32_t r3) {
  asm volatile("stmatrix.sync.aligned.m8n8.x4.trans.shared.b16 [%0],{%1,%2,%3,%4};" ::"r"(a), "r"(r0), "r"(r1), "r"(r2), "r"(r3) : "memory");
}
__device__ __forceinline__ void stsm2t(uint32_t a, uint32_t r0, uint32_t r1) {
  asm volatile("stmatrix.sync.aligned.m8n8.x2.trans.shared.b16 [%0],{%1,%2};" ::"r"(a), "r"(r0), "r"(r1) : "memory");
}
__device__ __forceinline__ void sts64(uint32_t a, uint32_t x, uint32_t y) { asm volatile("st.shared.v2.b32 [%0],{%1,%2};" ::"r"(a), "r"(x), "r"(y) : "memory"); }
__device__ __forceinline__ void st_async2u(uint32_t a, uint32_t x, uint32_t y, uint32_t bar) {
  asm volatile("st.async.weak.shared::cluster.mbarrier::complete_tx::bytes.v2.b32 [%0],{%1,%2},[%3];" ::"r"(a), "r"(x), "r"(y), "r"(bar) : "memory");
}
__device__ __forceinline__ void st_relaxed128(void* p, uint32_t x, uint32_t y, uint32_t z, uint32_t w) {
  asm volatile("{.reg .b128 v; mov.b128 v,{%1,%2,%3,%4}; st.relaxed.gpu.global.b128 [%0],v;}" ::"l"(p), "r"(x), "r"(y), "r"(z), "r"(w) : "memory");
}
__device__ __forceinline__ void st_relaxed64(void* p, uint32_t x, uint32_t y) {
  asm volatile("{.reg .b64 v; mov.b64 v,{%1,%2}; st.relaxed.gpu.global.b64 [%0],v;}" ::"l"(p), "r"(x), "r"(y) : "memory");
}
__device__ __forceinline__ uint4 ld_relaxed128(const void* p) {
  uint4 v;
  asm volatile("{.reg .b128 v; .reg .b64 lo, hi; ld.relaxed.gpu.global.b128 v,[%4]; mov.b128 {lo,hi},v; mov.b64 {%0,%1},lo; mov.b64 {%2,%3},hi;}" : "=r"(v.x), "=r"(v.y), "=r"(v.z), "=r"(v.w) : "l"(p) : "memory");
  return v;
}

__device__ __forceinline__ uint32_t pack_h2(float lo, float hi) {
  uint32_t r; asm("cvt.rn.satfinite.f16x2.f32 %0,%1,%2;" : "=r"(r) : "f"(hi), "f"(lo)); return r;
}
__device__ __forceinline__ void add_h2(float& lo, float& hi, uint32_t u, uint32_t v) {
  float a, b;
  asm("{.reg .b16 l, h; .reg .b32 s; add.rn.f16x2 s,%2,%3; mov.b32 {l,h},s; cvt.f32.f16 %0,l; cvt.f32.f16 %1,h;}" : "=f"(a), "=f"(b) : "r"(u), "r"(v));
  lo += a; hi += b;
}
__device__ __forceinline__ void mwait(uint32_t bar, uint32_t ph, int& spin) {
  asm volatile("{.reg .pred p, q;\nWAIT_LOOP:\n add.s32 %0,%0,1;\n setp.lt.s32 q,%0,%3;\n mbarrier.try_wait.parity.shared::cta.b64 p,[%1],%2;\n not.pred p,p;\n and.pred q,q,p;\n @q bra.uni WAIT_LOOP;\n}"
               : "+&r"(spin) : "r"(bar), "r"(ph), "n"(SPIN_TOT) : "memory");
}
__device__ __forceinline__ int keep(int x) { return __shfl_sync(0xffffffffu, x, threadIdx.x & 31); }
__device__ __forceinline__ uint32_t pin(uint32_t x) { asm volatile("" : "+r"(x)); return x; }
template <typename T> __device__ __forceinline__ T* pinp(T* x) { asm volatile("" : "+l"(x)); return x; }
__device__ __forceinline__ void st_async1u(uint32_t a, uint32_t x, uint32_t bar) {
  asm volatile("st.async.weak.shared::cluster.mbarrier::complete_tx::bytes.b32 [%0],%1,[%2];" ::"r"(a), "r"(x), "r"(bar) : "memory");
}
__device__ __forceinline__ uint32_t lds32(uint32_t a) { uint32_t v; asm volatile("ld.shared.b32 %0,[%1];" : "=r"(v) : "r"(a) : "memory"); return v; }
__device__ __forceinline__ uint2 lds64(uint32_t a) { uint2 v; asm volatile("ld.shared.v2.b32 {%0,%1},[%2];" : "=r"(v.x), "=r"(v.y) : "r"(a) : "memory"); return v; }

__device__ __forceinline__ void permute_cols(uint32_t tile, int tid, int n) {
#pragma unroll 2
  for (int it = tid; it < n; it += 128) {
    const int row = it >> 2, q = it & 3;
    const uint32_t a0 = tile + row * 128 + (((2 * q) ^ (row & 7)) << 4), a1 = tile + row * 128 + (((2 * q + 1) ^ (row & 7)) << 4);
    const uint4 u = lds128(a0), v = lds128(a1);
    sts128(a0, make_uint4(__byte_perm(u.x, u.y, 0x5410), __byte_perm(u.z, u.w, 0x5410), __byte_perm(v.x, v.y, 0x5410), __byte_perm(v.z, v.w, 0x5410)));
    sts128(a1, make_uint4(__byte_perm(u.x, u.y, 0x7632), __byte_perm(u.z, u.w, 0x7632), __byte_perm(v.x, v.y, 0x7632), __byte_perm(v.z, v.w, 0x7632)));
  }
}

__device__ __forceinline__ uint8_t* mkptr(uint32_t lo, uint32_t hi) { uint8_t* p; asm("mov.b64 %0,{%1,%2};" : "=l"(p) : "r"(lo), "r"(hi)); return p; }
__device__ __forceinline__ int uni(int x) { return __shfl_sync(0xffffffffu, x, 0); }

__device__ __forceinline__ bool elect_one() {
  uint32_t p; asm volatile("{.reg .pred q; elect.sync _|q, 0xffffffff; selp.u32 %0,1,0,q;}" : "=r"(p)); return p;
}
__device__ __forceinline__ uint64_t desc_at(uint64_t d, uint32_t off) {
  uint64_t r; asm("mov.b64 %0,{%1,%2};" : "=l"(r) : "r"((uint32_t)d + (off >> 4)), "r"((uint32_t)(d >> 32))); return r;
}
__device__ __forceinline__ uint32_t scale_bf16x2(uint32_t x, uint32_t s) { uint32_t r; asm("mul.rn.bf16x2 %0,%1,%2;" : "=r"(r) : "r"(x), "r"(s)); return r; }

__device__ __forceinline__ void stg128(void* p, const uint4& v) { asm volatile("st.global.v4.b32 [%0],{%1,%2,%3,%4};" ::"l"(p), "r"(v.x), "r"(v.y), "r"(v.z), "r"(v.w) : "memory"); }

__device__ __forceinline__ float quad_sum(float x) {
  const float a = __shfl_xor_sync(0xffffffffu, x, 1), b = __shfl_xor_sync(0xffffffffu, x, 2), c = __shfl_xor_sync(0xffffffffu, x, 3);
  return (x + a) + (b + c);
}
__device__ __forceinline__ float warp_sum(float x) {
  const uint32_t m = __reduce_max_sync(0xffffffffu, __float_as_uint(x) & 0x7FFFFFFFu), e = max(m >> 23, 25u);
  const int s = __reduce_add_sync(0xffffffffu, __float2int_rn(x * __uint_as_float((278 - e) << 23)));
  return fmaf(__uint_as_float(m), 0.f, (float)s * __uint_as_float((e - 24) << 23));
}
__device__ __forceinline__ void ln_row(float4 (&v)[5]) {
  float t0 = 0.f, t1 = 0.f;
#pragma unroll
  for (int m = 0; m < 5; m++) { t0 += v[m].x + v[m].y; t1 += v[m].z + v[m].w; }
  const float mean = warp_sum(t0 + t1) * (1.f / DM);
  float q0 = 0.f, q1 = 0.f, q2 = 0.f, q3 = 0.f;
#pragma unroll
  for (int m = 0; m < 5; m++) {
    v[m].x -= mean; v[m].y -= mean; v[m].z -= mean; v[m].w -= mean;
    q0 = fmaf(v[m].x, v[m].x, q0); q1 = fmaf(v[m].y, v[m].y, q1); q2 = fmaf(v[m].z, v[m].z, q2); q3 = fmaf(v[m].w, v[m].w, q3);
  }
  const float rs = rsqrtf(warp_sum((q0 + q1) + (q2 + q3)) * (1.f / DM) + 1e-5f);
#pragma unroll
  for (int m = 0; m < 5; m++) { v[m].x *= rs; v[m].y *= rs; v[m].z *= rs; v[m].w *= rs; }
}
__device__ __forceinline__ void ln0_load(const bf16* __restrict__ x, uint2 (&u)[5], int row, int lane) {
#pragma unroll
  for (int m = 0; m < 5; m++) u[m] = *reinterpret_cast<const uint2*>(x + (size_t)row * DM + m * 128 + lane * 4);
}
__device__ __forceinline__ void ln0_copy(const uint2 (&u)[5], int row, int lane) {
#pragma unroll
  for (int m = 0; m < 5; m++) stg128(g_x + (size_t)row * DM + m * 128 + lane * 4, make_uint4(u[m].x << 16, u[m].x & 0xFFFF0000u, u[m].y << 16, u[m].y & 0xFFFF0000u));
}
__device__ __forceinline__ void ln0_row(const uint2 (&u)[5], int row, int lane) {
  float4 v[5];
#pragma unroll
  for (int m = 0; m < 5; m++) v[m] = make_float4(bf_lo(u[m].x), bf_hi(u[m].x), bf_lo(u[m].y), bf_hi(u[m].y));
  ln_row(v);
  uint8_t* dst = g_xn[row >> 5] + ((row >> 3) & 3) * 4096 + (lane >> 4) * 1024 + (row & 7) * 128 + ((((lane >> 1) ^ row) & 7) << 4) + (lane & 1) * 8;
#pragma unroll
  for (int m = 0; m < 5; m++) *reinterpret_cast<uint2*>(dst + m * 16384) = make_uint2(pack_bf16(v[m].x, v[m].y), pack_bf16(v[m].z, v[m].w));
}

#define NOWORK 0
__device__ __forceinline__ void prep_row(const uint2 (&u)[5], const bf16* __restrict__ mem0, int k, int r, int lane) {
  const uint4 sent = make_uint4(SENT, SENT, SENT, SENT);
  if (k + 1 < NSTEP) {
    uint8_t* ex = ex_window(g_ex);
#pragma unroll
    for (int h = 0; h < 2; h++) {
      const int p = r * 40 + h * 32 + lane;
      if (h == 0 || lane < 8) {
        uint4 v = sent;
        if (k + 1 == LAG && (p & 8)) v = *reinterpret_cast<const uint4*>(mem0 + (p & 7) * DM + (p >> 4) * 8);
        stg128(ex + EX_M + (k + 1) * 20480 + p * 16, v);
      } else if (lane < 14) stg128(ex + EX_FLAG + (k + 1) * 3072 + (r * 6 + lane - 8) * 16, sent);
    }
  }
  if (k < LAG || k >= NSEG || NOWORK) {
    uint8_t* z = g_xn[k] + (r >> 3) * 4096 + (k < NSEG ? 2048 : 0) + (lane >> 4) * 1024 + (r & 7) * 128 + (lane & 15) * 8;
#pragma unroll
    for (int m = 0; m < 5; m++) *reinterpret_cast<uint2*>(z + m * 16384) = make_uint2(0, 0);
  }
  if (k < NSEG) {
    ln0_copy(u, k * 32 + r, lane);
    ln0_row(u, k * 32 + r, lane);
  }
}
__device__ __forceinline__ void pre_work(const bf16* __restrict__ x, const bf16* __restrict__ mem0, int cta, int tid) {
  constexpr int NT = 96 * 128;
  const int gt = cta * 128 + tid;
  uint8_t* ex = ex_window(g_ex);
#pragma unroll 1
  for (int row = cta + 96 * (tid >> 5); row < (NOWORK == 2 ? NSTEP : NPRE) * 32; row += 384) {
    uint2 u[5];
    ln0_load(x, u, min(row, SEQ - 1), tid & 31);
    prep_row(u, mem0, row >> 5, row & 31, tid & 31);
  }
#pragma unroll 1
  for (int i = gt; i < MAIL_BYTES / 16; i += NT) {
    stg128(ex + EX_MAIL + i * 16, make_uint4(SENT, SENT, SENT, SENT));
    stg128(ex + EX_MAIL + (1 << 20) + i * 16, make_uint4(SENT, SENT, SENT, SENT));
  }
  const int p = NT - 1 - gt;
  if (p < 1280) stg128(ex + EX_M + p * 16, *reinterpret_cast<const uint4*>(mem0 + (p & 7) * DM + (p >> 4) * 8));
  if (p < 192) stg128(ex + EX_FLAG + p * 16, make_uint4(0, 0, 0, 0));
  if (gt < 8 * CN_NUM) stg128(&g_cnt[0][0] + gt * 4, make_uint4(0, 0, 0, 0));
}
__device__ __forceinline__ void pre_wait(int which, uint32_t n, int& spin) {
  uint32_t old;
  asm volatile("atom.acq_rel.gpu.global.add.u32 %0,[%1],1;" : "=r"(old) : "l"(&g_ticket[which][0]) : "memory");
  const uint32_t target = (old / n + 1) * 96;
  while ((int)(ld_acquire(&g_ticket[0][0]) - target) < 0 && spin < SPIN_TOT) spin += 16;
  fence_async_all();
}

namespace C {
constexpr int NKR = 37;
constexpr int OFF_WQ = 0, OFF_WK = 81920;
constexpr int OFF_YO = 163840, OFF_YV = OFF_YO + 6144;
constexpr int OFF_M = 176128;
__host__ __device__ constexpr int og_off(int c) { return c ? OFF_M + 14336 + c * 2048 : 229376; }
constexpr int OFF_KT = 196608;
constexpr int OFF_XT = OFF_KT + 10240;
constexpr int OFF_VT = OFF_XT + 7168;
constexpr int OFF_XM = OFF_VT + 11392;
constexpr int OFF_PT = OFF_XM + 2560;
constexpr int KS = 1280, VS = 1408;
__host__ __device__ constexpr int slot_off(int p) { return p == 2 ? OFF_M : OFF_KT + (p % 3) * 16384; }
constexpr int OFF_ONE = 231424;
constexpr int OFF_BAR = 231552;
constexpr int OFF_SAFE = OFF_BAR + 144;
constexpr int OFF_TS = OFF_BAR + 256;
constexpr int SMEM = 232448;
constexpr uint32_t SB0 = 1024;
constexpr int BAR_F = OFF_BAR, BAR_XM = BAR_F + 40, BAR_XT = BAR_F + 48, BAR_OG = BAR_F + 56, BAR_E = OFF_BAR + 64, BAR_MOK = BAR_E + 40,
              BAR_M = OFF_BAR + 112, BAR_XF = OFF_BAR + 120, BAR_MF = OFF_BAR + 128, FLG_REDO = OFF_BAR + 136, BAR_W = OFF_BAR + 208;
constexpr int NB_PRO = 1, NB_RD = 2, NB_MR = 3, NB_QK = 4, NB_SM = 5, NB_VA = 6, NB_VQ = 7, NB_A = 8, NB_Q = 9, NB_C = 10, NB_WQ = 11, NB_QI = 12, NB_SI = 13, NB_WV = 14, NB_V = 15;
#define B1 600
#define AD0 16
#define AD1 128
#define AD2 16
#define AD3 128
#define BMX 1200
#define B2 800
#define FLP 1
#define OSG 2
#define OST 7
#define NBX 1
#define P1U 4
#define QIE 4
#define SIE 2
#define WOE 1
#define OGF 0
#define VSP 8
#define RFK 5
#define PFD 3
#define WOL 0
constexpr uint32_t SCQ = 0x3A003A00;
constexpr float SCE = 0.07216878364870322f * 1.4426950408889634f * 2048;
}

#define CBAR_SYNC(id, n) bar_sync(id, n)
#define CBAR_ARRIVE(id, n) bar_arrive(id, n)

__device__ __forceinline__ uint64_t wdesc(int off) { return mkdesc(C::SB0 + off, 8192, 1024); }
__device__ __forceinline__ uint64_t mdesc(int k) { return mkdesc_ns(C::SB0 + C::OFF_M + k * 512, 256, 128); }
__device__ __forceinline__ uint64_t tdesc(int k) { return mkdesc(C::SB0 + C::slot_off(k >> 3) + ((k >> 2) & 1) * 1024 + (k & 3) * 32, 16, 2048); }

__device__ __forceinline__ int dh_row(int n) { return (n & ~63) + (n & 32) + ((n >> 1) & 3) * 8 + ((n >> 3) & 3) * 2 + (n & 1); }
template <bool IS_O>
__device__ __forceinline__ void stage_box(const CUtensorMap& tm, uint32_t sb, int p, int cta, int rank) {
  using namespace C;
  const uint32_t bar = sb + BAR_W + 8 * p;
  const int head = cta / 3, col = head * DH + rank * 64;
  mbar_expect_tx(bar, 16384);
  if (!IS_O) tma2d(sb + OFF_WK + p * 16384, &tm, col, p * 128, bar);
  else for (int b = 2 * p - 1; b <= 2 * p; b++)
    tma2d(sb + OFF_WQ + (b + 1) * 8192, &tm, b < 0 ? 576 : (3 * rank + b / 3) * 64, b < 0 ? col : head * DH + ((rank + b) % 3) * 64, bar);
}
template <bool IS_O>
__device__ __forceinline__ void load_weights_rs(uint32_t (&wf)[C::NKR][4], const CUtensorMap& tms, const CUtensorMap& tm, int cta, int rank, uint32_t sb, int tid0, int& spin) {
  using namespace C;
  constexpr int STAGE = IS_O ? OFF_WQ : OFF_WK, YOFF = IS_O ? OFF_YO : OFF_YV, NB = IS_O ? NB_C : NB_V;
  const int i = (tid0 >> 3) & 3, n0 = (tid0 & 7) + (i >> 1) * 8;
  const int chunk = 2 * ((tid0 >> 5) & 3) + (i & 1);
  const int r0 = IS_O ? dh_row(n0) : n0, r1 = IS_O ? dh_row(n0 + 16) : n0 + 16;
  const uint32_t a0 = sb + STAGE + r0 * 128 + ((chunk ^ (r0 & 7)) << 4), a1 = sb + STAGE + r1 * 128 + ((chunk ^ (r1 & 7)) << 4);
#pragma unroll
  for (int p = 0; p < 5; p++) {
    mwait(sb + BAR_W + 8 * p, 0, spin);
    if (IS_O) PTS(8 + p);
    if (p + NBX < 5) { if ((tid0 & 127) == 96) stage_box<IS_O>(tms, sb, p + NBX, cta, rank); __syncwarp(); }
    if (IS_O) permute_cols(sb + STAGE + p * 16384, tid0, 512);
    else {
#pragma unroll 1
      for (int it = tid0 & 127; it < 256; it += 128) {
        const uint32_t base = sb + STAGE + p * 16384 + (it >> 1) * 128;
        const int sw = ((it >> 1) & 7) ^ ((it & 1) * 4);
        const uint4 u0 = lds128(base + (sw << 4)), u1 = lds128(base + ((sw ^ 1) << 4)), u2 = lds128(base + ((sw ^ 2) << 4)), u3 = lds128(base + ((sw ^ 3) << 4));
        sts128(base + (sw << 4), make_uint4(u0.x, u1.x, u2.x, u3.x)); sts128(base + ((sw ^ 1) << 4), make_uint4(u0.y, u1.y, u2.y, u3.y));
        sts128(base + ((sw ^ 2) << 4), make_uint4(u0.z, u1.z, u2.z, u3.z)); sts128(base + ((sw ^ 3) << 4), make_uint4(u0.w, u1.w, u2.w, u3.w));
      }
    }
    bar_sync(NB, 128);
#pragma unroll
    for (int k = 8 * p; k < 8 * p + 8; k++) {
      if (k < NKR) ldsm4t(wf[k < NKR ? k : 0], ((k & 1) ? a1 : a0) + (k >> 1) * 4096);
      else {
        const int n = k * 16 + ((tid0 & 127) >> 3), r = IS_O ? dh_row(n) : n, c = tid0 & 7;
        sts128(sb + YOFF + (n - NKR * 16) * 128 + ((c ^ (n & 7)) << 4), lds128(sb + STAGE + r * 128 + ((c ^ (r & 7)) << 4)));
      }
    }
    fence_async();
    bar_sync(NB, 128);
    if ((tid0 & 127) == 0) {
      mbar_expect_tx(sb + BAR_W + 8 * p, 16384);
      tma2d(sb + STAGE + p * 16384, &tm, (cta / 3) * DH + rank * 64, p * 128, sb + BAR_W + 8 * p);
    }
    __syncwarp();
  }
  PTS(IS_O ? 13 : 14);
  CBAR_SYNC(NB_PRO, 384);
}
template <int STRIDE>
__device__ __forceinline__ void store_mem(const float (&d)[8], uint32_t base, int tid) {
  const int m = (tid >> 3) & 3;
  stsm4(base + (((tid >> 5) & 3) * 2 + (m & 1)) * STRIDE + (m >> 1) * 640 + (tid & 7) * 16, pack_bf16(d[0], d[1]), pack_bf16(d[2], d[3]),
        pack_bf16(d[4], d[5]), pack_bf16(d[6], d[7]));
}

__device__ __forceinline__ void load_pair(uint32_t sb, int i, int p, uint32_t slot, uint32_t ph, int& spin) {
  using namespace C;
  mwait(sb + BAR_E + 8 * p, ph, spin);
  if (elect_one()) bulk_g2s_mc(sb + slot, g_xn[i] + p * 16384, 16384, sb + BAR_F + 8 * p);
}
__device__ __forceinline__ void release_round(uint32_t sb, int p, int lane) {
  if (lane < (p == 2 ? 3 : 1)) mbar_arrive_cluster(mapa(sb, p == 2 ? lane : p) + C::BAR_E + 8 * (3 + p));
}

template <int K0, int K1>
__device__ __forceinline__ void v_mem_pass(float (&d)[8], const uint32_t (&wf)[C::NKR][4]) {
  using namespace C;
  wg_fence();
#pragma unroll
  for (int k = K0; k < K1; k++) {
    if (k < NKR) wgmma_rs16(d, wf[k < NKR ? k : 0], mdesc(k), k != 32);
    else wgmma_ts16(d, wdesc(OFF_YV + (k - NKR) * 2048), mdesc(k), 1);
  }
  wg_commit();
}
__device__ __forceinline__ void chain_v(const CUtensorMap& tmWv, const CUtensorMap& tmWk, const uint32_t sb, const int tid0, const int cta, const int rank) {
  using namespace C;
  asm volatile("setmaxnreg.inc.sync.aligned.u32 208;");
  int spin = 0;
  uint32_t wf[NKR][4];
  const int wu = uni((tid0 >> 5) & 3);
  const uint32_t slot = rank == 2 ? OFF_M : OFF_KT + rank * 16384;
  load_weights_rs<false>(wf, tmWv, tmWk, cta, rank, sb, tid0, spin);
  PTS(5);
#pragma unroll 1
  for (int i = 0; i < NSTEP; i++) {
    {
      float d[32];
      if (i > 0) CBAR_SYNC(NB_WV, 256);
#pragma unroll
      for (int p = 0; p < 5; p++) {
        mwait(sb + BAR_F + 8 * p, i & 1, spin);
        TS(i, 25 + p);
        wg_fence();
#pragma unroll
        for (int k = 8 * p; k < 8 * p + 8; k++) {
          if (k < NKR) wgmma_rs64(d, wf[k < NKR ? k : 0], tdesc(k), k);
          else wgmma_ts64(d, wdesc(OFF_YV + (k - NKR) * 2048), tdesc(k), 1);
          if (k == 8 * p + 1 && p >= 1 && p <= 3) {
            wg_commit(); wg_wait<1>();
            release_round(sb, p - 1, tid0 & 31);
          }
          if (k == 8 * p + RFK && (p == 1 || p == 2)) {
            wg_commit();
            if (rank == p - 1 && wu == 0) load_pair(sb, i, p + 2, slot_off(p + 2), i & 1, spin);
            wg_fence();
          }
        }
        wg_commit();
      }
      wg_wait<0>();
      TS(i, 23);
      CBAR_SYNC(NB_RD, 256);
      const int tid = fresh(tid0) & 127, m = (tid >> 3) & 3;
      if (tid < 8) mbar_expect_tx(sb + BAR_F + 8 * tid, tid < 5 ? 16384 : tid == 5 ? 2560 : tid == 6 ? 7168 : 4096);
      if (tid < 3 && tid != rank) mbar_arrive_cluster(mapa(sb, tid) + BAR_XF);
      const uint32_t a = sb + OFF_VT + 256 + ((tid >> 5) * 2 + (m & 1)) * VS + (m >> 1) * 640 + (tid & 7) * 16;
#pragma unroll
      for (int s = 0; s < 4; s++)
        stsm4(a + s * 128, pack_bf16(d[8 * s], d[8 * s + 1]), pack_bf16(d[8 * s + 2], d[8 * s + 3]),
              pack_bf16(d[8 * s + 4], d[8 * s + 5]), pack_bf16(d[8 * s + 6], d[8 * s + 7]));
      if (tid < 80) sts128(sb + (tid < 72 ? OFF_VT + (tid >> 3) * VS : OFF_PT + 1280) + (tid & 7) * 16, make_uint4(0, 0, 0, 0));
      fence_async();
    }
    mwait(sb + BAR_XF, i & 1, spin);
    CBAR_ARRIVE(NB_QK, 384);
    const uint32_t* xc = &g_cnt[CN_X + i + 1][0];
    const uint32_t xn = i + 1 < LAG || NOWORK ? 16 : 48;
    bool seen = NOWORK == 2 || i + 1 < NPRE;
    if (wu == 0 && !seen) { seen = ld_acquire(xc) >= xn; fence_async_all(); }
    CBAR_SYNC(NB_QI, 256);
    float d[8];
    v_mem_pass<32, 40>(d, wf);
    CBAR_SYNC(NB_SM, 256);
    wg_wait<0>();
    if (__builtin_expect(lds32(sb + FLG_REDO), 0)) { v_mem_pass<32, 40>(d, wf); wg_wait<0>(); }
    if ((tid0 & 31) < 3 && (tid0 & 31) != rank) mbar_arrive_cluster(mapa(sb, tid0 & 31) + BAR_MF);
    v_mem_pass<0, 32>(d, wf);
    wg_wait<0>();
    TS(i, 24);
    const int tid = fresh(tid0);
    if ((tid & 31) == 0) mbar_arrive_cluster(mapa(sb, 2) + BAR_E + 16);
    store_mem<VS>(d, sb + OFF_VT + 128, tid);
    fence_async();
    CBAR_ARRIVE(NB_VA, 256);
    CBAR_ARRIVE(NB_VQ, 256);
    if (wu == 0 && i + 1 < NSTEP) {
      if (__builtin_expect(!seen, 0)) { while (ld_acquire(xc) < xn && spin < SPIN_TOT) spin += 16; fence_async_all(); }
      load_pair(sb, i + 1, rank, slot, i & 1, spin);
      TS(i + 1, 37);
    }
    TS_FLUSH(i - 1);
    __syncwarp();
  }
  CBAR_ARRIVE(NB_WV, 256);
  if (spin >= SPIN_TOT) g_err = 3;
}

__device__ __forceinline__ float quad_max(float x) {
  const float a = __shfl_xor_sync(0xffffffffu, x, 1), b = __shfl_xor_sync(0xffffffffu, x, 2), c = __shfl_xor_sync(0xffffffffu, x, 3);
  return fmaxf(fmaxf(x, a), fmaxf(b, c));
}
__device__ __forceinline__ float max10(const float (&y)[10]) {
  return fmaxf(fmaxf(fmaxf(fmaxf(y[0], y[1]), fmaxf(y[2], y[3])), fmaxf(fmaxf(y[4], y[5]), fmaxf(y[6], y[7]))), fmaxf(y[8], y[9]));
}
__device__ __forceinline__ float sum10(const float (&y)[10]) {
  return (((y[0] + y[1]) + (y[2] + y[3])) + ((y[4] + y[5]) + (y[6] + y[7]))) + (y[8] + y[9]);
}
__device__ __forceinline__ float rcp(float x) { float y; asm("rcp.approx.ftz.f32 %0,%1;" : "=f"(y) : "f"(x)); return y; }

__device__ __forceinline__ void signal_o(int i, int cta) { csignal(CN_O + i * 5 + min(cta / 19, 4)); }

__device__ __forceinline__ void chain_q(const bf16* x0, const bf16* mem0, const uint32_t sb, const int tid0, const int cta, const int rank) {
  using namespace C;
  asm volatile("setmaxnreg.dec.sync.aligned.u32 96;");
  int spin = 0;
  PTS(0);
  pre_work(x0, mem0, cta, tid0 & 127);
  PTS(3);
  CBAR_SYNC(NB_Q, 128);
  PTS(2);
  if (tid0 < 160) {
    if (tid0 == 128) pre_wait(0, 96, spin);
    __syncwarp();
    load_pair(sb, 0, rank, rank == 2 ? OFF_M : OFF_KT + rank * 16384, 1, spin);
  }
  PTS(4);
  CBAR_SYNC(NB_PRO, 384);
  mwait(sb + BAR_W, 1, spin);
  PTS(6);
  const int wu = uni((tid0 >> 5) & 3);
  uint4 ov[4] = {};
  uint8_t* op = &g_o[ORING - 1][cta][(tid0 & 124) * 32];
  const uint32_t o0 = ((tid0 ^ (tid0 >> 2)) & 3) * 16 + (tid0 & 16) * 4;
#pragma unroll 1
  for (int i = 0; i < NSTEP; i++) {
    const int ph = i & 1;
    uint32_t qf[4][4];
    {
      float d[64];
#define QK_STEP(K, SC) wgmma_st128(d, desc_at(mkdesc(SB0 + ((K) >> 2) * 1024 + ((K) & 3) * 32, 16, 2048), so), \
                                   desc_at(mkdesc(SB0 + OFF_WQ + (K) * 2048, OFF_WK - OFF_WQ, 1024), p * 16384), SC)
      int p = 0;
      uint32_t so = OFF_KT;
      mwait(sb + BAR_F, ph, spin);
      TS(i, 0);
      wg_fence();
#pragma unroll
      for (int k = 0; k < 8; k++) {
        QK_STEP(k, k);
        if (k == OST) {
          wg_commit();
          mwait(sb + BAR_F, ph, spin);
#pragma unroll
          for (int h = 0; h < 4; h++) stg128(op + (h & 1) * 4096 + (o0 ^ ((h >> 1) * 64)), ov[h]);
          if (i > 0) CBAR_ARRIVE(NB_MR, 160);
          if (k < 7) wg_fence();
        }
      }
      if (OST < 7) wg_commit();
#pragma unroll 1
      for (p = 1; p < 5; p++) {
        static_assert(OFF_KT - OFF_M == 5 << 12, "");
        so = OFF_M + (((0x95095u >> (4 * p)) & 15) << 12);
        if (i == 0) { mwait(sb + BAR_W + 8 * p, 1, spin); PTS(14 + p); }
        mwait(sb + BAR_F + 8 * p, ph, spin);
        wg_fence();
#pragma unroll
        for (int k = 0; k < 8; k++) {
          QK_STEP(k, 1);
          if (k == 1) {
            wg_commit(); wg_wait<1>();
            release_round(sb, p - 1, p < 4 ? tid0 & 31 : 32);
          }
        }
        wg_commit();
      }
#undef QK_STEP
      wg_wait<0>();
      TS(i, 1);
      CBAR_SYNC(NB_RD, 256);
      TSB(i, 2);
      const int tid = fresh(tid0), w = (tid >> 5) & 3, m = (tid >> 3) & 3;
      const uint32_t a = sb + OFF_KT + (m >> 1) * KS + (1 + w + 5 * (m & 1)) * 128 + (tid & 7) * 16;
#pragma unroll
      for (int s = 0; s < 4; s++)
        stsm4t(a + s * 2 * KS, pack_bf16(d[32 + 8 * s], d[33 + 8 * s]), pack_bf16(d[34 + 8 * s], d[35 + 8 * s]),
               pack_bf16(d[36 + 8 * s], d[37 + 8 * s]), pack_bf16(d[38 + 8 * s], d[39 + 8 * s]));
      fence_async();
      CBAR_ARRIVE(NB_QK, 384);
#pragma unroll
      for (int kk = 0; kk < 4; kk++)
#pragma unroll
        for (int j = 0; j < 4; j++) asm volatile("{.reg .b32 t; cvt.rn.bf16x2.f32 t,%1,%2; mul.rn.bf16x2 %0,t,%3;}" : "=r"(qf[kk][j]) : "f"(d[8 * kk + 2 * j + 1]), "f"(d[8 * kk + 2 * j]), "r"(SCQ));
    }
    CBAR_SYNC(NB_SI, 256);
    uint32_t pf[5][4];
    {
      float y0[10], y1[10];
      const int tidf = fresh(tid0), lane = tidf & 31;
      {
        float x[40];
        wg_fence();
#pragma unroll
        for (int kk = 0; kk < 4; kk++) wgmma_rt80(x, qf[kk], mkdesc_ns(SB0 + OFF_KT + kk * 2 * KS, KS, 128), kk);
        wg_commit();
        wg_wait<0>();
#pragma unroll
        for (int j = 0; j < 5; j++) { y0[2 * j] = x[4 * j]; y0[2 * j + 1] = x[4 * j + 1]; y1[2 * j] = x[22 + 4 * j]; y1[2 * j + 1] = x[23 + 4 * j]; }
      }
      TS(i, 17);
      const uint32_t xo = OFF_XT + (wu * (wu + 3) / 2) * 256 + lane * 16, x2 = xo + (wu >> 1) * 512 + 512 - lane * 8;
      {
        const uint4 h0 = make_uint4(pack_h2(y0[0], y0[1]), pack_h2(y1[0], y1[1]), pack_h2(y0[2], y0[3]), pack_h2(y1[2], y1[3]));
        const uint4 h1 = make_uint4(pack_h2(y0[4], y0[5]), pack_h2(y1[4], y1[5]), pack_h2(y0[6], y0[7]), pack_h2(y1[6], y1[7]));
        const uint32_t h2 = wu == 1 ? h1.x : pack_h2(y0[8], y0[9]), h3 = wu == 1 ? h1.y : pack_h2(y1[8], y1[9]);
        const uint32_t rb1 = mapa(sb, (rank + 1) % 3), rb2 = mapa(sb, (rank + 2) % 3);
        st_async4u(rb1 + xo + 3584, h0, rb1 + BAR_XT);
        st_async4u(rb2 + xo, h0, rb2 + BAR_XT);
        if (wu >= 2) { st_async4u(rb1 + xo + 4096, h1, rb1 + BAR_XT); st_async4u(rb2 + xo + 512, h1, rb2 + BAR_XT); }
        if (wu & 1) { st_async2u(rb1 + x2 + 3584, h2, h3, rb1 + BAR_XT); st_async2u(rb2 + x2, h2, h3, rb2 + BAR_XT); }
      }
      TS(i, 18);
      const int lim = 8 * wu + (lane >> 2) + 8 - 2 * (lane & 3);
#pragma unroll
      for (int j = 2; j < 10; j++)
        if (8 * (j >> 1) + (j & 1) > lim) { y0[j] = -INFINITY; y1[j] = -INFINITY; }
      mwait(sb + BAR_XT, ph, spin);
      TS(i, 19);
      {
        const uint4 u0 = lds128(sb + xo), v0 = lds128(sb + xo + 3584);
        uint2 u2 = make_uint2(0, 0), v2 = u2;
        if (wu & 1) { u2 = lds64(sb + x2); v2 = lds64(sb + x2 + 3584); }
        uint4 u1 = make_uint4(u2.x, u2.y, 0, 0), v1 = make_uint4(v2.x, v2.y, 0, 0);
        if (wu >= 2) { u1 = lds128(sb + xo + 512); v1 = lds128(sb + xo + 4096); }
        __syncwarp();
        if (lane == 0) mbar_arrive_cluster(mapa(sb, 0) + BAR_E);
        add_h2(y0[0], y0[1], u0.x, v0.x); add_h2(y1[0], y1[1], u0.y, v0.y); add_h2(y0[2], y0[3], u0.z, v0.z); add_h2(y1[2], y1[3], u0.w, v0.w);
        add_h2(y0[4], y0[5], u1.x, v1.x); add_h2(y1[4], y1[5], u1.y, v1.y); add_h2(y0[6], y0[7], u1.z, v1.z); add_h2(y1[6], y1[7], u1.w, v1.w);
        add_h2(y0[8], y0[9], u2.x, v2.x); add_h2(y1[8], y1[9], u2.y, v2.y);
      }
      const float m0 = quad_max(max10(y0)) * -SCE, m1 = quad_max(max10(y1)) * -SCE;
#pragma unroll
      for (int j = 0; j < 5; j++) {
        pf[j >> 1][2 * (j & 1)] = pack_bf16(ex2(fmaf(y0[2 * j], SCE, m0)), ex2(fmaf(y0[2 * j + 1], SCE, m0)));
        pf[j >> 1][2 * (j & 1) + 1] = tidf >> (10 + j);
        pf[(j + 5) >> 1][2 * ((j + 5) & 1)] = tidf >> (20 + j);
        pf[(j + 5) >> 1][2 * ((j + 5) & 1) + 1] = pack_bf16(ex2(fmaf(y1[2 * j], SCE, m1)), ex2(fmaf(y1[2 * j + 1], SCE, m1)));
      }
    }
#pragma unroll
    for (int q = 0; q < 20; q++) pf[q >> 2][q & 3] = pin(pf[q >> 2][q & 3]);
    CBAR_SYNC(NB_VQ, 256);
    TSB(i, 20);
    {
      float o[32], sm[4];
      wg_fence();
#pragma unroll
      for (int q = 0; q < 5; q++) wgmma_rs8(sm, pf[q], mkdesc_ns(SB0 + OFF_ONE, 0, 0), q);
#pragma unroll
      for (int q = 0; q < 5; q++) wgmma_rs64(o, pf[q], mkdesc_ns(SB0 + OFF_VT + 128 + q * 256, 128, VS), q);
      wg_commit();
      const int tid = fresh(tid0);
      op = &g_o[i % ORING][cta][(tid & 124) * 32];
      wg_wait<0>();
      TS(i, 21);
      if ((tid & 31) == 0) mbar_arrive_cluster(mapa(sb, 1) + BAR_E + 8);
      const float s0 = rcp(sm[0]), s1 = rcp(sm[2]);
#pragma unroll
      for (int h = 0; h < 2; h++) {
        const float* x = o + 16 * h;
        ov[2 * h] = make_uint4(pin(pack_bf16(x[0] * s0, x[1] * s0)), pin(pack_bf16(x[4] * s0, x[5] * s0)), pin(pack_bf16(x[8] * s0, x[9] * s0)), pin(pack_bf16(x[12] * s0, x[13] * s0)));
        ov[2 * h + 1] = make_uint4(pin(pack_bf16(x[2] * s1, x[3] * s1)), pin(pack_bf16(x[6] * s1, x[7] * s1)), pin(pack_bf16(x[10] * s1, x[11] * s1)), pin(pack_bf16(x[14] * s1, x[15] * s1)));
      }
      TS(i, 22);
      if (i + 1 < NSTEP) CBAR_SYNC(NB_WQ, 256); else CBAR_ARRIVE(NB_WQ, 256);
    }
  }
#pragma unroll
  for (int h = 0; h < 4; h++) stg128(op + (h & 1) * 4096 + (o0 ^ ((h >> 1) * 64)), ov[h]);
  CBAR_SYNC(NB_Q, 128);
  if (tid0 == 224) signal_o(NSTEP - 1, cta);
  if (spin >= SPIN_TOT) g_err = 2;
}

template <int NL> __device__ __forceinline__ void poll(uint4 (&x)[NL], const uint8_t* mb, uint32_t tag, int& spin);
template <> __device__ __forceinline__ void poll<4>(uint4 (&x)[4], const uint8_t* mb, uint32_t tag, int& spin) {
  asm volatile("{.reg .pred p<6>, q; .reg .b128 v; .reg .b32 t;\n"
               " ld.relaxed.gpu.global.b128 v,[%17+0]; mov.b128 {%0,%1,%2,%3},v;\n"
               " ld.relaxed.gpu.global.b128 v,[%17+512]; mov.b128 {%4,%5,%6,%7},v;\n"
               " ld.relaxed.gpu.global.b128 v,[%17+1024]; mov.b128 {%8,%9,%10,%11},v;\n"
               " ld.relaxed.gpu.global.b128 v,[%17+1536]; mov.b128 {%12,%13,%14,%15},v;\n"
               "POLL_LOOP:\n add.s32 %16,%16,16;\n"
               " lop3.b32 t,%0,%18,1,0x28; setp.ne.b32 p0,t,0;\n"
               " lop3.b32 t,%4,%18,1,0x28; setp.ne.b32 p1,t,0;\n"
               " lop3.b32 t,%8,%18,1,0x28; setp.ne.b32 p2,t,0;\n"
               " lop3.b32 t,%12,%18,1,0x28; setp.ne.b32 p3,t,0;\n"
               " or.pred q,p0,p1; or.pred q,q,p2; or.pred q,q,p3; setp.lt.and.s32 q,%16,%19,q; vote.sync.any.pred q,q,0xffffffff;\n"
               " mov.b128 v,{%0,%1,%2,%3}; @p0 ld.relaxed.gpu.global.b128 v,[%17+0]; mov.b128 {%0,%1,%2,%3},v;\n"
               " mov.b128 v,{%4,%5,%6,%7}; @p1 ld.relaxed.gpu.global.b128 v,[%17+512]; mov.b128 {%4,%5,%6,%7},v;\n"
               " mov.b128 v,{%8,%9,%10,%11}; @p2 ld.relaxed.gpu.global.b128 v,[%17+1024]; mov.b128 {%8,%9,%10,%11},v;\n"
               " mov.b128 v,{%12,%13,%14,%15}; @p3 ld.relaxed.gpu.global.b128 v,[%17+1536]; mov.b128 {%12,%13,%14,%15},v;\n"
               " @q bra.uni POLL_LOOP;\n}"
               : "=&r"(x[0].x), "=&r"(x[0].y), "=&r"(x[0].z), "=&r"(x[0].w), "=&r"(x[1].x), "=&r"(x[1].y), "=&r"(x[1].z), "=&r"(x[1].w), "=&r"(x[2].x), "=&r"(x[2].y), "=&r"(x[2].z), "=&r"(x[2].w), "=&r"(x[3].x), "=&r"(x[3].y), "=&r"(x[3].z), "=&r"(x[3].w), "+&r"(spin)
               : "l"(mb), "r"(tag), "n"(SPIN_TOT) : "memory");
}
template <> __device__ __forceinline__ void poll<6>(uint4 (&x)[6], const uint8_t* mb, uint32_t tag, int& spin) {
  asm volatile("{.reg .pred p<6>, q; .reg .b128 v; .reg .b32 t;\n"
               " ld.relaxed.gpu.global.b128 v,[%25+0]; mov.b128 {%0,%1,%2,%3},v;\n"
               " ld.relaxed.gpu.global.b128 v,[%25+512]; mov.b128 {%4,%5,%6,%7},v;\n"
               " ld.relaxed.gpu.global.b128 v,[%25+1024]; mov.b128 {%8,%9,%10,%11},v;\n"
               " ld.relaxed.gpu.global.b128 v,[%25+1536]; mov.b128 {%12,%13,%14,%15},v;\n"
               " ld.relaxed.gpu.global.b128 v,[%25+2048]; mov.b128 {%16,%17,%18,%19},v;\n"
               " ld.relaxed.gpu.global.b128 v,[%25+2560]; mov.b128 {%20,%21,%22,%23},v;\n"
               "POLL_LOOP:\n add.s32 %24,%24,16;\n"
               " lop3.b32 t,%0,%2,%26,0x7e; and.b32 t,t,1; setp.ne.b32 p0,t,0;\n"
               " lop3.b32 t,%4,%6,%26,0x7e; and.b32 t,t,1; setp.ne.b32 p1,t,0;\n"
               " lop3.b32 t,%8,%10,%26,0x7e; and.b32 t,t,1; setp.ne.b32 p2,t,0;\n"
               " lop3.b32 t,%12,%14,%26,0x7e; and.b32 t,t,1; setp.ne.b32 p3,t,0;\n"
               " lop3.b32 t,%16,%18,%26,0x7e; and.b32 t,t,1; setp.ne.b32 p4,t,0;\n"
               " lop3.b32 t,%20,%22,%26,0x7e; and.b32 t,t,1; setp.ne.b32 p5,t,0;\n"
               " or.pred q,p0,p1; or.pred q,q,p2; or.pred q,q,p3; or.pred q,q,p4; or.pred q,q,p5; setp.lt.and.s32 q,%24,%27,q; vote.sync.any.pred q,q,0xffffffff;\n"
               " mov.b128 v,{%0,%1,%2,%3}; @p0 ld.relaxed.gpu.global.b128 v,[%25+0]; mov.b128 {%0,%1,%2,%3},v;\n"
               " mov.b128 v,{%4,%5,%6,%7}; @p1 ld.relaxed.gpu.global.b128 v,[%25+512]; mov.b128 {%4,%5,%6,%7},v;\n"
               " mov.b128 v,{%8,%9,%10,%11}; @p2 ld.relaxed.gpu.global.b128 v,[%25+1024]; mov.b128 {%8,%9,%10,%11},v;\n"
               " mov.b128 v,{%12,%13,%14,%15}; @p3 ld.relaxed.gpu.global.b128 v,[%25+1536]; mov.b128 {%12,%13,%14,%15},v;\n"
               " mov.b128 v,{%16,%17,%18,%19}; @p4 ld.relaxed.gpu.global.b128 v,[%25+2048]; mov.b128 {%16,%17,%18,%19},v;\n"
               " mov.b128 v,{%20,%21,%22,%23}; @p5 ld.relaxed.gpu.global.b128 v,[%25+2560]; mov.b128 {%20,%21,%22,%23},v;\n"
               " @q bra.uni POLL_LOOP;\n}"
               : "=&r"(x[0].x), "=&r"(x[0].y), "=&r"(x[0].z), "=&r"(x[0].w), "=&r"(x[1].x), "=&r"(x[1].y), "=&r"(x[1].z), "=&r"(x[1].w), "=&r"(x[2].x), "=&r"(x[2].y), "=&r"(x[2].z), "=&r"(x[2].w), "=&r"(x[3].x), "=&r"(x[3].y), "=&r"(x[3].z), "=&r"(x[3].w), "=&r"(x[4].x), "=&r"(x[4].y), "=&r"(x[4].z), "=&r"(x[4].w), "=&r"(x[5].x), "=&r"(x[5].y), "=&r"(x[5].z), "=&r"(x[5].w), "+&r"(spin)
               : "l"(mb), "r"(tag), "n"(SPIN_TOT) : "memory");
}
template <int NL>
__device__ __forceinline__ void poll_add(const uint8_t* mb, uint32_t tag, float (&f)[8], uint8_t* flag, bool lead, int& spin) {
  uint4 x[NL];
  poll<NL>(x, mb, tag, spin);
  if (FLP == 0 && lead) st_relaxed(flag, 0);
#pragma unroll
  for (int i = 0; i < NL; i++) {
    const uint32_t u[4] = {x[i].x, x[i].y, x[i].z, x[i].w};
#pragma unroll
    for (int j = 0; j < 4; j++) {
      if (i == 0) { f[2 * j] = bf_lo(u[j]); f[2 * j + 1] = bf_hi(u[j]); }
      else { f[2 * j] += bf_lo(u[j]); f[2 * j + 1] += bf_hi(u[j]); }
    }
  }
}

template <int B, int SLOT>
__device__ __forceinline__ void wo_step(float (&acc)[8], const uint32_t (&wf)[C::NKR][4], int kk) {
  using namespace C;
  const int k = 4 * B + kk;
  const uint64_t db = mkdesc_ns(SB0 + og_off(SLOT) + kk * 512, 256, 128);
  if (k < NKR) wgmma_rt16(acc, wf[k < NKR ? k : 0], db, SLOT | kk);
  else wgmma_tt16(acc, wdesc(OFF_YO + (k - NKR) * 2048), db, 1);
}
template <int B, int SLOT>
__device__ __forceinline__ void wo_block(float (&acc)[8], const uint32_t (&wf)[C::NKR][4]) {
#pragma unroll
  for (int kk = 0; kk < 4; kk++) wo_step<B, SLOT>(acc, wf, kk);
}

__device__ __forceinline__ void chain_a(const CUtensorMap& tmWo, const CUtensorMap& tmWq, const uint32_t sb, const int tid0, const int cta, const int rank) {
  using namespace C;
  asm volatile("setmaxnreg.inc.sync.aligned.u32 200;");
  int spin = 0;
  uint32_t wf[NKR][4];
  load_weights_rs<true>(wf, tmWo, tmWq, cta, rank, sb, tid0, spin);
  const int wu = uni(tid0 >> 5);
  const bool t9 = cta >= 72 && cta < 88;
  const uint64_t exa = reinterpret_cast<uint64_t>(ex_window(g_ex));
  const uint32_t ehi = (uint32_t)(exa >> 32), elo = (uint32_t)exa;

  int b1 = B1, b2 = B2;
#pragma unroll 1
  for (int i = -1; i < NSTEP; i++) {
    const int ph = i & 1;
    if (i >= 0) {
      const int tid = fresh(tid0);
      const uint32_t mo = __shfl_xor_sync(0xffffffffu, elo + (ph << 20) + ((rank * 24 + (tid >> 4)) * 4 + (tid & 3)) * 2048 + (cta / 3) * 64 + (tid & 12) * 4, 0);
      const uint32_t m9 = __shfl_xor_sync(0xffffffffu, elo + (ph << 20) + MAIL9 + (((tid >> 4) * 2 + (tid & 1)) * 4 + (tid & 2)) * 3072 + cta * 32 + (tid & 12) * 2, 0);
      const uint32_t oo = __shfl_xor_sync(0xffffffffu, (tid >> 5) * 512 + (tid & 2) * 64 + (tid & 28) * 4 + (tid & 1) * 8, 0);
      if (i == 0) { mwait(sb + BAR_W + 24, 1, spin); mwait(sb + BAR_W + 32, 1, spin); PTS(7); }
      mwait(sb + BAR_M, ph, spin);
      TS(i, 3);
      {
        float x[20];
        int redo = 0;
      retry:
        bool bad;
        {
          float dq[8] = {}, dk[8] = {};
#pragma unroll 1
          for (int k0 = 0; k0 < 40; k0 += P1U) {
            wg_fence();
#pragma unroll
            for (int k = 0; k < P1U; k++) {
              if (k == P1U - QIE / 2 && k0 == 40 - P1U && !redo) CBAR_ARRIVE(NB_QI, 256);
              const uint64_t db = desc_at(mdesc(k), k0 * 512);
              wgmma_ts16(dq, desc_at(wdesc(OFF_WQ + k * 2048), k0 * 2048), db, 1);
              wgmma_ts16(dk, desc_at(wdesc(OFF_WK + k * 2048), k0 * 2048), db, 1);
            }
            wg_commit();
          }
          const int m = (tid >> 3) & 3, dg = (tid >> 5) * 2 + (m & 1);
          const uint32_t ka = sb + OFF_KT + dg * KS + (m >> 1) * 640 + (tid & 7) * 16;
          if (!redo) CBAR_SYNC(NB_QK, 384);
          sts32(sb + FLG_REDO, redo);
          wg_wait<0>();
          TS(i, 4);
          stsm4(ka, pack_bf16(dk[0], dk[1]), pack_bf16(dk[2], dk[3]), pack_bf16(dk[4], dk[5]), pack_bf16(dk[6], dk[7]));
          stsm4(ka + dg * (VS - KS) + (OFF_VT + 128 - OFF_KT), scale_bf16x2(pack_bf16(dq[0], dq[1]), SCQ), scale_bf16x2(pack_bf16(dq[2], dq[3]), SCQ),
                scale_bf16x2(pack_bf16(dq[4], dq[5]), SCQ), scale_bf16x2(pack_bf16(dq[6], dq[7]), SCQ));
          const float chk = (dq[0] + dq[1]) + (dq[4] + dq[5]);
          fence_async();
          bad = bar_red_or(NB_C, 128, chk != chk && !redo);
        }
        TSB(i, 5);
        wg_fence();
#pragma unroll
        for (int kk = 0; kk < 4; kk++) wgmma_tt40(x, mkdesc_ns(SB0 + OFF_VT + 128 + kk * 2 * VS, VS, 640), mkdesc_ns(SB0 + OFF_KT + kk * 2 * KS, KS, 128), kk);
#pragma unroll
        for (int kk = 0; kk < 4; kk++) {
          if (SIE && kk == 4 - SIE && !bad) CBAR_ARRIVE(NB_SI, 256);
          wgmma_tt40(x, mkdesc_ns(SB0 + OFF_VT + kk * 2 * VS, VS, 384), mkdesc_ns(SB0 + OFF_KT + 640 + kk * 2 * KS, KS, 128), 1);
        }
        wg_commit();
        if (!SIE && !bad) CBAR_ARRIVE(NB_SI, 256);
        if (__builtin_expect(__any_sync(0xffffffffu, bad), 0)) {
          wg_wait<0>();
#pragma unroll 1
          for (int k = 0; k < 10; k++) {
            uint4 v = lds128(sb + OFF_M + tid * 16 + k * 2048);
            if (v.x == SENT || v.y == SENT || v.z == SENT || v.w == SENT) {
              do { v = ld_relaxed4(mkptr(elo + EX_M + i * 20480 + tid * 16 + k * 2048, ehi)); spin += 16; } while ((v.x == SENT || v.y == SENT || v.z == SENT || v.w == SENT) && spin < SPIN_TOT);
              sts128(sb + OFF_M + tid * 16 + k * 2048, v);
            }
          }
          fence_async();
          bar_sync(NB_C, 128);
          redo = fresh(1);
          goto retry;
        }
        TSV(i, 36, redo);
        const uint32_t rb1 = mapa(sb, (rank + 1) % 3), rb2 = mapa(sb, (rank + 2) % 3);
        wg_wait<0>();
        TS(i, 6);
        if (wu < 2) {
          float y[10];
#pragma unroll
          for (int j = 0; j < 5; j++) { y[2 * j] = x[4 * j]; y[2 * j + 1] = x[4 * j + 1]; }
          const uint4 h0 = make_uint4(pack_h2(y[0], y[1]), pack_h2(y[2], y[3]), pack_h2(y[4], y[5]), pack_h2(y[6], y[7]));
          const uint32_t h1 = pack_h2(y[8], y[9]);
          st_async4u(rb1 + OFF_XM + 1024 + tid * 16, h0, rb1 + BAR_XM);
          st_async4u(rb2 + OFF_XM + tid * 16, h0, rb2 + BAR_XM);
          st_async1u(rb1 + OFF_XM + 2304 + tid * 4, h1, rb1 + BAR_XM);
          st_async1u(rb2 + OFF_XM + 2048 + tid * 4, h1, rb2 + BAR_XM);
          CBAR_ARRIVE(NB_SM, 256);
          if ((tid & 31) == 0) mbar_arrive_cluster(mapa(sb, 0) + BAR_E);
          TS(i, 7);
          const uint32_t sw = (tid & 7) * 4 + (tid & 8) * 8 + (tid & 16) * 2;
          mwait(sb + BAR_XM, ph, spin);
          TS(i, 8);
          const uint4 u0 = lds128(sb + OFF_XM + tid * 16), v0 = lds128(sb + OFF_XM + 1024 + tid * 16);
          const uint32_t u1 = lds32(sb + OFF_XM + 2048 + tid * 4), v1 = lds32(sb + OFF_XM + 2304 + tid * 4);
          add_h2(y[0], y[1], u0.x, v0.x); add_h2(y[2], y[3], u0.y, v0.y); add_h2(y[4], y[5], u0.z, v0.z); add_h2(y[6], y[7], u0.w, v0.w);
          add_h2(y[8], y[9], u1, v1);
          const float mx = quad_max(max10(y)) * -SCE;
#pragma unroll
          for (int j = 0; j < 5; j++) {
            y[2 * j] = ex2(fmaf(y[2 * j], SCE, mx)); y[2 * j + 1] = ex2(fmaf(y[2 * j + 1], SCE, mx));
            sts32(sb + OFF_PT + wu * 640 + sw + j * 128, pack_bf16(y[2 * j], y[2 * j + 1]));
          }
          sts32(sb + OFF_XM + 2048 + wu * 128 + sw, __float_as_uint(sum10(y)));
          fence_async();
          TS(i, 9);
        } else {
          CBAR_ARRIVE(NB_SM, 256);
          if ((tid & 31) == 0) mbar_arrive_cluster(mapa(sb, 0) + BAR_E);
          mwait(sb + BAR_MF, ph, spin);
        }
      }
      CBAR_SYNC(NB_VA, 256);
      TSB(i, 10);
      {
        float o[2][4];
        wg_fence();
#pragma unroll
        for (int c = 0; c < 2; c++)
#pragma unroll
          for (int q = 0; q < 3; q++)
            wgmma_ss8(o[c], mkdesc_ns(SB0 + OFF_VT + 128 + c * 640 + q * 256, 128, VS), mkdesc_ns(SB0 + OFF_PT + c * 640 + q * 256, q == 2 && c == 0 ? 768 : 128, 128), q);
        wg_commit();
        const float4 e = lds128f(sb + OFF_XM + 2048 + (tid & 15) * 16);
        const uint32_t rb1 = mapa(sb, (rank + 1) % 3), rb2 = mapa(sb, (rank + 2) % 3);
        const float inv = rcp((e.x + e.y) + (e.z + e.w));
        const int sl = (tid & 3) * 2;
        const float i0 = __shfl_sync(0xffffffffu, inv, sl), i1 = __shfl_sync(0xffffffffu, inv, sl + 1);
        const float i2 = __shfl_sync(0xffffffffu, inv, sl + 8), i3 = __shfl_sync(0xffffffffu, inv, sl + 9);
        wg_wait<0>();
        TS(i, 11);
        const uint32_t p0 = pack_bf16(o[0][0] * i0, o[0][1] * i1), p1 = pack_bf16(o[1][0] * i2, o[1][1] * i3);
        const uint32_t p2 = pack_bf16(o[0][2] * i0, o[0][3] * i1), p3 = pack_bf16(o[1][2] * i2, o[1][3] * i3);
        if (OGF) { sts64(sb + oo + og_off(0), p0, p1); sts64(sb + oo + og_off(0) + 256, p2, p3); fence_async(); }
        st_async2u(rb1 + oo + og_off(2), p0, p1, rb1 + BAR_OG);
        st_async2u(rb2 + oo + og_off(1), p0, p1, rb2 + BAR_OG);
        st_async2u(rb1 + oo + og_off(2) + 256, p2, p3, rb1 + BAR_OG);
        st_async2u(rb2 + oo + og_off(1) + 256, p2, p3, rb2 + BAR_OG);
        if (!OGF) { sts64(sb + oo + og_off(0), p0, p1); sts64(sb + oo + og_off(0) + 256, p2, p3); fence_async(); }
      }
      CBAR_SYNC(NB_A, 128);
      TSB(i, 12);
      {
        float acc[3][8];
        wg_fence();
        wo_block<0, 0>(acc[2], wf);
        wg_commit();
        if (tid == 0) mbar_arrive_cluster(mapa(sb, 1) + BAR_E + 8);
        wo_block<1, 0>(acc[0], wf);
        wo_block<4, 0>(acc[1], wf);
        wg_commit();
        const uint32_t tag = (i >> 1) & 1;
#define TAGGED(LO, HI) ((pack_bf16(LO, HI) & ~1u) | tag)
#define SEND(OFF, U) st_relaxed128(mkptr(mo, ehi) + (OFF), TAGGED(acc[U][0], acc[U][2]), pack_bf16(acc[U][1], acc[U][3]), pack_bf16(acc[U][4], acc[U][6]), pack_bf16(acc[U][5], acc[U][7]))
        wg_wait<1>();
        const uint32_t n0 = pin(TAGGED(acc[2][0], acc[2][2])), n1 = pin(pack_bf16(acc[2][1], acc[2][3]));
        const uint32_t n2 = pin(TAGGED(acc[2][4], acc[2][6])), n3 = pin(pack_bf16(acc[2][5], acc[2][7]));
        wg_fence();
        wo_block<7, 0>(acc[2], wf);
        wg_commit();
        st_relaxed64(mkptr(m9, ehi), n0, n1);
        st_relaxed64(mkptr(m9, ehi) + 3072, n2, n3);
        mwait(sb + BAR_OG, ph, spin);
        asm volatile("fence.proxy.async::generic.acquire.sync_restrict::shared::cluster.cluster;" ::: "memory");
        TS(i, 13);
        wg_fence();
        wo_block<2, 1>(acc[0], wf); wo_block<3, 2>(acc[0], wf);
        wg_commit();
        wo_block<5, 1>(acc[1], wf); wo_block<6, 2>(acc[1], wf);
        wg_commit();
        wg_wait<1>(); SEND(0, 0);
        wo_block<8, 1>(acc[2], wf); wo_block<9, 2>(acc[2], wf);
        wg_commit();
        if (WOE == 0) { CBAR_ARRIVE(NB_WV, 256); CBAR_ARRIVE(NB_WQ, 256); }
        wg_wait<1>(); SEND(32 * 2048, 1);
        if (WOE == 1) CBAR_ARRIVE(NB_WV, 256);
        wg_wait<0>(); SEND(64 * 2048, 2);
        if (WOE == 2) CBAR_ARRIVE(NB_WV, 256);
        if (WOE >= 1) CBAR_ARRIVE(NB_WQ, 256);
#undef SEND
#undef TAGGED
      }
      TS(i, 14);
      if (i < 2) PTS(19 + i);
      if (i + 1 >= NSTEP) break;
    }
    uint32_t t1 = clk32();
    if (i >= 0) {
      const int lane = fresh(tid0) & 31, j = lane >> 3;
      const uint8_t* mb = mkptr(elo + (ph << 20) + (t9 ? MAIL9 + (cta - 72) * 12288 + wu * 3072 : (cta < 72 ? cta : cta - 24) * 8192 + wu * 2048) + lane * 16, ehi);
      const uint32_t tag = (i >> 1) & 1;
      const bool pub = (lane & (t9 ? 6 : 4)) == 0 && !(((t9 ? cta : wu) & 1) && i + 1 == LAG) && cta < 88;
      const uint32_t dst = pin(elo + EX_M + (i + 1) * 20480 + (t9 ? (cta + 72) * 128 + wu * 32 + (j & 1) * 16 + (lane & 1) * 8 + (j >> 1) * 4
                                                                   : cta * 256 + (wu & 1) * 128 + (wu >> 1) * 64 + j * 16 + (lane & 3) * 4));
      uint8_t* flag = mkptr(elo + EX_FLAG + (i + 1) * 3072 + cta * 32 + wu * 4, ehi);
      while (clk32() - t1 < b1) {}
      TS(i + 1, 30);
      float f[8];
      const int n0 = spin;
      if (!t9) poll_add<4>(mb, tag, f, flag, lane == 0, spin);
      else poll_add<6>(mb, tag, f, flag, lane == 0, spin);
      if (FLP == 1 && lane == 0) st_relaxed(flag, __float_as_uint(f[0] + f[7]) >> 1);
      t1 = clk32();
      b1 = __any_sync(0xffffffffu, spin - n0 > 16) ? min(b1 + AD1, BMX) : max(b1 - AD0, 0);
      TSV(i + 1, 38, b1);
      TS(i + 1, 31); TSV(i + 1, 32, (spin - n0) >> 4);
      const bool h = lane & 16, q = lane & 8;
#pragma unroll
      for (int j = 0; j < 4; j++) f[j] = (h ? f[4 + j] : f[j]) + __shfl_xor_sync(0xffffffffu, h ? f[j] : f[4 + j], 16);
#pragma unroll
      for (int j = 0; j < 2; j++) f[j] = (q ? f[2 + j] : f[j]) + __shfl_xor_sync(0xffffffffu, q ? f[j] : f[2 + j], 8);
      f[0] += __shfl_xor_sync(0xffffffffu, f[0], 4); f[1] += __shfl_xor_sync(0xffffffffu, f[1], 4);
      if (t9) { f[0] += __shfl_xor_sync(0xffffffffu, f[0], 2); f[1] += __shfl_xor_sync(0xffffffffu, f[1], 2); }
      if (pub) st_relaxed(mkptr(dst, ehi), pack_bf16(f[0], f[1]));
      if (FLP == 2 && lane == 0) st_relaxed(flag, 0);
      if (wu == 3) {
        CBAR_SYNC(NB_MR, 160);
        if (elect_one()) signal_o(i, cta);
      }
      TS(i + 1, 15);
    }
    if (wu == 0) {
      const int tid = fresh(tid0);
      const uint8_t* pp = mkptr(elo + EX_FLAG + (i + 1) * 3072 + (rank * 28 + (tid < 28 || rank == 2 ? tid : 0)) * 32, ehi);
      while (clk32() - t1 < b2) {}
      TS(i + 1, 16);
      int n = 1;
      uint4 x = ld_relaxed4(pp);
      if (tid0 == 0) mbar_expect_tx(sb + BAR_M, 20480);
      bool mok = mbar_test(sb + BAR_MOK, ph ^ 1);
      while (__any_sync(0xffffffffu, (int)(x.x | x.y | x.z | x.w) < 0 && spin < SPIN_TOT)) { x = ld_relaxed4(pp); mok = mbar_test(sb + BAR_MOK, ph ^ 1); n++; spin += 16; }
      if (!mok) mwait(sb + BAR_MOK, ph ^ 1, spin);
      b2 = n > 1 ? min(b2 + AD3, BMX) : max(b2 - AD2, 0);
      TSV(i + 1, 35, n); TSV(i + 1, 39, b2);
      TS(i + 1, 34);
      if (elect_one()) bulk_g2s_mc(sb + OFF_M + rank * 7168, mkptr(elo + EX_M + (i + 1) * 20480 + rank * 7168, ehi), rank == 2 ? 6144 : 7168, sb + BAR_M);
      TS(i + 1, 33);
      __syncwarp();
    }
  }
  if (spin >= SPIN_TOT) g_err = 1;
}

__global__ void __cluster_dims__(3, 1, 1) __launch_bounds__(384, 1)
k_chain(const __grid_constant__ CUtensorMap tmWq, const __grid_constant__ CUtensorMap tmWk,
        const __grid_constant__ CUtensorMap tmWv, const __grid_constant__ CUtensorMap tmWo, const bf16* __restrict__ x0, const bf16* __restrict__ mem0) {
  using namespace C;
  extern __shared__ __align__(1024) uint8_t smem[];
  const uint32_t sb = smem_u32(smem);
  const int tid = threadIdx.x;
  const int wg = __shfl_sync(0xffffffffu, tid >> 7, 0);
  const int cta = uni(blockIdx.x), rank = uni(blockIdx.x % 3);

  asm volatile("griddepcontrol.launch_dependents;");
  if (cta < 4) prefetch_l2(tid < 320 ? x0 + (cta * 320 + tid) * 64 : mem0 + (cta * 20 + tid % 20) * 64);
  if (tid == 32) {
    for (int p = 0; p < 5; p++) mbar_init(sb + BAR_W + 8 * p, 2);
    fence_async();
    for (int p = 0; p < NBX; p++) { stage_box<false>(tmWv, sb, p, cta, rank); stage_box<true>(tmWo, sb, p, cta, rank); }
  }
  if (tid == 0) {
    if ((sb & 0xFFFFFF) != SB0) g_err = 100;
    for (int p = 0; p < 5; p++) { mbar_init(sb + BAR_F + 8 * p, 1); mbar_init(sb + BAR_E + 8 * p, p == 2 ? 12 : p == 1 ? 15 : 24); }
    mbar_init(sb + BAR_M, 1); mbar_init(sb + BAR_MOK, 24); mbar_init(sb + BAR_XM, 1); mbar_init(sb + BAR_XF, 2);
    mbar_init(sb + BAR_XT, 1); mbar_init(sb + BAR_MF, 8); mbar_init(sb + BAR_OG, 1);
    for (int p = 0; p < 5; p++) mbar_expect_tx(sb + BAR_F + 8 * p, 16384);
    for (int p = 0; p < 16; p++) sts32(sb + OFF_SAFE + 4 * p, 0);
    for (int p = 0; p < 32; p++) sts32(sb + OFF_ONE + 4 * p, 0x3F803F80);
    asm volatile("fence.mbarrier_init.release.cluster;" ::: "memory");
    fence_async();
  }
  __syncthreads();
  asm volatile("barrier.cluster.arrive.relaxed.aligned;" ::: "memory");
  asm volatile("barrier.cluster.wait.aligned;" ::: "memory");

  if (wg == 0) chain_a(tmWo, tmWq, sb, keep(tid), cta, rank);
  else if (wg == 1) chain_q(x0, mem0, sb, keep(tid), cta, rank);
  else chain_v(tmWv, tmWk, sb, keep(tid), cta, rank);
  asm volatile("barrier.cluster.arrive.release.aligned;" ::: "memory");
  asm volatile("barrier.cluster.wait.acquire.aligned;" ::: "memory");
}

namespace W {
constexpr int NP = 25, NBC = 11, NW = NP + NBC;
constexpr int PRS = 37, PW = 43 * 2048;
constexpr int OFF_W = 0;
constexpr int OFF_R = 2 * PW;
constexpr int BRS = 37, VSS = 39;
constexpr int OFF_WO = 0, OFF_Y = 81920;
constexpr int OFF_X = OFF_Y + 2 * (40 - BRS) * 2048;
constexpr int OFF_WV = OFF_X + 40960;
constexpr int OFF_S = OFF_WV + VSS * 2048;
constexpr int COL = 976;
constexpr int OFF_T = OFF_X + 16384;
constexpr int OFF_H = OFF_S + 7696;
constexpr int OFF_BAR = OFF_H + 8 * COL;
constexpr int OFF_SAFE = OFF_BAR + 256;
constexpr int SMEM = 232448;
static_assert(OFF_SAFE + 64 <= SMEM && OFF_R + 40960 <= OFF_BAR, "");
constexpr uint32_t SB0 = 1024;
constexpr int BAR_F = OFF_BAR, BAR_E = OFF_BAR + 40, BAR_G = OFF_BAR + 80, BAR_W = OFF_BAR + 160, BAR_R = OFF_BAR + 176;
constexpr int NB_G0 = 1, NB_SG = 4, NB_B = 5, NB_AS = 6, NB_SG1 = 7, NB_RED = 8, NB_SF = 9, NB_R = 11, NB_TD = 12;
}
#define FSW 1
#define FSA 2
#define WBAR_SYNC(id, n) bar_sync(id, n)
#define WBAR_ARRIVE(id, n) bar_arrive(id, n)

__device__ __forceinline__ uint64_t rdesc(int off, int kk) { return mkdesc(W::SB0 + off + kk * 32, 16, 1024); }
__device__ __forceinline__ uint64_t gdesc(int off, int kk) { return mkdesc_ns(W::SB0 + off + kk * 1024, 512, 512) | ((uint64_t)2 << 62); }
__device__ __forceinline__ uint32_t frag_addr(uint32_t base, int tid) {
  const int i = (tid >> 3) & 3, r = tid & 7;
  return base + (r + (i >> 1) * 8) * 128 + (((2 * ((tid >> 5) & 3) + (i & 1)) ^ r) << 4);
}
template <int NK>
__device__ __forceinline__ void load_frags(uint32_t (&wf)[NK][4], uint32_t base, int tid) {
  const uint32_t a0 = frag_addr(base, tid);
#pragma unroll
  for (int k = 0; k < NK; k++) ldsm4t(wf[k], a0 + k * 2048);
}
__device__ __forceinline__ void red_tile(const float* d, int seg, int col0, int tid) {
  float* p = g_x + (size_t)(seg * 32 + 2 * (tid & 3)) * DM + col0 + ((tid >> 5) & 3) * 16 + ((tid >> 2) & 7) * 2;
#pragma unroll
  for (int j = 0; j < 8; j++)
    asm volatile("red.relaxed.gpu.global.add.v2.f32 [%0],{%1,%2};" ::"l"(p + ((j >> 1) * 8 + (j & 1)) * DM), "f"(d[4 * (j >> 1) + (j & 1)]), "f"(d[4 * (j >> 1) + 2 + (j & 1)]) : "memory");
}

__device__ __forceinline__ void work_p(const CUtensorMap& tmWo, uint32_t sb, int pc, const int WG, int tid0) {
  using namespace W;
  asm volatile("setmaxnreg.inc.sync.aligned.u32 208;");
  int spin = 0;
  const int ks = pc / 5, col0 = (pc % 5) * 128 + WG * 64;
  const uint32_t wb = sb + OFF_W + WG * PW;
  uint32_t wf[PRS][4];
#pragma unroll 1
  for (int hf = 0; hf < 2; hf++) {
    const int nk = hf ? 80 - PRS : PRS;
    if ((tid0 & 127) == 0) {
      mbar_expect_tx(sb + BAR_W + 8 * WG, nk * 2048);
      for (int i = 0; i < nk; i++) tma2d(wb + i * 2048, &tmWo, col0, ks * 19 * 64 + (i < PRS ? 2 * i + hf : PRS + i) * 16, sb + BAR_W + 8 * WG);
    }
    __syncwarp();
    mwait(sb + BAR_W + 8 * WG, hf, spin);
    permute_cols(wb, tid0 & 127, nk * 64);
    if (hf == 1 && ks < 4) for (int it = 39 * 64 + (tid0 & 127) - 64; it < 43 * 64; it += 128) {
      const uint32_t a = wb + (it >> 2) * 128 + (((2 * (it & 3)) ^ ((it >> 2) & 6)) << 4);
      if (it >= 39 * 64) { sts128(a, make_uint4(0, 0, 0, 0)); sts128(a + 16, make_uint4(0, 0, 0, 0)); }
    }
    fence_async();
    WBAR_SYNC(NB_G0 + WG, 128);
    if (hf == 0) {
      load_frags<PRS>(wf, wb, tid0);
      fence_async();
      WBAR_SYNC(NB_G0 + WG, 128);
    }
  }
#pragma unroll 1
  for (int k = 0; k < NSTEP; k++) {
    float d[32];
#pragma unroll
    for (int f = 0; f < 20; f++) {
      mwait(sb + BAR_F + 8 * (f % 5), (f / 5) & 1, spin);
      if (f == 0 && WG == 0 && pc == WW) WTS(k, 1);
      wg_fence();
#pragma unroll
      for (int kk = 0; kk < 4; kk++) {
        const int q = 4 * f + kk;
        if (q < 2 * PRS && !(q & 1)) wgmma_rs64(d, wf[q < 2 * PRS ? q >> 1 : 0], rdesc(OFF_R + (f % 5) * 8192, kk), q);
        else wgmma_ts64(d, desc_at(mkdesc(SB0 + OFF_W + (q < 2 * PRS ? q >> 1 : q - PRS) * 2048, 8192, 1024), WG * PW), rdesc(OFF_R + (f % 5) * 8192, kk), 1);
        if (kk == 0 && f > 0) {
          wg_commit();
          wg_wait<1>();
          if ((tid0 & 31) == 0) mbar_arrive(sb + BAR_E + 8 * ((f - 1) % 5));
        }
      }
      wg_commit();
    }
    wg_wait<0>();
    if ((tid0 & 31) == 0) mbar_arrive(sb + BAR_E + 32);
    if (WG == 0 && pc == WW) WTS(k, 2);
    if (k < NSEG) red_tile(d, k, col0, tid0);
    if (k >= LAG) red_tile(d + 16, k - LAG, col0, tid0);
    if (WG == 0 && pc == WW) WTS(k, 13);
    WBAR_SYNC(NB_SG, 256);
    if (WG == 0) { if (tid0 == 0) { if (UNS & 8) csignal_fast(CN_P + k); else csignal_t(CN_P + k, 3); } __syncwarp(); }
  }
  if (spin >= SPIN_TOT) g_err = 11;
}
__device__ __forceinline__ void work_p_producer(uint32_t sb, int pc, int odd) {
  using namespace W;
  int spin = 0;
  const int ks = pc / 5;
#pragma unroll 1
  for (int k = 0; k < NSTEP; k++) {
    const uint32_t lo = k < NSEG ? 0 : 4096, len = k < LAG || k >= NSEG ? 4096 : 8192;
    const uint8_t* src = &g_o[k % ORING][ks * 19 + odd][lo];
    cwait(CN_O + k * 5 + ks, ks == 4 ? 20 : 19, spin);
    fence_async_all();
    if (pc == WW && !odd) WTS1(k, 0);
#pragma unroll
    for (int u = 0; u < 10; u++) {
      const int st = odd ? (2 * u + 1) % 5 : (2 * u) % 5, ph = odd ? ((2 * u + 1) / 5) & 1 : ((2 * u) / 5) & 1;
      mwait(sb + BAR_E + 8 * st, ph ^ 1, spin);
      if (elect_one()) {
        if (u == 9 && odd && ks < 4) mbar_arrive(sb + BAR_F + 8 * st);
        else {
          mbar_expect_tx(sb + BAR_F + 8 * st, len);
          bulk_g2s(sb + OFF_R + st * 8192 + lo, src + u * 16384, len, sb + BAR_F + 8 * st);
        }
      }
    }
  }
  if (spin >= SPIN_TOT) g_err = 12;
}
template <int DMS>
__device__ __forceinline__ void work_ln(const int kind, int r, int lane, bf16* out) {
  int spin = 0;
  const int l = kind & 1;
  const int rp = kind < 2 ? (r & 1) * 16 + (r >> 1) : r;
  const uint32_t sw = ((((lane >> 1) & 7) ^ (rp & 7)) << 4) + (lane & 1) * 8;
  uint8_t* dst = kind < 2 ? g_xnb[l * LAG] + (lane >> 4) * 8192 + l * 4096 + rp * 128 + sw
               : kind == 2 ? g_xn[LAG] + (r >> 3) * 4096 + 2048 + (lane >> 4) * 1024 + (r & 7) * 128 + sw
                           : reinterpret_cast<uint8_t*>(out) + r * 1280 + lane * 8;
#pragma unroll 1
  for (int s = 0; s < NSEG; s++) {
    float* xr = g_x + (size_t)(s * 32 + r) * DM;
    float4 v[5];
    if (kind < 2) {
#pragma unroll
      for (int u = 0; u < 5; u++) {
        const int p = u * 32 + lane;
        stg128((p < 80 ? g_ob[s + l * LAG] + (l * 32 + r) * 1280 : g_y[l] + (size_t)s * 40960 + (r - 1) * 1280) + p * 16, make_uint4(SENT, SENT, SENT, SENT));
      }
      if (lane == 0) cwait(CN_P + s + l * LAG, W::NP, spin);
      __syncwarp();
      if (r == 0 && lane == 0 && (l == 0 || s + LAG >= NSEG)) WTS1(s + l * LAG, 3);
#pragma unroll
      for (int m = 0; m < 5; m++) v[m] = ld_relaxed4f(xr + m * 128 + lane * 4);
    } else {
      if (lane == 0) cwait(CN_L + s + l * LAG, s + l * LAG < LAG || s + l * LAG >= NSEG ? 32 : 64, spin);
      __syncwarp();
#pragma unroll
      for (int m = 0; m < 5; m++) v[m] = ld_relaxed4f(xr + m * 128 + lane * 4);
      if (lane == 0) cwait(CN_W + l * 64 + s, 10, spin);
      __syncwarp();
      if (r == 0 && lane == 0 && (l == 0 || s + LAG >= NSEG)) WTS1(s + l * LAG, 11);
      const uint8_t* yp = g_y[l] + (size_t)s * 40960 + (lane >> 4) * 4096 + r * 128 + sw;
      float2 y[5];
      bool bad;
      do {
        bad = false;
#pragma unroll
        for (int m = 0; m < 5; m++) y[m] = ld_relaxed2f(yp + m * 8192);
#pragma unroll
        for (int m = 0; m < 5; m++) bad |= __float_as_uint(y[m].x) == SENT || __float_as_uint(y[m].y) == SENT;
        spin += 16;
      } while (__any_sync(0xffffffffu, bad && spin < SPIN_TOT));
#pragma unroll
      for (int m = 0; m < 5; m++) {
        v[m].x += bf_lo(__float_as_uint(y[m].x)); v[m].y += bf_hi(__float_as_uint(y[m].x));
        v[m].z += bf_lo(__float_as_uint(y[m].y)); v[m].w += bf_hi(__float_as_uint(y[m].y));
        if (kind == 2) *reinterpret_cast<float4*>(xr + m * 128 + lane * 4) = v[m];
      }
    }
    if (kind < 3) ln_row(v);
#pragma unroll
    for (int m = 0; m < 5; m++)
      asm volatile("st.global.v2.b32 [%0],{%1,%2};" ::"l"(dst + m * DMS), "r"(pack_bf16(v[m].x, v[m].y)), "r"(pack_bf16(v[m].z, v[m].w)) : "memory");
    dst += DMS == 256 ? 40960 : 81920;
    __syncwarp();
    if (r == 0 && lane == 0 && (l == 0 || s + LAG >= NSEG)) WTS1(s + l * LAG, kind < 2 ? 4 : 12);
    if (lane == 0 && kind < (NOWORK ? 2 : 3)) { if ((UNS >> (kind < 2 ? 1 : 2)) & 1) csignal_fast(kind < 2 ? CN_L + s + l * LAG : CN_X + s + LAG); else csignal_t(kind < 2 ? CN_L + s + l * LAG : CN_X + s + LAG, kind); }
  }
  if (spin >= SPIN_TOT) g_err = 13;
}

__device__ __forceinline__ void work_prep(const bf16* x0, const bf16* mem0, int r, int lane) {
  int spin = 0;
#pragma unroll 1
  for (int k = NPRE; k < NSTEP; k++) {
    if (lane < 20) prefetch_l2(x0 + (size_t)min(k * 32 + r + (lane < 10 ? 0 : 16), SEQ - 1) * DM + (lane % 10) * 64);
    if (lane == 0) cwait(CN_O + (k - NPRE) * 5, 1, spin);
    __syncwarp();
#pragma unroll 1
    for (int h = 0; h < 2; h++) {
      uint2 u[5];
      ln0_load(x0, u, min(k * 32 + r + 16 * h, SEQ - 1), lane);
      prep_row(u, mem0, k, r + 16 * h, lane);
    }
    __syncwarp();
    if (lane == 0) csignal(CN_X + k);
  }
  if (spin >= SPIN_TOT) g_err = 19;
}

__device__ __forceinline__ void stage_qkv(const bf16* wqkv, uint32_t base, int T, int bc, int tid) {
  const int q = tid & 15;
  const bool ok = q < 15 && bc * 60 + 4 * q < DM;
  const bf16* src = wqkv + T * DM + bc * 60 + 4 * q;
#pragma unroll 1
  for (int k0 = tid >> 4; k0 < 640; k0 += 80) {
    uint2 v[10];
#pragma unroll
    for (int u = 0; u < 10; u++) v[u] = ok ? *reinterpret_cast<const uint2*>(src + (size_t)(k0 + 8 * u) * 1920) : make_uint2(0, 0);
#pragma unroll
    for (int u = 0; u < 10; u++) sts64(base + (k0 + 8 * u) * 128 + (((q >> 1) ^ (k0 & 7)) << 4) + (q & 1) * 8, v[u].x, v[u].y);
  }
}
struct AttAddr { uint32_t qa, qb, ka, oa, ob, ml; };
__device__ __forceinline__ AttAddr att_addr(uint32_t sb, int bc, int hh, int tid) {
  using namespace W;
  const int r = tid & 7, m = (tid >> 3) & 3, g = (tid >> 2) & 7, t = tid & 3, lp = (tid >> 5) & 3;
  const int f2 = r < 4 ? 20 * hh + 16 + r : 60;
  const uint32_t tb = sb + OFF_T + 2 * lp * COL;
  const int fa = 20 * hh + (m >> 1) * 8 + r, pc = 2 * (lp & 1) + (m & 1);
  const uint32_t o0 = sb + OFF_S + (lp >> 1) * 3840;
  AttAddr x;
  x.qa = keep(tb + (m & 1) * COL + (20 * hh + (m >> 1) * 8 + r) * 16);
  x.qb = keep(tb + (m & 1) * COL + f2 * 16);
  x.ka = keep(tb + (m < 2 ? 20 * hh + 8 * m + r : f2) * 16);
  x.oa = keep(o0 + fa * 64 + ((pc ^ ((bc * 60 + fa) >> 1)) & 3) * 16);
  x.ob = keep(r < 4 ? o0 + f2 * 64 + ((pc ^ ((bc * 60 + f2) >> 1)) & 3) * 16 : sb + OFF_S + 7680);
  x.ml = keep((2 * t > g ? 0xFFFFu : 0u) | (2 * t + 1 > g ? 0xFFFF0000u : 0u));
  return x;
}
__device__ __forceinline__ void release_tiles(uint32_t sb, int tid) {
  fence_async();
  __syncwarp();
  if ((tid & 31) < 3) mbar_arrive(sb + W::BAR_E + 16 + 8 * (tid & 3));
}
__device__ __forceinline__ void attend(uint32_t sb, const AttAddr& x, int k0, int lp, int tid) {
  using namespace W;
  const uint32_t hd = OFF_H - OFF_T - lp * COL;
  const float scl = 0.22360679774997896f * 1.4426950408889634f;
  float sc[3][4];
  uint32_t v[3][4];
  {
    uint32_t q[4], q8a, q8b, k[3][4];
    ldsm4t(q, x.qa);
    ldsm4t(k[0], x.ka + hd); ldsm4t(k[1], x.ka + 8 * COL); ldsm4t(k[2], x.ka + 9 * COL);
    ldsm2t(q8a, q8b, x.qb);
#pragma unroll
    for (int c = 0; c < 3; c++) { sc[c][0] = sc[c][1] = sc[c][2] = sc[c][3] = 0.f; mma16816(sc[c], q[0], q[1], q[2], q[3], k[c][0], k[c][1]); }
#pragma unroll
    for (int c = 0; c < 3; c++) mma1688(sc[c], q8a, q8b, k[c][2]);
    stsm4t(x.ka + hd, k[2][0], k[2][1], k[2][2], k[2][3]);
  }
  ldsm4(v[0], x.ka + hd + 4 * COL); ldsm4(v[1], x.ka + 16 * COL); ldsm4(v[2], x.ka + 17 * COL);
  stsm4(x.ka + hd + 4 * COL, v[2][0], v[2][1], v[2][2], v[2][3]);
  release_tiles(sb, tid);
  const bool lo0 = x.ml & 1, lo1 = (int)x.ml < 0, first = k0 == (lp >> 1) * LAG;
  uint32_t pw[2];
  float inv[2];
#pragma unroll
  for (int h = 0; h < 2; h++) {
    float y0 = lo0 ? sc[h][2 * h] : sc[h + 1][2 * h], y1 = lo1 ? sc[h][2 * h + 1] : sc[h + 1][2 * h + 1];
    if (h == 0 && first) { y0 = lo0 ? -INFINITY : y0; y1 = lo1 ? -INFINITY : y1; }
    const float mx = quad_max(fmaxf(y0, y1)) * -scl;
    y0 = ex2(fmaf(y0, scl, mx)); y1 = ex2(fmaf(y1, scl, mx));
    pw[h] = pack_bf16(y0, y1);
    inv[h] = y0 + y1;
  }
  float o[3][4];
  const uint32_t a0 = pw[0] & x.ml, a2 = pw[0] & ~x.ml, a3 = pw[1] & x.ml, a5 = pw[1] & ~x.ml, z0 = tid >> 10, z1 = tid >> 11;
#pragma unroll
  for (int j = 0; j < 3; j++) { o[j][0] = o[j][1] = o[j][2] = o[j][3] = 0.f; mma16816(o[j], a0, z0, a2, a3, v[0][j], v[1][j]); }
#pragma unroll
  for (int j = 0; j < 3; j++) mma1688(o[j], z1, a5, v[2][j]);
  inv[0] = rcp(quad_sum(inv[0])); inv[1] = rcp(quad_sum(inv[1]));
  stsm4t(x.oa, pack_bf16(o[0][0] * inv[0], o[0][1] * inv[0]), pack_bf16(o[0][2] * inv[1], o[0][3] * inv[1]),
         pack_bf16(o[1][0] * inv[0], o[1][1] * inv[0]), pack_bf16(o[1][2] * inv[1], o[1][3] * inv[1]));
  stsm2t(x.ob, pack_bf16(o[2][0] * inv[0], o[2][1] * inv[0]), pack_bf16(o[2][2] * inv[1], o[2][3] * inv[1]));
  fence_async();
}
template <bool IS_V>
__device__ __forceinline__ void work_b(const CUtensorMap& tmBo, const bf16* wqkv, uint32_t sb, int bc, const int wg, int tid0) {
  using namespace W;
  if (!IS_V) asm volatile("setmaxnreg.inc.sync.aligned.u32 208;");
  else asm volatile("setmaxnreg.dec.sync.aligned.u32 72;");
  constexpr int NR = IS_V ? 40 - VSS : BRS;
  const int WG = IS_V ? 2 : wg;
  const uint32_t yo = WG * (40 - BRS) * 2048;
  int spin = 0;
  uint32_t wf[NR][4];
  if (!IS_V) {
    const uint32_t wb = sb + (WG ? OFF_WO : OFF_WV);
    stage_qkv(wqkv, wb, WG, bc, tid0 & 127);
    WBAR_SYNC(NB_G0 + WG, 128);
    load_frags<NR>(wf, wb, tid0);
#pragma unroll
    for (int k = NR; k < 40; k++) sts128(sb + OFF_Y + yo + (k - NR) * 2048 + (tid0 & 127) * 16, lds128(wb + k * 2048 + (tid0 & 127) * 16));
    fence_async();
  }
  WBAR_SYNC(NB_B, 384);
  if (WG == 1 && bc < 10) {
    if ((tid0 & 127) == 0) {
      mbar_expect_tx(sb + BAR_W, 81920);
      for (int i = 0; i < 10; i++) tma2d(sb + OFF_WO + i * 8192, &tmBo, bc * 64, i * 64, sb + BAR_W);
    }
    __syncwarp();
    mwait(sb + BAR_W, 0, spin);
  }
  if (IS_V) {
    stage_qkv(wqkv, sb + OFF_WV, 2, bc, tid0 & 127);
    WBAR_SYNC(NB_G0 + 2, 128);
    load_frags<NR>(wf, sb + OFF_WV + VSS * 2048, tid0);
  }
  fence_async();
  WBAR_SYNC(NB_B, 384);
  const int wu = uni((tid0 >> 5) & 3);
  uint32_t nredo = 0;
  const AttAddr aa = att_addr(sb, bc, WG, tid0);
#pragma unroll 1
  for (int k = 0; k < NSTEP + (WG == 0); k++) {
    if (WG || k < NSTEP) {
    {
      float d[32];
#pragma unroll
      for (int c = 0; c < 10; c++) {
        mwait(sb + BAR_F + 8 * (c % 5), c / 5, spin);
        if (c == 0 && bc == 0 && WG != 1) WTS(k, WG ? 15 : 6);
        wg_fence();
#pragma unroll
        for (int kk = 0; kk < 4; kk++) {
          const int q = 4 * c + kk;
          const uint64_t db = rdesc(OFF_X + (c % 5) * 8192, kk);
          if (IS_V ? q >= VSS : q < NR) wgmma_rs64(d, wf[IS_V ? (q >= VSS ? q - VSS : 0) : (q < NR ? q : 0)], db, q);
          else if (IS_V) wgmma_ts64(d, mkdesc(SB0 + OFF_WV + q * 2048, 8192, 1024), db, q);
          else wgmma_ts64(d, desc_at(mkdesc(SB0 + OFF_Y + (q - NR) * 2048, 8192, 1024), yo), db, 1);
        }
        wg_commit();
        if (c > 0 && c <= 7) {
          wg_wait<1>();
          if ((tid0 & 31) == 0) mbar_arrive(sb + BAR_E + 8 * ((c - 1) % 5));
        }
      }
      wg_wait<0>();
      if (bc == 0 && WG != 1) WTS(k, 16 + WG / 2);
      WBAR_SYNC(NB_B, 384);
      const int tid = fresh(tid0), m = (tid >> 3) & 3;
      const uint32_t a = sb + OFF_T + min(wu * 16 + (m & 1) * 8 + (tid & 7), 60) * 16 + (8 * WG + (m >> 1)) * COL;
#pragma unroll
      for (int p = 0; p < 4; p++) {
        stsm4(a + 2 * p * COL, pack_bf16(d[8 * p], d[8 * p + 1]), pack_bf16(d[8 * p + 2], d[8 * p + 3]), pack_bf16(d[8 * p + 4], d[8 * p + 5]), pack_bf16(d[8 * p + 6], d[8 * p + 7]));
      }
    }
    WBAR_SYNC(NB_TD, 448);
    if (bc == 0 && WG == 0) WTS(k, 7);
    if (bc * 3 + WG < NH && (wu < 2 ? k < NSEG : k >= LAG)) attend(sb, aa, k, wu, fresh(tid0));
    else release_tiles(sb, tid0);
    if (bc == 0 && WG == 0) WTS(k, 8);
    WBAR_SYNC(NB_AS, 416);
    }
    const int s = k - (1 - WG) * (LAG + 1);
    if (!IS_V && bc < 10 && s >= 0 && s < NSEG) {
      float d[16];
#pragma unroll
      for (int f = 0; f < 5; f++) {
        mwait(sb + BAR_G + 40 * WG + 8 * f, s & 1, spin);
        if (f == 0 && bc == 0) WTS(k - 1 + WG, WG || k > NSEG ? 20 : 23);
        wg_fence();
#pragma unroll
        for (int kk = 0; kk < 8; kk++) {
          wgmma_tt32(d, mkdesc(SB0 + OFF_WO + (8 * f + kk) * 2048, 8192, 1024), gdesc(OFF_X + f * 8192, kk), f | kk);
          if (kk == 1 && f > 0) {
            wg_commit();
            wg_wait<1>();
            if ((tid0 & 31) < 3) mbar_arrive(sb + BAR_E + 8 * (f - 1));
          }
        }
        wg_commit();
      }
      wg_wait<0>();
      if (WG == 1 && FSA) {
        const float chk = ((d[0] + d[1]) + (d[4] + d[5])) + ((d[8] + d[9]) + (d[12] + d[13]));
        if (__builtin_expect(bar_red_or(NB_RED, 128, chk != chk), 0)) {
          if (wu == 0) { cwait(CN_A + k, NBC, spin); fence_async_all(); }
#pragma unroll
          for (int q = 0; q < 16; q++) d[q] = 0.f;
#pragma unroll 1
          for (int f = 0; f < 5; f++) {
            if (wu == 0 && elect_one()) { mbar_expect_tx(sb + BAR_W + 8, 8192); bulk_g2s(sb + OFF_X + 32768, g_ob[k] + f * 8192, 8192, sb + BAR_W + 8); }
            __syncwarp();
            mwait(sb + BAR_W + 8, nredo & 1, spin);
            nredo++;
            wg_fence();
#pragma unroll
            for (int kk = 0; kk < 8; kk++)
              wgmma_tt32(d, desc_at(mkdesc(SB0 + OFF_WO + kk * 2048, 8192, 1024), f * 16384), gdesc(OFF_X + 32768, kk), 1);
            wg_commit();
            wg_wait<0>();
            bar_sync(NB_RED, 128);
          }
        }
      }
      else if (WG) bar_sync(NB_RED, 128);
      else {
        if ((tid0 & 31) < 3) mbar_arrive(sb + BAR_E + 32);
        WBAR_SYNC(NB_SF, 160);
      }
      if (bc == 0) WTS(k - 1 + WG, WG || k > NSEG ? 10 : 24);
      const int tid = fresh(tid0), m = (tid >> 3) & 3, row = (m >> 1) * 16 + 2 * (tid & 7);
      const uint32_t a = sb + (WG ? OFF_X + 32768 : OFF_S) + row * 128 + (((2 * wu + (m & 1)) ^ row) & 7) * 16;
#pragma unroll
      for (int p = 0; p < 2; p++)
        stsm4t(a ^ (p * 144), pack_bf16(d[8 * p], d[8 * p + 1]), pack_bf16(d[8 * p + 2], d[8 * p + 3]), pack_bf16(d[8 * p + 4], d[8 * p + 5]), pack_bf16(d[8 * p + 6], d[8 * p + 7]));
      fence_async();
      WBAR_SYNC(WG ? NB_SG : NB_SG1, 160);
    }
  }
  if (spin >= SPIN_TOT) g_err = 14;
}
__device__ __forceinline__ bool b_job(int k, int u, int bc) { return u < 2 ? k < NSTEP : bc < 10 && (u == 2 ? k > LAG : k < NSEG); }
__device__ __forceinline__ void work_b_watch(uint32_t sb, int bc) {
  using namespace W;
  int spin = 0;
#pragma unroll 1
  for (int j = 0; j < 4 * NSTEP + 3; j++) {
    const int k = j >> 2, u = j & 3;
    if (u == 1 || !b_job(k, u, bc)) continue;
    cwait(u == 0 ? CN_L + k : u == 2 ? CN_A + k - 1 : (FSA ? CN_F : CN_A) + k, u ? NBC : k < LAG || k >= NSEG ? 32 : 64, spin);
    fence_async_all();
    if (bc == 0 && (u != 2 || k > NSEG)) WTS1(k + (u ? u - 3 : 0), u ? 9 : 5);
    if (elect_one()) mbar_arrive(sb + BAR_R + 8 * u);
    __syncwarp();
    if (u == 0) WBAR_SYNC(NB_R, 64);
  }
  if (spin >= SPIN_TOT) g_err = 16;
}
__device__ __forceinline__ void work_b_producer(uint32_t sb, int bc) {
  using namespace W;
  int spin = 0;
  uint32_t pe = 1;
#pragma unroll 1
  for (int j = 0; j < 4 * NSTEP + 3; j++) {
    const int k = j >> 2, u = j & 3;
    if (!b_job(k, u, bc)) continue;
    const uint32_t half = u < 2 && (k < LAG || k >= NSEG), lo = half && k >= NSEG ? 4096 : 0, len = half ? 4096 : 8192, fb = sb + (u < 2 ? BAR_F : BAR_G + 40 * (u - 2));
    const uint8_t* src = (u < 2 ? g_xnb[k] + u * 40960 : u == 2 ? g_ob[k - 1] + 40960 : g_ob[k]) + lo;
    if (u != 1) mwait(sb + BAR_R + 8 * u, (u == 2 ? k - LAG - 1 : k) & 1, spin);
#pragma unroll
    for (int f = 0; f < 5; f++) {
      mwait(sb + BAR_E + 8 * f, pe, spin);
      if (elect_one()) {
        mbar_expect_tx(fb + 8 * f, len);
        bulk_g2s(sb + OFF_X + f * 8192 + lo, src + f * 8192, len, fb + 8 * f);
      }
    }
    if (u == 0) WBAR_SYNC(NB_R, 64);
    pe ^= 1;
  }
  if (spin >= SPIN_TOT) g_err = 15;
}

__global__ void __launch_bounds__(512, 1)
k_work(const __grid_constant__ CUtensorMap tmWo, const __grid_constant__ CUtensorMap tmBo, const bf16* __restrict__ wqkv, bf16* __restrict__ out,
       const bf16* __restrict__ x0, const bf16* __restrict__ mem0) {
  using namespace W;
  extern __shared__ __align__(1024) uint8_t smem[];
  const uint32_t sb = smem_u32(smem);
  const int tid = threadIdx.x, w = blockIdx.x;
  const int wg = __shfl_sync(0xffffffffu, tid >> 7, 0);
  if (tid == 0) {
    if (sb != SB0) g_err = 101;
    for (int i = 0; i < 5; i++) { mbar_init(sb + BAR_F + 8 * i, 1); mbar_init(sb + BAR_E + 8 * i, w < NP ? 8 : 12); }
    for (int i = 0; i < 16; i++) mbar_init(sb + BAR_G + 8 * i, 1);
    for (int p = 0; p < 16; p++) sts32(sb + OFF_SAFE + 4 * p, 0);
    asm volatile("fence.mbarrier_init.release.cluster;" ::: "memory");
    int spin = 0;
    pre_wait(1, NW, spin);
    if (spin >= SPIN_TOT) g_err = 18;
  }
  if (tid < 8 * COL / 16) sts128(sb + OFF_H + tid * 16, make_uint4(0, 0, 0, 0));
  fence_async();
  __syncthreads();

  if (w < NP) {
    if (wg < 2) work_p(tmWo, sb, w, wg, keep(tid));
    else {
      asm volatile("setmaxnreg.dec.sync.aligned.u32 48;");
      const int aw = uni(tid >> 5) - 8;
      if (aw < 2) {
        work_p_producer(sb, w, aw);
      } else {
        const int id = (aw - 2) * NP + w;
        if (id < 96) work_ln<16384>(id % 3, id / 3, tid & 31, out);
        else if (id < 128) work_ln<256>(3, id - 96, tid & 31, out);
        else if (id < 144 && NOWORK != 2) work_prep(x0, mem0, id - 128, tid & 31);
      }
    }
  } else {
    const int bc = w - NP;
    if (wg < 2) work_b<false>(tmBo, wqkv, sb, bc, wg, keep(tid));
    else if (wg == 2) work_b<true>(tmBo, wqkv, sb, bc, wg, keep(tid));
    else {
      asm volatile("setmaxnreg.dec.sync.aligned.u32 24;");
      const int aw = uni(tid >> 5) - 12;
      if (aw == 0) work_b_producer(sb, bc);
      else if (aw == 1) work_b_watch(sb, bc);
      else if (aw == 2) {
#pragma unroll 1
        for (int k = 0; k < NSTEP; k++) {
          WBAR_ARRIVE(NB_TD, 448);
          if (FSA == 3 && (tid & 31) == 0) csignal_fast(CN_F + k);
          WBAR_SYNC(NB_AS, 416);
          if (elect_one()) {
            const uint32_t len = bc < 10 ? 3840 : 2560;
            if (k < NSEG) {
              bulk_s2g(g_ob[k] + bc * 3840, sb + OFF_S, len);
              asm volatile("cp.async.bulk.commit_group;" ::: "memory");
              if (FSA == 1) asm volatile("cp.async.bulk.wait_group.read 0;" ::: "memory");
              if (FSA) csignal_fast(CN_F + k);
            }
            if (k >= LAG) bulk_s2g(g_ob[k] + 40960 + bc * 3840, sb + OFF_S + 3840, len);
            asm volatile("cp.async.bulk.commit_group;" ::: "memory");
            asm volatile("cp.async.bulk.wait_group 0;" ::: "memory");
          }
          __syncwarp();
          if (b_job(k, 2, bc)) WBAR_ARRIVE(NB_SF, 160);
          if (elect_one()) { fence_async_all(); csignal_t(CN_A + k, 5); }
          __syncwarp();
        }
        if (bc < 10) WBAR_SYNC(NB_SF + 1, 64), WBAR_ARRIVE(NB_SF, 160);
      } else {
#pragma unroll 1
        for (int j = 0; j < 2 * NSTEP + 1; j++) {
          const int l = (j & 1) ^ 1, s = (j >> 1) - l * (LAG + 1);
          if (l) { if (j < 2 * NSTEP) WBAR_SYNC(NB_TD, 448); else if (bc < 10) WBAR_ARRIVE(NB_SF + 1, 64); }
          if (s < 0 || s >= NSEG || bc == 10) continue;
          WBAR_SYNC(l ? NB_SG1 : NB_SG, 160);
          if (elect_one()) {
            bulk_s2g(g_y[l] + (size_t)s * 40960 + bc * 4096, sb + (l ? OFF_S : OFF_X + 32768), 4096);
            asm volatile("cp.async.bulk.commit_group;" ::: "memory");
            if (FSW) csignal_fast(CN_W + l * 64 + s);
            asm volatile("cp.async.bulk.wait_group.read 0;" ::: "memory");
            if (!FSW) csignal_fast(CN_W + l * 64 + s);
            if (!l) asm volatile("mbarrier.arrive.shared::cta.b64 _,[%0],12;" ::"r"(sb + BAR_E + 32) : "memory");
          }
          __syncwarp();
        }
      }
    }
  }
  __syncthreads();
  asm volatile("griddepcontrol.wait;" ::: "memory");
}

typedef CUresult (*EncodeFn)(CUtensorMap*, CUtensorMapDataType, cuuint32_t, void*, const cuuint64_t*, const cuuint64_t*,
                             const cuuint32_t*, const cuuint32_t*, CUtensorMapInterleave, CUtensorMapSwizzle,
                             CUtensorMapL2promotion, CUtensorMapFloatOOBfill);

static void make_map(EncodeFn enc, CUtensorMap* tm, const void* ptr, uint64_t cols, uint64_t rows, uint32_t boxc, uint32_t boxr) {
  cuuint64_t dims[2] = {cols, rows};
  cuuint64_t strides[1] = {cols * 2};
  cuuint32_t box[2] = {boxc, boxr};
  cuuint32_t es[2] = {1, 1};
  enc(tm, CU_TENSOR_MAP_DATA_TYPE_BFLOAT16, 2, const_cast<void*>(ptr), dims, strides, box, es, CU_TENSOR_MAP_INTERLEAVE_NONE,
      CU_TENSOR_MAP_SWIZZLE_128B, CU_TENSOR_MAP_L2_PROMOTION_L2_256B, CU_TENSOR_MAP_FLOAT_OOB_FILL_NONE);
}

extern "C" void kernel_launch(void* const* d_in, const int* in_sizes, int n_in, void* d_out, int out_size) {
  const bf16* x0 = (const bf16*)d_in[0];
  const bf16* mem0 = (const bf16*)d_in[1];
  const bf16* Wq = (const bf16*)d_in[2];
  const bf16* Wk = (const bf16*)d_in[3];
  const bf16* Wv = (const bf16*)d_in[4];
  const bf16* Wo = (const bf16*)d_in[5];
  const bf16* Bqkv = (const bf16*)d_in[8];
  const bf16* Bwo = (const bf16*)d_in[9];
  bf16* out = (bf16*)d_out;

  static EncodeFn enc = nullptr;
  if (!enc) {
    void* fn = nullptr;
    cudaDriverEntryPointQueryResult qr;
    cudaGetDriverEntryPoint("cuTensorMapEncodeTiled", &fn, cudaEnableDefault, &qr);
    enc = (EncodeFn)fn;
    cudaFuncSetAttribute(k_chain, cudaFuncAttributeMaxDynamicSharedMemorySize, C::SMEM);
    cudaFuncSetAttribute(k_work, cudaFuncAttributeMaxDynamicSharedMemorySize, W::SMEM);
  }
  CUtensorMap tmWq, tmWk, tmWv, tmWo, tmWp, tmBo;
  make_map(enc, &tmWq, Wq, NH * DH, DM, 64, 128);
  make_map(enc, &tmWk, Wk, NH * DH, DM, 64, 128);
  make_map(enc, &tmWv, Wv, NH * DH, DM, 64, 128);
  make_map(enc, &tmWo, Wo, DM, NH * DH, 64, 64);
  make_map(enc, &tmWp, Wo, DM, NH * DH, 64, 16);
  make_map(enc, &tmBo, Bwo, DM, DM, 64, 64);

  cudaStream_t st = cudaStreamPerThread;
  cudaLaunchAttribute at[1];
  at[0].id = cudaLaunchAttributeProgrammaticStreamSerialization; at[0].val.programmaticStreamSerializationAllowed = 1;
  {
    cudaLaunchConfig_t cfg = {};
    cfg.gridDim = dim3(96); cfg.blockDim = dim3(384); cfg.dynamicSmemBytes = C::SMEM; cfg.stream = st;
    cfg.attrs = at; cfg.numAttrs = 0;
    cudaLaunchKernelEx(&cfg, k_chain, tmWq, tmWk, tmWv, tmWo, x0, mem0);
  }
  cudaLaunchConfig_t cfg = {};
  cfg.gridDim = dim3(W::NW); cfg.blockDim = dim3(512); cfg.dynamicSmemBytes = W::SMEM; cfg.stream = st;
  cfg.attrs = at; cfg.numAttrs = NOWORK == 2 ? 0 : 1;
  cudaLaunchKernelEx(&cfg, k_work, tmWp, tmBo, Bqkv, out, x0, mem0);
}
```

```cpp
#include <cuda_runtime.h>
#include <cuda_bf16.h>
#include <cuda.h>
#include <stdint.h>

typedef __nv_bfloat16 bf16;

constexpr int SEQ = 2048, DM = 640, NH = 32, DH = 192, NSEG = 64;
#define LAG 5
constexpr int NSTEP = NSEG + LAG;
constexpr int NPRE = 4;
constexpr uint32_t SENT = 0xFFFFFFFFu;

constexpr int MAIL9 = 288 * 2048, MAIL_BYTES = MAIL9 + 64 * 3072;
__device__ __align__(1024) uint8_t g_xn[NSTEP][81920];
__device__ __align__(1024) uint8_t g_xnb[NSTEP][81920];
__device__ __align__(1024) uint8_t g_ob[NSTEP][81920];
__device__ __align__(1024) uint8_t g_y[2][NSEG * 40960];
#define ORING 8
static_assert(ORING > LAG, "a slot is free again LAG + 1 steps later");
__device__ __align__(1024) uint8_t g_o[ORING][96][8192];
__device__ __align__(1024) float g_x[SEQ * DM];
constexpr int EX_MAIL = 0;
constexpr int EX_M = 2 << 20;
constexpr int EX_FLAG = EX_M + NSTEP * 20480;
static_assert(EX_FLAG + NSTEP * 3072 <= (4 << 20), "");
__device__ __align__(1024) uint8_t g_ex[8 << 20];
__host__ __device__ __forceinline__ uint8_t* ex_window(uint8_t* p) { return reinterpret_cast<uint8_t*>((reinterpret_cast<uint64_t>(p) + (4 << 20) - 1) & ~(uint64_t)((4 << 20) - 1)); }
enum { CN_P = 0, CN_L = 128, CN_A = 256, CN_W = 384, CN_X = 512, CN_F = 640, CN_G = 768, CN_O = 896, CN_NUM = CN_O + 5 * NSTEP };
__device__ __align__(128) uint32_t g_cnt[CN_NUM][32];
__device__ __align__(128) uint32_t g_ticket[2][32];
__device__ int g_err;
#define TS(jj, i)
#define TS1(jj, i)
#define PTS(i)
#define TSB(jj, i)
#define TSV(jj, i, v)
#define TS_FLUSH(jj)
#define WTS(b, k)
#define WTS1(b, k)
#define WW -1

__device__ __forceinline__ uint32_t smem_u32(const void* p) { return (uint32_t)__cvta_generic_to_shared(p); }
__device__ __forceinline__ uint32_t clk32() { uint32_t t; asm volatile("mov.u32 %0, %%clock;" : "=r"(t)::"memory"); return t; }
__device__ __forceinline__ uint32_t mapa(uint32_t a, uint32_t r) { uint32_t o; asm("mapa.shared::cluster.u32 %0,%1,%2;" : "=r"(o) : "r"(a), "r"(r)); return o; }
__device__ __forceinline__ void mbar_init(uint32_t bar, uint32_t cnt) { asm volatile("mbarrier.init.shared::cta.b64 [%0],%1;" ::"r"(bar), "r"(cnt) : "memory"); }
__device__ __forceinline__ void mbar_expect_tx(uint32_t bar, uint32_t bytes) { asm volatile("mbarrier.arrive.expect_tx.shared::cta.b64 _,[%0],%1;" ::"r"(bar), "r"(bytes) : "memory"); }
__device__ __forceinline__ void mbar_arrive(uint32_t bar) { asm volatile("mbarrier.arrive.shared::cta.b64 _,[%0];" ::"r"(bar) : "memory"); }
__device__ __forceinline__ void mbar_arrive_cluster(uint32_t bar) { asm volatile("mbarrier.arrive.shared::cluster.b64 _,[%0];" ::"r"(bar) : "memory"); }
__device__ __forceinline__ bool mbar_try(uint32_t bar, uint32_t ph) {
  uint32_t ok;
  asm volatile("{.reg .pred p; mbarrier.try_wait.parity.shared::cta.b64 p,[%1],%2; selp.u32 %0,1,0,p;}" : "=r"(ok) : "r"(bar), "r"(ph) : "memory");
  return ok;
}
__device__ __forceinline__ bool mbar_test(uint32_t bar, uint32_t ph) {
  uint32_t ok;
  asm volatile("{.reg .pred p; mbarrier.test_wait.parity.shared::cta.b64 p,[%1],%2; selp.u32 %0,1,0,p;}" : "=r"(ok) : "r"(bar), "r"(ph) : "memory");
  return ok;
}
__device__ __forceinline__ int fresh(int x) { asm volatile("" : "+r"(x)); return x; }
#define PHASE_IDS const int tid = fresh(tid0), lane = tid & 31, w = tid >> 5, g = lane >> 2, t = lane & 3; (void)w; (void)g; (void)t
__device__ __forceinline__ void bar_sync(int id, int n) { asm volatile("bar.sync %0,%1;" ::"r"(id), "r"(n) : "memory"); }
__device__ __forceinline__ void bar_arrive(int id, int n) { asm volatile("bar.arrive %0,%1;" ::"r"(id), "r"(n) : "memory"); }
__device__ __forceinline__ bool bar_red_or(int id, int n, bool v) {
  uint32_t r;
  asm volatile("{\n .reg .pred p, q;\n setp.ne.u32 q, %3, 0;\n barrier.cta.red.or.pred p, %1, %2, q;\n selp.u32 %0, 1, 0, p;\n}" : "=r"(r) : "r"(id), "r"(n), "r"((uint32_t)v) : "memory");
  return r != 0;
}
__device__ __forceinline__ void fence_async() { asm volatile("fence.proxy.async.shared::cta;" ::: "memory"); }
__device__ __forceinline__ void bulk_g2s(uint32_t dst, const void* src, uint32_t bytes, uint32_t bar) {
  asm volatile("cp.async.bulk.shared::cluster.global.mbarrier::complete_tx::bytes [%0],[%1],%2,[%3];" ::"r"(dst), "l"(src), "r"(bytes), "r"(bar) : "memory");
}
__device__ __forceinline__ void bulk_g2s_mc(uint32_t dst, const void* src, uint32_t bytes, uint32_t bar) {
  asm volatile("cp.async.bulk.shared::cluster.global.mbarrier::complete_tx::bytes.multicast::cluster [%0],[%1],%2,[%3],%4;"
               ::"r"(dst), "l"(src), "r"(bytes), "r"(bar), "h"((uint16_t)7) : "memory");
}
__device__ __forceinline__ void bulk_s2g(void* dst, uint32_t src, uint32_t bytes) {
  asm volatile("cp.async.bulk.global.shared::cta.bulk_group [%0],[%1],%2;" ::"l"(dst), "r"(src), "r"(bytes) : "memory");
}
__device__ __forceinline__ void bulk_s2c(uint32_t dst, uint32_t src, uint32_t bytes, uint32_t bar) {
  asm volatile("cp.async.bulk.shared::cluster.shared::cta.mbarrier::complete_tx::bytes [%0],[%1],%2,[%3];" ::"r"(dst), "r"(src), "r"(bytes), "r"(bar) : "memory");
}
__device__ __forceinline__ void tma2d(uint32_t dst, const CUtensorMap* tm, int c0, int c1, uint32_t bar) {
  asm volatile("cp.async.bulk.tensor.2d.shared::cluster.global.mbarrier::complete_tx::bytes [%0],[%1,{%3,%4}],[%2];"
               ::"r"(dst), "l"(tm), "r"(bar), "r"(c0), "r"(c1) : "memory");
}
__device__ __forceinline__ void tma2d_prefetch(const CUtensorMap* tm, int c0, int c1) {
  asm volatile("cp.async.bulk.prefetch.tensor.2d.L2.global.tile [%0,{%1,%2}];" ::"l"(tm), "r"(c0), "r"(c1) : "memory");
}
__device__ __forceinline__ uint32_t pack_bf16(float lo, float hi) {
  uint32_t r; asm("cvt.rn.bf16x2.f32 %0,%1,%2;" : "=r"(r) : "f"(hi), "f"(lo)); return r;
}
__device__ __forceinline__ float bf_lo(uint32_t x) { return __uint_as_float(x << 16); }
__device__ __forceinline__ float bf_hi(uint32_t x) { return __uint_as_float(x & 0xFFFF0000u); }
__device__ __forceinline__ float ex2(float x) { float y; asm("ex2.approx.ftz.f32 %0,%1;" : "=f"(y) : "f"(x)); return y; }
__device__ __forceinline__ void ldsm4(uint32_t (&r)[4], uint32_t a) {
  asm volatile("ldmatrix.sync.aligned.m8n8.x4.shared.b16 {%0,%1,%2,%3},[%4];" : "=r"(r[0]), "=r"(r[1]), "=r"(r[2]), "=r"(r[3]) : "r"(a) : "memory");
}
__device__ __forceinline__ void ldsm4t(uint32_t (&r)[4], uint32_t a) {
  asm volatile("ldmatrix.sync.aligned.m8n8.x4.trans.shared.b16 {%0,%1,%2,%3},[%4];" : "=r"(r[0]), "=r"(r[1]), "=r"(r[2]), "=r"(r[3]) : "r"(a) : "memory");
}
__device__ __forceinline__ void ldsm2(uint32_t& r0, uint32_t& r1, uint32_t a) {
  asm volatile("ldmatrix.sync.aligned.m8n8.x2.shared.b16 {%0,%1},[%2];" : "=r"(r0), "=r"(r1) : "r"(a) : "memory");
}
__device__ __forceinline__ void ldsm2t(uint32_t& r0, uint32_t& r1, uint32_t a) {
  asm volatile("ldmatrix.sync.aligned.m8n8.x2.trans.shared.b16 {%0,%1},[%2];" : "=r"(r0), "=r"(r1) : "r"(a) : "memory");
}
__device__ __forceinline__ void ldsm1(uint32_t& r0, uint32_t a) {
  asm volatile("ldmatrix.sync.aligned.m8n8.x1.shared.b16 {%0},[%1];" : "=r"(r0) : "r"(a) : "memory");
}
__device__ __forceinline__ void mma16816(float (&d)[4], uint32_t a0, uint32_t a1, uint32_t a2, uint32_t a3, uint32_t b0, uint32_t b1) {
  asm volatile("mma.sync.aligned.m16n8k16.row.col.f32.bf16.bf16.f32 {%0,%1,%2,%3},{%4,%5,%6,%7},{%8,%9},{%0,%1,%2,%3};"
               : "+f"(d[0]), "+f"(d[1]), "+f"(d[2]), "+f"(d[3]) : "r"(a0), "r"(a1), "r"(a2), "r"(a3), "r"(b0), "r"(b1));
}
__device__ __forceinline__ void mma1688(float (&d)[4], uint32_t a0, uint32_t a1, uint32_t b0) {
  asm volatile("mma.sync.aligned.m16n8k8.row.col.f32.bf16.bf16.f32 {%0,%1,%2,%3},{%4,%5},{%6},{%0,%1,%2,%3};"
               : "+f"(d[0]), "+f"(d[1]), "+f"(d[2]), "+f"(d[3]) : "r"(a0), "r"(a1), "r"(b0));
}
__device__ __forceinline__ void sts32(uint32_t a, uint32_t v) { asm volatile("st.shared.b32 [%0],%1;" ::"r"(a), "r"(v) : "memory"); }
__device__ __forceinline__ void sts64f(uint32_t a, float x, float y) { asm volatile("st.shared.v2.f32 [%0],{%1,%2};" ::"r"(a), "f"(x), "f"(y) : "memory"); }
__device__ __forceinline__ void sts128(uint32_t a, uint4 v) { asm volatile("st.shared.v4.b32 [%0],{%1,%2,%3,%4};" ::"r"(a), "r"(v.x), "r"(v.y), "r"(v.z), "r"(v.w) : "memory"); }
__device__ __forceinline__ float lds32f(uint32_t a) { float v; asm volatile("ld.shared.f32 %0,[%1];" : "=f"(v) : "r"(a) : "memory"); return v; }
__device__ __forceinline__ float2 lds64f(uint32_t a) { float2 v; asm volatile("ld.shared.v2.f32 {%0,%1},[%2];" : "=f"(v.x), "=f"(v.y) : "r"(a) : "memory"); return v; }
__device__ __forceinline__ uint4 lds128(uint32_t a) { uint4 v; asm volatile("ld.shared.v4.b32 {%0,%1,%2,%3},[%4];" : "=r"(v.x), "=r"(v.y), "=r"(v.z), "=r"(v.w) : "r"(a) : "memory"); return v; }
__device__ __forceinline__ float4 lds128f(uint32_t a) { float4 v; asm volatile("ld.shared.v4.f32 {%0,%1,%2,%3},[%4];" : "=f"(v.x), "=f"(v.y), "=f"(v.z), "=f"(v.w) : "r"(a) : "memory"); return v; }
__device__ __forceinline__ void st_async2(uint32_t a, float x, float y, uint32_t bar) {
  asm volatile("st.async.weak.shared::cluster.mbarrier::complete_tx::bytes.v2.f32 [%0],{%1,%2},[%3];" ::"r"(a), "f"(x), "f"(y), "r"(bar) : "memory");
}
__device__ __forceinline__ void st_async4(uint32_t a, const float (&v)[4], uint32_t bar) {
  asm volatile("st.async.weak.shared::cluster.mbarrier::complete_tx::bytes.v4.f32 [%0],{%1,%2,%3,%4},[%5];" ::"r"(a), "f"(v[0]), "f"(v[1]), "f"(v[2]), "f"(v[3]), "r"(bar) : "memory");
}
__device__ __forceinline__ void st_async4v(uint32_t a, float x, float y, float z, float w, uint32_t bar) {
  asm volatile("st.async.weak.shared::cluster.mbarrier::complete_tx::bytes.v4.f32 [%0],{%1,%2,%3,%4},[%5];" ::"r"(a), "f"(x), "f"(y), "f"(z), "f"(w), "r"(bar) : "memory");
}
__device__ __forceinline__ void st_async4u(uint32_t a, const uint4& v, uint32_t bar) {
  asm volatile("st.async.weak.shared::cluster.mbarrier::complete_tx::bytes.v4.b32 [%0],{%1,%2,%3,%4},[%5];" ::"r"(a), "r"(v.x), "r"(v.y), "r"(v.z), "r"(v.w), "r"(bar) : "memory");
}
__device__ __forceinline__ uint4 ld_relaxed4(const void* p) {
  uint4 v; asm volatile("ld.relaxed.gpu.global.v4.u32 {%0,%1,%2,%3},[%4];" : "=r"(v.x), "=r"(v.y), "=r"(v.z), "=r"(v.w) : "l"(p) : "memory"); return v;
}
__device__ __forceinline__ uint32_t ld_relaxed(const void* p) {
  uint32_t v; asm volatile("ld.relaxed.gpu.global.u32 %0,[%1];" : "=r"(v) : "l"(p) : "memory"); return v;
}
__device__ __forceinline__ void st_relaxed(void* p, uint32_t v) { asm volatile("st.relaxed.gpu.global.b32 [%0],%1;" ::"l"(p), "r"(v) : "memory"); }
__device__ __forceinline__ void st_relaxed4(void* p, uint32_t v) { asm volatile("st.relaxed.gpu.global.v4.b32 [%0],{%1,%1,%1,%1};" ::"l"(p), "r"(v) : "memory"); }

__device__ __forceinline__ uint32_t ld_acquire(const void* p) {
  uint32_t v; asm volatile("ld.acquire.gpu.global.u32 %0,[%1];" : "=r"(v) : "l"(p) : "memory"); return v;
}
__device__ __forceinline__ float4 ld_relaxed4f(const void* p) {
  float4 v; asm volatile("ld.relaxed.gpu.global.v4.f32 {%0,%1,%2,%3},[%4];" : "=f"(v.x), "=f"(v.y), "=f"(v.z), "=f"(v.w) : "l"(p) : "memory"); return v;
}
__device__ __forceinline__ float2 ld_relaxed2f(const void* p) {
  float2 v; asm volatile("ld.relaxed.gpu.global.v2.f32 {%0,%1},[%2];" : "=f"(v.x), "=f"(v.y) : "l"(p) : "memory"); return v;
}
__device__ __forceinline__ void prefetch_l2(const void* p) { asm volatile("prefetch.global.L2 [%0];" ::"l"(p)); }
__device__ __forceinline__ void fence_gpu() { asm volatile("fence.acq_rel.gpu;" ::: "memory"); }
__device__ __forceinline__ void fence_async_all() { asm volatile("fence.proxy.async.global;" ::: "memory"); }
constexpr int SPIN_TOT = 1 << 22;
__device__ __forceinline__ void csignal(int idx) { asm volatile("red.release.gpu.global.add.u32 [%0],1;" ::"l"(&g_cnt[idx][0]) : "memory"); }
__device__ __forceinline__ void csignal_fast(int idx) { asm volatile("red.relaxed.gpu.global.add.u32 [%0],1;" ::"l"(&g_cnt[idx][0]) : "memory"); }
#define RLX 1
#define csignal_t(idx, role) csignal(idx)
__device__ __forceinline__ void cwait(int idx, uint32_t target, int& spin) {
  while (ld_relaxed(&g_cnt[idx][0]) < target && spin < SPIN_TOT) spin += 16;
}

__device__ __forceinline__ uint64_t mkdesc(uint32_t addr, uint32_t lbo, uint32_t sbo) {
  return (uint64_t)((addr & 0x3FFFF) >> 4) | ((uint64_t)(lbo >> 4) << 16) | ((uint64_t)(sbo >> 4) << 32) | ((uint64_t)1 << 62);
}
__device__ __forceinline__ uint64_t mkdesc_ns(uint32_t addr, uint32_t lbo, uint32_t sbo) {
  return (uint64_t)((addr & 0x3FFFF) >> 4) | ((uint64_t)(lbo >> 4) << 16) | ((uint64_t)(sbo >> 4) << 32);
}
__device__ __forceinline__ void wg_fence() { asm volatile("wgmma.fence.sync.aligned;" ::: "memory"); }
__device__ __forceinline__ void wg_commit() { asm volatile("wgmma.commit_group.sync.aligned;" ::: "memory"); }
template <int N> __device__ __forceinline__ void wg_wait() { asm volatile("wgmma.wait_group.sync.aligned %0;" ::"n"(N) : "memory"); }

__device__ __forceinline__ void wgmma_rs16(float (&d)[8], const uint32_t (&a)[4], uint64_t db, int sc) {
  asm volatile("{.reg .pred p; setp.ne.b32 p,%13,0; wgmma.mma_async.sync.aligned.m64n16k16.f32.bf16.bf16 "
               "{%0,%1,%2,%3,%4,%5,%6,%7},{%8,%9,%10,%11},%12,p,1,1,0;}"
               : "+f"(d[0]), "+f"(d[1]), "+f"(d[2]), "+f"(d[3]), "+f"(d[4]), "+f"(d[5]), "+f"(d[6]), "+f"(d[7])
               : "r"(a[0]), "r"(a[1]), "r"(a[2]), "r"(a[3]), "l"(db), "r"(sc));
}
__device__ __forceinline__ void wgmma_rs64(float (&d)[32], const uint32_t (&a)[4], uint64_t db, int sc) {
  asm volatile("{.reg .pred p; setp.ne.b32 p,%37,0; wgmma.mma_async.sync.aligned.m64n64k16.f32.bf16.bf16 "
               "{%0,%1,%2,%3,%4,%5,%6,%7,%8,%9,%10,%11,%12,%13,%14,%15,%16,%17,%18,%19,%20,%21,%22,%23,%24,%25,%26,%27,%28,%29,%30,%31},{%32,%33,%34,%35},%36,p,1,1,0;}"
               : "+f"(d[0]), "+f"(d[1]), "+f"(d[2]), "+f"(d[3]), "+f"(d[4]), "+f"(d[5]), "+f"(d[6]), "+f"(d[7]), "+f"(d[8]), "+f"(d[9]), "+f"(d[10]), "+f"(d[11]), "+f"(d[12]), "+f"(d[13]), "+f"(d[14]), "+f"(d[15]), "+f"(d[16]), "+f"(d[17]), "+f"(d[18]), "+f"(d[19]), "+f"(d[20]), "+f"(d[21]), "+f"(d[22]), "+f"(d[23]), "+f"(d[24]), "+f"(d[25]), "+f"(d[26]), "+f"(d[27]), "+f"(d[28]), "+f"(d[29]), "+f"(d[30]), "+f"(d[31])
               : "r"(a[0]), "r"(a[1]), "r"(a[2]), "r"(a[3]), "l"(db), "r"(sc));
}
__device__ __forceinline__ void wgmma_rt16(float (&d)[8], const uint32_t (&a)[4], uint64_t db, int sc) {
  asm volatile("{.reg .pred p; setp.ne.b32 p,%13,0; wgmma.mma_async.sync.aligned.m64n16k16.f32.bf16.bf16 "
               "{%0,%1,%2,%3,%4,%5,%6,%7},{%8,%9,%10,%11},%12,p,1,1,1;}"
               : "+f"(d[0]), "+f"(d[1]), "+f"(d[2]), "+f"(d[3]), "+f"(d[4]), "+f"(d[5]), "+f"(d[6]), "+f"(d[7])
               : "r"(a[0]), "r"(a[1]), "r"(a[2]), "r"(a[3]), "l"(db), "r"(sc));
}
__device__ __forceinline__ void wgmma_rt80(float (&d)[40], const uint32_t (&a)[4], uint64_t db, int sc) {
  asm volatile("{.reg .pred p; setp.ne.b32 p,%45,0; wgmma.mma_async.sync.aligned.m64n80k16.f32.bf16.bf16 "
               "{%0,%1,%2,%3,%4,%5,%6,%7,%8,%9,%10,%11,%12,%13,%14,%15,%16,%17,%18,%19,%20,%21,%22,%23,%24,%25,%26,%27,%28,%29,%30,%31,%32,%33,%34,%35,%36,%37,%38,%39},{%40,%41,%42,%43},%44,p,1,1,1;}"
               : "+f"(d[0]), "+f"(d[1]), "+f"(d[2]), "+f"(d[3]), "+f"(d[4]), "+f"(d[5]), "+f"(d[6]), "+f"(d[7]), "+f"(d[8]), "+f"(d[9]), "+f"(d[10]), "+f"(d[11]), "+f"(d[12]), "+f"(d[13]), "+f"(d[14]), "+f"(d[15]), "+f"(d[16]), "+f"(d[17]), "+f"(d[18]), "+f"(d[19]), "+f"(d[20]), "+f"(d[21]), "+f"(d[22]), "+f"(d[23]), "+f"(d[24]), "+f"(d[25]), "+f"(d[26]), "+f"(d[27]), "+f"(d[28]), "+f"(d[29]), "+f"(d[30]), "+f"(d[31]), "+f"(d[32]), "+f"(d[33]), "+f"(d[34]), "+f"(d[35]), "+f"(d[36]), "+f"(d[37]), "+f"(d[38]), "+f"(d[39])
               : "r"(a[0]), "r"(a[1]), "r"(a[2]), "r"(a[3]), "l"(db), "r"(sc));
}
__device__ __forceinline__ void wgmma_rs32(float (&d)[16], const uint32_t (&a)[4], uint64_t db, int sc) {
  asm volatile("{.reg .pred p; setp.ne.b32 p,%21,0; wgmma.mma_async.sync.aligned.m64n32k16.f32.bf16.bf16 "
               "{%0,%1,%2,%3,%4,%5,%6,%7,%8,%9,%10,%11,%12,%13,%14,%15},{%16,%17,%18,%19},%20,p,1,1,0;}"
               : "+f"(d[0]), "+f"(d[1]), "+f"(d[2]), "+f"(d[3]), "+f"(d[4]), "+f"(d[5]), "+f"(d[6]), "+f"(d[7]), "+f"(d[8]), "+f"(d[9]), "+f"(d[10]), "+f"(d[11]), "+f"(d[12]), "+f"(d[13]), "+f"(d[14]), "+f"(d[15])
               : "r"(a[0]), "r"(a[1]), "r"(a[2]), "r"(a[3]), "l"(db), "r"(sc));
}
__device__ __forceinline__ void wgmma_ts32(float (&d)[16], uint64_t da, uint64_t db, int sc) {
  asm volatile("{.reg .pred p; setp.ne.b32 p,%18,0; wgmma.mma_async.sync.aligned.m64n32k16.f32.bf16.bf16 "
               "{%0,%1,%2,%3,%4,%5,%6,%7,%8,%9,%10,%11,%12,%13,%14,%15},%16,%17,p,1,1,1,0;}"
               : "+f"(d[0]), "+f"(d[1]), "+f"(d[2]), "+f"(d[3]), "+f"(d[4]), "+f"(d[5]), "+f"(d[6]), "+f"(d[7]), "+f"(d[8]), "+f"(d[9]), "+f"(d[10]), "+f"(d[11]), "+f"(d[12]), "+f"(d[13]), "+f"(d[14]), "+f"(d[15])
               : "l"(da), "l"(db), "r"(sc));
}
__device__ __forceinline__ void wgmma_rs8(float (&d)[4], const uint32_t (&a)[4], uint64_t db, int sc) {
  asm volatile("{.reg .pred p; setp.ne.b32 p,%9,0; wgmma.mma_async.sync.aligned.m64n8k16.f32.bf16.bf16 "
               "{%0,%1,%2,%3},{%4,%5,%6,%7},%8,p,1,1,0;}"
               : "+f"(d[0]), "+f"(d[1]), "+f"(d[2]), "+f"(d[3])
               : "r"(a[0]), "r"(a[1]), "r"(a[2]), "r"(a[3]), "l"(db), "r"(sc));
}
__device__ __forceinline__ void wgmma_tt32(float (&d)[16], uint64_t da, uint64_t db, int sc) {
  asm volatile("{.reg .pred p; setp.ne.b32 p,%18,0; wgmma.mma_async.sync.aligned.m64n32k16.f32.bf16.bf16 "
               "{%0,%1,%2,%3,%4,%5,%6,%7,%8,%9,%10,%11,%12,%13,%14,%15},%16,%17,p,1,1,1,1;}"
               : "+f"(d[0]), "+f"(d[1]), "+f"(d[2]), "+f"(d[3]), "+f"(d[4]), "+f"(d[5]), "+f"(d[6]), "+f"(d[7]), "+f"(d[8]), "+f"(d[9]), "+f"(d[10]), "+f"(d[11]), "+f"(d[12]), "+f"(d[13]), "+f"(d[14]), "+f"(d[15])
               : "l"(da), "l"(db), "r"(sc));
}
__device__ __forceinline__ void wgmma_ts16(float (&d)[8], uint64_t da, uint64_t db, int sc) {
  asm volatile("{.reg .pred p; setp.ne.b32 p,%10,0; wgmma.mma_async.sync.aligned.m64n16k16.f32.bf16.bf16 "
               "{%0,%1,%2,%3,%4,%5,%6,%7},%8,%9,p,1,1,1,0;}"
               : "+f"(d[0]), "+f"(d[1]), "+f"(d[2]), "+f"(d[3]), "+f"(d[4]), "+f"(d[5]), "+f"(d[6]), "+f"(d[7])
               : "l"(da), "l"(db), "r"(sc));
}
__device__ __forceinline__ void wgmma_ts64(float (&d)[32], uint64_t da, uint64_t db, int sc) {
  asm volatile("{.reg .pred p; setp.ne.b32 p,%34,0; wgmma.mma_async.sync.aligned.m64n64k16.f32.bf16.bf16 "
               "{%0,%1,%2,%3,%4,%5,%6,%7,%8,%9,%10,%11,%12,%13,%14,%15,%16,%17,%18,%19,%20,%21,%22,%23,%24,%25,%26,%27,%28,%29,%30,%31},%32,%33,p,1,1,1,0;}"
               : "+f"(d[0]), "+f"(d[1]), "+f"(d[2]), "+f"(d[3]), "+f"(d[4]), "+f"(d[5]), "+f"(d[6]), "+f"(d[7]), "+f"(d[8]), "+f"(d[9]), "+f"(d[10]), "+f"(d[11]), "+f"(d[12]), "+f"(d[13]), "+f"(d[14]), "+f"(d[15]), "+f"(d[16]), "+f"(d[17]), "+f"(d[18]), "+f"(d[19]), "+f"(d[20]), "+f"(d[21]), "+f"(d[22]), "+f"(d[23]), "+f"(d[24]), "+f"(d[25]), "+f"(d[26]), "+f"(d[27]), "+f"(d[28]), "+f"(d[29]), "+f"(d[30]), "+f"(d[31])
               : "l"(da), "l"(db), "r"(sc));
}
__device__ __forceinline__ void wgmma_tt16(float (&d)[8], uint64_t da, uint64_t db, int sc) {
  asm volatile("{.reg .pred p; setp.ne.b32 p,%10,0; wgmma.mma_async.sync.aligned.m64n16k16.f32.bf16.bf16 "
               "{%0,%1,%2,%3,%4,%5,%6,%7},%8,%9,p,1,1,1,1;}"
               : "+f"(d[0]), "+f"(d[1]), "+f"(d[2]), "+f"(d[3]), "+f"(d[4]), "+f"(d[5]), "+f"(d[6]), "+f"(d[7])
               : "l"(da), "l"(db), "r"(sc));
}
__device__ __forceinline__ void wgmma_tt40(float (&d)[20], uint64_t da, uint64_t db, int sc) {
  asm volatile("{.reg .pred p; setp.ne.b32 p,%22,0; wgmma.mma_async.sync.aligned.m64n40k16.f32.bf16.bf16 "
               "{%0,%1,%2,%3,%4,%5,%6,%7,%8,%9,%10,%11,%12,%13,%14,%15,%16,%17,%18,%19},%20,%21,p,1,1,1,1;}"
               : "+f"(d[0]), "+f"(d[1]), "+f"(d[2]), "+f"(d[3]), "+f"(d[4]), "+f"(d[5]), "+f"(d[6]), "+f"(d[7]), "+f"(d[8]), "+f"(d[9]), "+f"(d[10]), "+f"(d[11]), "+f"(d[12]), "+f"(d[13]), "+f"(d[14]), "+f"(d[15]), "+f"(d[16]), "+f"(d[17]), "+f"(d[18]), "+f"(d[19])
               : "l"(da), "l"(db), "r"(sc));
}
__device__ __forceinline__ void wgmma_ss8(float (&d)[4], uint64_t da, uint64_t db, int sc) {
  asm volatile("{.reg .pred p; setp.ne.b32 p,%6,0; wgmma.mma_async.sync.aligned.m64n8k16.f32.bf16.bf16 "
               "{%0,%1,%2,%3},%4,%5,p,1,1,0,0;}"
               : "+f"(d[0]), "+f"(d[1]), "+f"(d[2]), "+f"(d[3])
               : "l"(da), "l"(db), "r"(sc));
}
__device__ __forceinline__ void wgmma_ss32(float (&d)[16], uint64_t da, uint64_t db, int sc) {
  asm volatile("{.reg .pred p; setp.ne.b32 p,%18,0; wgmma.mma_async.sync.aligned.m64n32k16.f32.bf16.bf16 "
               "{%0,%1,%2,%3,%4,%5,%6,%7,%8,%9,%10,%11,%12,%13,%14,%15},%16,%17,p,1,1,0,0;}"
               : "+f"(d[0]), "+f"(d[1]), "+f"(d[2]), "+f"(d[3]), "+f"(d[4]), "+f"(d[5]), "+f"(d[6]), "+f"(d[7]), "+f"(d[8]), "+f"(d[9]), "+f"(d[10]), "+f"(d[11]), "+f"(d[12]), "+f"(d[13]), "+f"(d[14]), "+f"(d[15])
               : "l"(da), "l"(db), "r"(sc));
}
__device__ __forceinline__ void wgmma_st64(float (&d)[32], uint64_t da, uint64_t db, int sc) {
  asm volatile("{.reg .pred p; setp.ne.b32 p,%34,0; wgmma.mma_async.sync.aligned.m64n64k16.f32.bf16.bf16 "
               "{%0,%1,%2,%3,%4,%5,%6,%7,%8,%9,%10,%11,%12,%13,%14,%15,%16,%17,%18,%19,%20,%21,%22,%23,%24,%25,%26,%27,%28,%29,%30,%31},%32,%33,p,1,1,0,1;}"
               : "+f"(d[0]), "+f"(d[1]), "+f"(d[2]), "+f"(d[3]), "+f"(d[4]), "+f"(d[5]), "+f"(d[6]), "+f"(d[7]), "+f"(d[8]), "+f"(d[9]), "+f"(d[10]), "+f"(d[11]), "+f"(d[12]), "+f"(d[13]), "+f"(d[14]), "+f"(d[15]), "+f"(d[16]), "+f"(d[17]), "+f"(d[18]), "+f"(d[19]), "+f"(d[20]), "+f"(d[21]), "+f"(d[22]), "+f"(d[23]), "+f"(d[24]), "+f"(d[25]), "+f"(d[26]), "+f"(d[27]), "+f"(d[28]), "+f"(d[29]), "+f"(d[30]), "+f"(d[31])
               : "l"(da), "l"(db), "r"(sc));
}
__device__ __forceinline__ void wgmma_st128(float (&d)[64], uint64_t da, uint64_t db, int sc) {
  asm volatile("{.reg .pred p; setp.ne.b32 p,%66,0; wgmma.mma_async.sync.aligned.m64n128k16.f32.bf16.bf16 "
               "{%0,%1,%2,%3,%4,%5,%6,%7,%8,%9,%10,%11,%12,%13,%14,%15,%16,%17,%18,%19,%20,%21,%22,%23,%24,%25,%26,%27,%28,%29,%30,%31,%32,%33,%34,%35,%36,%37,%38,%39,%40,%41,%42,%43,%44,%45,%46,%47,%48,%49,%50,%51,%52,%53,%54,%55,%56,%57,%58,%59,%60,%61,%62,%63},%64,%65,p,1,1,0,1;}"
               : "+f"(d[0]), "+f"(d[1]), "+f"(d[2]), "+f"(d[3]), "+f"(d[4]), "+f"(d[5]), "+f"(d[6]), "+f"(d[7]), "+f"(d[8]), "+f"(d[9]), "+f"(d[10]), "+f"(d[11]), "+f"(d[12]), "+f"(d[13]), "+f"(d[14]), "+f"(d[15]), "+f"(d[16]), "+f"(d[17]), "+f"(d[18]), "+f"(d[19]), "+f"(d[20]), "+f"(d[21]), "+f"(d[22]), "+f"(d[23]), "+f"(d[24]), "+f"(d[25]), "+f"(d[26]), "+f"(d[27]), "+f"(d[28]), "+f"(d[29]), "+f"(d[30]), "+f"(d[31]), "+f"(d[32]), "+f"(d[33]), "+f"(d[34]), "+f"(d[35]), "+f"(d[36]), "+f"(d[37]), "+f"(d[38]), "+f"(d[39]), "+f"(d[40]), "+f"(d[41]), "+f"(d[42]), "+f"(d[43]), "+f"(d[44]), "+f"(d[45]), "+f"(d[46]), "+f"(d[47]), "+f"(d[48]), "+f"(d[49]), "+f"(d[50]), "+f"(d[51]), "+f"(d[52]), "+f"(d[53]), "+f"(d[54]), "+f"(d[55]), "+f"(d[56]), "+f"(d[57]), "+f"(d[58]), "+f"(d[59]), "+f"(d[60]), "+f"(d[61]), "+f"(d[62]), "+f"(d[63])
               : "l"(da), "l"(db), "r"(sc));
}

__device__ __forceinline__ void stsm4(uint32_t a, uint32_t r0, uint32_t r1, uint32_t r2, uint32_t r3) {
  asm volatile("stmatrix.sync.aligned.m8n8.x4.shared.b16 [%0],{%1,%2,%3,%4};" ::"r"(a), "r"(r0), "r"(r1), "r"(r2), "r"(r3) : "memory");
}
__device__ __forceinline__ void stsm4t(uint32_t a, uint32_t r0, uint32_t r1, uint32_t r2, uint32_t r3) {
  asm volatile("stmatrix.sync.aligned.m8n8.x4.trans.shared.b16 [%0],{%1,%2,%3,%4};" ::"r"(a), "r"(r0), "r"(r1), "r"(r2), "r"(r3) : "memory");
}
__device__ __forceinline__ void stsm2t(uint32_t a, uint32_t r0, uint32_t r1) {
  asm volatile("stmatrix.sync.aligned.m8n8.x2.trans.shared.b16 [%0],{%1,%2};" ::"r"(a), "r"(r0), "r"(r1) : "memory");
}
__device__ __forceinline__ void sts64(uint32_t a, uint32_t x, uint32_t y) { asm volatile("st.shared.v2.b32 [%0],{%1,%2};" ::"r"(a), "r"(x), "r"(y) : "memory"); }
__device__ __forceinline__ void st_async2u(uint32_t a, uint32_t x, uint32_t y, uint32_t bar) {
  asm volatile("st.async.weak.shared::cluster.mbarrier::complete_tx::bytes.v2.b32 [%0],{%1,%2},[%3];" ::"r"(a), "r"(x), "r"(y), "r"(bar) : "memory");
}
__device__ __forceinline__ void st_relaxed128(void* p, uint32_t x, uint32_t y, uint32_t z, uint32_t w) {
  asm volatile("{.reg .b128 v; mov.b128 v,{%1,%2,%3,%4}; st.relaxed.gpu.global.b128 [%0],v;}" ::"l"(p), "r"(x), "r"(y), "r"(z), "r"(w) : "memory");
}
__device__ __forceinline__ void st_relaxed64(void* p, uint32_t x, uint32_t y) {
  asm volatile("{.reg .b64 v; mov.b64 v,{%1,%2}; st.relaxed.gpu.global.b64 [%0],v;}" ::"l"(p), "r"(x), "r"(y) : "memory");
}
__device__ __forceinline__ uint4 ld_relaxed128(const void* p) {
  uint4 v;
  asm volatile("{.reg .b128 v; .reg .b64 lo, hi; ld.relaxed.gpu.global.b128 v,[%4]; mov.b128 {lo,hi},v; mov.b64 {%0,%1},lo; mov.b64 {%2,%3},hi;}" : "=r"(v.x), "=r"(v.y), "=r"(v.z), "=r"(v.w) : "l"(p) : "memory");
  return v;
}

__device__ __forceinline__ uint32_t pack_h2(float lo, float hi) {
  uint32_t r; asm("cvt.rn.satfinite.f16x2.f32 %0,%1,%2;" : "=r"(r) : "f"(hi), "f"(lo)); return r;
}
__device__ __forceinline__ void add_h2(float& lo, float& hi, uint32_t u, uint32_t v) {
  float a, b;
  asm("{.reg .b16 l, h; .reg .b32 s; add.rn.f16x2 s,%2,%3; mov.b32 {l,h},s; cvt.f32.f16 %0,l; cvt.f32.f16 %1,h;}" : "=f"(a), "=f"(b) : "r"(u), "r"(v));
  lo += a; hi += b;
}
__device__ __forceinline__ void mwait(uint32_t bar, uint32_t ph, int& spin) {
  asm volatile("{.reg .pred p, q;\nWAIT_LOOP:\n add.s32 %0,%0,1;\n setp.lt.s32 q,%0,%3;\n mbarrier.try_wait.parity.shared::cta.b64 p,[%1],%2;\n not.pred p,p;\n and.pred q,q,p;\n @q bra.uni WAIT_LOOP;\n}"
               : "+&r"(spin) : "r"(bar), "r"(ph), "n"(SPIN_TOT) : "memory");
}
__device__ __forceinline__ int keep(int x) { return __shfl_sync(0xffffffffu, x, threadIdx.x & 31); }
__device__ __forceinline__ uint32_t pin(uint32_t x) { asm volatile("" : "+r"(x)); return x; }
template <typename T> __device__ __forceinline__ T* pinp(T* x) { asm volatile("" : "+l"(x)); return x; }
__device__ __forceinline__ void st_async1u(uint32_t a, uint32_t x, uint32_t bar) {
  asm volatile("st.async.weak.shared::cluster.mbarrier::complete_tx::bytes.b32 [%0],%1,[%2];" ::"r"(a), "r"(x), "r"(bar) : "memory");
}
__device__ __forceinline__ uint32_t lds32(uint32_t a) { uint32_t v; asm volatile("ld.shared.b32 %0,[%1];" : "=r"(v) : "r"(a) : "memory"); return v; }
__device__ __forceinline__ uint2 lds64(uint32_t a) { uint2 v; asm volatile("ld.shared.v2.b32 {%0,%1},[%2];" : "=r"(v.x), "=r"(v.y) : "r"(a) : "memory"); return v; }

__device__ __forceinline__ void permute_cols(uint32_t tile, int tid, int n) {
#pragma unroll 2
  for (int it = tid; it < n; it += 128) {
    const int row = it >> 2, q = it & 3;
    const uint32_t a0 = tile + row * 128 + (((2 * q) ^ (row & 7)) << 4), a1 = tile + row * 128 + (((2 * q + 1) ^ (row & 7)) << 4);
    const uint4 u = lds128(a0), v = lds128(a1);
    sts128(a0, make_uint4(__byte_perm(u.x, u.y, 0x5410), __byte_perm(u.z, u.w, 0x5410), __byte_perm(v.x, v.y, 0x5410), __byte_perm(v.z, v.w, 0x5410)));
    sts128(a1, make_uint4(__byte_perm(u.x, u.y, 0x7632), __byte_perm(u.z, u.w, 0x7632), __byte_perm(v.x, v.y, 0x7632), __byte_perm(v.z, v.w, 0x7632)));
  }
}

__device__ __forceinline__ uint8_t* mkptr(uint32_t lo, uint32_t hi) { uint8_t* p; asm("mov.b64 %0,{%1,%2};" : "=l"(p) : "r"(lo), "r"(hi)); return p; }
__device__ __forceinline__ int uni(int x) { return __shfl_sync(0xffffffffu, x, 0); }

__device__ __forceinline__ bool elect_one() {
  uint32_t p; asm volatile("{.reg .pred q; elect.sync _|q, 0xffffffff; selp.u32 %0,1,0,q;}" : "=r"(p)); return p;
}
__device__ __forceinline__ uint64_t desc_at(uint64_t d, uint32_t off) {
  uint64_t r; asm("mov.b64 %0,{%1,%2};" : "=l"(r) : "r"((uint32_t)d + (off >> 4)), "r"((uint32_t)(d >> 32))); return r;
}
__device__ __forceinline__ uint32_t scale_bf16x2(uint32_t x, uint32_t s) { uint32_t r; asm("mul.rn.bf16x2 %0,%1,%2;" : "=r"(r) : "r"(x), "r"(s)); return r; }

__device__ __forceinline__ void stg128(void* p, const uint4& v) { asm volatile("st.global.v4.b32 [%0],{%1,%2,%3,%4};" ::"l"(p), "r"(v.x), "r"(v.y), "r"(v.z), "r"(v.w) : "memory"); }

__device__ __forceinline__ float quad_sum(float x) {
  const float a = __shfl_xor_sync(0xffffffffu, x, 1), b = __shfl_xor_sync(0xffffffffu, x, 2), c = __shfl_xor_sync(0xffffffffu, x, 3);
  return (x + a) + (b + c);
}
__device__ __forceinline__ float warp_sum(float x) {
  const uint32_t m = __reduce_max_sync(0xffffffffu, __float_as_uint(x) & 0x7FFFFFFFu), e = max(m >> 23, 25u);
  const int s = __reduce_add_sync(0xffffffffu, __float2int_rn(x * __uint_as_float((278 - e) << 23)));
  return fmaf(__uint_as_float(m), 0.f, (float)s * __uint_as_float((e - 24) << 23));
}
__device__ __forceinline__ void ln_row(float4 (&v)[5]) {
  float t0 = 0.f, t1 = 0.f;
#pragma unroll
  for (int m = 0; m < 5; m++) { t0 += v[m].x + v[m].y; t1 += v[m].z + v[m].w; }
  const float mean = warp_sum(t0 + t1) * (1.f / DM);
  float q0 = 0.f, q1 = 0.f, q2 = 0.f, q3 = 0.f;
#pragma unroll
  for (int m = 0; m < 5; m++) {
    v[m].x -= mean; v[m].y -= mean; v[m].z -= mean; v[m].w -= mean;
    q0 = fmaf(v[m].x, v[m].x, q0); q1 = fmaf(v[m].y, v[m].y, q1); q2 = fmaf(v[m].z, v[m].z, q2); q3 = fmaf(v[m].w, v[m].w, q3);
  }
  const float rs = rsqrtf(warp_sum((q0 + q1) + (q2 + q3)) * (1.f / DM) + 1e-5f);
#pragma unroll
  for (int m = 0; m < 5; m++) { v[m].x *= rs; v[m].y *= rs; v[m].z *= rs; v[m].w *= rs; }
}
__device__ __forceinline__ void ln0_load(const bf16* __restrict__ x, uint2 (&u)[5], int row, int lane) {
#pragma unroll
  for (int m = 0; m < 5; m++) u[m] = *reinterpret_cast<const uint2*>(x + (size_t)row * DM + m * 128 + lane * 4);
}
__device__ __forceinline__ void ln0_copy(const uint2 (&u)[5], int row, int lane) {
#pragma unroll
  for (int m = 0; m < 5; m++) stg128(g_x + (size_t)row * DM + m * 128 + lane * 4, make_uint4(u[m].x << 16, u[m].x & 0xFFFF0000u, u[m].y << 16, u[m].y & 0xFFFF0000u));
}
__device__ __forceinline__ void ln0_row(const uint2 (&u)[5], int row, int lane) {
  float4 v[5];
#pragma unroll
  for (int m = 0; m < 5; m++) v[m] = make_float4(bf_lo(u[m].x), bf_hi(u[m].x), bf_lo(u[m].y), bf_hi(u[m].y));
  ln_row(v);
  uint8_t* dst = g_xn[row >> 5] + ((row >> 3) & 3) * 4096 + (lane >> 4) * 1024 + (row & 7) * 128 + ((((lane >> 1) ^ row) & 7) << 4) + (lane & 1) * 8;
#pragma unroll
  for (int m = 0; m < 5; m++) *reinterpret_cast<uint2*>(dst + m * 16384) = make_uint2(pack_bf16(v[m].x, v[m].y), pack_bf16(v[m].z, v[m].w));
}

#define NOWORK 0
__device__ __forceinline__ void prep_row(const uint2 (&u)[5], const bf16* __restrict__ mem0, int k, int r, int lane) {
  const uint4 sent = make_uint4(SENT, SENT, SENT, SENT);
  if (k + 1 < NSTEP) {
    uint8_t* ex = ex_window(g_ex);
#pragma unroll
    for (int h = 0; h < 2; h++) {
      const int p = r * 40 + h * 32 + lane;
      if (h == 0 || lane < 8) {
        uint4 v = sent;
        if (k + 1 == LAG && (p & 8)) v = *reinterpret_cast<const uint4*>(mem0 + (p & 7) * DM + (p >> 4) * 8);
        stg128(ex + EX_M + (k + 1) * 20480 + p * 16, v);
      } else if (lane < 14) stg128(ex + EX_FLAG + (k + 1) * 3072 + (r * 6 + lane - 8) * 16, sent);
    }
  }
  if (k < LAG || k >= NSEG || NOWORK) {
    uint8_t* z = g_xn[k] + (r >> 3) * 4096 + (k < NSEG ? 2048 : 0) + (lane >> 4) * 1024 + (r & 7) * 128 + (lane & 15) * 8;
#pragma unroll
    for (int m = 0; m < 5; m++) *reinterpret_cast<uint2*>(z + m * 16384) = make_uint2(0, 0);
  }
  if (k < NSEG) {
    ln0_copy(u, k * 32 + r, lane);
    ln0_row(u, k * 32 + r, lane);
  }
}
__device__ __forceinline__ void pre_work(const bf16* __restrict__ x, const bf16* __restrict__ mem0, int cta, int tid) {
  constexpr int NT = 96 * 128;
  const int gt = cta * 128 + tid;
  uint8_t* ex = ex_window(g_ex);
#pragma unroll 1
  for (int row = cta + 96 * (tid >> 5); row < (NOWORK == 2 ? NSTEP : NPRE) * 32; row += 384) {
    uint2 u[5];
    ln0_load(x, u, min(row, SEQ - 1), tid & 31);
    prep_row(u, mem0, row >> 5, row & 31, tid & 31);
  }
#pragma unroll 1
  for (int i = gt; i < MAIL_BYTES / 16; i += NT) {
    stg128(ex + EX_MAIL + i * 16, make_uint4(SENT, SENT, SENT, SENT));
    stg128(ex + EX_MAIL + (1 << 20) + i * 16, make_uint4(SENT, SENT, SENT, SENT));
  }
  const int p = NT - 1 - gt;
  if (p < 1280) stg128(ex + EX_M + p * 16, *reinterpret_cast<const uint4*>(mem0 + (p & 7) * DM + (p >> 4) * 8));
  if (p < 192) stg128(ex + EX_FLAG + p * 16, make_uint4(0, 0, 0, 0));
  if (gt < 8 * CN_NUM) stg128(&g_cnt[0][0] + gt * 4, make_uint4(0, 0, 0, 0));
}
__device__ __forceinline__ void pre_wait(int which, uint32_t n, int& spin) {
  uint32_t old;
  asm volatile("atom.acq_rel.gpu.global.add.u32 %0,[%1],1;" : "=r"(old) : "l"(&g_ticket[which][0]) : "memory");
  const uint32_t target = (old / n + 1) * 96;
  while ((int)(ld_acquire(&g_ticket[0][0]) - target) < 0 && spin < SPIN_TOT) spin += 16;
  fence_async_all();
}

namespace C {
constexpr int NKR = 37;
constexpr int OFF_WQ = 0, OFF_WK = 81920;
constexpr int OFF_YO = 163840, OFF_YV = OFF_YO + 6144;
constexpr int OFF_M = 176128;
__host__ __device__ constexpr int og_off(int c) { return c ? OFF_M + 14336 + c * 2048 : 229376; }
constexpr int OFF_KT = 196608;
constexpr int OFF_XT = OFF_KT + 10240;
constexpr int OFF_VT = OFF_XT + 7168;
constexpr int OFF_XM = OFF_VT + 11392;
constexpr int OFF_PT = OFF_XM + 2560;
constexpr int KS = 1280, VS = 1408;
__host__ __device__ constexpr int slot_off(int p) { return p == 2 ? OFF_M : OFF_KT + (p % 3) * 16384; }
constexpr int OFF_ONE = 231424;
constexpr int OFF_BAR = 231552;
constexpr int OFF_SAFE = OFF_BAR + 144;
constexpr int OFF_TS = OFF_BAR + 256;
constexpr int SMEM = 232448;
constexpr uint32_t SB0 = 1024;
constexpr int BAR_F = OFF_BAR, BAR_XM = BAR_F + 40, BAR_XT = BAR_F + 48, BAR_OG = BAR_F + 56, BAR_E = OFF_BAR + 64, BAR_MOK = BAR_E + 40,
              BAR_M = OFF_BAR + 112, BAR_XF = OFF_BAR + 120, BAR_MF = OFF_BAR + 128, FLG_REDO = OFF_BAR + 136, BAR_W = OFF_BAR + 208;
constexpr int NB_PRO = 1, NB_RD = 2, NB_MR = 3, NB_QK = 4, NB_SM = 5, NB_VA = 6, NB_VQ = 7, NB_A = 8, NB_Q = 9, NB_C = 10, NB_WQ = 11, NB_QI = 12, NB_SI = 13, NB_WV = 14, NB_V = 15;
#define B1 600
#define AD0 16
#define AD1 128
#define AD2 16
#define AD3 128
#define BMX 1200
#define B2 800
#define FLP 2
#define OSG 2
#define OST 7
#define NBX 1
#define PVB 2
#define QPV 0
#define ONES 0
#define E0L 0
#define E2L 0
#define T2E 1
#define XMB 0
#define B3 0
#define OSV 0
#define T9L 0
#define P1U 4
#define QIE 4
#define SIE 2
#define WOE 1
#define OGF 2
#define VSP 8
#define RFK 5
#define PFD 3
#define WOL 0
constexpr uint32_t SCQ = 0x3A003A00;
constexpr float SCE = 0.07216878364870322f * 1.4426950408889634f * 2048;
}

#define CBAR_SYNC(id, n) bar_sync(id, n)
#define CBAR_ARRIVE(id, n) bar_arrive(id, n)

__device__ __forceinline__ uint64_t wdesc(int off) { return mkdesc(C::SB0 + off, 8192, 1024); }
__device__ __forceinline__ uint64_t mdesc(int k) { return mkdesc_ns(C::SB0 + C::OFF_M + k * 512, 256, 128); }
__device__ __forceinline__ uint64_t tdesc(int k) { return mkdesc(C::SB0 + C::slot_off(k >> 3) + ((k >> 2) & 1) * 1024 + (k & 3) * 32, 16, 2048); }

__device__ __forceinline__ int dh_row(int n) { return (n & ~63) + (n & 32) + ((n >> 1) & 3) * 8 + ((n >> 3) & 3) * 2 + (n & 1); }
template <bool IS_O>
__device__ __forceinline__ void stage_box(const CUtensorMap& tm, uint32_t sb, int p, int cta, int rank) {
  using namespace C;
  const uint32_t bar = sb + BAR_W + 8 * p;
  const int head = cta / 3, col = head * DH + rank * 64;
  mbar_expect_tx(bar, 16384);
  if (!IS_O) tma2d(sb + OFF_WK + p * 16384, &tm, col, p * 128, bar);
  else for (int b = 2 * p - 1; b <= 2 * p; b++)
    tma2d(sb + OFF_WQ + (b + 1) * 8192, &tm, b < 0 ? 576 : (3 * rank + b / 3) * 64, b < 0 ? col : head * DH + ((rank + b) % 3) * 64, bar);
}
template <bool IS_O>
__device__ __forceinline__ void load_weights_rs(uint32_t (&wf)[C::NKR][4], const CUtensorMap& tms, const CUtensorMap& tm, int cta, int rank, uint32_t sb, int tid0, int& spin) {
  using namespace C;
  constexpr int STAGE = IS_O ? OFF_WQ : OFF_WK, YOFF = IS_O ? OFF_YO : OFF_YV, NB = IS_O ? NB_C : NB_V;
  const int i = (tid0 >> 3) & 3, n0 = (tid0 & 7) + (i >> 1) * 8;
  const int chunk = 2 * ((tid0 >> 5) & 3) + (i & 1);
  const int r0 = IS_O ? dh_row(n0) : n0, r1 = IS_O ? dh_row(n0 + 16) : n0 + 16;
  const uint32_t a0 = sb + STAGE + r0 * 128 + ((chunk ^ (r0 & 7)) << 4), a1 = sb + STAGE + r1 * 128 + ((chunk ^ (r1 & 7)) << 4);
#pragma unroll
  for (int p = 0; p < 5; p++) {
    mwait(sb + BAR_W + 8 * p, 0, spin);
    if (IS_O) PTS(8 + p);
    if (p + NBX < 5) { if ((tid0 & 127) == 96) stage_box<IS_O>(tms, sb, p + NBX, cta, rank); __syncwarp(); }
    if (IS_O) permute_cols(sb + STAGE + p * 16384, tid0, 512);
    else {
#pragma unroll 1
      for (int it = tid0 & 127; it < 256; it += 128) {
        const uint32_t base = sb + STAGE + p * 16384 + (it >> 1) * 128;
        const int sw = ((it >> 1) & 7) ^ ((it & 1) * 4);
        const uint4 u0 = lds128(base + (sw << 4)), u1 = lds128(base + ((sw ^ 1) << 4)), u2 = lds128(base + ((sw ^ 2) << 4)), u3 = lds128(base + ((sw ^ 3) << 4));
        sts128(base + (sw << 4), make_uint4(u0.x, u1.x, u2.x, u3.x)); sts128(base + ((sw ^ 1) << 4), make_uint4(u0.y, u1.y, u2.y, u3.y));
        sts128(base + ((sw ^ 2) << 4), make_uint4(u0.z, u1.z, u2.z, u3.z)); sts128(base + ((sw ^ 3) << 4), make_uint4(u0.w, u1.w, u2.w, u3.w));
      }
    }
    bar_sync(NB, 128);
#pragma unroll
    for (int k = 8 * p; k < 8 * p + 8; k++) {
      if (k < NKR) ldsm4t(wf[k < NKR ? k : 0], ((k & 1) ? a1 : a0) + (k >> 1) * 4096);
      else {
        const int n = k * 16 + ((tid0 & 127) >> 3), r = IS_O ? dh_row(n) : n, c = tid0 & 7;
        sts128(sb + YOFF + (n - NKR * 16) * 128 + ((c ^ (n & 7)) << 4), lds128(sb + STAGE + r * 128 + ((c ^ (r & 7)) << 4)));
      }
    }
    fence_async();
    bar_sync(NB, 128);
    if ((tid0 & 127) == 0) {
      mbar_expect_tx(sb + BAR_W + 8 * p, 16384);
      tma2d(sb + STAGE + p * 16384, &tm, (cta / 3) * DH + rank * 64, p * 128, sb + BAR_W + 8 * p);
    }
    __syncwarp();
  }
  PTS(IS_O ? 13 : 14);
  CBAR_SYNC(NB_PRO, 384);
}
template <int STRIDE>
__device__ __forceinline__ void store_mem(const float (&d)[8], uint32_t base, int tid) {
  const int m = (tid >> 3) & 3;
  stsm4(base + (((tid >> 5) & 3) * 2 + (m & 1)) * STRIDE + (m >> 1) * 640 + (tid & 7) * 16, pack_bf16(d[0], d[1]), pack_bf16(d[2], d[3]),
        pack_bf16(d[4], d[5]), pack_bf16(d[6], d[7]));
}

__device__ __forceinline__ void load_pair(uint32_t sb, int i, int p, uint32_t slot, uint32_t ph, int& spin) {
  using namespace C;
  mwait(sb + BAR_E + 8 * p, ph, spin);
  if (elect_one()) bulk_g2s_mc(sb + slot, g_xn[i] + p * 16384, 16384, sb + BAR_F + 8 * p);
}
__device__ __forceinline__ void release_round(uint32_t sb, int p, int lane) {
  if (lane < (p == 2 ? 3 : 1)) mbar_arrive_cluster(mapa(sb, p == 2 ? lane : p) + C::BAR_E + 8 * (3 + p));
}

__device__ __forceinline__ void signal_o(int i, int cta) { csignal(CN_O + i * 5 + min(cta / 19, 4)); }

template <int K0, int K1>
__device__ __forceinline__ void v_mem_pass(float (&d)[8], const uint32_t (&wf)[C::NKR][4]) {
  using namespace C;
  wg_fence();
#pragma unroll
  for (int k = K0; k < K1; k++) {
    if (k < NKR) wgmma_rs16(d, wf[k < NKR ? k : 0], mdesc(k), k != 32);
    else wgmma_ts16(d, wdesc(OFF_YV + (k - NKR) * 2048), mdesc(k), 1);
  }
  wg_commit();
}
__device__ __forceinline__ void chain_v(const CUtensorMap& tmWv, const CUtensorMap& tmWk, const uint32_t sb, const int tid0, const int cta, const int rank) {
  using namespace C;
  asm volatile("setmaxnreg.inc.sync.aligned.u32 208;");
  int spin = 0;
  uint32_t wf[NKR][4];
  const int wu = uni((tid0 >> 5) & 3);
  const uint32_t slot = rank == 2 ? OFF_M : OFF_KT + rank * 16384;
  load_weights_rs<false>(wf, tmWv, tmWk, cta, rank, sb, tid0, spin);
  PTS(5);
#pragma unroll 1
  for (int i = 0; i < NSTEP; i++) {
    {
      float d[32];
      if (i > 0) CBAR_SYNC(NB_WV, 256);
#pragma unroll
      for (int p = 0; p < 5; p++) {
        if (OSV && p == 3) {
          wg_wait<0>();
          release_round(sb, 2, tid0 & 31);
          if (wu == 1 && i > 0) {
            CBAR_SYNC(NB_MR, 160);
            if (elect_one()) signal_o(i - 1, cta);
          }
        }
        mwait(sb + BAR_F + 8 * p, i & 1, spin);
        TS(i, 25 + p);
        wg_fence();
#pragma unroll
        for (int k = 8 * p; k < 8 * p + 8; k++) {
          if (k < NKR) wgmma_rs64(d, wf[k < NKR ? k : 0], tdesc(k), k);
          else wgmma_ts64(d, wdesc(OFF_YV + (k - NKR) * 2048), tdesc(k), 1);
          if (k == 8 * p + 1 && p >= 1 && p <= (OSV ? 2 : 3)) {
            wg_commit(); wg_wait<1>();
            release_round(sb, p - 1, tid0 & 31);
          }
          if (k == 8 * p + RFK && (p == 1 || p == 2)) {
            wg_commit();
            if (rank == p - 1 && wu == 0) load_pair(sb, i, p + 2, slot_off(p + 2), i & 1, spin);
            wg_fence();
          }
        }
        wg_commit();
      }
      wg_wait<0>();
      TS(i, 23);
      CBAR_SYNC(NB_RD, 256);
      const int tid = fresh(tid0) & 127, m = (tid >> 3) & 3;
      if (tid < 8) mbar_expect_tx(sb + BAR_F + 8 * tid, tid < 5 ? 16384 : tid == 5 ? 2560 : tid == 6 ? 7168 : 4096);
      if (tid < 3 && tid != rank) mbar_arrive_cluster(mapa(sb, tid) + BAR_XF);
      const uint32_t a = sb + OFF_VT + 256 + ((tid >> 5) * 2 + (m & 1)) * VS + (m >> 1) * 640 + (tid & 7) * 16;
#pragma unroll
      for (int s = 0; s < 4; s++)
        stsm4(a + s * 128, pack_bf16(d[8 * s], d[8 * s + 1]), pack_bf16(d[8 * s + 2], d[8 * s + 3]),
              pack_bf16(d[8 * s + 4], d[8 * s + 5]), pack_bf16(d[8 * s + 6], d[8 * s + 7]));
      if (tid < 80) sts128(sb + (tid < 72 ? OFF_VT + (tid >> 3) * VS : OFF_PT + 1280) + (tid & 7) * 16, make_uint4(0, 0, 0, 0));
      fence_async();
    }
    mwait(sb + BAR_XF, i & 1, spin);
    CBAR_ARRIVE(NB_QK, 384);
    const uint32_t* xc = &g_cnt[CN_X + i + 1][0];
    const uint32_t xn = i + 1 < LAG || NOWORK ? 16 : 48;
    bool seen = NOWORK == 2 || i + 1 < NPRE;
    if (wu == 0 && !seen) { seen = ld_acquire(xc) >= xn; fence_async_all(); }
    CBAR_SYNC(NB_QI, 256);
    float d[8];
    v_mem_pass<32, 40>(d, wf);
    CBAR_SYNC(NB_SM, 256);
    wg_wait<0>();
    if (__builtin_expect(lds32(sb + FLG_REDO), 0)) { v_mem_pass<32, 40>(d, wf); wg_wait<0>(); }
    if ((tid0 & 31) < 3 && (tid0 & 31) != rank) mbar_arrive_cluster(mapa(sb, tid0 & 31) + BAR_MF);
    v_mem_pass<0, 32>(d, wf);
    wg_wait<0>();
    TS(i, 24);
    const int tid = fresh(tid0);
    if (!E2L && (tid & 31) == 0) mbar_arrive_cluster(mapa(sb, 2) + BAR_E + 16);
    store_mem<VS>(d, sb + OFF_VT + 128, tid);
    fence_async();
    CBAR_ARRIVE(NB_VA, 256);
    CBAR_ARRIVE(NB_VQ, QPV ? 384 : 256);
    if (wu == 0 && i + 1 < NSTEP) {
      if (__builtin_expect(!seen, 0)) { while (ld_acquire(xc) < xn && spin < SPIN_TOT) spin += 16; fence_async_all(); }
      load_pair(sb, i + 1, rank, slot, i & 1, spin);
      TS(i + 1, 37);
    }
    TS_FLUSH(i - 1);
    __syncwarp();
  }
  CBAR_ARRIVE(NB_WV, 256);
  if (spin >= SPIN_TOT) g_err = 3;
}

__device__ __forceinline__ float quad_max(float x) {
  const float a = __shfl_xor_sync(0xffffffffu, x, 1), b = __shfl_xor_sync(0xffffffffu, x, 2), c = __shfl_xor_sync(0xffffffffu, x, 3);
  return fmaxf(fmaxf(x, a), fmaxf(b, c));
}
__device__ __forceinline__ float max10(const float (&y)[10]) {
  return fmaxf(fmaxf(fmaxf(fmaxf(y[0], y[1]), fmaxf(y[2], y[3])), fmaxf(fmaxf(y[4], y[5]), fmaxf(y[6], y[7]))), fmaxf(y[8], y[9]));
}
__device__ __forceinline__ float sum10(const float (&y)[10]) {
  return (((y[0] + y[1]) + (y[2] + y[3])) + ((y[4] + y[5]) + (y[6] + y[7]))) + (y[8] + y[9]);
}
__device__ __forceinline__ float rcp(float x) { float y; asm("rcp.approx.ftz.f32 %0,%1;" : "=f"(y) : "f"(x)); return y; }

__device__ __forceinline__ void chain_q(const bf16* x0, const bf16* mem0, const uint32_t sb, const int tid0, const int cta, const int rank) {
  using namespace C;
  asm volatile("setmaxnreg.dec.sync.aligned.u32 96;");
  int spin = 0;
  PTS(0);
  pre_work(x0, mem0, cta, tid0 & 127);
  PTS(3);
  CBAR_SYNC(NB_Q, 128);
  PTS(2);
  if (tid0 < 160) {
    if (tid0 == 128) pre_wait(0, 96, spin);
    __syncwarp();
    load_pair(sb, 0, rank, rank == 2 ? OFF_M : OFF_KT + rank * 16384, 1, spin);
  }
  PTS(4);
  CBAR_SYNC(NB_PRO, 384);
  mwait(sb + BAR_W, 1, spin);
  PTS(6);
  const int wu = uni((tid0 >> 5) & 3);
  uint4 ov[4] = {};
  uint8_t* op = &g_o[ORING - 1][cta][(tid0 & 124) * 32];
  const uint32_t o0 = ((tid0 ^ (tid0 >> 2)) & 3) * 16 + (tid0 & 16) * 4;
#pragma unroll 1
  for (int i = 0; i < NSTEP; i++) {
    const int ph = i & 1;
    uint32_t qf[4][4];
    {
      float d[64];
#define QK_STEP(K, SC) wgmma_st128(d, desc_at(mkdesc(SB0 + ((K) >> 2) * 1024 + ((K) & 3) * 32, 16, 2048), so), \
                                   desc_at(mkdesc(SB0 + OFF_WQ + (K) * 2048, OFF_WK - OFF_WQ, 1024), p * 16384), SC)
      int p = 0;
      uint32_t so = OFF_KT;
      mwait(sb + BAR_F, ph, spin);
      TS(i, 0);
      wg_fence();
#pragma unroll
      for (int k = 0; k < 8; k++) {
        QK_STEP(k, k);
        if (k == OST) {
          wg_commit();
          mwait(sb + BAR_F, ph, spin);
#pragma unroll
          for (int h = 0; h < 4; h++) stg128(op + (h & 1) * 4096 + (o0 ^ ((h >> 1) * 64)), ov[h]);
          if (i > 0) CBAR_ARRIVE(NB_MR, 160);
          if (k < 7) wg_fence();
        }
      }
      if (OST < 7) wg_commit();
#pragma unroll 1
      for (p = 1; p < 5; p++) {
        static_assert(OFF_KT - OFF_M == 5 << 12, "");
        so = OFF_M + (((0x95095u >> (4 * p)) & 15) << 12);
        if (i == 0) { mwait(sb + BAR_W + 8 * p, 1, spin); PTS(14 + p); }
        mwait(sb + BAR_F + 8 * p, ph, spin);
        wg_fence();
#pragma unroll
        for (int k = 0; k < 8; k++) {
          QK_STEP(k, 1);
          if (k == 1) {
            wg_commit(); wg_wait<1>();
            release_round(sb, p - 1, p < 4 ? tid0 & 31 : 32);
          }
        }
        wg_commit();
      }
#undef QK_STEP
      wg_wait<0>();
      TS(i, 1);
      CBAR_SYNC(NB_RD, 256);
      TSB(i, 2);
      const int tid = fresh(tid0), w = (tid >> 5) & 3, m = (tid >> 3) & 3;
      const uint32_t a = sb + OFF_KT + (m >> 1) * KS + (1 + w + 5 * (m & 1)) * 128 + (tid & 7) * 16;
#pragma unroll
      for (int s = 0; s < 4; s++)
        stsm4t(a + s * 2 * KS, pack_bf16(d[32 + 8 * s], d[33 + 8 * s]), pack_bf16(d[34 + 8 * s], d[35 + 8 * s]),
               pack_bf16(d[36 + 8 * s], d[37 + 8 * s]), pack_bf16(d[38 + 8 * s], d[39 + 8 * s]));
      fence_async();
      CBAR_ARRIVE(NB_QK, 384);
#pragma unroll
      for (int kk = 0; kk < 4; kk++)
#pragma unroll
        for (int j = 0; j < 4; j++) asm volatile("{.reg .b32 t; cvt.rn.bf16x2.f32 t,%1,%2; mul.rn.bf16x2 %0,t,%3;}" : "=r"(qf[kk][j]) : "f"(d[8 * kk + 2 * j + 1]), "f"(d[8 * kk + 2 * j]), "r"(SCQ));
    }
    CBAR_SYNC(NB_SI, 256);
    uint32_t pf[5][4];
    float sa = 0.f, sb2 = 0.f;
    {
      float y0[10], y1[10];
      const int tidf = fresh(tid0), lane = tidf & 31;
      {
        float x[40];
        wg_fence();
#pragma unroll
        for (int kk = 0; kk < 4; kk++) wgmma_rt80(x, qf[kk], mkdesc_ns(SB0 + OFF_KT + kk * 2 * KS, KS, 128), kk);
        wg_commit();
        wg_wait<0>();
#pragma unroll
        for (int j = 0; j < 5; j++) { y0[2 * j] = x[4 * j]; y0[2 * j + 1] = x[4 * j + 1]; y1[2 * j] = x[22 + 4 * j]; y1[2 * j + 1] = x[23 + 4 * j]; }
      }
      TS(i, 17);
      const uint32_t xo = OFF_XT + (wu * (wu + 3) / 2) * 256 + lane * 16, x2 = xo + (wu >> 1) * 512 + 512 - lane * 8;
      {
        const uint4 h0 = make_uint4(pack_h2(y0[0], y0[1]), pack_h2(y1[0], y1[1]), pack_h2(y0[2], y0[3]), pack_h2(y1[2], y1[3]));
        const uint4 h1 = make_uint4(pack_h2(y0[4], y0[5]), pack_h2(y1[4], y1[5]), pack_h2(y0[6], y0[7]), pack_h2(y1[6], y1[7]));
        const uint32_t h2 = wu == 1 ? h1.x : pack_h2(y0[8], y0[9]), h3 = wu == 1 ? h1.y : pack_h2(y1[8], y1[9]);
        const uint32_t rb1 = mapa(sb, (rank + 1) % 3), rb2 = mapa(sb, (rank + 2) % 3);
        st_async4u(rb1 + xo + 3584, h0, rb1 + BAR_XT);
        st_async4u(rb2 + xo, h0, rb2 + BAR_XT);
        if (wu >= 2) { st_async4u(rb1 + xo + 4096, h1, rb1 + BAR_XT); st_async4u(rb2 + xo + 512, h1, rb2 + BAR_XT); }
        if (wu & 1) { st_async2u(rb1 + x2 + 3584, h2, h3, rb1 + BAR_XT); st_async2u(rb2 + x2, h2, h3, rb2 + BAR_XT); }
      }
      TS(i, 18);
      const int lim = 8 * wu + (lane >> 2) + 8 - 2 * (lane & 3);
#pragma unroll
      for (int j = 2; j < 10; j++)
        if (8 * (j >> 1) + (j & 1) > lim) { y0[j] = -INFINITY; y1[j] = -INFINITY; }
      mwait(sb + BAR_XT, ph, spin);
      TS(i, 19);
      {
        const uint4 u0 = lds128(sb + xo), v0 = lds128(sb + xo + 3584);
        uint2 u2 = make_uint2(0, 0), v2 = u2;
        if (wu & 1) { u2 = lds64(sb + x2); v2 = lds64(sb + x2 + 3584); }
        uint4 u1 = make_uint4(u2.x, u2.y, 0, 0), v1 = make_uint4(v2.x, v2.y, 0, 0);
        if (wu >= 2) { u1 = lds128(sb + xo + 512); v1 = lds128(sb + xo + 4096); }
        __syncwarp();
        if (lane == 0) mbar_arrive_cluster(mapa(sb, 0) + BAR_E);
        add_h2(y0[0], y0[1], u0.x, v0.x); add_h2(y1[0], y1[1], u0.y, v0.y); add_h2(y0[2], y0[3], u0.z, v0.z); add_h2(y1[2], y1[3], u0.w, v0.w);
        add_h2(y0[4], y0[5], u1.x, v1.x); add_h2(y1[4], y1[5], u1.y, v1.y); add_h2(y0[6], y0[7], u1.z, v1.z); add_h2(y1[6], y1[7], u1.w, v1.w);
        add_h2(y0[8], y0[9], u2.x, v2.x); add_h2(y1[8], y1[9], u2.y, v2.y);
      }
      const float m0 = quad_max(max10(y0)) * -SCE, m1 = quad_max(max10(y1)) * -SCE;
#pragma unroll
      for (int j = 0; j < 5; j++) {
        y0[2 * j] = ex2(fmaf(y0[2 * j], SCE, m0)); y0[2 * j + 1] = ex2(fmaf(y0[2 * j + 1], SCE, m0));
        y1[2 * j] = ex2(fmaf(y1[2 * j], SCE, m1)); y1[2 * j + 1] = ex2(fmaf(y1[2 * j + 1], SCE, m1));
        if (!ONES) { sa += y0[2 * j] + y0[2 * j + 1]; sb2 += y1[2 * j] + y1[2 * j + 1]; }
        pf[j >> 1][2 * (j & 1)] = pack_bf16(y0[2 * j], y0[2 * j + 1]);
        pf[j >> 1][2 * (j & 1) + 1] = tidf >> (10 + j);
        pf[(j + 5) >> 1][2 * ((j + 5) & 1)] = tidf >> (20 + j);
        pf[(j + 5) >> 1][2 * ((j + 5) & 1) + 1] = pack_bf16(y1[2 * j], y1[2 * j + 1]);
      }
    }
#pragma unroll
    for (int q = 0; q < 20; q++) pf[q >> 2][q & 3] = pin(pf[q >> 2][q & 3]);
    CBAR_SYNC(NB_VQ, QPV ? 384 : 256);
    TSB(i, 20);
    {
      float o[32], sm[4];
      wg_fence();
#pragma unroll
      for (int q = 0; q < 5; q++) if (ONES) wgmma_rs8(sm, pf[q], mkdesc_ns(SB0 + OFF_ONE, 0, 0), q);
#pragma unroll
      for (int q = 0; q < 5; q++) wgmma_rs64(o, pf[q], mkdesc_ns(SB0 + OFF_VT + 128 + q * 256, 128, VS), q);
      wg_commit();
      if (!ONES) { sm[0] = quad_sum(sa); sm[2] = quad_sum(sb2); }
      const int tid = fresh(tid0);
      op = &g_o[i % ORING][cta][(tid & 124) * 32];
      wg_wait<0>();
      TS(i, 21);
      if ((tid & 31) == 0) mbar_arrive_cluster(mapa(sb, 1) + BAR_E + 8);
      const float s0 = rcp(sm[0]), s1 = rcp(sm[2]);
#pragma unroll
      for (int h = 0; h < 2; h++) {
        const float* x = o + 16 * h;
        ov[2 * h] = make_uint4(pin(pack_bf16(x[0] * s0, x[1] * s0)), pin(pack_bf16(x[4] * s0, x[5] * s0)), pin(pack_bf16(x[8] * s0, x[9] * s0)), pin(pack_bf16(x[12] * s0, x[13] * s0)));
        ov[2 * h + 1] = make_uint4(pin(pack_bf16(x[2] * s1, x[3] * s1)), pin(pack_bf16(x[6] * s1, x[7] * s1)), pin(pack_bf16(x[10] * s1, x[11] * s1)), pin(pack_bf16(x[14] * s1, x[15] * s1)));
      }
      TS(i, 22);
      if (i + 1 < NSTEP) CBAR_SYNC(NB_WQ, 256); else CBAR_ARRIVE(NB_WQ, 256);
    }
  }
#pragma unroll
  for (int h = 0; h < 4; h++) stg128(op + (h & 1) * 4096 + (o0 ^ ((h >> 1) * 64)), ov[h]);
  CBAR_SYNC(NB_Q, 128);
  if (tid0 == 224) signal_o(NSTEP - 1, cta);
  if (spin >= SPIN_TOT) g_err = 2;
}

template <int NL> __device__ __forceinline__ void poll(uint4 (&x)[NL], const uint8_t* mb, uint32_t tag, int& spin);
template <> __device__ __forceinline__ void poll<4>(uint4 (&x)[4], const uint8_t* mb, uint32_t tag, int& spin) {
  asm volatile("{.reg .pred p<6>, q; .reg .b128 v; .reg .b32 t;\n"
               " ld.relaxed.gpu.global.b128 v,[%17+0]; mov.b128 {%0,%1,%2,%3},v;\n"
               " ld.relaxed.gpu.global.b128 v,[%17+512]; mov.b128 {%4,%5,%6,%7},v;\n"
               " ld.relaxed.gpu.global.b128 v,[%17+1024]; mov.b128 {%8,%9,%10,%11},v;\n"
               " ld.relaxed.gpu.global.b128 v,[%17+1536]; mov.b128 {%12,%13,%14,%15},v;\n"
               "POLL_LOOP:\n add.s32 %16,%16,16;\n"
               " lop3.b32 t,%0,%18,1,0x28; setp.ne.b32 p0,t,0;\n"
               " lop3.b32 t,%4,%18,1,0x28; setp.ne.b32 p1,t,0;\n"
               " lop3.b32 t,%8,%18,1,0x28; setp.ne.b32 p2,t,0;\n"
               " lop3.b32 t,%12,%18,1,0x28; setp.ne.b32 p3,t,0;\n"
               " or.pred q,p0,p1; or.pred q,q,p2; or.pred q,q,p3; setp.lt.and.s32 q,%16,%19,q; vote.sync.any.pred q,q,0xffffffff;\n"
               " mov.b128 v,{%0,%1,%2,%3}; @p0 ld.relaxed.gpu.global.b128 v,[%17+0]; mov.b128 {%0,%1,%2,%3},v;\n"
               " mov.b128 v,{%4,%5,%6,%7}; @p1 ld.relaxed.gpu.global.b128 v,[%17+512]; mov.b128 {%4,%5,%6,%7},v;\n"
               " mov.b128 v,{%8,%9,%10,%11}; @p2 ld.relaxed.gpu.global.b128 v,[%17+1024]; mov.b128 {%8,%9,%10,%11},v;\n"
               " mov.b128 v,{%12,%13,%14,%15}; @p3 ld.relaxed.gpu.global.b128 v,[%17+1536]; mov.b128 {%12,%13,%14,%15},v;\n"
               " @q bra.uni POLL_LOOP;\n}"
               : "=&r"(x[0].x), "=&r"(x[0].y), "=&r"(x[0].z), "=&r"(x[0].w), "=&r"(x[1].x), "=&r"(x[1].y), "=&r"(x[1].z), "=&r"(x[1].w), "=&r"(x[2].x), "=&r"(x[2].y), "=&r"(x[2].z), "=&r"(x[2].w), "=&r"(x[3].x), "=&r"(x[3].y), "=&r"(x[3].z), "=&r"(x[3].w), "+&r"(spin)
               : "l"(mb), "r"(tag), "n"(SPIN_TOT) : "memory");
}
template <> __device__ __forceinline__ void poll<6>(uint4 (&x)[6], const uint8_t* mb, uint32_t tag, int& spin) {
  asm volatile("{.reg .pred p<6>, q; .reg .b128 v; .reg .b32 t;\n"
               " ld.relaxed.gpu.global.b128 v,[%25+0]; mov.b128 {%0,%1,%2,%3},v;\n"
               " ld.relaxed.gpu.global.b128 v,[%25+512]; mov.b128 {%4,%5,%6,%7},v;\n"
               " ld.relaxed.gpu.global.b128 v,[%25+1024]; mov.b128 {%8,%9,%10,%11},v;\n"
               " ld.relaxed.gpu.global.b128 v,[%25+1536]; mov.b128 {%12,%13,%14,%15},v;\n"
               " ld.relaxed.gpu.global.b128 v,[%25+2048]; mov.b128 {%16,%17,%18,%19},v;\n"
               " ld.relaxed.gpu.global.b128 v,[%25+2560]; mov.b128 {%20,%21,%22,%23},v;\n"
               "POLL_LOOP:\n add.s32 %24,%24,16;\n"
               " lop3.b32 t,%0,%2,%26,0x7e; and.b32 t,t,1; setp.ne.b32 p0,t,0;\n"
               " lop3.b32 t,%4,%6,%26,0x7e; and.b32 t,t,1; setp.ne.b32 p1,t,0;\n"
               " lop3.b32 t,%8,%10,%26,0x7e; and.b32 t,t,1; setp.ne.b32 p2,t,0;\n"
               " lop3.b32 t,%12,%14,%26,0x7e; and.b32 t,t,1; setp.ne.b32 p3,t,0;\n"
               " lop3.b32 t,%16,%18,%26,0x7e; and.b32 t,t,1; setp.ne.b32 p4,t,0;\n"
               " lop3.b32 t,%20,%22,%26,0x7e; and.b32 t,t,1; setp.ne.b32 p5,t,0;\n"
               " or.pred q,p0,p1; or.pred q,q,p2; or.pred q,q,p3; or.pred q,q,p4; or.pred q,q,p5; setp.lt.and.s32 q,%24,%27,q; vote.sync.any.pred q,q,0xffffffff;\n"
               " mov.b128 v,{%0,%1,%2,%3}; @p0 ld.relaxed.gpu.global.b128 v,[%25+0]; mov.b128 {%0,%1,%2,%3},v;\n"
               " mov.b128 v,{%4,%5,%6,%7}; @p1 ld.relaxed.gpu.global.b128 v,[%25+512]; mov.b128 {%4,%5,%6,%7},v;\n"
               " mov.b128 v,{%8,%9,%10,%11}; @p2 ld.relaxed.gpu.global.b128 v,[%25+1024]; mov.b128 {%8,%9,%10,%11},v;\n"
               " mov.b128 v,{%12,%13,%14,%15}; @p3 ld.relaxed.gpu.global.b128 v,[%25+1536]; mov.b128 {%12,%13,%14,%15},v;\n"
               " mov.b128 v,{%16,%17,%18,%19}; @p4 ld.relaxed.gpu.global.b128 v,[%25+2048]; mov.b128 {%16,%17,%18,%19},v;\n"
               " mov.b128 v,{%20,%21,%22,%23}; @p5 ld.relaxed.gpu.global.b128 v,[%25+2560]; mov.b128 {%20,%21,%22,%23},v;\n"
               " @q bra.uni POLL_LOOP;\n}"
               : "=&r"(x[0].x), "=&r"(x[0].y), "=&r"(x[0].z), "=&r"(x[0].w), "=&r"(x[1].x), "=&r"(x[1].y), "=&r"(x[1].z), "=&r"(x[1].w), "=&r"(x[2].x), "=&r"(x[2].y), "=&r"(x[2].z), "=&r"(x[2].w), "=&r"(x[3].x), "=&r"(x[3].y), "=&r"(x[3].z), "=&r"(x[3].w), "=&r"(x[4].x), "=&r"(x[4].y), "=&r"(x[4].z), "=&r"(x[4].w), "=&r"(x[5].x), "=&r"(x[5].y), "=&r"(x[5].z), "=&r"(x[5].w), "+&r"(spin)
               : "l"(mb), "r"(tag), "n"(SPIN_TOT) : "memory");
}
template <int NL>
__device__ __forceinline__ void poll_add(const uint8_t* mb, uint32_t tag, float (&f)[8], uint8_t* flag, bool lead, int& spin) {
  uint4 x[NL];
  poll<NL>(x, mb, tag, spin);
  if (FLP == 0 && lead) st_relaxed(flag, 0);
#pragma unroll
  for (int i = 0; i < NL; i++) {
    const uint32_t u[4] = {x[i].x, x[i].y, x[i].z, x[i].w};
#pragma unroll
    for (int j = 0; j < 4; j++) {
      if (i == 0) { f[2 * j] = bf_lo(u[j]); f[2 * j + 1] = bf_hi(u[j]); }
      else { f[2 * j] += bf_lo(u[j]); f[2 * j + 1] += bf_hi(u[j]); }
    }
  }
}

template <int B, int SLOT>
__device__ __forceinline__ void wo_step(float (&acc)[8], const uint32_t (&wf)[C::NKR][4], int kk) {
  using namespace C;
  const int k = 4 * B + kk;
  const uint64_t db = mkdesc_ns(SB0 + og_off(SLOT) + kk * 512, 256, 128);
  if (k < NKR) wgmma_rt16(acc, wf[k < NKR ? k : 0], db, SLOT | kk);
  else wgmma_tt16(acc, wdesc(OFF_YO + (k - NKR) * 2048), db, 1);
}
template <int B, int SLOT>
__device__ __forceinline__ void wo_block(float (&acc)[8], const uint32_t (&wf)[C::NKR][4]) {
#pragma unroll
  for (int kk = 0; kk < 4; kk++) wo_step<B, SLOT>(acc, wf, kk);
}

__device__ __forceinline__ void chain_a(const CUtensorMap& tmWo, const CUtensorMap& tmWq, const uint32_t sb, const int tid0, const int cta, const int rank) {
  using namespace C;
  asm volatile("setmaxnreg.inc.sync.aligned.u32 200;");
  int spin = 0;
  uint32_t wf[NKR][4];
  load_weights_rs<true>(wf, tmWo, tmWq, cta, rank, sb, tid0, spin);
  const int wu = uni(tid0 >> 5);
  const bool t9 = cta >= 72 && cta < 88;
  const uint64_t exa = reinterpret_cast<uint64_t>(ex_window(g_ex));
  const uint32_t ehi = (uint32_t)(exa >> 32), elo = (uint32_t)exa;

  int b1 = B1, b2 = B2;
#pragma unroll 1
  for (int i = -1; i < NSTEP; i++) {
    const int ph = i & 1;
    if (i >= 0) {
      const int tid = fresh(tid0);
      const uint32_t mo = __shfl_xor_sync(0xffffffffu, elo + ((rank * 24 + (tid >> 4)) * 4 + (tid & 3)) * 2048 + (cta / 3) * 64 + (tid & 12) * 4, 0);
      const uint32_t m9 = __shfl_xor_sync(0xffffffffu, elo + MAIL9 + (((tid >> 4) * 2 + (tid & 1)) * 4 + (tid & 2)) * 3072 + cta * 32 + (tid & 12) * 2, 0);
      const uint32_t oo = __shfl_xor_sync(0xffffffffu, (tid >> 5) * 512 + (tid & 2) * 64 + (tid & 28) * 4 + (tid & 1) * 8, 0);
      if (i == 0) { mwait(sb + BAR_W + 24, 1, spin); mwait(sb + BAR_W + 32, 1, spin); PTS(7); }
      mwait(sb + BAR_M, ph, spin);
      TS(i, 3);
      {
        float x[20];
        int redo = 0;
      retry:
        bool bad;
        {
          float dq[8] = {}, dk[8] = {};
#pragma unroll 1
          for (int k0 = 0; k0 < 40; k0 += P1U) {
            wg_fence();
#pragma unroll
            for (int k = 0; k < P1U; k++) {
              if (k == P1U - QIE / 2 && k0 == 40 - P1U && !redo) CBAR_ARRIVE(NB_QI, 256);
              const uint64_t db = desc_at(mdesc(k), k0 * 512);
              wgmma_ts16(dq, desc_at(wdesc(OFF_WQ + k * 2048), k0 * 2048), db, 1);
              wgmma_ts16(dk, desc_at(wdesc(OFF_WK + k * 2048), k0 * 2048), db, 1);
            }
            wg_commit();
          }
          const int m = (tid >> 3) & 3, dg = (tid >> 5) * 2 + (m & 1);
          const uint32_t ka = sb + OFF_KT + dg * KS + (m >> 1) * 640 + (tid & 7) * 16;
          if (!redo) CBAR_SYNC(NB_QK, 384);
          sts32(sb + FLG_REDO, redo);
          wg_wait<0>();
          TS(i, 4);
          stsm4(ka, pack_bf16(dk[0], dk[1]), pack_bf16(dk[2], dk[3]), pack_bf16(dk[4], dk[5]), pack_bf16(dk[6], dk[7]));
          stsm4(ka + dg * (VS - KS) + (OFF_VT + 128 - OFF_KT), scale_bf16x2(pack_bf16(dq[0], dq[1]), SCQ), scale_bf16x2(pack_bf16(dq[2], dq[3]), SCQ),
                scale_bf16x2(pack_bf16(dq[4], dq[5]), SCQ), scale_bf16x2(pack_bf16(dq[6], dq[7]), SCQ));
          const float chk = (dq[0] + dq[1]) + (dq[4] + dq[5]);
          fence_async();
          bad = bar_red_or(NB_C, 128, chk != chk && !redo);
        }
        TSB(i, 5);
        wg_fence();
#pragma unroll
        for (int kk = 0; kk < 4; kk++) wgmma_tt40(x, mkdesc_ns(SB0 + OFF_VT + 128 + kk * 2 * VS, VS, 640), mkdesc_ns(SB0 + OFF_KT + kk * 2 * KS, KS, 128), kk);
#pragma unroll
        for (int kk = 0; kk < 4; kk++) {
          if (SIE && kk == 4 - SIE && !bad) CBAR_ARRIVE(NB_SI, 256);
          wgmma_tt40(x, mkdesc_ns(SB0 + OFF_VT + kk * 2 * VS, VS, 384), mkdesc_ns(SB0 + OFF_KT + 640 + kk * 2 * KS, KS, 128), 1);
        }
        wg_commit();
        if (!SIE && !bad) CBAR_ARRIVE(NB_SI, 256);
        if (__builtin_expect(__any_sync(0xffffffffu, bad), 0)) {
          wg_wait<0>();
#pragma unroll 1
          for (int k = 0; k < 10; k++) {
            uint4 v = lds128(sb + OFF_M + tid * 16 + k * 2048);
            if (v.x == SENT || v.y == SENT || v.z == SENT || v.w == SENT) {
              do { v = ld_relaxed4(mkptr(elo + EX_M + i * 20480 + tid * 16 + k * 2048, ehi)); spin += 16; } while ((v.x == SENT || v.y == SENT || v.z == SENT || v.w == SENT) && spin < SPIN_TOT);
              sts128(sb + OFF_M + tid * 16 + k * 2048, v);
            }
          }
          fence_async();
          bar_sync(NB_C, 128);
          redo = fresh(1);
          goto retry;
        }
        TSV(i, 36, redo);
        const uint32_t rb1 = mapa(sb, (rank + 1) % 3), rb2 = mapa(sb, (rank + 2) % 3);
        wg_wait<0>();
        TS(i, 6);
        if (wu < 2) {
          float y[10];
#pragma unroll
          for (int j = 0; j < 5; j++) { y[2 * j] = x[4 * j]; y[2 * j + 1] = x[4 * j + 1]; }
          const uint4 h0 = make_uint4(pack_h2(y[0], y[1]), pack_h2(y[2], y[3]), pack_h2(y[4], y[5]), pack_h2(y[6], y[7]));
          const uint32_t h1 = pack_h2(y[8], y[9]);
          const uint32_t xo = wu * 640 + (tid & 31) * 16, xp = wu * 640 + 512 + (tid & 31) * 4;
          if (XMB) {
            sts128(sb + og_off(0) + xo, h0); sts32(sb + og_off(0) + xp, h1);
            fence_async();
            __syncwarp();
            if (elect_one()) {
              bulk_s2c(rb1 + OFF_XM + 1280 + wu * 640, sb + og_off(0) + wu * 640, 640, rb1 + BAR_XM);
              bulk_s2c(rb2 + OFF_XM + wu * 640, sb + og_off(0) + wu * 640, 640, rb2 + BAR_XM);
            }
          } else {
            st_async4u(rb1 + OFF_XM + 1280 + xo, h0, rb1 + BAR_XM);
            st_async4u(rb2 + OFF_XM + xo, h0, rb2 + BAR_XM);
            st_async1u(rb1 + OFF_XM + 1280 + xp, h1, rb1 + BAR_XM);
            st_async1u(rb2 + OFF_XM + xp, h1, rb2 + BAR_XM);
          }
          CBAR_ARRIVE(NB_SM, 256);
          if (!E0L && (tid & 31) == 0) mbar_arrive_cluster(mapa(sb, 0) + BAR_E);
          TS(i, 7);
          const uint32_t sw = (tid & 7) * 4 + (tid & 8) * 8 + (tid & 16) * 2;
          mwait(sb + BAR_XM, ph, spin);
          TS(i, 8);
          const uint4 u0 = lds128(sb + OFF_XM + xo), v0 = lds128(sb + OFF_XM + 1280 + xo);
          const uint32_t u1 = lds32(sb + OFF_XM + xp), v1 = lds32(sb + OFF_XM + 1280 + xp);
          add_h2(y[0], y[1], u0.x, v0.x); add_h2(y[2], y[3], u0.y, v0.y); add_h2(y[4], y[5], u0.z, v0.z); add_h2(y[6], y[7], u0.w, v0.w);
          add_h2(y[8], y[9], u1, v1);
          const float mx = quad_max(max10(y)) * -SCE;
#pragma unroll
          for (int j = 0; j < 5; j++) {
            y[2 * j] = ex2(fmaf(y[2 * j], SCE, mx)); y[2 * j + 1] = ex2(fmaf(y[2 * j + 1], SCE, mx));
            sts32(sb + OFF_PT + wu * 640 + sw + j * 128, pack_bf16(y[2 * j], y[2 * j + 1]));
          }
          sts32(sb + OFF_XM + 512 + wu * 128 + sw, __float_as_uint(sum10(y)));
          fence_async();
          TS(i, 9);
        } else {
          CBAR_ARRIVE(NB_SM, 256);
          if (!E0L && (tid & 31) == 0) mbar_arrive_cluster(mapa(sb, 0) + BAR_E);
          mwait(sb + BAR_MF, ph, spin);
        }
      }
      CBAR_SYNC(NB_VA, 256);
      TSB(i, 10);
      {
        float o[2][4];
        const float4 e = lds128f(sb + OFF_XM + 512 + (tid & 15) * 16);
        wg_fence();
#pragma unroll
        for (int c = 0; c < 2; c++)
#pragma unroll
          for (int q = 0; q < 3; q++)
            wgmma_ss8(o[c], mkdesc_ns(SB0 + OFF_VT + 128 + c * 640 + q * 256, 128, VS), mkdesc_ns(SB0 + OFF_PT + c * 640 + q * 256, q == 2 && c == 0 ? 768 : 128, 128), q);
        wg_commit();
        if (PVB && __builtin_expect(b1 < 0, 0)) { wg_wait<0>(); break; }
        const uint32_t rb1 = mapa(sb, (rank + 1) % 3), rb2 = mapa(sb, (rank + 2) % 3);
        const float inv = rcp((e.x + e.y) + (e.z + e.w));
        const int sl = (tid & 3) * 2;
        const float i0 = __shfl_sync(0xffffffffu, inv, sl), i1 = __shfl_sync(0xffffffffu, inv, sl + 1);
        const float i2 = __shfl_sync(0xffffffffu, inv, sl + 8), i3 = __shfl_sync(0xffffffffu, inv, sl + 9);
        if (E0L == 1 && (tid & 31) == 0) mbar_arrive_cluster(mapa(sb, 0) + BAR_E);
        if (PVB > 1 && __builtin_expect(b2 < 0, 0)) { wg_wait<0>(); break; }
        wg_wait<0>();
        TS(i, 11);
        const uint32_t p0 = pack_bf16(o[0][0] * i0, o[0][1] * i1), p1 = pack_bf16(o[1][0] * i2, o[1][1] * i3);
        const uint32_t p2 = pack_bf16(o[0][2] * i0, o[0][3] * i1), p3 = pack_bf16(o[1][2] * i2, o[1][3] * i3);
        if (OGF) { sts64(sb + oo + og_off(0), p0, p1); sts64(sb + oo + og_off(0) + 256, p2, p3); fence_async(); }
        if (OGF == 2) {
          __syncwarp();
          if (elect_one()) {
            bulk_s2c(rb1 + og_off(2) + wu * 512, sb + og_off(0) + wu * 512, 512, rb1 + BAR_OG);
            bulk_s2c(rb2 + og_off(1) + wu * 512, sb + og_off(0) + wu * 512, 512, rb2 + BAR_OG);
          }
        } else if (OGF < 2) {
          st_async2u(rb1 + oo + og_off(2), p0, p1, rb1 + BAR_OG);
          st_async2u(rb2 + oo + og_off(1), p0, p1, rb2 + BAR_OG);
          st_async2u(rb1 + oo + og_off(2) + 256, p2, p3, rb1 + BAR_OG);
          st_async2u(rb2 + oo + og_off(1) + 256, p2, p3, rb2 + BAR_OG);
        }
        if (!OGF) { sts64(sb + oo + og_off(0), p0, p1); sts64(sb + oo + og_off(0) + 256, p2, p3); fence_async(); }
      }
      if (E0L == 2 && (tid & 31) == 0) mbar_arrive_cluster(mapa(sb, 0) + BAR_E);
      CBAR_SYNC(NB_A, 128);
      TSB(i, 12);
      if (OGF == 3 && wu < 2 && elect_one()) {
        const uint32_t rb = mapa(sb, (rank + 1 + wu) % 3);
        bulk_s2c(rb + og_off(2) - wu * 2048, sb + og_off(0), 2048, rb + BAR_OG);
      }
      {
        float acc[3][8];
        wg_fence();
        wo_block<0, 0>(acc[2], wf);
        wg_commit();
        wo_block<1, 0>(acc[0], wf);
        if (QPV == 1) CBAR_ARRIVE(NB_VQ, 384);
        wo_block<4, 0>(acc[1], wf);
        wg_commit();
        if (QPV == 2) CBAR_ARRIVE(NB_VQ, 384);
        if (tid < (E2L == 1 ? 2 : 1)) mbar_arrive_cluster(mapa(sb, 1 + tid) + BAR_E + 8 + 8 * tid);
        const uint32_t tag = (i >> 1) & 1;
#define TAGGED(LO, HI) ((pack_bf16(LO, HI) & ~1u) | tag)
#define SEND(OFF, U) st_relaxed128(mkptr(mo + (ph << 20), ehi) + (OFF), TAGGED(acc[U][0], acc[U][2]), pack_bf16(acc[U][1], acc[U][3]), pack_bf16(acc[U][4], acc[U][6]), pack_bf16(acc[U][5], acc[U][7]))
        wg_wait<1>();
        const uint32_t n0 = pin(TAGGED(acc[2][0], acc[2][2])), n1 = pin(pack_bf16(acc[2][1], acc[2][3]));
        const uint32_t n2 = pin(TAGGED(acc[2][4], acc[2][6])), n3 = pin(pack_bf16(acc[2][5], acc[2][7]));
        if (T2E) { wg_fence(); wo_block<7, 0>(acc[2], wf); wg_commit(); }
        if (!T9L) { st_relaxed64(mkptr(m9 + (ph << 20), ehi), n0, n1); st_relaxed64(mkptr(m9 + (ph << 20), ehi) + 3072, n2, n3); }
        mwait(sb + BAR_OG, ph, spin);
        asm volatile("fence.proxy.async::generic.acquire.sync_restrict::shared::cluster.cluster;" ::: "memory");
        if (E2L == 2 && tid == 0) mbar_arrive_cluster(mapa(sb, 2) + BAR_E + 16);
        TS(i, 13);
        wg_fence();
        wo_block<2, 1>(acc[0], wf); wo_block<3, 2>(acc[0], wf);
        wg_commit();
        wo_block<5, 1>(acc[1], wf); wo_block<6, 2>(acc[1], wf);
        wg_commit();
        if (QPV == 3) CBAR_ARRIVE(NB_VQ, 384);
        wg_wait<1>();
        if (T9L) { st_relaxed64(mkptr(m9 + (ph << 20), ehi), n0, n1); st_relaxed64(mkptr(m9 + (ph << 20), ehi) + 3072, n2, n3); }
        SEND(0, 0);
        if (!T2E) wo_block<7, 0>(acc[2], wf);
        wo_block<8, 1>(acc[2], wf); wo_block<9, 2>(acc[2], wf);
        wg_commit();
        if (WOE == 0) { CBAR_ARRIVE(NB_WV, 256); CBAR_ARRIVE(NB_WQ, 256); }
        wg_wait<1>(); SEND(32 * 2048, 1);
        if (WOE == 1) CBAR_ARRIVE(NB_WV, 256);
        wg_wait<0>(); SEND(64 * 2048, 2);
        if (WOE == 2) CBAR_ARRIVE(NB_WV, 256);
        if (WOE >= 1) CBAR_ARRIVE(NB_WQ, 256);
#undef SEND
#undef TAGGED
      }
      TS(i, 14);
      if (i < 2) PTS(19 + i);
      if (i + 1 >= NSTEP) break;
    }
    uint32_t t1 = clk32();
    if (i >= 0) {
      const int lane = fresh(tid0) & 31, j = lane >> 3;
      const uint8_t* mb = mkptr(elo + (ph << 20) + (t9 ? MAIL9 + (cta - 72) * 12288 + wu * 3072 : (cta < 72 ? cta : cta - 24) * 8192 + wu * 2048) + lane * 16, ehi);
      const uint32_t tag = (i >> 1) & 1;
      const bool pub = (lane & (t9 ? 6 : 4)) == 0 && !(((t9 ? cta : wu) & 1) && i + 1 == LAG) && cta < 88;
      const uint32_t dst = pin(elo + EX_M + (i + 1) * 20480 + (t9 ? (cta + 72) * 128 + wu * 32 + (j & 1) * 16 + (lane & 1) * 8 + (j >> 1) * 4
                                                                   : cta * 256 + (wu & 1) * 128 + (wu >> 1) * 64 + j * 16 + (lane & 3) * 4));
      uint8_t* flag = mkptr(elo + EX_FLAG + (i + 1) * 3072 + cta * 32 + wu * 4, ehi);
      while (clk32() - t1 < b1) {}
      TS(i + 1, 30);
      float f[8];
      const int n0 = spin;
      if (!t9) poll_add<4>(mb, tag, f, flag, lane == 0, spin);
      else poll_add<6>(mb, tag, f, flag, lane == 0, spin);
      if (FLP == 1 && lane == 0) st_relaxed(flag, __float_as_uint(f[0] + f[7]) >> 1);
      t1 = clk32();
      b1 = __any_sync(0xffffffffu, spin - n0 > 16) ? min(b1 + AD1, BMX) : max(b1 - AD0, 0);
      TSV(i + 1, 38, b1);
      TS(i + 1, 31); TSV(i + 1, 32, (spin - n0) >> 4);
      const bool h = lane & 16, q = lane & 8;
#pragma unroll
      for (int j = 0; j < 4; j++) f[j] = (h ? f[4 + j] : f[j]) + __shfl_xor_sync(0xffffffffu, h ? f[j] : f[4 + j], 16);
#pragma unroll
      for (int j = 0; j < 2; j++) f[j] = (q ? f[2 + j] : f[j]) + __shfl_xor_sync(0xffffffffu, q ? f[j] : f[2 + j], 8);
      f[0] += __shfl_xor_sync(0xffffffffu, f[0], 4); f[1] += __shfl_xor_sync(0xffffffffu, f[1], 4);
      if (t9) { f[0] += __shfl_xor_sync(0xffffffffu, f[0], 2); f[1] += __shfl_xor_sync(0xffffffffu, f[1], 2); }
      if (pub) st_relaxed(mkptr(dst, ehi), pack_bf16(f[0], f[1]));
      if (FLP == 2 && lane == 0) st_relaxed(flag, 0);
      if (!OSV && wu == 3) {
        CBAR_SYNC(NB_MR, 160);
        if (elect_one()) signal_o(i, cta);
      }
      TS(i + 1, 15);
    }
    if (wu == 0) {
      const int tid = fresh(tid0);
      const uint8_t* pp = mkptr(elo + EX_FLAG + (i + 1) * 3072 + (rank * 28 + (tid < 28 || rank == 2 ? tid : 0)) * 32, ehi);
      while (clk32() - t1 < b2) {}
      TS(i + 1, 16);
      int n = 1;
      uint4 x = ld_relaxed4(pp);
      if (tid0 == 0) mbar_expect_tx(sb + BAR_M, 20480);
      bool mok = mbar_test(sb + BAR_MOK, ph ^ 1);
      while (__any_sync(0xffffffffu, (int)(x.x | x.y | x.z | x.w) < 0 && spin < SPIN_TOT)) { x = ld_relaxed4(pp); mok = mbar_test(sb + BAR_MOK, ph ^ 1); n++; spin += 16; }
      if (!mok) mwait(sb + BAR_MOK, ph ^ 1, spin);
      if (B3 && n > 1) { const uint32_t t3 = clk32(); while (clk32() - t3 < B3) {} }
      b2 = n > 1 ? min(b2 + AD3, BMX) : max(b2 - AD2, 0);
      TSV(i + 1, 35, n); TSV(i + 1, 39, b2);
      TS(i + 1, 34);
      if (elect_one()) bulk_g2s_mc(sb + OFF_M + rank * 7168, mkptr(elo + EX_M + (i + 1) * 20480 + rank * 7168, ehi), rank == 2 ? 6144 : 7168, sb + BAR_M);
      TS(i + 1, 33);
      __syncwarp();
    }
  }
  if (spin >= SPIN_TOT) g_err = 1;
}

__global__ void __cluster_dims__(3, 1, 1) __launch_bounds__(384, 1)
k_chain(const __grid_constant__ CUtensorMap tmWq, const __grid_constant__ CUtensorMap tmWk,
        const __grid_constant__ CUtensorMap tmWv, const __grid_constant__ CUtensorMap tmWo, const bf16* __restrict__ x0, const bf16* __restrict__ mem0) {
  using namespace C;
  extern __shared__ __align__(1024) uint8_t smem[];
  const uint32_t sb = smem_u32(smem);
  const int tid = threadIdx.x;
  const int wg = __shfl_sync(0xffffffffu, tid >> 7, 0);
  const int cta = uni(blockIdx.x), rank = uni(blockIdx.x % 3);

  asm volatile("griddepcontrol.launch_dependents;");
  if (cta < 4) prefetch_l2(tid < 320 ? x0 + (cta * 320 + tid) * 64 : mem0 + (cta * 20 + tid % 20) * 64);
  if (tid == 32) {
    for (int p = 0; p < 5; p++) mbar_init(sb + BAR_W + 8 * p, 2);
    fence_async();
    for (int p = 0; p < NBX; p++) { stage_box<false>(tmWv, sb, p, cta, rank); stage_box<true>(tmWo, sb, p, cta, rank); }
  }
  if (tid == 0) {
    if ((sb & 0xFFFFFF) != SB0) g_err = 100;
    for (int p = 0; p < 5; p++) { mbar_init(sb + BAR_F + 8 * p, 1); mbar_init(sb + BAR_E + 8 * p, p == 2 ? (E2L ? 3 : 12) : p == 1 ? 15 : 24); }
    mbar_init(sb + BAR_M, 1); mbar_init(sb + BAR_MOK, 24); mbar_init(sb + BAR_XM, 1); mbar_init(sb + BAR_XF, 2);
    mbar_init(sb + BAR_XT, 1); mbar_init(sb + BAR_MF, 8); mbar_init(sb + BAR_OG, 1);
    for (int p = 0; p < 5; p++) mbar_expect_tx(sb + BAR_F + 8 * p, 16384);
    for (int p = 0; p < 16; p++) sts32(sb + OFF_SAFE + 4 * p, 0);
    for (int p = 0; p < 32; p++) sts32(sb + OFF_ONE + 4 * p, 0x3F803F80);
    asm volatile("fence.mbarrier_init.release.cluster;" ::: "memory");
    fence_async();
  }
  __syncthreads();
  asm volatile("barrier.cluster.arrive.relaxed.aligned;" ::: "memory");
  asm volatile("barrier.cluster.wait.aligned;" ::: "memory");

  if (wg == 0) chain_a(tmWo, tmWq, sb, keep(tid), cta, rank);
  else if (wg == 1) chain_q(x0, mem0, sb, keep(tid), cta, rank);
  else chain_v(tmWv, tmWk, sb, keep(tid), cta, rank);
  asm volatile("barrier.cluster.arrive.release.aligned;" ::: "memory");
  asm volatile("barrier.cluster.wait.acquire.aligned;" ::: "memory");
}

namespace W {
constexpr int NP = 25, NBC = 11, NW = NP + NBC;
constexpr int PRS = 37, PW = 43 * 2048;
constexpr int OFF_W = 0;
constexpr int OFF_R = 2 * PW;
constexpr int BRS = 37, VSS = 39;
constexpr int OFF_WO = 0, OFF_Y = 81920;
constexpr int OFF_X = OFF_Y + 2 * (40 - BRS) * 2048;
constexpr int OFF_WV = OFF_X + 40960;
constexpr int OFF_S = OFF_WV + VSS * 2048;
constexpr int COL = 976;
constexpr int OFF_T = OFF_X + 16384;
constexpr int OFF_H = OFF_S + 7696;
constexpr int OFF_BAR = OFF_H + 8 * COL;
constexpr int OFF_SAFE = OFF_BAR + 256;
constexpr int SMEM = 232448;
static_assert(OFF_SAFE + 64 <= SMEM && OFF_R + 40960 <= OFF_BAR, "");
constexpr uint32_t SB0 = 1024;
constexpr int BAR_F = OFF_BAR, BAR_E = OFF_BAR + 40, BAR_G = OFF_BAR + 80, BAR_W = OFF_BAR + 160, BAR_R = OFF_BAR + 176;
constexpr int NB_G0 = 1, NB_SG = 4, NB_B = 5, NB_AS = 6, NB_SG1 = 7, NB_RED = 8, NB_SF = 9, NB_R = 11, NB_TD = 12, NB_RED3 = 13;
}
#define FSL 1
#define FSW 1
#define FSA 2
#define WBAR_SYNC(id, n) bar_sync(id, n)
#define WBAR_ARRIVE(id, n) bar_arrive(id, n)

__device__ __forceinline__ uint64_t rdesc(int off, int kk) { return mkdesc(W::SB0 + off + kk * 32, 16, 1024); }
__device__ __forceinline__ uint64_t gdesc(int off, int kk) { return mkdesc_ns(W::SB0 + off + kk * 1024, 512, 512) | ((uint64_t)2 << 62); }
__device__ __forceinline__ uint32_t frag_addr(uint32_t base, int tid) {
  const int i = (tid >> 3) & 3, r = tid & 7;
  return base + (r + (i >> 1) * 8) * 128 + (((2 * ((tid >> 5) & 3) + (i & 1)) ^ r) << 4);
}
template <int NK>
__device__ __forceinline__ void load_frags(uint32_t (&wf)[NK][4], uint32_t base, int tid) {
  const uint32_t a0 = frag_addr(base, tid);
#pragma unroll
  for (int k = 0; k < NK; k++) ldsm4t(wf[k], a0 + k * 2048);
}
__device__ __forceinline__ void red_tile(const float* d, int seg, int col0, int tid) {
  float* p = g_x + (size_t)(seg * 32 + 2 * (tid & 3)) * DM + col0 + ((tid >> 5) & 3) * 16 + ((tid >> 2) & 7) * 2;
#pragma unroll
  for (int j = 0; j < 8; j++)
    asm volatile("red.relaxed.gpu.global.add.v2.f32 [%0],{%1,%2};" ::"l"(p + ((j >> 1) * 8 + (j & 1)) * DM), "f"(d[4 * (j >> 1) + (j & 1)]), "f"(d[4 * (j >> 1) + 2 + (j & 1)]) : "memory");
}

__device__ __forceinline__ void work_p(const CUtensorMap& tmWo, uint32_t sb, int pc, const int WG, int tid0) {
  using namespace W;
  asm volatile("setmaxnreg.inc.sync.aligned.u32 208;");
  int spin = 0;
  const int ks = pc / 5, col0 = (pc % 5) * 128 + WG * 64;
  const uint32_t wb = sb + OFF_W + WG * PW;
  uint32_t wf[PRS][4];
#pragma unroll 1
  for (int hf = 0; hf < 2; hf++) {
    const int nk = hf ? 80 - PRS : PRS;
    if ((tid0 & 127) == 0) {
      mbar_expect_tx(sb + BAR_W + 8 * WG, nk * 2048);
      for (int i = 0; i < nk; i++) tma2d(wb + i * 2048, &tmWo, col0, ks * 19 * 64 + (i < PRS ? 2 * i + hf : PRS + i) * 16, sb + BAR_W + 8 * WG);
    }
    __syncwarp();
    mwait(sb + BAR_W + 8 * WG, hf, spin);
    permute_cols(wb, tid0 & 127, nk * 64);
    if (hf == 1 && ks < 4) for (int it = 39 * 64 + (tid0 & 127) - 64; it < 43 * 64; it += 128) {
      const uint32_t a = wb + (it >> 2) * 128 + (((2 * (it & 3)) ^ ((it >> 2) & 6)) << 4);
      if (it >= 39 * 64) { sts128(a, make_uint4(0, 0, 0, 0)); sts128(a + 16, make_uint4(0, 0, 0, 0)); }
    }
    fence_async();
    WBAR_SYNC(NB_G0 + WG, 128);
    if (hf == 0) {
      load_frags<PRS>(wf, wb, tid0);
      fence_async();
      WBAR_SYNC(NB_G0 + WG, 128);
    }
  }
#pragma unroll 1
  for (int k = 0; k < NSTEP; k++) {
    float d[32];
#pragma unroll
    for (int f = 0; f < 20; f++) {
      mwait(sb + BAR_F + 8 * (f % 5), (f / 5) & 1, spin);
      if (f == 0 && WG == 0 && pc == WW) WTS(k, 1);
      wg_fence();
#pragma unroll
      for (int kk = 0; kk < 4; kk++) {
        const int q = 4 * f + kk;
        if (q < 2 * PRS && !(q & 1)) wgmma_rs64(d, wf[q < 2 * PRS ? q >> 1 : 0], rdesc(OFF_R + (f % 5) * 8192, kk), q);
        else wgmma_ts64(d, desc_at(mkdesc(SB0 + OFF_W + (q < 2 * PRS ? q >> 1 : q - PRS) * 2048, 8192, 1024), WG * PW), rdesc(OFF_R + (f % 5) * 8192, kk), 1);
        if (kk == 0 && f > 0) {
          wg_commit();
          wg_wait<1>();
          if ((tid0 & 31) == 0) mbar_arrive(sb + BAR_E + 8 * ((f - 1) % 5));
        }
      }
      wg_commit();
    }
    wg_wait<0>();
    if ((tid0 & 31) == 0) mbar_arrive(sb + BAR_E + 32);
    if (WG == 0 && pc == WW) WTS(k, 2);
    if (k < NSEG) red_tile(d, k, col0, tid0);
    if (k >= LAG) red_tile(d + 16, k - LAG, col0, tid0);
    if (WG == 0 && pc == WW) WTS(k, 13);
    WBAR_SYNC(NB_SG, 256);
    if (WG == 0) { if (tid0 == 0) csignal_t(CN_P + k, 3); __syncwarp(); }
  }
  if (spin >= SPIN_TOT) g_err = 11;
}
__device__ __forceinline__ void work_p_producer(uint32_t sb, int pc, int odd) {
  using namespace W;
  int spin = 0;
  const int ks = pc / 5;
#pragma unroll 1
  for (int k = 0; k < NSTEP; k++) {
    const uint32_t lo = k < NSEG ? 0 : 4096, len = k < LAG || k >= NSEG ? 4096 : 8192;
    const uint8_t* src = &g_o[k % ORING][ks * 19 + odd][lo];
    cwait(CN_O + k * 5 + ks, ks == 4 ? 20 : 19, spin);
    fence_async_all();
    if (pc == WW && !odd) WTS1(k, 0);
#pragma unroll
    for (int u = 0; u < 10; u++) {
      const int st = odd ? (2 * u + 1) % 5 : (2 * u) % 5, ph = odd ? ((2 * u + 1) / 5) & 1 : ((2 * u) / 5) & 1;
      mwait(sb + BAR_E + 8 * st, ph ^ 1, spin);
      if (elect_one()) {
        if (u == 9 && odd && ks < 4) mbar_arrive(sb + BAR_F + 8 * st);
        else {
          mbar_expect_tx(sb + BAR_F + 8 * st, len);
          bulk_g2s(sb + OFF_R + st * 8192 + lo, src + u * 16384, len, sb + BAR_F + 8 * st);
        }
      }
    }
  }
  if (spin >= SPIN_TOT) g_err = 12;
}
template <int DMS>
__device__ __forceinline__ void work_ln(const int kind, int r, int lane, bf16* out) {
  int spin = 0;
  const int l = kind & 1;
  const int rp = kind < 2 ? (r & 1) * 16 + (r >> 1) : r;
  const uint32_t sw = ((((lane >> 1) & 7) ^ (rp & 7)) << 4) + (lane & 1) * 8;
  uint8_t* dst = kind < 2 ? g_xnb[l * LAG] + (lane >> 4) * 8192 + l * 4096 + rp * 128 + sw
               : kind == 2 ? g_xn[LAG] + (r >> 3) * 4096 + 2048 + (lane >> 4) * 1024 + (r & 7) * 128 + sw
                           : reinterpret_cast<uint8_t*>(out) + r * 1280 + lane * 8;
  if (FSL && kind < 2) {
#pragma unroll
    for (int m = 0; m < 5; m++) asm volatile("st.global.v2.b32 [%0],{%1,%1};" ::"l"(dst + m * DMS), "r"(SENT) : "memory");
    fence_gpu();
  }
#pragma unroll 1
  for (int s = 0; s < NSEG; s++) {
    float* xr = g_x + (size_t)(s * 32 + r) * DM;
    float4 v[5];
    if (kind < 2) {
#pragma unroll
      for (int u = 0; u < 5; u++) {
        const int p = u * 32 + lane;
        stg128((p < 80 ? g_ob[s + l * LAG] + (l * 32 + r) * 1280 : g_y[l] + (size_t)s * 40960 + (r - 1) * 1280) + p * 16, make_uint4(SENT, SENT, SENT, SENT));
      }
      if (FSL && s + 1 < NSEG) {
#pragma unroll
        for (int m = 0; m < 5; m++) asm volatile("st.global.v2.b32 [%0],{%1,%1};" ::"l"(dst + 81920 + m * DMS), "r"(SENT) : "memory");
      }
      if (lane == 0) cwait(CN_P + s + l * LAG, W::NP, spin);
      __syncwarp();
      if (r == 0 && lane == 0 && (l == 0 || s + LAG >= NSEG)) WTS1(s + l * LAG, 3);
#pragma unroll
      for (int m = 0; m < 5; m++) v[m] = ld_relaxed4f(xr + m * 128 + lane * 4);
    } else {
      if (lane == 0) cwait(CN_L + s + l * LAG, s + l * LAG < LAG || s + l * LAG >= NSEG ? 32 : 64, spin);
      __syncwarp();
#pragma unroll
      for (int m = 0; m < 5; m++) v[m] = ld_relaxed4f(xr + m * 128 + lane * 4);
      if (lane == 0) cwait(CN_W + l * 64 + s, 10, spin);
      __syncwarp();
      if (r == 0 && lane == 0 && (l == 0 || s + LAG >= NSEG)) WTS1(s + l * LAG, 11);
      const uint8_t* yp = g_y[l] + (size_t)s * 40960 + (lane >> 4) * 4096 + r * 128 + sw;
      float2 y[5];
      bool bad;
      do {
        bad = false;
#pragma unroll
        for (int m = 0; m < 5; m++) y[m] = ld_relaxed2f(yp + m * 8192);
#pragma unroll
        for (int m = 0; m < 5; m++) bad |= __float_as_uint(y[m].x) == SENT || __float_as_uint(y[m].y) == SENT;
        spin += 16;
      } while (__any_sync(0xffffffffu, bad && spin < SPIN_TOT));
#pragma unroll
      for (int m = 0; m < 5; m++) {
        v[m].x += bf_lo(__float_as_uint(y[m].x)); v[m].y += bf_hi(__float_as_uint(y[m].x));
        v[m].z += bf_lo(__float_as_uint(y[m].y)); v[m].w += bf_hi(__float_as_uint(y[m].y));
        if (kind == 2) *reinterpret_cast<float4*>(xr + m * 128 + lane * 4) = v[m];
      }
    }
    if (FSL == 3 && kind < 2 && lane == 0) csignal_fast(CN_G + s + l * LAG);
    if (kind < 3) ln_row(v);
#pragma unroll
    for (int m = 0; m < 5; m++)
      asm volatile("st.global.v2.b32 [%0],{%1,%2};" ::"l"(dst + m * DMS), "r"(pack_bf16(v[m].x, v[m].y)), "r"(pack_bf16(v[m].z, v[m].w)) : "memory");
    dst += DMS == 256 ? 40960 : 81920;
    __syncwarp();
    if (r == 0 && lane == 0 && (l == 0 || s + LAG >= NSEG)) WTS1(s + l * LAG, kind < 2 ? 4 : 12);
    if (lane == 0 && kind < (NOWORK ? 2 : 3)) {
      if (FSL && kind < 2) csignal_fast(CN_G + s + l * LAG);
      csignal_t(kind < 2 ? CN_L + s + l * LAG : CN_X + s + LAG, kind);
    }
  }
  if (spin >= SPIN_TOT) g_err = 13;
}

__device__ __forceinline__ void work_prep(const bf16* x0, const bf16* mem0, int r, int lane) {
  int spin = 0;
#pragma unroll 1
  for (int k = NPRE; k < NSTEP; k++) {
    if (lane < 20) prefetch_l2(x0 + (size_t)min(k * 32 + r + (lane < 10 ? 0 : 16), SEQ - 1) * DM + (lane % 10) * 64);
    if (lane == 0) cwait(CN_O + (k - NPRE) * 5, 1, spin);
    __syncwarp();
#pragma unroll 1
    for (int h = 0; h < 2; h++) {
      uint2 u[5];
      ln0_load(x0, u, min(k * 32 + r + 16 * h, SEQ - 1), lane);
      prep_row(u, mem0, k, r + 16 * h, lane);
    }
    __syncwarp();
    if (lane == 0) csignal(CN_X + k);
  }
  if (spin >= SPIN_TOT) g_err = 19;
}

__device__ __forceinline__ void stage_qkv(const bf16* wqkv, uint32_t base, int T, int bc, int tid) {
  const int q = tid & 15;
  const bool ok = q < 15 && bc * 60 + 4 * q < DM;
  const bf16* src = wqkv + T * DM + bc * 60 + 4 * q;
#pragma unroll 1
  for (int k0 = tid >> 4; k0 < 640; k0 += 80) {
    uint2 v[10];
#pragma unroll
    for (int u = 0; u < 10; u++) v[u] = ok ? *reinterpret_cast<const uint2*>(src + (size_t)(k0 + 8 * u) * 1920) : make_uint2(0, 0);
#pragma unroll
    for (int u = 0; u < 10; u++) sts64(base + (k0 + 8 * u) * 128 + (((q >> 1) ^ (k0 & 7)) << 4) + (q & 1) * 8, v[u].x, v[u].y);
  }
}
struct AttAddr { uint32_t qa, qb, ka, oa, ob, ml; };
__device__ __forceinline__ AttAddr att_addr(uint32_t sb, int bc, int hh, int tid) {
  using namespace W;
  const int r = tid & 7, m = (tid >> 3) & 3, g = (tid >> 2) & 7, t = tid & 3, lp = (tid >> 5) & 3;
  const int f2 = r < 4 ? 20 * hh + 16 + r : 60;
  const uint32_t tb = sb + OFF_T + 2 * lp * COL;
  const int fa = 20 * hh + (m >> 1) * 8 + r, pc = 2 * (lp & 1) + (m & 1);
  const uint32_t o0 = sb + OFF_S + (lp >> 1) * 3840;
  AttAddr x;
  x.qa = keep(tb + (m & 1) * COL + (20 * hh + (m >> 1) * 8 + r) * 16);
  x.qb = keep(tb + (m & 1) * COL + f2 * 16);
  x.ka = keep(tb + (m < 2 ? 20 * hh + 8 * m + r : f2) * 16);
  x.oa = keep(o0 + fa * 64 + ((pc ^ ((bc * 60 + fa) >> 1)) & 3) * 16);
  x.ob = keep(r < 4 ? o0 + f2 * 64 + ((pc ^ ((bc * 60 + f2) >> 1)) & 3) * 16 : sb + OFF_S + 7680);
  x.ml = keep((2 * t > g ? 0xFFFFu : 0u) | (2 * t + 1 > g ? 0xFFFF0000u : 0u));
  return x;
}
__device__ __forceinline__ void release_tiles(uint32_t sb, int tid) {
  fence_async();
  __syncwarp();
  if ((tid & 31) < 3) mbar_arrive(sb + W::BAR_E + 16 + 8 * (tid & 3));
}
__device__ __forceinline__ void attend(uint32_t sb, const AttAddr& x, int k0, int lp, int tid) {
  using namespace W;
  const uint32_t hd = OFF_H - OFF_T - lp * COL;
  const float scl = 0.22360679774997896f * 1.4426950408889634f;
  float sc[3][4];
  uint32_t v[3][4];
  {
    uint32_t q[4], q8a, q8b, k[3][4];
    ldsm4t(q, x.qa);
    ldsm4t(k[0], x.ka + hd); ldsm4t(k[1], x.ka + 8 * COL); ldsm4t(k[2], x.ka + 9 * COL);
    ldsm2t(q8a, q8b, x.qb);
#pragma unroll
    for (int c = 0; c < 3; c++) { sc[c][0] = sc[c][1] = sc[c][2] = sc[c][3] = 0.f; mma16816(sc[c], q[0], q[1], q[2], q[3], k[c][0], k[c][1]); }
#pragma unroll
    for (int c = 0; c < 3; c++) mma1688(sc[c], q8a, q8b, k[c][2]);
    stsm4t(x.ka + hd, k[2][0], k[2][1], k[2][2], k[2][3]);
  }
  ldsm4(v[0], x.ka + hd + 4 * COL); ldsm4(v[1], x.ka + 16 * COL); ldsm4(v[2], x.ka + 17 * COL);
  stsm4(x.ka + hd + 4 * COL, v[2][0], v[2][1], v[2][2], v[2][3]);
  release_tiles(sb, tid);
  const bool lo0 = x.ml & 1, lo1 = (int)x.ml < 0, first = k0 == (lp >> 1) * LAG;
  uint32_t pw[2];
  float inv[2];
#pragma unroll
  for (int h = 0; h < 2; h++) {
    float y0 = lo0 ? sc[h][2 * h] : sc[h + 1][2 * h], y1 = lo1 ? sc[h][2 * h + 1] : sc[h + 1][2 * h + 1];
    if (h == 0 && first) { y0 = lo0 ? -INFINITY : y0; y1 = lo1 ? -INFINITY : y1; }
    const float mx = quad_max(fmaxf(y0, y1)) * -scl;
    y0 = ex2(fmaf(y0, scl, mx)); y1 = ex2(fmaf(y1, scl, mx));
    pw[h] = pack_bf16(y0, y1);
    inv[h] = y0 + y1;
  }
  float o[3][4];
  const uint32_t a0 = pw[0] & x.ml, a2 = pw[0] & ~x.ml, a3 = pw[1] & x.ml, a5 = pw[1] & ~x.ml, z0 = tid >> 10, z1 = tid >> 11;
#pragma unroll
  for (int j = 0; j < 3; j++) { o[j][0] = o[j][1] = o[j][2] = o[j][3] = 0.f; mma16816(o[j], a0, z0, a2, a3, v[0][j], v[1][j]); }
#pragma unroll
  for (int j = 0; j < 3; j++) mma1688(o[j], z1, a5, v[2][j]);
  inv[0] = rcp(quad_sum(inv[0])); inv[1] = rcp(quad_sum(inv[1]));
  stsm4t(x.oa, pack_bf16(o[0][0] * inv[0], o[0][1] * inv[0]), pack_bf16(o[0][2] * inv[1], o[0][3] * inv[1]),
         pack_bf16(o[1][0] * inv[0], o[1][1] * inv[0]), pack_bf16(o[1][2] * inv[1], o[1][3] * inv[1]));
  stsm2t(x.ob, pack_bf16(o[2][0] * inv[0], o[2][1] * inv[0]), pack_bf16(o[2][2] * inv[1], o[2][3] * inv[1]));
  fence_async();
}
template <bool IS_V>
__device__ __forceinline__ void work_b(const CUtensorMap& tmBo, const bf16* wqkv, uint32_t sb, int bc, const int wg, int tid0) {
  using namespace W;
  if (!IS_V) asm volatile("setmaxnreg.inc.sync.aligned.u32 208;");
  else asm volatile("setmaxnreg.dec.sync.aligned.u32 72;");
  constexpr int NR = IS_V ? 40 - VSS : BRS;
  const int WG = IS_V ? 2 : wg;
  const uint32_t yo = WG * (40 - BRS) * 2048;
  int spin = 0;
  uint32_t wf[NR][4];
  if (!IS_V) {
    const uint32_t wb = sb + (WG ? OFF_WO : OFF_WV);
    stage_qkv(wqkv, wb, WG, bc, tid0 & 127);
    WBAR_SYNC(NB_G0 + WG, 128);
    load_frags<NR>(wf, wb, tid0);
#pragma unroll
    for (int k = NR; k < 40; k++) sts128(sb + OFF_Y + yo + (k - NR) * 2048 + (tid0 & 127) * 16, lds128(wb + k * 2048 + (tid0 & 127) * 16));
    fence_async();
  }
  WBAR_SYNC(NB_B, 384);
  if (WG == 1 && bc < 10) {
    if ((tid0 & 127) == 0) {
      mbar_expect_tx(sb + BAR_W, 81920);
      for (int i = 0; i < 10; i++) tma2d(sb + OFF_WO + i * 8192, &tmBo, bc * 64, i * 64, sb + BAR_W);
    }
    __syncwarp();
    mwait(sb + BAR_W, 0, spin);
  }
  if (IS_V) {
    stage_qkv(wqkv, sb + OFF_WV, 2, bc, tid0 & 127);
    WBAR_SYNC(NB_G0 + 2, 128);
    load_frags<NR>(wf, sb + OFF_WV + VSS * 2048, tid0);
  }
  fence_async();
  WBAR_SYNC(NB_B, 384);
  const int wu = uni((tid0 >> 5) & 3);
  uint32_t nredo = 0;
  const AttAddr aa = att_addr(sb, bc, WG, tid0);
#pragma unroll 1
  for (int k = 0; k < NSTEP + (WG == 0); k++) {
    if (WG || k < NSTEP) {
    {
      float d[32];
#define QKV_STEP(Q, DB)                                                                                                                  \
  {                                                                                                                                      \
    const int q = (Q);                                                                                                                   \
    if (IS_V ? q >= VSS : q < NR) wgmma_rs64(d, wf[IS_V ? (q >= VSS ? q - VSS : 0) : (q < NR ? q : 0)], DB, q);                          \
    else if (IS_V) wgmma_ts64(d, mkdesc(SB0 + OFF_WV + q * 2048, 8192, 1024), DB, q);                                                    \
    else wgmma_ts64(d, desc_at(mkdesc(SB0 + OFF_Y + (q - NR) * 2048, 8192, 1024), yo), DB, 1);                                           \
  }
#pragma unroll
      for (int c = 0; c < 10; c++) {
        mwait(sb + BAR_F + 8 * (c % 5), c / 5, spin);
        if (c == 0 && bc == 0 && WG != 1) WTS(k, WG ? 15 : 6);
        wg_fence();
#pragma unroll
        for (int kk = 0; kk < 4; kk++) {
          QKV_STEP(4 * c + kk, rdesc(OFF_X + (c % 5) * 8192, kk));
        }
        wg_commit();
        if (c > 0 && c <= 7) {
          wg_wait<1>();
          if ((tid0 & 31) == 0) mbar_arrive(sb + BAR_E + 8 * ((c - 1) % 5));
        }
      }
      wg_wait<0>();
      if (bc == 0 && WG != 1) WTS(k, 16 + WG / 2);
      uint32_t pk[16];
#pragma unroll
      for (int q = 0; q < 16; q++) pk[q] = pin(pack_bf16(d[2 * q], d[2 * q + 1]));
      const int tid = fresh(tid0), m = (tid >> 3) & 3;
      const uint32_t a = pin(sb + OFF_T + min(wu * 16 + (m & 1) * 8 + (tid & 7), 60) * 16 + (8 * WG + (m >> 1)) * COL);
      if (!FSL) WBAR_SYNC(NB_B, 384);
      else {
        const float c0 = ((d[0] + d[1]) + (d[4] + d[5])) + ((d[8] + d[9]) + (d[12] + d[13]));
        const float c1 = ((d[16] + d[17]) + (d[20] + d[21])) + ((d[24] + d[25]) + (d[28] + d[29]));
        if (__builtin_expect(bar_red_or(NB_RED3, 384, IS_V && ((c0 != c0 && k < NSEG) || (c1 != c1 && k >= LAG))), 0)) {
          if (IS_V && wu == 0) { cwait(CN_L + k, k < LAG || k >= NSEG ? 32 : 64, spin); fence_async_all(); }
#pragma unroll
          for (int c = 0; c < 10; c++) {
            if (IS_V && wu == 0 && elect_one()) { mbar_expect_tx(sb + BAR_R + 8, 8192); bulk_g2s(sb + OFF_X + 32768, g_xnb[k] + c * 8192, 8192, sb + BAR_R + 8); }
            __syncwarp();
            mwait(sb + BAR_R + 8, c & 1, spin);
            wg_fence();
#pragma unroll
            for (int kk = 0; kk < 4; kk++) QKV_STEP(4 * c + kk, rdesc(OFF_X + 32768, kk));
            wg_commit();
            wg_wait<0>();
            bar_sync(NB_RED3, 384);
          }
#pragma unroll
          for (int q = 0; q < 16; q++) pk[q] = pin(pack_bf16(d[2 * q], d[2 * q + 1]));
        }
      }
#undef QKV_STEP
#pragma unroll
      for (int p = 0; p < 4; p++) stsm4(a + 2 * p * COL, pk[4 * p], pk[4 * p + 1], pk[4 * p + 2], pk[4 * p + 3]);
    }
    WBAR_SYNC(NB_TD, 448);
    if (bc == 0 && WG == 0) WTS(k, 7);
    if (bc * 3 + WG < NH && (wu < 2 ? k < NSEG : k >= LAG)) attend(sb, aa, k, wu, fresh(tid0));
    else release_tiles(sb, tid0);
    if (bc == 0 && WG == 0) WTS(k, 8);
    WBAR_SYNC(NB_AS, 416);
    }
    const int s = k - (1 - WG) * (LAG + 1);
    if (!IS_V && bc < 10 && s >= 0 && s < NSEG) {
      float d[16];
#pragma unroll
      for (int f = 0; f < 5; f++) {
        mwait(sb + BAR_G + 40 * WG + 8 * f, s & 1, spin);
        if (f == 0 && bc == 0) WTS(k - 1 + WG, WG || k > NSEG ? 20 : 23);
        wg_fence();
#pragma unroll
        for (int kk = 0; kk < 8; kk++) {
          wgmma_tt32(d, mkdesc(SB0 + OFF_WO + (8 * f + kk) * 2048, 8192, 1024), gdesc(OFF_X + f * 8192, kk), f | kk);
          if (kk == 1 && f > 0) {
            wg_commit();
            wg_wait<1>();
            if ((tid0 & 31) < 3) mbar_arrive(sb + BAR_E + 8 * (f - 1));
          }
        }
        wg_commit();
      }
      wg_wait<0>();
      if (WG == 1 && FSA) {
        const float chk = ((d[0] + d[1]) + (d[4] + d[5])) + ((d[8] + d[9]) + (d[12] + d[13]));
        if (__builtin_expect(bar_red_or(NB_RED, 128, chk != chk), 0)) {
          if (wu == 0) { cwait(CN_A + k, NBC, spin); fence_async_all(); }
#pragma unroll
          for (int q = 0; q < 16; q++) d[q] = 0.f;
#pragma unroll 1
          for (int f = 0; f < 5; f++) {
            if (wu == 0 && elect_one()) { mbar_expect_tx(sb + BAR_W + 8, 8192); bulk_g2s(sb + OFF_X + 32768, g_ob[k] + f * 8192, 8192, sb + BAR_W + 8); }
            __syncwarp();
            mwait(sb + BAR_W + 8, nredo & 1, spin);
            nredo++;
            wg_fence();
#pragma unroll
            for (int kk = 0; kk < 8; kk++)
              wgmma_tt32(d, desc_at(mkdesc(SB0 + OFF_WO + kk * 2048, 8192, 1024), f * 16384), gdesc(OFF_X + 32768, kk), 1);
            wg_commit();
            wg_wait<0>();
            bar_sync(NB_RED, 128);
          }
        }
      }
      else if (WG) bar_sync(NB_RED, 128);
      else {
        if ((tid0 & 31) < 3) mbar_arrive(sb + BAR_E + 32);
        WBAR_SYNC(NB_SF, 160);
      }
      if (bc == 0) WTS(k - 1 + WG, WG || k > NSEG ? 10 : 24);
      const int tid = fresh(tid0), m = (tid >> 3) & 3, row = (m >> 1) * 16 + 2 * (tid & 7);
      const uint32_t a = sb + (WG ? OFF_X + 32768 : OFF_S) + row * 128 + (((2 * wu + (m & 1)) ^ row) & 7) * 16;
#pragma unroll
      for (int p = 0; p < 2; p++)
        stsm4t(a ^ (p * 144), pack_bf16(d[8 * p], d[8 * p + 1]), pack_bf16(d[8 * p + 2], d[8 * p + 3]), pack_bf16(d[8 * p + 4], d[8 * p + 5]), pack_bf16(d[8 * p + 6], d[8 * p + 7]));
      fence_async();
      WBAR_SYNC(WG ? NB_SG : NB_SG1, 160);
    }
  }
  if (spin >= SPIN_TOT) g_err = 14;
}
__device__ __forceinline__ bool b_job(int k, int u, int bc) { return u < 2 ? k < NSTEP : bc < 10 && (u == 2 ? k > LAG : k < NSEG); }
__device__ __forceinline__ void work_b_watch(uint32_t sb, int bc) {
  using namespace W;
  int spin = 0;
#pragma unroll 1
  for (int j = 0; j < 4 * NSTEP + 3; j++) {
    const int k = j >> 2, u = j & 3;
    if (u == 1 || !b_job(k, u, bc)) continue;
    cwait(u == 0 ? (FSL ? CN_G : CN_L) + k : u == 2 ? CN_A + k - 1 : (FSA ? CN_F : CN_A) + k, u ? NBC : k < LAG || k >= NSEG ? 32 : 64, spin);
    fence_async_all();
    if (bc == 0 && (u != 2 || k > NSEG)) WTS1(k + (u ? u - 3 : 0), u ? 9 : 5);
    if (elect_one()) mbar_arrive(sb + BAR_R + 8 * u);
    __syncwarp();
    if (u == 0) WBAR_SYNC(NB_R, 64);
  }
  if (spin >= SPIN_TOT) g_err = 16;
}
__device__ __forceinline__ void work_b_producer(uint32_t sb, int bc) {
  using namespace W;
  int spin = 0;
  uint32_t pe = 1;
#pragma unroll 1
  for (int j = 0; j < 4 * NSTEP + 3; j++) {
    const int k = j >> 2, u = j & 3;
    if (!b_job(k, u, bc)) continue;
    const uint32_t half = u < 2 && (k < LAG || k >= NSEG), lo = half && k >= NSEG ? 4096 : 0, len = half ? 4096 : 8192, fb = sb + (u < 2 ? BAR_F : BAR_G + 40 * (u - 2));
    const uint8_t* src = (u < 2 ? g_xnb[k] + u * 40960 : u == 2 ? g_ob[k - 1] + 40960 : g_ob[k]) + lo;
    if (u != 1) mwait(sb + BAR_R + 8 * u, (u == 2 ? k - LAG - 1 : k) & 1, spin);
#pragma unroll
    for (int f = 0; f < 5; f++) {
      mwait(sb + BAR_E + 8 * f, pe, spin);
      if (elect_one()) {
        mbar_expect_tx(fb + 8 * f, len);
        bulk_g2s(sb + OFF_X + f * 8192 + lo, src + f * 8192, len, fb + 8 * f);
      }
    }
    if (u == 0) WBAR_SYNC(NB_R, 64);
    pe ^= 1;
  }
  if (spin >= SPIN_TOT) g_err = 15;
}

__global__ void __launch_bounds__(512, 1)
k_work(const __grid_constant__ CUtensorMap tmWo, const __grid_constant__ CUtensorMap tmBo, const bf16* __restrict__ wqkv, bf16* __restrict__ out,
       const bf16* __restrict__ x0, const bf16* __restrict__ mem0) {
  using namespace W;
  extern __shared__ __align__(1024) uint8_t smem[];
  const uint32_t sb = smem_u32(smem);
  const int tid = threadIdx.x, w = blockIdx.x;
  const int wg = __shfl_sync(0xffffffffu, tid >> 7, 0);
  if (tid == 0) {
    if (sb != SB0) g_err = 101;
    for (int i = 0; i < 5; i++) { mbar_init(sb + BAR_F + 8 * i, 1); mbar_init(sb + BAR_E + 8 * i, w < NP ? 8 : 12); }
    for (int i = 0; i < 16; i++) mbar_init(sb + BAR_G + 8 * i, 1);
    for (int p = 0; p < 16; p++) sts32(sb + OFF_SAFE + 4 * p, 0);
    asm volatile("fence.mbarrier_init.release.cluster;" ::: "memory");
    int spin = 0;
    pre_wait(1, NW, spin);
    if (spin >= SPIN_TOT) g_err = 18;
  }
  if (tid < 8 * COL / 16) sts128(sb + OFF_H + tid * 16, make_uint4(0, 0, 0, 0));
  fence_async();
  __syncthreads();

  if (w < NP) {
    if (wg < 2) work_p(tmWo, sb, w, wg, keep(tid));
    else {
      asm volatile("setmaxnreg.dec.sync.aligned.u32 48;");
      const int aw = uni(tid >> 5) - 8;
      if (aw < 2) {
        work_p_producer(sb, w, aw);
      } else {
        const int id = (aw - 2) * NP + w;
        if (id < 96) work_ln<16384>(id % 3, id / 3, tid & 31, out);
        else if (id < 128) work_ln<256>(3, id - 96, tid & 31, out);
        else if (id < 144 && NOWORK != 2) work_prep(x0, mem0, id - 128, tid & 31);
      }
    }
  } else {
    const int bc = w - NP;
    if (wg < 2) work_b<false>(tmBo, wqkv, sb, bc, wg, keep(tid));
    else if (wg == 2) work_b<true>(tmBo, wqkv, sb, bc, wg, keep(tid));
    else {
      asm volatile("setmaxnreg.dec.sync.aligned.u32 24;");
      const int aw = uni(tid >> 5) - 12;
      if (aw == 0) work_b_producer(sb, bc);
      else if (aw == 1) work_b_watch(sb, bc);
      else if (aw == 2) {
#pragma unroll 1
        for (int k = 0; k < NSTEP; k++) {
          WBAR_ARRIVE(NB_TD, 448);
          if (FSA == 3 && (tid & 31) == 0) csignal_fast(CN_F + k);
          WBAR_SYNC(NB_AS, 416);
          if (elect_one()) {
            const uint32_t len = bc < 10 ? 3840 : 2560;
            if (k < NSEG) {
              bulk_s2g(g_ob[k] + bc * 3840, sb + OFF_S, len);
              asm volatile("cp.async.bulk.commit_group;" ::: "memory");
              if (FSA == 1) asm volatile("cp.async.bulk.wait_group.read 0;" ::: "memory");
              if (FSA) csignal_fast(CN_F + k);
            }
            if (k >= LAG) bulk_s2g(g_ob[k] + 40960 + bc * 3840, sb + OFF_S + 3840, len);
            asm volatile("cp.async.bulk.commit_group;" ::: "memory");
            asm volatile("cp.async.bulk.wait_group 0;" ::: "memory");
          }
          __syncwarp();
          if (b_job(k, 2, bc)) WBAR_ARRIVE(NB_SF, 160);
          if (elect_one()) { fence_async_all(); csignal_t(CN_A + k, 5); }
          __syncwarp();
        }
        if (bc < 10) WBAR_SYNC(NB_SF + 1, 64), WBAR_ARRIVE(NB_SF, 160);
      } else {
#pragma unroll 1
        for (int j = 0; j < 2 * NSTEP + 1; j++) {
          const int l = (j & 1) ^ 1, s = (j >> 1) - l * (LAG + 1);
          if (l) { if (j < 2 * NSTEP) WBAR_SYNC(NB_TD, 448); else if (bc < 10) WBAR_ARRIVE(NB_SF + 1, 64); }
          if (s < 0 || s >= NSEG || bc == 10) continue;
          WBAR_SYNC(l ? NB_SG1 : NB_SG, 160);
          if (elect_one()) {
            bulk_s2g(g_y[l] + (size_t)s * 40960 + bc * 4096, sb + (l ? OFF_S : OFF_X + 32768), 4096);
            asm volatile("cp.async.bulk.commit_group;" ::: "memory");
            if (FSW) csignal_fast(CN_W + l * 64 + s);
            asm volatile("cp.async.bulk.wait_group.read 0;" ::: "memory");
            if (!FSW) csignal_fast(CN_W + l * 64 + s);
            if (!l) asm volatile("mbarrier.arrive.shared::cta.b64 _,[%0],12;" ::"r"(sb + BAR_E + 32) : "memory");
          }
          __syncwarp();
        }
      }
    }
  }
  __syncthreads();
  asm volatile("griddepcontrol.wait;" ::: "memory");
}

typedef CUresult (*EncodeFn)(CUtensorMap*, CUtensorMapDataType, cuuint32_t, void*, const cuuint64_t*, const cuuint64_t*,
                             const cuuint32_t*, const cuuint32_t*, CUtensorMapInterleave, CUtensorMapSwizzle,
                             CUtensorMapL2promotion, CUtensorMapFloatOOBfill);

static void make_map(EncodeFn enc, CUtensorMap* tm, const void* ptr, uint64_t cols, uint64_t rows, uint32_t boxc, uint32_t boxr) {
  cuuint64_t dims[2] = {cols, rows};
  cuuint64_t strides[1] = {cols * 2};
  cuuint32_t box[2] = {boxc, boxr};
  cuuint32_t es[2] = {1, 1};
  enc(tm, CU_TENSOR_MAP_DATA_TYPE_BFLOAT16, 2, const_cast<void*>(ptr), dims, strides, box, es, CU_TENSOR_MAP_INTERLEAVE_NONE,
      CU_TENSOR_MAP_SWIZZLE_128B, CU_TENSOR_MAP_L2_PROMOTION_L2_256B, CU_TENSOR_MAP_FLOAT_OOB_FILL_NONE);
}

extern "C" void kernel_launch(void* const* d_in, const int* in_sizes, int n_in, void* d_out, int out_size) {
  const bf16* x0 = (const bf16*)d_in[0];
  const bf16* mem0 = (const bf16*)d_in[1];
  const bf16* Wq = (const bf16*)d_in[2];
  const bf16* Wk = (const bf16*)d_in[3];
  const bf16* Wv = (const bf16*)d_in[4];
  const bf16* Wo = (const bf16*)d_in[5];
  const bf16* Bqkv = (const bf16*)d_in[8];
  const bf16* Bwo = (const bf16*)d_in[9];
  bf16* out = (bf16*)d_out;

  static EncodeFn enc = nullptr;
  if (!enc) {
    void* fn = nullptr;
    cudaDriverEntryPointQueryResult qr;
    cudaGetDriverEntryPoint("cuTensorMapEncodeTiled", &fn, cudaEnableDefault, &qr);
    enc = (EncodeFn)fn;
    cudaFuncSetAttribute(k_chain, cudaFuncAttributeMaxDynamicSharedMemorySize, C::SMEM);
    cudaFuncSetAttribute(k_work, cudaFuncAttributeMaxDynamicSharedMemorySize, W::SMEM);
  }
  CUtensorMap tmWq, tmWk, tmWv, tmWo, tmWp, tmBo;
  make_map(enc, &tmWq, Wq, NH * DH, DM, 64, 128);
  make_map(enc, &tmWk, Wk, NH * DH, DM, 64, 128);
  make_map(enc, &tmWv, Wv, NH * DH, DM, 64, 128);
  make_map(enc, &tmWo, Wo, DM, NH * DH, 64, 64);
  make_map(enc, &tmWp, Wo, DM, NH * DH, 64, 16);
  make_map(enc, &tmBo, Bwo, DM, DM, 64, 64);

  cudaStream_t st = cudaStreamPerThread;
  cudaLaunchAttribute at[1];
  at[0].id = cudaLaunchAttributeProgrammaticStreamSerialization; at[0].val.programmaticStreamSerializationAllowed = 1;
  {
    cudaLaunchConfig_t cfg = {};
    cfg.gridDim = dim3(96); cfg.blockDim = dim3(384); cfg.dynamicSmemBytes = C::SMEM; cfg.stream = st;
    cfg.attrs = at; cfg.numAttrs = 0;
    cudaLaunchKernelEx(&cfg, k_chain, tmWq, tmWk, tmWv, tmWo, x0, mem0);
  }
  cudaLaunchConfig_t cfg = {};
  cfg.gridDim = dim3(W::NW); cfg.blockDim = dim3(512); cfg.dynamicSmemBytes = W::SMEM; cfg.stream = st;
  cfg.attrs = at; cfg.numAttrs = NOWORK == 2 ? 0 : 1;
  cudaLaunchKernelEx(&cfg, k_work, tmWp, tmBo, Bqkv, out, x0, mem0);
}
```

```cpp
#include <cuda_runtime.h>
#include <cuda_bf16.h>
#include <cuda.h>
#include <stdint.h>

typedef __nv_bfloat16 bf16;

constexpr int SEQ = 2048, DM = 640, NH = 32, DH = 192, NSEG = 64;
#define LAG 5
constexpr int NSTEP = NSEG + LAG;
constexpr int NPRE = 4;
constexpr uint32_t SENT = 0xFFFFFFFFu;

constexpr int MAIL9 = 288 * 2048, MAIL_BYTES = MAIL9 + 64 * 3072;
__device__ __align__(1024) uint8_t g_xn[NSTEP][81920];
__device__ __align__(1024) uint8_t g_xnb[NSTEP][81920];
__device__ __align__(1024) uint8_t g_ob[NSTEP][81920];
__device__ __align__(1024) uint8_t g_y[2][NSEG * 40960];
#define ORING 8
static_assert(ORING > LAG, "a slot is free again LAG + 1 steps later");
__device__ __align__(1024) uint8_t g_o[ORING][96][8192];
__device__ __align__(1024) float g_x[SEQ * DM];
constexpr int EX_MAIL = 0;
constexpr int EX_M = 2 << 20;
constexpr int EX_FLAG = EX_M + NSTEP * 20480;
static_assert(EX_FLAG + NSTEP * 3072 <= (4 << 20), "");
__device__ __align__(1024) uint8_t g_ex[8 << 20];
__host__ __device__ __forceinline__ uint8_t* ex_window(uint8_t* p) { return reinterpret_cast<uint8_t*>((reinterpret_cast<uint64_t>(p) + (4 << 20) - 1) & ~(uint64_t)((4 << 20) - 1)); }
enum { CN_P = 0, CN_L = 128, CN_A = 256, CN_W = 384, CN_X = 512, CN_F = 640, CN_G = 768, CN_O = 896, CN_NUM = CN_O + 5 * NSTEP };
__device__ __align__(128) uint32_t g_cnt[CN_NUM][32];
__device__ __align__(128) uint32_t g_ticket[2][32];
__device__ int g_err;
#define TS(jj, i)
#define TS1(jj, i)
#define PTS(i)
#define TSB(jj, i)
#define TSV(jj, i, v)
#define TS_FLUSH(jj)
#define WTS(b, k)
#define WTS1(b, k)
#define WW -1

__device__ __forceinline__ uint32_t smem_u32(const void* p) { return (uint32_t)__cvta_generic_to_shared(p); }
__device__ __forceinline__ uint32_t clk32() { uint32_t t; asm volatile("mov.u32 %0, %%clock;" : "=r"(t)::"memory"); return t; }
__device__ __forceinline__ uint32_t mapa(uint32_t a, uint32_t r) { uint32_t o; asm("mapa.shared::cluster.u32 %0,%1,%2;" : "=r"(o) : "r"(a), "r"(r)); return o; }
__device__ __forceinline__ void mbar_init(uint32_t bar, uint32_t cnt) { asm volatile("mbarrier.init.shared::cta.b64 [%0],%1;" ::"r"(bar), "r"(cnt) : "memory"); }
__device__ __forceinline__ void mbar_expect_tx(uint32_t bar, uint32_t bytes) { asm volatile("mbarrier.arrive.expect_tx.shared::cta.b64 _,[%0],%1;" ::"r"(bar), "r"(bytes) : "memory"); }
__device__ __forceinline__ void mbar_arrive(uint32_t bar) { asm volatile("mbarrier.arrive.shared::cta.b64 _,[%0];" ::"r"(bar) : "memory"); }
__device__ __forceinline__ void mbar_arrive_cluster(uint32_t bar) { asm volatile("mbarrier.arrive.shared::cluster.b64 _,[%0];" ::"r"(bar) : "memory"); }
__device__ __forceinline__ bool mbar_try(uint32_t bar, uint32_t ph) {
  uint32_t ok;
  asm volatile("{.reg .pred p; mbarrier.try_wait.parity.shared::cta.b64 p,[%1],%2; selp.u32 %0,1,0,p;}" : "=r"(ok) : "r"(bar), "r"(ph) : "memory");
  return ok;
}
__device__ __forceinline__ bool mbar_test(uint32_t bar, uint32_t ph) {
  uint32_t ok;
  asm volatile("{.reg .pred p; mbarrier.test_wait.parity.shared::cta.b64 p,[%1],%2; selp.u32 %0,1,0,p;}" : "=r"(ok) : "r"(bar), "r"(ph) : "memory");
  return ok;
}
__device__ __forceinline__ int fresh(int x) { asm volatile("" : "+r"(x)); return x; }
#define PHASE_IDS const int tid = fresh(tid0), lane = tid & 31, w = tid >> 5, g = lane >> 2, t = lane & 3; (void)w; (void)g; (void)t
__device__ __forceinline__ void bar_sync(int id, int n) { asm volatile("bar.sync %0,%1;" ::"r"(id), "r"(n) : "memory"); }
__device__ __forceinline__ void bar_arrive(int id, int n) { asm volatile("bar.arrive %0,%1;" ::"r"(id), "r"(n) : "memory"); }
__device__ __forceinline__ bool bar_red_or(int id, int n, bool v) {
  uint32_t r;
  asm volatile("{\n .reg .pred p, q;\n setp.ne.u32 q, %3, 0;\n barrier.cta.red.or.pred p, %1, %2, q;\n selp.u32 %0, 1, 0, p;\n}" : "=r"(r) : "r"(id), "r"(n), "r"((uint32_t)v) : "memory");
  return r != 0;
}
__device__ __forceinline__ void fence_async() { asm volatile("fence.proxy.async.shared::cta;" ::: "memory"); }
__device__ __forceinline__ void bulk_g2s(uint32_t dst, const void* src, uint32_t bytes, uint32_t bar) {
  asm volatile("cp.async.bulk.shared::cluster.global.mbarrier::complete_tx::bytes [%0],[%1],%2,[%3];" ::"r"(dst), "l"(src), "r"(bytes), "r"(bar) : "memory");
}
__device__ __forceinline__ void bulk_g2s_mc(uint32_t dst, const void* src, uint32_t bytes, uint32_t bar) {
  asm volatile("cp.async.bulk.shared::cluster.global.mbarrier::complete_tx::bytes.multicast::cluster [%0],[%1],%2,[%3],%4;"
               ::"r"(dst), "l"(src), "r"(bytes), "r"(bar), "h"((uint16_t)7) : "memory");
}
__device__ __forceinline__ void bulk_s2g(void* dst, uint32_t src, uint32_t bytes) {
  asm volatile("cp.async.bulk.global.shared::cta.bulk_group [%0],[%1],%2;" ::"l"(dst), "r"(src), "r"(bytes) : "memory");
}
__device__ __forceinline__ void bulk_s2c(uint32_t dst, uint32_t src, uint32_t bytes, uint32_t bar) {
  asm volatile("cp.async.bulk.shared::cluster.shared::cta.mbarrier::complete_tx::bytes [%0],[%1],%2,[%3];" ::"r"(dst), "r"(src), "r"(bytes), "r"(bar) : "memory");
}
__device__ __forceinline__ void tma2d(uint32_t dst, const CUtensorMap* tm, int c0, int c1, uint32_t bar) {
  asm volatile("cp.async.bulk.tensor.2d.shared::cluster.global.mbarrier::complete_tx::bytes [%0],[%1,{%3,%4}],[%2];"
               ::"r"(dst), "l"(tm), "r"(bar), "r"(c0), "r"(c1) : "memory");
}
__device__ __forceinline__ void tma2d_prefetch(const CUtensorMap* tm, int c0, int c1) {
  asm volatile("cp.async.bulk.prefetch.tensor.2d.L2.global.tile [%0,{%1,%2}];" ::"l"(tm), "r"(c0), "r"(c1) : "memory");
}
__device__ __forceinline__ uint32_t pack_bf16(float lo, float hi) {
  uint32_t r; asm("cvt.rn.bf16x2.f32 %0,%1,%2;" : "=r"(r) : "f"(hi), "f"(lo)); return r;
}
__device__ __forceinline__ float bf_lo(uint32_t x) { return __uint_as_float(x << 16); }
__device__ __forceinline__ float bf_hi(uint32_t x) { return __uint_as_float(x & 0xFFFF0000u); }
__device__ __forceinline__ float ex2(float x) { float y; asm("ex2.approx.ftz.f32 %0,%1;" : "=f"(y) : "f"(x)); return y; }
__device__ __forceinline__ void ldsm4(uint32_t (&r)[4], uint32_t a) {
  asm volatile("ldmatrix.sync.aligned.m8n8.x4.shared.b16 {%0,%1,%2,%3},[%4];" : "=r"(r[0]), "=r"(r[1]), "=r"(r[2]), "=r"(r[3]) : "r"(a) : "memory");
}
__device__ __forceinline__ void ldsm4t(uint32_t (&r)[4], uint32_t a) {
  asm volatile("ldmatrix.sync.aligned.m8n8.x4.trans.shared.b16 {%0,%1,%2,%3},[%4];" : "=r"(r[0]), "=r"(r[1]), "=r"(r[2]), "=r"(r[3]) : "r"(a) : "memory");
}
__device__ __forceinline__ void ldsm2(uint32_t& r0, uint32_t& r1, uint32_t a) {
  asm volatile("ldmatrix.sync.aligned.m8n8.x2.shared.b16 {%0,%1},[%2];" : "=r"(r0), "=r"(r1) : "r"(a) : "memory");
}
__device__ __forceinline__ void ldsm2t(uint32_t& r0, uint32_t& r1, uint32_t a) {
  asm volatile("ldmatrix.sync.aligned.m8n8.x2.trans.shared.b16 {%0,%1},[%2];" : "=r"(r0), "=r"(r1) : "r"(a) : "memory");
}
__device__ __forceinline__ void ldsm1(uint32_t& r0, uint32_t a) {
  asm volatile("ldmatrix.sync.aligned.m8n8.x1.shared.b16 {%0},[%1];" : "=r"(r0) : "r"(a) : "memory");
}
__device__ __forceinline__ void mma16816(float (&d)[4], uint32_t a0, uint32_t a1, uint32_t a2, uint32_t a3, uint32_t b0, uint32_t b1) {
  asm volatile("mma.sync.aligned.m16n8k16.row.col.f32.bf16.bf16.f32 {%0,%1,%2,%3},{%4,%5,%6,%7},{%8,%9},{%0,%1,%2,%3};"
               : "+f"(d[0]), "+f"(d[1]), "+f"(d[2]), "+f"(d[3]) : "r"(a0), "r"(a1), "r"(a2), "r"(a3), "r"(b0), "r"(b1));
}
__device__ __forceinline__ void mma1688(float (&d)[4], uint32_t a0, uint32_t a1, uint32_t b0) {
  asm volatile("mma.sync.aligned.m16n8k8.row.col.f32.bf16.bf16.f32 {%0,%1,%2,%3},{%4,%5},{%6},{%0,%1,%2,%3};"
               : "+f"(d[0]), "+f"(d[1]), "+f"(d[2]), "+f"(d[3]) : "r"(a0), "r"(a1), "r"(b0));
}
__device__ __forceinline__ void sts32(uint32_t a, uint32_t v) { asm volatile("st.shared.b32 [%0],%1;" ::"r"(a), "r"(v) : "memory"); }
__device__ __forceinline__ void sts64f(uint32_t a, float x, float y) { asm volatile("st.shared.v2.f32 [%0],{%1,%2};" ::"r"(a), "f"(x), "f"(y) : "memory"); }
__device__ __forceinline__ void sts128(uint32_t a, uint4 v) { asm volatile("st.shared.v4.b32 [%0],{%1,%2,%3,%4};" ::"r"(a), "r"(v.x), "r"(v.y), "r"(v.z), "r"(v.w) : "memory"); }
__device__ __forceinline__ float lds32f(uint32_t a) { float v; asm volatile("ld.shared.f32 %0,[%1];" : "=f"(v) : "r"(a) : "memory"); return v; }
__device__ __forceinline__ float2 lds64f(uint32_t a) { float2 v; asm volatile("ld.shared.v2.f32 {%0,%1},[%2];" : "=f"(v.x), "=f"(v.y) : "r"(a) : "memory"); return v; }
__device__ __forceinline__ uint4 lds128(uint32_t a) { uint4 v; asm volatile("ld.shared.v4.b32 {%0,%1,%2,%3},[%4];" : "=r"(v.x), "=r"(v.y), "=r"(v.z), "=r"(v.w) : "r"(a) : "memory"); return v; }
__device__ __forceinline__ float4 lds128f(uint32_t a) { float4 v; asm volatile("ld.shared.v4.f32 {%0,%1,%2,%3},[%4];" : "=f"(v.x), "=f"(v.y), "=f"(v.z), "=f"(v.w) : "r"(a) : "memory"); return v; }
__device__ __forceinline__ void st_async2(uint32_t a, float x, float y, uint32_t bar) {
  asm volatile("st.async.weak.shared::cluster.mbarrier::complete_tx::bytes.v2.f32 [%0],{%1,%2},[%3];" ::"r"(a), "f"(x), "f"(y), "r"(bar) : "memory");
}
__device__ __forceinline__ void st_async4(uint32_t a, const float (&v)[4], uint32_t bar) {
  asm volatile("st.async.weak.shared::cluster.mbarrier::complete_tx::bytes.v4.f32 [%0],{%1,%2,%3,%4},[%5];" ::"r"(a), "f"(v[0]), "f"(v[1]), "f"(v[2]), "f"(v[3]), "r"(bar) : "memory");
}
__device__ __forceinline__ void st_async4v(uint32_t a, float x, float y, float z, float w, uint32_t bar) {
  asm volatile("st.async.weak.shared::cluster.mbarrier::complete_tx::bytes.v4.f32 [%0],{%1,%2,%3,%4},[%5];" ::"r"(a), "f"(x), "f"(y), "f"(z), "f"(w), "r"(bar) : "memory");
}
__device__ __forceinline__ void st_async4u(uint32_t a, const uint4& v, uint32_t bar) {
  asm volatile("st.async.weak.shared::cluster.mbarrier::complete_tx::bytes.v4.b32 [%0],{%1,%2,%3,%4},[%5];" ::"r"(a), "r"(v.x), "r"(v.y), "r"(v.z), "r"(v.w), "r"(bar) : "memory");
}
__device__ __forceinline__ uint4 ld_relaxed4(const void* p) {
  uint4 v; asm volatile("ld.relaxed.gpu.global.v4.u32 {%0,%1,%2,%3},[%4];" : "=r"(v.x), "=r"(v.y), "=r"(v.z), "=r"(v.w) : "l"(p) : "memory"); return v;
}
__device__ __forceinline__ uint32_t ld_relaxed(const void* p) {
  uint32_t v; asm volatile("ld.relaxed.gpu.global.u32 %0,[%1];" : "=r"(v) : "l"(p) : "memory"); return v;
}
__device__ __forceinline__ void st_relaxed(void* p, uint32_t v) { asm volatile("st.relaxed.gpu.global.b32 [%0],%1;" ::"l"(p), "r"(v) : "memory"); }
__device__ __forceinline__ void st_relaxed4(void* p, uint32_t v) { asm volatile("st.relaxed.gpu.global.v4.b32 [%0],{%1,%1,%1,%1};" ::"l"(p), "r"(v) : "memory"); }

__device__ __forceinline__ uint32_t ld_acquire(const void* p) {
  uint32_t v; asm volatile("ld.acquire.gpu.global.u32 %0,[%1];" : "=r"(v) : "l"(p) : "memory"); return v;
}
__device__ __forceinline__ float4 ld_relaxed4f(const void* p) {
  float4 v; asm volatile("ld.relaxed.gpu.global.v4.f32 {%0,%1,%2,%3},[%4];" : "=f"(v.x), "=f"(v.y), "=f"(v.z), "=f"(v.w) : "l"(p) : "memory"); return v;
}
__device__ __forceinline__ float2 ld_relaxed2f(const void* p) {
  float2 v; asm volatile("ld.relaxed.gpu.global.v2.f32 {%0,%1},[%2];" : "=f"(v.x), "=f"(v.y) : "l"(p) : "memory"); return v;
}
__device__ __forceinline__ void prefetch_l2(const void* p) { asm volatile("prefetch.global.L2 [%0];" ::"l"(p)); }
__device__ __forceinline__ void fence_gpu() { asm volatile("fence.acq_rel.gpu;" ::: "memory"); }
__device__ __forceinline__ void fence_async_all() { asm volatile("fence.proxy.async.global;" ::: "memory"); }
constexpr int SPIN_TOT = 1 << 22;
__device__ __forceinline__ void csignal(int idx) { asm volatile("red.release.gpu.global.add.u32 [%0],1;" ::"l"(&g_cnt[idx][0]) : "memory"); }
__device__ __forceinline__ void csignal_fast(int idx) { asm volatile("red.relaxed.gpu.global.add.u32 [%0],1;" ::"l"(&g_cnt[idx][0]) : "memory"); }
#define RLX 1
#define csignal_t(idx, role) csignal(idx)
__device__ __forceinline__ void cwait(int idx, uint32_t target, int& spin) {
  while (ld_relaxed(&g_cnt[idx][0]) < target && spin < SPIN_TOT) spin += 16;
}

__device__ __forceinline__ uint64_t mkdesc(uint32_t addr, uint32_t lbo, uint32_t sbo) {
  return (uint64_t)((addr & 0x3FFFF) >> 4) | ((uint64_t)(lbo >> 4) << 16) | ((uint64_t)(sbo >> 4) << 32) | ((uint64_t)1 << 62);
}
__device__ __forceinline__ uint64_t mkdesc_ns(uint32_t addr, uint32_t lbo, uint32_t sbo) {
  return (uint64_t)((addr & 0x3FFFF) >> 4) | ((uint64_t)(lbo >> 4) << 16) | ((uint64_t)(sbo >> 4) << 32);
}
__device__ __forceinline__ void wg_fence() { asm volatile("wgmma.fence.sync.aligned;" ::: "memory"); }
__device__ __forceinline__ void wg_commit() { asm volatile("wgmma.commit_group.sync.aligned;" ::: "memory"); }
template <int N> __device__ __forceinline__ void wg_wait() { asm volatile("wgmma.wait_group.sync.aligned %0;" ::"n"(N) : "memory"); }

__device__ __forceinline__ void wgmma_rs16(float (&d)[8], const uint32_t (&a)[4], uint64_t db, int sc) {
  asm volatile("{.reg .pred p; setp.ne.b32 p,%13,0; wgmma.mma_async.sync.aligned.m64n16k16.f32.bf16.bf16 "
               "{%0,%1,%2,%3,%4,%5,%6,%7},{%8,%9,%10,%11},%12,p,1,1,0;}"
               : "+f"(d[0]), "+f"(d[1]), "+f"(d[2]), "+f"(d[3]), "+f"(d[4]), "+f"(d[5]), "+f"(d[6]), "+f"(d[7])
               : "r"(a[0]), "r"(a[1]), "r"(a[2]), "r"(a[3]), "l"(db), "r"(sc));
}
__device__ __forceinline__ void wgmma_rs64(float (&d)[32], const uint32_t (&a)[4], uint64_t db, int sc) {
  asm volatile("{.reg .pred p; setp.ne.b32 p,%37,0; wgmma.mma_async.sync.aligned.m64n64k16.f32.bf16.bf16 "
               "{%0,%1,%2,%3,%4,%5,%6,%7,%8,%9,%10,%11,%12,%13,%14,%15,%16,%17,%18,%19,%20,%21,%22,%23,%24,%25,%26,%27,%28,%29,%30,%31},{%32,%33,%34,%35},%36,p,1,1,0;}"
               : "+f"(d[0]), "+f"(d[1]), "+f"(d[2]), "+f"(d[3]), "+f"(d[4]), "+f"(d[5]), "+f"(d[6]), "+f"(d[7]), "+f"(d[8]), "+f"(d[9]), "+f"(d[10]), "+f"(d[11]), "+f"(d[12]), "+f"(d[13]), "+f"(d[14]), "+f"(d[15]), "+f"(d[16]), "+f"(d[17]), "+f"(d[18]), "+f"(d[19]), "+f"(d[20]), "+f"(d[21]), "+f"(d[22]), "+f"(d[23]), "+f"(d[24]), "+f"(d[25]), "+f"(d[26]), "+f"(d[27]), "+f"(d[28]), "+f"(d[29]), "+f"(d[30]), "+f"(d[31])
               : "r"(a[0]), "r"(a[1]), "r"(a[2]), "r"(a[3]), "l"(db), "r"(sc));
}
__device__ __forceinline__ void wgmma_rt16(float (&d)[8], const uint32_t (&a)[4], uint64_t db, int sc) {
  asm volatile("{.reg .pred p; setp.ne.b32 p,%13,0; wgmma.mma_async.sync.aligned.m64n16k16.f32.bf16.bf16 "
               "{%0,%1,%2,%3,%4,%5,%6,%7},{%8,%9,%10,%11},%12,p,1,1,1;}"
               : "+f"(d[0]), "+f"(d[1]), "+f"(d[2]), "+f"(d[3]), "+f"(d[4]), "+f"(d[5]), "+f"(d[6]), "+f"(d[7])
               : "r"(a[0]), "r"(a[1]), "r"(a[2]), "r"(a[3]), "l"(db), "r"(sc));
}
__device__ __forceinline__ void wgmma_rt80(float (&d)[40], const uint32_t (&a)[4], uint64_t db, int sc) {
  asm volatile("{.reg .pred p; setp.ne.b32 p,%45,0; wgmma.mma_async.sync.aligned.m64n80k16.f32.bf16.bf16 "
               "{%0,%1,%2,%3,%4,%5,%6,%7,%8,%9,%10,%11,%12,%13,%14,%15,%16,%17,%18,%19,%20,%21,%22,%23,%24,%25,%26,%27,%28,%29,%30,%31,%32,%33,%34,%35,%36,%37,%38,%39},{%40,%41,%42,%43},%44,p,1,1,1;}"
               : "+f"(d[0]), "+f"(d[1]), "+f"(d[2]), "+f"(d[3]), "+f"(d[4]), "+f"(d[5]), "+f"(d[6]), "+f"(d[7]), "+f"(d[8]), "+f"(d[9]), "+f"(d[10]), "+f"(d[11]), "+f"(d[12]), "+f"(d[13]), "+f"(d[14]), "+f"(d[15]), "+f"(d[16]), "+f"(d[17]), "+f"(d[18]), "+f"(d[19]), "+f"(d[20]), "+f"(d[21]), "+f"(d[22]), "+f"(d[23]), "+f"(d[24]), "+f"(d[25]), "+f"(d[26]), "+f"(d[27]), "+f"(d[28]), "+f"(d[29]), "+f"(d[30]), "+f"(d[31]), "+f"(d[32]), "+f"(d[33]), "+f"(d[34]), "+f"(d[35]), "+f"(d[36]), "+f"(d[37]), "+f"(d[38]), "+f"(d[39])
               : "r"(a[0]), "r"(a[1]), "r"(a[2]), "r"(a[3]), "l"(db), "r"(sc));
}
__device__ __forceinline__ void wgmma_rs32(float (&d)[16], const uint32_t (&a)[4], uint64_t db, int sc) {
  asm volatile("{.reg .pred p; setp.ne.b32 p,%21,0; wgmma.mma_async.sync.aligned.m64n32k16.f32.bf16.bf16 "
               "{%0,%1,%2,%3,%4,%5,%6,%7,%8,%9,%10,%11,%12,%13,%14,%15},{%16,%17,%18,%19},%20,p,1,1,0;}"
               : "+f"(d[0]), "+f"(d[1]), "+f"(d[2]), "+f"(d[3]), "+f"(d[4]), "+f"(d[5]), "+f"(d[6]), "+f"(d[7]), "+f"(d[8]), "+f"(d[9]), "+f"(d[10]), "+f"(d[11]), "+f"(d[12]), "+f"(d[13]), "+f"(d[14]), "+f"(d[15])
               : "r"(a[0]), "r"(a[1]), "r"(a[2]), "r"(a[3]), "l"(db), "r"(sc));
}
__device__ __forceinline__ void wgmma_ts32(float (&d)[16], uint64_t da, uint64_t db, int sc) {
  asm volatile("{.reg .pred p; setp.ne.b32 p,%18,0; wgmma.mma_async.sync.aligned.m64n32k16.f32.bf16.bf16 "
               "{%0,%1,%2,%3,%4,%5,%6,%7,%8,%9,%10,%11,%12,%13,%14,%15},%16,%17,p,1,1,1,0;}"
               : "+f"(d[0]), "+f"(d[1]), "+f"(d[2]), "+f"(d[3]), "+f"(d[4]), "+f"(d[5]), "+f"(d[6]), "+f"(d[7]), "+f"(d[8]), "+f"(d[9]), "+f"(d[10]), "+f"(d[11]), "+f"(d[12]), "+f"(d[13]), "+f"(d[14]), "+f"(d[15])
               : "l"(da), "l"(db), "r"(sc));
}
__device__ __forceinline__ void wgmma_rs8(float (&d)[4], const uint32_t (&a)[4], uint64_t db, int sc) {
  asm volatile("{.reg .pred p; setp.ne.b32 p,%9,0; wgmma.mma_async.sync.aligned.m64n8k16.f32.bf16.bf16 "
               "{%0,%1,%2,%3},{%4,%5,%6,%7},%8,p,1,1,0;}"
               : "+f"(d[0]), "+f"(d[1]), "+f"(d[2]), "+f"(d[3])
               : "r"(a[0]), "r"(a[1]), "r"(a[2]), "r"(a[3]), "l"(db), "r"(sc));
}
__device__ __forceinline__ void wgmma_tt32(float (&d)[16], uint64_t da, uint64_t db, int sc) {
  asm volatile("{.reg .pred p; setp.ne.b32 p,%18,0; wgmma.mma_async.sync.aligned.m64n32k16.f32.bf16.bf16 "
               "{%0,%1,%2,%3,%4,%5,%6,%7,%8,%9,%10,%11,%12,%13,%14,%15},%16,%17,p,1,1,1,1;}"
               : "+f"(d[0]), "+f"(d[1]), "+f"(d[2]), "+f"(d[3]), "+f"(d[4]), "+f"(d[5]), "+f"(d[6]), "+f"(d[7]), "+f"(d[8]), "+f"(d[9]), "+f"(d[10]), "+f"(d[11]), "+f"(d[12]), "+f"(d[13]), "+f"(d[14]), "+f"(d[15])
               : "l"(da), "l"(db), "r"(sc));
}
__device__ __forceinline__ void wgmma_ts16(float (&d)[8], uint64_t da, uint64_t db, int sc) {
  asm volatile("{.reg .pred p; setp.ne.b32 p,%10,0; wgmma.mma_async.sync.aligned.m64n16k16.f32.bf16.bf16 "
               "{%0,%1,%2,%3,%4,%5,%6,%7},%8,%9,p,1,1,1,0;}"
               : "+f"(d[0]), "+f"(d[1]), "+f"(d[2]), "+f"(d[3]), "+f"(d[4]), "+f"(d[5]), "+f"(d[6]), "+f"(d[7])
               : "l"(da), "l"(db), "r"(sc));
}
__device__ __forceinline__ void wgmma_ts64(float (&d)[32], uint64_t da, uint64_t db, int sc) {
  asm volatile("{.reg .pred p; setp.ne.b32 p,%34,0; wgmma.mma_async.sync.aligned.m64n64k16.f32.bf16.bf16 "
               "{%0,%1,%2,%3,%4,%5,%6,%7,%8,%9,%10,%11,%12,%13,%14,%15,%16,%17,%18,%19,%20,%21,%22,%23,%24,%25,%26,%27,%28,%29,%30,%31},%32,%33,p,1,1,1,0;}"
               : "+f"(d[0]), "+f"(d[1]), "+f"(d[2]), "+f"(d[3]), "+f"(d[4]), "+f"(d[5]), "+f"(d[6]), "+f"(d[7]), "+f"(d[8]), "+f"(d[9]), "+f"(d[10]), "+f"(d[11]), "+f"(d[12]), "+f"(d[13]), "+f"(d[14]), "+f"(d[15]), "+f"(d[16]), "+f"(d[17]), "+f"(d[18]), "+f"(d[19]), "+f"(d[20]), "+f"(d[21]), "+f"(d[22]), "+f"(d[23]), "+f"(d[24]), "+f"(d[25]), "+f"(d[26]), "+f"(d[27]), "+f"(d[28]), "+f"(d[29]), "+f"(d[30]), "+f"(d[31])
               : "l"(da), "l"(db), "r"(sc));
}
__device__ __forceinline__ void wgmma_tt16(float (&d)[8], uint64_t da, uint64_t db, int sc) {
  asm volatile("{.reg .pred p; setp.ne.b32 p,%10,0; wgmma.mma_async.sync.aligned.m64n16k16.f32.bf16.bf16 "
               "{%0,%1,%2,%3,%4,%5,%6,%7},%8,%9,p,1,1,1,1;}"
               : "+f"(d[0]), "+f"(d[1]), "+f"(d[2]), "+f"(d[3]), "+f"(d[4]), "+f"(d[5]), "+f"(d[6]), "+f"(d[7])
               : "l"(da), "l"(db), "r"(sc));
}
__device__ __forceinline__ void wgmma_tt40(float (&d)[20], uint64_t da, uint64_t db, int sc) {
  asm volatile("{.reg .pred p; setp.ne.b32 p,%22,0; wgmma.mma_async.sync.aligned.m64n40k16.f32.bf16.bf16 "
               "{%0,%1,%2,%3,%4,%5,%6,%7,%8,%9,%10,%11,%12,%13,%14,%15,%16,%17,%18,%19},%20,%21,p,1,1,1,1;}"
               : "+f"(d[0]), "+f"(d[1]), "+f"(d[2]), "+f"(d[3]), "+f"(d[4]), "+f"(d[5]), "+f"(d[6]), "+f"(d[7]), "+f"(d[8]), "+f"(d[9]), "+f"(d[10]), "+f"(d[11]), "+f"(d[12]), "+f"(d[13]), "+f"(d[14]), "+f"(d[15]), "+f"(d[16]), "+f"(d[17]), "+f"(d[18]), "+f"(d[19])
               : "l"(da), "l"(db), "r"(sc));
}
__device__ __forceinline__ void wgmma_ss8(float (&d)[4], uint64_t da, uint64_t db, int sc) {
  asm volatile("{.reg .pred p; setp.ne.b32 p,%6,0; wgmma.mma_async.sync.aligned.m64n8k16.f32.bf16.bf16 "
               "{%0,%1,%2,%3},%4,%5,p,1,1,0,0;}"
               : "+f"(d[0]), "+f"(d[1]), "+f"(d[2]), "+f"(d[3])
               : "l"(da), "l"(db), "r"(sc));
}
__device__ __forceinline__ void wgmma_ss32(float (&d)[16], uint64_t da, uint64_t db, int sc) {
  asm volatile("{.reg .pred p; setp.ne.b32 p,%18,0; wgmma.mma_async.sync.aligned.m64n32k16.f32.bf16.bf16 "
               "{%0,%1,%2,%3,%4,%5,%6,%7,%8,%9,%10,%11,%12,%13,%14,%15},%16,%17,p,1,1,0,0;}"
               : "+f"(d[0]), "+f"(d[1]), "+f"(d[2]), "+f"(d[3]), "+f"(d[4]), "+f"(d[5]), "+f"(d[6]), "+f"(d[7]), "+f"(d[8]), "+f"(d[9]), "+f"(d[10]), "+f"(d[11]), "+f"(d[12]), "+f"(d[13]), "+f"(d[14]), "+f"(d[15])
               : "l"(da), "l"(db), "r"(sc));
}
__device__ __forceinline__ void wgmma_st64(float (&d)[32], uint64_t da, uint64_t db, int sc) {
  asm volatile("{.reg .pred p; setp.ne.b32 p,%34,0; wgmma.mma_async.sync.aligned.m64n64k16.f32.bf16.bf16 "
               "{%0,%1,%2,%3,%4,%5,%6,%7,%8,%9,%10,%11,%12,%13,%14,%15,%16,%17,%18,%19,%20,%21,%22,%23,%24,%25,%26,%27,%28,%29,%30,%31},%32,%33,p,1,1,0,1;}"
               : "+f"(d[0]), "+f"(d[1]), "+f"(d[2]), "+f"(d[3]), "+f"(d[4]), "+f"(d[5]), "+f"(d[6]), "+f"(d[7]), "+f"(d[8]), "+f"(d[9]), "+f"(d[10]), "+f"(d[11]), "+f"(d[12]), "+f"(d[13]), "+f"(d[14]), "+f"(d[15]), "+f"(d[16]), "+f"(d[17]), "+f"(d[18]), "+f"(d[19]), "+f"(d[20]), "+f"(d[21]), "+f"(d[22]), "+f"(d[23]), "+f"(d[24]), "+f"(d[25]), "+f"(d[26]), "+f"(d[27]), "+f"(d[28]), "+f"(d[29]), "+f"(d[30]), "+f"(d[31])
               : "l"(da), "l"(db), "r"(sc));
}
__device__ __forceinline__ void wgmma_st128(float (&d)[64], uint64_t da, uint64_t db, int sc) {
  asm volatile("{.reg .pred p; setp.ne.b32 p,%66,0; wgmma.mma_async.sync.aligned.m64n128k16.f32.bf16.bf16 "
               "{%0,%1,%2,%3,%4,%5,%6,%7,%8,%9,%10,%11,%12,%13,%14,%15,%16,%17,%18,%19,%20,%21,%22,%23,%24,%25,%26,%27,%28,%29,%30,%31,%32,%33,%34,%35,%36,%37,%38,%39,%40,%41,%42,%43,%44,%45,%46,%47,%48,%49,%50,%51,%52,%53,%54,%55,%56,%57,%58,%59,%60,%61,%62,%63},%64,%65,p,1,1,0,1;}"
               : "+f"(d[0]), "+f"(d[1]), "+f"(d[2]), "+f"(d[3]), "+f"(d[4]), "+f"(d[5]), "+f"(d[6]), "+f"(d[7]), "+f"(d[8]), "+f"(d[9]), "+f"(d[10]), "+f"(d[11]), "+f"(d[12]), "+f"(d[13]), "+f"(d[14]), "+f"(d[15]), "+f"(d[16]), "+f"(d[17]), "+f"(d[18]), "+f"(d[19]), "+f"(d[20]), "+f"(d[21]), "+f"(d[22]), "+f"(d[23]), "+f"(d[24]), "+f"(d[25]), "+f"(d[26]), "+f"(d[27]), "+f"(d[28]), "+f"(d[29]), "+f"(d[30]), "+f"(d[31]), "+f"(d[32]), "+f"(d[33]), "+f"(d[34]), "+f"(d[35]), "+f"(d[36]), "+f"(d[37]), "+f"(d[38]), "+f"(d[39]), "+f"(d[40]), "+f"(d[41]), "+f"(d[42]), "+f"(d[43]), "+f"(d[44]), "+f"(d[45]), "+f"(d[46]), "+f"(d[47]), "+f"(d[48]), "+f"(d[49]), "+f"(d[50]), "+f"(d[51]), "+f"(d[52]), "+f"(d[53]), "+f"(d[54]), "+f"(d[55]), "+f"(d[56]), "+f"(d[57]), "+f"(d[58]), "+f"(d[59]), "+f"(d[60]), "+f"(d[61]), "+f"(d[62]), "+f"(d[63])
               : "l"(da), "l"(db), "r"(sc));
}

__device__ __forceinline__ void stsm4(uint32_t a, uint32_t r0, uint32_t r1, uint32_t r2, uint32_t r3) {
  asm volatile("stmatrix.sync.aligned.m8n8.x4.shared.b16 [%0],{%1,%2,%3,%4};" ::"r"(a), "r"(r0), "r"(r1), "r"(r2), "r"(r3) : "memory");
}
__device__ __forceinline__ void stsm4t(uint32_t a, uint32_t r0, uint32_t r1, uint32_t r2, uint32_t r3) {
  asm volatile("stmatrix.sync.aligned.m8n8.x4.trans.shared.b16 [%0],{%1,%2,%3,%4};" ::"r"(a), "r"(r0), "r"(r1), "r"(r2), "r"(r3) : "memory");
}
__device__ __forceinline__ void stsm2t(uint32_t a, uint32_t r0, uint32_t r1) {
  asm volatile("stmatrix.sync.aligned.m8n8.x2.trans.shared.b16 [%0],{%1,%2};" ::"r"(a), "r"(r0), "r"(r1) : "memory");
}
__device__ __forceinline__ void sts64(uint32_t a, uint32_t x, uint32_t y) { asm volatile("st.shared.v2.b32 [%0],{%1,%2};" ::"r"(a), "r"(x), "r"(y) : "memory"); }
__device__ __forceinline__ void st_async2u(uint32_t a, uint32_t x, uint32_t y, uint32_t bar) {
  asm volatile("st.async.weak.shared::cluster.mbarrier::complete_tx::bytes.v2.b32 [%0],{%1,%2},[%3];" ::"r"(a), "r"(x), "r"(y), "r"(bar) : "memory");
}
__device__ __forceinline__ void st_relaxed128(void* p, uint32_t x, uint32_t y, uint32_t z, uint32_t w) {
  asm volatile("{.reg .b128 v; mov.b128 v,{%1,%2,%3,%4}; st.relaxed.gpu.global.b128 [%0],v;}" ::"l"(p), "r"(x), "r"(y), "r"(z), "r"(w) : "memory");
}
__device__ __forceinline__ void st_relaxed64(void* p, uint32_t x, uint32_t y) {
  asm volatile("{.reg .b64 v; mov.b64 v,{%1,%2}; st.relaxed.gpu.global.b64 [%0],v;}" ::"l"(p), "r"(x), "r"(y) : "memory");
}
__device__ __forceinline__ uint4 ld_relaxed128(const void* p) {
  uint4 v;
  asm volatile("{.reg .b128 v; .reg .b64 lo, hi; ld.relaxed.gpu.global.b128 v,[%4]; mov.b128 {lo,hi},v; mov.b64 {%0,%1},lo; mov.b64 {%2,%3},hi;}" : "=r"(v.x), "=r"(v.y), "=r"(v.z), "=r"(v.w) : "l"(p) : "memory");
  return v;
}

__device__ __forceinline__ uint32_t pack_h2(float lo, float hi) {
  uint32_t r; asm("cvt.rn.satfinite.f16x2.f32 %0,%1,%2;" : "=r"(r) : "f"(hi), "f"(lo)); return r;
}
__device__ __forceinline__ void add_h2(float& lo, float& hi, uint32_t u, uint32_t v) {
  float a, b;
  asm("{.reg .b16 l, h; .reg .b32 s; add.rn.f16x2 s,%2,%3; mov.b32 {l,h},s; cvt.f32.f16 %0,l; cvt.f32.f16 %1,h;}" : "=f"(a), "=f"(b) : "r"(u), "r"(v));
  lo += a; hi += b;
}
__device__ __forceinline__ void mwait(uint32_t bar, uint32_t ph, int& spin) {
  asm volatile("{.reg .pred p, q;\nWAIT_LOOP:\n add.s32 %0,%0,1;\n setp.lt.s32 q,%0,%3;\n mbarrier.try_wait.parity.shared::cta.b64 p,[%1],%2;\n not.pred p,p;\n and.pred q,q,p;\n @q bra.uni WAIT_LOOP;\n}"
               : "+&r"(spin) : "r"(bar), "r"(ph), "n"(SPIN_TOT) : "memory");
}
__device__ __forceinline__ int keep(int x) { return __shfl_sync(0xffffffffu, x, threadIdx.x & 31); }
__device__ __forceinline__ uint32_t pin(uint32_t x) { asm volatile("" : "+r"(x)); return x; }
template <typename T> __device__ __forceinline__ T* pinp(T* x) { asm volatile("" : "+l"(x)); return x; }
__device__ __forceinline__ void st_async1u(uint32_t a, uint32_t x, uint32_t bar) {
  asm volatile("st.async.weak.shared::cluster.mbarrier::complete_tx::bytes.b32 [%0],%1,[%2];" ::"r"(a), "r"(x), "r"(bar) : "memory");
}
__device__ __forceinline__ uint32_t lds32(uint32_t a) { uint32_t v; asm volatile("ld.shared.b32 %0,[%1];" : "=r"(v) : "r"(a) : "memory"); return v; }
__device__ __forceinline__ uint2 lds64(uint32_t a) { uint2 v; asm volatile("ld.shared.v2.b32 {%0,%1},[%2];" : "=r"(v.x), "=r"(v.y) : "r"(a) : "memory"); return v; }

__device__ __forceinline__ void permute_cols(uint32_t tile, int tid, int n) {
#pragma unroll 2
  for (int it = tid; it < n; it += 128) {
    const int row = it >> 2, q = it & 3;
    const uint32_t a0 = tile + row * 128 + (((2 * q) ^ (row & 7)) << 4), a1 = tile + row * 128 + (((2 * q + 1) ^ (row & 7)) << 4);
    const uint4 u = lds128(a0), v = lds128(a1);
    sts128(a0, make_uint4(__byte_perm(u.x, u.y, 0x5410), __byte_perm(u.z, u.w, 0x5410), __byte_perm(v.x, v.y, 0x5410), __byte_perm(v.z, v.w, 0x5410)));
    sts128(a1, make_uint4(__byte_perm(u.x, u.y, 0x7632), __byte_perm(u.z, u.w, 0x7632), __byte_perm(v.x, v.y, 0x7632), __byte_perm(v.z, v.w, 0x7632)));
  }
}

__device__ __forceinline__ uint8_t* mkptr(uint32_t lo, uint32_t hi) { uint8_t* p; asm("mov.b64 %0,{%1,%2};" : "=l"(p) : "r"(lo), "r"(hi)); return p; }
__device__ __forceinline__ int uni(int x) { return __shfl_sync(0xffffffffu, x, 0); }

__device__ __forceinline__ bool elect_one() {
  uint32_t p; asm volatile("{.reg .pred q; elect.sync _|q, 0xffffffff; selp.u32 %0,1,0,q;}" : "=r"(p)); return p;
}
__device__ __forceinline__ uint64_t desc_at(uint64_t d, uint32_t off) {
  uint64_t r; asm("mov.b64 %0,{%1,%2};" : "=l"(r) : "r"((uint32_t)d + (off >> 4)), "r"((uint32_t)(d >> 32))); return r;
}
__device__ __forceinline__ uint32_t scale_bf16x2(uint32_t x, uint32_t s) { uint32_t r; asm("mul.rn.bf16x2 %0,%1,%2;" : "=r"(r) : "r"(x), "r"(s)); return r; }

__device__ __forceinline__ void stg128(void* p, const uint4& v) { asm volatile("st.global.v4.b32 [%0],{%1,%2,%3,%4};" ::"l"(p), "r"(v.x), "r"(v.y), "r"(v.z), "r"(v.w) : "memory"); }

__device__ __forceinline__ float quad_sum(float x) {
  const float a = __shfl_xor_sync(0xffffffffu, x, 1), b = __shfl_xor_sync(0xffffffffu, x, 2), c = __shfl_xor_sync(0xffffffffu, x, 3);
  return (x + a) + (b + c);
}
__device__ __forceinline__ float warp_sum(float x) {
  const uint32_t m = __reduce_max_sync(0xffffffffu, __float_as_uint(x) & 0x7FFFFFFFu), e = max(m >> 23, 25u);
  const int s = __reduce_add_sync(0xffffffffu, __float2int_rn(x * __uint_as_float((278 - e) << 23)));
  return fmaf(__uint_as_float(m), 0.f, (float)s * __uint_as_float((e - 24) << 23));
}
__device__ __forceinline__ void ln_row(float4 (&v)[5]) {
  float t0 = 0.f, t1 = 0.f;
#pragma unroll
  for (int m = 0; m < 5; m++) { t0 += v[m].x + v[m].y; t1 += v[m].z + v[m].w; }
  const float mean = warp_sum(t0 + t1) * (1.f / DM);
  float q0 = 0.f, q1 = 0.f, q2 = 0.f, q3 = 0.f;
#pragma unroll
  for (int m = 0; m < 5; m++) {
    v[m].x -= mean; v[m].y -= mean; v[m].z -= mean; v[m].w -= mean;
    q0 = fmaf(v[m].x, v[m].x, q0); q1 = fmaf(v[m].y, v[m].y, q1); q2 = fmaf(v[m].z, v[m].z, q2); q3 = fmaf(v[m].w, v[m].w, q3);
  }
  const float rs = rsqrtf(warp_sum((q0 + q1) + (q2 + q3)) * (1.f / DM) + 1e-5f);
#pragma unroll
  for (int m = 0; m < 5; m++) { v[m].x *= rs; v[m].y *= rs; v[m].z *= rs; v[m].w *= rs; }
}
__device__ __forceinline__ void ln0_load(const bf16* __restrict__ x, uint2 (&u)[5], int row, int lane) {
#pragma unroll
  for (int m = 0; m < 5; m++) u[m] = *reinterpret_cast<const uint2*>(x + (size_t)row * DM + m * 128 + lane * 4);
}
__device__ __forceinline__ void ln0_copy(const uint2 (&u)[5], int row, int lane) {
#pragma unroll
  for (int m = 0; m < 5; m++) stg128(g_x + (size_t)row * DM + m * 128 + lane * 4, make_uint4(u[m].x << 16, u[m].x & 0xFFFF0000u, u[m].y << 16, u[m].y & 0xFFFF0000u));
}
__device__ __forceinline__ void ln0_row(const uint2 (&u)[5], int row, int lane) {
  float4 v[5];
#pragma unroll
  for (int m = 0; m < 5; m++) v[m] = make_float4(bf_lo(u[m].x), bf_hi(u[m].x), bf_lo(u[m].y), bf_hi(u[m].y));
  ln_row(v);
  uint8_t* dst = g_xn[row >> 5] + ((row >> 3) & 3) * 4096 + (lane >> 4) * 1024 + (row & 7) * 128 + ((((lane >> 1) ^ row) & 7) << 4) + (lane & 1) * 8;
#pragma unroll
  for (int m = 0; m < 5; m++) *reinterpret_cast<uint2*>(dst + m * 16384) = make_uint2(pack_bf16(v[m].x, v[m].y), pack_bf16(v[m].z, v[m].w));
}

#define NOWORK 0
__device__ __forceinline__ void prep_row(const uint2 (&u)[5], const bf16* __restrict__ mem0, int k, int r, int lane) {
  const uint4 sent = make_uint4(SENT, SENT, SENT, SENT);
  if (k + 1 < NSTEP) {
    uint8_t* ex = ex_window(g_ex);
#pragma unroll
    for (int h = 0; h < 2; h++) {
      const int p = r * 40 + h * 32 + lane;
      if (h == 0 || lane < 8) {
        uint4 v = sent;
        if (k + 1 == LAG && (p & 8)) v = *reinterpret_cast<const uint4*>(mem0 + (p & 7) * DM + (p >> 4) * 8);
        stg128(ex + EX_M + (k + 1) * 20480 + p * 16, v);
      } else if (lane < 14) stg128(ex + EX_FLAG + (k + 1) * 3072 + (r * 6 + lane - 8) * 16, sent);
    }
  }
  if (k < LAG || k >= NSEG || NOWORK) {
    uint8_t* z = g_xn[k] + (r >> 3) * 4096 + (k < NSEG ? 2048 : 0) + (lane >> 4) * 1024 + (r & 7) * 128 + (lane & 15) * 8;
#pragma unroll
    for (int m = 0; m < 5; m++) *reinterpret_cast<uint2*>(z + m * 16384) = make_uint2(0, 0);
  }
  if (k < NSEG) {
    ln0_copy(u, k * 32 + r, lane);
    ln0_row(u, k * 32 + r, lane);
  }
}
__device__ __forceinline__ void pre_work(const bf16* __restrict__ x, const bf16* __restrict__ mem0, int cta, int tid) {
  constexpr int NT = 96 * 128;
  const int gt = cta * 128 + tid;
  uint8_t* ex = ex_window(g_ex);
#pragma unroll 1
  for (int row = cta + 96 * (tid >> 5); row < (NOWORK == 2 ? NSTEP : NPRE) * 32; row += 384) {
    uint2 u[5];
    ln0_load(x, u, min(row, SEQ - 1), tid & 31);
    prep_row(u, mem0, row >> 5, row & 31, tid & 31);
  }
#pragma unroll 1
  for (int i = gt; i < MAIL_BYTES / 16; i += NT) {
    stg128(ex + EX_MAIL + i * 16, make_uint4(SENT, SENT, SENT, SENT));
    stg128(ex + EX_MAIL + (1 << 20) + i * 16, make_uint4(SENT, SENT, SENT, SENT));
  }
  const int p = NT - 1 - gt;
  if (p < 1280) stg128(ex + EX_M + p * 16, *reinterpret_cast<const uint4*>(mem0 + (p & 7) * DM + (p >> 4) * 8));
  if (p < 192) stg128(ex + EX_FLAG + p * 16, make_uint4(0, 0, 0, 0));
  if (gt < 8 * CN_NUM) stg128(&g_cnt[0][0] + gt * 4, make_uint4(0, 0, 0, 0));
}
__device__ __forceinline__ void pre_wait(int which, uint32_t n, int& spin) {
  uint32_t old;
  asm volatile("atom.acq_rel.gpu.global.add.u32 %0,[%1],1;" : "=r"(old) : "l"(&g_ticket[which][0]) : "memory");
  const uint32_t target = (old / n + 1) * 96;
  while ((int)(ld_acquire(&g_ticket[0][0]) - target) < 0 && spin < SPIN_TOT) spin += 16;
  fence_async_all();
}

namespace C {
constexpr int NKR = 37;
constexpr int OFF_WQ = 0, OFF_WK = 81920;
constexpr int OFF_YO = 163840, OFF_YV = OFF_YO + 6144;
constexpr int OFF_M = 176128;
__host__ __device__ constexpr int og_off(int c) { return c ? OFF_M + 14336 + c * 2048 : 229376; }
constexpr int OFF_KT = 196608;
constexpr int OFF_XT = OFF_KT + 10240;
constexpr int OFF_VT = OFF_XT + 7168;
constexpr int OFF_XM = OFF_VT + 11392;
constexpr int OFF_PT = OFF_XM + 2560;
constexpr int KS = 1280, VS = 1408;
__host__ __device__ constexpr int slot_off(int p) { return p == 2 ? OFF_M : OFF_KT + (p % 3) * 16384; }
constexpr int OFF_ONE = 231424;
constexpr int OFF_BAR = 231552;
constexpr int OFF_SAFE = OFF_BAR + 144;
constexpr int OFF_TS = OFF_BAR + 256;
constexpr int SMEM = 232448;
constexpr uint32_t SB0 = 1024;
constexpr int BAR_F = OFF_BAR, BAR_XM = BAR_F + 40, BAR_XT = BAR_F + 48, BAR_OG = BAR_F + 56, BAR_E = OFF_BAR + 64, BAR_MOK = BAR_E + 40,
              BAR_M = OFF_BAR + 112, BAR_XF = OFF_BAR + 120, BAR_MF = OFF_BAR + 128, BAR_W = OFF_BAR + 208;
constexpr int NB_PRO = 1, NB_RD = 2, NB_MR = 3, NB_QK = 4, NB_SM = 5, NB_VA = 6, NB_VQ = 7, NB_A = 8, NB_Q = 9, NB_C = 10, NB_WQ = 11, NB_SI = 13, NB_WV = 14, NB_V = 15;
#define B1 600
#define AD0 16
#define AD1 128
#define AD2 16
#define AD3 128
#define BMX 1200
#define B2 800
#define FLP 2
#define OSG 2
#define OST 7
#define NBX 1
#define PVB 2
#define QPV 0
#define ONES 0
#define E0L 0
#define E2L 0
#define T2E 1
#define XMB 0
#define B3 0
#define OSV 0
#define XTD 0
#define VSL 2
#define VTI 4
#define T9L 0
#define P1U 4
#define SIE 2
#define WOE 1
#define OGF 2
#define VSP 8
#define RFK 5
#define PFD 3
#define WOL 0
constexpr uint32_t SCQ = 0x3A003A00;
constexpr float SCE = 0.07216878364870322f * 1.4426950408889634f * 2048;
}

#define CBAR_SYNC(id, n) bar_sync(id, n)
#define CBAR_ARRIVE(id, n) bar_arrive(id, n)

__device__ __forceinline__ uint64_t wdesc(int off) { return mkdesc(C::SB0 + off, 8192, 1024); }
__device__ __forceinline__ uint64_t mdesc(int k) { return mkdesc_ns(C::SB0 + C::OFF_M + k * 512, 256, 128); }
__device__ __forceinline__ uint64_t tdesc(int k) { return mkdesc(C::SB0 + C::slot_off(k >> 3) + ((k >> 2) & 1) * 1024 + (k & 3) * 32, 16, 2048); }

__device__ __forceinline__ int dh_row(int n) { return (n & ~63) + (n & 32) + ((n >> 1) & 3) * 8 + ((n >> 3) & 3) * 2 + (n & 1); }
template <bool IS_O>
__device__ __forceinline__ void stage_box(const CUtensorMap& tm, uint32_t sb, int p, int cta, int rank) {
  using namespace C;
  const uint32_t bar = sb + BAR_W + 8 * p;
  const int head = cta / 3, col = head * DH + rank * 64;
  mbar_expect_tx(bar, 16384);
  if (!IS_O) tma2d(sb + OFF_WK + p * 16384, &tm, col, p * 128, bar);
  else for (int b = 2 * p - 1; b <= 2 * p; b++)
    tma2d(sb + OFF_WQ + (b + 1) * 8192, &tm, b < 0 ? 576 : (3 * rank + b / 3) * 64, b < 0 ? col : head * DH + ((rank + b) % 3) * 64, bar);
}
template <bool IS_O>
__device__ __forceinline__ void load_weights_rs(uint32_t (&wf)[C::NKR][4], const CUtensorMap& tms, const CUtensorMap& tm, int cta, int rank, uint32_t sb, int tid0, int& spin) {
  using namespace C;
  constexpr int STAGE = IS_O ? OFF_WQ : OFF_WK, YOFF = IS_O ? OFF_YO : OFF_YV, NB = IS_O ? NB_C : NB_V;
  const int i = (tid0 >> 3) & 3, n0 = (tid0 & 7) + (i >> 1) * 8;
  const int chunk = 2 * ((tid0 >> 5) & 3) + (i & 1);
  const int r0 = IS_O ? dh_row(n0) : n0, r1 = IS_O ? dh_row(n0 + 16) : n0 + 16;
  const uint32_t a0 = sb + STAGE + r0 * 128 + ((chunk ^ (r0 & 7)) << 4), a1 = sb + STAGE + r1 * 128 + ((chunk ^ (r1 & 7)) << 4);
#pragma unroll
  for (int p = 0; p < 5; p++) {
    mwait(sb + BAR_W + 8 * p, 0, spin);
    if (IS_O) PTS(8 + p);
    if (p + NBX < 5) { if ((tid0 & 127) == 96) stage_box<IS_O>(tms, sb, p + NBX, cta, rank); __syncwarp(); }
    if (IS_O) permute_cols(sb + STAGE + p * 16384, tid0, 512);
    else {
#pragma unroll 1
      for (int it = tid0 & 127; it < 256; it += 128) {
        const uint32_t base = sb + STAGE + p * 16384 + (it >> 1) * 128;
        const int sw = ((it >> 1) & 7) ^ ((it & 1) * 4);
        const uint4 u0 = lds128(base + (sw << 4)), u1 = lds128(base + ((sw ^ 1) << 4)), u2 = lds128(base + ((sw ^ 2) << 4)), u3 = lds128(base + ((sw ^ 3) << 4));
        sts128(base + (sw << 4), make_uint4(u0.x, u1.x, u2.x, u3.x)); sts128(base + ((sw ^ 1) << 4), make_uint4(u0.y, u1.y, u2.y, u3.y));
        sts128(base + ((sw ^ 2) << 4), make_uint4(u0.z, u1.z, u2.z, u3.z)); sts128(base + ((sw ^ 3) << 4), make_uint4(u0.w, u1.w, u2.w, u3.w));
      }
    }
    bar_sync(NB, 128);
#pragma unroll
    for (int k = 8 * p; k < 8 * p + 8; k++) {
      if (k < NKR) ldsm4t(wf[k < NKR ? k : 0], ((k & 1) ? a1 : a0) + (k >> 1) * 4096);
      else {
        const int n = k * 16 + ((tid0 & 127) >> 3), r = IS_O ? dh_row(n) : n, c = tid0 & 7;
        sts128(sb + YOFF + (n - NKR * 16) * 128 + ((c ^ (n & 7)) << 4), lds128(sb + STAGE + r * 128 + ((c ^ (r & 7)) << 4)));
      }
    }
    fence_async();
    bar_sync(NB, 128);
    if ((tid0 & 127) == 0) {
      mbar_expect_tx(sb + BAR_W + 8 * p, 16384);
      tma2d(sb + STAGE + p * 16384, &tm, (cta / 3) * DH + rank * 64, p * 128, sb + BAR_W + 8 * p);
    }
    __syncwarp();
  }
  PTS(IS_O ? 13 : 14);
  CBAR_SYNC(NB_PRO, 384);
}

__device__ __forceinline__ void load_pair(uint32_t sb, int i, int p, uint32_t slot, uint32_t ph, int& spin) {
  using namespace C;
  mwait(sb + BAR_E + 8 * p, ph, spin);
  if (elect_one()) bulk_g2s_mc(sb + slot, g_xn[i] + p * 16384, 16384, sb + BAR_F + 8 * p);
}
__device__ __forceinline__ void release_round(uint32_t sb, int p, int lane) {
  if (lane < (p == 2 ? 3 : 1)) mbar_arrive_cluster(mapa(sb, p == 2 ? lane : p) + C::BAR_E + 8 * (3 + p));
}

__device__ __forceinline__ void signal_o(int i, int cta) { csignal(CN_O + i * 5 + min(cta / 19, 4)); }

template <int K0, int K1>
__device__ __forceinline__ void v_mem_pass(float (&d)[8], const uint32_t (&wf)[C::NKR][4]) {
  using namespace C;
#pragma unroll
  for (int k = K0; k < K1; k++) {
    if (k < NKR) wgmma_rs16(d, wf[k < NKR ? k : 0], mdesc(k), k != 32);
    else wgmma_ts16(d, wdesc(OFF_YV + (k - NKR) * 2048), mdesc(k), 1);
  }
  wg_commit();
}
__device__ __forceinline__ void chain_v(const CUtensorMap& tmWv, const CUtensorMap& tmWk, const uint32_t sb, const int tid0, const int cta, const int rank) {
  using namespace C;
  asm volatile("setmaxnreg.inc.sync.aligned.u32 208;");
  int spin = 0;
  uint32_t wf[NKR][4];
  const int wu = uni((tid0 >> 5) & 3);
  const uint32_t slot = rank == 2 ? OFF_M : OFF_KT + rank * 16384;
  load_weights_rs<false>(wf, tmWv, tmWk, cta, rank, sb, tid0, spin);
  PTS(5);
#pragma unroll 1
  for (int i = 0; i < NSTEP; i++) {
    uint32_t vp[16], va;
#define STORE_V { _Pragma("unroll") for (int s = 0; s < 4; s++) stsm4(va + 128 + s * 128, vp[4 * s], vp[4 * s + 1], vp[4 * s + 2], vp[4 * s + 3]); }
    {
      float d[32];
      if (i > 0) CBAR_SYNC(NB_WV, 256);
#pragma unroll
      for (int p = 0; p < 5; p++) {
        if (OSV && p == 3) {
          wg_wait<0>();
          release_round(sb, 2, tid0 & 31);
          if (wu == 1 && i > 0) {
            CBAR_SYNC(NB_MR, 160);
            if (elect_one()) signal_o(i - 1, cta);
          }
        }
        mwait(sb + BAR_F + 8 * p, i & 1, spin);
        TS(i, 25 + p);
        wg_fence();
#pragma unroll
        for (int k = 8 * p; k < 8 * p + 8; k++) {
          if (k < NKR) wgmma_rs64(d, wf[k < NKR ? k : 0], tdesc(k), k);
          else wgmma_ts64(d, wdesc(OFF_YV + (k - NKR) * 2048), tdesc(k), 1);
          if (k == 8 * p + 1 && p >= 1 && p <= (OSV ? 2 : 3)) {
            wg_commit(); wg_wait<1>();
            release_round(sb, p - 1, tid0 & 31);
          }
          if (k == 8 * p + RFK && (p == 1 || p == 2)) {
            wg_commit();
            if (rank == p - 1 && wu == 0) load_pair(sb, i, p + 2, slot_off(p + 2), i & 1, spin);
            wg_fence();
          }
        }
        wg_commit();
      }
      wg_wait<0>();
      TS(i, 23);
      CBAR_SYNC(NB_RD, 256);
      const int tid = fresh(tid0) & 127, m = (tid >> 3) & 3;
      if (tid < 8) mbar_expect_tx(sb + BAR_F + 8 * tid, tid < 5 ? 16384 : tid == 5 ? 2560 : tid == 6 ? 7168 : 4096);
      if (tid < 3 && tid != rank) mbar_arrive_cluster(mapa(sb, tid) + BAR_XF);
      va = sb + OFF_VT + 128 + ((tid >> 5) * 2 + (m & 1)) * VS + (m >> 1) * 640 + (tid & 7) * 16;
#pragma unroll
      for (int q = 0; q < 16; q++) vp[q] = pin(pack_bf16(d[2 * q], d[2 * q + 1]));
      if (VSL == 0) STORE_V
      if (tid < 80) sts128(sb + (tid < 72 ? OFF_VT + (tid >> 3) * VS : OFF_PT + 1280) + (tid & 7) * 16, make_uint4(0, 0, 0, 0));
      fence_async();
    }
    mwait(sb + BAR_XF, i & 1, spin);
    CBAR_ARRIVE(NB_QK, 384);
    const uint32_t* xc = &g_cnt[CN_X + i + 1][0];
    const uint32_t xn = NOWORK == 2 || i + 1 < NPRE ? 0 : i + 1 < LAG || NOWORK ? 16 : 48;
    bool seen = false;
    if (wu == 0) seen = __any_sync(0xffffffffu, ld_relaxed(xc) >= xn);
    CBAR_SYNC(NB_V, 256);
    float d[8];
    wg_fence();
    v_mem_pass<32, 40>(d, wf);
    v_mem_pass<0, 6>(d, wf);
    wg_wait<1>();
    if ((tid0 & 31) < 3 && (tid0 & 31) != rank) mbar_arrive_cluster(mapa(sb, tid0 & 31) + BAR_MF);
    v_mem_pass<6, 32>(d, wf);
    if (VSL == 2) STORE_V
    CBAR_SYNC(NB_SM, 256);
    wg_wait<0>();
    TS(i, 24);
    const int tid = fresh(tid0);
    if (!E2L && (tid & 31) == 0) mbar_arrive_cluster(mapa(sb, 2) + BAR_E + 16);
    stsm4(va, pack_bf16(d[0], d[1]), pack_bf16(d[2], d[3]), pack_bf16(d[4], d[5]), pack_bf16(d[6], d[7]));
#undef STORE_V
    fence_async();
    CBAR_ARRIVE(NB_VA, 256);
    CBAR_ARRIVE(NB_VQ, QPV ? 384 : 256);
    if (wu == 0 && i + 1 < NSTEP) {
      if (!seen) while (ld_relaxed(xc) < xn && spin < SPIN_TOT) spin += 16;
      fence_async_all();
      load_pair(sb, i + 1, rank, slot, i & 1, spin);
      TS(i + 1, 37);
    }
    TS_FLUSH(i - 1);
    __syncwarp();
  }
  CBAR_ARRIVE(NB_WV, 256);
  if (spin >= SPIN_TOT) g_err = 3;
}

__device__ __forceinline__ float quad_max(float x) {
  const float a = __shfl_xor_sync(0xffffffffu, x, 1), b = __shfl_xor_sync(0xffffffffu, x, 2), c = __shfl_xor_sync(0xffffffffu, x, 3);
  return fmaxf(fmaxf(x, a), fmaxf(b, c));
}
__device__ __forceinline__ float max10(const float (&y)[10]) {
  return fmaxf(fmaxf(fmaxf(fmaxf(y[0], y[1]), fmaxf(y[2], y[3])), fmaxf(fmaxf(y[4], y[5]), fmaxf(y[6], y[7]))), fmaxf(y[8], y[9]));
}
__device__ __forceinline__ float sum10(const float (&y)[10]) {
  return (((y[0] + y[1]) + (y[2] + y[3])) + ((y[4] + y[5]) + (y[6] + y[7]))) + (y[8] + y[9]);
}
__device__ __forceinline__ float rcp(float x) { float y; asm("rcp.approx.ftz.f32 %0,%1;" : "=f"(y) : "f"(x)); return y; }

__device__ __forceinline__ void chain_q(const bf16* x0, const bf16* mem0, const uint32_t sb, const int tid0, const int cta, const int rank) {
  using namespace C;
  asm volatile("setmaxnreg.dec.sync.aligned.u32 96;");
  int spin = 0;
  PTS(0);
  pre_work(x0, mem0, cta, tid0 & 127);
  PTS(3);
  CBAR_SYNC(NB_Q, 128);
  PTS(2);
  if (tid0 < 160) {
    if (tid0 == 128) pre_wait(0, 96, spin);
    __syncwarp();
    load_pair(sb, 0, rank, rank == 2 ? OFF_M : OFF_KT + rank * 16384, 1, spin);
  }
  PTS(4);
  CBAR_SYNC(NB_PRO, 384);
  mwait(sb + BAR_W, 1, spin);
  PTS(6);
  const int wu = uni((tid0 >> 5) & 3);
  uint4 ov[4] = {};
  uint8_t* op = &g_o[ORING - 1][cta][(tid0 & 124) * 32];
  const uint32_t o0 = ((tid0 ^ (tid0 >> 2)) & 3) * 16 + (tid0 & 16) * 4;
#pragma unroll 1
  for (int i = 0; i < NSTEP; i++) {
    const int ph = i & 1;
    uint32_t qf[4][4];
    {
      float d[64];
#define QK_STEP(K, SC) wgmma_st128(d, desc_at(mkdesc(SB0 + ((K) >> 2) * 1024 + ((K) & 3) * 32, 16, 2048), so), \
                                   desc_at(mkdesc(SB0 + OFF_WQ + (K) * 2048, OFF_WK - OFF_WQ, 1024), p * 16384), SC)
      int p = 0;
      uint32_t so = OFF_KT;
      mwait(sb + BAR_F, ph, spin);
      TS(i, 0);
      wg_fence();
#pragma unroll
      for (int k = 0; k < 8; k++) {
        QK_STEP(k, k);
        if (k == OST) {
          wg_commit();
          mwait(sb + BAR_F, ph, spin);
#pragma unroll
          for (int h = 0; h < 4; h++) stg128(op + (h & 1) * 4096 + (o0 ^ ((h >> 1) * 64)), ov[h]);
          if (i > 0) CBAR_ARRIVE(NB_MR, 160);
          if (k < 7) wg_fence();
        }
      }
      if (OST < 7) wg_commit();
#pragma unroll 1
      for (p = 1; p < 5; p++) {
        static_assert(OFF_KT - OFF_M == 5 << 12, "");
        so = OFF_M + (((0x95095u >> (4 * p)) & 15) << 12);
        if (i == 0) { mwait(sb + BAR_W + 8 * p, 1, spin); PTS(14 + p); }
        mwait(sb + BAR_F + 8 * p, ph, spin);
        wg_fence();
#pragma unroll
        for (int k = 0; k < 8; k++) {
          QK_STEP(k, 1);
          if (k == 1) {
            wg_commit(); wg_wait<1>();
            release_round(sb, p - 1, p < 4 ? tid0 & 31 : 32);
          }
        }
        wg_commit();
      }
#undef QK_STEP
      wg_wait<0>();
      TS(i, 1);
      CBAR_SYNC(NB_RD, 256);
      TSB(i, 2);
      const int tid = fresh(tid0), w = (tid >> 5) & 3, m = (tid >> 3) & 3;
      const uint32_t a = sb + OFF_KT + (m >> 1) * KS + (1 + w + 5 * (m & 1)) * 128 + (tid & 7) * 16;
#pragma unroll
      for (int s = 0; s < 4; s++)
        stsm4t(a + s * 2 * KS, pack_bf16(d[32 + 8 * s], d[33 + 8 * s]), pack_bf16(d[34 + 8 * s], d[35 + 8 * s]),
               pack_bf16(d[36 + 8 * s], d[37 + 8 * s]), pack_bf16(d[38 + 8 * s], d[39 + 8 * s]));
      fence_async();
      CBAR_ARRIVE(NB_QK, 384);
#pragma unroll
      for (int kk = 0; kk < 4; kk++)
#pragma unroll
        for (int j = 0; j < 4; j++) asm volatile("{.reg .b32 t; cvt.rn.bf16x2.f32 t,%1,%2; mul.rn.bf16x2 %0,t,%3;}" : "=r"(qf[kk][j]) : "f"(d[8 * kk + 2 * j + 1]), "f"(d[8 * kk + 2 * j]), "r"(SCQ));
    }
    CBAR_SYNC(NB_SI, 256);
    uint32_t pf[5][4];
    float sa = 0.f, sb2 = 0.f;
    {
      float y0[10], y1[10];
      const int tidf = fresh(tid0), lane = tidf & 31;
      {
        float x[40];
        wg_fence();
#pragma unroll
        for (int kk = 0; kk < 4; kk++) {
          if (VTI && kk == 4 - VTI) CBAR_ARRIVE(NB_V, 256);
          wgmma_rt80(x, qf[kk], mkdesc_ns(SB0 + OFF_KT + kk * 2 * KS, KS, 128), kk);
        }
        wg_commit();
        wg_wait<0>();
#pragma unroll
        for (int j = 0; j < 5; j++) { y0[2 * j] = x[4 * j]; y0[2 * j + 1] = x[4 * j + 1]; y1[2 * j] = x[22 + 4 * j]; y1[2 * j + 1] = x[23 + 4 * j]; }
      }
      TS(i, 17);
      const uint32_t xo = OFF_XT + (wu * (wu + 3) / 2) * 256 + lane * 16, x2 = xo + (wu >> 1) * 512 + 512 - lane * 8;
      {
        const uint4 h0 = make_uint4(pack_h2(y0[0], y0[1]), pack_h2(y1[0], y1[1]), pack_h2(y0[2], y0[3]), pack_h2(y1[2], y1[3]));
        const uint4 h1 = make_uint4(pack_h2(y0[4], y0[5]), pack_h2(y1[4], y1[5]), pack_h2(y0[6], y0[7]), pack_h2(y1[6], y1[7]));
        const uint32_t h2 = wu == 1 ? h1.x : pack_h2(y0[8], y0[9]), h3 = wu == 1 ? h1.y : pack_h2(y1[8], y1[9]);
        const uint32_t rb1 = mapa(sb, (rank + 1) % 3), rb2 = mapa(sb, (rank + 2) % 3);
        if (XTD == 1) mwait(sb + BAR_XM, ph, spin);
        if (XTD > 1) for (const uint32_t t0 = clk32(); clk32() - t0 < XTD;) {}
        st_async4u(rb1 + xo + 3584, h0, rb1 + BAR_XT);
        st_async4u(rb2 + xo, h0, rb2 + BAR_XT);
        if (wu >= 2) { st_async4u(rb1 + xo + 4096, h1, rb1 + BAR_XT); st_async4u(rb2 + xo + 512, h1, rb2 + BAR_XT); }
        if (wu & 1) { st_async2u(rb1 + x2 + 3584, h2, h3, rb1 + BAR_XT); st_async2u(rb2 + x2, h2, h3, rb2 + BAR_XT); }
      }
      TS(i, 18);
      const int lim = 8 * wu + (lane >> 2) + 8 - 2 * (lane & 3);
#pragma unroll
      for (int j = 2; j < 10; j++)
        if (8 * (j >> 1) + (j & 1) > lim) { y0[j] = -INFINITY; y1[j] = -INFINITY; }
      mwait(sb + BAR_XT, ph, spin);
      TS(i, 19);
      {
        const uint4 u0 = lds128(sb + xo), v0 = lds128(sb + xo + 3584);
        uint2 u2 = make_uint2(0, 0), v2 = u2;
        if (wu & 1) { u2 = lds64(sb + x2); v2 = lds64(sb + x2 + 3584); }
        uint4 u1 = make_uint4(u2.x, u2.y, 0, 0), v1 = make_uint4(v2.x, v2.y, 0, 0);
        if (wu >= 2) { u1 = lds128(sb + xo + 512); v1 = lds128(sb + xo + 4096); }
        __syncwarp();
        if (lane == 0) mbar_arrive_cluster(mapa(sb, 0) + BAR_E);
        add_h2(y0[0], y0[1], u0.x, v0.x); add_h2(y1[0], y1[1], u0.y, v0.y); add_h2(y0[2], y0[3], u0.z, v0.z); add_h2(y1[2], y1[3], u0.w, v0.w);
        add_h2(y0[4], y0[5], u1.x, v1.x); add_h2(y1[4], y1[5], u1.y, v1.y); add_h2(y0[6], y0[7], u1.z, v1.z); add_h2(y1[6], y1[7], u1.w, v1.w);
        add_h2(y0[8], y0[9], u2.x, v2.x); add_h2(y1[8], y1[9], u2.y, v2.y);
      }
      const float m0 = quad_max(max10(y0)) * -SCE, m1 = quad_max(max10(y1)) * -SCE;
#pragma unroll
      for (int j = 0; j < 5; j++) {
        y0[2 * j] = ex2(fmaf(y0[2 * j], SCE, m0)); y0[2 * j + 1] = ex2(fmaf(y0[2 * j + 1], SCE, m0));
        y1[2 * j] = ex2(fmaf(y1[2 * j], SCE, m1)); y1[2 * j + 1] = ex2(fmaf(y1[2 * j + 1], SCE, m1));
        if (!ONES) { sa += y0[2 * j] + y0[2 * j + 1]; sb2 += y1[2 * j] + y1[2 * j + 1]; }
        pf[j >> 1][2 * (j & 1)] = pack_bf16(y0[2 * j], y0[2 * j + 1]);
        pf[j >> 1][2 * (j & 1) + 1] = tidf >> (10 + j);
        pf[(j + 5) >> 1][2 * ((j + 5) & 1)] = tidf >> (20 + j);
        pf[(j + 5) >> 1][2 * ((j + 5) & 1) + 1] = pack_bf16(y1[2 * j], y1[2 * j + 1]);
      }
    }
#pragma unroll
    for (int q = 0; q < 20; q++) pf[q >> 2][q & 3] = pin(pf[q >> 2][q & 3]);
    CBAR_SYNC(NB_VQ, QPV ? 384 : 256);
    TSB(i, 20);
    {
      float o[32], sm[4];
      wg_fence();
#pragma unroll
      for (int q = 0; q < 5; q++) if (ONES) wgmma_rs8(sm, pf[q], mkdesc_ns(SB0 + OFF_ONE, 0, 0), q);
#pragma unroll
      for (int q = 0; q < 5; q++) wgmma_rs64(o, pf[q], mkdesc_ns(SB0 + OFF_VT + 128 + q * 256, 128, VS), q);
      wg_commit();
      if (!ONES) { sm[0] = quad_sum(sa); sm[2] = quad_sum(sb2); }
      const int tid = fresh(tid0);
      op = &g_o[i % ORING][cta][(tid & 124) * 32];
      wg_wait<0>();
      TS(i, 21);
      if ((tid & 31) == 0) mbar_arrive_cluster(mapa(sb, 1) + BAR_E + 8);
      const float s0 = rcp(sm[0]), s1 = rcp(sm[2]);
#pragma unroll
      for (int h = 0; h < 2; h++) {
        const float* x = o + 16 * h;
        ov[2 * h] = make_uint4(pin(pack_bf16(x[0] * s0, x[1] * s0)), pin(pack_bf16(x[4] * s0, x[5] * s0)), pin(pack_bf16(x[8] * s0, x[9] * s0)), pin(pack_bf16(x[12] * s0, x[13] * s0)));
        ov[2 * h + 1] = make_uint4(pin(pack_bf16(x[2] * s1, x[3] * s1)), pin(pack_bf16(x[6] * s1, x[7] * s1)), pin(pack_bf16(x[10] * s1, x[11] * s1)), pin(pack_bf16(x[14] * s1, x[15] * s1)));
      }
      TS(i, 22);
      if (i + 1 < NSTEP) CBAR_SYNC(NB_WQ, 256); else CBAR_ARRIVE(NB_WQ, 256);
    }
  }
#pragma unroll
  for (int h = 0; h < 4; h++) stg128(op + (h & 1) * 4096 + (o0 ^ ((h >> 1) * 64)), ov[h]);
  CBAR_SYNC(NB_Q, 128);
  if (tid0 == 224) signal_o(NSTEP - 1, cta);
  if (spin >= SPIN_TOT) g_err = 2;
}

template <int NL> __device__ __forceinline__ void poll(uint4 (&x)[NL], const uint8_t* mb, uint32_t tag, int& spin);
template <> __device__ __forceinline__ void poll<4>(uint4 (&x)[4], const uint8_t* mb, uint32_t tag, int& spin) {
  asm volatile("{.reg .pred p<6>, q; .reg .b128 v; .reg .b32 t;\n"
               " ld.relaxed.gpu.global.b128 v,[%17+0]; mov.b128 {%0,%1,%2,%3},v;\n"
               " ld.relaxed.gpu.global.b128 v,[%17+512]; mov.b128 {%4,%5,%6,%7},v;\n"
               " ld.relaxed.gpu.global.b128 v,[%17+1024]; mov.b128 {%8,%9,%10,%11},v;\n"
               " ld.relaxed.gpu.global.b128 v,[%17+1536]; mov.b128 {%12,%13,%14,%15},v;\n"
               "POLL_LOOP:\n add.s32 %16,%16,16;\n"
               " lop3.b32 t,%0,%18,1,0x28; setp.ne.b32 p0,t,0;\n"
               " lop3.b32 t,%4,%18,1,0x28; setp.ne.b32 p1,t,0;\n"
               " lop3.b32 t,%8,%18,1,0x28; setp.ne.b32 p2,t,0;\n"
               " lop3.b32 t,%12,%18,1,0x28; setp.ne.b32 p3,t,0;\n"
               " or.pred q,p0,p1; or.pred q,q,p2; or.pred q,q,p3; setp.lt.and.s32 q,%16,%19,q; vote.sync.any.pred q,q,0xffffffff;\n"
               " mov.b128 v,{%0,%1,%2,%3}; @p0 ld.relaxed.gpu.global.b128 v,[%17+0]; mov.b128 {%0,%1,%2,%3},v;\n"
               " mov.b128 v,{%4,%5,%6,%7}; @p1 ld.relaxed.gpu.global.b128 v,[%17+512]; mov.b128 {%4,%5,%6,%7},v;\n"
               " mov.b128 v,{%8,%9,%10,%11}; @p2 ld.relaxed.gpu.global.b128 v,[%17+1024]; mov.b128 {%8,%9,%10,%11},v;\n"
               " mov.b128 v,{%12,%13,%14,%15}; @p3 ld.relaxed.gpu.global.b128 v,[%17+1536]; mov.b128 {%12,%13,%14,%15},v;\n"
               " @q bra.uni POLL_LOOP;\n}"
               : "=&r"(x[0].x), "=&r"(x[0].y), "=&r"(x[0].z), "=&r"(x[0].w), "=&r"(x[1].x), "=&r"(x[1].y), "=&r"(x[1].z), "=&r"(x[1].w), "=&r"(x[2].x), "=&r"(x[2].y), "=&r"(x[2].z), "=&r"(x[2].w), "=&r"(x[3].x), "=&r"(x[3].y), "=&r"(x[3].z), "=&r"(x[3].w), "+&r"(spin)
               : "l"(mb), "r"(tag), "n"(SPIN_TOT) : "memory");
}
template <> __device__ __forceinline__ void poll<6>(uint4 (&x)[6], const uint8_t* mb, uint32_t tag, int& spin) {
  asm volatile("{.reg .pred p<6>, q; .reg .b128 v; .reg .b32 t;\n"
               " ld.relaxed.gpu.global.b128 v,[%25+0]; mov.b128 {%0,%1,%2,%3},v;\n"
               " ld.relaxed.gpu.global.b128 v,[%25+512]; mov.b128 {%4,%5,%6,%7},v;\n"
               " ld.relaxed.gpu.global.b128 v,[%25+1024]; mov.b128 {%8,%9,%10,%11},v;\n"
               " ld.relaxed.gpu.global.b128 v,[%25+1536]; mov.b128 {%12,%13,%14,%15},v;\n"
               " ld.relaxed.gpu.global.b128 v,[%25+2048]; mov.b128 {%16,%17,%18,%19},v;\n"
               " ld.relaxed.gpu.global.b128 v,[%25+2560]; mov.b128 {%20,%21,%22,%23},v;\n"
               "POLL_LOOP:\n add.s32 %24,%24,16;\n"
               " lop3.b32 t,%0,%2,%26,0x7e; and.b32 t,t,1; setp.ne.b32 p0,t,0;\n"
               " lop3.b32 t,%4,%6,%26,0x7e; and.b32 t,t,1; setp.ne.b32 p1,t,0;\n"
               " lop3.b32 t,%8,%10,%26,0x7e; and.b32 t,t,1; setp.ne.b32 p2,t,0;\n"
               " lop3.b32 t,%12,%14,%26,0x7e; and.b32 t,t,1; setp.ne.b32 p3,t,0;\n"
               " lop3.b32 t,%16,%18,%26,0x7e; and.b32 t,t,1; setp.ne.b32 p4,t,0;\n"
               " lop3.b32 t,%20,%22,%26,0x7e; and.b32 t,t,1; setp.ne.b32 p5,t,0;\n"
               " or.pred q,p0,p1; or.pred q,q,p2; or.pred q,q,p3; or.pred q,q,p4; or.pred q,q,p5; setp.lt.and.s32 q,%24,%27,q; vote.sync.any.pred q,q,0xffffffff;\n"
               " mov.b128 v,{%0,%1,%2,%3}; @p0 ld.relaxed.gpu.global.b128 v,[%25+0]; mov.b128 {%0,%1,%2,%3},v;\n"
               " mov.b128 v,{%4,%5,%6,%7}; @p1 ld.relaxed.gpu.global.b128 v,[%25+512]; mov.b128 {%4,%5,%6,%7},v;\n"
               " mov.b128 v,{%8,%9,%10,%11}; @p2 ld.relaxed.gpu.global.b128 v,[%25+1024]; mov.b128 {%8,%9,%10,%11},v;\n"
               " mov.b128 v,{%12,%13,%14,%15}; @p3 ld.relaxed.gpu.global.b128 v,[%25+1536]; mov.b128 {%12,%13,%14,%15},v;\n"
               " mov.b128 v,{%16,%17,%18,%19}; @p4 ld.relaxed.gpu.global.b128 v,[%25+2048]; mov.b128 {%16,%17,%18,%19},v;\n"
               " mov.b128 v,{%20,%21,%22,%23}; @p5 ld.relaxed.gpu.global.b128 v,[%25+2560]; mov.b128 {%20,%21,%22,%23},v;\n"
               " @q bra.uni POLL_LOOP;\n}"
               : "=&r"(x[0].x), "=&r"(x[0].y), "=&r"(x[0].z), "=&r"(x[0].w), "=&r"(x[1].x), "=&r"(x[1].y), "=&r"(x[1].z), "=&r"(x[1].w), "=&r"(x[2].x), "=&r"(x[2].y), "=&r"(x[2].z), "=&r"(x[2].w), "=&r"(x[3].x), "=&r"(x[3].y), "=&r"(x[3].z), "=&r"(x[3].w), "=&r"(x[4].x), "=&r"(x[4].y), "=&r"(x[4].z), "=&r"(x[4].w), "=&r"(x[5].x), "=&r"(x[5].y), "=&r"(x[5].z), "=&r"(x[5].w), "+&r"(spin)
               : "l"(mb), "r"(tag), "n"(SPIN_TOT) : "memory");
}
template <int NL>
__device__ __forceinline__ void poll_add(const uint8_t* mb, uint32_t tag, float (&f)[8], uint8_t* flag, bool lead, int& spin) {
  uint4 x[NL];
  poll<NL>(x, mb, tag, spin);
  if (FLP == 0 && lead) st_relaxed(flag, 0);
#pragma unroll
  for (int i = 0; i < NL; i++) {
    const uint32_t u[4] = {x[i].x, x[i].y, x[i].z, x[i].w};
#pragma unroll
    for (int j = 0; j < 4; j++) {
      if (i == 0) { f[2 * j] = bf_lo(u[j]); f[2 * j + 1] = bf_hi(u[j]); }
      else { f[2 * j] += bf_lo(u[j]); f[2 * j + 1] += bf_hi(u[j]); }
    }
  }
}

template <int B, int SLOT>
__device__ __forceinline__ void wo_step(float (&acc)[8], const uint32_t (&wf)[C::NKR][4], int kk) {
  using namespace C;
  const int k = 4 * B + kk;
  const uint64_t db = mkdesc_ns(SB0 + og_off(SLOT) + kk * 512, 256, 128);
  if (k < NKR) wgmma_rt16(acc, wf[k < NKR ? k : 0], db, SLOT | kk);
  else wgmma_tt16(acc, wdesc(OFF_YO + (k - NKR) * 2048), db, 1);
}
template <int B, int SLOT>
__device__ __forceinline__ void wo_block(float (&acc)[8], const uint32_t (&wf)[C::NKR][4]) {
#pragma unroll
  for (int kk = 0; kk < 4; kk++) wo_step<B, SLOT>(acc, wf, kk);
}

__device__ __forceinline__ void chain_a(const CUtensorMap& tmWo, const CUtensorMap& tmWq, const uint32_t sb, const int tid0, const int cta, const int rank) {
  using namespace C;
  asm volatile("setmaxnreg.inc.sync.aligned.u32 200;");
  int spin = 0;
  uint32_t wf[NKR][4];
  load_weights_rs<true>(wf, tmWo, tmWq, cta, rank, sb, tid0, spin);
  const int wu = uni(tid0 >> 5);
  const bool t9 = cta >= 72 && cta < 88;
  const uint64_t exa = reinterpret_cast<uint64_t>(ex_window(g_ex));
  const uint32_t ehi = (uint32_t)(exa >> 32), elo = (uint32_t)exa;

  int b1 = B1, b2 = B2;
#pragma unroll 1
  for (int i = -1; i < NSTEP; i++) {
    const int ph = i & 1;
    if (i >= 0) {
      const int tid = fresh(tid0);
      const uint32_t mo = __shfl_xor_sync(0xffffffffu, elo + ((rank * 24 + (tid >> 4)) * 4 + (tid & 3)) * 2048 + (cta / 3) * 64 + (tid & 12) * 4, 0);
      const uint32_t m9 = __shfl_xor_sync(0xffffffffu, elo + MAIL9 + (((tid >> 4) * 2 + (tid & 1)) * 4 + (tid & 2)) * 3072 + cta * 32 + (tid & 12) * 2, 0);
      const uint32_t oo = __shfl_xor_sync(0xffffffffu, (tid >> 5) * 512 + (tid & 2) * 64 + (tid & 28) * 4 + (tid & 1) * 8, 0);
      if (i == 0) { mwait(sb + BAR_W + 24, 1, spin); mwait(sb + BAR_W + 32, 1, spin); PTS(7); }
      mwait(sb + BAR_M, ph, spin);
      TS(i, 3);
      {
        float x[20];
        int redo = 0;
      retry:
        bool bad;
        {
          float dq[8] = {}, dk[8] = {};
#pragma unroll 1
          for (int k0 = 0; k0 < 40; k0 += P1U) {
            wg_fence();
#pragma unroll
            for (int k = 0; k < P1U; k++) {
              const uint64_t db = desc_at(mdesc(k), k0 * 512);
              wgmma_ts16(dq, desc_at(wdesc(OFF_WQ + k * 2048), k0 * 2048), db, 1);
              wgmma_ts16(dk, desc_at(wdesc(OFF_WK + k * 2048), k0 * 2048), db, 1);
            }
            wg_commit();
          }
          const int m = (tid >> 3) & 3, dg = (tid >> 5) * 2 + (m & 1);
          const uint32_t ka = sb + OFF_KT + dg * KS + (m >> 1) * 640 + (tid & 7) * 16;
          if (!redo) CBAR_SYNC(NB_QK, 384);
          wg_wait<0>();
          TS(i, 4);
          stsm4(ka, pack_bf16(dk[0], dk[1]), pack_bf16(dk[2], dk[3]), pack_bf16(dk[4], dk[5]), pack_bf16(dk[6], dk[7]));
          stsm4(ka + dg * (VS - KS) + (OFF_VT + 128 - OFF_KT), scale_bf16x2(pack_bf16(dq[0], dq[1]), SCQ), scale_bf16x2(pack_bf16(dq[2], dq[3]), SCQ),
                scale_bf16x2(pack_bf16(dq[4], dq[5]), SCQ), scale_bf16x2(pack_bf16(dq[6], dq[7]), SCQ));
          const float chk = (dq[0] + dq[1]) + (dq[4] + dq[5]);
          fence_async();
          bad = bar_red_or(NB_C, 128, chk != chk && !redo);
        }
        TSB(i, 5);
        wg_fence();
#pragma unroll
        for (int kk = 0; kk < 4; kk++) wgmma_tt40(x, mkdesc_ns(SB0 + OFF_VT + 128 + kk * 2 * VS, VS, 640), mkdesc_ns(SB0 + OFF_KT + kk * 2 * KS, KS, 128), kk);
#pragma unroll
        for (int kk = 0; kk < 4; kk++) {
          if (SIE && kk == 4 - SIE && !bad) CBAR_ARRIVE(NB_SI, 256);
          wgmma_tt40(x, mkdesc_ns(SB0 + OFF_VT + kk * 2 * VS, VS, 384), mkdesc_ns(SB0 + OFF_KT + 640 + kk * 2 * KS, KS, 128), 1);
        }
        wg_commit();
        if (!SIE && !bad) CBAR_ARRIVE(NB_SI, 256);
        if (__builtin_expect(__any_sync(0xffffffffu, bad), 0)) {
          wg_wait<0>();
#pragma unroll 1
          for (int k = 0; k < 10; k++) {
            uint4 v = lds128(sb + OFF_M + tid * 16 + k * 2048);
            if (v.x == SENT || v.y == SENT || v.z == SENT || v.w == SENT) {
              do { v = ld_relaxed4(mkptr(elo + EX_M + i * 20480 + tid * 16 + k * 2048, ehi)); spin += 16; } while ((v.x == SENT || v.y == SENT || v.z == SENT || v.w == SENT) && spin < SPIN_TOT);
              sts128(sb + OFF_M + tid * 16 + k * 2048, v);
            }
          }
          fence_async();
          bar_sync(NB_C, 128);
          redo = fresh(1);
          goto retry;
        }
        TSV(i, 36, redo);
        const uint32_t rb1 = mapa(sb, (rank + 1) % 3), rb2 = mapa(sb, (rank + 2) % 3);
        wg_wait<0>();
        TS(i, 6);
        if (wu < 2) {
          float y[10];
#pragma unroll
          for (int j = 0; j < 5; j++) { y[2 * j] = x[4 * j]; y[2 * j + 1] = x[4 * j + 1]; }
          const uint4 h0 = make_uint4(pack_h2(y[0], y[1]), pack_h2(y[2], y[3]), pack_h2(y[4], y[5]), pack_h2(y[6], y[7]));
          const uint32_t h1 = pack_h2(y[8], y[9]);
          const uint32_t xo = wu * 640 + (tid & 31) * 16, xp = wu * 640 + 512 + (tid & 31) * 4;
          if (XMB) {
            sts128(sb + og_off(0) + xo, h0); sts32(sb + og_off(0) + xp, h1);
            fence_async();
            __syncwarp();
            if (elect_one()) {
              bulk_s2c(rb1 + OFF_XM + 1280 + wu * 640, sb + og_off(0) + wu * 640, 640, rb1 + BAR_XM);
              bulk_s2c(rb2 + OFF_XM + wu * 640, sb + og_off(0) + wu * 640, 640, rb2 + BAR_XM);
            }
          } else {
            st_async4u(rb1 + OFF_XM + 1280 + xo, h0, rb1 + BAR_XM);
            st_async4u(rb2 + OFF_XM + xo, h0, rb2 + BAR_XM);
            st_async1u(rb1 + OFF_XM + 1280 + xp, h1, rb1 + BAR_XM);
            st_async1u(rb2 + OFF_XM + xp, h1, rb2 + BAR_XM);
          }
          CBAR_ARRIVE(NB_SM, 256);
          if (!E0L && (tid & 31) == 0) mbar_arrive_cluster(mapa(sb, 0) + BAR_E);
          TS(i, 7);
          const uint32_t sw = (tid & 7) * 4 + (tid & 8) * 8 + (tid & 16) * 2;
          mwait(sb + BAR_XM, ph, spin);
          TS(i, 8);
          const uint4 u0 = lds128(sb + OFF_XM + xo), v0 = lds128(sb + OFF_XM + 1280 + xo);
          const uint32_t u1 = lds32(sb + OFF_XM + xp), v1 = lds32(sb + OFF_XM + 1280 + xp);
          add_h2(y[0], y[1], u0.x, v0.x); add_h2(y[2], y[3], u0.y, v0.y); add_h2(y[4], y[5], u0.z, v0.z); add_h2(y[6], y[7], u0.w, v0.w);
          add_h2(y[8], y[9], u1, v1);
          const float mx = quad_max(max10(y)) * -SCE;
#pragma unroll
          for (int j = 0; j < 5; j++) {
            y[2 * j] = ex2(fmaf(y[2 * j], SCE, mx)); y[2 * j + 1] = ex2(fmaf(y[2 * j + 1], SCE, mx));
            sts32(sb + OFF_PT + wu * 640 + sw + j * 128, pack_bf16(y[2 * j], y[2 * j + 1]));
          }
          sts32(sb + OFF_XM + 512 + wu * 128 + sw, __float_as_uint(sum10(y)));
          fence_async();
          TS(i, 9);
        } else {
          CBAR_ARRIVE(NB_SM, 256);
          if (!E0L && (tid & 31) == 0) mbar_arrive_cluster(mapa(sb, 0) + BAR_E);
          mwait(sb + BAR_MF, ph, spin);
        }
      }
      CBAR_SYNC(NB_VA, 256);
      TSB(i, 10);
      {
        float o[2][4];
        const float4 e = lds128f(sb + OFF_XM + 512 + (tid & 15) * 16);
        wg_fence();
#pragma unroll
        for (int c = 0; c < 2; c++)
#pragma unroll
          for (int q = 0; q < 3; q++)
            wgmma_ss8(o[c], mkdesc_ns(SB0 + OFF_VT + 128 + c * 640 + q * 256, 128, VS), mkdesc_ns(SB0 + OFF_PT + c * 640 + q * 256, q == 2 && c == 0 ? 768 : 128, 128), q);
        wg_commit();
        if (PVB && __builtin_expect(b1 < 0, 0)) { wg_wait<0>(); break; }
        const uint32_t rb1 = mapa(sb, (rank + 1) % 3), rb2 = mapa(sb, (rank + 2) % 3);
        const float inv = rcp((e.x + e.y) + (e.z + e.w));
        const int sl = (tid & 3) * 2;
        const float i0 = __shfl_sync(0xffffffffu, inv, sl), i1 = __shfl_sync(0xffffffffu, inv, sl + 1);
        const float i2 = __shfl_sync(0xffffffffu, inv, sl + 8), i3 = __shfl_sync(0xffffffffu, inv, sl + 9);
        if (E0L == 1 && (tid & 31) == 0) mbar_arrive_cluster(mapa(sb, 0) + BAR_E);
        if (PVB > 1 && __builtin_expect(b2 < 0, 0)) { wg_wait<0>(); break; }
        wg_wait<0>();
        TS(i, 11);
        const uint32_t p0 = pack_bf16(o[0][0] * i0, o[0][1] * i1), p1 = pack_bf16(o[1][0] * i2, o[1][1] * i3);
        const uint32_t p2 = pack_bf16(o[0][2] * i0, o[0][3] * i1), p3 = pack_bf16(o[1][2] * i2, o[1][3] * i3);
        if (OGF) { sts64(sb + oo + og_off(0), p0, p1); sts64(sb + oo + og_off(0) + 256, p2, p3); fence_async(); }
        if (OGF == 2) {
          __syncwarp();
          if (elect_one()) {
            bulk_s2c(rb1 + og_off(2) + wu * 512, sb + og_off(0) + wu * 512, 512, rb1 + BAR_OG);
            bulk_s2c(rb2 + og_off(1) + wu * 512, sb + og_off(0) + wu * 512, 512, rb2 + BAR_OG);
          }
        } else if (OGF < 2) {
          st_async2u(rb1 + oo + og_off(2), p0, p1, rb1 + BAR_OG);
          st_async2u(rb2 + oo + og_off(1), p0, p1, rb2 + BAR_OG);
          st_async2u(rb1 + oo + og_off(2) + 256, p2, p3, rb1 + BAR_OG);
          st_async2u(rb2 + oo + og_off(1) + 256, p2, p3, rb2 + BAR_OG);
        }
        if (!OGF) { sts64(sb + oo + og_off(0), p0, p1); sts64(sb + oo + og_off(0) + 256, p2, p3); fence_async(); }
      }
      if (E0L == 2 && (tid & 31) == 0) mbar_arrive_cluster(mapa(sb, 0) + BAR_E);
      CBAR_SYNC(NB_A, 128);
      TSB(i, 12);
      if (OGF == 3 && wu < 2 && elect_one()) {
        const uint32_t rb = mapa(sb, (rank + 1 + wu) % 3);
        bulk_s2c(rb + og_off(2) - wu * 2048, sb + og_off(0), 2048, rb + BAR_OG);
      }
      {
        float acc[3][8];
        wg_fence();
        wo_block<0, 0>(acc[2], wf);
        wg_commit();
        wo_block<1, 0>(acc[0], wf);
        if (QPV == 1) CBAR_ARRIVE(NB_VQ, 384);
        wo_block<4, 0>(acc[1], wf);
        wg_commit();
        if (QPV == 2) CBAR_ARRIVE(NB_VQ, 384);
        if (tid < (E2L == 1 ? 2 : 1)) mbar_arrive_cluster(mapa(sb, 1 + tid) + BAR_E + 8 + 8 * tid);
        const uint32_t tag = (i >> 1) & 1;
#define TAGGED(LO, HI) ((pack_bf16(LO, HI) & ~1u) | tag)
#define SEND(OFF, U) st_relaxed128(mkptr(mo + (ph << 20), ehi) + (OFF), TAGGED(acc[U][0], acc[U][2]), pack_bf16(acc[U][1], acc[U][3]), pack_bf16(acc[U][4], acc[U][6]), pack_bf16(acc[U][5], acc[U][7]))
        wg_wait<1>();
        const uint32_t n0 = pin(TAGGED(acc[2][0], acc[2][2])), n1 = pin(pack_bf16(acc[2][1], acc[2][3]));
        const uint32_t n2 = pin(TAGGED(acc[2][4], acc[2][6])), n3 = pin(pack_bf16(acc[2][5], acc[2][7]));
        if (T2E) { wg_fence(); wo_block<7, 0>(acc[2], wf); wg_commit(); }
        if (!T9L) { st_relaxed64(mkptr(m9 + (ph << 20), ehi), n0, n1); st_relaxed64(mkptr(m9 + (ph << 20), ehi) + 3072, n2, n3); }
        mwait(sb + BAR_OG, ph, spin);
        asm volatile("fence.proxy.async::generic.acquire.sync_restrict::shared::cluster.cluster;" ::: "memory");
        if (E2L == 2 && tid == 0) mbar_arrive_cluster(mapa(sb, 2) + BAR_E + 16);
        TS(i, 13);
        wg_fence();
        wo_block<2, 1>(acc[0], wf); wo_block<3, 2>(acc[0], wf);
        wg_commit();
        wo_block<5, 1>(acc[1], wf); wo_block<6, 2>(acc[1], wf);
        wg_commit();
        if (QPV == 3) CBAR_ARRIVE(NB_VQ, 384);
        wg_wait<1>();
        if (T9L) { st_relaxed64(mkptr(m9 + (ph << 20), ehi), n0, n1); st_relaxed64(mkptr(m9 + (ph << 20), ehi) + 3072, n2, n3); }
        SEND(0, 0);
        if (!T2E) wo_block<7, 0>(acc[2], wf);
        wo_block<8, 1>(acc[2], wf); wo_block<9, 2>(acc[2], wf);
        wg_commit();
        if (WOE == 0) { CBAR_ARRIVE(NB_WV, 256); CBAR_ARRIVE(NB_WQ, 256); }
        wg_wait<1>(); SEND(32 * 2048, 1);
        if (WOE == 1) CBAR_ARRIVE(NB_WV, 256);
        wg_wait<0>(); SEND(64 * 2048, 2);
        if (WOE == 2) CBAR_ARRIVE(NB_WV, 256);
        if (WOE >= 1) CBAR_ARRIVE(NB_WQ, 256);
#undef SEND
#undef TAGGED
      }
      TS(i, 14);
      if (i < 2) PTS(19 + i);
      if (i + 1 >= NSTEP) break;
    }
    uint32_t t1 = clk32();
    if (i >= 0) {
      const int lane = fresh(tid0) & 31, j = lane >> 3;
      const uint8_t* mb = mkptr(elo + (ph << 20) + (t9 ? MAIL9 + (cta - 72) * 12288 + wu * 3072 : (cta < 72 ? cta : cta - 24) * 8192 + wu * 2048) + lane * 16, ehi);
      const uint32_t tag = (i >> 1) & 1;
      const bool pub = (lane & (t9 ? 6 : 4)) == 0 && !(((t9 ? cta : wu) & 1) && i + 1 == LAG) && cta < 88;
      const uint32_t dst = pin(elo + EX_M + (i + 1) * 20480 + (t9 ? (cta + 72) * 128 + wu * 32 + (j & 1) * 16 + (lane & 1) * 8 + (j >> 1) * 4
                                                                   : cta * 256 + (wu & 1) * 128 + (wu >> 1) * 64 + j * 16 + (lane & 3) * 4));
      uint8_t* flag = mkptr(elo + EX_FLAG + (i + 1) * 3072 + cta * 32 + wu * 4, ehi);
      while (clk32() - t1 < b1) {}
      TS(i + 1, 30);
      float f[8];
      const int n0 = spin;
      if (!t9) poll_add<4>(mb, tag, f, flag, lane == 0, spin);
      else poll_add<6>(mb, tag, f, flag, lane == 0, spin);
      if (FLP == 1 && lane == 0) st_relaxed(flag, __float_as_uint(f[0] + f[7]) >> 1);
      t1 = clk32();
      b1 = __any_sync(0xffffffffu, spin - n0 > 16) ? min(b1 + AD1, BMX) : max(b1 - AD0, 0);
      TSV(i + 1, 38, b1);
      TS(i + 1, 31); TSV(i + 1, 32, (spin - n0) >> 4);
      const bool h = lane & 16, q = lane & 8;
#pragma unroll
      for (int j = 0; j < 4; j++) f[j] = (h ? f[4 + j] : f[j]) + __shfl_xor_sync(0xffffffffu, h ? f[j] : f[4 + j], 16);
#pragma unroll
      for (int j = 0; j < 2; j++) f[j] = (q ? f[2 + j] : f[j]) + __shfl_xor_sync(0xffffffffu, q ? f[j] : f[2 + j], 8);
      f[0] += __shfl_xor_sync(0xffffffffu, f[0], 4); f[1] += __shfl_xor_sync(0xffffffffu, f[1], 4);
      if (t9) { f[0] += __shfl_xor_sync(0xffffffffu, f[0], 2); f[1] += __shfl_xor_sync(0xffffffffu, f[1], 2); }
      if (pub) st_relaxed(mkptr(dst, ehi), pack_bf16(f[0], f[1]));
      if (FLP == 2 && lane == 0) st_relaxed(flag, 0);
      if (!OSV && wu == 3) {
        CBAR_SYNC(NB_MR, 160);
        if (elect_one()) signal_o(i, cta);
      }
      TS(i + 1, 15);
    }
    if (wu == 0) {
      const int tid = fresh(tid0);
      const uint8_t* pp = mkptr(elo + EX_FLAG + (i + 1) * 3072 + (rank * 28 + (tid < 28 || rank == 2 ? tid : 0)) * 32, ehi);
      while (clk32() - t1 < b2) {}
      TS(i + 1, 16);
      int n = 1;
      uint4 x = ld_relaxed4(pp);
      if (tid0 == 0) mbar_expect_tx(sb + BAR_M, 20480);
      bool mok = mbar_test(sb + BAR_MOK, ph ^ 1);
      while (__any_sync(0xffffffffu, (int)(x.x | x.y | x.z | x.w) < 0 && spin < SPIN_TOT)) { x = ld_relaxed4(pp); mok = mbar_test(sb + BAR_MOK, ph ^ 1); n++; spin += 16; }
      if (!mok) mwait(sb + BAR_MOK, ph ^ 1, spin);
      if (B3 && n > 1) { const uint32_t t3 = clk32(); while (clk32() - t3 < B3) {} }
      b2 = n > 1 ? min(b2 + AD3, BMX) : max(b2 - AD2, 0);
      TSV(i + 1, 35, n); TSV(i + 1, 39, b2);
      TS(i + 1, 34);
      if (elect_one()) bulk_g2s_mc(sb + OFF_M + rank * 7168, mkptr(elo + EX_M + (i + 1) * 20480 + rank * 7168, ehi), rank == 2 ? 6144 : 7168, sb + BAR_M);
      TS(i + 1, 33);
      __syncwarp();
    }
  }
  if (spin >= SPIN_TOT) g_err = 1;
}

__global__ void __cluster_dims__(3, 1, 1) __launch_bounds__(384, 1)
k_chain(const __grid_constant__ CUtensorMap tmWq, const __grid_constant__ CUtensorMap tmWk,
        const __grid_constant__ CUtensorMap tmWv, const __grid_constant__ CUtensorMap tmWo, const bf16* __restrict__ x0, const bf16* __restrict__ mem0) {
  using namespace C;
  extern __shared__ __align__(1024) uint8_t smem[];
  const uint32_t sb = smem_u32(smem);
  const int tid = threadIdx.x;
  const int wg = __shfl_sync(0xffffffffu, tid >> 7, 0);
  const int cta = uni(blockIdx.x), rank = uni(blockIdx.x % 3);

  asm volatile("griddepcontrol.launch_dependents;");
  if (cta < 4) prefetch_l2(tid < 320 ? x0 + (cta * 320 + tid) * 64 : mem0 + (cta * 20 + tid % 20) * 64);
  if (tid == 32) {
    for (int p = 0; p < 5; p++) mbar_init(sb + BAR_W + 8 * p, 2);
    fence_async();
    for (int p = 0; p < NBX; p++) { stage_box<false>(tmWv, sb, p, cta, rank); stage_box<true>(tmWo, sb, p, cta, rank); }
  }
  if (tid == 0) {
    if ((sb & 0xFFFFFF) != SB0) g_err = 100;
    for (int p = 0; p < 5; p++) { mbar_init(sb + BAR_F + 8 * p, 1); mbar_init(sb + BAR_E + 8 * p, p == 2 ? (E2L ? 3 : 12) : p == 1 ? 15 : 24); }
    mbar_init(sb + BAR_M, 1); mbar_init(sb + BAR_MOK, 24); mbar_init(sb + BAR_XM, 1); mbar_init(sb + BAR_XF, 2);
    mbar_init(sb + BAR_XT, 1); mbar_init(sb + BAR_MF, 8); mbar_init(sb + BAR_OG, 1);
    for (int p = 0; p < 5; p++) mbar_expect_tx(sb + BAR_F + 8 * p, 16384);
    for (int p = 0; p < 16; p++) sts32(sb + OFF_SAFE + 4 * p, 0);
    for (int p = 0; p < 32; p++) sts32(sb + OFF_ONE + 4 * p, 0x3F803F80);
    asm volatile("fence.mbarrier_init.release.cluster;" ::: "memory");
    fence_async();
  }
  __syncthreads();
  asm volatile("barrier.cluster.arrive.relaxed.aligned;" ::: "memory");
  asm volatile("barrier.cluster.wait.aligned;" ::: "memory");

  if (wg == 0) chain_a(tmWo, tmWq, sb, keep(tid), cta, rank);
  else if (wg == 1) chain_q(x0, mem0, sb, keep(tid), cta, rank);
  else chain_v(tmWv, tmWk, sb, keep(tid), cta, rank);
  asm volatile("barrier.cluster.arrive.release.aligned;" ::: "memory");
  asm volatile("barrier.cluster.wait.acquire.aligned;" ::: "memory");
}

namespace W {
constexpr int NP = 25, NBC = 11, NW = NP + NBC;
constexpr int PRS = 37, PW = 43 * 2048;
constexpr int OFF_W = 0;
constexpr int OFF_R = 2 * PW;
constexpr int BRS = 37, VSS = 39;
constexpr int OFF_WO = 0, OFF_Y = 81920;
constexpr int OFF_X = OFF_Y + 2 * (40 - BRS) * 2048;
constexpr int OFF_WV = OFF_X + 40960;
constexpr int OFF_S = OFF_WV + VSS * 2048;
constexpr int COL = 976;
constexpr int OFF_T = OFF_X + 16384;
constexpr int OFF_H = OFF_S + 7696;
constexpr int OFF_BAR = OFF_H + 8 * COL;
constexpr int OFF_SAFE = OFF_BAR + 256;
constexpr int SMEM = 232448;
static_assert(OFF_SAFE + 64 <= SMEM && OFF_R + 40960 <= OFF_BAR, "");
constexpr uint32_t SB0 = 1024;
constexpr int BAR_F = OFF_BAR, BAR_E = OFF_BAR + 40, BAR_G = OFF_BAR + 80, BAR_W = OFF_BAR + 160, BAR_R = OFF_BAR + 176;
constexpr int NB_G0 = 1, NB_SG = 4, NB_B = 5, NB_AS = 6, NB_SG1 = 7, NB_RED = 8, NB_SF = 9, NB_R = 11, NB_TD = 12, NB_RED3 = 13;
}
#define WDP 0
#define WDB 0
#define FSL 1
#define FSW 1
#define FSA 2
#define WBAR_SYNC(id, n) bar_sync(id, n)
#define WBAR_ARRIVE(id, n) bar_arrive(id, n)

__device__ __forceinline__ uint64_t rdesc(int off, int kk) { return mkdesc(W::SB0 + off + kk * 32, 16, 1024); }
__device__ __forceinline__ uint64_t gdesc(int off, int kk) { return mkdesc_ns(W::SB0 + off + kk * 1024, 512, 512) | ((uint64_t)2 << 62); }
__device__ __forceinline__ uint32_t frag_addr(uint32_t base, int tid) {
  const int i = (tid >> 3) & 3, r = tid & 7;
  return base + (r + (i >> 1) * 8) * 128 + (((2 * ((tid >> 5) & 3) + (i & 1)) ^ r) << 4);
}
template <int NK>
__device__ __forceinline__ void load_frags(uint32_t (&wf)[NK][4], uint32_t base, int tid) {
  const uint32_t a0 = frag_addr(base, tid);
#pragma unroll
  for (int k = 0; k < NK; k++) ldsm4t(wf[k], a0 + k * 2048);
}
__device__ __forceinline__ void red_tile(const float* d, int seg, int col0, int tid) {
  float* p = g_x + (size_t)(seg * 32 + 2 * (tid & 3)) * DM + col0 + ((tid >> 5) & 3) * 16 + ((tid >> 2) & 7) * 2;
#pragma unroll
  for (int j = 0; j < 8; j++)
    asm volatile("red.relaxed.gpu.global.add.v2.f32 [%0],{%1,%2};" ::"l"(p + ((j >> 1) * 8 + (j & 1)) * DM), "f"(d[4 * (j >> 1) + (j & 1)]), "f"(d[4 * (j >> 1) + 2 + (j & 1)]) : "memory");
}

__device__ __forceinline__ void work_p(const CUtensorMap& tmWo, uint32_t sb, int pc, const int WG, int tid0) {
  using namespace W;
  asm volatile("setmaxnreg.inc.sync.aligned.u32 208;");
  int spin = 0;
  const int ks = pc / 5, col0 = (pc % 5) * 128 + WG * 64;
  const uint32_t wb = sb + OFF_W + WG * PW;
  uint32_t wf[PRS][4];
#pragma unroll 1
  for (int hf = 0; hf < 2; hf++) {
    const int nk = hf ? 80 - PRS : PRS;
    if ((tid0 & 127) == 0) {
      mbar_expect_tx(sb + BAR_W + 8 * WG, nk * 2048);
      for (int i = 0; i < nk; i++) tma2d(wb + i * 2048, &tmWo, col0, ks * 19 * 64 + (i < PRS ? 2 * i + hf : PRS + i) * 16, sb + BAR_W + 8 * WG);
    }
    __syncwarp();
    mwait(sb + BAR_W + 8 * WG, hf, spin);
    permute_cols(wb, tid0 & 127, nk * 64);
    if (hf == 1 && ks < 4) for (int it = 39 * 64 + (tid0 & 127) - 64; it < 43 * 64; it += 128) {
      const uint32_t a = wb + (it >> 2) * 128 + (((2 * (it & 3)) ^ ((it >> 2) & 6)) << 4);
      if (it >= 39 * 64) { sts128(a, make_uint4(0, 0, 0, 0)); sts128(a + 16, make_uint4(0, 0, 0, 0)); }
    }
    fence_async();
    WBAR_SYNC(NB_G0 + WG, 128);
    if (hf == 0) {
      load_frags<PRS>(wf, wb, tid0);
      fence_async();
      WBAR_SYNC(NB_G0 + WG, 128);
    }
  }
#pragma unroll 1
  for (int k = 0; k < NSTEP; k++) {
    float d[32];
#pragma unroll
    for (int f = 0; f < 20; f++) {
      mwait(sb + BAR_F + 8 * (f % 5), (f / 5) & 1, spin);
      if (f == 0 && WG == 0 && pc == WW) WTS(k, 1);
      wg_fence();
#pragma unroll
      for (int kk = 0; kk < 4; kk++) {
        const int q = 4 * f + kk;
        if (q < 2 * PRS && !(q & 1)) wgmma_rs64(d, wf[q < 2 * PRS ? q >> 1 : 0], rdesc(OFF_R + (f % 5) * 8192, kk), q);
        else wgmma_ts64(d, desc_at(mkdesc(SB0 + OFF_W + (q < 2 * PRS ? q >> 1 : q - PRS) * 2048, 8192, 1024), WG * PW), rdesc(OFF_R + (f % 5) * 8192, kk), 1);
        if (kk == 0 && f > 0) {
          wg_commit();
          wg_wait<1>();
          if ((tid0 & 31) == 0) mbar_arrive(sb + BAR_E + 8 * ((f - 1) % 5));
        }
      }
      wg_commit();
    }
    wg_wait<0>();
    if ((tid0 & 31) == 0) mbar_arrive(sb + BAR_E + 32);
    if (WG == 0 && pc == WW) WTS(k, 2);
    if (k < NSEG) red_tile(d, k, col0, tid0);
    if (k >= LAG) red_tile(d + 16, k - LAG, col0, tid0);
    if (WG == 0 && pc == WW) WTS(k, 13);
    WBAR_SYNC(NB_SG, 288);
  }
  if (spin >= SPIN_TOT) g_err = 11;
}
__device__ __forceinline__ void work_p_producer(uint32_t sb, int pc) {
  using namespace W;
  int spin = 0;
  const int ks = pc / 5;
#pragma unroll 1
  for (int k = 0; k < NSTEP; k++) {
    const uint32_t lo = k < NSEG ? 0 : 4096, len = k < LAG || k >= NSEG ? 4096 : 8192;
    const uint8_t* src = &g_o[k % ORING][ks * 19][lo];
    cwait(CN_O + k * 5 + ks, ks == 4 ? 20 : 19, spin);
    fence_async_all();
    if (pc == WW) WTS1(k, 0);
#pragma unroll 1
    for (int u = 0; u < 4; u++) {
#pragma unroll
      for (int st = 0; st < 5; st++) {
        mwait(sb + BAR_E + 8 * st, (u & 1) ^ 1, spin);
        if (elect_one()) {
          if (st == 4 && u == 3 && ks < 4) mbar_arrive(sb + BAR_F + 8 * st);
          else {
            mbar_expect_tx(sb + BAR_F + 8 * st, len);
            bulk_g2s(sb + OFF_R + st * 8192 + lo, src + (u * 5 + st) * 8192, len, sb + BAR_F + 8 * st);
          }
        }
      }
    }
  }
  if (spin >= SPIN_TOT) g_err = 12;
}
template <int DMS>
__device__ __forceinline__ void work_ln(const int kind, int r, int lane, bf16* out) {
  int spin = 0;
  const int l = kind & 1;
  const int rp = kind < 2 ? (r & 1) * 16 + (r >> 1) : r;
  const uint32_t sw = ((((lane >> 1) & 7) ^ (rp & 7)) << 4) + (lane & 1) * 8;
  uint8_t* dst = kind < 2 ? g_xnb[l * LAG] + (lane >> 4) * 8192 + l * 4096 + rp * 128 + sw
               : kind == 2 ? g_xn[LAG] + (r >> 3) * 4096 + 2048 + (lane >> 4) * 1024 + (r & 7) * 128 + sw
                           : reinterpret_cast<uint8_t*>(out) + r * 1280 + lane * 8;
  if (FSL && kind < 2) {
#pragma unroll
    for (int m = 0; m < 5; m++) asm volatile("st.global.v2.b32 [%0],{%1,%1};" ::"l"(dst + m * DMS), "r"(SENT) : "memory");
    fence_gpu();
  }
#pragma unroll 1
  for (int s = 0; s < NSEG; s++) {
    float* xr = g_x + (size_t)(s * 32 + r) * DM;
    float4 v[5];
    if (kind < 2) {
#pragma unroll
      for (int u = 0; u < 5; u++) {
        const int p = u * 32 + lane;
        stg128((p < 80 ? g_ob[s + l * LAG] + (l * 32 + r) * 1280 : g_y[l] + (size_t)s * 40960 + (r - 1) * 1280) + p * 16, make_uint4(SENT, SENT, SENT, SENT));
      }
      if (FSL && s + 1 < NSEG) {
#pragma unroll
        for (int m = 0; m < 5; m++) asm volatile("st.global.v2.b32 [%0],{%1,%1};" ::"l"(dst + 81920 + m * DMS), "r"(SENT) : "memory");
      }
      if (lane == 0) cwait(CN_P + s + l * LAG, W::NP, spin);
      __syncwarp();
      if (r == 0 && lane == 0 && (l == 0 || s + LAG >= NSEG)) WTS1(s + l * LAG, 3);
#pragma unroll
      for (int m = 0; m < 5; m++) v[m] = ld_relaxed4f(xr + m * 128 + lane * 4);
    } else {
      if (lane == 0) cwait(CN_L + s + l * LAG, s + l * LAG < LAG || s + l * LAG >= NSEG ? 32 : 64, spin);
      __syncwarp();
#pragma unroll
      for (int m = 0; m < 5; m++) v[m] = ld_relaxed4f(xr + m * 128 + lane * 4);
      if (lane == 0) cwait(CN_W + l * 64 + s, 10, spin);
      __syncwarp();
      if (r == 0 && lane == 0 && (l == 0 || s + LAG >= NSEG)) WTS1(s + l * LAG, 11);
      const uint8_t* yp = g_y[l] + (size_t)s * 40960 + (lane >> 4) * 4096 + r * 128 + sw;
      float2 y[5];
      bool bad;
      do {
        bad = false;
#pragma unroll
        for (int m = 0; m < 5; m++) y[m] = ld_relaxed2f(yp + m * 8192);
#pragma unroll
        for (int m = 0; m < 5; m++) bad |= __float_as_uint(y[m].x) == SENT || __float_as_uint(y[m].y) == SENT;
        spin += 16;
      } while (__any_sync(0xffffffffu, bad && spin < SPIN_TOT));
#pragma unroll
      for (int m = 0; m < 5; m++) {
        v[m].x += bf_lo(__float_as_uint(y[m].x)); v[m].y += bf_hi(__float_as_uint(y[m].x));
        v[m].z += bf_lo(__float_as_uint(y[m].y)); v[m].w += bf_hi(__float_as_uint(y[m].y));
        if (kind == 2) *reinterpret_cast<float4*>(xr + m * 128 + lane * 4) = v[m];
      }
    }
    if (FSL == 3 && kind < 2 && lane == 0) csignal_fast(CN_G + s + l * LAG);
    if (kind < 3) ln_row(v);
#pragma unroll
    for (int m = 0; m < 5; m++)
      asm volatile("st.global.v2.b32 [%0],{%1,%2};" ::"l"(dst + m * DMS), "r"(pack_bf16(v[m].x, v[m].y)), "r"(pack_bf16(v[m].z, v[m].w)) : "memory");
    dst += DMS == 256 ? 40960 : 81920;
    __syncwarp();
    if (r == 0 && lane == 0 && (l == 0 || s + LAG >= NSEG)) WTS1(s + l * LAG, kind < 2 ? 4 : 12);
    if (lane == 0 && kind < (NOWORK ? 2 : 3)) {
      if (FSL && kind < 2) csignal_fast(CN_G + s + l * LAG);
      csignal_t(kind < 2 ? CN_L + s + l * LAG : CN_X + s + LAG, kind);
    }
  }
  if (spin >= SPIN_TOT) g_err = 13;
}

__device__ __forceinline__ void work_prep(const bf16* x0, const bf16* mem0, int r, int lane) {
  int spin = 0;
#pragma unroll 1
  for (int k = NPRE; k < NSTEP; k++) {
    if (lane < 20) prefetch_l2(x0 + (size_t)min(k * 32 + r + (lane < 10 ? 0 : 16), SEQ - 1) * DM + (lane % 10) * 64);
    if (lane == 0) cwait(CN_O + (k - NPRE) * 5, 1, spin);
    __syncwarp();
#pragma unroll 1
    for (int h = 0; h < 2; h++) {
      uint2 u[5];
      ln0_load(x0, u, min(k * 32 + r + 16 * h, SEQ - 1), lane);
      prep_row(u, mem0, k, r + 16 * h, lane);
    }
    __syncwarp();
    if (lane == 0) csignal(CN_X + k);
  }
  if (spin >= SPIN_TOT) g_err = 19;
}

__device__ __forceinline__ void stage_qkv(const bf16* wqkv, uint32_t base, int T, int bc, int tid) {
  const int q = tid & 15;
  const bool ok = q < 15 && bc * 60 + 4 * q < DM;
  const bf16* src = wqkv + T * DM + bc * 60 + 4 * q;
#pragma unroll 1
  for (int k0 = tid >> 4; k0 < 640; k0 += 80) {
    uint2 v[10];
#pragma unroll
    for (int u = 0; u < 10; u++) v[u] = ok ? *reinterpret_cast<const uint2*>(src + (size_t)(k0 + 8 * u) * 1920) : make_uint2(0, 0);
#pragma unroll
    for (int u = 0; u < 10; u++) sts64(base + (k0 + 8 * u) * 128 + (((q >> 1) ^ (k0 & 7)) << 4) + (q & 1) * 8, v[u].x, v[u].y);
  }
}
struct AttAddr { uint32_t qa, qb, ka, oa, ob, ml; };
__device__ __forceinline__ AttAddr att_addr(uint32_t sb, int bc, int hh, int tid) {
  using namespace W;
  const int r = tid & 7, m = (tid >> 3) & 3, g = (tid >> 2) & 7, t = tid & 3, lp = (tid >> 5) & 3;
  const int f2 = r < 4 ? 20 * hh + 16 + r : 60;
  const uint32_t tb = sb + OFF_T + 2 * lp * COL;
  const int fa = 20 * hh + (m >> 1) * 8 + r, pc = 2 * (lp & 1) + (m & 1);
  const uint32_t o0 = sb + OFF_S + (lp >> 1) * 3840;
  AttAddr x;
  x.qa = keep(tb + (m & 1) * COL + (20 * hh + (m >> 1) * 8 + r) * 16);
  x.qb = keep(tb + (m & 1) * COL + f2 * 16);
  x.ka = keep(tb + (m < 2 ? 20 * hh + 8 * m + r : f2) * 16);
  x.oa = keep(o0 + fa * 64 + ((pc ^ ((bc * 60 + fa) >> 1)) & 3) * 16);
  x.ob = keep(r < 4 ? o0 + f2 * 64 + ((pc ^ ((bc * 60 + f2) >> 1)) & 3) * 16 : sb + OFF_S + 7680);
  x.ml = keep((2 * t > g ? 0xFFFFu : 0u) | (2 * t + 1 > g ? 0xFFFF0000u : 0u));
  return x;
}
__device__ __forceinline__ void release_tiles(uint32_t sb, int tid) {
  fence_async();
  __syncwarp();
  if ((tid & 31) < 3) mbar_arrive(sb + W::BAR_E + 16 + 8 * (tid & 3));
}
__device__ __forceinline__ void attend(uint32_t sb, const AttAddr& x, int k0, int lp, int tid) {
  using namespace W;
  const uint32_t hd = OFF_H - OFF_T - lp * COL;
  const float scl = 0.22360679774997896f * 1.4426950408889634f;
  float sc[3][4];
  uint32_t v[3][4];
  {
    uint32_t q[4], q8a, q8b, k[3][4];
    ldsm4t(q, x.qa);
    ldsm4t(k[0], x.ka + hd); ldsm4t(k[1], x.ka + 8 * COL); ldsm4t(k[2], x.ka + 9 * COL);
    ldsm2t(q8a, q8b, x.qb);
#pragma unroll
    for (int c = 0; c < 3; c++) { sc[c][0] = sc[c][1] = sc[c][2] = sc[c][3] = 0.f; mma16816(sc[c], q[0], q[1], q[2], q[3], k[c][0], k[c][1]); }
#pragma unroll
    for (int c = 0; c < 3; c++) mma1688(sc[c], q8a, q8b, k[c][2]);
    stsm4t(x.ka + hd, k[2][0], k[2][1], k[2][2], k[2][3]);
  }
  ldsm4(v[0], x.ka + hd + 4 * COL); ldsm4(v[1], x.ka + 16 * COL); ldsm4(v[2], x.ka + 17 * COL);
  stsm4(x.ka + hd + 4 * COL, v[2][0], v[2][1], v[2][2], v[2][3]);
  release_tiles(sb, tid);
  const bool lo0 = x.ml & 1, lo1 = (int)x.ml < 0, first = k0 == (lp >> 1) * LAG;
  uint32_t pw[2];
  float inv[2];
#pragma unroll
  for (int h = 0; h < 2; h++) {
    float y0 = lo0 ? sc[h][2 * h] : sc[h + 1][2 * h], y1 = lo1 ? sc[h][2 * h + 1] : sc[h + 1][2 * h + 1];
    if (h == 0 && first) { y0 = lo0 ? -INFINITY : y0; y1 = lo1 ? -INFINITY : y1; }
    const float mx = quad_max(fmaxf(y0, y1)) * -scl;
    y0 = ex2(fmaf(y0, scl, mx)); y1 = ex2(fmaf(y1, scl, mx));
    pw[h] = pack_bf16(y0, y1);
    inv[h] = y0 + y1;
  }
  float o[3][4];
  const uint32_t a0 = pw[0] & x.ml, a2 = pw[0] & ~x.ml, a3 = pw[1] & x.ml, a5 = pw[1] & ~x.ml, z0 = tid >> 10, z1 = tid >> 11;
#pragma unroll
  for (int j = 0; j < 3; j++) { o[j][0] = o[j][1] = o[j][2] = o[j][3] = 0.f; mma16816(o[j], a0, z0, a2, a3, v[0][j], v[1][j]); }
#pragma unroll
  for (int j = 0; j < 3; j++) mma1688(o[j], z1, a5, v[2][j]);
  inv[0] = rcp(quad_sum(inv[0])); inv[1] = rcp(quad_sum(inv[1]));
  stsm4t(x.oa, pack_bf16(o[0][0] * inv[0], o[0][1] * inv[0]), pack_bf16(o[0][2] * inv[1], o[0][3] * inv[1]),
         pack_bf16(o[1][0] * inv[0], o[1][1] * inv[0]), pack_bf16(o[1][2] * inv[1], o[1][3] * inv[1]));
  stsm2t(x.ob, pack_bf16(o[2][0] * inv[0], o[2][1] * inv[0]), pack_bf16(o[2][2] * inv[1], o[2][3] * inv[1]));
  fence_async();
}
template <bool IS_V>
__device__ __forceinline__ void work_b(const CUtensorMap& tmBo, const bf16* wqkv, uint32_t sb, int bc, const int wg, int tid0) {
  using namespace W;
  if (!IS_V) asm volatile("setmaxnreg.inc.sync.aligned.u32 208;");
  else asm volatile("setmaxnreg.dec.sync.aligned.u32 72;");
  constexpr int NR = IS_V ? 40 - VSS : BRS;
  const int WG = IS_V ? 2 : wg;
  const uint32_t yo = WG * (40 - BRS) * 2048;
  int spin = 0;
  uint32_t wf[NR][4];
  if (!IS_V) {
    const uint32_t wb = sb + (WG ? OFF_WO : OFF_WV);
    stage_qkv(wqkv, wb, WG, bc, tid0 & 127);
    WBAR_SYNC(NB_G0 + WG, 128);
    load_frags<NR>(wf, wb, tid0);
#pragma unroll
    for (int k = NR; k < 40; k++) sts128(sb + OFF_Y + yo + (k - NR) * 2048 + (tid0 & 127) * 16, lds128(wb + k * 2048 + (tid0 & 127) * 16));
    fence_async();
  }
  WBAR_SYNC(NB_B, 384);
  if (WG == 1 && bc < 10) {
    if ((tid0 & 127) == 0) {
      mbar_expect_tx(sb + BAR_W, 81920);
      for (int i = 0; i < 10; i++) tma2d(sb + OFF_WO + i * 8192, &tmBo, bc * 64, i * 64, sb + BAR_W);
    }
    __syncwarp();
    mwait(sb + BAR_W, 0, spin);
  }
  if (IS_V) {
    stage_qkv(wqkv, sb + OFF_WV, 2, bc, tid0 & 127);
    WBAR_SYNC(NB_G0 + 2, 128);
    load_frags<NR>(wf, sb + OFF_WV + VSS * 2048, tid0);
  }
  fence_async();
  WBAR_SYNC(NB_B, 384);
  const int wu = uni((tid0 >> 5) & 3);
  uint32_t nredo = 0;
  const AttAddr aa = att_addr(sb, bc, WG, tid0);
#pragma unroll 1
  for (int k = 0; k < NSTEP + (WG == 0); k++) {
    if (WG || k < NSTEP) {
    {
      float d[32];
#define QKV_STEP(Q, DB)                                                                                                                  \
  {                                                                                                                                      \
    const int q = (Q);                                                                                                                   \
    if (IS_V ? q >= VSS : q < NR) wgmma_rs64(d, wf[IS_V ? (q >= VSS ? q - VSS : 0) : (q < NR ? q : 0)], DB, q);                          \
    else if (IS_V) wgmma_ts64(d, mkdesc(SB0 + OFF_WV + q * 2048, 8192, 1024), DB, q);                                                    \
    else wgmma_ts64(d, desc_at(mkdesc(SB0 + OFF_Y + (q - NR) * 2048, 8192, 1024), yo), DB, 1);                                           \
  }
#pragma unroll
      for (int c = 0; c < 10; c++) {
        mwait(sb + BAR_F + 8 * (c % 5), c / 5, spin);
        if (c == 0 && bc == 0 && WG != 1) WTS(k, WG ? 15 : 6);
        wg_fence();
#pragma unroll
        for (int kk = 0; kk < 4; kk++) {
          QKV_STEP(4 * c + kk, rdesc(OFF_X + (c % 5) * 8192, kk));
        }
        wg_commit();
        if (c > 0 && c <= 7) {
          wg_wait<1>();
          if ((tid0 & 31) == 0) mbar_arrive(sb + BAR_E + 8 * ((c - 1) % 5));
        }
      }
      wg_wait<0>();
      if (bc == 0 && WG != 1) WTS(k, 16 + WG / 2);
      uint32_t pk[16];
#pragma unroll
      for (int q = 0; q < 16; q++) pk[q] = pin(pack_bf16(d[2 * q], d[2 * q + 1]));
      const int tid = fresh(tid0), m = (tid >> 3) & 3;
      const uint32_t a = pin(sb + OFF_T + min(wu * 16 + (m & 1) * 8 + (tid & 7), 60) * 16 + (8 * WG + (m >> 1)) * COL);
      if (!FSL) WBAR_SYNC(NB_B, 384);
      else {
        const float c0 = ((d[0] + d[1]) + (d[4] + d[5])) + ((d[8] + d[9]) + (d[12] + d[13]));
        const float c1 = ((d[16] + d[17]) + (d[20] + d[21])) + ((d[24] + d[25]) + (d[28] + d[29]));
        if (__builtin_expect(bar_red_or(NB_RED3, 384, IS_V && ((c0 != c0 && k < NSEG) || (c1 != c1 && k >= LAG))), 0)) {
          if (IS_V && wu == 0) { cwait(CN_L + k, k < LAG || k >= NSEG ? 32 : 64, spin); fence_async_all(); }
#pragma unroll
          for (int c = 0; c < 10; c++) {
            if (IS_V && wu == 0 && elect_one()) { mbar_expect_tx(sb + BAR_R + 8, 8192); bulk_g2s(sb + OFF_X + 32768, g_xnb[k] + c * 8192, 8192, sb + BAR_R + 8); }
            __syncwarp();
            mwait(sb + BAR_R + 8, c & 1, spin);
            wg_fence();
#pragma unroll
            for (int kk = 0; kk < 4; kk++) QKV_STEP(4 * c + kk, rdesc(OFF_X + 32768, kk));
            wg_commit();
            wg_wait<0>();
            bar_sync(NB_RED3, 384);
          }
#pragma unroll
          for (int q = 0; q < 16; q++) pk[q] = pin(pack_bf16(d[2 * q], d[2 * q + 1]));
        }
      }
#undef QKV_STEP
#pragma unroll
      for (int p = 0; p < 4; p++) stsm4(a + 2 * p * COL, pk[4 * p], pk[4 * p + 1], pk[4 * p + 2], pk[4 * p + 3]);
    }
    WBAR_SYNC(NB_TD, 448);
    if (bc == 0 && WG == 0) WTS(k, 7);
    if (bc * 3 + WG < NH && (wu < 2 ? k < NSEG : k >= LAG)) attend(sb, aa, k, wu, fresh(tid0));
    else release_tiles(sb, tid0);
    if (bc == 0 && WG == 0) WTS(k, 8);
    WBAR_SYNC(NB_AS, 416);
    }
    const int s = k - (1 - WG) * (LAG + 1);
    if (!IS_V && bc < 10 && s >= 0 && s < NSEG) {
      float d[16];
#pragma unroll
      for (int f = 0; f < 5; f++) {
        mwait(sb + BAR_G + 40 * WG + 8 * f, s & 1, spin);
        if (f == 0 && bc == 0) WTS(k - 1 + WG, WG || k > NSEG ? 20 : 23);
        wg_fence();
#pragma unroll
        for (int kk = 0; kk < 8; kk++) {
          wgmma_tt32(d, mkdesc(SB0 + OFF_WO + (8 * f + kk) * 2048, 8192, 1024), gdesc(OFF_X + f * 8192, kk), f | kk);
          if (kk == 1 && f > 0) {
            wg_commit();
            wg_wait<1>();
            if ((tid0 & 31) < 3) mbar_arrive(sb + BAR_E + 8 * (f - 1));
          }
        }
        wg_commit();
      }
      wg_wait<0>();
      if (WG == 1 && FSA) {
        const float chk = ((d[0] + d[1]) + (d[4] + d[5])) + ((d[8] + d[9]) + (d[12] + d[13]));
        if (__builtin_expect(bar_red_or(NB_RED, 128, chk != chk), 0)) {
          if (wu == 0) { cwait(CN_A + k, NBC, spin); fence_async_all(); }
#pragma unroll
          for (int q = 0; q < 16; q++) d[q] = 0.f;
#pragma unroll 1
          for (int f = 0; f < 5; f++) {
            if (wu == 0 && elect_one()) { mbar_expect_tx(sb + BAR_W + 8, 8192); bulk_g2s(sb + OFF_X + 32768, g_ob[k] + f * 8192, 8192, sb + BAR_W + 8); }
            __syncwarp();
            mwait(sb + BAR_W + 8, nredo & 1, spin);
            nredo++;
            wg_fence();
#pragma unroll
            for (int kk = 0; kk < 8; kk++)
              wgmma_tt32(d, desc_at(mkdesc(SB0 + OFF_WO + kk * 2048, 8192, 1024), f * 16384), gdesc(OFF_X + 32768, kk), 1);
            wg_commit();
            wg_wait<0>();
            bar_sync(NB_RED, 128);
          }
        }
      }
      else if (WG) bar_sync(NB_RED, 128);
      else {
        if ((tid0 & 31) < 3) mbar_arrive(sb + BAR_E + 32);
        WBAR_SYNC(NB_SF, 160);
      }
      if (bc == 0) WTS(k - 1 + WG, WG || k > NSEG ? 10 : 24);
      const int tid = fresh(tid0), m = (tid >> 3) & 3, row = (m >> 1) * 16 + 2 * (tid & 7);
      const uint32_t a = sb + (WG ? OFF_X + 32768 : OFF_S) + row * 128 + (((2 * wu + (m & 1)) ^ row) & 7) * 16;
#pragma unroll
      for (int p = 0; p < 2; p++)
        stsm4t(a ^ (p * 144), pack_bf16(d[8 * p], d[8 * p + 1]), pack_bf16(d[8 * p + 2], d[8 * p + 3]), pack_bf16(d[8 * p + 4], d[8 * p + 5]), pack_bf16(d[8 * p + 6], d[8 * p + 7]));
      fence_async();
      WBAR_SYNC(WG ? NB_SG : NB_SG1, 160);
    }
  }
  if (spin >= SPIN_TOT) g_err = 14;
}
__device__ __forceinline__ bool b_job(int k, int u, int bc) { return u < 2 ? k < NSTEP : bc < 10 && (u == 2 ? k > LAG : k < NSEG); }
__device__ __forceinline__ void work_b_watch(uint32_t sb, int bc) {
  using namespace W;
  int spin = 0;
#pragma unroll 1
  for (int j = 0; j < 4 * NSTEP + 3; j++) {
    const int k = j >> 2, u = j & 3;
    if (u == 1 || !b_job(k, u, bc)) continue;
    cwait(u == 0 ? (FSL ? CN_G : CN_L) + k : u == 2 ? CN_A + k - 1 : (FSA ? CN_F : CN_A) + k, u ? NBC : k < LAG || k >= NSEG ? 32 : 64, spin);
    fence_async_all();
    if (bc == 0 && (u != 2 || k > NSEG)) WTS1(k + (u ? u - 3 : 0), u ? 9 : 5);
    if (elect_one()) mbar_arrive(sb + BAR_R + 8 * u);
    __syncwarp();
    if (u == 0) WBAR_SYNC(NB_R, 64);
  }
  if (spin >= SPIN_TOT) g_err = 16;
}
__device__ __forceinline__ void work_b_producer(uint32_t sb, int bc) {
  using namespace W;
  int spin = 0;
  uint32_t pe = 1;
#pragma unroll 1
  for (int j = 0; j < 4 * NSTEP + 3; j++) {
    const int k = j >> 2, u = j & 3;
    if (!b_job(k, u, bc)) continue;
    const uint32_t half = u < 2 && (k < LAG || k >= NSEG), lo = half && k >= NSEG ? 4096 : 0, len = half ? 4096 : 8192, fb = sb + (u < 2 ? BAR_F : BAR_G + 40 * (u - 2));
    const uint8_t* src = (u < 2 ? g_xnb[k] + u * 40960 : u == 2 ? g_ob[k - 1] + 40960 : g_ob[k]) + lo;
    if (u != 1) mwait(sb + BAR_R + 8 * u, (u == 2 ? k - LAG - 1 : k) & 1, spin);
#pragma unroll
    for (int f = 0; f < 5; f++) {
      mwait(sb + BAR_E + 8 * f, pe, spin);
      if (elect_one()) {
        mbar_expect_tx(fb + 8 * f, len);
        bulk_g2s(sb + OFF_X + f * 8192 + lo, src + f * 8192, len, fb + 8 * f);
      }
    }
    if (u == 0) WBAR_SYNC(NB_R, 64);
    pe ^= 1;
  }
  if (spin >= SPIN_TOT) g_err = 15;
}

__global__ void __launch_bounds__(512, 1)
k_work(const __grid_constant__ CUtensorMap tmWo, const __grid_constant__ CUtensorMap tmBo, const bf16* __restrict__ wqkv, bf16* __restrict__ out,
       const bf16* __restrict__ x0, const bf16* __restrict__ mem0) {
  using namespace W;
  extern __shared__ __align__(1024) uint8_t smem[];
  const uint32_t sb = smem_u32(smem);
  const int tid = threadIdx.x, w = blockIdx.x;
  const int wg = __shfl_sync(0xffffffffu, tid >> 7, 0);
  if (tid == 0) {
    if (sb != SB0) g_err = 101;
    for (int i = 0; i < 5; i++) { mbar_init(sb + BAR_F + 8 * i, 1); mbar_init(sb + BAR_E + 8 * i, w < NP ? 8 : 12); }
    for (int i = 0; i < 16; i++) mbar_init(sb + BAR_G + 8 * i, 1);
    for (int p = 0; p < 16; p++) sts32(sb + OFF_SAFE + 4 * p, 0);
    asm volatile("fence.mbarrier_init.release.cluster;" ::: "memory");
    int spin = 0;
    pre_wait(1, NW, spin);
    for (const uint32_t t0 = clk32(); clk32() - t0 < (w < NP ? WDP : WDB);) {}
    if (spin >= SPIN_TOT) g_err = 18;
  }
  if (tid < 8 * COL / 16) sts128(sb + OFF_H + tid * 16, make_uint4(0, 0, 0, 0));
  fence_async();
  __syncthreads();

  if (w < NP) {
    if (wg < 2) work_p(tmWo, sb, w, wg, keep(tid));
    else {
      asm volatile("setmaxnreg.dec.sync.aligned.u32 48;");
      const int aw = uni(tid >> 5) - 8;
      if (aw == 0) work_p_producer(sb, w);
      else if (aw == 1) {
#pragma unroll 1
        for (int k = 0; k < NSTEP; k++) {
          WBAR_SYNC(NB_SG, 288);
          if (elect_one()) csignal_t(CN_P + k, 3);
          __syncwarp();
        }
      } else {
        const int id = (aw - 2) * NP + w;
        if (id < 96) work_ln<16384>(id % 3, id / 3, tid & 31, out);
        else if (id < 128) work_ln<256>(3, id - 96, tid & 31, out);
        else if (id < 144 && NOWORK != 2) work_prep(x0, mem0, id - 128, tid & 31);
      }
    }
  } else {
    const int bc = w - NP;
    if (wg < 2) work_b<false>(tmBo, wqkv, sb, bc, wg, keep(tid));
    else if (wg == 2) work_b<true>(tmBo, wqkv, sb, bc, wg, keep(tid));
    else {
      asm volatile("setmaxnreg.dec.sync.aligned.u32 24;");
      const int aw = uni(tid >> 5) - 12;
      if (aw == 0) work_b_producer(sb, bc);
      else if (aw == 1) work_b_watch(sb, bc);
      else if (aw == 2) {
#pragma unroll 1
        for (int k = 0; k < NSTEP; k++) {
          WBAR_ARRIVE(NB_TD, 448);
          if (FSA == 3 && (tid & 31) == 0) csignal_fast(CN_F + k);
          WBAR_SYNC(NB_AS, 416);
          if (elect_one()) {
            const uint32_t len = bc < 10 ? 3840 : 2560;
            if (k < NSEG) {
              bulk_s2g(g_ob[k] + bc * 3840, sb + OFF_S, len);
              asm volatile("cp.async.bulk.commit_group;" ::: "memory");
              if (FSA == 1) asm volatile("cp.async.bulk.wait_group.read 0;" ::: "memory");
              if (FSA) csignal_fast(CN_F + k);
            }
            if (k >= LAG) bulk_s2g(g_ob[k] + 40960 + bc * 3840, sb + OFF_S + 3840, len);
            asm volatile("cp.async.bulk.commit_group;" ::: "memory");
            asm volatile("cp.async.bulk.wait_group 0;" ::: "memory");
          }
          __syncwarp();
          if (b_job(k, 2, bc)) WBAR_ARRIVE(NB_SF, 160);
          if (elect_one()) { fence_async_all(); csignal_t(CN_A + k, 5); }
          __syncwarp();
        }
        if (bc < 10) WBAR_SYNC(NB_SF + 1, 64), WBAR_ARRIVE(NB_SF, 160);
      } else {
#pragma unroll 1
        for (int j = 0; j < 2 * NSTEP + 1; j++) {
          const int l = (j & 1) ^ 1, s = (j >> 1) - l * (LAG + 1);
          if (l) { if (j < 2 * NSTEP) WBAR_SYNC(NB_TD, 448); else if (bc < 10) WBAR_ARRIVE(NB_SF + 1, 64); }
          if (s < 0 || s >= NSEG || bc == 10) continue;
          WBAR_SYNC(l ? NB_SG1 : NB_SG, 160);
          if (elect_one()) {
            bulk_s2g(g_y[l] + (size_t)s * 40960 + bc * 4096, sb + (l ? OFF_S : OFF_X + 32768), 4096);
            asm volatile("cp.async.bulk.commit_group;" ::: "memory");
            if (FSW) csignal_fast(CN_W + l * 64 + s);
            asm volatile("cp.async.bulk.wait_group.read 0;" ::: "memory");
            if (!FSW) csignal_fast(CN_W + l * 64 + s);
            if (!l) asm volatile("mbarrier.arrive.shared::cta.b64 _,[%0],12;" ::"r"(sb + BAR_E + 32) : "memory");
          }
          __syncwarp();
        }
      }
    }
  }
  __syncthreads();
  asm volatile("griddepcontrol.wait;" ::: "memory");
}

typedef CUresult (*EncodeFn)(CUtensorMap*, CUtensorMapDataType, cuuint32_t, void*, const cuuint64_t*, const cuuint64_t*,
                             const cuuint32_t*, const cuuint32_t*, CUtensorMapInterleave, CUtensorMapSwizzle,
                             CUtensorMapL2promotion, CUtensorMapFloatOOBfill);

static void make_map(EncodeFn enc, CUtensorMap* tm, const void* ptr, uint64_t cols, uint64_t rows, uint32_t boxc, uint32_t boxr) {
  cuuint64_t dims[2] = {cols, rows};
  cuuint64_t strides[1] = {cols * 2};
  cuuint32_t box[2] = {boxc, boxr};
  cuuint32_t es[2] = {1, 1};
  enc(tm, CU_TENSOR_MAP_DATA_TYPE_BFLOAT16, 2, const_cast<void*>(ptr), dims, strides, box, es, CU_TENSOR_MAP_INTERLEAVE_NONE,
      CU_TENSOR_MAP_SWIZZLE_128B, CU_TENSOR_MAP_L2_PROMOTION_L2_256B, CU_TENSOR_MAP_FLOAT_OOB_FILL_NONE);
}

extern "C" void kernel_launch(void* const* d_in, const int* in_sizes, int n_in, void* d_out, int out_size) {
  const bf16* x0 = (const bf16*)d_in[0];
  const bf16* mem0 = (const bf16*)d_in[1];
  const bf16* Wq = (const bf16*)d_in[2];
  const bf16* Wk = (const bf16*)d_in[3];
  const bf16* Wv = (const bf16*)d_in[4];
  const bf16* Wo = (const bf16*)d_in[5];
  const bf16* Bqkv = (const bf16*)d_in[8];
  const bf16* Bwo = (const bf16*)d_in[9];
  bf16* out = (bf16*)d_out;

  static EncodeFn enc = nullptr;
  if (!enc) {
    void* fn = nullptr;
    cudaDriverEntryPointQueryResult qr;
    cudaGetDriverEntryPoint("cuTensorMapEncodeTiled", &fn, cudaEnableDefault, &qr);
    enc = (EncodeFn)fn;
    cudaFuncSetAttribute(k_chain, cudaFuncAttributeMaxDynamicSharedMemorySize, C::SMEM);
    cudaFuncSetAttribute(k_work, cudaFuncAttributeMaxDynamicSharedMemorySize, W::SMEM);
  }
  CUtensorMap tmWq, tmWk, tmWv, tmWo, tmWp, tmBo;
  make_map(enc, &tmWq, Wq, NH * DH, DM, 64, 128);
  make_map(enc, &tmWk, Wk, NH * DH, DM, 64, 128);
  make_map(enc, &tmWv, Wv, NH * DH, DM, 64, 128);
  make_map(enc, &tmWo, Wo, DM, NH * DH, 64, 64);
  make_map(enc, &tmWp, Wo, DM, NH * DH, 64, 16);
  make_map(enc, &tmBo, Bwo, DM, DM, 64, 64);

  cudaStream_t st = cudaStreamPerThread;
  cudaLaunchAttribute at[1];
  at[0].id = cudaLaunchAttributeProgrammaticStreamSerialization; at[0].val.programmaticStreamSerializationAllowed = 1;
  {
    cudaLaunchConfig_t cfg = {};
    cfg.gridDim = dim3(96); cfg.blockDim = dim3(384); cfg.dynamicSmemBytes = C::SMEM; cfg.stream = st;
    cfg.attrs = at; cfg.numAttrs = 0;
    cudaLaunchKernelEx(&cfg, k_chain, tmWq, tmWk, tmWv, tmWo, x0, mem0);
  }
  cudaLaunchConfig_t cfg = {};
  cfg.gridDim = dim3(W::NW); cfg.blockDim = dim3(512); cfg.dynamicSmemBytes = W::SMEM; cfg.stream = st;
  cfg.attrs = at; cfg.numAttrs = NOWORK == 2 ? 0 : 1;
  cudaLaunchKernelEx(&cfg, k_work, tmWp, tmBo, Bqkv, out, x0, mem0);
}
```

```cpp
#include <cuda_runtime.h>
#include <cuda_bf16.h>
#include <cuda.h>
#include <stdint.h>

typedef __nv_bfloat16 bf16;

constexpr int SEQ = 2048, DM = 640, NH = 32, DH = 192, NSEG = 64;
#define LAG 5
constexpr int NSTEP = NSEG + LAG;
constexpr int NPRE = 4;
constexpr uint32_t SENT = 0xFFFFFFFFu;

constexpr int MAIL9 = 288 * 2048, MAIL_BYTES = MAIL9 + 64 * 3072;
__device__ __align__(1024) uint8_t g_xn[NSTEP][81920];
__device__ __align__(1024) uint8_t g_xnb[NSTEP][81920];
__device__ __align__(1024) uint8_t g_ob[NSTEP][81920];
__device__ __align__(1024) uint8_t g_y[2][NSEG * 40960];
#define ORING 8
static_assert(ORING > LAG, "a slot is free again LAG + 1 steps later");
__device__ __align__(1024) uint8_t g_o[ORING][96][8192];
__device__ __align__(1024) float g_x[SEQ * DM];
constexpr int EX_MAIL = 0;
constexpr int EX_M = 2 << 20;
constexpr int EX_FLAG = EX_M + NSTEP * 20480;
static_assert(EX_FLAG + NSTEP * 3072 <= (4 << 20), "");
__device__ __align__(1024) uint8_t g_ex[8 << 20];
__host__ __device__ __forceinline__ uint8_t* ex_window(uint8_t* p) { return reinterpret_cast<uint8_t*>((reinterpret_cast<uint64_t>(p) + (4 << 20) - 1) & ~(uint64_t)((4 << 20) - 1)); }
enum { CN_P = 0, CN_L = 128, CN_A = 256, CN_W = 384, CN_X = 512, CN_F = 640, CN_G = 768, CN_O = 896, CN_NUM = CN_O + 5 * NSTEP };
__device__ __align__(128) uint32_t g_cnt[CN_NUM][32];
__device__ __align__(128) uint32_t g_ticket[2][32];
__device__ int g_err;
#define TS(jj, i)
#define TS1(jj, i)
#define PTS(i)
#define TSB(jj, i)
#define TSV(jj, i, v)
#define TS_FLUSH(jj)
#define WTS(b, k)
#define WTS1(b, k)
#define WW -1

__device__ __forceinline__ uint32_t smem_u32(const void* p) { return (uint32_t)__cvta_generic_to_shared(p); }
__device__ __forceinline__ uint32_t clk32() { uint32_t t; asm volatile("mov.u32 %0, %%clock;" : "=r"(t)::"memory"); return t; }
__device__ __forceinline__ uint32_t mapa(uint32_t a, uint32_t r) { uint32_t o; asm("mapa.shared::cluster.u32 %0,%1,%2;" : "=r"(o) : "r"(a), "r"(r)); return o; }
__device__ __forceinline__ void mbar_init(uint32_t bar, uint32_t cnt) { asm volatile("mbarrier.init.shared::cta.b64 [%0],%1;" ::"r"(bar), "r"(cnt) : "memory"); }
__device__ __forceinline__ void mbar_expect_tx(uint32_t bar, uint32_t bytes) { asm volatile("mbarrier.arrive.expect_tx.shared::cta.b64 _,[%0],%1;" ::"r"(bar), "r"(bytes) : "memory"); }
__device__ __forceinline__ void mbar_arrive(uint32_t bar) { asm volatile("mbarrier.arrive.shared::cta.b64 _,[%0];" ::"r"(bar) : "memory"); }
__device__ __forceinline__ void mbar_arrive_cluster(uint32_t bar) { asm volatile("mbarrier.arrive.shared::cluster.b64 _,[%0];" ::"r"(bar) : "memory"); }
__device__ __forceinline__ bool mbar_try(uint32_t bar, uint32_t ph) {
  uint32_t ok;
  asm volatile("{.reg .pred p; mbarrier.try_wait.parity.shared::cta.b64 p,[%1],%2; selp.u32 %0,1,0,p;}" : "=r"(ok) : "r"(bar), "r"(ph) : "memory");
  return ok;
}
__device__ __forceinline__ bool mbar_test(uint32_t bar, uint32_t ph) {
  uint32_t ok;
  asm volatile("{.reg .pred p; mbarrier.test_wait.parity.shared::cta.b64 p,[%1],%2; selp.u32 %0,1,0,p;}" : "=r"(ok) : "r"(bar), "r"(ph) : "memory");
  return ok;
}
__device__ __forceinline__ int fresh(int x) { asm volatile("" : "+r"(x)); return x; }
#define PHASE_IDS const int tid = fresh(tid0), lane = tid & 31, w = tid >> 5, g = lane >> 2, t = lane & 3; (void)w; (void)g; (void)t
__device__ __forceinline__ void bar_sync(int id, int n) { asm volatile("bar.sync %0,%1;" ::"r"(id), "r"(n) : "memory"); }
__device__ __forceinline__ void bar_arrive(int id, int n) { asm volatile("bar.arrive %0,%1;" ::"r"(id), "r"(n) : "memory"); }
__device__ __forceinline__ bool bar_red_or(int id, int n, bool v) {
  uint32_t r;
  asm volatile("{\n .reg .pred p, q;\n setp.ne.u32 q, %3, 0;\n barrier.cta.red.or.pred p, %1, %2, q;\n selp.u32 %0, 1, 0, p;\n}" : "=r"(r) : "r"(id), "r"(n), "r"((uint32_t)v) : "memory");
  return r != 0;
}
__device__ __forceinline__ void fence_async() { asm volatile("fence.proxy.async.shared::cta;" ::: "memory"); }
__device__ __forceinline__ void bulk_g2s(uint32_t dst, const void* src, uint32_t bytes, uint32_t bar) {
  asm volatile("cp.async.bulk.shared::cluster.global.mbarrier::complete_tx::bytes [%0],[%1],%2,[%3];" ::"r"(dst), "l"(src), "r"(bytes), "r"(bar) : "memory");
}
__device__ __forceinline__ void bulk_g2s_mc(uint32_t dst, const void* src, uint32_t bytes, uint32_t bar) {
  asm volatile("cp.async.bulk.shared::cluster.global.mbarrier::complete_tx::bytes.multicast::cluster [%0],[%1],%2,[%3],%4;"
               ::"r"(dst), "l"(src), "r"(bytes), "r"(bar), "h"((uint16_t)7) : "memory");
}
__device__ __forceinline__ void bulk_s2g(void* dst, uint32_t src, uint32_t bytes) {
  asm volatile("cp.async.bulk.global.shared::cta.bulk_group [%0],[%1],%2;" ::"l"(dst), "r"(src), "r"(bytes) : "memory");
}
__device__ __forceinline__ void bulk_s2c(uint32_t dst, uint32_t src, uint32_t bytes, uint32_t bar) {
  asm volatile("cp.async.bulk.shared::cluster.shared::cta.mbarrier::complete_tx::bytes [%0],[%1],%2,[%3];" ::"r"(dst), "r"(src), "r"(bytes), "r"(bar) : "memory");
}
__device__ __forceinline__ void tma2d(uint32_t dst, const CUtensorMap* tm, int c0, int c1, uint32_t bar) {
  asm volatile("cp.async.bulk.tensor.2d.shared::cluster.global.mbarrier::complete_tx::bytes [%0],[%1,{%3,%4}],[%2];"
               ::"r"(dst), "l"(tm), "r"(bar), "r"(c0), "r"(c1) : "memory");
}
__device__ __forceinline__ void tma2d_prefetch(const CUtensorMap* tm, int c0, int c1) {
  asm volatile("cp.async.bulk.prefetch.tensor.2d.L2.global.tile [%0,{%1,%2}];" ::"l"(tm), "r"(c0), "r"(c1) : "memory");
}
__device__ __forceinline__ uint32_t pack_bf16(float lo, float hi) {
  uint32_t r; asm("cvt.rn.bf16x2.f32 %0,%1,%2;" : "=r"(r) : "f"(hi), "f"(lo)); return r;
}
__device__ __forceinline__ float bf_lo(uint32_t x) { return __uint_as_float(x << 16); }
__device__ __forceinline__ float bf_hi(uint32_t x) { return __uint_as_float(x & 0xFFFF0000u); }
__device__ __forceinline__ float ex2(float x) { float y; asm("ex2.approx.ftz.f32 %0,%1;" : "=f"(y) : "f"(x)); return y; }
__device__ __forceinline__ void ldsm4(uint32_t (&r)[4], uint32_t a) {
  asm volatile("ldmatrix.sync.aligned.m8n8.x4.shared.b16 {%0,%1,%2,%3},[%4];" : "=r"(r[0]), "=r"(r[1]), "=r"(r[2]), "=r"(r[3]) : "r"(a) : "memory");
}
__device__ __forceinline__ void ldsm4t(uint32_t (&r)[4], uint32_t a) {
  asm volatile("ldmatrix.sync.aligned.m8n8.x4.trans.shared.b16 {%0,%1,%2,%3},[%4];" : "=r"(r[0]), "=r"(r[1]), "=r"(r[2]), "=r"(r[3]) : "r"(a) : "memory");
}
__device__ __forceinline__ void ldsm2(uint32_t& r0, uint32_t& r1, uint32_t a) {
  asm volatile("ldmatrix.sync.aligned.m8n8.x2.shared.b16 {%0,%1},[%2];" : "=r"(r0), "=r"(r1) : "r"(a) : "memory");
}
__device__ __forceinline__ void ldsm2t(uint32_t& r0, uint32_t& r1, uint32_t a) {
  asm volatile("ldmatrix.sync.aligned.m8n8.x2.trans.shared.b16 {%0,%1},[%2];" : "=r"(r0), "=r"(r1) : "r"(a) : "memory");
}
__device__ __forceinline__ void ldsm1(uint32_t& r0, uint32_t a) {
  asm volatile("ldmatrix.sync.aligned.m8n8.x1.shared.b16 {%0},[%1];" : "=r"(r0) : "r"(a) : "memory");
}
__device__ __forceinline__ void mma16816(float (&d)[4], uint32_t a0, uint32_t a1, uint32_t a2, uint32_t a3, uint32_t b0, uint32_t b1) {
  asm volatile("mma.sync.aligned.m16n8k16.row.col.f32.bf16.bf16.f32 {%0,%1,%2,%3},{%4,%5,%6,%7},{%8,%9},{%0,%1,%2,%3};"
               : "+f"(d[0]), "+f"(d[1]), "+f"(d[2]), "+f"(d[3]) : "r"(a0), "r"(a1), "r"(a2), "r"(a3), "r"(b0), "r"(b1));
}
__device__ __forceinline__ void mma1688(float (&d)[4], uint32_t a0, uint32_t a1, uint32_t b0) {
  asm volatile("mma.sync.aligned.m16n8k8.row.col.f32.bf16.bf16.f32 {%0,%1,%2,%3},{%4,%5},{%6},{%0,%1,%2,%3};"
               : "+f"(d[0]), "+f"(d[1]), "+f"(d[2]), "+f"(d[3]) : "r"(a0), "r"(a1), "r"(b0));
}
__device__ __forceinline__ void sts32(uint32_t a, uint32_t v) { asm volatile("st.shared.b32 [%0],%1;" ::"r"(a), "r"(v) : "memory"); }
__device__ __forceinline__ void sts64f(uint32_t a, float x, float y) { asm volatile("st.shared.v2.f32 [%0],{%1,%2};" ::"r"(a), "f"(x), "f"(y) : "memory"); }
__device__ __forceinline__ void sts128(uint32_t a, uint4 v) { asm volatile("st.shared.v4.b32 [%0],{%1,%2,%3,%4};" ::"r"(a), "r"(v.x), "r"(v.y), "r"(v.z), "r"(v.w) : "memory"); }
__device__ __forceinline__ float lds32f(uint32_t a) { float v; asm volatile("ld.shared.f32 %0,[%1];" : "=f"(v) : "r"(a) : "memory"); return v; }
__device__ __forceinline__ float2 lds64f(uint32_t a) { float2 v; asm volatile("ld.shared.v2.f32 {%0,%1},[%2];" : "=f"(v.x), "=f"(v.y) : "r"(a) : "memory"); return v; }
__device__ __forceinline__ uint4 lds128(uint32_t a) { uint4 v; asm volatile("ld.shared.v4.b32 {%0,%1,%2,%3},[%4];" : "=r"(v.x), "=r"(v.y), "=r"(v.z), "=r"(v.w) : "r"(a) : "memory"); return v; }
__device__ __forceinline__ float4 lds128f(uint32_t a) { float4 v; asm volatile("ld.shared.v4.f32 {%0,%1,%2,%3},[%4];" : "=f"(v.x), "=f"(v.y), "=f"(v.z), "=f"(v.w) : "r"(a) : "memory"); return v; }
__device__ __forceinline__ void st_async2(uint32_t a, float x, float y, uint32_t bar) {
  asm volatile("st.async.weak.shared::cluster.mbarrier::complete_tx::bytes.v2.f32 [%0],{%1,%2},[%3];" ::"r"(a), "f"(x), "f"(y), "r"(bar) : "memory");
}
__device__ __forceinline__ void st_async4(uint32_t a, const float (&v)[4], uint32_t bar) {
  asm volatile("st.async.weak.shared::cluster.mbarrier::complete_tx::bytes.v4.f32 [%0],{%1,%2,%3,%4},[%5];" ::"r"(a), "f"(v[0]), "f"(v[1]), "f"(v[2]), "f"(v[3]), "r"(bar) : "memory");
}
__device__ __forceinline__ void st_async4v(uint32_t a, float x, float y, float z, float w, uint32_t bar) {
  asm volatile("st.async.weak.shared::cluster.mbarrier::complete_tx::bytes.v4.f32 [%0],{%1,%2,%3,%4},[%5];" ::"r"(a), "f"(x), "f"(y), "f"(z), "f"(w), "r"(bar) : "memory");
}
__device__ __forceinline__ void st_async4u(uint32_t a, const uint4& v, uint32_t bar) {
  asm volatile("st.async.weak.shared::cluster.mbarrier::complete_tx::bytes.v4.b32 [%0],{%1,%2,%3,%4},[%5];" ::"r"(a), "r"(v.x), "r"(v.y), "r"(v.z), "r"(v.w), "r"(bar) : "memory");
}
__device__ __forceinline__ uint4 ld_relaxed4(const void* p) {
  uint4 v; asm volatile("ld.relaxed.gpu.global.v4.u32 {%0,%1,%2,%3},[%4];" : "=r"(v.x), "=r"(v.y), "=r"(v.z), "=r"(v.w) : "l"(p) : "memory"); return v;
}
__device__ __forceinline__ uint32_t ld_relaxed(const void* p) {
  uint32_t v; asm volatile("ld.relaxed.gpu.global.u32 %0,[%1];" : "=r"(v) : "l"(p) : "memory"); return v;
}
__device__ __forceinline__ void st_relaxed(void* p, uint32_t v) { asm volatile("st.relaxed.gpu.global.b32 [%0],%1;" ::"l"(p), "r"(v) : "memory"); }
__device__ __forceinline__ void st_relaxed4(void* p, uint32_t v) { asm volatile("st.relaxed.gpu.global.v4.b32 [%0],{%1,%1,%1,%1};" ::"l"(p), "r"(v) : "memory"); }

__device__ __forceinline__ uint32_t ld_acquire(const void* p) {
  uint32_t v; asm volatile("ld.acquire.gpu.global.u32 %0,[%1];" : "=r"(v) : "l"(p) : "memory"); return v;
}
__device__ __forceinline__ float4 ld_relaxed4f(const void* p) {
  float4 v; asm volatile("ld.relaxed.gpu.global.v4.f32 {%0,%1,%2,%3},[%4];" : "=f"(v.x), "=f"(v.y), "=f"(v.z), "=f"(v.w) : "l"(p) : "memory"); return v;
}
__device__ __forceinline__ float2 ld_relaxed2f(const void* p) {
  float2 v; asm volatile("ld.relaxed.gpu.global.v2.f32 {%0,%1},[%2];" : "=f"(v.x), "=f"(v.y) : "l"(p) : "memory"); return v;
}
__device__ __forceinline__ void prefetch_l2(const void* p) { asm volatile("prefetch.global.L2 [%0];" ::"l"(p)); }
__device__ __forceinline__ void fence_gpu() { asm volatile("fence.acq_rel.gpu;" ::: "memory"); }
__device__ __forceinline__ void fence_async_all() { asm volatile("fence.proxy.async.global;" ::: "memory"); }
constexpr int SPIN_TOT = 1 << 22;
__device__ __forceinline__ void csignal(int idx) { asm volatile("red.release.gpu.global.add.u32 [%0],1;" ::"l"(&g_cnt[idx][0]) : "memory"); }
__device__ __forceinline__ void csignal_fast(int idx) { asm volatile("red.relaxed.gpu.global.add.u32 [%0],1;" ::"l"(&g_cnt[idx][0]) : "memory"); }
#define RLX 1
#define csignal_t(idx, role) csignal(idx)
__device__ __forceinline__ void cwait(int idx, uint32_t target, int& spin) {
  while (ld_relaxed(&g_cnt[idx][0]) < target && spin < SPIN_TOT) spin += 16;
}

__device__ __forceinline__ uint64_t mkdesc(uint32_t addr, uint32_t lbo, uint32_t sbo) {
  return (uint64_t)((addr & 0x3FFFF) >> 4) | ((uint64_t)(lbo >> 4) << 16) | ((uint64_t)(sbo >> 4) << 32) | ((uint64_t)1 << 62);
}
__device__ __forceinline__ uint64_t mkdesc_ns(uint32_t addr, uint32_t lbo, uint32_t sbo) {
  return (uint64_t)((addr & 0x3FFFF) >> 4) | ((uint64_t)(lbo >> 4) << 16) | ((uint64_t)(sbo >> 4) << 32);
}
__device__ __forceinline__ void wg_fence() { asm volatile("wgmma.fence.sync.aligned;" ::: "memory"); }
__device__ __forceinline__ void wg_commit() { asm volatile("wgmma.commit_group.sync.aligned;" ::: "memory"); }
template <int N> __device__ __forceinline__ void wg_wait() { asm volatile("wgmma.wait_group.sync.aligned %0;" ::"n"(N) : "memory"); }

__device__ __forceinline__ void wgmma_rs16(float (&d)[8], const uint32_t (&a)[4], uint64_t db, int sc) {
  asm volatile("{.reg .pred p; setp.ne.b32 p,%13,0; wgmma.mma_async.sync.aligned.m64n16k16.f32.bf16.bf16 "
               "{%0,%1,%2,%3,%4,%5,%6,%7},{%8,%9,%10,%11},%12,p,1,1,0;}"
               : "+f"(d[0]), "+f"(d[1]), "+f"(d[2]), "+f"(d[3]), "+f"(d[4]), "+f"(d[5]), "+f"(d[6]), "+f"(d[7])
               : "r"(a[0]), "r"(a[1]), "r"(a[2]), "r"(a[3]), "l"(db), "r"(sc));
}
__device__ __forceinline__ void wgmma_rs64(float (&d)[32], const uint32_t (&a)[4], uint64_t db, int sc) {
  asm volatile("{.reg .pred p; setp.ne.b32 p,%37,0; wgmma.mma_async.sync.aligned.m64n64k16.f32.bf16.bf16 "
               "{%0,%1,%2,%3,%4,%5,%6,%7,%8,%9,%10,%11,%12,%13,%14,%15,%16,%17,%18,%19,%20,%21,%22,%23,%24,%25,%26,%27,%28,%29,%30,%31},{%32,%33,%34,%35},%36,p,1,1,0;}"
               : "+f"(d[0]), "+f"(d[1]), "+f"(d[2]), "+f"(d[3]), "+f"(d[4]), "+f"(d[5]), "+f"(d[6]), "+f"(d[7]), "+f"(d[8]), "+f"(d[9]), "+f"(d[10]), "+f"(d[11]), "+f"(d[12]), "+f"(d[13]), "+f"(d[14]), "+f"(d[15]), "+f"(d[16]), "+f"(d[17]), "+f"(d[18]), "+f"(d[19]), "+f"(d[20]), "+f"(d[21]), "+f"(d[22]), "+f"(d[23]), "+f"(d[24]), "+f"(d[25]), "+f"(d[26]), "+f"(d[27]), "+f"(d[28]), "+f"(d[29]), "+f"(d[30]), "+f"(d[31])
               : "r"(a[0]), "r"(a[1]), "r"(a[2]), "r"(a[3]), "l"(db), "r"(sc));
}
__device__ __forceinline__ void wgmma_rt16(float (&d)[8], const uint32_t (&a)[4], uint64_t db, int sc) {
  asm volatile("{.reg .pred p; setp.ne.b32 p,%13,0; wgmma.mma_async.sync.aligned.m64n16k16.f32.bf16.bf16 "
               "{%0,%1,%2,%3,%4,%5,%6,%7},{%8,%9,%10,%11},%12,p,1,1,1;}"
               : "+f"(d[0]), "+f"(d[1]), "+f"(d[2]), "+f"(d[3]), "+f"(d[4]), "+f"(d[5]), "+f"(d[6]), "+f"(d[7])
               : "r"(a[0]), "r"(a[1]), "r"(a[2]), "r"(a[3]), "l"(db), "r"(sc));
}
__device__ __forceinline__ void wgmma_rt80(float (&d)[40], const uint32_t (&a)[4], uint64_t db, int sc) {
  asm volatile("{.reg .pred p; setp.ne.b32 p,%45,0; wgmma.mma_async.sync.aligned.m64n80k16.f32.bf16.bf16 "
               "{%0,%1,%2,%3,%4,%5,%6,%7,%8,%9,%10,%11,%12,%13,%14,%15,%16,%17,%18,%19,%20,%21,%22,%23,%24,%25,%26,%27,%28,%29,%30,%31,%32,%33,%34,%35,%36,%37,%38,%39},{%40,%41,%42,%43},%44,p,1,1,1;}"
               : "+f"(d[0]), "+f"(d[1]), "+f"(d[2]), "+f"(d[3]), "+f"(d[4]), "+f"(d[5]), "+f"(d[6]), "+f"(d[7]), "+f"(d[8]), "+f"(d[9]), "+f"(d[10]), "+f"(d[11]), "+f"(d[12]), "+f"(d[13]), "+f"(d[14]), "+f"(d[15]), "+f"(d[16]), "+f"(d[17]), "+f"(d[18]), "+f"(d[19]), "+f"(d[20]), "+f"(d[21]), "+f"(d[22]), "+f"(d[23]), "+f"(d[24]), "+f"(d[25]), "+f"(d[26]), "+f"(d[27]), "+f"(d[28]), "+f"(d[29]), "+f"(d[30]), "+f"(d[31]), "+f"(d[32]), "+f"(d[33]), "+f"(d[34]), "+f"(d[35]), "+f"(d[36]), "+f"(d[37]), "+f"(d[38]), "+f"(d[39])
               : "r"(a[0]), "r"(a[1]), "r"(a[2]), "r"(a[3]), "l"(db), "r"(sc));
}
__device__ __forceinline__ void wgmma_rs32(float (&d)[16], const uint32_t (&a)[4], uint64_t db, int sc) {
  asm volatile("{.reg .pred p; setp.ne.b32 p,%21,0; wgmma.mma_async.sync.aligned.m64n32k16.f32.bf16.bf16 "
               "{%0,%1,%2,%3,%4,%5,%6,%7,%8,%9,%10,%11,%12,%13,%14,%15},{%16,%17,%18,%19},%20,p,1,1,0;}"
               : "+f"(d[0]), "+f"(d[1]), "+f"(d[2]), "+f"(d[3]), "+f"(d[4]), "+f"(d[5]), "+f"(d[6]), "+f"(d[7]), "+f"(d[8]), "+f"(d[9]), "+f"(d[10]), "+f"(d[11]), "+f"(d[12]), "+f"(d[13]), "+f"(d[14]), "+f"(d[15])
               : "r"(a[0]), "r"(a[1]), "r"(a[2]), "r"(a[3]), "l"(db), "r"(sc));
}
__device__ __forceinline__ void wgmma_ts32(float (&d)[16], uint64_t da, uint64_t db, int sc) {
  asm volatile("{.reg .pred p; setp.ne.b32 p,%18,0; wgmma.mma_async.sync.aligned.m64n32k16.f32.bf16.bf16 "
               "{%0,%1,%2,%3,%4,%5,%6,%7,%8,%9,%10,%11,%12,%13,%14,%15},%16,%17,p,1,1,1,0;}"
               : "+f"(d[0]), "+f"(d[1]), "+f"(d[2]), "+f"(d[3]), "+f"(d[4]), "+f"(d[5]), "+f"(d[6]), "+f"(d[7]), "+f"(d[8]), "+f"(d[9]), "+f"(d[10]), "+f"(d[11]), "+f"(d[12]), "+f"(d[13]), "+f"(d[14]), "+f"(d[15])
               : "l"(da), "l"(db), "r"(sc));
}
__device__ __forceinline__ void wgmma_rs8(float (&d)[4], const uint32_t (&a)[4], uint64_t db, int sc) {
  asm volatile("{.reg .pred p; setp.ne.b32 p,%9,0; wgmma.mma_async.sync.aligned.m64n8k16.f32.bf16.bf16 "
               "{%0,%1,%2,%3},{%4,%5,%6,%7},%8,p,1,1,0;}"
               : "+f"(d[0]), "+f"(d[1]), "+f"(d[2]), "+f"(d[3])
               : "r"(a[0]), "r"(a[1]), "r"(a[2]), "r"(a[3]), "l"(db), "r"(sc));
}
__device__ __forceinline__ void wgmma_tt32(float (&d)[16], uint64_t da, uint64_t db, int sc) {
  asm volatile("{.reg .pred p; setp.ne.b32 p,%18,0; wgmma.mma_async.sync.aligned.m64n32k16.f32.bf16.bf16 "
               "{%0,%1,%2,%3,%4,%5,%6,%7,%8,%9,%10,%11,%12,%13,%14,%15},%16,%17,p,1,1,1,1;}"
               : "+f"(d[0]), "+f"(d[1]), "+f"(d[2]), "+f"(d[3]), "+f"(d[4]), "+f"(d[5]), "+f"(d[6]), "+f"(d[7]), "+f"(d[8]), "+f"(d[9]), "+f"(d[10]), "+f"(d[11]), "+f"(d[12]), "+f"(d[13]), "+f"(d[14]), "+f"(d[15])
               : "l"(da), "l"(db), "r"(sc));
}
__device__ __forceinline__ void wgmma_ts16(float (&d)[8], uint64_t da, uint64_t db, int sc) {
  asm volatile("{.reg .pred p; setp.ne.b32 p,%10,0; wgmma.mma_async.sync.aligned.m64n16k16.f32.bf16.bf16 "
               "{%0,%1,%2,%3,%4,%5,%6,%7},%8,%9,p,1,1,1,0;}"
               : "+f"(d[0]), "+f"(d[1]), "+f"(d[2]), "+f"(d[3]), "+f"(d[4]), "+f"(d[5]), "+f"(d[6]), "+f"(d[7])
               : "l"(da), "l"(db), "r"(sc));
}
__device__ __forceinline__ void wgmma_ts64(float (&d)[32], uint64_t da, uint64_t db, int sc) {
  asm volatile("{.reg .pred p; setp.ne.b32 p,%34,0; wgmma.mma_async.sync.aligned.m64n64k16.f32.bf16.bf16 "
               "{%0,%1,%2,%3,%4,%5,%6,%7,%8,%9,%10,%11,%12,%13,%14,%15,%16,%17,%18,%19,%20,%21,%22,%23,%24,%25,%26,%27,%28,%29,%30,%31},%32,%33,p,1,1,1,0;}"
               : "+f"(d[0]), "+f"(d[1]), "+f"(d[2]), "+f"(d[3]), "+f"(d[4]), "+f"(d[5]), "+f"(d[6]), "+f"(d[7]), "+f"(d[8]), "+f"(d[9]), "+f"(d[10]), "+f"(d[11]), "+f"(d[12]), "+f"(d[13]), "+f"(d[14]), "+f"(d[15]), "+f"(d[16]), "+f"(d[17]), "+f"(d[18]), "+f"(d[19]), "+f"(d[20]), "+f"(d[21]), "+f"(d[22]), "+f"(d[23]), "+f"(d[24]), "+f"(d[25]), "+f"(d[26]), "+f"(d[27]), "+f"(d[28]), "+f"(d[29]), "+f"(d[30]), "+f"(d[31])
               : "l"(da), "l"(db), "r"(sc));
}
__device__ __forceinline__ void wgmma_tt16(float (&d)[8], uint64_t da, uint64_t db, int sc) {
  asm volatile("{.reg .pred p; setp.ne.b32 p,%10,0; wgmma.mma_async.sync.aligned.m64n16k16.f32.bf16.bf16 "
               "{%0,%1,%2,%3,%4,%5,%6,%7},%8,%9,p,1,1,1,1;}"
               : "+f"(d[0]), "+f"(d[1]), "+f"(d[2]), "+f"(d[3]), "+f"(d[4]), "+f"(d[5]), "+f"(d[6]), "+f"(d[7])
               : "l"(da), "l"(db), "r"(sc));
}
__device__ __forceinline__ void wgmma_tt40(float (&d)[20], uint64_t da, uint64_t db, int sc) {
  asm volatile("{.reg .pred p; setp.ne.b32 p,%22,0; wgmma.mma_async.sync.aligned.m64n40k16.f32.bf16.bf16 "
               "{%0,%1,%2,%3,%4,%5,%6,%7,%8,%9,%10,%11,%12,%13,%14,%15,%16,%17,%18,%19},%20,%21,p,1,1,1,1;}"
               : "+f"(d[0]), "+f"(d[1]), "+f"(d[2]), "+f"(d[3]), "+f"(d[4]), "+f"(d[5]), "+f"(d[6]), "+f"(d[7]), "+f"(d[8]), "+f"(d[9]), "+f"(d[10]), "+f"(d[11]), "+f"(d[12]), "+f"(d[13]), "+f"(d[14]), "+f"(d[15]), "+f"(d[16]), "+f"(d[17]), "+f"(d[18]), "+f"(d[19])
               : "l"(da), "l"(db), "r"(sc));
}
__device__ __forceinline__ void wgmma_ss8(float (&d)[4], uint64_t da, uint64_t db, int sc) {
  asm volatile("{.reg .pred p; setp.ne.b32 p,%6,0; wgmma.mma_async.sync.aligned.m64n8k16.f32.bf16.bf16 "
               "{%0,%1,%2,%3},%4,%5,p,1,1,0,0;}"
               : "+f"(d[0]), "+f"(d[1]), "+f"(d[2]), "+f"(d[3])
               : "l"(da), "l"(db), "r"(sc));
}
__device__ __forceinline__ void wgmma_ss32(float (&d)[16], uint64_t da, uint64_t db, int sc) {
  asm volatile("{.reg .pred p; setp.ne.b32 p,%18,0; wgmma.mma_async.sync.aligned.m64n32k16.f32.bf16.bf16 "
               "{%0,%1,%2,%3,%4,%5,%6,%7,%8,%9,%10,%11,%12,%13,%14,%15},%16,%17,p,1,1,0,0;}"
               : "+f"(d[0]), "+f"(d[1]), "+f"(d[2]), "+f"(d[3]), "+f"(d[4]), "+f"(d[5]), "+f"(d[6]), "+f"(d[7]), "+f"(d[8]), "+f"(d[9]), "+f"(d[10]), "+f"(d[11]), "+f"(d[12]), "+f"(d[13]), "+f"(d[14]), "+f"(d[15])
               : "l"(da), "l"(db), "r"(sc));
}
__device__ __forceinline__ void wgmma_st64(float (&d)[32], uint64_t da, uint64_t db, int sc) {
  asm volatile("{.reg .pred p; setp.ne.b32 p,%34,0; wgmma.mma_async.sync.aligned.m64n64k16.f32.bf16.bf16 "
               "{%0,%1,%2,%3,%4,%5,%6,%7,%8,%9,%10,%11,%12,%13,%14,%15,%16,%17,%18,%19,%20,%21,%22,%23,%24,%25,%26,%27,%28,%29,%30,%31},%32,%33,p,1,1,0,1;}"
               : "+f"(d[0]), "+f"(d[1]), "+f"(d[2]), "+f"(d[3]), "+f"(d[4]), "+f"(d[5]), "+f"(d[6]), "+f"(d[7]), "+f"(d[8]), "+f"(d[9]), "+f"(d[10]), "+f"(d[11]), "+f"(d[12]), "+f"(d[13]), "+f"(d[14]), "+f"(d[15]), "+f"(d[16]), "+f"(d[17]), "+f"(d[18]), "+f"(d[19]), "+f"(d[20]), "+f"(d[21]), "+f"(d[22]), "+f"(d[23]), "+f"(d[24]), "+f"(d[25]), "+f"(d[26]), "+f"(d[27]), "+f"(d[28]), "+f"(d[29]), "+f"(d[30]), "+f"(d[31])
               : "l"(da), "l"(db), "r"(sc));
}
__device__ __forceinline__ void wgmma_st128(float (&d)[64], uint64_t da, uint64_t db, int sc) {
  asm volatile("{.reg .pred p; setp.ne.b32 p,%66,0; wgmma.mma_async.sync.aligned.m64n128k16.f32.bf16.bf16 "
               "{%0,%1,%2,%3,%4,%5,%6,%7,%8,%9,%10,%11,%12,%13,%14,%15,%16,%17,%18,%19,%20,%21,%22,%23,%24,%25,%26,%27,%28,%29,%30,%31,%32,%33,%34,%35,%36,%37,%38,%39,%40,%41,%42,%43,%44,%45,%46,%47,%48,%49,%50,%51,%52,%53,%54,%55,%56,%57,%58,%59,%60,%61,%62,%63},%64,%65,p,1,1,0,1;}"
               : "+f"(d[0]), "+f"(d[1]), "+f"(d[2]), "+f"(d[3]), "+f"(d[4]), "+f"(d[5]), "+f"(d[6]), "+f"(d[7]), "+f"(d[8]), "+f"(d[9]), "+f"(d[10]), "+f"(d[11]), "+f"(d[12]), "+f"(d[13]), "+f"(d[14]), "+f"(d[15]), "+f"(d[16]), "+f"(d[17]), "+f"(d[18]), "+f"(d[19]), "+f"(d[20]), "+f"(d[21]), "+f"(d[22]), "+f"(d[23]), "+f"(d[24]), "+f"(d[25]), "+f"(d[26]), "+f"(d[27]), "+f"(d[28]), "+f"(d[29]), "+f"(d[30]), "+f"(d[31]), "+f"(d[32]), "+f"(d[33]), "+f"(d[34]), "+f"(d[35]), "+f"(d[36]), "+f"(d[37]), "+f"(d[38]), "+f"(d[39]), "+f"(d[40]), "+f"(d[41]), "+f"(d[42]), "+f"(d[43]), "+f"(d[44]), "+f"(d[45]), "+f"(d[46]), "+f"(d[47]), "+f"(d[48]), "+f"(d[49]), "+f"(d[50]), "+f"(d[51]), "+f"(d[52]), "+f"(d[53]), "+f"(d[54]), "+f"(d[55]), "+f"(d[56]), "+f"(d[57]), "+f"(d[58]), "+f"(d[59]), "+f"(d[60]), "+f"(d[61]), "+f"(d[62]), "+f"(d[63])
               : "l"(da), "l"(db), "r"(sc));
}

__device__ __forceinline__ void stsm4(uint32_t a, uint32_t r0, uint32_t r1, uint32_t r2, uint32_t r3) {
  asm volatile("stmatrix.sync.aligned.m8n8.x4.shared.b16 [%0],{%1,%2,%3,%4};" ::"r"(a), "r"(r0), "r"(r1), "r"(r2), "r"(r3) : "memory");
}
__device__ __forceinline__ void stsm4t(uint32_t a, uint32_t r0, uint32_t r1, uint32_t r2, uint32_t r3) {
  asm volatile("stmatrix.sync.aligned.m8n8.x4.trans.shared.b16 [%0],{%1,%2,%3,%4};" ::"r"(a), "r"(r0), "r"(r1), "r"(r2), "r"(r3) : "memory");
}
__device__ __forceinline__ void stsm2t(uint32_t a, uint32_t r0, uint32_t r1) {
  asm volatile("stmatrix.sync.aligned.m8n8.x2.trans.shared.b16 [%0],{%1,%2};" ::"r"(a), "r"(r0), "r"(r1) : "memory");
}
__device__ __forceinline__ void sts64(uint32_t a, uint32_t x, uint32_t y) { asm volatile("st.shared.v2.b32 [%0],{%1,%2};" ::"r"(a), "r"(x), "r"(y) : "memory"); }
__device__ __forceinline__ void st_async2u(uint32_t a, uint32_t x, uint32_t y, uint32_t bar) {
  asm volatile("st.async.weak.shared::cluster.mbarrier::complete_tx::bytes.v2.b32 [%0],{%1,%2},[%3];" ::"r"(a), "r"(x), "r"(y), "r"(bar) : "memory");
}
__device__ __forceinline__ void st_relaxed128(void* p, uint32_t x, uint32_t y, uint32_t z, uint32_t w) {
  asm volatile("{.reg .b128 v; mov.b128 v,{%1,%2,%3,%4}; st.relaxed.gpu.global.b128 [%0],v;}" ::"l"(p), "r"(x), "r"(y), "r"(z), "r"(w) : "memory");
}
__device__ __forceinline__ void st_relaxed64(void* p, uint32_t x, uint32_t y) {
  asm volatile("{.reg .b64 v; mov.b64 v,{%1,%2}; st.relaxed.gpu.global.b64 [%0],v;}" ::"l"(p), "r"(x), "r"(y) : "memory");
}
__device__ __forceinline__ uint4 ld_relaxed128(const void* p) {
  uint4 v;
  asm volatile("{.reg .b128 v; .reg .b64 lo, hi; ld.relaxed.gpu.global.b128 v,[%4]; mov.b128 {lo,hi},v; mov.b64 {%0,%1},lo; mov.b64 {%2,%3},hi;}" : "=r"(v.x), "=r"(v.y), "=r"(v.z), "=r"(v.w) : "l"(p) : "memory");
  return v;
}

__device__ __forceinline__ uint32_t pack_h2(float lo, float hi) {
  uint32_t r; asm("cvt.rn.satfinite.f16x2.f32 %0,%1,%2;" : "=r"(r) : "f"(hi), "f"(lo)); return r;
}
__device__ __forceinline__ void add_h2(float& lo, float& hi, uint32_t u, uint32_t v) {
  float a, b;
  asm("{.reg .b16 l, h; .reg .b32 s; add.rn.f16x2 s,%2,%3; mov.b32 {l,h},s; cvt.f32.f16 %0,l; cvt.f32.f16 %1,h;}" : "=f"(a), "=f"(b) : "r"(u), "r"(v));
  lo += a; hi += b;
}
__device__ __forceinline__ void mwait(uint32_t bar, uint32_t ph, int& spin) {
  asm volatile("{.reg .pred p, q;\nWAIT_LOOP:\n add.s32 %0,%0,1;\n setp.lt.s32 q,%0,%3;\n mbarrier.try_wait.parity.shared::cta.b64 p,[%1],%2;\n not.pred p,p;\n and.pred q,q,p;\n @q bra.uni WAIT_LOOP;\n}"
               : "+&r"(spin) : "r"(bar), "r"(ph), "n"(SPIN_TOT) : "memory");
}
__device__ __forceinline__ int keep(int x) { return __shfl_sync(0xffffffffu, x, threadIdx.x & 31); }
__device__ __forceinline__ uint32_t pin(uint32_t x) { asm volatile("" : "+r"(x)); return x; }
template <typename T> __device__ __forceinline__ T* pinp(T* x) { asm volatile("" : "+l"(x)); return x; }
__device__ __forceinline__ void st_async1u(uint32_t a, uint32_t x, uint32_t bar) {
  asm volatile("st.async.weak.shared::cluster.mbarrier::complete_tx::bytes.b32 [%0],%1,[%2];" ::"r"(a), "r"(x), "r"(bar) : "memory");
}
__device__ __forceinline__ uint32_t lds32(uint32_t a) { uint32_t v; asm volatile("ld.shared.b32 %0,[%1];" : "=r"(v) : "r"(a) : "memory"); return v; }
__device__ __forceinline__ uint2 lds64(uint32_t a) { uint2 v; asm volatile("ld.shared.v2.b32 {%0,%1},[%2];" : "=r"(v.x), "=r"(v.y) : "r"(a) : "memory"); return v; }

__device__ __forceinline__ void permute_cols(uint32_t tile, int tid, int n) {
#pragma unroll 2
  for (int it = tid; it < n; it += 128) {
    const int row = it >> 2, q = it & 3;
    const uint32_t a0 = tile + row * 128 + (((2 * q) ^ (row & 7)) << 4), a1 = tile + row * 128 + (((2 * q + 1) ^ (row & 7)) << 4);
    const uint4 u = lds128(a0), v = lds128(a1);
    sts128(a0, make_uint4(__byte_perm(u.x, u.y, 0x5410), __byte_perm(u.z, u.w, 0x5410), __byte_perm(v.x, v.y, 0x5410), __byte_perm(v.z, v.w, 0x5410)));
    sts128(a1, make_uint4(__byte_perm(u.x, u.y, 0x7632), __byte_perm(u.z, u.w, 0x7632), __byte_perm(v.x, v.y, 0x7632), __byte_perm(v.z, v.w, 0x7632)));
  }
}

__device__ __forceinline__ uint8_t* mkptr(uint32_t lo, uint32_t hi) { uint8_t* p; asm("mov.b64 %0,{%1,%2};" : "=l"(p) : "r"(lo), "r"(hi)); return p; }
__device__ __forceinline__ int uni(int x) { return __shfl_sync(0xffffffffu, x, 0); }

__device__ __forceinline__ bool elect_one() {
  uint32_t p; asm volatile("{.reg .pred q; elect.sync _|q, 0xffffffff; selp.u32 %0,1,0,q;}" : "=r"(p)); return p;
}
__device__ __forceinline__ uint64_t desc_at(uint64_t d, uint32_t off) {
  uint64_t r; asm("mov.b64 %0,{%1,%2};" : "=l"(r) : "r"((uint32_t)d + (off >> 4)), "r"((uint32_t)(d >> 32))); return r;
}
__device__ __forceinline__ uint32_t scale_bf16x2(uint32_t x, uint32_t s) { uint32_t r; asm("mul.rn.bf16x2 %0,%1,%2;" : "=r"(r) : "r"(x), "r"(s)); return r; }

__device__ __forceinline__ void stg128(void* p, const uint4& v) { asm volatile("st.global.v4.b32 [%0],{%1,%2,%3,%4};" ::"l"(p), "r"(v.x), "r"(v.y), "r"(v.z), "r"(v.w) : "memory"); }

__device__ __forceinline__ float quad_sum(float x) {
  const float a = __shfl_xor_sync(0xffffffffu, x, 1), b = __shfl_xor_sync(0xffffffffu, x, 2), c = __shfl_xor_sync(0xffffffffu, x, 3);
  return (x + a) + (b + c);
}
__device__ __forceinline__ float warp_sum(float x) {
  const uint32_t m = __reduce_max_sync(0xffffffffu, __float_as_uint(x) & 0x7FFFFFFFu), e = max(m >> 23, 25u);
  const int s = __reduce_add_sync(0xffffffffu, __float2int_rn(x * __uint_as_float((278 - e) << 23)));
  return fmaf(__uint_as_float(m), 0.f, (float)s * __uint_as_float((e - 24) << 23));
}
__device__ __forceinline__ void ln_row(float4 (&v)[5]) {
  float t0 = 0.f, t1 = 0.f;
#pragma unroll
  for (int m = 0; m < 5; m++) { t0 += v[m].x + v[m].y; t1 += v[m].z + v[m].w; }
  const float mean = warp_sum(t0 + t1) * (1.f / DM);
  float q0 = 0.f, q1 = 0.f, q2 = 0.f, q3 = 0.f;
#pragma unroll
  for (int m = 0; m < 5; m++) {
    v[m].x -= mean; v[m].y -= mean; v[m].z -= mean; v[m].w -= mean;
    q0 = fmaf(v[m].x, v[m].x, q0); q1 = fmaf(v[m].y, v[m].y, q1); q2 = fmaf(v[m].z, v[m].z, q2); q3 = fmaf(v[m].w, v[m].w, q3);
  }
  const float rs = rsqrtf(warp_sum((q0 + q1) + (q2 + q3)) * (1.f / DM) + 1e-5f);
#pragma unroll
  for (int m = 0; m < 5; m++) { v[m].x *= rs; v[m].y *= rs; v[m].z *= rs; v[m].w *= rs; }
}
__device__ __forceinline__ void ln0_load(const bf16* __restrict__ x, uint2 (&u)[5], int row, int lane) {
#pragma unroll
  for (int m = 0; m < 5; m++) u[m] = *reinterpret_cast<const uint2*>(x + (size_t)row * DM + m * 128 + lane * 4);
}
__device__ __forceinline__ void ln0_copy(const uint2 (&u)[5], int row, int lane) {
#pragma unroll
  for (int m = 0; m < 5; m++) stg128(g_x + (size_t)row * DM + m * 128 + lane * 4, make_uint4(u[m].x << 16, u[m].x & 0xFFFF0000u, u[m].y << 16, u[m].y & 0xFFFF0000u));
}
__device__ __forceinline__ void ln0_row(const uint2 (&u)[5], int row, int lane) {
  float4 v[5];
#pragma unroll
  for (int m = 0; m < 5; m++) v[m] = make_float4(bf_lo(u[m].x), bf_hi(u[m].x), bf_lo(u[m].y), bf_hi(u[m].y));
  ln_row(v);
  uint8_t* dst = g_xn[row >> 5] + ((row >> 3) & 3) * 4096 + (lane >> 4) * 1024 + (row & 7) * 128 + ((((lane >> 1) ^ row) & 7) << 4) + (lane & 1) * 8;
#pragma unroll
  for (int m = 0; m < 5; m++) *reinterpret_cast<uint2*>(dst + m * 16384) = make_uint2(pack_bf16(v[m].x, v[m].y), pack_bf16(v[m].z, v[m].w));
}

#define NOWORK 0
__device__ __forceinline__ void prep_row(const uint2 (&u)[5], const bf16* __restrict__ mem0, int k, int r, int lane) {
  const uint4 sent = make_uint4(SENT, SENT, SENT, SENT);
  if (k + 1 < NSTEP) {
    uint8_t* ex = ex_window(g_ex);
#pragma unroll
    for (int h = 0; h < 2; h++) {
      const int p = r * 40 + h * 32 + lane;
      if (h == 0 || lane < 8) {
        uint4 v = sent;
        if (k + 1 == LAG && (p & 8)) v = *reinterpret_cast<const uint4*>(mem0 + (p & 7) * DM + (p >> 4) * 8);
        stg128(ex + EX_M + (k + 1) * 20480 + p * 16, v);
      } else if (lane < 14) stg128(ex + EX_FLAG + (k + 1) * 3072 + (r * 6 + lane - 8) * 16, sent);
    }
  }
  if (k < LAG || k >= NSEG || NOWORK) {
    uint8_t* z = g_xn[k] + (r >> 3) * 4096 + (k < NSEG ? 2048 : 0) + (lane >> 4) * 1024 + (r & 7) * 128 + (lane & 15) * 8;
#pragma unroll
    for (int m = 0; m < 5; m++) *reinterpret_cast<uint2*>(z + m * 16384) = make_uint2(0, 0);
  }
  if (k < NSEG) {
    ln0_copy(u, k * 32 + r, lane);
    ln0_row(u, k * 32 + r, lane);
  }
}
__device__ __forceinline__ void pre_work(const bf16* __restrict__ x, const bf16* __restrict__ mem0, int cta, int tid) {
  constexpr int NT = 96 * 128;
  const int gt = cta * 128 + tid;
  uint8_t* ex = ex_window(g_ex);
#pragma unroll 1
  for (int row = cta + 96 * (tid >> 5); row < (NOWORK == 2 ? NSTEP : NPRE) * 32; row += 384) {
    uint2 u[5];
    ln0_load(x, u, min(row, SEQ - 1), tid & 31);
    prep_row(u, mem0, row >> 5, row & 31, tid & 31);
  }
#pragma unroll 1
  for (int i = gt; i < MAIL_BYTES / 16; i += NT) {
    stg128(ex + EX_MAIL + i * 16, make_uint4(SENT, SENT, SENT, SENT));
    stg128(ex + EX_MAIL + (1 << 20) + i * 16, make_uint4(SENT, SENT, SENT, SENT));
  }
  const int p = NT - 1 - gt;
  if (p < 1280) stg128(ex + EX_M + p * 16, *reinterpret_cast<const uint4*>(mem0 + (p & 7) * DM + (p >> 4) * 8));
  if (p < 192) stg128(ex + EX_FLAG + p * 16, make_uint4(0, 0, 0, 0));
  if (gt < 8 * CN_NUM) stg128(&g_cnt[0][0] + gt * 4, make_uint4(0, 0, 0, 0));
}
__device__ __forceinline__ void pre_wait(int which, uint32_t n, int& spin) {
  uint32_t old;
  asm volatile("atom.acq_rel.gpu.global.add.u32 %0,[%1],1;" : "=r"(old) : "l"(&g_ticket[which][0]) : "memory");
  const uint32_t target = (old / n + 1) * 96;
  while ((int)(ld_acquire(&g_ticket[0][0]) - target) < 0 && spin < SPIN_TOT) spin += 16;
  fence_async_all();
}

namespace C {
constexpr int NKR = 37;
constexpr int OFF_WQ = 0, OFF_WK = 81920;
constexpr int OFF_YO = 163840, OFF_YV = OFF_YO + 6144;
constexpr int OFF_M = 176128;
__host__ __device__ constexpr int og_off(int c) { return c ? OFF_M + 14336 + c * 2048 : 229376; }
constexpr int OFF_KT = 196608;
constexpr int OFF_XT = OFF_KT + 10240;
constexpr int OFF_VT = OFF_XT + 7168;
constexpr int OFF_XM = OFF_VT + 11392;
constexpr int OFF_PT = OFF_XM + 2560;
constexpr int KS = 1280, VS = 1408;
__host__ __device__ constexpr int slot_off(int p) { return p == 2 ? OFF_M : OFF_KT + (p % 3) * 16384; }
constexpr int OFF_ONE = 231424;
constexpr int OFF_BAR = 231552;
constexpr int OFF_SAFE = OFF_BAR + 144;
constexpr int OFF_TS = OFF_BAR + 256;
constexpr int SMEM = 232448;
constexpr uint32_t SB0 = 1024;
constexpr int BAR_F = OFF_BAR, BAR_XM = BAR_F + 40, BAR_XT = BAR_F + 48, BAR_OG = BAR_F + 56, BAR_E = OFF_BAR + 64, BAR_MOK = BAR_E + 40,
              BAR_M = OFF_BAR + 112, BAR_XF = OFF_BAR + 120, BAR_MF = OFF_BAR + 128, BAR_W = OFF_BAR + 208;
constexpr int NB_PRO = 1, NB_RD = 2, NB_MR = 3, NB_QK = 4, NB_SM = 5, NB_VA = 6, NB_VQ = 7, NB_A = 8, NB_Q = 9, NB_C = 10, NB_WQ = 11, NB_SI = 13, NB_WV = 14, NB_V = 15;
#define B1 600
#define AD0 16
#define AD1 128
#define AD2 16
#define AD3 128
#define BMX 1200
#define B2 800
#define FLP 2
#define OSG 2
#define OST 7
#define NBX 1
#define PVB 2
#define QPV 0
#define ONES 0
#define E0L 0
#define E2L 0
#define T2E 1
#define XMB 0
#define B3 0
#define OSV 0
#define XTD 0
#define VSL 2
#define VTI 4
#define T9L 0
#define P1U 4
#define SIE 2
#define WOE 1
#define OGF 2
#define VSP 8
#define RFK 5
#define PFD 3
#define WOL 0
constexpr uint32_t SCQ = 0x3A003A00;
constexpr float SCE = 0.07216878364870322f * 1.4426950408889634f * 2048;
}

#define CBAR_SYNC(id, n) bar_sync(id, n)
#define CBAR_ARRIVE(id, n) bar_arrive(id, n)

__device__ __forceinline__ uint64_t wdesc(int off) { return mkdesc(C::SB0 + off, 8192, 1024); }
__device__ __forceinline__ uint64_t mdesc(int k) { return mkdesc_ns(C::SB0 + C::OFF_M + k * 512, 256, 128); }
__device__ __forceinline__ uint64_t tdesc(int k) { return mkdesc(C::SB0 + C::slot_off(k >> 3) + ((k >> 2) & 1) * 1024 + (k & 3) * 32, 16, 2048); }

__device__ __forceinline__ int dh_row(int n) { return (n & ~63) + (n & 32) + ((n >> 1) & 3) * 8 + ((n >> 3) & 3) * 2 + (n & 1); }
template <bool IS_O>
__device__ __forceinline__ void stage_box(const CUtensorMap& tm, uint32_t sb, int p, int cta, int rank) {
  using namespace C;
  const uint32_t bar = sb + BAR_W + 8 * p;
  const int head = cta / 3, col = head * DH + rank * 64;
  mbar_expect_tx(bar, 16384);
  if (!IS_O) tma2d(sb + OFF_WK + p * 16384, &tm, col, p * 128, bar);
  else for (int b = 2 * p - 1; b <= 2 * p; b++)
    tma2d(sb + OFF_WQ + (b + 1) * 8192, &tm, b < 0 ? 576 : (3 * rank + b / 3) * 64, b < 0 ? col : head * DH + ((rank + b) % 3) * 64, bar);
}
template <bool IS_O>
__device__ __forceinline__ void load_weights_rs(uint32_t (&wf)[C::NKR][4], const CUtensorMap& tms, const CUtensorMap& tm, int cta, int rank, uint32_t sb, int tid0, int& spin) {
  using namespace C;
  constexpr int STAGE = IS_O ? OFF_WQ : OFF_WK, YOFF = IS_O ? OFF_YO : OFF_YV, NB = IS_O ? NB_C : NB_V;
  const int i = (tid0 >> 3) & 3, n0 = (tid0 & 7) + (i >> 1) * 8;
  const int chunk = 2 * ((tid0 >> 5) & 3) + (i & 1);
  const int r0 = IS_O ? dh_row(n0) : n0, r1 = IS_O ? dh_row(n0 + 16) : n0 + 16;
  const uint32_t a0 = sb + STAGE + r0 * 128 + ((chunk ^ (r0 & 7)) << 4), a1 = sb + STAGE + r1 * 128 + ((chunk ^ (r1 & 7)) << 4);
#pragma unroll
  for (int p = 0; p < 5; p++) {
    mwait(sb + BAR_W + 8 * p, 0, spin);
    if (IS_O) PTS(8 + p);
    if (p + NBX < 5) { if ((tid0 & 127) == 96) stage_box<IS_O>(tms, sb, p + NBX, cta, rank); __syncwarp(); }
    if (IS_O) permute_cols(sb + STAGE + p * 16384, tid0, 512);
    else {
#pragma unroll 1
      for (int it = tid0 & 127; it < 256; it += 128) {
        const uint32_t base = sb + STAGE + p * 16384 + (it >> 1) * 128;
        const int sw = ((it >> 1) & 7) ^ ((it & 1) * 4);
        const uint4 u0 = lds128(base + (sw << 4)), u1 = lds128(base + ((sw ^ 1) << 4)), u2 = lds128(base + ((sw ^ 2) << 4)), u3 = lds128(base + ((sw ^ 3) << 4));
        sts128(base + (sw << 4), make_uint4(u0.x, u1.x, u2.x, u3.x)); sts128(base + ((sw ^ 1) << 4), make_uint4(u0.y, u1.y, u2.y, u3.y));
        sts128(base + ((sw ^ 2) << 4), make_uint4(u0.z, u1.z, u2.z, u3.z)); sts128(base + ((sw ^ 3) << 4), make_uint4(u0.w, u1.w, u2.w, u3.w));
      }
    }
    bar_sync(NB, 128);
#pragma unroll
    for (int k = 8 * p; k < 8 * p + 8; k++) {
      if (k < NKR) ldsm4t(wf[k < NKR ? k : 0], ((k & 1) ? a1 : a0) + (k >> 1) * 4096);
      else {
        const int n = k * 16 + ((tid0 & 127) >> 3), r = IS_O ? dh_row(n) : n, c = tid0 & 7;
        sts128(sb + YOFF + (n - NKR * 16) * 128 + ((c ^ (n & 7)) << 4), lds128(sb + STAGE + r * 128 + ((c ^ (r & 7)) << 4)));
      }
    }
    fence_async();
    bar_sync(NB, 128);
    if ((tid0 & 127) == 0) {
      mbar_expect_tx(sb + BAR_W + 8 * p, 16384);
      tma2d(sb + STAGE + p * 16384, &tm, (cta / 3) * DH + rank * 64, p * 128, sb + BAR_W + 8 * p);
    }
    __syncwarp();
  }
  PTS(IS_O ? 13 : 14);
  CBAR_SYNC(NB_PRO, 384);
}

__device__ __forceinline__ void load_pair(uint32_t sb, int i, int p, uint32_t slot, uint32_t ph, int& spin) {
  using namespace C;
  mwait(sb + BAR_E + 8 * p, ph, spin);
  if (elect_one()) bulk_g2s_mc(sb + slot, g_xn[i] + p * 16384, 16384, sb + BAR_F + 8 * p);
}
__device__ __forceinline__ void release_round(uint32_t sb, int p, int lane) {
  if (lane < (p == 2 ? 3 : 1)) mbar_arrive_cluster(mapa(sb, p == 2 ? lane : p) + C::BAR_E + 8 * (3 + p));
}

__device__ __forceinline__ void signal_o(int i, int cta) { csignal(CN_O + i * 5 + min(cta / 19, 4)); }

template <int K0, int K1>
__device__ __forceinline__ void v_mem_pass(float (&d)[8], const uint32_t (&wf)[C::NKR][4]) {
  using namespace C;
#pragma unroll
  for (int k = K0; k < K1; k++) {
    if (k < NKR) wgmma_rs16(d, wf[k < NKR ? k : 0], mdesc(k), k != 32);
    else wgmma_ts16(d, wdesc(OFF_YV + (k - NKR) * 2048), mdesc(k), 1);
  }
  wg_commit();
}
__device__ __forceinline__ void chain_v(const CUtensorMap& tmWv, const CUtensorMap& tmWk, const uint32_t sb, const int tid0, const int cta, const int rank) {
  using namespace C;
  asm volatile("setmaxnreg.inc.sync.aligned.u32 208;");
  int spin = 0;
  uint32_t wf[NKR][4];
  const int wu = uni((tid0 >> 5) & 3);
  const uint32_t slot = rank == 2 ? OFF_M : OFF_KT + rank * 16384;
  load_weights_rs<false>(wf, tmWv, tmWk, cta, rank, sb, tid0, spin);
  PTS(5);
#pragma unroll 1
  for (int i = 0; i < NSTEP; i++) {
    uint32_t vp[16], va;
#define STORE_V { _Pragma("unroll") for (int s = 0; s < 4; s++) stsm4(va + 128 + s * 128, vp[4 * s], vp[4 * s + 1], vp[4 * s + 2], vp[4 * s + 3]); }
    {
      float d[32];
      if (i > 0) CBAR_SYNC(NB_WV, 256);
#pragma unroll
      for (int p = 0; p < 5; p++) {
        if (OSV && p == 3) {
          wg_wait<0>();
          release_round(sb, 2, tid0 & 31);
          if (wu == 1 && i > 0) {
            CBAR_SYNC(NB_MR, 160);
            if (elect_one()) signal_o(i - 1, cta);
          }
        }
        mwait(sb + BAR_F + 8 * p, i & 1, spin);
        TS(i, 25 + p);
        wg_fence();
#pragma unroll
        for (int k = 8 * p; k < 8 * p + 8; k++) {
          if (k < NKR) wgmma_rs64(d, wf[k < NKR ? k : 0], tdesc(k), k);
          else wgmma_ts64(d, wdesc(OFF_YV + (k - NKR) * 2048), tdesc(k), 1);
          if (k == 8 * p + 1 && p >= 1 && p <= (OSV ? 2 : 3)) {
            wg_commit(); wg_wait<1>();
            release_round(sb, p - 1, tid0 & 31);
          }
          if (k == 8 * p + RFK && (p == 1 || p == 2)) {
            wg_commit();
            if (rank == p - 1 && wu == 0) load_pair(sb, i, p + 2, slot_off(p + 2), i & 1, spin);
            wg_fence();
          }
        }
        wg_commit();
      }
      wg_wait<0>();
      TS(i, 23);
#pragma unroll
      for (int q = 0; q < 16; q++) vp[q] = pin(pack_bf16(d[2 * q], d[2 * q + 1]));
      CBAR_SYNC(NB_RD, 256);
      const int tid = fresh(tid0) & 127, m = (tid >> 3) & 3;
      if (wu == 3) {
        const int lane = tid & 31;
        if (lane < 3 && lane != rank) mbar_arrive_cluster(mapa(sb, lane) + BAR_XF);
        if (lane < 8) mbar_expect_tx(sb + BAR_F + 8 * lane, lane < 5 ? 16384 : lane == 5 ? 2560 : lane == 6 ? 7168 : 4096);
        mwait(sb + BAR_XF, i & 1, spin);
      } else {
        if (tid < 80) sts128(sb + (tid < 72 ? OFF_VT + (tid >> 3) * VS : OFF_PT + 1280) + (tid & 7) * 16, make_uint4(0, 0, 0, 0));
        fence_async();
      }
      CBAR_ARRIVE(NB_QK, 384);
      TS(i, 16);
      va = sb + OFF_VT + 128 + ((tid >> 5) * 2 + (m & 1)) * VS + (m >> 1) * 640 + (tid & 7) * 16;
    }
    const uint32_t* xc = &g_cnt[CN_X + i + 1][0];
    const uint32_t xn = NOWORK == 2 || i + 1 < NPRE ? 0 : i + 1 < LAG || NOWORK ? 16 : 48;
    bool seen = false;
    if (wu == 0) seen = __any_sync(0xffffffffu, ld_relaxed(xc) >= xn);
    CBAR_SYNC(NB_V, 256);
    float d[8];
    wg_fence();
    v_mem_pass<32, 40>(d, wf);
    v_mem_pass<0, 6>(d, wf);
    wg_wait<1>();
    if ((tid0 & 31) < 3 && (tid0 & 31) != rank) mbar_arrive_cluster(mapa(sb, tid0 & 31) + BAR_MF);
    v_mem_pass<6, 32>(d, wf);
    if (VSL == 2) STORE_V
    CBAR_SYNC(NB_SM, 256);
    wg_wait<0>();
    TS(i, 24);
    const int tid = fresh(tid0);
    if (!E2L && (tid & 31) == 0) mbar_arrive_cluster(mapa(sb, 2) + BAR_E + 16);
    stsm4(va, pack_bf16(d[0], d[1]), pack_bf16(d[2], d[3]), pack_bf16(d[4], d[5]), pack_bf16(d[6], d[7]));
#undef STORE_V
    fence_async();
    CBAR_ARRIVE(NB_VA, 256);
    CBAR_ARRIVE(NB_VQ, QPV ? 384 : 256);
    if (wu == 0 && i + 1 < NSTEP) {
      if (!seen) while (ld_relaxed(xc) < xn && spin < SPIN_TOT) spin += 16;
      fence_async_all();
      load_pair(sb, i + 1, rank, slot, i & 1, spin);
      TS(i + 1, 37);
    }
    TS_FLUSH(i - 1);
    __syncwarp();
  }
  CBAR_ARRIVE(NB_WV, 256);
  if (spin >= SPIN_TOT) g_err = 3;
}

__device__ __forceinline__ float quad_max(float x) {
  const float a = __shfl_xor_sync(0xffffffffu, x, 1), b = __shfl_xor_sync(0xffffffffu, x, 2), c = __shfl_xor_sync(0xffffffffu, x, 3);
  return fmaxf(fmaxf(x, a), fmaxf(b, c));
}
__device__ __forceinline__ float max10(const float (&y)[10]) {
  return fmaxf(fmaxf(fmaxf(fmaxf(y[0], y[1]), fmaxf(y[2], y[3])), fmaxf(fmaxf(y[4], y[5]), fmaxf(y[6], y[7]))), fmaxf(y[8], y[9]));
}
__device__ __forceinline__ float sum10(const float (&y)[10]) {
  return (((y[0] + y[1]) + (y[2] + y[3])) + ((y[4] + y[5]) + (y[6] + y[7]))) + (y[8] + y[9]);
}
__device__ __forceinline__ float rcp(float x) { float y; asm("rcp.approx.ftz.f32 %0,%1;" : "=f"(y) : "f"(x)); return y; }

__device__ __forceinline__ void chain_q(const bf16* x0, const bf16* mem0, const uint32_t sb, const int tid0, const int cta, const int rank) {
  using namespace C;
  asm volatile("setmaxnreg.dec.sync.aligned.u32 96;");
  int spin = 0;
  PTS(0);
  pre_work(x0, mem0, cta, tid0 & 127);
  PTS(3);
  CBAR_SYNC(NB_Q, 128);
  PTS(2);
  if (tid0 < 160) {
    if (tid0 == 128) pre_wait(0, 96, spin);
    __syncwarp();
    load_pair(sb, 0, rank, rank == 2 ? OFF_M : OFF_KT + rank * 16384, 1, spin);
  }
  PTS(4);
  CBAR_SYNC(NB_PRO, 384);
  mwait(sb + BAR_W, 1, spin);
  PTS(6);
  const int wu = uni((tid0 >> 5) & 3);
  uint4 ov[4] = {};
  uint8_t* op = &g_o[ORING - 1][cta][(tid0 & 124) * 32];
  const uint32_t o0 = ((tid0 ^ (tid0 >> 2)) & 3) * 16 + (tid0 & 16) * 4;
#pragma unroll 1
  for (int i = 0; i < NSTEP; i++) {
    const int ph = i & 1;
    uint32_t qf[4][4];
    {
      float d[64];
#define QK_STEP(K, SC) wgmma_st128(d, desc_at(mkdesc(SB0 + ((K) >> 2) * 1024 + ((K) & 3) * 32, 16, 2048), so), \
                                   desc_at(mkdesc(SB0 + OFF_WQ + (K) * 2048, OFF_WK - OFF_WQ, 1024), p * 16384), SC)
      int p = 0;
      uint32_t so = OFF_KT;
      mwait(sb + BAR_F, ph, spin);
      TS(i, 0);
      wg_fence();
#pragma unroll
      for (int k = 0; k < 8; k++) {
        QK_STEP(k, k);
        if (k == OST) {
          wg_commit();
          mwait(sb + BAR_F, ph, spin);
#pragma unroll
          for (int h = 0; h < 4; h++) stg128(op + (h & 1) * 4096 + (o0 ^ ((h >> 1) * 64)), ov[h]);
          if (i > 0) CBAR_ARRIVE(NB_MR, 160);
          if (k < 7) wg_fence();
        }
      }
      if (OST < 7) wg_commit();
#pragma unroll 1
      for (p = 1; p < 5; p++) {
        static_assert(OFF_KT - OFF_M == 5 << 12, "");
        so = OFF_M + (((0x95095u >> (4 * p)) & 15) << 12);
        if (i == 0) { mwait(sb + BAR_W + 8 * p, 1, spin); PTS(14 + p); }
        mwait(sb + BAR_F + 8 * p, ph, spin);
        wg_fence();
#pragma unroll
        for (int k = 0; k < 8; k++) {
          QK_STEP(k, 1);
          if (k == 1) {
            wg_commit(); wg_wait<1>();
            release_round(sb, p - 1, p < 4 ? tid0 & 31 : 32);
          }
        }
        wg_commit();
      }
#undef QK_STEP
      wg_wait<0>();
      TS(i, 1);
      CBAR_SYNC(NB_RD, 256);
      TSB(i, 2);
      const int tid = fresh(tid0), w = (tid >> 5) & 3, m = (tid >> 3) & 3;
      const uint32_t a = sb + OFF_KT + (m >> 1) * KS + (1 + w + 5 * (m & 1)) * 128 + (tid & 7) * 16;
#pragma unroll
      for (int s = 0; s < 4; s++)
        stsm4t(a + s * 2 * KS, pack_bf16(d[32 + 8 * s], d[33 + 8 * s]), pack_bf16(d[34 + 8 * s], d[35 + 8 * s]),
               pack_bf16(d[36 + 8 * s], d[37 + 8 * s]), pack_bf16(d[38 + 8 * s], d[39 + 8 * s]));
      fence_async();
      CBAR_ARRIVE(NB_QK, 384);
      TS(i, 15);
#pragma unroll
      for (int kk = 0; kk < 4; kk++)
#pragma unroll
        for (int j = 0; j < 4; j++) asm volatile("{.reg .b32 t; cvt.rn.bf16x2.f32 t,%1,%2; mul.rn.bf16x2 %0,t,%3;}" : "=r"(qf[kk][j]) : "f"(d[8 * kk + 2 * j + 1]), "f"(d[8 * kk + 2 * j]), "r"(SCQ));
    }
    CBAR_SYNC(NB_SI, 256);
    uint32_t pf[5][4];
    float sa = 0.f, sb2 = 0.f;
    {
      float y0[10], y1[10];
      const int tidf = fresh(tid0), lane = tidf & 31;
      {
        float x[40];
        wg_fence();
#pragma unroll
        for (int kk = 0; kk < 4; kk++) {
          if (VTI && kk == 4 - VTI) CBAR_ARRIVE(NB_V, 256);
          wgmma_rt80(x, qf[kk], mkdesc_ns(SB0 + OFF_KT + kk * 2 * KS, KS, 128), kk);
        }
        wg_commit();
        wg_wait<0>();
#pragma unroll
        for (int j = 0; j < 5; j++) { y0[2 * j] = x[4 * j]; y0[2 * j + 1] = x[4 * j + 1]; y1[2 * j] = x[22 + 4 * j]; y1[2 * j + 1] = x[23 + 4 * j]; }
      }
      TS(i, 17);
      const uint32_t xo = OFF_XT + (wu * (wu + 3) / 2) * 256 + lane * 16, x2 = xo + (wu >> 1) * 512 + 512 - lane * 8;
      {
        const uint4 h0 = make_uint4(pack_h2(y0[0], y0[1]), pack_h2(y1[0], y1[1]), pack_h2(y0[2], y0[3]), pack_h2(y1[2], y1[3]));
        const uint4 h1 = make_uint4(pack_h2(y0[4], y0[5]), pack_h2(y1[4], y1[5]), pack_h2(y0[6], y0[7]), pack_h2(y1[6], y1[7]));
        const uint32_t h2 = wu == 1 ? h1.x : pack_h2(y0[8], y0[9]), h3 = wu == 1 ? h1.y : pack_h2(y1[8], y1[9]);
        const uint32_t rb1 = mapa(sb, (rank + 1) % 3), rb2 = mapa(sb, (rank + 2) % 3);
        if (XTD == 1) mwait(sb + BAR_XM, ph, spin);
        if (XTD > 1) for (const uint32_t t0 = clk32(); clk32() - t0 < XTD;) {}
        st_async4u(rb1 + xo + 3584, h0, rb1 + BAR_XT);
        st_async4u(rb2 + xo, h0, rb2 + BAR_XT);
        if (wu >= 2) { st_async4u(rb1 + xo + 4096, h1, rb1 + BAR_XT); st_async4u(rb2 + xo + 512, h1, rb2 + BAR_XT); }
        if (wu & 1) { st_async2u(rb1 + x2 + 3584, h2, h3, rb1 + BAR_XT); st_async2u(rb2 + x2, h2, h3, rb2 + BAR_XT); }
      }
      TS(i, 18);
      const int lim = 8 * wu + (lane >> 2) + 8 - 2 * (lane & 3);
#pragma unroll
      for (int j = 2; j < 10; j++)
        if (8 * (j >> 1) + (j & 1) > lim) { y0[j] = -INFINITY; y1[j] = -INFINITY; }
      mwait(sb + BAR_XT, ph, spin);
      TS(i, 19);
      {
        const uint4 u0 = lds128(sb + xo), v0 = lds128(sb + xo + 3584);
        uint2 u2 = make_uint2(0, 0), v2 = u2;
        if (wu & 1) { u2 = lds64(sb + x2); v2 = lds64(sb + x2 + 3584); }
        uint4 u1 = make_uint4(u2.x, u2.y, 0, 0), v1 = make_uint4(v2.x, v2.y, 0, 0);
        if (wu >= 2) { u1 = lds128(sb + xo + 512); v1 = lds128(sb + xo + 4096); }
        __syncwarp();
        if (lane == 0) mbar_arrive_cluster(mapa(sb, 0) + BAR_E);
        add_h2(y0[0], y0[1], u0.x, v0.x); add_h2(y1[0], y1[1], u0.y, v0.y); add_h2(y0[2], y0[3], u0.z, v0.z); add_h2(y1[2], y1[3], u0.w, v0.w);
        add_h2(y0[4], y0[5], u1.x, v1.x); add_h2(y1[4], y1[5], u1.y, v1.y); add_h2(y0[6], y0[7], u1.z, v1.z); add_h2(y1[6], y1[7], u1.w, v1.w);
        add_h2(y0[8], y0[9], u2.x, v2.x); add_h2(y1[8], y1[9], u2.y, v2.y);
      }
      const float m0 = quad_max(max10(y0)) * -SCE, m1 = quad_max(max10(y1)) * -SCE;
#pragma unroll
      for (int j = 0; j < 5; j++) {
        y0[2 * j] = ex2(fmaf(y0[2 * j], SCE, m0)); y0[2 * j + 1] = ex2(fmaf(y0[2 * j + 1], SCE, m0));
        y1[2 * j] = ex2(fmaf(y1[2 * j], SCE, m1)); y1[2 * j + 1] = ex2(fmaf(y1[2 * j + 1], SCE, m1));
        if (!ONES) { sa += y0[2 * j] + y0[2 * j + 1]; sb2 += y1[2 * j] + y1[2 * j + 1]; }
        pf[j >> 1][2 * (j & 1)] = pack_bf16(y0[2 * j], y0[2 * j + 1]);
        pf[j >> 1][2 * (j & 1) + 1] = tidf >> (10 + j);
        pf[(j + 5) >> 1][2 * ((j + 5) & 1)] = tidf >> (20 + j);
        pf[(j + 5) >> 1][2 * ((j + 5) & 1) + 1] = pack_bf16(y1[2 * j], y1[2 * j + 1]);
      }
    }
#pragma unroll
    for (int q = 0; q < 20; q++) pf[q >> 2][q & 3] = pin(pf[q >> 2][q & 3]);
    CBAR_SYNC(NB_VQ, QPV ? 384 : 256);
    TSB(i, 20);
    {
      float o[32], sm[4];
      wg_fence();
#pragma unroll
      for (int q = 0; q < 5; q++) if (ONES) wgmma_rs8(sm, pf[q], mkdesc_ns(SB0 + OFF_ONE, 0, 0), q);
#pragma unroll
      for (int q = 0; q < 5; q++) wgmma_rs64(o, pf[q], mkdesc_ns(SB0 + OFF_VT + 128 + q * 256, 128, VS), q);
      wg_commit();
      if (!ONES) { sm[0] = quad_sum(sa); sm[2] = quad_sum(sb2); }
      const int tid = fresh(tid0);
      op = &g_o[i % ORING][cta][(tid & 124) * 32];
      wg_wait<0>();
      TS(i, 21);
      if ((tid & 31) == 0) mbar_arrive_cluster(mapa(sb, 1) + BAR_E + 8);
      const float s0 = rcp(sm[0]), s1 = rcp(sm[2]);
#pragma unroll
      for (int h = 0; h < 2; h++) {
        const float* x = o + 16 * h;
        ov[2 * h] = make_uint4(pin(pack_bf16(x[0] * s0, x[1] * s0)), pin(pack_bf16(x[4] * s0, x[5] * s0)), pin(pack_bf16(x[8] * s0, x[9] * s0)), pin(pack_bf16(x[12] * s0, x[13] * s0)));
        ov[2 * h + 1] = make_uint4(pin(pack_bf16(x[2] * s1, x[3] * s1)), pin(pack_bf16(x[6] * s1, x[7] * s1)), pin(pack_bf16(x[10] * s1, x[11] * s1)), pin(pack_bf16(x[14] * s1, x[15] * s1)));
      }
      TS(i, 22);
      if (i + 1 < NSTEP) CBAR_SYNC(NB_WQ, 256); else CBAR_ARRIVE(NB_WQ, 256);
    }
  }
#pragma unroll
  for (int h = 0; h < 4; h++) stg128(op + (h & 1) * 4096 + (o0 ^ ((h >> 1) * 64)), ov[h]);
  CBAR_SYNC(NB_Q, 128);
  if (tid0 == 224) signal_o(NSTEP - 1, cta);
  if (spin >= SPIN_TOT) g_err = 2;
}

template <int NL> __device__ __forceinline__ void poll(uint4 (&x)[NL], const uint8_t* mb, uint32_t tag, int& spin);
template <> __device__ __forceinline__ void poll<4>(uint4 (&x)[4], const uint8_t* mb, uint32_t tag, int& spin) {
  asm volatile("{.reg .pred p<6>, q; .reg .b128 v; .reg .b32 t;\n"
               " ld.relaxed.gpu.global.b128 v,[%17+0]; mov.b128 {%0,%1,%2,%3},v;\n"
               " ld.relaxed.gpu.global.b128 v,[%17+512]; mov.b128 {%4,%5,%6,%7},v;\n"
               " ld.relaxed.gpu.global.b128 v,[%17+1024]; mov.b128 {%8,%9,%10,%11},v;\n"
               " ld.relaxed.gpu.global.b128 v,[%17+1536]; mov.b128 {%12,%13,%14,%15},v;\n"
               "POLL_LOOP:\n add.s32 %16,%16,16;\n"
               " lop3.b32 t,%0,%18,1,0x28; setp.ne.b32 p0,t,0;\n"
               " lop3.b32 t,%4,%18,1,0x28; setp.ne.b32 p1,t,0;\n"
               " lop3.b32 t,%8,%18,1,0x28; setp.ne.b32 p2,t,0;\n"
               " lop3.b32 t,%12,%18,1,0x28; setp.ne.b32 p3,t,0;\n"
               " or.pred q,p0,p1; or.pred q,q,p2; or.pred q,q,p3; setp.lt.and.s32 q,%16,%19,q; vote.sync.any.pred q,q,0xffffffff;\n"
               " mov.b128 v,{%0,%1,%2,%3}; @p0 ld.relaxed.gpu.global.b128 v,[%17+0]; mov.b128 {%0,%1,%2,%3},v;\n"
               " mov.b128 v,{%4,%5,%6,%7}; @p1 ld.relaxed.gpu.global.b128 v,[%17+512]; mov.b128 {%4,%5,%6,%7},v;\n"
               " mov.b128 v,{%8,%9,%10,%11}; @p2 ld.relaxed.gpu.global.b128 v,[%17+1024]; mov.b128 {%8,%9,%10,%11},v;\n"
               " mov.b128 v,{%12,%13,%14,%15}; @p3 ld.relaxed.gpu.global.b128 v,[%17+1536]; mov.b128 {%12,%13,%14,%15},v;\n"
               " @q bra.uni POLL_LOOP;\n}"
               : "=&r"(x[0].x), "=&r"(x[0].y), "=&r"(x[0].z), "=&r"(x[0].w), "=&r"(x[1].x), "=&r"(x[1].y), "=&r"(x[1].z), "=&r"(x[1].w), "=&r"(x[2].x), "=&r"(x[2].y), "=&r"(x[2].z), "=&r"(x[2].w), "=&r"(x[3].x), "=&r"(x[3].y), "=&r"(x[3].z), "=&r"(x[3].w), "+&r"(spin)
               : "l"(mb), "r"(tag), "n"(SPIN_TOT) : "memory");
}
template <> __device__ __forceinline__ void poll<6>(uint4 (&x)[6], const uint8_t* mb, uint32_t tag, int& spin) {
  asm volatile("{.reg .pred p<6>, q; .reg .b128 v; .reg .b32 t;\n"
               " ld.relaxed.gpu.global.b128 v,[%25+0]; mov.b128 {%0,%1,%2,%3},v;\n"
               " ld.relaxed.gpu.global.b128 v,[%25+512]; mov.b128 {%4,%5,%6,%7},v;\n"
               " ld.relaxed.gpu.global.b128 v,[%25+1024]; mov.b128 {%8,%9,%10,%11},v;\n"
               " ld.relaxed.gpu.global.b128 v,[%25+1536]; mov.b128 {%12,%13,%14,%15},v;\n"
               " ld.relaxed.gpu.global.b128 v,[%25+2048]; mov.b128 {%16,%17,%18,%19},v;\n"
               " ld.relaxed.gpu.global.b128 v,[%25+2560]; mov.b128 {%20,%21,%22,%23},v;\n"
               "POLL_LOOP:\n add.s32 %24,%24,16;\n"
               " lop3.b32 t,%0,%2,%26,0x7e; and.b32 t,t,1; setp.ne.b32 p0,t,0;\n"
               " lop3.b32 t,%4,%6,%26,0x7e; and.b32 t,t,1; setp.ne.b32 p1,t,0;\n"
               " lop3.b32 t,%8,%10,%26,0x7e; and.b32 t,t,1; setp.ne.b32 p2,t,0;\n"
               " lop3.b32 t,%12,%14,%26,0x7e; and.b32 t,t,1; setp.ne.b32 p3,t,0;\n"
               " lop3.b32 t,%16,%18,%26,0x7e; and.b32 t,t,1; setp.ne.b32 p4,t,0;\n"
               " lop3.b32 t,%20,%22,%26,0x7e; and.b32 t,t,1; setp.ne.b32 p5,t,0;\n"
               " or.pred q,p0,p1; or.pred q,q,p2; or.pred q,q,p3; or.pred q,q,p4; or.pred q,q,p5; setp.lt.and.s32 q,%24,%27,q; vote.sync.any.pred q,q,0xffffffff;\n"
               " mov.b128 v,{%0,%1,%2,%3}; @p0 ld.relaxed.gpu.global.b128 v,[%25+0]; mov.b128 {%0,%1,%2,%3},v;\n"
               " mov.b128 v,{%4,%5,%6,%7}; @p1 ld.relaxed.gpu.global.b128 v,[%25+512]; mov.b128 {%4,%5,%6,%7},v;\n"
               " mov.b128 v,{%8,%9,%10,%11}; @p2 ld.relaxed.gpu.global.b128 v,[%25+1024]; mov.b128 {%8,%9,%10,%11},v;\n"
               " mov.b128 v,{%12,%13,%14,%15}; @p3 ld.relaxed.gpu.global.b128 v,[%25+1536]; mov.b128 {%12,%13,%14,%15},v;\n"
               " mov.b128 v,{%16,%17,%18,%19}; @p4 ld.relaxed.gpu.global.b128 v,[%25+2048]; mov.b128 {%16,%17,%18,%19},v;\n"
               " mov.b128 v,{%20,%21,%22,%23}; @p5 ld.relaxed.gpu.global.b128 v,[%25+2560]; mov.b128 {%20,%21,%22,%23},v;\n"
               " @q bra.uni POLL_LOOP;\n}"
               : "=&r"(x[0].x), "=&r"(x[0].y), "=&r"(x[0].z), "=&r"(x[0].w), "=&r"(x[1].x), "=&r"(x[1].y), "=&r"(x[1].z), "=&r"(x[1].w), "=&r"(x[2].x), "=&r"(x[2].y), "=&r"(x[2].z), "=&r"(x[2].w), "=&r"(x[3].x), "=&r"(x[3].y), "=&r"(x[3].z), "=&r"(x[3].w), "=&r"(x[4].x), "=&r"(x[4].y), "=&r"(x[4].z), "=&r"(x[4].w), "=&r"(x[5].x), "=&r"(x[5].y), "=&r"(x[5].z), "=&r"(x[5].w), "+&r"(spin)
               : "l"(mb), "r"(tag), "n"(SPIN_TOT) : "memory");
}
template <int NL>
__device__ __forceinline__ void poll_add(const uint8_t* mb, uint32_t tag, float (&f)[8], uint8_t* flag, bool lead, int& spin) {
  uint4 x[NL];
  poll<NL>(x, mb, tag, spin);
  if (FLP == 0 && lead) st_relaxed(flag, 0);
#pragma unroll
  for (int i = 0; i < NL; i++) {
    const uint32_t u[4] = {x[i].x, x[i].y, x[i].z, x[i].w};
#pragma unroll
    for (int j = 0; j < 4; j++) {
      if (i == 0) { f[2 * j] = bf_lo(u[j]); f[2 * j + 1] = bf_hi(u[j]); }
      else { f[2 * j] += bf_lo(u[j]); f[2 * j + 1] += bf_hi(u[j]); }
    }
  }
}

template <int B, int SLOT>
__device__ __forceinline__ void wo_step(float (&acc)[8], const uint32_t (&wf)[C::NKR][4], int kk) {
  using namespace C;
  const int k = 4 * B + kk;
  const uint64_t db = mkdesc_ns(SB0 + og_off(SLOT) + kk * 512, 256, 128);
  if (k < NKR) wgmma_rt16(acc, wf[k < NKR ? k : 0], db, SLOT | kk);
  else wgmma_tt16(acc, wdesc(OFF_YO + (k - NKR) * 2048), db, 1);
}
template <int B, int SLOT>
__device__ __forceinline__ void wo_block(float (&acc)[8], const uint32_t (&wf)[C::NKR][4]) {
#pragma unroll
  for (int kk = 0; kk < 4; kk++) wo_step<B, SLOT>(acc, wf, kk);
}

__device__ __forceinline__ void chain_a(const CUtensorMap& tmWo, const CUtensorMap& tmWq, const uint32_t sb, const int tid0, const int cta, const int rank) {
  using namespace C;
  asm volatile("setmaxnreg.inc.sync.aligned.u32 200;");
  int spin = 0;
  uint32_t wf[NKR][4];
  load_weights_rs<true>(wf, tmWo, tmWq, cta, rank, sb, tid0, spin);
  const int wu = uni(tid0 >> 5);
  const bool t9 = cta >= 72 && cta < 88;
  const uint64_t exa = reinterpret_cast<uint64_t>(ex_window(g_ex));
  const uint32_t ehi = (uint32_t)(exa >> 32), elo = (uint32_t)exa;

  int b1 = B1, b2 = B2;
#pragma unroll 1
  for (int i = -1; i < NSTEP; i++) {
    const int ph = i & 1;
    if (i >= 0) {
      const int tid = fresh(tid0);
      const uint32_t mo = __shfl_xor_sync(0xffffffffu, elo + ((rank * 24 + (tid >> 4)) * 4 + (tid & 3)) * 2048 + (cta / 3) * 64 + (tid & 12) * 4, 0);
      const uint32_t m9 = __shfl_xor_sync(0xffffffffu, elo + MAIL9 + (((tid >> 4) * 2 + (tid & 1)) * 4 + (tid & 2)) * 3072 + cta * 32 + (tid & 12) * 2, 0);
      const uint32_t oo = __shfl_xor_sync(0xffffffffu, (tid >> 5) * 512 + (tid & 2) * 64 + (tid & 28) * 4 + (tid & 1) * 8, 0);
      if (i == 0) { mwait(sb + BAR_W + 24, 1, spin); mwait(sb + BAR_W + 32, 1, spin); PTS(7); }
      mwait(sb + BAR_M, ph, spin);
      TS(i, 3);
      {
        float x[20];
        int redo = 0;
      retry:
        bool bad;
        {
          float dq[8] = {}, dk[8] = {};
#pragma unroll 1
          for (int k0 = 0; k0 < 40; k0 += P1U) {
            wg_fence();
#pragma unroll
            for (int k = 0; k < P1U; k++) {
              const uint64_t db = desc_at(mdesc(k), k0 * 512);
              wgmma_ts16(dq, desc_at(wdesc(OFF_WQ + k * 2048), k0 * 2048), db, 1);
              wgmma_ts16(dk, desc_at(wdesc(OFF_WK + k * 2048), k0 * 2048), db, 1);
            }
            wg_commit();
          }
          const int m = (tid >> 3) & 3, dg = (tid >> 5) * 2 + (m & 1);
          const uint32_t ka = sb + OFF_KT + dg * KS + (m >> 1) * 640 + (tid & 7) * 16;
          if (!redo) CBAR_SYNC(NB_QK, 384);
          wg_wait<0>();
          TS(i, 4);
          stsm4(ka, pack_bf16(dk[0], dk[1]), pack_bf16(dk[2], dk[3]), pack_bf16(dk[4], dk[5]), pack_bf16(dk[6], dk[7]));
          stsm4(ka + dg * (VS - KS) + (OFF_VT + 128 - OFF_KT), scale_bf16x2(pack_bf16(dq[0], dq[1]), SCQ), scale_bf16x2(pack_bf16(dq[2], dq[3]), SCQ),
                scale_bf16x2(pack_bf16(dq[4], dq[5]), SCQ), scale_bf16x2(pack_bf16(dq[6], dq[7]), SCQ));
          const float chk = (dq[0] + dq[1]) + (dq[4] + dq[5]);
          fence_async();
          bad = bar_red_or(NB_C, 128, chk != chk && !redo);
        }
        TSB(i, 5);
        wg_fence();
#pragma unroll
        for (int kk = 0; kk < 4; kk++) wgmma_tt40(x, mkdesc_ns(SB0 + OFF_VT + 128 + kk * 2 * VS, VS, 640), mkdesc_ns(SB0 + OFF_KT + kk * 2 * KS, KS, 128), kk);
#pragma unroll
        for (int kk = 0; kk < 4; kk++) {
          if (SIE && kk == 4 - SIE && !bad) CBAR_ARRIVE(NB_SI, 256);
          wgmma_tt40(x, mkdesc_ns(SB0 + OFF_VT + kk * 2 * VS, VS, 384), mkdesc_ns(SB0 + OFF_KT + 640 + kk * 2 * KS, KS, 128), 1);
        }
        wg_commit();
        if (!SIE && !bad) CBAR_ARRIVE(NB_SI, 256);
        if (__builtin_expect(__any_sync(0xffffffffu, bad), 0)) {
          wg_wait<0>();
#pragma unroll 1
          for (int k = 0; k < 10; k++) {
            uint4 v = lds128(sb + OFF_M + tid * 16 + k * 2048);
            if (v.x == SENT || v.y == SENT || v.z == SENT || v.w == SENT) {
              do { v = ld_relaxed4(mkptr(elo + EX_M + i * 20480 + tid * 16 + k * 2048, ehi)); spin += 16; } while ((v.x == SENT || v.y == SENT || v.z == SENT || v.w == SENT) && spin < SPIN_TOT);
              sts128(sb + OFF_M + tid * 16 + k * 2048, v);
            }
          }
          fence_async();
          bar_sync(NB_C, 128);
          redo = fresh(1);
          goto retry;
        }
        TSV(i, 36, redo);
        const uint32_t rb1 = mapa(sb, (rank + 1) % 3), rb2 = mapa(sb, (rank + 2) % 3);
        wg_wait<0>();
        TS(i, 6);
        if (wu < 2) {
          float y[10];
#pragma unroll
          for (int j = 0; j < 5; j++) { y[2 * j] = x[4 * j]; y[2 * j + 1] = x[4 * j + 1]; }
          const uint4 h0 = make_uint4(pack_h2(y[0], y[1]), pack_h2(y[2], y[3]), pack_h2(y[4], y[5]), pack_h2(y[6], y[7]));
          const uint32_t h1 = pack_h2(y[8], y[9]);
          const uint32_t xo = wu * 640 + (tid & 31) * 16, xp = wu * 640 + 512 + (tid & 31) * 4;
          if (XMB) {
            sts128(sb + og_off(0) + xo, h0); sts32(sb + og_off(0) + xp, h1);
            fence_async();
            __syncwarp();
            if (elect_one()) {
              bulk_s2c(rb1 + OFF_XM + 1280 + wu * 640, sb + og_off(0) + wu * 640, 640, rb1 + BAR_XM);
              bulk_s2c(rb2 + OFF_XM + wu * 640, sb + og_off(0) + wu * 640, 640, rb2 + BAR_XM);
            }
          } else {
            st_async4u(rb1 + OFF_XM + 1280 + xo, h0, rb1 + BAR_XM);
            st_async4u(rb2 + OFF_XM + xo, h0, rb2 + BAR_XM);
            st_async1u(rb1 + OFF_XM + 1280 + xp, h1, rb1 + BAR_XM);
            st_async1u(rb2 + OFF_XM + xp, h1, rb2 + BAR_XM);
          }
          CBAR_ARRIVE(NB_SM, 256);
          if (!E0L && (tid & 31) == 0) mbar_arrive_cluster(mapa(sb, 0) + BAR_E);
          TS(i, 7);
          const uint32_t sw = (tid & 7) * 4 + (tid & 8) * 8 + (tid & 16) * 2;
          mwait(sb + BAR_XM, ph, spin);
          TS(i, 8);
          const uint4 u0 = lds128(sb + OFF_XM + xo), v0 = lds128(sb + OFF_XM + 1280 + xo);
          const uint32_t u1 = lds32(sb + OFF_XM + xp), v1 = lds32(sb + OFF_XM + 1280 + xp);
          add_h2(y[0], y[1], u0.x, v0.x); add_h2(y[2], y[3], u0.y, v0.y); add_h2(y[4], y[5], u0.z, v0.z); add_h2(y[6], y[7], u0.w, v0.w);
          add_h2(y[8], y[9], u1, v1);
          const float mx = quad_max(max10(y)) * -SCE;
#pragma unroll
          for (int j = 0; j < 5; j++) {
            y[2 * j] = ex2(fmaf(y[2 * j], SCE, mx)); y[2 * j + 1] = ex2(fmaf(y[2 * j + 1], SCE, mx));
            sts32(sb + OFF_PT + wu * 640 + sw + j * 128, pack_bf16(y[2 * j], y[2 * j + 1]));
          }
          sts32(sb + OFF_XM + 512 + wu * 128 + sw, __float_as_uint(sum10(y)));
          fence_async();
          TS(i, 9);
        } else {
          CBAR_ARRIVE(NB_SM, 256);
          if (!E0L && (tid & 31) == 0) mbar_arrive_cluster(mapa(sb, 0) + BAR_E);
          mwait(sb + BAR_MF, ph, spin);
        }
      }
      CBAR_SYNC(NB_VA, 256);
      TSB(i, 10);
      {
        float o[2][4];
        const float4 e = lds128f(sb + OFF_XM + 512 + (tid & 15) * 16);
        wg_fence();
#pragma unroll
        for (int c = 0; c < 2; c++)
#pragma unroll
          for (int q = 0; q < 3; q++)
            wgmma_ss8(o[c], mkdesc_ns(SB0 + OFF_VT + 128 + c * 640 + q * 256, 128, VS), mkdesc_ns(SB0 + OFF_PT + c * 640 + q * 256, q == 2 && c == 0 ? 768 : 128, 128), q);
        wg_commit();
        if (PVB && __builtin_expect(b1 < 0, 0)) { wg_wait<0>(); break; }
        const uint32_t rb1 = mapa(sb, (rank + 1) % 3), rb2 = mapa(sb, (rank + 2) % 3);
        const float inv = rcp((e.x + e.y) + (e.z + e.w));
        const int sl = (tid & 3) * 2;
        const float i0 = __shfl_sync(0xffffffffu, inv, sl), i1 = __shfl_sync(0xffffffffu, inv, sl + 1);
        const float i2 = __shfl_sync(0xffffffffu, inv, sl + 8), i3 = __shfl_sync(0xffffffffu, inv, sl + 9);
        if (E0L == 1 && (tid & 31) == 0) mbar_arrive_cluster(mapa(sb, 0) + BAR_E);
        if (PVB > 1 && __builtin_expect(b2 < 0, 0)) { wg_wait<0>(); break; }
        wg_wait<0>();
        TS(i, 11);
        const uint32_t p0 = pack_bf16(o[0][0] * i0, o[0][1] * i1), p1 = pack_bf16(o[1][0] * i2, o[1][1] * i3);
        const uint32_t p2 = pack_bf16(o[0][2] * i0, o[0][3] * i1), p3 = pack_bf16(o[1][2] * i2, o[1][3] * i3);
        if (OGF) { sts64(sb + oo + og_off(0), p0, p1); sts64(sb + oo + og_off(0) + 256, p2, p3); fence_async(); }
        if (OGF == 2) {
          __syncwarp();
          if (elect_one()) {
            bulk_s2c(rb1 + og_off(2) + wu * 512, sb + og_off(0) + wu * 512, 512, rb1 + BAR_OG);
            bulk_s2c(rb2 + og_off(1) + wu * 512, sb + og_off(0) + wu * 512, 512, rb2 + BAR_OG);
          }
        } else if (OGF < 2) {
          st_async2u(rb1 + oo + og_off(2), p0, p1, rb1 + BAR_OG);
          st_async2u(rb2 + oo + og_off(1), p0, p1, rb2 + BAR_OG);
          st_async2u(rb1 + oo + og_off(2) + 256, p2, p3, rb1 + BAR_OG);
          st_async2u(rb2 + oo + og_off(1) + 256, p2, p3, rb2 + BAR_OG);
        }
        if (!OGF) { sts64(sb + oo + og_off(0), p0, p1); sts64(sb + oo + og_off(0) + 256, p2, p3); fence_async(); }
      }
      if (E0L == 2 && (tid & 31) == 0) mbar_arrive_cluster(mapa(sb, 0) + BAR_E);
      CBAR_SYNC(NB_A, 128);
      TSB(i, 12);
      if (OGF == 3 && wu < 2 && elect_one()) {
        const uint32_t rb = mapa(sb, (rank + 1 + wu) % 3);
        bulk_s2c(rb + og_off(2) - wu * 2048, sb + og_off(0), 2048, rb + BAR_OG);
      }
      {
        float acc[3][8];
        wg_fence();
        wo_block<0, 0>(acc[2], wf);
        wg_commit();
        wo_block<1, 0>(acc[0], wf);
        if (QPV == 1) CBAR_ARRIVE(NB_VQ, 384);
        wo_block<4, 0>(acc[1], wf);
        wg_commit();
        if (QPV == 2) CBAR_ARRIVE(NB_VQ, 384);
        if (tid < (E2L == 1 ? 2 : 1)) mbar_arrive_cluster(mapa(sb, 1 + tid) + BAR_E + 8 + 8 * tid);
        const uint32_t tag = (i >> 1) & 1;
#define TAGGED(LO, HI) ((pack_bf16(LO, HI) & ~1u) | tag)
#define SEND(OFF, U) st_relaxed128(mkptr(mo + (ph << 20), ehi) + (OFF), TAGGED(acc[U][0], acc[U][2]), pack_bf16(acc[U][1], acc[U][3]), pack_bf16(acc[U][4], acc[U][6]), pack_bf16(acc[U][5], acc[U][7]))
        wg_wait<1>();
        const uint32_t n0 = pin(TAGGED(acc[2][0], acc[2][2])), n1 = pin(pack_bf16(acc[2][1], acc[2][3]));
        const uint32_t n2 = pin(TAGGED(acc[2][4], acc[2][6])), n3 = pin(pack_bf16(acc[2][5], acc[2][7]));
        if (T2E) { wg_fence(); wo_block<7, 0>(acc[2], wf); wg_commit(); }
        if (!T9L) { st_relaxed64(mkptr(m9 + (ph << 20), ehi), n0, n1); st_relaxed64(mkptr(m9 + (ph << 20), ehi) + 3072, n2, n3); }
        mwait(sb + BAR_OG, ph, spin);
        asm volatile("fence.proxy.async::generic.acquire.sync_restrict::shared::cluster.cluster;" ::: "memory");
        if (E2L == 2 && tid == 0) mbar_arrive_cluster(mapa(sb, 2) + BAR_E + 16);
        TS(i, 13);
        wg_fence();
        wo_block<2, 1>(acc[0], wf); wo_block<3, 2>(acc[0], wf);
        wg_commit();
        wo_block<5, 1>(acc[1], wf); wo_block<6, 2>(acc[1], wf);
        wg_commit();
        if (QPV == 3) CBAR_ARRIVE(NB_VQ, 384);
        wg_wait<1>();
        if (T9L) { st_relaxed64(mkptr(m9 + (ph << 20), ehi), n0, n1); st_relaxed64(mkptr(m9 + (ph << 20), ehi) + 3072, n2, n3); }
        SEND(0, 0);
        if (!T2E) wo_block<7, 0>(acc[2], wf);
        wo_block<8, 1>(acc[2], wf); wo_block<9, 2>(acc[2], wf);
        wg_commit();
        if (WOE == 0) { CBAR_ARRIVE(NB_WV, 256); CBAR_ARRIVE(NB_WQ, 256); }
        wg_wait<1>(); SEND(32 * 2048, 1);
        if (WOE == 1) CBAR_ARRIVE(NB_WV, 256);
        wg_wait<0>(); SEND(64 * 2048, 2);
        if (WOE == 2) CBAR_ARRIVE(NB_WV, 256);
        if (WOE >= 1) CBAR_ARRIVE(NB_WQ, 256);
#undef SEND
#undef TAGGED
      }
      TS(i, 14);
      if (i < 2) PTS(19 + i);
      if (i + 1 >= NSTEP) break;
    }
    uint32_t t1 = clk32();
    if (i >= 0) {
      const int lane = fresh(tid0) & 31, j = lane >> 3;
      const uint8_t* mb = mkptr(elo + (ph << 20) + (t9 ? MAIL9 + (cta - 72) * 12288 + wu * 3072 : (cta < 72 ? cta : cta - 24) * 8192 + wu * 2048) + lane * 16, ehi);
      const uint32_t tag = (i >> 1) & 1;
      const bool pub = (lane & (t9 ? 6 : 4)) == 0 && !(((t9 ? cta : wu) & 1) && i + 1 == LAG) && cta < 88;
      const uint32_t dst = pin(elo + EX_M + (i + 1) * 20480 + (t9 ? (cta + 72) * 128 + wu * 32 + (j & 1) * 16 + (lane & 1) * 8 + (j >> 1) * 4
                                                                   : cta * 256 + (wu & 1) * 128 + (wu >> 1) * 64 + j * 16 + (lane & 3) * 4));
      uint8_t* flag = mkptr(elo + EX_FLAG + (i + 1) * 3072 + cta * 32 + wu * 4, ehi);
      while (clk32() - t1 < b1) {}
      TS(i + 1, 30);
      float f[8];
      const int n0 = spin;
      if (!t9) poll_add<4>(mb, tag, f, flag, lane == 0, spin);
      else poll_add<6>(mb, tag, f, flag, lane == 0, spin);
      if (FLP == 1 && lane == 0) st_relaxed(flag, __float_as_uint(f[0] + f[7]) >> 1);
      t1 = clk32();
      b1 = __any_sync(0xffffffffu, spin - n0 > 16) ? min(b1 + AD1, BMX) : max(b1 - AD0, 0);
      TSV(i + 1, 38, b1);
      TS(i + 1, 31); TSV(i + 1, 32, (spin - n0) >> 4);
      const bool h = lane & 16, q = lane & 8;
#pragma unroll
      for (int j = 0; j < 4; j++) f[j] = (h ? f[4 + j] : f[j]) + __shfl_xor_sync(0xffffffffu, h ? f[j] : f[4 + j], 16);
#pragma unroll
      for (int j = 0; j < 2; j++) f[j] = (q ? f[2 + j] : f[j]) + __shfl_xor_sync(0xffffffffu, q ? f[j] : f[2 + j], 8);
      f[0] += __shfl_xor_sync(0xffffffffu, f[0], 4); f[1] += __shfl_xor_sync(0xffffffffu, f[1], 4);
      if (t9) { f[0] += __shfl_xor_sync(0xffffffffu, f[0], 2); f[1] += __shfl_xor_sync(0xffffffffu, f[1], 2); }
      if (pub) st_relaxed(mkptr(dst, ehi), pack_bf16(f[0], f[1]));
      if (FLP == 2 && lane == 0) st_relaxed(flag, 0);
      if (!OSV && wu == 3) {
        CBAR_SYNC(NB_MR, 160);
        if (elect_one()) signal_o(i, cta);
      }

    }
    if (wu == 0) {
      const int tid = fresh(tid0);
      const uint8_t* pp = mkptr(elo + EX_FLAG + (i + 1) * 3072 + (rank * 28 + (tid < 28 || rank == 2 ? tid : 0)) * 32, ehi);
      while (clk32() - t1 < b2) {}

      int n = 1;
      uint4 x = ld_relaxed4(pp);
      if (tid0 == 0) mbar_expect_tx(sb + BAR_M, 20480);
      bool mok = mbar_test(sb + BAR_MOK, ph ^ 1);
      while (__any_sync(0xffffffffu, (int)(x.x | x.y | x.z | x.w) < 0 && spin < SPIN_TOT)) { x = ld_relaxed4(pp); mok = mbar_test(sb + BAR_MOK, ph ^ 1); n++; spin += 16; }
      if (!mok) mwait(sb + BAR_MOK, ph ^ 1, spin);
      if (B3 && n > 1) { const uint32_t t3 = clk32(); while (clk32() - t3 < B3) {} }
      b2 = n > 1 ? min(b2 + AD3, BMX) : max(b2 - AD2, 0);
      TSV(i + 1, 35, n); TSV(i + 1, 39, b2);
      TS(i + 1, 34);
      if (elect_one()) bulk_g2s_mc(sb + OFF_M + rank * 7168, mkptr(elo + EX_M + (i + 1) * 20480 + rank * 7168, ehi), rank == 2 ? 6144 : 7168, sb + BAR_M);
      TS(i + 1, 33);
      __syncwarp();
    }
  }
  if (spin >= SPIN_TOT) g_err = 1;
}

__global__ void __cluster_dims__(3, 1, 1) __launch_bounds__(384, 1)
k_chain(const __grid_constant__ CUtensorMap tmWq, const __grid_constant__ CUtensorMap tmWk,
        const __grid_constant__ CUtensorMap tmWv, const __grid_constant__ CUtensorMap tmWo, const bf16* __restrict__ x0, const bf16* __restrict__ mem0) {
  using namespace C;
  extern __shared__ __align__(1024) uint8_t smem[];
  const uint32_t sb = smem_u32(smem);
  const int tid = threadIdx.x;
  const int wg = __shfl_sync(0xffffffffu, tid >> 7, 0);
  const int cta = uni(blockIdx.x), rank = uni(blockIdx.x % 3);

  asm volatile("griddepcontrol.launch_dependents;");
  if (cta < 4) prefetch_l2(tid < 320 ? x0 + (cta * 320 + tid) * 64 : mem0 + (cta * 20 + tid % 20) * 64);
  if (tid == 32) {
    for (int p = 0; p < 5; p++) mbar_init(sb + BAR_W + 8 * p, 2);
    fence_async();
    for (int p = 0; p < NBX; p++) { stage_box<false>(tmWv, sb, p, cta, rank); stage_box<true>(tmWo, sb, p, cta, rank); }
  }
  if (tid == 0) {
    if ((sb & 0xFFFFFF) != SB0) g_err = 100;
    for (int p = 0; p < 5; p++) { mbar_init(sb + BAR_F + 8 * p, 1); mbar_init(sb + BAR_E + 8 * p, p == 2 ? (E2L ? 3 : 12) : p == 1 ? 15 : 24); }
    mbar_init(sb + BAR_M, 1); mbar_init(sb + BAR_MOK, 24); mbar_init(sb + BAR_XM, 1); mbar_init(sb + BAR_XF, 2);
    mbar_init(sb + BAR_XT, 1); mbar_init(sb + BAR_MF, 8); mbar_init(sb + BAR_OG, 1);
    for (int p = 0; p < 5; p++) mbar_expect_tx(sb + BAR_F + 8 * p, 16384);
    for (int p = 0; p < 16; p++) sts32(sb + OFF_SAFE + 4 * p, 0);
    for (int p = 0; p < 32; p++) sts32(sb + OFF_ONE + 4 * p, 0x3F803F80);
    asm volatile("fence.mbarrier_init.release.cluster;" ::: "memory");
    fence_async();
  }
  __syncthreads();
  asm volatile("barrier.cluster.arrive.relaxed.aligned;" ::: "memory");
  asm volatile("barrier.cluster.wait.aligned;" ::: "memory");

  if (wg == 0) chain_a(tmWo, tmWq, sb, keep(tid), cta, rank);
  else if (wg == 1) chain_q(x0, mem0, sb, keep(tid), cta, rank);
  else chain_v(tmWv, tmWk, sb, keep(tid), cta, rank);
  asm volatile("barrier.cluster.arrive.release.aligned;" ::: "memory");
  asm volatile("barrier.cluster.wait.acquire.aligned;" ::: "memory");
}

namespace W {
constexpr int NP = 25, NBC = 11, NW = NP + NBC;
constexpr int PRS = 37, PW = 43 * 2048;
constexpr int OFF_W = 0;
constexpr int OFF_R = 2 * PW;
constexpr int BRS = 37, VSS = 39;
constexpr int OFF_WO = 0, OFF_Y = 81920;
constexpr int OFF_X = OFF_Y + 2 * (40 - BRS) * 2048;
constexpr int OFF_WV = OFF_X + 40960;
constexpr int OFF_S = OFF_WV + VSS * 2048;
constexpr int COL = 976;
constexpr int OFF_T = OFF_X + 16384;
constexpr int OFF_H = OFF_S + 7696;
constexpr int OFF_BAR = OFF_H + 8 * COL;
constexpr int OFF_SAFE = OFF_BAR + 256;
constexpr int SMEM = 232448;
static_assert(OFF_SAFE + 64 <= SMEM && OFF_R + 40960 <= OFF_BAR, "");
constexpr uint32_t SB0 = 1024;
constexpr int BAR_F = OFF_BAR, BAR_E = OFF_BAR + 40, BAR_G = OFF_BAR + 80, BAR_W = OFF_BAR + 160, BAR_R = OFF_BAR + 176;
constexpr int NB_G0 = 1, NB_SG = 4, NB_B = 5, NB_AS = 6, NB_SG1 = 7, NB_RED = 8, NB_SF = 9, NB_R = 11, NB_TD = 12, NB_RED3 = 13;
}
#define WDP 0
#define WDB 0
#define FSL 1
#define FSW 1
#define FSA 2
#define WBAR_SYNC(id, n) bar_sync(id, n)
#define WBAR_ARRIVE(id, n) bar_arrive(id, n)

__device__ __forceinline__ uint64_t rdesc(int off, int kk) { return mkdesc(W::SB0 + off + kk * 32, 16, 1024); }
__device__ __forceinline__ uint64_t gdesc(int off, int kk) { return mkdesc_ns(W::SB0 + off + kk * 1024, 512, 512) | ((uint64_t)2 << 62); }
__device__ __forceinline__ uint32_t frag_addr(uint32_t base, int tid) {
  const int i = (tid >> 3) & 3, r = tid & 7;
  return base + (r + (i >> 1) * 8) * 128 + (((2 * ((tid >> 5) & 3) + (i & 1)) ^ r) << 4);
}
template <int NK>
__device__ __forceinline__ void load_frags(uint32_t (&wf)[NK][4], uint32_t base, int tid) {
  const uint32_t a0 = frag_addr(base, tid);
#pragma unroll
  for (int k = 0; k < NK; k++) ldsm4t(wf[k], a0 + k * 2048);
}
__device__ __forceinline__ void red_tile(const float* d, int seg, int col0, int tid) {
  float* p = g_x + (size_t)(seg * 32 + 2 * (tid & 3)) * DM + col0 + ((tid >> 5) & 3) * 16 + ((tid >> 2) & 7) * 2;
#pragma unroll
  for (int j = 0; j < 8; j++)
    asm volatile("red.relaxed.gpu.global.add.v2.f32 [%0],{%1,%2};" ::"l"(p + ((j >> 1) * 8 + (j & 1)) * DM), "f"(d[4 * (j >> 1) + (j & 1)]), "f"(d[4 * (j >> 1) + 2 + (j & 1)]) : "memory");
}

__device__ __forceinline__ void work_p(const CUtensorMap& tmWo, uint32_t sb, int pc, const int WG, int tid0) {
  using namespace W;
  asm volatile("setmaxnreg.inc.sync.aligned.u32 208;");
  int spin = 0;
  const int ks = pc / 5, col0 = (pc % 5) * 128 + WG * 64;
  const uint32_t wb = sb + OFF_W + WG * PW;
  uint32_t wf[PRS][4];
#pragma unroll 1
  for (int hf = 0; hf < 2; hf++) {
    const int nk = hf ? 80 - PRS : PRS;
    if ((tid0 & 127) == 0) {
      mbar_expect_tx(sb + BAR_W + 8 * WG, nk * 2048);
      for (int i = 0; i < nk; i++) tma2d(wb + i * 2048, &tmWo, col0, ks * 19 * 64 + (i < PRS ? 2 * i + hf : PRS + i) * 16, sb + BAR_W + 8 * WG);
    }
    __syncwarp();
    mwait(sb + BAR_W + 8 * WG, hf, spin);
    permute_cols(wb, tid0 & 127, nk * 64);
    if (hf == 1 && ks < 4) for (int it = 39 * 64 + (tid0 & 127) - 64; it < 43 * 64; it += 128) {
      const uint32_t a = wb + (it >> 2) * 128 + (((2 * (it & 3)) ^ ((it >> 2) & 6)) << 4);
      if (it >= 39 * 64) { sts128(a, make_uint4(0, 0, 0, 0)); sts128(a + 16, make_uint4(0, 0, 0, 0)); }
    }
    fence_async();
    WBAR_SYNC(NB_G0 + WG, 128);
    if (hf == 0) {
      load_frags<PRS>(wf, wb, tid0);
      fence_async();
      WBAR_SYNC(NB_G0 + WG, 128);
    }
  }
#pragma unroll 1
  for (int k = 0; k < NSTEP; k++) {
    float d[32];
#pragma unroll
    for (int f = 0; f < 20; f++) {
      mwait(sb + BAR_F + 8 * (f % 5), (f / 5) & 1, spin);
      if (f == 0 && WG == 0 && pc == WW) WTS(k, 1);
      wg_fence();
#pragma unroll
      for (int kk = 0; kk < 4; kk++) {
        const int q = 4 * f + kk;
        if (q < 2 * PRS && !(q & 1)) wgmma_rs64(d, wf[q < 2 * PRS ? q >> 1 : 0], rdesc(OFF_R + (f % 5) * 8192, kk), q);
        else wgmma_ts64(d, desc_at(mkdesc(SB0 + OFF_W + (q < 2 * PRS ? q >> 1 : q - PRS) * 2048, 8192, 1024), WG * PW), rdesc(OFF_R + (f % 5) * 8192, kk), 1);
        if (kk == 0 && f > 0) {
          wg_commit();
          wg_wait<1>();
          if ((tid0 & 31) == 0) mbar_arrive(sb + BAR_E + 8 * ((f - 1) % 5));
        }
      }
      wg_commit();
    }
    wg_wait<0>();
    if ((tid0 & 31) == 0) mbar_arrive(sb + BAR_E + 32);
    if (WG == 0 && pc == WW) WTS(k, 2);
    if (k < NSEG) red_tile(d, k, col0, tid0);
    if (k >= LAG) red_tile(d + 16, k - LAG, col0, tid0);
    if (WG == 0 && pc == WW) WTS(k, 13);
    WBAR_SYNC(NB_SG, 288);
  }
  if (spin >= SPIN_TOT) g_err = 11;
}
__device__ __forceinline__ void work_p_producer(uint32_t sb, int pc) {
  using namespace W;
  int spin = 0;
  const int ks = pc / 5;
#pragma unroll 1
  for (int k = 0; k < NSTEP; k++) {
    const uint32_t lo = k < NSEG ? 0 : 4096, len = k < LAG || k >= NSEG ? 4096 : 8192;
    const uint8_t* src = &g_o[k % ORING][ks * 19][lo];
    cwait(CN_O + k * 5 + ks, ks == 4 ? 20 : 19, spin);
    fence_async_all();
    if (pc == WW) WTS1(k, 0);
#pragma unroll 1
    for (int u = 0; u < 4; u++) {
#pragma unroll
      for (int st = 0; st < 5; st++) {
        mwait(sb + BAR_E + 8 * st, (u & 1) ^ 1, spin);
        if (elect_one()) {
          if (st == 4 && u == 3 && ks < 4) mbar_arrive(sb + BAR_F + 8 * st);
          else {
            mbar_expect_tx(sb + BAR_F + 8 * st, len);
            bulk_g2s(sb + OFF_R + st * 8192 + lo, src + (u * 5 + st) * 8192, len, sb + BAR_F + 8 * st);
          }
        }
      }
    }
  }
  if (spin >= SPIN_TOT) g_err = 12;
}
template <int DMS>
__device__ __forceinline__ void work_ln(const int kind, int r, int lane, bf16* out) {
  int spin = 0;
  const int l = kind & 1;
  const int rp = kind < 2 ? (r & 1) * 16 + (r >> 1) : r;
  const uint32_t sw = ((((lane >> 1) & 7) ^ (rp & 7)) << 4) + (lane & 1) * 8;
  uint8_t* dst = kind < 2 ? g_xnb[l * LAG] + (lane >> 4) * 8192 + l * 4096 + rp * 128 + sw
               : kind == 2 ? g_xn[LAG] + (r >> 3) * 4096 + 2048 + (lane >> 4) * 1024 + (r & 7) * 128 + sw
                           : reinterpret_cast<uint8_t*>(out) + r * 1280 + lane * 8;
  if (FSL && kind < 2) {
#pragma unroll
    for (int m = 0; m < 5; m++) asm volatile("st.global.v2.b32 [%0],{%1,%1};" ::"l"(dst + m * DMS), "r"(SENT) : "memory");
    fence_gpu();
  }
#pragma unroll 1
  for (int s = 0; s < NSEG; s++) {
    float* xr = g_x + (size_t)(s * 32 + r) * DM;
    float4 v[5];
    if (kind < 2) {
#pragma unroll
      for (int u = 0; u < 5; u++) {
        const int p = u * 32 + lane;
        stg128((p < 80 ? g_ob[s + l * LAG] + (l * 32 + r) * 1280 : g_y[l] + (size_t)s * 40960 + (r - 1) * 1280) + p * 16, make_uint4(SENT, SENT, SENT, SENT));
      }
      if (FSL && s + 1 < NSEG) {
#pragma unroll
        for (int m = 0; m < 5; m++) asm volatile("st.global.v2.b32 [%0],{%1,%1};" ::"l"(dst + 81920 + m * DMS), "r"(SENT) : "memory");
      }
      if (lane == 0) cwait(CN_P + s + l * LAG, W::NP, spin);
      __syncwarp();
      if (r == 0 && lane == 0 && (l == 0 || s + LAG >= NSEG)) WTS1(s + l * LAG, 3);
#pragma unroll
      for (int m = 0; m < 5; m++) v[m] = ld_relaxed4f(xr + m * 128 + lane * 4);
    } else {
      if (lane == 0) cwait(CN_L + s + l * LAG, s + l * LAG < LAG || s + l * LAG >= NSEG ? 32 : 64, spin);
      __syncwarp();
#pragma unroll
      for (int m = 0; m < 5; m++) v[m] = ld_relaxed4f(xr + m * 128 + lane * 4);
      if (lane == 0) cwait(CN_W + l * 64 + s, 10, spin);
      __syncwarp();
      if (r == 0 && lane == 0 && (l == 0 || s + LAG >= NSEG)) WTS1(s + l * LAG, 11);
      const uint8_t* yp = g_y[l] + (size_t)s * 40960 + (lane >> 4) * 4096 + r * 128 + sw;
      float2 y[5];
      bool bad;
      do {
        bad = false;
#pragma unroll
        for (int m = 0; m < 5; m++) y[m] = ld_relaxed2f(yp + m * 8192);
#pragma unroll
        for (int m = 0; m < 5; m++) bad |= __float_as_uint(y[m].x) == SENT || __float_as_uint(y[m].y) == SENT;
        spin += 16;
      } while (__any_sync(0xffffffffu, bad && spin < SPIN_TOT));
#pragma unroll
      for (int m = 0; m < 5; m++) {
        v[m].x += bf_lo(__float_as_uint(y[m].x)); v[m].y += bf_hi(__float_as_uint(y[m].x));
        v[m].z += bf_lo(__float_as_uint(y[m].y)); v[m].w += bf_hi(__float_as_uint(y[m].y));
        if (kind == 2) *reinterpret_cast<float4*>(xr + m * 128 + lane * 4) = v[m];
      }
    }
    if (FSL == 3 && kind < 2 && lane == 0) csignal_fast(CN_G + s + l * LAG);
    if (kind < 3) ln_row(v);
#pragma unroll
    for (int m = 0; m < 5; m++)
      asm volatile("st.global.v2.b32 [%0],{%1,%2};" ::"l"(dst + m * DMS), "r"(pack_bf16(v[m].x, v[m].y)), "r"(pack_bf16(v[m].z, v[m].w)) : "memory");
    dst += DMS == 256 ? 40960 : 81920;
    __syncwarp();
    if (r == 0 && lane == 0 && (l == 0 || s + LAG >= NSEG)) WTS1(s + l * LAG, kind < 2 ? 4 : 12);
    if (lane == 0 && kind < (NOWORK ? 2 : 3)) {
      if (FSL && kind < 2) csignal_fast(CN_G + s + l * LAG);
      csignal_t(kind < 2 ? CN_L + s + l * LAG : CN_X + s + LAG, kind);
    }
  }
  if (spin >= SPIN_TOT) g_err = 13;
}

__device__ __forceinline__ void work_prep(const bf16* x0, const bf16* mem0, int r, int lane) {
  int spin = 0;
#pragma unroll 1
  for (int k = NPRE; k < NSTEP; k++) {
    if (lane < 20) prefetch_l2(x0 + (size_t)min(k * 32 + r + (lane < 10 ? 0 : 16), SEQ - 1) * DM + (lane % 10) * 64);
    if (lane == 0) cwait(CN_O + (k - NPRE) * 5, 1, spin);
    __syncwarp();
#pragma unroll 1
    for (int h = 0; h < 2; h++) {
      uint2 u[5];
      ln0_load(x0, u, min(k * 32 + r + 16 * h, SEQ - 1), lane);
      prep_row(u, mem0, k, r + 16 * h, lane);
    }
    __syncwarp();
    if (lane == 0) csignal(CN_X + k);
  }
  if (spin >= SPIN_TOT) g_err = 19;
}

__device__ __forceinline__ void stage_qkv(const bf16* wqkv, uint32_t base, int T, int bc, int tid) {
  const int q = tid & 15;
  const bool ok = q < 15 && bc * 60 + 4 * q < DM;
  const bf16* src = wqkv + T * DM + bc * 60 + 4 * q;
#pragma unroll 1
  for (int k0 = tid >> 4; k0 < 640; k0 += 80) {
    uint2 v[10];
#pragma unroll
    for (int u = 0; u < 10; u++) v[u] = ok ? *reinterpret_cast<const uint2*>(src + (size_t)(k0 + 8 * u) * 1920) : make_uint2(0, 0);
#pragma unroll
    for (int u = 0; u < 10; u++) sts64(base + (k0 + 8 * u) * 128 + (((q >> 1) ^ (k0 & 7)) << 4) + (q & 1) * 8, v[u].x, v[u].y);
  }
}
struct AttAddr { uint32_t qa, qb, ka, oa, ob, ml; };
__device__ __forceinline__ AttAddr att_addr(uint32_t sb, int bc, int hh, int tid) {
  using namespace W;
  const int r = tid & 7, m = (tid >> 3) & 3, g = (tid >> 2) & 7, t = tid & 3, lp = (tid >> 5) & 3;
  const int f2 = r < 4 ? 20 * hh + 16 + r : 60;
  const uint32_t tb = sb + OFF_T + 2 * lp * COL;
  const int fa = 20 * hh + (m >> 1) * 8 + r, pc = 2 * (lp & 1) + (m & 1);
  const uint32_t o0 = sb + OFF_S + (lp >> 1) * 3840;
  AttAddr x;
  x.qa = keep(tb + (m & 1) * COL + (20 * hh + (m >> 1) * 8 + r) * 16);
  x.qb = keep(tb + (m & 1) * COL + f2 * 16);
  x.ka = keep(tb + (m < 2 ? 20 * hh + 8 * m + r : f2) * 16);
  x.oa = keep(o0 + fa * 64 + ((pc ^ ((bc * 60 + fa) >> 1)) & 3) * 16);
  x.ob = keep(r < 4 ? o0 + f2 * 64 + ((pc ^ ((bc * 60 + f2) >> 1)) & 3) * 16 : sb + OFF_S + 7680);
  x.ml = keep((2 * t > g ? 0xFFFFu : 0u) | (2 * t + 1 > g ? 0xFFFF0000u : 0u));
  return x;
}
__device__ __forceinline__ void release_tiles(uint32_t sb, int tid) {
  fence_async();
  __syncwarp();
  if ((tid & 31) < 3) mbar_arrive(sb + W::BAR_E + 16 + 8 * (tid & 3));
}
__device__ __forceinline__ void attend(uint32_t sb, const AttAddr& x, int k0, int lp, int tid) {
  using namespace W;
  const uint32_t hd = OFF_H - OFF_T - lp * COL;
  const float scl = 0.22360679774997896f * 1.4426950408889634f;
  float sc[3][4];
  uint32_t v[3][4];
  {
    uint32_t q[4], q8a, q8b, k[3][4];
    ldsm4t(q, x.qa);
    ldsm4t(k[0], x.ka + hd); ldsm4t(k[1], x.ka + 8 * COL); ldsm4t(k[2], x.ka + 9 * COL);
    ldsm2t(q8a, q8b, x.qb);
#pragma unroll
    for (int c = 0; c < 3; c++) { sc[c][0] = sc[c][1] = sc[c][2] = sc[c][3] = 0.f; mma16816(sc[c], q[0], q[1], q[2], q[3], k[c][0], k[c][1]); }
#pragma unroll
    for (int c = 0; c < 3; c++) mma1688(sc[c], q8a, q8b, k[c][2]);
    stsm4t(x.ka + hd, k[2][0], k[2][1], k[2][2], k[2][3]);
  }
  ldsm4(v[0], x.ka + hd + 4 * COL); ldsm4(v[1], x.ka + 16 * COL); ldsm4(v[2], x.ka + 17 * COL);
  stsm4(x.ka + hd + 4 * COL, v[2][0], v[2][1], v[2][2], v[2][3]);
  release_tiles(sb, tid);
  const bool lo0 = x.ml & 1, lo1 = (int)x.ml < 0, first = k0 == (lp >> 1) * LAG;
  uint32_t pw[2];
  float inv[2];
#pragma unroll
  for (int h = 0; h < 2; h++) {
    float y0 = lo0 ? sc[h][2 * h] : sc[h + 1][2 * h], y1 = lo1 ? sc[h][2 * h + 1] : sc[h + 1][2 * h + 1];
    if (h == 0 && first) { y0 = lo0 ? -INFINITY : y0; y1 = lo1 ? -INFINITY : y1; }
    const float mx = quad_max(fmaxf(y0, y1)) * -scl;
    y0 = ex2(fmaf(y0, scl, mx)); y1 = ex2(fmaf(y1, scl, mx));
    pw[h] = pack_bf16(y0, y1);
    inv[h] = y0 + y1;
  }
  float o[3][4];
  const uint32_t a0 = pw[0] & x.ml, a2 = pw[0] & ~x.ml, a3 = pw[1] & x.ml, a5 = pw[1] & ~x.ml, z0 = tid >> 10, z1 = tid >> 11;
#pragma unroll
  for (int j = 0; j < 3; j++) { o[j][0] = o[j][1] = o[j][2] = o[j][3] = 0.f; mma16816(o[j], a0, z0, a2, a3, v[0][j], v[1][j]); }
#pragma unroll
  for (int j = 0; j < 3; j++) mma1688(o[j], z1, a5, v[2][j]);
  inv[0] = rcp(quad_sum(inv[0])); inv[1] = rcp(quad_sum(inv[1]));
  stsm4t(x.oa, pack_bf16(o[0][0] * inv[0], o[0][1] * inv[0]), pack_bf16(o[0][2] * inv[1], o[0][3] * inv[1]),
         pack_bf16(o[1][0] * inv[0], o[1][1] * inv[0]), pack_bf16(o[1][2] * inv[1], o[1][3] * inv[1]));
  stsm2t(x.ob, pack_bf16(o[2][0] * inv[0], o[2][1] * inv[0]), pack_bf16(o[2][2] * inv[1], o[2][3] * inv[1]));
  fence_async();
}
template <bool IS_V>
__device__ __forceinline__ void work_b(const CUtensorMap& tmBo, const bf16* wqkv, uint32_t sb, int bc, const int wg, int tid0) {
  using namespace W;
  if (!IS_V) asm volatile("setmaxnreg.inc.sync.aligned.u32 208;");
  else asm volatile("setmaxnreg.dec.sync.aligned.u32 72;");
  constexpr int NR = IS_V ? 40 - VSS : BRS;
  const int WG = IS_V ? 2 : wg;
  const uint32_t yo = WG * (40 - BRS) * 2048;
  int spin = 0;
  uint32_t wf[NR][4];
  if (!IS_V) {
    const uint32_t wb = sb + (WG ? OFF_WO : OFF_WV);
    stage_qkv(wqkv, wb, WG, bc, tid0 & 127);
    WBAR_SYNC(NB_G0 + WG, 128);
    load_frags<NR>(wf, wb, tid0);
#pragma unroll
    for (int k = NR; k < 40; k++) sts128(sb + OFF_Y + yo + (k - NR) * 2048 + (tid0 & 127) * 16, lds128(wb + k * 2048 + (tid0 & 127) * 16));
    fence_async();
  }
  WBAR_SYNC(NB_B, 384);
  if (WG == 1 && bc < 10) {
    if ((tid0 & 127) == 0) {
      mbar_expect_tx(sb + BAR_W, 81920);
      for (int i = 0; i < 10; i++) tma2d(sb + OFF_WO + i * 8192, &tmBo, bc * 64, i * 64, sb + BAR_W);
    }
    __syncwarp();
    mwait(sb + BAR_W, 0, spin);
  }
  if (IS_V) {
    stage_qkv(wqkv, sb + OFF_WV, 2, bc, tid0 & 127);
    WBAR_SYNC(NB_G0 + 2, 128);
    load_frags<NR>(wf, sb + OFF_WV + VSS * 2048, tid0);
  }
  fence_async();
  WBAR_SYNC(NB_B, 384);
  const int wu = uni((tid0 >> 5) & 3);
  uint32_t nredo = 0;
  const AttAddr aa = att_addr(sb, bc, WG, tid0);
#pragma unroll 1
  for (int k = 0; k < NSTEP + (WG == 0); k++) {
    if (WG || k < NSTEP) {
    {
      float d[32];
#define QKV_STEP(Q, DB)                                                                                                                  \
  {                                                                                                                                      \
    const int q = (Q);                                                                                                                   \
    if (IS_V ? q >= VSS : q < NR) wgmma_rs64(d, wf[IS_V ? (q >= VSS ? q - VSS : 0) : (q < NR ? q : 0)], DB, q);                          \
    else if (IS_V) wgmma_ts64(d, mkdesc(SB0 + OFF_WV + q * 2048, 8192, 1024), DB, q);                                                    \
    else wgmma_ts64(d, desc_at(mkdesc(SB0 + OFF_Y + (q - NR) * 2048, 8192, 1024), yo), DB, 1);                                           \
  }
#pragma unroll
      for (int c = 0; c < 10; c++) {
        mwait(sb + BAR_F + 8 * (c % 5), c / 5, spin);
        if (c == 0 && bc == 0 && WG != 1) WTS(k, WG ? 15 : 6);
        wg_fence();
#pragma unroll
        for (int kk = 0; kk < 4; kk++) {
          QKV_STEP(4 * c + kk, rdesc(OFF_X + (c % 5) * 8192, kk));
        }
        wg_commit();
        if (c > 0 && c <= 7) {
          wg_wait<1>();
          if ((tid0 & 31) == 0) mbar_arrive(sb + BAR_E + 8 * ((c - 1) % 5));
        }
      }
      wg_wait<0>();
      if (bc == 0 && WG != 1) WTS(k, 16 + WG / 2);
      uint32_t pk[16];
#pragma unroll
      for (int q = 0; q < 16; q++) pk[q] = pin(pack_bf16(d[2 * q], d[2 * q + 1]));
      const int tid = fresh(tid0), m = (tid >> 3) & 3;
      const uint32_t a = pin(sb + OFF_T + min(wu * 16 + (m & 1) * 8 + (tid & 7), 60) * 16 + (8 * WG + (m >> 1)) * COL);
      if (!FSL) WBAR_SYNC(NB_B, 384);
      else {
        const float c0 = ((d[0] + d[1]) + (d[4] + d[5])) + ((d[8] + d[9]) + (d[12] + d[13]));
        const float c1 = ((d[16] + d[17]) + (d[20] + d[21])) + ((d[24] + d[25]) + (d[28] + d[29]));
        if (__builtin_expect(bar_red_or(NB_RED3, 384, IS_V && ((c0 != c0 && k < NSEG) || (c1 != c1 && k >= LAG))), 0)) {
          if (IS_V && wu == 0) { cwait(CN_L + k, k < LAG || k >= NSEG ? 32 : 64, spin); fence_async_all(); }
#pragma unroll
          for (int c = 0; c < 10; c++) {
            if (IS_V && wu == 0 && elect_one()) { mbar_expect_tx(sb + BAR_R + 8, 8192); bulk_g2s(sb + OFF_X + 32768, g_xnb[k] + c * 8192, 8192, sb + BAR_R + 8); }
            __syncwarp();
            mwait(sb + BAR_R + 8, c & 1, spin);
            wg_fence();
#pragma unroll
            for (int kk = 0; kk < 4; kk++) QKV_STEP(4 * c + kk, rdesc(OFF_X + 32768, kk));
            wg_commit();
            wg_wait<0>();
            bar_sync(NB_RED3, 384);
          }
#pragma unroll
          for (int q = 0; q < 16; q++) pk[q] = pin(pack_bf16(d[2 * q], d[2 * q + 1]));
        }
      }
#undef QKV_STEP
#pragma unroll
      for (int p = 0; p < 4; p++) stsm4(a + 2 * p * COL, pk[4 * p], pk[4 * p + 1], pk[4 * p + 2], pk[4 * p + 3]);
    }
    WBAR_SYNC(NB_TD, 448);
    if (bc == 0 && WG == 0) WTS(k, 7);
    if (bc * 3 + WG < NH && (wu < 2 ? k < NSEG : k >= LAG)) attend(sb, aa, k, wu, fresh(tid0));
    else release_tiles(sb, tid0);
    if (bc == 0 && WG == 0) WTS(k, 8);
    WBAR_SYNC(NB_AS, 416);
    }
    const int s = k - (1 - WG) * (LAG + 1);
    if (!IS_V && bc < 10 && s >= 0 && s < NSEG) {
      float d[16];
#pragma unroll
      for (int f = 0; f < 5; f++) {
        mwait(sb + BAR_G + 40 * WG + 8 * f, s & 1, spin);
        if (f == 0 && bc == 0) WTS(k - 1 + WG, WG || k > NSEG ? 20 : 23);
        wg_fence();
#pragma unroll
        for (int kk = 0; kk < 8; kk++) {
          wgmma_tt32(d, mkdesc(SB0 + OFF_WO + (8 * f + kk) * 2048, 8192, 1024), gdesc(OFF_X + f * 8192, kk), f | kk);
          if (kk == 1 && f > 0) {
            wg_commit();
            wg_wait<1>();
            if ((tid0 & 31) < 3) mbar_arrive(sb + BAR_E + 8 * (f - 1));
          }
        }
        wg_commit();
      }
      wg_wait<0>();
      if (WG == 1 && FSA) {
        const float chk = ((d[0] + d[1]) + (d[4] + d[5])) + ((d[8] + d[9]) + (d[12] + d[13]));
        if (__builtin_expect(bar_red_or(NB_RED, 128, chk != chk), 0)) {
          if (wu == 0) { cwait(CN_A + k, NBC, spin); fence_async_all(); }
#pragma unroll
          for (int q = 0; q < 16; q++) d[q] = 0.f;
#pragma unroll 1
          for (int f = 0; f < 5; f++) {
            if (wu == 0 && elect_one()) { mbar_expect_tx(sb + BAR_W + 8, 8192); bulk_g2s(sb + OFF_X + 32768, g_ob[k] + f * 8192, 8192, sb + BAR_W + 8); }
            __syncwarp();
            mwait(sb + BAR_W + 8, nredo & 1, spin);
            nredo++;
            wg_fence();
#pragma unroll
            for (int kk = 0; kk < 8; kk++)
              wgmma_tt32(d, desc_at(mkdesc(SB0 + OFF_WO + kk * 2048, 8192, 1024), f * 16384), gdesc(OFF_X + 32768, kk), 1);
            wg_commit();
            wg_wait<0>();
            bar_sync(NB_RED, 128);
          }
        }
      }
      else if (WG) bar_sync(NB_RED, 128);
      else {
        if ((tid0 & 31) < 3) mbar_arrive(sb + BAR_E + 32);
        WBAR_SYNC(NB_SF, 160);
      }
      if (bc == 0) WTS(k - 1 + WG, WG || k > NSEG ? 10 : 24);
      const int tid = fresh(tid0), m = (tid >> 3) & 3, row = (m >> 1) * 16 + 2 * (tid & 7);
      const uint32_t a = sb + (WG ? OFF_X + 32768 : OFF_S) + row * 128 + (((2 * wu + (m & 1)) ^ row) & 7) * 16;
#pragma unroll
      for (int p = 0; p < 2; p++)
        stsm4t(a ^ (p * 144), pack_bf16(d[8 * p], d[8 * p + 1]), pack_bf16(d[8 * p + 2], d[8 * p + 3]), pack_bf16(d[8 * p + 4], d[8 * p + 5]), pack_bf16(d[8 * p + 6], d[8 * p + 7]));
      fence_async();
      WBAR_SYNC(WG ? NB_SG : NB_SG1, 160);
    }
  }
  if (spin >= SPIN_TOT) g_err = 14;
}
__device__ __forceinline__ bool b_job(int k, int u, int bc) { return u < 2 ? k < NSTEP : bc < 10 && (u == 2 ? k > LAG : k < NSEG); }
__device__ __forceinline__ void work_b_watch(uint32_t sb, int bc) {
  using namespace W;
  int spin = 0;
#pragma unroll 1
  for (int j = 0; j < 4 * NSTEP + 3; j++) {
    const int k = j >> 2, u = j & 3;
    if (u == 1 || !b_job(k, u, bc)) continue;
    cwait(u == 0 ? (FSL ? CN_G : CN_L) + k : u == 2 ? CN_A + k - 1 : (FSA ? CN_F : CN_A) + k, u ? NBC : k < LAG || k >= NSEG ? 32 : 64, spin);
    fence_async_all();
    if (bc == 0 && (u != 2 || k > NSEG)) WTS1(k + (u ? u - 3 : 0), u ? 9 : 5);
    if (elect_one()) mbar_arrive(sb + BAR_R + 8 * u);
    __syncwarp();
    if (u == 0) WBAR_SYNC(NB_R, 64);
  }
  if (spin >= SPIN_TOT) g_err = 16;
}
__device__ __forceinline__ void work_b_producer(uint32_t sb, int bc) {
  using namespace W;
  int spin = 0;
  uint32_t pe = 1;
#pragma unroll 1
  for (int j = 0; j < 4 * NSTEP + 3; j++) {
    const int k = j >> 2, u = j & 3;
    if (!b_job(k, u, bc)) continue;
    const uint32_t half = u < 2 && (k < LAG || k >= NSEG), lo = half && k >= NSEG ? 4096 : 0, len = half ? 4096 : 8192, fb = sb + (u < 2 ? BAR_F : BAR_G + 40 * (u - 2));
    const uint8_t* src = (u < 2 ? g_xnb[k] + u * 40960 : u == 2 ? g_ob[k - 1] + 40960 : g_ob[k]) + lo;
    if (u != 1) mwait(sb + BAR_R + 8 * u, (u == 2 ? k - LAG - 1 : k) & 1, spin);
#pragma unroll
    for (int f = 0; f < 5; f++) {
      mwait(sb + BAR_E + 8 * f, pe, spin);
      if (elect_one()) {
        mbar_expect_tx(fb + 8 * f, len);
        bulk_g2s(sb + OFF_X + f * 8192 + lo, src + f * 8192, len, fb + 8 * f);
      }
    }
    if (u == 0) WBAR_SYNC(NB_R, 64);
    pe ^= 1;
  }
  if (spin >= SPIN_TOT) g_err = 15;
}

__global__ void __launch_bounds__(512, 1)
k_work(const __grid_constant__ CUtensorMap tmWo, const __grid_constant__ CUtensorMap tmBo, const bf16* __restrict__ wqkv, bf16* __restrict__ out,
       const bf16* __restrict__ x0, const bf16* __restrict__ mem0) {
  using namespace W;
  extern __shared__ __align__(1024) uint8_t smem[];
  const uint32_t sb = smem_u32(smem);
  const int tid = threadIdx.x, w = blockIdx.x;
  const int wg = __shfl_sync(0xffffffffu, tid >> 7, 0);
  if (tid == 0) {
    if (sb != SB0) g_err = 101;
    for (int i = 0; i < 5; i++) { mbar_init(sb + BAR_F + 8 * i, 1); mbar_init(sb + BAR_E + 8 * i, w < NP ? 8 : 12); }
    for (int i = 0; i < 16; i++) mbar_init(sb + BAR_G + 8 * i, 1);
    for (int p = 0; p < 16; p++) sts32(sb + OFF_SAFE + 4 * p, 0);
    asm volatile("fence.mbarrier_init.release.cluster;" ::: "memory");
    int spin = 0;
    pre_wait(1, NW, spin);
    for (const uint32_t t0 = clk32(); clk32() - t0 < (w < NP ? WDP : WDB);) {}
    if (spin >= SPIN_TOT) g_err = 18;
  }
  if (tid < 8 * COL / 16) sts128(sb + OFF_H + tid * 16, make_uint4(0, 0, 0, 0));
  fence_async();
  __syncthreads();

  if (w < NP) {
    if (wg < 2) work_p(tmWo, sb, w, wg, keep(tid));
    else {
      asm volatile("setmaxnreg.dec.sync.aligned.u32 48;");
      const int aw = uni(tid >> 5) - 8;
      if (aw == 0) work_p_producer(sb, w);
      else if (aw == 1) {
#pragma unroll 1
        for (int k = 0; k < NSTEP; k++) {
          WBAR_SYNC(NB_SG, 288);
          if (elect_one()) csignal_t(CN_P + k, 3);
          __syncwarp();
        }
      } else {
        const int id = (aw - 2) * NP + w;
        if (id < 96) work_ln<16384>(id % 3, id / 3, tid & 31, out);
        else if (id < 128) work_ln<256>(3, id - 96, tid & 31, out);
        else if (id < 144 && NOWORK != 2) work_prep(x0, mem0, id - 128, tid & 31);
      }
    }
  } else {
    const int bc = w - NP;
    if (wg < 2) work_b<false>(tmBo, wqkv, sb, bc, wg, keep(tid));
    else if (wg == 2) work_b<true>(tmBo, wqkv, sb, bc, wg, keep(tid));
    else {
      asm volatile("setmaxnreg.dec.sync.aligned.u32 24;");
      const int aw = uni(tid >> 5) - 12;
      if (aw == 0) work_b_producer(sb, bc);
      else if (aw == 1) work_b_watch(sb, bc);
      else if (aw == 2) {
#pragma unroll 1
        for (int k = 0; k < NSTEP; k++) {
          WBAR_ARRIVE(NB_TD, 448);
          if (FSA == 3 && (tid & 31) == 0) csignal_fast(CN_F + k);
          WBAR_SYNC(NB_AS, 416);
          if (elect_one()) {
            const uint32_t len = bc < 10 ? 3840 : 2560;
            if (k < NSEG) {
              bulk_s2g(g_ob[k] + bc * 3840, sb + OFF_S, len);
              asm volatile("cp.async.bulk.commit_group;" ::: "memory");
              if (FSA == 1) asm volatile("cp.async.bulk.wait_group.read 0;" ::: "memory");
              if (FSA) csignal_fast(CN_F + k);
            }
            if (k >= LAG) bulk_s2g(g_ob[k] + 40960 + bc * 3840, sb + OFF_S + 3840, len);
            asm volatile("cp.async.bulk.commit_group;" ::: "memory");
            asm volatile("cp.async.bulk.wait_group 0;" ::: "memory");
          }
          __syncwarp();
          if (b_job(k, 2, bc)) WBAR_ARRIVE(NB_SF, 160);
          if (elect_one()) { fence_async_all(); csignal_t(CN_A + k, 5); }
          __syncwarp();
        }
        if (bc < 10) WBAR_SYNC(NB_SF + 1, 64), WBAR_ARRIVE(NB_SF, 160);
      } else {
#pragma unroll 1
        for (int j = 0; j < 2 * NSTEP + 1; j++) {
          const int l = (j & 1) ^ 1, s = (j >> 1) - l * (LAG + 1);
          if (l) { if (j < 2 * NSTEP) WBAR_SYNC(NB_TD, 448); else if (bc < 10) WBAR_ARRIVE(NB_SF + 1, 64); }
          if (s < 0 || s >= NSEG || bc == 10) continue;
          WBAR_SYNC(l ? NB_SG1 : NB_SG, 160);
          if (elect_one()) {
            bulk_s2g(g_y[l] + (size_t)s * 40960 + bc * 4096, sb + (l ? OFF_S : OFF_X + 32768), 4096);
            asm volatile("cp.async.bulk.commit_group;" ::: "memory");
            if (FSW) csignal_fast(CN_W + l * 64 + s);
            asm volatile("cp.async.bulk.wait_group.read 0;" ::: "memory");
            if (!FSW) csignal_fast(CN_W + l * 64 + s);
            if (!l) asm volatile("mbarrier.arrive.shared::cta.b64 _,[%0],12;" ::"r"(sb + BAR_E + 32) : "memory");
          }
          __syncwarp();
        }
      }
    }
  }
  __syncthreads();
  asm volatile("griddepcontrol.wait;" ::: "memory");
}

typedef CUresult (*EncodeFn)(CUtensorMap*, CUtensorMapDataType, cuuint32_t, void*, const cuuint64_t*, const cuuint64_t*,
                             const cuuint32_t*, const cuuint32_t*, CUtensorMapInterleave, CUtensorMapSwizzle,
                             CUtensorMapL2promotion, CUtensorMapFloatOOBfill);

static void make_map(EncodeFn enc, CUtensorMap* tm, const void* ptr, uint64_t cols, uint64_t rows, uint32_t boxc, uint32_t boxr) {
  cuuint64_t dims[2] = {cols, rows};
  cuuint64_t strides[1] = {cols * 2};
  cuuint32_t box[2] = {boxc, boxr};
  cuuint32_t es[2] = {1, 1};
  enc(tm, CU_TENSOR_MAP_DATA_TYPE_BFLOAT16, 2, const_cast<void*>(ptr), dims, strides, box, es, CU_TENSOR_MAP_INTERLEAVE_NONE,
      CU_TENSOR_MAP_SWIZZLE_128B, CU_TENSOR_MAP_L2_PROMOTION_L2_256B, CU_TENSOR_MAP_FLOAT_OOB_FILL_NONE);
}

extern "C" void kernel_launch(void* const* d_in, const int* in_sizes, int n_in, void* d_out, int out_size) {
  const bf16* x0 = (const bf16*)d_in[0];
  const bf16* mem0 = (const bf16*)d_in[1];
  const bf16* Wq = (const bf16*)d_in[2];
  const bf16* Wk = (const bf16*)d_in[3];
  const bf16* Wv = (const bf16*)d_in[4];
  const bf16* Wo = (const bf16*)d_in[5];
  const bf16* Bqkv = (const bf16*)d_in[8];
  const bf16* Bwo = (const bf16*)d_in[9];
  bf16* out = (bf16*)d_out;

  static EncodeFn enc = nullptr;
  if (!enc) {
    void* fn = nullptr;
    cudaDriverEntryPointQueryResult qr;
    cudaGetDriverEntryPoint("cuTensorMapEncodeTiled", &fn, cudaEnableDefault, &qr);
    enc = (EncodeFn)fn;
    cudaFuncSetAttribute(k_chain, cudaFuncAttributeMaxDynamicSharedMemorySize, C::SMEM);
    cudaFuncSetAttribute(k_work, cudaFuncAttributeMaxDynamicSharedMemorySize, W::SMEM);
  }
  CUtensorMap tmWq, tmWk, tmWv, tmWo, tmWp, tmBo;
  make_map(enc, &tmWq, Wq, NH * DH, DM, 64, 128);
  make_map(enc, &tmWk, Wk, NH * DH, DM, 64, 128);
  make_map(enc, &tmWv, Wv, NH * DH, DM, 64, 128);
  make_map(enc, &tmWo, Wo, DM, NH * DH, 64, 64);
  make_map(enc, &tmWp, Wo, DM, NH * DH, 64, 16);
  make_map(enc, &tmBo, Bwo, DM, DM, 64, 64);

  cudaStream_t st = cudaStreamPerThread;
  cudaLaunchAttribute at[1];
  at[0].id = cudaLaunchAttributeProgrammaticStreamSerialization; at[0].val.programmaticStreamSerializationAllowed = 1;
  {
    cudaLaunchConfig_t cfg = {};
    cfg.gridDim = dim3(96); cfg.blockDim = dim3(384); cfg.dynamicSmemBytes = C::SMEM; cfg.stream = st;
    cfg.attrs = at; cfg.numAttrs = 0;
    cudaLaunchKernelEx(&cfg, k_chain, tmWq, tmWk, tmWv, tmWo, x0, mem0);
  }
  cudaLaunchConfig_t cfg = {};
  cfg.gridDim = dim3(W::NW); cfg.blockDim = dim3(512); cfg.dynamicSmemBytes = W::SMEM; cfg.stream = st;
  cfg.attrs = at; cfg.numAttrs = NOWORK == 2 ? 0 : 1;
  cudaLaunchKernelEx(&cfg, k_work, tmWp, tmBo, Bqkv, out, x0, mem0);
}
```

```cpp
#include <cuda_runtime.h>
#include <cuda_bf16.h>
#include <cuda.h>
#include <stdint.h>

typedef __nv_bfloat16 bf16;

constexpr int SEQ = 2048, DM = 640, NH = 32, DH = 192, NSEG = 64;
#define LAG 5
constexpr int NSTEP = NSEG + LAG;
constexpr int NPRE = 4;
constexpr uint32_t SENT = 0xFFFFFFFFu;

constexpr int MAIL9 = 288 * 2048, MAIL_BYTES = MAIL9 + 64 * 3072;
__device__ __align__(1024) uint8_t g_xn[NSTEP][81920];
__device__ __align__(1024) uint8_t g_xnb[NSTEP][81920];
__device__ __align__(1024) uint8_t g_ob[NSTEP][81920];
__device__ __align__(1024) uint8_t g_y[2][NSEG * 40960];
#define ORING 8
static_assert(ORING > LAG, "a slot is free again LAG + 1 steps later");
__device__ __align__(1024) uint8_t g_o[ORING][96][8192];
__device__ __align__(1024) float g_x[SEQ * DM];
constexpr int EX_MAIL = 0;
constexpr int EX_M = 2 << 20;
constexpr int EX_FLAG = EX_M + NSTEP * 20480;
static_assert(EX_FLAG + NSTEP * 3072 <= (4 << 20), "");
__device__ __align__(1024) uint8_t g_ex[8 << 20];
__host__ __device__ __forceinline__ uint8_t* ex_window(uint8_t* p) { return reinterpret_cast<uint8_t*>((reinterpret_cast<uint64_t>(p) + (4 << 20) - 1) & ~(uint64_t)((4 << 20) - 1)); }
enum { CN_P = 0, CN_L = 128, CN_A = 256, CN_W = 384, CN_X = 512, CN_F = 640, CN_G = 768, CN_O = 896, CN_NUM = CN_O + 5 * NSTEP };
__device__ __align__(128) uint32_t g_cnt[CN_NUM][32];
__device__ __align__(128) uint32_t g_ticket[2][32];
__device__ int g_err;
#define TS(jj, i)
#define TS1(jj, i)
#define PTS(i)
#define TSB(jj, i)
#define TSV(jj, i, v)
#define TS_FLUSH(jj)
#define WTS(b, k)
#define WTS1(b, k)
#define WW -1

__device__ __forceinline__ uint32_t smem_u32(const void* p) { return (uint32_t)__cvta_generic_to_shared(p); }
__device__ __forceinline__ uint32_t clk32() { uint32_t t; asm volatile("mov.u32 %0, %%clock;" : "=r"(t)::"memory"); return t; }
__device__ __forceinline__ uint32_t mapa(uint32_t a, uint32_t r) { uint32_t o; asm("mapa.shared::cluster.u32 %0,%1,%2;" : "=r"(o) : "r"(a), "r"(r)); return o; }
__device__ __forceinline__ void mbar_init(uint32_t bar, uint32_t cnt) { asm volatile("mbarrier.init.shared::cta.b64 [%0],%1;" ::"r"(bar), "r"(cnt) : "memory"); }
__device__ __forceinline__ void mbar_expect_tx(uint32_t bar, uint32_t bytes) { asm volatile("mbarrier.arrive.expect_tx.shared::cta.b64 _,[%0],%1;" ::"r"(bar), "r"(bytes) : "memory"); }
__device__ __forceinline__ void mbar_arrive(uint32_t bar) { asm volatile("mbarrier.arrive.shared::cta.b64 _,[%0];" ::"r"(bar) : "memory"); }
__device__ __forceinline__ void mbar_arrive_cluster(uint32_t bar) { asm volatile("mbarrier.arrive.shared::cluster.b64 _,[%0];" ::"r"(bar) : "memory"); }
__device__ __forceinline__ bool mbar_try(uint32_t bar, uint32_t ph) {
  uint32_t ok;
  asm volatile("{.reg .pred p; mbarrier.try_wait.parity.shared::cta.b64 p,[%1],%2; selp.u32 %0,1,0,p;}" : "=r"(ok) : "r"(bar), "r"(ph) : "memory");
  return ok;
}
__device__ __forceinline__ bool mbar_test(uint32_t bar, uint32_t ph) {
  uint32_t ok;
  asm volatile("{.reg .pred p; mbarrier.test_wait.parity.shared::cta.b64 p,[%1],%2; selp.u32 %0,1,0,p;}" : "=r"(ok) : "r"(bar), "r"(ph) : "memory");
  return ok;
}
__device__ __forceinline__ int fresh(int x) { asm volatile("" : "+r"(x)); return x; }
#define PHASE_IDS const int tid = fresh(tid0), lane = tid & 31, w = tid >> 5, g = lane >> 2, t = lane & 3; (void)w; (void)g; (void)t
__device__ __forceinline__ void bar_sync(int id, int n) { asm volatile("bar.sync %0,%1;" ::"r"(id), "r"(n) : "memory"); }
__device__ __forceinline__ void bar_arrive(int id, int n) { asm volatile("bar.arrive %0,%1;" ::"r"(id), "r"(n) : "memory"); }
__device__ __forceinline__ bool bar_red_or(int id, int n, bool v) {
  uint32_t r;
  asm volatile("{\n .reg .pred p, q;\n setp.ne.u32 q, %3, 0;\n barrier.cta.red.or.pred p, %1, %2, q;\n selp.u32 %0, 1, 0, p;\n}" : "=r"(r) : "r"(id), "r"(n), "r"((uint32_t)v) : "memory");
  return r != 0;
}
__device__ __forceinline__ void fence_async() { asm volatile("fence.proxy.async.shared::cta;" ::: "memory"); }
__device__ __forceinline__ void bulk_g2s(uint32_t dst, const void* src, uint32_t bytes, uint32_t bar) {
  asm volatile("cp.async.bulk.shared::cluster.global.mbarrier::complete_tx::bytes [%0],[%1],%2,[%3];" ::"r"(dst), "l"(src), "r"(bytes), "r"(bar) : "memory");
}
__device__ __forceinline__ void bulk_g2s_mc(uint32_t dst, const void* src, uint32_t bytes, uint32_t bar) {
  asm volatile("cp.async.bulk.shared::cluster.global.mbarrier::complete_tx::bytes.multicast::cluster [%0],[%1],%2,[%3],%4;"
               ::"r"(dst), "l"(src), "r"(bytes), "r"(bar), "h"((uint16_t)7) : "memory");
}
__device__ __forceinline__ void bulk_s2g(void* dst, uint32_t src, uint32_t bytes) {
  asm volatile("cp.async.bulk.global.shared::cta.bulk_group [%0],[%1],%2;" ::"l"(dst), "r"(src), "r"(bytes) : "memory");
}
__device__ __forceinline__ void bulk_s2c(uint32_t dst, uint32_t src, uint32_t bytes, uint32_t bar) {
  asm volatile("cp.async.bulk.shared::cluster.shared::cta.mbarrier::complete_tx::bytes [%0],[%1],%2,[%3];" ::"r"(dst), "r"(src), "r"(bytes), "r"(bar) : "memory");
}
__device__ __forceinline__ void tma2d(uint32_t dst, const CUtensorMap* tm, int c0, int c1, uint32_t bar) {
  asm volatile("cp.async.bulk.tensor.2d.shared::cluster.global.mbarrier::complete_tx::bytes [%0],[%1,{%3,%4}],[%2];"
               ::"r"(dst), "l"(tm), "r"(bar), "r"(c0), "r"(c1) : "memory");
}
__device__ __forceinline__ void tma2d_prefetch(const CUtensorMap* tm, int c0, int c1) {
  asm volatile("cp.async.bulk.prefetch.tensor.2d.L2.global.tile [%0,{%1,%2}];" ::"l"(tm), "r"(c0), "r"(c1) : "memory");
}
__device__ __forceinline__ uint32_t pack_bf16(float lo, float hi) {
  uint32_t r; asm("cvt.rn.bf16x2.f32 %0,%1,%2;" : "=r"(r) : "f"(hi), "f"(lo)); return r;
}
__device__ __forceinline__ float bf_lo(uint32_t x) { return __uint_as_float(x << 16); }
__device__ __forceinline__ float bf_hi(uint32_t x) { return __uint_as_float(x & 0xFFFF0000u); }
__device__ __forceinline__ float ex2(float x) { float y; asm("ex2.approx.ftz.f32 %0,%1;" : "=f"(y) : "f"(x)); return y; }
__device__ __forceinline__ void ldsm4(uint32_t (&r)[4], uint32_t a) {
  asm volatile("ldmatrix.sync.aligned.m8n8.x4.shared.b16 {%0,%1,%2,%3},[%4];" : "=r"(r[0]), "=r"(r[1]), "=r"(r[2]), "=r"(r[3]) : "r"(a) : "memory");
}
__device__ __forceinline__ void ldsm4t(uint32_t (&r)[4], uint32_t a) {
  asm volatile("ldmatrix.sync.aligned.m8n8.x4.trans.shared.b16 {%0,%1,%2,%3},[%4];" : "=r"(r[0]), "=r"(r[1]), "=r"(r[2]), "=r"(r[3]) : "r"(a) : "memory");
}
__device__ __forceinline__ void ldsm2(uint32_t& r0, uint32_t& r1, uint32_t a) {
  asm volatile("ldmatrix.sync.aligned.m8n8.x2.shared.b16 {%0,%1},[%2];" : "=r"(r0), "=r"(r1) : "r"(a) : "memory");
}
__device__ __forceinline__ void ldsm2t(uint32_t& r0, uint32_t& r1, uint32_t a) {
  asm volatile("ldmatrix.sync.aligned.m8n8.x2.trans.shared.b16 {%0,%1},[%2];" : "=r"(r0), "=r"(r1) : "r"(a) : "memory");
}
__device__ __forceinline__ void ldsm1(uint32_t& r0, uint32_t a) {
  asm volatile("ldmatrix.sync.aligned.m8n8.x1.shared.b16 {%0},[%1];" : "=r"(r0) : "r"(a) : "memory");
}
__device__ __forceinline__ void mma16816(float (&d)[4], uint32_t a0, uint32_t a1, uint32_t a2, uint32_t a3, uint32_t b0, uint32_t b1) {
  asm volatile("mma.sync.aligned.m16n8k16.row.col.f32.bf16.bf16.f32 {%0,%1,%2,%3},{%4,%5,%6,%7},{%8,%9},{%0,%1,%2,%3};"
               : "+f"(d[0]), "+f"(d[1]), "+f"(d[2]), "+f"(d[3]) : "r"(a0), "r"(a1), "r"(a2), "r"(a3), "r"(b0), "r"(b1));
}
__device__ __forceinline__ void mma1688(float (&d)[4], uint32_t a0, uint32_t a1, uint32_t b0) {
  asm volatile("mma.sync.aligned.m16n8k8.row.col.f32.bf16.bf16.f32 {%0,%1,%2,%3},{%4,%5},{%6},{%0,%1,%2,%3};"
               : "+f"(d[0]), "+f"(d[1]), "+f"(d[2]), "+f"(d[3]) : "r"(a0), "r"(a1), "r"(b0));
}
__device__ __forceinline__ void sts32(uint32_t a, uint32_t v) { asm volatile("st.shared.b32 [%0],%1;" ::"r"(a), "r"(v) : "memory"); }
__device__ __forceinline__ void sts64f(uint32_t a, float x, float y) { asm volatile("st.shared.v2.f32 [%0],{%1,%2};" ::"r"(a), "f"(x), "f"(y) : "memory"); }
__device__ __forceinline__ void sts128(uint32_t a, uint4 v) { asm volatile("st.shared.v4.b32 [%0],{%1,%2,%3,%4};" ::"r"(a), "r"(v.x), "r"(v.y), "r"(v.z), "r"(v.w) : "memory"); }
__device__ __forceinline__ float lds32f(uint32_t a) { float v; asm volatile("ld.shared.f32 %0,[%1];" : "=f"(v) : "r"(a) : "memory"); return v; }
__device__ __forceinline__ float2 lds64f(uint32_t a) { float2 v; asm volatile("ld.shared.v2.f32 {%0,%1},[%2];" : "=f"(v.x), "=f"(v.y) : "r"(a) : "memory"); return v; }
__device__ __forceinline__ uint4 lds128(uint32_t a) { uint4 v; asm volatile("ld.shared.v4.b32 {%0,%1,%2,%3},[%4];" : "=r"(v.x), "=r"(v.y), "=r"(v.z), "=r"(v.w) : "r"(a) : "memory"); return v; }
__device__ __forceinline__ float4 lds128f(uint32_t a) { float4 v; asm volatile("ld.shared.v4.f32 {%0,%1,%2,%3},[%4];" : "=f"(v.x), "=f"(v.y), "=f"(v.z), "=f"(v.w) : "r"(a) : "memory"); return v; }
__device__ __forceinline__ void st_async2(uint32_t a, float x, float y, uint32_t bar) {
  asm volatile("st.async.weak.shared::cluster.mbarrier::complete_tx::bytes.v2.f32 [%0],{%1,%2},[%3];" ::"r"(a), "f"(x), "f"(y), "r"(bar) : "memory");
}
__device__ __forceinline__ void st_async4(uint32_t a, const float (&v)[4], uint32_t bar) {
  asm volatile("st.async.weak.shared::cluster.mbarrier::complete_tx::bytes.v4.f32 [%0],{%1,%2,%3,%4},[%5];" ::"r"(a), "f"(v[0]), "f"(v[1]), "f"(v[2]), "f"(v[3]), "r"(bar) : "memory");
}
__device__ __forceinline__ void st_async4v(uint32_t a, float x, float y, float z, float w, uint32_t bar) {
  asm volatile("st.async.weak.shared::cluster.mbarrier::complete_tx::bytes.v4.f32 [%0],{%1,%2,%3,%4},[%5];" ::"r"(a), "f"(x), "f"(y), "f"(z), "f"(w), "r"(bar) : "memory");
}
__device__ __forceinline__ void st_async4u(uint32_t a, const uint4& v, uint32_t bar) {
  asm volatile("st.async.weak.shared::cluster.mbarrier::complete_tx::bytes.v4.b32 [%0],{%1,%2,%3,%4},[%5];" ::"r"(a), "r"(v.x), "r"(v.y), "r"(v.z), "r"(v.w), "r"(bar) : "memory");
}
__device__ __forceinline__ uint4 ld_relaxed4(const void* p) {
  uint4 v; asm volatile("ld.relaxed.gpu.global.v4.u32 {%0,%1,%2,%3},[%4];" : "=r"(v.x), "=r"(v.y), "=r"(v.z), "=r"(v.w) : "l"(p) : "memory"); return v;
}
__device__ __forceinline__ uint32_t ld_relaxed(const void* p) {
  uint32_t v; asm volatile("ld.relaxed.gpu.global.u32 %0,[%1];" : "=r"(v) : "l"(p) : "memory"); return v;
}
__device__ __forceinline__ void st_relaxed(void* p, uint32_t v) { asm volatile("st.relaxed.gpu.global.b32 [%0],%1;" ::"l"(p), "r"(v) : "memory"); }
__device__ __forceinline__ void st_relaxed4(void* p, uint32_t v) { asm volatile("st.relaxed.gpu.global.v4.b32 [%0],{%1,%1,%1,%1};" ::"l"(p), "r"(v) : "memory"); }

__device__ __forceinline__ uint32_t ld_acquire(const void* p) {
  uint32_t v; asm volatile("ld.acquire.gpu.global.u32 %0,[%1];" : "=r"(v) : "l"(p) : "memory"); return v;
}
__device__ __forceinline__ float4 ld_relaxed4f(const void* p) {
  float4 v; asm volatile("ld.relaxed.gpu.global.v4.f32 {%0,%1,%2,%3},[%4];" : "=f"(v.x), "=f"(v.y), "=f"(v.z), "=f"(v.w) : "l"(p) : "memory"); return v;
}
__device__ __forceinline__ float2 ld_relaxed2f(const void* p) {
  float2 v; asm volatile("ld.relaxed.gpu.global.v2.f32 {%0,%1},[%2];" : "=f"(v.x), "=f"(v.y) : "l"(p) : "memory"); return v;
}
__device__ __forceinline__ void prefetch_l2(const void* p) { asm volatile("prefetch.global.L2 [%0];" ::"l"(p)); }
__device__ __forceinline__ void fence_gpu() { asm volatile("fence.acq_rel.gpu;" ::: "memory"); }
__device__ __forceinline__ void fence_async_all() { asm volatile("fence.proxy.async.global;" ::: "memory"); }
constexpr int SPIN_TOT = 1 << 22;
__device__ __forceinline__ void csignal(int idx) { asm volatile("red.release.gpu.global.add.u32 [%0],1;" ::"l"(&g_cnt[idx][0]) : "memory"); }
__device__ __forceinline__ void csignal_fast(int idx) { asm volatile("red.relaxed.gpu.global.add.u32 [%0],1;" ::"l"(&g_cnt[idx][0]) : "memory"); }
#define RLX 1
#define csignal_t(idx, role) csignal(idx)
__device__ __forceinline__ void cwait(int idx, uint32_t target, int& spin) {
  while (ld_relaxed(&g_cnt[idx][0]) < target && spin < SPIN_TOT) spin += 16;
}

__device__ __forceinline__ uint64_t mkdesc(uint32_t addr, uint32_t lbo, uint32_t sbo) {
  return (uint64_t)((addr & 0x3FFFF) >> 4) | ((uint64_t)(lbo >> 4) << 16) | ((uint64_t)(sbo >> 4) << 32) | ((uint64_t)1 << 62);
}
__device__ __forceinline__ uint64_t mkdesc_ns(uint32_t addr, uint32_t lbo, uint32_t sbo) {
  return (uint64_t)((addr & 0x3FFFF) >> 4) | ((uint64_t)(lbo >> 4) << 16) | ((uint64_t)(sbo >> 4) << 32);
}
__device__ __forceinline__ void wg_fence() { asm volatile("wgmma.fence.sync.aligned;" ::: "memory"); }
__device__ __forceinline__ void wg_commit() { asm volatile("wgmma.commit_group.sync.aligned;" ::: "memory"); }
template <int N> __device__ __forceinline__ void wg_wait() { asm volatile("wgmma.wait_group.sync.aligned %0;" ::"n"(N) : "memory"); }

__device__ __forceinline__ void wgmma_rs16(float (&d)[8], const uint32_t (&a)[4], uint64_t db, int sc) {
  asm volatile("{.reg .pred p; setp.ne.b32 p,%13,0; wgmma.mma_async.sync.aligned.m64n16k16.f32.bf16.bf16 "
               "{%0,%1,%2,%3,%4,%5,%6,%7},{%8,%9,%10,%11},%12,p,1,1,0;}"
               : "+f"(d[0]), "+f"(d[1]), "+f"(d[2]), "+f"(d[3]), "+f"(d[4]), "+f"(d[5]), "+f"(d[6]), "+f"(d[7])
               : "r"(a[0]), "r"(a[1]), "r"(a[2]), "r"(a[3]), "l"(db), "r"(sc));
}
__device__ __forceinline__ void wgmma_rs64(float (&d)[32], const uint32_t (&a)[4], uint64_t db, int sc) {
  asm volatile("{.reg .pred p; setp.ne.b32 p,%37,0; wgmma.mma_async.sync.aligned.m64n64k16.f32.bf16.bf16 "
               "{%0,%1,%2,%3,%4,%5,%6,%7,%8,%9,%10,%11,%12,%13,%14,%15,%16,%17,%18,%19,%20,%21,%22,%23,%24,%25,%26,%27,%28,%29,%30,%31},{%32,%33,%34,%35},%36,p,1,1,0;}"
               : "+f"(d[0]), "+f"(d[1]), "+f"(d[2]), "+f"(d[3]), "+f"(d[4]), "+f"(d[5]), "+f"(d[6]), "+f"(d[7]), "+f"(d[8]), "+f"(d[9]), "+f"(d[10]), "+f"(d[11]), "+f"(d[12]), "+f"(d[13]), "+f"(d[14]), "+f"(d[15]), "+f"(d[16]), "+f"(d[17]), "+f"(d[18]), "+f"(d[19]), "+f"(d[20]), "+f"(d[21]), "+f"(d[22]), "+f"(d[23]), "+f"(d[24]), "+f"(d[25]), "+f"(d[26]), "+f"(d[27]), "+f"(d[28]), "+f"(d[29]), "+f"(d[30]), "+f"(d[31])
               : "r"(a[0]), "r"(a[1]), "r"(a[2]), "r"(a[3]), "l"(db), "r"(sc));
}
__device__ __forceinline__ void wgmma_rt16(float (&d)[8], const uint32_t (&a)[4], uint64_t db, int sc) {
  asm volatile("{.reg .pred p; setp.ne.b32 p,%13,0; wgmma.mma_async.sync.aligned.m64n16k16.f32.bf16.bf16 "
               "{%0,%1,%2,%3,%4,%5,%6,%7},{%8,%9,%10,%11},%12,p,1,1,1;}"
               : "+f"(d[0]), "+f"(d[1]), "+f"(d[2]), "+f"(d[3]), "+f"(d[4]), "+f"(d[5]), "+f"(d[6]), "+f"(d[7])
               : "r"(a[0]), "r"(a[1]), "r"(a[2]), "r"(a[3]), "l"(db), "r"(sc));
}
__device__ __forceinline__ void wgmma_rt80(float (&d)[40], const uint32_t (&a)[4], uint64_t db, int sc) {
  asm volatile("{.reg .pred p; setp.ne.b32 p,%45,0; wgmma.mma_async.sync.aligned.m64n80k16.f32.bf16.bf16 "
               "{%0,%1,%2,%3,%4,%5,%6,%7,%8,%9,%10,%11,%12,%13,%14,%15,%16,%17,%18,%19,%20,%21,%22,%23,%24,%25,%26,%27,%28,%29,%30,%31,%32,%33,%34,%35,%36,%37,%38,%39},{%40,%41,%42,%43},%44,p,1,1,1;}"
               : "+f"(d[0]), "+f"(d[1]), "+f"(d[2]), "+f"(d[3]), "+f"(d[4]), "+f"(d[5]), "+f"(d[6]), "+f"(d[7]), "+f"(d[8]), "+f"(d[9]), "+f"(d[10]), "+f"(d[11]), "+f"(d[12]), "+f"(d[13]), "+f"(d[14]), "+f"(d[15]), "+f"(d[16]), "+f"(d[17]), "+f"(d[18]), "+f"(d[19]), "+f"(d[20]), "+f"(d[21]), "+f"(d[22]), "+f"(d[23]), "+f"(d[24]), "+f"(d[25]), "+f"(d[26]), "+f"(d[27]), "+f"(d[28]), "+f"(d[29]), "+f"(d[30]), "+f"(d[31]), "+f"(d[32]), "+f"(d[33]), "+f"(d[34]), "+f"(d[35]), "+f"(d[36]), "+f"(d[37]), "+f"(d[38]), "+f"(d[39])
               : "r"(a[0]), "r"(a[1]), "r"(a[2]), "r"(a[3]), "l"(db), "r"(sc));
}
__device__ __forceinline__ void wgmma_rs32(float (&d)[16], const uint32_t (&a)[4], uint64_t db, int sc) {
  asm volatile("{.reg .pred p; setp.ne.b32 p,%21,0; wgmma.mma_async.sync.aligned.m64n32k16.f32.bf16.bf16 "
               "{%0,%1,%2,%3,%4,%5,%6,%7,%8,%9,%10,%11,%12,%13,%14,%15},{%16,%17,%18,%19},%20,p,1,1,0;}"
               : "+f"(d[0]), "+f"(d[1]), "+f"(d[2]), "+f"(d[3]), "+f"(d[4]), "+f"(d[5]), "+f"(d[6]), "+f"(d[7]), "+f"(d[8]), "+f"(d[9]), "+f"(d[10]), "+f"(d[11]), "+f"(d[12]), "+f"(d[13]), "+f"(d[14]), "+f"(d[15])
               : "r"(a[0]), "r"(a[1]), "r"(a[2]), "r"(a[3]), "l"(db), "r"(sc));
}
__device__ __forceinline__ void wgmma_ts32(float (&d)[16], uint64_t da, uint64_t db, int sc) {
  asm volatile("{.reg .pred p; setp.ne.b32 p,%18,0; wgmma.mma_async.sync.aligned.m64n32k16.f32.bf16.bf16 "
               "{%0,%1,%2,%3,%4,%5,%6,%7,%8,%9,%10,%11,%12,%13,%14,%15},%16,%17,p,1,1,1,0;}"
               : "+f"(d[0]), "+f"(d[1]), "+f"(d[2]), "+f"(d[3]), "+f"(d[4]), "+f"(d[5]), "+f"(d[6]), "+f"(d[7]), "+f"(d[8]), "+f"(d[9]), "+f"(d[10]), "+f"(d[11]), "+f"(d[12]), "+f"(d[13]), "+f"(d[14]), "+f"(d[15])
               : "l"(da), "l"(db), "r"(sc));
}
__device__ __forceinline__ void wgmma_rs8(float (&d)[4], const uint32_t (&a)[4], uint64_t db, int sc) {
  asm volatile("{.reg .pred p; setp.ne.b32 p,%9,0; wgmma.mma_async.sync.aligned.m64n8k16.f32.bf16.bf16 "
               "{%0,%1,%2,%3},{%4,%5,%6,%7},%8,p,1,1,0;}"
               : "+f"(d[0]), "+f"(d[1]), "+f"(d[2]), "+f"(d[3])
               : "r"(a[0]), "r"(a[1]), "r"(a[2]), "r"(a[3]), "l"(db), "r"(sc));
}
__device__ __forceinline__ void wgmma_tt32(float (&d)[16], uint64_t da, uint64_t db, int sc) {
  asm volatile("{.reg .pred p; setp.ne.b32 p,%18,0; wgmma.mma_async.sync.aligned.m64n32k16.f32.bf16.bf16 "
               "{%0,%1,%2,%3,%4,%5,%6,%7,%8,%9,%10,%11,%12,%13,%14,%15},%16,%17,p,1,1,1,1;}"
               : "+f"(d[0]), "+f"(d[1]), "+f"(d[2]), "+f"(d[3]), "+f"(d[4]), "+f"(d[5]), "+f"(d[6]), "+f"(d[7]), "+f"(d[8]), "+f"(d[9]), "+f"(d[10]), "+f"(d[11]), "+f"(d[12]), "+f"(d[13]), "+f"(d[14]), "+f"(d[15])
               : "l"(da), "l"(db), "r"(sc));
}
__device__ __forceinline__ void wgmma_ts16(float (&d)[8], uint64_t da, uint64_t db, int sc) {
  asm volatile("{.reg .pred p; setp.ne.b32 p,%10,0; wgmma.mma_async.sync.aligned.m64n16k16.f32.bf16.bf16 "
               "{%0,%1,%2,%3,%4,%5,%6,%7},%8,%9,p,1,1,1,0;}"
               : "+f"(d[0]), "+f"(d[1]), "+f"(d[2]), "+f"(d[3]), "+f"(d[4]), "+f"(d[5]), "+f"(d[6]), "+f"(d[7])
               : "l"(da), "l"(db), "r"(sc));
}
__device__ __forceinline__ void wgmma_ts64(float (&d)[32], uint64_t da, uint64_t db, int sc) {
  asm volatile("{.reg .pred p; setp.ne.b32 p,%34,0; wgmma.mma_async.sync.aligned.m64n64k16.f32.bf16.bf16 "
               "{%0,%1,%2,%3,%4,%5,%6,%7,%8,%9,%10,%11,%12,%13,%14,%15,%16,%17,%18,%19,%20,%21,%22,%23,%24,%25,%26,%27,%28,%29,%30,%31},%32,%33,p,1,1,1,0;}"
               : "+f"(d[0]), "+f"(d[1]), "+f"(d[2]), "+f"(d[3]), "+f"(d[4]), "+f"(d[5]), "+f"(d[6]), "+f"(d[7]), "+f"(d[8]), "+f"(d[9]), "+f"(d[10]), "+f"(d[11]), "+f"(d[12]), "+f"(d[13]), "+f"(d[14]), "+f"(d[15]), "+f"(d[16]), "+f"(d[17]), "+f"(d[18]), "+f"(d[19]), "+f"(d[20]), "+f"(d[21]), "+f"(d[22]), "+f"(d[23]), "+f"(d[24]), "+f"(d[25]), "+f"(d[26]), "+f"(d[27]), "+f"(d[28]), "+f"(d[29]), "+f"(d[30]), "+f"(d[31])
               : "l"(da), "l"(db), "r"(sc));
}
__device__ __forceinline__ void wgmma_tt16(float (&d)[8], uint64_t da, uint64_t db, int sc) {
  asm volatile("{.reg .pred p; setp.ne.b32 p,%10,0; wgmma.mma_async.sync.aligned.m64n16k16.f32.bf16.bf16 "
               "{%0,%1,%2,%3,%4,%5,%6,%7},%8,%9,p,1,1,1,1;}"
               : "+f"(d[0]), "+f"(d[1]), "+f"(d[2]), "+f"(d[3]), "+f"(d[4]), "+f"(d[5]), "+f"(d[6]), "+f"(d[7])
               : "l"(da), "l"(db), "r"(sc));
}
__device__ __forceinline__ void wgmma_tt40(float (&d)[20], uint64_t da, uint64_t db, int sc) {
  asm volatile("{.reg .pred p; setp.ne.b32 p,%22,0; wgmma.mma_async.sync.aligned.m64n40k16.f32.bf16.bf16 "
               "{%0,%1,%2,%3,%4,%5,%6,%7,%8,%9,%10,%11,%12,%13,%14,%15,%16,%17,%18,%19},%20,%21,p,1,1,1,1;}"
               : "+f"(d[0]), "+f"(d[1]), "+f"(d[2]), "+f"(d[3]), "+f"(d[4]), "+f"(d[5]), "+f"(d[6]), "+f"(d[7]), "+f"(d[8]), "+f"(d[9]), "+f"(d[10]), "+f"(d[11]), "+f"(d[12]), "+f"(d[13]), "+f"(d[14]), "+f"(d[15]), "+f"(d[16]), "+f"(d[17]), "+f"(d[18]), "+f"(d[19])
               : "l"(da), "l"(db), "r"(sc));
}
__device__ __forceinline__ void wgmma_ss8(float (&d)[4], uint64_t da, uint64_t db, int sc) {
  asm volatile("{.reg .pred p; setp.ne.b32 p,%6,0; wgmma.mma_async.sync.aligned.m64n8k16.f32.bf16.bf16 "
               "{%0,%1,%2,%3},%4,%5,p,1,1,0,0;}"
               : "+f"(d[0]), "+f"(d[1]), "+f"(d[2]), "+f"(d[3])
               : "l"(da), "l"(db), "r"(sc));
}
__device__ __forceinline__ void wgmma_ss32(float (&d)[16], uint64_t da, uint64_t db, int sc) {
  asm volatile("{.reg .pred p; setp.ne.b32 p,%18,0; wgmma.mma_async.sync.aligned.m64n32k16.f32.bf16.bf16 "
               "{%0,%1,%2,%3,%4,%5,%6,%7,%8,%9,%10,%11,%12,%13,%14,%15},%16,%17,p,1,1,0,0;}"
               : "+f"(d[0]), "+f"(d[1]), "+f"(d[2]), "+f"(d[3]), "+f"(d[4]), "+f"(d[5]), "+f"(d[6]), "+f"(d[7]), "+f"(d[8]), "+f"(d[9]), "+f"(d[10]), "+f"(d[11]), "+f"(d[12]), "+f"(d[13]), "+f"(d[14]), "+f"(d[15])
               : "l"(da), "l"(db), "r"(sc));
}
__device__ __forceinline__ void wgmma_st64(float (&d)[32], uint64_t da, uint64_t db, int sc) {
  asm volatile("{.reg .pred p; setp.ne.b32 p,%34,0; wgmma.mma_async.sync.aligned.m64n64k16.f32.bf16.bf16 "
               "{%0,%1,%2,%3,%4,%5,%6,%7,%8,%9,%10,%11,%12,%13,%14,%15,%16,%17,%18,%19,%20,%21,%22,%23,%24,%25,%26,%27,%28,%29,%30,%31},%32,%33,p,1,1,0,1;}"
               : "+f"(d[0]), "+f"(d[1]), "+f"(d[2]), "+f"(d[3]), "+f"(d[4]), "+f"(d[5]), "+f"(d[6]), "+f"(d[7]), "+f"(d[8]), "+f"(d[9]), "+f"(d[10]), "+f"(d[11]), "+f"(d[12]), "+f"(d[13]), "+f"(d[14]), "+f"(d[15]), "+f"(d[16]), "+f"(d[17]), "+f"(d[18]), "+f"(d[19]), "+f"(d[20]), "+f"(d[21]), "+f"(d[22]), "+f"(d[23]), "+f"(d[24]), "+f"(d[25]), "+f"(d[26]), "+f"(d[27]), "+f"(d[28]), "+f"(d[29]), "+f"(d[30]), "+f"(d[31])
               : "l"(da), "l"(db), "r"(sc));
}
__device__ __forceinline__ void wgmma_st128(float (&d)[64], uint64_t da, uint64_t db, int sc) {
  asm volatile("{.reg .pred p; setp.ne.b32 p,%66,0; wgmma.mma_async.sync.aligned.m64n128k16.f32.bf16.bf16 "
               "{%0,%1,%2,%3,%4,%5,%6,%7,%8,%9,%10,%11,%12,%13,%14,%15,%16,%17,%18,%19,%20,%21,%22,%23,%24,%25,%26,%27,%28,%29,%30,%31,%32,%33,%34,%35,%36,%37,%38,%39,%40,%41,%42,%43,%44,%45,%46,%47,%48,%49,%50,%51,%52,%53,%54,%55,%56,%57,%58,%59,%60,%61,%62,%63},%64,%65,p,1,1,0,1;}"
               : "+f"(d[0]), "+f"(d[1]), "+f"(d[2]), "+f"(d[3]), "+f"(d[4]), "+f"(d[5]), "+f"(d[6]), "+f"(d[7]), "+f"(d[8]), "+f"(d[9]), "+f"(d[10]), "+f"(d[11]), "+f"(d[12]), "+f"(d[13]), "+f"(d[14]), "+f"(d[15]), "+f"(d[16]), "+f"(d[17]), "+f"(d[18]), "+f"(d[19]), "+f"(d[20]), "+f"(d[21]), "+f"(d[22]), "+f"(d[23]), "+f"(d[24]), "+f"(d[25]), "+f"(d[26]), "+f"(d[27]), "+f"(d[28]), "+f"(d[29]), "+f"(d[30]), "+f"(d[31]), "+f"(d[32]), "+f"(d[33]), "+f"(d[34]), "+f"(d[35]), "+f"(d[36]), "+f"(d[37]), "+f"(d[38]), "+f"(d[39]), "+f"(d[40]), "+f"(d[41]), "+f"(d[42]), "+f"(d[43]), "+f"(d[44]), "+f"(d[45]), "+f"(d[46]), "+f"(d[47]), "+f"(d[48]), "+f"(d[49]), "+f"(d[50]), "+f"(d[51]), "+f"(d[52]), "+f"(d[53]), "+f"(d[54]), "+f"(d[55]), "+f"(d[56]), "+f"(d[57]), "+f"(d[58]), "+f"(d[59]), "+f"(d[60]), "+f"(d[61]), "+f"(d[62]), "+f"(d[63])
               : "l"(da), "l"(db), "r"(sc));
}

__device__ __forceinline__ void stsm4(uint32_t a, uint32_t r0, uint32_t r1, uint32_t r2, uint32_t r3) {
  asm volatile("stmatrix.sync.aligned.m8n8.x4.shared.b16 [%0],{%1,%2,%3,%4};" ::"r"(a), "r"(r0), "r"(r1), "r"(r2), "r"(r3) : "memory");
}
__device__ __forceinline__ void stsm4t(uint32_t a, uint32_t r0, uint32_t r1, uint32_t r2, uint32_t r3) {
  asm volatile("stmatrix.sync.aligned.m8n8.x4.trans.shared.b16 [%0],{%1,%2,%3,%4};" ::"r"(a), "r"(r0), "r"(r1), "r"(r2), "r"(r3) : "memory");
}
__device__ __forceinline__ void stsm2t(uint32_t a, uint32_t r0, uint32_t r1) {
  asm volatile("stmatrix.sync.aligned.m8n8.x2.trans.shared.b16 [%0],{%1,%2};" ::"r"(a), "r"(r0), "r"(r1) : "memory");
}
__device__ __forceinline__ void sts64(uint32_t a, uint32_t x, uint32_t y) { asm volatile("st.shared.v2.b32 [%0],{%1,%2};" ::"r"(a), "r"(x), "r"(y) : "memory"); }
__device__ __forceinline__ void st_async2u(uint32_t a, uint32_t x, uint32_t y, uint32_t bar) {
  asm volatile("st.async.weak.shared::cluster.mbarrier::complete_tx::bytes.v2.b32 [%0],{%1,%2},[%3];" ::"r"(a), "r"(x), "r"(y), "r"(bar) : "memory");
}
__device__ __forceinline__ void st_relaxed128(void* p, uint32_t x, uint32_t y, uint32_t z, uint32_t w) {
  asm volatile("{.reg .b128 v; mov.b128 v,{%1,%2,%3,%4}; st.relaxed.gpu.global.b128 [%0],v;}" ::"l"(p), "r"(x), "r"(y), "r"(z), "r"(w) : "memory");
}
__device__ __forceinline__ void st_relaxed64(void* p, uint32_t x, uint32_t y) {
  asm volatile("{.reg .b64 v; mov.b64 v,{%1,%2}; st.relaxed.gpu.global.b64 [%0],v;}" ::"l"(p), "r"(x), "r"(y) : "memory");
}
__device__ __forceinline__ uint4 ld_relaxed128(const void* p) {
  uint4 v;
  asm volatile("{.reg .b128 v; .reg .b64 lo, hi; ld.relaxed.gpu.global.b128 v,[%4]; mov.b128 {lo,hi},v; mov.b64 {%0,%1},lo; mov.b64 {%2,%3},hi;}" : "=r"(v.x), "=r"(v.y), "=r"(v.z), "=r"(v.w) : "l"(p) : "memory");
  return v;
}

__device__ __forceinline__ uint32_t pack_h2(float lo, float hi) {
  uint32_t r; asm("cvt.rn.satfinite.f16x2.f32 %0,%1,%2;" : "=r"(r) : "f"(hi), "f"(lo)); return r;
}
__device__ __forceinline__ void add_h2(float& lo, float& hi, uint32_t u, uint32_t v) {
  float a, b;
  asm("{.reg .b16 l, h; .reg .b32 s; add.rn.f16x2 s,%2,%3; mov.b32 {l,h},s; cvt.f32.f16 %0,l; cvt.f32.f16 %1,h;}" : "=f"(a), "=f"(b) : "r"(u), "r"(v));
  lo += a; hi += b;
}
__device__ __forceinline__ void mwait(uint32_t bar, uint32_t ph, int& spin) {
  asm volatile("{.reg .pred p, q;\nWAIT_LOOP:\n add.s32 %0,%0,1;\n setp.lt.s32 q,%0,%3;\n mbarrier.try_wait.parity.shared::cta.b64 p,[%1],%2;\n not.pred p,p;\n and.pred q,q,p;\n @q bra.uni WAIT_LOOP;\n}"
               : "+&r"(spin) : "r"(bar), "r"(ph), "n"(SPIN_TOT) : "memory");
}
__device__ __forceinline__ int keep(int x) { return __shfl_sync(0xffffffffu, x, threadIdx.x & 31); }
__device__ __forceinline__ uint32_t pin(uint32_t x) { asm volatile("" : "+r"(x)); return x; }
template <typename T> __device__ __forceinline__ T* pinp(T* x) { asm volatile("" : "+l"(x)); return x; }
__device__ __forceinline__ void st_async1u(uint32_t a, uint32_t x, uint32_t bar) {
  asm volatile("st.async.weak.shared::cluster.mbarrier::complete_tx::bytes.b32 [%0],%1,[%2];" ::"r"(a), "r"(x), "r"(bar) : "memory");
}
__device__ __forceinline__ uint32_t lds32(uint32_t a) { uint32_t v; asm volatile("ld.shared.b32 %0,[%1];" : "=r"(v) : "r"(a) : "memory"); return v; }
__device__ __forceinline__ uint2 lds64(uint32_t a) { uint2 v; asm volatile("ld.shared.v2.b32 {%0,%1},[%2];" : "=r"(v.x), "=r"(v.y) : "r"(a) : "memory"); return v; }

__device__ __forceinline__ void permute_cols(uint32_t tile, int tid, int n) {
#pragma unroll 2
  for (int it = tid; it < n; it += 128) {
    const int row = it >> 2, q = it & 3;
    const uint32_t a0 = tile + row * 128 + (((2 * q) ^ (row & 7)) << 4), a1 = tile + row * 128 + (((2 * q + 1) ^ (row & 7)) << 4);
    const uint4 u = lds128(a0), v = lds128(a1);
    sts128(a0, make_uint4(__byte_perm(u.x, u.y, 0x5410), __byte_perm(u.z, u.w, 0x5410), __byte_perm(v.x, v.y, 0x5410), __byte_perm(v.z, v.w, 0x5410)));
    sts128(a1, make_uint4(__byte_perm(u.x, u.y, 0x7632), __byte_perm(u.z, u.w, 0x7632), __byte_perm(v.x, v.y, 0x7632), __byte_perm(v.z, v.w, 0x7632)));
  }
}

__device__ __forceinline__ uint8_t* mkptr(uint32_t lo, uint32_t hi) { uint8_t* p; asm("mov.b64 %0,{%1,%2};" : "=l"(p) : "r"(lo), "r"(hi)); return p; }
__device__ __forceinline__ int uni(int x) { return __shfl_sync(0xffffffffu, x, 0); }

__device__ __forceinline__ bool elect_one() {
  uint32_t p; asm volatile("{.reg .pred q; elect.sync _|q, 0xffffffff; selp.u32 %0,1,0,q;}" : "=r"(p)); return p;
}
__device__ __forceinline__ uint64_t desc_at(uint64_t d, uint32_t off) {
  uint64_t r; asm("mov.b64 %0,{%1,%2};" : "=l"(r) : "r"((uint32_t)d + (off >> 4)), "r"((uint32_t)(d >> 32))); return r;
}
__device__ __forceinline__ uint32_t scale_bf16x2(uint32_t x, uint32_t s) { uint32_t r; asm("mul.rn.bf16x2 %0,%1,%2;" : "=r"(r) : "r"(x), "r"(s)); return r; }

__device__ __forceinline__ void stg128(void* p, const uint4& v) { asm volatile("st.global.v4.b32 [%0],{%1,%2,%3,%4};" ::"l"(p), "r"(v.x), "r"(v.y), "r"(v.z), "r"(v.w) : "memory"); }

__device__ __forceinline__ void elect_g2s_mc(uint32_t dst, const void* src, uint32_t bytes, uint32_t bar) {
  asm volatile("{.reg .pred p; elect.sync _|p, 0xffffffff;\n"
               " @p cp.async.bulk.shared::cluster.global.mbarrier::complete_tx::bytes.multicast::cluster [%0],[%1],%2,[%3],%4;}"
               ::"r"(dst), "l"(src), "r"(bytes), "r"(bar), "h"((uint16_t)7) : "memory");
}
__device__ __forceinline__ void elect_s2c2(uint32_t dst0, uint32_t bar0, uint32_t dst1, uint32_t bar1, uint32_t src, uint32_t bytes) {
  asm volatile("{.reg .pred p; elect.sync _|p, 0xffffffff;\n"
               " @p cp.async.bulk.shared::cluster.shared::cta.mbarrier::complete_tx::bytes [%0],[%4],%5,[%1];\n"
               " @p cp.async.bulk.shared::cluster.shared::cta.mbarrier::complete_tx::bytes [%2],[%4],%5,[%3];}"
               ::"r"(dst0), "r"(bar0), "r"(dst1), "r"(bar1), "r"(src), "r"(bytes) : "memory");
}
__device__ __forceinline__ void fill_stage(uint32_t dst, const void* src, uint32_t bytes, uint32_t bar) {
  asm volatile("{.reg .pred p; elect.sync _|p, 0xffffffff;\n"
               " @p cp.async.bulk.shared::cluster.global.mbarrier::complete_tx::bytes [%0],[%1],%2,[%3];\n"
               " @p mbarrier.arrive.expect_tx.shared::cta.b64 _,[%3],%2;}" ::"r"(dst), "l"(src), "r"(bytes), "r"(bar) : "memory");
}
__device__ __forceinline__ void fill_stage2(uint32_t dst, const void* src0, const void* src1, uint32_t bar) {
  asm volatile("{.reg .pred p; elect.sync _|p, 0xffffffff;\n"
               " @p cp.async.bulk.shared::cluster.global.mbarrier::complete_tx::bytes [%0],[%1],4096,[%3];\n"
               " @p cp.async.bulk.shared::cluster.global.mbarrier::complete_tx::bytes [%0+4096],[%2],4096,[%3];\n"
               " @p mbarrier.arrive.expect_tx.shared::cta.b64 _,[%3],8192;}" ::"r"(dst), "l"(src0), "l"(src1), "r"(bar) : "memory");
}

__device__ __forceinline__ float quad_sum(float x) {
  const float a = __shfl_xor_sync(0xffffffffu, x, 1), b = __shfl_xor_sync(0xffffffffu, x, 2), c = __shfl_xor_sync(0xffffffffu, x, 3);
  return (x + a) + (b + c);
}
__device__ __forceinline__ float warp_sum(float x) {
  const uint32_t m = __reduce_max_sync(0xffffffffu, __float_as_uint(x) & 0x7FFFFFFFu), e = max(m >> 23, 25u);
  const int s = __reduce_add_sync(0xffffffffu, __float2int_rn(x * __uint_as_float((278 - e) << 23)));
  return fmaf(__uint_as_float(m), 0.f, (float)s * __uint_as_float((e - 24) << 23));
}
__device__ __forceinline__ void ln_row(float4 (&v)[5]) {
  float t0 = 0.f, t1 = 0.f;
#pragma unroll
  for (int m = 0; m < 5; m++) { t0 += v[m].x + v[m].y; t1 += v[m].z + v[m].w; }
  const float mean = warp_sum(t0 + t1) * (1.f / DM);
  float q0 = 0.f, q1 = 0.f, q2 = 0.f, q3 = 0.f;
#pragma unroll
  for (int m = 0; m < 5; m++) {
    v[m].x -= mean; v[m].y -= mean; v[m].z -= mean; v[m].w -= mean;
    q0 = fmaf(v[m].x, v[m].x, q0); q1 = fmaf(v[m].y, v[m].y, q1); q2 = fmaf(v[m].z, v[m].z, q2); q3 = fmaf(v[m].w, v[m].w, q3);
  }
  const float rs = rsqrtf(warp_sum((q0 + q1) + (q2 + q3)) * (1.f / DM) + 1e-5f);
#pragma unroll
  for (int m = 0; m < 5; m++) { v[m].x *= rs; v[m].y *= rs; v[m].z *= rs; v[m].w *= rs; }
}
__device__ __forceinline__ void ln0_load(const bf16* __restrict__ x, uint2 (&u)[5], int row, int lane) {
#pragma unroll
  for (int m = 0; m < 5; m++) u[m] = *reinterpret_cast<const uint2*>(x + (size_t)row * DM + m * 128 + lane * 4);
}
__device__ __forceinline__ void ln0_copy(const uint2 (&u)[5], int row, int lane) {
#pragma unroll
  for (int m = 0; m < 5; m++) stg128(g_x + (size_t)row * DM + m * 128 + lane * 4, make_uint4(u[m].x << 16, u[m].x & 0xFFFF0000u, u[m].y << 16, u[m].y & 0xFFFF0000u));
}
__device__ __forceinline__ void ln0_row(const uint2 (&u)[5], int row, int lane) {
  float4 v[5];
#pragma unroll
  for (int m = 0; m < 5; m++) v[m] = make_float4(bf_lo(u[m].x), bf_hi(u[m].x), bf_lo(u[m].y), bf_hi(u[m].y));
  ln_row(v);
  uint8_t* dst = g_xn[row >> 5] + ((row >> 3) & 3) * 4096 + (lane >> 4) * 1024 + (row & 7) * 128 + ((((lane >> 1) ^ row) & 7) << 4) + (lane & 1) * 8;
#pragma unroll
  for (int m = 0; m < 5; m++) *reinterpret_cast<uint2*>(dst + m * 16384) = make_uint2(pack_bf16(v[m].x, v[m].y), pack_bf16(v[m].z, v[m].w));
}

#define NOWORK 0
__device__ __forceinline__ void prep_row(const uint2 (&u)[5], const bf16* __restrict__ mem0, int k, int r, int lane) {
  const uint4 sent = make_uint4(SENT, SENT, SENT, SENT);
  if (k + 1 < NSTEP) {
    uint8_t* ex = ex_window(g_ex);
#pragma unroll
    for (int h = 0; h < 2; h++) {
      const int p = r * 40 + h * 32 + lane;
      if (h == 0 || lane < 8) {
        uint4 v = sent;
        if (k + 1 == LAG && (p & 8)) v = *reinterpret_cast<const uint4*>(mem0 + (p & 7) * DM + (p >> 4) * 8);
        stg128(ex + EX_M + (k + 1) * 20480 + p * 16, v);
      } else if (lane < 14) stg128(ex + EX_FLAG + (k + 1) * 3072 + (r * 6 + lane - 8) * 16, sent);
    }
  }
  if (k < LAG || k >= NSEG || NOWORK) {
    uint8_t* z = g_xn[k] + (r >> 3) * 4096 + (k < NSEG ? 2048 : 0) + (lane >> 4) * 1024 + (r & 7) * 128 + (lane & 15) * 8;
#pragma unroll
    for (int m = 0; m < 5; m++) *reinterpret_cast<uint2*>(z + m * 16384) = make_uint2(0, 0);
  }
  if (k < NSEG) {
    ln0_copy(u, k * 32 + r, lane);
    ln0_row(u, k * 32 + r, lane);
  }
}
__device__ __forceinline__ void pre_work(const bf16* __restrict__ x, const bf16* __restrict__ mem0, int cta, int tid) {
  constexpr int NT = 96 * 128;
  const int gt = cta * 128 + tid;
  uint8_t* ex = ex_window(g_ex);
#pragma unroll 1
  for (int row = cta + 96 * (tid >> 5); row < (NOWORK == 2 ? NSTEP : NPRE) * 32; row += 384) {
    uint2 u[5];
    ln0_load(x, u, min(row, SEQ - 1), tid & 31);
    prep_row(u, mem0, row >> 5, row & 31, tid & 31);
  }
#pragma unroll 1
  for (int i = gt; i < MAIL_BYTES / 16; i += NT) {
    stg128(ex + EX_MAIL + i * 16, make_uint4(SENT, SENT, SENT, SENT));
    stg128(ex + EX_MAIL + (1 << 20) + i * 16, make_uint4(SENT, SENT, SENT, SENT));
  }
  const int p = NT - 1 - gt;
  if (p < 1280) stg128(ex + EX_M + p * 16, *reinterpret_cast<const uint4*>(mem0 + (p & 7) * DM + (p >> 4) * 8));
  if (p < 192) stg128(ex + EX_FLAG + p * 16, make_uint4(0, 0, 0, 0));
  if (gt < 8 * CN_NUM) stg128(&g_cnt[0][0] + gt * 4, make_uint4(0, 0, 0, 0));
}
__device__ __forceinline__ void pre_wait(int which, uint32_t n, int& spin) {
  uint32_t old;
  asm volatile("atom.acq_rel.gpu.global.add.u32 %0,[%1],1;" : "=r"(old) : "l"(&g_ticket[which][0]) : "memory");
  const uint32_t target = (old / n + 1) * 96;
  while ((int)(ld_acquire(&g_ticket[0][0]) - target) < 0 && spin < SPIN_TOT) spin += 16;
  fence_async_all();
}

namespace C {
constexpr int NKR = 37;
constexpr int OFF_WQ = 0, OFF_WK = 81920;
constexpr int OFF_YO = 163840, OFF_YV = OFF_YO + 6144;
constexpr int OFF_M = 176128;
__host__ __device__ constexpr int og_off(int c) { return c ? OFF_M + 14336 + c * 2048 : 229376; }
constexpr int OFF_KT = 196608;
constexpr int OFF_XT = OFF_KT + 10240;
constexpr int OFF_VT = OFF_XT + 7168;
constexpr int OFF_XM = OFF_VT + 11392;
constexpr int OFF_PT = OFF_XM + 2560;
constexpr int KS = 1280, VS = 1408;
__host__ __device__ constexpr int slot_off(int p) { return p == 2 ? OFF_M : OFF_KT + (p % 3) * 16384; }
constexpr int OFF_ONE = 231424;
constexpr int OFF_BAR = 231552;
constexpr int OFF_SAFE = OFF_BAR + 144;
constexpr int OFF_TS = OFF_BAR + 256;
constexpr int SMEM = 232448;
constexpr uint32_t SB0 = 1024;
constexpr int BAR_F = OFF_BAR, BAR_XM = BAR_F + 40, BAR_XT = BAR_F + 48, BAR_OG = BAR_F + 56, BAR_E = OFF_BAR + 64, BAR_MOK = BAR_E + 40,
              BAR_M = OFF_BAR + 112, BAR_XF = OFF_BAR + 120, BAR_MF = OFF_BAR + 128, BAR_W = OFF_BAR + 208;
constexpr int NB_PRO = 1, NB_RD = 2, NB_MR = 3, NB_QK = 4, NB_SM = 5, NB_VA = 6, NB_VQ = 7, NB_A = 8, NB_Q = 9, NB_C = 10, NB_WQ = 11, NB_SI = 13, NB_WV = 14, NB_V = 15;
#define B1 600
#define AD0 16
#define AD1 128
#define AD2 16
#define AD3 128
#define BMX 1200
#define B2 800
#define FLP 1
#define OSG 2
#define OST 7
#define NBX 1
#define PVB 2
#define QPV 0
#define ONES 0
#define E0L 0
#define E2L 0
#define T2E 1
#define XMB 0
#define B3 0
#define OSV 0
#define XTD 0
#define VSL 2
#define VTI 4
#define T9L 0
#define P1U 4
#define SIE 2
#define WOE 1
#define OGF 2
#define VSP 8
#define RFK 5
#define PFD 3
#define WOL 0
constexpr uint32_t SCQ = 0x3A003A00;
constexpr float SCE = 0.07216878364870322f * 1.4426950408889634f * 2048;
}

#define CBAR_SYNC(id, n) bar_sync(id, n)
#define CBAR_ARRIVE(id, n) bar_arrive(id, n)

__device__ __forceinline__ uint64_t wdesc(int off) { return mkdesc(C::SB0 + off, 8192, 1024); }
__device__ __forceinline__ uint64_t mdesc(int k) { return mkdesc_ns(C::SB0 + C::OFF_M + k * 512, 256, 128); }
__device__ __forceinline__ uint64_t tdesc(int k) { return mkdesc(C::SB0 + C::slot_off(k >> 3) + ((k >> 2) & 1) * 1024 + (k & 3) * 32, 16, 2048); }

__device__ __forceinline__ int dh_row(int n) { return (n & ~63) + (n & 32) + ((n >> 1) & 3) * 8 + ((n >> 3) & 3) * 2 + (n & 1); }
template <bool IS_O>
__device__ __forceinline__ void stage_box(const CUtensorMap& tm, uint32_t sb, int p, int cta, int rank) {
  using namespace C;
  const uint32_t bar = sb + BAR_W + 8 * p;
  const int head = cta / 3, col = head * DH + rank * 64;
  mbar_expect_tx(bar, 16384);
  if (!IS_O) tma2d(sb + OFF_WK + p * 16384, &tm, col, p * 128, bar);
  else for (int b = 2 * p - 1; b <= 2 * p; b++)
    tma2d(sb + OFF_WQ + (b + 1) * 8192, &tm, b < 0 ? 576 : (3 * rank + b / 3) * 64, b < 0 ? col : head * DH + ((rank + b) % 3) * 64, bar);
}
template <bool IS_O>
__device__ __forceinline__ void load_weights_rs(uint32_t (&wf)[C::NKR][4], const CUtensorMap& tms, const CUtensorMap& tm, int cta, int rank, uint32_t sb, int tid0, int& spin) {
  using namespace C;
  constexpr int STAGE = IS_O ? OFF_WQ : OFF_WK, YOFF = IS_O ? OFF_YO : OFF_YV, NB = IS_O ? NB_C : NB_V;
  const int i = (tid0 >> 3) & 3, n0 = (tid0 & 7) + (i >> 1) * 8;
  const int chunk = 2 * ((tid0 >> 5) & 3) + (i & 1);
  const int r0 = IS_O ? dh_row(n0) : n0, r1 = IS_O ? dh_row(n0 + 16) : n0 + 16;
  const uint32_t a0 = sb + STAGE + r0 * 128 + ((chunk ^ (r0 & 7)) << 4), a1 = sb + STAGE + r1 * 128 + ((chunk ^ (r1 & 7)) << 4);
#pragma unroll
  for (int p = 0; p < 5; p++) {
    mwait(sb + BAR_W + 8 * p, 0, spin);
    if (IS_O) PTS(8 + p);
    if (p + NBX < 5) { if ((tid0 & 127) == 96) stage_box<IS_O>(tms, sb, p + NBX, cta, rank); __syncwarp(); }
    if (IS_O) permute_cols(sb + STAGE + p * 16384, tid0, 512);
    else {
#pragma unroll 1
      for (int it = tid0 & 127; it < 256; it += 128) {
        const uint32_t base = sb + STAGE + p * 16384 + (it >> 1) * 128;
        const int sw = ((it >> 1) & 7) ^ ((it & 1) * 4);
        const uint4 u0 = lds128(base + (sw << 4)), u1 = lds128(base + ((sw ^ 1) << 4)), u2 = lds128(base + ((sw ^ 2) << 4)), u3 = lds128(base + ((sw ^ 3) << 4));
        sts128(base + (sw << 4), make_uint4(u0.x, u1.x, u2.x, u3.x)); sts128(base + ((sw ^ 1) << 4), make_uint4(u0.y, u1.y, u2.y, u3.y));
        sts128(base + ((sw ^ 2) << 4), make_uint4(u0.z, u1.z, u2.z, u3.z)); sts128(base + ((sw ^ 3) << 4), make_uint4(u0.w, u1.w, u2.w, u3.w));
      }
    }
    bar_sync(NB, 128);
#pragma unroll
    for (int k = 8 * p; k < 8 * p + 8; k++) {
      if (k < NKR) ldsm4t(wf[k < NKR ? k : 0], ((k & 1) ? a1 : a0) + (k >> 1) * 4096);
      else {
        const int n = k * 16 + ((tid0 & 127) >> 3), r = IS_O ? dh_row(n) : n, c = tid0 & 7;
        sts128(sb + YOFF + (n - NKR * 16) * 128 + ((c ^ (n & 7)) << 4), lds128(sb + STAGE + r * 128 + ((c ^ (r & 7)) << 4)));
      }
    }
    fence_async();
    bar_sync(NB, 128);
    if ((tid0 & 127) == 0) {
      mbar_expect_tx(sb + BAR_W + 8 * p, 16384);
      tma2d(sb + STAGE + p * 16384, &tm, (cta / 3) * DH + rank * 64, p * 128, sb + BAR_W + 8 * p);
    }
    __syncwarp();
  }
  PTS(IS_O ? 13 : 14);
  CBAR_SYNC(NB_PRO, 384);
}

__device__ __forceinline__ void load_pair(uint32_t sb, int i, int p, uint32_t slot, uint32_t ph, int& spin) {
  using namespace C;
  mwait(sb + BAR_E + 8 * p, ph, spin);
  elect_g2s_mc(sb + slot, g_xn[i] + p * 16384, 16384, sb + BAR_F + 8 * p);
}
__device__ __forceinline__ void release_round(uint32_t sb, int p, int lane) {
  if (lane < (p == 2 ? 3 : 1)) mbar_arrive_cluster(mapa(sb, p == 2 ? lane : p) + C::BAR_E + 8 * (3 + p));
}

__device__ __forceinline__ void signal_o(int i, int cta) { csignal(CN_O + i * 5 + min(cta / 19, 4)); }

template <int K0, int K1>
__device__ __forceinline__ void v_mem_pass(float (&d)[8], const uint32_t (&wf)[C::NKR][4]) {
  using namespace C;
#pragma unroll
  for (int k = K0; k < K1; k++) {
    if (k < NKR) wgmma_rs16(d, wf[k < NKR ? k : 0], mdesc(k), k != 32);
    else wgmma_ts16(d, wdesc(OFF_YV + (k - NKR) * 2048), mdesc(k), 1);
  }
  wg_commit();
}
__device__ __forceinline__ void chain_v(const CUtensorMap& tmWv, const CUtensorMap& tmWk, const uint32_t sb, const int tid0, const int cta, const int rank) {
  using namespace C;
  asm volatile("setmaxnreg.inc.sync.aligned.u32 208;");
  int spin = 0;
  uint32_t wf[NKR][4];
  const int wu = uni((tid0 >> 5) & 3);
  const uint32_t slot = rank == 2 ? OFF_M : OFF_KT + rank * 16384;
  load_weights_rs<false>(wf, tmWv, tmWk, cta, rank, sb, tid0, spin);
  PTS(5);
#pragma unroll 1
  for (int i = 0; i < NSTEP; i++) {
    uint32_t vp[16], va;
#define STORE_V { _Pragma("unroll") for (int s = 0; s < 4; s++) stsm4(va + 128 + s * 128, vp[4 * s], vp[4 * s + 1], vp[4 * s + 2], vp[4 * s + 3]); }
    {
      float d[32];
      if (i > 0) CBAR_SYNC(NB_WV, 256);
#pragma unroll
      for (int p = 0; p < 5; p++) {
        if (OSV && p == 3) {
          wg_wait<0>();
          release_round(sb, 2, tid0 & 31);
          if (wu == 1 && i > 0) {
            CBAR_SYNC(NB_MR, 160);
            if (elect_one()) signal_o(i - 1, cta);
          }
        }
        mwait(sb + BAR_F + 8 * p, i & 1, spin);
        TS(i, 25 + p);
        wg_fence();
#pragma unroll
        for (int k = 8 * p; k < 8 * p + 8; k++) {
          if (k < NKR) wgmma_rs64(d, wf[k < NKR ? k : 0], tdesc(k), k);
          else wgmma_ts64(d, wdesc(OFF_YV + (k - NKR) * 2048), tdesc(k), 1);
          if (k == 8 * p + 1 && p >= 1 && p <= (OSV ? 2 : 3)) {
            wg_commit(); wg_wait<1>();
            release_round(sb, p - 1, tid0 & 31);
          }
          if (k == 8 * p + RFK && (p == 1 || p == 2)) {
            wg_commit();
            if (rank == p - 1 && wu == 0) load_pair(sb, i, p + 2, slot_off(p + 2), i & 1, spin);
            wg_fence();
          }
        }
        wg_commit();
      }
      wg_wait<0>();
      TS(i, 23);
#pragma unroll
      for (int q = 0; q < 16; q++) vp[q] = pin(pack_bf16(d[2 * q], d[2 * q + 1]));
      CBAR_SYNC(NB_RD, 256);
      const int tid = fresh(tid0) & 127, m = (tid >> 3) & 3;
      if (wu == 3) {
        const int lane = tid & 31;
        if (lane < 3 && lane != rank) mbar_arrive_cluster(mapa(sb, lane) + BAR_XF);
        if (lane < 8) mbar_expect_tx(sb + BAR_F + 8 * lane, lane < 5 ? 16384 : lane == 5 ? 2560 : lane == 6 ? 7168 : 4096);
        mwait(sb + BAR_XF, i & 1, spin);
      } else {
        if (tid < 80) sts128(sb + (tid < 72 ? OFF_VT + (tid >> 3) * VS : OFF_PT + 1280) + (tid & 7) * 16, make_uint4(0, 0, 0, 0));
        fence_async();
      }
      CBAR_ARRIVE(NB_QK, 384);
      TS(i, 16);
      va = sb + OFF_VT + 128 + ((tid >> 5) * 2 + (m & 1)) * VS + (m >> 1) * 640 + (tid & 7) * 16;
    }
    const uint32_t* xc = &g_cnt[CN_X + i + 1][0];
    const uint32_t xn = NOWORK == 2 || i + 1 < NPRE ? 0 : i + 1 < LAG || NOWORK ? 16 : 48;
    bool seen = false;
    if (wu == 0) seen = __any_sync(0xffffffffu, ld_relaxed(xc) >= xn);
    CBAR_SYNC(NB_V, 256);
    float d[8];
    wg_fence();
    v_mem_pass<32, 40>(d, wf);
    v_mem_pass<0, 6>(d, wf);
    wg_wait<1>();
    if ((tid0 & 31) < 3 && (tid0 & 31) != rank) mbar_arrive_cluster(mapa(sb, tid0 & 31) + BAR_MF);
    v_mem_pass<6, 32>(d, wf);
    if (VSL == 2) STORE_V
    CBAR_SYNC(NB_SM, 256);
    wg_wait<0>();
    TS(i, 24);
    const int tid = fresh(tid0);
    if (!E2L && (tid & 31) == 0) mbar_arrive_cluster(mapa(sb, 2) + BAR_E + 16);
    stsm4(va, pack_bf16(d[0], d[1]), pack_bf16(d[2], d[3]), pack_bf16(d[4], d[5]), pack_bf16(d[6], d[7]));
#undef STORE_V
    fence_async();
    CBAR_ARRIVE(NB_VA, 256);
    CBAR_ARRIVE(NB_VQ, QPV ? 384 : 256);
    if (wu == 0 && i + 1 < NSTEP) {
      if (!seen) while (ld_relaxed(xc) < xn && spin < SPIN_TOT) spin += 16;
      fence_async_all();
      load_pair(sb, i + 1, rank, slot, i & 1, spin);
      TS(i + 1, 37);
    }
    TS_FLUSH(i - 1);
    __syncwarp();
  }
  CBAR_ARRIVE(NB_WV, 256);
  if (spin >= SPIN_TOT) g_err = 3;
}

__device__ __forceinline__ float quad_max(float x) {
  const float a = __shfl_xor_sync(0xffffffffu, x, 1), b = __shfl_xor_sync(0xffffffffu, x, 2), c = __shfl_xor_sync(0xffffffffu, x, 3);
  return fmaxf(fmaxf(x, a), fmaxf(b, c));
}
__device__ __forceinline__ float max10(const float (&y)[10]) {
  return fmaxf(fmaxf(fmaxf(fmaxf(y[0], y[1]), fmaxf(y[2], y[3])), fmaxf(fmaxf(y[4], y[5]), fmaxf(y[6], y[7]))), fmaxf(y[8], y[9]));
}
__device__ __forceinline__ float sum10(const float (&y)[10]) {
  return (((y[0] + y[1]) + (y[2] + y[3])) + ((y[4] + y[5]) + (y[6] + y[7]))) + (y[8] + y[9]);
}
__device__ __forceinline__ float rcp(float x) { float y; asm("rcp.approx.ftz.f32 %0,%1;" : "=f"(y) : "f"(x)); return y; }

__device__ __forceinline__ void chain_q(const bf16* x0, const bf16* mem0, const uint32_t sb, const int tid0, const int cta, const int rank) {
  using namespace C;
  asm volatile("setmaxnreg.dec.sync.aligned.u32 96;");
  int spin = 0;
  PTS(0);
  pre_work(x0, mem0, cta, tid0 & 127);
  PTS(3);
  CBAR_SYNC(NB_Q, 128);
  PTS(2);
  if (tid0 < 160) {
    if (tid0 == 128) pre_wait(0, 96, spin);
    __syncwarp();
    load_pair(sb, 0, rank, rank == 2 ? OFF_M : OFF_KT + rank * 16384, 1, spin);
  }
  PTS(4);
  CBAR_SYNC(NB_PRO, 384);
  mwait(sb + BAR_W, 1, spin);
  PTS(6);
  const int wu = uni((tid0 >> 5) & 3);
  uint4 ov[4] = {};
  uint8_t* op = &g_o[ORING - 1][cta][(tid0 & 124) * 32];
  const uint32_t o0 = ((tid0 ^ (tid0 >> 2)) & 3) * 16 + (tid0 & 16) * 4;
#pragma unroll 1
  for (int i = 0; i < NSTEP; i++) {
    const int ph = i & 1;
    uint32_t qf[4][4];
    {
      float d[64];
#define QK_STEP(K, SC) wgmma_st128(d, desc_at(mkdesc(SB0 + ((K) >> 2) * 1024 + ((K) & 3) * 32, 16, 2048), so), \
                                   desc_at(mkdesc(SB0 + OFF_WQ + (K) * 2048, OFF_WK - OFF_WQ, 1024), p * 16384), SC)
      int p = 0;
      uint32_t so = OFF_KT;
      mwait(sb + BAR_F, ph, spin);
      TS(i, 0);
      wg_fence();
#pragma unroll
      for (int k = 0; k < 8; k++) {
        QK_STEP(k, k);
        if (k == OST) {
          wg_commit();
          mwait(sb + BAR_F, ph, spin);
#pragma unroll
          for (int h = 0; h < 4; h++) stg128(op + (h & 1) * 4096 + (o0 ^ ((h >> 1) * 64)), ov[h]);
          if (i > 0) CBAR_ARRIVE(NB_MR, 160);
          if (k < 7) wg_fence();
        }
      }
      if (OST < 7) wg_commit();
#pragma unroll 1
      for (p = 1; p < 5; p++) {
        static_assert(OFF_KT - OFF_M == 5 << 12, "");
        so = OFF_M + (((0x95095u >> (4 * p)) & 15) << 12);
        if (i == 0) { mwait(sb + BAR_W + 8 * p, 1, spin); PTS(14 + p); }
        mwait(sb + BAR_F + 8 * p, ph, spin);
        wg_fence();
#pragma unroll
        for (int k = 0; k < 8; k++) {
          QK_STEP(k, 1);
          if (k == 1) {
            wg_commit(); wg_wait<1>();
            release_round(sb, p - 1, p < 4 ? tid0 & 31 : 32);
          }
        }
        wg_commit();
      }
#undef QK_STEP
      wg_wait<0>();
      TS(i, 1);
      CBAR_SYNC(NB_RD, 256);
      TSB(i, 2);
      const int tid = fresh(tid0), w = (tid >> 5) & 3, m = (tid >> 3) & 3;
      const uint32_t a = sb + OFF_KT + (m >> 1) * KS + (1 + w + 5 * (m & 1)) * 128 + (tid & 7) * 16;
#pragma unroll
      for (int s = 0; s < 4; s++)
        stsm4t(a + s * 2 * KS, pack_bf16(d[32 + 8 * s], d[33 + 8 * s]), pack_bf16(d[34 + 8 * s], d[35 + 8 * s]),
               pack_bf16(d[36 + 8 * s], d[37 + 8 * s]), pack_bf16(d[38 + 8 * s], d[39 + 8 * s]));
      fence_async();
      CBAR_ARRIVE(NB_QK, 384);
      TS(i, 15);
#pragma unroll
      for (int kk = 0; kk < 4; kk++)
#pragma unroll
        for (int j = 0; j < 4; j++) asm volatile("{.reg .b32 t; cvt.rn.bf16x2.f32 t,%1,%2; mul.rn.bf16x2 %0,t,%3;}" : "=r"(qf[kk][j]) : "f"(d[8 * kk + 2 * j + 1]), "f"(d[8 * kk + 2 * j]), "r"(SCQ));
    }
    CBAR_SYNC(NB_SI, 256);
    uint32_t pf[5][4];
    float sa = 0.f, sb2 = 0.f;
    {
      float y0[10], y1[10];
      const int tidf = fresh(tid0), lane = tidf & 31;
      {
        float x[40];
        wg_fence();
#pragma unroll
        for (int kk = 0; kk < 4; kk++) {
          if (VTI && kk == 4 - VTI) CBAR_ARRIVE(NB_V, 256);
          wgmma_rt80(x, qf[kk], mkdesc_ns(SB0 + OFF_KT + kk * 2 * KS, KS, 128), kk);
        }
        wg_commit();
        wg_wait<0>();
#pragma unroll
        for (int j = 0; j < 5; j++) { y0[2 * j] = x[4 * j]; y0[2 * j + 1] = x[4 * j + 1]; y1[2 * j] = x[22 + 4 * j]; y1[2 * j + 1] = x[23 + 4 * j]; }
      }
      TS(i, 17);
      const uint32_t xo = OFF_XT + (wu * (wu + 3) / 2) * 256 + lane * 16, x2 = xo + (wu >> 1) * 512 + 512 - lane * 8;
      {
        const uint4 h0 = make_uint4(pack_h2(y0[0], y0[1]), pack_h2(y1[0], y1[1]), pack_h2(y0[2], y0[3]), pack_h2(y1[2], y1[3]));
        const uint4 h1 = make_uint4(pack_h2(y0[4], y0[5]), pack_h2(y1[4], y1[5]), pack_h2(y0[6], y0[7]), pack_h2(y1[6], y1[7]));
        const uint32_t h2 = wu == 1 ? h1.x : pack_h2(y0[8], y0[9]), h3 = wu == 1 ? h1.y : pack_h2(y1[8], y1[9]);
        const uint32_t rb1 = mapa(sb, (rank + 1) % 3), rb2 = mapa(sb, (rank + 2) % 3);
        if (XTD == 1) mwait(sb + BAR_XM, ph, spin);
        if (XTD > 1) for (const uint32_t t0 = clk32(); clk32() - t0 < XTD;) {}
        st_async4u(rb1 + xo + 3584, h0, rb1 + BAR_XT);
        st_async4u(rb2 + xo, h0, rb2 + BAR_XT);
        if (wu >= 2) { st_async4u(rb1 + xo + 4096, h1, rb1 + BAR_XT); st_async4u(rb2 + xo + 512, h1, rb2 + BAR_XT); }
        if (wu & 1) { st_async2u(rb1 + x2 + 3584, h2, h3, rb1 + BAR_XT); st_async2u(rb2 + x2, h2, h3, rb2 + BAR_XT); }
      }
      TS(i, 18);
      const int lim = 8 * wu + (lane >> 2) + 8 - 2 * (lane & 3);
#pragma unroll
      for (int j = 2; j < 10; j++)
        if (8 * (j >> 1) + (j & 1) > lim) { y0[j] = -INFINITY; y1[j] = -INFINITY; }
      mwait(sb + BAR_XT, ph, spin);
      TS(i, 19);
      {
        const uint4 u0 = lds128(sb + xo), v0 = lds128(sb + xo + 3584);
        uint2 u2 = make_uint2(0, 0), v2 = u2;
        if (wu & 1) { u2 = lds64(sb + x2); v2 = lds64(sb + x2 + 3584); }
        uint4 u1 = make_uint4(u2.x, u2.y, 0, 0), v1 = make_uint4(v2.x, v2.y, 0, 0);
        if (wu >= 2) { u1 = lds128(sb + xo + 512); v1 = lds128(sb + xo + 4096); }
        __syncwarp();
        if (lane == 0) mbar_arrive_cluster(mapa(sb, 0) + BAR_E);
        add_h2(y0[0], y0[1], u0.x, v0.x); add_h2(y1[0], y1[1], u0.y, v0.y); add_h2(y0[2], y0[3], u0.z, v0.z); add_h2(y1[2], y1[3], u0.w, v0.w);
        add_h2(y0[4], y0[5], u1.x, v1.x); add_h2(y1[4], y1[5], u1.y, v1.y); add_h2(y0[6], y0[7], u1.z, v1.z); add_h2(y1[6], y1[7], u1.w, v1.w);
        add_h2(y0[8], y0[9], u2.x, v2.x); add_h2(y1[8], y1[9], u2.y, v2.y);
      }
      const float m0 = quad_max(max10(y0)) * -SCE, m1 = quad_max(max10(y1)) * -SCE;
#pragma unroll
      for (int j = 0; j < 5; j++) {
        y0[2 * j] = ex2(fmaf(y0[2 * j], SCE, m0)); y0[2 * j + 1] = ex2(fmaf(y0[2 * j + 1], SCE, m0));
        y1[2 * j] = ex2(fmaf(y1[2 * j], SCE, m1)); y1[2 * j + 1] = ex2(fmaf(y1[2 * j + 1], SCE, m1));
        if (!ONES) { sa += y0[2 * j] + y0[2 * j + 1]; sb2 += y1[2 * j] + y1[2 * j + 1]; }
        pf[j >> 1][2 * (j & 1)] = pack_bf16(y0[2 * j], y0[2 * j + 1]);
        pf[j >> 1][2 * (j & 1) + 1] = tidf >> (10 + j);
        pf[(j + 5) >> 1][2 * ((j + 5) & 1)] = tidf >> (20 + j);
        pf[(j + 5) >> 1][2 * ((j + 5) & 1) + 1] = pack_bf16(y1[2 * j], y1[2 * j + 1]);
      }
    }
#pragma unroll
    for (int q = 0; q < 20; q++) pf[q >> 2][q & 3] = pin(pf[q >> 2][q & 3]);
    CBAR_SYNC(NB_VQ, QPV ? 384 : 256);
    TSB(i, 20);
    {
      float o[32], sm[4];
      wg_fence();
#pragma unroll
      for (int q = 0; q < 5; q++) if (ONES) wgmma_rs8(sm, pf[q], mkdesc_ns(SB0 + OFF_ONE, 0, 0), q);
#pragma unroll
      for (int q = 0; q < 5; q++) wgmma_rs64(o, pf[q], mkdesc_ns(SB0 + OFF_VT + 128 + q * 256, 128, VS), q);
      wg_commit();
      if (!ONES) { sm[0] = quad_sum(sa); sm[2] = quad_sum(sb2); }
      const int tid = fresh(tid0);
      op = &g_o[i % ORING][cta][(tid & 124) * 32];
      wg_wait<0>();
      TS(i, 21);
      if ((tid & 31) == 0) mbar_arrive_cluster(mapa(sb, 1) + BAR_E + 8);
      const float s0 = rcp(sm[0]), s1 = rcp(sm[2]);
#pragma unroll
      for (int h = 0; h < 2; h++) {
        const float* x = o + 16 * h;
        ov[2 * h] = make_uint4(pin(pack_bf16(x[0] * s0, x[1] * s0)), pin(pack_bf16(x[4] * s0, x[5] * s0)), pin(pack_bf16(x[8] * s0, x[9] * s0)), pin(pack_bf16(x[12] * s0, x[13] * s0)));
        ov[2 * h + 1] = make_uint4(pin(pack_bf16(x[2] * s1, x[3] * s1)), pin(pack_bf16(x[6] * s1, x[7] * s1)), pin(pack_bf16(x[10] * s1, x[11] * s1)), pin(pack_bf16(x[14] * s1, x[15] * s1)));
      }
      TS(i, 22);
      if (i + 1 < NSTEP) CBAR_SYNC(NB_WQ, 256); else CBAR_ARRIVE(NB_WQ, 256);
    }
  }
#pragma unroll
  for (int h = 0; h < 4; h++) stg128(op + (h & 1) * 4096 + (o0 ^ ((h >> 1) * 64)), ov[h]);
  CBAR_SYNC(NB_Q, 128);
  if (tid0 == 224) signal_o(NSTEP - 1, cta);
  if (spin >= SPIN_TOT) g_err = 2;
}

template <int NL> __device__ __forceinline__ void poll(uint4 (&x)[NL], const uint8_t* mb, uint32_t tag, int& spin);
template <> __device__ __forceinline__ void poll<4>(uint4 (&x)[4], const uint8_t* mb, uint32_t tag, int& spin) {
  asm volatile("{.reg .pred p<6>, q; .reg .b128 v; .reg .b32 t;\n"
               " ld.relaxed.gpu.global.b128 v,[%17+0]; mov.b128 {%0,%1,%2,%3},v;\n"
               " ld.relaxed.gpu.global.b128 v,[%17+512]; mov.b128 {%4,%5,%6,%7},v;\n"
               " ld.relaxed.gpu.global.b128 v,[%17+1024]; mov.b128 {%8,%9,%10,%11},v;\n"
               " ld.relaxed.gpu.global.b128 v,[%17+1536]; mov.b128 {%12,%13,%14,%15},v;\n"
               "POLL_LOOP:\n add.s32 %16,%16,16;\n"
               " lop3.b32 t,%0,%18,1,0x28; setp.ne.b32 p0,t,0;\n"
               " lop3.b32 t,%4,%18,1,0x28; setp.ne.b32 p1,t,0;\n"
               " lop3.b32 t,%8,%18,1,0x28; setp.ne.b32 p2,t,0;\n"
               " lop3.b32 t,%12,%18,1,0x28; setp.ne.b32 p3,t,0;\n"
               " or.pred q,p0,p1; or.pred q,q,p2; or.pred q,q,p3; setp.lt.and.s32 q,%16,%19,q; vote.sync.any.pred q,q,0xffffffff;\n"
               " mov.b128 v,{%0,%1,%2,%3}; @p0 ld.relaxed.gpu.global.b128 v,[%17+0]; mov.b128 {%0,%1,%2,%3},v;\n"
               " mov.b128 v,{%4,%5,%6,%7}; @p1 ld.relaxed.gpu.global.b128 v,[%17+512]; mov.b128 {%4,%5,%6,%7},v;\n"
               " mov.b128 v,{%8,%9,%10,%11}; @p2 ld.relaxed.gpu.global.b128 v,[%17+1024]; mov.b128 {%8,%9,%10,%11},v;\n"
               " mov.b128 v,{%12,%13,%14,%15}; @p3 ld.relaxed.gpu.global.b128 v,[%17+1536]; mov.b128 {%12,%13,%14,%15},v;\n"
               " @q bra.uni POLL_LOOP;\n}"
               : "=&r"(x[0].x), "=&r"(x[0].y), "=&r"(x[0].z), "=&r"(x[0].w), "=&r"(x[1].x), "=&r"(x[1].y), "=&r"(x[1].z), "=&r"(x[1].w), "=&r"(x[2].x), "=&r"(x[2].y), "=&r"(x[2].z), "=&r"(x[2].w), "=&r"(x[3].x), "=&r"(x[3].y), "=&r"(x[3].z), "=&r"(x[3].w), "+&r"(spin)
               : "l"(mb), "r"(tag), "n"(SPIN_TOT) : "memory");
}
template <> __device__ __forceinline__ void poll<6>(uint4 (&x)[6], const uint8_t* mb, uint32_t tag, int& spin) {
  asm volatile("{.reg .pred p<6>, q; .reg .b128 v; .reg .b32 t;\n"
               " ld.relaxed.gpu.global.b128 v,[%25+0]; mov.b128 {%0,%1,%2,%3},v;\n"
               " ld.relaxed.gpu.global.b128 v,[%25+512]; mov.b128 {%4,%5,%6,%7},v;\n"
               " ld.relaxed.gpu.global.b128 v,[%25+1024]; mov.b128 {%8,%9,%10,%11},v;\n"
               " ld.relaxed.gpu.global.b128 v,[%25+1536]; mov.b128 {%12,%13,%14,%15},v;\n"
               " ld.relaxed.gpu.global.b128 v,[%25+2048]; mov.b128 {%16,%17,%18,%19},v;\n"
               " ld.relaxed.gpu.global.b128 v,[%25+2560]; mov.b128 {%20,%21,%22,%23},v;\n"
               "POLL_LOOP:\n add.s32 %24,%24,16;\n"
               " lop3.b32 t,%0,%2,%26,0x7e; and.b32 t,t,1; setp.ne.b32 p0,t,0;\n"
               " lop3.b32 t,%4,%6,%26,0x7e; and.b32 t,t,1; setp.ne.b32 p1,t,0;\n"
               " lop3.b32 t,%8,%10,%26,0x7e; and.b32 t,t,1; setp.ne.b32 p2,t,0;\n"
               " lop3.b32 t,%12,%14,%26,0x7e; and.b32 t,t,1; setp.ne.b32 p3,t,0;\n"
               " lop3.b32 t,%16,%18,%26,0x7e; and.b32 t,t,1; setp.ne.b32 p4,t,0;\n"
               " lop3.b32 t,%20,%22,%26,0x7e; and.b32 t,t,1; setp.ne.b32 p5,t,0;\n"
               " or.pred q,p0,p1; or.pred q,q,p2; or.pred q,q,p3; or.pred q,q,p4; or.pred q,q,p5; setp.lt.and.s32 q,%24,%27,q; vote.sync.any.pred q,q,0xffffffff;\n"
               " mov.b128 v,{%0,%1,%2,%3}; @p0 ld.relaxed.gpu.global.b128 v,[%25+0]; mov.b128 {%0,%1,%2,%3},v;\n"
               " mov.b128 v,{%4,%5,%6,%7}; @p1 ld.relaxed.gpu.global.b128 v,[%25+512]; mov.b128 {%4,%5,%6,%7},v;\n"
               " mov.b128 v,{%8,%9,%10,%11}; @p2 ld.relaxed.gpu.global.b128 v,[%25+1024]; mov.b128 {%8,%9,%10,%11},v;\n"
               " mov.b128 v,{%12,%13,%14,%15}; @p3 ld.relaxed.gpu.global.b128 v,[%25+1536]; mov.b128 {%12,%13,%14,%15},v;\n"
               " mov.b128 v,{%16,%17,%18,%19}; @p4 ld.relaxed.gpu.global.b128 v,[%25+2048]; mov.b128 {%16,%17,%18,%19},v;\n"
               " mov.b128 v,{%20,%21,%22,%23}; @p5 ld.relaxed.gpu.global.b128 v,[%25+2560]; mov.b128 {%20,%21,%22,%23},v;\n"
               " @q bra.uni POLL_LOOP;\n}"
               : "=&r"(x[0].x), "=&r"(x[0].y), "=&r"(x[0].z), "=&r"(x[0].w), "=&r"(x[1].x), "=&r"(x[1].y), "=&r"(x[1].z), "=&r"(x[1].w), "=&r"(x[2].x), "=&r"(x[2].y), "=&r"(x[2].z), "=&r"(x[2].w), "=&r"(x[3].x), "=&r"(x[3].y), "=&r"(x[3].z), "=&r"(x[3].w), "=&r"(x[4].x), "=&r"(x[4].y), "=&r"(x[4].z), "=&r"(x[4].w), "=&r"(x[5].x), "=&r"(x[5].y), "=&r"(x[5].z), "=&r"(x[5].w), "+&r"(spin)
               : "l"(mb), "r"(tag), "n"(SPIN_TOT) : "memory");
}
template <int NL>
__device__ __forceinline__ void poll_add(const uint8_t* mb, uint32_t tag, float (&f)[8], uint8_t* flag, bool lead, int& spin) {
  uint4 x[NL];
  poll<NL>(x, mb, tag, spin);
  if (FLP == 0 && lead) st_relaxed(flag, 0);
#pragma unroll
  for (int i = 0; i < NL; i++) {
    const uint32_t u[4] = {x[i].x, x[i].y, x[i].z, x[i].w};
#pragma unroll
    for (int j = 0; j < 4; j++) {
      if (i == 0) { f[2 * j] = bf_lo(u[j]); f[2 * j + 1] = bf_hi(u[j]); }
      else { f[2 * j] += bf_lo(u[j]); f[2 * j + 1] += bf_hi(u[j]); }
    }
  }
}

template <int B, int SLOT>
__device__ __forceinline__ void wo_step(float (&acc)[8], const uint32_t (&wf)[C::NKR][4], int kk) {
  using namespace C;
  const int k = 4 * B + kk;
  const uint64_t db = mkdesc_ns(SB0 + og_off(SLOT) + kk * 512, 256, 128);
  if (k < NKR) wgmma_rt16(acc, wf[k < NKR ? k : 0], db, SLOT | kk);
  else wgmma_tt16(acc, wdesc(OFF_YO + (k - NKR) * 2048), db, 1);
}
template <int B, int SLOT>
__device__ __forceinline__ void wo_block(float (&acc)[8], const uint32_t (&wf)[C::NKR][4]) {
#pragma unroll
  for (int kk = 0; kk < 4; kk++) wo_step<B, SLOT>(acc, wf, kk);
}

__device__ __forceinline__ void chain_a(const CUtensorMap& tmWo, const CUtensorMap& tmWq, const uint32_t sb, const int tid0, const int cta, const int rank) {
  using namespace C;
  asm volatile("setmaxnreg.inc.sync.aligned.u32 200;");
  int spin = 0;
  uint32_t wf[NKR][4];
  load_weights_rs<true>(wf, tmWo, tmWq, cta, rank, sb, tid0, spin);
  const int wu = uni(tid0 >> 5);
  const bool t9 = cta >= 72 && cta < 88;
  const uint64_t exa = reinterpret_cast<uint64_t>(ex_window(g_ex));
  const uint32_t ehi = (uint32_t)(exa >> 32), elo = (uint32_t)exa;

  int b1 = B1, b2 = B2;
#pragma unroll 1
  for (int i = -1; i < NSTEP; i++) {
    const int ph = i & 1;
    if (i >= 0) {
      const int tid = fresh(tid0);
      const uint32_t mo = __shfl_xor_sync(0xffffffffu, elo + ((rank * 24 + (tid >> 4)) * 4 + (tid & 3)) * 2048 + (cta / 3) * 64 + (tid & 12) * 4, 0);
      const uint32_t m9 = __shfl_xor_sync(0xffffffffu, elo + MAIL9 + (((tid >> 4) * 2 + (tid & 1)) * 4 + (tid & 2)) * 3072 + cta * 32 + (tid & 12) * 2, 0);
      const uint32_t oo = __shfl_xor_sync(0xffffffffu, (tid >> 5) * 512 + (tid & 2) * 64 + (tid & 28) * 4 + (tid & 1) * 8, 0);
      if (i == 0) { mwait(sb + BAR_W + 24, 1, spin); mwait(sb + BAR_W + 32, 1, spin); PTS(7); }
      mwait(sb + BAR_M, ph, spin);
      TS(i, 3);
      {
        float x[20];
        int redo = 0;
      retry:
        bool bad;
        {
          float dq[8] = {}, dk[8] = {};
#pragma unroll 1
          for (int k0 = 0; k0 < 40; k0 += P1U) {
            wg_fence();
#pragma unroll
            for (int k = 0; k < P1U; k++) {
              const uint64_t db = desc_at(mdesc(k), k0 * 512);
              wgmma_ts16(dq, desc_at(wdesc(OFF_WQ + k * 2048), k0 * 2048), db, 1);
              wgmma_ts16(dk, desc_at(wdesc(OFF_WK + k * 2048), k0 * 2048), db, 1);
            }
            wg_commit();
          }
          const int m = (tid >> 3) & 3, dg = (tid >> 5) * 2 + (m & 1);
          const uint32_t ka = sb + OFF_KT + dg * KS + (m >> 1) * 640 + (tid & 7) * 16;
          if (!redo) CBAR_SYNC(NB_QK, 384);
          wg_wait<0>();
          TS(i, 4);
          stsm4(ka, pack_bf16(dk[0], dk[1]), pack_bf16(dk[2], dk[3]), pack_bf16(dk[4], dk[5]), pack_bf16(dk[6], dk[7]));
          stsm4(ka + dg * (VS - KS) + (OFF_VT + 128 - OFF_KT), scale_bf16x2(pack_bf16(dq[0], dq[1]), SCQ), scale_bf16x2(pack_bf16(dq[2], dq[3]), SCQ),
                scale_bf16x2(pack_bf16(dq[4], dq[5]), SCQ), scale_bf16x2(pack_bf16(dq[6], dq[7]), SCQ));
          const float chk = (dq[0] + dq[1]) + (dq[4] + dq[5]);
          fence_async();
          bad = bar_red_or(NB_C, 128, chk != chk && !redo);
        }
        TSB(i, 5);
        wg_fence();
#pragma unroll
        for (int kk = 0; kk < 4; kk++) wgmma_tt40(x, mkdesc_ns(SB0 + OFF_VT + 128 + kk * 2 * VS, VS, 640), mkdesc_ns(SB0 + OFF_KT + kk * 2 * KS, KS, 128), kk);
#pragma unroll
        for (int kk = 0; kk < 4; kk++) {
          if (SIE && kk == 4 - SIE && !bad) CBAR_ARRIVE(NB_SI, 256);
          wgmma_tt40(x, mkdesc_ns(SB0 + OFF_VT + kk * 2 * VS, VS, 384), mkdesc_ns(SB0 + OFF_KT + 640 + kk * 2 * KS, KS, 128), 1);
        }
        wg_commit();
        if (!SIE && !bad) CBAR_ARRIVE(NB_SI, 256);
        if (__builtin_expect(__any_sync(0xffffffffu, bad), 0)) {
          wg_wait<0>();
#pragma unroll 1
          for (int k = 0; k < 10; k++) {
            uint4 v = lds128(sb + OFF_M + tid * 16 + k * 2048);
            if (v.x == SENT || v.y == SENT || v.z == SENT || v.w == SENT) {
              do { v = ld_relaxed4(mkptr(elo + EX_M + i * 20480 + tid * 16 + k * 2048, ehi)); spin += 16; } while ((v.x == SENT || v.y == SENT || v.z == SENT || v.w == SENT) && spin < SPIN_TOT);
              sts128(sb + OFF_M + tid * 16 + k * 2048, v);
            }
          }
          fence_async();
          bar_sync(NB_C, 128);
          redo = fresh(1);
          goto retry;
        }
        TSV(i, 36, redo);
        const uint32_t rb1 = mapa(sb, (rank + 1) % 3), rb2 = mapa(sb, (rank + 2) % 3);
        wg_wait<0>();
        TS(i, 6);
        if (wu < 2) {
          float y[10];
#pragma unroll
          for (int j = 0; j < 5; j++) { y[2 * j] = x[4 * j]; y[2 * j + 1] = x[4 * j + 1]; }
          const uint4 h0 = make_uint4(pack_h2(y[0], y[1]), pack_h2(y[2], y[3]), pack_h2(y[4], y[5]), pack_h2(y[6], y[7]));
          const uint32_t h1 = pack_h2(y[8], y[9]);
          const uint32_t xo = wu * 640 + (tid & 31) * 16, xp = wu * 640 + 512 + (tid & 31) * 4;
          if (XMB) {
            sts128(sb + og_off(0) + xo, h0); sts32(sb + og_off(0) + xp, h1);
            fence_async();
            __syncwarp();
            if (elect_one()) {
              bulk_s2c(rb1 + OFF_XM + 1280 + wu * 640, sb + og_off(0) + wu * 640, 640, rb1 + BAR_XM);
              bulk_s2c(rb2 + OFF_XM + wu * 640, sb + og_off(0) + wu * 640, 640, rb2 + BAR_XM);
            }
          } else {
            st_async4u(rb1 + OFF_XM + 1280 + xo, h0, rb1 + BAR_XM);
            st_async4u(rb2 + OFF_XM + xo, h0, rb2 + BAR_XM);
            st_async1u(rb1 + OFF_XM + 1280 + xp, h1, rb1 + BAR_XM);
            st_async1u(rb2 + OFF_XM + xp, h1, rb2 + BAR_XM);
          }
          CBAR_ARRIVE(NB_SM, 256);
          if (!E0L && (tid & 31) == 0) mbar_arrive_cluster(mapa(sb, 0) + BAR_E);
          TS(i, 7);
          const uint32_t sw = (tid & 7) * 4 + (tid & 8) * 8 + (tid & 16) * 2;
          mwait(sb + BAR_XM, ph, spin);
          TS(i, 8);
          const uint4 u0 = lds128(sb + OFF_XM + xo), v0 = lds128(sb + OFF_XM + 1280 + xo);
          const uint32_t u1 = lds32(sb + OFF_XM + xp), v1 = lds32(sb + OFF_XM + 1280 + xp);
          add_h2(y[0], y[1], u0.x, v0.x); add_h2(y[2], y[3], u0.y, v0.y); add_h2(y[4], y[5], u0.z, v0.z); add_h2(y[6], y[7], u0.w, v0.w);
          add_h2(y[8], y[9], u1, v1);
          const float mx = quad_max(max10(y)) * -SCE;
#pragma unroll
          for (int j = 0; j < 5; j++) {
            y[2 * j] = ex2(fmaf(y[2 * j], SCE, mx)); y[2 * j + 1] = ex2(fmaf(y[2 * j + 1], SCE, mx));
            sts32(sb + OFF_PT + wu * 640 + sw + j * 128, pack_bf16(y[2 * j], y[2 * j + 1]));
          }
          sts32(sb + OFF_XM + 512 + wu * 128 + sw, __float_as_uint(sum10(y)));
          fence_async();
          TS(i, 9);
        } else {
          CBAR_ARRIVE(NB_SM, 256);
          if (!E0L && (tid & 31) == 0) mbar_arrive_cluster(mapa(sb, 0) + BAR_E);
          mwait(sb + BAR_MF, ph, spin);
        }
      }
      CBAR_SYNC(NB_VA, 256);
      TSB(i, 10);
      {
        float o[2][4];
        const float4 e = lds128f(sb + OFF_XM + 512 + (tid & 15) * 16);
        wg_fence();
#pragma unroll
        for (int c = 0; c < 2; c++)
#pragma unroll
          for (int q = 0; q < 3; q++)
            wgmma_ss8(o[c], mkdesc_ns(SB0 + OFF_VT + 128 + c * 640 + q * 256, 128, VS), mkdesc_ns(SB0 + OFF_PT + c * 640 + q * 256, q == 2 && c == 0 ? 768 : 128, 128), q);
        wg_commit();
        if (PVB && __builtin_expect(b1 < 0, 0)) { wg_wait<0>(); break; }
        const uint32_t rb1 = mapa(sb, (rank + 1) % 3), rb2 = mapa(sb, (rank + 2) % 3);
        const float inv = rcp((e.x + e.y) + (e.z + e.w));
        const int sl = (tid & 3) * 2;
        const float i0 = __shfl_sync(0xffffffffu, inv, sl), i1 = __shfl_sync(0xffffffffu, inv, sl + 1);
        const float i2 = __shfl_sync(0xffffffffu, inv, sl + 8), i3 = __shfl_sync(0xffffffffu, inv, sl + 9);
        if (E0L == 1 && (tid & 31) == 0) mbar_arrive_cluster(mapa(sb, 0) + BAR_E);
        if (PVB > 1 && __builtin_expect(b2 < 0, 0)) { wg_wait<0>(); break; }
        wg_wait<0>();
        TS(i, 11);
        const uint32_t p0 = pack_bf16(o[0][0] * i0, o[0][1] * i1), p1 = pack_bf16(o[1][0] * i2, o[1][1] * i3);
        const uint32_t p2 = pack_bf16(o[0][2] * i0, o[0][3] * i1), p3 = pack_bf16(o[1][2] * i2, o[1][3] * i3);
        if (OGF) { sts64(sb + oo + og_off(0), p0, p1); sts64(sb + oo + og_off(0) + 256, p2, p3); fence_async(); }
        if (OGF == 2) {
          __syncwarp();
          elect_s2c2(rb1 + og_off(2) + wu * 512, rb1 + BAR_OG, rb2 + og_off(1) + wu * 512, rb2 + BAR_OG, sb + og_off(0) + wu * 512, 512);
        } else if (OGF < 2) {
          st_async2u(rb1 + oo + og_off(2), p0, p1, rb1 + BAR_OG);
          st_async2u(rb2 + oo + og_off(1), p0, p1, rb2 + BAR_OG);
          st_async2u(rb1 + oo + og_off(2) + 256, p2, p3, rb1 + BAR_OG);
          st_async2u(rb2 + oo + og_off(1) + 256, p2, p3, rb2 + BAR_OG);
        }
        if (!OGF) { sts64(sb + oo + og_off(0), p0, p1); sts64(sb + oo + og_off(0) + 256, p2, p3); fence_async(); }
      }
      if (E0L == 2 && (tid & 31) == 0) mbar_arrive_cluster(mapa(sb, 0) + BAR_E);
      CBAR_SYNC(NB_A, 128);
      TSB(i, 12);
      if (OGF == 3 && wu < 2 && elect_one()) {
        const uint32_t rb = mapa(sb, (rank + 1 + wu) % 3);
        bulk_s2c(rb + og_off(2) - wu * 2048, sb + og_off(0), 2048, rb + BAR_OG);
      }
      {
        float acc[3][8];
        wg_fence();
        wo_block<0, 0>(acc[2], wf);
        wg_commit();
        wo_block<1, 0>(acc[0], wf);
        if (QPV == 1) CBAR_ARRIVE(NB_VQ, 384);
        wo_block<4, 0>(acc[1], wf);
        wg_commit();
        if (QPV == 2) CBAR_ARRIVE(NB_VQ, 384);
        if (tid < (E2L == 1 ? 2 : 1)) mbar_arrive_cluster(mapa(sb, 1 + tid) + BAR_E + 8 + 8 * tid);
        const uint32_t tag = (i >> 1) & 1;
#define TAGGED(LO, HI) ((pack_bf16(LO, HI) & ~1u) | tag)
#define SEND(OFF, U) st_relaxed128(mkptr(mo + (ph << 20), ehi) + (OFF), TAGGED(acc[U][0], acc[U][2]), pack_bf16(acc[U][1], acc[U][3]), pack_bf16(acc[U][4], acc[U][6]), pack_bf16(acc[U][5], acc[U][7]))
        wg_wait<1>();
        const uint32_t n0 = pin(TAGGED(acc[2][0], acc[2][2])), n1 = pin(pack_bf16(acc[2][1], acc[2][3]));
        const uint32_t n2 = pin(TAGGED(acc[2][4], acc[2][6])), n3 = pin(pack_bf16(acc[2][5], acc[2][7]));
        if (T2E) { wg_fence(); wo_block<7, 0>(acc[2], wf); wg_commit(); }
        if (!T9L) { st_relaxed64(mkptr(m9 + (ph << 20), ehi), n0, n1); st_relaxed64(mkptr(m9 + (ph << 20), ehi) + 3072, n2, n3); }
        mwait(sb + BAR_OG, ph, spin);
        asm volatile("fence.proxy.async::generic.acquire.sync_restrict::shared::cluster.cluster;" ::: "memory");
        if (E2L == 2 && tid == 0) mbar_arrive_cluster(mapa(sb, 2) + BAR_E + 16);
        TS(i, 13);
        wg_fence();
        wo_block<2, 1>(acc[0], wf); wo_block<3, 2>(acc[0], wf);
        wg_commit();
        wo_block<5, 1>(acc[1], wf); wo_block<6, 2>(acc[1], wf);
        wg_commit();
        if (QPV == 3) CBAR_ARRIVE(NB_VQ, 384);
        wg_wait<1>();
        if (T9L) { st_relaxed64(mkptr(m9 + (ph << 20), ehi), n0, n1); st_relaxed64(mkptr(m9 + (ph << 20), ehi) + 3072, n2, n3); }
        SEND(0, 0);
        if (!T2E) wo_block<7, 0>(acc[2], wf);
        wo_block<8, 1>(acc[2], wf); wo_block<9, 2>(acc[2], wf);
        wg_commit();
        if (WOE == 0) { CBAR_ARRIVE(NB_WV, 256); CBAR_ARRIVE(NB_WQ, 256); }
        wg_wait<1>(); SEND(32 * 2048, 1);
        if (WOE == 1) CBAR_ARRIVE(NB_WV, 256);
        wg_wait<0>(); SEND(64 * 2048, 2);
        if (WOE == 2) CBAR_ARRIVE(NB_WV, 256);
        if (WOE >= 1) CBAR_ARRIVE(NB_WQ, 256);
#undef SEND
#undef TAGGED
      }
      TS(i, 14);
      if (i < 2) PTS(19 + i);
      if (i + 1 >= NSTEP) break;
    }
    uint32_t t1 = clk32();
    if (i >= 0) {
      const int lane = fresh(tid0) & 31, j = lane >> 3;
      const uint8_t* mb = mkptr(elo + (ph << 20) + (t9 ? MAIL9 + (cta - 72) * 12288 + wu * 3072 : (cta < 72 ? cta : cta - 24) * 8192 + wu * 2048) + lane * 16, ehi);
      const uint32_t tag = (i >> 1) & 1;
      const bool pub = (lane & (t9 ? 6 : 4)) == 0 && !(((t9 ? cta : wu) & 1) && i + 1 == LAG) && cta < 88;
      const uint32_t dst = pin(elo + EX_M + (i + 1) * 20480 + (t9 ? (cta + 72) * 128 + wu * 32 + (j & 1) * 16 + (lane & 1) * 8 + (j >> 1) * 4
                                                                   : cta * 256 + (wu & 1) * 128 + (wu >> 1) * 64 + j * 16 + (lane & 3) * 4));
      uint8_t* flag = mkptr(elo + EX_FLAG + (i + 1) * 3072 + cta * 32 + wu * 4, ehi);
      while (clk32() - t1 < b1) {}
      TS(i + 1, 30);
      float f[8];
      const int n0 = spin;
      if (!t9) poll_add<4>(mb, tag, f, flag, lane == 0, spin);
      else poll_add<6>(mb, tag, f, flag, lane == 0, spin);
      if (FLP == 1 && lane == 0) st_relaxed(flag, __float_as_uint(f[0] + f[7]) >> 1);
      t1 = clk32();
      b1 = __any_sync(0xffffffffu, spin - n0 > 16) ? min(b1 + AD1, BMX) : max(b1 - AD0, 0);
      TSV(i + 1, 38, b1);
      TS(i + 1, 31); TSV(i + 1, 32, (spin - n0) >> 4);
      const bool h = lane & 16, q = lane & 8;
#pragma unroll
      for (int j = 0; j < 4; j++) f[j] = (h ? f[4 + j] : f[j]) + __shfl_xor_sync(0xffffffffu, h ? f[j] : f[4 + j], 16);
#pragma unroll
      for (int j = 0; j < 2; j++) f[j] = (q ? f[2 + j] : f[j]) + __shfl_xor_sync(0xffffffffu, q ? f[j] : f[2 + j], 8);
      f[0] += __shfl_xor_sync(0xffffffffu, f[0], 4); f[1] += __shfl_xor_sync(0xffffffffu, f[1], 4);
      if (t9) { f[0] += __shfl_xor_sync(0xffffffffu, f[0], 2); f[1] += __shfl_xor_sync(0xffffffffu, f[1], 2); }
      if (pub) st_relaxed(mkptr(dst, ehi), pack_bf16(f[0], f[1]));
      if (FLP == 2 && lane == 0) st_relaxed(flag, 0);
      if (!OSV && wu == 3) {
        CBAR_SYNC(NB_MR, 160);
        if (elect_one()) signal_o(i, cta);
      }

    }
    if (wu == 0) {
      const int tid = fresh(tid0);
      const uint8_t* pp = mkptr(elo + EX_FLAG + (i + 1) * 3072 + (rank * 28 + (tid < 28 || rank == 2 ? tid : 0)) * 32, ehi);
      while (clk32() - t1 < b2) {}

      int n = 1;
      uint4 x = ld_relaxed4(pp);
      if (tid0 == 0) mbar_expect_tx(sb + BAR_M, 20480);
      bool mok = mbar_test(sb + BAR_MOK, ph ^ 1);
      while (__any_sync(0xffffffffu, (int)(x.x | x.y | x.z | x.w) < 0 && spin < SPIN_TOT)) { x = ld_relaxed4(pp); mok = mbar_test(sb + BAR_MOK, ph ^ 1); n++; spin += 16; }
      if (!mok) mwait(sb + BAR_MOK, ph ^ 1, spin);
      if (B3 && n > 1) { const uint32_t t3 = clk32(); while (clk32() - t3 < B3) {} }
      b2 = n > 1 ? min(b2 + AD3, BMX) : max(b2 - AD2, 0);
      TSV(i + 1, 35, n); TSV(i + 1, 39, b2);
      TS(i + 1, 34);
      elect_g2s_mc(sb + OFF_M + rank * 7168, mkptr(elo + EX_M + (i + 1) * 20480 + rank * 7168, ehi), rank == 2 ? 6144 : 7168, sb + BAR_M);
      TS(i + 1, 33);
      __syncwarp();
    }
  }
  if (spin >= SPIN_TOT) g_err = 1;
}

__global__ void __cluster_dims__(3, 1, 1) __launch_bounds__(384, 1)
k_chain(const __grid_constant__ CUtensorMap tmWq, const __grid_constant__ CUtensorMap tmWk,
        const __grid_constant__ CUtensorMap tmWv, const __grid_constant__ CUtensorMap tmWo, const bf16* __restrict__ x0, const bf16* __restrict__ mem0) {
  using namespace C;
  extern __shared__ __align__(1024) uint8_t smem[];
  const uint32_t sb = smem_u32(smem);
  const int tid = threadIdx.x;
  const int wg = __shfl_sync(0xffffffffu, tid >> 7, 0);
  const int cta = uni(blockIdx.x), rank = uni(blockIdx.x % 3);

  asm volatile("griddepcontrol.launch_dependents;");
  if (cta < 4) prefetch_l2(tid < 320 ? x0 + (cta * 320 + tid) * 64 : mem0 + (cta * 20 + tid % 20) * 64);
  if (tid == 32) {
    for (int p = 0; p < 5; p++) mbar_init(sb + BAR_W + 8 * p, 2);
    fence_async();
    for (int p = 0; p < NBX; p++) { stage_box<false>(tmWv, sb, p, cta, rank); stage_box<true>(tmWo, sb, p, cta, rank); }
  }
  if (tid == 0) {
    if ((sb & 0xFFFFFF) != SB0) g_err = 100;
    for (int p = 0; p < 5; p++) { mbar_init(sb + BAR_F + 8 * p, 1); mbar_init(sb + BAR_E + 8 * p, p == 2 ? (E2L ? 3 : 12) : p == 1 ? 15 : 24); }
    mbar_init(sb + BAR_M, 1); mbar_init(sb + BAR_MOK, 24); mbar_init(sb + BAR_XM, 1); mbar_init(sb + BAR_XF, 2);
    mbar_init(sb + BAR_XT, 1); mbar_init(sb + BAR_MF, 8); mbar_init(sb + BAR_OG, 1);
    for (int p = 0; p < 5; p++) mbar_expect_tx(sb + BAR_F + 8 * p, 16384);
    for (int p = 0; p < 16; p++) sts32(sb + OFF_SAFE + 4 * p, 0);
    for (int p = 0; p < 32; p++) sts32(sb + OFF_ONE + 4 * p, 0x3F803F80);
    asm volatile("fence.mbarrier_init.release.cluster;" ::: "memory");
    fence_async();
  }
  __syncthreads();
  asm volatile("barrier.cluster.arrive.relaxed.aligned;" ::: "memory");
  asm volatile("barrier.cluster.wait.aligned;" ::: "memory");

  if (wg == 0) chain_a(tmWo, tmWq, sb, keep(tid), cta, rank);
  else if (wg == 1) chain_q(x0, mem0, sb, keep(tid), cta, rank);
  else chain_v(tmWv, tmWk, sb, keep(tid), cta, rank);
  asm volatile("barrier.cluster.arrive.release.aligned;" ::: "memory");
  asm volatile("barrier.cluster.wait.acquire.aligned;" ::: "memory");
}

namespace W {
constexpr int NP = 25, NBC = 11, NW = NP + NBC;
constexpr int PRS = 37, PW = 43 * 2048;
constexpr int OFF_W = 0;
constexpr int OFF_R = 2 * PW;
constexpr int BRS = 36;
constexpr int OFF_WO = 0, OFF_Y = 81920;
constexpr int OFF_X = OFF_Y + 2 * (40 - BRS) * 2048;
constexpr int OFF_WV = OFF_X + 40960;
constexpr int OFF_S = OFF_WV + 81920;
constexpr int COL = 976;
constexpr int OFF_T = OFF_X + 16384;
constexpr int OFF_BAR = 232064;
constexpr int OFF_SAFE = OFF_BAR + 256;
constexpr int SMEM = 232448;
static_assert(OFF_SAFE + 64 <= SMEM && OFF_R + 40960 <= OFF_BAR && OFF_S + 7696 <= OFF_BAR, "");
constexpr uint32_t SB0 = 1024;
constexpr int BAR_F = OFF_BAR, BAR_E = OFF_BAR + 40, BAR_G = OFF_BAR + 80, BAR_W = OFF_BAR + 160, BAR_R = OFF_BAR + 176;
constexpr int NB_G0 = 1, NB_SG = 4, NB_B = 5, NB_AS = 6, NB_SG1 = 7, NB_RED = 8, NB_SF = 9, NB_R = 11, NB_TD = 12, NB_RED3 = 13;
}
#define RTL 1
#define FSL 1
#define FSW 1
#define FSA 2
#define WBAR_SYNC(id, n) bar_sync(id, n)
#define WBAR_ARRIVE(id, n) bar_arrive(id, n)

__device__ __forceinline__ uint64_t rdesc(int off, int kk) { return mkdesc(W::SB0 + off + kk * 32, 16, 1024); }
__device__ __forceinline__ uint64_t gdesc(int off, int kk) { return mkdesc_ns(W::SB0 + off + kk * 1024, 512, 512) | ((uint64_t)2 << 62); }
__device__ __forceinline__ void mma_r(float (&d)[32], const uint32_t (&a)[4], uint64_t db, int sc) { wgmma_rs64(d, a, db, sc); }
__device__ __forceinline__ void mma_r(float (&d)[16], const uint32_t (&a)[4], uint64_t db, int sc) { wgmma_rs32(d, a, db, sc); }
__device__ __forceinline__ void mma_s(float (&d)[32], uint64_t da, uint64_t db, int sc) { wgmma_ts64(d, da, db, sc); }
__device__ __forceinline__ void mma_s(float (&d)[16], uint64_t da, uint64_t db, int sc) { wgmma_ts32(d, da, db, sc); }
__device__ __forceinline__ bool dual(int k) { return k >= LAG && k < NSEG; }
__device__ __forceinline__ uint32_t frag_addr(uint32_t base, int tid) {
  const int i = (tid >> 3) & 3, r = tid & 7;
  return base + (r + (i >> 1) * 8) * 128 + (((2 * ((tid >> 5) & 3) + (i & 1)) ^ r) << 4);
}
template <int NK>
__device__ __forceinline__ void load_frags(uint32_t (&wf)[NK][4], uint32_t base, int tid) {
  const uint32_t a0 = frag_addr(base, tid);
#pragma unroll
  for (int k = 0; k < NK; k++) ldsm4t(wf[k], a0 + k * 2048);
}
__device__ __forceinline__ void red_tile(const float* d, int seg, int col0, int tid) {
  float* p = g_x + (size_t)(seg * 32 + 2 * (tid & 3)) * DM + col0 + ((tid >> 5) & 3) * 16 + ((tid >> 2) & 7) * 2;
#pragma unroll
  for (int j = 0; j < 8; j++)
    asm volatile("red.relaxed.gpu.global.add.v2.f32 [%0],{%1,%2};" ::"l"(p + ((j >> 1) * 8 + (j & 1)) * DM), "f"(d[4 * (j >> 1) + (j & 1)]), "f"(d[4 * (j >> 1) + 2 + (j & 1)]) : "memory");
}

template <int ND>
__device__ __forceinline__ void p_products(float (&d)[ND], const uint32_t (&wf)[W::PRS][4], uint32_t sb, int tid0, int& spin) {
  using namespace W;
  constexpr int KF = ND == 32 ? 4 : 8;
  const uint32_t wo = uni(fresh(tid0) >> 7) * PW;
#pragma unroll
  for (int f = 0; f < 80 / KF; f++) {
    mwait(sb + BAR_F + 8 * (f % 5), (f / 5) & 1, spin);
    wg_fence();
#pragma unroll
    for (int kk = 0; kk < KF; kk++) {
      const int q = KF * f + kk;
      const uint64_t db = rdesc(OFF_R + (f % 5) * 8192 + (kk >> 2) * 4096, kk & 3);
      if (q < 2 * PRS && !(q & 1)) mma_r(d, wf[q < 2 * PRS ? q >> 1 : 0], db, q);
      else mma_s(d, desc_at(mkdesc(SB0 + OFF_W + (q < 2 * PRS ? q >> 1 : q - PRS) * 2048, 8192, 1024), wo), db, 1);
      if (kk == KF / 4 - 1 && f > 0) {
        wg_commit();
        wg_wait<1>();
        if ((tid0 & 31) == 0) mbar_arrive(sb + BAR_E + 8 * ((f - 1) % 5));
      }
    }
    wg_commit();
  }
  wg_wait<0>();
  if ((tid0 & 31) == 0) mbar_arrive(sb + BAR_E + 32);
}
__device__ __forceinline__ void work_p(const CUtensorMap& tmWo, uint32_t sb, int pc, const int WG, int tid0) {
  using namespace W;
  asm volatile("setmaxnreg.inc.sync.aligned.u32 208;");
  int spin = 0;
  const int ks = pc / 5, col0 = (pc % 5) * 128 + WG * 64;
  const uint32_t wb = sb + OFF_W + WG * PW;
  uint32_t wf[PRS][4];
#pragma unroll 1
  for (int hf = 0; hf < 2; hf++) {
    const int nk = hf ? 80 - PRS : PRS;
    if ((tid0 & 127) == 0) {
      mbar_expect_tx(sb + BAR_W + 8 * WG, nk * 2048);
      for (int i = 0; i < nk; i++) tma2d(wb + i * 2048, &tmWo, col0, ks * 19 * 64 + (i < PRS ? 2 * i + hf : PRS + i) * 16, sb + BAR_W + 8 * WG);
    }
    __syncwarp();
    mwait(sb + BAR_W + 8 * WG, hf, spin);
    permute_cols(wb, tid0 & 127, nk * 64);
    if (hf == 1 && ks < 4) for (int it = 39 * 64 + (tid0 & 127) - 64; it < 43 * 64; it += 128) {
      const uint32_t a = wb + (it >> 2) * 128 + (((2 * (it & 3)) ^ ((it >> 2) & 6)) << 4);
      if (it >= 39 * 64) { sts128(a, make_uint4(0, 0, 0, 0)); sts128(a + 16, make_uint4(0, 0, 0, 0)); }
    }
    fence_async();
    WBAR_SYNC(NB_G0 + WG, 128);
    if (hf == 0) {
      load_frags<PRS>(wf, wb, tid0);
      fence_async();
      WBAR_SYNC(NB_G0 + WG, 128);
    }
  }
#pragma unroll 1
  for (int k = 0; k < NSTEP; k++) {
    if (dual(k)) {
      float d[32];
      p_products(d, wf, sb, tid0, spin);
      if (WG == 0 && pc == WW) WTS(k, 2);
      red_tile(d, k, col0, tid0);
      red_tile(d + 16, k - LAG, col0, tid0);
    } else {
      float d[16];
      p_products(d, wf, sb, tid0, spin);
      if (WG == 0 && pc == WW) WTS(k, 2);
      red_tile(d, k < LAG ? k : k - LAG, col0, tid0);
    }
    if (WG == 0 && pc == WW) WTS(k, 13);
    WBAR_SYNC(NB_SG, 288);
  }
  if (spin >= SPIN_TOT) g_err = 11;
}
__device__ __forceinline__ void work_p_producer(uint32_t sb, int pc) {
  using namespace W;
  int spin = 0;
  const int ks = pc / 5;
#pragma unroll 1
  for (int k = 0; k < NSTEP; k++) {
    const bool two = dual(k);
    const uint8_t* src = &g_o[k % ORING][ks * 19][k < NSEG ? 0 : 4096];
    cwait(CN_O + k * 5 + ks, ks == 4 ? 20 : 19, spin);
    fence_async_all();
    if (pc == WW) WTS1(k, 0);
    if (two) {
#pragma unroll 1
      for (int u = 0; u < 4; u++, src += 40960) {
#pragma unroll
        for (int st = 0; st < 5; st++) {
          const uint8_t* p = src + (st == 4 && u == 3 && ks < 4 ? 3 : st) * 8192;
          mwait(sb + BAR_E + 8 * st, (u & 1) ^ 1, spin);
          fill_stage(sb + OFF_R + st * 8192, p, 8192, sb + BAR_F + 8 * st);
        }
      }
    } else {
#pragma unroll 1
      for (int f = 0; f < 10; f++, src += 16384) {
        const int st = f % 5;
        mwait(sb + BAR_E + 8 * st, f < 5, spin);
        fill_stage2(sb + OFF_R + st * 8192, src, src + (f == 9 && ks < 4 ? 0 : 8192), sb + BAR_F + 8 * st);
      }
    }
  }
  if (spin >= SPIN_TOT) g_err = 12;
}
template <int DMS>
__device__ __forceinline__ void work_ln(const int kind, int r, int lane, bf16* out) {
  int spin = 0;
  const int l = kind & 1;
  const int rp = kind < 2 ? (r & 1) * 16 + (r >> 1) : r;
  const uint32_t sw = ((((lane >> 1) & 7) ^ (rp & 7)) << 4) + (lane & 1) * 8;
  uint8_t* dst = kind < 2 ? g_xnb[l * LAG] + (lane >> 4) * 8192 + l * 4096 + rp * 128 + sw
               : kind == 2 ? g_xn[LAG] + (r >> 3) * 4096 + 2048 + (lane >> 4) * 1024 + (r & 7) * 128 + sw
                           : reinterpret_cast<uint8_t*>(out) + r * 1280 + lane * 8;
  if (FSL && kind < 2) {
#pragma unroll
    for (int m = 0; m < 5; m++) asm volatile("st.global.v2.b32 [%0],{%1,%1};" ::"l"(dst + m * DMS), "r"(SENT) : "memory");
    fence_gpu();
  }
#pragma unroll 1
  for (int s = 0; s < NSEG; s++) {
    float* xr = g_x + (size_t)(s * 32 + r) * DM;
    float4 v[5];
    if (kind < 2) {
#pragma unroll
      for (int u = 0; u < 5; u++) {
        const int p = u * 32 + lane;
        stg128((p < 80 ? g_ob[s + l * LAG] + (l * 32 + r) * 1280 : g_y[l] + (size_t)s * 40960 + (r - 1) * 1280) + p * 16, make_uint4(SENT, SENT, SENT, SENT));
      }
      if (FSL && s + 1 < NSEG) {
#pragma unroll
        for (int m = 0; m < 5; m++) asm volatile("st.global.v2.b32 [%0],{%1,%1};" ::"l"(dst + 81920 + m * DMS), "r"(SENT) : "memory");
      }
      if (lane == 0) cwait(CN_P + s + l * LAG, W::NP, spin);
      __syncwarp();
      if (r == 0 && lane == 0 && (l == 0 || s + LAG >= NSEG)) WTS1(s + l * LAG, 3);
#pragma unroll
      for (int m = 0; m < 5; m++) v[m] = ld_relaxed4f(xr + m * 128 + lane * 4);
    } else {
      if (lane == 0) cwait(CN_L + s + l * LAG, s + l * LAG < LAG || s + l * LAG >= NSEG ? 32 : 64, spin);
      __syncwarp();
#pragma unroll
      for (int m = 0; m < 5; m++) v[m] = ld_relaxed4f(xr + m * 128 + lane * 4);
      if (lane == 0) cwait(CN_W + l * 64 + s, 10, spin);
      __syncwarp();
      if (r == 0 && lane == 0 && (l == 0 || s + LAG >= NSEG)) WTS1(s + l * LAG, 11);
      const uint8_t* yp = g_y[l] + (size_t)s * 40960 + (lane >> 4) * 4096 + r * 128 + sw;
      float2 y[5];
      bool bad;
      do {
        bad = false;
#pragma unroll
        for (int m = 0; m < 5; m++) y[m] = ld_relaxed2f(yp + m * 8192);
#pragma unroll
        for (int m = 0; m < 5; m++) bad |= __float_as_uint(y[m].x) == SENT || __float_as_uint(y[m].y) == SENT;
        spin += 16;
      } while (__any_sync(0xffffffffu, bad && spin < SPIN_TOT));
#pragma unroll
      for (int m = 0; m < 5; m++) {
        v[m].x += bf_lo(__float_as_uint(y[m].x)); v[m].y += bf_hi(__float_as_uint(y[m].x));
        v[m].z += bf_lo(__float_as_uint(y[m].y)); v[m].w += bf_hi(__float_as_uint(y[m].y));
        if (kind == 2) *reinterpret_cast<float4*>(xr + m * 128 + lane * 4) = v[m];
      }
    }
    if (FSL == 3 && kind < 2 && lane == 0) csignal_fast(CN_G + s + l * LAG);
    if (kind < 3) ln_row(v);
#pragma unroll
    for (int m = 0; m < 5; m++)
      asm volatile("st.global.v2.b32 [%0],{%1,%2};" ::"l"(dst + m * DMS), "r"(pack_bf16(v[m].x, v[m].y)), "r"(pack_bf16(v[m].z, v[m].w)) : "memory");
    dst += DMS == 256 ? 40960 : 81920;
    __syncwarp();
    if (r == 0 && lane == 0 && (l == 0 || s + LAG >= NSEG)) WTS1(s + l * LAG, kind < 2 ? 4 : 12);
    if (lane == 0 && kind < (NOWORK ? 2 : 3)) {
      if (FSL && kind < 2) csignal_fast(CN_G + s + l * LAG);
      csignal_t(kind < 2 ? CN_L + s + l * LAG : CN_X + s + LAG, kind);
    }
  }
  if (spin >= SPIN_TOT) g_err = 13;
}

__device__ __forceinline__ void work_prep(const bf16* x0, const bf16* mem0, int r, int lane) {
  int spin = 0;
#pragma unroll 1
  for (int k = NPRE; k < NSTEP; k++) {
    if (lane < 20) prefetch_l2(x0 + (size_t)min(k * 32 + r + (lane < 10 ? 0 : 16), SEQ - 1) * DM + (lane % 10) * 64);
    if (lane == 0) cwait(CN_O + (k - NPRE) * 5, 1, spin);
    __syncwarp();
#pragma unroll 1
    for (int h = 0; h < 2; h++) {
      uint2 u[5];
      ln0_load(x0, u, min(k * 32 + r + 16 * h, SEQ - 1), lane);
      prep_row(u, mem0, k, r + 16 * h, lane);
    }
    __syncwarp();
    if (lane == 0) csignal(CN_X + k);
  }
  if (spin >= SPIN_TOT) g_err = 19;
}

__device__ __forceinline__ void stage_qkv(const bf16* wqkv, uint32_t base, int T, int bc, int tid) {
  const int q = tid & 15;
  const bool ok = q < 15 && bc * 60 + 4 * q < DM;
  const bf16* src = wqkv + T * DM + bc * 60 + 4 * q;
#pragma unroll 1
  for (int k0 = tid >> 4; k0 < 640; k0 += 80) {
    uint2 v[10];
#pragma unroll
    for (int u = 0; u < 10; u++) v[u] = ok ? *reinterpret_cast<const uint2*>(src + (size_t)(k0 + 8 * u) * 1920) : make_uint2(0, 0);
#pragma unroll
    for (int u = 0; u < 10; u++) sts64(base + (k0 + 8 * u) * 128 + (((q >> 1) ^ (k0 & 7)) << 4) + (q & 1) * 8, v[u].x, v[u].y);
  }
}
struct AttAddr { uint32_t qa, qb, ka, oa, ob, ml; };
__device__ __forceinline__ AttAddr att_addr(uint32_t sb, int bc, int hh, int tid) {
  using namespace W;
  const int r = tid & 7, m = (tid >> 3) & 3, g = (tid >> 2) & 7, t = tid & 3, lp = (tid >> 5) & 3;
  const int f2 = r < 4 ? 20 * hh + 16 + r : 60;
  const uint32_t tb = sb + OFF_T + 2 * lp * COL;
  const int fa = 20 * hh + (m >> 1) * 8 + r, pc = 2 * (lp & 1) + (m & 1);
  const uint32_t o0 = sb + OFF_S + (lp >> 1) * 3840;
  AttAddr x;
  x.qa = keep(tb + (m & 1) * COL + (20 * hh + (m >> 1) * 8 + r) * 16);
  x.qb = keep(tb + (m & 1) * COL + f2 * 16);
  x.ka = keep(tb + (m < 2 ? 20 * hh + 8 * m + r : f2) * 16);
  x.oa = keep(o0 + fa * 64 + ((pc ^ ((bc * 60 + fa) >> 1)) & 3) * 16);
  x.ob = keep(r < 4 ? o0 + f2 * 64 + ((pc ^ ((bc * 60 + f2) >> 1)) & 3) * 16 : sb + OFF_S + 7680);
  x.ml = keep((2 * t > g ? 0xFFFFu : 0u) | (2 * t + 1 > g ? 0xFFFF0000u : 0u));
  return x;
}
__device__ __forceinline__ void release_tiles(uint32_t sb, int tid) {
  fence_async();
  __syncwarp();
  if ((tid & 31) < 3) mbar_arrive(sb + W::BAR_E + 16 + 8 * (tid & 3));
}
__device__ __forceinline__ void attend(uint32_t sb, const AttAddr& x, uint32_t (&hist)[6], int k0, int lp, int tid) {
  using namespace W;
  const float scl = 0.22360679774997896f * 1.4426950408889634f;
  float sc[3][4];
  uint32_t v[3][4];
  {
    uint32_t q[4], q8a, q8b, k[3][4];
    ldsm4t(q, x.qa);
    ldsm4t(k[1], x.ka + 8 * COL); ldsm4t(k[2], x.ka + 9 * COL);
    ldsm2t(q8a, q8b, x.qb);
    ldsm4(v[1], x.ka + 16 * COL); ldsm4(v[2], x.ka + 17 * COL);
#pragma unroll
    for (int j = 0; j < 3; j++) { k[0][j] = hist[j]; v[0][j] = hist[3 + j]; hist[j] = k[2][j]; hist[3 + j] = v[2][j]; }
#pragma unroll
    for (int c = 0; c < 3; c++) { sc[c][0] = sc[c][1] = sc[c][2] = sc[c][3] = 0.f; mma16816(sc[c], q[0], q[1], q[2], q[3], k[c][0], k[c][1]); }
#pragma unroll
    for (int c = 0; c < 3; c++) mma1688(sc[c], q8a, q8b, k[c][2]);
  }
  if (RTL == 0) release_tiles(sb, tid);
  const bool lo0 = x.ml & 1, lo1 = (int)x.ml < 0, first = k0 == (lp >> 1) * LAG;
  uint32_t pw[2];
  float inv[2];
#pragma unroll
  for (int h = 0; h < 2; h++) {
    float y0 = lo0 ? sc[h][2 * h] : sc[h + 1][2 * h], y1 = lo1 ? sc[h][2 * h + 1] : sc[h + 1][2 * h + 1];
    if (h == 0 && first) { y0 = lo0 ? -INFINITY : y0; y1 = lo1 ? -INFINITY : y1; }
    const float mx = quad_max(fmaxf(y0, y1)) * -scl;
    y0 = ex2(fmaf(y0, scl, mx)); y1 = ex2(fmaf(y1, scl, mx));
    pw[h] = pack_bf16(y0, y1);
    inv[h] = y0 + y1;
  }
  float o[3][4];
  const uint32_t a0 = pw[0] & x.ml, a2 = pw[0] & ~x.ml, a3 = pw[1] & x.ml, a5 = pw[1] & ~x.ml, z0 = tid >> 10, z1 = tid >> 11;
#pragma unroll
  for (int j = 0; j < 3; j++) { o[j][0] = o[j][1] = o[j][2] = o[j][3] = 0.f; mma16816(o[j], a0, z0, a2, a3, v[0][j], v[1][j]); }
#pragma unroll
  for (int j = 0; j < 3; j++) mma1688(o[j], z1, a5, v[2][j]);
  if (RTL == 1) release_tiles(sb, tid);
  inv[0] = rcp(quad_sum(inv[0])); inv[1] = rcp(quad_sum(inv[1]));
  stsm4t(x.oa, pack_bf16(o[0][0] * inv[0], o[0][1] * inv[0]), pack_bf16(o[0][2] * inv[1], o[0][3] * inv[1]),
         pack_bf16(o[1][0] * inv[0], o[1][1] * inv[0]), pack_bf16(o[1][2] * inv[1], o[1][3] * inv[1]));
  stsm2t(x.ob, pack_bf16(o[2][0] * inv[0], o[2][1] * inv[0]), pack_bf16(o[2][2] * inv[1], o[2][3] * inv[1]));
  if (RTL == 2) release_tiles(sb, tid); else fence_async();
}
__device__ __forceinline__ bool b_job(int k, int u, int bc) { return u == 0 || (u == 1 ? dual(k) : bc < 10 && (u == 3 || dual(k - 1))); }
template <bool IS_V, int ND, int NR>
__device__ __forceinline__ void qkv_step(float (&d)[ND], const uint32_t (&wf)[NR][4], const int q, uint32_t yo, uint64_t db) {
  using namespace W;
  if (!IS_V && q < NR) mma_r(d, wf[q < NR ? q : 0], db, q);
  else if (IS_V) mma_s(d, mkdesc(SB0 + OFF_WV + q * 2048, 8192, 1024), db, q);
  else mma_s(d, desc_at(mkdesc(SB0 + OFF_Y + (q - NR) * 2048, 8192, 1024), yo), db, 1);
}
template <bool IS_V, int ND, int NR>
__device__ __forceinline__ bool qkv_products(uint32_t (&pk)[16], const uint32_t (&wf)[NR][4], uint32_t sb, uint32_t pf, int tid0, int& spin) {
  using namespace W;
  constexpr int KF = ND == 32 ? 4 : 8, NF = 40 / KF;
  const uint32_t yo = uni(fresh(tid0) >> 7) * (40 - BRS) * 2048;
  float d[ND];
#pragma unroll
  for (int c = 0; c < NF; c++) {
    mwait(sb + BAR_F + 8 * (c % 5), pf ^ (c / 5), spin);
    wg_fence();
#pragma unroll
    for (int kk = 0; kk < KF; kk++) qkv_step<IS_V>(d, wf, KF * c + kk, yo, rdesc(OFF_X + (c % 5) * 8192 + (kk >> 2) * 4096, kk & 3));
    wg_commit();
    if (c > 0 && c <= NF - 3) {
      wg_wait<1>();
      if ((tid0 & 31) == 0) mbar_arrive(sb + BAR_E + 8 * ((c - 1) % 5));
    }
  }
  wg_wait<0>();
#pragma unroll
  for (int q = 0; q < 16; q++) pk[q] = pin(pack_bf16(d[(2 * q) % ND], d[(2 * q + 1) % ND]));
  float c0 = ((d[0] + d[1]) + (d[4] + d[5])) + ((d[8] + d[9]) + (d[12] + d[13]));
  if (ND == 32) c0 += ((d[16 % ND] + d[17 % ND]) + (d[20 % ND] + d[21 % ND])) + ((d[24 % ND] + d[25 % ND]) + (d[28 % ND] + d[29 % ND]));
  return IS_V && c0 != c0;
}
template <bool IS_V>
__device__ __forceinline__ void work_b(const CUtensorMap& tmBo, const bf16* wqkv, uint32_t sb, int bc, const int wg, int tid0) {
  using namespace W;
  if (!IS_V) asm volatile("setmaxnreg.inc.sync.aligned.u32 208;");
  else asm volatile("setmaxnreg.dec.sync.aligned.u32 72;");
  constexpr int NR = IS_V ? 1 : BRS;
  const int WG = IS_V ? 2 : wg;
  const uint32_t yo = WG * (40 - BRS) * 2048;
  int spin = 0;
  uint32_t wf[NR][4];
  if (!IS_V) {
    const uint32_t wb = sb + (WG ? OFF_WO : OFF_WV);
    stage_qkv(wqkv, wb, WG, bc, tid0 & 127);
    WBAR_SYNC(NB_G0 + WG, 128);
    load_frags<NR>(wf, wb, tid0);
#pragma unroll
    for (int k = NR; k < 40; k++) sts128(sb + OFF_Y + yo + (k - NR) * 2048 + (tid0 & 127) * 16, lds128(wb + k * 2048 + (tid0 & 127) * 16));
    fence_async();
  }
  WBAR_SYNC(NB_B, 384);
  if (WG == 1 && bc < 10) {
    if ((tid0 & 127) == 0) {
      mbar_expect_tx(sb + BAR_W, 81920);
      for (int i = 0; i < 10; i++) tma2d(sb + OFF_WO + i * 8192, &tmBo, bc * 64, i * 64, sb + BAR_W);
    }
    __syncwarp();
    mwait(sb + BAR_W, 0, spin);
  }
  if (IS_V) stage_qkv(wqkv, sb + OFF_WV, 2, bc, tid0 & 127);
  fence_async();
  WBAR_SYNC(NB_B, 384);
  const int wu = uni((tid0 >> 5) & 3);
  uint32_t nredo = 0, hist[6] = {};
  const AttAddr aa = att_addr(sb, bc, WG, tid0);
#pragma unroll 1
  for (int k = 0; k < NSTEP; k++) {
    {
      uint32_t pk[16];
      const bool bad = dual(k) ? qkv_products<IS_V, 32>(pk, wf, sb, LAG & 1, tid0, spin) : qkv_products<IS_V, 16>(pk, wf, sb, (k < LAG ? k : k - NSEG + LAG) & 1, tid0, spin);
      if (bc == 0 && WG != 1) WTS(k, 16 + WG / 2);
      const int tid = fresh(tid0), m = (tid >> 3) & 3;
      const uint32_t a = pin(sb + OFF_T + min(wu * 16 + (m & 1) * 8 + (tid & 7), 60) * 16 + (8 * WG + (m >> 1)) * COL);
      if (!FSL) WBAR_SYNC(NB_B, 384);
      else {
        if (__builtin_expect(bar_red_or(NB_RED3, 384, bad), 0)) {
          float d[32];
          if (IS_V && wu == 0) { cwait(CN_L + k, k < LAG || k >= NSEG ? 32 : 64, spin); fence_async_all(); }
#pragma unroll
          for (int c = 0; c < 10; c++) {
            if (IS_V && wu == 0 && elect_one()) { mbar_expect_tx(sb + BAR_R + 8, 8192); bulk_g2s(sb + OFF_X + 32768, g_xnb[k] + c * 8192, 8192, sb + BAR_R + 8); }
            __syncwarp();
            mwait(sb + BAR_R + 8, c & 1, spin);
            wg_fence();
#pragma unroll
            for (int kk = 0; kk < 4; kk++) qkv_step<IS_V>(d, wf, 4 * c + kk, yo, rdesc(OFF_X + 32768, kk));
            wg_commit();
            wg_wait<0>();
            bar_sync(NB_RED3, 384);
          }
#pragma unroll
          for (int q = 0; q < 16; q++) pk[q] = pin(pack_bf16(d[2 * q], d[2 * q + 1]));
        }
      }
#pragma unroll
      for (int p = 0; p < 4; p++) stsm4(a + 2 * p * COL, pk[4 * p], pk[4 * p + 1], pk[4 * p + 2], pk[4 * p + 3]);
    }
    WBAR_SYNC(NB_TD, 448);
    if (bc == 0 && WG == 0) WTS(k, 7);
    if (bc * 3 + WG < NH && (wu < 2 ? k < NSEG : k >= LAG)) attend(sb, aa, hist, k, wu, fresh(tid0));
    else release_tiles(sb, tid0);
    if (bc == 0 && WG == 0) WTS(k, 8);
    WBAR_SYNC(NB_AS, 416);
    if (!IS_V && b_job(k, 2 + WG, bc)) {
      float d[16];
#pragma unroll
      for (int f = 0; f < 5; f++) {
        mwait(sb + BAR_G + 40 * WG + 8 * f, (WG ? k : k - LAG - 1) & 1, spin);
        if (f == 0 && bc == 0) WTS(k - 1 + WG, WG ? 20 : 23);
        wg_fence();
#pragma unroll
        for (int kk = 0; kk < 8; kk++) {
          wgmma_tt32(d, mkdesc(SB0 + OFF_WO + (8 * f + kk) * 2048, 8192, 1024), gdesc(OFF_X + f * 8192, kk), f | kk);
          if (kk == 1 && f > 0) {
            wg_commit();
            wg_wait<1>();
            if ((tid0 & 31) < 3) mbar_arrive(sb + BAR_E + 8 * (f - 1));
          }
        }
        wg_commit();
      }
      wg_wait<0>();
      if (WG == 1 && FSA) {
        const float chk = ((d[0] + d[1]) + (d[4] + d[5])) + ((d[8] + d[9]) + (d[12] + d[13]));
        if (__builtin_expect(bar_red_or(NB_RED, 128, chk != chk), 0)) {
          if (wu == 0) { cwait(CN_A + k, NBC, spin); fence_async_all(); }
#pragma unroll
          for (int q = 0; q < 16; q++) d[q] = 0.f;
#pragma unroll 1
          for (int f = 0; f < 5; f++) {
            if (wu == 0 && elect_one()) { mbar_expect_tx(sb + BAR_W + 8, 8192); bulk_g2s(sb + OFF_X + 32768, g_ob[k] + (k < NSEG ? 0 : 40960) + f * 8192, 8192, sb + BAR_W + 8); }
            __syncwarp();
            mwait(sb + BAR_W + 8, nredo & 1, spin);
            nredo++;
            wg_fence();
#pragma unroll
            for (int kk = 0; kk < 8; kk++)
              wgmma_tt32(d, desc_at(mkdesc(SB0 + OFF_WO + kk * 2048, 8192, 1024), f * 16384), gdesc(OFF_X + 32768, kk), 1);
            wg_commit();
            wg_wait<0>();
            bar_sync(NB_RED, 128);
          }
        }
      }
      else if (WG) bar_sync(NB_RED, 128);
      else {
        if ((tid0 & 31) < 3) mbar_arrive(sb + BAR_E + 32);
        WBAR_SYNC(NB_SF, 160);
      }
      if (bc == 0) WTS(k - 1 + WG, WG ? 10 : 24);
      const int tid = fresh(tid0), m = (tid >> 3) & 3, row = (m >> 1) * 16 + 2 * (tid & 7);
      const uint32_t a = sb + (WG ? OFF_X + 32768 : OFF_S) + row * 128 + (((2 * wu + (m & 1)) ^ row) & 7) * 16;
#pragma unroll
      for (int p = 0; p < 2; p++)
        stsm4t(a ^ (p * 144), pack_bf16(d[8 * p], d[8 * p + 1]), pack_bf16(d[8 * p + 2], d[8 * p + 3]), pack_bf16(d[8 * p + 4], d[8 * p + 5]), pack_bf16(d[8 * p + 6], d[8 * p + 7]));
      fence_async();
      WBAR_SYNC(WG ? NB_SG : NB_SG1, 160);
    }
  }
  if (spin >= SPIN_TOT) g_err = 14;
}
__device__ __forceinline__ void work_b_watch(uint32_t sb, int bc) {
  using namespace W;
  int spin = 0;
#pragma unroll 1
  for (int j = 0; j < 4 * NSTEP; j++) {
    const int k = j >> 2, u = j & 3;
    if (u == 1 || !b_job(k, u, bc)) continue;
    cwait(u == 0 ? (FSL ? CN_G : CN_L) + k : u == 2 ? CN_A + k - 1 : (FSA ? CN_F : CN_A) + k, u ? NBC : k < LAG || k >= NSEG ? 32 : 64, spin);
    fence_async_all();
    if (bc == 0 && u != 2) WTS1(k, u ? 9 : 5);
    if (elect_one()) mbar_arrive(sb + BAR_R + 8 * u);
    __syncwarp();
    if (u == 0) WBAR_SYNC(NB_R, 64);
  }
  if (spin >= SPIN_TOT) g_err = 16;
}
__device__ __forceinline__ void work_b_producer(uint32_t sb, int bc) {
  using namespace W;
  int spin = 0;
  uint32_t pe = 1;
#pragma unroll 1
  for (int j = 0; j < 4 * NSTEP; j++) {
    const int k = j >> 2, u = j & 3;
    if (!b_job(k, u, bc)) continue;
    const uint32_t half = u < 2 && !dual(k), lo = half && k >= NSEG ? 4096 : 0, fb = sb + (u < 2 ? BAR_F : BAR_G + 40 * (u - 2));
    const uint8_t* src = (u < 2 ? g_xnb[k] + u * 40960 : u == 2 ? g_ob[k - 1] + 40960 : g_ob[k] + (k < NSEG ? 0 : 40960)) + lo;
    mwait(sb + BAR_E, pe, spin);
    if (u != 1) mwait(sb + BAR_R + 8 * u, (u == 2 ? k - LAG - 1 : k) & 1, spin);
    if (!half) {
#pragma unroll
      for (int f = 0; f < 5; f++) {
        if (f) mwait(sb + BAR_E + 8 * f, pe, spin);
        fill_stage(sb + OFF_X + f * 8192, src + f * 8192, 8192, fb + 8 * f);
      }
    } else {
#pragma unroll 1
      for (int f = 0; f < 5; f++) {
        mwait(sb + BAR_E + 8 * f, pe, spin);
        fill_stage2(sb + OFF_X + f * 8192, src + f * 16384, src + f * 16384 + 8192, fb + 8 * f);
      }
    }
    if (u == 0) WBAR_SYNC(NB_R, 64);
    pe ^= 1;
  }
  if (spin >= SPIN_TOT) g_err = 15;
}

__global__ void __launch_bounds__(512, 1)
k_work(const __grid_constant__ CUtensorMap tmWo, const __grid_constant__ CUtensorMap tmBo, const bf16* __restrict__ wqkv, bf16* __restrict__ out,
       const bf16* __restrict__ x0, const bf16* __restrict__ mem0) {
  using namespace W;
  extern __shared__ __align__(1024) uint8_t smem[];
  const uint32_t sb = smem_u32(smem);
  const int tid = threadIdx.x, w = blockIdx.x;
  const int wg = __shfl_sync(0xffffffffu, tid >> 7, 0);
  if (tid == 0) {
    if (sb != SB0) g_err = 101;
    for (int i = 0; i < 5; i++) { mbar_init(sb + BAR_F + 8 * i, 1); mbar_init(sb + BAR_E + 8 * i, w < NP ? 8 : 12); }
    for (int i = 0; i < 16; i++) mbar_init(sb + BAR_G + 8 * i, 1);
    for (int p = 0; p < 16; p++) sts32(sb + OFF_SAFE + 4 * p, 0);
    asm volatile("fence.mbarrier_init.release.cluster;" ::: "memory");
    int spin = 0;
    pre_wait(1, NW, spin);
    if (spin >= SPIN_TOT) g_err = 18;
  }
  fence_async();
  __syncthreads();

  if (w < NP) {
    if (wg < 2) work_p(tmWo, sb, w, wg, keep(tid));
    else {
      asm volatile("setmaxnreg.dec.sync.aligned.u32 48;");
      const int aw = uni(tid >> 5) - 8;
      if (aw == 0) work_p_producer(sb, w);
      else if (aw == 1) {
#pragma unroll 1
        for (int k = 0; k < NSTEP; k++) {
          WBAR_SYNC(NB_SG, 288);
          if (elect_one()) csignal_t(CN_P + k, 3);
          __syncwarp();
        }
      } else {
        const int id = (aw - 2) * NP + w;
        if (id < 96) work_ln<16384>(id % 3, id / 3, tid & 31, out);
        else if (id < 128) work_ln<256>(3, id - 96, tid & 31, out);
        else if (id < 144 && NOWORK != 2) work_prep(x0, mem0, id - 128, tid & 31);
      }
    }
  } else {
    const int bc = w - NP;
    if (wg < 2) work_b<false>(tmBo, wqkv, sb, bc, wg, keep(tid));
    else if (wg == 2) work_b<true>(tmBo, wqkv, sb, bc, wg, keep(tid));
    else {
      asm volatile("setmaxnreg.dec.sync.aligned.u32 24;");
      const int aw = uni(tid >> 5) - 12;
      if (aw == 0) work_b_producer(sb, bc);
      else if (aw == 1) work_b_watch(sb, bc);
      else if (aw == 2) {
#pragma unroll 1
        for (int k = 0; k < NSTEP; k++) {
          WBAR_ARRIVE(NB_TD, 448);
          if (FSA == 3 && (tid & 31) == 0) csignal_fast(CN_F + k);
          WBAR_SYNC(NB_AS, 416);
          if (elect_one()) {
            const uint32_t len = bc < 10 ? 3840 : 2560;
            const int l = k >= NSEG;
            bulk_s2g(g_ob[k] + l * 40960 + bc * 3840, sb + OFF_S + l * 3840, len);
            if (FSA) csignal_fast(CN_F + k);
            if (dual(k)) bulk_s2g(g_ob[k] + 40960 + bc * 3840, sb + OFF_S + 3840, len);
            asm volatile("cp.async.bulk.commit_group;" ::: "memory");
            asm volatile("cp.async.bulk.wait_group 0;" ::: "memory");
          }
          __syncwarp();
          if (b_job(k, 2, bc)) WBAR_ARRIVE(NB_SF, 160);
          if (elect_one()) { fence_async_all(); csignal_t(CN_A + k, 5); }
          __syncwarp();
        }
      } else {
#pragma unroll 1
        for (int j = 0; j < 2 * NSTEP; j++) {
          const int k = j >> 1, pr = j & 1, l = !pr || k >= NSEG, s = k - l * LAG - !pr;
          if (!pr) WBAR_SYNC(NB_TD, 448);
          if (!b_job(k, 2 + pr, bc)) continue;
          WBAR_SYNC(pr ? NB_SG : NB_SG1, 160);
          if (elect_one()) {
            bulk_s2g(g_y[l] + (size_t)s * 40960 + bc * 4096, sb + (pr ? OFF_X + 32768 : OFF_S), 4096);
            asm volatile("cp.async.bulk.commit_group;" ::: "memory");
            if (FSW) csignal_fast(CN_W + l * 64 + s);
            asm volatile("cp.async.bulk.wait_group.read 0;" ::: "memory");
            if (!FSW) csignal_fast(CN_W + l * 64 + s);
            if (pr) asm volatile("mbarrier.arrive.shared::cta.b64 _,[%0],12;" ::"r"(sb + BAR_E + 32) : "memory");
          }
          __syncwarp();
        }
      }
    }
  }
  __syncthreads();
  asm volatile("griddepcontrol.wait;" ::: "memory");
}

typedef CUresult (*EncodeFn)(CUtensorMap*, CUtensorMapDataType, cuuint32_t, void*, const cuuint64_t*, const cuuint64_t*,
                             const cuuint32_t*, const cuuint32_t*, CUtensorMapInterleave, CUtensorMapSwizzle,
                             CUtensorMapL2promotion, CUtensorMapFloatOOBfill);

static void make_map(EncodeFn enc, CUtensorMap* tm, const void* ptr, uint64_t cols, uint64_t rows, uint32_t boxc, uint32_t boxr) {
  cuuint64_t dims[2] = {cols, rows};
  cuuint64_t strides[1] = {cols * 2};
  cuuint32_t box[2] = {boxc, boxr};
  cuuint32_t es[2] = {1, 1};
  enc(tm, CU_TENSOR_MAP_DATA_TYPE_BFLOAT16, 2, const_cast<void*>(ptr), dims, strides, box, es, CU_TENSOR_MAP_INTERLEAVE_NONE,
      CU_TENSOR_MAP_SWIZZLE_128B, CU_TENSOR_MAP_L2_PROMOTION_L2_256B, CU_TENSOR_MAP_FLOAT_OOB_FILL_NONE);
}

extern "C" void kernel_launch(void* const* d_in, const int* in_sizes, int n_in, void* d_out, int out_size) {
  const bf16* x0 = (const bf16*)d_in[0];
  const bf16* mem0 = (const bf16*)d_in[1];
  const bf16* Wq = (const bf16*)d_in[2];
  const bf16* Wk = (const bf16*)d_in[3];
  const bf16* Wv = (const bf16*)d_in[4];
  const bf16* Wo = (const bf16*)d_in[5];
  const bf16* Bqkv = (const bf16*)d_in[8];
  const bf16* Bwo = (const bf16*)d_in[9];
  bf16* out = (bf16*)d_out;

  static EncodeFn enc = nullptr;
  if (!enc) {
    void* fn = nullptr;
    cudaDriverEntryPointQueryResult qr;
    cudaGetDriverEntryPoint("cuTensorMapEncodeTiled", &fn, cudaEnableDefault, &qr);
    enc = (EncodeFn)fn;
    cudaFuncSetAttribute(k_chain, cudaFuncAttributeMaxDynamicSharedMemorySize, C::SMEM);
    cudaFuncSetAttribute(k_work, cudaFuncAttributeMaxDynamicSharedMemorySize, W::SMEM);
  }
  CUtensorMap tmWq, tmWk, tmWv, tmWo, tmWp, tmBo;
  make_map(enc, &tmWq, Wq, NH * DH, DM, 64, 128);
  make_map(enc, &tmWk, Wk, NH * DH, DM, 64, 128);
  make_map(enc, &tmWv, Wv, NH * DH, DM, 64, 128);
  make_map(enc, &tmWo, Wo, DM, NH * DH, 64, 64);
  make_map(enc, &tmWp, Wo, DM, NH * DH, 64, 16);
  make_map(enc, &tmBo, Bwo, DM, DM, 64, 64);

  cudaStream_t st = cudaStreamPerThread;
  cudaLaunchAttribute at[1];
  at[0].id = cudaLaunchAttributeProgrammaticStreamSerialization; at[0].val.programmaticStreamSerializationAllowed = 1;
  {
    cudaLaunchConfig_t cfg = {};
    cfg.gridDim = dim3(96); cfg.blockDim = dim3(384); cfg.dynamicSmemBytes = C::SMEM; cfg.stream = st;
    cfg.attrs = at; cfg.numAttrs = 0;
    cudaLaunchKernelEx(&cfg, k_chain, tmWq, tmWk, tmWv, tmWo, x0, mem0);
  }
  cudaLaunchConfig_t cfg = {};
  cfg.gridDim = dim3(W::NW); cfg.blockDim = dim3(512); cfg.dynamicSmemBytes = W::SMEM; cfg.stream = st;
  cfg.attrs = at; cfg.numAttrs = NOWORK == 2 ? 0 : 1;
  cudaLaunchKernelEx(&cfg, k_work, tmWp, tmBo, Bqkv, out, x0, mem0);
}
```

```cpp
#include <cuda_runtime.h>
#include <cuda_bf16.h>
#include <cuda.h>
#include <stdint.h>

typedef __nv_bfloat16 bf16;

constexpr int SEQ = 2048, DM = 640, NH = 32, DH = 192, NSEG = 64;
#define LAG 5
constexpr int NSTEP = NSEG + LAG;
constexpr int NPRE = 4;
constexpr uint32_t SENT = 0xFFFFFFFFu;

constexpr int MAIL9 = 288 * 2048, MAIL_BYTES = MAIL9 + 64 * 3072;
__device__ __align__(1024) uint8_t g_xn[NSTEP][81920];
__device__ __align__(1024) uint8_t g_xnb[NSTEP][81920];
__device__ __align__(1024) uint8_t g_ob[NSTEP][81920];
__device__ __align__(1024) uint8_t g_y[2][NSEG * 40960];
#define ORING 8
static_assert(ORING > LAG, "a slot is free again LAG + 1 steps later");
__device__ __align__(1024) uint8_t g_o[ORING][96][8192];
__device__ __align__(1024) float g_x[SEQ * DM];
constexpr int EX_MAIL = 0;
constexpr int EX_M = 2 << 20;
constexpr int EX_FLAG = EX_M + NSTEP * 20480;
__host__ __device__ constexpr int m_tile(int j) { return (int)((0x9852741630ull >> (4 * j)) & 15); }
static_assert(EX_FLAG + NSTEP * 3072 <= (4 << 20), "");
__device__ __align__(1024) uint8_t g_ex[8 << 20];
__host__ __device__ __forceinline__ uint8_t* ex_window(uint8_t* p) { return reinterpret_cast<uint8_t*>((reinterpret_cast<uint64_t>(p) + (4 << 20) - 1) & ~(uint64_t)((4 << 20) - 1)); }
enum { CN_P = 0, CN_L = 128, CN_A = 256, CN_W = 384, CN_X = 512, CN_F = 640, CN_G = 768, CN_O = 896, CN_NUM = CN_O + 5 * NSTEP };
__device__ __align__(128) uint32_t g_cnt[CN_NUM][32];
__device__ __align__(128) uint32_t g_ticket[2][32];
__device__ int g_err;
#define TS(jj, i)
#define TS1(jj, i)
#define PTS(i)
#define TSB(jj, i)
#define TSV(jj, i, v)
#define TS_FLUSH(jj)
#define WTS(b, k)
#define WTS1(b, k)
#define WW -1

__device__ __forceinline__ uint32_t smem_u32(const void* p) { return (uint32_t)__cvta_generic_to_shared(p); }
__device__ __forceinline__ uint32_t clk32() { uint32_t t; asm volatile("mov.u32 %0, %%clock;" : "=r"(t)::"memory"); return t; }
__device__ __forceinline__ uint32_t mapa(uint32_t a, uint32_t r) { uint32_t o; asm("mapa.shared::cluster.u32 %0,%1,%2;" : "=r"(o) : "r"(a), "r"(r)); return o; }
__device__ __forceinline__ void mbar_init(uint32_t bar, uint32_t cnt) { asm volatile("mbarrier.init.shared::cta.b64 [%0],%1;" ::"r"(bar), "r"(cnt) : "memory"); }
__device__ __forceinline__ void mbar_expect_tx(uint32_t bar, uint32_t bytes) { asm volatile("mbarrier.arrive.expect_tx.shared::cta.b64 _,[%0],%1;" ::"r"(bar), "r"(bytes) : "memory"); }
__device__ __forceinline__ void mbar_arrive(uint32_t bar) { asm volatile("mbarrier.arrive.shared::cta.b64 _,[%0];" ::"r"(bar) : "memory"); }
__device__ __forceinline__ void mbar_arrive_cluster(uint32_t bar) { asm volatile("mbarrier.arrive.shared::cluster.b64 _,[%0];" ::"r"(bar) : "memory"); }
__device__ __forceinline__ bool mbar_try(uint32_t bar, uint32_t ph) {
  uint32_t ok;
  asm volatile("{.reg .pred p; mbarrier.try_wait.parity.shared::cta.b64 p,[%1],%2; selp.u32 %0,1,0,p;}" : "=r"(ok) : "r"(bar), "r"(ph) : "memory");
  return ok;
}
__device__ __forceinline__ bool mbar_test(uint32_t bar, uint32_t ph) {
  uint32_t ok;
  asm volatile("{.reg .pred p; mbarrier.test_wait.parity.shared::cta.b64 p,[%1],%2; selp.u32 %0,1,0,p;}" : "=r"(ok) : "r"(bar), "r"(ph) : "memory");
  return ok;
}
__device__ __forceinline__ int fresh(int x) { asm volatile("" : "+r"(x)); return x; }
#define PHASE_IDS const int tid = fresh(tid0), lane = tid & 31, w = tid >> 5, g = lane >> 2, t = lane & 3; (void)w; (void)g; (void)t
__device__ __forceinline__ void bar_sync(int id, int n) { asm volatile("bar.sync %0,%1;" ::"r"(id), "r"(n) : "memory"); }
__device__ __forceinline__ void bar_arrive(int id, int n) { asm volatile("bar.arrive %0,%1;" ::"r"(id), "r"(n) : "memory"); }
__device__ __forceinline__ bool bar_red_or(int id, int n, bool v) {
  uint32_t r;
  asm volatile("{\n .reg .pred p, q;\n setp.ne.u32 q, %3, 0;\n barrier.cta.red.or.pred p, %1, %2, q;\n selp.u32 %0, 1, 0, p;\n}" : "=r"(r) : "r"(id), "r"(n), "r"((uint32_t)v) : "memory");
  return r != 0;
}
__device__ __forceinline__ void fence_async() { asm volatile("fence.proxy.async.shared::cta;" ::: "memory"); }
__device__ __forceinline__ void bulk_g2s(uint32_t dst, const void* src, uint32_t bytes, uint32_t bar) {
  asm volatile("cp.async.bulk.shared::cluster.global.mbarrier::complete_tx::bytes [%0],[%1],%2,[%3];" ::"r"(dst), "l"(src), "r"(bytes), "r"(bar) : "memory");
}
__device__ __forceinline__ void bulk_g2s_mc(uint32_t dst, const void* src, uint32_t bytes, uint32_t bar) {
  asm volatile("cp.async.bulk.shared::cluster.global.mbarrier::complete_tx::bytes.multicast::cluster [%0],[%1],%2,[%3],%4;"
               ::"r"(dst), "l"(src), "r"(bytes), "r"(bar), "h"((uint16_t)7) : "memory");
}
__device__ __forceinline__ void bulk_s2g(void* dst, uint32_t src, uint32_t bytes) {
  asm volatile("cp.async.bulk.global.shared::cta.bulk_group [%0],[%1],%2;" ::"l"(dst), "r"(src), "r"(bytes) : "memory");
}
__device__ __forceinline__ void bulk_s2c(uint32_t dst, uint32_t src, uint32_t bytes, uint32_t bar) {
  asm volatile("cp.async.bulk.shared::cluster.shared::cta.mbarrier::complete_tx::bytes [%0],[%1],%2,[%3];" ::"r"(dst), "r"(src), "r"(bytes), "r"(bar) : "memory");
}
__device__ __forceinline__ void tma2d(uint32_t dst, const CUtensorMap* tm, int c0, int c1, uint32_t bar) {
  asm volatile("cp.async.bulk.tensor.2d.shared::cluster.global.mbarrier::complete_tx::bytes [%0],[%1,{%3,%4}],[%2];"
               ::"r"(dst), "l"(tm), "r"(bar), "r"(c0), "r"(c1) : "memory");
}
__device__ __forceinline__ void tma2d_prefetch(const CUtensorMap* tm, int c0, int c1) {
  asm volatile("cp.async.bulk.prefetch.tensor.2d.L2.global.tile [%0,{%1,%2}];" ::"l"(tm), "r"(c0), "r"(c1) : "memory");
}
__device__ __forceinline__ uint32_t pack_bf16(float lo, float hi) {
  uint32_t r; asm("cvt.rn.bf16x2.f32 %0,%1,%2;" : "=r"(r) : "f"(hi), "f"(lo)); return r;
}
__device__ __forceinline__ float bf_lo(uint32_t x) { return __uint_as_float(x << 16); }
__device__ __forceinline__ float bf_hi(uint32_t x) { return __uint_as_float(x & 0xFFFF0000u); }
__device__ __forceinline__ float ex2(float x) { float y; asm("ex2.approx.ftz.f32 %0,%1;" : "=f"(y) : "f"(x)); return y; }
__device__ __forceinline__ void ldsm4(uint32_t (&r)[4], uint32_t a) {
  asm volatile("ldmatrix.sync.aligned.m8n8.x4.shared.b16 {%0,%1,%2,%3},[%4];" : "=r"(r[0]), "=r"(r[1]), "=r"(r[2]), "=r"(r[3]) : "r"(a) : "memory");
}
__device__ __forceinline__ void ldsm4t(uint32_t (&r)[4], uint32_t a) {
  asm volatile("ldmatrix.sync.aligned.m8n8.x4.trans.shared.b16 {%0,%1,%2,%3},[%4];" : "=r"(r[0]), "=r"(r[1]), "=r"(r[2]), "=r"(r[3]) : "r"(a) : "memory");
}
__device__ __forceinline__ void ldsm2(uint32_t& r0, uint32_t& r1, uint32_t a) {
  asm volatile("ldmatrix.sync.aligned.m8n8.x2.shared.b16 {%0,%1},[%2];" : "=r"(r0), "=r"(r1) : "r"(a) : "memory");
}
__device__ __forceinline__ void ldsm2t(uint32_t& r0, uint32_t& r1, uint32_t a) {
  asm volatile("ldmatrix.sync.aligned.m8n8.x2.trans.shared.b16 {%0,%1},[%2];" : "=r"(r0), "=r"(r1) : "r"(a) : "memory");
}
__device__ __forceinline__ void ldsm1(uint32_t& r0, uint32_t a) {
  asm volatile("ldmatrix.sync.aligned.m8n8.x1.shared.b16 {%0},[%1];" : "=r"(r0) : "r"(a) : "memory");
}
__device__ __forceinline__ void mma16816(float (&d)[4], uint32_t a0, uint32_t a1, uint32_t a2, uint32_t a3, uint32_t b0, uint32_t b1) {
  asm volatile("mma.sync.aligned.m16n8k16.row.col.f32.bf16.bf16.f32 {%0,%1,%2,%3},{%4,%5,%6,%7},{%8,%9},{%0,%1,%2,%3};"
               : "+f"(d[0]), "+f"(d[1]), "+f"(d[2]), "+f"(d[3]) : "r"(a0), "r"(a1), "r"(a2), "r"(a3), "r"(b0), "r"(b1));
}
__device__ __forceinline__ void mma1688(float (&d)[4], uint32_t a0, uint32_t a1, uint32_t b0) {
  asm volatile("mma.sync.aligned.m16n8k8.row.col.f32.bf16.bf16.f32 {%0,%1,%2,%3},{%4,%5},{%6},{%0,%1,%2,%3};"
               : "+f"(d[0]), "+f"(d[1]), "+f"(d[2]), "+f"(d[3]) : "r"(a0), "r"(a1), "r"(b0));
}
__device__ __forceinline__ void sts32(uint32_t a, uint32_t v) { asm volatile("st.shared.b32 [%0],%1;" ::"r"(a), "r"(v) : "memory"); }
__device__ __forceinline__ void sts64f(uint32_t a, float x, float y) { asm volatile("st.shared.v2.f32 [%0],{%1,%2};" ::"r"(a), "f"(x), "f"(y) : "memory"); }
__device__ __forceinline__ void sts128(uint32_t a, uint4 v) { asm volatile("st.shared.v4.b32 [%0],{%1,%2,%3,%4};" ::"r"(a), "r"(v.x), "r"(v.y), "r"(v.z), "r"(v.w) : "memory"); }
__device__ __forceinline__ float lds32f(uint32_t a) { float v; asm volatile("ld.shared.f32 %0,[%1];" : "=f"(v) : "r"(a) : "memory"); return v; }
__device__ __forceinline__ float2 lds64f(uint32_t a) { float2 v; asm volatile("ld.shared.v2.f32 {%0,%1},[%2];" : "=f"(v.x), "=f"(v.y) : "r"(a) : "memory"); return v; }
__device__ __forceinline__ uint4 lds128(uint32_t a) { uint4 v; asm volatile("ld.shared.v4.b32 {%0,%1,%2,%3},[%4];" : "=r"(v.x), "=r"(v.y), "=r"(v.z), "=r"(v.w) : "r"(a) : "memory"); return v; }
__device__ __forceinline__ float4 lds128f(uint32_t a) { float4 v; asm volatile("ld.shared.v4.f32 {%0,%1,%2,%3},[%4];" : "=f"(v.x), "=f"(v.y), "=f"(v.z), "=f"(v.w) : "r"(a) : "memory"); return v; }
__device__ __forceinline__ void st_async2(uint32_t a, float x, float y, uint32_t bar) {
  asm volatile("st.async.weak.shared::cluster.mbarrier::complete_tx::bytes.v2.f32 [%0],{%1,%2},[%3];" ::"r"(a), "f"(x), "f"(y), "r"(bar) : "memory");
}
__device__ __forceinline__ void st_async4(uint32_t a, const float (&v)[4], uint32_t bar) {
  asm volatile("st.async.weak.shared::cluster.mbarrier::complete_tx::bytes.v4.f32 [%0],{%1,%2,%3,%4},[%5];" ::"r"(a), "f"(v[0]), "f"(v[1]), "f"(v[2]), "f"(v[3]), "r"(bar) : "memory");
}
__device__ __forceinline__ void st_async4v(uint32_t a, float x, float y, float z, float w, uint32_t bar) {
  asm volatile("st.async.weak.shared::cluster.mbarrier::complete_tx::bytes.v4.f32 [%0],{%1,%2,%3,%4},[%5];" ::"r"(a), "f"(x), "f"(y), "f"(z), "f"(w), "r"(bar) : "memory");
}
__device__ __forceinline__ void st_async4u(uint32_t a, const uint4& v, uint32_t bar) {
  asm volatile("st.async.weak.shared::cluster.mbarrier::complete_tx::bytes.v4.b32 [%0],{%1,%2,%3,%4},[%5];" ::"r"(a), "r"(v.x), "r"(v.y), "r"(v.z), "r"(v.w), "r"(bar) : "memory");
}
__device__ __forceinline__ uint4 ld_relaxed4(const void* p) {
  uint4 v; asm volatile("ld.relaxed.gpu.global.v4.u32 {%0,%1,%2,%3},[%4];" : "=r"(v.x), "=r"(v.y), "=r"(v.z), "=r"(v.w) : "l"(p) : "memory"); return v;
}
__device__ __forceinline__ uint32_t ld_relaxed(const void* p) {
  uint32_t v; asm volatile("ld.relaxed.gpu.global.u32 %0,[%1];" : "=r"(v) : "l"(p) : "memory"); return v;
}
__device__ __forceinline__ void st_relaxed(void* p, uint32_t v) { asm volatile("st.relaxed.gpu.global.b32 [%0],%1;" ::"l"(p), "r"(v) : "memory"); }
__device__ __forceinline__ void st_relaxed4(void* p, uint32_t v) { asm volatile("st.relaxed.gpu.global.v4.b32 [%0],{%1,%1,%1,%1};" ::"l"(p), "r"(v) : "memory"); }

__device__ __forceinline__ uint32_t ld_acquire(const void* p) {
  uint32_t v; asm volatile("ld.acquire.gpu.global.u32 %0,[%1];" : "=r"(v) : "l"(p) : "memory"); return v;
}
__device__ __forceinline__ float4 ld_relaxed4f(const void* p) {
  float4 v; asm volatile("ld.relaxed.gpu.global.v4.f32 {%0,%1,%2,%3},[%4];" : "=f"(v.x), "=f"(v.y), "=f"(v.z), "=f"(v.w) : "l"(p) : "memory"); return v;
}
__device__ __forceinline__ float2 ld_relaxed2f(const void* p) {
  float2 v; asm volatile("ld.relaxed.gpu.global.v2.f32 {%0,%1},[%2];" : "=f"(v.x), "=f"(v.y) : "l"(p) : "memory"); return v;
}
__device__ __forceinline__ void prefetch_l2(const void* p) { asm volatile("prefetch.global.L2 [%0];" ::"l"(p)); }
__device__ __forceinline__ void fence_gpu() { asm volatile("fence.acq_rel.gpu;" ::: "memory"); }
__device__ __forceinline__ void fence_async_all() { asm volatile("fence.proxy.async.global;" ::: "memory"); }
constexpr int SPIN_TOT = 1 << 22;
__device__ __forceinline__ void csignal(int idx) { asm volatile("red.release.gpu.global.add.u32 [%0],1;" ::"l"(&g_cnt[idx][0]) : "memory"); }
__device__ __forceinline__ void csignal_fast(int idx) { asm volatile("red.relaxed.gpu.global.add.u32 [%0],1;" ::"l"(&g_cnt[idx][0]) : "memory"); }
#define RLX 1
#define csignal_t(idx, role) csignal(idx)
__device__ __forceinline__ void cwait(int idx, uint32_t target, int& spin) {
  while (ld_relaxed(&g_cnt[idx][0]) < target && spin < SPIN_TOT) spin += 16;
}

__device__ __forceinline__ uint64_t mkdesc(uint32_t addr, uint32_t lbo, uint32_t sbo) {
  return (uint64_t)((addr & 0x3FFFF) >> 4) | ((uint64_t)(lbo >> 4) << 16) | ((uint64_t)(sbo >> 4) << 32) | ((uint64_t)1 << 62);
}
__device__ __forceinline__ uint64_t mkdesc_ns(uint32_t addr, uint32_t lbo, uint32_t sbo) {
  return (uint64_t)((addr & 0x3FFFF) >> 4) | ((uint64_t)(lbo >> 4) << 16) | ((uint64_t)(sbo >> 4) << 32);
}
__device__ __forceinline__ void wg_fence() { asm volatile("wgmma.fence.sync.aligned;" ::: "memory"); }
__device__ __forceinline__ void wg_commit() { asm volatile("wgmma.commit_group.sync.aligned;" ::: "memory"); }
template <int N> __device__ __forceinline__ void wg_wait() { asm volatile("wgmma.wait_group.sync.aligned %0;" ::"n"(N) : "memory"); }

__device__ __forceinline__ void wgmma_rs16(float (&d)[8], const uint32_t (&a)[4], uint64_t db, int sc) {
  asm volatile("{.reg .pred p; setp.ne.b32 p,%13,0; wgmma.mma_async.sync.aligned.m64n16k16.f32.bf16.bf16 "
               "{%0,%1,%2,%3,%4,%5,%6,%7},{%8,%9,%10,%11},%12,p,1,1,0;}"
               : "+f"(d[0]), "+f"(d[1]), "+f"(d[2]), "+f"(d[3]), "+f"(d[4]), "+f"(d[5]), "+f"(d[6]), "+f"(d[7])
               : "r"(a[0]), "r"(a[1]), "r"(a[2]), "r"(a[3]), "l"(db), "r"(sc));
}
__device__ __forceinline__ void wgmma_rs64(float (&d)[32], const uint32_t (&a)[4], uint64_t db, int sc) {
  asm volatile("{.reg .pred p; setp.ne.b32 p,%37,0; wgmma.mma_async.sync.aligned.m64n64k16.f32.bf16.bf16 "
               "{%0,%1,%2,%3,%4,%5,%6,%7,%8,%9,%10,%11,%12,%13,%14,%15,%16,%17,%18,%19,%20,%21,%22,%23,%24,%25,%26,%27,%28,%29,%30,%31},{%32,%33,%34,%35},%36,p,1,1,0;}"
               : "+f"(d[0]), "+f"(d[1]), "+f"(d[2]), "+f"(d[3]), "+f"(d[4]), "+f"(d[5]), "+f"(d[6]), "+f"(d[7]), "+f"(d[8]), "+f"(d[9]), "+f"(d[10]), "+f"(d[11]), "+f"(d[12]), "+f"(d[13]), "+f"(d[14]), "+f"(d[15]), "+f"(d[16]), "+f"(d[17]), "+f"(d[18]), "+f"(d[19]), "+f"(d[20]), "+f"(d[21]), "+f"(d[22]), "+f"(d[23]), "+f"(d[24]), "+f"(d[25]), "+f"(d[26]), "+f"(d[27]), "+f"(d[28]), "+f"(d[29]), "+f"(d[30]), "+f"(d[31])
               : "r"(a[0]), "r"(a[1]), "r"(a[2]), "r"(a[3]), "l"(db), "r"(sc));
}
__device__ __forceinline__ void wgmma_rt16(float (&d)[8], const uint32_t (&a)[4], uint64_t db, int sc) {
  asm volatile("{.reg .pred p; setp.ne.b32 p,%13,0; wgmma.mma_async.sync.aligned.m64n16k16.f32.bf16.bf16 "
               "{%0,%1,%2,%3,%4,%5,%6,%7},{%8,%9,%10,%11},%12,p,1,1,1;}"
               : "+f"(d[0]), "+f"(d[1]), "+f"(d[2]), "+f"(d[3]), "+f"(d[4]), "+f"(d[5]), "+f"(d[6]), "+f"(d[7])
               : "r"(a[0]), "r"(a[1]), "r"(a[2]), "r"(a[3]), "l"(db), "r"(sc));
}
__device__ __forceinline__ void wgmma_rt80(float (&d)[40], const uint32_t (&a)[4], uint64_t db, int sc) {
  asm volatile("{.reg .pred p; setp.ne.b32 p,%45,0; wgmma.mma_async.sync.aligned.m64n80k16.f32.bf16.bf16 "
               "{%0,%1,%2,%3,%4,%5,%6,%7,%8,%9,%10,%11,%12,%13,%14,%15,%16,%17,%18,%19,%20,%21,%22,%23,%24,%25,%26,%27,%28,%29,%30,%31,%32,%33,%34,%35,%36,%37,%38,%39},{%40,%41,%42,%43},%44,p,1,1,1;}"
               : "+f"(d[0]), "+f"(d[1]), "+f"(d[2]), "+f"(d[3]), "+f"(d[4]), "+f"(d[5]), "+f"(d[6]), "+f"(d[7]), "+f"(d[8]), "+f"(d[9]), "+f"(d[10]), "+f"(d[11]), "+f"(d[12]), "+f"(d[13]), "+f"(d[14]), "+f"(d[15]), "+f"(d[16]), "+f"(d[17]), "+f"(d[18]), "+f"(d[19]), "+f"(d[20]), "+f"(d[21]), "+f"(d[22]), "+f"(d[23]), "+f"(d[24]), "+f"(d[25]), "+f"(d[26]), "+f"(d[27]), "+f"(d[28]), "+f"(d[29]), "+f"(d[30]), "+f"(d[31]), "+f"(d[32]), "+f"(d[33]), "+f"(d[34]), "+f"(d[35]), "+f"(d[36]), "+f"(d[37]), "+f"(d[38]), "+f"(d[39])
               : "r"(a[0]), "r"(a[1]), "r"(a[2]), "r"(a[3]), "l"(db), "r"(sc));
}
__device__ __forceinline__ void wgmma_rs32(float (&d)[16], const uint32_t (&a)[4], uint64_t db, int sc) {
  asm volatile("{.reg .pred p; setp.ne.b32 p,%21,0; wgmma.mma_async.sync.aligned.m64n32k16.f32.bf16.bf16 "
               "{%0,%1,%2,%3,%4,%5,%6,%7,%8,%9,%10,%11,%12,%13,%14,%15},{%16,%17,%18,%19},%20,p,1,1,0;}"
               : "+f"(d[0]), "+f"(d[1]), "+f"(d[2]), "+f"(d[3]), "+f"(d[4]), "+f"(d[5]), "+f"(d[6]), "+f"(d[7]), "+f"(d[8]), "+f"(d[9]), "+f"(d[10]), "+f"(d[11]), "+f"(d[12]), "+f"(d[13]), "+f"(d[14]), "+f"(d[15])
               : "r"(a[0]), "r"(a[1]), "r"(a[2]), "r"(a[3]), "l"(db), "r"(sc));
}
__device__ __forceinline__ void wgmma_ts32(float (&d)[16], uint64_t da, uint64_t db, int sc) {
  asm volatile("{.reg .pred p; setp.ne.b32 p,%18,0; wgmma.mma_async.sync.aligned.m64n32k16.f32.bf16.bf16 "
               "{%0,%1,%2,%3,%4,%5,%6,%7,%8,%9,%10,%11,%12,%13,%14,%15},%16,%17,p,1,1,1,0;}"
               : "+f"(d[0]), "+f"(d[1]), "+f"(d[2]), "+f"(d[3]), "+f"(d[4]), "+f"(d[5]), "+f"(d[6]), "+f"(d[7]), "+f"(d[8]), "+f"(d[9]), "+f"(d[10]), "+f"(d[11]), "+f"(d[12]), "+f"(d[13]), "+f"(d[14]), "+f"(d[15])
               : "l"(da), "l"(db), "r"(sc));
}
__device__ __forceinline__ void wgmma_rs8(float (&d)[4], const uint32_t (&a)[4], uint64_t db, int sc) {
  asm volatile("{.reg .pred p; setp.ne.b32 p,%9,0; wgmma.mma_async.sync.aligned.m64n8k16.f32.bf16.bf16 "
               "{%0,%1,%2,%3},{%4,%5,%6,%7},%8,p,1,1,0;}"
               : "+f"(d[0]), "+f"(d[1]), "+f"(d[2]), "+f"(d[3])
               : "r"(a[0]), "r"(a[1]), "r"(a[2]), "r"(a[3]), "l"(db), "r"(sc));
}
__device__ __forceinline__ void wgmma_tt32(float (&d)[16], uint64_t da, uint64_t db, int sc) {
  asm volatile("{.reg .pred p; setp.ne.b32 p,%18,0; wgmma.mma_async.sync.aligned.m64n32k16.f32.bf16.bf16 "
               "{%0,%1,%2,%3,%4,%5,%6,%7,%8,%9,%10,%11,%12,%13,%14,%15},%16,%17,p,1,1,1,1;}"
               : "+f"(d[0]), "+f"(d[1]), "+f"(d[2]), "+f"(d[3]), "+f"(d[4]), "+f"(d[5]), "+f"(d[6]), "+f"(d[7]), "+f"(d[8]), "+f"(d[9]), "+f"(d[10]), "+f"(d[11]), "+f"(d[12]), "+f"(d[13]), "+f"(d[14]), "+f"(d[15])
               : "l"(da), "l"(db), "r"(sc));
}
__device__ __forceinline__ void wgmma_ts16(float (&d)[8], uint64_t da, uint64_t db, int sc) {
  asm volatile("{.reg .pred p; setp.ne.b32 p,%10,0; wgmma.mma_async.sync.aligned.m64n16k16.f32.bf16.bf16 "
               "{%0,%1,%2,%3,%4,%5,%6,%7},%8,%9,p,1,1,1,0;}"
               : "+f"(d[0]), "+f"(d[1]), "+f"(d[2]), "+f"(d[3]), "+f"(d[4]), "+f"(d[5]), "+f"(d[6]), "+f"(d[7])
               : "l"(da), "l"(db), "r"(sc));
}
__device__ __forceinline__ void wgmma_ts64(float (&d)[32], uint64_t da, uint64_t db, int sc) {
  asm volatile("{.reg .pred p; setp.ne.b32 p,%34,0; wgmma.mma_async.sync.aligned.m64n64k16.f32.bf16.bf16 "
               "{%0,%1,%2,%3,%4,%5,%6,%7,%8,%9,%10,%11,%12,%13,%14,%15,%16,%17,%18,%19,%20,%21,%22,%23,%24,%25,%26,%27,%28,%29,%30,%31},%32,%33,p,1,1,1,0;}"
               : "+f"(d[0]), "+f"(d[1]), "+f"(d[2]), "+f"(d[3]), "+f"(d[4]), "+f"(d[5]), "+f"(d[6]), "+f"(d[7]), "+f"(d[8]), "+f"(d[9]), "+f"(d[10]), "+f"(d[11]), "+f"(d[12]), "+f"(d[13]), "+f"(d[14]), "+f"(d[15]), "+f"(d[16]), "+f"(d[17]), "+f"(d[18]), "+f"(d[19]), "+f"(d[20]), "+f"(d[21]), "+f"(d[22]), "+f"(d[23]), "+f"(d[24]), "+f"(d[25]), "+f"(d[26]), "+f"(d[27]), "+f"(d[28]), "+f"(d[29]), "+f"(d[30]), "+f"(d[31])
               : "l"(da), "l"(db), "r"(sc));
}
__device__ __forceinline__ void wgmma_tt16(float (&d)[8], uint64_t da, uint64_t db, int sc) {
  asm volatile("{.reg .pred p; setp.ne.b32 p,%10,0; wgmma.mma_async.sync.aligned.m64n16k16.f32.bf16.bf16 "
               "{%0,%1,%2,%3,%4,%5,%6,%7},%8,%9,p,1,1,1,1;}"
               : "+f"(d[0]), "+f"(d[1]), "+f"(d[2]), "+f"(d[3]), "+f"(d[4]), "+f"(d[5]), "+f"(d[6]), "+f"(d[7])
               : "l"(da), "l"(db), "r"(sc));
}
__device__ __forceinline__ void wgmma_tt40(float (&d)[20], uint64_t da, uint64_t db, int sc) {
  asm volatile("{.reg .pred p; setp.ne.b32 p,%22,0; wgmma.mma_async.sync.aligned.m64n40k16.f32.bf16.bf16 "
               "{%0,%1,%2,%3,%4,%5,%6,%7,%8,%9,%10,%11,%12,%13,%14,%15,%16,%17,%18,%19},%20,%21,p,1,1,1,1;}"
               : "+f"(d[0]), "+f"(d[1]), "+f"(d[2]), "+f"(d[3]), "+f"(d[4]), "+f"(d[5]), "+f"(d[6]), "+f"(d[7]), "+f"(d[8]), "+f"(d[9]), "+f"(d[10]), "+f"(d[11]), "+f"(d[12]), "+f"(d[13]), "+f"(d[14]), "+f"(d[15]), "+f"(d[16]), "+f"(d[17]), "+f"(d[18]), "+f"(d[19])
               : "l"(da), "l"(db), "r"(sc));
}
__device__ __forceinline__ void wgmma_ss8(float (&d)[4], uint64_t da, uint64_t db, int sc) {
  asm volatile("{.reg .pred p; setp.ne.b32 p,%6,0; wgmma.mma_async.sync.aligned.m64n8k16.f32.bf16.bf16 "
               "{%0,%1,%2,%3},%4,%5,p,1,1,0,0;}"
               : "+f"(d[0]), "+f"(d[1]), "+f"(d[2]), "+f"(d[3])
               : "l"(da), "l"(db), "r"(sc));
}
__device__ __forceinline__ void wgmma_ss32(float (&d)[16], uint64_t da, uint64_t db, int sc) {
  asm volatile("{.reg .pred p; setp.ne.b32 p,%18,0; wgmma.mma_async.sync.aligned.m64n32k16.f32.bf16.bf16 "
               "{%0,%1,%2,%3,%4,%5,%6,%7,%8,%9,%10,%11,%12,%13,%14,%15},%16,%17,p,1,1,0,0;}"
               : "+f"(d[0]), "+f"(d[1]), "+f"(d[2]), "+f"(d[3]), "+f"(d[4]), "+f"(d[5]), "+f"(d[6]), "+f"(d[7]), "+f"(d[8]), "+f"(d[9]), "+f"(d[10]), "+f"(d[11]), "+f"(d[12]), "+f"(d[13]), "+f"(d[14]), "+f"(d[15])
               : "l"(da), "l"(db), "r"(sc));
}
__device__ __forceinline__ void wgmma_st64(float (&d)[32], uint64_t da, uint64_t db, int sc) {
  asm volatile("{.reg .pred p; setp.ne.b32 p,%34,0; wgmma.mma_async.sync.aligned.m64n64k16.f32.bf16.bf16 "
               "{%0,%1,%2,%3,%4,%5,%6,%7,%8,%9,%10,%11,%12,%13,%14,%15,%16,%17,%18,%19,%20,%21,%22,%23,%24,%25,%26,%27,%28,%29,%30,%31},%32,%33,p,1,1,0,1;}"
               : "+f"(d[0]), "+f"(d[1]), "+f"(d[2]), "+f"(d[3]), "+f"(d[4]), "+f"(d[5]), "+f"(d[6]), "+f"(d[7]), "+f"(d[8]), "+f"(d[9]), "+f"(d[10]), "+f"(d[11]), "+f"(d[12]), "+f"(d[13]), "+f"(d[14]), "+f"(d[15]), "+f"(d[16]), "+f"(d[17]), "+f"(d[18]), "+f"(d[19]), "+f"(d[20]), "+f"(d[21]), "+f"(d[22]), "+f"(d[23]), "+f"(d[24]), "+f"(d[25]), "+f"(d[26]), "+f"(d[27]), "+f"(d[28]), "+f"(d[29]), "+f"(d[30]), "+f"(d[31])
               : "l"(da), "l"(db), "r"(sc));
}
__device__ __forceinline__ void wgmma_st128(float (&d)[64], uint64_t da, uint64_t db, int sc) {
  asm volatile("{.reg .pred p; setp.ne.b32 p,%66,0; wgmma.mma_async.sync.aligned.m64n128k16.f32.bf16.bf16 "
               "{%0,%1,%2,%3,%4,%5,%6,%7,%8,%9,%10,%11,%12,%13,%14,%15,%16,%17,%18,%19,%20,%21,%22,%23,%24,%25,%26,%27,%28,%29,%30,%31,%32,%33,%34,%35,%36,%37,%38,%39,%40,%41,%42,%43,%44,%45,%46,%47,%48,%49,%50,%51,%52,%53,%54,%55,%56,%57,%58,%59,%60,%61,%62,%63},%64,%65,p,1,1,0,1;}"
               : "+f"(d[0]), "+f"(d[1]), "+f"(d[2]), "+f"(d[3]), "+f"(d[4]), "+f"(d[5]), "+f"(d[6]), "+f"(d[7]), "+f"(d[8]), "+f"(d[9]), "+f"(d[10]), "+f"(d[11]), "+f"(d[12]), "+f"(d[13]), "+f"(d[14]), "+f"(d[15]), "+f"(d[16]), "+f"(d[17]), "+f"(d[18]), "+f"(d[19]), "+f"(d[20]), "+f"(d[21]), "+f"(d[22]), "+f"(d[23]), "+f"(d[24]), "+f"(d[25]), "+f"(d[26]), "+f"(d[27]), "+f"(d[28]), "+f"(d[29]), "+f"(d[30]), "+f"(d[31]), "+f"(d[32]), "+f"(d[33]), "+f"(d[34]), "+f"(d[35]), "+f"(d[36]), "+f"(d[37]), "+f"(d[38]), "+f"(d[39]), "+f"(d[40]), "+f"(d[41]), "+f"(d[42]), "+f"(d[43]), "+f"(d[44]), "+f"(d[45]), "+f"(d[46]), "+f"(d[47]), "+f"(d[48]), "+f"(d[49]), "+f"(d[50]), "+f"(d[51]), "+f"(d[52]), "+f"(d[53]), "+f"(d[54]), "+f"(d[55]), "+f"(d[56]), "+f"(d[57]), "+f"(d[58]), "+f"(d[59]), "+f"(d[60]), "+f"(d[61]), "+f"(d[62]), "+f"(d[63])
               : "l"(da), "l"(db), "r"(sc));
}

__device__ __forceinline__ void stsm4(uint32_t a, uint32_t r0, uint32_t r1, uint32_t r2, uint32_t r3) {
  asm volatile("stmatrix.sync.aligned.m8n8.x4.shared.b16 [%0],{%1,%2,%3,%4};" ::"r"(a), "r"(r0), "r"(r1), "r"(r2), "r"(r3) : "memory");
}
__device__ __forceinline__ void stsm4t(uint32_t a, uint32_t r0, uint32_t r1, uint32_t r2, uint32_t r3) {
  asm volatile("stmatrix.sync.aligned.m8n8.x4.trans.shared.b16 [%0],{%1,%2,%3,%4};" ::"r"(a), "r"(r0), "r"(r1), "r"(r2), "r"(r3) : "memory");
}
__device__ __forceinline__ void stsm2t(uint32_t a, uint32_t r0, uint32_t r1) {
  asm volatile("stmatrix.sync.aligned.m8n8.x2.trans.shared.b16 [%0],{%1,%2};" ::"r"(a), "r"(r0), "r"(r1) : "memory");
}
__device__ __forceinline__ void sts64(uint32_t a, uint32_t x, uint32_t y) { asm volatile("st.shared.v2.b32 [%0],{%1,%2};" ::"r"(a), "r"(x), "r"(y) : "memory"); }
__device__ __forceinline__ void st_async2u(uint32_t a, uint32_t x, uint32_t y, uint32_t bar) {
  asm volatile("st.async.weak.shared::cluster.mbarrier::complete_tx::bytes.v2.b32 [%0],{%1,%2},[%3];" ::"r"(a), "r"(x), "r"(y), "r"(bar) : "memory");
}
__device__ __forceinline__ void st_relaxed128(void* p, uint32_t x, uint32_t y, uint32_t z, uint32_t w) {
  asm volatile("{.reg .b128 v; mov.b128 v,{%1,%2,%3,%4}; st.relaxed.gpu.global.b128 [%0],v;}" ::"l"(p), "r"(x), "r"(y), "r"(z), "r"(w) : "memory");
}
__device__ __forceinline__ void st_relaxed16(void* p, uint32_t x) { asm volatile("st.relaxed.gpu.global.b16 [%0],%1;" ::"l"(p), "h"((uint16_t)x) : "memory"); }
__device__ __forceinline__ void st_relaxed64(void* p, uint32_t x, uint32_t y) {
  asm volatile("{.reg .b64 v; mov.b64 v,{%1,%2}; st.relaxed.gpu.global.b64 [%0],v;}" ::"l"(p), "r"(x), "r"(y) : "memory");
}
__device__ __forceinline__ uint4 ld_relaxed128(const void* p) {
  uint4 v;
  asm volatile("{.reg .b128 v; .reg .b64 lo, hi; ld.relaxed.gpu.global.b128 v,[%4]; mov.b128 {lo,hi},v; mov.b64 {%0,%1},lo; mov.b64 {%2,%3},hi;}" : "=r"(v.x), "=r"(v.y), "=r"(v.z), "=r"(v.w) : "l"(p) : "memory");
  return v;
}

__device__ __forceinline__ uint32_t pack_h2(float lo, float hi) {
  uint32_t r; asm("cvt.rn.satfinite.f16x2.f32 %0,%1,%2;" : "=r"(r) : "f"(hi), "f"(lo)); return r;
}
__device__ __forceinline__ void add_h2(float& lo, float& hi, uint32_t u, uint32_t v) {
  float a, b;
  asm("{.reg .b16 l, h; .reg .b32 s; add.rn.f16x2 s,%2,%3; mov.b32 {l,h},s; cvt.f32.f16 %0,l; cvt.f32.f16 %1,h;}" : "=f"(a), "=f"(b) : "r"(u), "r"(v));
  lo += a; hi += b;
}
__device__ __forceinline__ void mwait(uint32_t bar, uint32_t ph, int& spin) {
  asm volatile("{.reg .pred p, q;\nWAIT_LOOP:\n add.s32 %0,%0,1;\n setp.lt.s32 q,%0,%3;\n mbarrier.try_wait.parity.shared::cta.b64 p,[%1],%2;\n not.pred p,p;\n and.pred q,q,p;\n @q bra.uni WAIT_LOOP;\n}"
               : "+&r"(spin) : "r"(bar), "r"(ph), "n"(SPIN_TOT) : "memory");
}
__device__ __forceinline__ int keep(int x) { return __shfl_sync(0xffffffffu, x, threadIdx.x & 31); }
__device__ __forceinline__ uint32_t pin(uint32_t x) { asm volatile("" : "+r"(x)); return x; }
template <typename T> __device__ __forceinline__ T* pinp(T* x) { asm volatile("" : "+l"(x)); return x; }
__device__ __forceinline__ void st_async1u(uint32_t a, uint32_t x, uint32_t bar) {
  asm volatile("st.async.weak.shared::cluster.mbarrier::complete_tx::bytes.b32 [%0],%1,[%2];" ::"r"(a), "r"(x), "r"(bar) : "memory");
}
__device__ __forceinline__ uint32_t lds32(uint32_t a) { uint32_t v; asm volatile("ld.shared.b32 %0,[%1];" : "=r"(v) : "r"(a) : "memory"); return v; }
__device__ __forceinline__ uint2 lds64(uint32_t a) { uint2 v; asm volatile("ld.shared.v2.b32 {%0,%1},[%2];" : "=r"(v.x), "=r"(v.y) : "r"(a) : "memory"); return v; }

__device__ __forceinline__ void permute_cols(uint32_t tile, int tid, int n) {
#pragma unroll 2
  for (int it = tid; it < n; it += 128) {
    const int row = it >> 2, q = it & 3;
    const uint32_t a0 = tile + row * 128 + (((2 * q) ^ (row & 7)) << 4), a1 = tile + row * 128 + (((2 * q + 1) ^ (row & 7)) << 4);
    const uint4 u = lds128(a0), v = lds128(a1);
    sts128(a0, make_uint4(__byte_perm(u.x, u.y, 0x5410), __byte_perm(u.z, u.w, 0x5410), __byte_perm(v.x, v.y, 0x5410), __byte_perm(v.z, v.w, 0x5410)));
    sts128(a1, make_uint4(__byte_perm(u.x, u.y, 0x7632), __byte_perm(u.z, u.w, 0x7632), __byte_perm(v.x, v.y, 0x7632), __byte_perm(v.z, v.w, 0x7632)));
  }
}

__device__ __forceinline__ uint8_t* mkptr(uint32_t lo, uint32_t hi) { uint8_t* p; asm("mov.b64 %0,{%1,%2};" : "=l"(p) : "r"(lo), "r"(hi)); return p; }
__device__ __forceinline__ int uni(int x) { return __shfl_sync(0xffffffffu, x, 0); }

__device__ __forceinline__ bool elect_one() {
  uint32_t p; asm volatile("{.reg .pred q; elect.sync _|q, 0xffffffff; selp.u32 %0,1,0,q;}" : "=r"(p)); return p;
}
__device__ __forceinline__ uint64_t desc_at(uint64_t d, uint32_t off) {
  uint64_t r; asm("mov.b64 %0,{%1,%2};" : "=l"(r) : "r"((uint32_t)d + (off >> 4)), "r"((uint32_t)(d >> 32))); return r;
}
__device__ __forceinline__ uint32_t scale_bf16x2(uint32_t x, uint32_t s) { uint32_t r; asm("mul.rn.bf16x2 %0,%1,%2;" : "=r"(r) : "r"(x), "r"(s)); return r; }

__device__ __forceinline__ void stg128(void* p, const uint4& v) { asm volatile("st.global.v4.b32 [%0],{%1,%2,%3,%4};" ::"l"(p), "r"(v.x), "r"(v.y), "r"(v.z), "r"(v.w) : "memory"); }

__device__ __forceinline__ void elect_g2s_mc(uint32_t dst, const void* src, uint32_t bytes, uint32_t bar) {
  asm volatile("{.reg .pred p; elect.sync _|p, 0xffffffff;\n"
               " @p cp.async.bulk.shared::cluster.global.mbarrier::complete_tx::bytes.multicast::cluster [%0],[%1],%2,[%3],%4;}"
               ::"r"(dst), "l"(src), "r"(bytes), "r"(bar), "h"((uint16_t)7) : "memory");
}
__device__ __forceinline__ void elect_s2c2(uint32_t dst0, uint32_t bar0, uint32_t dst1, uint32_t bar1, uint32_t src, uint32_t bytes) {
  asm volatile("{.reg .pred p; elect.sync _|p, 0xffffffff;\n"
               " @p cp.async.bulk.shared::cluster.shared::cta.mbarrier::complete_tx::bytes [%0],[%4],%5,[%1];\n"
               " @p cp.async.bulk.shared::cluster.shared::cta.mbarrier::complete_tx::bytes [%2],[%4],%5,[%3];}"
               ::"r"(dst0), "r"(bar0), "r"(dst1), "r"(bar1), "r"(src), "r"(bytes) : "memory");
}
__device__ __forceinline__ void fill_stage(uint32_t dst, const void* src, uint32_t bytes, uint32_t bar) {
  asm volatile("{.reg .pred p; elect.sync _|p, 0xffffffff;\n"
               " @p cp.async.bulk.shared::cluster.global.mbarrier::complete_tx::bytes [%0],[%1],%2,[%3];\n"
               " @p mbarrier.arrive.expect_tx.shared::cta.b64 _,[%3],%2;}" ::"r"(dst), "l"(src), "r"(bytes), "r"(bar) : "memory");
}
__device__ __forceinline__ void fill_stage2(uint32_t dst, const void* src0, const void* src1, uint32_t bar) {
  asm volatile("{.reg .pred p; elect.sync _|p, 0xffffffff;\n"
               " @p cp.async.bulk.shared::cluster.global.mbarrier::complete_tx::bytes [%0],[%1],4096,[%3];\n"
               " @p cp.async.bulk.shared::cluster.global.mbarrier::complete_tx::bytes [%0+4096],[%2],4096,[%3];\n"
               " @p mbarrier.arrive.expect_tx.shared::cta.b64 _,[%3],8192;}" ::"r"(dst), "l"(src0), "l"(src1), "r"(bar) : "memory");
}

__device__ __forceinline__ float quad_sum(float x) {
  const float a = __shfl_xor_sync(0xffffffffu, x, 1), b = __shfl_xor_sync(0xffffffffu, x, 2), c = __shfl_xor_sync(0xffffffffu, x, 3);
  return (x + a) + (b + c);
}
__device__ __forceinline__ float warp_sum(float x) {
  const uint32_t m = __reduce_max_sync(0xffffffffu, __float_as_uint(x) & 0x7FFFFFFFu), e = max(m >> 23, 25u);
  const int s = __reduce_add_sync(0xffffffffu, __float2int_rn(x * __uint_as_float((278 - e) << 23)));
  return fmaf(__uint_as_float(m), 0.f, (float)s * __uint_as_float((e - 24) << 23));
}
__device__ __forceinline__ void ln_row(float4 (&v)[5]) {
  float t0 = 0.f, t1 = 0.f;
#pragma unroll
  for (int m = 0; m < 5; m++) { t0 += v[m].x + v[m].y; t1 += v[m].z + v[m].w; }
  const float mean = warp_sum(t0 + t1) * (1.f / DM);
  float q0 = 0.f, q1 = 0.f, q2 = 0.f, q3 = 0.f;
#pragma unroll
  for (int m = 0; m < 5; m++) {
    v[m].x -= mean; v[m].y -= mean; v[m].z -= mean; v[m].w -= mean;
    q0 = fmaf(v[m].x, v[m].x, q0); q1 = fmaf(v[m].y, v[m].y, q1); q2 = fmaf(v[m].z, v[m].z, q2); q3 = fmaf(v[m].w, v[m].w, q3);
  }
  const float rs = rsqrtf(warp_sum((q0 + q1) + (q2 + q3)) * (1.f / DM) + 1e-5f);
#pragma unroll
  for (int m = 0; m < 5; m++) { v[m].x *= rs; v[m].y *= rs; v[m].z *= rs; v[m].w *= rs; }
}
__device__ __forceinline__ void ln0_load(const bf16* __restrict__ x, uint2 (&u)[5], int row, int lane) {
#pragma unroll
  for (int m = 0; m < 5; m++) u[m] = *reinterpret_cast<const uint2*>(x + (size_t)row * DM + m * 128 + lane * 4);
}
__device__ __forceinline__ void ln0_copy(const uint2 (&u)[5], int row, int lane) {
#pragma unroll
  for (int m = 0; m < 5; m++) stg128(g_x + (size_t)row * DM + m * 128 + lane * 4, make_uint4(u[m].x << 16, u[m].x & 0xFFFF0000u, u[m].y << 16, u[m].y & 0xFFFF0000u));
}
__device__ __forceinline__ void ln0_row(const uint2 (&u)[5], int row, int lane) {
  float4 v[5];
#pragma unroll
  for (int m = 0; m < 5; m++) v[m] = make_float4(bf_lo(u[m].x), bf_hi(u[m].x), bf_lo(u[m].y), bf_hi(u[m].y));
  ln_row(v);
  uint8_t* dst = g_xn[row >> 5] + ((row >> 3) & 3) * 4096 + (lane >> 4) * 1024 + (row & 7) * 128 + ((((lane >> 1) ^ row) & 7) << 4) + (lane & 1) * 8;
#pragma unroll
  for (int m = 0; m < 5; m++) *reinterpret_cast<uint2*>(dst + m * 16384) = make_uint2(pack_bf16(v[m].x, v[m].y), pack_bf16(v[m].z, v[m].w));
}

#define NOWORK 0
__device__ __forceinline__ void prep_row(const uint2 (&u)[5], const bf16* __restrict__ mem0, int k, int r, int lane) {
  const uint4 sent = make_uint4(SENT, SENT, SENT, SENT);
  if (k + 1 < NSTEP) {
    uint8_t* ex = ex_window(g_ex);
#pragma unroll
    for (int h = 0; h < 2; h++) {
      const int p = r * 40 + h * 32 + lane;
      if (h == 0 || lane < 8) {
        uint4 v = sent;
        if (k + 1 == LAG && (p & 8)) v = *reinterpret_cast<const uint4*>(mem0 + (p & 7) * DM + m_tile(p >> 7) * 64 + ((p >> 4) & 7) * 8);
        stg128(ex + EX_M + (k + 1) * 20480 + p * 16, v);
      } else if (lane < 14) stg128(ex + EX_FLAG + (k + 1) * 3072 + (r * 6 + lane - 8) * 16, sent);
    }
  }
  if (k < LAG || k >= NSEG || NOWORK) {
    uint8_t* z = g_xn[k] + (r >> 3) * 4096 + (k < NSEG ? 2048 : 0) + (lane >> 4) * 1024 + (r & 7) * 128 + (lane & 15) * 8;
#pragma unroll
    for (int m = 0; m < 5; m++) *reinterpret_cast<uint2*>(z + m * 16384) = make_uint2(0, 0);
  }
  if (k < NSEG) {
    ln0_copy(u, k * 32 + r, lane);
    ln0_row(u, k * 32 + r, lane);
  }
}
__device__ __forceinline__ void pre_work(const bf16* __restrict__ x, const bf16* __restrict__ mem0, int cta, int tid) {
  constexpr int NT = 96 * 128;
  const int gt = cta * 128 + tid;
  uint8_t* ex = ex_window(g_ex);
#pragma unroll 1
  for (int row = cta + 96 * (tid >> 5); row < (NOWORK == 2 ? NSTEP : NPRE) * 32; row += 384) {
    uint2 u[5];
    ln0_load(x, u, min(row, SEQ - 1), tid & 31);
    prep_row(u, mem0, row >> 5, row & 31, tid & 31);
  }
#pragma unroll 1
  for (int i = gt; i < MAIL_BYTES / 16; i += NT) {
    stg128(ex + EX_MAIL + i * 16, make_uint4(SENT, SENT, SENT, SENT));
    stg128(ex + EX_MAIL + (1 << 20) + i * 16, make_uint4(SENT, SENT, SENT, SENT));
  }
  const int p = NT - 1 - gt;
  if (p < 1280) stg128(ex + EX_M + p * 16, *reinterpret_cast<const uint4*>(mem0 + (p & 7) * DM + m_tile(p >> 7) * 64 + ((p >> 4) & 7) * 8));
  if (p < 192) stg128(ex + EX_FLAG + p * 16, make_uint4(0, 0, 0, 0));
  if (gt < 8 * CN_NUM) stg128(&g_cnt[0][0] + gt * 4, make_uint4(0, 0, 0, 0));
}
__device__ __forceinline__ void pre_wait(int which, uint32_t n, int& spin) {
  uint32_t old;
  asm volatile("atom.acq_rel.gpu.global.add.u32 %0,[%1],1;" : "=r"(old) : "l"(&g_ticket[which][0]) : "memory");
  const uint32_t target = (old / n + 1) * 96;
  while ((int)(ld_acquire(&g_ticket[0][0]) - target) < 0 && spin < SPIN_TOT) spin += 16;
  fence_async_all();
}

namespace C {
constexpr int NKR = 37;
constexpr int OFF_WQ = 0, OFF_WK = 81920;
constexpr int OFF_YO = 163840, OFF_YV = OFF_YO + 6144;
constexpr int OFF_M = 176128;
__host__ __device__ constexpr int og_off(int c) { return c ? OFF_M + 14336 + c * 2048 : 229376; }
constexpr int OFF_KT = 196608;
constexpr int OFF_XT = OFF_KT + 10240;
constexpr int OFF_VT = OFF_XT + 7168;
constexpr int OFF_XM = OFF_VT + 11392;
constexpr int OFF_PT = OFF_XM + 2560;
constexpr int KS = 1280, VS = 1408;
__host__ __device__ constexpr int slot_off(int p) { return p == 2 ? OFF_M : OFF_KT + (p % 3) * 16384; }
constexpr int OFF_ONE = 231424;
constexpr int OFF_BAR = 231552;
constexpr int OFF_SAFE = OFF_BAR + 144;
constexpr int OFF_TS = OFF_BAR + 256;
constexpr int SMEM = 232448;
constexpr uint32_t SB0 = 1024;
constexpr int BAR_F = OFF_BAR, BAR_XM = BAR_F + 40, BAR_XT = BAR_F + 48, BAR_OG = BAR_F + 56, BAR_E = OFF_BAR + 64, BAR_MOK = BAR_E + 40,
              BAR_M = OFF_BAR + 120, BAR_XF = OFF_BAR + 112, BAR_MF = OFF_BAR + 248, BAR_W = OFF_BAR + 208;
constexpr int NB_PRO = 1, NB_RD = 2, NB_MR = 3, NB_QK = 4, NB_SM = 5, NB_VA = 6, NB_VQ = 7, NB_A = 8, NB_Q = 9, NB_C = 10, NB_WQ = 11, NB_SI = 13, NB_WV = 14, NB_V = 15;
#define B1 600
#define AD0 32
#define AD1 128
#define AD2 16
#define AD3 128
#define BMX 1200
#define B2 800
#define FLP 1
#define OSG 2
#define OST 7
#define NBX 1
#define PVB 2
#define QPV 0
#define ONES 0
#define E0L 0
#define E2L 0
#define T2E 1
#define XMB 0
#define B3 0
#define OSV 0
#define XTD 0
#define VSL 2
#define VTI 4
#define T9L 0
#define SIE 2
#define WOE 1
#define OGF 2
#define VSP 8
#define RFK 5
#define PFD 3
#define WOL 0
constexpr uint32_t SCQ = 0x3A003A00;
constexpr float SCE = 0.07216878364870322f * 1.4426950408889634f * 2048;
}

#define CBAR_SYNC(id, n) bar_sync(id, n)
#define CBAR_ARRIVE(id, n) bar_arrive(id, n)

__device__ __forceinline__ uint64_t wdesc(int off) { return mkdesc(C::SB0 + off, 8192, 1024); }
__device__ __forceinline__ uint64_t mdesc(int k) { return mkdesc_ns(C::SB0 + C::OFF_M + k * 512, 256, 128); }
__device__ __forceinline__ uint64_t tdesc(int k) { return mkdesc(C::SB0 + C::slot_off(k >> 3) + ((k >> 2) & 1) * 1024 + (k & 3) * 32, 16, 2048); }

__device__ __forceinline__ int dh_row(int n) { return (n & ~63) + (n & 32) + ((n >> 1) & 3) * 8 + ((n >> 3) & 3) * 2 + (n & 1); }
template <bool IS_O>
__device__ __forceinline__ void stage_box(const CUtensorMap& tm, uint32_t sb, int p, int cta, int rank) {
  using namespace C;
  const uint32_t bar = sb + BAR_W + 8 * p;
  const int head = cta / 3, col = head * DH + rank * 64;
  mbar_expect_tx(bar, 16384);
  if (!IS_O) tma2d(sb + OFF_WK + p * 16384, &tm, col, p * 128, bar);
  else for (int b = 2 * p - 1; b <= 2 * p; b++)
    tma2d(sb + OFF_WQ + (b + 1) * 8192, &tm, b < 0 ? 576 : (3 * rank + b / 3) * 64, b < 0 ? col : head * DH + ((rank + b) % 3) * 64, bar);
}
template <bool IS_O>
__device__ __forceinline__ void load_weights_rs(uint32_t (&wf)[C::NKR][4], const CUtensorMap& tms, const CUtensorMap& tm, int cta, int rank, uint32_t sb, int tid0, int& spin) {
  using namespace C;
  constexpr int STAGE = IS_O ? OFF_WQ : OFF_WK, YOFF = IS_O ? OFF_YO : OFF_YV, NB = IS_O ? NB_C : NB_V;
  const int i = (tid0 >> 3) & 3, n0 = (tid0 & 7) + (i >> 1) * 8;
  const int chunk = 2 * ((tid0 >> 5) & 3) + (i & 1);
  const int r0 = IS_O ? dh_row(n0) : n0, r1 = IS_O ? dh_row(n0 + 16) : n0 + 16;
  const uint32_t a0 = sb + STAGE + r0 * 128 + ((chunk ^ (r0 & 7)) << 4), a1 = sb + STAGE + r1 * 128 + ((chunk ^ (r1 & 7)) << 4);
#pragma unroll
  for (int p = 0; p < 5; p++) {
    mwait(sb + BAR_W + 8 * p, 0, spin);
    if (IS_O) PTS(8 + p);
    if (p + NBX < 5) { if ((tid0 & 127) == 96) stage_box<IS_O>(tms, sb, p + NBX, cta, rank); __syncwarp(); }
    if (IS_O) permute_cols(sb + STAGE + p * 16384, tid0, 512);
    else {
#pragma unroll 1
      for (int it = tid0 & 127; it < 256; it += 128) {
        const uint32_t base = sb + STAGE + p * 16384 + (it >> 1) * 128;
        const int sw = ((it >> 1) & 7) ^ ((it & 1) * 4);
        const uint4 u0 = lds128(base + (sw << 4)), u1 = lds128(base + ((sw ^ 1) << 4)), u2 = lds128(base + ((sw ^ 2) << 4)), u3 = lds128(base + ((sw ^ 3) << 4));
        sts128(base + (sw << 4), make_uint4(u0.x, u1.x, u2.x, u3.x)); sts128(base + ((sw ^ 1) << 4), make_uint4(u0.y, u1.y, u2.y, u3.y));
        sts128(base + ((sw ^ 2) << 4), make_uint4(u0.z, u1.z, u2.z, u3.z)); sts128(base + ((sw ^ 3) << 4), make_uint4(u0.w, u1.w, u2.w, u3.w));
      }
    }
    bar_sync(NB, 128);
#pragma unroll
    for (int k = 8 * p; k < 8 * p + 8; k++) {
      if (k < NKR) ldsm4t(wf[k < NKR ? k : 0], ((k & 1) ? a1 : a0) + (k >> 1) * 4096);
      else {
        const int n = k * 16 + ((tid0 & 127) >> 3), r = IS_O ? dh_row(n) : n, c = tid0 & 7;
        sts128(sb + YOFF + (n - NKR * 16) * 128 + ((c ^ (n & 7)) << 4), lds128(sb + STAGE + r * 128 + ((c ^ (r & 7)) << 4)));
      }
    }
    fence_async();
    bar_sync(NB, 128);
    if ((tid0 & 127) == 0) {
      mbar_expect_tx(sb + BAR_W + 8 * p, 16384);
      tma2d(sb + STAGE + p * 16384, &tm, (cta / 3) * DH + rank * 64, p * 128, sb + BAR_W + 8 * p);
    }
    __syncwarp();
  }
  PTS(IS_O ? 13 : 14);
  CBAR_SYNC(NB_PRO, 384);
}

__device__ __forceinline__ void load_pair(uint32_t sb, int i, int p, uint32_t slot, uint32_t ph, int& spin) {
  using namespace C;
  mwait(sb + BAR_E + 8 * p, ph, spin);
  elect_g2s_mc(sb + slot, g_xn[i] + p * 16384, 16384, sb + BAR_F + 8 * p);
}
__device__ __forceinline__ void release_round(uint32_t sb, int p, int lane) {
  if (lane < (p == 2 ? 3 : 1)) mbar_arrive_cluster(mapa(sb, p == 2 ? lane : p) + C::BAR_E + 8 * (3 + p));
}

__device__ __forceinline__ void signal_o(int i, int cta) { csignal(CN_O + i * 5 + min(cta / 19, 4)); }

template <int K0, int K1>
__device__ __forceinline__ void v_mem_pass(float (&d)[8], const uint32_t (&wf)[C::NKR][4]) {
  using namespace C;
#pragma unroll
  for (int j = K0; j < K1; j++) {
    const int k = m_tile(j >> 2) * 4 + (j & 3);
    if (k < NKR) wgmma_rs16(d, wf[k < NKR ? k : 0], mdesc(j), j != 32);
    else wgmma_ts16(d, wdesc(OFF_YV + (k - NKR) * 2048), mdesc(j), 1);
  }
  wg_commit();
}
__device__ __forceinline__ void chain_v(const CUtensorMap& tmWv, const CUtensorMap& tmWk, const uint32_t sb, const int tid0, const int cta, const int rank) {
  using namespace C;
  asm volatile("setmaxnreg.inc.sync.aligned.u32 208;");
  int spin = 0;
  uint32_t wf[NKR][4];
  const int wu = uni((tid0 >> 5) & 3);
  const uint32_t slot = rank == 2 ? OFF_M : OFF_KT + rank * 16384;
  load_weights_rs<false>(wf, tmWv, tmWk, cta, rank, sb, tid0, spin);
  PTS(5);
#pragma unroll 1
  for (int i = 0; i < NSTEP; i++) {
    uint32_t vp[16], va;
#define STORE_V { _Pragma("unroll") for (int s = 0; s < 4; s++) stsm4(va + 128 + s * 128, vp[4 * s], vp[4 * s + 1], vp[4 * s + 2], vp[4 * s + 3]); }
    {
      float d[32];
      if (i > 0) CBAR_SYNC(NB_WV, 256);
#pragma unroll
      for (int p = 0; p < 5; p++) {
        if (OSV && p == 3) {
          wg_wait<0>();
          release_round(sb, 2, tid0 & 31);
          if (wu == 1 && i > 0) {
            CBAR_SYNC(NB_MR, 160);
            if (elect_one()) signal_o(i - 1, cta);
          }
        }
        mwait(sb + BAR_F + 8 * p, i & 1, spin);
        TS(i, 25 + p);
        wg_fence();
#pragma unroll
        for (int k = 8 * p; k < 8 * p + 8; k++) {
          if (k < NKR) wgmma_rs64(d, wf[k < NKR ? k : 0], tdesc(k), k);
          else wgmma_ts64(d, wdesc(OFF_YV + (k - NKR) * 2048), tdesc(k), 1);
          if (k == 8 * p + 1 && p >= 1 && p <= (OSV ? 2 : 3)) {
            wg_commit(); wg_wait<1>();
            release_round(sb, p - 1, tid0 & 31);
          }
          if (k == 8 * p + RFK && (p == 1 || p == 2)) {
            wg_commit();
            if (rank == p - 1 && wu == 0) load_pair(sb, i, p + 2, slot_off(p + 2), i & 1, spin);
            wg_fence();
          }
        }
        wg_commit();
      }
      wg_wait<0>();
      TS(i, 23);
#pragma unroll
      for (int q = 0; q < 16; q++) vp[q] = pin(pack_bf16(d[2 * q], d[2 * q + 1]));
      CBAR_SYNC(NB_RD, 256);
      const int tid = fresh(tid0) & 127, m = (tid >> 3) & 3;
      if (wu == 3) {
        const int lane = tid & 31;
        if (lane < 3 && lane != rank) mbar_arrive_cluster(mapa(sb, lane) + BAR_XF);
        if (lane < 8) mbar_expect_tx(sb + BAR_F + 8 * lane, lane < 5 ? 16384 : lane == 5 ? 2560 : lane == 6 ? 7168 : 4096);
        mwait(sb + BAR_XF, i & 1, spin);
      } else {
        if (tid < 80) sts128(sb + (tid < 72 ? OFF_VT + (tid >> 3) * VS : OFF_PT + 1280) + (tid & 7) * 16, make_uint4(0, 0, 0, 0));
        fence_async();
      }
      CBAR_ARRIVE(NB_QK, 384);
      TS(i, 16);
      va = sb + OFF_VT + 128 + ((tid >> 5) * 2 + (m & 1)) * VS + (m >> 1) * 640 + (tid & 7) * 16;
    }
    const uint32_t* xc = &g_cnt[CN_X + i + 1][0];
    const uint32_t xn = NOWORK == 2 || i + 1 < NPRE ? 0 : i + 1 < LAG || NOWORK ? 16 : 48;
    bool seen = false;
    if (wu == 0) seen = __any_sync(0xffffffffu, ld_relaxed(xc) >= xn);
    CBAR_SYNC(NB_V, 256);
    float d[8];
    wg_fence();
    v_mem_pass<32, 40>(d, wf);
    v_mem_pass<0, 6>(d, wf);
    wg_wait<1>();
    if ((tid0 & 31) < 3 && (tid0 & 31) != rank) mbar_arrive_cluster(mapa(sb, tid0 & 31) + BAR_MF);
    v_mem_pass<6, 32>(d, wf);
    if (VSL == 2) STORE_V
    CBAR_SYNC(NB_SM, 256);
    wg_wait<0>();
    TS(i, 24);
    const int tid = fresh(tid0);
    if (!E2L && (tid & 31) == 0) mbar_arrive_cluster(mapa(sb, 2) + BAR_E + 16);
    stsm4(va, pack_bf16(d[0], d[1]), pack_bf16(d[2], d[3]), pack_bf16(d[4], d[5]), pack_bf16(d[6], d[7]));
#undef STORE_V
    fence_async();
    CBAR_ARRIVE(NB_VA, 256);
    CBAR_ARRIVE(NB_VQ, QPV ? 384 : 256);
    if (wu == 0 && i + 1 < NSTEP) {
      if (!seen) while (ld_relaxed(xc) < xn && spin < SPIN_TOT) spin += 16;
      fence_async_all();
      load_pair(sb, i + 1, rank, slot, i & 1, spin);
      TS(i + 1, 37);
    }
    TS_FLUSH(i - 1);
    __syncwarp();
  }
  CBAR_ARRIVE(NB_WV, 256);
  if (spin >= SPIN_TOT) g_err = 3;
}

__device__ __forceinline__ float quad_max(float x) {
  const float a = __shfl_xor_sync(0xffffffffu, x, 1), b = __shfl_xor_sync(0xffffffffu, x, 2), c = __shfl_xor_sync(0xffffffffu, x, 3);
  return fmaxf(fmaxf(x, a), fmaxf(b, c));
}
__device__ __forceinline__ float max10(const float (&y)[10]) {
  return fmaxf(fmaxf(fmaxf(fmaxf(y[0], y[1]), fmaxf(y[2], y[3])), fmaxf(fmaxf(y[4], y[5]), fmaxf(y[6], y[7]))), fmaxf(y[8], y[9]));
}
__device__ __forceinline__ float sum10(const float (&y)[10]) {
  return (((y[0] + y[1]) + (y[2] + y[3])) + ((y[4] + y[5]) + (y[6] + y[7]))) + (y[8] + y[9]);
}
__device__ __forceinline__ float rcp(float x) { float y; asm("rcp.approx.ftz.f32 %0,%1;" : "=f"(y) : "f"(x)); return y; }

__device__ __forceinline__ void chain_q(const bf16* x0, const bf16* mem0, const uint32_t sb, const int tid0, const int cta, const int rank) {
  using namespace C;
  asm volatile("setmaxnreg.dec.sync.aligned.u32 96;");
  int spin = 0;
  PTS(0);
  pre_work(x0, mem0, cta, tid0 & 127);
  PTS(3);
  CBAR_SYNC(NB_Q, 128);
  PTS(2);
  if (tid0 < 160) {
    if (tid0 == 128) pre_wait(0, 96, spin);
    __syncwarp();
    load_pair(sb, 0, rank, rank == 2 ? OFF_M : OFF_KT + rank * 16384, 1, spin);
  }
  PTS(4);
  CBAR_SYNC(NB_PRO, 384);
  mwait(sb + BAR_W, 1, spin);
  PTS(6);
  const int wu = uni((tid0 >> 5) & 3);
  uint4 ov[4] = {};
  uint8_t* op = &g_o[ORING - 1][cta][(tid0 & 124) * 32];
  const uint32_t o0 = ((tid0 ^ (tid0 >> 2)) & 3) * 16 + (tid0 & 16) * 4;
#pragma unroll 1
  for (int i = 0; i < NSTEP; i++) {
    const int ph = i & 1;
    uint32_t qf[4][4];
    {
      float d[64];
#define QK_STEP(K, SC) wgmma_st128(d, desc_at(mkdesc(SB0 + ((K) >> 2) * 1024 + ((K) & 3) * 32, 16, 2048), so), \
                                   desc_at(mkdesc(SB0 + OFF_WQ + (K) * 2048, OFF_WK - OFF_WQ, 1024), p * 16384), SC)
      int p = 0;
      uint32_t so = OFF_KT;
      mwait(sb + BAR_F, ph, spin);
      TS(i, 0);
      wg_fence();
#pragma unroll
      for (int k = 0; k < 8; k++) {
        QK_STEP(k, k);
        if (k == OST) {
          wg_commit();
          mwait(sb + BAR_F, ph, spin);
#pragma unroll
          for (int h = 0; h < 4; h++) stg128(op + (h & 1) * 4096 + (o0 ^ ((h >> 1) * 64)), ov[h]);
          if (i > 0) CBAR_ARRIVE(NB_MR, 160);
          if (k < 7) wg_fence();
        }
      }
      if (OST != 7) wg_commit();
#pragma unroll 1
      for (p = 1; p < 5; p++) {
        static_assert(OFF_KT - OFF_M == 5 << 12, "");
        so = OFF_M + (((0x95095u >> (4 * p)) & 15) << 12);
        if (i == 0) { mwait(sb + BAR_W + 8 * p, 1, spin); PTS(14 + p); }
        mwait(sb + BAR_F + 8 * p, ph, spin);
        if (OST > 7 && p == OST - 8) {
#pragma unroll
          for (int h = 0; h < 4; h++) stg128(op + (h & 1) * 4096 + (o0 ^ ((h >> 1) * 64)), ov[h]);
          if (i > 0) CBAR_ARRIVE(NB_MR, 160);
        }
        wg_fence();
#pragma unroll
        for (int k = 0; k < 8; k++) {
          QK_STEP(k, 1);
          if (k == 1) {
            wg_commit(); wg_wait<1>();
            release_round(sb, p - 1, p < 4 ? tid0 & 31 : 32);
          }
        }
        wg_commit();
      }
#undef QK_STEP
      wg_wait<0>();
      TS(i, 1);
      CBAR_SYNC(NB_RD, 256);
      TSB(i, 2);
      const int tid = fresh(tid0), w = (tid >> 5) & 3, m = (tid >> 3) & 3;
      const uint32_t a = sb + OFF_KT + (m >> 1) * KS + (1 + w + 5 * (m & 1)) * 128 + (tid & 7) * 16;
#pragma unroll
      for (int s = 0; s < 4; s++)
        stsm4t(a + s * 2 * KS, pack_bf16(d[32 + 8 * s], d[33 + 8 * s]), pack_bf16(d[34 + 8 * s], d[35 + 8 * s]),
               pack_bf16(d[36 + 8 * s], d[37 + 8 * s]), pack_bf16(d[38 + 8 * s], d[39 + 8 * s]));
      fence_async();
      CBAR_ARRIVE(NB_QK, 384);
      TS(i, 15);
#pragma unroll
      for (int kk = 0; kk < 4; kk++)
#pragma unroll
        for (int j = 0; j < 4; j++) asm volatile("{.reg .b32 t; cvt.rn.bf16x2.f32 t,%1,%2; mul.rn.bf16x2 %0,t,%3;}" : "=r"(qf[kk][j]) : "f"(d[8 * kk + 2 * j + 1]), "f"(d[8 * kk + 2 * j]), "r"(SCQ));
    }
    CBAR_SYNC(NB_SI, 256);
    uint32_t pf[5][4];
    float sa = 0.f, sb2 = 0.f;
    {
      float y0[10], y1[10];
      const int tidf = fresh(tid0), lane = tidf & 31;
      {
        float x[40];
        wg_fence();
#pragma unroll
        for (int kk = 0; kk < 4; kk++) {
          if (VTI && kk == 4 - VTI) CBAR_ARRIVE(NB_V, 256);
          wgmma_rt80(x, qf[kk], mkdesc_ns(SB0 + OFF_KT + kk * 2 * KS, KS, 128), kk);
        }
        wg_commit();
        wg_wait<0>();
#pragma unroll
        for (int j = 0; j < 5; j++) { y0[2 * j] = x[4 * j]; y0[2 * j + 1] = x[4 * j + 1]; y1[2 * j] = x[22 + 4 * j]; y1[2 * j + 1] = x[23 + 4 * j]; }
      }
      TS(i, 17);
      const uint32_t xo = OFF_XT + (wu * (wu + 3) / 2) * 256 + lane * 16, x2 = xo + (wu >> 1) * 512 + 512 - lane * 8;
      {
        const uint4 h0 = make_uint4(pack_h2(y0[0], y0[1]), pack_h2(y1[0], y1[1]), pack_h2(y0[2], y0[3]), pack_h2(y1[2], y1[3]));
        const uint4 h1 = make_uint4(pack_h2(y0[4], y0[5]), pack_h2(y1[4], y1[5]), pack_h2(y0[6], y0[7]), pack_h2(y1[6], y1[7]));
        const uint32_t h2 = wu == 1 ? h1.x : pack_h2(y0[8], y0[9]), h3 = wu == 1 ? h1.y : pack_h2(y1[8], y1[9]);
        const uint32_t rb1 = mapa(sb, (rank + 1) % 3), rb2 = mapa(sb, (rank + 2) % 3);
        if (XTD == 1) mwait(sb + BAR_XM, ph, spin);
        if (XTD > 1) for (const uint32_t t0 = clk32(); clk32() - t0 < XTD;) {}
        st_async4u(rb1 + xo + 3584, h0, rb1 + BAR_XT);
        st_async4u(rb2 + xo, h0, rb2 + BAR_XT);
        if (wu >= 2) { st_async4u(rb1 + xo + 4096, h1, rb1 + BAR_XT); st_async4u(rb2 + xo + 512, h1, rb2 + BAR_XT); }
        if (wu & 1) { st_async2u(rb1 + x2 + 3584, h2, h3, rb1 + BAR_XT); st_async2u(rb2 + x2, h2, h3, rb2 + BAR_XT); }
      }
      TS(i, 18);
      const int lim = 8 * wu + (lane >> 2) + 8 - 2 * (lane & 3);
#pragma unroll
      for (int j = 2; j < 10; j++)
        if (8 * (j >> 1) + (j & 1) > lim) { y0[j] = -INFINITY; y1[j] = -INFINITY; }
      mwait(sb + BAR_XT, ph, spin);
      TS(i, 19);
      {
        const uint4 u0 = lds128(sb + xo), v0 = lds128(sb + xo + 3584);
        uint2 u2 = make_uint2(0, 0), v2 = u2;
        if (wu & 1) { u2 = lds64(sb + x2); v2 = lds64(sb + x2 + 3584); }
        uint4 u1 = make_uint4(u2.x, u2.y, 0, 0), v1 = make_uint4(v2.x, v2.y, 0, 0);
        if (wu >= 2) { u1 = lds128(sb + xo + 512); v1 = lds128(sb + xo + 4096); }
        __syncwarp();
        if (lane == 0) mbar_arrive_cluster(mapa(sb, 0) + BAR_E);
        add_h2(y0[0], y0[1], u0.x, v0.x); add_h2(y1[0], y1[1], u0.y, v0.y); add_h2(y0[2], y0[3], u0.z, v0.z); add_h2(y1[2], y1[3], u0.w, v0.w);
        add_h2(y0[4], y0[5], u1.x, v1.x); add_h2(y1[4], y1[5], u1.y, v1.y); add_h2(y0[6], y0[7], u1.z, v1.z); add_h2(y1[6], y1[7], u1.w, v1.w);
        add_h2(y0[8], y0[9], u2.x, v2.x); add_h2(y1[8], y1[9], u2.y, v2.y);
      }
      const float m0 = quad_max(max10(y0)) * -SCE, m1 = quad_max(max10(y1)) * -SCE;
#pragma unroll
      for (int j = 0; j < 5; j++) {
        y0[2 * j] = ex2(fmaf(y0[2 * j], SCE, m0)); y0[2 * j + 1] = ex2(fmaf(y0[2 * j + 1], SCE, m0));
        y1[2 * j] = ex2(fmaf(y1[2 * j], SCE, m1)); y1[2 * j + 1] = ex2(fmaf(y1[2 * j + 1], SCE, m1));
        if (!ONES) { sa += y0[2 * j] + y0[2 * j + 1]; sb2 += y1[2 * j] + y1[2 * j + 1]; }
        pf[j >> 1][2 * (j & 1)] = pack_bf16(y0[2 * j], y0[2 * j + 1]);
        pf[j >> 1][2 * (j & 1) + 1] = tidf >> (10 + j);
        pf[(j + 5) >> 1][2 * ((j + 5) & 1)] = tidf >> (20 + j);
        pf[(j + 5) >> 1][2 * ((j + 5) & 1) + 1] = pack_bf16(y1[2 * j], y1[2 * j + 1]);
      }
    }
#pragma unroll
    for (int q = 0; q < 20; q++) pf[q >> 2][q & 3] = pin(pf[q >> 2][q & 3]);
    CBAR_SYNC(NB_VQ, QPV ? 384 : 256);
    TSB(i, 20);
    {
      float o[32], sm[4];
      wg_fence();
#pragma unroll
      for (int q = 0; q < 5; q++) if (ONES) wgmma_rs8(sm, pf[q], mkdesc_ns(SB0 + OFF_ONE, 0, 0), q);
#pragma unroll
      for (int q = 0; q < 5; q++) wgmma_rs64(o, pf[q], mkdesc_ns(SB0 + OFF_VT + 128 + q * 256, 128, VS), q);
      wg_commit();
      if (!ONES) { sm[0] = quad_sum(sa); sm[2] = quad_sum(sb2); }
      const int tid = fresh(tid0);
      op = &g_o[i % ORING][cta][(tid & 124) * 32];
      wg_wait<0>();
      TS(i, 21);
      if ((tid & 31) == 0) mbar_arrive_cluster(mapa(sb, 1) + BAR_E + 8);
      const float s0 = rcp(sm[0]), s1 = rcp(sm[2]);
#pragma unroll
      for (int h = 0; h < 2; h++) {
        const float* x = o + 16 * h;
        ov[2 * h] = make_uint4(pin(pack_bf16(x[0] * s0, x[1] * s0)), pin(pack_bf16(x[4] * s0, x[5] * s0)), pin(pack_bf16(x[8] * s0, x[9] * s0)), pin(pack_bf16(x[12] * s0, x[13] * s0)));
        ov[2 * h + 1] = make_uint4(pin(pack_bf16(x[2] * s1, x[3] * s1)), pin(pack_bf16(x[6] * s1, x[7] * s1)), pin(pack_bf16(x[10] * s1, x[11] * s1)), pin(pack_bf16(x[14] * s1, x[15] * s1)));
      }
      TS(i, 22);
      if (i + 1 < NSTEP) CBAR_SYNC(NB_WQ, 256); else CBAR_ARRIVE(NB_WQ, 256);
    }
  }
#pragma unroll
  for (int h = 0; h < 4; h++) stg128(op + (h & 1) * 4096 + (o0 ^ ((h >> 1) * 64)), ov[h]);
  CBAR_SYNC(NB_Q, 128);
  if (tid0 == 224) signal_o(NSTEP - 1, cta);
  if (spin >= SPIN_TOT) g_err = 2;
}

template <int NL> __device__ __forceinline__ void poll(uint4 (&x)[NL], const uint8_t* mb, uint32_t tag, int& spin);
template <> __device__ __forceinline__ void poll<4>(uint4 (&x)[4], const uint8_t* mb, uint32_t tag, int& spin) {
  asm volatile("{.reg .pred p<6>, q; .reg .b128 v; .reg .b32 t;\n"
               " ld.relaxed.gpu.global.b128 v,[%17+0]; mov.b128 {%0,%1,%2,%3},v;\n"
               " ld.relaxed.gpu.global.b128 v,[%17+512]; mov.b128 {%4,%5,%6,%7},v;\n"
               " ld.relaxed.gpu.global.b128 v,[%17+1024]; mov.b128 {%8,%9,%10,%11},v;\n"
               " ld.relaxed.gpu.global.b128 v,[%17+1536]; mov.b128 {%12,%13,%14,%15},v;\n"
               "POLL_LOOP:\n add.s32 %16,%16,16;\n"
               " lop3.b32 t,%0,%18,1,0x28; setp.ne.b32 p0,t,0;\n"
               " lop3.b32 t,%4,%18,1,0x28; setp.ne.b32 p1,t,0;\n"
               " lop3.b32 t,%8,%18,1,0x28; setp.ne.b32 p2,t,0;\n"
               " lop3.b32 t,%12,%18,1,0x28; setp.ne.b32 p3,t,0;\n"
               " or.pred q,p0,p1; or.pred q,q,p2; or.pred q,q,p3; setp.lt.and.s32 q,%16,%19,q; vote.sync.any.pred q,q,0xffffffff;\n"
               " mov.b128 v,{%0,%1,%2,%3}; @p0 ld.relaxed.gpu.global.b128 v,[%17+0]; mov.b128 {%0,%1,%2,%3},v;\n"
               " mov.b128 v,{%4,%5,%6,%7}; @p1 ld.relaxed.gpu.global.b128 v,[%17+512]; mov.b128 {%4,%5,%6,%7},v;\n"
               " mov.b128 v,{%8,%9,%10,%11}; @p2 ld.relaxed.gpu.global.b128 v,[%17+1024]; mov.b128 {%8,%9,%10,%11},v;\n"
               " mov.b128 v,{%12,%13,%14,%15}; @p3 ld.relaxed.gpu.global.b128 v,[%17+1536]; mov.b128 {%12,%13,%14,%15},v;\n"
               " @q bra.uni POLL_LOOP;\n}"
               : "=&r"(x[0].x), "=&r"(x[0].y), "=&r"(x[0].z), "=&r"(x[0].w), "=&r"(x[1].x), "=&r"(x[1].y), "=&r"(x[1].z), "=&r"(x[1].w), "=&r"(x[2].x), "=&r"(x[2].y), "=&r"(x[2].z), "=&r"(x[2].w), "=&r"(x[3].x), "=&r"(x[3].y), "=&r"(x[3].z), "=&r"(x[3].w), "+&r"(spin)
               : "l"(mb), "r"(tag), "n"(SPIN_TOT) : "memory");
}
template <> __device__ __forceinline__ void poll<6>(uint4 (&x)[6], const uint8_t* mb, uint32_t tag, int& spin) {
  asm volatile("{.reg .pred p<6>, q; .reg .b128 v; .reg .b32 t;\n"
               " ld.relaxed.gpu.global.b128 v,[%25+0]; mov.b128 {%0,%1,%2,%3},v;\n"
               " ld.relaxed.gpu.global.b128 v,[%25+512]; mov.b128 {%4,%5,%6,%7},v;\n"
               " ld.relaxed.gpu.global.b128 v,[%25+1024]; mov.b128 {%8,%9,%10,%11},v;\n"
               " ld.relaxed.gpu.global.b128 v,[%25+1536]; mov.b128 {%12,%13,%14,%15},v;\n"
               " ld.relaxed.gpu.global.b128 v,[%25+2048]; mov.b128 {%16,%17,%18,%19},v;\n"
               " ld.relaxed.gpu.global.b128 v,[%25+2560]; mov.b128 {%20,%21,%22,%23},v;\n"
               "POLL_LOOP:\n add.s32 %24,%24,16;\n"
               " lop3.b32 t,%0,%2,%26,0x7e; and.b32 t,t,1; setp.ne.b32 p0,t,0;\n"
               " lop3.b32 t,%4,%6,%26,0x7e; and.b32 t,t,1; setp.ne.b32 p1,t,0;\n"
               " lop3.b32 t,%8,%10,%26,0x7e; and.b32 t,t,1; setp.ne.b32 p2,t,0;\n"
               " lop3.b32 t,%12,%14,%26,0x7e; and.b32 t,t,1; setp.ne.b32 p3,t,0;\n"
               " lop3.b32 t,%16,%18,%26,0x7e; and.b32 t,t,1; setp.ne.b32 p4,t,0;\n"
               " lop3.b32 t,%20,%22,%26,0x7e; and.b32 t,t,1; setp.ne.b32 p5,t,0;\n"
               " or.pred q,p0,p1; or.pred q,q,p2; or.pred q,q,p3; or.pred q,q,p4; or.pred q,q,p5; setp.lt.and.s32 q,%24,%27,q; vote.sync.any.pred q,q,0xffffffff;\n"
               " mov.b128 v,{%0,%1,%2,%3}; @p0 ld.relaxed.gpu.global.b128 v,[%25+0]; mov.b128 {%0,%1,%2,%3},v;\n"
               " mov.b128 v,{%4,%5,%6,%7}; @p1 ld.relaxed.gpu.global.b128 v,[%25+512]; mov.b128 {%4,%5,%6,%7},v;\n"
               " mov.b128 v,{%8,%9,%10,%11}; @p2 ld.relaxed.gpu.global.b128 v,[%25+1024]; mov.b128 {%8,%9,%10,%11},v;\n"
               " mov.b128 v,{%12,%13,%14,%15}; @p3 ld.relaxed.gpu.global.b128 v,[%25+1536]; mov.b128 {%12,%13,%14,%15},v;\n"
               " mov.b128 v,{%16,%17,%18,%19}; @p4 ld.relaxed.gpu.global.b128 v,[%25+2048]; mov.b128 {%16,%17,%18,%19},v;\n"
               " mov.b128 v,{%20,%21,%22,%23}; @p5 ld.relaxed.gpu.global.b128 v,[%25+2560]; mov.b128 {%20,%21,%22,%23},v;\n"
               " @q bra.uni POLL_LOOP;\n}"
               : "=&r"(x[0].x), "=&r"(x[0].y), "=&r"(x[0].z), "=&r"(x[0].w), "=&r"(x[1].x), "=&r"(x[1].y), "=&r"(x[1].z), "=&r"(x[1].w), "=&r"(x[2].x), "=&r"(x[2].y), "=&r"(x[2].z), "=&r"(x[2].w), "=&r"(x[3].x), "=&r"(x[3].y), "=&r"(x[3].z), "=&r"(x[3].w), "=&r"(x[4].x), "=&r"(x[4].y), "=&r"(x[4].z), "=&r"(x[4].w), "=&r"(x[5].x), "=&r"(x[5].y), "=&r"(x[5].z), "=&r"(x[5].w), "+&r"(spin)
               : "l"(mb), "r"(tag), "n"(SPIN_TOT) : "memory");
}
template <int NL>
__device__ __forceinline__ void poll_add(const uint8_t* mb, uint32_t tag, float (&f)[8], uint8_t* flag, bool lead, int& spin) {
  uint4 x[NL];
  poll<NL>(x, mb, tag, spin);
  if (FLP == 0 && lead) st_relaxed16(flag, 0);
#pragma unroll
  for (int i = 0; i < NL; i++) {
    const uint32_t u[4] = {x[i].x, x[i].y, x[i].z, x[i].w};
#pragma unroll
    for (int j = 0; j < 4; j++) {
      if (i == 0) { f[2 * j] = bf_lo(u[j]); f[2 * j + 1] = bf_hi(u[j]); }
      else { f[2 * j] += bf_lo(u[j]); f[2 * j + 1] += bf_hi(u[j]); }
    }
  }
}

template <int B, int SLOT>
__device__ __forceinline__ void wo_step(float (&acc)[8], const uint32_t (&wf)[C::NKR][4], int kk) {
  using namespace C;
  const int k = 4 * B + kk;
  const uint64_t db = mkdesc_ns(SB0 + og_off(SLOT) + kk * 512, 256, 128);
  if (k < NKR) wgmma_rt16(acc, wf[k < NKR ? k : 0], db, SLOT | kk);
  else wgmma_tt16(acc, wdesc(OFF_YO + (k - NKR) * 2048), db, 1);
}
template <int B, int SLOT>
__device__ __forceinline__ void wo_block(float (&acc)[8], const uint32_t (&wf)[C::NKR][4]) {
#pragma unroll
  for (int kk = 0; kk < 4; kk++) wo_step<B, SLOT>(acc, wf, kk);
}

__device__ __forceinline__ void chain_a(const CUtensorMap& tmWo, const CUtensorMap& tmWq, const uint32_t sb, const int tid0, const int cta, const int rank) {
  using namespace C;
  asm volatile("setmaxnreg.inc.sync.aligned.u32 200;");
  int spin = 0;
  uint32_t wf[NKR][4];
  load_weights_rs<true>(wf, tmWo, tmWq, cta, rank, sb, tid0, spin);
  const int wu = uni(tid0 >> 5);
  const int head = cta / 3, c9 = rank * 8 + head - 32;
  const bool t9 = head >= 24 && rank > 0;
  const uint64_t exa = reinterpret_cast<uint64_t>(ex_window(g_ex));
  const uint32_t ehi = (uint32_t)(exa >> 32), elo = (uint32_t)exa;

  int b1 = B1, b2 = B2;
#pragma unroll 1
  for (int i = -1; i < NSTEP; i++) {
    const int ph = i & 1;
    if (i >= 0) {
      const int tid = fresh(tid0);
      const uint32_t mo = __shfl_xor_sync(0xffffffffu, elo + ((rank * 8 + (tid >> 4)) * 4 + (tid & 3)) * 2048 + head * 64 + (tid & 12) * 4, 0);
      const uint32_t m9 = __shfl_xor_sync(0xffffffffu, elo + MAIL9 + (((tid >> 4) * 2 + (tid & 1)) * 4 + (tid & 2)) * 3072 + cta * 32 + (tid & 12) * 2, 0);
      const uint32_t oo = __shfl_xor_sync(0xffffffffu, (tid >> 5) * 512 + (tid & 2) * 64 + (tid & 28) * 4 + (tid & 1) * 8, 0);
      if (i == 0) { mwait(sb + BAR_W + 24, 1, spin); mwait(sb + BAR_W + 32, 1, spin); PTS(7); }
      mwait(sb + BAR_M, ph, spin);
      TS(i, 3);
      {
        float x[20];
        int redo = 0;
      retry:
        bool bad;
        {
          float dq[8] = {}, dk[8] = {};
          const uint32_t late = (mbar_test(sb + BAR_M + 8, ph) ? 0 : 8) | (mbar_test(sb + BAR_M + 16, ph) ? 0 : 64);
#pragma unroll 1
          for (int j = 0; j < 10; j++) {
            if ((late >> j) & 1) mwait(sb + BAR_M + (j == 3 ? 8 : 16), ph, spin);
            const uint32_t wo = m_tile(j) * 8192;
            wg_fence();
#pragma unroll
            for (int k = 0; k < 4; k++) {
              const uint64_t db = desc_at(mdesc(k), j * 2048);
              wgmma_ts16(dq, desc_at(wdesc(OFF_WQ + k * 2048), wo), db, 1);
              wgmma_ts16(dk, desc_at(wdesc(OFF_WK + k * 2048), wo), db, 1);
            }
            wg_commit();
          }
          const int m = (tid >> 3) & 3, dg = (tid >> 5) * 2 + (m & 1);
          const uint32_t ka = sb + OFF_KT + dg * KS + (m >> 1) * 640 + (tid & 7) * 16;
          if (!redo) CBAR_SYNC(NB_QK, 384);
          wg_wait<0>();
          TS(i, 4);
          stsm4(ka, pack_bf16(dk[0], dk[1]), pack_bf16(dk[2], dk[3]), pack_bf16(dk[4], dk[5]), pack_bf16(dk[6], dk[7]));
          stsm4(ka + dg * (VS - KS) + (OFF_VT + 128 - OFF_KT), scale_bf16x2(pack_bf16(dq[0], dq[1]), SCQ), scale_bf16x2(pack_bf16(dq[2], dq[3]), SCQ),
                scale_bf16x2(pack_bf16(dq[4], dq[5]), SCQ), scale_bf16x2(pack_bf16(dq[6], dq[7]), SCQ));
          const float chk = (dq[0] + dq[1]) + (dq[4] + dq[5]);
          fence_async();
          bad = bar_red_or(NB_C, 128, chk != chk && !redo);
        }
        TSB(i, 5);
        wg_fence();
#pragma unroll
        for (int kk = 0; kk < 4; kk++) wgmma_tt40(x, mkdesc_ns(SB0 + OFF_VT + 128 + kk * 2 * VS, VS, 640), mkdesc_ns(SB0 + OFF_KT + kk * 2 * KS, KS, 128), kk);
#pragma unroll
        for (int kk = 0; kk < 4; kk++) {
          if (SIE && kk == 4 - SIE && !bad) CBAR_ARRIVE(NB_SI, 256);
          wgmma_tt40(x, mkdesc_ns(SB0 + OFF_VT + kk * 2 * VS, VS, 384), mkdesc_ns(SB0 + OFF_KT + 640 + kk * 2 * KS, KS, 128), 1);
        }
        wg_commit();
        if (!SIE && !bad) CBAR_ARRIVE(NB_SI, 256);
        if (__builtin_expect(__any_sync(0xffffffffu, bad), 0)) {
          wg_wait<0>();
#pragma unroll 1
          for (int k = 0; k < 10; k++) {
            uint4 v = lds128(sb + OFF_M + tid * 16 + k * 2048);
            if (v.x == SENT || v.y == SENT || v.z == SENT || v.w == SENT) {
              do { v = ld_relaxed4(mkptr(elo + EX_M + i * 20480 + tid * 16 + k * 2048, ehi)); spin += 16; } while ((v.x == SENT || v.y == SENT || v.z == SENT || v.w == SENT) && spin < SPIN_TOT);
              sts128(sb + OFF_M + tid * 16 + k * 2048, v);
            }
          }
          fence_async();
          bar_sync(NB_C, 128);
          redo = fresh(1);
          goto retry;
        }
        TSV(i, 36, redo);
        const uint32_t rb1 = mapa(sb, (rank + 1) % 3), rb2 = mapa(sb, (rank + 2) % 3);
        wg_wait<0>();
        TS(i, 6);
        if (wu < 2) {
          float y[10];
#pragma unroll
          for (int j = 0; j < 5; j++) { y[2 * j] = x[4 * j]; y[2 * j + 1] = x[4 * j + 1]; }
          const uint4 h0 = make_uint4(pack_h2(y[0], y[1]), pack_h2(y[2], y[3]), pack_h2(y[4], y[5]), pack_h2(y[6], y[7]));
          const uint32_t h1 = pack_h2(y[8], y[9]);
          const uint32_t xo = wu * 640 + (tid & 31) * 16, xp = wu * 640 + 512 + (tid & 31) * 4;
          if (XMB) {
            sts128(sb + og_off(0) + xo, h0); sts32(sb + og_off(0) + xp, h1);
            fence_async();
            __syncwarp();
            if (elect_one()) {
              bulk_s2c(rb1 + OFF_XM + 1280 + wu * 640, sb + og_off(0) + wu * 640, 640, rb1 + BAR_XM);
              bulk_s2c(rb2 + OFF_XM + wu * 640, sb + og_off(0) + wu * 640, 640, rb2 + BAR_XM);
            }
          } else {
            st_async4u(rb1 + OFF_XM + 1280 + xo, h0, rb1 + BAR_XM);
            st_async4u(rb2 + OFF_XM + xo, h0, rb2 + BAR_XM);
            st_async1u(rb1 + OFF_XM + 1280 + xp, h1, rb1 + BAR_XM);
            st_async1u(rb2 + OFF_XM + xp, h1, rb2 + BAR_XM);
          }
          CBAR_ARRIVE(NB_SM, 256);
          if (!E0L && (tid & 31) == 0) mbar_arrive_cluster(mapa(sb, 0) + BAR_E);
          TS(i, 7);
          const uint32_t sw = (tid & 7) * 4 + (tid & 8) * 8 + (tid & 16) * 2;
          mwait(sb + BAR_XM, ph, spin);
          TS(i, 8);
          const uint4 u0 = lds128(sb + OFF_XM + xo), v0 = lds128(sb + OFF_XM + 1280 + xo);
          const uint32_t u1 = lds32(sb + OFF_XM + xp), v1 = lds32(sb + OFF_XM + 1280 + xp);
          add_h2(y[0], y[1], u0.x, v0.x); add_h2(y[2], y[3], u0.y, v0.y); add_h2(y[4], y[5], u0.z, v0.z); add_h2(y[6], y[7], u0.w, v0.w);
          add_h2(y[8], y[9], u1, v1);
          const float mx = quad_max(max10(y)) * -SCE;
#pragma unroll
          for (int j = 0; j < 5; j++) {
            y[2 * j] = ex2(fmaf(y[2 * j], SCE, mx)); y[2 * j + 1] = ex2(fmaf(y[2 * j + 1], SCE, mx));
            sts32(sb + OFF_PT + wu * 640 + sw + j * 128, pack_bf16(y[2 * j], y[2 * j + 1]));
          }
          sts32(sb + OFF_XM + 512 + wu * 128 + sw, __float_as_uint(sum10(y)));
          fence_async();
          TS(i, 9);
        } else {
          CBAR_ARRIVE(NB_SM, 256);
          if (!E0L && (tid & 31) == 0) mbar_arrive_cluster(mapa(sb, 0) + BAR_E);
          mwait(sb + BAR_MF, ph, spin);
        }
      }
      CBAR_SYNC(NB_VA, 256);
      TSB(i, 10);
      {
        float o[2][4];
        const float4 e = lds128f(sb + OFF_XM + 512 + (tid & 15) * 16);
        wg_fence();
#pragma unroll
        for (int c = 0; c < 2; c++)
#pragma unroll
          for (int q = 0; q < 3; q++)
            wgmma_ss8(o[c], mkdesc_ns(SB0 + OFF_VT + 128 + c * 640 + q * 256, 128, VS), mkdesc_ns(SB0 + OFF_PT + c * 640 + q * 256, q == 2 && c == 0 ? 768 : 128, 128), q);
        wg_commit();
        if (PVB && __builtin_expect(b1 < 0, 0)) { wg_wait<0>(); break; }
        const uint32_t rb1 = mapa(sb, (rank + 1) % 3), rb2 = mapa(sb, (rank + 2) % 3);
        const float inv = rcp((e.x + e.y) + (e.z + e.w));
        const int sl = (tid & 3) * 2;
        const float i0 = __shfl_sync(0xffffffffu, inv, sl), i1 = __shfl_sync(0xffffffffu, inv, sl + 1);
        const float i2 = __shfl_sync(0xffffffffu, inv, sl + 8), i3 = __shfl_sync(0xffffffffu, inv, sl + 9);
        if (E0L == 1 && (tid & 31) == 0) mbar_arrive_cluster(mapa(sb, 0) + BAR_E);
        if (PVB > 1 && __builtin_expect(b2 < 0, 0)) { wg_wait<0>(); break; }
        wg_wait<0>();
        TS(i, 11);
        const uint32_t p0 = pack_bf16(o[0][0] * i0, o[0][1] * i1), p1 = pack_bf16(o[1][0] * i2, o[1][1] * i3);
        const uint32_t p2 = pack_bf16(o[0][2] * i0, o[0][3] * i1), p3 = pack_bf16(o[1][2] * i2, o[1][3] * i3);
        if (OGF) { sts64(sb + oo + og_off(0), p0, p1); sts64(sb + oo + og_off(0) + 256, p2, p3); fence_async(); }
        if (OGF == 2) {
          __syncwarp();
          elect_s2c2(rb1 + og_off(2) + wu * 512, rb1 + BAR_OG, rb2 + og_off(1) + wu * 512, rb2 + BAR_OG, sb + og_off(0) + wu * 512, 512);
        } else if (OGF < 2) {
          st_async2u(rb1 + oo + og_off(2), p0, p1, rb1 + BAR_OG);
          st_async2u(rb2 + oo + og_off(1), p0, p1, rb2 + BAR_OG);
          st_async2u(rb1 + oo + og_off(2) + 256, p2, p3, rb1 + BAR_OG);
          st_async2u(rb2 + oo + og_off(1) + 256, p2, p3, rb2 + BAR_OG);
        }
        if (!OGF) { sts64(sb + oo + og_off(0), p0, p1); sts64(sb + oo + og_off(0) + 256, p2, p3); fence_async(); }
      }
      if (E0L == 2 && (tid & 31) == 0) mbar_arrive_cluster(mapa(sb, 0) + BAR_E);
      CBAR_SYNC(NB_A, 128);
      TSB(i, 12);
      if (OGF == 3 && wu < 2 && elect_one()) {
        const uint32_t rb = mapa(sb, (rank + 1 + wu) % 3);
        bulk_s2c(rb + og_off(2) - wu * 2048, sb + og_off(0), 2048, rb + BAR_OG);
      }
      {
        float acc[3][8];
        wg_fence();
        wo_block<0, 0>(acc[2], wf);
        wg_commit();
        wo_block<1, 0>(acc[0], wf);
        if (QPV == 1) CBAR_ARRIVE(NB_VQ, 384);
        wo_block<4, 0>(acc[1], wf);
        wg_commit();
        if (QPV == 2) CBAR_ARRIVE(NB_VQ, 384);
        if (tid < (E2L == 1 ? 2 : 1)) mbar_arrive_cluster(mapa(sb, 1 + tid) + BAR_E + 8 + 8 * tid);
        const uint32_t tag = (i >> 1) & 1;
#define TAGGED(LO, HI) ((pack_bf16(LO, HI) & ~1u) | tag)
#define SEND(OFF, U) st_relaxed128(mkptr(mo + (ph << 20), ehi) + (OFF), TAGGED(acc[U][0], acc[U][2]), pack_bf16(acc[U][1], acc[U][3]), pack_bf16(acc[U][4], acc[U][6]), pack_bf16(acc[U][5], acc[U][7]))
        wg_wait<1>();
        const uint32_t n0 = pin(TAGGED(acc[2][0], acc[2][2])), n1 = pin(pack_bf16(acc[2][1], acc[2][3]));
        const uint32_t n2 = pin(TAGGED(acc[2][4], acc[2][6])), n3 = pin(pack_bf16(acc[2][5], acc[2][7]));
        if (T2E) { wg_fence(); wo_block<7, 0>(acc[2], wf); wg_commit(); }
        if (!T9L) { st_relaxed64(mkptr(m9 + (ph << 20), ehi), n0, n1); st_relaxed64(mkptr(m9 + (ph << 20), ehi) + 3072, n2, n3); }
        mwait(sb + BAR_OG, ph, spin);
        asm volatile("fence.proxy.async::generic.acquire.sync_restrict::shared::cluster.cluster;" ::: "memory");
        if (E2L == 2 && tid == 0) mbar_arrive_cluster(mapa(sb, 2) + BAR_E + 16);
        TS(i, 13);
        wg_fence();
        wo_block<2, 1>(acc[0], wf); wo_block<3, 2>(acc[0], wf);
        wg_commit();
        wo_block<5, 1>(acc[1], wf); wo_block<6, 2>(acc[1], wf);
        wg_commit();
        if (QPV == 3) CBAR_ARRIVE(NB_VQ, 384);
        wg_wait<1>();
        if (T9L) { st_relaxed64(mkptr(m9 + (ph << 20), ehi), n0, n1); st_relaxed64(mkptr(m9 + (ph << 20), ehi) + 3072, n2, n3); }
        SEND(0, 0);
        if (!T2E) wo_block<7, 0>(acc[2], wf);
        wo_block<8, 1>(acc[2], wf); wo_block<9, 2>(acc[2], wf);
        wg_commit();
        if (WOE == 0) { CBAR_ARRIVE(NB_WV, 256); CBAR_ARRIVE(NB_WQ, 256); }
        wg_wait<1>(); SEND(24 * 8192, 1);
        if (WOE == 1) CBAR_ARRIVE(NB_WV, 256);
        wg_wait<0>(); SEND(48 * 8192, 2);
        if (WOE == 2) CBAR_ARRIVE(NB_WV, 256);
        if (WOE >= 1) CBAR_ARRIVE(NB_WQ, 256);
#undef SEND
#undef TAGGED
      }
      TS(i, 14);
      if (i < 2) PTS(19 + i);
      if (i + 1 >= NSTEP) break;
    }
    uint32_t t1 = clk32();
    if (i >= 0) {
      const int lane = fresh(tid0) & 31, j = lane >> 3;
      const uint8_t* mb = mkptr(elo + (ph << 20) + (t9 ? MAIL9 + c9 * 12288 + wu * 3072 : (rank * 24 + head % 24) * 8192 + wu * 2048) + lane * 16, ehi);
      const uint32_t tag = (i >> 1) & 1;
      const bool pub = (lane & (t9 ? 6 : 4)) == 0 && !(((t9 ? head : wu) & 1) && i + 1 == LAG) && (t9 || head < 24);
      const uint32_t dst = pin(elo + EX_M + (i + 1) * 20480 +
                               (t9 ? (144 + c9) * 128 + wu * 32 + (j & 1) * 16 + (lane & 1) * 8 + (j >> 1) * 4
                                   : (rank * 24 + head) * 256 + (wu & 1) * 128 + (wu >> 1) * 64 + j * 16 + (lane & 3) * 4));
      uint8_t* flag = mkptr(elo + EX_FLAG + (i + 1) * 3072 + (t9 ? (88 + (c9 >> 1)) * 32 + (c9 & 1) * 8 + wu * 2 : (rank * 32 + head) * 32 + wu * 4 + lane * 2), ehi);
      const bool lead = lane < (t9 ? 1 : 2);
      while (clk32() - t1 < b1) {}
      TS(i + 1, 30);
      float f[8];
      const int n0 = spin;
      if (!t9) poll_add<4>(mb, tag, f, flag, lead, spin);
      else poll_add<6>(mb, tag, f, flag, lead, spin);
      if (FLP == 1 && lead) st_relaxed16(flag, __float_as_uint(f[0] + f[7]) >> 17);
      t1 = clk32();
      b1 = __any_sync(0xffffffffu, spin - n0 > 16) ? min(b1 + AD1, BMX) : max(b1 - AD0, 0);
      TSV(i + 1, 38, b1);
      TS(i + 1, 31); TSV(i + 1, 32, (spin - n0) >> 4);
      const bool h = lane & 16, q = lane & 8;
#pragma unroll
      for (int j = 0; j < 4; j++) f[j] = (h ? f[4 + j] : f[j]) + __shfl_xor_sync(0xffffffffu, h ? f[j] : f[4 + j], 16);
#pragma unroll
      for (int j = 0; j < 2; j++) f[j] = (q ? f[2 + j] : f[j]) + __shfl_xor_sync(0xffffffffu, q ? f[j] : f[2 + j], 8);
      f[0] += __shfl_xor_sync(0xffffffffu, f[0], 4); f[1] += __shfl_xor_sync(0xffffffffu, f[1], 4);
      if (t9) { f[0] += __shfl_xor_sync(0xffffffffu, f[0], 2); f[1] += __shfl_xor_sync(0xffffffffu, f[1], 2); }
      if (pub) st_relaxed(mkptr(dst, ehi), pack_bf16(f[0], f[1]));
      if (FLP == 2 && lead) st_relaxed16(flag, 0);
      if (!OSV && wu == 3) {
        CBAR_SYNC(NB_MR, 160);
        if (elect_one()) signal_o(i, cta);
      }

    }
    if (wu == 0) {
      const int tid = fresh(tid0);
      const uint8_t* pp = mkptr(elo + EX_FLAG + (i + 1) * 3072 + (rank * 32 + (tid < 24 || rank == 2 ? tid : 0)) * 32, ehi);
      while (clk32() - t1 < b2) {}

      int n = 1;
      uint4 x = ld_relaxed4(pp);
      if (tid < 3) mbar_expect_tx(sb + BAR_M + 8 * tid, tid == 2 ? 8192 : 6144);
      bool mok = mbar_test(sb + BAR_MOK, ph ^ 1);
      while (__any_sync(0xffffffffu, ((x.x | x.y | x.z | x.w) & 0x80008000u) && spin < SPIN_TOT)) { x = ld_relaxed4(pp); mok = mbar_test(sb + BAR_MOK, ph ^ 1); n++; spin += 16; }
      if (!mok) mwait(sb + BAR_MOK, ph ^ 1, spin);
      if (B3 && n > 1) { const uint32_t t3 = clk32(); while (clk32() - t3 < B3) {} }
      b2 = n > 1 ? min(b2 + AD3, BMX) : max(b2 - AD2, 0);
      TSV(i + 1, 35, n); TSV(i + 1, 39, b2);
      TS(i + 1, 34);
      elect_g2s_mc(sb + OFF_M + rank * 6144, mkptr(elo + EX_M + (i + 1) * 20480 + rank * 6144, ehi), rank == 2 ? 8192 : 6144, sb + BAR_M + 8 * rank);
      TS(i + 1, 33);
      __syncwarp();
    }
  }
  if (spin >= SPIN_TOT) g_err = 1;
}

__global__ void __cluster_dims__(3, 1, 1) __launch_bounds__(384, 1)
k_chain(const __grid_constant__ CUtensorMap tmWq, const __grid_constant__ CUtensorMap tmWk,
        const __grid_constant__ CUtensorMap tmWv, const __grid_constant__ CUtensorMap tmWo, const bf16* __restrict__ x0, const bf16* __restrict__ mem0) {
  using namespace C;
  extern __shared__ __align__(1024) uint8_t smem[];
  const uint32_t sb = smem_u32(smem);
  const int tid = threadIdx.x;
  const int wg = __shfl_sync(0xffffffffu, tid >> 7, 0);
  const int cta = uni(blockIdx.x), rank = uni(blockIdx.x % 3);

  asm volatile("griddepcontrol.launch_dependents;");
  if (cta < 4) prefetch_l2(tid < 320 ? x0 + (cta * 320 + tid) * 64 : mem0 + (cta * 20 + tid % 20) * 64);
  if (tid == 32) {
    for (int p = 0; p < 5; p++) mbar_init(sb + BAR_W + 8 * p, 2);
    fence_async();
    for (int p = 0; p < NBX; p++) { stage_box<false>(tmWv, sb, p, cta, rank); stage_box<true>(tmWo, sb, p, cta, rank); }
  }
  if (tid == 0) {
    if ((sb & 0xFFFFFF) != SB0) g_err = 100;
    for (int p = 0; p < 5; p++) { mbar_init(sb + BAR_F + 8 * p, 1); mbar_init(sb + BAR_E + 8 * p, p == 2 ? (E2L ? 3 : 12) : p == 1 ? 15 : 24); }
    mbar_init(sb + BAR_M, 1); mbar_init(sb + BAR_M + 8, 1); mbar_init(sb + BAR_M + 16, 1); mbar_init(sb + BAR_MOK, 24); mbar_init(sb + BAR_XM, 1); mbar_init(sb + BAR_XF, 2);
    mbar_init(sb + BAR_XT, 1); mbar_init(sb + BAR_MF, 8); mbar_init(sb + BAR_OG, 1);
    for (int p = 0; p < 5; p++) mbar_expect_tx(sb + BAR_F + 8 * p, 16384);
    for (int p = 0; p < 16; p++) sts32(sb + OFF_SAFE + 4 * p, 0);
    for (int p = 0; p < 32; p++) sts32(sb + OFF_ONE + 4 * p, 0x3F803F80);
    asm volatile("fence.mbarrier_init.release.cluster;" ::: "memory");
    fence_async();
  }
  __syncthreads();
  asm volatile("barrier.cluster.arrive.relaxed.aligned;" ::: "memory");
  asm volatile("barrier.cluster.wait.aligned;" ::: "memory");

  if (wg == 0) chain_a(tmWo, tmWq, sb, keep(tid), cta, rank);
  else if (wg == 1) chain_q(x0, mem0, sb, keep(tid), cta, rank);
  else chain_v(tmWv, tmWk, sb, keep(tid), cta, rank);
  asm volatile("barrier.cluster.arrive.release.aligned;" ::: "memory");
  asm volatile("barrier.cluster.wait.acquire.aligned;" ::: "memory");
}

namespace W {
constexpr int NP = 25, NBC = 11, NW = NP + NBC;
constexpr int PRS = 37, PW = 43 * 2048;
constexpr int OFF_W = 0;
constexpr int OFF_R = 2 * PW;
constexpr int BRS = 36;
constexpr int OFF_WO = 0, OFF_Y = 81920;
constexpr int OFF_X = OFF_Y + 2 * (40 - BRS) * 2048;
constexpr int OFF_WV = OFF_X + 40960;
constexpr int OFF_S = OFF_WV + 81920;
constexpr int COL = 976;
constexpr int OFF_T = OFF_X + 16384;
constexpr int OFF_BAR = 232064;
constexpr int OFF_SAFE = OFF_BAR + 256;
constexpr int SMEM = 232448;
static_assert(OFF_SAFE + 64 <= SMEM && OFF_R + 40960 <= OFF_BAR && OFF_S + 7696 <= OFF_BAR, "");
constexpr uint32_t SB0 = 1024;
constexpr int BAR_F = OFF_BAR, BAR_E = OFF_BAR + 40, BAR_G = OFF_BAR + 80, BAR_W = OFF_BAR + 160, BAR_R = OFF_BAR + 176;
constexpr int NB_G0 = 1, NB_SG = 4, NB_B = 5, NB_AS = 6, NB_SG1 = 7, NB_RED = 8, NB_SF = 9, NB_R = 11, NB_TD = 12, NB_RED3 = 13;
}
#define RTL 1
#define FSL 1
#define FSW 1
#define FSA 2
#define WBAR_SYNC(id, n) bar_sync(id, n)
#define WBAR_ARRIVE(id, n) bar_arrive(id, n)

__device__ __forceinline__ uint64_t rdesc(int off, int kk) { return mkdesc(W::SB0 + off + kk * 32, 16, 1024); }
__device__ __forceinline__ uint64_t gdesc(int off, int kk) { return mkdesc_ns(W::SB0 + off + kk * 1024, 512, 512) | ((uint64_t)2 << 62); }
__device__ __forceinline__ void mma_r(float (&d)[32], const uint32_t (&a)[4], uint64_t db, int sc) { wgmma_rs64(d, a, db, sc); }
__device__ __forceinline__ void mma_r(float (&d)[16], const uint32_t (&a)[4], uint64_t db, int sc) { wgmma_rs32(d, a, db, sc); }
__device__ __forceinline__ void mma_s(float (&d)[32], uint64_t da, uint64_t db, int sc) { wgmma_ts64(d, da, db, sc); }
__device__ __forceinline__ void mma_s(float (&d)[16], uint64_t da, uint64_t db, int sc) { wgmma_ts32(d, da, db, sc); }
__device__ __forceinline__ bool dual(int k) { return k >= LAG && k < NSEG; }
__device__ __forceinline__ uint32_t frag_addr(uint32_t base, int tid) {
  const int i = (tid >> 3) & 3, r = tid & 7;
  return base + (r + (i >> 1) * 8) * 128 + (((2 * ((tid >> 5) & 3) + (i & 1)) ^ r) << 4);
}
template <int NK>
__device__ __forceinline__ void load_frags(uint32_t (&wf)[NK][4], uint32_t base, int tid) {
  const uint32_t a0 = frag_addr(base, tid);
#pragma unroll
  for (int k = 0; k < NK; k++) ldsm4t(wf[k], a0 + k * 2048);
}
__device__ __forceinline__ void red_tile(const float* d, int seg, int col0, int tid) {
  float* p = g_x + (size_t)(seg * 32 + 2 * (tid & 3)) * DM + col0 + ((tid >> 5) & 3) * 16 + ((tid >> 2) & 7) * 2;
#pragma unroll
  for (int j = 0; j < 8; j++)
    asm volatile("red.relaxed.gpu.global.add.v2.f32 [%0],{%1,%2};" ::"l"(p + ((j >> 1) * 8 + (j & 1)) * DM), "f"(d[4 * (j >> 1) + (j & 1)]), "f"(d[4 * (j >> 1) + 2 + (j & 1)]) : "memory");
}

template <int ND>
__device__ __forceinline__ void p_products(float (&d)[ND], const uint32_t (&wf)[W::PRS][4], uint32_t sb, int tid0, int& spin) {
  using namespace W;
  constexpr int KF = ND == 32 ? 4 : 8;
  const uint32_t wo = uni(fresh(tid0) >> 7) * PW;
#pragma unroll
  for (int f = 0; f < 80 / KF; f++) {
    mwait(sb + BAR_F + 8 * (f % 5), (f / 5) & 1, spin);
    wg_fence();
#pragma unroll
    for (int kk = 0; kk < KF; kk++) {
      const int q = KF * f + kk;
      const uint64_t db = rdesc(OFF_R + (f % 5) * 8192 + (kk >> 2) * 4096, kk & 3);
      if (q < 2 * PRS && !(q & 1)) mma_r(d, wf[q < 2 * PRS ? q >> 1 : 0], db, q);
      else mma_s(d, desc_at(mkdesc(SB0 + OFF_W + (q < 2 * PRS ? q >> 1 : q - PRS) * 2048, 8192, 1024), wo), db, 1);
      if (kk == KF / 4 - 1 && f > 0) {
        wg_commit();
        wg_wait<1>();
        if ((tid0 & 31) == 0) mbar_arrive(sb + BAR_E + 8 * ((f - 1) % 5));
      }
    }
    wg_commit();
  }
  wg_wait<0>();
  if ((tid0 & 31) == 0) mbar_arrive(sb + BAR_E + 32);
}
__device__ __forceinline__ void work_p(const CUtensorMap& tmWo, uint32_t sb, int pc, const int WG, int tid0) {
  using namespace W;
  asm volatile("setmaxnreg.inc.sync.aligned.u32 208;");
  int spin = 0;
  const int ks = pc / 5, col0 = (pc % 5) * 128 + WG * 64;
  const uint32_t wb = sb + OFF_W + WG * PW;
  uint32_t wf[PRS][4];
#pragma unroll 1
  for (int hf = 0; hf < 2; hf++) {
    const int nk = hf ? 80 - PRS : PRS;
    if ((tid0 & 127) == 0) {
      mbar_expect_tx(sb + BAR_W + 8 * WG, nk * 2048);
      for (int i = 0; i < nk; i++) tma2d(wb + i * 2048, &tmWo, col0, ks * 19 * 64 + (i < PRS ? 2 * i + hf : PRS + i) * 16, sb + BAR_W + 8 * WG);
    }
    __syncwarp();
    mwait(sb + BAR_W + 8 * WG, hf, spin);
    permute_cols(wb, tid0 & 127, nk * 64);
    if (hf == 1 && ks < 4) for (int it = 39 * 64 + (tid0 & 127) - 64; it < 43 * 64; it += 128) {
      const uint32_t a = wb + (it >> 2) * 128 + (((2 * (it & 3)) ^ ((it >> 2) & 6)) << 4);
      if (it >= 39 * 64) { sts128(a, make_uint4(0, 0, 0, 0)); sts128(a + 16, make_uint4(0, 0, 0, 0)); }
    }
    fence_async();
    WBAR_SYNC(NB_G0 + WG, 128);
    if (hf == 0) {
      load_frags<PRS>(wf, wb, tid0);
      fence_async();
      WBAR_SYNC(NB_G0 + WG, 128);
    }
  }
#pragma unroll 1
  for (int k = 0; k < NSTEP; k++) {
    if (dual(k)) {
      float d[32];
      p_products(d, wf, sb, tid0, spin);
      if (WG == 0 && pc == WW) WTS(k, 2);
      red_tile(d, k, col0, tid0);
      red_tile(d + 16, k - LAG, col0, tid0);
    } else {
      float d[16];
      p_products(d, wf, sb, tid0, spin);
      if (WG == 0 && pc == WW) WTS(k, 2);
      red_tile(d, k < LAG ? k : k - LAG, col0, tid0);
    }
    if (WG == 0 && pc == WW) WTS(k, 13);
    WBAR_SYNC(NB_SG, 288);
  }
  if (spin >= SPIN_TOT) g_err = 11;
}
__device__ __forceinline__ void work_p_producer(uint32_t sb, int pc) {
  using namespace W;
  int spin = 0;
  const int ks = pc / 5;
#pragma unroll 1
  for (int k = 0; k < NSTEP; k++) {
    const bool two = dual(k);
    const uint8_t* src = &g_o[k % ORING][ks * 19][k < NSEG ? 0 : 4096];
    cwait(CN_O + k * 5 + ks, ks == 4 ? 20 : 19, spin);
    fence_async_all();
    if (pc == WW) WTS1(k, 0);
    if (two) {
#pragma unroll 1
      for (int u = 0; u < 4; u++, src += 40960) {
#pragma unroll
        for (int st = 0; st < 5; st++) {
          const uint8_t* p = src + (st == 4 && u == 3 && ks < 4 ? 3 : st) * 8192;
          mwait(sb + BAR_E + 8 * st, (u & 1) ^ 1, spin);
          fill_stage(sb + OFF_R + st * 8192, p, 8192, sb + BAR_F + 8 * st);
        }
      }
    } else {
#pragma unroll 1
      for (int f = 0; f < 10; f++, src += 16384) {
        const int st = f % 5;
        mwait(sb + BAR_E + 8 * st, f < 5, spin);
        fill_stage2(sb + OFF_R + st * 8192, src, src + (f == 9 && ks < 4 ? 0 : 8192), sb + BAR_F + 8 * st);
      }
    }
  }
  if (spin >= SPIN_TOT) g_err = 12;
}
template <int DMS>
__device__ __forceinline__ void work_ln(const int kind, int r, int lane, bf16* out) {
  int spin = 0;
  const int l = kind & 1;
  const int rp = kind < 2 ? (r & 1) * 16 + (r >> 1) : r;
  const uint32_t sw = ((((lane >> 1) & 7) ^ (rp & 7)) << 4) + (lane & 1) * 8;
  uint8_t* dst = kind < 2 ? g_xnb[l * LAG] + (lane >> 4) * 8192 + l * 4096 + rp * 128 + sw
               : kind == 2 ? g_xn[LAG] + (r >> 3) * 4096 + 2048 + (lane >> 4) * 1024 + (r & 7) * 128 + sw
                           : reinterpret_cast<uint8_t*>(out) + r * 1280 + lane * 8;
  if (FSL && kind < 2) {
#pragma unroll
    for (int m = 0; m < 5; m++) asm volatile("st.global.v2.b32 [%0],{%1,%1};" ::"l"(dst + m * DMS), "r"(SENT) : "memory");
    fence_gpu();
  }
#pragma unroll 1
  for (int s = 0; s < NSEG; s++) {
    float* xr = g_x + (size_t)(s * 32 + r) * DM;
    float4 v[5];
    if (kind < 2) {
#pragma unroll
      for (int u = 0; u < 5; u++) {
        const int p = u * 32 + lane;
        stg128((p < 80 ? g_ob[s + l * LAG] + (l * 32 + r) * 1280 : g_y[l] + (size_t)s * 40960 + (r - 1) * 1280) + p * 16, make_uint4(SENT, SENT, SENT, SENT));
      }
      if (FSL && s + 1 < NSEG) {
#pragma unroll
        for (int m = 0; m < 5; m++) asm volatile("st.global.v2.b32 [%0],{%1,%1};" ::"l"(dst + 81920 + m * DMS), "r"(SENT) : "memory");
      }
      if (lane == 0) cwait(CN_P + s + l * LAG, W::NP, spin);
      __syncwarp();
      if (r == 0 && lane == 0 && (l == 0 || s + LAG >= NSEG)) WTS1(s + l * LAG, 3);
#pragma unroll
      for (int m = 0; m < 5; m++) v[m] = ld_relaxed4f(xr + m * 128 + lane * 4);
    } else {
      if (lane == 0) cwait(CN_L + s + l * LAG, s + l * LAG < LAG || s + l * LAG >= NSEG ? 32 : 64, spin);
      __syncwarp();
#pragma unroll
      for (int m = 0; m < 5; m++) v[m] = ld_relaxed4f(xr + m * 128 + lane * 4);
      if (lane == 0) cwait(CN_W + l * 64 + s, 10, spin);
      __syncwarp();
      if (r == 0 && lane == 0 && (l == 0 || s + LAG >= NSEG)) WTS1(s + l * LAG, 11);
      const uint8_t* yp = g_y[l] + (size_t)s * 40960 + (lane >> 4) * 4096 + r * 128 + sw;
      float2 y[5];
      bool bad;
      do {
        bad = false;
#pragma unroll
        for (int m = 0; m < 5; m++) y[m] = ld_relaxed2f(yp + m * 8192);
#pragma unroll
        for (int m = 0; m < 5; m++) bad |= __float_as_uint(y[m].x) == SENT || __float_as_uint(y[m].y) == SENT;
        spin += 16;
      } while (__any_sync(0xffffffffu, bad && spin < SPIN_TOT));
#pragma unroll
      for (int m = 0; m < 5; m++) {
        v[m].x += bf_lo(__float_as_uint(y[m].x)); v[m].y += bf_hi(__float_as_uint(y[m].x));
        v[m].z += bf_lo(__float_as_uint(y[m].y)); v[m].w += bf_hi(__float_as_uint(y[m].y));
        if (kind == 2) *reinterpret_cast<float4*>(xr + m * 128 + lane * 4) = v[m];
      }
    }
    if (FSL == 3 && kind < 2 && lane == 0) csignal_fast(CN_G + s + l * LAG);
    if (kind < 3) ln_row(v);
#pragma unroll
    for (int m = 0; m < 5; m++)
      asm volatile("st.global.v2.b32 [%0],{%1,%2};" ::"l"(dst + m * DMS), "r"(pack_bf16(v[m].x, v[m].y)), "r"(pack_bf16(v[m].z, v[m].w)) : "memory");
    dst += DMS == 256 ? 40960 : 81920;
    __syncwarp();
    if (r == 0 && lane == 0 && (l == 0 || s + LAG >= NSEG)) WTS1(s + l * LAG, kind < 2 ? 4 : 12);
    if (lane == 0 && kind < (NOWORK ? 2 : 3)) {
      if (FSL && kind < 2) csignal_fast(CN_G + s + l * LAG);
      csignal_t(kind < 2 ? CN_L + s + l * LAG : CN_X + s + LAG, kind);
    }
  }
  if (spin >= SPIN_TOT) g_err = 13;
}

__device__ __forceinline__ void work_prep(const bf16* x0, const bf16* mem0, int r, int lane) {
  int spin = 0;
#pragma unroll 1
  for (int k = NPRE; k < NSTEP; k++) {
    if (lane < 20) prefetch_l2(x0 + (size_t)min(k * 32 + r + (lane < 10 ? 0 : 16), SEQ - 1) * DM + (lane % 10) * 64);
    if (lane == 0) cwait(CN_O + (k - NPRE) * 5, 1, spin);
    __syncwarp();
#pragma unroll 1
    for (int h = 0; h < 2; h++) {
      uint2 u[5];
      ln0_load(x0, u, min(k * 32 + r + 16 * h, SEQ - 1), lane);
      prep_row(u, mem0, k, r + 16 * h, lane);
    }
    __syncwarp();
    if (lane == 0) csignal(CN_X + k);
  }
  if (spin >= SPIN_TOT) g_err = 19;
}

__device__ __forceinline__ void stage_qkv(const bf16* wqkv, uint32_t base, int T, int bc, int tid) {
  const int q = tid & 15;
  const bool ok = q < 15 && bc * 60 + 4 * q < DM;
  const bf16* src = wqkv + T * DM + bc * 60 + 4 * q;
#pragma unroll 1
  for (int k0 = tid >> 4; k0 < 640; k0 += 80) {
    uint2 v[10];
#pragma unroll
    for (int u = 0; u < 10; u++) v[u] = ok ? *reinterpret_cast<const uint2*>(src + (size_t)(k0 + 8 * u) * 1920) : make_uint2(0, 0);
#pragma unroll
    for (int u = 0; u < 10; u++) sts64(base + (k0 + 8 * u) * 128 + (((q >> 1) ^ (k0 & 7)) << 4) + (q & 1) * 8, v[u].x, v[u].y);
  }
}
struct AttAddr { uint32_t qa, qb, ka, oa, ob, ml; };
__device__ __forceinline__ AttAddr att_addr(uint32_t sb, int bc, int hh, int tid) {
  using namespace W;
  const int r = tid & 7, m = (tid >> 3) & 3, g = (tid >> 2) & 7, t = tid & 3, lp = (tid >> 5) & 3;
  const int f2 = r < 4 ? 20 * hh + 16 + r : 60;
  const uint32_t tb = sb + OFF_T + 2 * lp * COL;
  const int fa = 20 * hh + (m >> 1) * 8 + r, pc = 2 * (lp & 1) + (m & 1);
  const uint32_t o0 = sb + OFF_S + (lp >> 1) * 3840;
  AttAddr x;
  x.qa = keep(tb + (m & 1) * COL + (20 * hh + (m >> 1) * 8 + r) * 16);
  x.qb = keep(tb + (m & 1) * COL + f2 * 16);
  x.ka = keep(tb + (m < 2 ? 20 * hh + 8 * m + r : f2) * 16);
  x.oa = keep(o0 + fa * 64 + ((pc ^ ((bc * 60 + fa) >> 1)) & 3) * 16);
  x.ob = keep(r < 4 ? o0 + f2 * 64 + ((pc ^ ((bc * 60 + f2) >> 1)) & 3) * 16 : sb + OFF_S + 7680);
  x.ml = keep((2 * t > g ? 0xFFFFu : 0u) | (2 * t + 1 > g ? 0xFFFF0000u : 0u));
  return x;
}
__device__ __forceinline__ void release_tiles(uint32_t sb, int tid) {
  fence_async();
  __syncwarp();
  if ((tid & 31) < 3) mbar_arrive(sb + W::BAR_E + 16 + 8 * (tid & 3));
}
__device__ __forceinline__ void attend(uint32_t sb, const AttAddr& x, uint32_t (&hist)[6], int k0, int lp, int tid) {
  using namespace W;
  const float scl = 0.22360679774997896f * 1.4426950408889634f;
  float sc[3][4];
  uint32_t v[3][4];
  {
    uint32_t q[4], q8a, q8b, k[3][4];
    ldsm4t(q, x.qa);
    ldsm4t(k[1], x.ka + 8 * COL); ldsm4t(k[2], x.ka + 9 * COL);
    ldsm2t(q8a, q8b, x.qb);
    ldsm4(v[1], x.ka + 16 * COL); ldsm4(v[2], x.ka + 17 * COL);
#pragma unroll
    for (int j = 0; j < 3; j++) { k[0][j] = hist[j]; v[0][j] = hist[3 + j]; hist[j] = k[2][j]; hist[3 + j] = v[2][j]; }
#pragma unroll
    for (int c = 0; c < 3; c++) { sc[c][0] = sc[c][1] = sc[c][2] = sc[c][3] = 0.f; mma16816(sc[c], q[0], q[1], q[2], q[3], k[c][0], k[c][1]); }
#pragma unroll
    for (int c = 0; c < 3; c++) mma1688(sc[c], q8a, q8b, k[c][2]);
  }
  if (RTL == 0) release_tiles(sb, tid);
  const bool lo0 = x.ml & 1, lo1 = (int)x.ml < 0, first = k0 == (lp >> 1) * LAG;
  uint32_t pw[2];
  float inv[2];
#pragma unroll
  for (int h = 0; h < 2; h++) {
    float y0 = lo0 ? sc[h][2 * h] : sc[h + 1][2 * h], y1 = lo1 ? sc[h][2 * h + 1] : sc[h + 1][2 * h + 1];
    if (h == 0 && first) { y0 = lo0 ? -INFINITY : y0; y1 = lo1 ? -INFINITY : y1; }
    const float mx = quad_max(fmaxf(y0, y1)) * -scl;
    y0 = ex2(fmaf(y0, scl, mx)); y1 = ex2(fmaf(y1, scl, mx));
    pw[h] = pack_bf16(y0, y1);
    inv[h] = y0 + y1;
  }
  float o[3][4];
  const uint32_t a0 = pw[0] & x.ml, a2 = pw[0] & ~x.ml, a3 = pw[1] & x.ml, a5 = pw[1] & ~x.ml, z0 = tid >> 10, z1 = tid >> 11;
#pragma unroll
  for (int j = 0; j < 3; j++) { o[j][0] = o[j][1] = o[j][2] = o[j][3] = 0.f; mma16816(o[j], a0, z0, a2, a3, v[0][j], v[1][j]); }
#pragma unroll
  for (int j = 0; j < 3; j++) mma1688(o[j], z1, a5, v[2][j]);
  if (RTL == 1) release_tiles(sb, tid);
  inv[0] = rcp(quad_sum(inv[0])); inv[1] = rcp(quad_sum(inv[1]));
  stsm4t(x.oa, pack_bf16(o[0][0] * inv[0], o[0][1] * inv[0]), pack_bf16(o[0][2] * inv[1], o[0][3] * inv[1]),
         pack_bf16(o[1][0] * inv[0], o[1][1] * inv[0]), pack_bf16(o[1][2] * inv[1], o[1][3] * inv[1]));
  stsm2t(x.ob, pack_bf16(o[2][0] * inv[0], o[2][1] * inv[0]), pack_bf16(o[2][2] * inv[1], o[2][3] * inv[1]));
  if (RTL == 2) release_tiles(sb, tid); else fence_async();
}
__device__ __forceinline__ bool b_job(int k, int u, int bc) { return u == 0 || (u == 1 ? dual(k) : bc < 10 && (u == 3 || dual(k - 1))); }
template <bool IS_V, int ND, int NR>
__device__ __forceinline__ void qkv_step(float (&d)[ND], const uint32_t (&wf)[NR][4], const int q, uint32_t yo, uint64_t db) {
  using namespace W;
  if (!IS_V && q < NR) mma_r(d, wf[q < NR ? q : 0], db, q);
  else if (IS_V) mma_s(d, mkdesc(SB0 + OFF_WV + q * 2048, 8192, 1024), db, q);
  else mma_s(d, desc_at(mkdesc(SB0 + OFF_Y + (q - NR) * 2048, 8192, 1024), yo), db, 1);
}
template <bool IS_V, int ND, int NR>
__device__ __forceinline__ bool qkv_products(uint32_t (&pk)[16], const uint32_t (&wf)[NR][4], uint32_t sb, uint32_t pf, int tid0, int& spin) {
  using namespace W;
  constexpr int KF = ND == 32 ? 4 : 8, NF = 40 / KF;
  const uint32_t yo = uni(fresh(tid0) >> 7) * (40 - BRS) * 2048;
  float d[ND];
#pragma unroll
  for (int c = 0; c < NF; c++) {
    mwait(sb + BAR_F + 8 * (c % 5), pf ^ (c / 5), spin);
    wg_fence();
#pragma unroll
    for (int kk = 0; kk < KF; kk++) qkv_step<IS_V>(d, wf, KF * c + kk, yo, rdesc(OFF_X + (c % 5) * 8192 + (kk >> 2) * 4096, kk & 3));
    wg_commit();
    if (c > 0 && c <= NF - 3) {
      wg_wait<1>();
      if ((tid0 & 31) == 0) mbar_arrive(sb + BAR_E + 8 * ((c - 1) % 5));
    }
  }
  wg_wait<0>();
#pragma unroll
  for (int q = 0; q < 16; q++) pk[q] = pin(pack_bf16(d[(2 * q) % ND], d[(2 * q + 1) % ND]));
  float c0 = ((d[0] + d[1]) + (d[4] + d[5])) + ((d[8] + d[9]) + (d[12] + d[13]));
  if (ND == 32) c0 += ((d[16 % ND] + d[17 % ND]) + (d[20 % ND] + d[21 % ND])) + ((d[24 % ND] + d[25 % ND]) + (d[28 % ND] + d[29 % ND]));
  return IS_V && c0 != c0;
}
template <bool IS_V>
__device__ __forceinline__ void work_b(const CUtensorMap& tmBo, const bf16* wqkv, uint32_t sb, int bc, const int wg, int tid0) {
  using namespace W;
  if (!IS_V) asm volatile("setmaxnreg.inc.sync.aligned.u32 208;");
  else asm volatile("setmaxnreg.dec.sync.aligned.u32 72;");
  constexpr int NR = IS_V ? 1 : BRS;
  const int WG = IS_V ? 2 : wg;
  const uint32_t yo = WG * (40 - BRS) * 2048;
  int spin = 0;
  uint32_t wf[NR][4];
  if (!IS_V) {
    const uint32_t wb = sb + (WG ? OFF_WO : OFF_WV);
    stage_qkv(wqkv, wb, WG, bc, tid0 & 127);
    WBAR_SYNC(NB_G0 + WG, 128);
    load_frags<NR>(wf, wb, tid0);
#pragma unroll
    for (int k = NR; k < 40; k++) sts128(sb + OFF_Y + yo + (k - NR) * 2048 + (tid0 & 127) * 16, lds128(wb + k * 2048 + (tid0 & 127) * 16));
    fence_async();
  }
  WBAR_SYNC(NB_B, 384);
  if (WG == 1 && bc < 10) {
    if ((tid0 & 127) == 0) {
      mbar_expect_tx(sb + BAR_W, 81920);
      for (int i = 0; i < 10; i++) tma2d(sb + OFF_WO + i * 8192, &tmBo, bc * 64, i * 64, sb + BAR_W);
    }
    __syncwarp();
    mwait(sb + BAR_W, 0, spin);
  }
  if (IS_V) stage_qkv(wqkv, sb + OFF_WV, 2, bc, tid0 & 127);
  fence_async();
  WBAR_SYNC(NB_B, 384);
  const int wu = uni((tid0 >> 5) & 3);
  uint32_t nredo = 0, hist[6] = {};
  const AttAddr aa = att_addr(sb, bc, WG, tid0);
#pragma unroll 1
  for (int k = 0; k < NSTEP; k++) {
    {
      uint32_t pk[16];
      const bool bad = dual(k) ? qkv_products<IS_V, 32>(pk, wf, sb, LAG & 1, tid0, spin) : qkv_products<IS_V, 16>(pk, wf, sb, (k < LAG ? k : k - NSEG + LAG) & 1, tid0, spin);
      if (bc == 0 && WG != 1) WTS(k, 16 + WG / 2);
      const int tid = fresh(tid0), m = (tid >> 3) & 3;
      const uint32_t a = pin(sb + OFF_T + min(wu * 16 + (m & 1) * 8 + (tid & 7), 60) * 16 + (8 * WG + (m >> 1)) * COL);
      if (!FSL) WBAR_SYNC(NB_B, 384);
      else {
        if (__builtin_expect(bar_red_or(NB_RED3, 384, bad), 0)) {
          float d[32];
          if (IS_V && wu == 0) { cwait(CN_L + k, k < LAG || k >= NSEG ? 32 : 64, spin); fence_async_all(); }
#pragma unroll
          for (int c = 0; c < 10; c++) {
            if (IS_V && wu == 0 && elect_one()) { mbar_expect_tx(sb + BAR_R + 8, 8192); bulk_g2s(sb + OFF_X + 32768, g_xnb[k] + c * 8192, 8192, sb + BAR_R + 8); }
            __syncwarp();
            mwait(sb + BAR_R + 8, c & 1, spin);
            wg_fence();
#pragma unroll
            for (int kk = 0; kk < 4; kk++) qkv_step<IS_V>(d, wf, 4 * c + kk, yo, rdesc(OFF_X + 32768, kk));
            wg_commit();
            wg_wait<0>();
            bar_sync(NB_RED3, 384);
          }
#pragma unroll
          for (int q = 0; q < 16; q++) pk[q] = pin(pack_bf16(d[2 * q], d[2 * q + 1]));
        }
      }
#pragma unroll
      for (int p = 0; p < 4; p++) stsm4(a + 2 * p * COL, pk[4 * p], pk[4 * p + 1], pk[4 * p + 2], pk[4 * p + 3]);
    }
    WBAR_SYNC(NB_TD, 448);
    if (bc == 0 && WG == 0) WTS(k, 7);
    if (bc * 3 + WG < NH && (wu < 2 ? k < NSEG : k >= LAG)) attend(sb, aa, hist, k, wu, fresh(tid0));
    else release_tiles(sb, tid0);
    if (bc == 0 && WG == 0) WTS(k, 8);
    WBAR_SYNC(NB_AS, 416);
    if (!IS_V && b_job(k, 2 + WG, bc)) {
      float d[16];
#pragma unroll
      for (int f = 0; f < 5; f++) {
        mwait(sb + BAR_G + 40 * WG + 8 * f, (WG ? k : k - LAG - 1) & 1, spin);
        if (f == 0 && bc == 0) WTS(k - 1 + WG, WG ? 20 : 23);
        wg_fence();
#pragma unroll
        for (int kk = 0; kk < 8; kk++) {
          wgmma_tt32(d, mkdesc(SB0 + OFF_WO + (8 * f + kk) * 2048, 8192, 1024), gdesc(OFF_X + f * 8192, kk), f | kk);
          if (kk == 1 && f > 0) {
            wg_commit();
            wg_wait<1>();
            if ((tid0 & 31) < 3) mbar_arrive(sb + BAR_E + 8 * (f - 1));
          }
        }
        wg_commit();
      }
      wg_wait<0>();
      if (WG == 1 && FSA) {
        const float chk = ((d[0] + d[1]) + (d[4] + d[5])) + ((d[8] + d[9]) + (d[12] + d[13]));
        if (__builtin_expect(bar_red_or(NB_RED, 128, chk != chk), 0)) {
          if (wu == 0) { cwait(CN_A + k, NBC, spin); fence_async_all(); }
#pragma unroll
          for (int q = 0; q < 16; q++) d[q] = 0.f;
#pragma unroll 1
          for (int f = 0; f < 5; f++) {
            if (wu == 0 && elect_one()) { mbar_expect_tx(sb + BAR_W + 8, 8192); bulk_g2s(sb + OFF_X + 32768, g_ob[k] + (k < NSEG ? 0 : 40960) + f * 8192, 8192, sb + BAR_W + 8); }
            __syncwarp();
            mwait(sb + BAR_W + 8, nredo & 1, spin);
            nredo++;
            wg_fence();
#pragma unroll
            for (int kk = 0; kk < 8; kk++)
              wgmma_tt32(d, desc_at(mkdesc(SB0 + OFF_WO + kk * 2048, 8192, 1024), f * 16384), gdesc(OFF_X + 32768, kk), 1);
            wg_commit();
            wg_wait<0>();
            bar_sync(NB_RED, 128);
          }
        }
      }
      else if (WG) bar_sync(NB_RED, 128);
      else {
        if ((tid0 & 31) < 3) mbar_arrive(sb + BAR_E + 32);
        WBAR_SYNC(NB_SF, 160);
      }
      if (bc == 0) WTS(k - 1 + WG, WG ? 10 : 24);
      const int tid = fresh(tid0), m = (tid >> 3) & 3, row = (m >> 1) * 16 + 2 * (tid & 7);
      const uint32_t a = sb + (WG ? OFF_X + 32768 : OFF_S) + row * 128 + (((2 * wu + (m & 1)) ^ row) & 7) * 16;
#pragma unroll
      for (int p = 0; p < 2; p++)
        stsm4t(a ^ (p * 144), pack_bf16(d[8 * p], d[8 * p + 1]), pack_bf16(d[8 * p + 2], d[8 * p + 3]), pack_bf16(d[8 * p + 4], d[8 * p + 5]), pack_bf16(d[8 * p + 6], d[8 * p + 7]));
      fence_async();
      WBAR_SYNC(WG ? NB_SG : NB_SG1, 160);
    }
  }
  if (spin >= SPIN_TOT) g_err = 14;
}
__device__ __forceinline__ void work_b_watch(uint32_t sb, int bc) {
  using namespace W;
  int spin = 0;
#pragma unroll 1
  for (int j = 0; j < 4 * NSTEP; j++) {
    const int k = j >> 2, u = j & 3;
    if (u == 1 || !b_job(k, u, bc)) continue;
    cwait(u == 0 ? (FSL ? CN_G : CN_L) + k : u == 2 ? CN_A + k - 1 : (FSA ? CN_F : CN_A) + k, u ? NBC : k < LAG || k >= NSEG ? 32 : 64, spin);
    fence_async_all();
    if (bc == 0 && u != 2) WTS1(k, u ? 9 : 5);
    if (elect_one()) mbar_arrive(sb + BAR_R + 8 * u);
    __syncwarp();
    if (u == 0) WBAR_SYNC(NB_R, 64);
  }
  if (spin >= SPIN_TOT) g_err = 16;
}
__device__ __forceinline__ void work_b_producer(uint32_t sb, int bc) {
  using namespace W;
  int spin = 0;
  uint32_t pe = 1;
#pragma unroll 1
  for (int j = 0; j < 4 * NSTEP; j++) {
    const int k = j >> 2, u = j & 3;
    if (!b_job(k, u, bc)) continue;
    const uint32_t half = u < 2 && !dual(k), lo = half && k >= NSEG ? 4096 : 0, fb = sb + (u < 2 ? BAR_F : BAR_G + 40 * (u - 2));
    const uint8_t* src = (u < 2 ? g_xnb[k] + u * 40960 : u == 2 ? g_ob[k - 1] + 40960 : g_ob[k] + (k < NSEG ? 0 : 40960)) + lo;
    mwait(sb + BAR_E, pe, spin);
    if (u != 1) mwait(sb + BAR_R + 8 * u, (u == 2 ? k - LAG - 1 : k) & 1, spin);
    if (!half) {
#pragma unroll
      for (int f = 0; f < 5; f++) {
        if (f) mwait(sb + BAR_E + 8 * f, pe, spin);
        fill_stage(sb + OFF_X + f * 8192, src + f * 8192, 8192, fb + 8 * f);
      }
    } else {
#pragma unroll 1
      for (int f = 0; f < 5; f++) {
        mwait(sb + BAR_E + 8 * f, pe, spin);
        fill_stage2(sb + OFF_X + f * 8192, src + f * 16384, src + f * 16384 + 8192, fb + 8 * f);
      }
    }
    if (u == 0) WBAR_SYNC(NB_R, 64);
    pe ^= 1;
  }
  if (spin >= SPIN_TOT) g_err = 15;
}

__global__ void __launch_bounds__(512, 1)
k_work(const __grid_constant__ CUtensorMap tmWo, const __grid_constant__ CUtensorMap tmBo, const bf16* __restrict__ wqkv, bf16* __restrict__ out,
       const bf16* __restrict__ x0, const bf16* __restrict__ mem0) {
  using namespace W;
  extern __shared__ __align__(1024) uint8_t smem[];
  const uint32_t sb = smem_u32(smem);
  const int tid = threadIdx.x, w = blockIdx.x;
  const int wg = __shfl_sync(0xffffffffu, tid >> 7, 0);
  if (tid == 0) {
    if (sb != SB0) g_err = 101;
    for (int i = 0; i < 5; i++) { mbar_init(sb + BAR_F + 8 * i, 1); mbar_init(sb + BAR_E + 8 * i, w < NP ? 8 : 12); }
    for (int i = 0; i < 16; i++) mbar_init(sb + BAR_G + 8 * i, 1);
    for (int p = 0; p < 16; p++) sts32(sb + OFF_SAFE + 4 * p, 0);
    asm volatile("fence.mbarrier_init.release.cluster;" ::: "memory");
    int spin = 0;
    pre_wait(1, NW, spin);
    if (spin >= SPIN_TOT) g_err = 18;
  }
  fence_async();
  __syncthreads();

  if (w < NP) {
    if (wg < 2) work_p(tmWo, sb, w, wg, keep(tid));
    else {
      asm volatile("setmaxnreg.dec.sync.aligned.u32 48;");
      const int aw = uni(tid >> 5) - 8;
      if (aw == 0) work_p_producer(sb, w);
      else if (aw == 1) {
#pragma unroll 1
        for (int k = 0; k < NSTEP; k++) {
          WBAR_SYNC(NB_SG, 288);
          if (elect_one()) csignal_t(CN_P + k, 3);
          __syncwarp();
        }
      } else {
        const int id = (aw - 2) * NP + w;
        if (id < 96) work_ln<16384>(id % 3, id / 3, tid & 31, out);
        else if (id < 128) work_ln<256>(3, id - 96, tid & 31, out);
        else if (id < 144 && NOWORK != 2) work_prep(x0, mem0, id - 128, tid & 31);
      }
    }
  } else {
    const int bc = w - NP;
    if (wg < 2) work_b<false>(tmBo, wqkv, sb, bc, wg, keep(tid));
    else if (wg == 2) work_b<true>(tmBo, wqkv, sb, bc, wg, keep(tid));
    else {
      asm volatile("setmaxnreg.dec.sync.aligned.u32 24;");
      const int aw = uni(tid >> 5) - 12;
      if (aw == 0) work_b_producer(sb, bc);
      else if (aw == 1) work_b_watch(sb, bc);
      else if (aw == 2) {
#pragma unroll 1
        for (int k = 0; k < NSTEP; k++) {
          WBAR_ARRIVE(NB_TD, 448);
          if (FSA == 3 && (tid & 31) == 0) csignal_fast(CN_F + k);
          WBAR_SYNC(NB_AS, 416);
          if (elect_one()) {
            const uint32_t len = bc < 10 ? 3840 : 2560;
            const int l = k >= NSEG;
            bulk_s2g(g_ob[k] + l * 40960 + bc * 3840, sb + OFF_S + l * 3840, len);
            if (FSA) csignal_fast(CN_F + k);
            if (dual(k)) bulk_s2g(g_ob[k] + 40960 + bc * 3840, sb + OFF_S + 3840, len);
            asm volatile("cp.async.bulk.commit_group;" ::: "memory");
            asm volatile("cp.async.bulk.wait_group 0;" ::: "memory");
          }
          __syncwarp();
          if (b_job(k, 2, bc)) WBAR_ARRIVE(NB_SF, 160);
          if (elect_one()) { fence_async_all(); csignal_t(CN_A + k, 5); }
          __syncwarp();
        }
      } else {
#pragma unroll 1
        for (int j = 0; j < 2 * NSTEP; j++) {
          const int k = j >> 1, pr = j & 1, l = !pr || k >= NSEG, s = k - l * LAG - !pr;
          if (!pr) WBAR_SYNC(NB_TD, 448);
          if (!b_job(k, 2 + pr, bc)) continue;
          WBAR_SYNC(pr ? NB_SG : NB_SG1, 160);
          if (elect_one()) {
            bulk_s2g(g_y[l] + (size_t)s * 40960 + bc * 4096, sb + (pr ? OFF_X + 32768 : OFF_S), 4096);
            asm volatile("cp.async.bulk.commit_group;" ::: "memory");
            if (FSW) csignal_fast(CN_W + l * 64 + s);
            asm volatile("cp.async.bulk.wait_group.read 0;" ::: "memory");
            if (!FSW) csignal_fast(CN_W + l * 64 + s);
            if (pr) asm volatile("mbarrier.arrive.shared::cta.b64 _,[%0],12;" ::"r"(sb + BAR_E + 32) : "memory");
          }
          __syncwarp();
        }
      }
    }
  }
  __syncthreads();
  asm volatile("griddepcontrol.wait;" ::: "memory");
}

typedef CUresult (*EncodeFn)(CUtensorMap*, CUtensorMapDataType, cuuint32_t, void*, const cuuint64_t*, const cuuint64_t*,
                             const cuuint32_t*, const cuuint32_t*, CUtensorMapInterleave, CUtensorMapSwizzle,
                             CUtensorMapL2promotion, CUtensorMapFloatOOBfill);

static void make_map(EncodeFn enc, CUtensorMap* tm, const void* ptr, uint64_t cols, uint64_t rows, uint32_t boxc, uint32_t boxr) {
  cuuint64_t dims[2] = {cols, rows};
  cuuint64_t strides[1] = {cols * 2};
  cuuint32_t box[2] = {boxc, boxr};
  cuuint32_t es[2] = {1, 1};
  enc(tm, CU_TENSOR_MAP_DATA_TYPE_BFLOAT16, 2, const_cast<void*>(ptr), dims, strides, box, es, CU_TENSOR_MAP_INTERLEAVE_NONE,
      CU_TENSOR_MAP_SWIZZLE_128B, CU_TENSOR_MAP_L2_PROMOTION_L2_256B, CU_TENSOR_MAP_FLOAT_OOB_FILL_NONE);
}

extern "C" void kernel_launch(void* const* d_in, const int* in_sizes, int n_in, void* d_out, int out_size) {
  const bf16* x0 = (const bf16*)d_in[0];
  const bf16* mem0 = (const bf16*)d_in[1];
  const bf16* Wq = (const bf16*)d_in[2];
  const bf16* Wk = (const bf16*)d_in[3];
  const bf16* Wv = (const bf16*)d_in[4];
  const bf16* Wo = (const bf16*)d_in[5];
  const bf16* Bqkv = (const bf16*)d_in[8];
  const bf16* Bwo = (const bf16*)d_in[9];
  bf16* out = (bf16*)d_out;

  static EncodeFn enc = nullptr;
  if (!enc) {
    void* fn = nullptr;
    cudaDriverEntryPointQueryResult qr;
    cudaGetDriverEntryPoint("cuTensorMapEncodeTiled", &fn, cudaEnableDefault, &qr);
    enc = (EncodeFn)fn;
    cudaFuncSetAttribute(k_chain, cudaFuncAttributeMaxDynamicSharedMemorySize, C::SMEM);
    cudaFuncSetAttribute(k_work, cudaFuncAttributeMaxDynamicSharedMemorySize, W::SMEM);
  }
  CUtensorMap tmWq, tmWk, tmWv, tmWo, tmWp, tmBo;
  make_map(enc, &tmWq, Wq, NH * DH, DM, 64, 128);
  make_map(enc, &tmWk, Wk, NH * DH, DM, 64, 128);
  make_map(enc, &tmWv, Wv, NH * DH, DM, 64, 128);
  make_map(enc, &tmWo, Wo, DM, NH * DH, 64, 64);
  make_map(enc, &tmWp, Wo, DM, NH * DH, 64, 16);
  make_map(enc, &tmBo, Bwo, DM, DM, 64, 64);

  cudaStream_t st = cudaStreamPerThread;
  cudaLaunchAttribute at[1];
  at[0].id = cudaLaunchAttributeProgrammaticStreamSerialization; at[0].val.programmaticStreamSerializationAllowed = 1;
  {
    cudaLaunchConfig_t cfg = {};
    cfg.gridDim = dim3(96); cfg.blockDim = dim3(384); cfg.dynamicSmemBytes = C::SMEM; cfg.stream = st;
    cfg.attrs = at; cfg.numAttrs = 0;
    cudaLaunchKernelEx(&cfg, k_chain, tmWq, tmWk, tmWv, tmWo, x0, mem0);
  }
  cudaLaunchConfig_t cfg = {};
  cfg.gridDim = dim3(W::NW); cfg.blockDim = dim3(512); cfg.dynamicSmemBytes = W::SMEM; cfg.stream = st;
  cfg.attrs = at; cfg.numAttrs = NOWORK == 2 ? 0 : 1;
  cudaLaunchKernelEx(&cfg, k_work, tmWp, tmBo, Bqkv, out, x0, mem0);
}
```

```cpp
#include <cuda_runtime.h>
#include <cuda_bf16.h>
#include <cuda.h>
#include <stdint.h>

typedef __nv_bfloat16 bf16;

constexpr int SEQ = 2048, DM = 640, NH = 32, DH = 192, NSEG = 64;
#define LAG 5
constexpr int NSTEP = NSEG + LAG;
constexpr int NPRE = 4;
constexpr uint32_t SENT = 0xFFFFFFFFu;

constexpr int MAIL9 = 288 * 2048, MAIL_BYTES = MAIL9 + 64 * 3072;
__device__ __align__(1024) uint8_t g_xn[NSTEP][81920];
__device__ __align__(1024) uint8_t g_xnb[NSTEP][81920];
__device__ __align__(1024) uint8_t g_ob[NSTEP][81920];
__device__ __align__(1024) uint8_t g_y[2][NSEG * 40960];
#define ORING 8
static_assert(ORING > LAG, "a slot is free again LAG + 1 steps later");
__device__ __align__(1024) uint8_t g_o[ORING][96][8192];
__device__ __align__(1024) float g_x[SEQ * DM];
constexpr int EX_MAIL = 0;
constexpr int EX_M = 2 << 20;
constexpr int EX_FLAG = EX_M + NSTEP * 20480;
__host__ __device__ constexpr int m_tile(int j) { return (int)((0x9852741630ull >> (4 * j)) & 15); }
static_assert(EX_FLAG + NSTEP * 3072 <= (4 << 20), "");
__device__ __align__(1024) uint8_t g_ex[8 << 20];
__host__ __device__ __forceinline__ uint8_t* ex_window(uint8_t* p) { return reinterpret_cast<uint8_t*>((reinterpret_cast<uint64_t>(p) + (4 << 20) - 1) & ~(uint64_t)((4 << 20) - 1)); }
enum { CN_P = 0, CN_L = 128, CN_A = 256, CN_W = 384, CN_X = 512, CN_F = 640, CN_G = 768, CN_O = 896, CN_NUM = CN_O + 5 * NSTEP };
__device__ __align__(128) uint32_t g_cnt[CN_NUM][32];
__device__ __align__(128) uint32_t g_ticket[2][32];
__device__ int g_err;
#define TS(jj, i)
#define TS1(jj, i)
#define PTS(i)
#define TSB(jj, i)
#define TSV(jj, i, v)
#define TS_FLUSH(jj)
#define WTS(b, k)
#define WTS1(b, k)
#define WW -1

__device__ __forceinline__ uint32_t smem_u32(const void* p) { return (uint32_t)__cvta_generic_to_shared(p); }
__device__ __forceinline__ uint32_t clk32() { uint32_t t; asm volatile("mov.u32 %0, %%clock;" : "=r"(t)::"memory"); return t; }
__device__ __forceinline__ uint32_t mapa(uint32_t a, uint32_t r) { uint32_t o; asm("mapa.shared::cluster.u32 %0,%1,%2;" : "=r"(o) : "r"(a), "r"(r)); return o; }
__device__ __forceinline__ void mbar_init(uint32_t bar, uint32_t cnt) { asm volatile("mbarrier.init.shared::cta.b64 [%0],%1;" ::"r"(bar), "r"(cnt) : "memory"); }
__device__ __forceinline__ void mbar_expect_tx(uint32_t bar, uint32_t bytes) { asm volatile("mbarrier.arrive.expect_tx.shared::cta.b64 _,[%0],%1;" ::"r"(bar), "r"(bytes) : "memory"); }
__device__ __forceinline__ void mbar_arrive(uint32_t bar) { asm volatile("mbarrier.arrive.shared::cta.b64 _,[%0];" ::"r"(bar) : "memory"); }
__device__ __forceinline__ void mbar_arrive_cluster(uint32_t bar) { asm volatile("mbarrier.arrive.shared::cluster.b64 _,[%0];" ::"r"(bar) : "memory"); }
__device__ __forceinline__ bool mbar_try(uint32_t bar, uint32_t ph) {
  uint32_t ok;
  asm volatile("{.reg .pred p; mbarrier.try_wait.parity.shared::cta.b64 p,[%1],%2; selp.u32 %0,1,0,p;}" : "=r"(ok) : "r"(bar), "r"(ph) : "memory");
  return ok;
}
__device__ __forceinline__ bool mbar_test(uint32_t bar, uint32_t ph) {
  uint32_t ok;
  asm volatile("{.reg .pred p; mbarrier.test_wait.parity.shared::cta.b64 p,[%1],%2; selp.u32 %0,1,0,p;}" : "=r"(ok) : "r"(bar), "r"(ph) : "memory");
  return ok;
}
__device__ __forceinline__ int fresh(int x) { asm volatile("" : "+r"(x)); return x; }
#define PHASE_IDS const int tid = fresh(tid0), lane = tid & 31, w = tid >> 5, g = lane >> 2, t = lane & 3; (void)w; (void)g; (void)t
__device__ __forceinline__ void bar_sync(int id, int n) { asm volatile("bar.sync %0,%1;" ::"r"(id), "r"(n) : "memory"); }
__device__ __forceinline__ void bar_arrive(int id, int n) { asm volatile("bar.arrive %0,%1;" ::"r"(id), "r"(n) : "memory"); }
__device__ __forceinline__ bool bar_red_or(int id, int n, bool v) {
  uint32_t r;
  asm volatile("{\n .reg .pred p, q;\n setp.ne.u32 q, %3, 0;\n barrier.cta.red.or.pred p, %1, %2, q;\n selp.u32 %0, 1, 0, p;\n}" : "=r"(r) : "r"(id), "r"(n), "r"((uint32_t)v) : "memory");
  return r != 0;
}
__device__ __forceinline__ void fence_async() { asm volatile("fence.proxy.async.shared::cta;" ::: "memory"); }
__device__ __forceinline__ void bulk_g2s(uint32_t dst, const void* src, uint32_t bytes, uint32_t bar) {
  asm volatile("cp.async.bulk.shared::cluster.global.mbarrier::complete_tx::bytes [%0],[%1],%2,[%3];" ::"r"(dst), "l"(src), "r"(bytes), "r"(bar) : "memory");
}
__device__ __forceinline__ void bulk_g2s_mc(uint32_t dst, const void* src, uint32_t bytes, uint32_t bar) {
  asm volatile("cp.async.bulk.shared::cluster.global.mbarrier::complete_tx::bytes.multicast::cluster [%0],[%1],%2,[%3],%4;"
               ::"r"(dst), "l"(src), "r"(bytes), "r"(bar), "h"((uint16_t)7) : "memory");
}
__device__ __forceinline__ void bulk_s2g(void* dst, uint32_t src, uint32_t bytes) {
  asm volatile("cp.async.bulk.global.shared::cta.bulk_group [%0],[%1],%2;" ::"l"(dst), "r"(src), "r"(bytes) : "memory");
}
__device__ __forceinline__ void bulk_s2c(uint32_t dst, uint32_t src, uint32_t bytes, uint32_t bar) {
  asm volatile("cp.async.bulk.shared::cluster.shared::cta.mbarrier::complete_tx::bytes [%0],[%1],%2,[%3];" ::"r"(dst), "r"(src), "r"(bytes), "r"(bar) : "memory");
}
__device__ __forceinline__ void tma2d(uint32_t dst, const CUtensorMap* tm, int c0, int c1, uint32_t bar) {
  asm volatile("cp.async.bulk.tensor.2d.shared::cluster.global.mbarrier::complete_tx::bytes [%0],[%1,{%3,%4}],[%2];"
               ::"r"(dst), "l"(tm), "r"(bar), "r"(c0), "r"(c1) : "memory");
}
__device__ __forceinline__ void tma2d_prefetch(const CUtensorMap* tm, int c0, int c1) {
  asm volatile("cp.async.bulk.prefetch.tensor.2d.L2.global.tile [%0,{%1,%2}];" ::"l"(tm), "r"(c0), "r"(c1) : "memory");
}
__device__ __forceinline__ uint32_t pack_bf16(float lo, float hi) {
  uint32_t r; asm("cvt.rn.bf16x2.f32 %0,%1,%2;" : "=r"(r) : "f"(hi), "f"(lo)); return r;
}
__device__ __forceinline__ float bf_lo(uint32_t x) { return __uint_as_float(x << 16); }
__device__ __forceinline__ float bf_hi(uint32_t x) { return __uint_as_float(x & 0xFFFF0000u); }
__device__ __forceinline__ float ex2(float x) { float y; asm("ex2.approx.ftz.f32 %0,%1;" : "=f"(y) : "f"(x)); return y; }
__device__ __forceinline__ void ldsm4(uint32_t (&r)[4], uint32_t a) {
  asm volatile("ldmatrix.sync.aligned.m8n8.x4.shared.b16 {%0,%1,%2,%3},[%4];" : "=r"(r[0]), "=r"(r[1]), "=r"(r[2]), "=r"(r[3]) : "r"(a) : "memory");
}
__device__ __forceinline__ void ldsm4t(uint32_t (&r)[4], uint32_t a) {
  asm volatile("ldmatrix.sync.aligned.m8n8.x4.trans.shared.b16 {%0,%1,%2,%3},[%4];" : "=r"(r[0]), "=r"(r[1]), "=r"(r[2]), "=r"(r[3]) : "r"(a) : "memory");
}
__device__ __forceinline__ void ldsm2(uint32_t& r0, uint32_t& r1, uint32_t a) {
  asm volatile("ldmatrix.sync.aligned.m8n8.x2.shared.b16 {%0,%1},[%2];" : "=r"(r0), "=r"(r1) : "r"(a) : "memory");
}
__device__ __forceinline__ void ldsm2t(uint32_t& r0, uint32_t& r1, uint32_t a) {
  asm volatile("ldmatrix.sync.aligned.m8n8.x2.trans.shared.b16 {%0,%1},[%2];" : "=r"(r0), "=r"(r1) : "r"(a) : "memory");
}
__device__ __forceinline__ void ldsm1(uint32_t& r0, uint32_t a) {
  asm volatile("ldmatrix.sync.aligned.m8n8.x1.shared.b16 {%0},[%1];" : "=r"(r0) : "r"(a) : "memory");
}
__device__ __forceinline__ void mma16816(float (&d)[4], uint32_t a0, uint32_t a1, uint32_t a2, uint32_t a3, uint32_t b0, uint32_t b1) {
  asm volatile("mma.sync.aligned.m16n8k16.row.col.f32.bf16.bf16.f32 {%0,%1,%2,%3},{%4,%5,%6,%7},{%8,%9},{%0,%1,%2,%3};"
               : "+f"(d[0]), "+f"(d[1]), "+f"(d[2]), "+f"(d[3]) : "r"(a0), "r"(a1), "r"(a2), "r"(a3), "r"(b0), "r"(b1));
}
__device__ __forceinline__ void mma1688(float (&d)[4], uint32_t a0, uint32_t a1, uint32_t b0) {
  asm volatile("mma.sync.aligned.m16n8k8.row.col.f32.bf16.bf16.f32 {%0,%1,%2,%3},{%4,%5},{%6},{%0,%1,%2,%3};"
               : "+f"(d[0]), "+f"(d[1]), "+f"(d[2]), "+f"(d[3]) : "r"(a0), "r"(a1), "r"(b0));
}
__device__ __forceinline__ void sts32(uint32_t a, uint32_t v) { asm volatile("st.shared.b32 [%0],%1;" ::"r"(a), "r"(v) : "memory"); }
__device__ __forceinline__ void sts64f(uint32_t a, float x, float y) { asm volatile("st.shared.v2.f32 [%0],{%1,%2};" ::"r"(a), "f"(x), "f"(y) : "memory"); }
__device__ __forceinline__ void sts128(uint32_t a, uint4 v) { asm volatile("st.shared.v4.b32 [%0],{%1,%2,%3,%4};" ::"r"(a), "r"(v.x), "r"(v.y), "r"(v.z), "r"(v.w) : "memory"); }
__device__ __forceinline__ float lds32f(uint32_t a) { float v; asm volatile("ld.shared.f32 %0,[%1];" : "=f"(v) : "r"(a) : "memory"); return v; }
__device__ __forceinline__ float2 lds64f(uint32_t a) { float2 v; asm volatile("ld.shared.v2.f32 {%0,%1},[%2];" : "=f"(v.x), "=f"(v.y) : "r"(a) : "memory"); return v; }
__device__ __forceinline__ uint4 lds128(uint32_t a) { uint4 v; asm volatile("ld.shared.v4.b32 {%0,%1,%2,%3},[%4];" : "=r"(v.x), "=r"(v.y), "=r"(v.z), "=r"(v.w) : "r"(a) : "memory"); return v; }
__device__ __forceinline__ float4 lds128f(uint32_t a) { float4 v; asm volatile("ld.shared.v4.f32 {%0,%1,%2,%3},[%4];" : "=f"(v.x), "=f"(v.y), "=f"(v.z), "=f"(v.w) : "r"(a) : "memory"); return v; }
__device__ __forceinline__ void st_async2(uint32_t a, float x, float y, uint32_t bar) {
  asm volatile("st.async.weak.shared::cluster.mbarrier::complete_tx::bytes.v2.f32 [%0],{%1,%2},[%3];" ::"r"(a), "f"(x), "f"(y), "r"(bar) : "memory");
}
__device__ __forceinline__ void st_async4(uint32_t a, const float (&v)[4], uint32_t bar) {
  asm volatile("st.async.weak.shared::cluster.mbarrier::complete_tx::bytes.v4.f32 [%0],{%1,%2,%3,%4},[%5];" ::"r"(a), "f"(v[0]), "f"(v[1]), "f"(v[2]), "f"(v[3]), "r"(bar) : "memory");
}
__device__ __forceinline__ void st_async4v(uint32_t a, float x, float y, float z, float w, uint32_t bar) {
  asm volatile("st.async.weak.shared::cluster.mbarrier::complete_tx::bytes.v4.f32 [%0],{%1,%2,%3,%4},[%5];" ::"r"(a), "f"(x), "f"(y), "f"(z), "f"(w), "r"(bar) : "memory");
}
__device__ __forceinline__ void st_async4u(uint32_t a, const uint4& v, uint32_t bar) {
  asm volatile("st.async.weak.shared::cluster.mbarrier::complete_tx::bytes.v4.b32 [%0],{%1,%2,%3,%4},[%5];" ::"r"(a), "r"(v.x), "r"(v.y), "r"(v.z), "r"(v.w), "r"(bar) : "memory");
}
__device__ __forceinline__ uint4 ld_relaxed4(const void* p) {
  uint4 v; asm volatile("ld.relaxed.gpu.global.v4.u32 {%0,%1,%2,%3},[%4];" : "=r"(v.x), "=r"(v.y), "=r"(v.z), "=r"(v.w) : "l"(p) : "memory"); return v;
}
__device__ __forceinline__ uint32_t ld_relaxed(const void* p) {
  uint32_t v; asm volatile("ld.relaxed.gpu.global.u32 %0,[%1];" : "=r"(v) : "l"(p) : "memory"); return v;
}
__device__ __forceinline__ void st_relaxed(void* p, uint32_t v) { asm volatile("st.relaxed.gpu.global.b32 [%0],%1;" ::"l"(p), "r"(v) : "memory"); }
__device__ __forceinline__ void st_relaxed4(void* p, uint32_t v) { asm volatile("st.relaxed.gpu.global.v4.b32 [%0],{%1,%1,%1,%1};" ::"l"(p), "r"(v) : "memory"); }

__device__ __forceinline__ uint32_t ld_acquire(const void* p) {
  uint32_t v; asm volatile("ld.acquire.gpu.global.u32 %0,[%1];" : "=r"(v) : "l"(p) : "memory"); return v;
}
__device__ __forceinline__ float4 ld_relaxed4f(const void* p) {
  float4 v; asm volatile("ld.relaxed.gpu.global.v4.f32 {%0,%1,%2,%3},[%4];" : "=f"(v.x), "=f"(v.y), "=f"(v.z), "=f"(v.w) : "l"(p) : "memory"); return v;
}
__device__ __forceinline__ float2 ld_relaxed2f(const void* p) {
  float2 v; asm volatile("ld.relaxed.gpu.global.v2.f32 {%0,%1},[%2];" : "=f"(v.x), "=f"(v.y) : "l"(p) : "memory"); return v;
}
__device__ __forceinline__ void prefetch_l2(const void* p) { asm volatile("prefetch.global.L2 [%0];" ::"l"(p)); }
__device__ __forceinline__ void fence_gpu() { asm volatile("fence.acq_rel.gpu;" ::: "memory"); }
__device__ __forceinline__ void fence_async_all() { asm volatile("fence.proxy.async.global;" ::: "memory"); }
constexpr int SPIN_TOT = 1 << 22;
__device__ __forceinline__ void csignal(int idx) { asm volatile("red.release.gpu.global.add.u32 [%0],1;" ::"l"(&g_cnt[idx][0]) : "memory"); }
__device__ __forceinline__ void csignal_fast(int idx) { asm volatile("red.relaxed.gpu.global.add.u32 [%0],1;" ::"l"(&g_cnt[idx][0]) : "memory"); }
#define RLX 1
#define csignal_t(idx, role) csignal(idx)
__device__ __forceinline__ void cwait(int idx, uint32_t target, int& spin) {
  asm volatile("{.reg .pred p, q; .reg .b32 v;\nCNT_LOOP:\n ld.relaxed.gpu.global.u32 v,[%1];\n add.s32 %0,%0,16;\n setp.lt.s32 q,%0,%3;\n setp.lt.and.u32 p,v,%2,q;\n @p bra.uni CNT_LOOP;\n}"
               : "+&r"(spin) : "l"(&g_cnt[idx][0]), "r"(target), "n"(SPIN_TOT) : "memory");
}

__device__ __forceinline__ uint64_t mkdesc(uint32_t addr, uint32_t lbo, uint32_t sbo) {
  return (uint64_t)((addr & 0x3FFFF) >> 4) | ((uint64_t)(lbo >> 4) << 16) | ((uint64_t)(sbo >> 4) << 32) | ((uint64_t)1 << 62);
}
__device__ __forceinline__ uint64_t mkdesc_ns(uint32_t addr, uint32_t lbo, uint32_t sbo) {
  return (uint64_t)((addr & 0x3FFFF) >> 4) | ((uint64_t)(lbo >> 4) << 16) | ((uint64_t)(sbo >> 4) << 32);
}
__device__ __forceinline__ void wg_fence() { asm volatile("wgmma.fence.sync.aligned;" ::: "memory"); }
__device__ __forceinline__ void wg_commit() { asm volatile("wgmma.commit_group.sync.aligned;" ::: "memory"); }
template <int N> __device__ __forceinline__ void wg_wait() { asm volatile("wgmma.wait_group.sync.aligned %0;" ::"n"(N) : "memory"); }

__device__ __forceinline__ void wgmma_rs16(float (&d)[8], const uint32_t (&a)[4], uint64_t db, int sc) {
  asm volatile("{.reg .pred p; setp.ne.b32 p,%13,0; wgmma.mma_async.sync.aligned.m64n16k16.f32.bf16.bf16 "
               "{%0,%1,%2,%3,%4,%5,%6,%7},{%8,%9,%10,%11},%12,p,1,1,0;}"
               : "+f"(d[0]), "+f"(d[1]), "+f"(d[2]), "+f"(d[3]), "+f"(d[4]), "+f"(d[5]), "+f"(d[6]), "+f"(d[7])
               : "r"(a[0]), "r"(a[1]), "r"(a[2]), "r"(a[3]), "l"(db), "r"(sc));
}
__device__ __forceinline__ void wgmma_rs64(float (&d)[32], const uint32_t (&a)[4], uint64_t db, int sc) {
  asm volatile("{.reg .pred p; setp.ne.b32 p,%37,0; wgmma.mma_async.sync.aligned.m64n64k16.f32.bf16.bf16 "
               "{%0,%1,%2,%3,%4,%5,%6,%7,%8,%9,%10,%11,%12,%13,%14,%15,%16,%17,%18,%19,%20,%21,%22,%23,%24,%25,%26,%27,%28,%29,%30,%31},{%32,%33,%34,%35},%36,p,1,1,0;}"
               : "+f"(d[0]), "+f"(d[1]), "+f"(d[2]), "+f"(d[3]), "+f"(d[4]), "+f"(d[5]), "+f"(d[6]), "+f"(d[7]), "+f"(d[8]), "+f"(d[9]), "+f"(d[10]), "+f"(d[11]), "+f"(d[12]), "+f"(d[13]), "+f"(d[14]), "+f"(d[15]), "+f"(d[16]), "+f"(d[17]), "+f"(d[18]), "+f"(d[19]), "+f"(d[20]), "+f"(d[21]), "+f"(d[22]), "+f"(d[23]), "+f"(d[24]), "+f"(d[25]), "+f"(d[26]), "+f"(d[27]), "+f"(d[28]), "+f"(d[29]), "+f"(d[30]), "+f"(d[31])
               : "r"(a[0]), "r"(a[1]), "r"(a[2]), "r"(a[3]), "l"(db), "r"(sc));
}
__device__ __forceinline__ void wgmma_rt16(float (&d)[8], const uint32_t (&a)[4], uint64_t db, int sc) {
  asm volatile("{.reg .pred p; setp.ne.b32 p,%13,0; wgmma.mma_async.sync.aligned.m64n16k16.f32.bf16.bf16 "
               "{%0,%1,%2,%3,%4,%5,%6,%7},{%8,%9,%10,%11},%12,p,1,1,1;}"
               : "+f"(d[0]), "+f"(d[1]), "+f"(d[2]), "+f"(d[3]), "+f"(d[4]), "+f"(d[5]), "+f"(d[6]), "+f"(d[7])
               : "r"(a[0]), "r"(a[1]), "r"(a[2]), "r"(a[3]), "l"(db), "r"(sc));
}
__device__ __forceinline__ void wgmma_rt80(float (&d)[40], const uint32_t (&a)[4], uint64_t db, int sc) {
  asm volatile("{.reg .pred p; setp.ne.b32 p,%45,0; wgmma.mma_async.sync.aligned.m64n80k16.f32.bf16.bf16 "
               "{%0,%1,%2,%3,%4,%5,%6,%7,%8,%9,%10,%11,%12,%13,%14,%15,%16,%17,%18,%19,%20,%21,%22,%23,%24,%25,%26,%27,%28,%29,%30,%31,%32,%33,%34,%35,%36,%37,%38,%39},{%40,%41,%42,%43},%44,p,1,1,1;}"
               : "+f"(d[0]), "+f"(d[1]), "+f"(d[2]), "+f"(d[3]), "+f"(d[4]), "+f"(d[5]), "+f"(d[6]), "+f"(d[7]), "+f"(d[8]), "+f"(d[9]), "+f"(d[10]), "+f"(d[11]), "+f"(d[12]), "+f"(d[13]), "+f"(d[14]), "+f"(d[15]), "+f"(d[16]), "+f"(d[17]), "+f"(d[18]), "+f"(d[19]), "+f"(d[20]), "+f"(d[21]), "+f"(d[22]), "+f"(d[23]), "+f"(d[24]), "+f"(d[25]), "+f"(d[26]), "+f"(d[27]), "+f"(d[28]), "+f"(d[29]), "+f"(d[30]), "+f"(d[31]), "+f"(d[32]), "+f"(d[33]), "+f"(d[34]), "+f"(d[35]), "+f"(d[36]), "+f"(d[37]), "+f"(d[38]), "+f"(d[39])
               : "r"(a[0]), "r"(a[1]), "r"(a[2]), "r"(a[3]), "l"(db), "r"(sc));
}
__device__ __forceinline__ void wgmma_rs32(float (&d)[16], const uint32_t (&a)[4], uint64_t db, int sc) {
  asm volatile("{.reg .pred p; setp.ne.b32 p,%21,0; wgmma.mma_async.sync.aligned.m64n32k16.f32.bf16.bf16 "
               "{%0,%1,%2,%3,%4,%5,%6,%7,%8,%9,%10,%11,%12,%13,%14,%15},{%16,%17,%18,%19},%20,p,1,1,0;}"
               : "+f"(d[0]), "+f"(d[1]), "+f"(d[2]), "+f"(d[3]), "+f"(d[4]), "+f"(d[5]), "+f"(d[6]), "+f"(d[7]), "+f"(d[8]), "+f"(d[9]), "+f"(d[10]), "+f"(d[11]), "+f"(d[12]), "+f"(d[13]), "+f"(d[14]), "+f"(d[15])
               : "r"(a[0]), "r"(a[1]), "r"(a[2]), "r"(a[3]), "l"(db), "r"(sc));
}
__device__ __forceinline__ void wgmma_ts32(float (&d)[16], uint64_t da, uint64_t db, int sc) {
  asm volatile("{.reg .pred p; setp.ne.b32 p,%18,0; wgmma.mma_async.sync.aligned.m64n32k16.f32.bf16.bf16 "
               "{%0,%1,%2,%3,%4,%5,%6,%7,%8,%9,%10,%11,%12,%13,%14,%15},%16,%17,p,1,1,1,0;}"
               : "+f"(d[0]), "+f"(d[1]), "+f"(d[2]), "+f"(d[3]), "+f"(d[4]), "+f"(d[5]), "+f"(d[6]), "+f"(d[7]), "+f"(d[8]), "+f"(d[9]), "+f"(d[10]), "+f"(d[11]), "+f"(d[12]), "+f"(d[13]), "+f"(d[14]), "+f"(d[15])
               : "l"(da), "l"(db), "r"(sc));
}
__device__ __forceinline__ void wgmma_rs8(float (&d)[4], const uint32_t (&a)[4], uint64_t db, int sc) {
  asm volatile("{.reg .pred p; setp.ne.b32 p,%9,0; wgmma.mma_async.sync.aligned.m64n8k16.f32.bf16.bf16 "
               "{%0,%1,%2,%3},{%4,%5,%6,%7},%8,p,1,1,0;}"
               : "+f"(d[0]), "+f"(d[1]), "+f"(d[2]), "+f"(d[3])
               : "r"(a[0]), "r"(a[1]), "r"(a[2]), "r"(a[3]), "l"(db), "r"(sc));
}
__device__ __forceinline__ void wgmma_tt32(float (&d)[16], uint64_t da, uint64_t db, int sc) {
  asm volatile("{.reg .pred p; setp.ne.b32 p,%18,0; wgmma.mma_async.sync.aligned.m64n32k16.f32.bf16.bf16 "
               "{%0,%1,%2,%3,%4,%5,%6,%7,%8,%9,%10,%11,%12,%13,%14,%15},%16,%17,p,1,1,1,1;}"
               : "+f"(d[0]), "+f"(d[1]), "+f"(d[2]), "+f"(d[3]), "+f"(d[4]), "+f"(d[5]), "+f"(d[6]), "+f"(d[7]), "+f"(d[8]), "+f"(d[9]), "+f"(d[10]), "+f"(d[11]), "+f"(d[12]), "+f"(d[13]), "+f"(d[14]), "+f"(d[15])
               : "l"(da), "l"(db), "r"(sc));
}
__device__ __forceinline__ void wgmma_ts16(float (&d)[8], uint64_t da, uint64_t db, int sc) {
  asm volatile("{.reg .pred p; setp.ne.b32 p,%10,0; wgmma.mma_async.sync.aligned.m64n16k16.f32.bf16.bf16 "
               "{%0,%1,%2,%3,%4,%5,%6,%7},%8,%9,p,1,1,1,0;}"
               : "+f"(d[0]), "+f"(d[1]), "+f"(d[2]), "+f"(d[3]), "+f"(d[4]), "+f"(d[5]), "+f"(d[6]), "+f"(d[7])
               : "l"(da), "l"(db), "r"(sc));
}
__device__ __forceinline__ void wgmma_ts64(float (&d)[32], uint64_t da, uint64_t db, int sc) {
  asm volatile("{.reg .pred p; setp.ne.b32 p,%34,0; wgmma.mma_async.sync.aligned.m64n64k16.f32.bf16.bf16 "
               "{%0,%1,%2,%3,%4,%5,%6,%7,%8,%9,%10,%11,%12,%13,%14,%15,%16,%17,%18,%19,%20,%21,%22,%23,%24,%25,%26,%27,%28,%29,%30,%31},%32,%33,p,1,1,1,0;}"
               : "+f"(d[0]), "+f"(d[1]), "+f"(d[2]), "+f"(d[3]), "+f"(d[4]), "+f"(d[5]), "+f"(d[6]), "+f"(d[7]), "+f"(d[8]), "+f"(d[9]), "+f"(d[10]), "+f"(d[11]), "+f"(d[12]), "+f"(d[13]), "+f"(d[14]), "+f"(d[15]), "+f"(d[16]), "+f"(d[17]), "+f"(d[18]), "+f"(d[19]), "+f"(d[20]), "+f"(d[21]), "+f"(d[22]), "+f"(d[23]), "+f"(d[24]), "+f"(d[25]), "+f"(d[26]), "+f"(d[27]), "+f"(d[28]), "+f"(d[29]), "+f"(d[30]), "+f"(d[31])
               : "l"(da), "l"(db), "r"(sc));
}
__device__ __forceinline__ void wgmma_tt16(float (&d)[8], uint64_t da, uint64_t db, int sc) {
  asm volatile("{.reg .pred p; setp.ne.b32 p,%10,0; wgmma.mma_async.sync.aligned.m64n16k16.f32.bf16.bf16 "
               "{%0,%1,%2,%3,%4,%5,%6,%7},%8,%9,p,1,1,1,1;}"
               : "+f"(d[0]), "+f"(d[1]), "+f"(d[2]), "+f"(d[3]), "+f"(d[4]), "+f"(d[5]), "+f"(d[6]), "+f"(d[7])
               : "l"(da), "l"(db), "r"(sc));
}
__device__ __forceinline__ void wgmma_tt40(float (&d)[20], uint64_t da, uint64_t db, int sc) {
  asm volatile("{.reg .pred p; setp.ne.b32 p,%22,0; wgmma.mma_async.sync.aligned.m64n40k16.f32.bf16.bf16 "
               "{%0,%1,%2,%3,%4,%5,%6,%7,%8,%9,%10,%11,%12,%13,%14,%15,%16,%17,%18,%19},%20,%21,p,1,1,1,1;}"
               : "+f"(d[0]), "+f"(d[1]), "+f"(d[2]), "+f"(d[3]), "+f"(d[4]), "+f"(d[5]), "+f"(d[6]), "+f"(d[7]), "+f"(d[8]), "+f"(d[9]), "+f"(d[10]), "+f"(d[11]), "+f"(d[12]), "+f"(d[13]), "+f"(d[14]), "+f"(d[15]), "+f"(d[16]), "+f"(d[17]), "+f"(d[18]), "+f"(d[19])
               : "l"(da), "l"(db), "r"(sc));
}
__device__ __forceinline__ void wgmma_ss8(float (&d)[4], uint64_t da, uint64_t db, int sc) {
  asm volatile("{.reg .pred p; setp.ne.b32 p,%6,0; wgmma.mma_async.sync.aligned.m64n8k16.f32.bf16.bf16 "
               "{%0,%1,%2,%3},%4,%5,p,1,1,0,0;}"
               : "+f"(d[0]), "+f"(d[1]), "+f"(d[2]), "+f"(d[3])
               : "l"(da), "l"(db), "r"(sc));
}
__device__ __forceinline__ void wgmma_ss32(float (&d)[16], uint64_t da, uint64_t db, int sc) {
  asm volatile("{.reg .pred p; setp.ne.b32 p,%18,0; wgmma.mma_async.sync.aligned.m64n32k16.f32.bf16.bf16 "
               "{%0,%1,%2,%3,%4,%5,%6,%7,%8,%9,%10,%11,%12,%13,%14,%15},%16,%17,p,1,1,0,0;}"
               : "+f"(d[0]), "+f"(d[1]), "+f"(d[2]), "+f"(d[3]), "+f"(d[4]), "+f"(d[5]), "+f"(d[6]), "+f"(d[7]), "+f"(d[8]), "+f"(d[9]), "+f"(d[10]), "+f"(d[11]), "+f"(d[12]), "+f"(d[13]), "+f"(d[14]), "+f"(d[15])
               : "l"(da), "l"(db), "r"(sc));
}
__device__ __forceinline__ void wgmma_st64(float (&d)[32], uint64_t da, uint64_t db, int sc) {
  asm volatile("{.reg .pred p; setp.ne.b32 p,%34,0; wgmma.mma_async.sync.aligned.m64n64k16.f32.bf16.bf16 "
               "{%0,%1,%2,%3,%4,%5,%6,%7,%8,%9,%10,%11,%12,%13,%14,%15,%16,%17,%18,%19,%20,%21,%22,%23,%24,%25,%26,%27,%28,%29,%30,%31},%32,%33,p,1,1,0,1;}"
               : "+f"(d[0]), "+f"(d[1]), "+f"(d[2]), "+f"(d[3]), "+f"(d[4]), "+f"(d[5]), "+f"(d[6]), "+f"(d[7]), "+f"(d[8]), "+f"(d[9]), "+f"(d[10]), "+f"(d[11]), "+f"(d[12]), "+f"(d[13]), "+f"(d[14]), "+f"(d[15]), "+f"(d[16]), "+f"(d[17]), "+f"(d[18]), "+f"(d[19]), "+f"(d[20]), "+f"(d[21]), "+f"(d[22]), "+f"(d[23]), "+f"(d[24]), "+f"(d[25]), "+f"(d[26]), "+f"(d[27]), "+f"(d[28]), "+f"(d[29]), "+f"(d[30]), "+f"(d[31])
               : "l"(da), "l"(db), "r"(sc));
}
__device__ __forceinline__ void wgmma_st128(float (&d)[64], uint64_t da, uint64_t db, int sc) {
  asm volatile("{.reg .pred p; setp.ne.b32 p,%66,0; wgmma.mma_async.sync.aligned.m64n128k16.f32.bf16.bf16 "
               "{%0,%1,%2,%3,%4,%5,%6,%7,%8,%9,%10,%11,%12,%13,%14,%15,%16,%17,%18,%19,%20,%21,%22,%23,%24,%25,%26,%27,%28,%29,%30,%31,%32,%33,%34,%35,%36,%37,%38,%39,%40,%41,%42,%43,%44,%45,%46,%47,%48,%49,%50,%51,%52,%53,%54,%55,%56,%57,%58,%59,%60,%61,%62,%63},%64,%65,p,1,1,0,1;}"
               : "+f"(d[0]), "+f"(d[1]), "+f"(d[2]), "+f"(d[3]), "+f"(d[4]), "+f"(d[5]), "+f"(d[6]), "+f"(d[7]), "+f"(d[8]), "+f"(d[9]), "+f"(d[10]), "+f"(d[11]), "+f"(d[12]), "+f"(d[13]), "+f"(d[14]), "+f"(d[15]), "+f"(d[16]), "+f"(d[17]), "+f"(d[18]), "+f"(d[19]), "+f"(d[20]), "+f"(d[21]), "+f"(d[22]), "+f"(d[23]), "+f"(d[24]), "+f"(d[25]), "+f"(d[26]), "+f"(d[27]), "+f"(d[28]), "+f"(d[29]), "+f"(d[30]), "+f"(d[31]), "+f"(d[32]), "+f"(d[33]), "+f"(d[34]), "+f"(d[35]), "+f"(d[36]), "+f"(d[37]), "+f"(d[38]), "+f"(d[39]), "+f"(d[40]), "+f"(d[41]), "+f"(d[42]), "+f"(d[43]), "+f"(d[44]), "+f"(d[45]), "+f"(d[46]), "+f"(d[47]), "+f"(d[48]), "+f"(d[49]), "+f"(d[50]), "+f"(d[51]), "+f"(d[52]), "+f"(d[53]), "+f"(d[54]), "+f"(d[55]), "+f"(d[56]), "+f"(d[57]), "+f"(d[58]), "+f"(d[59]), "+f"(d[60]), "+f"(d[61]), "+f"(d[62]), "+f"(d[63])
               : "l"(da), "l"(db), "r"(sc));
}

__device__ __forceinline__ void stsm4(uint32_t a, uint32_t r0, uint32_t r1, uint32_t r2, uint32_t r3) {
  asm volatile("stmatrix.sync.aligned.m8n8.x4.shared.b16 [%0],{%1,%2,%3,%4};" ::"r"(a), "r"(r0), "r"(r1), "r"(r2), "r"(r3) : "memory");
}
__device__ __forceinline__ void stsm4t(uint32_t a, uint32_t r0, uint32_t r1, uint32_t r2, uint32_t r3) {
  asm volatile("stmatrix.sync.aligned.m8n8.x4.trans.shared.b16 [%0],{%1,%2,%3,%4};" ::"r"(a), "r"(r0), "r"(r1), "r"(r2), "r"(r3) : "memory");
}
__device__ __forceinline__ void stsm2t(uint32_t a, uint32_t r0, uint32_t r1) {
  asm volatile("stmatrix.sync.aligned.m8n8.x2.trans.shared.b16 [%0],{%1,%2};" ::"r"(a), "r"(r0), "r"(r1) : "memory");
}
__device__ __forceinline__ void sts64(uint32_t a, uint32_t x, uint32_t y) { asm volatile("st.shared.v2.b32 [%0],{%1,%2};" ::"r"(a), "r"(x), "r"(y) : "memory"); }
__device__ __forceinline__ void st_async2u(uint32_t a, uint32_t x, uint32_t y, uint32_t bar) {
  asm volatile("st.async.weak.shared::cluster.mbarrier::complete_tx::bytes.v2.b32 [%0],{%1,%2},[%3];" ::"r"(a), "r"(x), "r"(y), "r"(bar) : "memory");
}
__device__ __forceinline__ void st_relaxed128(void* p, uint32_t x, uint32_t y, uint32_t z, uint32_t w) {
  asm volatile("{.reg .b128 v; mov.b128 v,{%1,%2,%3,%4}; st.relaxed.gpu.global.b128 [%0],v;}" ::"l"(p), "r"(x), "r"(y), "r"(z), "r"(w) : "memory");
}
__device__ __forceinline__ void st_relaxed16(void* p, uint32_t x) { asm volatile("st.relaxed.gpu.global.b16 [%0],%1;" ::"l"(p), "h"((uint16_t)x) : "memory"); }
__device__ __forceinline__ void st_relaxed64(void* p, uint32_t x, uint32_t y) {
  asm volatile("{.reg .b64 v; mov.b64 v,{%1,%2}; st.relaxed.gpu.global.b64 [%0],v;}" ::"l"(p), "r"(x), "r"(y) : "memory");
}
__device__ __forceinline__ uint4 ld_relaxed128(const void* p) {
  uint4 v;
  asm volatile("{.reg .b128 v; .reg .b64 lo, hi; ld.relaxed.gpu.global.b128 v,[%4]; mov.b128 {lo,hi},v; mov.b64 {%0,%1},lo; mov.b64 {%2,%3},hi;}" : "=r"(v.x), "=r"(v.y), "=r"(v.z), "=r"(v.w) : "l"(p) : "memory");
  return v;
}

__device__ __forceinline__ uint32_t pack_h2(float lo, float hi) {
  uint32_t r; asm("cvt.rn.satfinite.f16x2.f32 %0,%1,%2;" : "=r"(r) : "f"(hi), "f"(lo)); return r;
}
__device__ __forceinline__ void add_h2(float& lo, float& hi, uint32_t u, uint32_t v) {
  float a, b;
  asm("{.reg .b16 l, h; .reg .b32 s; add.rn.f16x2 s,%2,%3; mov.b32 {l,h},s; cvt.f32.f16 %0,l; cvt.f32.f16 %1,h;}" : "=f"(a), "=f"(b) : "r"(u), "r"(v));
  lo += a; hi += b;
}
__device__ __forceinline__ void mwait(uint32_t bar, uint32_t ph, int& spin) {
  asm volatile("{.reg .pred p, q;\nWAIT_LOOP:\n add.s32 %0,%0,1;\n setp.lt.s32 q,%0,%3;\n mbarrier.try_wait.parity.shared::cta.b64 p,[%1],%2;\n not.pred p,p;\n and.pred q,q,p;\n @q bra.uni WAIT_LOOP;\n}"
               : "+&r"(spin) : "r"(bar), "r"(ph), "n"(SPIN_TOT) : "memory");
}
__device__ __forceinline__ int keep(int x) { return __shfl_sync(0xffffffffu, x, threadIdx.x & 31); }
__device__ __forceinline__ uint32_t pin(uint32_t x) { asm volatile("" : "+r"(x)); return x; }
template <typename T> __device__ __forceinline__ T* pinp(T* x) { asm volatile("" : "+l"(x)); return x; }
__device__ __forceinline__ void st_async1u(uint32_t a, uint32_t x, uint32_t bar) {
  asm volatile("st.async.weak.shared::cluster.mbarrier::complete_tx::bytes.b32 [%0],%1,[%2];" ::"r"(a), "r"(x), "r"(bar) : "memory");
}
__device__ __forceinline__ uint32_t lds32(uint32_t a) { uint32_t v; asm volatile("ld.shared.b32 %0,[%1];" : "=r"(v) : "r"(a) : "memory"); return v; }
__device__ __forceinline__ uint2 lds64(uint32_t a) { uint2 v; asm volatile("ld.shared.v2.b32 {%0,%1},[%2];" : "=r"(v.x), "=r"(v.y) : "r"(a) : "memory"); return v; }

__device__ __forceinline__ void permute_cols(uint32_t tile, int tid, int n) {
#pragma unroll 2
  for (int it = tid; it < n; it += 128) {
    const int row = it >> 2, q = it & 3;
    const uint32_t a0 = tile + row * 128 + (((2 * q) ^ (row & 7)) << 4), a1 = tile + row * 128 + (((2 * q + 1) ^ (row & 7)) << 4);
    const uint4 u = lds128(a0), v = lds128(a1);
    sts128(a0, make_uint4(__byte_perm(u.x, u.y, 0x5410), __byte_perm(u.z, u.w, 0x5410), __byte_perm(v.x, v.y, 0x5410), __byte_perm(v.z, v.w, 0x5410)));
    sts128(a1, make_uint4(__byte_perm(u.x, u.y, 0x7632), __byte_perm(u.z, u.w, 0x7632), __byte_perm(v.x, v.y, 0x7632), __byte_perm(v.z, v.w, 0x7632)));
  }
}

__device__ __forceinline__ uint8_t* mkptr(uint32_t lo, uint32_t hi) { uint8_t* p; asm("mov.b64 %0,{%1,%2};" : "=l"(p) : "r"(lo), "r"(hi)); return p; }
__device__ __forceinline__ int uni(int x) { return __shfl_sync(0xffffffffu, x, 0); }

__device__ __forceinline__ bool elect_one() {
  uint32_t p; asm volatile("{.reg .pred q; elect.sync _|q, 0xffffffff; selp.u32 %0,1,0,q;}" : "=r"(p)); return p;
}
__device__ __forceinline__ uint64_t desc_at(uint64_t d, uint32_t off) {
  uint64_t r; asm("mov.b64 %0,{%1,%2};" : "=l"(r) : "r"((uint32_t)d + (off >> 4)), "r"((uint32_t)(d >> 32))); return r;
}
__device__ __forceinline__ uint32_t scale_bf16x2(uint32_t x, uint32_t s) { uint32_t r; asm("mul.rn.bf16x2 %0,%1,%2;" : "=r"(r) : "r"(x), "r"(s)); return r; }

__device__ __forceinline__ void stg128(void* p, const uint4& v) { asm volatile("st.global.v4.b32 [%0],{%1,%2,%3,%4};" ::"l"(p), "r"(v.x), "r"(v.y), "r"(v.z), "r"(v.w) : "memory"); }

__device__ __forceinline__ void elect_g2s_mc(uint32_t dst, const void* src, uint32_t bytes, uint32_t bar) {
  asm volatile("{.reg .pred p; elect.sync _|p, 0xffffffff;\n"
               " @p cp.async.bulk.shared::cluster.global.mbarrier::complete_tx::bytes.multicast::cluster [%0],[%1],%2,[%3],%4;}"
               ::"r"(dst), "l"(src), "r"(bytes), "r"(bar), "h"((uint16_t)7) : "memory");
}
__device__ __forceinline__ void elect_s2c2(uint32_t dst0, uint32_t bar0, uint32_t dst1, uint32_t bar1, uint32_t src, uint32_t bytes) {
  asm volatile("{.reg .pred p; elect.sync _|p, 0xffffffff;\n"
               " @p cp.async.bulk.shared::cluster.shared::cta.mbarrier::complete_tx::bytes [%0],[%4],%5,[%1];\n"
               " @p cp.async.bulk.shared::cluster.shared::cta.mbarrier::complete_tx::bytes [%2],[%4],%5,[%3];}"
               ::"r"(dst0), "r"(bar0), "r"(dst1), "r"(bar1), "r"(src), "r"(bytes) : "memory");
}
__device__ __forceinline__ void fill_stage(uint32_t dst, const void* src, uint32_t bytes, uint32_t bar) {
  asm volatile("{.reg .pred p; elect.sync _|p, 0xffffffff;\n"
               " @p cp.async.bulk.shared::cluster.global.mbarrier::complete_tx::bytes [%0],[%1],%2,[%3];\n"
               " @p mbarrier.arrive.expect_tx.shared::cta.b64 _,[%3],%2;}" ::"r"(dst), "l"(src), "r"(bytes), "r"(bar) : "memory");
}
__device__ __forceinline__ void fill_stage2(uint32_t dst, const void* src0, const void* src1, uint32_t bar) {
  asm volatile("{.reg .pred p; elect.sync _|p, 0xffffffff;\n"
               " @p cp.async.bulk.shared::cluster.global.mbarrier::complete_tx::bytes [%0],[%1],4096,[%3];\n"
               " @p cp.async.bulk.shared::cluster.global.mbarrier::complete_tx::bytes [%0+4096],[%2],4096,[%3];\n"
               " @p mbarrier.arrive.expect_tx.shared::cta.b64 _,[%3],8192;}" ::"r"(dst), "l"(src0), "l"(src1), "r"(bar) : "memory");
}

__device__ __forceinline__ float quad_sum(float x) {
  const float a = __shfl_xor_sync(0xffffffffu, x, 1), b = __shfl_xor_sync(0xffffffffu, x, 2), c = __shfl_xor_sync(0xffffffffu, x, 3);
  return (x + a) + (b + c);
}
__device__ __forceinline__ float warp_sum(float x) {
  const uint32_t m = __reduce_max_sync(0xffffffffu, __float_as_uint(x) & 0x7FFFFFFFu), e = max(m >> 23, 25u);
  const int s = __reduce_add_sync(0xffffffffu, __float2int_rn(x * __uint_as_float((278 - e) << 23)));
  return fmaf(__uint_as_float(m), 0.f, (float)s * __uint_as_float((e - 24) << 23));
}
__device__ __forceinline__ void ln_row(float4 (&v)[5]) {
  float t0 = 0.f, t1 = 0.f;
#pragma unroll
  for (int m = 0; m < 5; m++) { t0 += v[m].x + v[m].y; t1 += v[m].z + v[m].w; }
  const float mean = warp_sum(t0 + t1) * (1.f / DM);
  float q0 = 0.f, q1 = 0.f, q2 = 0.f, q3 = 0.f;
#pragma unroll
  for (int m = 0; m < 5; m++) {
    v[m].x -= mean; v[m].y -= mean; v[m].z -= mean; v[m].w -= mean;
    q0 = fmaf(v[m].x, v[m].x, q0); q1 = fmaf(v[m].y, v[m].y, q1); q2 = fmaf(v[m].z, v[m].z, q2); q3 = fmaf(v[m].w, v[m].w, q3);
  }
  const float rs = rsqrtf(warp_sum((q0 + q1) + (q2 + q3)) * (1.f / DM) + 1e-5f);
#pragma unroll
  for (int m = 0; m < 5; m++) { v[m].x *= rs; v[m].y *= rs; v[m].z *= rs; v[m].w *= rs; }
}
__device__ __forceinline__ void ln0_load(const bf16* __restrict__ x, uint2 (&u)[5], int row, int lane) {
#pragma unroll
  for (int m = 0; m < 5; m++) u[m] = *reinterpret_cast<const uint2*>(x + (size_t)row * DM + m * 128 + lane * 4);
}
__device__ __forceinline__ void ln0_copy(const uint2 (&u)[5], int row, int lane) {
#pragma unroll
  for (int m = 0; m < 5; m++) stg128(g_x + (size_t)row * DM + m * 128 + lane * 4, make_uint4(u[m].x << 16, u[m].x & 0xFFFF0000u, u[m].y << 16, u[m].y & 0xFFFF0000u));
}
__device__ __forceinline__ void ln0_row(const uint2 (&u)[5], int row, int lane) {
  float4 v[5];
#pragma unroll
  for (int m = 0; m < 5; m++) v[m] = make_float4(bf_lo(u[m].x), bf_hi(u[m].x), bf_lo(u[m].y), bf_hi(u[m].y));
  ln_row(v);
  uint8_t* dst = g_xn[row >> 5] + ((row >> 3) & 3) * 4096 + (lane >> 4) * 1024 + (row & 7) * 128 + ((((lane >> 1) ^ row) & 7) << 4) + (lane & 1) * 8;
#pragma unroll
  for (int m = 0; m < 5; m++) *reinterpret_cast<uint2*>(dst + m * 16384) = make_uint2(pack_bf16(v[m].x, v[m].y), pack_bf16(v[m].z, v[m].w));
}

#define NOWORK 0
__device__ __forceinline__ void prep_row(const uint2 (&u)[5], const bf16* __restrict__ mem0, int k, int r, int lane) {
  const uint4 sent = make_uint4(SENT, SENT, SENT, SENT);
  if (k + 1 < NSTEP) {
    uint8_t* ex = ex_window(g_ex);
#pragma unroll
    for (int h = 0; h < 2; h++) {
      const int p = r * 40 + h * 32 + lane;
      if (h == 0 || lane < 8) {
        uint4 v = sent;
        if (k + 1 == LAG && (p & 8)) v = *reinterpret_cast<const uint4*>(mem0 + (p & 7) * DM + m_tile(p >> 7) * 64 + ((p >> 4) & 7) * 8);
        stg128(ex + EX_M + (k + 1) * 20480 + p * 16, v);
      } else if (lane < 14) stg128(ex + EX_FLAG + (k + 1) * 3072 + (r * 6 + lane - 8) * 16, sent);
    }
  }
  if (k < LAG || k >= NSEG || NOWORK) {
    uint8_t* z = g_xn[k] + (r >> 3) * 4096 + (k < NSEG ? 2048 : 0) + (lane >> 4) * 1024 + (r & 7) * 128 + (lane & 15) * 8;
#pragma unroll
    for (int m = 0; m < 5; m++) *reinterpret_cast<uint2*>(z + m * 16384) = make_uint2(0, 0);
  }
  if (k < NSEG) {
    ln0_copy(u, k * 32 + r, lane);
    ln0_row(u, k * 32 + r, lane);
  }
}
__device__ __forceinline__ void pre_work(const bf16* __restrict__ x, const bf16* __restrict__ mem0, int cta, int tid) {
  constexpr int NT = 96 * 128;
  const int gt = cta * 128 + tid;
  uint8_t* ex = ex_window(g_ex);
#pragma unroll 1
  for (int row = cta + 96 * (tid >> 5); row < (NOWORK == 2 ? NSTEP : NPRE) * 32; row += 384) {
    uint2 u[5];
    ln0_load(x, u, min(row, SEQ - 1), tid & 31);
    prep_row(u, mem0, row >> 5, row & 31, tid & 31);
  }
#pragma unroll 1
  for (int i = gt; i < MAIL_BYTES / 16; i += NT) {
    stg128(ex + EX_MAIL + i * 16, make_uint4(SENT, SENT, SENT, SENT));
    stg128(ex + EX_MAIL + (1 << 20) + i * 16, make_uint4(SENT, SENT, SENT, SENT));
  }
  const int p = NT - 1 - gt;
  if (p < 1280) stg128(ex + EX_M + p * 16, *reinterpret_cast<const uint4*>(mem0 + (p & 7) * DM + m_tile(p >> 7) * 64 + ((p >> 4) & 7) * 8));
  if (p < 192) stg128(ex + EX_FLAG + p * 16, make_uint4(0, 0, 0, 0));
  if (gt < 8 * CN_NUM) stg128(&g_cnt[0][0] + gt * 4, make_uint4(0, 0, 0, 0));
}
__device__ __forceinline__ void pre_wait(int which, uint32_t n, int& spin) {
  uint32_t old;
  asm volatile("atom.acq_rel.gpu.global.add.u32 %0,[%1],1;" : "=r"(old) : "l"(&g_ticket[which][0]) : "memory");
  const uint32_t target = (old / n + 1) * 96;
  while ((int)(ld_acquire(&g_ticket[0][0]) - target) < 0 && spin < SPIN_TOT) spin += 16;
  fence_async_all();
}

namespace C {
constexpr int NKR = 37;
constexpr int OFF_WQ = 0, OFF_WK = 81920;
constexpr int OFF_YO = 163840, OFF_YV = OFF_YO + 6144;
constexpr int OFF_M = 176128;
__host__ __device__ constexpr int og_off(int c) { return c ? OFF_M + 14336 + c * 2048 : 229376; }
constexpr int OFF_KT = 196608;
constexpr int OFF_XT = OFF_KT + 10240;
constexpr int OFF_VT = OFF_XT + 7168;
constexpr int OFF_XM = OFF_VT + 11392;
constexpr int OFF_PT = OFF_XM + 2560;
constexpr int KS = 1280, VS = 1408;
__host__ __device__ constexpr int slot_off(int p) { return p == 2 ? OFF_M : OFF_KT + (p % 3) * 16384; }
constexpr int OFF_ONE = 231424;
constexpr int OFF_BAR = 231552;
constexpr int OFF_SAFE = OFF_BAR + 144;
constexpr int OFF_TS = OFF_BAR + 256;
constexpr int SMEM = 232448;
constexpr uint32_t SB0 = 1024;
constexpr int BAR_F = OFF_BAR, BAR_XM = BAR_F + 40, BAR_XT = BAR_F + 48, BAR_OG = BAR_F + 56, BAR_E = OFF_BAR + 64, BAR_MOK = BAR_E + 40,
              BAR_M = OFF_BAR + 120, BAR_XF = OFF_BAR + 112, BAR_MF = OFF_BAR + 248, BAR_W = OFF_BAR + 208;
constexpr int NB_PRO = 1, NB_RD = 2, NB_MR = 3, NB_QK = 4, NB_SM = 5, NB_VA = 6, NB_VQ = 7, NB_A = 8, NB_Q = 9, NB_C = 10, NB_WQ = 11, NB_SI = 13, NB_WV = 14, NB_V = 15;
#define B1 600
#define AD0 32
#define AD1 128
#define AD2 16
#define AD3 128
#define BMX 1200
#define B2 800
#define FLP 1
#define OSG 2
#define OST 7
#define NBX 1
#define PVB 2
#define QPV 0
#define ONES 0
#define E0L 0
#define E2L 0
#define T2E 1
#define XMB 0
#define B3 0
#define OSV 0
#define XTD 0
#define VSL 2
#define VTI 4
#define T9L 0
#define SIE 2
#define WOE 1
#define OGF 2
#define VSP 8
#define RFK 5
#define PFD 3
#define WOL 0
constexpr uint32_t SCQ = 0x3A003A00;
constexpr float SCE = 0.07216878364870322f * 1.4426950408889634f * 2048;
}

#define CBAR_SYNC(id, n) bar_sync(id, n)
#define CBAR_ARRIVE(id, n) bar_arrive(id, n)

__device__ __forceinline__ uint64_t wdesc(int off) { return mkdesc(C::SB0 + off, 8192, 1024); }
__device__ __forceinline__ uint64_t mdesc(int k) { return mkdesc_ns(C::SB0 + C::OFF_M + k * 512, 256, 128); }
__device__ __forceinline__ uint64_t tdesc(int k) { return mkdesc(C::SB0 + C::slot_off(k >> 3) + ((k >> 2) & 1) * 1024 + (k & 3) * 32, 16, 2048); }

__device__ __forceinline__ int dh_row(int n) { return (n & ~63) + (n & 32) + ((n >> 1) & 3) * 8 + ((n >> 3) & 3) * 2 + (n & 1); }
template <bool IS_O>
__device__ __forceinline__ void stage_box(const CUtensorMap& tm, uint32_t sb, int p, int cta, int rank) {
  using namespace C;
  const uint32_t bar = sb + BAR_W + 8 * p;
  const int head = cta / 3, col = head * DH + rank * 64;
  mbar_expect_tx(bar, 16384);
  if (!IS_O) tma2d(sb + OFF_WK + p * 16384, &tm, col, p * 128, bar);
  else for (int b = 2 * p - 1; b <= 2 * p; b++)
    tma2d(sb + OFF_WQ + (b + 1) * 8192, &tm, b < 0 ? 576 : (3 * rank + b / 3) * 64, b < 0 ? col : head * DH + ((rank + b) % 3) * 64, bar);
}
template <bool IS_O>
__device__ __forceinline__ void load_weights_rs(uint32_t (&wf)[C::NKR][4], const CUtensorMap& tms, const CUtensorMap& tm, int cta, int rank, uint32_t sb, int tid0, int& spin) {
  using namespace C;
  constexpr int STAGE = IS_O ? OFF_WQ : OFF_WK, YOFF = IS_O ? OFF_YO : OFF_YV, NB = IS_O ? NB_C : NB_V;
  const int i = (tid0 >> 3) & 3, n0 = (tid0 & 7) + (i >> 1) * 8;
  const int chunk = 2 * ((tid0 >> 5) & 3) + (i & 1);
  const int r0 = IS_O ? dh_row(n0) : n0, r1 = IS_O ? dh_row(n0 + 16) : n0 + 16;
  const uint32_t a0 = sb + STAGE + r0 * 128 + ((chunk ^ (r0 & 7)) << 4), a1 = sb + STAGE + r1 * 128 + ((chunk ^ (r1 & 7)) << 4);
#pragma unroll
  for (int p = 0; p < 5; p++) {
    mwait(sb + BAR_W + 8 * p, 0, spin);
    if (IS_O) PTS(8 + p);
    if (p + NBX < 5) { if ((tid0 & 127) == 96) stage_box<IS_O>(tms, sb, p + NBX, cta, rank); __syncwarp(); }
    if (IS_O) permute_cols(sb + STAGE + p * 16384, tid0, 512);
    else {
#pragma unroll 1
      for (int it = tid0 & 127; it < 256; it += 128) {
        const uint32_t base = sb + STAGE + p * 16384 + (it >> 1) * 128;
        const int sw = ((it >> 1) & 7) ^ ((it & 1) * 4);
        const uint4 u0 = lds128(base + (sw << 4)), u1 = lds128(base + ((sw ^ 1) << 4)), u2 = lds128(base + ((sw ^ 2) << 4)), u3 = lds128(base + ((sw ^ 3) << 4));
        sts128(base + (sw << 4), make_uint4(u0.x, u1.x, u2.x, u3.x)); sts128(base + ((sw ^ 1) << 4), make_uint4(u0.y, u1.y, u2.y, u3.y));
        sts128(base + ((sw ^ 2) << 4), make_uint4(u0.z, u1.z, u2.z, u3.z)); sts128(base + ((sw ^ 3) << 4), make_uint4(u0.w, u1.w, u2.w, u3.w));
      }
    }
    bar_sync(NB, 128);
#pragma unroll
    for (int k = 8 * p; k < 8 * p + 8; k++) {
      if (k < NKR) ldsm4t(wf[k < NKR ? k : 0], ((k & 1) ? a1 : a0) + (k >> 1) * 4096);
      else {
        const int n = k * 16 + ((tid0 & 127) >> 3), r = IS_O ? dh_row(n) : n, c = tid0 & 7;
        sts128(sb + YOFF + (n - NKR * 16) * 128 + ((c ^ (n & 7)) << 4), lds128(sb + STAGE + r * 128 + ((c ^ (r & 7)) << 4)));
      }
    }
    fence_async();
    bar_sync(NB, 128);
    if ((tid0 & 127) == 0) {
      mbar_expect_tx(sb + BAR_W + 8 * p, 16384);
      tma2d(sb + STAGE + p * 16384, &tm, (cta / 3) * DH + rank * 64, p * 128, sb + BAR_W + 8 * p);
    }
    __syncwarp();
  }
  PTS(IS_O ? 13 : 14);
  CBAR_SYNC(NB_PRO, 384);
}

__device__ __forceinline__ void load_pair(uint32_t sb, int i, int p, uint32_t slot, uint32_t ph, int& spin) {
  using namespace C;
  mwait(sb + BAR_E + 8 * p, ph, spin);
  elect_g2s_mc(sb + slot, g_xn[i] + p * 16384, 16384, sb + BAR_F + 8 * p);
}
__device__ __forceinline__ void release_round(uint32_t sb, int p, int lane) {
  if (lane < (p == 2 ? 3 : 1)) mbar_arrive_cluster(mapa(sb, p == 2 ? lane : p) + C::BAR_E + 8 * (3 + p));
}

__device__ __forceinline__ void signal_o(int i, int cta) { csignal(CN_O + i * 5 + min(cta / 19, 4)); }

template <int K0, int K1>
__device__ __forceinline__ void v_mem_pass(float (&d)[8], const uint32_t (&wf)[C::NKR][4]) {
  using namespace C;
#pragma unroll
  for (int j = K0; j < K1; j++) {
    const int k = m_tile(j >> 2) * 4 + (j & 3);
    if (k < NKR) wgmma_rs16(d, wf[k < NKR ? k : 0], mdesc(j), j != 32);
    else wgmma_ts16(d, wdesc(OFF_YV + (k - NKR) * 2048), mdesc(j), 1);
  }
  wg_commit();
}
__device__ __forceinline__ void chain_v(const CUtensorMap& tmWv, const CUtensorMap& tmWk, const uint32_t sb, const int tid0, const int cta, const int rank) {
  using namespace C;
  asm volatile("setmaxnreg.inc.sync.aligned.u32 208;");
  int spin = 0;
  uint32_t wf[NKR][4];
  const int wu = uni((tid0 >> 5) & 3);
  const uint32_t slot = rank == 2 ? OFF_M : OFF_KT + rank * 16384;
  load_weights_rs<false>(wf, tmWv, tmWk, cta, rank, sb, tid0, spin);
  PTS(5);
#pragma unroll 1
  for (int i = 0; i < NSTEP; i++) {
    uint32_t vp[16], va;
#define STORE_V { _Pragma("unroll") for (int s = 0; s < 4; s++) stsm4(va + 128 + s * 128, vp[4 * s], vp[4 * s + 1], vp[4 * s + 2], vp[4 * s + 3]); }
    {
      float d[32];
      if (i > 0) CBAR_SYNC(NB_WV, 256);
#pragma unroll
      for (int p = 0; p < 5; p++) {
        if (OSV && p == 3) {
          wg_wait<0>();
          release_round(sb, 2, tid0 & 31);
          if (wu == 1 && i > 0) {
            CBAR_SYNC(NB_MR, 160);
            if (elect_one()) signal_o(i - 1, cta);
          }
        }
        mwait(sb + BAR_F + 8 * p, i & 1, spin);
        TS(i, 25 + p);
        wg_fence();
#pragma unroll
        for (int k = 8 * p; k < 8 * p + 8; k++) {
          if (k < NKR) wgmma_rs64(d, wf[k < NKR ? k : 0], tdesc(k), k);
          else wgmma_ts64(d, wdesc(OFF_YV + (k - NKR) * 2048), tdesc(k), 1);
          if (k == 8 * p + 1 && p >= 1 && p <= (OSV ? 2 : 3)) {
            wg_commit(); wg_wait<1>();
            release_round(sb, p - 1, tid0 & 31);
          }
          if (k == 8 * p + RFK && (p == 1 || p == 2)) {
            wg_commit();
            if (rank == p - 1 && wu == 0) load_pair(sb, i, p + 2, slot_off(p + 2), i & 1, spin);
            wg_fence();
          }
        }
        wg_commit();
      }
      wg_wait<0>();
      TS(i, 23);
#pragma unroll
      for (int q = 0; q < 16; q++) vp[q] = pin(pack_bf16(d[2 * q], d[2 * q + 1]));
      CBAR_SYNC(NB_RD, 256);
      const int tid = fresh(tid0) & 127, m = (tid >> 3) & 3;
      if (wu == 3) {
        const int lane = tid & 31;
        if (lane < 3 && lane != rank) mbar_arrive_cluster(mapa(sb, lane) + BAR_XF);
        if (lane < 8) mbar_expect_tx(sb + BAR_F + 8 * lane, lane < 5 ? 16384 : lane == 5 ? 2560 : lane == 6 ? 7168 : 4096);
        mwait(sb + BAR_XF, i & 1, spin);
      } else {
        if (tid < 80) sts128(sb + (tid < 72 ? OFF_VT + (tid >> 3) * VS : OFF_PT + 1280) + (tid & 7) * 16, make_uint4(0, 0, 0, 0));
        fence_async();
      }
      CBAR_ARRIVE(NB_QK, 384);
      TS(i, 16);
      va = sb + OFF_VT + 128 + ((tid >> 5) * 2 + (m & 1)) * VS + (m >> 1) * 640 + (tid & 7) * 16;
    }
    const uint32_t* xc = &g_cnt[CN_X + i + 1][0];
    const uint32_t xn = NOWORK == 2 || i + 1 < NPRE ? 0 : i + 1 < LAG || NOWORK ? 16 : 48;
    bool seen = false;
    if (wu == 0) seen = __any_sync(0xffffffffu, ld_relaxed(xc) >= xn);
    CBAR_SYNC(NB_V, 256);
    float d[8];
    wg_fence();
    v_mem_pass<32, 40>(d, wf);
    v_mem_pass<0, 6>(d, wf);
    wg_wait<1>();
    if ((tid0 & 31) < 3 && (tid0 & 31) != rank) mbar_arrive_cluster(mapa(sb, tid0 & 31) + BAR_MF);
    v_mem_pass<6, 32>(d, wf);
    if (VSL == 2) STORE_V
    CBAR_SYNC(NB_SM, 256);
    wg_wait<0>();
    TS(i, 24);
    const int tid = fresh(tid0);
    if (!E2L && (tid & 31) == 0) mbar_arrive_cluster(mapa(sb, 2) + BAR_E + 16);
    stsm4(va, pack_bf16(d[0], d[1]), pack_bf16(d[2], d[3]), pack_bf16(d[4], d[5]), pack_bf16(d[6], d[7]));
#undef STORE_V
    fence_async();
    CBAR_ARRIVE(NB_VA, 256);
    CBAR_ARRIVE(NB_VQ, QPV ? 384 : 256);
    if (wu == 0 && i + 1 < NSTEP) {
      if (!seen) while (ld_relaxed(xc) < xn && spin < SPIN_TOT) spin += 16;
      fence_async_all();
      load_pair(sb, i + 1, rank, slot, i & 1, spin);
      TS(i + 1, 37);
    }
    TS_FLUSH(i - 1);
    __syncwarp();
  }
  CBAR_ARRIVE(NB_WV, 256);
  if (spin >= SPIN_TOT) g_err = 3;
}

__device__ __forceinline__ float quad_max(float x) {
  const float a = __shfl_xor_sync(0xffffffffu, x, 1), b = __shfl_xor_sync(0xffffffffu, x, 2), c = __shfl_xor_sync(0xffffffffu, x, 3);
  return fmaxf(fmaxf(x, a), fmaxf(b, c));
}
__device__ __forceinline__ float max10(const float (&y)[10]) {
  return fmaxf(fmaxf(fmaxf(fmaxf(y[0], y[1]), fmaxf(y[2], y[3])), fmaxf(fmaxf(y[4], y[5]), fmaxf(y[6], y[7]))), fmaxf(y[8], y[9]));
}
__device__ __forceinline__ float sum10(const float (&y)[10]) {
  return (((y[0] + y[1]) + (y[2] + y[3])) + ((y[4] + y[5]) + (y[6] + y[7]))) + (y[8] + y[9]);
}
__device__ __forceinline__ float rcp(float x) { float y; asm("rcp.approx.ftz.f32 %0,%1;" : "=f"(y) : "f"(x)); return y; }

__device__ __forceinline__ void chain_q(const bf16* x0, const bf16* mem0, const uint32_t sb, const int tid0, const int cta, const int rank) {
  using namespace C;
  asm volatile("setmaxnreg.dec.sync.aligned.u32 96;");
  int spin = 0;
  PTS(0);
  pre_work(x0, mem0, cta, tid0 & 127);
  PTS(3);
  CBAR_SYNC(NB_Q, 128);
  PTS(2);
  if (tid0 < 160) {
    if (tid0 == 128) pre_wait(0, 96, spin);
    __syncwarp();
    load_pair(sb, 0, rank, rank == 2 ? OFF_M : OFF_KT + rank * 16384, 1, spin);
  }
  PTS(4);
  CBAR_SYNC(NB_PRO, 384);
  mwait(sb + BAR_W, 1, spin);
  PTS(6);
  const int wu = uni((tid0 >> 5) & 3);
  uint4 ov[4] = {};
  uint8_t* op = &g_o[ORING - 1][cta][(tid0 & 124) * 32];
  const uint32_t o0 = ((tid0 ^ (tid0 >> 2)) & 3) * 16 + (tid0 & 16) * 4;
#pragma unroll 1
  for (int i = 0; i < NSTEP; i++) {
    const int ph = i & 1;
    uint32_t qf[4][4];
    {
      float d[64];
#define QK_STEP(K, SC) wgmma_st128(d, desc_at(mkdesc(SB0 + ((K) >> 2) * 1024 + ((K) & 3) * 32, 16, 2048), so), \
                                   desc_at(mkdesc(SB0 + OFF_WQ + (K) * 2048, OFF_WK - OFF_WQ, 1024), p * 16384), SC)
      int p = 0;
      uint32_t so = OFF_KT;
      mwait(sb + BAR_F, ph, spin);
      TS(i, 0);
      wg_fence();
#pragma unroll
      for (int k = 0; k < 8; k++) {
        QK_STEP(k, k);
        if (k == OST) {
          wg_commit();
          mwait(sb + BAR_F, ph, spin);
#pragma unroll
          for (int h = 0; h < 4; h++) stg128(op + (h & 1) * 4096 + (o0 ^ ((h >> 1) * 64)), ov[h]);
          if (i > 0) CBAR_ARRIVE(NB_MR, 160);
          if (k < 7) wg_fence();
        }
      }
      if (OST != 7) wg_commit();
#pragma unroll 1
      for (p = 1; p < 5; p++) {
        static_assert(OFF_KT - OFF_M == 5 << 12, "");
        so = OFF_M + (((0x95095u >> (4 * p)) & 15) << 12);
        if (i == 0) { mwait(sb + BAR_W + 8 * p, 1, spin); PTS(14 + p); }
        mwait(sb + BAR_F + 8 * p, ph, spin);
        if (OST > 7 && p == OST - 8) {
#pragma unroll
          for (int h = 0; h < 4; h++) stg128(op + (h & 1) * 4096 + (o0 ^ ((h >> 1) * 64)), ov[h]);
          if (i > 0) CBAR_ARRIVE(NB_MR, 160);
        }
        wg_fence();
#pragma unroll
        for (int k = 0; k < 8; k++) {
          QK_STEP(k, 1);
          if (k == 1) {
            wg_commit(); wg_wait<1>();
            release_round(sb, p - 1, p < 4 ? tid0 & 31 : 32);
          }
        }
        wg_commit();
      }
#undef QK_STEP
      wg_wait<0>();
      TS(i, 1);
      CBAR_SYNC(NB_RD, 256);
      TSB(i, 2);
      const int tid = fresh(tid0), w = (tid >> 5) & 3, m = (tid >> 3) & 3;
      const uint32_t a = sb + OFF_KT + (m >> 1) * KS + (1 + w + 5 * (m & 1)) * 128 + (tid & 7) * 16;
#pragma unroll
      for (int s = 0; s < 4; s++)
        stsm4t(a + s * 2 * KS, pack_bf16(d[32 + 8 * s], d[33 + 8 * s]), pack_bf16(d[34 + 8 * s], d[35 + 8 * s]),
               pack_bf16(d[36 + 8 * s], d[37 + 8 * s]), pack_bf16(d[38 + 8 * s], d[39 + 8 * s]));
      fence_async();
      CBAR_ARRIVE(NB_QK, 384);
      TS(i, 15);
#pragma unroll
      for (int kk = 0; kk < 4; kk++)
#pragma unroll
        for (int j = 0; j < 4; j++) asm volatile("{.reg .b32 t; cvt.rn.bf16x2.f32 t,%1,%2; mul.rn.bf16x2 %0,t,%3;}" : "=r"(qf[kk][j]) : "f"(d[8 * kk + 2 * j + 1]), "f"(d[8 * kk + 2 * j]), "r"(SCQ));
    }
    CBAR_SYNC(NB_SI, 256);
    uint32_t pf[5][4];
    float sa = 0.f, sb2 = 0.f;
    {
      float y0[10], y1[10];
      const int tidf = fresh(tid0), lane = tidf & 31;
      {
        float x[40];
        wg_fence();
#pragma unroll
        for (int kk = 0; kk < 4; kk++) {
          if (VTI && kk == 4 - VTI) CBAR_ARRIVE(NB_V, 256);
          wgmma_rt80(x, qf[kk], mkdesc_ns(SB0 + OFF_KT + kk * 2 * KS, KS, 128), kk);
        }
        wg_commit();
        wg_wait<0>();
#pragma unroll
        for (int j = 0; j < 5; j++) { y0[2 * j] = x[4 * j]; y0[2 * j + 1] = x[4 * j + 1]; y1[2 * j] = x[22 + 4 * j]; y1[2 * j + 1] = x[23 + 4 * j]; }
      }
      TS(i, 17);
      const uint32_t xo = OFF_XT + (wu * (wu + 3) / 2) * 256 + lane * 16, x2 = xo + (wu >> 1) * 512 + 512 - lane * 8;
      {
        const uint4 h0 = make_uint4(pack_h2(y0[0], y0[1]), pack_h2(y1[0], y1[1]), pack_h2(y0[2], y0[3]), pack_h2(y1[2], y1[3]));
        const uint4 h1 = make_uint4(pack_h2(y0[4], y0[5]), pack_h2(y1[4], y1[5]), pack_h2(y0[6], y0[7]), pack_h2(y1[6], y1[7]));
        const uint32_t h2 = wu == 1 ? h1.x : pack_h2(y0[8], y0[9]), h3 = wu == 1 ? h1.y : pack_h2(y1[8], y1[9]);
        const uint32_t rb1 = mapa(sb, (rank + 1) % 3), rb2 = mapa(sb, (rank + 2) % 3);
        if (XTD == 1) mwait(sb + BAR_XM, ph, spin);
        if (XTD > 1) for (const uint32_t t0 = clk32(); clk32() - t0 < XTD;) {}
        st_async4u(rb1 + xo + 3584, h0, rb1 + BAR_XT);
        st_async4u(rb2 + xo, h0, rb2 + BAR_XT);
        if (wu >= 2) { st_async4u(rb1 + xo + 4096, h1, rb1 + BAR_XT); st_async4u(rb2 + xo + 512, h1, rb2 + BAR_XT); }
        if (wu & 1) { st_async2u(rb1 + x2 + 3584, h2, h3, rb1 + BAR_XT); st_async2u(rb2 + x2, h2, h3, rb2 + BAR_XT); }
      }
      TS(i, 18);
      const int lim = 8 * wu + (lane >> 2) + 8 - 2 * (lane & 3);
#pragma unroll
      for (int j = 2; j < 10; j++)
        if (8 * (j >> 1) + (j & 1) > lim) { y0[j] = -INFINITY; y1[j] = -INFINITY; }
      mwait(sb + BAR_XT, ph, spin);
      TS(i, 19);
      {
        const uint4 u0 = lds128(sb + xo), v0 = lds128(sb + xo + 3584);
        uint2 u2 = make_uint2(0, 0), v2 = u2;
        if (wu & 1) { u2 = lds64(sb + x2); v2 = lds64(sb + x2 + 3584); }
        uint4 u1 = make_uint4(u2.x, u2.y, 0, 0), v1 = make_uint4(v2.x, v2.y, 0, 0);
        if (wu >= 2) { u1 = lds128(sb + xo + 512); v1 = lds128(sb + xo + 4096); }
        __syncwarp();
        if (lane == 0) mbar_arrive_cluster(mapa(sb, 0) + BAR_E);
        add_h2(y0[0], y0[1], u0.x, v0.x); add_h2(y1[0], y1[1], u0.y, v0.y); add_h2(y0[2], y0[3], u0.z, v0.z); add_h2(y1[2], y1[3], u0.w, v0.w);
        add_h2(y0[4], y0[5], u1.x, v1.x); add_h2(y1[4], y1[5], u1.y, v1.y); add_h2(y0[6], y0[7], u1.z, v1.z); add_h2(y1[6], y1[7], u1.w, v1.w);
        add_h2(y0[8], y0[9], u2.x, v2.x); add_h2(y1[8], y1[9], u2.y, v2.y);
      }
      const float m0 = quad_max(max10(y0)) * -SCE, m1 = quad_max(max10(y1)) * -SCE;
#pragma unroll
      for (int j = 0; j < 5; j++) {
        y0[2 * j] = ex2(fmaf(y0[2 * j], SCE, m0)); y0[2 * j + 1] = ex2(fmaf(y0[2 * j + 1], SCE, m0));
        y1[2 * j] = ex2(fmaf(y1[2 * j], SCE, m1)); y1[2 * j + 1] = ex2(fmaf(y1[2 * j + 1], SCE, m1));
        if (!ONES) { sa += y0[2 * j] + y0[2 * j + 1]; sb2 += y1[2 * j] + y1[2 * j + 1]; }
        pf[j >> 1][2 * (j & 1)] = pack_bf16(y0[2 * j], y0[2 * j + 1]);
        pf[j >> 1][2 * (j & 1) + 1] = tidf >> (10 + j);
        pf[(j + 5) >> 1][2 * ((j + 5) & 1)] = tidf >> (20 + j);
        pf[(j + 5) >> 1][2 * ((j + 5) & 1) + 1] = pack_bf16(y1[2 * j], y1[2 * j + 1]);
      }
    }
#pragma unroll
    for (int q = 0; q < 20; q++) pf[q >> 2][q & 3] = pin(pf[q >> 2][q & 3]);
    CBAR_SYNC(NB_VQ, QPV ? 384 : 256);
    TSB(i, 20);
    {
      float o[32], sm[4];
      wg_fence();
#pragma unroll
      for (int q = 0; q < 5; q++) if (ONES) wgmma_rs8(sm, pf[q], mkdesc_ns(SB0 + OFF_ONE, 0, 0), q);
#pragma unroll
      for (int q = 0; q < 5; q++) wgmma_rs64(o, pf[q], mkdesc_ns(SB0 + OFF_VT + 128 + q * 256, 128, VS), q);
      wg_commit();
      if (!ONES) { sm[0] = quad_sum(sa); sm[2] = quad_sum(sb2); }
      const int tid = fresh(tid0);
      op = &g_o[i % ORING][cta][(tid & 124) * 32];
      wg_wait<0>();
      TS(i, 21);
      if ((tid & 31) == 0) mbar_arrive_cluster(mapa(sb, 1) + BAR_E + 8);
      const float s0 = rcp(sm[0]), s1 = rcp(sm[2]);
#pragma unroll
      for (int h = 0; h < 2; h++) {
        const float* x = o + 16 * h;
        ov[2 * h] = make_uint4(pin(pack_bf16(x[0] * s0, x[1] * s0)), pin(pack_bf16(x[4] * s0, x[5] * s0)), pin(pack_bf16(x[8] * s0, x[9] * s0)), pin(pack_bf16(x[12] * s0, x[13] * s0)));
        ov[2 * h + 1] = make_uint4(pin(pack_bf16(x[2] * s1, x[3] * s1)), pin(pack_bf16(x[6] * s1, x[7] * s1)), pin(pack_bf16(x[10] * s1, x[11] * s1)), pin(pack_bf16(x[14] * s1, x[15] * s1)));
      }
      TS(i, 22);
      if (i + 1 < NSTEP) CBAR_SYNC(NB_WQ, 256); else CBAR_ARRIVE(NB_WQ, 256);
    }
  }
#pragma unroll
  for (int h = 0; h < 4; h++) stg128(op + (h & 1) * 4096 + (o0 ^ ((h >> 1) * 64)), ov[h]);
  CBAR_SYNC(NB_Q, 128);
  if (tid0 == 224) signal_o(NSTEP - 1, cta);
  if (spin >= SPIN_TOT) g_err = 2;
}

template <int NL> __device__ __forceinline__ void poll(uint4 (&x)[NL], const uint8_t* mb, uint32_t tag, int& spin);
template <> __device__ __forceinline__ void poll<4>(uint4 (&x)[4], const uint8_t* mb, uint32_t tag, int& spin) {
  asm volatile("{.reg .pred p<6>, q; .reg .b128 v; .reg .b32 t;\n"
               " ld.relaxed.gpu.global.b128 v,[%17+0]; mov.b128 {%0,%1,%2,%3},v;\n"
               " ld.relaxed.gpu.global.b128 v,[%17+512]; mov.b128 {%4,%5,%6,%7},v;\n"
               " ld.relaxed.gpu.global.b128 v,[%17+1024]; mov.b128 {%8,%9,%10,%11},v;\n"
               " ld.relaxed.gpu.global.b128 v,[%17+1536]; mov.b128 {%12,%13,%14,%15},v;\n"
               "POLL_LOOP:\n add.s32 %16,%16,16;\n"
               " lop3.b32 t,%0,%18,1,0x28; setp.ne.b32 p0,t,0;\n"
               " lop3.b32 t,%4,%18,1,0x28; setp.ne.b32 p1,t,0;\n"
               " lop3.b32 t,%8,%18,1,0x28; setp.ne.b32 p2,t,0;\n"
               " lop3.b32 t,%12,%18,1,0x28; setp.ne.b32 p3,t,0;\n"
               " or.pred q,p0,p1; or.pred q,q,p2; or.pred q,q,p3; setp.lt.and.s32 q,%16,%19,q; vote.sync.any.pred q,q,0xffffffff;\n"
               " mov.b128 v,{%0,%1,%2,%3}; @p0 ld.relaxed.gpu.global.b128 v,[%17+0]; mov.b128 {%0,%1,%2,%3},v;\n"
               " mov.b128 v,{%4,%5,%6,%7}; @p1 ld.relaxed.gpu.global.b128 v,[%17+512]; mov.b128 {%4,%5,%6,%7},v;\n"
               " mov.b128 v,{%8,%9,%10,%11}; @p2 ld.relaxed.gpu.global.b128 v,[%17+1024]; mov.b128 {%8,%9,%10,%11},v;\n"
               " mov.b128 v,{%12,%13,%14,%15}; @p3 ld.relaxed.gpu.global.b128 v,[%17+1536]; mov.b128 {%12,%13,%14,%15},v;\n"
               " @q bra.uni POLL_LOOP;\n}"
               : "=&r"(x[0].x), "=&r"(x[0].y), "=&r"(x[0].z), "=&r"(x[0].w), "=&r"(x[1].x), "=&r"(x[1].y), "=&r"(x[1].z), "=&r"(x[1].w), "=&r"(x[2].x), "=&r"(x[2].y), "=&r"(x[2].z), "=&r"(x[2].w), "=&r"(x[3].x), "=&r"(x[3].y), "=&r"(x[3].z), "=&r"(x[3].w), "+&r"(spin)
               : "l"(mb), "r"(tag), "n"(SPIN_TOT) : "memory");
}
template <> __device__ __forceinline__ void poll<6>(uint4 (&x)[6], const uint8_t* mb, uint32_t tag, int& spin) {
  asm volatile("{.reg .pred p<6>, q; .reg .b128 v; .reg .b32 t;\n"
               " ld.relaxed.gpu.global.b128 v,[%25+0]; mov.b128 {%0,%1,%2,%3},v;\n"
               " ld.relaxed.gpu.global.b128 v,[%25+512]; mov.b128 {%4,%5,%6,%7},v;\n"
               " ld.relaxed.gpu.global.b128 v,[%25+1024]; mov.b128 {%8,%9,%10,%11},v;\n"
               " ld.relaxed.gpu.global.b128 v,[%25+1536]; mov.b128 {%12,%13,%14,%15},v;\n"
               " ld.relaxed.gpu.global.b128 v,[%25+2048]; mov.b128 {%16,%17,%18,%19},v;\n"
               " ld.relaxed.gpu.global.b128 v,[%25+2560]; mov.b128 {%20,%21,%22,%23},v;\n"
               "POLL_LOOP:\n add.s32 %24,%24,16;\n"
               " lop3.b32 t,%0,%2,%26,0x7e; and.b32 t,t,1; setp.ne.b32 p0,t,0;\n"
               " lop3.b32 t,%4,%6,%26,0x7e; and.b32 t,t,1; setp.ne.b32 p1,t,0;\n"
               " lop3.b32 t,%8,%10,%26,0x7e; and.b32 t,t,1; setp.ne.b32 p2,t,0;\n"
               " lop3.b32 t,%12,%14,%26,0x7e; and.b32 t,t,1; setp.ne.b32 p3,t,0;\n"
               " lop3.b32 t,%16,%18,%26,0x7e; and.b32 t,t,1; setp.ne.b32 p4,t,0;\n"
               " lop3.b32 t,%20,%22,%26,0x7e; and.b32 t,t,1; setp.ne.b32 p5,t,0;\n"
               " or.pred q,p0,p1; or.pred q,q,p2; or.pred q,q,p3; or.pred q,q,p4; or.pred q,q,p5; setp.lt.and.s32 q,%24,%27,q; vote.sync.any.pred q,q,0xffffffff;\n"
               " mov.b128 v,{%0,%1,%2,%3}; @p0 ld.relaxed.gpu.global.b128 v,[%25+0]; mov.b128 {%0,%1,%2,%3},v;\n"
               " mov.b128 v,{%4,%5,%6,%7}; @p1 ld.relaxed.gpu.global.b128 v,[%25+512]; mov.b128 {%4,%5,%6,%7},v;\n"
               " mov.b128 v,{%8,%9,%10,%11}; @p2 ld.relaxed.gpu.global.b128 v,[%25+1024]; mov.b128 {%8,%9,%10,%11},v;\n"
               " mov.b128 v,{%12,%13,%14,%15}; @p3 ld.relaxed.gpu.global.b128 v,[%25+1536]; mov.b128 {%12,%13,%14,%15},v;\n"
               " mov.b128 v,{%16,%17,%18,%19}; @p4 ld.relaxed.gpu.global.b128 v,[%25+2048]; mov.b128 {%16,%17,%18,%19},v;\n"
               " mov.b128 v,{%20,%21,%22,%23}; @p5 ld.relaxed.gpu.global.b128 v,[%25+2560]; mov.b128 {%20,%21,%22,%23},v;\n"
               " @q bra.uni POLL_LOOP;\n}"
               : "=&r"(x[0].x), "=&r"(x[0].y), "=&r"(x[0].z), "=&r"(x[0].w), "=&r"(x[1].x), "=&r"(x[1].y), "=&r"(x[1].z), "=&r"(x[1].w), "=&r"(x[2].x), "=&r"(x[2].y), "=&r"(x[2].z), "=&r"(x[2].w), "=&r"(x[3].x), "=&r"(x[3].y), "=&r"(x[3].z), "=&r"(x[3].w), "=&r"(x[4].x), "=&r"(x[4].y), "=&r"(x[4].z), "=&r"(x[4].w), "=&r"(x[5].x), "=&r"(x[5].y), "=&r"(x[5].z), "=&r"(x[5].w), "+&r"(spin)
               : "l"(mb), "r"(tag), "n"(SPIN_TOT) : "memory");
}
template <int NL>
__device__ __forceinline__ void poll_add(const uint8_t* mb, uint32_t tag, float (&f)[8], uint8_t* flag, bool lead, int& spin) {
  uint4 x[NL];
  poll<NL>(x, mb, tag, spin);
  if (FLP == 0 && lead) st_relaxed16(flag, 0);
#pragma unroll
  for (int i = 0; i < NL; i++) {
    const uint32_t u[4] = {x[i].x, x[i].y, x[i].z, x[i].w};
#pragma unroll
    for (int j = 0; j < 4; j++) {
      if (i == 0) { f[2 * j] = bf_lo(u[j]); f[2 * j + 1] = bf_hi(u[j]); }
      else { f[2 * j] += bf_lo(u[j]); f[2 * j + 1] += bf_hi(u[j]); }
    }
  }
}

template <int B, int SLOT>
__device__ __forceinline__ void wo_step(float (&acc)[8], const uint32_t (&wf)[C::NKR][4], int kk) {
  using namespace C;
  const int k = 4 * B + kk;
  const uint64_t db = mkdesc_ns(SB0 + og_off(SLOT) + kk * 512, 256, 128);
  if (k < NKR) wgmma_rt16(acc, wf[k < NKR ? k : 0], db, SLOT | kk);
  else wgmma_tt16(acc, wdesc(OFF_YO + (k - NKR) * 2048), db, 1);
}
template <int B, int SLOT>
__device__ __forceinline__ void wo_block(float (&acc)[8], const uint32_t (&wf)[C::NKR][4]) {
#pragma unroll
  for (int kk = 0; kk < 4; kk++) wo_step<B, SLOT>(acc, wf, kk);
}

__device__ __forceinline__ void chain_a(const CUtensorMap& tmWo, const CUtensorMap& tmWq, const uint32_t sb, const int tid0, const int cta, const int rank) {
  using namespace C;
  asm volatile("setmaxnreg.inc.sync.aligned.u32 200;");
  int spin = 0;
  uint32_t wf[NKR][4];
  load_weights_rs<true>(wf, tmWo, tmWq, cta, rank, sb, tid0, spin);
  const int wu = uni(tid0 >> 5);
  const int head = cta / 3, c9 = rank * 8 + head - 32;
  const bool t9 = head >= 24 && rank > 0;
  const uint64_t exa = reinterpret_cast<uint64_t>(ex_window(g_ex));
  const uint32_t ehi = (uint32_t)(exa >> 32), elo = (uint32_t)exa;

  int b1 = B1, b2 = B2;
#pragma unroll 1
  for (int i = -1; i < NSTEP; i++) {
    const int ph = i & 1;
    if (i >= 0) {
      const int tid = fresh(tid0);
      const uint32_t mo = __shfl_xor_sync(0xffffffffu, elo + ((rank * 8 + (tid >> 4)) * 4 + (tid & 3)) * 2048 + head * 64 + (tid & 12) * 4, 0);
      const uint32_t m9 = __shfl_xor_sync(0xffffffffu, elo + MAIL9 + (((tid >> 4) * 2 + (tid & 1)) * 4 + (tid & 2)) * 3072 + cta * 32 + (tid & 12) * 2, 0);
      const uint32_t oo = __shfl_xor_sync(0xffffffffu, (tid >> 5) * 512 + (tid & 2) * 64 + (tid & 28) * 4 + (tid & 1) * 8, 0);
      if (i == 0) { mwait(sb + BAR_W + 24, 1, spin); mwait(sb + BAR_W + 32, 1, spin); PTS(7); }
      mwait(sb + BAR_M, ph, spin);
      TS(i, 3);
      {
        float x[20];
        int redo = 0;
      retry:
        bool bad;
        {
          float dq[8] = {}, dk[8] = {};
          const uint32_t late = (mbar_test(sb + BAR_M + 8, ph) ? 0 : 8) | (mbar_test(sb + BAR_M + 16, ph) ? 0 : 64);
#pragma unroll 1
          for (int j = 0; j < 10; j++) {
            if ((late >> j) & 1) mwait(sb + BAR_M + (j == 3 ? 8 : 16), ph, spin);
            const uint32_t wo = m_tile(j) * 8192;
            wg_fence();
#pragma unroll
            for (int k = 0; k < 4; k++) {
              const uint64_t db = desc_at(mdesc(k), j * 2048);
              wgmma_ts16(dq, desc_at(wdesc(OFF_WQ + k * 2048), wo), db, 1);
              wgmma_ts16(dk, desc_at(wdesc(OFF_WK + k * 2048), wo), db, 1);
            }
            wg_commit();
          }
          const int m = (tid >> 3) & 3, dg = (tid >> 5) * 2 + (m & 1);
          const uint32_t ka = sb + OFF_KT + dg * KS + (m >> 1) * 640 + (tid & 7) * 16;
          if (!redo) CBAR_SYNC(NB_QK, 384);
          wg_wait<0>();
          TS(i, 4);
          stsm4(ka, pack_bf16(dk[0], dk[1]), pack_bf16(dk[2], dk[3]), pack_bf16(dk[4], dk[5]), pack_bf16(dk[6], dk[7]));
          stsm4(ka + dg * (VS - KS) + (OFF_VT + 128 - OFF_KT), scale_bf16x2(pack_bf16(dq[0], dq[1]), SCQ), scale_bf16x2(pack_bf16(dq[2], dq[3]), SCQ),
                scale_bf16x2(pack_bf16(dq[4], dq[5]), SCQ), scale_bf16x2(pack_bf16(dq[6], dq[7]), SCQ));
          const float chk = (dq[0] + dq[1]) + (dq[4] + dq[5]);
          fence_async();
          bad = bar_red_or(NB_C, 128, chk != chk && !redo);
        }
        TSB(i, 5);
        wg_fence();
#pragma unroll
        for (int kk = 0; kk < 4; kk++) wgmma_tt40(x, mkdesc_ns(SB0 + OFF_VT + 128 + kk * 2 * VS, VS, 640), mkdesc_ns(SB0 + OFF_KT + kk * 2 * KS, KS, 128), kk);
#pragma unroll
        for (int kk = 0; kk < 4; kk++) {
          if (SIE && kk == 4 - SIE && !bad) CBAR_ARRIVE(NB_SI, 256);
          wgmma_tt40(x, mkdesc_ns(SB0 + OFF_VT + kk * 2 * VS, VS, 384), mkdesc_ns(SB0 + OFF_KT + 640 + kk * 2 * KS, KS, 128), 1);
        }
        wg_commit();
        if (!SIE && !bad) CBAR_ARRIVE(NB_SI, 256);
        if (__builtin_expect(__any_sync(0xffffffffu, bad), 0)) {
          wg_wait<0>();
#pragma unroll 1
          for (int k = 0; k < 10; k++) {
            uint4 v = lds128(sb + OFF_M + tid * 16 + k * 2048);
            if (v.x == SENT || v.y == SENT || v.z == SENT || v.w == SENT) {
              do { v = ld_relaxed4(mkptr(elo + EX_M + i * 20480 + tid * 16 + k * 2048, ehi)); spin += 16; } while ((v.x == SENT || v.y == SENT || v.z == SENT || v.w == SENT) && spin < SPIN_TOT);
              sts128(sb + OFF_M + tid * 16 + k * 2048, v);
            }
          }
          fence_async();
          bar_sync(NB_C, 128);
          redo = fresh(1);
          goto retry;
        }
        TSV(i, 36, redo);
        const uint32_t rb1 = mapa(sb, (rank + 1) % 3), rb2 = mapa(sb, (rank + 2) % 3);
        wg_wait<0>();
        TS(i, 6);
        if (wu < 2) {
          float y[10];
#pragma unroll
          for (int j = 0; j < 5; j++) { y[2 * j] = x[4 * j]; y[2 * j + 1] = x[4 * j + 1]; }
          const uint4 h0 = make_uint4(pack_h2(y[0], y[1]), pack_h2(y[2], y[3]), pack_h2(y[4], y[5]), pack_h2(y[6], y[7]));
          const uint32_t h1 = pack_h2(y[8], y[9]);
          const uint32_t xo = wu * 640 + (tid & 31) * 16, xp = wu * 640 + 512 + (tid & 31) * 4;
          if (XMB) {
            sts128(sb + og_off(0) + xo, h0); sts32(sb + og_off(0) + xp, h1);
            fence_async();
            __syncwarp();
            if (elect_one()) {
              bulk_s2c(rb1 + OFF_XM + 1280 + wu * 640, sb + og_off(0) + wu * 640, 640, rb1 + BAR_XM);
              bulk_s2c(rb2 + OFF_XM + wu * 640, sb + og_off(0) + wu * 640, 640, rb2 + BAR_XM);
            }
          } else {
            st_async4u(rb1 + OFF_XM + 1280 + xo, h0, rb1 + BAR_XM);
            st_async4u(rb2 + OFF_XM + xo, h0, rb2 + BAR_XM);
            st_async1u(rb1 + OFF_XM + 1280 + xp, h1, rb1 + BAR_XM);
            st_async1u(rb2 + OFF_XM + xp, h1, rb2 + BAR_XM);
          }
          CBAR_ARRIVE(NB_SM, 256);
          if (!E0L && (tid & 31) == 0) mbar_arrive_cluster(mapa(sb, 0) + BAR_E);
          TS(i, 7);
          const uint32_t sw = (tid & 7) * 4 + (tid & 8) * 8 + (tid & 16) * 2;
          mwait(sb + BAR_XM, ph, spin);
          TS(i, 8);
          const uint4 u0 = lds128(sb + OFF_XM + xo), v0 = lds128(sb + OFF_XM + 1280 + xo);
          const uint32_t u1 = lds32(sb + OFF_XM + xp), v1 = lds32(sb + OFF_XM + 1280 + xp);
          add_h2(y[0], y[1], u0.x, v0.x); add_h2(y[2], y[3], u0.y, v0.y); add_h2(y[4], y[5], u0.z, v0.z); add_h2(y[6], y[7], u0.w, v0.w);
          add_h2(y[8], y[9], u1, v1);
          const float mx = quad_max(max10(y)) * -SCE;
#pragma unroll
          for (int j = 0; j < 5; j++) {
            y[2 * j] = ex2(fmaf(y[2 * j], SCE, mx)); y[2 * j + 1] = ex2(fmaf(y[2 * j + 1], SCE, mx));
            sts32(sb + OFF_PT + wu * 640 + sw + j * 128, pack_bf16(y[2 * j], y[2 * j + 1]));
          }
          sts32(sb + OFF_XM + 512 + wu * 128 + sw, __float_as_uint(sum10(y)));
          fence_async();
          TS(i, 9);
        } else {
          CBAR_ARRIVE(NB_SM, 256);
          if (!E0L && (tid & 31) == 0) mbar_arrive_cluster(mapa(sb, 0) + BAR_E);
          mwait(sb + BAR_MF, ph, spin);
        }
      }
      CBAR_SYNC(NB_VA, 256);
      TSB(i, 10);
      {
        float o[2][4];
        const float4 e = lds128f(sb + OFF_XM + 512 + (tid & 15) * 16);
        wg_fence();
#pragma unroll
        for (int c = 0; c < 2; c++)
#pragma unroll
          for (int q = 0; q < 3; q++)
            wgmma_ss8(o[c], mkdesc_ns(SB0 + OFF_VT + 128 + c * 640 + q * 256, 128, VS), mkdesc_ns(SB0 + OFF_PT + c * 640 + q * 256, q == 2 && c == 0 ? 768 : 128, 128), q);
        wg_commit();
        if (PVB && __builtin_expect(b1 < 0, 0)) { wg_wait<0>(); break; }
        const uint32_t rb1 = mapa(sb, (rank + 1) % 3), rb2 = mapa(sb, (rank + 2) % 3);
        const float inv = rcp((e.x + e.y) + (e.z + e.w));
        const int sl = (tid & 3) * 2;
        const float i0 = __shfl_sync(0xffffffffu, inv, sl), i1 = __shfl_sync(0xffffffffu, inv, sl + 1);
        const float i2 = __shfl_sync(0xffffffffu, inv, sl + 8), i3 = __shfl_sync(0xffffffffu, inv, sl + 9);
        if (E0L == 1 && (tid & 31) == 0) mbar_arrive_cluster(mapa(sb, 0) + BAR_E);
        if (PVB > 1 && __builtin_expect(b2 < 0, 0)) { wg_wait<0>(); break; }
        wg_wait<0>();
        TS(i, 11);
        const uint32_t p0 = pack_bf16(o[0][0] * i0, o[0][1] * i1), p1 = pack_bf16(o[1][0] * i2, o[1][1] * i3);
        const uint32_t p2 = pack_bf16(o[0][2] * i0, o[0][3] * i1), p3 = pack_bf16(o[1][2] * i2, o[1][3] * i3);
        if (OGF) { sts64(sb + oo + og_off(0), p0, p1); sts64(sb + oo + og_off(0) + 256, p2, p3); fence_async(); }
        if (OGF == 2) {
          __syncwarp();
          elect_s2c2(rb1 + og_off(2) + wu * 512, rb1 + BAR_OG, rb2 + og_off(1) + wu * 512, rb2 + BAR_OG, sb + og_off(0) + wu * 512, 512);
        } else if (OGF < 2) {
          st_async2u(rb1 + oo + og_off(2), p0, p1, rb1 + BAR_OG);
          st_async2u(rb2 + oo + og_off(1), p0, p1, rb2 + BAR_OG);
          st_async2u(rb1 + oo + og_off(2) + 256, p2, p3, rb1 + BAR_OG);
          st_async2u(rb2 + oo + og_off(1) + 256, p2, p3, rb2 + BAR_OG);
        }
        if (!OGF) { sts64(sb + oo + og_off(0), p0, p1); sts64(sb + oo + og_off(0) + 256, p2, p3); fence_async(); }
      }
      if (E0L == 2 && (tid & 31) == 0) mbar_arrive_cluster(mapa(sb, 0) + BAR_E);
      CBAR_SYNC(NB_A, 128);
      TSB(i, 12);
      if (OGF == 3 && wu < 2 && elect_one()) {
        const uint32_t rb = mapa(sb, (rank + 1 + wu) % 3);
        bulk_s2c(rb + og_off(2) - wu * 2048, sb + og_off(0), 2048, rb + BAR_OG);
      }
      {
        float acc[3][8];
        wg_fence();
        wo_block<0, 0>(acc[2], wf);
        wg_commit();
        wo_block<1, 0>(acc[0], wf);
        if (QPV == 1) CBAR_ARRIVE(NB_VQ, 384);
        wo_block<4, 0>(acc[1], wf);
        wg_commit();
        if (QPV == 2) CBAR_ARRIVE(NB_VQ, 384);
        if (tid < (E2L == 1 ? 2 : 1)) mbar_arrive_cluster(mapa(sb, 1 + tid) + BAR_E + 8 + 8 * tid);
        const uint32_t tag = (i >> 1) & 1;
#define TAGGED(LO, HI) ((pack_bf16(LO, HI) & ~1u) | tag)
#define SEND(OFF, U) st_relaxed128(mkptr(mo + (ph << 20), ehi) + (OFF), TAGGED(acc[U][0], acc[U][2]), pack_bf16(acc[U][1], acc[U][3]), pack_bf16(acc[U][4], acc[U][6]), pack_bf16(acc[U][5], acc[U][7]))
        wg_wait<1>();
        const uint32_t n0 = pin(TAGGED(acc[2][0], acc[2][2])), n1 = pin(pack_bf16(acc[2][1], acc[2][3]));
        const uint32_t n2 = pin(TAGGED(acc[2][4], acc[2][6])), n3 = pin(pack_bf16(acc[2][5], acc[2][7]));
        if (T2E) { wg_fence(); wo_block<7, 0>(acc[2], wf); wg_commit(); }
        if (!T9L) { st_relaxed64(mkptr(m9 + (ph << 20), ehi), n0, n1); st_relaxed64(mkptr(m9 + (ph << 20), ehi) + 3072, n2, n3); }
        mwait(sb + BAR_OG, ph, spin);
        asm volatile("fence.proxy.async::generic.acquire.sync_restrict::shared::cluster.cluster;" ::: "memory");
        if (E2L == 2 && tid == 0) mbar_arrive_cluster(mapa(sb, 2) + BAR_E + 16);
        TS(i, 13);
        wg_fence();
        wo_block<2, 1>(acc[0], wf); wo_block<3, 2>(acc[0], wf);
        wg_commit();
        wo_block<5, 1>(acc[1], wf); wo_block<6, 2>(acc[1], wf);
        wg_commit();
        if (QPV == 3) CBAR_ARRIVE(NB_VQ, 384);
        wg_wait<1>();
        if (T9L) { st_relaxed64(mkptr(m9 + (ph << 20), ehi), n0, n1); st_relaxed64(mkptr(m9 + (ph << 20), ehi) + 3072, n2, n3); }
        SEND(0, 0);
        if (!T2E) wo_block<7, 0>(acc[2], wf);
        wo_block<8, 1>(acc[2], wf); wo_block<9, 2>(acc[2], wf);
        wg_commit();
        if (WOE == 0) { CBAR_ARRIVE(NB_WV, 256); CBAR_ARRIVE(NB_WQ, 256); }
        wg_wait<1>(); SEND(24 * 8192, 1);
        if (WOE == 1) CBAR_ARRIVE(NB_WV, 256);
        wg_wait<0>(); SEND(48 * 8192, 2);
        if (WOE == 2) CBAR_ARRIVE(NB_WV, 256);
        if (WOE >= 1) CBAR_ARRIVE(NB_WQ, 256);
#undef SEND
#undef TAGGED
      }
      TS(i, 14);
      if (i < 2) PTS(19 + i);
      if (i + 1 >= NSTEP) break;
    }
    uint32_t t1 = clk32();
    if (i >= 0) {
      const int lane = fresh(tid0) & 31, j = lane >> 3;
      const uint8_t* mb = mkptr(elo + (ph << 20) + (t9 ? MAIL9 + c9 * 12288 + wu * 3072 : (rank * 24 + head % 24) * 8192 + wu * 2048) + lane * 16, ehi);
      const uint32_t tag = (i >> 1) & 1;
      const bool pub = (lane & (t9 ? 6 : 4)) == 0 && !(((t9 ? head : wu) & 1) && i + 1 == LAG) && (t9 || head < 24);
      const uint32_t dst = pin(elo + EX_M + (i + 1) * 20480 +
                               (t9 ? (144 + c9) * 128 + wu * 32 + (j & 1) * 16 + (lane & 1) * 8 + (j >> 1) * 4
                                   : (rank * 24 + head) * 256 + (wu & 1) * 128 + (wu >> 1) * 64 + j * 16 + (lane & 3) * 4));
      uint8_t* flag = mkptr(elo + EX_FLAG + (i + 1) * 3072 + (t9 ? (88 + (c9 >> 1)) * 32 + (c9 & 1) * 8 + wu * 2 : (rank * 32 + head) * 32 + wu * 4 + lane * 2), ehi);
      const bool lead = lane < (t9 ? 1 : 2);
      while (clk32() - t1 < b1) {}
      TS(i + 1, 30);
      float f[8];
      const int n0 = spin;
      if (!t9) poll_add<4>(mb, tag, f, flag, lead, spin);
      else poll_add<6>(mb, tag, f, flag, lead, spin);
      if (FLP == 1 && lead) st_relaxed16(flag, __float_as_uint(f[0] + f[7]) >> 17);
      t1 = clk32();
      b1 = __any_sync(0xffffffffu, spin - n0 > 16) ? min(b1 + AD1, BMX) : max(b1 - AD0, 0);
      TSV(i + 1, 38, b1);
      TS(i + 1, 31); TSV(i + 1, 32, (spin - n0) >> 4);
      const bool h = lane & 16, q = lane & 8;
#pragma unroll
      for (int j = 0; j < 4; j++) f[j] = (h ? f[4 + j] : f[j]) + __shfl_xor_sync(0xffffffffu, h ? f[j] : f[4 + j], 16);
#pragma unroll
      for (int j = 0; j < 2; j++) f[j] = (q ? f[2 + j] : f[j]) + __shfl_xor_sync(0xffffffffu, q ? f[j] : f[2 + j], 8);
      f[0] += __shfl_xor_sync(0xffffffffu, f[0], 4); f[1] += __shfl_xor_sync(0xffffffffu, f[1], 4);
      if (t9) { f[0] += __shfl_xor_sync(0xffffffffu, f[0], 2); f[1] += __shfl_xor_sync(0xffffffffu, f[1], 2); }
      if (pub) st_relaxed(mkptr(dst, ehi), pack_bf16(f[0], f[1]));
      if (FLP == 2 && lead) st_relaxed16(flag, 0);
      if (!OSV && wu == 3) {
        CBAR_SYNC(NB_MR, 160);
        if (elect_one()) signal_o(i, cta);
      }

    }
    if (wu == 0) {
      const int tid = fresh(tid0);
      const uint8_t* pp = mkptr(elo + EX_FLAG + (i + 1) * 3072 + (rank * 32 + (tid < 24 || rank == 2 ? tid : 0)) * 32, ehi);
      while (clk32() - t1 < b2) {}

      int n = 1;
      uint4 x = ld_relaxed4(pp);
      if (tid < 3) mbar_expect_tx(sb + BAR_M + 8 * tid, tid == 2 ? 8192 : 6144);
      bool mok = mbar_test(sb + BAR_MOK, ph ^ 1);
      while (__any_sync(0xffffffffu, ((x.x | x.y | x.z | x.w) & 0x80008000u) && spin < SPIN_TOT)) { x = ld_relaxed4(pp); mok = mbar_test(sb + BAR_MOK, ph ^ 1); n++; spin += 16; }
      if (!mok) mwait(sb + BAR_MOK, ph ^ 1, spin);
      if (B3 && n > 1) { const uint32_t t3 = clk32(); while (clk32() - t3 < B3) {} }
      b2 = n > 1 ? min(b2 + AD3, BMX) : max(b2 - AD2, 0);
      TSV(i + 1, 35, n); TSV(i + 1, 39, b2);
      TS(i + 1, 34);
      elect_g2s_mc(sb + OFF_M + rank * 6144, mkptr(elo + EX_M + (i + 1) * 20480 + rank * 6144, ehi), rank == 2 ? 8192 : 6144, sb + BAR_M + 8 * rank);
      TS(i + 1, 33);
      __syncwarp();
    }
  }
  if (spin >= SPIN_TOT) g_err = 1;
}

__global__ void __cluster_dims__(3, 1, 1) __launch_bounds__(384, 1)
k_chain(const __grid_constant__ CUtensorMap tmWq, const __grid_constant__ CUtensorMap tmWk,
        const __grid_constant__ CUtensorMap tmWv, const __grid_constant__ CUtensorMap tmWo, const bf16* __restrict__ x0, const bf16* __restrict__ mem0) {
  using namespace C;
  extern __shared__ __align__(1024) uint8_t smem[];
  const uint32_t sb = smem_u32(smem);
  const int tid = threadIdx.x;
  const int wg = __shfl_sync(0xffffffffu, tid >> 7, 0);
  const int cta = uni(blockIdx.x), rank = uni(blockIdx.x % 3);

  asm volatile("griddepcontrol.launch_dependents;");
  if (cta < 4) prefetch_l2(tid < 320 ? x0 + (cta * 320 + tid) * 64 : mem0 + (cta * 20 + tid % 20) * 64);
  if (tid == 32) {
    for (int p = 0; p < 5; p++) mbar_init(sb + BAR_W + 8 * p, 2);
    fence_async();
    for (int p = 0; p < NBX; p++) { stage_box<false>(tmWv, sb, p, cta, rank); stage_box<true>(tmWo, sb, p, cta, rank); }
  }
  if (tid == 0) {
    if ((sb & 0xFFFFFF) != SB0) g_err = 100;
    for (int p = 0; p < 5; p++) { mbar_init(sb + BAR_F + 8 * p, 1); mbar_init(sb + BAR_E + 8 * p, p == 2 ? (E2L ? 3 : 12) : p == 1 ? 15 : 24); }
    mbar_init(sb + BAR_M, 1); mbar_init(sb + BAR_M + 8, 1); mbar_init(sb + BAR_M + 16, 1); mbar_init(sb + BAR_MOK, 24); mbar_init(sb + BAR_XM, 1); mbar_init(sb + BAR_XF, 2);
    mbar_init(sb + BAR_XT, 1); mbar_init(sb + BAR_MF, 8); mbar_init(sb + BAR_OG, 1);
    for (int p = 0; p < 5; p++) mbar_expect_tx(sb + BAR_F + 8 * p, 16384);
    for (int p = 0; p < 16; p++) sts32(sb + OFF_SAFE + 4 * p, 0);
    for (int p = 0; p < 32; p++) sts32(sb + OFF_ONE + 4 * p, 0x3F803F80);
    asm volatile("fence.mbarrier_init.release.cluster;" ::: "memory");
    fence_async();
  }
  __syncthreads();
  asm volatile("barrier.cluster.arrive.relaxed.aligned;" ::: "memory");
  asm volatile("barrier.cluster.wait.aligned;" ::: "memory");

  if (wg == 0) chain_a(tmWo, tmWq, sb, keep(tid), cta, rank);
  else if (wg == 1) chain_q(x0, mem0, sb, keep(tid), cta, rank);
  else chain_v(tmWv, tmWk, sb, keep(tid), cta, rank);
  asm volatile("barrier.cluster.arrive.release.aligned;" ::: "memory");
  asm volatile("barrier.cluster.wait.acquire.aligned;" ::: "memory");
}

namespace W {
constexpr int NP = 25, NBC = 11, NW = NP + NBC;
constexpr int PRS = 37, PW = 43 * 2048;
constexpr int OFF_W = 0;
constexpr int OFF_R = 2 * PW;
constexpr int BRS = 36;
constexpr int OFF_WO = 0, OFF_Y = 81920;
constexpr int OFF_X = OFF_Y + 2 * (40 - BRS) * 2048;
constexpr int OFF_WV = OFF_X + 40960;
constexpr int OFF_S = OFF_WV + 81920;
constexpr int COL = 976;
constexpr int OFF_T = OFF_X + 16384;
constexpr int OFF_BAR = 232064;
constexpr int OFF_SAFE = OFF_BAR + 256;
constexpr int SMEM = 232448;
static_assert(OFF_SAFE + 64 <= SMEM && OFF_R + 40960 <= OFF_BAR && OFF_S + 7696 <= OFF_BAR, "");
constexpr uint32_t SB0 = 1024;
constexpr int BAR_F = OFF_BAR, BAR_E = OFF_BAR + 40, BAR_G = OFF_BAR + 80, BAR_W = OFF_BAR + 160, BAR_R = OFF_BAR + 176;
constexpr int NB_G0 = 1, NB_SG = 4, NB_B = 5, NB_AS = 6, NB_SG1 = 7, NB_RED = 8, NB_SF = 9, NB_R = 11, NB_TD = 12, NB_RED3 = 13;
}
#define RTL 1
#define XWL 1
#define FSL 1
#define FSW 1
#define FSA 2
#define WBAR_SYNC(id, n) bar_sync(id, n)
#define WBAR_ARRIVE(id, n) bar_arrive(id, n)

__device__ __forceinline__ uint64_t rdesc(int off, int kk) { return mkdesc(W::SB0 + off + kk * 32, 16, 1024); }
__device__ __forceinline__ uint64_t gdesc(int off, int kk) { return mkdesc_ns(W::SB0 + off + kk * 1024, 512, 512) | ((uint64_t)2 << 62); }
__device__ __forceinline__ void mma_r(float (&d)[32], const uint32_t (&a)[4], uint64_t db, int sc) { wgmma_rs64(d, a, db, sc); }
__device__ __forceinline__ void mma_r(float (&d)[16], const uint32_t (&a)[4], uint64_t db, int sc) { wgmma_rs32(d, a, db, sc); }
__device__ __forceinline__ void mma_s(float (&d)[32], uint64_t da, uint64_t db, int sc) { wgmma_ts64(d, da, db, sc); }
__device__ __forceinline__ void mma_s(float (&d)[16], uint64_t da, uint64_t db, int sc) { wgmma_ts32(d, da, db, sc); }
__device__ __forceinline__ bool dual(int k) { return k >= LAG && k < NSEG; }
__device__ __forceinline__ uint32_t frag_addr(uint32_t base, int tid) {
  const int i = (tid >> 3) & 3, r = tid & 7;
  return base + (r + (i >> 1) * 8) * 128 + (((2 * ((tid >> 5) & 3) + (i & 1)) ^ r) << 4);
}
template <int NK>
__device__ __forceinline__ void load_frags(uint32_t (&wf)[NK][4], uint32_t base, int tid) {
  const uint32_t a0 = frag_addr(base, tid);
#pragma unroll
  for (int k = 0; k < NK; k++) ldsm4t(wf[k], a0 + k * 2048);
}
__device__ __forceinline__ void red_tile(const float* d, int seg, int col0, int tid) {
  float* p = g_x + (size_t)(seg * 32 + 2 * (tid & 3)) * DM + col0 + ((tid >> 5) & 3) * 16 + ((tid >> 2) & 7) * 2;
#pragma unroll
  for (int j = 0; j < 8; j++)
    asm volatile("red.relaxed.gpu.global.add.v2.f32 [%0],{%1,%2};" ::"l"(p + ((j >> 1) * 8 + (j & 1)) * DM), "f"(d[4 * (j >> 1) + (j & 1)]), "f"(d[4 * (j >> 1) + 2 + (j & 1)]) : "memory");
}

template <int ND>
__device__ __forceinline__ void p_products(float (&d)[ND], const uint32_t (&wf)[W::PRS][4], uint32_t sb, int tid0, int& spin) {
  using namespace W;
  constexpr int KF = ND == 32 ? 4 : 8;
  const uint32_t wo = uni(fresh(tid0) >> 7) * PW;
#pragma unroll
  for (int f = 0; f < 80 / KF; f++) {
    mwait(sb + BAR_F + 8 * (f % 5), (f / 5) & 1, spin);
    wg_fence();
#pragma unroll
    for (int kk = 0; kk < KF; kk++) {
      const int q = KF * f + kk;
      const uint64_t db = rdesc(OFF_R + (f % 5) * 8192 + (kk >> 2) * 4096, kk & 3);
      if (q < 2 * PRS && !(q & 1)) mma_r(d, wf[q < 2 * PRS ? q >> 1 : 0], db, q);
      else mma_s(d, desc_at(mkdesc(SB0 + OFF_W + (q < 2 * PRS ? q >> 1 : q - PRS) * 2048, 8192, 1024), wo), db, 1);
      if (kk == KF / 4 - 1 && f > 0) {
        wg_commit();
        wg_wait<1>();
        if ((tid0 & 31) == 0) mbar_arrive(sb + BAR_E + 8 * ((f - 1) % 5));
      }
    }
    wg_commit();
  }
  wg_wait<0>();
  if ((tid0 & 31) == 0) mbar_arrive(sb + BAR_E + 32);
}
__device__ __forceinline__ void work_p(const CUtensorMap& tmWo, uint32_t sb, int pc, const int WG, int tid0) {
  using namespace W;
  asm volatile("setmaxnreg.inc.sync.aligned.u32 208;");
  int spin = 0;
  const int ks = pc / 5, col0 = (pc % 5) * 128 + WG * 64;
  const uint32_t wb = sb + OFF_W + WG * PW;
  uint32_t wf[PRS][4];
#pragma unroll 1
  for (int hf = 0; hf < 2; hf++) {
    const int nk = hf ? 80 - PRS : PRS;
    if ((tid0 & 127) == 0) {
      mbar_expect_tx(sb + BAR_W + 8 * WG, nk * 2048);
      for (int i = 0; i < nk; i++) tma2d(wb + i * 2048, &tmWo, col0, ks * 19 * 64 + (i < PRS ? 2 * i + hf : PRS + i) * 16, sb + BAR_W + 8 * WG);
    }
    __syncwarp();
    mwait(sb + BAR_W + 8 * WG, hf, spin);
    permute_cols(wb, tid0 & 127, nk * 64);
    if (hf == 1 && ks < 4) for (int it = 39 * 64 + (tid0 & 127) - 64; it < 43 * 64; it += 128) {
      const uint32_t a = wb + (it >> 2) * 128 + (((2 * (it & 3)) ^ ((it >> 2) & 6)) << 4);
      if (it >= 39 * 64) { sts128(a, make_uint4(0, 0, 0, 0)); sts128(a + 16, make_uint4(0, 0, 0, 0)); }
    }
    fence_async();
    WBAR_SYNC(NB_G0 + WG, 128);
    if (hf == 0) {
      load_frags<PRS>(wf, wb, tid0);
      fence_async();
      WBAR_SYNC(NB_G0 + WG, 128);
    }
  }
#pragma unroll 1
  for (int k = 0; k < NSTEP; k++) {
    if (dual(k)) {
      float d[32];
      p_products(d, wf, sb, tid0, spin);
      if (WG == 0 && pc == WW) WTS(k, 2);
      red_tile(d, k, col0, tid0);
      red_tile(d + 16, k - LAG, col0, tid0);
    } else {
      float d[16];
      p_products(d, wf, sb, tid0, spin);
      if (WG == 0 && pc == WW) WTS(k, 2);
      red_tile(d, k < LAG ? k : k - LAG, col0, tid0);
    }
    if (WG == 0 && pc == WW) WTS(k, 13);
    WBAR_SYNC(NB_SG, 288);
  }
  if (spin >= SPIN_TOT) g_err = 11;
}
__device__ __forceinline__ void work_p_producer(uint32_t sb, int pc) {
  using namespace W;
  int spin = 0;
  const int ks = pc / 5;
#pragma unroll 1
  for (int k = 0; k < NSTEP; k++) {
    const bool two = dual(k);
    const uint8_t* src = &g_o[k % ORING][ks * 19][k < NSEG ? 0 : 4096];
    cwait(CN_O + k * 5 + ks, ks == 4 ? 20 : 19, spin);
    fence_async_all();
    if (pc == WW) WTS1(k, 0);
    if (two) {
#pragma unroll 1
      for (int u = 0; u < 4; u++, src += 40960) {
#pragma unroll
        for (int st = 0; st < 5; st++) {
          const bool none = st == 4 && u == 3 && ks < 4;
          mwait(sb + BAR_E + 8 * st, (u & 1) ^ 1, spin);
          fill_stage(sb + OFF_R + st * 8192, src + (none ? 3 : st) * 8192, none ? 16 : 8192, sb + BAR_F + 8 * st);
        }
      }
    } else {
#pragma unroll 1
      for (int f = 0; f < 10; f++, src += 16384) {
        const int st = f % 5;
        mwait(sb + BAR_E + 8 * st, f < 5, spin);
        fill_stage2(sb + OFF_R + st * 8192, src, src + (f == 9 && ks < 4 ? 0 : 8192), sb + BAR_F + 8 * st);
      }
    }
  }
  if (spin >= SPIN_TOT) g_err = 12;
}
template <int DMS, int KIND>
__device__ __forceinline__ void work_ln(const int kind_, int r, int lane, bf16* out) {
  const int kind = KIND ? KIND : kind_ & 1;
  int spin = 0;
  const int l = kind & 1;
  const int rp = kind < 2 ? (r & 1) * 16 + (r >> 1) : r;
  const uint32_t sw = ((((lane >> 1) & 7) ^ (rp & 7)) << 4) + (lane & 1) * 8;
  uint8_t* dst = kind < 2 ? g_xnb[l * LAG] + (lane >> 4) * 8192 + l * 4096 + rp * 128 + sw
               : kind == 2 ? g_xn[LAG] + (r >> 3) * 4096 + 2048 + (lane >> 4) * 1024 + (r & 7) * 128 + sw
                           : reinterpret_cast<uint8_t*>(out) + r * 1280 + lane * 8;
  if (FSL && kind < 2) {
#pragma unroll
    for (int m = 0; m < 5; m++) asm volatile("st.global.v2.b32 [%0],{%1,%1};" ::"l"(dst + m * DMS), "r"(SENT) : "memory");
    fence_gpu();
  }
#pragma unroll 1
  for (int s = 0; s < NSEG; s++) {
    float* xr = g_x + (size_t)(s * 32 + r) * DM;
    float4 v[5];
    float2 y[5] = {};
    if (kind < 2) {
#pragma unroll
      for (int u = 0; u < 5; u++) {
        const int p = u * 32 + lane;
        stg128((p < 80 ? g_ob[s + l * LAG] + (l * 32 + r) * 1280 : g_y[l] + (size_t)s * 40960 + (r - 1) * 1280) + p * 16, make_uint4(SENT, SENT, SENT, SENT));
      }
      if (FSL && s + 1 < NSEG) {
#pragma unroll
        for (int m = 0; m < 5; m++) asm volatile("st.global.v2.b32 [%0],{%1,%1};" ::"l"(dst + 81920 + m * DMS), "r"(SENT) : "memory");
      }
      if (XWL && !NOWORK && l && s == NSEG - 1) cwait(CN_X + NSTEP, 32, spin);
      cwait(CN_P + s + l * LAG, W::NP, spin);
      if (r == 0 && lane == 0 && (l == 0 || s + LAG >= NSEG)) WTS1(s + l * LAG, 3);
#pragma unroll
      for (int m = 0; m < 5; m++) v[m] = ld_relaxed4f(xr + m * 128 + lane * 4);
    } else {
      cwait(CN_L + s + l * LAG, s + l * LAG < LAG || s + l * LAG >= NSEG ? 32 : 64, spin);
#pragma unroll
      for (int m = 0; m < 5; m++) v[m] = ld_relaxed4f(xr + m * 128 + lane * 4);
      cwait(CN_W + l * 64 + s, 10, spin);
      if (r == 0 && lane == 0 && (l == 0 || s + LAG >= NSEG)) WTS1(s + l * LAG, 11);
      const uint8_t* yp = g_y[l] + (size_t)s * 40960 + (lane >> 4) * 4096 + r * 128 + sw;
      bool bad;
      do {
        bad = false;
#pragma unroll
        for (int m = 0; m < 5; m++) y[m] = ld_relaxed2f(yp + m * 8192);
#pragma unroll
        for (int m = 0; m < 5; m++) bad |= __float_as_uint(y[m].x) == SENT || __float_as_uint(y[m].y) == SENT;
        spin += 16;
      } while (__any_sync(0xffffffffu, bad && spin < SPIN_TOT));
#pragma unroll
      for (int m = 0; m < 5; m++) {
        v[m].x += bf_lo(__float_as_uint(y[m].x)); v[m].y += bf_hi(__float_as_uint(y[m].x));
        v[m].z += bf_lo(__float_as_uint(y[m].y)); v[m].w += bf_hi(__float_as_uint(y[m].y));
        if (!XWL && kind == 2) *reinterpret_cast<float4*>(xr + m * 128 + lane * 4) = v[m];
      }
    }
    if (FSL == 3 && kind < 2 && lane == 0) csignal_fast(CN_G + s + l * LAG);
    if (kind < 3) ln_row(v);
#pragma unroll
    for (int m = 0; m < 5; m++)
      asm volatile("st.global.v2.b32 [%0],{%1,%2};" ::"l"(dst + m * DMS), "r"(pack_bf16(v[m].x, v[m].y)), "r"(pack_bf16(v[m].z, v[m].w)) : "memory");
    dst += DMS == 256 ? 40960 : 81920;
    __syncwarp();
    if (r == 0 && lane == 0 && (l == 0 || s + LAG >= NSEG)) WTS1(s + l * LAG, kind < 2 ? 4 : 12);
    if (lane == 0 && kind < (NOWORK ? 2 : 3)) {
      if (FSL && kind < 2) csignal_fast(CN_G + s + l * LAG);
      csignal_t(kind < 2 ? CN_L + s + l * LAG : CN_X + s + LAG, kind);
    }
    if (XWL && kind == 2) {
      __syncwarp();
#pragma unroll
      for (int m = 0; m < 5; m++)
        asm volatile("red.relaxed.gpu.global.add.v4.f32 [%0],{%1,%2,%3,%4};" ::"l"(xr + m * 128 + lane * 4), "f"(bf_lo(__float_as_uint(y[m].x))), "f"(bf_hi(__float_as_uint(y[m].x))),
                     "f"(bf_lo(__float_as_uint(y[m].y))), "f"(bf_hi(__float_as_uint(y[m].y))) : "memory");
      if (s == NSEG - 1) { __syncwarp(); if (lane == 0) csignal(CN_X + NSTEP); }
    }
  }
  if (spin >= SPIN_TOT) g_err = 13;
}

__device__ __forceinline__ void work_prep(const bf16* x0, const bf16* mem0, int r, int lane) {
  int spin = 0;
#pragma unroll 1
  for (int k = NPRE; k < NSTEP; k++) {
    if (lane < 20) prefetch_l2(x0 + (size_t)min(k * 32 + r + (lane < 10 ? 0 : 16), SEQ - 1) * DM + (lane % 10) * 64);
    if (lane == 0) cwait(CN_O + (k - NPRE) * 5, 1, spin);
    __syncwarp();
#pragma unroll 1
    for (int h = 0; h < 2; h++) {
      uint2 u[5];
      ln0_load(x0, u, min(k * 32 + r + 16 * h, SEQ - 1), lane);
      prep_row(u, mem0, k, r + 16 * h, lane);
    }
    __syncwarp();
    if (lane == 0) csignal(CN_X + k);
  }
  if (spin >= SPIN_TOT) g_err = 19;
}

__device__ __forceinline__ void stage_qkv(const bf16* wqkv, uint32_t base, int T, int bc, int tid) {
  const int q = tid & 15;
  const bool ok = q < 15 && bc * 60 + 4 * q < DM;
  const bf16* src = wqkv + T * DM + bc * 60 + 4 * q;
#pragma unroll 1
  for (int k0 = tid >> 4; k0 < 640; k0 += 80) {
    uint2 v[10];
#pragma unroll
    for (int u = 0; u < 10; u++) v[u] = ok ? *reinterpret_cast<const uint2*>(src + (size_t)(k0 + 8 * u) * 1920) : make_uint2(0, 0);
#pragma unroll
    for (int u = 0; u < 10; u++) sts64(base + (k0 + 8 * u) * 128 + (((q >> 1) ^ (k0 & 7)) << 4) + (q & 1) * 8, v[u].x, v[u].y);
  }
}
struct AttAddr { uint32_t qa, qb, ka, oa, ob, ml; };
__device__ __forceinline__ AttAddr att_addr(uint32_t sb, int bc, int hh, int tid) {
  using namespace W;
  const int r = tid & 7, m = (tid >> 3) & 3, g = (tid >> 2) & 7, t = tid & 3, lp = (tid >> 5) & 3;
  const int f2 = r < 4 ? 20 * hh + 16 + r : 60;
  const uint32_t tb = sb + OFF_T + 2 * lp * COL;
  const int fa = 20 * hh + (m >> 1) * 8 + r, pc = 2 * (lp & 1) + (m & 1);
  const uint32_t o0 = sb + OFF_S + (lp >> 1) * 3840;
  AttAddr x;
  x.qa = keep(tb + (m & 1) * COL + (20 * hh + (m >> 1) * 8 + r) * 16);
  x.qb = keep(tb + (m & 1) * COL + f2 * 16);
  x.ka = keep(tb + (m < 2 ? 20 * hh + 8 * m + r : f2) * 16);
  x.oa = keep(o0 + fa * 64 + ((pc ^ ((bc * 60 + fa) >> 1)) & 3) * 16);
  x.ob = keep(r < 4 ? o0 + f2 * 64 + ((pc ^ ((bc * 60 + f2) >> 1)) & 3) * 16 : sb + OFF_S + 7680);
  x.ml = keep((2 * t > g ? 0xFFFFu : 0u) | (2 * t + 1 > g ? 0xFFFF0000u : 0u));
  return x;
}
__device__ __forceinline__ void release_tiles(uint32_t sb, int tid) {
  fence_async();
  __syncwarp();
  if ((tid & 31) < 3) mbar_arrive(sb + W::BAR_E + 16 + 8 * (tid & 3));
}
__device__ __forceinline__ void attend(uint32_t sb, const AttAddr& x, uint32_t (&hist)[6], int k0, int lp, int tid) {
  using namespace W;
  const float scl = 0.22360679774997896f * 1.4426950408889634f;
  float sc[3][4];
  uint32_t v[3][4];
  {
    uint32_t q[4], q8a, q8b, k[3][4];
    ldsm4t(q, x.qa);
    ldsm4t(k[1], x.ka + 8 * COL); ldsm4t(k[2], x.ka + 9 * COL);
    ldsm2t(q8a, q8b, x.qb);
    ldsm4(v[1], x.ka + 16 * COL); ldsm4(v[2], x.ka + 17 * COL);
#pragma unroll
    for (int j = 0; j < 3; j++) { k[0][j] = hist[j]; v[0][j] = hist[3 + j]; hist[j] = k[2][j]; hist[3 + j] = v[2][j]; }
#pragma unroll
    for (int c = 0; c < 3; c++) { sc[c][0] = sc[c][1] = sc[c][2] = sc[c][3] = 0.f; mma16816(sc[c], q[0], q[1], q[2], q[3], k[c][0], k[c][1]); }
#pragma unroll
    for (int c = 0; c < 3; c++) mma1688(sc[c], q8a, q8b, k[c][2]);
  }
  if (RTL == 0) release_tiles(sb, tid);
  const bool lo0 = x.ml & 1, lo1 = (int)x.ml < 0, first = k0 == (lp >> 1) * LAG;
  uint32_t pw[2];
  float inv[2];
#pragma unroll
  for (int h = 0; h < 2; h++) {
    float y0 = lo0 ? sc[h][2 * h] : sc[h + 1][2 * h], y1 = lo1 ? sc[h][2 * h + 1] : sc[h + 1][2 * h + 1];
    if (h == 0 && first) { y0 = lo0 ? -INFINITY : y0; y1 = lo1 ? -INFINITY : y1; }
    const float mx = quad_max(fmaxf(y0, y1)) * -scl;
    y0 = ex2(fmaf(y0, scl, mx)); y1 = ex2(fmaf(y1, scl, mx));
    pw[h] = pack_bf16(y0, y1);
    inv[h] = y0 + y1;
  }
  float o[3][4];
  const uint32_t a0 = pw[0] & x.ml, a2 = pw[0] & ~x.ml, a3 = pw[1] & x.ml, a5 = pw[1] & ~x.ml, z0 = tid >> 10, z1 = tid >> 11;
#pragma unroll
  for (int j = 0; j < 3; j++) { o[j][0] = o[j][1] = o[j][2] = o[j][3] = 0.f; mma16816(o[j], a0, z0, a2, a3, v[0][j], v[1][j]); }
#pragma unroll
  for (int j = 0; j < 3; j++) mma1688(o[j], z1, a5, v[2][j]);
  if (RTL == 1) release_tiles(sb, tid);
  inv[0] = rcp(quad_sum(inv[0])); inv[1] = rcp(quad_sum(inv[1]));
  stsm4t(x.oa, pack_bf16(o[0][0] * inv[0], o[0][1] * inv[0]), pack_bf16(o[0][2] * inv[1], o[0][3] * inv[1]),
         pack_bf16(o[1][0] * inv[0], o[1][1] * inv[0]), pack_bf16(o[1][2] * inv[1], o[1][3] * inv[1]));
  stsm2t(x.ob, pack_bf16(o[2][0] * inv[0], o[2][1] * inv[0]), pack_bf16(o[2][2] * inv[1], o[2][3] * inv[1]));
  if (RTL == 2) release_tiles(sb, tid); else fence_async();
}
__device__ __forceinline__ bool b_job(int k, int u, int bc) { return u == 0 || (u == 1 ? dual(k) : bc < 10 && (u == 3 || dual(k - 1))); }
template <bool IS_V, int ND, int NR>
__device__ __forceinline__ void qkv_step(float (&d)[ND], const uint32_t (&wf)[NR][4], const int q, uint32_t yo, uint64_t db) {
  using namespace W;
  if (!IS_V && q < NR) mma_r(d, wf[q < NR ? q : 0], db, q);
  else if (IS_V) mma_s(d, mkdesc(SB0 + OFF_WV + q * 2048, 8192, 1024), db, q);
  else mma_s(d, desc_at(mkdesc(SB0 + OFF_Y + (q - NR) * 2048, 8192, 1024), yo), db, 1);
}
template <bool IS_V, int ND, int NR>
__device__ __forceinline__ bool qkv_products(uint32_t (&pk)[16], const uint32_t (&wf)[NR][4], uint32_t sb, uint32_t pf, int tid0, int& spin) {
  using namespace W;
  constexpr int KF = ND == 32 ? 4 : 8, NF = 40 / KF;
  const uint32_t yo = uni(fresh(tid0) >> 7) * (40 - BRS) * 2048;
  float d[ND];
#pragma unroll
  for (int c = 0; c < NF; c++) {
    mwait(sb + BAR_F + 8 * (c % 5), pf ^ (c / 5), spin);
    wg_fence();
#pragma unroll
    for (int kk = 0; kk < KF; kk++) qkv_step<IS_V>(d, wf, KF * c + kk, yo, rdesc(OFF_X + (c % 5) * 8192 + (kk >> 2) * 4096, kk & 3));
    wg_commit();
    if (c > 0 && c <= NF - 3) {
      wg_wait<1>();
      if ((tid0 & 31) == 0) mbar_arrive(sb + BAR_E + 8 * ((c - 1) % 5));
    }
  }
  wg_wait<0>();
#pragma unroll
  for (int q = 0; q < 16; q++) pk[q] = pin(pack_bf16(d[(2 * q) % ND], d[(2 * q + 1) % ND]));
  float c0 = ((d[0] + d[1]) + (d[4] + d[5])) + ((d[8] + d[9]) + (d[12] + d[13]));
  if (ND == 32) c0 += ((d[16 % ND] + d[17 % ND]) + (d[20 % ND] + d[21 % ND])) + ((d[24 % ND] + d[25 % ND]) + (d[28 % ND] + d[29 % ND]));
  return IS_V && c0 != c0;
}
template <bool IS_V>
__device__ __forceinline__ void work_b(const CUtensorMap& tmBo, const bf16* wqkv, uint32_t sb, int bc, const int wg, int tid0) {
  using namespace W;
  if (!IS_V) asm volatile("setmaxnreg.inc.sync.aligned.u32 208;");
  else asm volatile("setmaxnreg.dec.sync.aligned.u32 72;");
  constexpr int NR = IS_V ? 1 : BRS;
  const int WG = IS_V ? 2 : wg;
  const uint32_t yo = WG * (40 - BRS) * 2048;
  int spin = 0;
  uint32_t wf[NR][4];
  if (!IS_V) {
    const uint32_t wb = sb + (WG ? OFF_WO : OFF_WV);
    stage_qkv(wqkv, wb, WG, bc, tid0 & 127);
    WBAR_SYNC(NB_G0 + WG, 128);
    load_frags<NR>(wf, wb, tid0);
#pragma unroll
    for (int k = NR; k < 40; k++) sts128(sb + OFF_Y + yo + (k - NR) * 2048 + (tid0 & 127) * 16, lds128(wb + k * 2048 + (tid0 & 127) * 16));
    fence_async();
  }
  WBAR_SYNC(NB_B, 384);
  if (WG == 1 && bc < 10) {
    if ((tid0 & 127) == 0) {
      mbar_expect_tx(sb + BAR_W, 81920);
      for (int i = 0; i < 10; i++) tma2d(sb + OFF_WO + i * 8192, &tmBo, bc * 64, i * 64, sb + BAR_W);
    }
    __syncwarp();
    mwait(sb + BAR_W, 0, spin);
  }
  if (IS_V) stage_qkv(wqkv, sb + OFF_WV, 2, bc, tid0 & 127);
  fence_async();
  WBAR_SYNC(NB_B, 384);
  const int wu = uni((tid0 >> 5) & 3);
  uint32_t nredo = 0, hist[6] = {};
  const AttAddr aa = att_addr(sb, bc, WG, tid0);
#pragma unroll 1
  for (int k = 0; k < NSTEP; k++) {
    {
      uint32_t pk[16];
      const bool bad = dual(k) ? qkv_products<IS_V, 32>(pk, wf, sb, LAG & 1, tid0, spin) : qkv_products<IS_V, 16>(pk, wf, sb, (k < LAG ? k : k - NSEG + LAG) & 1, tid0, spin);
      if (bc == 0 && WG != 1) WTS(k, 16 + WG / 2);
      const int tid = fresh(tid0), m = (tid >> 3) & 3;
      const uint32_t a = pin(sb + OFF_T + min(wu * 16 + (m & 1) * 8 + (tid & 7), 60) * 16 + (8 * WG + (m >> 1)) * COL);
      if (!FSL) WBAR_SYNC(NB_B, 384);
      else {
        if (__builtin_expect(bar_red_or(NB_RED3, 384, bad), 0)) {
          float d[32];
          if (IS_V && wu == 0) { cwait(CN_L + k, k < LAG || k >= NSEG ? 32 : 64, spin); fence_async_all(); }
#pragma unroll
          for (int c = 0; c < 10; c++) {
            if (IS_V && wu == 0 && elect_one()) { mbar_expect_tx(sb + BAR_R + 8, 8192); bulk_g2s(sb + OFF_X + 32768, g_xnb[k] + c * 8192, 8192, sb + BAR_R + 8); }
            __syncwarp();
            mwait(sb + BAR_R + 8, c & 1, spin);
            wg_fence();
#pragma unroll
            for (int kk = 0; kk < 4; kk++) qkv_step<IS_V>(d, wf, 4 * c + kk, yo, rdesc(OFF_X + 32768, kk));
            wg_commit();
            wg_wait<0>();
            bar_sync(NB_RED3, 384);
          }
#pragma unroll
          for (int q = 0; q < 16; q++) pk[q] = pin(pack_bf16(d[2 * q], d[2 * q + 1]));
        }
      }
#pragma unroll
      for (int p = 0; p < 4; p++) stsm4(a + 2 * p * COL, pk[4 * p], pk[4 * p + 1], pk[4 * p + 2], pk[4 * p + 3]);
    }
    WBAR_SYNC(NB_TD, 448);
    if (bc == 0 && WG == 0) WTS(k, 7);
    if (bc * 3 + WG < NH && (wu < 2 ? k < NSEG : k >= LAG)) attend(sb, aa, hist, k, wu, fresh(tid0));
    else release_tiles(sb, tid0);
    if (bc == 0 && WG == 0) WTS(k, 8);
    WBAR_SYNC(NB_AS, 416);
    if (!IS_V && b_job(k, 2 + WG, bc)) {
      float d[16];
#pragma unroll
      for (int f = 0; f < 5; f++) {
        mwait(sb + BAR_G + 40 * WG + 8 * f, (WG ? k : k - LAG - 1) & 1, spin);
        if (f == 0 && bc == 0) WTS(k - 1 + WG, WG ? 20 : 23);
        wg_fence();
#pragma unroll
        for (int kk = 0; kk < 8; kk++) {
          wgmma_tt32(d, mkdesc(SB0 + OFF_WO + (8 * f + kk) * 2048, 8192, 1024), gdesc(OFF_X + f * 8192, kk), f | kk);
          if (kk == 1 && f > 0) {
            wg_commit();
            wg_wait<1>();
            if ((tid0 & 31) < 3) mbar_arrive(sb + BAR_E + 8 * (f - 1));
          }
        }
        wg_commit();
      }
      wg_wait<0>();
      if (WG == 1 && FSA) {
        const float chk = ((d[0] + d[1]) + (d[4] + d[5])) + ((d[8] + d[9]) + (d[12] + d[13]));
        if (__builtin_expect(bar_red_or(NB_RED, 128, chk != chk), 0)) {
          if (wu == 0) { cwait(CN_A + k, NBC, spin); fence_async_all(); }
#pragma unroll
          for (int q = 0; q < 16; q++) d[q] = 0.f;
#pragma unroll 1
          for (int f = 0; f < 5; f++) {
            if (wu == 0 && elect_one()) { mbar_expect_tx(sb + BAR_W + 8, 8192); bulk_g2s(sb + OFF_X + 32768, g_ob[k] + (k < NSEG ? 0 : 40960) + f * 8192, 8192, sb + BAR_W + 8); }
            __syncwarp();
            mwait(sb + BAR_W + 8, nredo & 1, spin);
            nredo++;
            wg_fence();
#pragma unroll
            for (int kk = 0; kk < 8; kk++)
              wgmma_tt32(d, desc_at(mkdesc(SB0 + OFF_WO + kk * 2048, 8192, 1024), f * 16384), gdesc(OFF_X + 32768, kk), 1);
            wg_commit();
            wg_wait<0>();
            bar_sync(NB_RED, 128);
          }
        }
      }
      else if (WG) bar_sync(NB_RED, 128);
      else {
        if ((tid0 & 31) < 3) mbar_arrive(sb + BAR_E + 32);
        WBAR_SYNC(NB_SF, 160);
      }
      if (bc == 0) WTS(k - 1 + WG, WG ? 10 : 24);
      const int tid = fresh(tid0), m = (tid >> 3) & 3, row = (m >> 1) * 16 + 2 * (tid & 7);
      const uint32_t a = sb + (WG ? OFF_X + 32768 : OFF_S) + row * 128 + (((2 * wu + (m & 1)) ^ row) & 7) * 16;
#pragma unroll
      for (int p = 0; p < 2; p++)
        stsm4t(a ^ (p * 144), pack_bf16(d[8 * p], d[8 * p + 1]), pack_bf16(d[8 * p + 2], d[8 * p + 3]), pack_bf16(d[8 * p + 4], d[8 * p + 5]), pack_bf16(d[8 * p + 6], d[8 * p + 7]));
      fence_async();
      WBAR_SYNC(WG ? NB_SG : NB_SG1, 160);
    }
  }
  if (spin >= SPIN_TOT) g_err = 14;
}
__device__ __forceinline__ void work_b_watch(uint32_t sb, int bc) {
  using namespace W;
  int spin = 0;
#pragma unroll 1
  for (int j = 0; j < 4 * NSTEP; j++) {
    const int k = j >> 2, u = j & 3;
    if (u == 1 || !b_job(k, u, bc)) continue;
    cwait(u == 0 ? (FSL ? CN_G : CN_L) + k : u == 2 ? CN_A + k - 1 : (FSA ? CN_F : CN_A) + k, u ? NBC : k < LAG || k >= NSEG ? 32 : 64, spin);
    fence_async_all();
    if (bc == 0 && u != 2) WTS1(k, u ? 9 : 5);
    if (elect_one()) mbar_arrive(sb + BAR_R + 8 * u);
    __syncwarp();
    if (u == 0) WBAR_SYNC(NB_R, 64);
  }
  if (spin >= SPIN_TOT) g_err = 16;
}
__device__ __forceinline__ void work_b_producer(uint32_t sb, int bc) {
  using namespace W;
  int spin = 0;
  uint32_t pe = 1;
#pragma unroll 1
  for (int j = 0; j < 4 * NSTEP; j++) {
    const int k = j >> 2, u = j & 3;
    if (!b_job(k, u, bc)) continue;
    const uint32_t half = u < 2 && !dual(k), lo = half && k >= NSEG ? 4096 : 0, fb = sb + (u < 2 ? BAR_F : BAR_G + 40 * (u - 2));
    const uint8_t* src = (u < 2 ? g_xnb[k] + u * 40960 : u == 2 ? g_ob[k - 1] + 40960 : g_ob[k] + (k < NSEG ? 0 : 40960)) + lo;
    mwait(sb + BAR_E, pe, spin);
    if (u != 1) mwait(sb + BAR_R + 8 * u, (u == 2 ? k - LAG - 1 : k) & 1, spin);
    if (!half) {
#pragma unroll
      for (int f = 0; f < 5; f++) {
        if (f) mwait(sb + BAR_E + 8 * f, pe, spin);
        fill_stage(sb + OFF_X + f * 8192, src + f * 8192, 8192, fb + 8 * f);
      }
    } else {
#pragma unroll 1
      for (int f = 0; f < 5; f++) {
        mwait(sb + BAR_E + 8 * f, pe, spin);
        fill_stage2(sb + OFF_X + f * 8192, src + f * 16384, src + f * 16384 + 8192, fb + 8 * f);
      }
    }
    if (u == 0) WBAR_SYNC(NB_R, 64);
    pe ^= 1;
  }
  if (spin >= SPIN_TOT) g_err = 15;
}

__global__ void __launch_bounds__(512, 1)
k_work(const __grid_constant__ CUtensorMap tmWo, const __grid_constant__ CUtensorMap tmBo, const bf16* __restrict__ wqkv, bf16* __restrict__ out,
       const bf16* __restrict__ x0, const bf16* __restrict__ mem0) {
  using namespace W;
  extern __shared__ __align__(1024) uint8_t smem[];
  const uint32_t sb = smem_u32(smem);
  const int tid = threadIdx.x, w = blockIdx.x;
  const int wg = __shfl_sync(0xffffffffu, tid >> 7, 0);
  if (tid == 0) {
    if (sb != SB0) g_err = 101;
    for (int i = 0; i < 5; i++) { mbar_init(sb + BAR_F + 8 * i, 1); mbar_init(sb + BAR_E + 8 * i, w < NP ? 8 : 12); }
    for (int i = 0; i < 16; i++) mbar_init(sb + BAR_G + 8 * i, 1);
    for (int p = 0; p < 16; p++) sts32(sb + OFF_SAFE + 4 * p, 0);
    asm volatile("fence.mbarrier_init.release.cluster;" ::: "memory");
    int spin = 0;
    pre_wait(1, NW, spin);
    if (spin >= SPIN_TOT) g_err = 18;
  }
  fence_async();
  __syncthreads();

  if (w < NP) {
    if (wg < 2) work_p(tmWo, sb, w, wg, keep(tid));
    else {
      asm volatile("setmaxnreg.dec.sync.aligned.u32 48;");
      const int aw = uni(tid >> 5) - 8;
      if (aw == 0) work_p_producer(sb, w);
      else if (aw == 1) {
#pragma unroll 1
        for (int k = 0; k < NSTEP; k++) {
          WBAR_SYNC(NB_SG, 288);
          if (elect_one()) csignal_t(CN_P + k, 3);
          __syncwarp();
        }
      } else {
        const int id = (aw - 2) * NP + w;
        if (id < 64) work_ln<16384, 0>(id & 1, id >> 1, tid & 31, out);
        else if (id < 96) work_ln<16384, 2>(2, id - 64, tid & 31, out);
        else if (id < 128) work_ln<256, 3>(3, id - 96, tid & 31, out);
        else if (id < 144 && NOWORK != 2) work_prep(x0, mem0, id - 128, tid & 31);
      }
    }
  } else {
    const int bc = w - NP;
    if (wg < 2) work_b<false>(tmBo, wqkv, sb, bc, wg, keep(tid));
    else if (wg == 2) work_b<true>(tmBo, wqkv, sb, bc, wg, keep(tid));
    else {
      asm volatile("setmaxnreg.dec.sync.aligned.u32 24;");
      const int aw = uni(tid >> 5) - 12;
      if (aw == 0) work_b_producer(sb, bc);
      else if (aw == 1) work_b_watch(sb, bc);
      else if (aw == 2) {
#pragma unroll 1
        for (int k = 0; k < NSTEP; k++) {
          WBAR_ARRIVE(NB_TD, 448);
          if (FSA == 3 && (tid & 31) == 0) csignal_fast(CN_F + k);
          WBAR_SYNC(NB_AS, 416);
          if (elect_one()) {
            const uint32_t len = bc < 10 ? 3840 : 2560;
            const int l = k >= NSEG;
            bulk_s2g(g_ob[k] + l * 40960 + bc * 3840, sb + OFF_S + l * 3840, len);
            if (FSA) csignal_fast(CN_F + k);
            if (dual(k)) bulk_s2g(g_ob[k] + 40960 + bc * 3840, sb + OFF_S + 3840, len);
            asm volatile("cp.async.bulk.commit_group;" ::: "memory");
            asm volatile("cp.async.bulk.wait_group 0;" ::: "memory");
          }
          __syncwarp();
          if (b_job(k, 2, bc)) WBAR_ARRIVE(NB_SF, 160);
          if (elect_one()) { fence_async_all(); csignal_t(CN_A + k, 5); }
          __syncwarp();
        }
      } else {
#pragma unroll 1
        for (int j = 0; j < 2 * NSTEP; j++) {
          const int k = j >> 1, pr = j & 1, l = !pr || k >= NSEG, s = k - l * LAG - !pr;
          if (!pr) WBAR_SYNC(NB_TD, 448);
          if (!b_job(k, 2 + pr, bc)) continue;
          WBAR_SYNC(pr ? NB_SG : NB_SG1, 160);
          if (elect_one()) {
            bulk_s2g(g_y[l] + (size_t)s * 40960 + bc * 4096, sb + (pr ? OFF_X + 32768 : OFF_S), 4096);
            asm volatile("cp.async.bulk.commit_group;" ::: "memory");
            if (FSW) csignal_fast(CN_W + l * 64 + s);
            asm volatile("cp.async.bulk.wait_group.read 0;" ::: "memory");
            if (!FSW) csignal_fast(CN_W + l * 64 + s);
            if (pr) asm volatile("mbarrier.arrive.shared::cta.b64 _,[%0],12;" ::"r"(sb + BAR_E + 32) : "memory");
          }
          __syncwarp();
        }
      }
    }
  }
  __syncthreads();
  asm volatile("griddepcontrol.wait;" ::: "memory");
}

typedef CUresult (*EncodeFn)(CUtensorMap*, CUtensorMapDataType, cuuint32_t, void*, const cuuint64_t*, const cuuint64_t*,
                             const cuuint32_t*, const cuuint32_t*, CUtensorMapInterleave, CUtensorMapSwizzle,
                             CUtensorMapL2promotion, CUtensorMapFloatOOBfill);

static void make_map(EncodeFn enc, CUtensorMap* tm, const void* ptr, uint64_t cols, uint64_t rows, uint32_t boxc, uint32_t boxr) {
  cuuint64_t dims[2] = {cols, rows};
  cuuint64_t strides[1] = {cols * 2};
  cuuint32_t box[2] = {boxc, boxr};
  cuuint32_t es[2] = {1, 1};
  enc(tm, CU_TENSOR_MAP_DATA_TYPE_BFLOAT16, 2, const_cast<void*>(ptr), dims, strides, box, es, CU_TENSOR_MAP_INTERLEAVE_NONE,
      CU_TENSOR_MAP_SWIZZLE_128B, CU_TENSOR_MAP_L2_PROMOTION_L2_256B, CU_TENSOR_MAP_FLOAT_OOB_FILL_NONE);
}

extern "C" void kernel_launch(void* const* d_in, const int* in_sizes, int n_in, void* d_out, int out_size) {
  const bf16* x0 = (const bf16*)d_in[0];
  const bf16* mem0 = (const bf16*)d_in[1];
  const bf16* Wq = (const bf16*)d_in[2];
  const bf16* Wk = (const bf16*)d_in[3];
  const bf16* Wv = (const bf16*)d_in[4];
  const bf16* Wo = (const bf16*)d_in[5];
  const bf16* Bqkv = (const bf16*)d_in[8];
  const bf16* Bwo = (const bf16*)d_in[9];
  bf16* out = (bf16*)d_out;

  static EncodeFn enc = nullptr;
  if (!enc) {
    void* fn = nullptr;
    cudaDriverEntryPointQueryResult qr;
    cudaGetDriverEntryPoint("cuTensorMapEncodeTiled", &fn, cudaEnableDefault, &qr);
    enc = (EncodeFn)fn;
    cudaFuncSetAttribute(k_chain, cudaFuncAttributeMaxDynamicSharedMemorySize, C::SMEM);
    cudaFuncSetAttribute(k_work, cudaFuncAttributeMaxDynamicSharedMemorySize, W::SMEM);
  }
  CUtensorMap tmWq, tmWk, tmWv, tmWo, tmWp, tmBo;
  make_map(enc, &tmWq, Wq, NH * DH, DM, 64, 128);
  make_map(enc, &tmWk, Wk, NH * DH, DM, 64, 128);
  make_map(enc, &tmWv, Wv, NH * DH, DM, 64, 128);
  make_map(enc, &tmWo, Wo, DM, NH * DH, 64, 64);
  make_map(enc, &tmWp, Wo, DM, NH * DH, 64, 16);
  make_map(enc, &tmBo, Bwo, DM, DM, 64, 64);

  cudaStream_t st = cudaStreamPerThread;
  cudaLaunchAttribute at[1];
  at[0].id = cudaLaunchAttributeProgrammaticStreamSerialization; at[0].val.programmaticStreamSerializationAllowed = 1;
  {
    cudaLaunchConfig_t cfg = {};
    cfg.gridDim = dim3(96); cfg.blockDim = dim3(384); cfg.dynamicSmemBytes = C::SMEM; cfg.stream = st;
    cfg.attrs = at; cfg.numAttrs = 0;
    cudaLaunchKernelEx(&cfg, k_chain, tmWq, tmWk, tmWv, tmWo, x0, mem0);
  }
  cudaLaunchConfig_t cfg = {};
  cfg.gridDim = dim3(W::NW); cfg.blockDim = dim3(512); cfg.dynamicSmemBytes = W::SMEM; cfg.stream = st;
  cfg.attrs = at; cfg.numAttrs = NOWORK == 2 ? 0 : 1;
  cudaLaunchKernelEx(&cfg, k_work, tmWp, tmBo, Bqkv, out, x0, mem0);
}
```
